```python
import torch

def _softmax(x, axis=-1):
    return torch.softmax(x, dim=axis)

def _gelu(x):
    return torch.nn.functional.gelu(x, approximate='tanh')

def _silu(x):
    return torch.nn.functional.silu(x)

def _sigmoid(x):
    return torch.sigmoid(x)

def _layernorm(x, axis=-1, eps=1e-05):
    m = x.mean(dim=axis, keepdim=True)
    v = x.var(dim=axis, keepdim=True, unbiased=False)
    return (x - m) / torch.sqrt(v + eps)

def _scatter_add(tgt, idx, src, axis=0):
    return tgt.clone().index_add_(axis, idx, src)

def _segment_sum(src, seg, n):
    out = torch.zeros((n,) + src.shape[1:], dtype=src.dtype)
    return out.index_add_(0, seg, src)

def _pad(x, pw):
    flat = tuple((v for pair in reversed(pw) for v in pair))
    return torch.nn.functional.pad(x, flat)
kernel_name = 'standalone__neighborhood_dinat__vision'

def setup_inputs():

    _w = lambda a: (lambda t: t.to(torch.bfloat16) if t.is_floating_point() else t)(torch.as_tensor(a))
    ks, dil, nh = (7, 2, 4)
    H = W = max(ks * dil, 224 // dil * dil)
    C = max(nh, 192 // nh * nh)
    return {'x': _w((lambda *s: torch.randn(*s, dtype=torch.bfloat16) * 0.2)(1, H, W, C)), 'wqkv': _w((lambda *s: torch.randn(*s, dtype=torch.bfloat16) * 0.2)(C, 3 * C)), 'wo': _w((lambda *s: torch.randn(*s, dtype=torch.bfloat16) * 0.4)(C, C)), 'rpb': _w((lambda *s: torch.randn(*s, dtype=torch.bfloat16) * 0.4)(nh, 2 * ks - 1, 2 * ks - 1))}

def reference(x, wqkv, wo, rpb):
    B, H, W, C = x.shape
    ks, dil, nh = (7, 2, 4)
    hd = C // nh
    scale = hd ** (-0.5)
    qkv = (x @ wqkv).reshape(B, H, W, 3, nh, hd)
    q = qkv[:, :, :, 0].clone()
    k = qkv[:, :, :, 1].clone()
    v = qkv[:, :, :, 2].clone()
    ih = torch.arange(H)
    iw = torch.arange(W)
    m = torch.arange(ks)
    sh = torch.clip(ih // dil - ks // 2, 0, H // dil - ks)
    sw = torch.clip(iw // dil - ks // 2, 0, W // dil - ks)
    kh = (sh[:, None] + m[None, :]) * dil + (ih % dil)[:, None]
    kw = (sw[:, None] + m[None, :]) * dil + (iw % dil)[:, None]
    rh = sh[:, None] + m[None, :] - (ih // dil)[:, None] + (ks - 1)
    rw = sw[:, None] + m[None, :] - (iw // dil)[:, None] + (ks - 1)
    ih4 = kh[:, :, None, None].clone()
    iw4 = kw[None, None, :, :].clone()
    kg = (lambda x, *d: x.permute(*d))(k[:, ih4, iw4, :, :], 0, 1, 3, 5, 2, 4, 6).reshape(B, H, W, nh, ks * ks, hd)
    vg = (lambda x, *d: x.permute(*d))(v[:, ih4, iw4, :, :], 0, 1, 3, 5, 2, 4, 6).reshape(B, H, W, nh, ks * ks, hd)
    bg = (lambda x, *d: x.permute(*d))(rpb[:, rh[:, :, None, None], rw[None, None, :, :]], 1, 3, 0, 2, 4).reshape(1, H, W, nh, ks * ks)
    logits = torch.einsum('bhwnd,bhwnkd->bhwnk', q, kg) * scale + bg
    attn = _softmax(logits, axis=-1)
    out = torch.einsum('bhwnk,bhwnkd->bhwnd', attn, vg).reshape(B, H, W, C)
    return out @ wo
```

```cpp
#include <cuda_runtime.h>
#include <cuda_bf16.h>
#include <cuda.h>
#include <stdint.h>

#define SPIN_LIMIT (1u << 18)

__device__ __forceinline__ uint32_t smem_u32(const void* p) { return (uint32_t)__cvta_generic_to_shared(p); }
__device__ __forceinline__ void wg_fence() { asm volatile("wgmma.fence.sync.aligned;" ::: "memory"); }
__device__ __forceinline__ void wg_commit() { asm volatile("wgmma.commit_group.sync.aligned;" ::: "memory"); }
template <int N> __device__ __forceinline__ void wg_wait() { asm volatile("wgmma.wait_group.sync.aligned %0;" ::"n"(N) : "memory"); }
template <int N> __device__ __forceinline__ void pin(float (&d)[N]) {
#pragma unroll
  for (int i = 0; i < N; i++) asm volatile("" : "+f"(d[i])::"memory");
}
__host__ __device__ constexpr uint64_t mkdesc(uint32_t addr, uint32_t lbo, uint32_t sbo, uint32_t sw) {
  return (uint64_t)((addr & 0x3FFFF) >> 4) | ((uint64_t)(lbo >> 4) << 16) | ((uint64_t)(sbo >> 4) << 32) | ((uint64_t)sw << 62);
}
__device__ __forceinline__ void mbar_init(uint32_t bar, uint32_t cnt) { asm volatile("mbarrier.init.shared::cta.b64 [%0], %1;" ::"r"(bar), "r"(cnt) : "memory"); }
__device__ __forceinline__ void mbar_arrive(uint32_t bar) { asm volatile("mbarrier.arrive.shared::cta.b64 _, [%0];" ::"r"(bar) : "memory"); }
__device__ __forceinline__ void mbar_expect(uint32_t bar, uint32_t bytes) { asm volatile("mbarrier.arrive.expect_tx.shared::cta.b64 _, [%0], %1;" ::"r"(bar), "r"(bytes) : "memory"); }
__device__ __forceinline__ void mbar_arrive_remote(uint32_t bar, uint32_t cta) {
  asm volatile("{\n.reg .b32 ra;\nmapa.shared::cluster.u32 ra, %0, %1;\nmbarrier.arrive.release.cluster.shared::cluster.b64 _, [ra];\n}" ::"r"(bar), "r"(cta) : "memory");
}
__device__ __forceinline__ void mbar_wait(uint32_t bar, uint32_t parity) {
  asm volatile("{\n.reg .pred p;\n.reg .b32 n;\nmov.b32 n, 0;\nWL:\nmbarrier.try_wait.parity.shared::cta.b64 p, [%0], %1;\n@p bra WD;\n"
               "add.u32 n, n, 1;\nsetp.lt.u32 p, n, 65536;\n@p bra WL;\nWD:\n}" ::"r"(bar), "r"(parity) : "memory");
}
__device__ __forceinline__ void mbar_wait_cluster(uint32_t bar, uint32_t parity) {
  asm volatile("{\n.reg .pred p;\n.reg .b32 n;\nmov.b32 n, 0;\nWL:\nmbarrier.try_wait.parity.acquire.cluster.shared::cta.b64 p, [%0], %1;\n@p bra WD;\n"
               "add.u32 n, n, 1;\nsetp.lt.u32 p, n, 65536;\n@p bra WL;\nWD:\n}" ::"r"(bar), "r"(parity) : "memory");
}
__device__ __forceinline__ void fence_async() { asm volatile("fence.proxy.async.shared::cta;" ::: "memory"); }
__device__ __forceinline__ void cluster_sync() {
  asm volatile("barrier.cluster.arrive.release.aligned;\nbarrier.cluster.wait.acquire.aligned;" ::: "memory");
}
__device__ __forceinline__ uint32_t pack2(float lo, float hi) {
  uint32_t r; asm("cvt.rn.bf16x2.f32 %0, %1, %2;" : "=r"(r) : "f"(hi), "f"(lo)); return r;
}
__device__ __forceinline__ void stsm4(uint32_t a, uint32_t r0, uint32_t r1, uint32_t r2, uint32_t r3) {
  asm volatile("stmatrix.sync.aligned.m8n8.x4.shared.b16 [%0], {%1,%2,%3,%4};" ::"r"(a), "r"(r0), "r"(r1), "r"(r2), "r"(r3) : "memory");
}
__device__ __forceinline__ void ldsm4(uint32_t a, uint32_t& r0, uint32_t& r1, uint32_t& r2, uint32_t& r3) {
  asm volatile("ldmatrix.sync.aligned.m8n8.x4.shared.b16 {%0,%1,%2,%3}, [%4];" : "=r"(r0), "=r"(r1), "=r"(r2), "=r"(r3) : "r"(a) : "memory");
}
__device__ __forceinline__ float lds_f32(uint32_t a) { float v; asm volatile("ld.shared.f32 %0, [%1];" : "=f"(v) : "r"(a)); return v; }
__device__ __forceinline__ float ex2(float x) { float y; asm("ex2.approx.ftz.f32 %0, %1;" : "=f"(y) : "f"(x)); return y; }

template<int SC> __device__ __forceinline__ void wg_ss144(float (&d)[72], uint64_t da, uint64_t db) {
  asm volatile("{\n.reg .pred p;\nsetp.ne.b32 p, %74, 0;\nwgmma.mma_async.sync.aligned.m64n144k16.f32.bf16.bf16 {%0,%1,%2,%3,%4,%5,%6,%7,%8,%9,%10,%11,%12,%13,%14,%15,%16,%17,%18,%19,%20,%21,%22,%23,%24,%25,%26,%27,%28,%29,%30,%31,%32,%33,%34,%35,%36,%37,%38,%39,%40,%41,%42,%43,%44,%45,%46,%47,%48,%49,%50,%51,%52,%53,%54,%55,%56,%57,%58,%59,%60,%61,%62,%63,%64,%65,%66,%67,%68,%69,%70,%71}, %72, %73, p, 1, 1, 0, 1;\n}\n"
    : "+f"(d[0]),"+f"(d[1]),"+f"(d[2]),"+f"(d[3]),"+f"(d[4]),"+f"(d[5]),"+f"(d[6]),"+f"(d[7]),"+f"(d[8]),"+f"(d[9]),"+f"(d[10]),"+f"(d[11]),"+f"(d[12]),"+f"(d[13]),"+f"(d[14]),"+f"(d[15]),"+f"(d[16]),"+f"(d[17]),"+f"(d[18]),"+f"(d[19]),"+f"(d[20]),"+f"(d[21]),"+f"(d[22]),"+f"(d[23]),"+f"(d[24]),"+f"(d[25]),"+f"(d[26]),"+f"(d[27]),"+f"(d[28]),"+f"(d[29]),"+f"(d[30]),"+f"(d[31]),"+f"(d[32]),"+f"(d[33]),"+f"(d[34]),"+f"(d[35]),"+f"(d[36]),"+f"(d[37]),"+f"(d[38]),"+f"(d[39]),"+f"(d[40]),"+f"(d[41]),"+f"(d[42]),"+f"(d[43]),"+f"(d[44]),"+f"(d[45]),"+f"(d[46]),"+f"(d[47]),"+f"(d[48]),"+f"(d[49]),"+f"(d[50]),"+f"(d[51]),"+f"(d[52]),"+f"(d[53]),"+f"(d[54]),"+f"(d[55]),"+f"(d[56]),"+f"(d[57]),"+f"(d[58]),"+f"(d[59]),"+f"(d[60]),"+f"(d[61]),"+f"(d[62]),"+f"(d[63]),"+f"(d[64]),"+f"(d[65]),"+f"(d[66]),"+f"(d[67]),"+f"(d[68]),"+f"(d[69]),"+f"(d[70]),"+f"(d[71]) : "l"(da), "l"(db), "n"(SC));
}
template<int SC> __device__ __forceinline__ void wg_ss96(float (&d)[48], uint64_t da, uint64_t db) {
  asm volatile("{\n.reg .pred p;\nsetp.ne.b32 p, %50, 0;\nwgmma.mma_async.sync.aligned.m64n96k16.f32.bf16.bf16 {%0,%1,%2,%3,%4,%5,%6,%7,%8,%9,%10,%11,%12,%13,%14,%15,%16,%17,%18,%19,%20,%21,%22,%23,%24,%25,%26,%27,%28,%29,%30,%31,%32,%33,%34,%35,%36,%37,%38,%39,%40,%41,%42,%43,%44,%45,%46,%47}, %48, %49, p, 1, 1, 0, 1;\n}\n"
    : "+f"(d[0]),"+f"(d[1]),"+f"(d[2]),"+f"(d[3]),"+f"(d[4]),"+f"(d[5]),"+f"(d[6]),"+f"(d[7]),"+f"(d[8]),"+f"(d[9]),"+f"(d[10]),"+f"(d[11]),"+f"(d[12]),"+f"(d[13]),"+f"(d[14]),"+f"(d[15]),"+f"(d[16]),"+f"(d[17]),"+f"(d[18]),"+f"(d[19]),"+f"(d[20]),"+f"(d[21]),"+f"(d[22]),"+f"(d[23]),"+f"(d[24]),"+f"(d[25]),"+f"(d[26]),"+f"(d[27]),"+f"(d[28]),"+f"(d[29]),"+f"(d[30]),"+f"(d[31]),"+f"(d[32]),"+f"(d[33]),"+f"(d[34]),"+f"(d[35]),"+f"(d[36]),"+f"(d[37]),"+f"(d[38]),"+f"(d[39]),"+f"(d[40]),"+f"(d[41]),"+f"(d[42]),"+f"(d[43]),"+f"(d[44]),"+f"(d[45]),"+f"(d[46]),"+f"(d[47]) : "l"(da), "l"(db), "n"(SC));
}
template<int SC> __device__ __forceinline__ void wg_rs112(float (&d)[56], uint32_t a0, uint32_t a1, uint32_t a2, uint32_t a3, uint64_t db) {
  asm volatile("{\n.reg .pred p;\nsetp.ne.b32 p, %61, 0;\nwgmma.mma_async.sync.aligned.m64n112k16.f32.bf16.bf16 {%0,%1,%2,%3,%4,%5,%6,%7,%8,%9,%10,%11,%12,%13,%14,%15,%16,%17,%18,%19,%20,%21,%22,%23,%24,%25,%26,%27,%28,%29,%30,%31,%32,%33,%34,%35,%36,%37,%38,%39,%40,%41,%42,%43,%44,%45,%46,%47,%48,%49,%50,%51,%52,%53,%54,%55}, {%56,%57,%58,%59}, %60, p, 1, 1, 0;\n}\n"
    : "+f"(d[0]),"+f"(d[1]),"+f"(d[2]),"+f"(d[3]),"+f"(d[4]),"+f"(d[5]),"+f"(d[6]),"+f"(d[7]),"+f"(d[8]),"+f"(d[9]),"+f"(d[10]),"+f"(d[11]),"+f"(d[12]),"+f"(d[13]),"+f"(d[14]),"+f"(d[15]),"+f"(d[16]),"+f"(d[17]),"+f"(d[18]),"+f"(d[19]),"+f"(d[20]),"+f"(d[21]),"+f"(d[22]),"+f"(d[23]),"+f"(d[24]),"+f"(d[25]),"+f"(d[26]),"+f"(d[27]),"+f"(d[28]),"+f"(d[29]),"+f"(d[30]),"+f"(d[31]),"+f"(d[32]),"+f"(d[33]),"+f"(d[34]),"+f"(d[35]),"+f"(d[36]),"+f"(d[37]),"+f"(d[38]),"+f"(d[39]),"+f"(d[40]),"+f"(d[41]),"+f"(d[42]),"+f"(d[43]),"+f"(d[44]),"+f"(d[45]),"+f"(d[46]),"+f"(d[47]),"+f"(d[48]),"+f"(d[49]),"+f"(d[50]),"+f"(d[51]),"+f"(d[52]),"+f"(d[53]),"+f"(d[54]),"+f"(d[55]) : "r"(a0), "r"(a1), "r"(a2), "r"(a3), "l"(db), "n"(SC));
}
template<int SC> __device__ __forceinline__ void wg_sp48(float (&d)[24], uint32_t a0, uint32_t a1, uint32_t a2, uint32_t a3, uint64_t db, uint32_t meta) {
  asm volatile("{\n.reg .pred p;\nsetp.ne.b32 p, %30, 0;\nwgmma.mma_async.sp.sync.aligned.m64n48k32.f32.bf16.bf16 {%0,%1,%2,%3,%4,%5,%6,%7,%8,%9,%10,%11,%12,%13,%14,%15,%16,%17,%18,%19,%20,%21,%22,%23}, {%24,%25,%26,%27}, %28, %29, 0, p, 1, 1, 1;\n}\n"
    : "+f"(d[0]),"+f"(d[1]),"+f"(d[2]),"+f"(d[3]),"+f"(d[4]),"+f"(d[5]),"+f"(d[6]),"+f"(d[7]),"+f"(d[8]),"+f"(d[9]),"+f"(d[10]),"+f"(d[11]),"+f"(d[12]),"+f"(d[13]),"+f"(d[14]),"+f"(d[15]),"+f"(d[16]),"+f"(d[17]),"+f"(d[18]),"+f"(d[19]),"+f"(d[20]),"+f"(d[21]),"+f"(d[22]),"+f"(d[23]) : "r"(a0), "r"(a1), "r"(a2), "r"(a3), "l"(db), "r"(meta), "n"(SC));
}
template<int SC> __device__ __forceinline__ void wg_rs96(float (&d)[48], uint32_t a0, uint32_t a1, uint32_t a2, uint32_t a3, uint64_t db) {
  asm volatile("{\n.reg .pred p;\nsetp.ne.b32 p, %53, 0;\nwgmma.mma_async.sync.aligned.m64n96k16.f32.bf16.bf16 {%0,%1,%2,%3,%4,%5,%6,%7,%8,%9,%10,%11,%12,%13,%14,%15,%16,%17,%18,%19,%20,%21,%22,%23,%24,%25,%26,%27,%28,%29,%30,%31,%32,%33,%34,%35,%36,%37,%38,%39,%40,%41,%42,%43,%44,%45,%46,%47}, {%48,%49,%50,%51}, %52, p, 1, 1, 1;\n}\n"
    : "+f"(d[0]),"+f"(d[1]),"+f"(d[2]),"+f"(d[3]),"+f"(d[4]),"+f"(d[5]),"+f"(d[6]),"+f"(d[7]),"+f"(d[8]),"+f"(d[9]),"+f"(d[10]),"+f"(d[11]),"+f"(d[12]),"+f"(d[13]),"+f"(d[14]),"+f"(d[15]),"+f"(d[16]),"+f"(d[17]),"+f"(d[18]),"+f"(d[19]),"+f"(d[20]),"+f"(d[21]),"+f"(d[22]),"+f"(d[23]),"+f"(d[24]),"+f"(d[25]),"+f"(d[26]),"+f"(d[27]),"+f"(d[28]),"+f"(d[29]),"+f"(d[30]),"+f"(d[31]),"+f"(d[32]),"+f"(d[33]),"+f"(d[34]),"+f"(d[35]),"+f"(d[36]),"+f"(d[37]),"+f"(d[38]),"+f"(d[39]),"+f"(d[40]),"+f"(d[41]),"+f"(d[42]),"+f"(d[43]),"+f"(d[44]),"+f"(d[45]),"+f"(d[46]),"+f"(d[47]) : "r"(a0), "r"(a1), "r"(a2), "r"(a3), "l"(db), "n"(SC));
}

constexpr uint32_t SBC = 1024;
constexpr int ROWB = 2 * 224 * 384;
constexpr int KS = 832;
constexpr int KSLOT = 22 * KS;
constexpr int SM_X0 = 0;
constexpr int SM_X1 = 18432;
constexpr int SM_X2 = SM_X1 + 24576;
constexpr int SM_W = SM_X2 + 24576;
constexpr int SM_K = SM_W + 55296;
constexpr int SM_V = SM_K + 2 * KSLOT;
constexpr int SM_Q = SM_V + 22 * 1536;
constexpr int SM_RPB = SM_Q + 24576;
constexpr int SM_BAR = SM_RPB + 768;
constexpr int SM_A_TOTAL = SM_BAR + 128;
enum { B_FULL = 0, B_EMPTY = 3, B_QRDY = 6, B_KRDY, B_VRDY, B_QKISS, B_PVISS, B_KFREE, B_VFREE, B_COUNT };

__device__ int g_flags[784 * 4];

struct GemmCtx {
  uint32_t sb;
  uint32_t kC, vC, qC;
  uint32_t kH, vH;
  int rC, rH;
  int cpC, cpH;
  bool lead, hvalid;
  int warp;
};

__device__ __forceinline__ uint32_t k_rowoff(int r) { return (((r + 3) >> 3) & 1) * KSLOT + ((r + 3) & 7) * 16; }
__device__ __forceinline__ uint32_t v_rowoff(int r, int cp) {
  int i = (r + 3) & 7, pos = (((r + 3) >> 3) ^ (i == 7) ^ cp) & 1;
  return (i >> 2) * 768 + (2 * (i & 3) + pos) * 16;
}
template <int STRIDE> __device__ __forceinline__ void dump12(uint32_t a, const uint32_t (&r)[12]) {
#pragma unroll
  for (int j = 0; j < 3; j++) stsm4(a + j * 2 * STRIDE, r[4 * j], r[4 * j + 1], r[4 * j + 2], r[4 * j + 3]);
}
template <int N> __device__ __forceinline__ void pack12(uint32_t (&r)[12], const float (&d)[N], int off) {
#pragma unroll
  for (int j = 0; j < 12; j++) r[j] = pack2(d[off + 2 * j], d[off + 2 * j + 1]);
}
template <int XS> __device__ __forceinline__ void issue_core(float (&d)[72]) {
  constexpr uint64_t da = mkdesc(SBC + XS, 16, 1024, 1), db = mkdesc(SBC + SM_W, 128, 3072, 0);
  wg_fence();
  wg_ss144<0>(d, da, db);
#pragma unroll
  for (int k = 1; k < 12; k++) wg_ss144<1>(d, da + (k >> 2) * 512 + (k & 3) * 2, db + k * 16);
  wg_commit();
}
__device__ __forceinline__ void issue_halo(float (&d)[48]) {
  constexpr uint64_t da = mkdesc(SBC + SM_X0, 16, 1024, 1), db = mkdesc(SBC + SM_W, 128, 3072, 0);
  wg_fence();
  wg_ss96<0>(d, da, db);
#pragma unroll
  for (int k = 1; k < 12; k++) wg_ss96<1>(d, da + (k >> 2) * 384 + (k & 3) * 2, db + k * 16);
  wg_commit();
}
__device__ __forceinline__ void release_stage(const GemmCtx& c, int st, uint32_t bytes) {
  if (c.lead) {
    if (c.warp == 0) mbar_expect(c.sb + SM_BAR + (B_FULL + st) * 8, bytes);
    mbar_arrive_remote(c.sb + SM_BAR + (B_EMPTY + st) * 8, st);
  }
}
__device__ __forceinline__ void publish(const GemmCtx& c, int bar, bool on) {
  fence_async();
  __syncwarp();
  if (c.lead && on) mbar_arrive(c.sb + SM_BAR + bar * 8);
}

template <bool FIRST, bool LAST>
__device__ __forceinline__ void gemm_period(const GemmCtx& c, int p, uint32_t (&hk)[12], uint32_t (&hv)[12]) {
  const uint32_t bar = c.sb + SM_BAR;
  const uint32_t pa = (p - 1) & 1;
  const bool w = p >= 1;
  float C[72];
  uint32_t pk[12], pv[12], pq[12];
  if (!FIRST) {
    if (w) mbar_wait(bar + B_QKISS * 8, pa);
    mbar_wait(bar + (B_FULL + 1) * 8, p & 1);
    issue_core<SM_X1>(C);
    if (w) mbar_wait(bar + B_KFREE * 8, pa);
  }
  const int rh = 8 * p + 4 + c.rH;
  if (c.hvalid) dump12<128>(c.kH + k_rowoff(rh), hk);
  if (!FIRST) {
    wg_wait<0>(); pin(C);
    if (!LAST) release_stage(c, 1, 24576);
    pack12(pk, C, 0);
    pack12(pv, C, 24);
    pack12(pq, C, 48);
  }
  if (!LAST) {
    if (w) mbar_wait(bar + B_PVISS * 8, pa);
    mbar_wait(bar + (B_FULL + 2) * 8, (p + 1) & 1);
    issue_core<SM_X2>(C);
  }
  int r = 8 * p + 4 + c.rC;
  if (!FIRST) {
    dump12<256>(c.qC ^ ((r & 15) * 16), pq);
    __syncwarp();
    if (c.lead) mbar_arrive(bar + B_QRDY * 8);
    dump12<128>(c.kC + k_rowoff(r), pk);
    if (LAST) publish(c, B_KRDY, true);
    if (w) mbar_wait(bar + B_VFREE * 8, pa);
  }
  if (c.hvalid) dump12<128>(c.vH + v_rowoff(rh, c.cpH), hv);
  if (!FIRST) dump12<128>(c.vC + v_rowoff(r, c.cpC), pv);
  if (LAST) { publish(c, B_VRDY, true); return; }
  float H[48];
  mbar_wait(bar + (B_FULL + 0) * 8, p & 1);
  issue_halo(H);
  wg_wait<1>(); pin(C);
  if (p < 12) release_stage(c, 2, 24576);
  r += 4;
  pack12(pk, C, 0);
  dump12<128>(c.kC + k_rowoff(r), pk);
  publish(c, B_KRDY, !FIRST);
  pack12(pv, C, 24);
  dump12<128>(c.vC + v_rowoff(r, c.cpC), pv);
  publish(c, B_VRDY, !FIRST);
  pack12(pq, C, 48);
  dump12<256>(c.qC ^ ((r & 15) * 16), pq);
  wg_wait<0>(); pin(H);
  if (p < 12) release_stage(c, 0, 18432);
  pack12(hk, H, 0);
  pack12(hv, H, 24);
}

template <int U, int L, bool BORDER>
__device__ __forceinline__ void softmax_tile(const float (&SA)[56], const float (&SB)[56], const float (&T)[14], bool b0, bool b1,
                                             uint32_t ra0, uint32_t ra1, int qcu, uint32_t (&P)[28], float& sumU, float& sumL) {
  const float cs = 0.14433756729740643f * 1.4426950408889634f;
  float lu[14], ll[14];
#pragma unroll
  for (int j = 0; j < 7; j++) {
    float tu0, tu1, tl0, tl1;
    if (BORDER) {
      tu0 = lds_f32(ra0 + (U + j + 3 - qcu) * 4); tu1 = lds_f32(ra1 + (U + j + 3 - qcu) * 4);
      tl0 = lds_f32(ra0 + (L + j + 2 - qcu) * 4); tl1 = lds_f32(ra1 + (L + j + 2 - qcu) * 4);
    } else { tu0 = tl0 = T[2 * j]; tu1 = tl1 = T[2 * j + 1]; }
    lu[2 * j]     = fmaf(b0 ? SB[4 * (U + j)]     : SA[4 * (U + j)],     cs, tu0);
    lu[2 * j + 1] = fmaf(b1 ? SB[4 * (U + j) + 1] : SA[4 * (U + j) + 1], cs, tu1);
    ll[2 * j]     = fmaf(b0 ? SB[4 * (L + j) + 2] : SA[4 * (L + j) + 2], cs, tl0);
    ll[2 * j + 1] = fmaf(b1 ? SB[4 * (L + j) + 3] : SA[4 * (L + j) + 3], cs, tl1);
  }
  float mu = lu[0], ml = ll[0], mu2 = lu[1], ml2 = ll[1];
#pragma unroll
  for (int j = 1; j < 7; j++) { mu = fmaxf(mu, lu[2 * j]); mu2 = fmaxf(mu2, lu[2 * j + 1]); ml = fmaxf(ml, ll[2 * j]); ml2 = fmaxf(ml2, ll[2 * j + 1]); }
  mu = fmaxf(mu, mu2); ml = fmaxf(ml, ml2);
  mu = fmaxf(mu, __shfl_xor_sync(0xffffffffu, mu, 1)); ml = fmaxf(ml, __shfl_xor_sync(0xffffffffu, ml, 1));
  mu = fmaxf(mu, __shfl_xor_sync(0xffffffffu, mu, 2)); ml = fmaxf(ml, __shfl_xor_sync(0xffffffffu, ml, 2));
  float su = 0.f, sl = 0.f, su2 = 0.f, sl2 = 0.f;
#pragma unroll
  for (int c = 0; c < 14; c++) {
    const int iu = (c >> 1) * 4 + (c & 1) * 2;
    if (c >= U && c < U + 7) {
      float e0 = ex2(lu[2 * (c - U)] - mu), e1 = ex2(lu[2 * (c - U) + 1] - mu);
      su += e0; su2 += e1; P[iu] = pack2(e0, e1);
    } else P[iu] = 0u;
    if (c >= L && c < L + 7) {
      float e0 = ex2(ll[2 * (c - L)] - ml), e1 = ex2(ll[2 * (c - L) + 1] - ml);
      sl += e0; sl2 += e1; P[iu + 1] = pack2(e0, e1);
    } else P[iu + 1] = 0u;
  }
  sumU = su + su2; sumL = sl + sl2;
}

__global__ void __cluster_dims__(4, 1, 1) __launch_bounds__(512, 1)
na_attn_kernel(const __grid_constant__ CUtensorMap mapC, const __grid_constant__ CUtensorMap mapH,
               const __nv_bfloat16* __restrict__ wqkv, const __nv_bfloat16* __restrict__ rpb, __nv_bfloat16* __restrict__ out) {
  extern __shared__ __align__(1024) uint8_t smem_raw[];
  const uint32_t sb = smem_u32(smem_raw);
  if ((sb & 0x3FFFF) != SBC) return;
  const uint32_t bar = sb + SM_BAR;
  const int tid = threadIdx.x, lane = tid & 31;
  const int warp = __shfl_sync(0xffffffffu, tid >> 5, 0);
  const int head = blockIdx.x & 3, cl = blockIdx.x >> 2;
  const int par = cl / 7, strip = cl - par * 7, ph = par >> 1, pw = par & 1;

  if (tid == 0) {
    for (int i = 0; i < 3; i++) { mbar_init(bar + (B_FULL + i) * 8, 1); mbar_init(bar + (B_EMPTY + i) * 8, 16); }
    mbar_init(bar + B_QRDY * 8, 4); mbar_init(bar + B_KRDY * 8, 4); mbar_init(bar + B_VRDY * 8, 4);
    mbar_init(bar + B_QKISS * 8, 8); mbar_init(bar + B_PVISS * 8, 8); mbar_init(bar + B_KFREE * 8, 8); mbar_init(bar + B_VFREE * 8, 8);
    mbar_expect(bar + (B_FULL + 0) * 8, 18432); mbar_expect(bar + (B_FULL + 1) * 8, 24576); mbar_expect(bar + (B_FULL + 2) * 8, 24576);
    asm volatile("fence.mbarrier_init.release.cluster;" ::: "memory");
  }
  asm volatile("barrier.cluster.arrive.release.aligned;" ::: "memory");
  {
    uint4 wv[7];
#pragma unroll
    for (int i = 0; i < 7; i++) {
      int pc = tid + i * 512;
      int kb = pc / 144, rem = pc - kb * 144, ng = rem >> 3, k = kb * 8 + (rem & 7);
      int part = ng / 6, col = ((part + 1) % 3) * 192 + head * 48 + (ng - part * 6) * 8;
      if (pc < 3456) wv[i] = __ldg(reinterpret_cast<const uint4*>(wqkv + k * 576 + col));
    }
    for (int i = tid; i < (2 * KSLOT + 22 * 1536) / 16; i += 512)
      asm volatile("st.shared.v4.b32 [%0], {%1,%1,%1,%1};" ::"r"(sb + SM_K + i * 16), "r"(0) : "memory");
    if (tid < 182) {
      float v = tid < 169 ? __bfloat162float(rpb[head * 169 + tid]) * 1.4426950408889634f : -INFINITY;
      asm volatile("st.shared.f32 [%0], %1;" ::"r"(sb + SM_RPB + tid * 4), "f"(v) : "memory");
    }
    asm volatile("barrier.cluster.wait.acquire.aligned;" ::: "memory");
    if (warp == 12 && lane == 0 && head < 3) {
      const uint32_t fb = bar + (B_FULL + head) * 8;
      if (head == 0) {
        int cc = strip == 0 ? 16 : (strip == 6 ? 74 : strip * 16 - 3), sd = strip == 0 ? -1 : (strip == 6 ? 1 : 0);
        asm volatile("cp.async.bulk.tensor.5d.shared::cluster.global.mbarrier::complete_tx::bytes.multicast::cluster [%0], [%1, {%3,%4,%5,%6,%7}], [%2], %8;"
                     ::"r"(sb + SM_X0), "l"(&mapH), "r"(fb), "r"(0), "r"(-4), "r"(ph * 112 + cc), "r"(sd), "r"(pw * 3), "h"((uint16_t)15) : "memory");
      } else {
        asm volatile("cp.async.bulk.tensor.4d.shared::cluster.global.mbarrier::complete_tx::bytes.multicast::cluster [%0], [%1, {%3,%4,%5,%6}], [%2], %7;"
                     ::"r"(sb + (head == 1 ? SM_X1 : SM_X2)), "l"(&mapC), "r"(fb), "r"(0), "r"(head == 1 ? 4 : 0), "r"(ph * 112 + strip * 16), "r"(pw * 3), "h"((uint16_t)15) : "memory");
      }
    }
#pragma unroll
    for (int i = 0; i < 7; i++) {
      int pc = tid + i * 512;
      int kb = pc / 144, rem = pc - kb * 144, ng = rem >> 3, k = kb * 8 + (rem & 7);
      if (pc < 3456) asm volatile("st.shared.v4.b32 [%0], {%1,%2,%3,%4};" ::"r"(sb + SM_W + ng * 3072 + k * 16), "r"(wv[i].x), "r"(wv[i].y), "r"(wv[i].z), "r"(wv[i].w) : "memory");
    }
    fence_async();
    __syncthreads();
  }

  if (warp >= 12) {
    asm volatile("setmaxnreg.dec.sync.aligned.u32 24;");
    if (warp == 12 && lane == 0 && head < 3) {
      const uint32_t fb = bar + (B_FULL + head) * 8, eb = bar + (B_EMPTY + head) * 8;
      if (head == 0) {
        int cc = ph * 112 + (strip == 0 ? 16 : (strip == 6 ? 74 : strip * 16 - 3)), sd = strip == 0 ? -1 : (strip == 6 ? 1 : 0);
        for (int n = 1; n < 15; n++) {
          asm volatile("cp.async.bulk.prefetch.tensor.5d.L2.global [%0, {%1,%2,%3,%4,%5}];" ::"l"(&mapH), "r"(0), "r"(8 * n - 4), "r"(cc), "r"(sd), "r"(pw * 3) : "memory");
          mbar_wait_cluster(eb, (n - 1) & 1);
          asm volatile("cp.async.bulk.tensor.5d.shared::cluster.global.mbarrier::complete_tx::bytes.multicast::cluster [%0], [%1, {%3,%4,%5,%6,%7}], [%2], %8;"
                       ::"r"(sb + SM_X0), "l"(&mapH), "r"(fb), "r"(0), "r"(8 * n - 4), "r"(cc), "r"(sd), "r"(pw * 3), "h"((uint16_t)15) : "memory");
        }
      } else {
        const int r0 = head == 1 ? 4 : 0, cc = ph * 112 + strip * 16;
        const uint32_t dst = sb + (head == 1 ? SM_X1 : SM_X2);
        for (int n = 1; n < 14; n++) {
          asm volatile("cp.async.bulk.prefetch.tensor.4d.L2.global [%0, {%1,%2,%3,%4}];" ::"l"(&mapC), "r"(0), "r"(8 * n + r0), "r"(cc), "r"(pw * 3) : "memory");
          mbar_wait_cluster(eb, (n - 1) & 1);
          asm volatile("cp.async.bulk.tensor.4d.shared::cluster.global.mbarrier::complete_tx::bytes.multicast::cluster [%0], [%1, {%3,%4,%5,%6}], [%2], %7;"
                       ::"r"(dst), "l"(&mapC), "r"(fb), "r"(0), "r"(8 * n + r0), "r"(cc), "r"(pw * 3), "h"((uint16_t)15) : "memory");
        }
      }
    }
    __syncwarp();
    cluster_sync();
  } else if (warp >= 8) {
    asm volatile("setmaxnreg.inc.sync.aligned.u32 168;");
    GemmCtx c;
    c.sb = sb; c.warp = warp - 8; c.lead = lane == 0;
    const int tk = c.warp * 16 + (lane & 15), hi = lane >> 4;
    { int col = tk >> 2; c.rC = tk & 3; c.cpC = (col + 3) & 1;
      c.kC = sb + SM_K + (col + 3) * KS + hi * 128;
      c.vC = sb + SM_V + (col + 3) * 1536 + hi * 128;
      c.qC = sb + SM_Q + col * 1536 + hi * 256 + (col & 1) * 64; }
    { int ci = tk >> 3, kc = ci < 3 ? ci : ci + 16; c.rH = tk & 7; c.cpH = kc & 1; c.hvalid = c.warp < 3;
      c.kH = sb + SM_K + kc * KS + hi * 128;
      c.vH = sb + SM_V + kc * 1536 + hi * 128; }
    uint32_t hk[12], hv[12];
    {
      float H[48];
      mbar_wait(bar + (B_FULL + 0) * 8, 0);
      issue_halo(H);
      wg_wait<0>(); pin(H);
      release_stage(c, 0, 18432);
      pack12(hk, H, 0);
      pack12(hv, H, 24);
    }
    gemm_period<true, false>(c, -1, hk, hv);
#pragma unroll 1
    for (int p = 0; p < 13; p++) gemm_period<false, false>(c, p, hk, hv);
    gemm_period<false, true>(c, 13, hk, hv);
    cluster_sync();
  } else {
    asm volatile("setmaxnreg.inc.sync.aligned.u32 160;");
    const int j = warp >> 2, w = warp & 3, g = lane >> 2, t = lane & 3;
    int variant = w;
    if (strip == 0 && j == 0 && w < 2) variant = 4;
    if (strip == 6 && j == 1 && w >= 2) variant = 5;
    const uint32_t qa = sb + SM_Q + (8 * j + 2 * w + ((lane >> 3) & 1)) * 1536 + (lane >> 4) * 256 + (((lane & 7) * 16) ^ (((lane >> 3) & 1) * 64));
    const uint64_t dK = mkdesc(SBC + SM_K, 128, KS, 0) + j * (8 * KS / 16);
    const uint64_t dV = mkdesc(SBC + SM_V, 768, 128, 0) + j * (8 * 1536 / 16);
    uint8_t* op = reinterpret_cast<uint8_t*>(out) + (size_t)(ph * 224 + 2 * (strip * 16 + 8 * j + 2 * w + (head >> 1)) + pw) * 384 + (size_t)(4 * (head & 1)) * ROWB;
    int* flag = g_flags + (cl * 2 + j) * 4 + w;
    float T[14];
    bool b0 = false, b1 = false;
    uint32_t ra0 = 0, ra1 = 0, meta = 0;
#pragma unroll 1
    for (int b = 0; b < 14; b++) {
      const uint32_t pa = b & 1;
      if (b <= 1 || b == 13) {
        const int sw = b == 0 ? max(g, 3) : (b == 13 ? min(g, 4) : g);
        const int i0 = 2 * t, i1 = 2 * t + 1;
        b0 = i0 <= sw - 2; b1 = i1 <= sw - 2;
        const int m = (sw + 7) & 7;
        ra0 = sb + SM_RPB + (i0 == m ? 13 : i0 + (b0 ? 8 : 0) - g + 3) * 52;
        ra1 = sb + SM_RPB + (i1 == m ? 13 : i1 + (b1 ? 8 : 0) - g + 3) * 52;
#pragma unroll
        for (int jj = 0; jj < 7; jj++) { T[2 * jj] = lds_f32(ra0 + (jj + 3) * 4); T[2 * jj + 1] = lds_f32(ra1 + (jj + 3) * 4); }
        uint32_t m16 = 0x8888u;
#pragma unroll
        for (int i = 0; i < 8; i++) m16 |= (uint32_t)(((i <= sw - 2) ^ (i == 7) ^ t ^ b) & 1) << (2 * i);
        meta = m16 | (m16 << 16);
      } else meta ^= 0x55555555u;
      uint32_t q[12];
      mbar_wait(bar + B_QRDY * 8, pa);
#pragma unroll
      for (int k = 0; k < 3; k++) ldsm4(qa + pa * 128 + k * 512, q[4 * k], q[4 * k + 1], q[4 * k + 2], q[4 * k + 3]);
      float SA[56], SB[56];
      const uint64_t dA = dK + pa * (KSLOT >> 4), dB = dK + (pa ^ 1) * (KSLOT >> 4);
      mbar_wait(bar + B_KRDY * 8, pa);
      wg_fence();
      wg_rs112<0>(SA, q[0], q[1], q[2], q[3], dA);
      wg_rs112<0>(SB, q[0], q[1], q[2], q[3], dB);
      wg_rs112<1>(SA, q[4], q[5], q[6], q[7], dA + 16);
      wg_rs112<1>(SB, q[4], q[5], q[6], q[7], dB + 16);
      wg_rs112<1>(SA, q[8], q[9], q[10], q[11], dA + 32);
      wg_rs112<1>(SB, q[8], q[9], q[10], q[11], dB + 32);
      wg_commit();
      if (lane == 0) mbar_arrive(bar + B_QKISS * 8);
      wg_wait<0>(); pin(SA); pin(SB);
      if (lane == 0) mbar_arrive(bar + B_KFREE * 8);
      uint32_t P[28];
      float su, sl;
      switch (variant) {
        case 0: softmax_tile<0, 1, false>(SA, SB, T, b0, b1, ra0, ra1, 0, P, su, sl); break;
        case 1: softmax_tile<2, 3, false>(SA, SB, T, b0, b1, ra0, ra1, 0, P, su, sl); break;
        case 2: softmax_tile<4, 5, false>(SA, SB, T, b0, b1, ra0, ra1, 0, P, su, sl); break;
        case 3: softmax_tile<6, 7, false>(SA, SB, T, b0, b1, ra0, ra1, 0, P, su, sl); break;
        case 4: softmax_tile<3, 3, true>(SA, SB, T, b0, b1, ra0, ra1, 2 * w, P, su, sl); break;
        default: softmax_tile<4, 4, true>(SA, SB, T, b0, b1, ra0, ra1, 2 * w, P, su, sl); break;
      }
      float O[24];
      mbar_wait(bar + B_VRDY * 8, pa);
      wg_fence();
      wg_sp48<0>(O, P[0], P[1], P[2], P[3], dV, meta);
#pragma unroll
      for (int s = 1; s < 7; s++) wg_sp48<1>(O, P[4 * s], P[4 * s + 1], P[4 * s + 2], P[4 * s + 3], dV + s * 192, meta);
      wg_commit();
      if (lane == 0) mbar_arrive(bar + B_PVISS * 8);
      su += __shfl_xor_sync(0xffffffffu, su, 1); sl += __shfl_xor_sync(0xffffffffu, sl, 1);
      su += __shfl_xor_sync(0xffffffffu, su, 2); sl += __shfl_xor_sync(0xffffffffu, sl, 2);
      const float ru = __fdividef(1.f, su), rl = __fdividef(1.f, sl);
      wg_wait<0>(); pin(O);
      if (lane == 0) mbar_arrive(bar + B_VFREE * 8);
#pragma unroll
      for (int i = 0; i < 3; i++) {
        const int pc = i * 32 + lane, tk = pc / 24;
        uint4 v;
        v.x = pack2(O[8 * i] * ru, O[8 * i + 1] * ru);     v.y = pack2(O[8 * i + 2] * rl, O[8 * i + 3] * rl);
        v.z = pack2(O[8 * i + 4] * ru, O[8 * i + 5] * ru); v.w = pack2(O[8 * i + 6] * rl, O[8 * i + 7] * rl);
        *reinterpret_cast<uint4*>(op + (size_t)(8 * b + tk) * ROWB + (pc - tk * 24) * 16) = v;
      }
      __syncwarp();
      if (lane == 0) asm volatile("red.release.gpu.global.add.s32 [%0], 1;" ::"l"(flag + b * 224) : "memory");
    }
    cluster_sync();
  }
}

constexpr int SM_B_W = 0;
constexpr int SM_B_ST = 73728;
constexpr int SM_B_TOTAL = SM_B_ST + 16 * 6144;

__global__ void __launch_bounds__(512, 1)
na_proj_kernel(const __grid_constant__ CUtensorMap mapO, const __nv_bfloat16* __restrict__ wo, __nv_bfloat16* out) {
  extern __shared__ __align__(1024) uint8_t smem_raw[];
  const uint32_t sb = smem_u32(smem_raw);
  if ((sb & 0x3FFFF) != SBC) return;
  const int tid = threadIdx.x, lane = tid & 31;
  const int warp = __shfl_sync(0xffffffffu, tid >> 5, 0);
  {
    uint4 wv[9];
#pragma unroll
    for (int i = 0; i < 9; i++) {
      int pc = tid + i * 512, kb = pc / 192, rem = pc - kb * 192;
      wv[i] = __ldg(reinterpret_cast<const uint4*>(wo + (kb * 8 + (rem & 7)) * 192 + (rem >> 3) * 8));
    }
#pragma unroll
    for (int i = 0; i < 9; i++) {
      int pc = tid + i * 512, kb = pc / 192, rem = pc - kb * 192;
      asm volatile("st.shared.v4.b32 [%0], {%1,%2,%3,%4};" ::"r"(sb + SM_B_W + (rem >> 3) * 3072 + (kb * 8 + (rem & 7)) * 16), "r"(wv[i].x), "r"(wv[i].y), "r"(wv[i].z), "r"(wv[i].w) : "memory");
    }
    fence_async();
    __syncthreads();
  }
  const int w = warp & 3;
  constexpr uint64_t db = mkdesc(SBC + SM_B_W, 128, 3072, 0);
  const uint32_t st = sb + SM_B_ST + warp * 6144;
  const uint32_t sta = st + (lane & 15) * 128 + (((lane >> 4) ^ (lane & 7)) * 16);
  uint32_t off[3];
#pragma unroll
  for (int i = 0; i < 3; i++) { int pc = i * 32 + lane, tk = pc / 24; off[i] = tk * ROWB + (pc - tk * 24) * 16; }
  const int nw = gridDim.x * 4;
#pragma unroll 1
  for (int n = (warp >> 2) * gridDim.x + blockIdx.x; n < 784; n += nw) {
    const int b = n / 56, rem = n - b * 56, cl = rem >> 1, j = rem & 1;
    const int par = cl / 7, strip = cl - par * 7, ph = par >> 1, pw = par & 1;
    const int col = strip * 16 + 8 * j + 2 * w;
    if (lane == 0) {
      int* f = g_flags + n * 4 + w;
      int v; uint32_t it = 0;
      do { asm volatile("ld.acquire.gpu.global.s32 %0, [%1];" : "=r"(v) : "l"(f) : "memory"); } while (v < 4 && ++it < SPIN_LIMIT);
      *f = 0;
    }
    __syncwarp();
    const uint8_t* ip = reinterpret_cast<const uint8_t*>(out) + (size_t)(ph * 224 + 2 * col + pw) * 384 + (size_t)(8 * b) * ROWB;
    uint32_t a[48];
#pragma unroll
    for (int h = 0; h < 4; h++)
#pragma unroll
      for (int i = 0; i < 3; i++)
        asm volatile("ld.global.cg.v4.b32 {%0,%1,%2,%3}, [%4];"
                     : "=r"(a[12 * h + 4 * i]), "=r"(a[12 * h + 4 * i + 1]), "=r"(a[12 * h + 4 * i + 2]), "=r"(a[12 * h + 4 * i + 3])
                     : "l"(ip + off[i] + (h & 1) * 4 * ROWB + (h >> 1) * 768) : "memory");
    if (lane == 0) asm volatile("cp.async.bulk.wait_group.read 0;" ::: "memory");
    __syncwarp();
#pragma unroll
    for (int hf = 0; hf < 2; hf++) {
      float D[48];
      wg_fence();
      wg_rs96<0>(D, a[0], a[1], a[2], a[3], db + hf * (12 * 3072 / 16));
#pragma unroll
      for (int k = 1; k < 12; k++) wg_rs96<1>(D, a[4 * k], a[4 * k + 1], a[4 * k + 2], a[4 * k + 3], db + hf * (12 * 3072 / 16) + k * 16);
      wg_commit();
      wg_wait<0>(); pin(D);
#pragma unroll
      for (int q = 0; q < 6; q++) {
        const int qq = hf * 6 + q;
        stsm4((sta ^ ((qq & 3) * 32)) + (qq >> 2) * 2048,
              pack2(D[8 * q], D[8 * q + 1]), pack2(D[8 * q + 2], D[8 * q + 3]), pack2(D[8 * q + 4], D[8 * q + 5]), pack2(D[8 * q + 6], D[8 * q + 7]));
      }
    }
    fence_async();
    __syncwarp();
    if (lane == 0) {
      asm volatile("cp.async.bulk.tensor.4d.global.shared::cta.bulk_group [%0, {%2,%3,%4,%5}], [%1];"
                   ::"l"(&mapO), "r"(st), "r"(0), "r"(8 * b), "r"(ph * 112 + col), "r"(pw * 3) : "memory");
      asm volatile("cp.async.bulk.commit_group;" ::: "memory");
    }
  }
  if (lane == 0) asm volatile("cp.async.bulk.wait_group 0;" ::: "memory");
}

typedef CUresult (*EncodeFn)(CUtensorMap*, CUtensorMapDataType, cuuint32_t, void*, const cuuint64_t*, const cuuint64_t*, const cuuint32_t*,
                             const cuuint32_t*, CUtensorMapInterleave, CUtensorMapSwizzle, CUtensorMapL2promotion, CUtensorMapFloatOOBfill);

extern "C" void kernel_launch(void* const* d_in, const int* in_sizes, int n_in, void* d_out, int out_size) {
  const __nv_bfloat16* x = (const __nv_bfloat16*)d_in[0];
  const __nv_bfloat16* wqkv = (const __nv_bfloat16*)d_in[1];
  const __nv_bfloat16* wo = (const __nv_bfloat16*)d_in[2];
  const __nv_bfloat16* rpb = (const __nv_bfloat16*)d_in[3];
  __nv_bfloat16* out = (__nv_bfloat16*)d_out;

  static EncodeFn enc = nullptr;
  if (!enc) {
    void* fn = nullptr; cudaDriverEntryPointQueryResult qr;
    cudaGetDriverEntryPoint("cuTensorMapEncodeTiled", &fn, cudaEnableDefault, &qr);
    enc = (EncodeFn)fn;
    cudaFuncSetAttribute(na_attn_kernel, cudaFuncAttributeMaxDynamicSharedMemorySize, SM_A_TOTAL);
    cudaFuncSetAttribute(na_proj_kernel, cudaFuncAttributeMaxDynamicSharedMemorySize, SM_B_TOTAL);
  }
  CUtensorMap mC, mH, mO;
  const cuuint32_t ones[5] = {1, 1, 1, 1, 1};
  {
    cuuint64_t dim[4] = {64, 112, 224, 6}, str[3] = {(cuuint64_t)ROWB, 768, 128};
    cuuint32_t box[4] = {64, 4, 16, 3}, boxo[4] = {64, 8, 2, 3};
    enc(&mC, CU_TENSOR_MAP_DATA_TYPE_BFLOAT16, 4, (void*)x, dim, str, box, ones, CU_TENSOR_MAP_INTERLEAVE_NONE, CU_TENSOR_MAP_SWIZZLE_128B,
        CU_TENSOR_MAP_L2_PROMOTION_L2_128B, CU_TENSOR_MAP_FLOAT_OOB_FILL_NONE);
    enc(&mO, CU_TENSOR_MAP_DATA_TYPE_BFLOAT16, 4, (void*)out, dim, str, boxo, ones, CU_TENSOR_MAP_INTERLEAVE_NONE, CU_TENSOR_MAP_SWIZZLE_128B,
        CU_TENSOR_MAP_L2_PROMOTION_NONE, CU_TENSOR_MAP_FLOAT_OOB_FILL_NONE);
  }
  {
    cuuint64_t dim[5] = {64, 112, 224, 2, 6}, str[4] = {(cuuint64_t)ROWB, 768, 19 * 768, 128};
    cuuint32_t box[5] = {64, 8, 3, 2, 3};
    enc(&mH, CU_TENSOR_MAP_DATA_TYPE_BFLOAT16, 5, (void*)x, dim, str, box, ones, CU_TENSOR_MAP_INTERLEAVE_NONE, CU_TENSOR_MAP_SWIZZLE_128B,
        CU_TENSOR_MAP_L2_PROMOTION_L2_128B, CU_TENSOR_MAP_FLOAT_OOB_FILL_NONE);
  }
  na_attn_kernel<<<112, 512, SM_A_TOTAL>>>(mC, mH, wqkv, rpb, out);
  na_proj_kernel<<<132, 512, SM_B_TOTAL>>>(mO, wo, out);
}
```

```cpp
#include <cuda_runtime.h>
#include <cuda_bf16.h>
#include <cuda.h>
#include <stdint.h>

#define SPIN_LIMIT (1u << 18)

__device__ __forceinline__ uint32_t smem_u32(const void* p) { return (uint32_t)__cvta_generic_to_shared(p); }
__device__ __forceinline__ void wg_fence() { asm volatile("wgmma.fence.sync.aligned;" ::: "memory"); }
__device__ __forceinline__ void wg_commit() { asm volatile("wgmma.commit_group.sync.aligned;" ::: "memory"); }
template <int N> __device__ __forceinline__ void wg_wait() { asm volatile("wgmma.wait_group.sync.aligned %0;" ::"n"(N) : "memory"); }
template <int N> __device__ __forceinline__ void pin(float (&d)[N]) {
#pragma unroll
  for (int i = 0; i < N; i++) asm volatile("" : "+f"(d[i])::"memory");
}
__host__ __device__ constexpr uint64_t mkdesc(uint32_t addr, uint32_t lbo, uint32_t sbo, uint32_t sw) {
  return (uint64_t)((addr & 0x3FFFF) >> 4) | ((uint64_t)(lbo >> 4) << 16) | ((uint64_t)(sbo >> 4) << 32) | ((uint64_t)sw << 62);
}
__device__ __forceinline__ void mbar_init(uint32_t bar, uint32_t cnt) { asm volatile("mbarrier.init.shared::cta.b64 [%0], %1;" ::"r"(bar), "r"(cnt) : "memory"); }
__device__ __forceinline__ void mbar_arrive(uint32_t bar) { asm volatile("mbarrier.arrive.shared::cta.b64 _, [%0];" ::"r"(bar) : "memory"); }
__device__ __forceinline__ void mbar_arrive_elect(uint32_t bar) {
  asm volatile("{\n.reg .pred p;\nelect.sync _|p, 0xffffffff;\n@p mbarrier.arrive.shared::cta.b64 _, [%0];\n}" ::"r"(bar) : "memory");
}
__device__ __forceinline__ void mbar_expect(uint32_t bar, uint32_t bytes) { asm volatile("mbarrier.arrive.expect_tx.shared::cta.b64 _, [%0], %1;" ::"r"(bar), "r"(bytes) : "memory"); }
__device__ __forceinline__ void mbar_arrive_remote(uint32_t bar, uint32_t cta) {
  asm volatile("{\n.reg .b32 ra;\nmapa.shared::cluster.u32 ra, %0, %1;\nmbarrier.arrive.shared::cluster.b64 _, [ra];\n}" ::"r"(bar), "r"(cta) : "memory");
}
__device__ __forceinline__ void mbar_wait(uint32_t bar, uint32_t parity) {
  asm volatile("{\n.reg .pred p;\n.reg .b32 n;\nmov.b32 n, 0;\nWL:\nmbarrier.try_wait.parity.shared::cta.b64 p, [%0], %1;\n@p bra WD;\n"
               "add.u32 n, n, 1;\nsetp.lt.u32 p, n, 65536;\n@p bra WL;\nWD:\n}" ::"r"(bar), "r"(parity) : "memory");
}
__device__ __forceinline__ void fence_async() { asm volatile("fence.proxy.async.shared::cta;" ::: "memory"); }
__device__ __forceinline__ void cluster_sync() {
  asm volatile("barrier.cluster.arrive.relaxed.aligned;\nbarrier.cluster.wait.aligned;" ::: "memory");
}
__device__ __forceinline__ uint32_t pack2(float lo, float hi) {
  uint32_t r; asm("cvt.rn.bf16x2.f32 %0, %1, %2;" : "=r"(r) : "f"(hi), "f"(lo)); return r;
}
__device__ __forceinline__ void stsm4(uint32_t a, uint32_t r0, uint32_t r1, uint32_t r2, uint32_t r3) {
  asm volatile("stmatrix.sync.aligned.m8n8.x4.shared.b16 [%0], {%1,%2,%3,%4};" ::"r"(a), "r"(r0), "r"(r1), "r"(r2), "r"(r3) : "memory");
}
__device__ __forceinline__ void ldsm4(uint32_t a, uint32_t& r0, uint32_t& r1, uint32_t& r2, uint32_t& r3) {
  asm volatile("ldmatrix.sync.aligned.m8n8.x4.shared.b16 {%0,%1,%2,%3}, [%4];" : "=r"(r0), "=r"(r1), "=r"(r2), "=r"(r3) : "r"(a) : "memory");
}
__device__ __forceinline__ float lds_f32(uint32_t a) { float v; asm volatile("ld.shared.f32 %0, [%1];" : "=f"(v) : "r"(a)); return v; }
__device__ __forceinline__ float ex2(float x) { float y; asm("ex2.approx.ftz.f32 %0, %1;" : "=f"(y) : "f"(x)); return y; }

template<int SC> __device__ __forceinline__ void wg_ss144(float (&d)[72], uint64_t da, uint64_t db) {
  asm volatile("{\n.reg .pred p;\nsetp.ne.b32 p, %74, 0;\nwgmma.mma_async.sync.aligned.m64n144k16.f32.bf16.bf16 {%0,%1,%2,%3,%4,%5,%6,%7,%8,%9,%10,%11,%12,%13,%14,%15,%16,%17,%18,%19,%20,%21,%22,%23,%24,%25,%26,%27,%28,%29,%30,%31,%32,%33,%34,%35,%36,%37,%38,%39,%40,%41,%42,%43,%44,%45,%46,%47,%48,%49,%50,%51,%52,%53,%54,%55,%56,%57,%58,%59,%60,%61,%62,%63,%64,%65,%66,%67,%68,%69,%70,%71}, %72, %73, p, 1, 1, 0, 1;\n}\n"
    : "+f"(d[0]),"+f"(d[1]),"+f"(d[2]),"+f"(d[3]),"+f"(d[4]),"+f"(d[5]),"+f"(d[6]),"+f"(d[7]),"+f"(d[8]),"+f"(d[9]),"+f"(d[10]),"+f"(d[11]),"+f"(d[12]),"+f"(d[13]),"+f"(d[14]),"+f"(d[15]),"+f"(d[16]),"+f"(d[17]),"+f"(d[18]),"+f"(d[19]),"+f"(d[20]),"+f"(d[21]),"+f"(d[22]),"+f"(d[23]),"+f"(d[24]),"+f"(d[25]),"+f"(d[26]),"+f"(d[27]),"+f"(d[28]),"+f"(d[29]),"+f"(d[30]),"+f"(d[31]),"+f"(d[32]),"+f"(d[33]),"+f"(d[34]),"+f"(d[35]),"+f"(d[36]),"+f"(d[37]),"+f"(d[38]),"+f"(d[39]),"+f"(d[40]),"+f"(d[41]),"+f"(d[42]),"+f"(d[43]),"+f"(d[44]),"+f"(d[45]),"+f"(d[46]),"+f"(d[47]),"+f"(d[48]),"+f"(d[49]),"+f"(d[50]),"+f"(d[51]),"+f"(d[52]),"+f"(d[53]),"+f"(d[54]),"+f"(d[55]),"+f"(d[56]),"+f"(d[57]),"+f"(d[58]),"+f"(d[59]),"+f"(d[60]),"+f"(d[61]),"+f"(d[62]),"+f"(d[63]),"+f"(d[64]),"+f"(d[65]),"+f"(d[66]),"+f"(d[67]),"+f"(d[68]),"+f"(d[69]),"+f"(d[70]),"+f"(d[71]) : "l"(da), "l"(db), "n"(SC));
}
template<int SC> __device__ __forceinline__ void wg_ss96(float (&d)[48], uint64_t da, uint64_t db) {
  asm volatile("{\n.reg .pred p;\nsetp.ne.b32 p, %50, 0;\nwgmma.mma_async.sync.aligned.m64n96k16.f32.bf16.bf16 {%0,%1,%2,%3,%4,%5,%6,%7,%8,%9,%10,%11,%12,%13,%14,%15,%16,%17,%18,%19,%20,%21,%22,%23,%24,%25,%26,%27,%28,%29,%30,%31,%32,%33,%34,%35,%36,%37,%38,%39,%40,%41,%42,%43,%44,%45,%46,%47}, %48, %49, p, 1, 1, 0, 1;\n}\n"
    : "+f"(d[0]),"+f"(d[1]),"+f"(d[2]),"+f"(d[3]),"+f"(d[4]),"+f"(d[5]),"+f"(d[6]),"+f"(d[7]),"+f"(d[8]),"+f"(d[9]),"+f"(d[10]),"+f"(d[11]),"+f"(d[12]),"+f"(d[13]),"+f"(d[14]),"+f"(d[15]),"+f"(d[16]),"+f"(d[17]),"+f"(d[18]),"+f"(d[19]),"+f"(d[20]),"+f"(d[21]),"+f"(d[22]),"+f"(d[23]),"+f"(d[24]),"+f"(d[25]),"+f"(d[26]),"+f"(d[27]),"+f"(d[28]),"+f"(d[29]),"+f"(d[30]),"+f"(d[31]),"+f"(d[32]),"+f"(d[33]),"+f"(d[34]),"+f"(d[35]),"+f"(d[36]),"+f"(d[37]),"+f"(d[38]),"+f"(d[39]),"+f"(d[40]),"+f"(d[41]),"+f"(d[42]),"+f"(d[43]),"+f"(d[44]),"+f"(d[45]),"+f"(d[46]),"+f"(d[47]) : "l"(da), "l"(db), "n"(SC));
}
template<int SC> __device__ __forceinline__ void wg_rs112(float (&d)[56], uint32_t a0, uint32_t a1, uint32_t a2, uint32_t a3, uint64_t db) {
  asm volatile("{\n.reg .pred p;\nsetp.ne.b32 p, %61, 0;\nwgmma.mma_async.sync.aligned.m64n112k16.f32.bf16.bf16 {%0,%1,%2,%3,%4,%5,%6,%7,%8,%9,%10,%11,%12,%13,%14,%15,%16,%17,%18,%19,%20,%21,%22,%23,%24,%25,%26,%27,%28,%29,%30,%31,%32,%33,%34,%35,%36,%37,%38,%39,%40,%41,%42,%43,%44,%45,%46,%47,%48,%49,%50,%51,%52,%53,%54,%55}, {%56,%57,%58,%59}, %60, p, 1, 1, 0;\n}\n"
    : "+f"(d[0]),"+f"(d[1]),"+f"(d[2]),"+f"(d[3]),"+f"(d[4]),"+f"(d[5]),"+f"(d[6]),"+f"(d[7]),"+f"(d[8]),"+f"(d[9]),"+f"(d[10]),"+f"(d[11]),"+f"(d[12]),"+f"(d[13]),"+f"(d[14]),"+f"(d[15]),"+f"(d[16]),"+f"(d[17]),"+f"(d[18]),"+f"(d[19]),"+f"(d[20]),"+f"(d[21]),"+f"(d[22]),"+f"(d[23]),"+f"(d[24]),"+f"(d[25]),"+f"(d[26]),"+f"(d[27]),"+f"(d[28]),"+f"(d[29]),"+f"(d[30]),"+f"(d[31]),"+f"(d[32]),"+f"(d[33]),"+f"(d[34]),"+f"(d[35]),"+f"(d[36]),"+f"(d[37]),"+f"(d[38]),"+f"(d[39]),"+f"(d[40]),"+f"(d[41]),"+f"(d[42]),"+f"(d[43]),"+f"(d[44]),"+f"(d[45]),"+f"(d[46]),"+f"(d[47]),"+f"(d[48]),"+f"(d[49]),"+f"(d[50]),"+f"(d[51]),"+f"(d[52]),"+f"(d[53]),"+f"(d[54]),"+f"(d[55]) : "r"(a0), "r"(a1), "r"(a2), "r"(a3), "l"(db), "n"(SC));
}
template<int SC> __device__ __forceinline__ void wg_sp48(float (&d)[24], uint32_t a0, uint32_t a1, uint32_t a2, uint32_t a3, uint64_t db, uint32_t meta) {
  asm volatile("{\n.reg .pred p;\nsetp.ne.b32 p, %30, 0;\nwgmma.mma_async.sp.sync.aligned.m64n48k32.f32.bf16.bf16 {%0,%1,%2,%3,%4,%5,%6,%7,%8,%9,%10,%11,%12,%13,%14,%15,%16,%17,%18,%19,%20,%21,%22,%23}, {%24,%25,%26,%27}, %28, %29, 0, p, 1, 1, 1;\n}\n"
    : "+f"(d[0]),"+f"(d[1]),"+f"(d[2]),"+f"(d[3]),"+f"(d[4]),"+f"(d[5]),"+f"(d[6]),"+f"(d[7]),"+f"(d[8]),"+f"(d[9]),"+f"(d[10]),"+f"(d[11]),"+f"(d[12]),"+f"(d[13]),"+f"(d[14]),"+f"(d[15]),"+f"(d[16]),"+f"(d[17]),"+f"(d[18]),"+f"(d[19]),"+f"(d[20]),"+f"(d[21]),"+f"(d[22]),"+f"(d[23]) : "r"(a0), "r"(a1), "r"(a2), "r"(a3), "l"(db), "r"(meta), "n"(SC));
}
template<int SC> __device__ __forceinline__ void wg_rs96(float (&d)[48], uint32_t a0, uint32_t a1, uint32_t a2, uint32_t a3, uint64_t db) {
  asm volatile("{\n.reg .pred p;\nsetp.ne.b32 p, %53, 0;\nwgmma.mma_async.sync.aligned.m64n96k16.f32.bf16.bf16 {%0,%1,%2,%3,%4,%5,%6,%7,%8,%9,%10,%11,%12,%13,%14,%15,%16,%17,%18,%19,%20,%21,%22,%23,%24,%25,%26,%27,%28,%29,%30,%31,%32,%33,%34,%35,%36,%37,%38,%39,%40,%41,%42,%43,%44,%45,%46,%47}, {%48,%49,%50,%51}, %52, p, 1, 1, 1;\n}\n"
    : "+f"(d[0]),"+f"(d[1]),"+f"(d[2]),"+f"(d[3]),"+f"(d[4]),"+f"(d[5]),"+f"(d[6]),"+f"(d[7]),"+f"(d[8]),"+f"(d[9]),"+f"(d[10]),"+f"(d[11]),"+f"(d[12]),"+f"(d[13]),"+f"(d[14]),"+f"(d[15]),"+f"(d[16]),"+f"(d[17]),"+f"(d[18]),"+f"(d[19]),"+f"(d[20]),"+f"(d[21]),"+f"(d[22]),"+f"(d[23]),"+f"(d[24]),"+f"(d[25]),"+f"(d[26]),"+f"(d[27]),"+f"(d[28]),"+f"(d[29]),"+f"(d[30]),"+f"(d[31]),"+f"(d[32]),"+f"(d[33]),"+f"(d[34]),"+f"(d[35]),"+f"(d[36]),"+f"(d[37]),"+f"(d[38]),"+f"(d[39]),"+f"(d[40]),"+f"(d[41]),"+f"(d[42]),"+f"(d[43]),"+f"(d[44]),"+f"(d[45]),"+f"(d[46]),"+f"(d[47]) : "r"(a0), "r"(a1), "r"(a2), "r"(a3), "l"(db), "n"(SC));
}

constexpr uint32_t SBC = 1024;
constexpr int ROWB = 2 * 224 * 384;
constexpr int KS = 832;
constexpr int KSLOT = 22 * KS;
constexpr int SM_X0 = 0;
constexpr int SM_X1 = 18432;
constexpr int SM_X2 = SM_X1 + 24576;
constexpr int SM_W = SM_X2 + 24576;
constexpr int SM_K = SM_W + 55296;
constexpr int SM_V = SM_K + 2 * KSLOT;
constexpr int SM_Q = SM_V + 22 * 1536;
constexpr int SM_RPB = SM_Q + 24576;
constexpr int SM_BAR = SM_RPB + 768;
constexpr int SM_A_TOTAL = SM_BAR + 512;
enum { B_FULL = 0, B_EMPTY = 3, B_QRDY = 6, B_KRDY, B_VRDY, B_QKISS, B_PVISS, B_KFREE, B_VFREE, B_ODONE, B_Q0 = B_ODONE + 28, B_COUNT };

__device__ int g_flags[784 * 4];

#define TR(role, it, k)

struct GemmCtx {
  uint32_t sb;
  uint32_t kC, vC, qC;
  uint32_t kH, vH;
  int rC, rH;
  int cpC, cpH;
  bool lead, hvalid;
  int warp;
};

__device__ __forceinline__ uint32_t k_rowoff(int r) { return (((r + 3) >> 3) & 1) * KSLOT + ((r + 3) & 7) * 16; }
__device__ __forceinline__ uint32_t v_rowoff(int r, int cp) {
  int i = (r + 3) & 7, pos = (((r + 3) >> 3) ^ (i == 7) ^ cp) & 1;
  return (i >> 2) * 768 + (2 * (i & 3) + pos) * 16;
}
template <int STRIDE> __device__ __forceinline__ void dump12(uint32_t a, const uint32_t (&r)[12]) {
#pragma unroll
  for (int j = 0; j < 3; j++) stsm4(a + j * 2 * STRIDE, r[4 * j], r[4 * j + 1], r[4 * j + 2], r[4 * j + 3]);
}
template <int N> __device__ __forceinline__ void pack12(uint32_t (&r)[12], const float (&d)[N], int off) {
#pragma unroll
  for (int j = 0; j < 12; j++) r[j] = pack2(d[off + 2 * j], d[off + 2 * j + 1]);
}
template <int XS> __device__ __forceinline__ void issue_core(float (&d)[72]) {
  constexpr uint64_t da = mkdesc(SBC + XS, 16, 1024, 1), db = mkdesc(SBC + SM_W, 128, 3072, 0);
  wg_fence();
  wg_ss144<0>(d, da, db);
#pragma unroll
  for (int k = 1; k < 12; k++) wg_ss144<1>(d, da + (k >> 2) * 512 + (k & 3) * 2, db + k * 16);
  wg_commit();
}
__device__ __forceinline__ void issue_halo(float (&d)[48]) {
  constexpr uint64_t da = mkdesc(SBC + SM_X0, 16, 1024, 1), db = mkdesc(SBC + SM_W, 128, 3072, 0);
  wg_fence();
  wg_ss96<0>(d, da, db);
#pragma unroll
  for (int k = 1; k < 12; k++) wg_ss96<1>(d, da + (k >> 2) * 384 + (k & 3) * 2, db + k * 16);
  wg_commit();
}
__device__ __forceinline__ void release_stage(const GemmCtx& c, int st, uint32_t bytes) {
  if (c.lead) {
    if (c.warp == 0) mbar_expect(c.sb + SM_BAR + (B_FULL + st) * 8, bytes);
    mbar_arrive_remote(c.sb + SM_BAR + (B_EMPTY + st) * 8, st);
  }
}
__device__ __forceinline__ void publish(const GemmCtx& c, int bar) {
  fence_async();
  __syncwarp();
  mbar_arrive_elect(c.sb + SM_BAR + bar * 8);
}

template <bool FIRST, bool LAST>
__device__ __forceinline__ void gemm_iter(const GemmCtx& c, int b, uint32_t (&pk)[12], uint32_t (&pv)[12], uint32_t (&pq)[12]) {
  const uint32_t bar = c.sb + SM_BAR;
  const uint32_t pa = b & 1;
  const bool w = b >= 0;
  const int r1 = 8 * b + 12 + c.rC, rh = 8 * b + 12 + c.rH;
  float H[48], C[72];
  uint32_t hk[12], hv[12], pv2[12];
  TR(2, b + 2, 0);
  if (!FIRST) {
    dump12<256>(c.qC ^ ((r1 & 15) * 16), pq);
    __syncwarp();
    mbar_arrive_elect(bar + (w ? B_QRDY : B_Q0) * 8);
  }
  mbar_wait(bar + (B_FULL + 0) * 8, pa);
  if (!LAST && !FIRST) mbar_wait(bar + (B_FULL + 2) * 8, pa);
  TR(2, b + 2, 1);
  if (w) mbar_wait(bar + B_QKISS * 8, pa);
  TR(2, b + 2, 2);
  issue_halo(H);
  TR(2, b + 2, 3);
  if (!FIRST) {
    if (w) mbar_wait(bar + B_KFREE * 8, pa);
    dump12<128>(c.kC + k_rowoff(r1), pk);
  }
  TR(2, b + 2, 4);
  if (!LAST) {
    if (FIRST) mbar_wait(bar + (B_FULL + 2) * 8, pa);
    issue_core<SM_X2>(C);
    TR(2, b + 2, 5);
    wg_wait<1>(); pin(H);
    release_stage(c, 0, 18432);
  } else { wg_wait<0>(); pin(H); }
  pack12(hk, H, 0);
  pack12(hv, H, 24);
  if (c.hvalid) dump12<128>(c.kH + k_rowoff(rh), hk);
  if (!LAST) {
    mbar_wait(bar + (B_FULL + 1) * 8, pa);
    TR(2, b + 2, 6);
    wg_wait<0>(); pin(C);
    TR(2, b + 2, 7);
    if (b < 11) release_stage(c, 2, 24576);
    pack12(pk, C, 0);
    pack12(pv2, C, 24);
    pack12(pq, C, 48);
    if (w) mbar_wait(bar + B_PVISS * 8, pa);
    TR(2, b + 2, 8);
    issue_core<SM_X1>(C);
    TR(2, b + 2, 9);
    dump12<128>(c.kC + k_rowoff(r1 + 4), pk);
  }
  if (!FIRST) publish(c, B_KRDY);
  TR(2, b + 2, 10);
  if (w) mbar_wait(bar + B_VFREE * 8, pa);
  if (!FIRST) dump12<128>(c.vC + v_rowoff(r1, c.cpC), pv);
  if (c.hvalid) dump12<128>(c.vH + v_rowoff(rh, c.cpH), hv);
  if (!LAST) dump12<128>(c.vC + v_rowoff(r1 + 4, c.cpC), pv2);
  if (!FIRST) publish(c, B_VRDY);
  TR(2, b + 2, 11);
  if (LAST) return;
  dump12<256>(c.qC ^ (((r1 + 4) & 15) * 16), pq);
  TR(2, b + 2, 12);
  wg_wait<0>(); pin(C);
  TR(2, b + 2, 13);
  if (b < 11) release_stage(c, 1, 24576);
  pack12(pk, C, 0);
  pack12(pv, C, 24);
  pack12(pq, C, 48);
}

template <int U, int L, bool BORDER>
__device__ __forceinline__ void softmax_tile(const float (&SA)[56], const float (&SB)[56], const float (&T)[14], bool b0, bool b1,
                                             uint32_t ra0, uint32_t ra1, int qcu, uint32_t (&P)[28], float& sumU, float& sumL) {
  const float cs = 0.14433756729740643f * 1.4426950408889634f;
  float lu[14], ll[14];
#pragma unroll
  for (int j = 0; j < 7; j++) {
    float tu0, tu1, tl0, tl1;
    if (BORDER) {
      tu0 = lds_f32(ra0 + (U + j + 3 - qcu) * 4); tu1 = lds_f32(ra1 + (U + j + 3 - qcu) * 4);
      tl0 = lds_f32(ra0 + (L + j + 2 - qcu) * 4); tl1 = lds_f32(ra1 + (L + j + 2 - qcu) * 4);
    } else { tu0 = tl0 = T[2 * j]; tu1 = tl1 = T[2 * j + 1]; }
    lu[2 * j]     = fmaf(b0 ? SB[4 * (U + j)]     : SA[4 * (U + j)],     cs, tu0);
    lu[2 * j + 1] = fmaf(b1 ? SB[4 * (U + j) + 1] : SA[4 * (U + j) + 1], cs, tu1);
    ll[2 * j]     = fmaf(b0 ? SB[4 * (L + j) + 2] : SA[4 * (L + j) + 2], cs, tl0);
    ll[2 * j + 1] = fmaf(b1 ? SB[4 * (L + j) + 3] : SA[4 * (L + j) + 3], cs, tl1);
  }
  float mu = lu[0], ml = ll[0], mu2 = lu[1], ml2 = ll[1];
#pragma unroll
  for (int j = 1; j < 7; j++) { mu = fmaxf(mu, lu[2 * j]); mu2 = fmaxf(mu2, lu[2 * j + 1]); ml = fmaxf(ml, ll[2 * j]); ml2 = fmaxf(ml2, ll[2 * j + 1]); }
  mu = fmaxf(mu, mu2); ml = fmaxf(ml, ml2);
  mu = fmaxf(mu, __shfl_xor_sync(0xffffffffu, mu, 1)); ml = fmaxf(ml, __shfl_xor_sync(0xffffffffu, ml, 1));
  mu = fmaxf(mu, __shfl_xor_sync(0xffffffffu, mu, 2)); ml = fmaxf(ml, __shfl_xor_sync(0xffffffffu, ml, 2));
  float su = 0.f, sl = 0.f, su2 = 0.f, sl2 = 0.f;
#pragma unroll
  for (int c = 0; c < 14; c++) {
    const int iu = (c >> 1) * 4 + (c & 1) * 2;
    if (c >= U && c < U + 7) {
      float e0 = ex2(lu[2 * (c - U)] - mu), e1 = ex2(lu[2 * (c - U) + 1] - mu);
      su += e0; su2 += e1; P[iu] = pack2(e0, e1);
    } else P[iu] = 0u;
    if (c >= L && c < L + 7) {
      float e0 = ex2(ll[2 * (c - L)] - ml), e1 = ex2(ll[2 * (c - L) + 1] - ml);
      sl += e0; sl2 += e1; P[iu + 1] = pack2(e0, e1);
    } else P[iu + 1] = 0u;
  }
  sumU = su + su2; sumL = sl + sl2;
}

__global__ void __cluster_dims__(4, 1, 1) __launch_bounds__(512, 1)
na_attn_kernel(const __grid_constant__ CUtensorMap mapC, const __grid_constant__ CUtensorMap mapH,
               const __nv_bfloat16* __restrict__ wqkv, const __nv_bfloat16* __restrict__ rpb, __nv_bfloat16* __restrict__ out) {
  extern __shared__ __align__(1024) uint8_t smem_raw[];
  const uint32_t sb = smem_u32(smem_raw);
  if ((sb & 0x3FFFF) != SBC) return;
  const uint32_t bar = sb + SM_BAR;
  TR(3, 0, threadIdx.x >> 7);
  const int tid = threadIdx.x, lane = tid & 31;
  const int warp = __shfl_sync(0xffffffffu, tid >> 5, 0);
  const int head = blockIdx.x & 3, cl = blockIdx.x >> 2;
  const int par = cl / 7, strip = cl - par * 7, ph = par >> 1, pw = par & 1;

  if (warp == 1 && lane < 29) mbar_init(bar + (B_ODONE + lane) * 8, 4);
  if (tid == 0) {
    for (int i = 0; i < 3; i++) { mbar_init(bar + (B_FULL + i) * 8, 1); mbar_init(bar + (B_EMPTY + i) * 8, 16); }
    mbar_init(bar + B_QRDY * 8, 4); mbar_init(bar + B_KRDY * 8, 4); mbar_init(bar + B_VRDY * 8, 4);
    mbar_init(bar + B_QKISS * 8, 8); mbar_init(bar + B_PVISS * 8, 8); mbar_init(bar + B_KFREE * 8, 8); mbar_init(bar + B_VFREE * 8, 8);
    mbar_expect(bar + (B_FULL + 0) * 8, 18432); mbar_expect(bar + (B_FULL + 1) * 8, 24576); mbar_expect(bar + (B_FULL + 2) * 8, 24576);
    asm volatile("fence.mbarrier_init.release.cluster;" ::: "memory");
  }
  __syncwarp();
  asm volatile("barrier.cluster.arrive.relaxed.aligned;" ::: "memory");
  {
    uint4 wv[7];
#pragma unroll
    for (int i = 0; i < 7; i++) {
      int pc = tid + i * 512;
      int kb = pc / 144, rem = pc - kb * 144, ng = rem >> 3, k = kb * 8 + (rem & 7);
      int part = ng / 6, col = ((part + 1) % 3) * 192 + head * 48 + (ng - part * 6) * 8;
      if (pc < 3456) wv[i] = __ldg(reinterpret_cast<const uint4*>(wqkv + k * 576 + col));
    }
    for (int i = tid; i < (2 * KSLOT + 22 * 1536) / 16; i += 512)
      asm volatile("st.shared.v4.b32 [%0], {%1,%1,%1,%1};" ::"r"(sb + SM_K + i * 16), "r"(0) : "memory");
    if (tid < 182) {
      float v = tid < 169 ? __bfloat162float(rpb[head * 169 + tid]) * 1.4426950408889634f : -INFINITY;
      asm volatile("st.shared.f32 [%0], %1;" ::"r"(sb + SM_RPB + tid * 4), "f"(v) : "memory");
    }
    asm volatile("barrier.cluster.wait.aligned;" ::: "memory");
    if (warp == 12 && lane == 0 && head < 3) {
      const uint32_t fb = bar + (B_FULL + head) * 8;
      if (head == 0) {
        int cc = strip == 0 ? 16 : (strip == 6 ? 74 : strip * 16 - 3), sd = strip == 0 ? -1 : (strip == 6 ? 1 : 0);
        asm volatile("cp.async.bulk.tensor.5d.shared::cluster.global.mbarrier::complete_tx::bytes.multicast::cluster [%0], [%1, {%3,%4,%5,%6,%7}], [%2], %8;"
                     ::"r"(sb + SM_X0), "l"(&mapH), "r"(fb), "r"(0), "r"(-4), "r"(ph * 112 + cc), "r"(sd), "r"(pw * 3), "h"((uint16_t)15) : "memory");
      } else {
        asm volatile("cp.async.bulk.tensor.4d.shared::cluster.global.mbarrier::complete_tx::bytes.multicast::cluster [%0], [%1, {%3,%4,%5,%6}], [%2], %7;"
                     ::"r"(sb + (head == 1 ? SM_X1 : SM_X2)), "l"(&mapC), "r"(fb), "r"(0), "r"(head == 1 ? 4 : 0), "r"(ph * 112 + strip * 16), "r"(pw * 3), "h"((uint16_t)15) : "memory");
      }
    }
#pragma unroll
    for (int i = 0; i < 7; i++) {
      int pc = tid + i * 512;
      int kb = pc / 144, rem = pc - kb * 144, ng = rem >> 3, k = kb * 8 + (rem & 7);
      if (pc < 3456) asm volatile("st.shared.v4.b32 [%0], {%1,%2,%3,%4};" ::"r"(sb + SM_W + ng * 3072 + k * 16), "r"(wv[i].x), "r"(wv[i].y), "r"(wv[i].z), "r"(wv[i].w) : "memory");
    }
    fence_async();
    __syncthreads();
    TR(3, 1, threadIdx.x >> 7);
  }

  if (warp >= 12) {
    asm volatile("setmaxnreg.dec.sync.aligned.u32 24;");
    if (warp == 12 && lane == 0 && head < 3) {
      const uint32_t fb = bar + (B_FULL + head) * 8, eb = bar + (B_EMPTY + head) * 8;
      if (head == 0) {
        int cc = ph * 112 + (strip == 0 ? 16 : (strip == 6 ? 74 : strip * 16 - 3)), sd = strip == 0 ? -1 : (strip == 6 ? 1 : 0);
#pragma unroll 1
        for (int n = 1; n < 15; n++) {
          asm volatile("cp.async.bulk.prefetch.tensor.5d.L2.global [%0, {%1,%2,%3,%4,%5}];" ::"l"(&mapH), "r"(0), "r"(8 * n - 4), "r"(cc), "r"(sd), "r"(pw * 3) : "memory");
          mbar_wait(eb, (n - 1) & 1);
          asm volatile("cp.async.bulk.tensor.5d.shared::cluster.global.mbarrier::complete_tx::bytes.multicast::cluster [%0], [%1, {%3,%4,%5,%6,%7}], [%2], %8;"
                       ::"r"(sb + SM_X0), "l"(&mapH), "r"(fb), "r"(0), "r"(8 * n - 4), "r"(cc), "r"(sd), "r"(pw * 3), "h"((uint16_t)15) : "memory");
        }
      } else {
        const int r0 = head == 1 ? 4 : 0, cc = ph * 112 + strip * 16;
        const uint32_t dst = sb + (head == 1 ? SM_X1 : SM_X2);
#pragma unroll 1
        for (int n = 1; n < 14; n++) {
          asm volatile("cp.async.bulk.prefetch.tensor.4d.L2.global [%0, {%1,%2,%3,%4}];" ::"l"(&mapC), "r"(0), "r"(8 * n + r0), "r"(cc), "r"(pw * 3) : "memory");
          mbar_wait(eb, (n - 1) & 1);
          asm volatile("cp.async.bulk.tensor.4d.shared::cluster.global.mbarrier::complete_tx::bytes.multicast::cluster [%0], [%1, {%3,%4,%5,%6}], [%2], %7;"
                       ::"r"(dst), "l"(&mapC), "r"(fb), "r"(0), "r"(8 * n + r0), "r"(cc), "r"(pw * 3), "h"((uint16_t)15) : "memory");
        }
      }
    }
    if ((warp == 13 || warp == 14) && lane < 4) {
      const int j = warp - 13;
      int* flag = g_flags + (cl * 2 + j) * 4 + lane;
#pragma unroll 1
      for (int b = 0; b < 14; b++) {
        mbar_wait(bar + (B_ODONE + 2 * b + j) * 8, 0);
        asm volatile("fence.acq_rel.gpu;\nred.relaxed.gpu.global.add.s32 [%0], 1;" ::"l"(flag + b * 224) : "memory");
      }
    }
    __syncwarp();
    cluster_sync();
  } else if (warp >= 8) {
    asm volatile("setmaxnreg.inc.sync.aligned.u32 168;");
    GemmCtx c;
    c.sb = sb; c.warp = warp - 8; c.lead = lane == 0;
    const int tk = c.warp * 16 + (lane & 15), hi = lane >> 4;
    { int col = tk >> 2; c.rC = tk & 3; c.cpC = (col + 3) & 1;
      c.kC = sb + SM_K + (col + 3) * KS + hi * 128;
      c.vC = sb + SM_V + (col + 3) * 1536 + hi * 128;
      c.qC = sb + SM_Q + col * 1536 + hi * 256 + (col & 1) * 64; }
    { int ci = tk >> 3, kc = ci < 3 ? ci : ci + 16; c.rH = tk & 7; c.cpH = kc & 1; c.hvalid = c.warp < 3;
      c.kH = sb + SM_K + kc * KS + hi * 128;
      c.vH = sb + SM_V + kc * 1536 + hi * 128; }
    uint32_t pk[12], pv[12], pq[12];
    gemm_iter<true, false>(c, -2, pk, pv, pq);
#pragma unroll 1
    for (int b = -1; b < 12; b++) gemm_iter<false, false>(c, b, pk, pv, pq);
    gemm_iter<false, true>(c, 12, pk, pv, pq);
    cluster_sync();
  } else {
    asm volatile("setmaxnreg.inc.sync.aligned.u32 160;");
    const int j = warp >> 2, w = warp & 3;
    int variant = w;
    if (strip == 0 && j == 0 && w < 2) variant = 4;
    if (strip == 6 && j == 1 && w >= 2) variant = 5;
    const uint32_t qa = sb + SM_Q + (8 * j + 2 * w + ((lane >> 3) & 1)) * 1536 + (lane >> 4) * 256 + (((lane & 7) * 16) ^ (((lane >> 3) & 1) * 64));
    const uint64_t dK = mkdesc(SBC + SM_K, 128, KS, 0) + j * (8 * KS / 16);
    const uint64_t dV = mkdesc(SBC + SM_V, 768, 128, 0) + j * (8 * 1536 / 16);
    uint8_t* op = reinterpret_cast<uint8_t*>(out) + (size_t)(ph * 224 + 2 * (strip * 16 + 8 * j + 2 * w + (head >> 1)) + pw) * 384 + (size_t)(4 * (head & 1)) * ROWB;
    uint32_t off[3];
#pragma unroll
    for (int i = 0; i < 3; i++) { const int pc = i * 32 + lane, tk = pc / 24; off[i] = tk * ROWB + (pc - tk * 24) * 16; }
    float T[14];
    bool b0 = false, b1 = false;
    uint32_t ra0 = 0, ra1 = 0, meta = 0;
    uint32_t q[12];
    mbar_wait(bar + B_Q0 * 8, 0);
#pragma unroll
    for (int k = 0; k < 3; k++) ldsm4(qa + k * 512, q[4 * k], q[4 * k + 1], q[4 * k + 2], q[4 * k + 3]);
#pragma unroll 1
    for (int b = 0; b < 14; b++) {
      const uint32_t pa = b & 1;
      if (b <= 1 || b == 13) {
        uint32_t ln; asm volatile("mov.u32 %0, %%laneid;" : "=r"(ln));
        const int g = ln >> 2, t = ln & 3;
        const int sw = b == 0 ? max(g, 3) : (b == 13 ? min(g, 4) : g);
        const int i0 = 2 * t, i1 = 2 * t + 1;
        b0 = i0 <= sw - 2; b1 = i1 <= sw - 2;
        const int m = (sw + 7) & 7;
        ra0 = sb + SM_RPB + (i0 == m ? 13 : i0 + (b0 ? 8 : 0) - g + 3) * 52;
        ra1 = sb + SM_RPB + (i1 == m ? 13 : i1 + (b1 ? 8 : 0) - g + 3) * 52;
#pragma unroll
        for (int jj = 0; jj < 7; jj++) { T[2 * jj] = lds_f32(ra0 + (jj + 3) * 4); T[2 * jj + 1] = lds_f32(ra1 + (jj + 3) * 4); }
        uint32_t m16 = 0x8888u;
#pragma unroll
        for (int i = 0; i < 8; i++) m16 |= (uint32_t)(((i <= sw - 2) ^ (i == 7) ^ t ^ b) & 1) << (2 * i);
        meta = m16 | (m16 << 16);
      } else meta ^= 0x55555555u;
      float SA[56], SB[56];
      const uint64_t dA = dK + pa * (KSLOT >> 4), dB = dK + (pa ^ 1) * (KSLOT >> 4);
      TR(j, b, 0);
      mbar_wait(bar + B_KRDY * 8, pa);
      TR(j, b, 1);
      wg_fence();
      wg_rs112<0>(SA, q[0], q[1], q[2], q[3], dA);
      wg_rs112<0>(SB, q[0], q[1], q[2], q[3], dB);
      wg_rs112<1>(SA, q[4], q[5], q[6], q[7], dA + 16);
      wg_rs112<1>(SB, q[4], q[5], q[6], q[7], dB + 16);
      wg_rs112<1>(SA, q[8], q[9], q[10], q[11], dA + 32);
      wg_rs112<1>(SB, q[8], q[9], q[10], q[11], dB + 32);
      wg_commit();
      mbar_arrive_elect(bar + B_QKISS * 8);
      TR(j, b, 2);
      wg_wait<0>(); pin(SA); pin(SB);
      mbar_arrive_elect(bar + B_KFREE * 8);
      TR(j, b, 3);
      uint32_t P[28];
      float su, sl;
      switch (variant) {
        case 0: softmax_tile<0, 1, false>(SA, SB, T, b0, b1, ra0, ra1, 0, P, su, sl); break;
        case 1: softmax_tile<2, 3, false>(SA, SB, T, b0, b1, ra0, ra1, 0, P, su, sl); break;
        case 2: softmax_tile<4, 5, false>(SA, SB, T, b0, b1, ra0, ra1, 0, P, su, sl); break;
        case 3: softmax_tile<6, 7, false>(SA, SB, T, b0, b1, ra0, ra1, 0, P, su, sl); break;
        case 4: softmax_tile<3, 3, true>(SA, SB, T, b0, b1, ra0, ra1, 2 * w, P, su, sl); break;
        default: softmax_tile<4, 4, true>(SA, SB, T, b0, b1, ra0, ra1, 2 * w, P, su, sl); break;
      }
      float O[24];
      TR(j, b, 4);
      if (b < 13) {
        mbar_wait(bar + B_QRDY * 8, pa);
#pragma unroll
        for (int k = 0; k < 3; k++) ldsm4(qa + (pa ^ 1) * 128 + k * 512, q[4 * k], q[4 * k + 1], q[4 * k + 2], q[4 * k + 3]);
      }
      su += __shfl_xor_sync(0xffffffffu, su, 1); sl += __shfl_xor_sync(0xffffffffu, sl, 1);
      mbar_wait(bar + B_VRDY * 8, pa);
      TR(j, b, 5);
      su += __shfl_xor_sync(0xffffffffu, su, 2); sl += __shfl_xor_sync(0xffffffffu, sl, 2);
      wg_fence();
      wg_sp48<0>(O, P[0], P[1], P[2], P[3], dV, meta);
#pragma unroll
      for (int s = 1; s < 7; s++) wg_sp48<1>(O, P[4 * s], P[4 * s + 1], P[4 * s + 2], P[4 * s + 3], dV + s * 192, meta);
      wg_commit();
      mbar_arrive_elect(bar + B_PVISS * 8);
      TR(j, b, 6);
      const float ru = __fdividef(1.f, su), rl = __fdividef(1.f, sl);
      wg_wait<0>(); pin(O);
      mbar_arrive_elect(bar + B_VFREE * 8);
      TR(j, b, 7);
#pragma unroll
      for (int i = 0; i < 3; i++) {
        uint4 v;
        v.x = pack2(O[8 * i] * ru, O[8 * i + 1] * ru);     v.y = pack2(O[8 * i + 2] * rl, O[8 * i + 3] * rl);
        v.z = pack2(O[8 * i + 4] * ru, O[8 * i + 5] * ru); v.w = pack2(O[8 * i + 6] * rl, O[8 * i + 7] * rl);
        *reinterpret_cast<uint4*>(op + off[i]) = v;
      }
      op += 8 * ROWB;
      __syncwarp();
      mbar_arrive_elect(bar + (B_ODONE + 2 * b + j) * 8);
      TR(j, b, 8);
    }
    cluster_sync();
  }
}

constexpr int SM_B_W = 0;
constexpr int SM_B_ST = 73728;
constexpr int SM_B_TOTAL = SM_B_ST + 16 * 6144;

__global__ void __launch_bounds__(512, 1)
na_proj_kernel(const __grid_constant__ CUtensorMap mapO, const __nv_bfloat16* __restrict__ wo, __nv_bfloat16* out) {
  extern __shared__ __align__(1024) uint8_t smem_raw[];
  const uint32_t sb = smem_u32(smem_raw);
  if ((sb & 0x3FFFF) != SBC) return;
  const int tid = threadIdx.x, lane = tid & 31;
  const int warp = __shfl_sync(0xffffffffu, tid >> 5, 0);
  {
    uint4 wv[9];
#pragma unroll
    for (int i = 0; i < 9; i++) {
      int pc = tid + i * 512, kb = pc / 192, rem = pc - kb * 192;
      wv[i] = __ldg(reinterpret_cast<const uint4*>(wo + (kb * 8 + (rem & 7)) * 192 + (rem >> 3) * 8));
    }
#pragma unroll
    for (int i = 0; i < 9; i++) {
      int pc = tid + i * 512, kb = pc / 192, rem = pc - kb * 192;
      asm volatile("st.shared.v4.b32 [%0], {%1,%2,%3,%4};" ::"r"(sb + SM_B_W + (rem >> 3) * 3072 + (kb * 8 + (rem & 7)) * 16), "r"(wv[i].x), "r"(wv[i].y), "r"(wv[i].z), "r"(wv[i].w) : "memory");
    }
    fence_async();
    __syncthreads();
  }
  const int w = warp & 3;
  constexpr uint64_t db = mkdesc(SBC + SM_B_W, 128, 3072, 0);
  const uint32_t st = sb + SM_B_ST + warp * 6144;
  const uint32_t sta = st + (lane & 15) * 128 + (((lane >> 4) ^ (lane & 7)) * 16);
  uint32_t off[3];
#pragma unroll
  for (int i = 0; i < 3; i++) { int pc = i * 32 + lane, tk = pc / 24; off[i] = tk * ROWB + (pc - tk * 24) * 16; }
  const int nw = gridDim.x * 4;
#pragma unroll 1
  for (int n = (warp >> 2) * gridDim.x + blockIdx.x; n < 784; n += nw) {
    const int b = n / 56, rem = n - b * 56, cl = rem >> 1, j = rem & 1;
    const int par = cl / 7, strip = cl - par * 7, ph = par >> 1, pw = par & 1;
    const int col = strip * 16 + 8 * j + 2 * w;
    if (lane == 0) {
      int* f = g_flags + n * 4 + w;
      int v; uint32_t it = 0;
      do { asm volatile("ld.acquire.gpu.global.s32 %0, [%1];" : "=r"(v) : "l"(f) : "memory"); } while (v < 4 && ++it < SPIN_LIMIT);
      *f = 0;
    }
    __syncwarp();
    const uint8_t* ip = reinterpret_cast<const uint8_t*>(out) + (size_t)(ph * 224 + 2 * col + pw) * 384 + (size_t)(8 * b) * ROWB;
    uint32_t a[48];
#pragma unroll
    for (int h = 0; h < 4; h++)
#pragma unroll
      for (int i = 0; i < 3; i++)
        asm volatile("ld.global.cg.v4.b32 {%0,%1,%2,%3}, [%4];"
                     : "=r"(a[12 * h + 4 * i]), "=r"(a[12 * h + 4 * i + 1]), "=r"(a[12 * h + 4 * i + 2]), "=r"(a[12 * h + 4 * i + 3])
                     : "l"(ip + off[i] + (h & 1) * 4 * ROWB + (h >> 1) * 768) : "memory");
    if (lane == 0) asm volatile("cp.async.bulk.wait_group.read 0;" ::: "memory");
    __syncwarp();
#pragma unroll
    for (int hf = 0; hf < 2; hf++) {
      float D[48];
      wg_fence();
      wg_rs96<0>(D, a[0], a[1], a[2], a[3], db + hf * (12 * 3072 / 16));
#pragma unroll
      for (int k = 1; k < 12; k++) wg_rs96<1>(D, a[4 * k], a[4 * k + 1], a[4 * k + 2], a[4 * k + 3], db + hf * (12 * 3072 / 16) + k * 16);
      wg_commit();
      wg_wait<0>(); pin(D);
#pragma unroll
      for (int q = 0; q < 6; q++) {
        const int qq = hf * 6 + q;
        stsm4((sta ^ ((qq & 3) * 32)) + (qq >> 2) * 2048,
              pack2(D[8 * q], D[8 * q + 1]), pack2(D[8 * q + 2], D[8 * q + 3]), pack2(D[8 * q + 4], D[8 * q + 5]), pack2(D[8 * q + 6], D[8 * q + 7]));
      }
    }
    fence_async();
    __syncwarp();
    if (lane == 0) {
      asm volatile("cp.async.bulk.tensor.4d.global.shared::cta.bulk_group [%0, {%2,%3,%4,%5}], [%1];"
                   ::"l"(&mapO), "r"(st), "r"(0), "r"(8 * b), "r"(ph * 112 + col), "r"(pw * 3) : "memory");
      asm volatile("cp.async.bulk.commit_group;" ::: "memory");
    }
  }
  if (lane == 0) asm volatile("cp.async.bulk.wait_group 0;" ::: "memory");
}

typedef CUresult (*EncodeFn)(CUtensorMap*, CUtensorMapDataType, cuuint32_t, void*, const cuuint64_t*, const cuuint64_t*, const cuuint32_t*,
                             const cuuint32_t*, CUtensorMapInterleave, CUtensorMapSwizzle, CUtensorMapL2promotion, CUtensorMapFloatOOBfill);

extern "C" void kernel_launch(void* const* d_in, const int* in_sizes, int n_in, void* d_out, int out_size) {
  const __nv_bfloat16* x = (const __nv_bfloat16*)d_in[0];
  const __nv_bfloat16* wqkv = (const __nv_bfloat16*)d_in[1];
  const __nv_bfloat16* wo = (const __nv_bfloat16*)d_in[2];
  const __nv_bfloat16* rpb = (const __nv_bfloat16*)d_in[3];
  __nv_bfloat16* out = (__nv_bfloat16*)d_out;

  static EncodeFn enc = nullptr;
  if (!enc) {
    void* fn = nullptr; cudaDriverEntryPointQueryResult qr;
    cudaGetDriverEntryPoint("cuTensorMapEncodeTiled", &fn, cudaEnableDefault, &qr);
    enc = (EncodeFn)fn;
    cudaFuncSetAttribute(na_attn_kernel, cudaFuncAttributeMaxDynamicSharedMemorySize, SM_A_TOTAL);
    cudaFuncSetAttribute(na_proj_kernel, cudaFuncAttributeMaxDynamicSharedMemorySize, SM_B_TOTAL);
  }
  CUtensorMap mC, mH, mO;
  const cuuint32_t ones[5] = {1, 1, 1, 1, 1};
  {
    cuuint64_t dim[4] = {64, 112, 224, 6}, str[3] = {(cuuint64_t)ROWB, 768, 128};
    cuuint32_t box[4] = {64, 4, 16, 3}, boxo[4] = {64, 8, 2, 3};
    enc(&mC, CU_TENSOR_MAP_DATA_TYPE_BFLOAT16, 4, (void*)x, dim, str, box, ones, CU_TENSOR_MAP_INTERLEAVE_NONE, CU_TENSOR_MAP_SWIZZLE_128B,
        CU_TENSOR_MAP_L2_PROMOTION_L2_128B, CU_TENSOR_MAP_FLOAT_OOB_FILL_NONE);
    enc(&mO, CU_TENSOR_MAP_DATA_TYPE_BFLOAT16, 4, (void*)out, dim, str, boxo, ones, CU_TENSOR_MAP_INTERLEAVE_NONE, CU_TENSOR_MAP_SWIZZLE_128B,
        CU_TENSOR_MAP_L2_PROMOTION_NONE, CU_TENSOR_MAP_FLOAT_OOB_FILL_NONE);
  }
  {
    cuuint64_t dim[5] = {64, 112, 224, 2, 6}, str[4] = {(cuuint64_t)ROWB, 768, 19 * 768, 128};
    cuuint32_t box[5] = {64, 8, 3, 2, 3};
    enc(&mH, CU_TENSOR_MAP_DATA_TYPE_BFLOAT16, 5, (void*)x, dim, str, box, ones, CU_TENSOR_MAP_INTERLEAVE_NONE, CU_TENSOR_MAP_SWIZZLE_128B,
        CU_TENSOR_MAP_L2_PROMOTION_L2_128B, CU_TENSOR_MAP_FLOAT_OOB_FILL_NONE);
  }
  na_attn_kernel<<<112, 512, SM_A_TOTAL>>>(mC, mH, wqkv, rpb, out);
  na_proj_kernel<<<132, 512, SM_B_TOTAL>>>(mO, wo, out);
}
```

```cpp
#include <cuda_runtime.h>
#include <cuda_bf16.h>
#include <cuda.h>
#include <stdint.h>

#define SPIN_LIMIT (1u << 18)

__device__ __forceinline__ uint32_t smem_u32(const void* p) { return (uint32_t)__cvta_generic_to_shared(p); }
__device__ __forceinline__ void wg_fence() { asm volatile("wgmma.fence.sync.aligned;" ::: "memory"); }
__device__ __forceinline__ void wg_commit() { asm volatile("wgmma.commit_group.sync.aligned;" ::: "memory"); }
template <int N> __device__ __forceinline__ void wg_wait() { asm volatile("wgmma.wait_group.sync.aligned %0;" ::"n"(N) : "memory"); }
template <int N> __device__ __forceinline__ void pin(float (&d)[N]) {
#pragma unroll
  for (int i = 0; i < N; i++) asm volatile("" : "+f"(d[i])::"memory");
}
__host__ __device__ constexpr uint64_t mkdesc(uint32_t addr, uint32_t lbo, uint32_t sbo, uint32_t sw) {
  return (uint64_t)((addr & 0x3FFFF) >> 4) | ((uint64_t)(lbo >> 4) << 16) | ((uint64_t)(sbo >> 4) << 32) | ((uint64_t)sw << 62);
}
__device__ __forceinline__ void mbar_init(uint32_t bar, uint32_t cnt) { asm volatile("mbarrier.init.shared::cta.b64 [%0], %1;" ::"r"(bar), "r"(cnt) : "memory"); }
__device__ __forceinline__ void mbar_arrive(uint32_t bar) { asm volatile("mbarrier.arrive.shared::cta.b64 _, [%0];" ::"r"(bar) : "memory"); }
__device__ __forceinline__ void mbar_arrive_elect(uint32_t bar) {
  asm volatile("{\n.reg .pred p;\nelect.sync _|p, 0xffffffff;\n@p mbarrier.arrive.shared::cta.b64 _, [%0];\n}" ::"r"(bar) : "memory");
}
__device__ __forceinline__ void mbar_expect(uint32_t bar, uint32_t bytes) { asm volatile("mbarrier.arrive.expect_tx.shared::cta.b64 _, [%0], %1;" ::"r"(bar), "r"(bytes) : "memory"); }
__device__ __forceinline__ void mbar_arrive_remote(uint32_t bar, uint32_t cta) {
  asm volatile("{\n.reg .b32 ra;\nmapa.shared::cluster.u32 ra, %0, %1;\nmbarrier.arrive.shared::cluster.b64 _, [ra];\n}" ::"r"(bar), "r"(cta) : "memory");
}
__device__ __forceinline__ void mbar_wait(uint32_t bar, uint32_t parity) {
  asm volatile("{\n.reg .pred p;\n.reg .b32 n;\nmov.b32 n, 0;\nWL:\nmbarrier.try_wait.parity.shared::cta.b64 p, [%0], %1;\n@p bra WD;\n"
               "add.u32 n, n, 1;\nsetp.lt.u32 p, n, 65536;\n@p bra WL;\nWD:\n}" ::"r"(bar), "r"(parity) : "memory");
}
__device__ __forceinline__ void fence_async() { asm volatile("fence.proxy.async.shared::cta;" ::: "memory"); }
__device__ __forceinline__ void cluster_sync() {
  asm volatile("barrier.cluster.arrive.relaxed.aligned;\nbarrier.cluster.wait.aligned;" ::: "memory");
}
__device__ __forceinline__ uint32_t pack2(float lo, float hi) {
  uint32_t r; asm("cvt.rn.bf16x2.f32 %0, %1, %2;" : "=r"(r) : "f"(hi), "f"(lo)); return r;
}
__device__ __forceinline__ void stsm4(uint32_t a, uint32_t r0, uint32_t r1, uint32_t r2, uint32_t r3) {
  asm volatile("stmatrix.sync.aligned.m8n8.x4.shared.b16 [%0], {%1,%2,%3,%4};" ::"r"(a), "r"(r0), "r"(r1), "r"(r2), "r"(r3) : "memory");
}
__device__ __forceinline__ void ldsm4(uint32_t a, uint32_t& r0, uint32_t& r1, uint32_t& r2, uint32_t& r3) {
  asm volatile("ldmatrix.sync.aligned.m8n8.x4.shared.b16 {%0,%1,%2,%3}, [%4];" : "=r"(r0), "=r"(r1), "=r"(r2), "=r"(r3) : "r"(a) : "memory");
}
__device__ __forceinline__ float lds_f32(uint32_t a) { float v; asm volatile("ld.shared.f32 %0, [%1];" : "=f"(v) : "r"(a)); return v; }
__device__ __forceinline__ float ex2(float x) { float y; asm("ex2.approx.ftz.f32 %0, %1;" : "=f"(y) : "f"(x)); return y; }

template<int SC> __device__ __forceinline__ void wg_ss144(float (&d)[72], uint64_t da, uint64_t db) {
  asm volatile("{\n.reg .pred p;\nsetp.ne.b32 p, %74, 0;\nwgmma.mma_async.sync.aligned.m64n144k16.f32.bf16.bf16 {%0,%1,%2,%3,%4,%5,%6,%7,%8,%9,%10,%11,%12,%13,%14,%15,%16,%17,%18,%19,%20,%21,%22,%23,%24,%25,%26,%27,%28,%29,%30,%31,%32,%33,%34,%35,%36,%37,%38,%39,%40,%41,%42,%43,%44,%45,%46,%47,%48,%49,%50,%51,%52,%53,%54,%55,%56,%57,%58,%59,%60,%61,%62,%63,%64,%65,%66,%67,%68,%69,%70,%71}, %72, %73, p, 1, 1, 0, 1;\n}\n"
    : "+f"(d[0]),"+f"(d[1]),"+f"(d[2]),"+f"(d[3]),"+f"(d[4]),"+f"(d[5]),"+f"(d[6]),"+f"(d[7]),"+f"(d[8]),"+f"(d[9]),"+f"(d[10]),"+f"(d[11]),"+f"(d[12]),"+f"(d[13]),"+f"(d[14]),"+f"(d[15]),"+f"(d[16]),"+f"(d[17]),"+f"(d[18]),"+f"(d[19]),"+f"(d[20]),"+f"(d[21]),"+f"(d[22]),"+f"(d[23]),"+f"(d[24]),"+f"(d[25]),"+f"(d[26]),"+f"(d[27]),"+f"(d[28]),"+f"(d[29]),"+f"(d[30]),"+f"(d[31]),"+f"(d[32]),"+f"(d[33]),"+f"(d[34]),"+f"(d[35]),"+f"(d[36]),"+f"(d[37]),"+f"(d[38]),"+f"(d[39]),"+f"(d[40]),"+f"(d[41]),"+f"(d[42]),"+f"(d[43]),"+f"(d[44]),"+f"(d[45]),"+f"(d[46]),"+f"(d[47]),"+f"(d[48]),"+f"(d[49]),"+f"(d[50]),"+f"(d[51]),"+f"(d[52]),"+f"(d[53]),"+f"(d[54]),"+f"(d[55]),"+f"(d[56]),"+f"(d[57]),"+f"(d[58]),"+f"(d[59]),"+f"(d[60]),"+f"(d[61]),"+f"(d[62]),"+f"(d[63]),"+f"(d[64]),"+f"(d[65]),"+f"(d[66]),"+f"(d[67]),"+f"(d[68]),"+f"(d[69]),"+f"(d[70]),"+f"(d[71]) : "l"(da), "l"(db), "n"(SC));
}
template<int SC> __device__ __forceinline__ void wg_ss96(float (&d)[48], uint64_t da, uint64_t db) {
  asm volatile("{\n.reg .pred p;\nsetp.ne.b32 p, %50, 0;\nwgmma.mma_async.sync.aligned.m64n96k16.f32.bf16.bf16 {%0,%1,%2,%3,%4,%5,%6,%7,%8,%9,%10,%11,%12,%13,%14,%15,%16,%17,%18,%19,%20,%21,%22,%23,%24,%25,%26,%27,%28,%29,%30,%31,%32,%33,%34,%35,%36,%37,%38,%39,%40,%41,%42,%43,%44,%45,%46,%47}, %48, %49, p, 1, 1, 0, 1;\n}\n"
    : "+f"(d[0]),"+f"(d[1]),"+f"(d[2]),"+f"(d[3]),"+f"(d[4]),"+f"(d[5]),"+f"(d[6]),"+f"(d[7]),"+f"(d[8]),"+f"(d[9]),"+f"(d[10]),"+f"(d[11]),"+f"(d[12]),"+f"(d[13]),"+f"(d[14]),"+f"(d[15]),"+f"(d[16]),"+f"(d[17]),"+f"(d[18]),"+f"(d[19]),"+f"(d[20]),"+f"(d[21]),"+f"(d[22]),"+f"(d[23]),"+f"(d[24]),"+f"(d[25]),"+f"(d[26]),"+f"(d[27]),"+f"(d[28]),"+f"(d[29]),"+f"(d[30]),"+f"(d[31]),"+f"(d[32]),"+f"(d[33]),"+f"(d[34]),"+f"(d[35]),"+f"(d[36]),"+f"(d[37]),"+f"(d[38]),"+f"(d[39]),"+f"(d[40]),"+f"(d[41]),"+f"(d[42]),"+f"(d[43]),"+f"(d[44]),"+f"(d[45]),"+f"(d[46]),"+f"(d[47]) : "l"(da), "l"(db), "n"(SC));
}
template<int SC> __device__ __forceinline__ void wg_rs112(float (&d)[56], uint32_t a0, uint32_t a1, uint32_t a2, uint32_t a3, uint64_t db) {
  asm volatile("{\n.reg .pred p;\nsetp.ne.b32 p, %61, 0;\nwgmma.mma_async.sync.aligned.m64n112k16.f32.bf16.bf16 {%0,%1,%2,%3,%4,%5,%6,%7,%8,%9,%10,%11,%12,%13,%14,%15,%16,%17,%18,%19,%20,%21,%22,%23,%24,%25,%26,%27,%28,%29,%30,%31,%32,%33,%34,%35,%36,%37,%38,%39,%40,%41,%42,%43,%44,%45,%46,%47,%48,%49,%50,%51,%52,%53,%54,%55}, {%56,%57,%58,%59}, %60, p, 1, 1, 0;\n}\n"
    : "+f"(d[0]),"+f"(d[1]),"+f"(d[2]),"+f"(d[3]),"+f"(d[4]),"+f"(d[5]),"+f"(d[6]),"+f"(d[7]),"+f"(d[8]),"+f"(d[9]),"+f"(d[10]),"+f"(d[11]),"+f"(d[12]),"+f"(d[13]),"+f"(d[14]),"+f"(d[15]),"+f"(d[16]),"+f"(d[17]),"+f"(d[18]),"+f"(d[19]),"+f"(d[20]),"+f"(d[21]),"+f"(d[22]),"+f"(d[23]),"+f"(d[24]),"+f"(d[25]),"+f"(d[26]),"+f"(d[27]),"+f"(d[28]),"+f"(d[29]),"+f"(d[30]),"+f"(d[31]),"+f"(d[32]),"+f"(d[33]),"+f"(d[34]),"+f"(d[35]),"+f"(d[36]),"+f"(d[37]),"+f"(d[38]),"+f"(d[39]),"+f"(d[40]),"+f"(d[41]),"+f"(d[42]),"+f"(d[43]),"+f"(d[44]),"+f"(d[45]),"+f"(d[46]),"+f"(d[47]),"+f"(d[48]),"+f"(d[49]),"+f"(d[50]),"+f"(d[51]),"+f"(d[52]),"+f"(d[53]),"+f"(d[54]),"+f"(d[55]) : "r"(a0), "r"(a1), "r"(a2), "r"(a3), "l"(db), "n"(SC));
}
template<int SC> __device__ __forceinline__ void wg_sp48(float (&d)[24], uint32_t a0, uint32_t a1, uint32_t a2, uint32_t a3, uint64_t db, uint32_t meta) {
  asm volatile("{\n.reg .pred p;\nsetp.ne.b32 p, %30, 0;\nwgmma.mma_async.sp.sync.aligned.m64n48k32.f32.bf16.bf16 {%0,%1,%2,%3,%4,%5,%6,%7,%8,%9,%10,%11,%12,%13,%14,%15,%16,%17,%18,%19,%20,%21,%22,%23}, {%24,%25,%26,%27}, %28, %29, 0, p, 1, 1, 1;\n}\n"
    : "+f"(d[0]),"+f"(d[1]),"+f"(d[2]),"+f"(d[3]),"+f"(d[4]),"+f"(d[5]),"+f"(d[6]),"+f"(d[7]),"+f"(d[8]),"+f"(d[9]),"+f"(d[10]),"+f"(d[11]),"+f"(d[12]),"+f"(d[13]),"+f"(d[14]),"+f"(d[15]),"+f"(d[16]),"+f"(d[17]),"+f"(d[18]),"+f"(d[19]),"+f"(d[20]),"+f"(d[21]),"+f"(d[22]),"+f"(d[23]) : "r"(a0), "r"(a1), "r"(a2), "r"(a3), "l"(db), "r"(meta), "n"(SC));
}
template<int SC> __device__ __forceinline__ void wg_rs96(float (&d)[48], uint32_t a0, uint32_t a1, uint32_t a2, uint32_t a3, uint64_t db) {
  asm volatile("{\n.reg .pred p;\nsetp.ne.b32 p, %53, 0;\nwgmma.mma_async.sync.aligned.m64n96k16.f32.bf16.bf16 {%0,%1,%2,%3,%4,%5,%6,%7,%8,%9,%10,%11,%12,%13,%14,%15,%16,%17,%18,%19,%20,%21,%22,%23,%24,%25,%26,%27,%28,%29,%30,%31,%32,%33,%34,%35,%36,%37,%38,%39,%40,%41,%42,%43,%44,%45,%46,%47}, {%48,%49,%50,%51}, %52, p, 1, 1, 1;\n}\n"
    : "+f"(d[0]),"+f"(d[1]),"+f"(d[2]),"+f"(d[3]),"+f"(d[4]),"+f"(d[5]),"+f"(d[6]),"+f"(d[7]),"+f"(d[8]),"+f"(d[9]),"+f"(d[10]),"+f"(d[11]),"+f"(d[12]),"+f"(d[13]),"+f"(d[14]),"+f"(d[15]),"+f"(d[16]),"+f"(d[17]),"+f"(d[18]),"+f"(d[19]),"+f"(d[20]),"+f"(d[21]),"+f"(d[22]),"+f"(d[23]),"+f"(d[24]),"+f"(d[25]),"+f"(d[26]),"+f"(d[27]),"+f"(d[28]),"+f"(d[29]),"+f"(d[30]),"+f"(d[31]),"+f"(d[32]),"+f"(d[33]),"+f"(d[34]),"+f"(d[35]),"+f"(d[36]),"+f"(d[37]),"+f"(d[38]),"+f"(d[39]),"+f"(d[40]),"+f"(d[41]),"+f"(d[42]),"+f"(d[43]),"+f"(d[44]),"+f"(d[45]),"+f"(d[46]),"+f"(d[47]) : "r"(a0), "r"(a1), "r"(a2), "r"(a3), "l"(db), "n"(SC));
}

constexpr uint32_t SBC = 1024;
constexpr int ROWB = 2 * 224 * 384;
constexpr int KS = 832;
constexpr int KSLOT = 22 * KS;
constexpr int SM_X0 = 0;
constexpr int SM_X1 = 18432;
constexpr int SM_X2 = SM_X1 + 24576;
constexpr int SM_W = SM_X2 + 24576;
constexpr int SM_K = SM_W + 55296;
constexpr int SM_V = SM_K + 2 * KSLOT;
constexpr int SM_Q = SM_V + 22 * 1536;
constexpr int SM_RPB = SM_Q + 24576;
constexpr int SM_BAR = SM_RPB + 768;
constexpr int SM_A_TOTAL = SM_BAR + 512;
enum { B_FULL = 0, B_EMPTY = 3, B_QRDY = 6, B_KRDY, B_VRDY, B_QKISS, B_PVISS, B_KFREE, B_VFREE, B_ODONE, B_Q0 = B_ODONE + 28, B_COUNT };

__device__ int g_flags[784 * 4];

#define TR(role, it, k)

struct GemmCtx {
  uint32_t sb;
  uint32_t kC, vC, qC;
  uint32_t kH, vH;
  int rC, rH;
  int cpC, cpH;
  bool lead, hvalid;
  int warp;
};

__device__ __forceinline__ uint32_t k_rowoff(int r) { return (((r + 3) >> 3) & 1) * KSLOT + ((r + 3) & 7) * 16; }
__device__ __forceinline__ uint32_t v_rowoff(int r, int cp) {
  int i = (r + 3) & 7, pos = (((r + 3) >> 3) ^ (i == 7) ^ cp) & 1;
  return (i >> 2) * 768 + (2 * (i & 3) + pos) * 16;
}
template <int STRIDE> __device__ __forceinline__ void dump12(uint32_t a, const uint32_t (&r)[12]) {
#pragma unroll
  for (int j = 0; j < 3; j++) stsm4(a + j * 2 * STRIDE, r[4 * j], r[4 * j + 1], r[4 * j + 2], r[4 * j + 3]);
}
template <int N> __device__ __forceinline__ void pack12(uint32_t (&r)[12], const float (&d)[N], int off) {
#pragma unroll
  for (int j = 0; j < 12; j++) r[j] = pack2(d[off + 2 * j], d[off + 2 * j + 1]);
}
template <int XS> __device__ __forceinline__ void issue_core(float (&d)[72]) {
  constexpr uint64_t da = mkdesc(SBC + XS, 16, 1024, 1), db = mkdesc(SBC + SM_W, 128, 3072, 0);
  wg_fence();
  wg_ss144<0>(d, da, db);
#pragma unroll
  for (int k = 1; k < 12; k++) wg_ss144<1>(d, da + (k >> 2) * 512 + (k & 3) * 2, db + k * 16);
  wg_commit();
}
__device__ __forceinline__ void issue_halo(float (&d)[48]) {
  constexpr uint64_t da = mkdesc(SBC + SM_X0, 16, 1024, 1), db = mkdesc(SBC + SM_W, 128, 3072, 0);
  wg_fence();
  wg_ss96<0>(d, da, db);
#pragma unroll
  for (int k = 1; k < 12; k++) wg_ss96<1>(d, da + (k >> 2) * 384 + (k & 3) * 2, db + k * 16);
  wg_commit();
}
__device__ __forceinline__ void release_stage(const GemmCtx& c, int st, uint32_t bytes) {
  if (c.lead) {
    if (c.warp == 0) mbar_expect(c.sb + SM_BAR + (B_FULL + st) * 8, bytes);
    mbar_arrive_remote(c.sb + SM_BAR + (B_EMPTY + st) * 8, st);
  }
}
__device__ __forceinline__ void publish(const GemmCtx& c, int bar) {
  fence_async();
  __syncwarp();
  mbar_arrive_elect(c.sb + SM_BAR + bar * 8);
}

template <bool FIRST, bool LAST>
__device__ __forceinline__ void gemm_iter(const GemmCtx& c, int b, uint32_t (&pk)[12], uint32_t (&pv)[12], uint32_t (&pq)[12]) {
  const uint32_t bar = c.sb + SM_BAR;
  const uint32_t pa = b & 1;
  const bool w = b >= 0;
  const int r1 = 8 * b + 12 + c.rC, rh = 8 * b + 12 + c.rH;
  float H[48], C[72];
  uint32_t hk[12], hv[12], pv2[12];
  TR(2, b + 2, 0);
  if (!FIRST) {
    dump12<256>(c.qC ^ ((r1 & 15) * 16), pq);
    __syncwarp();
    mbar_arrive_elect(bar + (w ? B_QRDY : B_Q0) * 8);
  }
  mbar_wait(bar + (B_FULL + 0) * 8, pa);
  if (!LAST && !FIRST) mbar_wait(bar + (B_FULL + 2) * 8, pa);
  TR(2, b + 2, 1);
  if (w) mbar_wait(bar + B_QKISS * 8, pa);
  TR(2, b + 2, 2);
  issue_halo(H);
  TR(2, b + 2, 3);
  if (!FIRST) {
    if (w) mbar_wait(bar + B_KFREE * 8, pa);
    dump12<128>(c.kC + k_rowoff(r1), pk);
  }
  TR(2, b + 2, 4);
  if (!LAST) {
    if (FIRST) mbar_wait(bar + (B_FULL + 2) * 8, pa);
    issue_core<SM_X2>(C);
    TR(2, b + 2, 5);
    wg_wait<1>(); pin(H);
    release_stage(c, 0, 18432);
  } else { wg_wait<0>(); pin(H); }
  pack12(hk, H, 0);
  pack12(hv, H, 24);
  if (c.hvalid) dump12<128>(c.kH + k_rowoff(rh), hk);
  if (!LAST) {
    mbar_wait(bar + (B_FULL + 1) * 8, pa);
    TR(2, b + 2, 6);
    wg_wait<0>(); pin(C);
    TR(2, b + 2, 7);
    if (b < 11) release_stage(c, 2, 24576);
    pack12(pk, C, 0);
    pack12(pv2, C, 24);
    pack12(pq, C, 48);
    if (w) mbar_wait(bar + B_PVISS * 8, pa);
    TR(2, b + 2, 8);
    issue_core<SM_X1>(C);
    TR(2, b + 2, 9);
    dump12<128>(c.kC + k_rowoff(r1 + 4), pk);
  }
  if (!FIRST) publish(c, B_KRDY);
  TR(2, b + 2, 10);
  if (w) mbar_wait(bar + B_VFREE * 8, pa);
  if (!FIRST) dump12<128>(c.vC + v_rowoff(r1, c.cpC), pv);
  if (c.hvalid) dump12<128>(c.vH + v_rowoff(rh, c.cpH), hv);
  if (!LAST) dump12<128>(c.vC + v_rowoff(r1 + 4, c.cpC), pv2);
  if (!FIRST) publish(c, B_VRDY);
  TR(2, b + 2, 11);
  if (LAST) return;
  dump12<256>(c.qC ^ (((r1 + 4) & 15) * 16), pq);
  TR(2, b + 2, 12);
  wg_wait<0>(); pin(C);
  TR(2, b + 2, 13);
  if (b < 11) release_stage(c, 1, 24576);
  pack12(pk, C, 0);
  pack12(pv, C, 24);
  pack12(pq, C, 48);
}

template <int U, int L, bool BORDER>
__device__ __forceinline__ void softmax_tile(const float (&SA)[56], const float (&SB)[56], const float (&T)[14], bool b0, bool b1,
                                             uint32_t ra0, uint32_t ra1, int qcu, uint32_t (&P)[28], float& sumU, float& sumL) {
  const float cs = 0.14433756729740643f * 1.4426950408889634f;
  float lu[14], ll[14];
#pragma unroll
  for (int j = 0; j < 7; j++) {
    float tu0, tu1, tl0, tl1;
    if (BORDER) {
      tu0 = lds_f32(ra0 + (U + j + 3 - qcu) * 4); tu1 = lds_f32(ra1 + (U + j + 3 - qcu) * 4);
      tl0 = lds_f32(ra0 + (L + j + 2 - qcu) * 4); tl1 = lds_f32(ra1 + (L + j + 2 - qcu) * 4);
    } else { tu0 = tl0 = T[2 * j]; tu1 = tl1 = T[2 * j + 1]; }
    lu[2 * j]     = fmaf(b0 ? SB[4 * (U + j)]     : SA[4 * (U + j)],     cs, tu0);
    lu[2 * j + 1] = fmaf(b1 ? SB[4 * (U + j) + 1] : SA[4 * (U + j) + 1], cs, tu1);
    ll[2 * j]     = fmaf(b0 ? SB[4 * (L + j) + 2] : SA[4 * (L + j) + 2], cs, tl0);
    ll[2 * j + 1] = fmaf(b1 ? SB[4 * (L + j) + 3] : SA[4 * (L + j) + 3], cs, tl1);
  }
  float mu = lu[0], ml = ll[0], mu2 = lu[1], ml2 = ll[1];
#pragma unroll
  for (int j = 1; j < 7; j++) { mu = fmaxf(mu, lu[2 * j]); mu2 = fmaxf(mu2, lu[2 * j + 1]); ml = fmaxf(ml, ll[2 * j]); ml2 = fmaxf(ml2, ll[2 * j + 1]); }
  mu = fmaxf(mu, mu2); ml = fmaxf(ml, ml2);
  mu = fmaxf(mu, __shfl_xor_sync(0xffffffffu, mu, 1)); ml = fmaxf(ml, __shfl_xor_sync(0xffffffffu, ml, 1));
  mu = fmaxf(mu, __shfl_xor_sync(0xffffffffu, mu, 2)); ml = fmaxf(ml, __shfl_xor_sync(0xffffffffu, ml, 2));
  float su = 0.f, sl = 0.f, su2 = 0.f, sl2 = 0.f;
#pragma unroll
  for (int c = 0; c < 14; c++) {
    const int iu = (c >> 1) * 4 + (c & 1) * 2;
    if (c >= U && c < U + 7) {
      float e0 = ex2(lu[2 * (c - U)] - mu), e1 = ex2(lu[2 * (c - U) + 1] - mu);
      su += e0; su2 += e1; P[iu] = pack2(e0, e1);
    } else P[iu] = 0u;
    if (c >= L && c < L + 7) {
      float e0 = ex2(ll[2 * (c - L)] - ml), e1 = ex2(ll[2 * (c - L) + 1] - ml);
      sl += e0; sl2 += e1; P[iu + 1] = pack2(e0, e1);
    } else P[iu + 1] = 0u;
  }
  sumU = su + su2; sumL = sl + sl2;
}

__global__ void __cluster_dims__(4, 1, 1) __launch_bounds__(512, 1)
na_attn_kernel(const __grid_constant__ CUtensorMap mapC, const __grid_constant__ CUtensorMap mapH,
               const __nv_bfloat16* __restrict__ wqkv, const __nv_bfloat16* __restrict__ rpb, __nv_bfloat16* __restrict__ out) {
  extern __shared__ __align__(1024) uint8_t smem_raw[];
  const uint32_t sb = smem_u32(smem_raw);
  if ((sb & 0x3FFFF) != SBC) return;
  const uint32_t bar = sb + SM_BAR;
  asm volatile("griddepcontrol.launch_dependents;");
  TR(3, 0, threadIdx.x >> 7);
  const int tid = threadIdx.x, lane = tid & 31;
  const int warp = __shfl_sync(0xffffffffu, tid >> 5, 0);
  const int head = blockIdx.x & 3, cl = blockIdx.x >> 2;
  const int par = cl / 7, strip = cl - par * 7, ph = par >> 1, pw = par & 1;

  if (warp == 1 && lane < 29) mbar_init(bar + (B_ODONE + lane) * 8, 4);
  if (tid == 0) {
    for (int i = 0; i < 3; i++) { mbar_init(bar + (B_FULL + i) * 8, 1); mbar_init(bar + (B_EMPTY + i) * 8, 16); }
    mbar_init(bar + B_QRDY * 8, 4); mbar_init(bar + B_KRDY * 8, 4); mbar_init(bar + B_VRDY * 8, 4);
    mbar_init(bar + B_QKISS * 8, 8); mbar_init(bar + B_PVISS * 8, 8); mbar_init(bar + B_KFREE * 8, 8); mbar_init(bar + B_VFREE * 8, 8);
    mbar_expect(bar + (B_FULL + 0) * 8, 18432); mbar_expect(bar + (B_FULL + 1) * 8, 24576); mbar_expect(bar + (B_FULL + 2) * 8, 24576);
    asm volatile("fence.mbarrier_init.release.cluster;" ::: "memory");
  }
  __syncwarp();
  asm volatile("barrier.cluster.arrive.relaxed.aligned;" ::: "memory");
  {
    uint4 wv[7];
#pragma unroll
    for (int i = 0; i < 7; i++) {
      int pc = tid + i * 512;
      int kb = pc / 144, rem = pc - kb * 144, ng = rem >> 3, k = kb * 8 + (rem & 7);
      int part = ng / 6, col = ((part + 1) % 3) * 192 + head * 48 + (ng - part * 6) * 8;
      if (pc < 3456) wv[i] = __ldg(reinterpret_cast<const uint4*>(wqkv + k * 576 + col));
    }
    for (int i = tid; i < (2 * KSLOT + 22 * 1536) / 16; i += 512)
      asm volatile("st.shared.v4.b32 [%0], {%1,%1,%1,%1};" ::"r"(sb + SM_K + i * 16), "r"(0) : "memory");
    if (tid < 182) {
      float v = tid < 169 ? __bfloat162float(rpb[head * 169 + tid]) * 1.4426950408889634f : -INFINITY;
      asm volatile("st.shared.f32 [%0], %1;" ::"r"(sb + SM_RPB + tid * 4), "f"(v) : "memory");
    }
    asm volatile("barrier.cluster.wait.aligned;" ::: "memory");
    if (warp == 12 && lane == 0 && head < 3) {
      const uint32_t fb = bar + (B_FULL + head) * 8;
      if (head == 0) {
        int cc = strip == 0 ? 16 : (strip == 6 ? 74 : strip * 16 - 3), sd = strip == 0 ? -1 : (strip == 6 ? 1 : 0);
        asm volatile("cp.async.bulk.tensor.5d.shared::cluster.global.mbarrier::complete_tx::bytes.multicast::cluster [%0], [%1, {%3,%4,%5,%6,%7}], [%2], %8;"
                     ::"r"(sb + SM_X0), "l"(&mapH), "r"(fb), "r"(0), "r"(-4), "r"(ph * 112 + cc), "r"(sd), "r"(pw * 3), "h"((uint16_t)15) : "memory");
      } else {
        asm volatile("cp.async.bulk.tensor.4d.shared::cluster.global.mbarrier::complete_tx::bytes.multicast::cluster [%0], [%1, {%3,%4,%5,%6}], [%2], %7;"
                     ::"r"(sb + (head == 1 ? SM_X1 : SM_X2)), "l"(&mapC), "r"(fb), "r"(0), "r"(head == 1 ? 4 : 0), "r"(ph * 112 + strip * 16), "r"(pw * 3), "h"((uint16_t)15) : "memory");
      }
    }
#pragma unroll
    for (int i = 0; i < 7; i++) {
      int pc = tid + i * 512;
      int kb = pc / 144, rem = pc - kb * 144, ng = rem >> 3, k = kb * 8 + (rem & 7);
      if (pc < 3456) asm volatile("st.shared.v4.b32 [%0], {%1,%2,%3,%4};" ::"r"(sb + SM_W + ng * 3072 + k * 16), "r"(wv[i].x), "r"(wv[i].y), "r"(wv[i].z), "r"(wv[i].w) : "memory");
    }
    fence_async();
    __syncthreads();
    TR(3, 1, threadIdx.x >> 7);
  }

  if (warp >= 12) {
    asm volatile("setmaxnreg.dec.sync.aligned.u32 24;");
    if (warp == 12 && lane == 0 && head < 3) {
      const uint32_t fb = bar + (B_FULL + head) * 8, eb = bar + (B_EMPTY + head) * 8;
      if (head == 0) {
        int cc = ph * 112 + (strip == 0 ? 16 : (strip == 6 ? 74 : strip * 16 - 3)), sd = strip == 0 ? -1 : (strip == 6 ? 1 : 0);
#pragma unroll 1
        for (int n = 1; n < 15; n++) {
          asm volatile("cp.async.bulk.prefetch.tensor.5d.L2.global [%0, {%1,%2,%3,%4,%5}];" ::"l"(&mapH), "r"(0), "r"(8 * n - 4), "r"(cc), "r"(sd), "r"(pw * 3) : "memory");
          mbar_wait(eb, (n - 1) & 1);
          asm volatile("cp.async.bulk.tensor.5d.shared::cluster.global.mbarrier::complete_tx::bytes.multicast::cluster [%0], [%1, {%3,%4,%5,%6,%7}], [%2], %8;"
                       ::"r"(sb + SM_X0), "l"(&mapH), "r"(fb), "r"(0), "r"(8 * n - 4), "r"(cc), "r"(sd), "r"(pw * 3), "h"((uint16_t)15) : "memory");
        }
      } else {
        const int r0 = head == 1 ? 4 : 0, cc = ph * 112 + strip * 16;
        const uint32_t dst = sb + (head == 1 ? SM_X1 : SM_X2);
#pragma unroll 1
        for (int n = 1; n < 14; n++) {
          asm volatile("cp.async.bulk.prefetch.tensor.4d.L2.global [%0, {%1,%2,%3,%4}];" ::"l"(&mapC), "r"(0), "r"(8 * n + r0), "r"(cc), "r"(pw * 3) : "memory");
          mbar_wait(eb, (n - 1) & 1);
          asm volatile("cp.async.bulk.tensor.4d.shared::cluster.global.mbarrier::complete_tx::bytes.multicast::cluster [%0], [%1, {%3,%4,%5,%6}], [%2], %7;"
                       ::"r"(dst), "l"(&mapC), "r"(fb), "r"(0), "r"(8 * n + r0), "r"(cc), "r"(pw * 3), "h"((uint16_t)15) : "memory");
        }
      }
    }
    if ((warp == 13 || warp == 14) && lane < 4) {
      const int j = warp - 13;
      int* flag = g_flags + (cl * 2 + j) * 4 + lane;
#pragma unroll 1
      for (int b = 0; b < 14; b++) {
        mbar_wait(bar + (B_ODONE + 2 * b + j) * 8, 0);
        asm volatile("fence.acq_rel.gpu;\nred.relaxed.gpu.global.add.s32 [%0], 1;" ::"l"(flag + b * 224) : "memory");
      }
    }
    __syncwarp();
    cluster_sync();
  } else if (warp >= 8) {
    asm volatile("setmaxnreg.inc.sync.aligned.u32 168;");
    GemmCtx c;
    c.sb = sb; c.warp = warp - 8; c.lead = lane == 0;
    const int tk = c.warp * 16 + (lane & 15), hi = lane >> 4;
    { int col = tk >> 2; c.rC = tk & 3; c.cpC = (col + 3) & 1;
      c.kC = sb + SM_K + (col + 3) * KS + hi * 128;
      c.vC = sb + SM_V + (col + 3) * 1536 + hi * 128;
      c.qC = sb + SM_Q + col * 1536 + hi * 256 + (col & 1) * 64; }
    { int ci = tk >> 3, kc = ci < 3 ? ci : ci + 16; c.rH = tk & 7; c.cpH = kc & 1; c.hvalid = c.warp < 3;
      c.kH = sb + SM_K + kc * KS + hi * 128;
      c.vH = sb + SM_V + kc * 1536 + hi * 128; }
    uint32_t pk[12], pv[12], pq[12];
    gemm_iter<true, false>(c, -2, pk, pv, pq);
#pragma unroll 1
    for (int b = -1; b < 12; b++) gemm_iter<false, false>(c, b, pk, pv, pq);
    gemm_iter<false, true>(c, 12, pk, pv, pq);
    cluster_sync();
  } else {
    asm volatile("setmaxnreg.inc.sync.aligned.u32 160;");
    const int j = warp >> 2, w = warp & 3;
    int variant = w;
    if (strip == 0 && j == 0 && w < 2) variant = 4;
    if (strip == 6 && j == 1 && w >= 2) variant = 5;
    const uint32_t qa = sb + SM_Q + (8 * j + 2 * w + ((lane >> 3) & 1)) * 1536 + (lane >> 4) * 256 + (((lane & 7) * 16) ^ (((lane >> 3) & 1) * 64));
    const uint64_t dK = mkdesc(SBC + SM_K, 128, KS, 0) + j * (8 * KS / 16);
    const uint64_t dV = mkdesc(SBC + SM_V, 768, 128, 0) + j * (8 * 1536 / 16);
    uint8_t* op = reinterpret_cast<uint8_t*>(out) + (size_t)(ph * 224 + 2 * (strip * 16 + 8 * j + 2 * w + (head >> 1)) + pw) * 384 + (size_t)(4 * (head & 1)) * ROWB;
    uint32_t off[3];
#pragma unroll
    for (int i = 0; i < 3; i++) { const int pc = i * 32 + lane, tk = pc / 24; off[i] = tk * ROWB + (pc - tk * 24) * 16; }
    float T[14];
    bool b0 = false, b1 = false;
    uint32_t ra0 = 0, ra1 = 0, meta = 0;
    uint32_t q[12];
    mbar_wait(bar + B_Q0 * 8, 0);
#pragma unroll
    for (int k = 0; k < 3; k++) ldsm4(qa + k * 512, q[4 * k], q[4 * k + 1], q[4 * k + 2], q[4 * k + 3]);
#pragma unroll 1
    for (int b = 0; b < 14; b++) {
      const uint32_t pa = b & 1;
      if (b <= 1 || b == 13) {
        uint32_t ln; asm volatile("mov.u32 %0, %%laneid;" : "=r"(ln));
        const int g = ln >> 2, t = ln & 3;
        const int sw = b == 0 ? max(g, 3) : (b == 13 ? min(g, 4) : g);
        const int i0 = 2 * t, i1 = 2 * t + 1;
        b0 = i0 <= sw - 2; b1 = i1 <= sw - 2;
        const int m = (sw + 7) & 7;
        ra0 = sb + SM_RPB + (i0 == m ? 13 : i0 + (b0 ? 8 : 0) - g + 3) * 52;
        ra1 = sb + SM_RPB + (i1 == m ? 13 : i1 + (b1 ? 8 : 0) - g + 3) * 52;
#pragma unroll
        for (int jj = 0; jj < 7; jj++) { T[2 * jj] = lds_f32(ra0 + (jj + 3) * 4); T[2 * jj + 1] = lds_f32(ra1 + (jj + 3) * 4); }
        uint32_t m16 = 0x8888u;
#pragma unroll
        for (int i = 0; i < 8; i++) m16 |= (uint32_t)(((i <= sw - 2) ^ (i == 7) ^ t ^ b) & 1) << (2 * i);
        meta = m16 | (m16 << 16);
      } else meta ^= 0x55555555u;
      float SA[56], SB[56];
      const uint64_t dA = dK + pa * (KSLOT >> 4), dB = dK + (pa ^ 1) * (KSLOT >> 4);
      TR(j, b, 0);
      mbar_wait(bar + B_KRDY * 8, pa);
      TR(j, b, 1);
      wg_fence();
      wg_rs112<0>(SA, q[0], q[1], q[2], q[3], dA);
      wg_rs112<0>(SB, q[0], q[1], q[2], q[3], dB);
      wg_rs112<1>(SA, q[4], q[5], q[6], q[7], dA + 16);
      wg_rs112<1>(SB, q[4], q[5], q[6], q[7], dB + 16);
      wg_rs112<1>(SA, q[8], q[9], q[10], q[11], dA + 32);
      wg_rs112<1>(SB, q[8], q[9], q[10], q[11], dB + 32);
      wg_commit();
      mbar_arrive_elect(bar + B_QKISS * 8);
      TR(j, b, 2);
      wg_wait<0>(); pin(SA); pin(SB);
      mbar_arrive_elect(bar + B_KFREE * 8);
      TR(j, b, 3);
      uint32_t P[28];
      float su, sl;
      switch (variant) {
        case 0: softmax_tile<0, 1, false>(SA, SB, T, b0, b1, ra0, ra1, 0, P, su, sl); break;
        case 1: softmax_tile<2, 3, false>(SA, SB, T, b0, b1, ra0, ra1, 0, P, su, sl); break;
        case 2: softmax_tile<4, 5, false>(SA, SB, T, b0, b1, ra0, ra1, 0, P, su, sl); break;
        case 3: softmax_tile<6, 7, false>(SA, SB, T, b0, b1, ra0, ra1, 0, P, su, sl); break;
        case 4: softmax_tile<3, 3, true>(SA, SB, T, b0, b1, ra0, ra1, 2 * w, P, su, sl); break;
        default: softmax_tile<4, 4, true>(SA, SB, T, b0, b1, ra0, ra1, 2 * w, P, su, sl); break;
      }
      float O[24];
      TR(j, b, 4);
      if (b < 13) {
        mbar_wait(bar + B_QRDY * 8, pa);
#pragma unroll
        for (int k = 0; k < 3; k++) ldsm4(qa + (pa ^ 1) * 128 + k * 512, q[4 * k], q[4 * k + 1], q[4 * k + 2], q[4 * k + 3]);
      }
      su += __shfl_xor_sync(0xffffffffu, su, 1); sl += __shfl_xor_sync(0xffffffffu, sl, 1);
      mbar_wait(bar + B_VRDY * 8, pa);
      TR(j, b, 5);
      su += __shfl_xor_sync(0xffffffffu, su, 2); sl += __shfl_xor_sync(0xffffffffu, sl, 2);
      wg_fence();
      wg_sp48<0>(O, P[0], P[1], P[2], P[3], dV, meta);
#pragma unroll
      for (int s = 1; s < 7; s++) wg_sp48<1>(O, P[4 * s], P[4 * s + 1], P[4 * s + 2], P[4 * s + 3], dV + s * 192, meta);
      wg_commit();
      mbar_arrive_elect(bar + B_PVISS * 8);
      TR(j, b, 6);
      const float ru = __fdividef(1.f, su), rl = __fdividef(1.f, sl);
      wg_wait<0>(); pin(O);
      mbar_arrive_elect(bar + B_VFREE * 8);
      TR(j, b, 7);
#pragma unroll
      for (int i = 0; i < 3; i++) {
        uint4 v;
        v.x = pack2(O[8 * i] * ru, O[8 * i + 1] * ru);     v.y = pack2(O[8 * i + 2] * rl, O[8 * i + 3] * rl);
        v.z = pack2(O[8 * i + 4] * ru, O[8 * i + 5] * ru); v.w = pack2(O[8 * i + 6] * rl, O[8 * i + 7] * rl);
        *reinterpret_cast<uint4*>(op + off[i]) = v;
      }
      op += 8 * ROWB;
      __syncwarp();
      mbar_arrive_elect(bar + (B_ODONE + 2 * b + j) * 8);
      TR(j, b, 8);
    }
    cluster_sync();
  }
}

constexpr int SM_B_W = 0;
constexpr int SM_B_ST = 73728;
constexpr int SM_B_TOTAL = SM_B_ST + 16 * 6144;

__global__ void __launch_bounds__(512, 1)
na_proj_kernel(const __grid_constant__ CUtensorMap mapO, const __nv_bfloat16* __restrict__ wo, __nv_bfloat16* out) {
  extern __shared__ __align__(1024) uint8_t smem_raw[];
  const uint32_t sb = smem_u32(smem_raw);
  if ((sb & 0x3FFFF) != SBC) return;
  const int tid = threadIdx.x, lane = tid & 31;
  const int warp = __shfl_sync(0xffffffffu, tid >> 5, 0);
  {
    uint4 wv[9];
#pragma unroll
    for (int i = 0; i < 9; i++) {
      int pc = tid + i * 512, kb = pc / 192, rem = pc - kb * 192;
      wv[i] = __ldg(reinterpret_cast<const uint4*>(wo + (kb * 8 + (rem & 7)) * 192 + (rem >> 3) * 8));
    }
#pragma unroll
    for (int i = 0; i < 9; i++) {
      int pc = tid + i * 512, kb = pc / 192, rem = pc - kb * 192;
      asm volatile("st.shared.v4.b32 [%0], {%1,%2,%3,%4};" ::"r"(sb + SM_B_W + (rem >> 3) * 3072 + (kb * 8 + (rem & 7)) * 16), "r"(wv[i].x), "r"(wv[i].y), "r"(wv[i].z), "r"(wv[i].w) : "memory");
    }
    fence_async();
    __syncthreads();
  }
  const int w = warp & 3;
  constexpr uint64_t db = mkdesc(SBC + SM_B_W, 128, 3072, 0);
  const uint32_t st = sb + SM_B_ST + warp * 6144;
  const uint32_t sta = st + (lane & 15) * 128 + (((lane >> 4) ^ (lane & 7)) * 16);
  uint32_t off[3];
#pragma unroll
  for (int i = 0; i < 3; i++) { int pc = i * 32 + lane, tk = pc / 24; off[i] = tk * ROWB + (pc - tk * 24) * 16; }
  const int nw = gridDim.x * 4;
#pragma unroll 1
  for (int n = (warp >> 2) * gridDim.x + blockIdx.x; n < 784; n += nw) {
    const int b = n / 56, rem = n - b * 56, cl = rem >> 1, j = rem & 1;
    const int par = cl / 7, strip = cl - par * 7, ph = par >> 1, pw = par & 1;
    const int col = strip * 16 + 8 * j + 2 * w;
    if (lane == 0) {
      int* f = g_flags + n * 4 + w;
      int v; uint32_t it = 0;
      do { asm volatile("ld.acquire.gpu.global.s32 %0, [%1];" : "=r"(v) : "l"(f) : "memory"); } while (v < 4 && ++it < SPIN_LIMIT);
      *f = 0;
    }
    __syncwarp();
    const uint8_t* ip = reinterpret_cast<const uint8_t*>(out) + (size_t)(ph * 224 + 2 * col + pw) * 384 + (size_t)(8 * b) * ROWB;
    uint32_t a[48];
#pragma unroll
    for (int h = 0; h < 4; h++)
#pragma unroll
      for (int i = 0; i < 3; i++)
        asm volatile("ld.global.cg.v4.b32 {%0,%1,%2,%3}, [%4];"
                     : "=r"(a[12 * h + 4 * i]), "=r"(a[12 * h + 4 * i + 1]), "=r"(a[12 * h + 4 * i + 2]), "=r"(a[12 * h + 4 * i + 3])
                     : "l"(ip + off[i] + (h & 1) * 4 * ROWB + (h >> 1) * 768) : "memory");
    if (lane == 0) asm volatile("cp.async.bulk.wait_group.read 0;" ::: "memory");
    __syncwarp();
#pragma unroll
    for (int hf = 0; hf < 2; hf++) {
      float D[48];
      wg_fence();
      wg_rs96<0>(D, a[0], a[1], a[2], a[3], db + hf * (12 * 3072 / 16));
#pragma unroll
      for (int k = 1; k < 12; k++) wg_rs96<1>(D, a[4 * k], a[4 * k + 1], a[4 * k + 2], a[4 * k + 3], db + hf * (12 * 3072 / 16) + k * 16);
      wg_commit();
      wg_wait<0>(); pin(D);
#pragma unroll
      for (int q = 0; q < 6; q++) {
        const int qq = hf * 6 + q;
        stsm4((sta ^ ((qq & 3) * 32)) + (qq >> 2) * 2048,
              pack2(D[8 * q], D[8 * q + 1]), pack2(D[8 * q + 2], D[8 * q + 3]), pack2(D[8 * q + 4], D[8 * q + 5]), pack2(D[8 * q + 6], D[8 * q + 7]));
      }
    }
    fence_async();
    __syncwarp();
    if (lane == 0) {
      asm volatile("cp.async.bulk.tensor.4d.global.shared::cta.bulk_group [%0, {%2,%3,%4,%5}], [%1];"
                   ::"l"(&mapO), "r"(st), "r"(0), "r"(8 * b), "r"(ph * 112 + col), "r"(pw * 3) : "memory");
      asm volatile("cp.async.bulk.commit_group;" ::: "memory");
    }
  }
  if (lane == 0) asm volatile("cp.async.bulk.wait_group 0;" ::: "memory");
}

typedef CUresult (*EncodeFn)(CUtensorMap*, CUtensorMapDataType, cuuint32_t, void*, const cuuint64_t*, const cuuint64_t*, const cuuint32_t*,
                             const cuuint32_t*, CUtensorMapInterleave, CUtensorMapSwizzle, CUtensorMapL2promotion, CUtensorMapFloatOOBfill);

extern "C" void kernel_launch(void* const* d_in, const int* in_sizes, int n_in, void* d_out, int out_size) {
  const __nv_bfloat16* x = (const __nv_bfloat16*)d_in[0];
  const __nv_bfloat16* wqkv = (const __nv_bfloat16*)d_in[1];
  const __nv_bfloat16* wo = (const __nv_bfloat16*)d_in[2];
  const __nv_bfloat16* rpb = (const __nv_bfloat16*)d_in[3];
  __nv_bfloat16* out = (__nv_bfloat16*)d_out;

  static EncodeFn enc = nullptr;
  if (!enc) {
    void* fn = nullptr; cudaDriverEntryPointQueryResult qr;
    cudaGetDriverEntryPoint("cuTensorMapEncodeTiled", &fn, cudaEnableDefault, &qr);
    enc = (EncodeFn)fn;
    cudaFuncSetAttribute(na_attn_kernel, cudaFuncAttributeMaxDynamicSharedMemorySize, SM_A_TOTAL);
    cudaFuncSetAttribute(na_proj_kernel, cudaFuncAttributeMaxDynamicSharedMemorySize, SM_B_TOTAL);
  }
  CUtensorMap mC, mH, mO;
  const cuuint32_t ones[5] = {1, 1, 1, 1, 1};
  {
    cuuint64_t dim[4] = {64, 112, 224, 6}, str[3] = {(cuuint64_t)ROWB, 768, 128};
    cuuint32_t box[4] = {64, 4, 16, 3}, boxo[4] = {64, 8, 2, 3};
    enc(&mC, CU_TENSOR_MAP_DATA_TYPE_BFLOAT16, 4, (void*)x, dim, str, box, ones, CU_TENSOR_MAP_INTERLEAVE_NONE, CU_TENSOR_MAP_SWIZZLE_128B,
        CU_TENSOR_MAP_L2_PROMOTION_L2_128B, CU_TENSOR_MAP_FLOAT_OOB_FILL_NONE);
    enc(&mO, CU_TENSOR_MAP_DATA_TYPE_BFLOAT16, 4, (void*)out, dim, str, boxo, ones, CU_TENSOR_MAP_INTERLEAVE_NONE, CU_TENSOR_MAP_SWIZZLE_128B,
        CU_TENSOR_MAP_L2_PROMOTION_NONE, CU_TENSOR_MAP_FLOAT_OOB_FILL_NONE);
  }
  {
    cuuint64_t dim[5] = {64, 112, 224, 2, 6}, str[4] = {(cuuint64_t)ROWB, 768, 19 * 768, 128};
    cuuint32_t box[5] = {64, 8, 3, 2, 3};
    enc(&mH, CU_TENSOR_MAP_DATA_TYPE_BFLOAT16, 5, (void*)x, dim, str, box, ones, CU_TENSOR_MAP_INTERLEAVE_NONE, CU_TENSOR_MAP_SWIZZLE_128B,
        CU_TENSOR_MAP_L2_PROMOTION_L2_128B, CU_TENSOR_MAP_FLOAT_OOB_FILL_NONE);
  }
  na_attn_kernel<<<112, 512, SM_A_TOTAL>>>(mC, mH, wqkv, rpb, out);
#define NBCTA 20
  cudaLaunchConfig_t cfg = {};
  cfg.gridDim = dim3(NBCTA); cfg.blockDim = dim3(512); cfg.dynamicSmemBytes = SM_B_TOTAL; cfg.stream = cudaStreamPerThread;
  cudaLaunchAttribute at[1];
  at[0].id = cudaLaunchAttributeProgrammaticStreamSerialization; at[0].val.programmaticStreamSerializationAllowed = 1;
  cfg.attrs = at; cfg.numAttrs = 1;
  cudaLaunchKernelEx(&cfg, na_proj_kernel, mO, wo, out);
}
```

```cpp
#include <cuda_runtime.h>
#include <cuda_bf16.h>
#include <cuda.h>
#include <stdint.h>

#define SPIN_LIMIT (1u << 18)

__device__ __forceinline__ uint32_t smem_u32(const void* p) { return (uint32_t)__cvta_generic_to_shared(p); }
__device__ __forceinline__ void wg_fence() { asm volatile("wgmma.fence.sync.aligned;" ::: "memory"); }
__device__ __forceinline__ void wg_commit() { asm volatile("wgmma.commit_group.sync.aligned;" ::: "memory"); }
template <int N> __device__ __forceinline__ void wg_wait() { asm volatile("wgmma.wait_group.sync.aligned %0;" ::"n"(N) : "memory"); }
template <int N> __device__ __forceinline__ void pin(float (&d)[N]) {
#pragma unroll
  for (int i = 0; i < N; i++) asm volatile("" : "+f"(d[i])::"memory");
}
__host__ __device__ constexpr uint64_t mkdesc(uint32_t addr, uint32_t lbo, uint32_t sbo, uint32_t sw) {
  return (uint64_t)((addr & 0x3FFFF) >> 4) | ((uint64_t)(lbo >> 4) << 16) | ((uint64_t)(sbo >> 4) << 32) | ((uint64_t)sw << 62);
}
__device__ __forceinline__ void mbar_init(uint32_t bar, uint32_t cnt) { asm volatile("mbarrier.init.shared::cta.b64 [%0], %1;" ::"r"(bar), "r"(cnt) : "memory"); }
__device__ __forceinline__ void mbar_arrive(uint32_t bar) { asm volatile("mbarrier.arrive.shared::cta.b64 _, [%0];" ::"r"(bar) : "memory"); }
__device__ __forceinline__ bool elect_one() {
  uint32_t r; asm volatile("{\n.reg .pred p;\nelect.sync _|p, 0xffffffff;\nselp.u32 %0, 1, 0, p;\n}" : "=r"(r)); return r;
}
__device__ __forceinline__ void mbar_arrive_elect(uint32_t bar) {
  asm volatile("{\n.reg .pred p;\nelect.sync _|p, 0xffffffff;\n@p mbarrier.arrive.shared::cta.b64 _, [%0];\n}" ::"r"(bar) : "memory");
}
__device__ __forceinline__ void mbar_expect(uint32_t bar, uint32_t bytes) { asm volatile("mbarrier.arrive.expect_tx.shared::cta.b64 _, [%0], %1;" ::"r"(bar), "r"(bytes) : "memory"); }
__device__ __forceinline__ void mbar_arrive_remote(uint32_t bar, uint32_t cta) {
  asm volatile("{\n.reg .b32 ra;\nmapa.shared::cluster.u32 ra, %0, %1;\nmbarrier.arrive.shared::cluster.b64 _, [ra];\n}" ::"r"(bar), "r"(cta) : "memory");
}
__device__ __forceinline__ void mbar_wait(uint32_t bar, uint32_t parity) {
  asm volatile("{\n.reg .pred p;\n.reg .b32 n;\nmov.b32 n, 0;\nWL:\nmbarrier.try_wait.parity.shared::cta.b64 p, [%0], %1;\n@p bra WD;\n"
               "add.u32 n, n, 1;\nsetp.lt.u32 p, n, 65536;\n@p bra WL;\nWD:\n}" ::"r"(bar), "r"(parity) : "memory");
}
__device__ __forceinline__ void fence_async() { asm volatile("fence.proxy.async.shared::cta;" ::: "memory"); }
__device__ __forceinline__ void cluster_sync() {
  asm volatile("barrier.cluster.arrive.relaxed.aligned;\nbarrier.cluster.wait.aligned;" ::: "memory");
}
__device__ __forceinline__ uint32_t pack2(float lo, float hi) {
  uint32_t r; asm("cvt.rn.bf16x2.f32 %0, %1, %2;" : "=r"(r) : "f"(hi), "f"(lo)); return r;
}
__device__ __forceinline__ void stsm4(uint32_t a, uint32_t r0, uint32_t r1, uint32_t r2, uint32_t r3) {
  asm volatile("stmatrix.sync.aligned.m8n8.x4.shared.b16 [%0], {%1,%2,%3,%4};" ::"r"(a), "r"(r0), "r"(r1), "r"(r2), "r"(r3) : "memory");
}
__device__ __forceinline__ void ldsm4(uint32_t a, uint32_t& r0, uint32_t& r1, uint32_t& r2, uint32_t& r3) {
  asm volatile("ldmatrix.sync.aligned.m8n8.x4.shared.b16 {%0,%1,%2,%3}, [%4];" : "=r"(r0), "=r"(r1), "=r"(r2), "=r"(r3) : "r"(a) : "memory");
}
__device__ __forceinline__ float lds_f32(uint32_t a) { float v; asm volatile("ld.shared.f32 %0, [%1];" : "=f"(v) : "r"(a)); return v; }
__device__ __forceinline__ float ex2(float x) { float y; asm("ex2.approx.ftz.f32 %0, %1;" : "=f"(y) : "f"(x)); return y; }

template<int SC> __device__ __forceinline__ void wg_ss144(float (&d)[72], uint64_t da, uint64_t db) {
  asm volatile("{\n.reg .pred p;\nsetp.ne.b32 p, %74, 0;\nwgmma.mma_async.sync.aligned.m64n144k16.f32.bf16.bf16 {%0,%1,%2,%3,%4,%5,%6,%7,%8,%9,%10,%11,%12,%13,%14,%15,%16,%17,%18,%19,%20,%21,%22,%23,%24,%25,%26,%27,%28,%29,%30,%31,%32,%33,%34,%35,%36,%37,%38,%39,%40,%41,%42,%43,%44,%45,%46,%47,%48,%49,%50,%51,%52,%53,%54,%55,%56,%57,%58,%59,%60,%61,%62,%63,%64,%65,%66,%67,%68,%69,%70,%71}, %72, %73, p, 1, 1, 0, 1;\n}\n"
    : "+f"(d[0]),"+f"(d[1]),"+f"(d[2]),"+f"(d[3]),"+f"(d[4]),"+f"(d[5]),"+f"(d[6]),"+f"(d[7]),"+f"(d[8]),"+f"(d[9]),"+f"(d[10]),"+f"(d[11]),"+f"(d[12]),"+f"(d[13]),"+f"(d[14]),"+f"(d[15]),"+f"(d[16]),"+f"(d[17]),"+f"(d[18]),"+f"(d[19]),"+f"(d[20]),"+f"(d[21]),"+f"(d[22]),"+f"(d[23]),"+f"(d[24]),"+f"(d[25]),"+f"(d[26]),"+f"(d[27]),"+f"(d[28]),"+f"(d[29]),"+f"(d[30]),"+f"(d[31]),"+f"(d[32]),"+f"(d[33]),"+f"(d[34]),"+f"(d[35]),"+f"(d[36]),"+f"(d[37]),"+f"(d[38]),"+f"(d[39]),"+f"(d[40]),"+f"(d[41]),"+f"(d[42]),"+f"(d[43]),"+f"(d[44]),"+f"(d[45]),"+f"(d[46]),"+f"(d[47]),"+f"(d[48]),"+f"(d[49]),"+f"(d[50]),"+f"(d[51]),"+f"(d[52]),"+f"(d[53]),"+f"(d[54]),"+f"(d[55]),"+f"(d[56]),"+f"(d[57]),"+f"(d[58]),"+f"(d[59]),"+f"(d[60]),"+f"(d[61]),"+f"(d[62]),"+f"(d[63]),"+f"(d[64]),"+f"(d[65]),"+f"(d[66]),"+f"(d[67]),"+f"(d[68]),"+f"(d[69]),"+f"(d[70]),"+f"(d[71]) : "l"(da), "l"(db), "n"(SC));
}
template<int SC> __device__ __forceinline__ void wg_ss96(float (&d)[48], uint64_t da, uint64_t db) {
  asm volatile("{\n.reg .pred p;\nsetp.ne.b32 p, %50, 0;\nwgmma.mma_async.sync.aligned.m64n96k16.f32.bf16.bf16 {%0,%1,%2,%3,%4,%5,%6,%7,%8,%9,%10,%11,%12,%13,%14,%15,%16,%17,%18,%19,%20,%21,%22,%23,%24,%25,%26,%27,%28,%29,%30,%31,%32,%33,%34,%35,%36,%37,%38,%39,%40,%41,%42,%43,%44,%45,%46,%47}, %48, %49, p, 1, 1, 0, 1;\n}\n"
    : "+f"(d[0]),"+f"(d[1]),"+f"(d[2]),"+f"(d[3]),"+f"(d[4]),"+f"(d[5]),"+f"(d[6]),"+f"(d[7]),"+f"(d[8]),"+f"(d[9]),"+f"(d[10]),"+f"(d[11]),"+f"(d[12]),"+f"(d[13]),"+f"(d[14]),"+f"(d[15]),"+f"(d[16]),"+f"(d[17]),"+f"(d[18]),"+f"(d[19]),"+f"(d[20]),"+f"(d[21]),"+f"(d[22]),"+f"(d[23]),"+f"(d[24]),"+f"(d[25]),"+f"(d[26]),"+f"(d[27]),"+f"(d[28]),"+f"(d[29]),"+f"(d[30]),"+f"(d[31]),"+f"(d[32]),"+f"(d[33]),"+f"(d[34]),"+f"(d[35]),"+f"(d[36]),"+f"(d[37]),"+f"(d[38]),"+f"(d[39]),"+f"(d[40]),"+f"(d[41]),"+f"(d[42]),"+f"(d[43]),"+f"(d[44]),"+f"(d[45]),"+f"(d[46]),"+f"(d[47]) : "l"(da), "l"(db), "n"(SC));
}
template<int SC> __device__ __forceinline__ void wg_rs112(float (&d)[56], uint32_t a0, uint32_t a1, uint32_t a2, uint32_t a3, uint64_t db) {
  asm volatile("{\n.reg .pred p;\nsetp.ne.b32 p, %61, 0;\nwgmma.mma_async.sync.aligned.m64n112k16.f32.bf16.bf16 {%0,%1,%2,%3,%4,%5,%6,%7,%8,%9,%10,%11,%12,%13,%14,%15,%16,%17,%18,%19,%20,%21,%22,%23,%24,%25,%26,%27,%28,%29,%30,%31,%32,%33,%34,%35,%36,%37,%38,%39,%40,%41,%42,%43,%44,%45,%46,%47,%48,%49,%50,%51,%52,%53,%54,%55}, {%56,%57,%58,%59}, %60, p, 1, 1, 0;\n}\n"
    : "+f"(d[0]),"+f"(d[1]),"+f"(d[2]),"+f"(d[3]),"+f"(d[4]),"+f"(d[5]),"+f"(d[6]),"+f"(d[7]),"+f"(d[8]),"+f"(d[9]),"+f"(d[10]),"+f"(d[11]),"+f"(d[12]),"+f"(d[13]),"+f"(d[14]),"+f"(d[15]),"+f"(d[16]),"+f"(d[17]),"+f"(d[18]),"+f"(d[19]),"+f"(d[20]),"+f"(d[21]),"+f"(d[22]),"+f"(d[23]),"+f"(d[24]),"+f"(d[25]),"+f"(d[26]),"+f"(d[27]),"+f"(d[28]),"+f"(d[29]),"+f"(d[30]),"+f"(d[31]),"+f"(d[32]),"+f"(d[33]),"+f"(d[34]),"+f"(d[35]),"+f"(d[36]),"+f"(d[37]),"+f"(d[38]),"+f"(d[39]),"+f"(d[40]),"+f"(d[41]),"+f"(d[42]),"+f"(d[43]),"+f"(d[44]),"+f"(d[45]),"+f"(d[46]),"+f"(d[47]),"+f"(d[48]),"+f"(d[49]),"+f"(d[50]),"+f"(d[51]),"+f"(d[52]),"+f"(d[53]),"+f"(d[54]),"+f"(d[55]) : "r"(a0), "r"(a1), "r"(a2), "r"(a3), "l"(db), "n"(SC));
}
template<int SC> __device__ __forceinline__ void wg_sp48(float (&d)[24], uint32_t a0, uint32_t a1, uint32_t a2, uint32_t a3, uint64_t db, uint32_t meta) {
  asm volatile("{\n.reg .pred p;\nsetp.ne.b32 p, %30, 0;\nwgmma.mma_async.sp.sync.aligned.m64n48k32.f32.bf16.bf16 {%0,%1,%2,%3,%4,%5,%6,%7,%8,%9,%10,%11,%12,%13,%14,%15,%16,%17,%18,%19,%20,%21,%22,%23}, {%24,%25,%26,%27}, %28, %29, 0, p, 1, 1, 1;\n}\n"
    : "+f"(d[0]),"+f"(d[1]),"+f"(d[2]),"+f"(d[3]),"+f"(d[4]),"+f"(d[5]),"+f"(d[6]),"+f"(d[7]),"+f"(d[8]),"+f"(d[9]),"+f"(d[10]),"+f"(d[11]),"+f"(d[12]),"+f"(d[13]),"+f"(d[14]),"+f"(d[15]),"+f"(d[16]),"+f"(d[17]),"+f"(d[18]),"+f"(d[19]),"+f"(d[20]),"+f"(d[21]),"+f"(d[22]),"+f"(d[23]) : "r"(a0), "r"(a1), "r"(a2), "r"(a3), "l"(db), "r"(meta), "n"(SC));
}
template<int SC> __device__ __forceinline__ void wg_ss192(float (&d)[96], uint64_t da, uint64_t db) {
  asm volatile("{\n.reg .pred p;\nsetp.ne.b32 p, %98, 0;\nwgmma.mma_async.sync.aligned.m64n192k16.f32.bf16.bf16 {%0,%1,%2,%3,%4,%5,%6,%7,%8,%9,%10,%11,%12,%13,%14,%15,%16,%17,%18,%19,%20,%21,%22,%23,%24,%25,%26,%27,%28,%29,%30,%31,%32,%33,%34,%35,%36,%37,%38,%39,%40,%41,%42,%43,%44,%45,%46,%47,%48,%49,%50,%51,%52,%53,%54,%55,%56,%57,%58,%59,%60,%61,%62,%63,%64,%65,%66,%67,%68,%69,%70,%71,%72,%73,%74,%75,%76,%77,%78,%79,%80,%81,%82,%83,%84,%85,%86,%87,%88,%89,%90,%91,%92,%93,%94,%95}, %96, %97, p, 1, 1, 0, 1;\n}\n"
    : "+f"(d[0]),"+f"(d[1]),"+f"(d[2]),"+f"(d[3]),"+f"(d[4]),"+f"(d[5]),"+f"(d[6]),"+f"(d[7]),"+f"(d[8]),"+f"(d[9]),"+f"(d[10]),"+f"(d[11]),"+f"(d[12]),"+f"(d[13]),"+f"(d[14]),"+f"(d[15]),"+f"(d[16]),"+f"(d[17]),"+f"(d[18]),"+f"(d[19]),"+f"(d[20]),"+f"(d[21]),"+f"(d[22]),"+f"(d[23]),"+f"(d[24]),"+f"(d[25]),"+f"(d[26]),"+f"(d[27]),"+f"(d[28]),"+f"(d[29]),"+f"(d[30]),"+f"(d[31]),"+f"(d[32]),"+f"(d[33]),"+f"(d[34]),"+f"(d[35]),"+f"(d[36]),"+f"(d[37]),"+f"(d[38]),"+f"(d[39]),"+f"(d[40]),"+f"(d[41]),"+f"(d[42]),"+f"(d[43]),"+f"(d[44]),"+f"(d[45]),"+f"(d[46]),"+f"(d[47]),"+f"(d[48]),"+f"(d[49]),"+f"(d[50]),"+f"(d[51]),"+f"(d[52]),"+f"(d[53]),"+f"(d[54]),"+f"(d[55]),"+f"(d[56]),"+f"(d[57]),"+f"(d[58]),"+f"(d[59]),"+f"(d[60]),"+f"(d[61]),"+f"(d[62]),"+f"(d[63]),"+f"(d[64]),"+f"(d[65]),"+f"(d[66]),"+f"(d[67]),"+f"(d[68]),"+f"(d[69]),"+f"(d[70]),"+f"(d[71]),"+f"(d[72]),"+f"(d[73]),"+f"(d[74]),"+f"(d[75]),"+f"(d[76]),"+f"(d[77]),"+f"(d[78]),"+f"(d[79]),"+f"(d[80]),"+f"(d[81]),"+f"(d[82]),"+f"(d[83]),"+f"(d[84]),"+f"(d[85]),"+f"(d[86]),"+f"(d[87]),"+f"(d[88]),"+f"(d[89]),"+f"(d[90]),"+f"(d[91]),"+f"(d[92]),"+f"(d[93]),"+f"(d[94]),"+f"(d[95]) : "l"(da), "l"(db), "n"(SC));
}

constexpr uint32_t SBC = 1024;
constexpr int ROWB = 2 * 224 * 384;
constexpr int KS = 832;
constexpr int KSLOT = 22 * KS;
constexpr int SM_X0 = 0;
constexpr int SM_X1 = 18432;
constexpr int SM_X2 = SM_X1 + 24576;
constexpr int SM_W = SM_X2 + 24576;
constexpr int SM_K = SM_W + 55296;
constexpr int SM_V = SM_K + 2 * KSLOT;
constexpr int SM_Q = SM_V + 22 * 1536;
constexpr int SM_RPB = SM_Q + 24576;
constexpr int SM_BAR = SM_RPB + 768;
constexpr int SM_A_TOTAL = SM_BAR + 512;
enum { B_FULL = 0, B_EMPTY = 3, B_QKISS = 6, B_PVISS, B_KFREE, B_VFREE, B_KRDY, B_VQRDY, B_Q0, B_W, B_ODONE = B_W + 6, B_COUNT = B_ODONE + 28 };

__device__ int g_flags[784];

#define TR(role, it, k)
#define TRB(it, k)
#define TR2(blk, k)

struct GemmCtx {
  uint32_t bar;
  uint32_t kC, vC, qC;
  uint32_t kH, vH;
  uint32_t em;
  bool hvalid;
  int warp;
};

template <int STRIDE> __device__ __forceinline__ void dump12(uint32_t a, const uint32_t (&r)[12]) {
#pragma unroll
  for (int j = 0; j < 3; j++) stsm4(a + j * 2 * STRIDE, r[4 * j], r[4 * j + 1], r[4 * j + 2], r[4 * j + 3]);
}
template <int N> __device__ __forceinline__ void pack12(uint32_t (&r)[12], const float (&d)[N], int off) {
#pragma unroll
  for (int j = 0; j < 12; j++) r[j] = pack2(d[off + 2 * j], d[off + 2 * j + 1]);
}
template <int XS, int K0, int K1> __device__ __forceinline__ void issue_core(float (&d)[72]) {
  constexpr uint64_t da = mkdesc(SBC + XS, 16, 1024, 1), db = mkdesc(SBC + SM_W, 2048, 256, 3);
  if (K0 == 0) { wg_fence(); wg_ss144<0>(d, da, db); }
#pragma unroll
  for (int k = K0 ? K0 : 1; k < K1; k++) wg_ss144<1>(d, da + (k >> 2) * 512 + (k & 3) * 2, db + (k >> 2) * 1152 + (k & 3) * 32);
  wg_commit();
}
template <int K0, int K1> __device__ __forceinline__ void issue_halo(float (&d)[48]) {
  constexpr uint64_t da = mkdesc(SBC + SM_X0, 16, 1024, 1), db = mkdesc(SBC + SM_W, 2048, 256, 3);
  if (K0 == 0) { wg_fence(); wg_ss96<0>(d, da, db); }
#pragma unroll
  for (int k = K0 ? K0 : 1; k < K1; k++) wg_ss96<1>(d, da + (k >> 2) * 384 + (k & 3) * 2, db + (k >> 2) * 1152 + (k & 3) * 32);
  wg_commit();
}
template <int ST, int BYTES> __device__ __forceinline__ void release_stage(const GemmCtx& c, bool on) {
  asm volatile("{\n.reg .pred p, q;\n.reg .b32 ra;\nsetp.ne.b32 q, %2, 0;\nelect.sync _|p, 0xffffffff;\nand.pred p, p, q;\n"
               "mapa.shared::cluster.u32 ra, %1, %4;\n"
               "@p mbarrier.arrive.expect_tx.shared::cta.b64 _, [%0], %3;\n@p mbarrier.arrive.shared::cluster.b64 _, [ra];\n}"
               ::"r"(c.bar + (B_FULL + ST) * 8), "r"(c.bar + (B_EMPTY + ST) * 8), "r"((int)on), "n"(BYTES / 4), "n"(ST) : "memory");
}
__device__ __forceinline__ void load_w(const CUtensorMap* m, uint32_t sb, int ch, int part, int head) {
  asm volatile("cp.async.bulk.tensor.3d.shared::cluster.global.mbarrier::complete_tx::bytes [%0], [%1, {%3,%4,%5}], [%2];"
               ::"r"(sb + SM_W + ch * 18432 + part * 6144), "l"(m), "r"(sb + SM_BAR + (B_W + ch + (part == 2 ? 3 : 0)) * 8),
                 "r"(0), "r"(ch * 64), "r"((part == 2 ? 0 : part * 12 + 12) + head * 3) : "memory");
}
__device__ __forceinline__ void publish(uint32_t bar) {
  fence_async();
  __syncwarp();
  mbar_arrive_elect(bar);
}

template <bool FIRST, bool LAST>
__device__ __forceinline__ void gemm_iter(const GemmCtx& c, int b, uint32_t (&pk)[12], uint32_t (&pv)[12], uint32_t (&pq)[12]) {
  const uint32_t bar = c.bar;
  const uint32_t pa = b & 1;
  const bool w = b >= 0;
  const uint32_t ko = pa * KSLOT, vx = pa * 16, qx = pa * 128;
  float H[48], C[72];
  uint32_t hk[12], hv[12], pv2[12];
  TR(2, b + 2, 0);
  mbar_wait(bar + (B_FULL + 0) * 8, pa);
  if (!LAST && !FIRST) mbar_wait(bar + (B_FULL + 2) * 8, pa);
  TR(2, b + 2, 1);
  if (w) mbar_wait(bar + B_QKISS * 8, pa);
  TR(2, b + 2, 2);
  if (FIRST) {
    mbar_wait(bar + (B_W + 0) * 8, 0); issue_halo<0, 4>(H);
    mbar_wait(bar + (B_W + 1) * 8, 0); issue_halo<4, 8>(H);
    mbar_wait(bar + (B_W + 2) * 8, 0);
  } else issue_halo<0, 8>(H);
  TR(2, b + 2, 3);
  if (!FIRST) {
    if (w) mbar_wait(bar + B_KFREE * 8, pa);
    dump12<128>(c.kC + ko, pk);
  }
  issue_halo<8, 12>(H);
  TR(2, b + 2, 4);
  if (!LAST) {
    if (FIRST) { mbar_wait(bar + (B_FULL + 2) * 8, pa); mbar_wait(bar + (B_W + 3) * 8, 0); mbar_wait(bar + (B_W + 4) * 8, 0); }
    issue_core<SM_X2, 0, 8>(C);
    TR(2, b + 2, 5);
    if (!FIRST) dump12<256>(c.qC ^ (qx ^ 192), pq);
    wg_wait<1>(); pin(H);
    release_stage<0, 18432>(c, true);
  } else {
    dump12<256>(c.qC ^ (qx ^ 192), pq);
    wg_wait<0>(); pin(H);
  }
  pack12(hk, H, 0);
  if (c.hvalid) dump12<128>(c.kH + ko, hk);
  pack12(hv, H, 24);
  if (FIRST) mbar_wait(bar + (B_W + 5) * 8, 0);
  if (!LAST) issue_core<SM_X2, 8, 12>(C);
  if (!FIRST) publish(bar + (w ? B_VQRDY : B_Q0) * 8);
  if (!LAST) {
    mbar_wait(bar + (B_FULL + 1) * 8, pa);
    TR(2, b + 2, 6);
    wg_wait<0>(); pin(C);
    TR(2, b + 2, 7);
    release_stage<2, 24576>(c, b < 11);
    pack12(pk, C, 0);
    pack12(pv2, C, 24);
    pack12(pq, C, 48);
    if (w) mbar_wait(bar + B_PVISS * 8, pa);
    TR(2, b + 2, 8);
    issue_core<SM_X1, 0, 8>(C);
    TR(2, b + 2, 9);
    dump12<128>(c.kC + ko + 64, pk);
  }
  if (!FIRST) publish(bar + B_KRDY * 8);
  TR(2, b + 2, 10);
  if (!LAST) issue_core<SM_X1, 8, 12>(C);
  if (w) mbar_wait(bar + B_VFREE * 8, pa);
  if (!FIRST) dump12<128>(c.vC ^ vx, pv);
  if (!LAST) dump12<256>(c.qC ^ qx, pq);
  if (c.hvalid) dump12<128>(c.vH ^ vx, hv);
  if (LAST) { publish(bar + B_VQRDY * 8); return; }
  dump12<128>((c.vC ^ vx ^ 16) + 768, pv2);
  TR(2, b + 2, 11);
  wg_wait<0>(); pin(C);
  TR(2, b + 2, 12);
  release_stage<1, 24576>(c, b < 11);
  pack12(pk, C, 0);
  pack12(pv, C, 24);
  pack12(pq, C, 48);
}

template <int U, int L, bool BORDER>
__device__ __forceinline__ void softmax_tile(const float (&SA)[56], const float (&SB)[56], const float (&T)[14], bool b0, bool b1,
                                             uint32_t ra0, uint32_t ra1, int qcu, uint32_t (&P)[28], float& sumU, float& sumL) {
  const float cs = 0.14433756729740643f * 1.4426950408889634f;
  float lu[14], ll[14];
#pragma unroll
  for (int j = 0; j < 7; j++) {
    float tu0, tu1, tl0, tl1;
    if (BORDER) {
      tu0 = lds_f32(ra0 + (U + j + 3 - qcu) * 4); tu1 = lds_f32(ra1 + (U + j + 3 - qcu) * 4);
      tl0 = lds_f32(ra0 + (L + j + 2 - qcu) * 4); tl1 = lds_f32(ra1 + (L + j + 2 - qcu) * 4);
    } else { tu0 = tl0 = T[2 * j]; tu1 = tl1 = T[2 * j + 1]; }
    lu[2 * j]     = fmaf(b0 ? SB[4 * (U + j)]     : SA[4 * (U + j)],     cs, tu0);
    lu[2 * j + 1] = fmaf(b1 ? SB[4 * (U + j) + 1] : SA[4 * (U + j) + 1], cs, tu1);
    ll[2 * j]     = fmaf(b0 ? SB[4 * (L + j) + 2] : SA[4 * (L + j) + 2], cs, tl0);
    ll[2 * j + 1] = fmaf(b1 ? SB[4 * (L + j) + 3] : SA[4 * (L + j) + 3], cs, tl1);
  }
  float mu = lu[0], ml = ll[0], mu2 = lu[1], ml2 = ll[1];
#pragma unroll
  for (int j = 1; j < 7; j++) { mu = fmaxf(mu, lu[2 * j]); mu2 = fmaxf(mu2, lu[2 * j + 1]); ml = fmaxf(ml, ll[2 * j]); ml2 = fmaxf(ml2, ll[2 * j + 1]); }
  mu = fmaxf(mu, mu2); ml = fmaxf(ml, ml2);
  mu = fmaxf(mu, __shfl_xor_sync(0xffffffffu, mu, 1)); ml = fmaxf(ml, __shfl_xor_sync(0xffffffffu, ml, 1));
  mu = fmaxf(mu, __shfl_xor_sync(0xffffffffu, mu, 2)); ml = fmaxf(ml, __shfl_xor_sync(0xffffffffu, ml, 2));
  float su = 0.f, sl = 0.f, su2 = 0.f, sl2 = 0.f;
#pragma unroll
  for (int c = 0; c < 14; c++) {
    const int iu = (c >> 1) * 4 + (c & 1) * 2;
    if (c >= U && c < U + 7) {
      float e0 = ex2(lu[2 * (c - U)] - mu), e1 = ex2(lu[2 * (c - U) + 1] - mu);
      su += e0; su2 += e1; P[iu] = pack2(e0, e1);
    } else P[iu] = 0u;
    if (c >= L && c < L + 7) {
      float e0 = ex2(ll[2 * (c - L)] - ml), e1 = ex2(ll[2 * (c - L) + 1] - ml);
      sl += e0; sl2 += e1; P[iu + 1] = pack2(e0, e1);
    } else P[iu + 1] = 0u;
  }
  sumU = su + su2; sumL = sl + sl2;
}

__global__ void __cluster_dims__(4, 1, 1) __launch_bounds__(512, 1)
na_attn_kernel(const __grid_constant__ CUtensorMap mapC, const __grid_constant__ CUtensorMap mapH,
               const __grid_constant__ CUtensorMap mapW, const __nv_bfloat16* __restrict__ rpb, __nv_bfloat16* __restrict__ out) {
  extern __shared__ __align__(1024) uint8_t smem_raw[];
  const uint32_t sb = smem_u32(smem_raw);
  if ((sb & 0x3FFFF) != SBC) return;
  const uint32_t bar = sb + SM_BAR;
  asm volatile("griddepcontrol.launch_dependents;");
  TR(3, 0, threadIdx.x >> 7);
  TR2(blockIdx.x, 0);
  const int tid = threadIdx.x, lane = tid & 31;
  const int warp = __shfl_sync(0xffffffffu, tid >> 5, 0);
  const int head = blockIdx.x & 3, cl = blockIdx.x >> 2;
  const int par = cl / 7, strip = cl - par * 7, ph = par >> 1, pw = par & 1;

  if (warp >= 12) {
    asm volatile("setmaxnreg.dec.sync.aligned.u32 24;");
    const int cc = ph * 112 + (head ? strip * 16 : (strip == 0 ? 16 : (strip == 6 ? 74 : strip * 16 - 3)));
    const int sd = strip == 0 ? -1 : (strip == 6 ? 1 : 0);
    const int r0 = head == 0 ? -4 : (head == 1 ? 4 : 0);
    const bool lead = elect_one();
    if (lead) {
      if (warp == 12) {
#pragma unroll
        for (int i = 0; i < 6; i++) mbar_init(bar + (B_W + i) * 8, 1);
        load_w(&mapW, sb, 0, 0, head); load_w(&mapW, sb, 0, 1, head);
#pragma unroll
        for (int i = 0; i < 6; i++) mbar_expect(bar + (B_W + i) * 8, i < 3 ? 12288 : 6144);
      } else if (warp == 13) {
#pragma unroll
        for (int i = 0; i < B_W; i++) mbar_init(bar + i * 8, i < B_EMPTY ? 4 : (i < B_QKISS ? 16 : (i < B_KRDY ? 8 : 4)));
#pragma unroll
        for (int i = 0; i < 3; i++) {
          asm volatile("mbarrier.expect_tx.shared::cta.b64 [%0], %1;" ::"r"(bar + (B_FULL + i) * 8), "r"(i ? 24576 : 18432) : "memory");
          asm volatile("mbarrier.arrive.shared::cta.b64 _, [%0], 4;" ::"r"(bar + (B_FULL + i) * 8) : "memory");
        }
      } else {
        if (warp == 14) {
          if (head == 0) asm volatile("cp.async.bulk.prefetch.tensor.5d.L2.global [%0, {%1,%2,%3,%4,%5}];" ::"l"(&mapH), "r"(0), "r"(r0), "r"(cc), "r"(sd), "r"(pw * 3) : "memory");
          else if (head < 3) asm volatile("cp.async.bulk.prefetch.tensor.4d.L2.global [%0, {%1,%2,%3,%4}];" ::"l"(&mapC), "r"(0), "r"(r0), "r"(cc), "r"(pw * 3) : "memory");
        }
#pragma unroll
        for (int i = 0; i < 14; i++) mbar_init(bar + (B_ODONE + warp - 14 + 2 * i) * 8, 4);
      }
      asm volatile("fence.mbarrier_init.release.cluster;" ::: "memory");
    }
    __syncwarp();
    TR(3, 2, 3);
    cluster_sync();
    TR(3, 2, 4);
    if (warp == 12 && lead) {
      const uint32_t fb = bar + (B_FULL + head) * 8, eb = bar + (B_EMPTY + head) * 8;
      const uint32_t dst = sb + (head == 0 ? SM_X0 : (head == 1 ? SM_X1 : SM_X2));
      const int nl = head == 0 ? 15 : (head == 3 ? 1 : 14);
#pragma unroll 1
      for (int n = 0; n < nl; n++) {
        if (n) mbar_wait(eb, (n - 1) & 1);
        if (head == 0) {
          asm volatile("cp.async.bulk.tensor.5d.shared::cluster.global.mbarrier::complete_tx::bytes.multicast::cluster [%0], [%1, {%3,%4,%5,%6,%7}], [%2], %8;"
                       ::"r"(dst), "l"(&mapH), "r"(fb), "r"(0), "r"(8 * n + r0), "r"(cc), "r"(sd), "r"(pw * 3), "h"((uint16_t)15) : "memory");
        } else if (head < 3) {
          asm volatile("cp.async.bulk.tensor.4d.shared::cluster.global.mbarrier::complete_tx::bytes.multicast::cluster [%0], [%1, {%3,%4,%5,%6}], [%2], %7;"
                       ::"r"(dst), "l"(&mapC), "r"(fb), "r"(0), "r"(8 * n + r0), "r"(cc), "r"(pw * 3), "h"((uint16_t)15) : "memory");
        }
        if (n == 0) {
#pragma unroll 1
          for (int i = 2; i < 9; i++) load_w(&mapW, sb, i < 6 ? i >> 1 : i - 6, i < 6 ? i & 1 : 2, head);
        }
        if (head == 0) {
          if (n + 1 < nl) asm volatile("cp.async.bulk.prefetch.tensor.5d.L2.global [%0, {%1,%2,%3,%4,%5}];" ::"l"(&mapH), "r"(0), "r"(8 * n + 8 + r0), "r"(cc), "r"(sd), "r"(pw * 3) : "memory");
        } else {
          if (n + 1 < nl) asm volatile("cp.async.bulk.prefetch.tensor.4d.L2.global [%0, {%1,%2,%3,%4}];" ::"l"(&mapC), "r"(0), "r"(8 * n + 8 + r0), "r"(cc), "r"(pw * 3) : "memory");
        }
      }
    }
    if (warp >= 14 && lead) {
      const int j = warp - 14;
      int* flag = g_flags + cl * 2 + j;
#pragma unroll 1
      for (int b = 0; b < 14; b++) {
        mbar_wait(bar + (B_ODONE + 2 * b + j) * 8, 0);
        asm volatile("fence.acq_rel.gpu;\nred.relaxed.gpu.global.add.s32 [%0], 1;" ::"l"(flag + b * 56) : "memory");
      }
    }
    __syncwarp();
    cluster_sync();
  } else if (warp >= 8) {
    asm volatile("barrier.cluster.arrive.relaxed.aligned;" ::: "memory");
    TR(3, 2, 2);
    asm volatile("setmaxnreg.inc.sync.aligned.u32 184;");
    GemmCtx c;
    c.bar = bar; c.warp = warp - 8;
    const int tk = c.warp * 16 + (lane & 15), hi = lane >> 4;
    { const int col = tk >> 2, i = tk & 3;
      c.kC = sb + SM_K + (col + 3) * KS + hi * 128 + i * 16;
      c.vC = sb + SM_V + (col + 3) * 1536 + hi * 128 + (2 * i + ((col + 3) & 1)) * 16;
      c.qC = sb + SM_Q + col * 1536 + hi * 256 + (col & 1) * 64 + i * 16; }
    { const int ci = tk >> 3, kc = ci < 3 ? ci : ci + 16, i = tk & 7; c.hvalid = c.warp < 3;
      c.kH = sb + SM_K + kc * KS + hi * 128 + i * 16;
      c.vH = sb + SM_V + kc * 1536 + hi * 128 + (i >> 2) * 768 + (2 * (i & 3) + ((kc ^ (i >> 2)) & 1)) * 16; }
    TR(3, 1, 2);
    asm volatile("barrier.cluster.wait.aligned;" ::: "memory");
    TR(3, 1, 0);
    uint32_t pk[12], pv[12], pq[12];
    gemm_iter<true, false>(c, -2, pk, pv, pq);
#pragma unroll 1
    for (int b = -1; b < 12; b++) gemm_iter<false, false>(c, b, pk, pv, pq);
    gemm_iter<false, true>(c, 12, pk, pv, pq);
    cluster_sync();
  } else {
    asm volatile("barrier.cluster.arrive.relaxed.aligned;" ::: "memory");
    TR(3, 2, threadIdx.x >> 7);
    asm volatile("setmaxnreg.inc.sync.aligned.u32 152;");
    if (tid < 182) {
      float v = tid < 169 ? __bfloat162float(rpb[head * 169 + tid]) * 1.4426950408889634f : -INFINITY;
      asm volatile("st.shared.f32 [%0], %1;" ::"r"(sb + SM_RPB + tid * 4), "f"(v) : "memory");
    }
    if (tid < 192) {
      const int x = tid % 96, kc = x / 6 + 3, ch = x % 6;
      const uint32_t a = tid < 96 ? sb + SM_K + kc * KS + ch * 128 + 48 : sb + SM_V + kc * 1536 + ch * 128 + (6 + (kc & 1)) * 16;
      asm volatile("st.shared.v4.b32 [%0], {%1,%1,%1,%1};" ::"r"(a), "r"(0) : "memory");
    }
    const int j = warp >> 2, w = warp & 3;
    int variant = w;
    if (strip == 0 && j == 0 && w < 2) variant = 4;
    if (strip == 6 && j == 1 && w >= 2) variant = 5;
    const uint32_t qa = sb + SM_Q + (8 * j + 2 * w + ((lane >> 3) & 1)) * 1536 + (lane >> 4) * 256 + (((lane & 7) * 16) ^ (((lane >> 3) & 1) * 64));
    const uint64_t dK = mkdesc(SBC + SM_K, 128, KS, 0) + j * (8 * KS / 16);
    const uint64_t dV = mkdesc(SBC + SM_V, 768, 128, 0) + j * (8 * 1536 / 16);
    uint8_t* op = reinterpret_cast<uint8_t*>(out) + (size_t)(ph * 224 + 2 * (strip * 16 + 8 * j + 2 * w) + pw) * 384 + (size_t)(2 * head) * ROWB;
    const uint32_t off0 = ((lane & 3) == 3 ? ROWB : (lane & 3) * 128) + (lane >> 2) * 16;
    const uint32_t off1 = ROWB + 128 + (lane & 2) * 64 + (lane >> 2) * 16 + (lane & 1) * 8;
    TR(3, 3, j);
    asm volatile("barrier.cluster.wait.aligned;" ::: "memory");
    TR(3, 3, 2 + j);
    fence_async();
    asm volatile("bar.sync 1, 256;" ::: "memory");
    float T[14];
    bool b0 = false, b1 = false;
    uint32_t ra0 = 0, ra1 = 0, meta = 0;
    uint32_t q[12];
    mbar_wait(bar + B_Q0 * 8, 0);
#pragma unroll
    for (int k = 0; k < 3; k++) ldsm4(qa + k * 512, q[4 * k], q[4 * k + 1], q[4 * k + 2], q[4 * k + 3]);
#pragma unroll 1
    for (int b = 0; b < 14; b++) {
      const uint32_t pa = b & 1;
      if (b <= 1 || b == 13) {
        uint32_t ln; asm volatile("mov.u32 %0, %%laneid;" : "=r"(ln));
        const int g = ln >> 2, t = ln & 3;
        const int sw = b == 0 ? max(g + 1, 4) : (b == 13 ? min(g + 1, 5) : g + 1);
        const int i0 = 2 * t, i1 = 2 * t + 1;
        b0 = i0 <= sw - 2; b1 = i1 <= sw - 2;
        const int m = sw - 1;
        ra0 = sb + SM_RPB + (i0 == m ? 13 : i0 + (b0 ? 8 : 0) - g + 2) * 52;
        ra1 = sb + SM_RPB + (i1 == m ? 13 : i1 + (b1 ? 8 : 0) - g + 2) * 52;
#pragma unroll
        for (int jj = 0; jj < 7; jj++) { T[2 * jj] = lds_f32(ra0 + (jj + 3) * 4); T[2 * jj + 1] = lds_f32(ra1 + (jj + 3) * 4); }
        uint32_t m16 = 0x8888u;
#pragma unroll
        for (int i = 0; i < 8; i++) m16 |= (uint32_t)(((i <= sw - 2) ^ (i >> 2) ^ t ^ b) & 1) << (2 * i);
        meta = m16 | (m16 << 16);
      } else meta ^= 0x55555555u;
      float SA[56], SB[56];
      const uint64_t dA = dK + pa * (KSLOT >> 4), dB = dK + (pa ^ 1) * (KSLOT >> 4);
      TR(j, b, 0);
      mbar_wait(bar + B_KRDY * 8, pa);
      TR(j, b, 1);
      wg_fence();
      wg_rs112<0>(SA, q[0], q[1], q[2], q[3], dA);
      wg_rs112<0>(SB, q[0], q[1], q[2], q[3], dB);
      wg_rs112<1>(SA, q[4], q[5], q[6], q[7], dA + 16);
      wg_rs112<1>(SB, q[4], q[5], q[6], q[7], dB + 16);
      wg_rs112<1>(SA, q[8], q[9], q[10], q[11], dA + 32);
      wg_rs112<1>(SB, q[8], q[9], q[10], q[11], dB + 32);
      wg_commit();
      mbar_arrive_elect(bar + B_QKISS * 8);
      TR(j, b, 2);
      wg_wait<0>(); pin(SA); pin(SB);
      mbar_arrive_elect(bar + B_KFREE * 8);
      TR(j, b, 3);
      uint32_t P[28];
      float su, sl;
      switch (variant) {
        case 0: softmax_tile<0, 1, false>(SA, SB, T, b0, b1, ra0, ra1, 0, P, su, sl); break;
        case 1: softmax_tile<2, 3, false>(SA, SB, T, b0, b1, ra0, ra1, 0, P, su, sl); break;
        case 2: softmax_tile<4, 5, false>(SA, SB, T, b0, b1, ra0, ra1, 0, P, su, sl); break;
        case 3: softmax_tile<6, 7, false>(SA, SB, T, b0, b1, ra0, ra1, 0, P, su, sl); break;
        case 4: softmax_tile<3, 3, true>(SA, SB, T, b0, b1, ra0, ra1, 2 * w, P, su, sl); break;
        default: softmax_tile<4, 4, true>(SA, SB, T, b0, b1, ra0, ra1, 2 * w, P, su, sl); break;
      }
      float O[24];
      TR(j, b, 4);
      su += __shfl_xor_sync(0xffffffffu, su, 1); sl += __shfl_xor_sync(0xffffffffu, sl, 1);
      mbar_wait(bar + B_VQRDY * 8, pa);
      TR(j, b, 5);
      su += __shfl_xor_sync(0xffffffffu, su, 2); sl += __shfl_xor_sync(0xffffffffu, sl, 2);
#pragma unroll
      for (int k = 0; k < 3; k++) ldsm4(qa + (pa ^ 1) * 128 + k * 512, q[4 * k], q[4 * k + 1], q[4 * k + 2], q[4 * k + 3]);
      wg_fence();
      wg_sp48<0>(O, P[0], P[1], P[2], P[3], dV, meta);
#pragma unroll
      for (int s = 1; s < 7; s++) wg_sp48<1>(O, P[4 * s], P[4 * s + 1], P[4 * s + 2], P[4 * s + 3], dV + s * 192, meta);
      wg_commit();
      mbar_arrive_elect(bar + B_PVISS * 8);
      TR(j, b, 6);
      const float ru = __fdividef(1.f, su), rl = __fdividef(1.f, sl);
      wg_wait<0>(); pin(O);
      mbar_arrive_elect(bar + B_VFREE * 8);
      TR(j, b, 7);
      *reinterpret_cast<uint4*>(op + off0) = make_uint4(pack2(O[0] * ru, O[1] * ru), pack2(O[4] * ru, O[5] * ru), pack2(O[8] * ru, O[9] * ru), pack2(O[12] * ru, O[13] * ru));
      *reinterpret_cast<uint4*>(op + off0 + 768) = make_uint4(pack2(O[2] * rl, O[3] * rl), pack2(O[6] * rl, O[7] * rl), pack2(O[10] * rl, O[11] * rl), pack2(O[14] * rl, O[15] * rl));
      *reinterpret_cast<uint2*>(op + off1) = make_uint2(pack2(O[16] * ru, O[17] * ru), pack2(O[20] * ru, O[21] * ru));
      *reinterpret_cast<uint2*>(op + off1 + 768) = make_uint2(pack2(O[18] * rl, O[19] * rl), pack2(O[22] * rl, O[23] * rl));
      op += 8 * ROWB;
      __syncwarp();
      mbar_arrive_elect(bar + (B_ODONE + 2 * b + j) * 8);
      TR(j, b, 8);
    }
    TR2(blockIdx.x, 2);
    cluster_sync();
  }
}

constexpr int NSTB = 4;
constexpr int SM_B_ST = 0;
constexpr int SM_B_IN = 49152;
constexpr int SM_B_W = SM_B_IN + NSTB * 24576;
constexpr int WOS = 3088;
constexpr int SM_B_BAR = SM_B_W + 24 * WOS;
constexpr int SM_B_TOTAL = SM_B_BAR + 64;

__global__ void __launch_bounds__(288, 1)
na_proj_kernel(const __grid_constant__ CUtensorMap mapI, const __grid_constant__ CUtensorMap mapO, const __nv_bfloat16* __restrict__ wo) {
  extern __shared__ __align__(1024) uint8_t smem_raw[];
  const uint32_t sb = smem_u32(smem_raw);
  if ((sb & 0x3FFFF) != SBC) return;
  const uint32_t bar = sb + SM_B_BAR;
  const int tid = threadIdx.x, lane = tid & 31;
  const int warp = __shfl_sync(0xffffffffu, tid >> 5, 0);
  TR2(132 + blockIdx.x, 0);
  TRB(47, 0);
  if (warp < 8) {
    uint4 wv[18];
#pragma unroll
    for (int i = 0; i < 18; i++) wv[i] = __ldg(reinterpret_cast<const uint4*>(wo) + tid + i * 256);
#pragma unroll
    for (int i = 0; i < 18; i++) {
      const int pc = tid + i * 256, row = pc / 24, ng = pc - row * 24, hd = row / 48, dim = row - hd * 48, g8 = dim >> 3, t = (dim >> 1) & 3;
      const int kk = (g8 < 4 ? t * 8 + g8 * 2 : 32 + t * 4 + (g8 - 4) * 2) + (dim & 1);
      asm volatile("st.shared.v4.b32 [%0], {%1,%2,%3,%4};" ::"r"(sb + SM_B_W + ng * WOS + (hd * 48 + kk) * 16), "r"(wv[i].x), "r"(wv[i].y), "r"(wv[i].z), "r"(wv[i].w) : "memory");
    }
    fence_async();
  } else if (elect_one()) {
#pragma unroll
    for (int i = 0; i < 2 * NSTB; i++) mbar_init(bar + i * 8, i < NSTB ? 1 : 4);
  }
  __syncthreads();
  const int step = gridDim.x;
  TRB(47, 1);
  if (warp == 8) {
    int it = 0;
    uint32_t spin = 0;
#pragma unroll 1
    for (int n = blockIdx.x; n < 784 && spin < SPIN_LIMIT; spin++) {
      int v = 0;
      const int mine = n + lane * step;
      if (lane < 8 && mine < 784) asm volatile("ld.acquire.gpu.global.s32 %0, [%1];" : "=r"(v) : "l"(g_flags + mine) : "memory");
      int cnt = __ffs(~__ballot_sync(0xffffffffu, v >= 4)) - 1;
      asm volatile("fence.proxy.async.global;" ::: "memory");
      __syncwarp();
#pragma unroll 1
      for (; cnt > 0; cnt--, n += step, it++) {
        TRB(it, 0);
        if (elect_one()) {
          const int b = n / 56, rem = n - b * 56, par = rem / 14;
          const int st = it & (NSTB - 1), use = it / NSTB;
          if (use) mbar_wait(bar + (NSTB + st) * 8, (use - 1) & 1);
          mbar_expect(bar + st * 8, 24576);
          asm volatile("cp.async.bulk.tensor.3d.shared::cluster.global.mbarrier::complete_tx::bytes [%0], [%1, {%3,%4,%5}], [%2];"
                       ::"r"(sb + SM_B_IN + st * 24576), "l"(&mapI), "r"(bar + st * 8), "r"((par & 1) * 192), "r"(8 * b), "r"((par >> 1) * 112 + (rem - par * 14) * 8) : "memory");
        }
        __syncwarp();
        TRB(it, 2);
      }
    }
    for (int n = blockIdx.x + lane * step; n < 784; n += 32 * step) g_flags[n] = 0;
  } else {
    const int wg = warp >> 2, w = warp & 3;
    constexpr uint64_t db = mkdesc(SBC + SM_B_W, 128, WOS, 0);
    const uint32_t st = sb + SM_B_ST + warp * 6144;
    const uint32_t sta = st + (lane & 15) * 128 + (((lane >> 4) ^ (lane & 7)) * 16);
    int it = wg;
#pragma unroll 1
    for (int n = blockIdx.x + wg * step; n < 784; n += 2 * step, it += 2) {
      const int b = n / 56, rem = n - b * 56, par = rem / 14, sg = it & (NSTB - 1);
      const uint64_t da = mkdesc(SBC + SM_B_IN, 128, 3072, 0) + sg * (24576 / 16);
      float D[96];
      mbar_wait(bar + sg * 8, (it / NSTB) & 1);
      TRB(it, 3);
      wg_fence();
      wg_ss192<0>(D, da, db);
#pragma unroll
      for (int k = 1; k < 12; k++) wg_ss192<1>(D, da + k * 16, db + k * 16);
      wg_commit();
      TRB(it, 4);
      if (lane == 0) asm volatile("cp.async.bulk.wait_group.read 0;" ::: "memory");
      __syncwarp();
      wg_wait<0>(); pin(D);
      mbar_arrive_elect(bar + (NSTB + sg) * 8);
      TRB(it, 5);
#pragma unroll
      for (int q = 0; q < 12; q++)
        stsm4((sta ^ ((q & 3) * 32)) + (q >> 2) * 2048,
              pack2(D[8 * q], D[8 * q + 1]), pack2(D[8 * q + 2], D[8 * q + 3]), pack2(D[8 * q + 4], D[8 * q + 5]), pack2(D[8 * q + 6], D[8 * q + 7]));
      fence_async();
      __syncwarp();
      if (lane == 0) {
        asm volatile("cp.async.bulk.tensor.4d.global.shared::cta.bulk_group [%0, {%2,%3,%4,%5}], [%1];"
                     ::"l"(&mapO), "r"(st), "r"(0), "r"(8 * b), "r"((par >> 1) * 112 + (rem - par * 14) * 8 + 2 * w), "r"((par & 1) * 3) : "memory");
        asm volatile("cp.async.bulk.commit_group;" ::: "memory");
      }
      TRB(it, 6);
    }
    if (lane == 0) asm volatile("cp.async.bulk.wait_group 0;" ::: "memory");
    TR2(132 + blockIdx.x, 2);
  }
}

typedef CUresult (*EncodeFn)(CUtensorMap*, CUtensorMapDataType, cuuint32_t, void*, const cuuint64_t*, const cuuint64_t*, const cuuint32_t*,
                             const cuuint32_t*, CUtensorMapInterleave, CUtensorMapSwizzle, CUtensorMapL2promotion, CUtensorMapFloatOOBfill);

extern "C" void kernel_launch(void* const* d_in, const int* in_sizes, int n_in, void* d_out, int out_size) {
  const __nv_bfloat16* x = (const __nv_bfloat16*)d_in[0];
  const __nv_bfloat16* wqkv = (const __nv_bfloat16*)d_in[1];
  const __nv_bfloat16* wo = (const __nv_bfloat16*)d_in[2];
  const __nv_bfloat16* rpb = (const __nv_bfloat16*)d_in[3];
  __nv_bfloat16* out = (__nv_bfloat16*)d_out;

  static EncodeFn enc = nullptr;
  if (!enc) {
    void* fn = nullptr; cudaDriverEntryPointQueryResult qr;
    cudaGetDriverEntryPoint("cuTensorMapEncodeTiled", &fn, cudaEnableDefault, &qr);
    enc = (EncodeFn)fn;
    cudaFuncSetAttribute(na_attn_kernel, cudaFuncAttributeMaxDynamicSharedMemorySize, SM_A_TOTAL);
    cudaFuncSetAttribute(na_proj_kernel, cudaFuncAttributeMaxDynamicSharedMemorySize, SM_B_TOTAL);
  }
  CUtensorMap mC, mH, mO, mI, mW;
  const cuuint32_t ones[5] = {1, 1, 1, 1, 1};
  {
    cuuint64_t dim[4] = {64, 112, 224, 6}, str[3] = {(cuuint64_t)ROWB, 768, 128};
    cuuint32_t box[4] = {64, 4, 16, 3}, boxo[4] = {64, 8, 2, 3};
    enc(&mC, CU_TENSOR_MAP_DATA_TYPE_BFLOAT16, 4, (void*)x, dim, str, box, ones, CU_TENSOR_MAP_INTERLEAVE_NONE, CU_TENSOR_MAP_SWIZZLE_128B,
        CU_TENSOR_MAP_L2_PROMOTION_L2_128B, CU_TENSOR_MAP_FLOAT_OOB_FILL_NONE);
    enc(&mO, CU_TENSOR_MAP_DATA_TYPE_BFLOAT16, 4, (void*)out, dim, str, boxo, ones, CU_TENSOR_MAP_INTERLEAVE_NONE, CU_TENSOR_MAP_SWIZZLE_128B,
        CU_TENSOR_MAP_L2_PROMOTION_NONE, CU_TENSOR_MAP_FLOAT_OOB_FILL_NONE);
  }
  {
    cuuint64_t dim[5] = {64, 112, 224, 2, 6}, str[4] = {(cuuint64_t)ROWB, 768, 19 * 768, 128};
    cuuint32_t box[5] = {64, 8, 3, 2, 3};
    enc(&mH, CU_TENSOR_MAP_DATA_TYPE_BFLOAT16, 5, (void*)x, dim, str, box, ones, CU_TENSOR_MAP_INTERLEAVE_NONE, CU_TENSOR_MAP_SWIZZLE_128B,
        CU_TENSOR_MAP_L2_PROMOTION_L2_128B, CU_TENSOR_MAP_FLOAT_OOB_FILL_NONE);
  }
  {
    cuuint64_t dim[3] = {384, 112, 224}, str[2] = {(cuuint64_t)ROWB, 768};
    cuuint32_t box[3] = {192, 8, 8};
    enc(&mI, CU_TENSOR_MAP_DATA_TYPE_BFLOAT16, 3, (void*)out, dim, str, box, ones, CU_TENSOR_MAP_INTERLEAVE_NONE, CU_TENSOR_MAP_SWIZZLE_NONE,
        CU_TENSOR_MAP_L2_PROMOTION_NONE, CU_TENSOR_MAP_FLOAT_OOB_FILL_NONE);
  }
  {
    cuuint64_t dim[3] = {16, 192, 36}, str[2] = {1152, 32};
    cuuint32_t box[3] = {16, 64, 3};
    enc(&mW, CU_TENSOR_MAP_DATA_TYPE_BFLOAT16, 3, (void*)wqkv, dim, str, box, ones, CU_TENSOR_MAP_INTERLEAVE_NONE, CU_TENSOR_MAP_SWIZZLE_32B,
        CU_TENSOR_MAP_L2_PROMOTION_L2_128B, CU_TENSOR_MAP_FLOAT_OOB_FILL_NONE);
  }
  na_attn_kernel<<<112, 512, SM_A_TOTAL>>>(mC, mH, mW, rpb, out);
#define NBCTA 20
  cudaLaunchConfig_t cfg = {};
  cfg.gridDim = dim3(NBCTA); cfg.blockDim = dim3(288); cfg.dynamicSmemBytes = SM_B_TOTAL; cfg.stream = cudaStreamPerThread;
  cudaLaunchAttribute at[1];
  at[0].id = cudaLaunchAttributeProgrammaticStreamSerialization; at[0].val.programmaticStreamSerializationAllowed = 1;
  cfg.attrs = at; cfg.numAttrs = 1;
  cudaLaunchKernelEx(&cfg, na_proj_kernel, mI, mO, wo);
}
```

```cpp
#include <cuda_runtime.h>
#include <cuda_bf16.h>
#include <cuda.h>
#include <stdint.h>

#define SPIN_LIMIT (1u << 18)

__device__ __forceinline__ uint32_t smem_u32(const void* p) { return (uint32_t)__cvta_generic_to_shared(p); }
__device__ __forceinline__ void wg_fence() { asm volatile("wgmma.fence.sync.aligned;" ::: "memory"); }
__device__ __forceinline__ void wg_commit() { asm volatile("wgmma.commit_group.sync.aligned;" ::: "memory"); }
template <int N> __device__ __forceinline__ void wg_wait() { asm volatile("wgmma.wait_group.sync.aligned %0;" ::"n"(N) : "memory"); }
template <int N> __device__ __forceinline__ void pin(float (&d)[N]) {
#pragma unroll
  for (int i = 0; i < N; i++) asm volatile("" : "+f"(d[i])::"memory");
}
__host__ __device__ constexpr uint64_t mkdesc(uint32_t addr, uint32_t lbo, uint32_t sbo, uint32_t sw) {
  return (uint64_t)((addr & 0x3FFFF) >> 4) | ((uint64_t)(lbo >> 4) << 16) | ((uint64_t)(sbo >> 4) << 32) | ((uint64_t)sw << 62);
}
__device__ __forceinline__ void mbar_init(uint32_t bar, uint32_t cnt) { asm volatile("mbarrier.init.shared::cta.b64 [%0], %1;" ::"r"(bar), "r"(cnt) : "memory"); }
__device__ __forceinline__ void mbar_arrive(uint32_t bar) { asm volatile("mbarrier.arrive.shared::cta.b64 _, [%0];" ::"r"(bar) : "memory"); }
__device__ __forceinline__ bool elect_one() {
  uint32_t r; asm volatile("{\n.reg .pred p;\nelect.sync _|p, 0xffffffff;\nselp.u32 %0, 1, 0, p;\n}" : "=r"(r)); return r;
}
__device__ __forceinline__ void mbar_arrive_elect(uint32_t bar) {
  asm volatile("{\n.reg .pred p;\nelect.sync _|p, 0xffffffff;\n@p mbarrier.arrive.shared::cta.b64 _, [%0];\n}" ::"r"(bar) : "memory");
}
__device__ __forceinline__ void mbar_expect(uint32_t bar, uint32_t bytes) { asm volatile("mbarrier.arrive.expect_tx.shared::cta.b64 _, [%0], %1;" ::"r"(bar), "r"(bytes) : "memory"); }
__device__ __forceinline__ void mbar_arrive_remote(uint32_t bar, uint32_t cta) {
  asm volatile("{\n.reg .b32 ra;\nmapa.shared::cluster.u32 ra, %0, %1;\nmbarrier.arrive.shared::cluster.b64 _, [ra];\n}" ::"r"(bar), "r"(cta) : "memory");
}
__device__ __forceinline__ void mbar_wait(uint32_t bar, uint32_t parity) {
  asm volatile("{\n.reg .pred p;\n.reg .b32 n;\nmov.b32 n, 0;\nWL:\nmbarrier.try_wait.parity.shared::cta.b64 p, [%0], %1;\n@p bra WD;\n"
               "add.u32 n, n, 1;\nsetp.lt.u32 p, n, 65536;\n@p bra WL;\nWD:\n}" ::"r"(bar), "r"(parity) : "memory");
}
__device__ __forceinline__ void fence_async() { asm volatile("fence.proxy.async.shared::cta;" ::: "memory"); }
__device__ __forceinline__ void cluster_sync() {
  asm volatile("barrier.cluster.arrive.relaxed.aligned;\nbarrier.cluster.wait.aligned;" ::: "memory");
}
__device__ __forceinline__ uint32_t pack2(float lo, float hi) {
  uint32_t r; asm("cvt.rn.bf16x2.f32 %0, %1, %2;" : "=r"(r) : "f"(hi), "f"(lo)); return r;
}
__device__ __forceinline__ void stsm4(uint32_t a, uint32_t r0, uint32_t r1, uint32_t r2, uint32_t r3) {
  asm volatile("stmatrix.sync.aligned.m8n8.x4.shared.b16 [%0], {%1,%2,%3,%4};" ::"r"(a), "r"(r0), "r"(r1), "r"(r2), "r"(r3) : "memory");
}
__device__ __forceinline__ void ldsm4(uint32_t a, uint32_t& r0, uint32_t& r1, uint32_t& r2, uint32_t& r3) {
  asm volatile("ldmatrix.sync.aligned.m8n8.x4.shared.b16 {%0,%1,%2,%3}, [%4];" : "=r"(r0), "=r"(r1), "=r"(r2), "=r"(r3) : "r"(a) : "memory");
}
__device__ __forceinline__ float lds_f32(uint32_t a) { float v; asm volatile("ld.shared.f32 %0, [%1];" : "=f"(v) : "r"(a)); return v; }
__device__ __forceinline__ float ex2(float x) { float y; asm("ex2.approx.ftz.f32 %0, %1;" : "=f"(y) : "f"(x)); return y; }

template<int SC> __device__ __forceinline__ void wg_ss144(float (&d)[72], uint64_t da, uint64_t db) {
  asm volatile("{\n.reg .pred p;\nsetp.ne.b32 p, %74, 0;\nwgmma.mma_async.sync.aligned.m64n144k16.f32.bf16.bf16 {%0,%1,%2,%3,%4,%5,%6,%7,%8,%9,%10,%11,%12,%13,%14,%15,%16,%17,%18,%19,%20,%21,%22,%23,%24,%25,%26,%27,%28,%29,%30,%31,%32,%33,%34,%35,%36,%37,%38,%39,%40,%41,%42,%43,%44,%45,%46,%47,%48,%49,%50,%51,%52,%53,%54,%55,%56,%57,%58,%59,%60,%61,%62,%63,%64,%65,%66,%67,%68,%69,%70,%71}, %72, %73, p, 1, 1, 0, 1;\n}\n"
    : "+f"(d[0]),"+f"(d[1]),"+f"(d[2]),"+f"(d[3]),"+f"(d[4]),"+f"(d[5]),"+f"(d[6]),"+f"(d[7]),"+f"(d[8]),"+f"(d[9]),"+f"(d[10]),"+f"(d[11]),"+f"(d[12]),"+f"(d[13]),"+f"(d[14]),"+f"(d[15]),"+f"(d[16]),"+f"(d[17]),"+f"(d[18]),"+f"(d[19]),"+f"(d[20]),"+f"(d[21]),"+f"(d[22]),"+f"(d[23]),"+f"(d[24]),"+f"(d[25]),"+f"(d[26]),"+f"(d[27]),"+f"(d[28]),"+f"(d[29]),"+f"(d[30]),"+f"(d[31]),"+f"(d[32]),"+f"(d[33]),"+f"(d[34]),"+f"(d[35]),"+f"(d[36]),"+f"(d[37]),"+f"(d[38]),"+f"(d[39]),"+f"(d[40]),"+f"(d[41]),"+f"(d[42]),"+f"(d[43]),"+f"(d[44]),"+f"(d[45]),"+f"(d[46]),"+f"(d[47]),"+f"(d[48]),"+f"(d[49]),"+f"(d[50]),"+f"(d[51]),"+f"(d[52]),"+f"(d[53]),"+f"(d[54]),"+f"(d[55]),"+f"(d[56]),"+f"(d[57]),"+f"(d[58]),"+f"(d[59]),"+f"(d[60]),"+f"(d[61]),"+f"(d[62]),"+f"(d[63]),"+f"(d[64]),"+f"(d[65]),"+f"(d[66]),"+f"(d[67]),"+f"(d[68]),"+f"(d[69]),"+f"(d[70]),"+f"(d[71]) : "l"(da), "l"(db), "n"(SC));
}
template<int SC> __device__ __forceinline__ void wg_ss96(float (&d)[48], uint64_t da, uint64_t db) {
  asm volatile("{\n.reg .pred p;\nsetp.ne.b32 p, %50, 0;\nwgmma.mma_async.sync.aligned.m64n96k16.f32.bf16.bf16 {%0,%1,%2,%3,%4,%5,%6,%7,%8,%9,%10,%11,%12,%13,%14,%15,%16,%17,%18,%19,%20,%21,%22,%23,%24,%25,%26,%27,%28,%29,%30,%31,%32,%33,%34,%35,%36,%37,%38,%39,%40,%41,%42,%43,%44,%45,%46,%47}, %48, %49, p, 1, 1, 0, 1;\n}\n"
    : "+f"(d[0]),"+f"(d[1]),"+f"(d[2]),"+f"(d[3]),"+f"(d[4]),"+f"(d[5]),"+f"(d[6]),"+f"(d[7]),"+f"(d[8]),"+f"(d[9]),"+f"(d[10]),"+f"(d[11]),"+f"(d[12]),"+f"(d[13]),"+f"(d[14]),"+f"(d[15]),"+f"(d[16]),"+f"(d[17]),"+f"(d[18]),"+f"(d[19]),"+f"(d[20]),"+f"(d[21]),"+f"(d[22]),"+f"(d[23]),"+f"(d[24]),"+f"(d[25]),"+f"(d[26]),"+f"(d[27]),"+f"(d[28]),"+f"(d[29]),"+f"(d[30]),"+f"(d[31]),"+f"(d[32]),"+f"(d[33]),"+f"(d[34]),"+f"(d[35]),"+f"(d[36]),"+f"(d[37]),"+f"(d[38]),"+f"(d[39]),"+f"(d[40]),"+f"(d[41]),"+f"(d[42]),"+f"(d[43]),"+f"(d[44]),"+f"(d[45]),"+f"(d[46]),"+f"(d[47]) : "l"(da), "l"(db), "n"(SC));
}
template<int SC> __device__ __forceinline__ void wg_rs112(float (&d)[56], uint32_t a0, uint32_t a1, uint32_t a2, uint32_t a3, uint64_t db) {
  asm volatile("{\n.reg .pred p;\nsetp.ne.b32 p, %61, 0;\nwgmma.mma_async.sync.aligned.m64n112k16.f32.bf16.bf16 {%0,%1,%2,%3,%4,%5,%6,%7,%8,%9,%10,%11,%12,%13,%14,%15,%16,%17,%18,%19,%20,%21,%22,%23,%24,%25,%26,%27,%28,%29,%30,%31,%32,%33,%34,%35,%36,%37,%38,%39,%40,%41,%42,%43,%44,%45,%46,%47,%48,%49,%50,%51,%52,%53,%54,%55}, {%56,%57,%58,%59}, %60, p, 1, 1, 0;\n}\n"
    : "+f"(d[0]),"+f"(d[1]),"+f"(d[2]),"+f"(d[3]),"+f"(d[4]),"+f"(d[5]),"+f"(d[6]),"+f"(d[7]),"+f"(d[8]),"+f"(d[9]),"+f"(d[10]),"+f"(d[11]),"+f"(d[12]),"+f"(d[13]),"+f"(d[14]),"+f"(d[15]),"+f"(d[16]),"+f"(d[17]),"+f"(d[18]),"+f"(d[19]),"+f"(d[20]),"+f"(d[21]),"+f"(d[22]),"+f"(d[23]),"+f"(d[24]),"+f"(d[25]),"+f"(d[26]),"+f"(d[27]),"+f"(d[28]),"+f"(d[29]),"+f"(d[30]),"+f"(d[31]),"+f"(d[32]),"+f"(d[33]),"+f"(d[34]),"+f"(d[35]),"+f"(d[36]),"+f"(d[37]),"+f"(d[38]),"+f"(d[39]),"+f"(d[40]),"+f"(d[41]),"+f"(d[42]),"+f"(d[43]),"+f"(d[44]),"+f"(d[45]),"+f"(d[46]),"+f"(d[47]),"+f"(d[48]),"+f"(d[49]),"+f"(d[50]),"+f"(d[51]),"+f"(d[52]),"+f"(d[53]),"+f"(d[54]),"+f"(d[55]) : "r"(a0), "r"(a1), "r"(a2), "r"(a3), "l"(db), "n"(SC));
}
template<int SC> __device__ __forceinline__ void wg_sp48(float (&d)[24], uint32_t a0, uint32_t a1, uint32_t a2, uint32_t a3, uint64_t db, uint32_t meta) {
  asm volatile("{\n.reg .pred p;\nsetp.ne.b32 p, %30, 0;\nwgmma.mma_async.sp.sync.aligned.m64n48k32.f32.bf16.bf16 {%0,%1,%2,%3,%4,%5,%6,%7,%8,%9,%10,%11,%12,%13,%14,%15,%16,%17,%18,%19,%20,%21,%22,%23}, {%24,%25,%26,%27}, %28, %29, 0, p, 1, 1, 1;\n}\n"
    : "+f"(d[0]),"+f"(d[1]),"+f"(d[2]),"+f"(d[3]),"+f"(d[4]),"+f"(d[5]),"+f"(d[6]),"+f"(d[7]),"+f"(d[8]),"+f"(d[9]),"+f"(d[10]),"+f"(d[11]),"+f"(d[12]),"+f"(d[13]),"+f"(d[14]),"+f"(d[15]),"+f"(d[16]),"+f"(d[17]),"+f"(d[18]),"+f"(d[19]),"+f"(d[20]),"+f"(d[21]),"+f"(d[22]),"+f"(d[23]) : "r"(a0), "r"(a1), "r"(a2), "r"(a3), "l"(db), "r"(meta), "n"(SC));
}
template<int SC> __device__ __forceinline__ void wg_ss192(float (&d)[96], uint64_t da, uint64_t db) {
  asm volatile("{\n.reg .pred p;\nsetp.ne.b32 p, %98, 0;\nwgmma.mma_async.sync.aligned.m64n192k16.f32.bf16.bf16 {%0,%1,%2,%3,%4,%5,%6,%7,%8,%9,%10,%11,%12,%13,%14,%15,%16,%17,%18,%19,%20,%21,%22,%23,%24,%25,%26,%27,%28,%29,%30,%31,%32,%33,%34,%35,%36,%37,%38,%39,%40,%41,%42,%43,%44,%45,%46,%47,%48,%49,%50,%51,%52,%53,%54,%55,%56,%57,%58,%59,%60,%61,%62,%63,%64,%65,%66,%67,%68,%69,%70,%71,%72,%73,%74,%75,%76,%77,%78,%79,%80,%81,%82,%83,%84,%85,%86,%87,%88,%89,%90,%91,%92,%93,%94,%95}, %96, %97, p, 1, 1, 0, 1;\n}\n"
    : "+f"(d[0]),"+f"(d[1]),"+f"(d[2]),"+f"(d[3]),"+f"(d[4]),"+f"(d[5]),"+f"(d[6]),"+f"(d[7]),"+f"(d[8]),"+f"(d[9]),"+f"(d[10]),"+f"(d[11]),"+f"(d[12]),"+f"(d[13]),"+f"(d[14]),"+f"(d[15]),"+f"(d[16]),"+f"(d[17]),"+f"(d[18]),"+f"(d[19]),"+f"(d[20]),"+f"(d[21]),"+f"(d[22]),"+f"(d[23]),"+f"(d[24]),"+f"(d[25]),"+f"(d[26]),"+f"(d[27]),"+f"(d[28]),"+f"(d[29]),"+f"(d[30]),"+f"(d[31]),"+f"(d[32]),"+f"(d[33]),"+f"(d[34]),"+f"(d[35]),"+f"(d[36]),"+f"(d[37]),"+f"(d[38]),"+f"(d[39]),"+f"(d[40]),"+f"(d[41]),"+f"(d[42]),"+f"(d[43]),"+f"(d[44]),"+f"(d[45]),"+f"(d[46]),"+f"(d[47]),"+f"(d[48]),"+f"(d[49]),"+f"(d[50]),"+f"(d[51]),"+f"(d[52]),"+f"(d[53]),"+f"(d[54]),"+f"(d[55]),"+f"(d[56]),"+f"(d[57]),"+f"(d[58]),"+f"(d[59]),"+f"(d[60]),"+f"(d[61]),"+f"(d[62]),"+f"(d[63]),"+f"(d[64]),"+f"(d[65]),"+f"(d[66]),"+f"(d[67]),"+f"(d[68]),"+f"(d[69]),"+f"(d[70]),"+f"(d[71]),"+f"(d[72]),"+f"(d[73]),"+f"(d[74]),"+f"(d[75]),"+f"(d[76]),"+f"(d[77]),"+f"(d[78]),"+f"(d[79]),"+f"(d[80]),"+f"(d[81]),"+f"(d[82]),"+f"(d[83]),"+f"(d[84]),"+f"(d[85]),"+f"(d[86]),"+f"(d[87]),"+f"(d[88]),"+f"(d[89]),"+f"(d[90]),"+f"(d[91]),"+f"(d[92]),"+f"(d[93]),"+f"(d[94]),"+f"(d[95]) : "l"(da), "l"(db), "n"(SC));
}

constexpr uint32_t SBC = 1024;
constexpr int ROWB = 2 * 224 * 384;
constexpr int KS = 832;
constexpr int KSLOT = 22 * KS;
constexpr int SM_X0 = 0;
constexpr int SM_X1 = 18432;
constexpr int SM_X2 = SM_X1 + 24576;
constexpr int SM_W = SM_X2 + 24576;
constexpr int SM_K = SM_W + 55296;
constexpr int SM_V = SM_K + 2 * KSLOT;
constexpr int SM_Q = SM_V + 22 * 1536;
constexpr int SM_RPB = SM_Q + 24576;
constexpr int SM_BAR = SM_RPB + 768;
constexpr int SM_A_TOTAL = SM_BAR + 512;
enum { B_FULL = 0, B_EMPTY = 3, B_QKISS = 6, B_PVISS, B_KFREE, B_VFREE, B_KRDY, B_VQRDY, B_Q0, B_W, B_ODONE = B_W + 6, B_COUNT = B_ODONE + 28 };

__device__ int g_flags[784];

#define TR(role, it, k)
#define TRB(it, k)
#define TR2(blk, k)

struct GemmCtx {
  uint32_t bar;
  uint32_t kC, vC, qC;
  uint32_t kH, vH;
  uint32_t em;
  bool hvalid;
  int warp;
};

template <int STRIDE> __device__ __forceinline__ void dump12(uint32_t a, const uint32_t (&r)[12]) {
#pragma unroll
  for (int j = 0; j < 3; j++) stsm4(a + j * 2 * STRIDE, r[4 * j], r[4 * j + 1], r[4 * j + 2], r[4 * j + 3]);
}
template <int N> __device__ __forceinline__ void pack12(uint32_t (&r)[12], const float (&d)[N], int off) {
#pragma unroll
  for (int j = 0; j < 12; j++) r[j] = pack2(d[off + 2 * j], d[off + 2 * j + 1]);
}
template <int XS, int K0, int K1> __device__ __forceinline__ void issue_core(float (&d)[72]) {
  constexpr uint64_t da = mkdesc(SBC + XS, 16, 1024, 1), db = mkdesc(SBC + SM_W, 2048, 256, 3);
  if (K0 == 0) { wg_fence(); wg_ss144<0>(d, da, db); }
#pragma unroll
  for (int k = K0 ? K0 : 1; k < K1; k++) wg_ss144<1>(d, da + (k >> 2) * 512 + (k & 3) * 2, db + (k >> 2) * 1152 + (k & 3) * 32);
  wg_commit();
}
template <int K0, int K1> __device__ __forceinline__ void issue_halo(float (&d)[48]) {
  constexpr uint64_t da = mkdesc(SBC + SM_X0, 16, 1024, 1), db = mkdesc(SBC + SM_W, 2048, 256, 3);
  if (K0 == 0) { wg_fence(); wg_ss96<0>(d, da, db); }
#pragma unroll
  for (int k = K0 ? K0 : 1; k < K1; k++) wg_ss96<1>(d, da + (k >> 2) * 384 + (k & 3) * 2, db + (k >> 2) * 1152 + (k & 3) * 32);
  wg_commit();
}
template <int ST, int BYTES> __device__ __forceinline__ void release_stage(const GemmCtx& c, bool on) {
  asm volatile("{\n.reg .pred p, q;\n.reg .b32 ra;\nsetp.ne.b32 q, %2, 0;\nelect.sync _|p, 0xffffffff;\nand.pred p, p, q;\n"
               "mapa.shared::cluster.u32 ra, %1, %4;\n"
               "@p mbarrier.arrive.expect_tx.shared::cta.b64 _, [%0], %3;\n@p mbarrier.arrive.shared::cluster.b64 _, [ra];\n}"
               ::"r"(c.bar + (B_FULL + ST) * 8), "r"(c.bar + (B_EMPTY + ST) * 8), "r"((int)on), "n"(BYTES / 4), "n"(ST) : "memory");
}
__device__ __forceinline__ void load_w(const CUtensorMap* m, uint32_t sb, int ch, int part, int head) {
  asm volatile("cp.async.bulk.tensor.3d.shared::cluster.global.mbarrier::complete_tx::bytes [%0], [%1, {%3,%4,%5}], [%2];"
               ::"r"(sb + SM_W + ch * 18432 + part * 6144), "l"(m), "r"(sb + SM_BAR + (B_W + ch + (part == 2 ? 3 : 0)) * 8),
                 "r"(0), "r"(ch * 64), "r"((part == 2 ? 0 : part * 12 + 12) + head * 3) : "memory");
}
__device__ __forceinline__ void publish(uint32_t bar) {
  fence_async();
  __syncwarp();
  mbar_arrive_elect(bar);
}

template <bool FIRST, bool LAST>
__device__ __forceinline__ void gemm_iter(const GemmCtx& c, int b, uint32_t (&pk)[12], uint32_t (&pv)[12], uint32_t (&pq)[12]) {
  const uint32_t bar = c.bar;
  const uint32_t pa = b & 1;
  const bool w = b >= 0;
  const uint32_t ko = pa * KSLOT, vx = pa * 16, qx = pa * 128;
  float H[48], C[72];
  uint32_t hk[12], hv[12], pv2[12];
  TR(2, b + 2, 0);
  mbar_wait(bar + (B_FULL + 0) * 8, pa);
  if (!LAST && !FIRST) mbar_wait(bar + (B_FULL + 2) * 8, pa);
  TR(2, b + 2, 1);
  if (w) mbar_wait(bar + B_QKISS * 8, pa);
  TR(2, b + 2, 2);
  if (FIRST) {
    mbar_wait(bar + (B_W + 0) * 8, 0); issue_halo<0, 4>(H);
    mbar_wait(bar + (B_W + 1) * 8, 0); issue_halo<4, 8>(H);
    mbar_wait(bar + (B_W + 2) * 8, 0);
  } else issue_halo<0, 8>(H);
  TR(2, b + 2, 3);
  if (!FIRST) {
    if (w) mbar_wait(bar + B_KFREE * 8, pa);
    dump12<128>(c.kC + ko, pk);
  }
  issue_halo<8, 12>(H);
  TR(2, b + 2, 4);
  if (!LAST) {
    if (FIRST) { mbar_wait(bar + (B_FULL + 2) * 8, pa); mbar_wait(bar + (B_W + 3) * 8, 0); mbar_wait(bar + (B_W + 4) * 8, 0); }
    issue_core<SM_X2, 0, 8>(C);
    TR(2, b + 2, 5);
    if (!FIRST) dump12<256>(c.qC ^ (qx ^ 192), pq);
    wg_wait<1>(); pin(H);
    release_stage<0, 18432>(c, true);
  } else {
    dump12<256>(c.qC ^ (qx ^ 192), pq);
    wg_wait<0>(); pin(H);
  }
  pack12(hk, H, 0);
  if (c.hvalid) dump12<128>(c.kH + ko, hk);
  pack12(hv, H, 24);
  if (FIRST) mbar_wait(bar + (B_W + 5) * 8, 0);
  if (!LAST) issue_core<SM_X2, 8, 12>(C);
  if (!FIRST) publish(bar + (w ? B_VQRDY : B_Q0) * 8);
  if (!LAST) {
    mbar_wait(bar + (B_FULL + 1) * 8, pa);
    TR(2, b + 2, 6);
    wg_wait<0>(); pin(C);
    TR(2, b + 2, 7);
    release_stage<2, 24576>(c, b < 11);
    pack12(pk, C, 0);
    pack12(pv2, C, 24);
    pack12(pq, C, 48);
    if (w) mbar_wait(bar + B_PVISS * 8, pa);
    TR(2, b + 2, 8);
    issue_core<SM_X1, 0, 8>(C);
    TR(2, b + 2, 9);
    dump12<128>(c.kC + ko + 64, pk);
  }
  if (!FIRST) publish(bar + B_KRDY * 8);
  TR(2, b + 2, 10);
  if (!LAST) issue_core<SM_X1, 8, 12>(C);
  if (w) mbar_wait(bar + B_VFREE * 8, pa);
  if (!FIRST) dump12<128>(c.vC ^ vx, pv);
  if (!LAST) dump12<256>(c.qC ^ qx, pq);
  if (c.hvalid) dump12<128>(c.vH ^ vx, hv);
  if (LAST) { publish(bar + B_VQRDY * 8); return; }
  dump12<128>((c.vC ^ vx ^ 16) + 768, pv2);
  TR(2, b + 2, 11);
  wg_wait<0>(); pin(C);
  TR(2, b + 2, 12);
  release_stage<1, 24576>(c, b < 11);
  pack12(pk, C, 0);
  pack12(pv, C, 24);
  pack12(pq, C, 48);
}

template <int U, int L, bool BORDER>
__device__ __forceinline__ void softmax_tile(const float (&SA)[56], const float (&SB)[56], const float (&T)[14], bool b0, bool b1,
                                             uint32_t ra0, uint32_t ra1, int qcu, uint32_t (&P)[28], float& sumU, float& sumL) {
  const float cs = 0.14433756729740643f * 1.4426950408889634f;
  float lu[14], ll[14];
#pragma unroll
  for (int j = 0; j < 7; j++) {
    float tu0, tu1, tl0, tl1;
    if (BORDER) {
      tu0 = lds_f32(ra0 + (U + j + 3 - qcu) * 4); tu1 = lds_f32(ra1 + (U + j + 3 - qcu) * 4);
      tl0 = lds_f32(ra0 + (L + j + 2 - qcu) * 4); tl1 = lds_f32(ra1 + (L + j + 2 - qcu) * 4);
    } else { tu0 = tl0 = T[2 * j]; tu1 = tl1 = T[2 * j + 1]; }
    lu[2 * j]     = fmaf(b0 ? SB[4 * (U + j)]     : SA[4 * (U + j)],     cs, tu0);
    lu[2 * j + 1] = fmaf(b1 ? SB[4 * (U + j) + 1] : SA[4 * (U + j) + 1], cs, tu1);
    ll[2 * j]     = fmaf(b0 ? SB[4 * (L + j) + 2] : SA[4 * (L + j) + 2], cs, tl0);
    ll[2 * j + 1] = fmaf(b1 ? SB[4 * (L + j) + 3] : SA[4 * (L + j) + 3], cs, tl1);
  }
  float mu = lu[0], ml = ll[0], mu2 = lu[1], ml2 = ll[1];
#pragma unroll
  for (int j = 1; j < 7; j++) { mu = fmaxf(mu, lu[2 * j]); mu2 = fmaxf(mu2, lu[2 * j + 1]); ml = fmaxf(ml, ll[2 * j]); ml2 = fmaxf(ml2, ll[2 * j + 1]); }
  mu = fmaxf(mu, mu2); ml = fmaxf(ml, ml2);
  mu = fmaxf(mu, __shfl_xor_sync(0xffffffffu, mu, 1)); ml = fmaxf(ml, __shfl_xor_sync(0xffffffffu, ml, 1));
  mu = fmaxf(mu, __shfl_xor_sync(0xffffffffu, mu, 2)); ml = fmaxf(ml, __shfl_xor_sync(0xffffffffu, ml, 2));
  float su = 0.f, sl = 0.f, su2 = 0.f, sl2 = 0.f;
#pragma unroll
  for (int c = 0; c < 14; c++) {
    const int iu = (c >> 1) * 4 + (c & 1) * 2;
    if (c >= U && c < U + 7) {
      float e0 = ex2(lu[2 * (c - U)] - mu), e1 = ex2(lu[2 * (c - U) + 1] - mu);
      su += e0; su2 += e1; P[iu] = pack2(e0, e1);
    } else P[iu] = 0u;
    if (c >= L && c < L + 7) {
      float e0 = ex2(ll[2 * (c - L)] - ml), e1 = ex2(ll[2 * (c - L) + 1] - ml);
      sl += e0; sl2 += e1; P[iu + 1] = pack2(e0, e1);
    } else P[iu + 1] = 0u;
  }
  sumU = su + su2; sumL = sl + sl2;
}

__global__ void __cluster_dims__(4, 1, 1) __launch_bounds__(512, 1)
na_attn_kernel(const __grid_constant__ CUtensorMap mapC, const __grid_constant__ CUtensorMap mapH,
               const __grid_constant__ CUtensorMap mapW, const __nv_bfloat16* __restrict__ rpb, __nv_bfloat16* __restrict__ out) {
  extern __shared__ __align__(1024) uint8_t smem_raw[];
  const uint32_t sb = smem_u32(smem_raw);
  if ((sb & 0x3FFFF) != SBC) return;
  const uint32_t bar = sb + SM_BAR;
  asm volatile("griddepcontrol.launch_dependents;");
  TR(3, 0, threadIdx.x >> 7);
  TR2(blockIdx.x, 0);
  const int tid = threadIdx.x, lane = tid & 31;
  const int warp = __shfl_sync(0xffffffffu, tid >> 5, 0);
  const int head = blockIdx.x & 3, cl = blockIdx.x >> 2;
  const int par = cl / 7, strip = cl - par * 7, ph = par >> 1, pw = par & 1;

  if (warp >= 12) {
    asm volatile("setmaxnreg.dec.sync.aligned.u32 24;");
    const int cc = ph * 112 + (head ? strip * 16 : (strip == 0 ? 16 : (strip == 6 ? 74 : strip * 16 - 3)));
    const int sd = strip == 0 ? -1 : (strip == 6 ? 1 : 0);
    const int r0 = head == 0 ? -4 : (head == 1 ? 4 : 0);
    const bool lead = elect_one();
    if (lead) {
      if (warp == 12) {
#pragma unroll
        for (int i = 0; i < 6; i++) mbar_init(bar + (B_W + i) * 8, 1);
        load_w(&mapW, sb, 0, 0, head); load_w(&mapW, sb, 0, 1, head);
#pragma unroll
        for (int i = 0; i < 6; i++) mbar_expect(bar + (B_W + i) * 8, i < 3 ? 12288 : 6144);
      } else if (warp == 13) {
#pragma unroll
        for (int i = 0; i < B_W; i++) mbar_init(bar + i * 8, i < B_EMPTY ? 4 : (i < B_QKISS ? 16 : (i < B_KRDY ? 8 : 4)));
#pragma unroll
        for (int i = 0; i < 3; i++) {
          asm volatile("mbarrier.expect_tx.shared::cta.b64 [%0], %1;" ::"r"(bar + (B_FULL + i) * 8), "r"(i ? 24576 : 18432) : "memory");
          asm volatile("mbarrier.arrive.shared::cta.b64 _, [%0], 4;" ::"r"(bar + (B_FULL + i) * 8) : "memory");
        }
      } else {
        if (warp == 14) {
          if (head == 0) asm volatile("cp.async.bulk.prefetch.tensor.5d.L2.global [%0, {%1,%2,%3,%4,%5}];" ::"l"(&mapH), "r"(0), "r"(r0), "r"(cc), "r"(sd), "r"(pw * 3) : "memory");
          else if (head < 3) asm volatile("cp.async.bulk.prefetch.tensor.4d.L2.global [%0, {%1,%2,%3,%4}];" ::"l"(&mapC), "r"(0), "r"(r0), "r"(cc), "r"(pw * 3) : "memory");
        }
#pragma unroll
        for (int i = 0; i < 14; i++) mbar_init(bar + (B_ODONE + warp - 14 + 2 * i) * 8, 4);
      }
      asm volatile("fence.mbarrier_init.release.cluster;" ::: "memory");
    }
    __syncwarp();
    TR(3, 2, 3);
    cluster_sync();
    TR(3, 2, 4);
    if (warp == 12 && lead) {
      const uint32_t fb = bar + (B_FULL + head) * 8, eb = bar + (B_EMPTY + head) * 8;
      const uint32_t dst = sb + (head == 0 ? SM_X0 : (head == 1 ? SM_X1 : SM_X2));
      const int nl = head == 0 ? 15 : (head == 3 ? 1 : 14);
#pragma unroll 1
      for (int n = 0; n < nl; n++) {
        if (n) mbar_wait(eb, (n - 1) & 1);
        if (head == 0) {
          asm volatile("cp.async.bulk.tensor.5d.shared::cluster.global.mbarrier::complete_tx::bytes.multicast::cluster [%0], [%1, {%3,%4,%5,%6,%7}], [%2], %8;"
                       ::"r"(dst), "l"(&mapH), "r"(fb), "r"(0), "r"(8 * n + r0), "r"(cc), "r"(sd), "r"(pw * 3), "h"((uint16_t)15) : "memory");
        } else if (head < 3) {
          asm volatile("cp.async.bulk.tensor.4d.shared::cluster.global.mbarrier::complete_tx::bytes.multicast::cluster [%0], [%1, {%3,%4,%5,%6}], [%2], %7;"
                       ::"r"(dst), "l"(&mapC), "r"(fb), "r"(0), "r"(8 * n + r0), "r"(cc), "r"(pw * 3), "h"((uint16_t)15) : "memory");
        }
        if (n == 0) {
#pragma unroll 1
          for (int i = 2; i < 9; i++) load_w(&mapW, sb, i < 6 ? i >> 1 : i - 6, i < 6 ? i & 1 : 2, head);
        }
        if (head == 0) {
          if (n + 1 < nl) asm volatile("cp.async.bulk.prefetch.tensor.5d.L2.global [%0, {%1,%2,%3,%4,%5}];" ::"l"(&mapH), "r"(0), "r"(8 * n + 8 + r0), "r"(cc), "r"(sd), "r"(pw * 3) : "memory");
        } else {
          if (n + 1 < nl) asm volatile("cp.async.bulk.prefetch.tensor.4d.L2.global [%0, {%1,%2,%3,%4}];" ::"l"(&mapC), "r"(0), "r"(8 * n + 8 + r0), "r"(cc), "r"(pw * 3) : "memory");
        }
      }
    }
    if (warp >= 14 && lead) {
      const int j = warp - 14;
      int* flag = g_flags + cl * 2 + j;
#pragma unroll 1
      for (int b = 0; b < 14; b++) {
        mbar_wait(bar + (B_ODONE + 2 * b + j) * 8, 0);
        asm volatile("fence.acq_rel.gpu;\nred.relaxed.gpu.global.add.s32 [%0], 1;" ::"l"(flag + b * 56) : "memory");
      }
    }
    __syncwarp();
    cluster_sync();
  } else if (warp >= 8) {
    asm volatile("barrier.cluster.arrive.relaxed.aligned;" ::: "memory");
    TR(3, 2, 2);
    asm volatile("setmaxnreg.inc.sync.aligned.u32 184;");
    GemmCtx c;
    c.bar = bar; c.warp = warp - 8;
    const int tk = c.warp * 16 + (lane & 15), hi = lane >> 4;
    { const int col = tk >> 2, i = tk & 3;
      c.kC = sb + SM_K + (col + 3) * KS + hi * 128 + i * 16;
      c.vC = sb + SM_V + (col + 3) * 1536 + hi * 128 + (2 * i + ((col + 3) & 1)) * 16;
      c.qC = sb + SM_Q + col * 1536 + hi * 256 + (col & 1) * 64 + i * 16; }
    { const int ci = tk >> 3, kc = ci < 3 ? ci : ci + 16, i = tk & 7; c.hvalid = c.warp < 3;
      c.kH = sb + SM_K + kc * KS + hi * 128 + i * 16;
      c.vH = sb + SM_V + kc * 1536 + hi * 128 + (i >> 2) * 768 + (2 * (i & 3) + ((kc ^ (i >> 2)) & 1)) * 16; }
    TR(3, 1, 2);
    asm volatile("barrier.cluster.wait.aligned;" ::: "memory");
    TR(3, 1, 0);
    uint32_t pk[12], pv[12], pq[12];
    gemm_iter<true, false>(c, -2, pk, pv, pq);
#pragma unroll 1
    for (int b = -1; b < 12; b++) gemm_iter<false, false>(c, b, pk, pv, pq);
    gemm_iter<false, true>(c, 12, pk, pv, pq);
    cluster_sync();
  } else {
    asm volatile("barrier.cluster.arrive.relaxed.aligned;" ::: "memory");
    TR(3, 2, threadIdx.x >> 7);
    asm volatile("setmaxnreg.inc.sync.aligned.u32 152;");
    if (tid < 182) {
      float v = tid < 169 ? __bfloat162float(rpb[head * 169 + tid]) * 1.4426950408889634f : -INFINITY;
      asm volatile("st.shared.f32 [%0], %1;" ::"r"(sb + SM_RPB + tid * 4), "f"(v) : "memory");
    }
    if (tid < 192) {
      const int x = tid % 96, kc = x / 6 + 3, ch = x % 6;
      const uint32_t a = tid < 96 ? sb + SM_K + kc * KS + ch * 128 + 48 : sb + SM_V + kc * 1536 + ch * 128 + (6 + (kc & 1)) * 16;
      asm volatile("st.shared.v4.b32 [%0], {%1,%1,%1,%1};" ::"r"(a), "r"(0) : "memory");
    }
    const int j = warp >> 2, w = warp & 3;
    int variant = w;
    if (strip == 0 && j == 0 && w < 2) variant = 4;
    if (strip == 6 && j == 1 && w >= 2) variant = 5;
    const uint32_t qa = sb + SM_Q + (8 * j + 2 * w + ((lane >> 3) & 1)) * 1536 + (lane >> 4) * 256 + (((lane & 7) * 16) ^ (((lane >> 3) & 1) * 64));
    const uint64_t dK = mkdesc(SBC + SM_K, 128, KS, 0) + j * (8 * KS / 16);
    const uint64_t dV = mkdesc(SBC + SM_V, 768, 128, 0) + j * (8 * 1536 / 16);
    uint8_t* op = reinterpret_cast<uint8_t*>(out) + (size_t)(ph * 224 + 2 * (strip * 16 + 8 * j + 2 * w) + pw) * 384 + (size_t)(2 * head) * ROWB;
    const uint32_t off0 = ((lane & 3) == 3 ? ROWB : (lane & 3) * 128) + (lane >> 2) * 16;
    const uint32_t off1 = ROWB + 128 + (lane & 2) * 64 + (lane >> 2) * 16 + (lane & 1) * 8;
    TR(3, 3, j);
    asm volatile("barrier.cluster.wait.aligned;" ::: "memory");
    TR(3, 3, 2 + j);
    fence_async();
    asm volatile("bar.sync 1, 256;" ::: "memory");
    float T[14];
    bool b0 = false, b1 = false;
    uint32_t ra0 = 0, ra1 = 0, meta = 0;
    uint32_t q[12];
    mbar_wait(bar + B_Q0 * 8, 0);
#pragma unroll
    for (int k = 0; k < 3; k++) ldsm4(qa + k * 512, q[4 * k], q[4 * k + 1], q[4 * k + 2], q[4 * k + 3]);
#pragma unroll 1
    for (int b = 0; b < 14; b++) {
      const uint32_t pa = b & 1;
      if (b <= 1 || b == 13) {
        uint32_t ln; asm volatile("mov.u32 %0, %%laneid;" : "=r"(ln));
        const int g = ln >> 2, t = ln & 3;
        const int sw = b == 0 ? max(g + 1, 4) : (b == 13 ? min(g + 1, 5) : g + 1);
        const int i0 = 2 * t, i1 = 2 * t + 1;
        b0 = i0 <= sw - 2; b1 = i1 <= sw - 2;
        const int m = sw - 1;
        ra0 = sb + SM_RPB + (i0 == m ? 13 : i0 + (b0 ? 8 : 0) - g + 2) * 52;
        ra1 = sb + SM_RPB + (i1 == m ? 13 : i1 + (b1 ? 8 : 0) - g + 2) * 52;
#pragma unroll
        for (int jj = 0; jj < 7; jj++) { T[2 * jj] = lds_f32(ra0 + (jj + 3) * 4); T[2 * jj + 1] = lds_f32(ra1 + (jj + 3) * 4); }
        uint32_t m16 = 0x8888u;
#pragma unroll
        for (int i = 0; i < 8; i++) m16 |= (uint32_t)(((i <= sw - 2) ^ (i >> 2) ^ t ^ b) & 1) << (2 * i);
        meta = m16 | (m16 << 16);
      } else meta ^= 0x55555555u;
      float SA[56], SB[56];
      const uint64_t dA = dK + pa * (KSLOT >> 4), dB = dK + (pa ^ 1) * (KSLOT >> 4);
      TR(j, b, 0);
      mbar_wait(bar + B_KRDY * 8, pa);
      TR(j, b, 1);
      wg_fence();
      wg_rs112<0>(SA, q[0], q[1], q[2], q[3], dA);
      wg_rs112<0>(SB, q[0], q[1], q[2], q[3], dB);
      wg_rs112<1>(SA, q[4], q[5], q[6], q[7], dA + 16);
      wg_rs112<1>(SB, q[4], q[5], q[6], q[7], dB + 16);
      wg_rs112<1>(SA, q[8], q[9], q[10], q[11], dA + 32);
      wg_rs112<1>(SB, q[8], q[9], q[10], q[11], dB + 32);
      wg_commit();
      mbar_arrive_elect(bar + B_QKISS * 8);
      TR(j, b, 2);
      wg_wait<0>(); pin(SA); pin(SB);
      mbar_arrive_elect(bar + B_KFREE * 8);
      TR(j, b, 3);
      uint32_t P[28];
      float su, sl;
      switch (variant) {
        case 0: softmax_tile<0, 1, false>(SA, SB, T, b0, b1, ra0, ra1, 0, P, su, sl); break;
        case 1: softmax_tile<2, 3, false>(SA, SB, T, b0, b1, ra0, ra1, 0, P, su, sl); break;
        case 2: softmax_tile<4, 5, false>(SA, SB, T, b0, b1, ra0, ra1, 0, P, su, sl); break;
        case 3: softmax_tile<6, 7, false>(SA, SB, T, b0, b1, ra0, ra1, 0, P, su, sl); break;
        case 4: softmax_tile<3, 3, true>(SA, SB, T, b0, b1, ra0, ra1, 2 * w, P, su, sl); break;
        default: softmax_tile<4, 4, true>(SA, SB, T, b0, b1, ra0, ra1, 2 * w, P, su, sl); break;
      }
      float O[24];
      TR(j, b, 4);
      su += __shfl_xor_sync(0xffffffffu, su, 1); sl += __shfl_xor_sync(0xffffffffu, sl, 1);
      mbar_wait(bar + B_VQRDY * 8, pa);
      TR(j, b, 5);
      su += __shfl_xor_sync(0xffffffffu, su, 2); sl += __shfl_xor_sync(0xffffffffu, sl, 2);
#pragma unroll
      for (int k = 0; k < 3; k++) ldsm4(qa + (pa ^ 1) * 128 + k * 512, q[4 * k], q[4 * k + 1], q[4 * k + 2], q[4 * k + 3]);
      wg_fence();
      wg_sp48<0>(O, P[0], P[1], P[2], P[3], dV, meta);
#pragma unroll
      for (int s = 1; s < 7; s++) wg_sp48<1>(O, P[4 * s], P[4 * s + 1], P[4 * s + 2], P[4 * s + 3], dV + s * 192, meta);
      wg_commit();
      mbar_arrive_elect(bar + B_PVISS * 8);
      TR(j, b, 6);
      const float ru = __fdividef(1.f, su), rl = __fdividef(1.f, sl);
      wg_wait<0>(); pin(O);
      mbar_arrive_elect(bar + B_VFREE * 8);
      TR(j, b, 7);
      *reinterpret_cast<uint4*>(op + off0) = make_uint4(pack2(O[0] * ru, O[1] * ru), pack2(O[4] * ru, O[5] * ru), pack2(O[8] * ru, O[9] * ru), pack2(O[12] * ru, O[13] * ru));
      *reinterpret_cast<uint4*>(op + off0 + 768) = make_uint4(pack2(O[2] * rl, O[3] * rl), pack2(O[6] * rl, O[7] * rl), pack2(O[10] * rl, O[11] * rl), pack2(O[14] * rl, O[15] * rl));
      *reinterpret_cast<uint2*>(op + off1) = make_uint2(pack2(O[16] * ru, O[17] * ru), pack2(O[20] * ru, O[21] * ru));
      *reinterpret_cast<uint2*>(op + off1 + 768) = make_uint2(pack2(O[18] * rl, O[19] * rl), pack2(O[22] * rl, O[23] * rl));
      op += 8 * ROWB;
      __syncwarp();
      mbar_arrive_elect(bar + (B_ODONE + 2 * b + j) * 8);
      TR(j, b, 8);
    }
    TR2(blockIdx.x, 2);
    cluster_sync();
  }
}

constexpr int NSTB = 4;
constexpr int SM_B_IN = 0;
constexpr int SM_B_W = SM_B_IN + NSTB * 24576;
constexpr int WOS = 3088;
constexpr int SM_B_BAR = SM_B_W + 24 * WOS;
constexpr int SM_B_TOTAL = SM_B_BAR + 64;

__global__ void __launch_bounds__(288, 1)
na_proj_kernel(const __grid_constant__ CUtensorMap mapI, const __nv_bfloat16* __restrict__ wo, __nv_bfloat16* out) {
  extern __shared__ __align__(1024) uint8_t smem_raw[];
  const uint32_t sb = smem_u32(smem_raw);
  if ((sb & 0x3FFFF) != SBC) return;
  const uint32_t bar = sb + SM_B_BAR;
  const int tid = threadIdx.x, lane = tid & 31;
  const int warp = __shfl_sync(0xffffffffu, tid >> 5, 0);
  TR2(132 + blockIdx.x, 0);
  TRB(47, 0);
  if (warp < 8) {
#pragma unroll
    for (int i = 0; i < 5; i++) {
      const int pc = tid + i * 256;
      if (pc < 1152) {
        const uint4* src = reinterpret_cast<const uint4*>(wo) + pc * 4;
        const uint4 a = __ldg(src), b = __ldg(src + 1), c = __ldg(src + 2), d = __ldg(src + 3);
        const int row = pc / 6, jj = pc - row * 6, hd = row / 48, dim = row - hd * 48, g8 = dim >> 3, t = (dim >> 1) & 3;
        const int kk = (g8 < 4 ? t * 8 + g8 * 2 : 32 + t * 4 + (g8 - 4) * 2) + (dim & 1);
        const uint32_t dst = sb + SM_B_W + jj * 4 * WOS + (hd * 48 + kk) * 16;
        asm volatile("st.shared.v4.b32 [%0], {%1,%2,%3,%4};" ::"r"(dst), "r"(a.x), "r"(b.x), "r"(c.x), "r"(d.x) : "memory");
        asm volatile("st.shared.v4.b32 [%0], {%1,%2,%3,%4};" ::"r"(dst + WOS), "r"(a.y), "r"(b.y), "r"(c.y), "r"(d.y) : "memory");
        asm volatile("st.shared.v4.b32 [%0], {%1,%2,%3,%4};" ::"r"(dst + 2 * WOS), "r"(a.z), "r"(b.z), "r"(c.z), "r"(d.z) : "memory");
        asm volatile("st.shared.v4.b32 [%0], {%1,%2,%3,%4};" ::"r"(dst + 3 * WOS), "r"(a.w), "r"(b.w), "r"(c.w), "r"(d.w) : "memory");
      }
    }
    fence_async();
  } else if (elect_one()) {
#pragma unroll
    for (int i = 0; i < 2 * NSTB; i++) mbar_init(bar + i * 8, i < NSTB ? 1 : 4);
  }
  __syncthreads();
  const int step = gridDim.x;
  TRB(47, 1);
  if (warp == 8) {
    int it = 0;
    uint32_t spin = 0;
#pragma unroll 1
    for (int n = blockIdx.x; n < 784 && spin < SPIN_LIMIT; spin++) {
      int v = 0;
      const int mine = n + lane * step;
      if (lane < 8 && mine < 784) asm volatile("ld.acquire.gpu.global.s32 %0, [%1];" : "=r"(v) : "l"(g_flags + mine) : "memory");
      int cnt = __ffs(~__ballot_sync(0xffffffffu, v >= 4)) - 1;
      asm volatile("fence.proxy.async.global;" ::: "memory");
      __syncwarp();
#pragma unroll 1
      for (; cnt > 0; cnt--, n += step, it++) {
        TRB(it, 0);
        if (elect_one()) {
          const int b = n / 56, rem = n - b * 56, par = rem / 14;
          const int st = it & (NSTB - 1), use = it / NSTB;
          if (use) mbar_wait(bar + (NSTB + st) * 8, (use - 1) & 1);
          mbar_expect(bar + st * 8, 24576);
          asm volatile("cp.async.bulk.tensor.3d.shared::cluster.global.mbarrier::complete_tx::bytes [%0], [%1, {%3,%4,%5}], [%2];"
                       ::"r"(sb + SM_B_IN + st * 24576), "l"(&mapI), "r"(bar + st * 8), "r"((par & 1) * 192), "r"(8 * b), "r"((par >> 1) * 112 + (rem - par * 14) * 8) : "memory");
        }
        __syncwarp();
        TRB(it, 2);
      }
    }
    for (int n = blockIdx.x + lane * step; n < 784; n += 32 * step) g_flags[n] = 0;
  } else {
    const int wg = warp >> 2, w = warp & 3;
    constexpr uint64_t db = mkdesc(SBC + SM_B_W, 128, WOS, 0);
    uint8_t* const ob = reinterpret_cast<uint8_t*>(out) + (size_t)(lane >> 2) * ROWB + w * 1536 + (lane & 3) * 16;
    int it = wg;
#pragma unroll 1
    for (int n = blockIdx.x + wg * step; n < 784; n += 2 * step, it += 2) {
      const int b = n / 56, rem = n - b * 56, par = rem / 14, sg = it & (NSTB - 1);
      const uint64_t da = mkdesc(SBC + SM_B_IN, 128, 3072, 0) + sg * (24576 / 16);
      float D[96];
      mbar_wait(bar + sg * 8, (it / NSTB) & 1);
      TRB(it, 3);
      wg_fence();
      wg_ss192<0>(D, da, db);
#pragma unroll
      for (int k = 1; k < 12; k++) wg_ss192<1>(D, da + k * 16, db + k * 16);
      wg_commit();
      TRB(it, 4);
      uint8_t* o = ob + (size_t)(8 * b) * ROWB + ((par >> 1) * 112 + (rem - par * 14) * 8) * 768 + (par & 1) * 384;
      wg_wait<0>(); pin(D);
      mbar_arrive_elect(bar + (NSTB + sg) * 8);
      TRB(it, 5);
#pragma unroll
      for (int q = 0; q < 6; q++) {
        *reinterpret_cast<uint4*>(o + q * 64) = make_uint4(pack2(D[16 * q], D[16 * q + 1]), pack2(D[16 * q + 4], D[16 * q + 5]), pack2(D[16 * q + 8], D[16 * q + 9]), pack2(D[16 * q + 12], D[16 * q + 13]));
        *reinterpret_cast<uint4*>(o + 768 + q * 64) = make_uint4(pack2(D[16 * q + 2], D[16 * q + 3]), pack2(D[16 * q + 6], D[16 * q + 7]), pack2(D[16 * q + 10], D[16 * q + 11]), pack2(D[16 * q + 14], D[16 * q + 15]));
      }
      TRB(it, 6);
    }
    TR2(132 + blockIdx.x, 2);
  }
}

typedef CUresult (*EncodeFn)(CUtensorMap*, CUtensorMapDataType, cuuint32_t, void*, const cuuint64_t*, const cuuint64_t*, const cuuint32_t*,
                             const cuuint32_t*, CUtensorMapInterleave, CUtensorMapSwizzle, CUtensorMapL2promotion, CUtensorMapFloatOOBfill);

extern "C" void kernel_launch(void* const* d_in, const int* in_sizes, int n_in, void* d_out, int out_size) {
  const __nv_bfloat16* x = (const __nv_bfloat16*)d_in[0];
  const __nv_bfloat16* wqkv = (const __nv_bfloat16*)d_in[1];
  const __nv_bfloat16* wo = (const __nv_bfloat16*)d_in[2];
  const __nv_bfloat16* rpb = (const __nv_bfloat16*)d_in[3];
  __nv_bfloat16* out = (__nv_bfloat16*)d_out;

  static EncodeFn enc = nullptr;
  if (!enc) {
    void* fn = nullptr; cudaDriverEntryPointQueryResult qr;
    cudaGetDriverEntryPoint("cuTensorMapEncodeTiled", &fn, cudaEnableDefault, &qr);
    enc = (EncodeFn)fn;
    cudaFuncSetAttribute(na_attn_kernel, cudaFuncAttributeMaxDynamicSharedMemorySize, SM_A_TOTAL);
    cudaFuncSetAttribute(na_proj_kernel, cudaFuncAttributeMaxDynamicSharedMemorySize, SM_B_TOTAL);
  }
  CUtensorMap mC, mH, mI, mW;
  const cuuint32_t ones[5] = {1, 1, 1, 1, 1};
  {
    cuuint64_t dim[4] = {64, 112, 224, 6}, str[3] = {(cuuint64_t)ROWB, 768, 128};
    cuuint32_t box[4] = {64, 4, 16, 3};
    enc(&mC, CU_TENSOR_MAP_DATA_TYPE_BFLOAT16, 4, (void*)x, dim, str, box, ones, CU_TENSOR_MAP_INTERLEAVE_NONE, CU_TENSOR_MAP_SWIZZLE_128B,
        CU_TENSOR_MAP_L2_PROMOTION_L2_128B, CU_TENSOR_MAP_FLOAT_OOB_FILL_NONE);
  }
  {
    cuuint64_t dim[5] = {64, 112, 224, 2, 6}, str[4] = {(cuuint64_t)ROWB, 768, 19 * 768, 128};
    cuuint32_t box[5] = {64, 8, 3, 2, 3};
    enc(&mH, CU_TENSOR_MAP_DATA_TYPE_BFLOAT16, 5, (void*)x, dim, str, box, ones, CU_TENSOR_MAP_INTERLEAVE_NONE, CU_TENSOR_MAP_SWIZZLE_128B,
        CU_TENSOR_MAP_L2_PROMOTION_L2_128B, CU_TENSOR_MAP_FLOAT_OOB_FILL_NONE);
  }
  {
    cuuint64_t dim[3] = {384, 112, 224}, str[2] = {(cuuint64_t)ROWB, 768};
    cuuint32_t box[3] = {192, 8, 8};
    enc(&mI, CU_TENSOR_MAP_DATA_TYPE_BFLOAT16, 3, (void*)out, dim, str, box, ones, CU_TENSOR_MAP_INTERLEAVE_NONE, CU_TENSOR_MAP_SWIZZLE_NONE,
        CU_TENSOR_MAP_L2_PROMOTION_NONE, CU_TENSOR_MAP_FLOAT_OOB_FILL_NONE);
  }
  {
    cuuint64_t dim[3] = {16, 192, 36}, str[2] = {1152, 32};
    cuuint32_t box[3] = {16, 64, 3};
    enc(&mW, CU_TENSOR_MAP_DATA_TYPE_BFLOAT16, 3, (void*)wqkv, dim, str, box, ones, CU_TENSOR_MAP_INTERLEAVE_NONE, CU_TENSOR_MAP_SWIZZLE_32B,
        CU_TENSOR_MAP_L2_PROMOTION_L2_128B, CU_TENSOR_MAP_FLOAT_OOB_FILL_NONE);
  }
  na_attn_kernel<<<112, 512, SM_A_TOTAL>>>(mC, mH, mW, rpb, out);
#define NBCTA 20
  cudaLaunchConfig_t cfg = {};
  cfg.gridDim = dim3(NBCTA); cfg.blockDim = dim3(288); cfg.dynamicSmemBytes = SM_B_TOTAL; cfg.stream = cudaStreamPerThread;
  cudaLaunchAttribute at[1];
  at[0].id = cudaLaunchAttributeProgrammaticStreamSerialization; at[0].val.programmaticStreamSerializationAllowed = 1;
  cfg.attrs = at; cfg.numAttrs = 1;
  cudaLaunchKernelEx(&cfg, na_proj_kernel, mI, wo, out);
}
```

```cpp
#include <cuda_runtime.h>
#include <cuda_bf16.h>
#include <cuda.h>
#include <stdint.h>

#define SPIN_LIMIT (1u << 18)

__device__ __forceinline__ uint32_t smem_u32(const void* p) { return (uint32_t)__cvta_generic_to_shared(p); }
__device__ __forceinline__ void wg_fence() { asm volatile("wgmma.fence.sync.aligned;" ::: "memory"); }
__device__ __forceinline__ void wg_commit() { asm volatile("wgmma.commit_group.sync.aligned;" ::: "memory"); }
template <int N> __device__ __forceinline__ void wg_wait() { asm volatile("wgmma.wait_group.sync.aligned %0;" ::"n"(N) : "memory"); }
template <int N> __device__ __forceinline__ void pin(float (&d)[N]) {
#pragma unroll
  for (int i = 0; i < N; i++) asm volatile("" : "+f"(d[i])::"memory");
}
__host__ __device__ constexpr uint64_t mkdesc(uint32_t addr, uint32_t lbo, uint32_t sbo, uint32_t sw) {
  return (uint64_t)((addr & 0x3FFFF) >> 4) | ((uint64_t)(lbo >> 4) << 16) | ((uint64_t)(sbo >> 4) << 32) | ((uint64_t)sw << 62);
}
__device__ __forceinline__ void mbar_init(uint32_t bar, uint32_t cnt) { asm volatile("mbarrier.init.shared::cta.b64 [%0], %1;" ::"r"(bar), "r"(cnt) : "memory"); }
__device__ __forceinline__ void mbar_arrive(uint32_t bar) { asm volatile("mbarrier.arrive.shared::cta.b64 _, [%0];" ::"r"(bar) : "memory"); }
__device__ __forceinline__ bool elect_one() {
  uint32_t r; asm volatile("{\n.reg .pred p;\nelect.sync _|p, 0xffffffff;\nselp.u32 %0, 1, 0, p;\n}" : "=r"(r)); return r;
}
__device__ __forceinline__ void mbar_arrive_elect(uint32_t bar) {
  asm volatile("{\n.reg .pred p;\nelect.sync _|p, 0xffffffff;\n@p mbarrier.arrive.shared::cta.b64 _, [%0];\n}" ::"r"(bar) : "memory");
}
__device__ __forceinline__ void mbar_expect(uint32_t bar, uint32_t bytes) { asm volatile("mbarrier.arrive.expect_tx.shared::cta.b64 _, [%0], %1;" ::"r"(bar), "r"(bytes) : "memory"); }
__device__ __forceinline__ void mbar_arrive_remote(uint32_t bar, uint32_t cta) {
  asm volatile("{\n.reg .b32 ra;\nmapa.shared::cluster.u32 ra, %0, %1;\nmbarrier.arrive.shared::cluster.b64 _, [ra];\n}" ::"r"(bar), "r"(cta) : "memory");
}
__device__ __forceinline__ void mbar_wait(uint32_t bar, uint32_t parity) {
  asm volatile("{\n.reg .pred p;\n.reg .b32 n;\nmov.b32 n, 0;\nWL:\nmbarrier.try_wait.parity.shared::cta.b64 p, [%0], %1;\n@p bra WD;\n"
               "add.u32 n, n, 1;\nsetp.lt.u32 p, n, 65536;\n@p bra WL;\nWD:\n}" ::"r"(bar), "r"(parity) : "memory");
}
__device__ __forceinline__ void fence_async() { asm volatile("fence.proxy.async.shared::cta;" ::: "memory"); }
__device__ __forceinline__ void cluster_sync() {
  asm volatile("barrier.cluster.arrive.relaxed.aligned;\nbarrier.cluster.wait.aligned;" ::: "memory");
}
__device__ __forceinline__ uint32_t pack2(float lo, float hi) {
  uint32_t r; asm("cvt.rn.bf16x2.f32 %0, %1, %2;" : "=r"(r) : "f"(hi), "f"(lo)); return r;
}
__device__ __forceinline__ void stsm4(uint32_t a, uint32_t r0, uint32_t r1, uint32_t r2, uint32_t r3) {
  asm volatile("stmatrix.sync.aligned.m8n8.x4.shared.b16 [%0], {%1,%2,%3,%4};" ::"r"(a), "r"(r0), "r"(r1), "r"(r2), "r"(r3) : "memory");
}
__device__ __forceinline__ void ldsm4(uint32_t a, uint32_t& r0, uint32_t& r1, uint32_t& r2, uint32_t& r3) {
  asm volatile("ldmatrix.sync.aligned.m8n8.x4.shared.b16 {%0,%1,%2,%3}, [%4];" : "=r"(r0), "=r"(r1), "=r"(r2), "=r"(r3) : "r"(a) : "memory");
}
__device__ __forceinline__ float lds_f32(uint32_t a) { float v; asm volatile("ld.shared.f32 %0, [%1];" : "=f"(v) : "r"(a)); return v; }
__device__ __forceinline__ float ex2(float x) { float y; asm("ex2.approx.ftz.f32 %0, %1;" : "=f"(y) : "f"(x)); return y; }

template<int SC> __device__ __forceinline__ void wg_ss144(float (&d)[72], uint64_t da, uint64_t db) {
  asm volatile("{\n.reg .pred p;\nsetp.ne.b32 p, %74, 0;\nwgmma.mma_async.sync.aligned.m64n144k16.f32.bf16.bf16 {%0,%1,%2,%3,%4,%5,%6,%7,%8,%9,%10,%11,%12,%13,%14,%15,%16,%17,%18,%19,%20,%21,%22,%23,%24,%25,%26,%27,%28,%29,%30,%31,%32,%33,%34,%35,%36,%37,%38,%39,%40,%41,%42,%43,%44,%45,%46,%47,%48,%49,%50,%51,%52,%53,%54,%55,%56,%57,%58,%59,%60,%61,%62,%63,%64,%65,%66,%67,%68,%69,%70,%71}, %72, %73, p, 1, 1, 0, 1;\n}\n"
    : "+f"(d[0]),"+f"(d[1]),"+f"(d[2]),"+f"(d[3]),"+f"(d[4]),"+f"(d[5]),"+f"(d[6]),"+f"(d[7]),"+f"(d[8]),"+f"(d[9]),"+f"(d[10]),"+f"(d[11]),"+f"(d[12]),"+f"(d[13]),"+f"(d[14]),"+f"(d[15]),"+f"(d[16]),"+f"(d[17]),"+f"(d[18]),"+f"(d[19]),"+f"(d[20]),"+f"(d[21]),"+f"(d[22]),"+f"(d[23]),"+f"(d[24]),"+f"(d[25]),"+f"(d[26]),"+f"(d[27]),"+f"(d[28]),"+f"(d[29]),"+f"(d[30]),"+f"(d[31]),"+f"(d[32]),"+f"(d[33]),"+f"(d[34]),"+f"(d[35]),"+f"(d[36]),"+f"(d[37]),"+f"(d[38]),"+f"(d[39]),"+f"(d[40]),"+f"(d[41]),"+f"(d[42]),"+f"(d[43]),"+f"(d[44]),"+f"(d[45]),"+f"(d[46]),"+f"(d[47]),"+f"(d[48]),"+f"(d[49]),"+f"(d[50]),"+f"(d[51]),"+f"(d[52]),"+f"(d[53]),"+f"(d[54]),"+f"(d[55]),"+f"(d[56]),"+f"(d[57]),"+f"(d[58]),"+f"(d[59]),"+f"(d[60]),"+f"(d[61]),"+f"(d[62]),"+f"(d[63]),"+f"(d[64]),"+f"(d[65]),"+f"(d[66]),"+f"(d[67]),"+f"(d[68]),"+f"(d[69]),"+f"(d[70]),"+f"(d[71]) : "l"(da), "l"(db), "n"(SC));
}
template<int SC> __device__ __forceinline__ void wg_ss96(float (&d)[48], uint64_t da, uint64_t db) {
  asm volatile("{\n.reg .pred p;\nsetp.ne.b32 p, %50, 0;\nwgmma.mma_async.sync.aligned.m64n96k16.f32.bf16.bf16 {%0,%1,%2,%3,%4,%5,%6,%7,%8,%9,%10,%11,%12,%13,%14,%15,%16,%17,%18,%19,%20,%21,%22,%23,%24,%25,%26,%27,%28,%29,%30,%31,%32,%33,%34,%35,%36,%37,%38,%39,%40,%41,%42,%43,%44,%45,%46,%47}, %48, %49, p, 1, 1, 0, 1;\n}\n"
    : "+f"(d[0]),"+f"(d[1]),"+f"(d[2]),"+f"(d[3]),"+f"(d[4]),"+f"(d[5]),"+f"(d[6]),"+f"(d[7]),"+f"(d[8]),"+f"(d[9]),"+f"(d[10]),"+f"(d[11]),"+f"(d[12]),"+f"(d[13]),"+f"(d[14]),"+f"(d[15]),"+f"(d[16]),"+f"(d[17]),"+f"(d[18]),"+f"(d[19]),"+f"(d[20]),"+f"(d[21]),"+f"(d[22]),"+f"(d[23]),"+f"(d[24]),"+f"(d[25]),"+f"(d[26]),"+f"(d[27]),"+f"(d[28]),"+f"(d[29]),"+f"(d[30]),"+f"(d[31]),"+f"(d[32]),"+f"(d[33]),"+f"(d[34]),"+f"(d[35]),"+f"(d[36]),"+f"(d[37]),"+f"(d[38]),"+f"(d[39]),"+f"(d[40]),"+f"(d[41]),"+f"(d[42]),"+f"(d[43]),"+f"(d[44]),"+f"(d[45]),"+f"(d[46]),"+f"(d[47]) : "l"(da), "l"(db), "n"(SC));
}
template<int SC> __device__ __forceinline__ void wg_rs112(float (&d)[56], uint32_t a0, uint32_t a1, uint32_t a2, uint32_t a3, uint64_t db) {
  asm volatile("{\n.reg .pred p;\nsetp.ne.b32 p, %61, 0;\nwgmma.mma_async.sync.aligned.m64n112k16.f32.bf16.bf16 {%0,%1,%2,%3,%4,%5,%6,%7,%8,%9,%10,%11,%12,%13,%14,%15,%16,%17,%18,%19,%20,%21,%22,%23,%24,%25,%26,%27,%28,%29,%30,%31,%32,%33,%34,%35,%36,%37,%38,%39,%40,%41,%42,%43,%44,%45,%46,%47,%48,%49,%50,%51,%52,%53,%54,%55}, {%56,%57,%58,%59}, %60, p, 1, 1, 0;\n}\n"
    : "+f"(d[0]),"+f"(d[1]),"+f"(d[2]),"+f"(d[3]),"+f"(d[4]),"+f"(d[5]),"+f"(d[6]),"+f"(d[7]),"+f"(d[8]),"+f"(d[9]),"+f"(d[10]),"+f"(d[11]),"+f"(d[12]),"+f"(d[13]),"+f"(d[14]),"+f"(d[15]),"+f"(d[16]),"+f"(d[17]),"+f"(d[18]),"+f"(d[19]),"+f"(d[20]),"+f"(d[21]),"+f"(d[22]),"+f"(d[23]),"+f"(d[24]),"+f"(d[25]),"+f"(d[26]),"+f"(d[27]),"+f"(d[28]),"+f"(d[29]),"+f"(d[30]),"+f"(d[31]),"+f"(d[32]),"+f"(d[33]),"+f"(d[34]),"+f"(d[35]),"+f"(d[36]),"+f"(d[37]),"+f"(d[38]),"+f"(d[39]),"+f"(d[40]),"+f"(d[41]),"+f"(d[42]),"+f"(d[43]),"+f"(d[44]),"+f"(d[45]),"+f"(d[46]),"+f"(d[47]),"+f"(d[48]),"+f"(d[49]),"+f"(d[50]),"+f"(d[51]),"+f"(d[52]),"+f"(d[53]),"+f"(d[54]),"+f"(d[55]) : "r"(a0), "r"(a1), "r"(a2), "r"(a3), "l"(db), "n"(SC));
}
template<int SC> __device__ __forceinline__ void wg_sp48(float (&d)[24], uint32_t a0, uint32_t a1, uint32_t a2, uint32_t a3, uint64_t db, uint32_t meta) {
  asm volatile("{\n.reg .pred p;\nsetp.ne.b32 p, %30, 0;\nwgmma.mma_async.sp.sync.aligned.m64n48k32.f32.bf16.bf16 {%0,%1,%2,%3,%4,%5,%6,%7,%8,%9,%10,%11,%12,%13,%14,%15,%16,%17,%18,%19,%20,%21,%22,%23}, {%24,%25,%26,%27}, %28, %29, 0, p, 1, 1, 1;\n}\n"
    : "+f"(d[0]),"+f"(d[1]),"+f"(d[2]),"+f"(d[3]),"+f"(d[4]),"+f"(d[5]),"+f"(d[6]),"+f"(d[7]),"+f"(d[8]),"+f"(d[9]),"+f"(d[10]),"+f"(d[11]),"+f"(d[12]),"+f"(d[13]),"+f"(d[14]),"+f"(d[15]),"+f"(d[16]),"+f"(d[17]),"+f"(d[18]),"+f"(d[19]),"+f"(d[20]),"+f"(d[21]),"+f"(d[22]),"+f"(d[23]) : "r"(a0), "r"(a1), "r"(a2), "r"(a3), "l"(db), "r"(meta), "n"(SC));
}
template<int SC> __device__ __forceinline__ void wg_ss192(float (&d)[96], uint64_t da, uint64_t db) {
  asm volatile("{\n.reg .pred p;\nsetp.ne.b32 p, %98, 0;\nwgmma.mma_async.sync.aligned.m64n192k16.f32.bf16.bf16 {%0,%1,%2,%3,%4,%5,%6,%7,%8,%9,%10,%11,%12,%13,%14,%15,%16,%17,%18,%19,%20,%21,%22,%23,%24,%25,%26,%27,%28,%29,%30,%31,%32,%33,%34,%35,%36,%37,%38,%39,%40,%41,%42,%43,%44,%45,%46,%47,%48,%49,%50,%51,%52,%53,%54,%55,%56,%57,%58,%59,%60,%61,%62,%63,%64,%65,%66,%67,%68,%69,%70,%71,%72,%73,%74,%75,%76,%77,%78,%79,%80,%81,%82,%83,%84,%85,%86,%87,%88,%89,%90,%91,%92,%93,%94,%95}, %96, %97, p, 1, 1, 0, 1;\n}\n"
    : "+f"(d[0]),"+f"(d[1]),"+f"(d[2]),"+f"(d[3]),"+f"(d[4]),"+f"(d[5]),"+f"(d[6]),"+f"(d[7]),"+f"(d[8]),"+f"(d[9]),"+f"(d[10]),"+f"(d[11]),"+f"(d[12]),"+f"(d[13]),"+f"(d[14]),"+f"(d[15]),"+f"(d[16]),"+f"(d[17]),"+f"(d[18]),"+f"(d[19]),"+f"(d[20]),"+f"(d[21]),"+f"(d[22]),"+f"(d[23]),"+f"(d[24]),"+f"(d[25]),"+f"(d[26]),"+f"(d[27]),"+f"(d[28]),"+f"(d[29]),"+f"(d[30]),"+f"(d[31]),"+f"(d[32]),"+f"(d[33]),"+f"(d[34]),"+f"(d[35]),"+f"(d[36]),"+f"(d[37]),"+f"(d[38]),"+f"(d[39]),"+f"(d[40]),"+f"(d[41]),"+f"(d[42]),"+f"(d[43]),"+f"(d[44]),"+f"(d[45]),"+f"(d[46]),"+f"(d[47]),"+f"(d[48]),"+f"(d[49]),"+f"(d[50]),"+f"(d[51]),"+f"(d[52]),"+f"(d[53]),"+f"(d[54]),"+f"(d[55]),"+f"(d[56]),"+f"(d[57]),"+f"(d[58]),"+f"(d[59]),"+f"(d[60]),"+f"(d[61]),"+f"(d[62]),"+f"(d[63]),"+f"(d[64]),"+f"(d[65]),"+f"(d[66]),"+f"(d[67]),"+f"(d[68]),"+f"(d[69]),"+f"(d[70]),"+f"(d[71]),"+f"(d[72]),"+f"(d[73]),"+f"(d[74]),"+f"(d[75]),"+f"(d[76]),"+f"(d[77]),"+f"(d[78]),"+f"(d[79]),"+f"(d[80]),"+f"(d[81]),"+f"(d[82]),"+f"(d[83]),"+f"(d[84]),"+f"(d[85]),"+f"(d[86]),"+f"(d[87]),"+f"(d[88]),"+f"(d[89]),"+f"(d[90]),"+f"(d[91]),"+f"(d[92]),"+f"(d[93]),"+f"(d[94]),"+f"(d[95]) : "l"(da), "l"(db), "n"(SC));
}

constexpr uint32_t SBC = 1024;
constexpr int ROWB = 2 * 224 * 384;
constexpr int KS = 832;
constexpr int KSLOT = 22 * KS;
constexpr int SM_X0 = 0;
constexpr int SM_X1 = 18432;
constexpr int SM_X2 = SM_X1 + 24576;
constexpr int SM_W = SM_X2 + 24576;
constexpr int SM_K = SM_W + 55296;
constexpr int SM_V = SM_K + 2 * KSLOT;
constexpr int SM_Q = SM_V + 22 * 1536;
constexpr int SM_RPB = SM_Q + 24576;
constexpr int SM_BAR = SM_RPB + 768;
constexpr int SM_A_TOTAL = SM_BAR + 512;
enum { B_FULL = 0, B_EMPTY = 3, B_QKISS = 6, B_PVISS, B_KFREE, B_VFREE, B_KRDY, B_VQRDY, B_Q0, B_W, B_ODONE = B_W + 6, B_COUNT = B_ODONE + 28 };

__device__ int g_flags[784];

#define TR(role, it, k)
#define TRB(it, k)
#define TR2(blk, k)

struct GemmCtx {
  uint32_t bar;
  uint32_t kC, vC, qC;
  uint32_t kH, vH;
  uint32_t em;
  bool hvalid;
  int warp;
};

template <int STRIDE> __device__ __forceinline__ void dump12(uint32_t a, const uint32_t (&r)[12]) {
#pragma unroll
  for (int j = 0; j < 3; j++) stsm4(a + j * 2 * STRIDE, r[4 * j], r[4 * j + 1], r[4 * j + 2], r[4 * j + 3]);
}
template <int N> __device__ __forceinline__ void pack12(uint32_t (&r)[12], const float (&d)[N], int off) {
#pragma unroll
  for (int j = 0; j < 12; j++) r[j] = pack2(d[off + 2 * j], d[off + 2 * j + 1]);
}
template <int XS, int K0, int K1> __device__ __forceinline__ void issue_core(float (&d)[72]) {
  constexpr uint64_t da = mkdesc(SBC + XS, 16, 1024, 1), db = mkdesc(SBC + SM_W, 2048, 256, 3);
  if (K0 == 0) { wg_fence(); wg_ss144<0>(d, da, db); }
#pragma unroll
  for (int k = K0 ? K0 : 1; k < K1; k++) wg_ss144<1>(d, da + (k >> 2) * 512 + (k & 3) * 2, db + (k >> 2) * 1152 + (k & 3) * 32);
  wg_commit();
}
template <int K0, int K1> __device__ __forceinline__ void issue_halo(float (&d)[48]) {
  constexpr uint64_t da = mkdesc(SBC + SM_X0, 16, 1024, 1), db = mkdesc(SBC + SM_W, 2048, 256, 3);
  if (K0 == 0) { wg_fence(); wg_ss96<0>(d, da, db); }
#pragma unroll
  for (int k = K0 ? K0 : 1; k < K1; k++) wg_ss96<1>(d, da + (k >> 2) * 384 + (k & 3) * 2, db + (k >> 2) * 1152 + (k & 3) * 32);
  wg_commit();
}
template <int ST, int BYTES> __device__ __forceinline__ void release_stage(const GemmCtx& c, bool on) {
  asm volatile("{\n.reg .pred p, q;\n.reg .b32 ra;\nsetp.ne.b32 q, %2, 0;\nelect.sync _|p, 0xffffffff;\nand.pred p, p, q;\n"
               "mapa.shared::cluster.u32 ra, %1, %4;\n"
               "@p mbarrier.arrive.expect_tx.shared::cta.b64 _, [%0], %3;\n@p mbarrier.arrive.shared::cluster.b64 _, [ra];\n}"
               ::"r"(c.bar + (B_FULL + ST) * 8), "r"(c.bar + (B_EMPTY + ST) * 8), "r"((int)on), "n"(BYTES / 4), "n"(ST) : "memory");
}
__device__ __forceinline__ void load_w(const CUtensorMap* m, uint32_t sb, int ch, int part, int head) {
  asm volatile("cp.async.bulk.tensor.3d.shared::cluster.global.mbarrier::complete_tx::bytes [%0], [%1, {%3,%4,%5}], [%2];"
               ::"r"(sb + SM_W + ch * 18432 + part * 6144), "l"(m), "r"(sb + SM_BAR + (B_W + ch + (part == 2 ? 3 : 0)) * 8),
                 "r"(0), "r"(ch * 64), "r"((part == 2 ? 0 : part * 12 + 12) + head * 3) : "memory");
}
__device__ __forceinline__ void publish(uint32_t bar) {
  fence_async();
  __syncwarp();
  mbar_arrive_elect(bar);
}

template <bool FIRST, bool LAST>
__device__ __forceinline__ void gemm_iter(const GemmCtx& c, int b, uint32_t (&pk)[12], uint32_t (&pv)[12], uint32_t (&pq)[12]) {
  const uint32_t bar = c.bar;
  const uint32_t pa = b & 1;
  const bool w = b >= 0;
  const uint32_t ko = pa * KSLOT, vx = pa * 16, qx = pa * 128;
  float H[48], C[72];
  uint32_t hk[12], hv[12], pv2[12];
  TR(2, b + 2, 0);
  mbar_wait(bar + (B_FULL + 0) * 8, pa);
  if (!LAST && !FIRST) mbar_wait(bar + (B_FULL + 2) * 8, pa);
  TR(2, b + 2, 1);
  if (w) mbar_wait(bar + B_QKISS * 8, pa);
  TR(2, b + 2, 2);
  if (FIRST) {
    mbar_wait(bar + (B_W + 0) * 8, 0); issue_halo<0, 4>(H);
    mbar_wait(bar + (B_W + 1) * 8, 0); issue_halo<4, 8>(H);
    mbar_wait(bar + (B_W + 2) * 8, 0);
  } else issue_halo<0, 8>(H);
  TR(2, b + 2, 3);
  if (!FIRST) {
    if (w) mbar_wait(bar + B_KFREE * 8, pa);
    dump12<128>(c.kC + ko, pk);
  }
  issue_halo<8, 12>(H);
  TR(2, b + 2, 4);
  if (!LAST) {
    if (FIRST) { mbar_wait(bar + (B_FULL + 2) * 8, pa); mbar_wait(bar + (B_W + 3) * 8, 0); mbar_wait(bar + (B_W + 4) * 8, 0); }
    issue_core<SM_X2, 0, 8>(C);
    TR(2, b + 2, 5);
    if (!FIRST) dump12<256>(c.qC ^ (qx ^ 192), pq);
    wg_wait<1>(); pin(H);
    release_stage<0, 18432>(c, true);
  } else {
    dump12<256>(c.qC ^ (qx ^ 192), pq);
    wg_wait<0>(); pin(H);
  }
  pack12(hk, H, 0);
  if (c.hvalid) dump12<128>(c.kH + ko, hk);
  pack12(hv, H, 24);
  if (FIRST) mbar_wait(bar + (B_W + 5) * 8, 0);
  if (!LAST) issue_core<SM_X2, 8, 12>(C);
  if (!FIRST) publish(bar + (w ? B_VQRDY : B_Q0) * 8);
  if (!LAST) {
    mbar_wait(bar + (B_FULL + 1) * 8, pa);
    TR(2, b + 2, 6);
    wg_wait<0>(); pin(C);
    TR(2, b + 2, 7);
    release_stage<2, 24576>(c, b < 11);
    pack12(pk, C, 0);
    pack12(pv2, C, 24);
    pack12(pq, C, 48);
    if (w) mbar_wait(bar + B_PVISS * 8, pa);
    TR(2, b + 2, 8);
    issue_core<SM_X1, 0, 8>(C);
    TR(2, b + 2, 9);
    dump12<128>(c.kC + ko + 64, pk);
  }
  if (!FIRST) publish(bar + B_KRDY * 8);
  TR(2, b + 2, 10);
  if (!LAST) issue_core<SM_X1, 8, 12>(C);
  if (w) mbar_wait(bar + B_VFREE * 8, pa);
  if (!FIRST) dump12<128>(c.vC ^ vx, pv);
  if (!LAST) dump12<256>(c.qC ^ qx, pq);
  if (c.hvalid) dump12<128>(c.vH ^ vx, hv);
  if (LAST) { publish(bar + B_VQRDY * 8); return; }
  dump12<128>((c.vC ^ vx ^ 16) + 768, pv2);
  TR(2, b + 2, 11);
  wg_wait<0>(); pin(C);
  TR(2, b + 2, 12);
  release_stage<1, 24576>(c, b < 11);
  pack12(pk, C, 0);
  pack12(pv, C, 24);
  pack12(pq, C, 48);
}

template <int U, int L, bool BORDER>
__device__ __forceinline__ void softmax_tile(const float (&SA)[56], const float (&SB)[56], const float (&T)[14], bool b0, bool b1,
                                             uint32_t ra0, uint32_t ra1, int qcu, uint32_t (&P)[28], float& sumU, float& sumL) {
  const float cs = 0.14433756729740643f * 1.4426950408889634f;
  float lu[14], ll[14];
#pragma unroll
  for (int j = 0; j < 7; j++) {
    float tu0, tu1, tl0, tl1;
    if (BORDER) {
      tu0 = lds_f32(ra0 + (U + j + 3 - qcu) * 4); tu1 = lds_f32(ra1 + (U + j + 3 - qcu) * 4);
      tl0 = lds_f32(ra0 + (L + j + 2 - qcu) * 4); tl1 = lds_f32(ra1 + (L + j + 2 - qcu) * 4);
    } else { tu0 = tl0 = T[2 * j]; tu1 = tl1 = T[2 * j + 1]; }
    lu[2 * j]     = fmaf(b0 ? SB[4 * (U + j)]     : SA[4 * (U + j)],     cs, tu0);
    lu[2 * j + 1] = fmaf(b1 ? SB[4 * (U + j) + 1] : SA[4 * (U + j) + 1], cs, tu1);
    ll[2 * j]     = fmaf(b0 ? SB[4 * (L + j) + 2] : SA[4 * (L + j) + 2], cs, tl0);
    ll[2 * j + 1] = fmaf(b1 ? SB[4 * (L + j) + 3] : SA[4 * (L + j) + 3], cs, tl1);
  }
  float mu = lu[0], ml = ll[0], mu2 = lu[1], ml2 = ll[1];
#pragma unroll
  for (int j = 1; j < 7; j++) { mu = fmaxf(mu, lu[2 * j]); mu2 = fmaxf(mu2, lu[2 * j + 1]); ml = fmaxf(ml, ll[2 * j]); ml2 = fmaxf(ml2, ll[2 * j + 1]); }
  mu = fmaxf(mu, mu2); ml = fmaxf(ml, ml2);
  mu = fmaxf(mu, __shfl_xor_sync(0xffffffffu, mu, 1)); ml = fmaxf(ml, __shfl_xor_sync(0xffffffffu, ml, 1));
  mu = fmaxf(mu, __shfl_xor_sync(0xffffffffu, mu, 2)); ml = fmaxf(ml, __shfl_xor_sync(0xffffffffu, ml, 2));
  float su = 0.f, sl = 0.f, su2 = 0.f, sl2 = 0.f;
#pragma unroll
  for (int c = 0; c < 14; c++) {
    const int iu = (c >> 1) * 4 + (c & 1) * 2;
    if (c >= U && c < U + 7) {
      float e0 = ex2(lu[2 * (c - U)] - mu), e1 = ex2(lu[2 * (c - U) + 1] - mu);
      su += e0; su2 += e1; P[iu] = pack2(e0, e1);
    } else P[iu] = 0u;
    if (c >= L && c < L + 7) {
      float e0 = ex2(ll[2 * (c - L)] - ml), e1 = ex2(ll[2 * (c - L) + 1] - ml);
      sl += e0; sl2 += e1; P[iu + 1] = pack2(e0, e1);
    } else P[iu + 1] = 0u;
  }
  sumU = su + su2; sumL = sl + sl2;
}

__global__ void __cluster_dims__(4, 1, 1) __launch_bounds__(512, 1)
na_attn_kernel(const __grid_constant__ CUtensorMap mapC, const __grid_constant__ CUtensorMap mapH,
               const __grid_constant__ CUtensorMap mapW, const __nv_bfloat16* __restrict__ rpb, __nv_bfloat16* __restrict__ out) {
  extern __shared__ __align__(1024) uint8_t smem_raw[];
  const uint32_t sb = smem_u32(smem_raw);
  if ((sb & 0x3FFFF) != SBC) return;
  const uint32_t bar = sb + SM_BAR;
  asm volatile("griddepcontrol.launch_dependents;");
  TR(3, 0, threadIdx.x >> 7);
  TR2(blockIdx.x, 0);
  const int tid = threadIdx.x, lane = tid & 31;
  const int warp = __shfl_sync(0xffffffffu, tid >> 5, 0);
  const int head = blockIdx.x & 3, cl = blockIdx.x >> 2;
  const int par = cl / 7, strip = cl - par * 7, ph = par >> 1, pw = par & 1;

  if (warp >= 12) {
    asm volatile("setmaxnreg.dec.sync.aligned.u32 24;");
    const int cc = ph * 112 + (head ? strip * 16 : (strip == 0 ? 16 : (strip == 6 ? 74 : strip * 16 - 3)));
    const int sd = strip == 0 ? -1 : (strip == 6 ? 1 : 0);
    const int r0 = head == 0 ? -4 : (head == 1 ? 4 : 0);
    if (elect_one()) {
      if (warp == 12) {
#pragma unroll
        for (int i = 0; i < 6; i++) mbar_init(bar + (B_W + i) * 8, 1);
        load_w(&mapW, sb, 0, 0, head); load_w(&mapW, sb, 0, 1, head);
#pragma unroll
        for (int i = 0; i < 6; i++) mbar_expect(bar + (B_W + i) * 8, i < 3 ? 12288 : 6144);
      } else if (warp == 13) {
#pragma unroll
        for (int i = 0; i < B_W; i++) mbar_init(bar + i * 8, i < B_EMPTY ? 4 : (i < B_QKISS ? 16 : (i < B_KRDY ? 8 : 4)));
#pragma unroll
        for (int i = 0; i < 3; i++) {
          asm volatile("mbarrier.expect_tx.shared::cta.b64 [%0], %1;" ::"r"(bar + (B_FULL + i) * 8), "r"(i ? 24576 : 18432) : "memory");
          asm volatile("mbarrier.arrive.shared::cta.b64 _, [%0], 4;" ::"r"(bar + (B_FULL + i) * 8) : "memory");
        }
      } else {
        if (warp == 14) {
          if (head == 0) asm volatile("cp.async.bulk.prefetch.tensor.5d.L2.global [%0, {%1,%2,%3,%4,%5}];" ::"l"(&mapH), "r"(0), "r"(r0), "r"(cc), "r"(sd), "r"(pw * 3) : "memory");
          else if (head < 3) asm volatile("cp.async.bulk.prefetch.tensor.4d.L2.global [%0, {%1,%2,%3,%4}];" ::"l"(&mapC), "r"(0), "r"(r0), "r"(cc), "r"(pw * 3) : "memory");
        }
#pragma unroll
        for (int i = 0; i < 14; i++) mbar_init(bar + (B_ODONE + warp - 14 + 2 * i) * 8, 4);
      }
      asm volatile("fence.mbarrier_init.release.cluster;" ::: "memory");
    }
    __syncwarp();
    TR(3, 2, 3);
    cluster_sync();
    TR(3, 2, 4);
    if (warp == 12) {
      const uint32_t fb = bar + (B_FULL + head) * 8, eb = bar + (B_EMPTY + head) * 8;
      const uint32_t dst = sb + (head == 0 ? SM_X0 : (head == 1 ? SM_X1 : SM_X2));
      const int nl = head == 0 ? 15 : (head == 3 ? 1 : 14);
#pragma unroll 1
      for (int n = 0; n < nl; n++) {
        if (n) mbar_wait(eb, (n - 1) & 1);
        if (elect_one()) {
        if (head == 0) {
          asm volatile("cp.async.bulk.tensor.5d.shared::cluster.global.mbarrier::complete_tx::bytes.multicast::cluster [%0], [%1, {%3,%4,%5,%6,%7}], [%2], %8;"
                       ::"r"(dst), "l"(&mapH), "r"(fb), "r"(0), "r"(8 * n + r0), "r"(cc), "r"(sd), "r"(pw * 3), "h"((uint16_t)15) : "memory");
        } else if (head < 3) {
          asm volatile("cp.async.bulk.tensor.4d.shared::cluster.global.mbarrier::complete_tx::bytes.multicast::cluster [%0], [%1, {%3,%4,%5,%6}], [%2], %7;"
                       ::"r"(dst), "l"(&mapC), "r"(fb), "r"(0), "r"(8 * n + r0), "r"(cc), "r"(pw * 3), "h"((uint16_t)15) : "memory");
        }
        if (n == 0) {
#pragma unroll 1
          for (int i = 2; i < 9; i++) load_w(&mapW, sb, i < 6 ? i >> 1 : i - 6, i < 6 ? i & 1 : 2, head);
        }
        if (head == 0) {
          if (n + 1 < nl) asm volatile("cp.async.bulk.prefetch.tensor.5d.L2.global [%0, {%1,%2,%3,%4,%5}];" ::"l"(&mapH), "r"(0), "r"(8 * n + 8 + r0), "r"(cc), "r"(sd), "r"(pw * 3) : "memory");
        } else {
          if (n + 1 < nl) asm volatile("cp.async.bulk.prefetch.tensor.4d.L2.global [%0, {%1,%2,%3,%4}];" ::"l"(&mapC), "r"(0), "r"(8 * n + 8 + r0), "r"(cc), "r"(pw * 3) : "memory");
        }
        }
        __syncwarp();
      }
    }
    if (warp >= 14) {
      const int j = warp - 14;
      int* flag = g_flags + cl * 2 + j;
#pragma unroll 1
      for (int b = 0; b < 14; b++) {
        mbar_wait(bar + (B_ODONE + 2 * b + j) * 8, 0);
        asm volatile("{\n.reg .pred p;\nfence.acq_rel.gpu;\nelect.sync _|p, 0xffffffff;\n@p red.relaxed.gpu.global.add.s32 [%0], 1;\n}" ::"l"(flag + b * 56) : "memory");
      }
    }
    __syncwarp();
    cluster_sync();
  } else if (warp >= 8) {
    asm volatile("barrier.cluster.arrive.relaxed.aligned;" ::: "memory");
    TR(3, 2, 2);
    asm volatile("setmaxnreg.inc.sync.aligned.u32 184;");
    GemmCtx c;
    c.bar = bar; c.warp = warp - 8;
    const int tk = c.warp * 16 + (lane & 15), hi = lane >> 4;
    { const int col = tk >> 2, i = tk & 3;
      c.kC = sb + SM_K + (col + 3) * KS + hi * 128 + i * 16;
      c.vC = sb + SM_V + (col + 3) * 1536 + hi * 128 + (2 * i + ((col + 3) & 1)) * 16;
      c.qC = sb + SM_Q + col * 1536 + hi * 256 + (col & 1) * 64 + i * 16; }
    { const int ci = tk >> 3, kc = ci < 3 ? ci : ci + 16, i = tk & 7; c.hvalid = c.warp < 3;
      c.kH = sb + SM_K + kc * KS + hi * 128 + i * 16;
      c.vH = sb + SM_V + kc * 1536 + hi * 128 + (i >> 2) * 768 + (2 * (i & 3) + ((kc ^ (i >> 2)) & 1)) * 16; }
    TR(3, 1, 2);
    asm volatile("barrier.cluster.wait.aligned;" ::: "memory");
    TR(3, 1, 0);
    uint32_t pk[12], pv[12], pq[12];
    gemm_iter<true, false>(c, -2, pk, pv, pq);
#pragma unroll 1
    for (int b = -1; b < 12; b++) gemm_iter<false, false>(c, b, pk, pv, pq);
    gemm_iter<false, true>(c, 12, pk, pv, pq);
    cluster_sync();
  } else {
    asm volatile("barrier.cluster.arrive.relaxed.aligned;" ::: "memory");
    TR(3, 2, threadIdx.x >> 7);
    asm volatile("setmaxnreg.inc.sync.aligned.u32 152;");
    if (tid < 182) {
      float v = tid < 169 ? __bfloat162float(rpb[head * 169 + tid]) * 1.4426950408889634f : -INFINITY;
      asm volatile("st.shared.f32 [%0], %1;" ::"r"(sb + SM_RPB + tid * 4), "f"(v) : "memory");
    }
    if (tid < 192) {
      const int x = tid % 96, kc = x / 6 + 3, ch = x % 6;
      const uint32_t a = tid < 96 ? sb + SM_K + kc * KS + ch * 128 + 48 : sb + SM_V + kc * 1536 + ch * 128 + (6 + (kc & 1)) * 16;
      asm volatile("st.shared.v4.b32 [%0], {%1,%1,%1,%1};" ::"r"(a), "r"(0) : "memory");
    }
    const int j = warp >> 2, w = warp & 3;
    int variant = w;
    if (strip == 0 && j == 0 && w < 2) variant = 4;
    if (strip == 6 && j == 1 && w >= 2) variant = 5;
    const uint32_t qa = sb + SM_Q + (8 * j + 2 * w + ((lane >> 3) & 1)) * 1536 + (lane >> 4) * 256 + (((lane & 7) * 16) ^ (((lane >> 3) & 1) * 64));
    const uint64_t dK = mkdesc(SBC + SM_K, 128, KS, 0) + j * (8 * KS / 16);
    const uint64_t dV = mkdesc(SBC + SM_V, 768, 128, 0) + j * (8 * 1536 / 16);
    uint8_t* op = reinterpret_cast<uint8_t*>(out) + (size_t)(ph * 224 + 2 * (strip * 16 + 8 * j + 2 * w) + pw) * 384 + (size_t)(2 * head) * ROWB;
    const uint32_t off0 = ((lane & 3) == 3 ? ROWB : (lane & 3) * 128) + (lane >> 2) * 16;
    const uint32_t off1 = ROWB + 128 + (lane & 2) * 64 + (lane >> 2) * 16 + (lane & 1) * 8;
    TR(3, 3, j);
    asm volatile("barrier.cluster.wait.aligned;" ::: "memory");
    TR(3, 3, 2 + j);
    fence_async();
    asm volatile("bar.sync 1, 256;" ::: "memory");
    float T[14];
    bool b0 = false, b1 = false;
    uint32_t ra0 = 0, ra1 = 0, meta = 0;
    uint32_t q[12];
    mbar_wait(bar + B_Q0 * 8, 0);
#pragma unroll
    for (int k = 0; k < 3; k++) ldsm4(qa + k * 512, q[4 * k], q[4 * k + 1], q[4 * k + 2], q[4 * k + 3]);
#pragma unroll 1
    for (int b = 0; b < 14; b++) {
      const uint32_t pa = b & 1;
      if (b <= 1 || b == 13) {
        uint32_t ln; asm volatile("mov.u32 %0, %%laneid;" : "=r"(ln));
        const int g = ln >> 2, t = ln & 3;
        const int sw = b == 0 ? max(g + 1, 4) : (b == 13 ? min(g + 1, 5) : g + 1);
        const int i0 = 2 * t, i1 = 2 * t + 1;
        b0 = i0 <= sw - 2; b1 = i1 <= sw - 2;
        const int m = sw - 1;
        ra0 = sb + SM_RPB + (i0 == m ? 13 : i0 + (b0 ? 8 : 0) - g + 2) * 52;
        ra1 = sb + SM_RPB + (i1 == m ? 13 : i1 + (b1 ? 8 : 0) - g + 2) * 52;
#pragma unroll
        for (int jj = 0; jj < 7; jj++) { T[2 * jj] = lds_f32(ra0 + (jj + 3) * 4); T[2 * jj + 1] = lds_f32(ra1 + (jj + 3) * 4); }
        uint32_t m16 = 0x8888u;
#pragma unroll
        for (int i = 0; i < 8; i++) m16 |= (uint32_t)(((i <= sw - 2) ^ (i >> 2) ^ t ^ b) & 1) << (2 * i);
        meta = m16 | (m16 << 16);
      } else meta ^= 0x55555555u;
      float SA[56], SB[56];
      const uint64_t dA = dK + pa * (KSLOT >> 4), dB = dK + (pa ^ 1) * (KSLOT >> 4);
      TR(j, b, 0);
      mbar_wait(bar + B_KRDY * 8, pa);
      TR(j, b, 1);
      wg_fence();
      wg_rs112<0>(SA, q[0], q[1], q[2], q[3], dA);
      wg_rs112<0>(SB, q[0], q[1], q[2], q[3], dB);
      wg_rs112<1>(SA, q[4], q[5], q[6], q[7], dA + 16);
      wg_rs112<1>(SB, q[4], q[5], q[6], q[7], dB + 16);
      wg_rs112<1>(SA, q[8], q[9], q[10], q[11], dA + 32);
      wg_rs112<1>(SB, q[8], q[9], q[10], q[11], dB + 32);
      wg_commit();
      mbar_arrive_elect(bar + B_QKISS * 8);
      TR(j, b, 2);
      wg_wait<0>(); pin(SA); pin(SB);
      mbar_arrive_elect(bar + B_KFREE * 8);
      TR(j, b, 3);
      uint32_t P[28];
      float su, sl;
      switch (variant) {
        case 0: softmax_tile<0, 1, false>(SA, SB, T, b0, b1, ra0, ra1, 0, P, su, sl); break;
        case 1: softmax_tile<2, 3, false>(SA, SB, T, b0, b1, ra0, ra1, 0, P, su, sl); break;
        case 2: softmax_tile<4, 5, false>(SA, SB, T, b0, b1, ra0, ra1, 0, P, su, sl); break;
        case 3: softmax_tile<6, 7, false>(SA, SB, T, b0, b1, ra0, ra1, 0, P, su, sl); break;
        case 4: softmax_tile<3, 3, true>(SA, SB, T, b0, b1, ra0, ra1, 2 * w, P, su, sl); break;
        default: softmax_tile<4, 4, true>(SA, SB, T, b0, b1, ra0, ra1, 2 * w, P, su, sl); break;
      }
      float O[24];
      TR(j, b, 4);
      su += __shfl_xor_sync(0xffffffffu, su, 1); sl += __shfl_xor_sync(0xffffffffu, sl, 1);
      mbar_wait(bar + B_VQRDY * 8, pa);
      TR(j, b, 5);
      su += __shfl_xor_sync(0xffffffffu, su, 2); sl += __shfl_xor_sync(0xffffffffu, sl, 2);
#pragma unroll
      for (int k = 0; k < 3; k++) ldsm4(qa + (pa ^ 1) * 128 + k * 512, q[4 * k], q[4 * k + 1], q[4 * k + 2], q[4 * k + 3]);
      wg_fence();
      wg_sp48<0>(O, P[0], P[1], P[2], P[3], dV, meta);
#pragma unroll
      for (int s = 1; s < 7; s++) wg_sp48<1>(O, P[4 * s], P[4 * s + 1], P[4 * s + 2], P[4 * s + 3], dV + s * 192, meta);
      wg_commit();
      mbar_arrive_elect(bar + B_PVISS * 8);
      TR(j, b, 6);
      const float ru = __fdividef(1.f, su), rl = __fdividef(1.f, sl);
      wg_wait<0>(); pin(O);
      mbar_arrive_elect(bar + B_VFREE * 8);
      TR(j, b, 7);
      *reinterpret_cast<uint4*>(op + off0) = make_uint4(pack2(O[0] * ru, O[1] * ru), pack2(O[4] * ru, O[5] * ru), pack2(O[8] * ru, O[9] * ru), pack2(O[12] * ru, O[13] * ru));
      *reinterpret_cast<uint4*>(op + off0 + 768) = make_uint4(pack2(O[2] * rl, O[3] * rl), pack2(O[6] * rl, O[7] * rl), pack2(O[10] * rl, O[11] * rl), pack2(O[14] * rl, O[15] * rl));
      *reinterpret_cast<uint2*>(op + off1) = make_uint2(pack2(O[16] * ru, O[17] * ru), pack2(O[20] * ru, O[21] * ru));
      *reinterpret_cast<uint2*>(op + off1 + 768) = make_uint2(pack2(O[18] * rl, O[19] * rl), pack2(O[22] * rl, O[23] * rl));
      op += 8 * ROWB;
      __syncwarp();
      mbar_arrive_elect(bar + (B_ODONE + 2 * b + j) * 8);
      TR(j, b, 8);
    }
    TR2(blockIdx.x, 2);
    cluster_sync();
  }
}

constexpr int NSTB = 4;
constexpr int SM_B_IN = 0;
constexpr int SM_B_W = SM_B_IN + NSTB * 24576;
constexpr int WOS = 3088;
constexpr int SM_B_BAR = SM_B_W + 24 * WOS;
constexpr int SM_B_TOTAL = SM_B_BAR + 64;

__global__ void __launch_bounds__(288, 1)
na_proj_kernel(const __grid_constant__ CUtensorMap mapI, const __nv_bfloat16* __restrict__ wo, __nv_bfloat16* out) {
  extern __shared__ __align__(1024) uint8_t smem_raw[];
  const uint32_t sb = smem_u32(smem_raw);
  if ((sb & 0x3FFFF) != SBC) return;
  const uint32_t bar = sb + SM_B_BAR;
  const int tid = threadIdx.x, lane = tid & 31;
  const int warp = __shfl_sync(0xffffffffu, tid >> 5, 0);
  TR2(132 + blockIdx.x, 0);
  TRB(47, 0);
  if (warp < 8) {
#pragma unroll
    for (int i = 0; i < 5; i++) {
      const int pc = tid + i * 256;
      if (pc < 1152) {
        const uint4* src = reinterpret_cast<const uint4*>(wo) + pc * 4;
        const uint4 a = __ldg(src), b = __ldg(src + 1), c = __ldg(src + 2), d = __ldg(src + 3);
        const int row = pc / 6, jj = pc - row * 6, hd = row / 48, dim = row - hd * 48, g8 = dim >> 3, t = (dim >> 1) & 3;
        const int kk = (g8 < 4 ? t * 8 + g8 * 2 : 32 + t * 4 + (g8 - 4) * 2) + (dim & 1);
        const uint32_t dst = sb + SM_B_W + jj * 4 * WOS + (hd * 48 + kk) * 16;
        asm volatile("st.shared.v4.b32 [%0], {%1,%2,%3,%4};" ::"r"(dst), "r"(a.x), "r"(b.x), "r"(c.x), "r"(d.x) : "memory");
        asm volatile("st.shared.v4.b32 [%0], {%1,%2,%3,%4};" ::"r"(dst + WOS), "r"(a.y), "r"(b.y), "r"(c.y), "r"(d.y) : "memory");
        asm volatile("st.shared.v4.b32 [%0], {%1,%2,%3,%4};" ::"r"(dst + 2 * WOS), "r"(a.z), "r"(b.z), "r"(c.z), "r"(d.z) : "memory");
        asm volatile("st.shared.v4.b32 [%0], {%1,%2,%3,%4};" ::"r"(dst + 3 * WOS), "r"(a.w), "r"(b.w), "r"(c.w), "r"(d.w) : "memory");
      }
    }
    fence_async();
  } else if (elect_one()) {
#pragma unroll
    for (int i = 0; i < 2 * NSTB; i++) mbar_init(bar + i * 8, i < NSTB ? 1 : 4);
  }
  __syncthreads();
  const int step = gridDim.x;
  TRB(47, 1);
  if (warp == 8) {
    int it = 0;
    uint32_t spin = 0;
#pragma unroll 1
    for (int n = blockIdx.x; n < 784 && spin < SPIN_LIMIT; spin++) {
      int v = 0;
      const int mine = n + lane * step;
      if (lane < 8 && mine < 784) asm volatile("ld.acquire.gpu.global.s32 %0, [%1];" : "=r"(v) : "l"(g_flags + mine) : "memory");
      int cnt = __ffs(~__ballot_sync(0xffffffffu, v >= 4)) - 1;
      asm volatile("fence.proxy.async.global;" ::: "memory");
      __syncwarp();
#pragma unroll 1
      for (; cnt > 0; cnt--, n += step, it++) {
        TRB(it, 0);
        const int b = n / 56, rem = n - b * 56, par = rem / 14;
        const int st = it & (NSTB - 1), use = it / NSTB;
        if (use) mbar_wait(bar + (NSTB + st) * 8, (use - 1) & 1);
        if (elect_one()) {
          mbar_expect(bar + st * 8, 24576);
          asm volatile("cp.async.bulk.tensor.3d.shared::cluster.global.mbarrier::complete_tx::bytes [%0], [%1, {%3,%4,%5}], [%2];"
                       ::"r"(sb + SM_B_IN + st * 24576), "l"(&mapI), "r"(bar + st * 8), "r"((par & 1) * 192), "r"(8 * b), "r"((par >> 1) * 112 + (rem - par * 14) * 8) : "memory");
        }
        __syncwarp();
        TRB(it, 2);
      }
    }
    for (int n = blockIdx.x + lane * step; n < 784; n += 32 * step) g_flags[n] = 0;
  } else {
    const int wg = warp >> 2, w = warp & 3;
    constexpr uint64_t db = mkdesc(SBC + SM_B_W, 128, WOS, 0);
    uint8_t* const ob = reinterpret_cast<uint8_t*>(out) + (size_t)(lane >> 2) * ROWB + w * 1536 + (lane & 3) * 16;
    int it = wg;
#pragma unroll 1
    for (int n = blockIdx.x + wg * step; n < 784; n += 2 * step, it += 2) {
      const int b = n / 56, rem = n - b * 56, par = rem / 14, sg = it & (NSTB - 1);
      const uint64_t da = mkdesc(SBC + SM_B_IN, 128, 3072, 0) + sg * (24576 / 16);
      float D[96];
      mbar_wait(bar + sg * 8, (it / NSTB) & 1);
      TRB(it, 3);
      wg_fence();
      wg_ss192<0>(D, da, db);
#pragma unroll
      for (int k = 1; k < 12; k++) wg_ss192<1>(D, da + k * 16, db + k * 16);
      wg_commit();
      TRB(it, 4);
      uint8_t* o = ob + (size_t)(8 * b) * ROWB + ((par >> 1) * 112 + (rem - par * 14) * 8) * 768 + (par & 1) * 384;
      wg_wait<0>(); pin(D);
      mbar_arrive_elect(bar + (NSTB + sg) * 8);
      TRB(it, 5);
#pragma unroll
      for (int q = 0; q < 6; q++) {
        *reinterpret_cast<uint4*>(o + q * 64) = make_uint4(pack2(D[16 * q], D[16 * q + 1]), pack2(D[16 * q + 4], D[16 * q + 5]), pack2(D[16 * q + 8], D[16 * q + 9]), pack2(D[16 * q + 12], D[16 * q + 13]));
        *reinterpret_cast<uint4*>(o + 768 + q * 64) = make_uint4(pack2(D[16 * q + 2], D[16 * q + 3]), pack2(D[16 * q + 6], D[16 * q + 7]), pack2(D[16 * q + 10], D[16 * q + 11]), pack2(D[16 * q + 14], D[16 * q + 15]));
      }
      TRB(it, 6);
    }
    TR2(132 + blockIdx.x, 2);
  }
}

typedef CUresult (*EncodeFn)(CUtensorMap*, CUtensorMapDataType, cuuint32_t, void*, const cuuint64_t*, const cuuint64_t*, const cuuint32_t*,
                             const cuuint32_t*, CUtensorMapInterleave, CUtensorMapSwizzle, CUtensorMapL2promotion, CUtensorMapFloatOOBfill);

extern "C" void kernel_launch(void* const* d_in, const int* in_sizes, int n_in, void* d_out, int out_size) {
  const __nv_bfloat16* x = (const __nv_bfloat16*)d_in[0];
  const __nv_bfloat16* wqkv = (const __nv_bfloat16*)d_in[1];
  const __nv_bfloat16* wo = (const __nv_bfloat16*)d_in[2];
  const __nv_bfloat16* rpb = (const __nv_bfloat16*)d_in[3];
  __nv_bfloat16* out = (__nv_bfloat16*)d_out;

  static EncodeFn enc = nullptr;
  if (!enc) {
    void* fn = nullptr; cudaDriverEntryPointQueryResult qr;
    cudaGetDriverEntryPoint("cuTensorMapEncodeTiled", &fn, cudaEnableDefault, &qr);
    enc = (EncodeFn)fn;
    cudaFuncSetAttribute(na_attn_kernel, cudaFuncAttributeMaxDynamicSharedMemorySize, SM_A_TOTAL);
    cudaFuncSetAttribute(na_proj_kernel, cudaFuncAttributeMaxDynamicSharedMemorySize, SM_B_TOTAL);
  }
  CUtensorMap mC, mH, mI, mW;
  const cuuint32_t ones[5] = {1, 1, 1, 1, 1};
  {
    cuuint64_t dim[4] = {64, 112, 224, 6}, str[3] = {(cuuint64_t)ROWB, 768, 128};
    cuuint32_t box[4] = {64, 4, 16, 3};
    enc(&mC, CU_TENSOR_MAP_DATA_TYPE_BFLOAT16, 4, (void*)x, dim, str, box, ones, CU_TENSOR_MAP_INTERLEAVE_NONE, CU_TENSOR_MAP_SWIZZLE_128B,
        CU_TENSOR_MAP_L2_PROMOTION_L2_128B, CU_TENSOR_MAP_FLOAT_OOB_FILL_NONE);
  }
  {
    cuuint64_t dim[5] = {64, 112, 224, 2, 6}, str[4] = {(cuuint64_t)ROWB, 768, 19 * 768, 128};
    cuuint32_t box[5] = {64, 8, 3, 2, 3};
    enc(&mH, CU_TENSOR_MAP_DATA_TYPE_BFLOAT16, 5, (void*)x, dim, str, box, ones, CU_TENSOR_MAP_INTERLEAVE_NONE, CU_TENSOR_MAP_SWIZZLE_128B,
        CU_TENSOR_MAP_L2_PROMOTION_L2_128B, CU_TENSOR_MAP_FLOAT_OOB_FILL_NONE);
  }
  {
    cuuint64_t dim[3] = {384, 112, 224}, str[2] = {(cuuint64_t)ROWB, 768};
    cuuint32_t box[3] = {192, 8, 8};
    enc(&mI, CU_TENSOR_MAP_DATA_TYPE_BFLOAT16, 3, (void*)out, dim, str, box, ones, CU_TENSOR_MAP_INTERLEAVE_NONE, CU_TENSOR_MAP_SWIZZLE_NONE,
        CU_TENSOR_MAP_L2_PROMOTION_NONE, CU_TENSOR_MAP_FLOAT_OOB_FILL_NONE);
  }
  {
    cuuint64_t dim[3] = {16, 192, 36}, str[2] = {1152, 32};
    cuuint32_t box[3] = {16, 64, 3};
    enc(&mW, CU_TENSOR_MAP_DATA_TYPE_BFLOAT16, 3, (void*)wqkv, dim, str, box, ones, CU_TENSOR_MAP_INTERLEAVE_NONE, CU_TENSOR_MAP_SWIZZLE_32B,
        CU_TENSOR_MAP_L2_PROMOTION_L2_128B, CU_TENSOR_MAP_FLOAT_OOB_FILL_NONE);
  }
  na_attn_kernel<<<112, 512, SM_A_TOTAL>>>(mC, mH, mW, rpb, out);
#define NBCTA 20
  cudaLaunchConfig_t cfg = {};
  cfg.gridDim = dim3(NBCTA); cfg.blockDim = dim3(288); cfg.dynamicSmemBytes = SM_B_TOTAL; cfg.stream = cudaStreamPerThread;
  cudaLaunchAttribute at[1];
  at[0].id = cudaLaunchAttributeProgrammaticStreamSerialization; at[0].val.programmaticStreamSerializationAllowed = 1;
  cfg.attrs = at; cfg.numAttrs = 1;
  cudaLaunchKernelEx(&cfg, na_proj_kernel, mI, wo, out);
}
```

```cpp
#include <cuda_runtime.h>
#include <cuda_bf16.h>
#include <cuda.h>
#include <stdint.h>

#define SPIN_LIMIT (1u << 18)

__device__ __forceinline__ uint32_t smem_u32(const void* p) { return (uint32_t)__cvta_generic_to_shared(p); }
__device__ __forceinline__ void wg_fence() { asm volatile("wgmma.fence.sync.aligned;" ::: "memory"); }
__device__ __forceinline__ void wg_commit() { asm volatile("wgmma.commit_group.sync.aligned;" ::: "memory"); }
template <int N> __device__ __forceinline__ void wg_wait() { asm volatile("wgmma.wait_group.sync.aligned %0;" ::"n"(N) : "memory"); }
template <int N> __device__ __forceinline__ void pin(float (&d)[N]) {
#pragma unroll
  for (int i = 0; i < N; i++) asm volatile("" : "+f"(d[i])::"memory");
}
__host__ __device__ constexpr uint64_t mkdesc(uint32_t addr, uint32_t lbo, uint32_t sbo, uint32_t sw) {
  return (uint64_t)((addr & 0x3FFFF) >> 4) | ((uint64_t)(lbo >> 4) << 16) | ((uint64_t)(sbo >> 4) << 32) | ((uint64_t)sw << 62);
}
__device__ __forceinline__ void mbar_init(uint32_t bar, uint32_t cnt) { asm volatile("mbarrier.init.shared::cta.b64 [%0], %1;" ::"r"(bar), "r"(cnt) : "memory"); }
__device__ __forceinline__ void mbar_arrive(uint32_t bar) { asm volatile("mbarrier.arrive.shared::cta.b64 _, [%0];" ::"r"(bar) : "memory"); }
__device__ __forceinline__ bool elect_one() {
  uint32_t r; asm volatile("{\n.reg .pred p;\nelect.sync _|p, 0xffffffff;\nselp.u32 %0, 1, 0, p;\n}" : "=r"(r)); return r;
}
__device__ __forceinline__ void mbar_arrive_elect(uint32_t bar) {
  asm volatile("{\n.reg .pred p;\nelect.sync _|p, 0xffffffff;\n@p mbarrier.arrive.shared::cta.b64 _, [%0];\n}" ::"r"(bar) : "memory");
}
__device__ __forceinline__ void mbar_expect(uint32_t bar, uint32_t bytes) { asm volatile("mbarrier.arrive.expect_tx.shared::cta.b64 _, [%0], %1;" ::"r"(bar), "r"(bytes) : "memory"); }
__device__ __forceinline__ void mbar_arrive_remote(uint32_t bar, uint32_t cta) {
  asm volatile("{\n.reg .b32 ra;\nmapa.shared::cluster.u32 ra, %0, %1;\nmbarrier.arrive.shared::cluster.b64 _, [ra];\n}" ::"r"(bar), "r"(cta) : "memory");
}
__device__ __forceinline__ void mbar_wait(uint32_t bar, uint32_t parity) {
  asm volatile("{\n.reg .pred p;\n.reg .b32 n;\nmov.b32 n, 0;\nWL:\nmbarrier.try_wait.parity.shared::cta.b64 p, [%0], %1;\n@p bra WD;\n"
               "add.u32 n, n, 1;\nsetp.lt.u32 p, n, 65536;\n@p bra WL;\nWD:\n}" ::"r"(bar), "r"(parity) : "memory");
}
__device__ __forceinline__ void fence_async() { asm volatile("fence.proxy.async.shared::cta;" ::: "memory"); }
__device__ __forceinline__ void cluster_sync() {
  asm volatile("barrier.cluster.arrive.relaxed.aligned;\nbarrier.cluster.wait.aligned;" ::: "memory");
}
__device__ __forceinline__ uint32_t pack2(float lo, float hi) {
  uint32_t r; asm("cvt.rn.bf16x2.f32 %0, %1, %2;" : "=r"(r) : "f"(hi), "f"(lo)); return r;
}
__device__ __forceinline__ void stsm4(uint32_t a, uint32_t r0, uint32_t r1, uint32_t r2, uint32_t r3) {
  asm volatile("stmatrix.sync.aligned.m8n8.x4.shared.b16 [%0], {%1,%2,%3,%4};" ::"r"(a), "r"(r0), "r"(r1), "r"(r2), "r"(r3) : "memory");
}
__device__ __forceinline__ void ldsm4(uint32_t a, uint32_t& r0, uint32_t& r1, uint32_t& r2, uint32_t& r3) {
  asm volatile("ldmatrix.sync.aligned.m8n8.x4.shared.b16 {%0,%1,%2,%3}, [%4];" : "=r"(r0), "=r"(r1), "=r"(r2), "=r"(r3) : "r"(a) : "memory");
}
__device__ __forceinline__ float lds_f32(uint32_t a) { float v; asm volatile("ld.shared.f32 %0, [%1];" : "=f"(v) : "r"(a)); return v; }
__device__ __forceinline__ float ex2(float x) { float y; asm("ex2.approx.ftz.f32 %0, %1;" : "=f"(y) : "f"(x)); return y; }

template<int SC> __device__ __forceinline__ void wg_ss144(float (&d)[72], uint64_t da, uint64_t db) {
  asm volatile("{\n.reg .pred p;\nsetp.ne.b32 p, %74, 0;\nwgmma.mma_async.sync.aligned.m64n144k16.f32.bf16.bf16 {%0,%1,%2,%3,%4,%5,%6,%7,%8,%9,%10,%11,%12,%13,%14,%15,%16,%17,%18,%19,%20,%21,%22,%23,%24,%25,%26,%27,%28,%29,%30,%31,%32,%33,%34,%35,%36,%37,%38,%39,%40,%41,%42,%43,%44,%45,%46,%47,%48,%49,%50,%51,%52,%53,%54,%55,%56,%57,%58,%59,%60,%61,%62,%63,%64,%65,%66,%67,%68,%69,%70,%71}, %72, %73, p, 1, 1, 0, 1;\n}\n"
    : "+f"(d[0]),"+f"(d[1]),"+f"(d[2]),"+f"(d[3]),"+f"(d[4]),"+f"(d[5]),"+f"(d[6]),"+f"(d[7]),"+f"(d[8]),"+f"(d[9]),"+f"(d[10]),"+f"(d[11]),"+f"(d[12]),"+f"(d[13]),"+f"(d[14]),"+f"(d[15]),"+f"(d[16]),"+f"(d[17]),"+f"(d[18]),"+f"(d[19]),"+f"(d[20]),"+f"(d[21]),"+f"(d[22]),"+f"(d[23]),"+f"(d[24]),"+f"(d[25]),"+f"(d[26]),"+f"(d[27]),"+f"(d[28]),"+f"(d[29]),"+f"(d[30]),"+f"(d[31]),"+f"(d[32]),"+f"(d[33]),"+f"(d[34]),"+f"(d[35]),"+f"(d[36]),"+f"(d[37]),"+f"(d[38]),"+f"(d[39]),"+f"(d[40]),"+f"(d[41]),"+f"(d[42]),"+f"(d[43]),"+f"(d[44]),"+f"(d[45]),"+f"(d[46]),"+f"(d[47]),"+f"(d[48]),"+f"(d[49]),"+f"(d[50]),"+f"(d[51]),"+f"(d[52]),"+f"(d[53]),"+f"(d[54]),"+f"(d[55]),"+f"(d[56]),"+f"(d[57]),"+f"(d[58]),"+f"(d[59]),"+f"(d[60]),"+f"(d[61]),"+f"(d[62]),"+f"(d[63]),"+f"(d[64]),"+f"(d[65]),"+f"(d[66]),"+f"(d[67]),"+f"(d[68]),"+f"(d[69]),"+f"(d[70]),"+f"(d[71]) : "l"(da), "l"(db), "n"(SC));
}
template<int SC> __device__ __forceinline__ void wg_ss96(float (&d)[48], uint64_t da, uint64_t db) {
  asm volatile("{\n.reg .pred p;\nsetp.ne.b32 p, %50, 0;\nwgmma.mma_async.sync.aligned.m64n96k16.f32.bf16.bf16 {%0,%1,%2,%3,%4,%5,%6,%7,%8,%9,%10,%11,%12,%13,%14,%15,%16,%17,%18,%19,%20,%21,%22,%23,%24,%25,%26,%27,%28,%29,%30,%31,%32,%33,%34,%35,%36,%37,%38,%39,%40,%41,%42,%43,%44,%45,%46,%47}, %48, %49, p, 1, 1, 0, 1;\n}\n"
    : "+f"(d[0]),"+f"(d[1]),"+f"(d[2]),"+f"(d[3]),"+f"(d[4]),"+f"(d[5]),"+f"(d[6]),"+f"(d[7]),"+f"(d[8]),"+f"(d[9]),"+f"(d[10]),"+f"(d[11]),"+f"(d[12]),"+f"(d[13]),"+f"(d[14]),"+f"(d[15]),"+f"(d[16]),"+f"(d[17]),"+f"(d[18]),"+f"(d[19]),"+f"(d[20]),"+f"(d[21]),"+f"(d[22]),"+f"(d[23]),"+f"(d[24]),"+f"(d[25]),"+f"(d[26]),"+f"(d[27]),"+f"(d[28]),"+f"(d[29]),"+f"(d[30]),"+f"(d[31]),"+f"(d[32]),"+f"(d[33]),"+f"(d[34]),"+f"(d[35]),"+f"(d[36]),"+f"(d[37]),"+f"(d[38]),"+f"(d[39]),"+f"(d[40]),"+f"(d[41]),"+f"(d[42]),"+f"(d[43]),"+f"(d[44]),"+f"(d[45]),"+f"(d[46]),"+f"(d[47]) : "l"(da), "l"(db), "n"(SC));
}
template<int SC> __device__ __forceinline__ void wg_rs112(float (&d)[56], uint32_t a0, uint32_t a1, uint32_t a2, uint32_t a3, uint64_t db) {
  asm volatile("{\n.reg .pred p;\nsetp.ne.b32 p, %61, 0;\nwgmma.mma_async.sync.aligned.m64n112k16.f32.bf16.bf16 {%0,%1,%2,%3,%4,%5,%6,%7,%8,%9,%10,%11,%12,%13,%14,%15,%16,%17,%18,%19,%20,%21,%22,%23,%24,%25,%26,%27,%28,%29,%30,%31,%32,%33,%34,%35,%36,%37,%38,%39,%40,%41,%42,%43,%44,%45,%46,%47,%48,%49,%50,%51,%52,%53,%54,%55}, {%56,%57,%58,%59}, %60, p, 1, 1, 0;\n}\n"
    : "+f"(d[0]),"+f"(d[1]),"+f"(d[2]),"+f"(d[3]),"+f"(d[4]),"+f"(d[5]),"+f"(d[6]),"+f"(d[7]),"+f"(d[8]),"+f"(d[9]),"+f"(d[10]),"+f"(d[11]),"+f"(d[12]),"+f"(d[13]),"+f"(d[14]),"+f"(d[15]),"+f"(d[16]),"+f"(d[17]),"+f"(d[18]),"+f"(d[19]),"+f"(d[20]),"+f"(d[21]),"+f"(d[22]),"+f"(d[23]),"+f"(d[24]),"+f"(d[25]),"+f"(d[26]),"+f"(d[27]),"+f"(d[28]),"+f"(d[29]),"+f"(d[30]),"+f"(d[31]),"+f"(d[32]),"+f"(d[33]),"+f"(d[34]),"+f"(d[35]),"+f"(d[36]),"+f"(d[37]),"+f"(d[38]),"+f"(d[39]),"+f"(d[40]),"+f"(d[41]),"+f"(d[42]),"+f"(d[43]),"+f"(d[44]),"+f"(d[45]),"+f"(d[46]),"+f"(d[47]),"+f"(d[48]),"+f"(d[49]),"+f"(d[50]),"+f"(d[51]),"+f"(d[52]),"+f"(d[53]),"+f"(d[54]),"+f"(d[55]) : "r"(a0), "r"(a1), "r"(a2), "r"(a3), "l"(db), "n"(SC));
}
template<int SC> __device__ __forceinline__ void wg_sp48(float (&d)[24], uint32_t a0, uint32_t a1, uint32_t a2, uint32_t a3, uint64_t db, uint32_t meta) {
  asm volatile("{\n.reg .pred p;\nsetp.ne.b32 p, %30, 0;\nwgmma.mma_async.sp.sync.aligned.m64n48k32.f32.bf16.bf16 {%0,%1,%2,%3,%4,%5,%6,%7,%8,%9,%10,%11,%12,%13,%14,%15,%16,%17,%18,%19,%20,%21,%22,%23}, {%24,%25,%26,%27}, %28, %29, 0, p, 1, 1, 1;\n}\n"
    : "+f"(d[0]),"+f"(d[1]),"+f"(d[2]),"+f"(d[3]),"+f"(d[4]),"+f"(d[5]),"+f"(d[6]),"+f"(d[7]),"+f"(d[8]),"+f"(d[9]),"+f"(d[10]),"+f"(d[11]),"+f"(d[12]),"+f"(d[13]),"+f"(d[14]),"+f"(d[15]),"+f"(d[16]),"+f"(d[17]),"+f"(d[18]),"+f"(d[19]),"+f"(d[20]),"+f"(d[21]),"+f"(d[22]),"+f"(d[23]) : "r"(a0), "r"(a1), "r"(a2), "r"(a3), "l"(db), "r"(meta), "n"(SC));
}
template<int SC> __device__ __forceinline__ void wg_ss192(float (&d)[96], uint64_t da, uint64_t db) {
  asm volatile("{\n.reg .pred p;\nsetp.ne.b32 p, %98, 0;\nwgmma.mma_async.sync.aligned.m64n192k16.f32.bf16.bf16 {%0,%1,%2,%3,%4,%5,%6,%7,%8,%9,%10,%11,%12,%13,%14,%15,%16,%17,%18,%19,%20,%21,%22,%23,%24,%25,%26,%27,%28,%29,%30,%31,%32,%33,%34,%35,%36,%37,%38,%39,%40,%41,%42,%43,%44,%45,%46,%47,%48,%49,%50,%51,%52,%53,%54,%55,%56,%57,%58,%59,%60,%61,%62,%63,%64,%65,%66,%67,%68,%69,%70,%71,%72,%73,%74,%75,%76,%77,%78,%79,%80,%81,%82,%83,%84,%85,%86,%87,%88,%89,%90,%91,%92,%93,%94,%95}, %96, %97, p, 1, 1, 0, 1;\n}\n"
    : "+f"(d[0]),"+f"(d[1]),"+f"(d[2]),"+f"(d[3]),"+f"(d[4]),"+f"(d[5]),"+f"(d[6]),"+f"(d[7]),"+f"(d[8]),"+f"(d[9]),"+f"(d[10]),"+f"(d[11]),"+f"(d[12]),"+f"(d[13]),"+f"(d[14]),"+f"(d[15]),"+f"(d[16]),"+f"(d[17]),"+f"(d[18]),"+f"(d[19]),"+f"(d[20]),"+f"(d[21]),"+f"(d[22]),"+f"(d[23]),"+f"(d[24]),"+f"(d[25]),"+f"(d[26]),"+f"(d[27]),"+f"(d[28]),"+f"(d[29]),"+f"(d[30]),"+f"(d[31]),"+f"(d[32]),"+f"(d[33]),"+f"(d[34]),"+f"(d[35]),"+f"(d[36]),"+f"(d[37]),"+f"(d[38]),"+f"(d[39]),"+f"(d[40]),"+f"(d[41]),"+f"(d[42]),"+f"(d[43]),"+f"(d[44]),"+f"(d[45]),"+f"(d[46]),"+f"(d[47]),"+f"(d[48]),"+f"(d[49]),"+f"(d[50]),"+f"(d[51]),"+f"(d[52]),"+f"(d[53]),"+f"(d[54]),"+f"(d[55]),"+f"(d[56]),"+f"(d[57]),"+f"(d[58]),"+f"(d[59]),"+f"(d[60]),"+f"(d[61]),"+f"(d[62]),"+f"(d[63]),"+f"(d[64]),"+f"(d[65]),"+f"(d[66]),"+f"(d[67]),"+f"(d[68]),"+f"(d[69]),"+f"(d[70]),"+f"(d[71]),"+f"(d[72]),"+f"(d[73]),"+f"(d[74]),"+f"(d[75]),"+f"(d[76]),"+f"(d[77]),"+f"(d[78]),"+f"(d[79]),"+f"(d[80]),"+f"(d[81]),"+f"(d[82]),"+f"(d[83]),"+f"(d[84]),"+f"(d[85]),"+f"(d[86]),"+f"(d[87]),"+f"(d[88]),"+f"(d[89]),"+f"(d[90]),"+f"(d[91]),"+f"(d[92]),"+f"(d[93]),"+f"(d[94]),"+f"(d[95]) : "l"(da), "l"(db), "n"(SC));
}

constexpr uint32_t SBC = 1024;
constexpr int ROWB = 2 * 224 * 384;
constexpr int KS = 832;
constexpr int KSLOT = 22 * KS;
constexpr int SM_X0 = 0;
constexpr int SM_X1 = 18432;
constexpr int SM_X2 = SM_X1 + 24576;
constexpr int SM_W = SM_X2 + 24576;
constexpr int SM_K = SM_W + 55296;
constexpr int SM_V = SM_K + 2 * KSLOT;
constexpr int SM_Q = SM_V + 22 * 1536;
constexpr int SM_RPB = SM_Q + 24576;
constexpr int SM_BAR = SM_RPB + 768;
constexpr int SM_A_TOTAL = SM_BAR + 512;
enum { B_FULL = 0, B_EMPTY = 3, B_QKISS = 6, B_PVISS, B_KFREE, B_VFREE, B_KRDY, B_VQRDY, B_Q0, B_W, B_ODONE = B_W + 6, B_COUNT = B_ODONE + 28 };

__device__ int g_flags[784];

#define TR(role, it, k)
#define TRB(it, k)
#define TR2(blk, k)

struct GemmCtx {
  uint32_t bar;
  uint32_t kC, vC, qC;
  uint32_t kH, vH;
  uint32_t em;
  bool hvalid;
  int warp;
};

template <int STRIDE> __device__ __forceinline__ void dump12(uint32_t a, const uint32_t (&r)[12]) {
#pragma unroll
  for (int j = 0; j < 3; j++) stsm4(a + j * 2 * STRIDE, r[4 * j], r[4 * j + 1], r[4 * j + 2], r[4 * j + 3]);
}
template <int N> __device__ __forceinline__ void pack12(uint32_t (&r)[12], const float (&d)[N], int off) {
#pragma unroll
  for (int j = 0; j < 12; j++) r[j] = pack2(d[off + 2 * j], d[off + 2 * j + 1]);
}
template <int XS, int K0, int K1> __device__ __forceinline__ void issue_core(float (&d)[72]) {
  constexpr uint64_t da = mkdesc(SBC + XS, 16, 1024, 1), db = mkdesc(SBC + SM_W, 2048, 256, 3);
  if (K0 == 0) { wg_fence(); wg_ss144<0>(d, da, db); }
#pragma unroll
  for (int k = K0 ? K0 : 1; k < K1; k++) wg_ss144<1>(d, da + (k >> 2) * 512 + (k & 3) * 2, db + (k >> 2) * 1152 + (k & 3) * 32);
  wg_commit();
}
template <int K0, int K1> __device__ __forceinline__ void issue_halo(float (&d)[48]) {
  constexpr uint64_t da = mkdesc(SBC + SM_X0, 16, 1024, 1), db = mkdesc(SBC + SM_W, 2048, 256, 3);
  if (K0 == 0) { wg_fence(); wg_ss96<0>(d, da, db); }
#pragma unroll
  for (int k = K0 ? K0 : 1; k < K1; k++) wg_ss96<1>(d, da + (k >> 2) * 384 + (k & 3) * 2, db + (k >> 2) * 1152 + (k & 3) * 32);
  wg_commit();
}
template <int ST, int BYTES> __device__ __forceinline__ void release_stage(const GemmCtx& c, bool on) {
  asm volatile("{\n.reg .pred p, q;\n.reg .b32 ra;\nsetp.ne.b32 q, %2, 0;\nelect.sync _|p, 0xffffffff;\nand.pred p, p, q;\n"
               "mapa.shared::cluster.u32 ra, %1, %4;\n"
               "@p mbarrier.arrive.expect_tx.shared::cta.b64 _, [%0], %3;\n@p mbarrier.arrive.shared::cluster.b64 _, [ra];\n}"
               ::"r"(c.bar + (B_FULL + ST) * 8), "r"(c.bar + (B_EMPTY + ST) * 8), "r"((int)on), "n"(BYTES / 4), "n"(ST) : "memory");
}
__device__ __forceinline__ void load_w(const CUtensorMap* m, uint32_t sb, int ch, int part, int head) {
  asm volatile("cp.async.bulk.tensor.3d.shared::cluster.global.mbarrier::complete_tx::bytes [%0], [%1, {%3,%4,%5}], [%2];"
               ::"r"(sb + SM_W + ch * 18432 + part * 6144), "l"(m), "r"(sb + SM_BAR + (B_W + ch + (part == 2 ? 3 : 0)) * 8),
                 "r"(0), "r"(ch * 64), "r"((part == 2 ? 0 : part * 12 + 12) + head * 3) : "memory");
}
__device__ __forceinline__ void publish(uint32_t bar) {
  fence_async();
  __syncwarp();
  mbar_arrive_elect(bar);
}

template <bool FIRST, bool LAST>
__device__ __forceinline__ void gemm_iter(const GemmCtx& c, int b, uint32_t (&pk)[12], uint32_t (&pv)[12], uint32_t (&pq)[12]) {
  const uint32_t bar = c.bar;
  const uint32_t pa = b & 1;
  const bool w = b >= 0;
  const uint32_t ko = pa * KSLOT, vx = pa * 16, qx = pa * 128;
  float H[48], C[72];
  uint32_t hk[12], hv[12], pv2[12];
  TR(2, b + 2, 0);
  mbar_wait(bar + (B_FULL + 0) * 8, pa);
  if (!LAST && !FIRST) mbar_wait(bar + (B_FULL + 2) * 8, pa);
  TR(2, b + 2, 1);
  if (w) mbar_wait(bar + B_QKISS * 8, pa);
  TR(2, b + 2, 2);
  if (FIRST) {
    mbar_wait(bar + (B_W + 0) * 8, 0); issue_halo<0, 4>(H);
    mbar_wait(bar + (B_W + 1) * 8, 0); issue_halo<4, 8>(H);
    mbar_wait(bar + (B_W + 2) * 8, 0);
  } else issue_halo<0, 8>(H);
  TR(2, b + 2, 3);
  if (!FIRST) {
    if (w) mbar_wait(bar + B_KFREE * 8, pa);
    dump12<128>(c.kC + ko, pk);
  }
  issue_halo<8, 12>(H);
  TR(2, b + 2, 4);
  if (!LAST) {
    if (FIRST) { mbar_wait(bar + (B_FULL + 2) * 8, pa); mbar_wait(bar + (B_W + 3) * 8, 0); mbar_wait(bar + (B_W + 4) * 8, 0); }
    issue_core<SM_X2, 0, 8>(C);
    TR(2, b + 2, 5);
    if (!FIRST) dump12<256>(c.qC ^ (qx ^ 192), pq);
    wg_wait<1>(); pin(H);
    release_stage<0, 18432>(c, true);
  } else {
    dump12<256>(c.qC ^ (qx ^ 192), pq);
    wg_wait<0>(); pin(H);
  }
  pack12(hk, H, 0);
  if (c.hvalid) dump12<128>(c.kH + ko, hk);
  pack12(hv, H, 24);
  if (FIRST) mbar_wait(bar + (B_W + 5) * 8, 0);
  if (!LAST) issue_core<SM_X2, 8, 12>(C);
  if (!FIRST) publish(bar + (w ? B_VQRDY : B_Q0) * 8);
  if (!LAST) {
    mbar_wait(bar + (B_FULL + 1) * 8, pa);
    TR(2, b + 2, 6);
    wg_wait<0>(); pin(C);
    TR(2, b + 2, 7);
    release_stage<2, 24576>(c, b < 11);
    pack12(pk, C, 0);
    pack12(pv2, C, 24);
    pack12(pq, C, 48);
    if (w) mbar_wait(bar + B_PVISS * 8, pa);
    TR(2, b + 2, 8);
    issue_core<SM_X1, 0, 8>(C);
    TR(2, b + 2, 9);
    dump12<128>(c.kC + ko + 64, pk);
  }
  if (!FIRST) publish(bar + B_KRDY * 8);
  TR(2, b + 2, 10);
  if (!LAST) issue_core<SM_X1, 8, 12>(C);
  if (w) mbar_wait(bar + B_VFREE * 8, pa);
  if (!FIRST) dump12<128>(c.vC ^ vx, pv);
  if (!LAST) dump12<256>(c.qC ^ qx, pq);
  if (c.hvalid) dump12<128>(c.vH ^ vx, hv);
  if (LAST) { publish(bar + B_VQRDY * 8); return; }
  dump12<128>((c.vC ^ vx ^ 16) + 768, pv2);
  TR(2, b + 2, 11);
  wg_wait<0>(); pin(C);
  TR(2, b + 2, 12);
  release_stage<1, 24576>(c, b < 11);
  pack12(pk, C, 0);
  pack12(pv, C, 24);
  pack12(pq, C, 48);
}

template <int U, int L, bool BORDER>
__device__ __forceinline__ void softmax_tile(const float (&SA)[56], const float (&SB)[56], const float (&T)[14], bool b0, bool b1,
                                             uint32_t ra0, uint32_t ra1, int qcu, uint32_t (&P)[28], float& sumU, float& sumL) {
  const float cs = 0.14433756729740643f * 1.4426950408889634f;
  float lu[14], ll[14];
#pragma unroll
  for (int j = 0; j < 7; j++) {
    float tu0, tu1, tl0, tl1;
    if (BORDER) {
      tu0 = lds_f32(ra0 + (U + j + 3 - qcu) * 4); tu1 = lds_f32(ra1 + (U + j + 3 - qcu) * 4);
      tl0 = lds_f32(ra0 + (L + j + 2 - qcu) * 4); tl1 = lds_f32(ra1 + (L + j + 2 - qcu) * 4);
    } else { tu0 = tl0 = T[2 * j]; tu1 = tl1 = T[2 * j + 1]; }
    lu[2 * j]     = fmaf(b0 ? SB[4 * (U + j)]     : SA[4 * (U + j)],     cs, tu0);
    lu[2 * j + 1] = fmaf(b1 ? SB[4 * (U + j) + 1] : SA[4 * (U + j) + 1], cs, tu1);
    ll[2 * j]     = fmaf(b0 ? SB[4 * (L + j) + 2] : SA[4 * (L + j) + 2], cs, tl0);
    ll[2 * j + 1] = fmaf(b1 ? SB[4 * (L + j) + 3] : SA[4 * (L + j) + 3], cs, tl1);
  }
  float mu = lu[0], ml = ll[0], mu2 = lu[1], ml2 = ll[1];
#pragma unroll
  for (int j = 1; j < 7; j++) { mu = fmaxf(mu, lu[2 * j]); mu2 = fmaxf(mu2, lu[2 * j + 1]); ml = fmaxf(ml, ll[2 * j]); ml2 = fmaxf(ml2, ll[2 * j + 1]); }
  mu = fmaxf(mu, mu2); ml = fmaxf(ml, ml2);
  mu = fmaxf(mu, __shfl_xor_sync(0xffffffffu, mu, 1)); ml = fmaxf(ml, __shfl_xor_sync(0xffffffffu, ml, 1));
  mu = fmaxf(mu, __shfl_xor_sync(0xffffffffu, mu, 2)); ml = fmaxf(ml, __shfl_xor_sync(0xffffffffu, ml, 2));
  float su = 0.f, sl = 0.f, su2 = 0.f, sl2 = 0.f;
#pragma unroll
  for (int c = 0; c < 14; c++) {
    const int iu = (c >> 1) * 4 + (c & 1) * 2;
    if (c >= U && c < U + 7) {
      float e0 = ex2(lu[2 * (c - U)] - mu), e1 = ex2(lu[2 * (c - U) + 1] - mu);
      su += e0; su2 += e1; P[iu] = pack2(e0, e1);
    } else P[iu] = 0u;
    if (c >= L && c < L + 7) {
      float e0 = ex2(ll[2 * (c - L)] - ml), e1 = ex2(ll[2 * (c - L) + 1] - ml);
      sl += e0; sl2 += e1; P[iu + 1] = pack2(e0, e1);
    } else P[iu + 1] = 0u;
  }
  sumU = su + su2; sumL = sl + sl2;
}

__global__ void __cluster_dims__(4, 1, 1) __launch_bounds__(512, 1)
na_attn_kernel(const __grid_constant__ CUtensorMap mapC, const __grid_constant__ CUtensorMap mapH,
               const __grid_constant__ CUtensorMap mapW, const __nv_bfloat16* __restrict__ rpb, __nv_bfloat16* __restrict__ out) {
  extern __shared__ __align__(1024) uint8_t smem_raw[];
  const uint32_t sb = smem_u32(smem_raw);
  if ((sb & 0x3FFFF) != SBC) return;
  const uint32_t bar = sb + SM_BAR;
  asm volatile("griddepcontrol.launch_dependents;");
  TR(3, 0, threadIdx.x >> 7);
  TR2(blockIdx.x, 0);
  const int tid = threadIdx.x, lane = tid & 31;
  const int warp = __shfl_sync(0xffffffffu, tid >> 5, 0);
  const int head = blockIdx.x & 3, cl = blockIdx.x >> 2;
  const int par = cl / 7, strip = cl - par * 7, ph = par >> 1, pw = par & 1;

  if (warp >= 12) {
    asm volatile("setmaxnreg.dec.sync.aligned.u32 24;");
    const int cc = ph * 112 + (head ? strip * 16 : (strip == 0 ? 16 : (strip == 6 ? 74 : strip * 16 - 3)));
    const int sd = strip == 0 ? -1 : (strip == 6 ? 1 : 0);
    const int r0 = head == 0 ? -4 : (head == 1 ? 4 : 0);
    if (elect_one()) {
      if (warp == 12) {
#pragma unroll
        for (int i = 0; i < 6; i++) mbar_init(bar + (B_W + i) * 8, 1);
        load_w(&mapW, sb, 0, 0, head); load_w(&mapW, sb, 0, 1, head);
#pragma unroll
        for (int i = 0; i < 6; i++) mbar_expect(bar + (B_W + i) * 8, i < 3 ? 12288 : 6144);
      } else if (warp == 13) {
#pragma unroll
        for (int i = 0; i < B_W; i++) mbar_init(bar + i * 8, i < B_EMPTY ? 4 : (i < B_QKISS ? 16 : (i < B_KRDY ? 8 : 4)));
#pragma unroll
        for (int i = 0; i < 3; i++) {
          asm volatile("mbarrier.expect_tx.shared::cta.b64 [%0], %1;" ::"r"(bar + (B_FULL + i) * 8), "r"(i ? 24576 : 18432) : "memory");
          asm volatile("mbarrier.arrive.shared::cta.b64 _, [%0], 4;" ::"r"(bar + (B_FULL + i) * 8) : "memory");
        }
      } else {
        if (warp == 14) {
          if (head == 0) asm volatile("cp.async.bulk.prefetch.tensor.5d.L2.global [%0, {%1,%2,%3,%4,%5}];" ::"l"(&mapH), "r"(0), "r"(r0), "r"(cc), "r"(sd), "r"(pw * 3) : "memory");
          else if (head < 3) asm volatile("cp.async.bulk.prefetch.tensor.4d.L2.global [%0, {%1,%2,%3,%4}];" ::"l"(&mapC), "r"(0), "r"(r0), "r"(cc), "r"(pw * 3) : "memory");
        }
#pragma unroll
        for (int i = 0; i < 14; i++) mbar_init(bar + (B_ODONE + warp - 14 + 2 * i) * 8, 4);
      }
      asm volatile("fence.mbarrier_init.release.cluster;" ::: "memory");
    }
    __syncwarp();
    TR(3, 2, 3);
    cluster_sync();
    TR(3, 2, 4);
    if (warp == 12) {
      const uint32_t fb = bar + (B_FULL + head) * 8, eb = bar + (B_EMPTY + head) * 8;
      const uint32_t dst = sb + (head == 0 ? SM_X0 : (head == 1 ? SM_X1 : SM_X2));
      const int nl = head == 0 ? 15 : (head == 3 ? 1 : 14);
#pragma unroll 1
      for (int n = 0; n < nl; n++) {
        if (n) mbar_wait(eb, (n - 1) & 1);
        if (elect_one()) {
        if (head == 0) {
          asm volatile("cp.async.bulk.tensor.5d.shared::cluster.global.mbarrier::complete_tx::bytes.multicast::cluster [%0], [%1, {%3,%4,%5,%6,%7}], [%2], %8;"
                       ::"r"(dst), "l"(&mapH), "r"(fb), "r"(0), "r"(8 * n + r0), "r"(cc), "r"(sd), "r"(pw * 3), "h"((uint16_t)15) : "memory");
        } else if (head < 3) {
          asm volatile("cp.async.bulk.tensor.4d.shared::cluster.global.mbarrier::complete_tx::bytes.multicast::cluster [%0], [%1, {%3,%4,%5,%6}], [%2], %7;"
                       ::"r"(dst), "l"(&mapC), "r"(fb), "r"(0), "r"(8 * n + r0), "r"(cc), "r"(pw * 3), "h"((uint16_t)15) : "memory");
        }
        if (n == 0) {
#pragma unroll 1
          for (int i = 2; i < 9; i++) load_w(&mapW, sb, i < 6 ? i >> 1 : i - 6, i < 6 ? i & 1 : 2, head);
        }
        if (head == 0) {
          if (n + 1 < nl) asm volatile("cp.async.bulk.prefetch.tensor.5d.L2.global [%0, {%1,%2,%3,%4,%5}];" ::"l"(&mapH), "r"(0), "r"(8 * n + 8 + r0), "r"(cc), "r"(sd), "r"(pw * 3) : "memory");
        } else {
          if (n + 1 < nl) asm volatile("cp.async.bulk.prefetch.tensor.4d.L2.global [%0, {%1,%2,%3,%4}];" ::"l"(&mapC), "r"(0), "r"(8 * n + 8 + r0), "r"(cc), "r"(pw * 3) : "memory");
        }
        }
        __syncwarp();
      }
    }
    if (warp >= 14) {
      const int j = warp - 14;
      int* flag = g_flags + cl * 2 + j;
#pragma unroll 1
      for (int b = 0; b < 14; b++) {
        mbar_wait(bar + (B_ODONE + 2 * b + j) * 8, 0);
        asm volatile("{\n.reg .pred p;\nfence.acq_rel.gpu;\nelect.sync _|p, 0xffffffff;\n@p red.relaxed.gpu.global.add.s32 [%0], 1;\n}" ::"l"(flag + b * 56) : "memory");
      }
    }
    __syncwarp();
    cluster_sync();
  } else if (warp >= 8) {
    asm volatile("barrier.cluster.arrive.relaxed.aligned;" ::: "memory");
    TR(3, 2, 2);
    asm volatile("setmaxnreg.inc.sync.aligned.u32 184;");
    GemmCtx c;
    c.bar = bar; c.warp = warp - 8;
    const int tk = c.warp * 16 + (lane & 15), hi = lane >> 4;
    { const int col = tk >> 2, i = tk & 3;
      c.kC = sb + SM_K + (col + 3) * KS + hi * 128 + i * 16;
      c.vC = sb + SM_V + (col + 3) * 1536 + hi * 128 + (2 * i + ((col + 3) & 1)) * 16;
      c.qC = sb + SM_Q + col * 1536 + hi * 256 + (col & 1) * 64 + i * 16; }
    { const int ci = tk >> 3, kc = ci < 3 ? ci : ci + 16, i = tk & 7; c.hvalid = c.warp < 3;
      c.kH = sb + SM_K + kc * KS + hi * 128 + i * 16;
      c.vH = sb + SM_V + kc * 1536 + hi * 128 + (i >> 2) * 768 + (2 * (i & 3) + ((kc ^ (i >> 2)) & 1)) * 16; }
    TR(3, 1, 2);
    asm volatile("barrier.cluster.wait.aligned;" ::: "memory");
    TR(3, 1, 0);
    uint32_t pk[12], pv[12], pq[12];
    gemm_iter<true, false>(c, -2, pk, pv, pq);
#pragma unroll 1
    for (int b = -1; b < 12; b++) gemm_iter<false, false>(c, b, pk, pv, pq);
    gemm_iter<false, true>(c, 12, pk, pv, pq);
    cluster_sync();
  } else {
    asm volatile("barrier.cluster.arrive.relaxed.aligned;" ::: "memory");
    TR(3, 2, threadIdx.x >> 7);
    asm volatile("setmaxnreg.inc.sync.aligned.u32 152;");
    if (tid < 182) {
      float v = tid < 169 ? __bfloat162float(rpb[head * 169 + tid]) * 1.4426950408889634f : -INFINITY;
      asm volatile("st.shared.f32 [%0], %1;" ::"r"(sb + SM_RPB + tid * 4), "f"(v) : "memory");
    }
    if (tid < 192) {
      const int x = tid % 96, kc = x / 6 + 3, ch = x % 6;
      const uint32_t a = tid < 96 ? sb + SM_K + kc * KS + ch * 128 + 48 : sb + SM_V + kc * 1536 + ch * 128 + (6 + (kc & 1)) * 16;
      asm volatile("st.shared.v4.b32 [%0], {%1,%1,%1,%1};" ::"r"(a), "r"(0) : "memory");
    }
    const int j = warp >> 2, w = warp & 3;
    int variant = w;
    if (strip == 0 && j == 0 && w < 2) variant = 4;
    if (strip == 6 && j == 1 && w >= 2) variant = 5;
    const uint32_t qa = sb + SM_Q + (8 * j + 2 * w + ((lane >> 3) & 1)) * 1536 + (lane >> 4) * 256 + (((lane & 7) * 16) ^ (((lane >> 3) & 1) * 64));
    const uint64_t dK = mkdesc(SBC + SM_K, 128, KS, 0) + j * (8 * KS / 16);
    const uint64_t dV = mkdesc(SBC + SM_V, 768, 128, 0) + j * (8 * 1536 / 16);
    uint8_t* op = reinterpret_cast<uint8_t*>(out) + (size_t)(ph * 224 + 2 * (strip * 16 + 8 * j + 2 * w) + pw) * 384 + (size_t)(2 * head) * ROWB;
    const uint32_t off0 = ((lane & 3) == 3 ? ROWB : (lane & 3) * 128) + (lane >> 2) * 16;
    const uint32_t off1 = ROWB + 128 + (lane & 2) * 64 + (lane >> 2) * 16 + (lane & 1) * 8;
    TR(3, 3, j);
    asm volatile("barrier.cluster.wait.aligned;" ::: "memory");
    TR(3, 3, 2 + j);
    fence_async();
    asm volatile("bar.sync 1, 256;" ::: "memory");
    float T[14];
    bool b0 = false, b1 = false;
    uint32_t ra0 = 0, ra1 = 0, meta = 0;
    uint32_t q[12];
    mbar_wait(bar + B_Q0 * 8, 0);
#pragma unroll
    for (int k = 0; k < 3; k++) ldsm4(qa + k * 512, q[4 * k], q[4 * k + 1], q[4 * k + 2], q[4 * k + 3]);
#pragma unroll 1
    for (int b = 0; b < 14; b++) {
      const uint32_t pa = b & 1;
      if (b <= 1 || b == 13) {
        uint32_t ln; asm volatile("mov.u32 %0, %%laneid;" : "=r"(ln));
        const int g = ln >> 2, t = ln & 3;
        const int sw = b == 0 ? max(g + 1, 4) : (b == 13 ? min(g + 1, 5) : g + 1);
        const int i0 = 2 * t, i1 = 2 * t + 1;
        b0 = i0 <= sw - 2; b1 = i1 <= sw - 2;
        const int m = sw - 1;
        ra0 = sb + SM_RPB + (i0 == m ? 13 : i0 + (b0 ? 8 : 0) - g + 2) * 52;
        ra1 = sb + SM_RPB + (i1 == m ? 13 : i1 + (b1 ? 8 : 0) - g + 2) * 52;
#pragma unroll
        for (int jj = 0; jj < 7; jj++) { T[2 * jj] = lds_f32(ra0 + (jj + 3) * 4); T[2 * jj + 1] = lds_f32(ra1 + (jj + 3) * 4); }
        uint32_t m16 = 0x8888u;
#pragma unroll
        for (int i = 0; i < 8; i++) m16 |= (uint32_t)(((i <= sw - 2) ^ (i >> 2) ^ t ^ b) & 1) << (2 * i);
        meta = m16 | (m16 << 16);
      } else meta ^= 0x55555555u;
      float SA[56], SB[56];
      const uint64_t dA = dK + pa * (KSLOT >> 4), dB = dK + (pa ^ 1) * (KSLOT >> 4);
      TR(j, b, 0);
      mbar_wait(bar + B_KRDY * 8, pa);
      TR(j, b, 1);
      wg_fence();
      wg_rs112<0>(SA, q[0], q[1], q[2], q[3], dA);
      wg_rs112<0>(SB, q[0], q[1], q[2], q[3], dB);
      wg_rs112<1>(SA, q[4], q[5], q[6], q[7], dA + 16);
      wg_rs112<1>(SB, q[4], q[5], q[6], q[7], dB + 16);
      wg_rs112<1>(SA, q[8], q[9], q[10], q[11], dA + 32);
      wg_rs112<1>(SB, q[8], q[9], q[10], q[11], dB + 32);
      wg_commit();
      mbar_arrive_elect(bar + B_QKISS * 8);
      TR(j, b, 2);
      wg_wait<0>(); pin(SA); pin(SB);
      mbar_arrive_elect(bar + B_KFREE * 8);
      TR(j, b, 3);
      uint32_t P[28];
      float su, sl;
      switch (variant) {
        case 0: softmax_tile<0, 1, false>(SA, SB, T, b0, b1, ra0, ra1, 0, P, su, sl); break;
        case 1: softmax_tile<2, 3, false>(SA, SB, T, b0, b1, ra0, ra1, 0, P, su, sl); break;
        case 2: softmax_tile<4, 5, false>(SA, SB, T, b0, b1, ra0, ra1, 0, P, su, sl); break;
        case 3: softmax_tile<6, 7, false>(SA, SB, T, b0, b1, ra0, ra1, 0, P, su, sl); break;
        case 4: softmax_tile<3, 3, true>(SA, SB, T, b0, b1, ra0, ra1, 2 * w, P, su, sl); break;
        default: softmax_tile<4, 4, true>(SA, SB, T, b0, b1, ra0, ra1, 2 * w, P, su, sl); break;
      }
      float O[24];
      TR(j, b, 4);
      su += __shfl_xor_sync(0xffffffffu, su, 1); sl += __shfl_xor_sync(0xffffffffu, sl, 1);
      mbar_wait(bar + B_VQRDY * 8, pa);
      TR(j, b, 5);
      su += __shfl_xor_sync(0xffffffffu, su, 2); sl += __shfl_xor_sync(0xffffffffu, sl, 2);
#pragma unroll
      for (int k = 0; k < 3; k++) ldsm4(qa + (pa ^ 1) * 128 + k * 512, q[4 * k], q[4 * k + 1], q[4 * k + 2], q[4 * k + 3]);
      wg_fence();
      wg_sp48<0>(O, P[0], P[1], P[2], P[3], dV, meta);
#pragma unroll
      for (int s = 1; s < 7; s++) wg_sp48<1>(O, P[4 * s], P[4 * s + 1], P[4 * s + 2], P[4 * s + 3], dV + s * 192, meta);
      wg_commit();
      mbar_arrive_elect(bar + B_PVISS * 8);
      TR(j, b, 6);
      const float ru = __fdividef(1.f, su), rl = __fdividef(1.f, sl);
      wg_wait<0>(); pin(O);
      mbar_arrive_elect(bar + B_VFREE * 8);
      TR(j, b, 7);
      *reinterpret_cast<uint4*>(op + off0) = make_uint4(pack2(O[0] * ru, O[1] * ru), pack2(O[4] * ru, O[5] * ru), pack2(O[8] * ru, O[9] * ru), pack2(O[12] * ru, O[13] * ru));
      *reinterpret_cast<uint4*>(op + off0 + 768) = make_uint4(pack2(O[2] * rl, O[3] * rl), pack2(O[6] * rl, O[7] * rl), pack2(O[10] * rl, O[11] * rl), pack2(O[14] * rl, O[15] * rl));
      *reinterpret_cast<uint2*>(op + off1) = make_uint2(pack2(O[16] * ru, O[17] * ru), pack2(O[20] * ru, O[21] * ru));
      *reinterpret_cast<uint2*>(op + off1 + 768) = make_uint2(pack2(O[18] * rl, O[19] * rl), pack2(O[22] * rl, O[23] * rl));
      op += 8 * ROWB;
      __syncwarp();
      mbar_arrive_elect(bar + (B_ODONE + 2 * b + j) * 8);
      TR(j, b, 8);
    }
    TR2(blockIdx.x, 2);
    cluster_sync();
  }
}

constexpr int NSTB = 4;
constexpr int SM_B_ST = 0;
constexpr int SM_B_IN = 49152;
constexpr int SM_B_W = SM_B_IN + NSTB * 24576;
constexpr int WOS = 3088;
constexpr int SM_B_BAR = SM_B_W + 24 * WOS;
constexpr int SM_B_TOTAL = SM_B_BAR + 64;

__global__ void __launch_bounds__(288, 1)
na_proj_kernel(const __grid_constant__ CUtensorMap mapI, const __grid_constant__ CUtensorMap mapO, const __nv_bfloat16* __restrict__ wo) {
  extern __shared__ __align__(1024) uint8_t smem_raw[];
  const uint32_t sb = smem_u32(smem_raw);
  if ((sb & 0x3FFFF) != SBC) return;
  const uint32_t bar = sb + SM_B_BAR;
  const int tid = threadIdx.x, lane = tid & 31;
  const int warp = __shfl_sync(0xffffffffu, tid >> 5, 0);
  TR2(132 + blockIdx.x, 0);
  TRB(47, 0);
  if (warp < 8) {
    uint4 wv[18];
#pragma unroll
    for (int i = 0; i < 18; i++) wv[i] = __ldg(reinterpret_cast<const uint4*>(wo) + tid + i * 256);
#pragma unroll
    for (int i = 0; i < 18; i++) {
      const int pc = tid + i * 256, row = pc / 24, ng = pc - row * 24, hd = row / 48, dim = row - hd * 48, g8 = dim >> 3, t = (dim >> 1) & 3;
      const int kk = (g8 < 4 ? t * 8 + g8 * 2 : 32 + t * 4 + (g8 - 4) * 2) + (dim & 1);
      asm volatile("st.shared.v4.b32 [%0], {%1,%2,%3,%4};" ::"r"(sb + SM_B_W + ng * WOS + (hd * 48 + kk) * 16), "r"(wv[i].x), "r"(wv[i].y), "r"(wv[i].z), "r"(wv[i].w) : "memory");
    }
    fence_async();
  } else if (elect_one()) {
#pragma unroll
    for (int i = 0; i < 2 * NSTB; i++) mbar_init(bar + i * 8, i < NSTB ? 1 : 4);
  }
  __syncthreads();
  const int step = gridDim.x;
  TRB(47, 1);
  if (warp == 8) {
    int it = 0;
    uint32_t spin = 0;
#pragma unroll 1
    for (int n = blockIdx.x; n < 784 && spin < SPIN_LIMIT; spin++) {
      int v = 0;
      const int mine = n + lane * step;
      if (lane < 8 && mine < 784) asm volatile("ld.acquire.gpu.global.s32 %0, [%1];" : "=r"(v) : "l"(g_flags + mine) : "memory");
      int cnt = __ffs(~__ballot_sync(0xffffffffu, v >= 4)) - 1;
      asm volatile("fence.proxy.async.global;" ::: "memory");
      __syncwarp();
#pragma unroll 1
      for (; cnt > 0; cnt--, n += step, it++) {
        TRB(it, 0);
        const int b = n / 56, rem = n - b * 56, par = rem / 14;
        const int st = it & (NSTB - 1), use = it / NSTB;
        if (use) mbar_wait(bar + (NSTB + st) * 8, (use - 1) & 1);
        if (elect_one()) {
          mbar_expect(bar + st * 8, 24576);
          asm volatile("cp.async.bulk.tensor.3d.shared::cluster.global.mbarrier::complete_tx::bytes [%0], [%1, {%3,%4,%5}], [%2];"
                       ::"r"(sb + SM_B_IN + st * 24576), "l"(&mapI), "r"(bar + st * 8), "r"((par & 1) * 192), "r"(8 * b), "r"((par >> 1) * 112 + (rem - par * 14) * 8) : "memory");
        }
        __syncwarp();
        TRB(it, 2);
      }
    }
    for (int n = blockIdx.x + lane * step; n < 784; n += 32 * step) g_flags[n] = 0;
  } else {
    const int wg = warp >> 2, w = warp & 3;
    constexpr uint64_t db = mkdesc(SBC + SM_B_W, 128, WOS, 0);
    const uint32_t st = sb + SM_B_ST + warp * 6144;
    const uint32_t sta = st + (lane & 15) * 128 + (((lane >> 4) ^ (lane & 7)) * 16);
    int it = wg;
#pragma unroll 1
    for (int n = blockIdx.x + wg * step; n < 784; n += 2 * step, it += 2) {
      const int b = n / 56, rem = n - b * 56, par = rem / 14, sg = it & (NSTB - 1);
      const uint64_t da = mkdesc(SBC + SM_B_IN, 128, 3072, 0) + sg * (24576 / 16);
      float D[96];
      mbar_wait(bar + sg * 8, (it / NSTB) & 1);
      TRB(it, 3);
      wg_fence();
      wg_ss192<0>(D, da, db);
#pragma unroll
      for (int k = 1; k < 12; k++) wg_ss192<1>(D, da + k * 16, db + k * 16);
      wg_commit();
      TRB(it, 4);
      if (lane == 0) asm volatile("cp.async.bulk.wait_group.read 0;" ::: "memory");
      __syncwarp();
      wg_wait<0>(); pin(D);
      mbar_arrive_elect(bar + (NSTB + sg) * 8);
      TRB(it, 5);
#pragma unroll
      for (int q = 0; q < 12; q++)
        stsm4((sta ^ ((q & 3) * 32)) + (q >> 2) * 2048,
              pack2(D[8 * q], D[8 * q + 1]), pack2(D[8 * q + 2], D[8 * q + 3]), pack2(D[8 * q + 4], D[8 * q + 5]), pack2(D[8 * q + 6], D[8 * q + 7]));
      fence_async();
      __syncwarp();
      if (lane == 0) {
        asm volatile("cp.async.bulk.tensor.4d.global.shared::cta.bulk_group [%0, {%2,%3,%4,%5}], [%1];"
                     ::"l"(&mapO), "r"(st), "r"(0), "r"(8 * b), "r"((par >> 1) * 112 + (rem - par * 14) * 8 + 2 * w), "r"((par & 1) * 3) : "memory");
        asm volatile("cp.async.bulk.commit_group;" ::: "memory");
      }
      TRB(it, 6);
    }
    if (lane == 0) asm volatile("cp.async.bulk.wait_group 0;" ::: "memory");
    TR2(132 + blockIdx.x, 2);
  }
}

typedef CUresult (*EncodeFn)(CUtensorMap*, CUtensorMapDataType, cuuint32_t, void*, const cuuint64_t*, const cuuint64_t*, const cuuint32_t*,
                             const cuuint32_t*, CUtensorMapInterleave, CUtensorMapSwizzle, CUtensorMapL2promotion, CUtensorMapFloatOOBfill);

extern "C" void kernel_launch(void* const* d_in, const int* in_sizes, int n_in, void* d_out, int out_size) {
  const __nv_bfloat16* x = (const __nv_bfloat16*)d_in[0];
  const __nv_bfloat16* wqkv = (const __nv_bfloat16*)d_in[1];
  const __nv_bfloat16* wo = (const __nv_bfloat16*)d_in[2];
  const __nv_bfloat16* rpb = (const __nv_bfloat16*)d_in[3];
  __nv_bfloat16* out = (__nv_bfloat16*)d_out;

  static EncodeFn enc = nullptr;
  if (!enc) {
    void* fn = nullptr; cudaDriverEntryPointQueryResult qr;
    cudaGetDriverEntryPoint("cuTensorMapEncodeTiled", &fn, cudaEnableDefault, &qr);
    enc = (EncodeFn)fn;
    cudaFuncSetAttribute(na_attn_kernel, cudaFuncAttributeMaxDynamicSharedMemorySize, SM_A_TOTAL);
    cudaFuncSetAttribute(na_proj_kernel, cudaFuncAttributeMaxDynamicSharedMemorySize, SM_B_TOTAL);
  }
  CUtensorMap mC, mH, mO, mI, mW;
  const cuuint32_t ones[5] = {1, 1, 1, 1, 1};
  {
    cuuint64_t dim[4] = {64, 112, 224, 6}, str[3] = {(cuuint64_t)ROWB, 768, 128};
    cuuint32_t box[4] = {64, 4, 16, 3}, boxo[4] = {64, 8, 2, 3};
    enc(&mC, CU_TENSOR_MAP_DATA_TYPE_BFLOAT16, 4, (void*)x, dim, str, box, ones, CU_TENSOR_MAP_INTERLEAVE_NONE, CU_TENSOR_MAP_SWIZZLE_128B,
        CU_TENSOR_MAP_L2_PROMOTION_L2_128B, CU_TENSOR_MAP_FLOAT_OOB_FILL_NONE);
    enc(&mO, CU_TENSOR_MAP_DATA_TYPE_BFLOAT16, 4, (void*)out, dim, str, boxo, ones, CU_TENSOR_MAP_INTERLEAVE_NONE, CU_TENSOR_MAP_SWIZZLE_128B,
        CU_TENSOR_MAP_L2_PROMOTION_NONE, CU_TENSOR_MAP_FLOAT_OOB_FILL_NONE);
  }
  {
    cuuint64_t dim[5] = {64, 112, 224, 2, 6}, str[4] = {(cuuint64_t)ROWB, 768, 19 * 768, 128};
    cuuint32_t box[5] = {64, 8, 3, 2, 3};
    enc(&mH, CU_TENSOR_MAP_DATA_TYPE_BFLOAT16, 5, (void*)x, dim, str, box, ones, CU_TENSOR_MAP_INTERLEAVE_NONE, CU_TENSOR_MAP_SWIZZLE_128B,
        CU_TENSOR_MAP_L2_PROMOTION_L2_128B, CU_TENSOR_MAP_FLOAT_OOB_FILL_NONE);
  }
  {
    cuuint64_t dim[3] = {384, 112, 224}, str[2] = {(cuuint64_t)ROWB, 768};
    cuuint32_t box[3] = {192, 8, 8};
    enc(&mI, CU_TENSOR_MAP_DATA_TYPE_BFLOAT16, 3, (void*)out, dim, str, box, ones, CU_TENSOR_MAP_INTERLEAVE_NONE, CU_TENSOR_MAP_SWIZZLE_NONE,
        CU_TENSOR_MAP_L2_PROMOTION_NONE, CU_TENSOR_MAP_FLOAT_OOB_FILL_NONE);
  }
  {
    cuuint64_t dim[3] = {16, 192, 36}, str[2] = {1152, 32};
    cuuint32_t box[3] = {16, 64, 3};
    enc(&mW, CU_TENSOR_MAP_DATA_TYPE_BFLOAT16, 3, (void*)wqkv, dim, str, box, ones, CU_TENSOR_MAP_INTERLEAVE_NONE, CU_TENSOR_MAP_SWIZZLE_32B,
        CU_TENSOR_MAP_L2_PROMOTION_L2_128B, CU_TENSOR_MAP_FLOAT_OOB_FILL_NONE);
  }
  na_attn_kernel<<<112, 512, SM_A_TOTAL>>>(mC, mH, mW, rpb, out);
#define NBCTA 20
  cudaLaunchConfig_t cfg = {};
  cfg.gridDim = dim3(NBCTA); cfg.blockDim = dim3(288); cfg.dynamicSmemBytes = SM_B_TOTAL; cfg.stream = cudaStreamPerThread;
  cudaLaunchAttribute at[1];
  at[0].id = cudaLaunchAttributeProgrammaticStreamSerialization; at[0].val.programmaticStreamSerializationAllowed = 1;
  cfg.attrs = at; cfg.numAttrs = 1;
  cudaLaunchKernelEx(&cfg, na_proj_kernel, mI, mO, wo);
}
```

```cpp
#include <cuda_runtime.h>
#include <cuda_bf16.h>
#include <cuda.h>
#include <stdint.h>

#define SPIN_LIMIT (1u << 18)

__device__ __forceinline__ uint32_t smem_u32(const void* p) { return (uint32_t)__cvta_generic_to_shared(p); }
__device__ __forceinline__ void wg_fence() { asm volatile("wgmma.fence.sync.aligned;" ::: "memory"); }
__device__ __forceinline__ void wg_commit() { asm volatile("wgmma.commit_group.sync.aligned;" ::: "memory"); }
template <int N> __device__ __forceinline__ void wg_wait() { asm volatile("wgmma.wait_group.sync.aligned %0;" ::"n"(N) : "memory"); }
template <int N> __device__ __forceinline__ void pin(float (&d)[N]) {
#pragma unroll
  for (int i = 0; i < N; i++) asm volatile("" : "+f"(d[i])::"memory");
}
__host__ __device__ constexpr uint64_t mkdesc(uint32_t addr, uint32_t lbo, uint32_t sbo, uint32_t sw) {
  return (uint64_t)((addr & 0x3FFFF) >> 4) | ((uint64_t)(lbo >> 4) << 16) | ((uint64_t)(sbo >> 4) << 32) | ((uint64_t)sw << 62);
}
__device__ __forceinline__ void mbar_init(uint32_t bar, uint32_t cnt) { asm volatile("mbarrier.init.shared::cta.b64 [%0], %1;" ::"r"(bar), "r"(cnt) : "memory"); }
__device__ __forceinline__ void mbar_arrive(uint32_t bar) { asm volatile("mbarrier.arrive.shared::cta.b64 _, [%0];" ::"r"(bar) : "memory"); }
__device__ __forceinline__ bool elect_one() {
  uint32_t r; asm volatile("{\n.reg .pred p;\nelect.sync _|p, 0xffffffff;\nselp.u32 %0, 1, 0, p;\n}" : "=r"(r)); return r;
}
__device__ __forceinline__ void mbar_arrive_elect(uint32_t bar) {
  asm volatile("{\n.reg .pred p;\nelect.sync _|p, 0xffffffff;\n@p mbarrier.arrive.shared::cta.b64 _, [%0];\n}" ::"r"(bar) : "memory");
}
__device__ __forceinline__ void mbar_expect(uint32_t bar, uint32_t bytes) { asm volatile("mbarrier.arrive.expect_tx.shared::cta.b64 _, [%0], %1;" ::"r"(bar), "r"(bytes) : "memory"); }
__device__ __forceinline__ void mbar_arrive_remote(uint32_t bar, uint32_t cta) {
  asm volatile("{\n.reg .b32 ra;\nmapa.shared::cluster.u32 ra, %0, %1;\nmbarrier.arrive.shared::cluster.b64 _, [ra];\n}" ::"r"(bar), "r"(cta) : "memory");
}
__device__ __forceinline__ void mbar_wait(uint32_t bar, uint32_t parity) {
  asm volatile("{\n.reg .pred p;\n.reg .b32 n;\nmov.b32 n, 0;\nWL:\nmbarrier.try_wait.parity.shared::cta.b64 p, [%0], %1;\n@p bra WD;\n"
               "add.u32 n, n, 1;\nsetp.lt.u32 p, n, 65536;\n@p bra WL;\nWD:\n}" ::"r"(bar), "r"(parity) : "memory");
}
__device__ __forceinline__ void fence_async() { asm volatile("fence.proxy.async.shared::cta;" ::: "memory"); }
__device__ __forceinline__ void cluster_sync() {
  asm volatile("barrier.cluster.arrive.relaxed.aligned;\nbarrier.cluster.wait.aligned;" ::: "memory");
}
__device__ __forceinline__ uint32_t pack2(float lo, float hi) {
  uint32_t r; asm("cvt.rn.bf16x2.f32 %0, %1, %2;" : "=r"(r) : "f"(hi), "f"(lo)); return r;
}
__device__ __forceinline__ void stsm4(uint32_t a, uint32_t r0, uint32_t r1, uint32_t r2, uint32_t r3) {
  asm volatile("stmatrix.sync.aligned.m8n8.x4.shared.b16 [%0], {%1,%2,%3,%4};" ::"r"(a), "r"(r0), "r"(r1), "r"(r2), "r"(r3) : "memory");
}
__device__ __forceinline__ void ldsm4(uint32_t a, uint32_t& r0, uint32_t& r1, uint32_t& r2, uint32_t& r3) {
  asm volatile("ldmatrix.sync.aligned.m8n8.x4.shared.b16 {%0,%1,%2,%3}, [%4];" : "=r"(r0), "=r"(r1), "=r"(r2), "=r"(r3) : "r"(a) : "memory");
}
__device__ __forceinline__ void sts128(uint32_t a, uint4 v) {
  asm volatile("st.shared.v4.b32 [%0], {%1,%2,%3,%4};" ::"r"(a), "r"(v.x), "r"(v.y), "r"(v.z), "r"(v.w) : "memory");
}
__device__ __forceinline__ float lds_f32(uint32_t a) { float v; asm volatile("ld.shared.f32 %0, [%1];" : "=f"(v) : "r"(a)); return v; }
__device__ __forceinline__ float ex2(float x) { float y; asm("ex2.approx.ftz.f32 %0, %1;" : "=f"(y) : "f"(x)); return y; }

template<int SC> __device__ __forceinline__ void wg_ss144(float (&d)[72], uint64_t da, uint64_t db) {
  asm volatile("{\n.reg .pred p;\nsetp.ne.b32 p, %74, 0;\nwgmma.mma_async.sync.aligned.m64n144k16.f32.bf16.bf16 {%0,%1,%2,%3,%4,%5,%6,%7,%8,%9,%10,%11,%12,%13,%14,%15,%16,%17,%18,%19,%20,%21,%22,%23,%24,%25,%26,%27,%28,%29,%30,%31,%32,%33,%34,%35,%36,%37,%38,%39,%40,%41,%42,%43,%44,%45,%46,%47,%48,%49,%50,%51,%52,%53,%54,%55,%56,%57,%58,%59,%60,%61,%62,%63,%64,%65,%66,%67,%68,%69,%70,%71}, %72, %73, p, 1, 1, 0, 1;\n}\n"
    : "+f"(d[0]),"+f"(d[1]),"+f"(d[2]),"+f"(d[3]),"+f"(d[4]),"+f"(d[5]),"+f"(d[6]),"+f"(d[7]),"+f"(d[8]),"+f"(d[9]),"+f"(d[10]),"+f"(d[11]),"+f"(d[12]),"+f"(d[13]),"+f"(d[14]),"+f"(d[15]),"+f"(d[16]),"+f"(d[17]),"+f"(d[18]),"+f"(d[19]),"+f"(d[20]),"+f"(d[21]),"+f"(d[22]),"+f"(d[23]),"+f"(d[24]),"+f"(d[25]),"+f"(d[26]),"+f"(d[27]),"+f"(d[28]),"+f"(d[29]),"+f"(d[30]),"+f"(d[31]),"+f"(d[32]),"+f"(d[33]),"+f"(d[34]),"+f"(d[35]),"+f"(d[36]),"+f"(d[37]),"+f"(d[38]),"+f"(d[39]),"+f"(d[40]),"+f"(d[41]),"+f"(d[42]),"+f"(d[43]),"+f"(d[44]),"+f"(d[45]),"+f"(d[46]),"+f"(d[47]),"+f"(d[48]),"+f"(d[49]),"+f"(d[50]),"+f"(d[51]),"+f"(d[52]),"+f"(d[53]),"+f"(d[54]),"+f"(d[55]),"+f"(d[56]),"+f"(d[57]),"+f"(d[58]),"+f"(d[59]),"+f"(d[60]),"+f"(d[61]),"+f"(d[62]),"+f"(d[63]),"+f"(d[64]),"+f"(d[65]),"+f"(d[66]),"+f"(d[67]),"+f"(d[68]),"+f"(d[69]),"+f"(d[70]),"+f"(d[71]) : "l"(da), "l"(db), "n"(SC));
}
template<int SC> __device__ __forceinline__ void wg_ss96(float (&d)[48], uint64_t da, uint64_t db) {
  asm volatile("{\n.reg .pred p;\nsetp.ne.b32 p, %50, 0;\nwgmma.mma_async.sync.aligned.m64n96k16.f32.bf16.bf16 {%0,%1,%2,%3,%4,%5,%6,%7,%8,%9,%10,%11,%12,%13,%14,%15,%16,%17,%18,%19,%20,%21,%22,%23,%24,%25,%26,%27,%28,%29,%30,%31,%32,%33,%34,%35,%36,%37,%38,%39,%40,%41,%42,%43,%44,%45,%46,%47}, %48, %49, p, 1, 1, 0, 1;\n}\n"
    : "+f"(d[0]),"+f"(d[1]),"+f"(d[2]),"+f"(d[3]),"+f"(d[4]),"+f"(d[5]),"+f"(d[6]),"+f"(d[7]),"+f"(d[8]),"+f"(d[9]),"+f"(d[10]),"+f"(d[11]),"+f"(d[12]),"+f"(d[13]),"+f"(d[14]),"+f"(d[15]),"+f"(d[16]),"+f"(d[17]),"+f"(d[18]),"+f"(d[19]),"+f"(d[20]),"+f"(d[21]),"+f"(d[22]),"+f"(d[23]),"+f"(d[24]),"+f"(d[25]),"+f"(d[26]),"+f"(d[27]),"+f"(d[28]),"+f"(d[29]),"+f"(d[30]),"+f"(d[31]),"+f"(d[32]),"+f"(d[33]),"+f"(d[34]),"+f"(d[35]),"+f"(d[36]),"+f"(d[37]),"+f"(d[38]),"+f"(d[39]),"+f"(d[40]),"+f"(d[41]),"+f"(d[42]),"+f"(d[43]),"+f"(d[44]),"+f"(d[45]),"+f"(d[46]),"+f"(d[47]) : "l"(da), "l"(db), "n"(SC));
}
template<int SC> __device__ __forceinline__ void wg_rs112(float (&d)[56], uint32_t a0, uint32_t a1, uint32_t a2, uint32_t a3, uint64_t db) {
  asm volatile("{\n.reg .pred p;\nsetp.ne.b32 p, %61, 0;\nwgmma.mma_async.sync.aligned.m64n112k16.f32.bf16.bf16 {%0,%1,%2,%3,%4,%5,%6,%7,%8,%9,%10,%11,%12,%13,%14,%15,%16,%17,%18,%19,%20,%21,%22,%23,%24,%25,%26,%27,%28,%29,%30,%31,%32,%33,%34,%35,%36,%37,%38,%39,%40,%41,%42,%43,%44,%45,%46,%47,%48,%49,%50,%51,%52,%53,%54,%55}, {%56,%57,%58,%59}, %60, p, 1, 1, 0;\n}\n"
    : "+f"(d[0]),"+f"(d[1]),"+f"(d[2]),"+f"(d[3]),"+f"(d[4]),"+f"(d[5]),"+f"(d[6]),"+f"(d[7]),"+f"(d[8]),"+f"(d[9]),"+f"(d[10]),"+f"(d[11]),"+f"(d[12]),"+f"(d[13]),"+f"(d[14]),"+f"(d[15]),"+f"(d[16]),"+f"(d[17]),"+f"(d[18]),"+f"(d[19]),"+f"(d[20]),"+f"(d[21]),"+f"(d[22]),"+f"(d[23]),"+f"(d[24]),"+f"(d[25]),"+f"(d[26]),"+f"(d[27]),"+f"(d[28]),"+f"(d[29]),"+f"(d[30]),"+f"(d[31]),"+f"(d[32]),"+f"(d[33]),"+f"(d[34]),"+f"(d[35]),"+f"(d[36]),"+f"(d[37]),"+f"(d[38]),"+f"(d[39]),"+f"(d[40]),"+f"(d[41]),"+f"(d[42]),"+f"(d[43]),"+f"(d[44]),"+f"(d[45]),"+f"(d[46]),"+f"(d[47]),"+f"(d[48]),"+f"(d[49]),"+f"(d[50]),"+f"(d[51]),"+f"(d[52]),"+f"(d[53]),"+f"(d[54]),"+f"(d[55]) : "r"(a0), "r"(a1), "r"(a2), "r"(a3), "l"(db), "n"(SC));
}
template<int SC> __device__ __forceinline__ void wg_sp48(float (&d)[24], uint32_t a0, uint32_t a1, uint32_t a2, uint32_t a3, uint64_t db, uint32_t meta) {
  asm volatile("{\n.reg .pred p;\nsetp.ne.b32 p, %30, 0;\nwgmma.mma_async.sp.sync.aligned.m64n48k32.f32.bf16.bf16 {%0,%1,%2,%3,%4,%5,%6,%7,%8,%9,%10,%11,%12,%13,%14,%15,%16,%17,%18,%19,%20,%21,%22,%23}, {%24,%25,%26,%27}, %28, %29, 0, p, 1, 1, 1;\n}\n"
    : "+f"(d[0]),"+f"(d[1]),"+f"(d[2]),"+f"(d[3]),"+f"(d[4]),"+f"(d[5]),"+f"(d[6]),"+f"(d[7]),"+f"(d[8]),"+f"(d[9]),"+f"(d[10]),"+f"(d[11]),"+f"(d[12]),"+f"(d[13]),"+f"(d[14]),"+f"(d[15]),"+f"(d[16]),"+f"(d[17]),"+f"(d[18]),"+f"(d[19]),"+f"(d[20]),"+f"(d[21]),"+f"(d[22]),"+f"(d[23]) : "r"(a0), "r"(a1), "r"(a2), "r"(a3), "l"(db), "r"(meta), "n"(SC));
}
template<int SC> __device__ __forceinline__ void wg_ss192(float (&d)[96], uint64_t da, uint64_t db) {
  asm volatile("{\n.reg .pred p;\nsetp.ne.b32 p, %98, 0;\nwgmma.mma_async.sync.aligned.m64n192k16.f32.bf16.bf16 {%0,%1,%2,%3,%4,%5,%6,%7,%8,%9,%10,%11,%12,%13,%14,%15,%16,%17,%18,%19,%20,%21,%22,%23,%24,%25,%26,%27,%28,%29,%30,%31,%32,%33,%34,%35,%36,%37,%38,%39,%40,%41,%42,%43,%44,%45,%46,%47,%48,%49,%50,%51,%52,%53,%54,%55,%56,%57,%58,%59,%60,%61,%62,%63,%64,%65,%66,%67,%68,%69,%70,%71,%72,%73,%74,%75,%76,%77,%78,%79,%80,%81,%82,%83,%84,%85,%86,%87,%88,%89,%90,%91,%92,%93,%94,%95}, %96, %97, p, 1, 1, 0, 1;\n}\n"
    : "+f"(d[0]),"+f"(d[1]),"+f"(d[2]),"+f"(d[3]),"+f"(d[4]),"+f"(d[5]),"+f"(d[6]),"+f"(d[7]),"+f"(d[8]),"+f"(d[9]),"+f"(d[10]),"+f"(d[11]),"+f"(d[12]),"+f"(d[13]),"+f"(d[14]),"+f"(d[15]),"+f"(d[16]),"+f"(d[17]),"+f"(d[18]),"+f"(d[19]),"+f"(d[20]),"+f"(d[21]),"+f"(d[22]),"+f"(d[23]),"+f"(d[24]),"+f"(d[25]),"+f"(d[26]),"+f"(d[27]),"+f"(d[28]),"+f"(d[29]),"+f"(d[30]),"+f"(d[31]),"+f"(d[32]),"+f"(d[33]),"+f"(d[34]),"+f"(d[35]),"+f"(d[36]),"+f"(d[37]),"+f"(d[38]),"+f"(d[39]),"+f"(d[40]),"+f"(d[41]),"+f"(d[42]),"+f"(d[43]),"+f"(d[44]),"+f"(d[45]),"+f"(d[46]),"+f"(d[47]),"+f"(d[48]),"+f"(d[49]),"+f"(d[50]),"+f"(d[51]),"+f"(d[52]),"+f"(d[53]),"+f"(d[54]),"+f"(d[55]),"+f"(d[56]),"+f"(d[57]),"+f"(d[58]),"+f"(d[59]),"+f"(d[60]),"+f"(d[61]),"+f"(d[62]),"+f"(d[63]),"+f"(d[64]),"+f"(d[65]),"+f"(d[66]),"+f"(d[67]),"+f"(d[68]),"+f"(d[69]),"+f"(d[70]),"+f"(d[71]),"+f"(d[72]),"+f"(d[73]),"+f"(d[74]),"+f"(d[75]),"+f"(d[76]),"+f"(d[77]),"+f"(d[78]),"+f"(d[79]),"+f"(d[80]),"+f"(d[81]),"+f"(d[82]),"+f"(d[83]),"+f"(d[84]),"+f"(d[85]),"+f"(d[86]),"+f"(d[87]),"+f"(d[88]),"+f"(d[89]),"+f"(d[90]),"+f"(d[91]),"+f"(d[92]),"+f"(d[93]),"+f"(d[94]),"+f"(d[95]) : "l"(da), "l"(db), "n"(SC));
}

constexpr uint32_t SBC = 1024;
constexpr int ROWB = 2 * 224 * 384;
constexpr int TB = 12;
constexpr int KS = 832;
constexpr int KSLOT = 22 * KS;
constexpr int SM_X0 = 0;
constexpr int SM_X1 = 18432;
constexpr int SM_X2 = SM_X1 + 24576;
constexpr int SM_W = SM_X2 + 24576;
constexpr int SM_K = SM_W + 55296;
constexpr int SM_V = SM_K + 2 * KSLOT;
constexpr int SM_Q = SM_V + 22 * 1536;
constexpr int SM_O = SM_Q + 24576;
constexpr int SM_RPB = SM_O + 12288;
constexpr int SM_BAR = SM_RPB + 768;
constexpr int SM_A_TOTAL = SM_BAR + 256;
constexpr int SM_TWO = SM_X1;
constexpr int SM_TST = SM_TWO + 36864;
constexpr int SM_TIN = SM_W;
enum { B_FULL = 0, B_EMPTY = 3, B_TIN = 6, B_TFREE = 8, B_WK = 10, B_WQ, B_WO, B_QK0, B_QK1, B_KRDY, B_Q0, B_ODONE, B_VQRDY = B_ODONE + 2,
       B_PVISS, B_KFREE, B_VFREE, B_COUNT };

__device__ int g_flags[TB * 56];

#define TR(role, it, k)
#define TRB(it, k)
#define TR2(blk, k)

struct GemmCtx {
  uint32_t bar;
  uint32_t kC, vC, qC;
  uint32_t kH, vH;
  bool hvalid;
};

template <int STRIDE> __device__ __forceinline__ void dump12(uint32_t a, const uint32_t (&r)[12]) {
#pragma unroll
  for (int j = 0; j < 3; j++) stsm4(a + j * 2 * STRIDE, r[4 * j], r[4 * j + 1], r[4 * j + 2], r[4 * j + 3]);
}
template <int N> __device__ __forceinline__ void pack12(uint32_t (&r)[12], const float (&d)[N], int off) {
#pragma unroll
  for (int j = 0; j < 12; j++) r[j] = pack2(d[off + 2 * j], d[off + 2 * j + 1]);
}
template <int XS, int K0, int K1> __device__ __forceinline__ void issue_core(float (&d)[72]) {
  constexpr uint64_t da = mkdesc(SBC + XS, 16, 1024, 1), db = mkdesc(SBC + SM_W, 6144, 256, 3);
  wg_fence();
  if (K0 == 0) wg_ss144<0>(d, da, db);
#pragma unroll
  for (int k = K0 ? K0 : 1; k < K1; k++) wg_ss144<1>(d, da + (k >> 2) * 512 + (k & 3) * 2, db + k * 32);
  wg_commit();
}
template <int K0, int K1> __device__ __forceinline__ void issue_halo(float (&d)[48]) {
  constexpr uint64_t da = mkdesc(SBC + SM_X0, 16, 1024, 1), db = mkdesc(SBC + SM_W, 6144, 256, 3);
  wg_fence();
  if (K0 == 0) wg_ss96<0>(d, da, db);
#pragma unroll
  for (int k = K0 ? K0 : 1; k < K1; k++) wg_ss96<1>(d, da + (k >> 2) * 384 + (k & 3) * 2, db + k * 32);
  wg_commit();
}
template <int ST, int BYTES> __device__ __forceinline__ void release_stage(const GemmCtx& c, bool on) {
  asm volatile("{\n.reg .pred p, q;\n.reg .b32 ra;\nsetp.ne.b32 q, %2, 0;\nelect.sync _|p, 0xffffffff;\nand.pred p, p, q;\n"
               "mapa.shared::cluster.u32 ra, %1, %4;\n"
               "@p mbarrier.arrive.expect_tx.shared::cta.b64 _, [%0], %3;\n@p mbarrier.arrive.shared::cluster.b64 _, [ra];\n}"
               ::"r"(c.bar + (B_FULL + ST) * 8), "r"(c.bar + (B_EMPTY + ST) * 8), "r"((int)on), "n"(BYTES / 4), "n"(ST) : "memory");
}
__device__ __forceinline__ void load_w(const CUtensorMap* m, uint32_t dst, uint32_t bar, int col) {
  asm volatile("cp.async.bulk.tensor.2d.shared::cluster.global.mbarrier::complete_tx::bytes [%0], [%1, {%3,%4}], [%2];"
               ::"r"(dst), "l"(m), "r"(bar), "r"(col), "r"(0) : "memory");
}
__device__ __forceinline__ void publish(uint32_t bar) {
  fence_async();
  __syncwarp();
  mbar_arrive_elect(bar);
}

template <bool FIRST, bool LAST>
__device__ __forceinline__ void gemm_iter(const GemmCtx& c, int b, uint32_t (&pk)[12], uint32_t (&pv)[12], uint32_t (&pq)[12], int head) {
  const uint32_t bar = c.bar;
  const uint32_t pa = b & 1;
  const bool w = b >= 0;
  const uint32_t ko = pa * KSLOT, vx = pa * 16, qx = pa * 128;
  float H[48], C[72];
  uint32_t hk[12], hv[12], pv2[12];
  TR(2, b + 2, 0);
  mbar_wait(bar + (B_FULL + 0) * 8, pa);
  if (!LAST && !FIRST) mbar_wait(bar + (B_FULL + 2) * 8, pa);
  TR(2, b + 2, 1);
  if (w) mbar_wait(bar + B_QK1 * 8, pa);
  TR(2, b + 2, 2);
  issue_halo<0, 8>(H);
  TR(2, b + 2, 3);
  if (!FIRST) {
    if (w) mbar_wait(bar + B_KFREE * 8, pa);
    dump12<128>(c.kC + ko, pk);
  }
  issue_halo<8, 12>(H);
  TR(2, b + 2, 4);
  if (!LAST) {
    if (FIRST) { mbar_wait(bar + (B_FULL + 2) * 8, pa); mbar_wait(bar + B_WQ * 8, 0); }
    issue_core<SM_X2, 0, 8>(C);
    TR(2, b + 2, 5);
    if (!FIRST) dump12<256>(c.qC ^ (qx ^ 192), pq);
    wg_wait<1>(); pin(H);
    release_stage<0, 18432>(c, true);
  } else {
    dump12<256>(c.qC ^ (qx ^ 192), pq);
    wg_wait<0>(); pin(H);
    uint32_t ln; asm volatile("mov.u32 %0, %%laneid;" : "=r"(ln));
    if (ln < 4) mbar_arrive_remote(bar + (B_TFREE + (head >> 1)) * 8, ln);
  }
  pack12(hk, H, 0);
  if (c.hvalid) dump12<128>(c.kH + ko, hk);
  pack12(hv, H, 24);
  if (!LAST) issue_core<SM_X2, 8, 12>(C);
  if (!FIRST) publish(bar + (w ? B_VQRDY : B_Q0) * 8);
  if (!LAST) {
    mbar_wait(bar + (B_FULL + 1) * 8, pa);
    TR(2, b + 2, 6);
    wg_wait<0>(); pin(C);
    TR(2, b + 2, 7);
    pack12(pk, C, 0);
    dump12<128>(c.kC + ko + 64, pk);
    release_stage<2, 24576>(c, b < 11);
    pack12(pv2, C, 24);
    pack12(pq, C, 48);
    if (w) mbar_wait(bar + B_PVISS * 8, pa);
    TR(2, b + 2, 8);
    issue_core<SM_X1, 0, 8>(C);
    TR(2, b + 2, 9);
    if (!FIRST) publish(bar + B_KRDY * 8);
  } else mbar_arrive_elect(bar + B_KRDY * 8);
  TR(2, b + 2, 10);
  if (w) mbar_wait(bar + B_VFREE * 8, pa);
  if (!FIRST) dump12<128>(c.vC ^ vx, pv);
  if (!LAST) dump12<256>(c.qC ^ qx, pq);
  if (c.hvalid) dump12<128>(c.vH ^ vx, hv);
  if (LAST) { publish(bar + B_VQRDY * 8); return; }
  issue_core<SM_X1, 8, 12>(C);
  dump12<128>((c.vC ^ vx ^ 16) + 768, pv2);
  TR(2, b + 2, 11);
  wg_wait<0>(); pin(C);
  TR(2, b + 2, 12);
  release_stage<1, 24576>(c, b < 11);
  pack12(pk, C, 0);
  pack12(pv, C, 24);
  pack12(pq, C, 48);
}

__device__ __forceinline__ float fold(float a, float b, float t, int useb) {
  float r;
  asm("{\n.reg .pred p;\nsetp.ne.b32 p, %4, 0;\nfma.rn.f32 %0, %1, 0f3E553B95, %3;\n@p fma.rn.f32 %0, %2, 0f3E553B95, %3;\n}"
      : "=&f"(r) : "f"(a), "f"(b), "f"(t), "r"(useb));
  return r;
}
template <int U, int L, bool BORDER>
__device__ __forceinline__ void softmax_tile(const float (&SA)[56], const float (&SB)[56], const float (&T)[14], int b0, int b1,
                                             uint32_t ra0, uint32_t ra1, int qcu, uint32_t (&P)[28], float& sumU, float& sumL) {
  float lu[14], ll[14];
#pragma unroll
  for (int j = 0; j < 7; j++) {
    float tu0, tu1, tl0, tl1;
    if (BORDER) {
      tu0 = lds_f32(ra0 + (U + j + 3 - qcu) * 4); tu1 = lds_f32(ra1 + (U + j + 3 - qcu) * 4);
      tl0 = lds_f32(ra0 + (L + j + 2 - qcu) * 4); tl1 = lds_f32(ra1 + (L + j + 2 - qcu) * 4);
    } else { tu0 = tl0 = T[2 * j]; tu1 = tl1 = T[2 * j + 1]; }
    lu[2 * j]     = fold(SA[4 * (U + j)],     SB[4 * (U + j)],     tu0, b0);
    ll[2 * j]     = fold(SA[4 * (L + j) + 2], SB[4 * (L + j) + 2], tl0, b0);
    lu[2 * j + 1] = fold(SA[4 * (U + j) + 1], SB[4 * (U + j) + 1], tu1, b1);
    ll[2 * j + 1] = fold(SA[4 * (L + j) + 3], SB[4 * (L + j) + 3], tl1, b1);
  }
  float mu = lu[0], ml = ll[0], mu2 = lu[1], ml2 = ll[1];
#pragma unroll
  for (int j = 1; j < 7; j++) { mu = fmaxf(mu, lu[2 * j]); mu2 = fmaxf(mu2, lu[2 * j + 1]); ml = fmaxf(ml, ll[2 * j]); ml2 = fmaxf(ml2, ll[2 * j + 1]); }
  mu = fmaxf(mu, mu2); ml = fmaxf(ml, ml2);
  mu = fmaxf(mu, __shfl_xor_sync(0xffffffffu, mu, 1)); ml = fmaxf(ml, __shfl_xor_sync(0xffffffffu, ml, 1));
  mu = fmaxf(mu, __shfl_xor_sync(0xffffffffu, mu, 2)); ml = fmaxf(ml, __shfl_xor_sync(0xffffffffu, ml, 2));
  float su = 0.f, sl = 0.f;
#pragma unroll
  for (int c = 0; c < 14; c++) {
    const int iu = (c >> 1) * 4 + (c & 1) * 2;
    if (c >= U && c < U + 7) {
      float e0 = ex2(lu[2 * (c - U)] - mu), e1 = ex2(lu[2 * (c - U) + 1] - mu);
      su = c == U ? e0 + e1 : (su + e0) + e1; P[iu] = pack2(e0, e1);
    } else P[iu] = 0u;
    if (c >= L && c < L + 7) {
      float e0 = ex2(ll[2 * (c - L)] - ml), e1 = ex2(ll[2 * (c - L) + 1] - ml);
      sl = c == L ? e0 + e1 : (sl + e0) + e1; P[iu + 1] = pack2(e0, e1);
    } else P[iu + 1] = 0u;
  }
  sumU = su; sumL = sl;
}

struct Maps { CUtensorMap xc, xh, w, os, wo, ot; };

__global__ void __cluster_dims__(4, 1, 1) __launch_bounds__(512, 1)
na_attn_kernel(const __grid_constant__ Maps mp, const __nv_bfloat16* __restrict__ wqkv, const __nv_bfloat16* __restrict__ rpb) {
  extern __shared__ __align__(1024) uint8_t smem_raw[];
  const uint32_t sb = smem_u32(smem_raw);
  if ((sb & 0x3FFFF) != SBC) return;
  const uint32_t bar = sb + SM_BAR;
  TR(3, 0, threadIdx.x >> 7);
  TR2(blockIdx.x, 0);
  const int tid = threadIdx.x, lane = tid & 31;
  const int warp = __shfl_sync(0xffffffffu, tid >> 5, 0);
  const int head = blockIdx.x & 3, cl = blockIdx.x >> 2;
  const int par = cl / 7, strip = cl - par * 7, ph = par >> 1, pw = par & 1;

  uint4 wv[3];
  const int wr = tid / 6, wc = tid - wr * 6;
  if (warp < 12) {
#pragma unroll
    for (int i = 0; i < 3; i++) wv[i] = __ldg(reinterpret_cast<const uint4*>(wqkv + (wr + i * 64) * 576 + 384 + head * 48 + wc * 8));
  } else if (elect_one()) {
    if (warp == 12) {
      mbar_init(bar + B_WK * 8, 1);
#pragma unroll
      for (int i = 0; i < 3; i++) load_w(&mp.w, sb + SM_W + i * 6144, bar + B_WK * 8, 192 + head * 48 + i * 16);
      mbar_expect(bar + B_WK * 8, 18432);
    } else if (warp == 13) {
#pragma unroll
      for (int i = 0; i < B_WK; i++) mbar_init(bar + i * 8, i < B_EMPTY ? 4 : (i < B_TIN ? 16 : (i < B_TFREE ? 1 : 8)));
    } else if (warp == 14) {
#pragma unroll
      for (int i = B_WQ; i < B_COUNT; i++) mbar_init(bar + i * 8, i < B_QK0 ? 1 : (i < B_VQRDY ? 4 : (i == B_VQRDY ? 6 : 8)));
    }
    asm volatile("fence.mbarrier_init.release.cluster;" ::: "memory");
  }
  __syncwarp();
  asm volatile("barrier.cluster.arrive.relaxed.aligned;" ::: "memory");
  TR(3, 2, threadIdx.x >> 7);

  if (warp >= 12) {
    asm volatile("setmaxnreg.dec.sync.aligned.u32 24;");
    asm volatile("griddepcontrol.launch_dependents;");
    const int cc = ph * 112 + (head ? strip * 16 : (strip == 0 ? 16 : (strip == 6 ? 74 : strip * 16 - 3)));
    const int sd = strip == 0 ? -1 : (strip == 6 ? 1 : 0);
    const int r0 = head == 0 ? -4 : (head == 1 ? 4 : 0);
    asm volatile("barrier.cluster.wait.aligned;" ::: "memory");
    TR(3, 2, 4);
    if (warp == 12) {
      const uint32_t fb = bar + (B_FULL + head) * 8, eb = bar + (B_EMPTY + head) * 8;
      const uint32_t dst = sb + (head == 0 ? SM_X0 : (head == 1 ? SM_X1 : SM_X2));
      const int nl = head == 0 ? 15 : (head == 3 ? 1 : 14);
#pragma unroll 1
      for (int n = 0; n < nl; n++) {
        if (n) mbar_wait(eb, (n - 1) & 1);
        if (elect_one()) {
          if (head == 0) {
            asm volatile("cp.async.bulk.tensor.5d.shared::cluster.global.mbarrier::complete_tx::bytes.multicast::cluster [%0], [%1, {%3,%4,%5,%6,%7}], [%2], %8;"
                         ::"r"(dst), "l"(&mp.xh), "r"(fb), "r"(0), "r"(8 * n + r0), "r"(cc), "r"(sd), "r"(pw * 3), "h"((uint16_t)15) : "memory");
            if (n + 1 < nl) asm volatile("cp.async.bulk.prefetch.tensor.5d.L2.global [%0, {%1,%2,%3,%4,%5}];" ::"l"(&mp.xh), "r"(0), "r"(8 * n + 8 + r0), "r"(cc), "r"(sd), "r"(pw * 3) : "memory");
          } else if (head < 3) {
            asm volatile("cp.async.bulk.tensor.4d.shared::cluster.global.mbarrier::complete_tx::bytes.multicast::cluster [%0], [%1, {%3,%4,%5,%6}], [%2], %7;"
                         ::"r"(dst), "l"(&mp.xc), "r"(fb), "r"(0), "r"(8 * n + r0), "r"(cc), "r"(pw * 3), "h"((uint16_t)15) : "memory");
          }
          if (n == 0) {
#pragma unroll
            for (int i = 0; i < 3; i++) load_w(&mp.w, sb + SM_W + (6 + i) * 6144, bar + B_WQ * 8, head * 48 + i * 16);
            mbar_expect(bar + B_WQ * 8, 18432);
            mbar_expect(bar + B_TIN * 8, 24576); mbar_expect(bar + (B_TIN + 1) * 8, 24576);
          }
          if (head && n + 1 < nl) asm volatile("cp.async.bulk.prefetch.tensor.4d.L2.global [%0, {%1,%2,%3,%4}];" ::"l"(&mp.xc), "r"(0), "r"(8 * n + 8 + r0), "r"(cc), "r"(pw * 3) : "memory");
        }
        __syncwarp();
      }
    }
    if (warp >= 14) {
      const int j = warp - 14;
      int* flag = g_flags + cl * 2 + j;
      mbar_arrive_elect(bar + B_VQRDY * 8);
#pragma unroll 1
      for (int b = 0; b < TB; b++) {
        mbar_wait(bar + (B_ODONE + j) * 8, b & 1);
        if (lane == 0) {
          asm volatile("cp.async.bulk.tensor.3d.global.shared::cta.bulk_group [%0, {%2,%3,%4}], [%1];"
                       ::"l"(&mp.os), "r"(sb + SM_O + j * 6144), "r"(pw * 192), "r"(8 * b + 2 * head), "r"(ph * 112 + strip * 16 + 8 * j) : "memory");
          asm volatile("cp.async.bulk.commit_group;\ncp.async.bulk.wait_group.read 0;" ::: "memory");
          mbar_arrive(bar + B_VQRDY * 8);
          asm volatile("cp.async.bulk.wait_group 0;\nfence.proxy.async.global;\nred.release.gpu.global.add.s32 [%0], 1;" ::"l"(flag + b * 56) : "memory");
        }
        __syncwarp();
      }
#pragma unroll 1
      for (int i = 0; i < 2; i++) {
        mbar_wait(bar + (B_ODONE + j) * 8, i);
        if (i == 0) { mbar_arrive_elect(bar + B_VQRDY * 8); mbar_wait(bar + (B_TFREE + j) * 8, 0); }
        if (elect_one()) {
#pragma unroll
          for (int d = 0; d < 2; d++)
            asm volatile("{\n.reg .b32 rd, rb;\nmapa.shared::cluster.u32 rd, %0, %3;\nmapa.shared::cluster.u32 rb, %2, %3;\n"
                         "cp.async.bulk.shared::cluster.shared::cta.mbarrier::complete_tx::bytes [rd], [%1], 6144, [rb];\n}"
                         ::"r"(sb + SM_TIN + i * 24576 + head * 6144), "r"(sb + (i ? SM_Q + j * 12288 : SM_O + j * 6144)), "r"(bar + (B_TIN + i) * 8), "r"(2 * j + d) : "memory");
        }
        __syncwarp();
      }
    }
    cluster_sync();
  } else if (warp >= 8) {
    asm volatile("setmaxnreg.inc.sync.aligned.u32 184;");
    GemmCtx c;
    c.bar = bar;
    const int gw = warp - 8, tk = gw * 16 + (lane & 15), hi = lane >> 4;
    { const int col = tk >> 2, i = tk & 3;
      c.kC = sb + SM_K + (col + 3) * KS + hi * 128 + i * 16;
      c.vC = sb + SM_V + (col + 3) * 1536 + hi * 128 + (2 * i + ((col + 3) & 1)) * 16;
      c.qC = sb + SM_Q + col * 1536 + hi * 256 + (col & 1) * 64 + i * 16; }
    { const int ci = tk >> 3, kc = ci < 3 ? ci : ci + 16, i = tk & 7; c.hvalid = gw < 3;
      c.kH = sb + SM_K + kc * KS + hi * 128 + i * 16;
      c.vH = sb + SM_V + kc * 1536 + hi * 128 + (i >> 2) * 768 + (2 * (i & 3) + ((kc ^ (i >> 2)) & 1)) * 16; }
    asm volatile("barrier.cluster.wait.aligned;" ::: "memory");
    TR(3, 1, 1);
    if (elect_one()) { mbar_expect(bar + B_FULL * 8, 4608); mbar_expect(bar + (B_FULL + 1) * 8, 6144); mbar_expect(bar + (B_FULL + 2) * 8, 6144); }
    __syncwarp();
#pragma unroll
    for (int i = 0; i < 3; i++) sts128(sb + SM_W + (3 + (wc >> 1)) * 6144 + (wr + i * 64) * 32 + ((wc ^ (wr >> 2)) & 1) * 16, wv[i]);
    fence_async();
    TR(3, 1, 2);
    asm volatile("bar.sync 1, 384;" ::: "memory");
    TR(3, 1, 3);
    mbar_wait(bar + B_WK * 8, 0);
    TR(3, 1, 0);
    uint32_t pk[12], pv[12], pq[12];
    gemm_iter<true, false>(c, -2, pk, pv, pq, head);
#pragma unroll 1
    for (int b = -1; b < 12; b++) gemm_iter<false, false>(c, b, pk, pv, pq, head);
    asm volatile("bar.sync 2, 128;" ::: "memory");
    if (gw == 0 && elect_one()) {
      mbar_expect(bar + B_WO * 8, 36864);
      asm volatile("cp.async.bulk.tensor.3d.shared::cluster.global.mbarrier::complete_tx::bytes [%0], [%1, {%3,%4,%5}], [%2];"
                   ::"r"(sb + SM_TWO), "l"(&mp.wo), "r"(bar + B_WO * 8), "r"(0), "r"(0), "r"((head & 1) * 3) : "memory");
    }
    __syncwarp();
    gemm_iter<false, true>(c, 12, pk, pv, pq, head);
    mbar_wait(bar + B_WO * 8, 0);
    mbar_wait(bar + B_QK1 * 8, 1);
    const uint32_t st = sb + SM_TST + gw * 3072;
    const uint32_t sta = st + (lane & 15) * 64 + ((hi ^ ((lane >> 1) & 3)) * 16);
#pragma unroll 1
    for (int i = 0; i < 2; i++) {
      constexpr uint64_t db = mkdesc(SBC + SM_TWO, 12288, 512, 2);
      const uint64_t da = mkdesc(SBC + SM_TIN, 128, 768, 0) + i * (24576 / 16);
      float D[48];
      mbar_wait(bar + (B_TIN + i) * 8, 0);
      TR(2, 15, 3 * i);
      wg_fence();
      wg_ss96<0>(D, da, db);
#pragma unroll
      for (int k = 1; k < 12; k++) wg_ss96<1>(D, da + (k / 3) * 384 + (k % 3) * 16, db + k * 64);
      wg_commit();
      if (lane == 0) asm volatile("cp.async.bulk.wait_group.read 0;" ::: "memory");
      __syncwarp();
      wg_wait<0>(); pin(D);
      TR(2, 15, 3 * i + 1);
#pragma unroll
      for (int q = 0; q < 6; q++)
        stsm4((sta ^ ((q & 1) * 32)) + (q >> 1) * 1024,
              pack2(D[8 * q], D[8 * q + 1]), pack2(D[8 * q + 2], D[8 * q + 3]), pack2(D[8 * q + 4], D[8 * q + 5]), pack2(D[8 * q + 6], D[8 * q + 7]));
      fence_async();
      __syncwarp();
      if (lane == 0) {
        asm volatile("cp.async.bulk.tensor.4d.global.shared::cta.bulk_group [%0, {%2,%3,%4,%5}], [%1];"
                     ::"l"(&mp.ot), "r"(st), "r"(0), "r"(8 * (TB + i)), "r"(ph * 112 + strip * 16 + 8 * (head >> 1) + 2 * gw), "r"(pw * 6 + (head & 1) * 3) : "memory");
        asm volatile("cp.async.bulk.commit_group;" ::: "memory");
      }
      TR(2, 15, 3 * i + 2);
    }
    asm volatile("barrier.cluster.arrive.relaxed.aligned;" ::: "memory");
    if (lane == 0) asm volatile("cp.async.bulk.wait_group 0;" ::: "memory");
    __syncwarp();
    TR(2, 15, 6);
    asm volatile("barrier.cluster.wait.aligned;" ::: "memory");
  } else {
    asm volatile("setmaxnreg.inc.sync.aligned.u32 152;");
    float rv = -INFINITY;
    if (tid < 169) rv = __bfloat162float(rpb[head * 169 + tid]) * 1.4426950408889634f;
    if (tid < 192) {
      const int kc = (wr & 15) + 3;
      sts128(tid < 96 ? sb + SM_K + kc * KS + wc * 128 + 48 : sb + SM_V + kc * 1536 + wc * 128 + (6 + (kc & 1)) * 16, make_uint4(0, 0, 0, 0));
    }
#pragma unroll
    for (int i = 0; i < 3; i++) sts128(sb + SM_W + (3 + (wc >> 1)) * 6144 + (wr + i * 64) * 32 + ((wc ^ (wr >> 2)) & 1) * 16, wv[i]);
    fence_async();
    asm volatile("bar.arrive 1, 384;" ::: "memory");
    if (tid < 182) asm volatile("st.shared.f32 [%0], %1;" ::"r"(sb + SM_RPB + tid * 4), "f"(rv) : "memory");
    const int j = warp >> 2, w = warp & 3;
    int variant = w;
    if (strip == 0 && j == 0 && w < 2) variant = 4;
    if (strip == 6 && j == 1 && w >= 2) variant = 5;
    const uint32_t qa = sb + SM_Q + (8 * j + 2 * w + ((lane >> 3) & 1)) * 1536 + (lane >> 4) * 256 + (((lane & 7) * 16) ^ (((lane >> 3) & 1) * 64));
    uint32_t oa = sb + SM_O + j * 6144 + (2 * w + ((lane >> 3) & 1)) * 768 + (lane >> 4) * 128 + (lane & 7) * 16;
    const uint64_t dK = mkdesc(SBC + SM_K, 128, KS, 0) + j * (8 * KS / 16);
    const uint64_t dV = mkdesc(SBC + SM_V, 768, 128, 0) + j * (8 * 1536 / 16);
    asm volatile("barrier.cluster.wait.aligned;" ::: "memory");
    asm volatile("bar.sync 3, 256;" ::: "memory");
    float T[14];
    int b0 = 0, b1 = 0;
    uint32_t ra0 = 0, ra1 = 0, meta = 0;
    uint32_t q[12];
    mbar_wait(bar + B_Q0 * 8, 0);
#pragma unroll
    for (int k = 0; k < 3; k++) ldsm4(qa + k * 512, q[4 * k], q[4 * k + 1], q[4 * k + 2], q[4 * k + 3]);
#pragma unroll 1
    for (int b = 0; b < 14; b++) {
      const uint32_t pa = b & 1;
      if (b <= 1 || b == 13) {
        uint32_t ln; asm volatile("mov.u32 %0, %%laneid;" : "=r"(ln));
        const int g = ln >> 2, t = ln & 3;
        const int sw = b == 0 ? max(g + 1, 4) : (b == 13 ? min(g + 1, 5) : g + 1);
        const int i0 = 2 * t, i1 = 2 * t + 1;
        b0 = i0 <= sw - 2; b1 = i1 <= sw - 2;
        const int m = sw - 1;
        ra0 = sb + SM_RPB + (i0 == m ? 13 : i0 + (b0 ? 8 : 0) - g + 2) * 52;
        ra1 = sb + SM_RPB + (i1 == m ? 13 : i1 + (b1 ? 8 : 0) - g + 2) * 52;
#pragma unroll
        for (int jj = 0; jj < 7; jj++) { T[2 * jj] = lds_f32(ra0 + (jj + 3) * 4); T[2 * jj + 1] = lds_f32(ra1 + (jj + 3) * 4); }
        uint32_t m16 = 0x8888u;
#pragma unroll
        for (int i = 0; i < 8; i++) m16 |= (uint32_t)(((i <= sw - 2) ^ (i >> 2) ^ t ^ b) & 1) << (2 * i);
        meta = m16 | (m16 << 16);
        if (b == 13) oa += SM_Q - SM_O + j * 6144;
      } else meta ^= 0x55555555u;
      float SA[56], SB[56];
      const uint64_t dA = dK + pa * (KSLOT >> 4), dB = dK + (pa ^ 1) * (KSLOT >> 4);
      TR(j, b, 0);
      mbar_wait(bar + (j ? B_QK0 : B_KRDY) * 8, pa);
      TR(j, b, 1);
      wg_fence();
      wg_rs112<0>(SA, q[0], q[1], q[2], q[3], dA);
      wg_rs112<0>(SB, q[0], q[1], q[2], q[3], dB);
      wg_rs112<1>(SA, q[4], q[5], q[6], q[7], dA + 16);
      wg_rs112<1>(SB, q[4], q[5], q[6], q[7], dB + 16);
      wg_rs112<1>(SA, q[8], q[9], q[10], q[11], dA + 32);
      wg_rs112<1>(SB, q[8], q[9], q[10], q[11], dB + 32);
      wg_commit();
      mbar_arrive_elect(bar + (B_QK0 + j) * 8);
      TR(j, b, 2);
      wg_wait<0>(); pin(SA); pin(SB);
      mbar_arrive_elect(bar + B_KFREE * 8);
      TR(j, b, 3);
      uint32_t P[28];
      float su, sl;
      switch (variant) {
        case 0: softmax_tile<0, 1, false>(SA, SB, T, b0, b1, ra0, ra1, 0, P, su, sl); break;
        case 1: softmax_tile<2, 3, false>(SA, SB, T, b0, b1, ra0, ra1, 0, P, su, sl); break;
        case 2: softmax_tile<4, 5, false>(SA, SB, T, b0, b1, ra0, ra1, 0, P, su, sl); break;
        case 3: softmax_tile<6, 7, false>(SA, SB, T, b0, b1, ra0, ra1, 0, P, su, sl); break;
        case 4: softmax_tile<3, 3, true>(SA, SB, T, b0, b1, ra0, ra1, 2 * w, P, su, sl); break;
        default: softmax_tile<4, 4, true>(SA, SB, T, b0, b1, ra0, ra1, 2 * w, P, su, sl); break;
      }
      float O[24];
      TR(j, b, 4);
      su += __shfl_xor_sync(0xffffffffu, su, 1); sl += __shfl_xor_sync(0xffffffffu, sl, 1);
      mbar_wait(bar + B_VQRDY * 8, pa);
      TR(j, b, 5);
      su += __shfl_xor_sync(0xffffffffu, su, 2); sl += __shfl_xor_sync(0xffffffffu, sl, 2);
      if (b < 13) {
#pragma unroll
        for (int k = 0; k < 3; k++) ldsm4(qa + (pa ^ 1) * 128 + k * 512, q[4 * k], q[4 * k + 1], q[4 * k + 2], q[4 * k + 3]);
      }
      wg_fence();
      wg_sp48<0>(O, P[0], P[1], P[2], P[3], dV, meta);
#pragma unroll
      for (int s = 1; s < 7; s++) wg_sp48<1>(O, P[4 * s], P[4 * s + 1], P[4 * s + 2], P[4 * s + 3], dV + s * 192, meta);
      wg_commit();
      mbar_arrive_elect(bar + B_PVISS * 8);
      TR(j, b, 6);
      const float ru = __fdividef(1.f, su), rl = __fdividef(1.f, sl);
      wg_wait<0>(); pin(O);
      mbar_arrive_elect(bar + B_VFREE * 8);
      TR(j, b, 7);
#pragma unroll
      for (int i = 0; i < 3; i++)
        stsm4(oa + i * 256, pack2(O[8 * i] * ru, O[8 * i + 1] * ru), pack2(O[8 * i + 2] * rl, O[8 * i + 3] * rl),
              pack2(O[8 * i + 4] * ru, O[8 * i + 5] * ru), pack2(O[8 * i + 6] * rl, O[8 * i + 7] * rl));
      publish(bar + (B_ODONE + j) * 8);
      TR(j, b, 8);
    }
    TR2(blockIdx.x, 2);
    cluster_sync();
  }
}

constexpr int NSTB = 4;
constexpr int NTB = TB * 56;
constexpr int SM_B_ST = 0;
constexpr int SM_B_IN = 49152;
constexpr int SM_B_W = SM_B_IN + NSTB * 24576;
constexpr int SM_B_BAR = SM_B_W + 73728;
constexpr int SM_B_TOTAL = SM_B_BAR + 128;
struct MapsB { CUtensorMap oi, oo, wo; };

__global__ void __launch_bounds__(288, 1)
na_proj_kernel(const __grid_constant__ MapsB mp) {
  extern __shared__ __align__(1024) uint8_t smem_raw[];
  const uint32_t sb = smem_u32(smem_raw);
  if ((sb & 0x3FFFF) != SBC) return;
  const uint32_t bar = sb + SM_B_BAR;
  const int tid = threadIdx.x, lane = tid & 31;
  const int warp = __shfl_sync(0xffffffffu, tid >> 5, 0);
  TR2(132 + blockIdx.x, 0);
  TRB(47, 0);
  if (warp == 8 && elect_one()) {
#pragma unroll
    for (int i = 0; i <= 2 * NSTB; i++) mbar_init(bar + i * 8, i < NSTB || i == 2 * NSTB ? 1 : 4);
    mbar_expect(bar + 2 * NSTB * 8, 73728);
#pragma unroll
    for (int i = 0; i < 2; i++)
      asm volatile("cp.async.bulk.tensor.3d.shared::cluster.global.mbarrier::complete_tx::bytes [%0], [%1, {%3,%4,%5}], [%2];"
                   ::"r"(sb + SM_B_W + i * 36864), "l"(&mp.wo), "r"(bar + 2 * NSTB * 8), "r"(0), "r"(0), "r"(i * 3) : "memory");
  }
  __syncthreads();
  const int step = gridDim.x;
  if (warp == 8) {
    int it = 0;
    uint32_t spin = 0;
#pragma unroll 1
    for (int n = blockIdx.x; n < NTB && spin < SPIN_LIMIT; spin++) {
      int v = 0;
      const int mine = n + lane * step;
      if (lane < 8 && mine < NTB) asm volatile("ld.acquire.gpu.global.s32 %0, [%1];" : "=r"(v) : "l"(g_flags + mine) : "memory");
      int cnt = __ffs(~__ballot_sync(0xffffffffu, v >= 4)) - 1;
      asm volatile("fence.proxy.async.global;" ::: "memory");
      __syncwarp();
#pragma unroll 1
      for (; cnt > 0; cnt--, n += step, it++) {
        TRB(it, 0);
        const int b = n / 56, rem = n - b * 56, par = rem / 14;
        const int st = it & (NSTB - 1), use = it / NSTB;
        if (use) mbar_wait(bar + (NSTB + st) * 8, (use - 1) & 1);
        if (elect_one()) {
          mbar_expect(bar + st * 8, 24576);
          asm volatile("cp.async.bulk.tensor.3d.shared::cluster.global.mbarrier::complete_tx::bytes [%0], [%1, {%3,%4,%5}], [%2];"
                       ::"r"(sb + SM_B_IN + st * 24576), "l"(&mp.oi), "r"(bar + st * 8), "r"((par & 1) * 192), "r"(8 * b), "r"((par >> 1) * 112 + (rem - par * 14) * 8) : "memory");
        }
        __syncwarp();
        TRB(it, 2);
      }
    }
    for (int n = blockIdx.x + lane * step; n < NTB; n += 32 * step) g_flags[n] = 0;
  } else {
    const int wg = warp >> 2, w = warp & 3;
    constexpr uint64_t db = mkdesc(SBC + SM_B_W, 12288, 512, 2);
    const uint32_t st = sb + SM_B_ST + warp * 6144;
    const uint32_t sta = st + (lane & 15) * 128 + (((lane >> 4) ^ (lane & 7)) * 16);
    mbar_wait(bar + 2 * NSTB * 8, 0);
    TRB(47, 1);
    int it = wg;
#pragma unroll 1
    for (int n = blockIdx.x + wg * step; n < NTB; n += 2 * step, it += 2) {
      const int b = n / 56, rem = n - b * 56, par = rem / 14, sg = it & (NSTB - 1);
      const uint64_t da = mkdesc(SBC + SM_B_IN, 128, 3072, 0) + sg * (24576 / 16);
      float D[96];
      mbar_wait(bar + sg * 8, (it / NSTB) & 1);
      TRB(it, 3);
      wg_fence();
      wg_ss192<0>(D, da, db);
#pragma unroll
      for (int k = 1; k < 12; k++) wg_ss192<1>(D, da + k * 16, db + k * 64);
      wg_commit();
      TRB(it, 4);
      if (lane == 0) asm volatile("cp.async.bulk.wait_group.read 0;" ::: "memory");
      __syncwarp();
      wg_wait<0>(); pin(D);
      mbar_arrive_elect(bar + (NSTB + sg) * 8);
      TRB(it, 5);
#pragma unroll
      for (int q = 0; q < 12; q++)
        stsm4((sta ^ ((q & 3) * 32)) + (q >> 2) * 2048,
              pack2(D[8 * q], D[8 * q + 1]), pack2(D[8 * q + 2], D[8 * q + 3]), pack2(D[8 * q + 4], D[8 * q + 5]), pack2(D[8 * q + 6], D[8 * q + 7]));
      fence_async();
      __syncwarp();
      if (lane == 0) {
        asm volatile("cp.async.bulk.tensor.4d.global.shared::cta.bulk_group [%0, {%2,%3,%4,%5}], [%1];"
                     ::"l"(&mp.oo), "r"(st), "r"(0), "r"(8 * b), "r"((par >> 1) * 112 + (rem - par * 14) * 8 + 2 * w), "r"((par & 1) * 3) : "memory");
        asm volatile("cp.async.bulk.commit_group;" ::: "memory");
      }
      TRB(it, 6);
    }
    if (lane == 0) asm volatile("cp.async.bulk.wait_group 0;" ::: "memory");
    TR2(132 + blockIdx.x, 2);
  }
}

typedef CUresult (*EncodeFn)(CUtensorMap*, CUtensorMapDataType, cuuint32_t, void*, const cuuint64_t*, const cuuint64_t*, const cuuint32_t*,
                             const cuuint32_t*, CUtensorMapInterleave, CUtensorMapSwizzle, CUtensorMapL2promotion, CUtensorMapFloatOOBfill);
static EncodeFn g_enc = nullptr;
static void make_map(CUtensorMap* m, const void* p, int rank, const cuuint64_t* dim, const cuuint64_t* str, const cuuint32_t* box, CUtensorMapSwizzle sw) {
  const cuuint32_t ones[5] = {1, 1, 1, 1, 1};
  g_enc(m, CU_TENSOR_MAP_DATA_TYPE_BFLOAT16, rank, (void*)p, dim, str, box, ones, CU_TENSOR_MAP_INTERLEAVE_NONE, sw,
        CU_TENSOR_MAP_L2_PROMOTION_L2_128B, CU_TENSOR_MAP_FLOAT_OOB_FILL_NONE);
}

extern "C" void kernel_launch(void* const* d_in, const int* in_sizes, int n_in, void* d_out, int out_size) {
  const __nv_bfloat16* x = (const __nv_bfloat16*)d_in[0];
  const __nv_bfloat16* wqkv = (const __nv_bfloat16*)d_in[1];
  const __nv_bfloat16* wo = (const __nv_bfloat16*)d_in[2];
  const __nv_bfloat16* rpb = (const __nv_bfloat16*)d_in[3];

  if (!g_enc) {
    void* fn = nullptr; cudaDriverEntryPointQueryResult qr;
    cudaGetDriverEntryPoint("cuTensorMapEncodeTiled", &fn, cudaEnableDefault, &qr);
    g_enc = (EncodeFn)fn;
    cudaFuncSetAttribute(na_attn_kernel, cudaFuncAttributeMaxDynamicSharedMemorySize, SM_A_TOTAL);
    cudaFuncSetAttribute(na_proj_kernel, cudaFuncAttributeMaxDynamicSharedMemorySize, SM_B_TOTAL);
  }
  Maps ma; MapsB mb;
  { cuuint64_t dim[4] = {64, 112, 224, 6}, str[3] = {(cuuint64_t)ROWB, 768, 128};
    cuuint32_t box[4] = {64, 4, 16, 3}, boxo[4] = {64, 8, 2, 3};
    make_map(&ma.xc, x, 4, dim, str, box, CU_TENSOR_MAP_SWIZZLE_128B);
    make_map(&mb.oo, d_out, 4, dim, str, boxo, CU_TENSOR_MAP_SWIZZLE_128B); }
  { cuuint64_t dim[5] = {64, 112, 224, 2, 6}, str[4] = {(cuuint64_t)ROWB, 768, 19 * 768, 128};
    cuuint32_t box[5] = {64, 8, 3, 2, 3};
    make_map(&ma.xh, x, 5, dim, str, box, CU_TENSOR_MAP_SWIZZLE_128B); }
  { cuuint64_t dim[3] = {384, 112, 224}, str[2] = {(cuuint64_t)ROWB, 768};
    cuuint32_t box[3] = {192, 8, 8}, boxs[3] = {192, 2, 8};
    make_map(&mb.oi, d_out, 3, dim, str, box, CU_TENSOR_MAP_SWIZZLE_NONE);
    make_map(&ma.os, d_out, 3, dim, str, boxs, CU_TENSOR_MAP_SWIZZLE_NONE); }
  { cuuint64_t dim[4] = {32, 112, 224, 12}, str[3] = {(cuuint64_t)ROWB, 768, 64};
    cuuint32_t box[4] = {32, 8, 2, 3};
    make_map(&ma.ot, d_out, 4, dim, str, box, CU_TENSOR_MAP_SWIZZLE_64B); }
  { cuuint64_t dim[2] = {576, 192}, str[1] = {1152};
    cuuint32_t box[2] = {16, 192};
    make_map(&ma.w, wqkv, 2, dim, str, box, CU_TENSOR_MAP_SWIZZLE_32B); }
  { cuuint64_t dim[3] = {32, 192, 6}, str[2] = {384, 64};
    cuuint32_t box[3] = {32, 192, 3};
    make_map(&ma.wo, wo, 3, dim, str, box, CU_TENSOR_MAP_SWIZZLE_64B);
    mb.wo = ma.wo; }
  na_attn_kernel<<<112, 512, SM_A_TOTAL>>>(ma, wqkv, rpb);
  cudaLaunchConfig_t cfg = {};
  cfg.gridDim = dim3(20); cfg.blockDim = dim3(288); cfg.dynamicSmemBytes = SM_B_TOTAL; cfg.stream = cudaStreamPerThread;
  cudaLaunchAttribute at[1];
  at[0].id = cudaLaunchAttributeProgrammaticStreamSerialization; at[0].val.programmaticStreamSerializationAllowed = 1;
  cfg.attrs = at; cfg.numAttrs = 1;
  cudaLaunchKernelEx(&cfg, na_proj_kernel, mb);
}
```

```cpp
#include <cuda_runtime.h>
#include <cuda_bf16.h>
#include <cuda.h>
#include <stdint.h>

#define SPIN_LIMIT (1u << 18)

__device__ __forceinline__ uint32_t smem_u32(const void* p) { return (uint32_t)__cvta_generic_to_shared(p); }
__device__ __forceinline__ void wg_fence() { asm volatile("wgmma.fence.sync.aligned;" ::: "memory"); }
__device__ __forceinline__ void wg_commit() { asm volatile("wgmma.commit_group.sync.aligned;" ::: "memory"); }
template <int N> __device__ __forceinline__ void wg_wait() { asm volatile("wgmma.wait_group.sync.aligned %0;" ::"n"(N) : "memory"); }
template <int N> __device__ __forceinline__ void pin(float (&d)[N]) {
#pragma unroll
  for (int i = 0; i < N; i++) asm volatile("" : "+f"(d[i])::"memory");
}
__host__ __device__ constexpr uint64_t mkdesc(uint32_t addr, uint32_t lbo, uint32_t sbo, uint32_t sw) {
  return (uint64_t)((addr & 0x3FFFF) >> 4) | ((uint64_t)(lbo >> 4) << 16) | ((uint64_t)(sbo >> 4) << 32) | ((uint64_t)sw << 62);
}
__device__ __forceinline__ void mbar_init(uint32_t bar, uint32_t cnt) { asm volatile("mbarrier.init.shared::cta.b64 [%0], %1;" ::"r"(bar), "r"(cnt) : "memory"); }
__device__ __forceinline__ void mbar_arrive(uint32_t bar) { asm volatile("mbarrier.arrive.shared::cta.b64 _, [%0];" ::"r"(bar) : "memory"); }
__device__ __forceinline__ bool elect_one() {
  uint32_t r; asm volatile("{\n.reg .pred p;\nelect.sync _|p, 0xffffffff;\nselp.u32 %0, 1, 0, p;\n}" : "=r"(r)); return r;
}
__device__ __forceinline__ void mbar_arrive_elect(uint32_t bar) {
  asm volatile("{\n.reg .pred p;\nelect.sync _|p, 0xffffffff;\n@p mbarrier.arrive.shared::cta.b64 _, [%0];\n}" ::"r"(bar) : "memory");
}
__device__ __forceinline__ void mbar_expect(uint32_t bar, uint32_t bytes) { asm volatile("mbarrier.arrive.expect_tx.shared::cta.b64 _, [%0], %1;" ::"r"(bar), "r"(bytes) : "memory"); }
__device__ __forceinline__ void mbar_arrive_remote(uint32_t bar, uint32_t cta) {
  asm volatile("{\n.reg .b32 ra;\nmapa.shared::cluster.u32 ra, %0, %1;\nmbarrier.arrive.shared::cluster.b64 _, [ra];\n}" ::"r"(bar), "r"(cta) : "memory");
}
__device__ __forceinline__ void mbar_wait(uint32_t bar, uint32_t parity) {
  asm volatile("{\n.reg .pred p;\n.reg .b32 n;\nmov.b32 n, 0;\nWL:\nmbarrier.try_wait.parity.shared::cta.b64 p, [%0], %1;\n@p bra WD;\n"
               "add.u32 n, n, 1;\nsetp.lt.u32 p, n, 65536;\n@p bra WL;\nWD:\n}" ::"r"(bar), "r"(parity) : "memory");
}
__device__ __forceinline__ void nb_sync(int id, int n) { asm volatile("bar.sync %0, %1;" ::"r"(id), "r"(n) : "memory"); }
__device__ __forceinline__ void nb_arrive(int id, int n) { asm volatile("bar.arrive %0, %1;" ::"r"(id), "r"(n) : "memory"); }
__device__ __forceinline__ void fence_async() { asm volatile("fence.proxy.async.shared::cta;" ::: "memory"); }
__device__ __forceinline__ void cluster_sync() {
  asm volatile("barrier.cluster.arrive.relaxed.aligned;\nbarrier.cluster.wait.aligned;" ::: "memory");
}
__device__ __forceinline__ uint32_t pack2(float lo, float hi) {
  uint32_t r; asm("cvt.rn.bf16x2.f32 %0, %1, %2;" : "=r"(r) : "f"(hi), "f"(lo)); return r;
}
__device__ __forceinline__ void stsm4(uint32_t a, uint32_t r0, uint32_t r1, uint32_t r2, uint32_t r3) {
  asm volatile("stmatrix.sync.aligned.m8n8.x4.shared.b16 [%0], {%1,%2,%3,%4};" ::"r"(a), "r"(r0), "r"(r1), "r"(r2), "r"(r3) : "memory");
}
__device__ __forceinline__ void ldsm4(uint32_t a, uint32_t& r0, uint32_t& r1, uint32_t& r2, uint32_t& r3) {
  asm volatile("ldmatrix.sync.aligned.m8n8.x4.shared.b16 {%0,%1,%2,%3}, [%4];" : "=r"(r0), "=r"(r1), "=r"(r2), "=r"(r3) : "r"(a) : "memory");
}
__device__ __forceinline__ void sts128(uint32_t a, uint4 v) {
  asm volatile("st.shared.v4.b32 [%0], {%1,%2,%3,%4};" ::"r"(a), "r"(v.x), "r"(v.y), "r"(v.z), "r"(v.w) : "memory");
}
__device__ __forceinline__ float lds_f32(uint32_t a) { float v; asm volatile("ld.shared.f32 %0, [%1];" : "=f"(v) : "r"(a)); return v; }
__device__ __forceinline__ float ex2(float x) { float y; asm("ex2.approx.ftz.f32 %0, %1;" : "=f"(y) : "f"(x)); return y; }

template<int SC> __device__ __forceinline__ void wg_ss144(float (&d)[72], uint64_t da, uint64_t db) {
  asm volatile("{\n.reg .pred p;\nsetp.ne.b32 p, %74, 0;\nwgmma.mma_async.sync.aligned.m64n144k16.f32.bf16.bf16 {%0,%1,%2,%3,%4,%5,%6,%7,%8,%9,%10,%11,%12,%13,%14,%15,%16,%17,%18,%19,%20,%21,%22,%23,%24,%25,%26,%27,%28,%29,%30,%31,%32,%33,%34,%35,%36,%37,%38,%39,%40,%41,%42,%43,%44,%45,%46,%47,%48,%49,%50,%51,%52,%53,%54,%55,%56,%57,%58,%59,%60,%61,%62,%63,%64,%65,%66,%67,%68,%69,%70,%71}, %72, %73, p, 1, 1, 0, 1;\n}\n"
    : "+f"(d[0]),"+f"(d[1]),"+f"(d[2]),"+f"(d[3]),"+f"(d[4]),"+f"(d[5]),"+f"(d[6]),"+f"(d[7]),"+f"(d[8]),"+f"(d[9]),"+f"(d[10]),"+f"(d[11]),"+f"(d[12]),"+f"(d[13]),"+f"(d[14]),"+f"(d[15]),"+f"(d[16]),"+f"(d[17]),"+f"(d[18]),"+f"(d[19]),"+f"(d[20]),"+f"(d[21]),"+f"(d[22]),"+f"(d[23]),"+f"(d[24]),"+f"(d[25]),"+f"(d[26]),"+f"(d[27]),"+f"(d[28]),"+f"(d[29]),"+f"(d[30]),"+f"(d[31]),"+f"(d[32]),"+f"(d[33]),"+f"(d[34]),"+f"(d[35]),"+f"(d[36]),"+f"(d[37]),"+f"(d[38]),"+f"(d[39]),"+f"(d[40]),"+f"(d[41]),"+f"(d[42]),"+f"(d[43]),"+f"(d[44]),"+f"(d[45]),"+f"(d[46]),"+f"(d[47]),"+f"(d[48]),"+f"(d[49]),"+f"(d[50]),"+f"(d[51]),"+f"(d[52]),"+f"(d[53]),"+f"(d[54]),"+f"(d[55]),"+f"(d[56]),"+f"(d[57]),"+f"(d[58]),"+f"(d[59]),"+f"(d[60]),"+f"(d[61]),"+f"(d[62]),"+f"(d[63]),"+f"(d[64]),"+f"(d[65]),"+f"(d[66]),"+f"(d[67]),"+f"(d[68]),"+f"(d[69]),"+f"(d[70]),"+f"(d[71]) : "l"(da), "l"(db), "n"(SC));
}
template<int SC> __device__ __forceinline__ void wg_ss96(float (&d)[48], uint64_t da, uint64_t db) {
  asm volatile("{\n.reg .pred p;\nsetp.ne.b32 p, %50, 0;\nwgmma.mma_async.sync.aligned.m64n96k16.f32.bf16.bf16 {%0,%1,%2,%3,%4,%5,%6,%7,%8,%9,%10,%11,%12,%13,%14,%15,%16,%17,%18,%19,%20,%21,%22,%23,%24,%25,%26,%27,%28,%29,%30,%31,%32,%33,%34,%35,%36,%37,%38,%39,%40,%41,%42,%43,%44,%45,%46,%47}, %48, %49, p, 1, 1, 0, 1;\n}\n"
    : "+f"(d[0]),"+f"(d[1]),"+f"(d[2]),"+f"(d[3]),"+f"(d[4]),"+f"(d[5]),"+f"(d[6]),"+f"(d[7]),"+f"(d[8]),"+f"(d[9]),"+f"(d[10]),"+f"(d[11]),"+f"(d[12]),"+f"(d[13]),"+f"(d[14]),"+f"(d[15]),"+f"(d[16]),"+f"(d[17]),"+f"(d[18]),"+f"(d[19]),"+f"(d[20]),"+f"(d[21]),"+f"(d[22]),"+f"(d[23]),"+f"(d[24]),"+f"(d[25]),"+f"(d[26]),"+f"(d[27]),"+f"(d[28]),"+f"(d[29]),"+f"(d[30]),"+f"(d[31]),"+f"(d[32]),"+f"(d[33]),"+f"(d[34]),"+f"(d[35]),"+f"(d[36]),"+f"(d[37]),"+f"(d[38]),"+f"(d[39]),"+f"(d[40]),"+f"(d[41]),"+f"(d[42]),"+f"(d[43]),"+f"(d[44]),"+f"(d[45]),"+f"(d[46]),"+f"(d[47]) : "l"(da), "l"(db), "n"(SC));
}
template<int SC> __device__ __forceinline__ void wg_rs112(float (&d)[56], uint32_t a0, uint32_t a1, uint32_t a2, uint32_t a3, uint64_t db) {
  asm volatile("{\n.reg .pred p;\nsetp.ne.b32 p, %61, 0;\nwgmma.mma_async.sync.aligned.m64n112k16.f32.bf16.bf16 {%0,%1,%2,%3,%4,%5,%6,%7,%8,%9,%10,%11,%12,%13,%14,%15,%16,%17,%18,%19,%20,%21,%22,%23,%24,%25,%26,%27,%28,%29,%30,%31,%32,%33,%34,%35,%36,%37,%38,%39,%40,%41,%42,%43,%44,%45,%46,%47,%48,%49,%50,%51,%52,%53,%54,%55}, {%56,%57,%58,%59}, %60, p, 1, 1, 0;\n}\n"
    : "+f"(d[0]),"+f"(d[1]),"+f"(d[2]),"+f"(d[3]),"+f"(d[4]),"+f"(d[5]),"+f"(d[6]),"+f"(d[7]),"+f"(d[8]),"+f"(d[9]),"+f"(d[10]),"+f"(d[11]),"+f"(d[12]),"+f"(d[13]),"+f"(d[14]),"+f"(d[15]),"+f"(d[16]),"+f"(d[17]),"+f"(d[18]),"+f"(d[19]),"+f"(d[20]),"+f"(d[21]),"+f"(d[22]),"+f"(d[23]),"+f"(d[24]),"+f"(d[25]),"+f"(d[26]),"+f"(d[27]),"+f"(d[28]),"+f"(d[29]),"+f"(d[30]),"+f"(d[31]),"+f"(d[32]),"+f"(d[33]),"+f"(d[34]),"+f"(d[35]),"+f"(d[36]),"+f"(d[37]),"+f"(d[38]),"+f"(d[39]),"+f"(d[40]),"+f"(d[41]),"+f"(d[42]),"+f"(d[43]),"+f"(d[44]),"+f"(d[45]),"+f"(d[46]),"+f"(d[47]),"+f"(d[48]),"+f"(d[49]),"+f"(d[50]),"+f"(d[51]),"+f"(d[52]),"+f"(d[53]),"+f"(d[54]),"+f"(d[55]) : "r"(a0), "r"(a1), "r"(a2), "r"(a3), "l"(db), "n"(SC));
}
template<int SC> __device__ __forceinline__ void wg_sp48(float (&d)[24], uint32_t a0, uint32_t a1, uint32_t a2, uint32_t a3, uint64_t db, uint32_t meta) {
  asm volatile("{\n.reg .pred p;\nsetp.ne.b32 p, %30, 0;\nwgmma.mma_async.sp.sync.aligned.m64n48k32.f32.bf16.bf16 {%0,%1,%2,%3,%4,%5,%6,%7,%8,%9,%10,%11,%12,%13,%14,%15,%16,%17,%18,%19,%20,%21,%22,%23}, {%24,%25,%26,%27}, %28, %29, 0, p, 1, 1, 1;\n}\n"
    : "+f"(d[0]),"+f"(d[1]),"+f"(d[2]),"+f"(d[3]),"+f"(d[4]),"+f"(d[5]),"+f"(d[6]),"+f"(d[7]),"+f"(d[8]),"+f"(d[9]),"+f"(d[10]),"+f"(d[11]),"+f"(d[12]),"+f"(d[13]),"+f"(d[14]),"+f"(d[15]),"+f"(d[16]),"+f"(d[17]),"+f"(d[18]),"+f"(d[19]),"+f"(d[20]),"+f"(d[21]),"+f"(d[22]),"+f"(d[23]) : "r"(a0), "r"(a1), "r"(a2), "r"(a3), "l"(db), "r"(meta), "n"(SC));
}
template<int SC> __device__ __forceinline__ void wg_ss192(float (&d)[96], uint64_t da, uint64_t db) {
  asm volatile("{\n.reg .pred p;\nsetp.ne.b32 p, %98, 0;\nwgmma.mma_async.sync.aligned.m64n192k16.f32.bf16.bf16 {%0,%1,%2,%3,%4,%5,%6,%7,%8,%9,%10,%11,%12,%13,%14,%15,%16,%17,%18,%19,%20,%21,%22,%23,%24,%25,%26,%27,%28,%29,%30,%31,%32,%33,%34,%35,%36,%37,%38,%39,%40,%41,%42,%43,%44,%45,%46,%47,%48,%49,%50,%51,%52,%53,%54,%55,%56,%57,%58,%59,%60,%61,%62,%63,%64,%65,%66,%67,%68,%69,%70,%71,%72,%73,%74,%75,%76,%77,%78,%79,%80,%81,%82,%83,%84,%85,%86,%87,%88,%89,%90,%91,%92,%93,%94,%95}, %96, %97, p, 1, 1, 0, 1;\n}\n"
    : "+f"(d[0]),"+f"(d[1]),"+f"(d[2]),"+f"(d[3]),"+f"(d[4]),"+f"(d[5]),"+f"(d[6]),"+f"(d[7]),"+f"(d[8]),"+f"(d[9]),"+f"(d[10]),"+f"(d[11]),"+f"(d[12]),"+f"(d[13]),"+f"(d[14]),"+f"(d[15]),"+f"(d[16]),"+f"(d[17]),"+f"(d[18]),"+f"(d[19]),"+f"(d[20]),"+f"(d[21]),"+f"(d[22]),"+f"(d[23]),"+f"(d[24]),"+f"(d[25]),"+f"(d[26]),"+f"(d[27]),"+f"(d[28]),"+f"(d[29]),"+f"(d[30]),"+f"(d[31]),"+f"(d[32]),"+f"(d[33]),"+f"(d[34]),"+f"(d[35]),"+f"(d[36]),"+f"(d[37]),"+f"(d[38]),"+f"(d[39]),"+f"(d[40]),"+f"(d[41]),"+f"(d[42]),"+f"(d[43]),"+f"(d[44]),"+f"(d[45]),"+f"(d[46]),"+f"(d[47]),"+f"(d[48]),"+f"(d[49]),"+f"(d[50]),"+f"(d[51]),"+f"(d[52]),"+f"(d[53]),"+f"(d[54]),"+f"(d[55]),"+f"(d[56]),"+f"(d[57]),"+f"(d[58]),"+f"(d[59]),"+f"(d[60]),"+f"(d[61]),"+f"(d[62]),"+f"(d[63]),"+f"(d[64]),"+f"(d[65]),"+f"(d[66]),"+f"(d[67]),"+f"(d[68]),"+f"(d[69]),"+f"(d[70]),"+f"(d[71]),"+f"(d[72]),"+f"(d[73]),"+f"(d[74]),"+f"(d[75]),"+f"(d[76]),"+f"(d[77]),"+f"(d[78]),"+f"(d[79]),"+f"(d[80]),"+f"(d[81]),"+f"(d[82]),"+f"(d[83]),"+f"(d[84]),"+f"(d[85]),"+f"(d[86]),"+f"(d[87]),"+f"(d[88]),"+f"(d[89]),"+f"(d[90]),"+f"(d[91]),"+f"(d[92]),"+f"(d[93]),"+f"(d[94]),"+f"(d[95]) : "l"(da), "l"(db), "n"(SC));
}

constexpr uint32_t SBC = 1024;
constexpr int ROWB = 2 * 224 * 384;
constexpr int TB = 12;
constexpr int KS = 832;
constexpr int KSLOT = 22 * KS;
constexpr int SM_X0 = 0;
constexpr int SM_X1 = 18432;
constexpr int SM_X2 = SM_X1 + 24576;
constexpr int SM_W = SM_X2 + 24576;
constexpr int SM_K = SM_W + 55296;
constexpr int SM_V = SM_K + 2 * KSLOT;
constexpr int SM_Q = SM_V + 22 * 1536;
constexpr int SM_O = SM_Q + 24576;
constexpr int SM_RPB = SM_O + 12288;
constexpr int SM_BAR = SM_RPB + 768;
constexpr int SM_A_TOTAL = SM_BAR + 256;
constexpr int SM_TWO = SM_X1;
constexpr int SM_TST = SM_TWO + 36864;
constexpr int SM_TIN = SM_W;
enum { B_FULL = 0, B_EMPTY = 3, B_TIN = 6, B_TFREE = 8, B_WK = 10, B_WQ, B_WO, B_Q0, B_ODONE, B_KFREE = B_ODONE + 2, B_VFREE, B_COUNT };
enum { N_KRDY = 4, N_QK0, N_QK1, N_VQ0, N_VQ1, N_PVISS };

#define SPL 4
#define RA 152
#define RG 184
__device__ int g_flags[TB * 56];

#define TR(role, it, k)
#define TRDECL
#define TRARG
#define TRPASS
#define TRDUMP
#define TRB(it, k)
#define TR2(blk, k)

struct GemmCtx {
  uint32_t bar;
  uint32_t kC, vC, qC;
  uint32_t kH, vH;
  bool hvalid;
};

template <int STRIDE> __device__ __forceinline__ void dump12(uint32_t a, const uint32_t (&r)[12]) {
#pragma unroll
  for (int j = 0; j < 3; j++) stsm4(a + j * 2 * STRIDE, r[4 * j], r[4 * j + 1], r[4 * j + 2], r[4 * j + 3]);
}
template <int N> __device__ __forceinline__ void pack12(uint32_t (&r)[12], const float (&d)[N], int off) {
#pragma unroll
  for (int j = 0; j < 12; j++) r[j] = pack2(d[off + 2 * j], d[off + 2 * j + 1]);
}
template <int XS, int K0, int K1> __device__ __forceinline__ void issue_core(float (&d)[72]) {
  constexpr uint64_t da = mkdesc(SBC + XS, 16, 1024, 1), db = mkdesc(SBC + SM_W, 6144, 256, 3);
  wg_fence();
  if (K0 == 0) wg_ss144<0>(d, da, db);
#pragma unroll
  for (int k = K0 ? K0 : 1; k < K1; k++) wg_ss144<1>(d, da + (k >> 2) * 512 + (k & 3) * 2, db + k * 32);
  wg_commit();
}
template <int K0, int K1> __device__ __forceinline__ void issue_halo(float (&d)[48]) {
  constexpr uint64_t da = mkdesc(SBC + SM_X0, 16, 1024, 1), db = mkdesc(SBC + SM_W, 6144, 256, 3);
  wg_fence();
  if (K0 == 0) wg_ss96<0>(d, da, db);
#pragma unroll
  for (int k = K0 ? K0 : 1; k < K1; k++) wg_ss96<1>(d, da + (k >> 2) * 384 + (k & 3) * 2, db + k * 32);
  wg_commit();
}
template <int ST, int BYTES> __device__ __forceinline__ void release_stage(const GemmCtx& c, bool on) {
  asm volatile("{\n.reg .pred p, q;\n.reg .b32 ra;\nsetp.ne.b32 q, %2, 0;\nelect.sync _|p, 0xffffffff;\nand.pred p, p, q;\n"
               "mapa.shared::cluster.u32 ra, %1, %4;\n"
               "@p mbarrier.arrive.expect_tx.shared::cta.b64 _, [%0], %3;\n@p mbarrier.arrive.shared::cluster.b64 _, [ra];\n}"
               ::"r"(c.bar + (B_FULL + ST) * 8), "r"(c.bar + (B_EMPTY + ST) * 8), "r"((int)on), "n"(BYTES / 4), "n"(ST) : "memory");
}
__device__ __forceinline__ void load_w(const CUtensorMap* m, uint32_t dst, uint32_t bar, int col) {
  asm volatile("cp.async.bulk.tensor.2d.shared::cluster.global.mbarrier::complete_tx::bytes [%0], [%1, {%3,%4}], [%2];"
               ::"r"(dst), "l"(m), "r"(bar), "r"(col), "r"(0) : "memory");
}
__device__ __forceinline__ void publish(uint32_t bar) {
  fence_async();
  __syncwarp();
  mbar_arrive_elect(bar);
}

template <bool FIRST, bool LAST>
__device__ __forceinline__ void gemm_iter(const GemmCtx& c, int b, uint32_t (&pk)[12], uint32_t (&pv)[12], uint32_t (&pq)[12], int head TRARG) {
  const uint32_t bar = c.bar;
  const uint32_t pa = b & 1;
  const bool w = b >= 0;
  const uint32_t ko = pa * KSLOT, vx = pa * 16, qx = pa * 128;
  float H[48], C[72];
  uint32_t hk[12], hv[12], pv2[12];
  TR(2, b, 0);
  if (FIRST) mbar_wait(bar + (B_FULL + 0) * 8, pa);
  if (w) nb_sync(N_QK1, 256);
  TR(2, b, 2);
  issue_halo<0, 8>(H);
  TR(2, b, 3);
  if (!FIRST) {
    fence_async();
    if (w) mbar_wait(bar + B_KFREE * 8, pa);
    if (!LAST) mbar_wait(bar + (B_FULL + 2) * 8, pa);
    dump12<128>(c.kC + ko, pk);
  }
  issue_halo<8, 12>(H);
  TR(2, b, 4);
  if (!LAST) {
    if (FIRST) { mbar_wait(bar + (B_FULL + 2) * 8, pa); mbar_wait(bar + B_WQ * 8, 0); }
    issue_core<SM_X2, 0, 8>(C);
    TR(2, b, 5);
    if (!FIRST) dump12<256>(c.qC ^ (qx ^ 192), pq);
    wg_wait<1>(); pin(H);
    release_stage<0, 18432>(c, true);
  } else {
    dump12<256>(c.qC ^ (qx ^ 192), pq);
    nb_arrive(N_VQ0, 288); nb_arrive(N_VQ1, 288);
    wg_wait<0>(); pin(H);
    uint32_t ln; asm volatile("mov.u32 %0, %%laneid;" : "=r"(ln));
    if (ln < 4) mbar_arrive_remote(bar + (B_TFREE + (head >> 1)) * 8, ln);
  }
  pack12(hk, H, 0);
  if (c.hvalid) dump12<128>(c.kH + ko, hk);
  pack12(hv, H, 24);
  if (!LAST) {
    issue_core<SM_X2, 8, 12>(C);
    if (w) { nb_arrive(N_VQ0, 288); nb_arrive(N_VQ1, 288); }
    else if (!FIRST) { __syncwarp(); mbar_arrive_elect(bar + B_Q0 * 8); }
    mbar_wait(bar + (B_FULL + 1) * 8, pa);
    TR(2, b, 6);
    wg_wait<0>(); pin(C);
    TR(2, b, 7);
    pack12(pk, C, 0);
    dump12<128>(c.kC + ko + 64, pk);
    release_stage<2, 24576>(c, b < 11);
    pack12(pv2, C, 24);
    pack12(pq, C, 48);
    TR(2, b, 8);
    issue_core<SM_X1, 0, SPL>(C);
    if (w) nb_sync(N_PVISS, 384);
    issue_core<SM_X1, SPL, 8>(C);
    TR(2, b, 9);
    mbar_wait(bar + (B_FULL + 0) * 8, pa ^ 1);
  }
  fence_async();
  if (LAST) nb_arrive(N_KRDY, 256);
  if (w) mbar_wait(bar + B_VFREE * 8, pa);
  TR(2, b, 10);
  if (!FIRST) dump12<128>(c.vC ^ vx, pv);
  if (!LAST) {
    dump12<256>(c.qC ^ qx, pq);
    issue_core<SM_X1, 8, 12>(C);
    if (!FIRST) nb_arrive(N_KRDY, 256);
  }
  TR(2, b, 1);
  if (c.hvalid) dump12<128>(c.vH ^ vx, hv);
  if (LAST) { fence_async(); nb_arrive(N_VQ0, 288); nb_arrive(N_VQ1, 288); return; }
  dump12<128>((c.vC ^ vx ^ 16) + 768, pv2);
  TR(2, b, 11);
  wg_wait<0>(); pin(C);
  TR(2, b, 12);
  release_stage<1, 24576>(c, b < 11);
  pack12(pk, C, 0);
  pack12(pv, C, 24);
  pack12(pq, C, 48);
}

__device__ __forceinline__ float fold(float a, float b, float t, int useb) {
  float r;
  asm("{\n.reg .pred p;\nsetp.ne.b32 p, %4, 0;\nfma.rn.f32 %0, %1, 0f3E553B95, %3;\n@p fma.rn.f32 %0, %2, 0f3E553B95, %3;\n}"
      : "=&f"(r) : "f"(a), "f"(b), "f"(t), "r"(useb));
  return r;
}
template <int U, int L, bool BORDER>
__device__ __forceinline__ void softmax_tile(const float (&SA)[56], const float (&SB)[56], const float (&T)[14], int b0, int b1,
                                             uint32_t ra0, uint32_t ra1, int qcu, uint32_t (&P)[28], float (&sx)[8]) {
  float lu[14], ll[14];
#pragma unroll
  for (int j = 0; j < 7; j++) {
    float tu0, tu1, tl0, tl1;
    if (BORDER) {
      tu0 = lds_f32(ra0 + (U + j + 3 - qcu) * 4); tu1 = lds_f32(ra1 + (U + j + 3 - qcu) * 4);
      tl0 = lds_f32(ra0 + (L + j + 2 - qcu) * 4); tl1 = lds_f32(ra1 + (L + j + 2 - qcu) * 4);
    } else { tu0 = tl0 = T[2 * j]; tu1 = tl1 = T[2 * j + 1]; }
    lu[2 * j]     = fold(SA[4 * (U + j)],     SB[4 * (U + j)],     tu0, b0);
    ll[2 * j]     = fold(SA[4 * (L + j) + 2], SB[4 * (L + j) + 2], tl0, b0);
    lu[2 * j + 1] = fold(SA[4 * (U + j) + 1], SB[4 * (U + j) + 1], tu1, b1);
    ll[2 * j + 1] = fold(SA[4 * (L + j) + 3], SB[4 * (L + j) + 3], tl1, b1);
  }
  float mu = lu[0], ml = ll[0], mu2 = lu[1], ml2 = ll[1];
#pragma unroll
  for (int j = 1; j < 7; j++) { mu = fmaxf(mu, lu[2 * j]); mu2 = fmaxf(mu2, lu[2 * j + 1]); ml = fmaxf(ml, ll[2 * j]); ml2 = fmaxf(ml2, ll[2 * j + 1]); }
  mu = fmaxf(mu, mu2); ml = fmaxf(ml, ml2);
  { const float a1 = __shfl_xor_sync(0xffffffffu, mu, 1), a2 = __shfl_xor_sync(0xffffffffu, mu, 2), a3 = __shfl_xor_sync(0xffffffffu, mu, 3);
    const float c1 = __shfl_xor_sync(0xffffffffu, ml, 1), c2 = __shfl_xor_sync(0xffffffffu, ml, 2), c3 = __shfl_xor_sync(0xffffffffu, ml, 3);
    mu = fmaxf(fmaxf(mu, a1), fmaxf(a2, a3)); ml = fmaxf(fmaxf(ml, c1), fmaxf(c2, c3)); }
  float su = 0.f, sl = 0.f;
#pragma unroll
  for (int c = 0; c < 14; c++) {
    const int iu = (c >> 1) * 4 + (c & 1) * 2;
    if (c >= U && c < U + 7) {
      float e0 = ex2(lu[2 * (c - U)] - mu), e1 = ex2(lu[2 * (c - U) + 1] - mu);
      su = c == U ? e0 + e1 : (su + e0) + e1; P[iu] = pack2(e0, e1);
    } else P[iu] = 0u;
    if (c >= L && c < L + 7) {
      float e0 = ex2(ll[2 * (c - L)] - ml), e1 = ex2(ll[2 * (c - L) + 1] - ml);
      sl = c == L ? e0 + e1 : (sl + e0) + e1; P[iu + 1] = pack2(e0, e1);
    } else P[iu + 1] = 0u;
  }
  sx[0] = su; sx[4] = sl;
#pragma unroll
  for (int k = 1; k < 4; k++) { sx[k] = __shfl_xor_sync(0xffffffffu, su, k); sx[4 + k] = __shfl_xor_sync(0xffffffffu, sl, k); }
}

struct Maps { CUtensorMap xc, xh, w, os, wo, ot; };

__global__ void __cluster_dims__(4, 1, 1) __launch_bounds__(512, 1)
na_attn_kernel(const __grid_constant__ Maps mp, const __nv_bfloat16* __restrict__ wqkv, const __nv_bfloat16* __restrict__ rpb) {
  extern __shared__ __align__(1024) uint8_t smem_raw[];
  const uint32_t sb = smem_u32(smem_raw);
  if ((sb & 0x3FFFF) != SBC) return;
  const uint32_t bar = sb + SM_BAR;
  TR2(blockIdx.x, 0);
  const int tid = threadIdx.x, lane = tid & 31;
  const int warp = __shfl_sync(0xffffffffu, tid >> 5, 0);
  const int head = blockIdx.x & 3, cl = blockIdx.x >> 2;
  const int par = cl / 7, strip = cl - par * 7, ph = par >> 1, pw = par & 1;

  uint4 wv[3];
  const int wr = tid / 6, wc = tid - wr * 6;
  if (warp < 12) {
#pragma unroll
    for (int i = 0; i < 3; i++) wv[i] = __ldg(reinterpret_cast<const uint4*>(wqkv + (wr + i * 64) * 576 + 384 + head * 48 + wc * 8));
  } else if (elect_one()) {
    if (warp == 12) {
      mbar_init(bar + B_WK * 8, 1);
#pragma unroll
      for (int i = 0; i < 3; i++) load_w(&mp.w, sb + SM_W + i * 6144, bar + B_WK * 8, 192 + head * 48 + i * 16);
      mbar_expect(bar + B_WK * 8, 18432);
    } else if (warp == 13) {
#pragma unroll
      for (int i = 0; i < B_WK; i++) mbar_init(bar + i * 8, i < B_EMPTY ? 4 : (i < B_TIN ? 16 : (i < B_TFREE ? 1 : 8)));
    } else if (warp == 14) {
#pragma unroll
      for (int i = B_WQ; i < B_COUNT; i++) mbar_init(bar + i * 8, i < B_Q0 ? 1 : (i < B_KFREE ? 4 : 8));
    }
    asm volatile("fence.mbarrier_init.release.cluster;" ::: "memory");
  }
  __syncwarp();
  asm volatile("barrier.cluster.arrive.relaxed.aligned;" ::: "memory");

  if (warp >= 12) {
    asm volatile("setmaxnreg.dec.sync.aligned.u32 24;");
    asm volatile("griddepcontrol.launch_dependents;");
    const int cc = ph * 112 + (head ? strip * 16 : (strip == 0 ? 16 : (strip == 6 ? 74 : strip * 16 - 3)));
    const int sd = strip == 0 ? -1 : (strip == 6 ? 1 : 0);
    const int r0 = head == 0 ? -4 : (head == 1 ? 4 : 0);
    asm volatile("barrier.cluster.wait.aligned;" ::: "memory");
    if (warp == 12) {
      const uint32_t fb = bar + (B_FULL + head) * 8, eb = bar + (B_EMPTY + head) * 8;
      const uint32_t dst = sb + (head == 0 ? SM_X0 : (head == 1 ? SM_X1 : SM_X2));
      const int nl = head == 0 ? 15 : (head == 3 ? 1 : 14);
#pragma unroll 1
      for (int n = 0; n < nl; n++) {
        if (n) mbar_wait(eb, (n - 1) & 1);
        if (elect_one()) {
          if (head == 0) {
            asm volatile("cp.async.bulk.tensor.5d.shared::cluster.global.mbarrier::complete_tx::bytes.multicast::cluster [%0], [%1, {%3,%4,%5,%6,%7}], [%2], %8;"
                         ::"r"(dst), "l"(&mp.xh), "r"(fb), "r"(0), "r"(8 * n + r0), "r"(cc), "r"(sd), "r"(pw * 3), "h"((uint16_t)15) : "memory");
            if (n + 1 < nl) asm volatile("cp.async.bulk.prefetch.tensor.5d.L2.global [%0, {%1,%2,%3,%4,%5}];" ::"l"(&mp.xh), "r"(0), "r"(8 * n + 8 + r0), "r"(cc), "r"(sd), "r"(pw * 3) : "memory");
          } else if (head < 3) {
            asm volatile("cp.async.bulk.tensor.4d.shared::cluster.global.mbarrier::complete_tx::bytes.multicast::cluster [%0], [%1, {%3,%4,%5,%6}], [%2], %7;"
                         ::"r"(dst), "l"(&mp.xc), "r"(fb), "r"(0), "r"(8 * n + r0), "r"(cc), "r"(pw * 3), "h"((uint16_t)15) : "memory");
          }
          if (n == 0) {
#pragma unroll
            for (int i = 0; i < 3; i++) load_w(&mp.w, sb + SM_W + (6 + i) * 6144, bar + B_WQ * 8, head * 48 + i * 16);
            mbar_expect(bar + B_WQ * 8, 18432);
            mbar_expect(bar + B_TIN * 8, 24576); mbar_expect(bar + (B_TIN + 1) * 8, 24576);
          }
          if (head && n + 1 < nl) asm volatile("cp.async.bulk.prefetch.tensor.4d.L2.global [%0, {%1,%2,%3,%4}];" ::"l"(&mp.xc), "r"(0), "r"(8 * n + 8 + r0), "r"(cc), "r"(pw * 3) : "memory");
        }
        __syncwarp();
      }
    }
    if (warp >= 14) {
      const int j = warp - 14;
      int* flag = g_flags + cl * 2 + j;
      nb_arrive(N_VQ0 + j, 288);
#pragma unroll 1
      for (int b = 0; b < TB; b++) {
        mbar_wait(bar + (B_ODONE + j) * 8, b & 1);
        if (lane == 0) {
          asm volatile("cp.async.bulk.tensor.3d.global.shared::cta.bulk_group [%0, {%2,%3,%4}], [%1];"
                       ::"l"(&mp.os), "r"(sb + SM_O + j * 6144), "r"(pw * 192), "r"(8 * b + 2 * head), "r"(ph * 112 + strip * 16 + 8 * j) : "memory");
          asm volatile("cp.async.bulk.commit_group;\ncp.async.bulk.wait_group.read 0;" ::: "memory");
        }
        __syncwarp();
        nb_arrive(N_VQ0 + j, 288);
        if (lane == 0) {
          asm volatile("cp.async.bulk.wait_group 0;\nfence.proxy.async.global;\nred.release.gpu.global.add.s32 [%0], 1;" ::"l"(flag + b * 56) : "memory");
        }
        __syncwarp();
      }
#pragma unroll 1
      for (int i = 0; i < 2; i++) {
        mbar_wait(bar + (B_ODONE + j) * 8, i);
        if (i == 0) { nb_arrive(N_VQ0 + j, 288); mbar_wait(bar + (B_TFREE + j) * 8, 0); }
        if (elect_one()) {
#pragma unroll
          for (int d = 0; d < 2; d++)
            asm volatile("{\n.reg .b32 rd, rb;\nmapa.shared::cluster.u32 rd, %0, %3;\nmapa.shared::cluster.u32 rb, %2, %3;\n"
                         "cp.async.bulk.shared::cluster.shared::cta.mbarrier::complete_tx::bytes [rd], [%1], 6144, [rb];\n}"
                         ::"r"(sb + SM_TIN + i * 24576 + head * 6144), "r"(sb + (i ? SM_Q + j * 12288 : SM_O + j * 6144)), "r"(bar + (B_TIN + i) * 8), "r"(2 * j + d) : "memory");
        }
        __syncwarp();
      }
    }
    cluster_sync();
  } else if (warp >= 8) {
    asm volatile("setmaxnreg.inc.sync.aligned.u32 %0;" ::"n"(RG));
    GemmCtx c;
    c.bar = bar;
    const int gw = warp - 8, tk = gw * 16 + (lane & 15), hi = lane >> 4;
    { const int col = tk >> 2, i = tk & 3;
      c.kC = sb + SM_K + (col + 3) * KS + hi * 128 + i * 16;
      c.vC = sb + SM_V + (col + 3) * 1536 + hi * 128 + (2 * i + ((col + 3) & 1)) * 16;
      c.qC = sb + SM_Q + col * 1536 + hi * 256 + (col & 1) * 64 + i * 16; }
    { const int ci = tk >> 3, kc = ci < 3 ? ci : ci + 16, i = tk & 7; c.hvalid = gw < 3;
      c.kH = sb + SM_K + kc * KS + hi * 128 + i * 16;
      c.vH = sb + SM_V + kc * 1536 + hi * 128 + (i >> 2) * 768 + (2 * (i & 3) + ((kc ^ (i >> 2)) & 1)) * 16; }
    asm volatile("barrier.cluster.wait.aligned;" ::: "memory");
    if (elect_one()) { mbar_expect(bar + B_FULL * 8, 4608); mbar_expect(bar + (B_FULL + 1) * 8, 6144); mbar_expect(bar + (B_FULL + 2) * 8, 6144); }
    __syncwarp();
#pragma unroll
    for (int i = 0; i < 3; i++) sts128(sb + SM_W + (3 + (wc >> 1)) * 6144 + (wr + i * 64) * 32 + ((wc ^ (wr >> 2)) & 1) * 16, wv[i]);
    fence_async();
    asm volatile("bar.sync 1, 384;" ::: "memory");
    mbar_wait(bar + B_WK * 8, 0);
    uint32_t pk[12], pv[12], pq[12];
    TRDECL;
    gemm_iter<true, false>(c, -2, pk, pv, pq, head TRPASS);
#pragma unroll 1
    for (int b = -1; b < 12; b++) gemm_iter<false, false>(c, b, pk, pv, pq, head TRPASS);
    asm volatile("bar.sync 2, 128;" ::: "memory");
    if (gw == 0 && elect_one()) {
      mbar_expect(bar + B_WO * 8, 36864);
      asm volatile("cp.async.bulk.tensor.3d.shared::cluster.global.mbarrier::complete_tx::bytes [%0], [%1, {%3,%4,%5}], [%2];"
                   ::"r"(sb + SM_TWO), "l"(&mp.wo), "r"(bar + B_WO * 8), "r"(0), "r"(0), "r"((head & 1) * 3) : "memory");
    }
    __syncwarp();
    gemm_iter<false, true>(c, 12, pk, pv, pq, head TRPASS);
    TRDUMP;
    mbar_wait(bar + B_WO * 8, 0);
    nb_sync(N_QK1, 256);
    const uint32_t st = sb + SM_TST + gw * 3072;
    const uint32_t sta = st + (lane & 15) * 64 + ((hi ^ ((lane >> 1) & 3)) * 16);
#pragma unroll 1
    for (int i = 0; i < 2; i++) {
      constexpr uint64_t db = mkdesc(SBC + SM_TWO, 12288, 512, 2);
      const uint64_t da = mkdesc(SBC + SM_TIN, 128, 768, 0) + i * (24576 / 16);
      float D[48];
      mbar_wait(bar + (B_TIN + i) * 8, 0);
      wg_fence();
      wg_ss96<0>(D, da, db);
#pragma unroll
      for (int k = 1; k < 12; k++) wg_ss96<1>(D, da + (k / 3) * 384 + (k % 3) * 16, db + k * 64);
      wg_commit();
      if (lane == 0) asm volatile("cp.async.bulk.wait_group.read 0;" ::: "memory");
      __syncwarp();
      wg_wait<0>(); pin(D);
#pragma unroll
      for (int q = 0; q < 6; q++)
        stsm4((sta ^ ((q & 1) * 32)) + (q >> 1) * 1024,
              pack2(D[8 * q], D[8 * q + 1]), pack2(D[8 * q + 2], D[8 * q + 3]), pack2(D[8 * q + 4], D[8 * q + 5]), pack2(D[8 * q + 6], D[8 * q + 7]));
      fence_async();
      __syncwarp();
      if (lane == 0) {
        asm volatile("cp.async.bulk.tensor.4d.global.shared::cta.bulk_group [%0, {%2,%3,%4,%5}], [%1];"
                     ::"l"(&mp.ot), "r"(st), "r"(0), "r"(8 * (TB + i)), "r"(ph * 112 + strip * 16 + 8 * (head >> 1) + 2 * gw), "r"(pw * 6 + (head & 1) * 3) : "memory");
        asm volatile("cp.async.bulk.commit_group;" ::: "memory");
      }
    }
    asm volatile("barrier.cluster.arrive.relaxed.aligned;" ::: "memory");
    if (lane == 0) asm volatile("cp.async.bulk.wait_group 0;" ::: "memory");
    __syncwarp();
    asm volatile("barrier.cluster.wait.aligned;" ::: "memory");
  } else {
    asm volatile("setmaxnreg.inc.sync.aligned.u32 %0;" ::"n"(RA));
    float rv = -INFINITY;
    if (tid < 169) rv = __bfloat162float(rpb[head * 169 + tid]) * 1.4426950408889634f;
    if (tid < 192) {
      const int kc = (wr & 15) + 3;
      sts128(tid < 96 ? sb + SM_K + kc * KS + wc * 128 + 48 : sb + SM_V + kc * 1536 + wc * 128 + (6 + (kc & 1)) * 16, make_uint4(0, 0, 0, 0));
    }
#pragma unroll
    for (int i = 0; i < 3; i++) sts128(sb + SM_W + (3 + (wc >> 1)) * 6144 + (wr + i * 64) * 32 + ((wc ^ (wr >> 2)) & 1) * 16, wv[i]);
    fence_async();
    asm volatile("bar.arrive 1, 384;" ::: "memory");
    if (tid < 182) asm volatile("st.shared.f32 [%0], %1;" ::"r"(sb + SM_RPB + tid * 4), "f"(rv) : "memory");
    const int j = warp >> 2, w = warp & 3;
    int variant = w;
    if (strip == 0 && j == 0 && w < 2) variant = 4;
    if (strip == 6 && j == 1 && w >= 2) variant = 5;
    const uint32_t qa = sb + SM_Q + (8 * j + 2 * w + ((lane >> 3) & 1)) * 1536 + (lane >> 4) * 256 + (((lane & 7) * 16) ^ (((lane >> 3) & 1) * 64));
    uint32_t oa = sb + SM_O + j * 6144 + (2 * w + ((lane >> 3) & 1)) * 768 + (lane >> 4) * 128 + (lane & 7) * 16;
    const uint64_t dK = mkdesc(SBC + SM_K, 128, KS, 0) + j * (8 * KS / 16);
    const uint64_t dV = mkdesc(SBC + SM_V, 768, 128, 0) + j * (8 * 1536 / 16);
    asm volatile("barrier.cluster.wait.aligned;" ::: "memory");
    asm volatile("bar.sync 3, 256;" ::: "memory");
    float T[14];
    TRDECL;
    int b0 = 0, b1 = 0;
    uint32_t ra0 = 0, ra1 = 0, meta = 0;
    uint32_t q[12];
    mbar_wait(bar + B_Q0 * 8, 0);
#pragma unroll
    for (int k = 0; k < 3; k++) ldsm4(qa + k * 512, q[4 * k], q[4 * k + 1], q[4 * k + 2], q[4 * k + 3]);
#pragma unroll 1
    for (int b = 0; b < 14; b++) {
      const uint32_t pa = b & 1;
      if (b <= 1 || b == 13) {
        uint32_t ln; asm volatile("mov.u32 %0, %%laneid;" : "=r"(ln));
        const int g = ln >> 2, t = ln & 3;
        const int sw = b == 0 ? max(g + 1, 4) : (b == 13 ? min(g + 1, 5) : g + 1);
        const int i0 = 2 * t, i1 = 2 * t + 1;
        b0 = i0 <= sw - 2; b1 = i1 <= sw - 2;
        const int m = sw - 1;
        ra0 = sb + SM_RPB + (i0 == m ? 13 : i0 + (b0 ? 8 : 0) - g + 2) * 52;
        ra1 = sb + SM_RPB + (i1 == m ? 13 : i1 + (b1 ? 8 : 0) - g + 2) * 52;
#pragma unroll
        for (int jj = 0; jj < 7; jj++) { T[2 * jj] = lds_f32(ra0 + (jj + 3) * 4); T[2 * jj + 1] = lds_f32(ra1 + (jj + 3) * 4); }
        uint32_t m16 = 0x8888u;
#pragma unroll
        for (int i = 0; i < 8; i++) m16 |= (uint32_t)(((i <= sw - 2) ^ (i >> 2) ^ t ^ b) & 1) << (2 * i);
        meta = m16 | (m16 << 16);
        if (b == 13) oa += SM_Q - SM_O + j * 6144;
      } else meta ^= 0x55555555u;
      float SA[56], SB[56];
      const uint64_t dA = dK + pa * (KSLOT >> 4), dB = dK + (pa ^ 1) * (KSLOT >> 4);
      TR(0, b, 0);
      nb_sync(N_KRDY + j, 256);
      TR(0, b, 1);
      TR(0, b - 1, 9);
      wg_fence();
      wg_rs112<0>(SA, q[0], q[1], q[2], q[3], dA);
      wg_rs112<0>(SB, q[0], q[1], q[2], q[3], dB);
      wg_rs112<1>(SA, q[4], q[5], q[6], q[7], dA + 16);
      wg_rs112<1>(SB, q[4], q[5], q[6], q[7], dB + 16);
      wg_rs112<1>(SA, q[8], q[9], q[10], q[11], dA + 32);
      wg_rs112<1>(SB, q[8], q[9], q[10], q[11], dB + 32);
      wg_commit();
      nb_arrive(N_QK0 + j, 256);
      TR(0, b, 2);
      wg_wait<0>(); pin(SA); pin(SB);
      mbar_arrive_elect(bar + B_KFREE * 8);
      TR(0, b, 3);
      TR(0, b - 1, 10);
      uint32_t P[28];
      float sx[8];
      switch (variant) {
        case 0: softmax_tile<0, 1, false>(SA, SB, T, b0, b1, ra0, ra1, 0, P, sx); break;
        case 1: softmax_tile<2, 3, false>(SA, SB, T, b0, b1, ra0, ra1, 0, P, sx); break;
        case 2: softmax_tile<4, 5, false>(SA, SB, T, b0, b1, ra0, ra1, 0, P, sx); break;
        case 3: softmax_tile<6, 7, false>(SA, SB, T, b0, b1, ra0, ra1, 0, P, sx); break;
        case 4: softmax_tile<3, 3, true>(SA, SB, T, b0, b1, ra0, ra1, 2 * w, P, sx); break;
        default: softmax_tile<4, 4, true>(SA, SB, T, b0, b1, ra0, ra1, 2 * w, P, sx); break;
      }
      float O[24];
      TR(0, b, 4);
      nb_sync(N_VQ0 + j, 288);
      TR(0, b, 5);
#pragma unroll
      for (int k = 0; k < 3; k++) ldsm4(qa + (pa ^ 1) * 128 + k * 512, q[4 * k], q[4 * k + 1], q[4 * k + 2], q[4 * k + 3]);
      wg_fence();
      wg_sp48<0>(O, P[0], P[1], P[2], P[3], dV, meta);
#pragma unroll
      for (int s = 1; s < 7; s++) wg_sp48<1>(O, P[4 * s], P[4 * s + 1], P[4 * s + 2], P[4 * s + 3], dV + s * 192, meta);
      wg_commit();
      if (b < 12) nb_arrive(N_PVISS, 384);
      TR(0, b, 6);
      wg_wait<0>(); pin(O);
      mbar_arrive_elect(bar + B_VFREE * 8);
      TR(0, b, 7);
      float ru, rl;
      asm("rcp.approx.ftz.f32 %0, %1;" : "=f"(ru) : "f"(((fmaf(O[0], 0.f, sx[0]) + sx[1]) + sx[2]) + sx[3]));
      asm("rcp.approx.ftz.f32 %0, %1;" : "=f"(rl) : "f"(((fmaf(O[2], 0.f, sx[4]) + sx[5]) + sx[6]) + sx[7]));
#pragma unroll
      for (int i = 0; i < 3; i++)
        stsm4(oa + i * 256, pack2(O[8 * i] * ru, O[8 * i + 1] * ru), pack2(O[8 * i + 2] * rl, O[8 * i + 3] * rl),
              pack2(O[8 * i + 4] * ru, O[8 * i + 5] * ru), pack2(O[8 * i + 6] * rl, O[8 * i + 7] * rl));
      publish(bar + (B_ODONE + j) * 8);
      TR(0, b, 8);
    }
    TRDUMP;
    TR2(blockIdx.x, 2);
    cluster_sync();
  }
}

constexpr int NSTB = 4;
constexpr int NTB = TB * 56;
constexpr int SM_B_ST = 0;
constexpr int SM_B_IN = 49152;
constexpr int SM_B_W = SM_B_IN + NSTB * 24576;
constexpr int SM_B_BAR = SM_B_W + 73728;
constexpr int SM_B_TOTAL = SM_B_BAR + 128;
struct MapsB { CUtensorMap oi, oo, wo; };

__global__ void __launch_bounds__(288, 1)
na_proj_kernel(const __grid_constant__ MapsB mp) {
  extern __shared__ __align__(1024) uint8_t smem_raw[];
  const uint32_t sb = smem_u32(smem_raw);
  if ((sb & 0x3FFFF) != SBC) return;
  const uint32_t bar = sb + SM_B_BAR;
  const int tid = threadIdx.x, lane = tid & 31;
  const int warp = __shfl_sync(0xffffffffu, tid >> 5, 0);
  TR2(132 + blockIdx.x, 0);
  TRB(47, 0);
  if (warp == 8 && elect_one()) {
#pragma unroll
    for (int i = 0; i <= 2 * NSTB; i++) mbar_init(bar + i * 8, i < NSTB || i == 2 * NSTB ? 1 : 4);
    mbar_expect(bar + 2 * NSTB * 8, 73728);
#pragma unroll
    for (int i = 0; i < 2; i++)
      asm volatile("cp.async.bulk.tensor.3d.shared::cluster.global.mbarrier::complete_tx::bytes [%0], [%1, {%3,%4,%5}], [%2];"
                   ::"r"(sb + SM_B_W + i * 36864), "l"(&mp.wo), "r"(bar + 2 * NSTB * 8), "r"(0), "r"(0), "r"(i * 3) : "memory");
  }
  __syncthreads();
  const int step = gridDim.x;
  if (warp == 8) {
    int it = 0;
    uint32_t spin = 0;
#pragma unroll 1
    for (int n = blockIdx.x; n < NTB && spin < SPIN_LIMIT; spin++) {
      int v = 0;
      const int mine = n + lane * step;
      if (lane < 8 && mine < NTB) asm volatile("ld.acquire.gpu.global.s32 %0, [%1];" : "=r"(v) : "l"(g_flags + mine) : "memory");
      int cnt = __ffs(~__ballot_sync(0xffffffffu, v >= 4)) - 1;
      asm volatile("fence.proxy.async.global;" ::: "memory");
      __syncwarp();
#pragma unroll 1
      for (; cnt > 0; cnt--, n += step, it++) {
        TRB(it, 0);
        const int b = n / 56, rem = n - b * 56, par = rem / 14;
        const int st = it & (NSTB - 1), use = it / NSTB;
        if (use) mbar_wait(bar + (NSTB + st) * 8, (use - 1) & 1);
        if (elect_one()) {
          mbar_expect(bar + st * 8, 24576);
          asm volatile("cp.async.bulk.tensor.3d.shared::cluster.global.mbarrier::complete_tx::bytes [%0], [%1, {%3,%4,%5}], [%2];"
                       ::"r"(sb + SM_B_IN + st * 24576), "l"(&mp.oi), "r"(bar + st * 8), "r"((par & 1) * 192), "r"(8 * b), "r"((par >> 1) * 112 + (rem - par * 14) * 8) : "memory");
        }
        __syncwarp();
        TRB(it, 2);
      }
    }
    for (int n = blockIdx.x + lane * step; n < NTB; n += 32 * step) g_flags[n] = 0;
  } else {
    const int wg = warp >> 2, w = warp & 3;
    constexpr uint64_t db = mkdesc(SBC + SM_B_W, 12288, 512, 2);
    const uint32_t st = sb + SM_B_ST + warp * 6144;
    const uint32_t sta = st + (lane & 15) * 128 + (((lane >> 4) ^ (lane & 7)) * 16);
    mbar_wait(bar + 2 * NSTB * 8, 0);
    TRB(47, 1);
    int it = wg;
#pragma unroll 1
    for (int n = blockIdx.x + wg * step; n < NTB; n += 2 * step, it += 2) {
      const int b = n / 56, rem = n - b * 56, par = rem / 14, sg = it & (NSTB - 1);
      const uint64_t da = mkdesc(SBC + SM_B_IN, 128, 3072, 0) + sg * (24576 / 16);
      float D[96];
      mbar_wait(bar + sg * 8, (it / NSTB) & 1);
      TRB(it, 3);
      wg_fence();
      wg_ss192<0>(D, da, db);
#pragma unroll
      for (int k = 1; k < 12; k++) wg_ss192<1>(D, da + k * 16, db + k * 64);
      wg_commit();
      TRB(it, 4);
      if (lane == 0) asm volatile("cp.async.bulk.wait_group.read 0;" ::: "memory");
      __syncwarp();
      wg_wait<0>(); pin(D);
      mbar_arrive_elect(bar + (NSTB + sg) * 8);
      TRB(it, 5);
#pragma unroll
      for (int q = 0; q < 12; q++)
        stsm4((sta ^ ((q & 3) * 32)) + (q >> 2) * 2048,
              pack2(D[8 * q], D[8 * q + 1]), pack2(D[8 * q + 2], D[8 * q + 3]), pack2(D[8 * q + 4], D[8 * q + 5]), pack2(D[8 * q + 6], D[8 * q + 7]));
      fence_async();
      __syncwarp();
      if (lane == 0) {
        asm volatile("cp.async.bulk.tensor.4d.global.shared::cta.bulk_group [%0, {%2,%3,%4,%5}], [%1];"
                     ::"l"(&mp.oo), "r"(st), "r"(0), "r"(8 * b), "r"((par >> 1) * 112 + (rem - par * 14) * 8 + 2 * w), "r"((par & 1) * 3) : "memory");
        asm volatile("cp.async.bulk.commit_group;" ::: "memory");
      }
      TRB(it, 6);
    }
    if (lane == 0) asm volatile("cp.async.bulk.wait_group 0;" ::: "memory");
    TR2(132 + blockIdx.x, 2);
  }
}

typedef CUresult (*EncodeFn)(CUtensorMap*, CUtensorMapDataType, cuuint32_t, void*, const cuuint64_t*, const cuuint64_t*, const cuuint32_t*,
                             const cuuint32_t*, CUtensorMapInterleave, CUtensorMapSwizzle, CUtensorMapL2promotion, CUtensorMapFloatOOBfill);
static EncodeFn g_enc = nullptr;
static void make_map(CUtensorMap* m, const void* p, int rank, const cuuint64_t* dim, const cuuint64_t* str, const cuuint32_t* box, CUtensorMapSwizzle sw) {
  const cuuint32_t ones[5] = {1, 1, 1, 1, 1};
  g_enc(m, CU_TENSOR_MAP_DATA_TYPE_BFLOAT16, rank, (void*)p, dim, str, box, ones, CU_TENSOR_MAP_INTERLEAVE_NONE, sw,
        CU_TENSOR_MAP_L2_PROMOTION_L2_128B, CU_TENSOR_MAP_FLOAT_OOB_FILL_NONE);
}

extern "C" void kernel_launch(void* const* d_in, const int* in_sizes, int n_in, void* d_out, int out_size) {
  const __nv_bfloat16* x = (const __nv_bfloat16*)d_in[0];
  const __nv_bfloat16* wqkv = (const __nv_bfloat16*)d_in[1];
  const __nv_bfloat16* wo = (const __nv_bfloat16*)d_in[2];
  const __nv_bfloat16* rpb = (const __nv_bfloat16*)d_in[3];

  if (!g_enc) {
    void* fn = nullptr; cudaDriverEntryPointQueryResult qr;
    cudaGetDriverEntryPoint("cuTensorMapEncodeTiled", &fn, cudaEnableDefault, &qr);
    g_enc = (EncodeFn)fn;
    cudaFuncSetAttribute(na_attn_kernel, cudaFuncAttributeMaxDynamicSharedMemorySize, SM_A_TOTAL);
    cudaFuncSetAttribute(na_proj_kernel, cudaFuncAttributeMaxDynamicSharedMemorySize, SM_B_TOTAL);
  }
  Maps ma; MapsB mb;
  { cuuint64_t dim[4] = {64, 112, 224, 6}, str[3] = {(cuuint64_t)ROWB, 768, 128};
    cuuint32_t box[4] = {64, 4, 16, 3}, boxo[4] = {64, 8, 2, 3};
    make_map(&ma.xc, x, 4, dim, str, box, CU_TENSOR_MAP_SWIZZLE_128B);
    make_map(&mb.oo, d_out, 4, dim, str, boxo, CU_TENSOR_MAP_SWIZZLE_128B); }
  { cuuint64_t dim[5] = {64, 112, 224, 2, 6}, str[4] = {(cuuint64_t)ROWB, 768, 19 * 768, 128};
    cuuint32_t box[5] = {64, 8, 3, 2, 3};
    make_map(&ma.xh, x, 5, dim, str, box, CU_TENSOR_MAP_SWIZZLE_128B); }
  { cuuint64_t dim[3] = {384, 112, 224}, str[2] = {(cuuint64_t)ROWB, 768};
    cuuint32_t box[3] = {192, 8, 8}, boxs[3] = {192, 2, 8};
    make_map(&mb.oi, d_out, 3, dim, str, box, CU_TENSOR_MAP_SWIZZLE_NONE);
    make_map(&ma.os, d_out, 3, dim, str, boxs, CU_TENSOR_MAP_SWIZZLE_NONE); }
  { cuuint64_t dim[4] = {32, 112, 224, 12}, str[3] = {(cuuint64_t)ROWB, 768, 64};
    cuuint32_t box[4] = {32, 8, 2, 3};
    make_map(&ma.ot, d_out, 4, dim, str, box, CU_TENSOR_MAP_SWIZZLE_64B); }
  { cuuint64_t dim[2] = {576, 192}, str[1] = {1152};
    cuuint32_t box[2] = {16, 192};
    make_map(&ma.w, wqkv, 2, dim, str, box, CU_TENSOR_MAP_SWIZZLE_32B); }
  { cuuint64_t dim[3] = {32, 192, 6}, str[2] = {384, 64};
    cuuint32_t box[3] = {32, 192, 3};
    make_map(&ma.wo, wo, 3, dim, str, box, CU_TENSOR_MAP_SWIZZLE_64B);
    mb.wo = ma.wo; }
  na_attn_kernel<<<112, 512, SM_A_TOTAL>>>(ma, wqkv, rpb);
  cudaLaunchConfig_t cfg = {};
  cfg.gridDim = dim3(20); cfg.blockDim = dim3(288); cfg.dynamicSmemBytes = SM_B_TOTAL; cfg.stream = cudaStreamPerThread;
  cudaLaunchAttribute at[1];
  at[0].id = cudaLaunchAttributeProgrammaticStreamSerialization; at[0].val.programmaticStreamSerializationAllowed = 1;
  cfg.attrs = at; cfg.numAttrs = 1;
  cudaLaunchKernelEx(&cfg, na_proj_kernel, mb);
}
```

```cpp
#include <cuda_runtime.h>
#include <cuda_bf16.h>
#include <cuda.h>
#include <stdint.h>

#define SPIN_LIMIT (1u << 18)

__device__ __forceinline__ uint32_t smem_u32(const void* p) { return (uint32_t)__cvta_generic_to_shared(p); }
__device__ __forceinline__ void wg_fence() { asm volatile("wgmma.fence.sync.aligned;" ::: "memory"); }
__device__ __forceinline__ void wg_commit() { asm volatile("wgmma.commit_group.sync.aligned;" ::: "memory"); }
template <int N> __device__ __forceinline__ void wg_wait() { asm volatile("wgmma.wait_group.sync.aligned %0;" ::"n"(N) : "memory"); }
template <int N> __device__ __forceinline__ void pin(float (&d)[N]) {
#pragma unroll
  for (int i = 0; i < N; i++) asm volatile("" : "+f"(d[i])::"memory");
}
__host__ __device__ constexpr uint64_t mkdesc(uint32_t addr, uint32_t lbo, uint32_t sbo, uint32_t sw) {
  return (uint64_t)((addr & 0x3FFFF) >> 4) | ((uint64_t)(lbo >> 4) << 16) | ((uint64_t)(sbo >> 4) << 32) | ((uint64_t)sw << 62);
}
__device__ __forceinline__ void mbar_init(uint32_t bar, uint32_t cnt) { asm volatile("mbarrier.init.shared::cta.b64 [%0], %1;" ::"r"(bar), "r"(cnt) : "memory"); }
__device__ __forceinline__ void mbar_arrive(uint32_t bar) { asm volatile("mbarrier.arrive.shared::cta.b64 _, [%0];" ::"r"(bar) : "memory"); }
__device__ __forceinline__ bool elect_one() {
  uint32_t r; asm volatile("{\n.reg .pred p;\nelect.sync _|p, 0xffffffff;\nselp.u32 %0, 1, 0, p;\n}" : "=r"(r)); return r;
}
__device__ __forceinline__ void mbar_arrive_elect(uint32_t bar) {
  asm volatile("{\n.reg .pred p;\nelect.sync _|p, 0xffffffff;\n@p mbarrier.arrive.shared::cta.b64 _, [%0];\n}" ::"r"(bar) : "memory");
}
__device__ __forceinline__ void mbar_expect(uint32_t bar, uint32_t bytes) { asm volatile("mbarrier.arrive.expect_tx.shared::cta.b64 _, [%0], %1;" ::"r"(bar), "r"(bytes) : "memory"); }
__device__ __forceinline__ void mbar_arrive_remote(uint32_t bar, uint32_t cta) {
  asm volatile("{\n.reg .b32 ra;\nmapa.shared::cluster.u32 ra, %0, %1;\nmbarrier.arrive.shared::cluster.b64 _, [ra];\n}" ::"r"(bar), "r"(cta) : "memory");
}
__device__ __forceinline__ void mbar_wait(uint32_t bar, uint32_t parity) {
  asm volatile("{\n.reg .pred p;\n.reg .b32 n;\nmov.b32 n, 0;\nWL:\nmbarrier.try_wait.parity.shared::cta.b64 p, [%0], %1;\n@p bra WD;\n"
               "add.u32 n, n, 1;\nsetp.lt.u32 p, n, 65536;\n@p bra WL;\nWD:\n}" ::"r"(bar), "r"(parity) : "memory");
}
__device__ __forceinline__ void nb_sync(int id, int n) { asm volatile("bar.sync %0, %1;" ::"r"(id), "r"(n) : "memory"); }
__device__ __forceinline__ void nb_arrive(int id, int n) { asm volatile("bar.arrive %0, %1;" ::"r"(id), "r"(n) : "memory"); }
__device__ __forceinline__ void fence_async() { asm volatile("fence.proxy.async.shared::cta;" ::: "memory"); }
__device__ __forceinline__ void cluster_sync() {
  asm volatile("barrier.cluster.arrive.relaxed.aligned;\nbarrier.cluster.wait.aligned;" ::: "memory");
}
__device__ __forceinline__ uint32_t pack2(float lo, float hi) {
  uint32_t r; asm("cvt.rn.bf16x2.f32 %0, %1, %2;" : "=r"(r) : "f"(hi), "f"(lo)); return r;
}
__device__ __forceinline__ void stsm4(uint32_t a, uint32_t r0, uint32_t r1, uint32_t r2, uint32_t r3) {
  asm volatile("stmatrix.sync.aligned.m8n8.x4.shared.b16 [%0], {%1,%2,%3,%4};" ::"r"(a), "r"(r0), "r"(r1), "r"(r2), "r"(r3) : "memory");
}
__device__ __forceinline__ void ldsm4(uint32_t a, uint32_t& r0, uint32_t& r1, uint32_t& r2, uint32_t& r3) {
  asm volatile("ldmatrix.sync.aligned.m8n8.x4.shared.b16 {%0,%1,%2,%3}, [%4];" : "=r"(r0), "=r"(r1), "=r"(r2), "=r"(r3) : "r"(a) : "memory");
}
__device__ __forceinline__ void sts128(uint32_t a, uint4 v) {
  asm volatile("st.shared.v4.b32 [%0], {%1,%2,%3,%4};" ::"r"(a), "r"(v.x), "r"(v.y), "r"(v.z), "r"(v.w) : "memory");
}
__device__ __forceinline__ float lds_f32(uint32_t a) { float v; asm volatile("ld.shared.f32 %0, [%1];" : "=f"(v) : "r"(a)); return v; }
__device__ __forceinline__ float ex2(float x) { float y; asm("ex2.approx.ftz.f32 %0, %1;" : "=f"(y) : "f"(x)); return y; }

template<int SC> __device__ __forceinline__ void wg_ss144(float (&d)[72], uint64_t da, uint64_t db) {
  asm volatile("{\n.reg .pred p;\nsetp.ne.b32 p, %74, 0;\nwgmma.mma_async.sync.aligned.m64n144k16.f32.bf16.bf16 {%0,%1,%2,%3,%4,%5,%6,%7,%8,%9,%10,%11,%12,%13,%14,%15,%16,%17,%18,%19,%20,%21,%22,%23,%24,%25,%26,%27,%28,%29,%30,%31,%32,%33,%34,%35,%36,%37,%38,%39,%40,%41,%42,%43,%44,%45,%46,%47,%48,%49,%50,%51,%52,%53,%54,%55,%56,%57,%58,%59,%60,%61,%62,%63,%64,%65,%66,%67,%68,%69,%70,%71}, %72, %73, p, 1, 1, 0, 1;\n}\n"
    : "+f"(d[0]),"+f"(d[1]),"+f"(d[2]),"+f"(d[3]),"+f"(d[4]),"+f"(d[5]),"+f"(d[6]),"+f"(d[7]),"+f"(d[8]),"+f"(d[9]),"+f"(d[10]),"+f"(d[11]),"+f"(d[12]),"+f"(d[13]),"+f"(d[14]),"+f"(d[15]),"+f"(d[16]),"+f"(d[17]),"+f"(d[18]),"+f"(d[19]),"+f"(d[20]),"+f"(d[21]),"+f"(d[22]),"+f"(d[23]),"+f"(d[24]),"+f"(d[25]),"+f"(d[26]),"+f"(d[27]),"+f"(d[28]),"+f"(d[29]),"+f"(d[30]),"+f"(d[31]),"+f"(d[32]),"+f"(d[33]),"+f"(d[34]),"+f"(d[35]),"+f"(d[36]),"+f"(d[37]),"+f"(d[38]),"+f"(d[39]),"+f"(d[40]),"+f"(d[41]),"+f"(d[42]),"+f"(d[43]),"+f"(d[44]),"+f"(d[45]),"+f"(d[46]),"+f"(d[47]),"+f"(d[48]),"+f"(d[49]),"+f"(d[50]),"+f"(d[51]),"+f"(d[52]),"+f"(d[53]),"+f"(d[54]),"+f"(d[55]),"+f"(d[56]),"+f"(d[57]),"+f"(d[58]),"+f"(d[59]),"+f"(d[60]),"+f"(d[61]),"+f"(d[62]),"+f"(d[63]),"+f"(d[64]),"+f"(d[65]),"+f"(d[66]),"+f"(d[67]),"+f"(d[68]),"+f"(d[69]),"+f"(d[70]),"+f"(d[71]) : "l"(da), "l"(db), "n"(SC));
}
template<int SC> __device__ __forceinline__ void wg_ss96(float (&d)[48], uint64_t da, uint64_t db) {
  asm volatile("{\n.reg .pred p;\nsetp.ne.b32 p, %50, 0;\nwgmma.mma_async.sync.aligned.m64n96k16.f32.bf16.bf16 {%0,%1,%2,%3,%4,%5,%6,%7,%8,%9,%10,%11,%12,%13,%14,%15,%16,%17,%18,%19,%20,%21,%22,%23,%24,%25,%26,%27,%28,%29,%30,%31,%32,%33,%34,%35,%36,%37,%38,%39,%40,%41,%42,%43,%44,%45,%46,%47}, %48, %49, p, 1, 1, 0, 1;\n}\n"
    : "+f"(d[0]),"+f"(d[1]),"+f"(d[2]),"+f"(d[3]),"+f"(d[4]),"+f"(d[5]),"+f"(d[6]),"+f"(d[7]),"+f"(d[8]),"+f"(d[9]),"+f"(d[10]),"+f"(d[11]),"+f"(d[12]),"+f"(d[13]),"+f"(d[14]),"+f"(d[15]),"+f"(d[16]),"+f"(d[17]),"+f"(d[18]),"+f"(d[19]),"+f"(d[20]),"+f"(d[21]),"+f"(d[22]),"+f"(d[23]),"+f"(d[24]),"+f"(d[25]),"+f"(d[26]),"+f"(d[27]),"+f"(d[28]),"+f"(d[29]),"+f"(d[30]),"+f"(d[31]),"+f"(d[32]),"+f"(d[33]),"+f"(d[34]),"+f"(d[35]),"+f"(d[36]),"+f"(d[37]),"+f"(d[38]),"+f"(d[39]),"+f"(d[40]),"+f"(d[41]),"+f"(d[42]),"+f"(d[43]),"+f"(d[44]),"+f"(d[45]),"+f"(d[46]),"+f"(d[47]) : "l"(da), "l"(db), "n"(SC));
}
template<int SC> __device__ __forceinline__ void wg_rs112(float (&d)[56], uint32_t a0, uint32_t a1, uint32_t a2, uint32_t a3, uint64_t db) {
  asm volatile("{\n.reg .pred p;\nsetp.ne.b32 p, %61, 0;\nwgmma.mma_async.sync.aligned.m64n112k16.f32.bf16.bf16 {%0,%1,%2,%3,%4,%5,%6,%7,%8,%9,%10,%11,%12,%13,%14,%15,%16,%17,%18,%19,%20,%21,%22,%23,%24,%25,%26,%27,%28,%29,%30,%31,%32,%33,%34,%35,%36,%37,%38,%39,%40,%41,%42,%43,%44,%45,%46,%47,%48,%49,%50,%51,%52,%53,%54,%55}, {%56,%57,%58,%59}, %60, p, 1, 1, 0;\n}\n"
    : "+f"(d[0]),"+f"(d[1]),"+f"(d[2]),"+f"(d[3]),"+f"(d[4]),"+f"(d[5]),"+f"(d[6]),"+f"(d[7]),"+f"(d[8]),"+f"(d[9]),"+f"(d[10]),"+f"(d[11]),"+f"(d[12]),"+f"(d[13]),"+f"(d[14]),"+f"(d[15]),"+f"(d[16]),"+f"(d[17]),"+f"(d[18]),"+f"(d[19]),"+f"(d[20]),"+f"(d[21]),"+f"(d[22]),"+f"(d[23]),"+f"(d[24]),"+f"(d[25]),"+f"(d[26]),"+f"(d[27]),"+f"(d[28]),"+f"(d[29]),"+f"(d[30]),"+f"(d[31]),"+f"(d[32]),"+f"(d[33]),"+f"(d[34]),"+f"(d[35]),"+f"(d[36]),"+f"(d[37]),"+f"(d[38]),"+f"(d[39]),"+f"(d[40]),"+f"(d[41]),"+f"(d[42]),"+f"(d[43]),"+f"(d[44]),"+f"(d[45]),"+f"(d[46]),"+f"(d[47]),"+f"(d[48]),"+f"(d[49]),"+f"(d[50]),"+f"(d[51]),"+f"(d[52]),"+f"(d[53]),"+f"(d[54]),"+f"(d[55]) : "r"(a0), "r"(a1), "r"(a2), "r"(a3), "l"(db), "n"(SC));
}
template<int SC> __device__ __forceinline__ void wg_sp48(float (&d)[24], uint32_t a0, uint32_t a1, uint32_t a2, uint32_t a3, uint64_t db, uint32_t meta) {
  asm volatile("{\n.reg .pred p;\nsetp.ne.b32 p, %30, 0;\nwgmma.mma_async.sp.sync.aligned.m64n48k32.f32.bf16.bf16 {%0,%1,%2,%3,%4,%5,%6,%7,%8,%9,%10,%11,%12,%13,%14,%15,%16,%17,%18,%19,%20,%21,%22,%23}, {%24,%25,%26,%27}, %28, %29, 0, p, 1, 1, 1;\n}\n"
    : "+f"(d[0]),"+f"(d[1]),"+f"(d[2]),"+f"(d[3]),"+f"(d[4]),"+f"(d[5]),"+f"(d[6]),"+f"(d[7]),"+f"(d[8]),"+f"(d[9]),"+f"(d[10]),"+f"(d[11]),"+f"(d[12]),"+f"(d[13]),"+f"(d[14]),"+f"(d[15]),"+f"(d[16]),"+f"(d[17]),"+f"(d[18]),"+f"(d[19]),"+f"(d[20]),"+f"(d[21]),"+f"(d[22]),"+f"(d[23]) : "r"(a0), "r"(a1), "r"(a2), "r"(a3), "l"(db), "r"(meta), "n"(SC));
}
template<int SC> __device__ __forceinline__ void wg_ss192(float (&d)[96], uint64_t da, uint64_t db) {
  asm volatile("{\n.reg .pred p;\nsetp.ne.b32 p, %98, 0;\nwgmma.mma_async.sync.aligned.m64n192k16.f32.bf16.bf16 {%0,%1,%2,%3,%4,%5,%6,%7,%8,%9,%10,%11,%12,%13,%14,%15,%16,%17,%18,%19,%20,%21,%22,%23,%24,%25,%26,%27,%28,%29,%30,%31,%32,%33,%34,%35,%36,%37,%38,%39,%40,%41,%42,%43,%44,%45,%46,%47,%48,%49,%50,%51,%52,%53,%54,%55,%56,%57,%58,%59,%60,%61,%62,%63,%64,%65,%66,%67,%68,%69,%70,%71,%72,%73,%74,%75,%76,%77,%78,%79,%80,%81,%82,%83,%84,%85,%86,%87,%88,%89,%90,%91,%92,%93,%94,%95}, %96, %97, p, 1, 1, 0, 1;\n}\n"
    : "+f"(d[0]),"+f"(d[1]),"+f"(d[2]),"+f"(d[3]),"+f"(d[4]),"+f"(d[5]),"+f"(d[6]),"+f"(d[7]),"+f"(d[8]),"+f"(d[9]),"+f"(d[10]),"+f"(d[11]),"+f"(d[12]),"+f"(d[13]),"+f"(d[14]),"+f"(d[15]),"+f"(d[16]),"+f"(d[17]),"+f"(d[18]),"+f"(d[19]),"+f"(d[20]),"+f"(d[21]),"+f"(d[22]),"+f"(d[23]),"+f"(d[24]),"+f"(d[25]),"+f"(d[26]),"+f"(d[27]),"+f"(d[28]),"+f"(d[29]),"+f"(d[30]),"+f"(d[31]),"+f"(d[32]),"+f"(d[33]),"+f"(d[34]),"+f"(d[35]),"+f"(d[36]),"+f"(d[37]),"+f"(d[38]),"+f"(d[39]),"+f"(d[40]),"+f"(d[41]),"+f"(d[42]),"+f"(d[43]),"+f"(d[44]),"+f"(d[45]),"+f"(d[46]),"+f"(d[47]),"+f"(d[48]),"+f"(d[49]),"+f"(d[50]),"+f"(d[51]),"+f"(d[52]),"+f"(d[53]),"+f"(d[54]),"+f"(d[55]),"+f"(d[56]),"+f"(d[57]),"+f"(d[58]),"+f"(d[59]),"+f"(d[60]),"+f"(d[61]),"+f"(d[62]),"+f"(d[63]),"+f"(d[64]),"+f"(d[65]),"+f"(d[66]),"+f"(d[67]),"+f"(d[68]),"+f"(d[69]),"+f"(d[70]),"+f"(d[71]),"+f"(d[72]),"+f"(d[73]),"+f"(d[74]),"+f"(d[75]),"+f"(d[76]),"+f"(d[77]),"+f"(d[78]),"+f"(d[79]),"+f"(d[80]),"+f"(d[81]),"+f"(d[82]),"+f"(d[83]),"+f"(d[84]),"+f"(d[85]),"+f"(d[86]),"+f"(d[87]),"+f"(d[88]),"+f"(d[89]),"+f"(d[90]),"+f"(d[91]),"+f"(d[92]),"+f"(d[93]),"+f"(d[94]),"+f"(d[95]) : "l"(da), "l"(db), "n"(SC));
}

constexpr uint32_t SBC = 1024;
constexpr int ROWB = 2 * 224 * 384;
constexpr int TB = 12;
constexpr int KS = 832;
constexpr int KSLOT = 22 * KS;
constexpr int SM_X0 = 0;
constexpr int SM_X1 = 18432;
constexpr int SM_X2 = SM_X1 + 24576;
constexpr int SM_W = SM_X2 + 24576;
constexpr int SM_K = SM_W + 55296;
constexpr int SM_V = SM_K + 2 * KSLOT;
constexpr int SM_Q = SM_V + 22 * 1536;
constexpr int SM_O = SM_Q + 24576;
constexpr int SM_RPB = SM_O + 12288;
constexpr int SM_BAR = SM_RPB + 768;
constexpr int SM_A_TOTAL = SM_BAR + 256;
constexpr int SM_TWO = SM_X1;
constexpr int SM_TST = SM_TWO + 36864;
constexpr int SM_TIN = SM_W;
enum { B_FULL = 0, B_EMPTY = 3, B_TIN = 6, B_TFREE = 8, B_WK = 10, B_WQ, B_WO, B_Q0, B_ODONE, B_KFREE = B_ODONE + 2, B_VFREE, B_COUNT };
enum { N_KRDY = 4, N_QK0, N_QK1, N_VQ0, N_VQ1, N_PVISS };

#define SPL 4
#define RA 152
#define RG 184
__device__ int g_flags[TB * 56];

#define TR(role, it, k)
#define TRDECL
#define TRARG
#define TRPASS
#define TRDUMP
#define TRB(it, k)
#define TR2(blk, k)

struct GemmCtx {
  uint32_t bar;
  uint32_t kC, vC, qC;
  uint32_t kH, vH;
  bool hvalid;
};

template <int STRIDE> __device__ __forceinline__ void dump12(uint32_t a, const uint32_t (&r)[12]) {
#pragma unroll
  for (int j = 0; j < 3; j++) stsm4(a + j * 2 * STRIDE, r[4 * j], r[4 * j + 1], r[4 * j + 2], r[4 * j + 3]);
}
template <int N> __device__ __forceinline__ void pack12(uint32_t (&r)[12], const float (&d)[N], int off) {
#pragma unroll
  for (int j = 0; j < 12; j++) r[j] = pack2(d[off + 2 * j], d[off + 2 * j + 1]);
}
template <int XS, int K0, int K1> __device__ __forceinline__ void issue_core(float (&d)[72]) {
  constexpr uint64_t da = mkdesc(SBC + XS, 16, 1024, 1), db = mkdesc(SBC + SM_W, 6144, 256, 3);
  wg_fence();
  if (K0 == 0) wg_ss144<0>(d, da, db);
#pragma unroll
  for (int k = K0 ? K0 : 1; k < K1; k++) wg_ss144<1>(d, da + (k >> 2) * 512 + (k & 3) * 2, db + k * 32);
  wg_commit();
}
template <int K0, int K1> __device__ __forceinline__ void issue_halo(float (&d)[48]) {
  constexpr uint64_t da = mkdesc(SBC + SM_X0, 16, 1024, 1), db = mkdesc(SBC + SM_W, 6144, 256, 3);
  wg_fence();
  if (K0 == 0) wg_ss96<0>(d, da, db);
#pragma unroll
  for (int k = K0 ? K0 : 1; k < K1; k++) wg_ss96<1>(d, da + (k >> 2) * 384 + (k & 3) * 2, db + k * 32);
  wg_commit();
}
template <int ST, int BYTES> __device__ __forceinline__ void release_stage(const GemmCtx& c, bool on) {
  asm volatile("{\n.reg .pred p, q;\n.reg .b32 ra;\nsetp.ne.b32 q, %2, 0;\nelect.sync _|p, 0xffffffff;\nand.pred p, p, q;\n"
               "mapa.shared::cluster.u32 ra, %1, %4;\n"
               "@p mbarrier.arrive.expect_tx.shared::cta.b64 _, [%0], %3;\n@p mbarrier.arrive.shared::cluster.b64 _, [ra];\n}"
               ::"r"(c.bar + (B_FULL + ST) * 8), "r"(c.bar + (B_EMPTY + ST) * 8), "r"((int)on), "n"(BYTES / 4), "n"(ST) : "memory");
}
__device__ __forceinline__ void load_w(const CUtensorMap* m, uint32_t dst, uint32_t bar, int col) {
  asm volatile("cp.async.bulk.tensor.2d.shared::cluster.global.mbarrier::complete_tx::bytes [%0], [%1, {%3,%4}], [%2];"
               ::"r"(dst), "l"(m), "r"(bar), "r"(col), "r"(0) : "memory");
}
__device__ __forceinline__ void publish(uint32_t bar) {
  fence_async();
  __syncwarp();
  mbar_arrive_elect(bar);
}

template <bool FIRST, bool LAST>
__device__ __forceinline__ void gemm_iter(const GemmCtx& c, int b, uint32_t (&pk)[12], uint32_t (&pv)[12], uint32_t (&pq)[12], int head TRARG) {
  const uint32_t bar = c.bar;
  const uint32_t pa = b & 1;
  const bool w = b >= 0;
  const uint32_t ko = pa * KSLOT, vx = pa * 16, qx = pa * 128;
  float H[48], C[72];
  uint32_t hk[12], hv[12], pv2[12];
  TR(2, b, 0);
  if (FIRST) mbar_wait(bar + (B_FULL + 0) * 8, pa);
  else if (!LAST) mbar_wait(bar + (B_FULL + 2) * 8, pa);
  TR(2, b, 13);
  if (w) nb_sync(N_QK1, 256);
  TR(2, b, 2);
  issue_halo<0, 8>(H);
  TR(2, b, 3);
  if (!FIRST) {
    if (w) mbar_wait(bar + B_KFREE * 8, pa);
    dump12<128>(c.kC + ko, pk);
  }
  issue_halo<8, 12>(H);
  TR(2, b, 4);
  if (!LAST) {
    if (FIRST) { mbar_wait(bar + (B_FULL + 2) * 8, pa); mbar_wait(bar + B_WQ * 8, 0); }
    issue_core<SM_X2, 0, 8>(C);
    TR(2, b, 5);
    if (!FIRST) { fence_async(); dump12<256>(c.qC ^ (qx ^ 192), pq); }
    wg_wait<1>(); pin(H);
    release_stage<0, 18432>(c, true);
  } else {
    dump12<256>(c.qC ^ (qx ^ 192), pq);
    fence_async();
    nb_arrive(N_VQ0, 288); nb_arrive(N_VQ1, 288);
    wg_wait<0>(); pin(H);
    uint32_t ln; asm volatile("mov.u32 %0, %%laneid;" : "=r"(ln));
    if (ln < 4) mbar_arrive_remote(bar + (B_TFREE + (head >> 1)) * 8, ln);
  }
  pack12(hk, H, 0);
  if (c.hvalid) dump12<128>(c.kH + ko, hk);
  pack12(hv, H, 24);
  if (!LAST) {
    issue_core<SM_X2, 8, 12>(C);
    if (w) { nb_arrive(N_VQ0, 288); nb_arrive(N_VQ1, 288); }
    else if (!FIRST) { __syncwarp(); mbar_arrive_elect(bar + B_Q0 * 8); }
    mbar_wait(bar + (B_FULL + 1) * 8, pa);
    TR(2, b, 6);
    wg_wait<0>(); pin(C);
    TR(2, b, 7);
    pack12(pk, C, 0);
    dump12<128>(c.kC + ko + 64, pk);
    release_stage<2, 24576>(c, b < 11);
    pack12(pv2, C, 24);
    pack12(pq, C, 48);
    TR(2, b, 8);
    issue_core<SM_X1, 0, SPL>(C);
    if (w) nb_sync(N_PVISS, 384);
    issue_core<SM_X1, SPL, 12>(C);
    TR(2, b, 9);
  }
  if (!FIRST) { fence_async(); nb_arrive(N_KRDY, 256); }
  TR(2, b, 1);
  if (!LAST) mbar_wait(bar + (B_FULL + 0) * 8, pa ^ 1);
  if (w) mbar_wait(bar + B_VFREE * 8, pa);
  TR(2, b, 10);
  if (!FIRST) dump12<128>(c.vC ^ vx, pv);
  if (!LAST) dump12<256>(c.qC ^ qx, pq);
  if (c.hvalid) dump12<128>(c.vH ^ vx, hv);
  if (LAST) { fence_async(); nb_arrive(N_VQ0, 288); nb_arrive(N_VQ1, 288); return; }
  dump12<128>((c.vC ^ vx ^ 16) + 768, pv2);
  TR(2, b, 11);
  wg_wait<0>(); pin(C);
  TR(2, b, 12);
  release_stage<1, 24576>(c, b < 11);
  pack12(pk, C, 0);
  pack12(pv, C, 24);
  pack12(pq, C, 48);
}

__device__ __forceinline__ float fold(float a, float b, float t, int useb) {
  float r;
  asm("{\n.reg .pred p;\nsetp.ne.b32 p, %4, 0;\nfma.rn.f32 %0, %1, 0f3E553B95, %3;\n@p fma.rn.f32 %0, %2, 0f3E553B95, %3;\n}"
      : "=&f"(r) : "f"(a), "f"(b), "f"(t), "r"(useb));
  return r;
}
template <int U, int L, bool BORDER>
__device__ __forceinline__ void softmax_tile(const float (&SA)[56], const float (&SB)[56], const float (&T)[14], int b0, int b1,
                                             uint32_t ra0, uint32_t ra1, int qcu, uint32_t (&P)[28], float (&sx)[8]) {
  float lu[14], ll[14];
#pragma unroll
  for (int j = 0; j < 7; j++) {
    float tu0, tu1, tl0, tl1;
    if (BORDER) {
      tu0 = lds_f32(ra0 + (U + j + 3 - qcu) * 4); tu1 = lds_f32(ra1 + (U + j + 3 - qcu) * 4);
      tl0 = lds_f32(ra0 + (L + j + 2 - qcu) * 4); tl1 = lds_f32(ra1 + (L + j + 2 - qcu) * 4);
    } else { tu0 = tl0 = T[2 * j]; tu1 = tl1 = T[2 * j + 1]; }
    lu[2 * j]     = fold(SA[4 * (U + j)],     SB[4 * (U + j)],     tu0, b0);
    ll[2 * j]     = fold(SA[4 * (L + j) + 2], SB[4 * (L + j) + 2], tl0, b0);
    lu[2 * j + 1] = fold(SA[4 * (U + j) + 1], SB[4 * (U + j) + 1], tu1, b1);
    ll[2 * j + 1] = fold(SA[4 * (L + j) + 3], SB[4 * (L + j) + 3], tl1, b1);
  }
  float mu = lu[0], ml = ll[0], mu2 = lu[1], ml2 = ll[1];
#pragma unroll
  for (int j = 1; j < 7; j++) { mu = fmaxf(mu, lu[2 * j]); mu2 = fmaxf(mu2, lu[2 * j + 1]); ml = fmaxf(ml, ll[2 * j]); ml2 = fmaxf(ml2, ll[2 * j + 1]); }
  mu = fmaxf(mu, mu2); ml = fmaxf(ml, ml2);
  { const float a1 = __shfl_xor_sync(0xffffffffu, mu, 1), a2 = __shfl_xor_sync(0xffffffffu, mu, 2), a3 = __shfl_xor_sync(0xffffffffu, mu, 3);
    const float c1 = __shfl_xor_sync(0xffffffffu, ml, 1), c2 = __shfl_xor_sync(0xffffffffu, ml, 2), c3 = __shfl_xor_sync(0xffffffffu, ml, 3);
    mu = fmaxf(fmaxf(mu, a1), fmaxf(a2, a3)); ml = fmaxf(fmaxf(ml, c1), fmaxf(c2, c3)); }
  float su = 0.f, sl = 0.f;
#pragma unroll
  for (int c = 0; c < 14; c++) {
    const int iu = (c >> 1) * 4 + (c & 1) * 2;
    if (c >= U && c < U + 7) {
      float e0 = ex2(lu[2 * (c - U)] - mu), e1 = ex2(lu[2 * (c - U) + 1] - mu);
      su = c == U ? e0 + e1 : (su + e0) + e1; P[iu] = pack2(e0, e1);
    } else P[iu] = 0u;
    if (c >= L && c < L + 7) {
      float e0 = ex2(ll[2 * (c - L)] - ml), e1 = ex2(ll[2 * (c - L) + 1] - ml);
      sl = c == L ? e0 + e1 : (sl + e0) + e1; P[iu + 1] = pack2(e0, e1);
    } else P[iu + 1] = 0u;
  }
  sx[0] = su; sx[4] = sl;
#pragma unroll
  for (int k = 1; k < 4; k++) { sx[k] = __shfl_xor_sync(0xffffffffu, su, k); sx[4 + k] = __shfl_xor_sync(0xffffffffu, sl, k); }
}

struct Maps { CUtensorMap xc, xh, w, os, wo, ot; };

__global__ void __cluster_dims__(4, 1, 1) __launch_bounds__(512, 1)
na_attn_kernel(const __grid_constant__ Maps mp, const __nv_bfloat16* __restrict__ wqkv, const __nv_bfloat16* __restrict__ rpb) {
  extern __shared__ __align__(1024) uint8_t smem_raw[];
  const uint32_t sb = smem_u32(smem_raw);
  if ((sb & 0x3FFFF) != SBC) return;
  const uint32_t bar = sb + SM_BAR;
  TR2(blockIdx.x, 0);
  const int tid = threadIdx.x, lane = tid & 31;
  const int warp = __shfl_sync(0xffffffffu, tid >> 5, 0);
  const int head = blockIdx.x & 3, cl = blockIdx.x >> 2;
  const int par = cl / 7, strip = cl - par * 7, ph = par >> 1, pw = par & 1;

  uint4 wv[3];
  const int wr = tid / 6, wc = tid - wr * 6;
  if (warp < 12) {
#pragma unroll
    for (int i = 0; i < 3; i++) wv[i] = __ldg(reinterpret_cast<const uint4*>(wqkv + (wr + i * 64) * 576 + 384 + head * 48 + wc * 8));
  } else if (elect_one()) {
    if (warp == 12) {
      mbar_init(bar + B_WK * 8, 1);
#pragma unroll
      for (int i = 0; i < 3; i++) load_w(&mp.w, sb + SM_W + i * 6144, bar + B_WK * 8, 192 + head * 48 + i * 16);
      mbar_expect(bar + B_WK * 8, 18432);
    } else if (warp == 13) {
#pragma unroll
      for (int i = 0; i < B_WK; i++) mbar_init(bar + i * 8, i < B_EMPTY ? 4 : (i < B_TIN ? 16 : (i < B_TFREE ? 1 : 8)));
    } else if (warp == 14) {
#pragma unroll
      for (int i = B_WQ; i < B_COUNT; i++) mbar_init(bar + i * 8, i < B_Q0 ? 1 : (i < B_KFREE ? 4 : 8));
    }
    asm volatile("fence.mbarrier_init.release.cluster;" ::: "memory");
  }
  __syncwarp();
  asm volatile("barrier.cluster.arrive.relaxed.aligned;" ::: "memory");

  if (warp >= 12) {
    asm volatile("setmaxnreg.dec.sync.aligned.u32 24;");
    asm volatile("griddepcontrol.launch_dependents;");
    const int cc = ph * 112 + (head ? strip * 16 : (strip == 0 ? 16 : (strip == 6 ? 74 : strip * 16 - 3)));
    const int sd = strip == 0 ? -1 : (strip == 6 ? 1 : 0);
    const int r0 = head == 0 ? -4 : (head == 1 ? 4 : 0);
    asm volatile("barrier.cluster.wait.aligned;" ::: "memory");
    if (warp == 12) {
      const uint32_t fb = bar + (B_FULL + head) * 8, eb = bar + (B_EMPTY + head) * 8;
      const uint32_t dst = sb + (head == 0 ? SM_X0 : (head == 1 ? SM_X1 : SM_X2));
      const int nl = head == 0 ? 15 : (head == 3 ? 1 : 14);
#pragma unroll 1
      for (int n = 0; n < nl; n++) {
        if (n) mbar_wait(eb, (n - 1) & 1);
        if (elect_one()) {
          if (head == 0) {
            asm volatile("cp.async.bulk.tensor.5d.shared::cluster.global.mbarrier::complete_tx::bytes.multicast::cluster [%0], [%1, {%3,%4,%5,%6,%7}], [%2], %8;"
                         ::"r"(dst), "l"(&mp.xh), "r"(fb), "r"(0), "r"(8 * n + r0), "r"(cc), "r"(sd), "r"(pw * 3), "h"((uint16_t)15) : "memory");
            if (n + 1 < nl) asm volatile("cp.async.bulk.prefetch.tensor.5d.L2.global [%0, {%1,%2,%3,%4,%5}];" ::"l"(&mp.xh), "r"(0), "r"(8 * n + 8 + r0), "r"(cc), "r"(sd), "r"(pw * 3) : "memory");
          } else if (head < 3) {
            asm volatile("cp.async.bulk.tensor.4d.shared::cluster.global.mbarrier::complete_tx::bytes.multicast::cluster [%0], [%1, {%3,%4,%5,%6}], [%2], %7;"
                         ::"r"(dst), "l"(&mp.xc), "r"(fb), "r"(0), "r"(8 * n + r0), "r"(cc), "r"(pw * 3), "h"((uint16_t)15) : "memory");
          }
          if (n == 0) {
#pragma unroll
            for (int i = 0; i < 3; i++) load_w(&mp.w, sb + SM_W + (6 + i) * 6144, bar + B_WQ * 8, head * 48 + i * 16);
            mbar_expect(bar + B_WQ * 8, 18432);
            mbar_expect(bar + B_TIN * 8, 24576); mbar_expect(bar + (B_TIN + 1) * 8, 24576);
          }
          if (head && n + 1 < nl) asm volatile("cp.async.bulk.prefetch.tensor.4d.L2.global [%0, {%1,%2,%3,%4}];" ::"l"(&mp.xc), "r"(0), "r"(8 * n + 8 + r0), "r"(cc), "r"(pw * 3) : "memory");
        }
        __syncwarp();
      }
    }
    if (warp >= 14) {
      const int j = warp - 14;
      int* flag = g_flags + cl * 2 + j;
      nb_arrive(N_VQ0 + j, 288);
#pragma unroll 1
      for (int b = 0; b < TB; b++) {
        mbar_wait(bar + (B_ODONE + j) * 8, b & 1);
        if (lane == 0) {
          asm volatile("cp.async.bulk.tensor.3d.global.shared::cta.bulk_group [%0, {%2,%3,%4}], [%1];"
                       ::"l"(&mp.os), "r"(sb + SM_O + j * 6144), "r"(pw * 192), "r"(8 * b + 2 * head), "r"(ph * 112 + strip * 16 + 8 * j) : "memory");
          asm volatile("cp.async.bulk.commit_group;\ncp.async.bulk.wait_group.read 0;" ::: "memory");
        }
        __syncwarp();
        nb_arrive(N_VQ0 + j, 288);
        if (lane == 0) {
          asm volatile("cp.async.bulk.wait_group 0;\nfence.proxy.async.global;\nred.release.gpu.global.add.s32 [%0], 1;" ::"l"(flag + b * 56) : "memory");
        }
        __syncwarp();
      }
#pragma unroll 1
      for (int i = 0; i < 2; i++) {
        mbar_wait(bar + (B_ODONE + j) * 8, i);
        if (i == 0) { nb_arrive(N_VQ0 + j, 288); mbar_wait(bar + (B_TFREE + j) * 8, 0); }
        if (elect_one()) {
#pragma unroll
          for (int d = 0; d < 2; d++)
            asm volatile("{\n.reg .b32 rd, rb;\nmapa.shared::cluster.u32 rd, %0, %3;\nmapa.shared::cluster.u32 rb, %2, %3;\n"
                         "cp.async.bulk.shared::cluster.shared::cta.mbarrier::complete_tx::bytes [rd], [%1], 6144, [rb];\n}"
                         ::"r"(sb + SM_TIN + i * 24576 + head * 6144), "r"(sb + (i ? SM_Q + j * 12288 : SM_O + j * 6144)), "r"(bar + (B_TIN + i) * 8), "r"(2 * j + d) : "memory");
        }
        __syncwarp();
      }
    }
    cluster_sync();
  } else if (warp >= 8) {
    asm volatile("setmaxnreg.inc.sync.aligned.u32 %0;" ::"n"(RG));
    GemmCtx c;
    c.bar = bar;
    const int gw = warp - 8, tk = gw * 16 + (lane & 15), hi = lane >> 4;
    { const int col = tk >> 2, i = tk & 3;
      c.kC = sb + SM_K + (col + 3) * KS + hi * 128 + i * 16;
      c.vC = sb + SM_V + (col + 3) * 1536 + hi * 128 + (2 * i + ((col + 3) & 1)) * 16;
      c.qC = sb + SM_Q + col * 1536 + hi * 256 + (col & 1) * 64 + i * 16; }
    { const int ci = tk >> 3, kc = ci < 3 ? ci : ci + 16, i = tk & 7; c.hvalid = gw < 3;
      c.kH = sb + SM_K + kc * KS + hi * 128 + i * 16;
      c.vH = sb + SM_V + kc * 1536 + hi * 128 + (i >> 2) * 768 + (2 * (i & 3) + ((kc ^ (i >> 2)) & 1)) * 16; }
    asm volatile("barrier.cluster.wait.aligned;" ::: "memory");
    if (elect_one()) { mbar_expect(bar + B_FULL * 8, 4608); mbar_expect(bar + (B_FULL + 1) * 8, 6144); mbar_expect(bar + (B_FULL + 2) * 8, 6144); }
    __syncwarp();
#pragma unroll
    for (int i = 0; i < 3; i++) sts128(sb + SM_W + (3 + (wc >> 1)) * 6144 + (wr + i * 64) * 32 + ((wc ^ (wr >> 2)) & 1) * 16, wv[i]);
    fence_async();
    asm volatile("bar.sync 1, 384;" ::: "memory");
    mbar_wait(bar + B_WK * 8, 0);
    uint32_t pk[12], pv[12], pq[12];
    TRDECL;
    gemm_iter<true, false>(c, -2, pk, pv, pq, head TRPASS);
#pragma unroll 1
    for (int b = -1; b < 12; b++) gemm_iter<false, false>(c, b, pk, pv, pq, head TRPASS);
    asm volatile("bar.sync 2, 128;" ::: "memory");
    if (gw == 0 && elect_one()) {
      mbar_expect(bar + B_WO * 8, 36864);
      asm volatile("cp.async.bulk.tensor.3d.shared::cluster.global.mbarrier::complete_tx::bytes [%0], [%1, {%3,%4,%5}], [%2];"
                   ::"r"(sb + SM_TWO), "l"(&mp.wo), "r"(bar + B_WO * 8), "r"(0), "r"(0), "r"((head & 1) * 3) : "memory");
    }
    __syncwarp();
    gemm_iter<false, true>(c, 12, pk, pv, pq, head TRPASS);
    TRDUMP;
    mbar_wait(bar + B_WO * 8, 0);
    nb_sync(N_QK1, 256);
    const uint32_t st = sb + SM_TST + gw * 3072;
    const uint32_t sta = st + (lane & 15) * 64 + ((hi ^ ((lane >> 1) & 3)) * 16);
#pragma unroll 1
    for (int i = 0; i < 2; i++) {
      constexpr uint64_t db = mkdesc(SBC + SM_TWO, 12288, 512, 2);
      const uint64_t da = mkdesc(SBC + SM_TIN, 128, 768, 0) + i * (24576 / 16);
      float D[48];
      mbar_wait(bar + (B_TIN + i) * 8, 0);
      wg_fence();
      wg_ss96<0>(D, da, db);
#pragma unroll
      for (int k = 1; k < 12; k++) wg_ss96<1>(D, da + (k / 3) * 384 + (k % 3) * 16, db + k * 64);
      wg_commit();
      if (lane == 0) asm volatile("cp.async.bulk.wait_group.read 0;" ::: "memory");
      __syncwarp();
      wg_wait<0>(); pin(D);
#pragma unroll
      for (int q = 0; q < 6; q++)
        stsm4((sta ^ ((q & 1) * 32)) + (q >> 1) * 1024,
              pack2(D[8 * q], D[8 * q + 1]), pack2(D[8 * q + 2], D[8 * q + 3]), pack2(D[8 * q + 4], D[8 * q + 5]), pack2(D[8 * q + 6], D[8 * q + 7]));
      fence_async();
      __syncwarp();
      if (lane == 0) {
        asm volatile("cp.async.bulk.tensor.4d.global.shared::cta.bulk_group [%0, {%2,%3,%4,%5}], [%1];"
                     ::"l"(&mp.ot), "r"(st), "r"(0), "r"(8 * (TB + i)), "r"(ph * 112 + strip * 16 + 8 * (head >> 1) + 2 * gw), "r"(pw * 6 + (head & 1) * 3) : "memory");
        asm volatile("cp.async.bulk.commit_group;" ::: "memory");
      }
    }
    asm volatile("barrier.cluster.arrive.relaxed.aligned;" ::: "memory");
    if (lane == 0) asm volatile("cp.async.bulk.wait_group 0;" ::: "memory");
    __syncwarp();
    asm volatile("barrier.cluster.wait.aligned;" ::: "memory");
  } else {
    asm volatile("setmaxnreg.inc.sync.aligned.u32 %0;" ::"n"(RA));
    float rv = -INFINITY;
    if (tid < 169) rv = __bfloat162float(rpb[head * 169 + tid]) * 1.4426950408889634f;
    if (tid < 192) {
      const int kc = (wr & 15) + 3;
      sts128(tid < 96 ? sb + SM_K + kc * KS + wc * 128 + 48 : sb + SM_V + kc * 1536 + wc * 128 + (6 + (kc & 1)) * 16, make_uint4(0, 0, 0, 0));
    }
#pragma unroll
    for (int i = 0; i < 3; i++) sts128(sb + SM_W + (3 + (wc >> 1)) * 6144 + (wr + i * 64) * 32 + ((wc ^ (wr >> 2)) & 1) * 16, wv[i]);
    fence_async();
    asm volatile("bar.arrive 1, 384;" ::: "memory");
    if (tid < 182) asm volatile("st.shared.f32 [%0], %1;" ::"r"(sb + SM_RPB + tid * 4), "f"(rv) : "memory");
    const int j = warp >> 2, w = warp & 3;
    int variant = w;
    if (strip == 0 && j == 0 && w < 2) variant = 4;
    if (strip == 6 && j == 1 && w >= 2) variant = 5;
    const uint32_t qa = sb + SM_Q + (8 * j + 2 * w + ((lane >> 3) & 1)) * 1536 + (lane >> 4) * 256 + (((lane & 7) * 16) ^ (((lane >> 3) & 1) * 64));
    uint32_t oa = sb + SM_O + j * 6144 + (2 * w + ((lane >> 3) & 1)) * 768 + (lane >> 4) * 128 + (lane & 7) * 16;
    const uint64_t dK = mkdesc(SBC + SM_K, 128, KS, 0) + j * (8 * KS / 16);
    const uint64_t dV = mkdesc(SBC + SM_V, 768, 128, 0) + j * (8 * 1536 / 16);
    asm volatile("barrier.cluster.wait.aligned;" ::: "memory");
    asm volatile("bar.sync 3, 256;" ::: "memory");
    float T[14];
    TRDECL;
    int b0 = 0, b1 = 0;
    uint32_t ra0 = 0, ra1 = 0, meta = 0;
    uint32_t q[12];
    mbar_wait(bar + B_Q0 * 8, 0);
#pragma unroll
    for (int k = 0; k < 3; k++) ldsm4(qa + k * 512, q[4 * k], q[4 * k + 1], q[4 * k + 2], q[4 * k + 3]);
#pragma unroll 1
    for (int b = 0; b < 14; b++) {
      const uint32_t pa = b & 1;
      if (b <= 1 || b == 13) {
        uint32_t ln; asm volatile("mov.u32 %0, %%laneid;" : "=r"(ln));
        const int g = ln >> 2, t = ln & 3;
        const int sw = b == 0 ? max(g + 1, 4) : (b == 13 ? min(g + 1, 5) : g + 1);
        const int i0 = 2 * t, i1 = 2 * t + 1;
        b0 = i0 <= sw - 2; b1 = i1 <= sw - 2;
        const int m = sw - 1;
        ra0 = sb + SM_RPB + (i0 == m ? 13 : i0 + (b0 ? 8 : 0) - g + 2) * 52;
        ra1 = sb + SM_RPB + (i1 == m ? 13 : i1 + (b1 ? 8 : 0) - g + 2) * 52;
#pragma unroll
        for (int jj = 0; jj < 7; jj++) { T[2 * jj] = lds_f32(ra0 + (jj + 3) * 4); T[2 * jj + 1] = lds_f32(ra1 + (jj + 3) * 4); }
        uint32_t m16 = 0x8888u;
#pragma unroll
        for (int i = 0; i < 8; i++) m16 |= (uint32_t)(((i <= sw - 2) ^ (i >> 2) ^ t ^ b) & 1) << (2 * i);
        meta = m16 | (m16 << 16);
        if (b == 13) oa += SM_Q - SM_O + j * 6144;
      } else meta ^= 0x55555555u;
      float SA[56], SB[56];
      const uint64_t dA = dK + pa * (KSLOT >> 4), dB = dK + (pa ^ 1) * (KSLOT >> 4);
      TR(0, b, 0);
      nb_sync(N_KRDY + j, 256);
      TR(0, b, 1);
      TR(0, b - 1, 9);
      wg_fence();
      wg_rs112<0>(SA, q[0], q[1], q[2], q[3], dA);
      wg_rs112<0>(SB, q[0], q[1], q[2], q[3], dB);
      wg_rs112<1>(SA, q[4], q[5], q[6], q[7], dA + 16);
      wg_rs112<1>(SB, q[4], q[5], q[6], q[7], dB + 16);
      wg_rs112<1>(SA, q[8], q[9], q[10], q[11], dA + 32);
      wg_rs112<1>(SB, q[8], q[9], q[10], q[11], dB + 32);
      wg_commit();
      nb_arrive(N_QK0 + j, 256);
      TR(0, b, 2);
      wg_wait<0>(); pin(SA); pin(SB);
      mbar_arrive_elect(bar + B_KFREE * 8);
      TR(0, b, 3);
      TR(0, b - 1, 10);
      uint32_t P[28];
      float sx[8];
      switch (variant) {
        case 0: softmax_tile<0, 1, false>(SA, SB, T, b0, b1, ra0, ra1, 0, P, sx); break;
        case 1: softmax_tile<2, 3, false>(SA, SB, T, b0, b1, ra0, ra1, 0, P, sx); break;
        case 2: softmax_tile<4, 5, false>(SA, SB, T, b0, b1, ra0, ra1, 0, P, sx); break;
        case 3: softmax_tile<6, 7, false>(SA, SB, T, b0, b1, ra0, ra1, 0, P, sx); break;
        case 4: softmax_tile<3, 3, true>(SA, SB, T, b0, b1, ra0, ra1, 2 * w, P, sx); break;
        default: softmax_tile<4, 4, true>(SA, SB, T, b0, b1, ra0, ra1, 2 * w, P, sx); break;
      }
      float O[24];
      TR(0, b, 4);
      nb_sync(N_VQ0 + j, 288);
      TR(0, b, 5);
#pragma unroll
      for (int k = 0; k < 3; k++) ldsm4(qa + (pa ^ 1) * 128 + k * 512, q[4 * k], q[4 * k + 1], q[4 * k + 2], q[4 * k + 3]);
      wg_fence();
      wg_sp48<0>(O, P[0], P[1], P[2], P[3], dV, meta);
#pragma unroll
      for (int s = 1; s < 7; s++) wg_sp48<1>(O, P[4 * s], P[4 * s + 1], P[4 * s + 2], P[4 * s + 3], dV + s * 192, meta);
      wg_commit();
      if (b < 12) nb_arrive(N_PVISS, 384);
      TR(0, b, 6);
      wg_wait<0>(); pin(O);
      mbar_arrive_elect(bar + B_VFREE * 8);
      TR(0, b, 7);
      float ru, rl;
      asm("rcp.approx.ftz.f32 %0, %1;" : "=f"(ru) : "f"(((fmaf(O[0], 0.f, sx[0]) + sx[1]) + sx[2]) + sx[3]));
      asm("rcp.approx.ftz.f32 %0, %1;" : "=f"(rl) : "f"(((fmaf(O[2], 0.f, sx[4]) + sx[5]) + sx[6]) + sx[7]));
#pragma unroll
      for (int i = 0; i < 3; i++)
        stsm4(oa + i * 256, pack2(O[8 * i] * ru, O[8 * i + 1] * ru), pack2(O[8 * i + 2] * rl, O[8 * i + 3] * rl),
              pack2(O[8 * i + 4] * ru, O[8 * i + 5] * ru), pack2(O[8 * i + 6] * rl, O[8 * i + 7] * rl));
      publish(bar + (B_ODONE + j) * 8);
      TR(0, b, 8);
    }
    TRDUMP;
    TR2(blockIdx.x, 2);
    cluster_sync();
  }
}

constexpr int NSTB = 4;
constexpr int NTB = TB * 56;
constexpr int SM_B_ST = 0;
constexpr int SM_B_IN = 49152;
constexpr int SM_B_W = SM_B_IN + NSTB * 24576;
constexpr int SM_B_BAR = SM_B_W + 73728;
constexpr int SM_B_TOTAL = SM_B_BAR + 128;
struct MapsB { CUtensorMap oi, oo, wo; };

__global__ void __launch_bounds__(288, 1)
na_proj_kernel(const __grid_constant__ MapsB mp) {
  extern __shared__ __align__(1024) uint8_t smem_raw[];
  const uint32_t sb = smem_u32(smem_raw);
  if ((sb & 0x3FFFF) != SBC) return;
  const uint32_t bar = sb + SM_B_BAR;
  const int tid = threadIdx.x, lane = tid & 31;
  const int warp = __shfl_sync(0xffffffffu, tid >> 5, 0);
  TR2(132 + blockIdx.x, 0);
  TRB(47, 0);
  if (warp == 8 && elect_one()) {
#pragma unroll
    for (int i = 0; i <= 2 * NSTB; i++) mbar_init(bar + i * 8, i < NSTB || i == 2 * NSTB ? 1 : 4);
    mbar_expect(bar + 2 * NSTB * 8, 73728);
#pragma unroll
    for (int i = 0; i < 2; i++)
      asm volatile("cp.async.bulk.tensor.3d.shared::cluster.global.mbarrier::complete_tx::bytes [%0], [%1, {%3,%4,%5}], [%2];"
                   ::"r"(sb + SM_B_W + i * 36864), "l"(&mp.wo), "r"(bar + 2 * NSTB * 8), "r"(0), "r"(0), "r"(i * 3) : "memory");
  }
  __syncthreads();
  const int step = gridDim.x;
  if (warp == 8) {
    int it = 0;
    uint32_t spin = 0;
#pragma unroll 1
    for (int n = blockIdx.x; n < NTB && spin < SPIN_LIMIT; spin++) {
      int v = 0;
      const int mine = n + lane * step;
      if (lane < 8 && mine < NTB) asm volatile("ld.acquire.gpu.global.s32 %0, [%1];" : "=r"(v) : "l"(g_flags + mine) : "memory");
      int cnt = __ffs(~__ballot_sync(0xffffffffu, v >= 4)) - 1;
      asm volatile("fence.proxy.async.global;" ::: "memory");
      __syncwarp();
#pragma unroll 1
      for (; cnt > 0; cnt--, n += step, it++) {
        TRB(it, 0);
        const int b = n / 56, rem = n - b * 56, par = rem / 14;
        const int st = it & (NSTB - 1), use = it / NSTB;
        if (use) mbar_wait(bar + (NSTB + st) * 8, (use - 1) & 1);
        if (elect_one()) {
          mbar_expect(bar + st * 8, 24576);
          asm volatile("cp.async.bulk.tensor.3d.shared::cluster.global.mbarrier::complete_tx::bytes [%0], [%1, {%3,%4,%5}], [%2];"
                       ::"r"(sb + SM_B_IN + st * 24576), "l"(&mp.oi), "r"(bar + st * 8), "r"((par & 1) * 192), "r"(8 * b), "r"((par >> 1) * 112 + (rem - par * 14) * 8) : "memory");
        }
        __syncwarp();
        TRB(it, 2);
      }
    }
    for (int n = blockIdx.x + lane * step; n < NTB; n += 32 * step) g_flags[n] = 0;
  } else {
    const int wg = warp >> 2, w = warp & 3;
    constexpr uint64_t db = mkdesc(SBC + SM_B_W, 12288, 512, 2);
    const uint32_t st = sb + SM_B_ST + warp * 6144;
    const uint32_t sta = st + (lane & 15) * 128 + (((lane >> 4) ^ (lane & 7)) * 16);
    mbar_wait(bar + 2 * NSTB * 8, 0);
    TRB(47, 1);
    int it = wg;
#pragma unroll 1
    for (int n = blockIdx.x + wg * step; n < NTB; n += 2 * step, it += 2) {
      const int b = n / 56, rem = n - b * 56, par = rem / 14, sg = it & (NSTB - 1);
      const uint64_t da = mkdesc(SBC + SM_B_IN, 128, 3072, 0) + sg * (24576 / 16);
      float D[96];
      mbar_wait(bar + sg * 8, (it / NSTB) & 1);
      TRB(it, 3);
      wg_fence();
      wg_ss192<0>(D, da, db);
#pragma unroll
      for (int k = 1; k < 12; k++) wg_ss192<1>(D, da + k * 16, db + k * 64);
      wg_commit();
      TRB(it, 4);
      if (lane == 0) asm volatile("cp.async.bulk.wait_group.read 0;" ::: "memory");
      __syncwarp();
      wg_wait<0>(); pin(D);
      mbar_arrive_elect(bar + (NSTB + sg) * 8);
      TRB(it, 5);
#pragma unroll
      for (int q = 0; q < 12; q++)
        stsm4((sta ^ ((q & 3) * 32)) + (q >> 2) * 2048,
              pack2(D[8 * q], D[8 * q + 1]), pack2(D[8 * q + 2], D[8 * q + 3]), pack2(D[8 * q + 4], D[8 * q + 5]), pack2(D[8 * q + 6], D[8 * q + 7]));
      fence_async();
      __syncwarp();
      if (lane == 0) {
        asm volatile("cp.async.bulk.tensor.4d.global.shared::cta.bulk_group [%0, {%2,%3,%4,%5}], [%1];"
                     ::"l"(&mp.oo), "r"(st), "r"(0), "r"(8 * b), "r"((par >> 1) * 112 + (rem - par * 14) * 8 + 2 * w), "r"((par & 1) * 3) : "memory");
        asm volatile("cp.async.bulk.commit_group;" ::: "memory");
      }
      TRB(it, 6);
    }
    if (lane == 0) asm volatile("cp.async.bulk.wait_group 0;" ::: "memory");
    TR2(132 + blockIdx.x, 2);
  }
}

typedef CUresult (*EncodeFn)(CUtensorMap*, CUtensorMapDataType, cuuint32_t, void*, const cuuint64_t*, const cuuint64_t*, const cuuint32_t*,
                             const cuuint32_t*, CUtensorMapInterleave, CUtensorMapSwizzle, CUtensorMapL2promotion, CUtensorMapFloatOOBfill);
static EncodeFn g_enc = nullptr;
static void make_map(CUtensorMap* m, const void* p, int rank, const cuuint64_t* dim, const cuuint64_t* str, const cuuint32_t* box, CUtensorMapSwizzle sw) {
  const cuuint32_t ones[5] = {1, 1, 1, 1, 1};
  g_enc(m, CU_TENSOR_MAP_DATA_TYPE_BFLOAT16, rank, (void*)p, dim, str, box, ones, CU_TENSOR_MAP_INTERLEAVE_NONE, sw,
        CU_TENSOR_MAP_L2_PROMOTION_L2_128B, CU_TENSOR_MAP_FLOAT_OOB_FILL_NONE);
}

extern "C" void kernel_launch(void* const* d_in, const int* in_sizes, int n_in, void* d_out, int out_size) {
  const __nv_bfloat16* x = (const __nv_bfloat16*)d_in[0];
  const __nv_bfloat16* wqkv = (const __nv_bfloat16*)d_in[1];
  const __nv_bfloat16* wo = (const __nv_bfloat16*)d_in[2];
  const __nv_bfloat16* rpb = (const __nv_bfloat16*)d_in[3];

  if (!g_enc) {
    void* fn = nullptr; cudaDriverEntryPointQueryResult qr;
    cudaGetDriverEntryPoint("cuTensorMapEncodeTiled", &fn, cudaEnableDefault, &qr);
    g_enc = (EncodeFn)fn;
    cudaFuncSetAttribute(na_attn_kernel, cudaFuncAttributeMaxDynamicSharedMemorySize, SM_A_TOTAL);
    cudaFuncSetAttribute(na_proj_kernel, cudaFuncAttributeMaxDynamicSharedMemorySize, SM_B_TOTAL);
  }
  Maps ma; MapsB mb;
  { cuuint64_t dim[4] = {64, 112, 224, 6}, str[3] = {(cuuint64_t)ROWB, 768, 128};
    cuuint32_t box[4] = {64, 4, 16, 3}, boxo[4] = {64, 8, 2, 3};
    make_map(&ma.xc, x, 4, dim, str, box, CU_TENSOR_MAP_SWIZZLE_128B);
    make_map(&mb.oo, d_out, 4, dim, str, boxo, CU_TENSOR_MAP_SWIZZLE_128B); }
  { cuuint64_t dim[5] = {64, 112, 224, 2, 6}, str[4] = {(cuuint64_t)ROWB, 768, 19 * 768, 128};
    cuuint32_t box[5] = {64, 8, 3, 2, 3};
    make_map(&ma.xh, x, 5, dim, str, box, CU_TENSOR_MAP_SWIZZLE_128B); }
  { cuuint64_t dim[3] = {384, 112, 224}, str[2] = {(cuuint64_t)ROWB, 768};
    cuuint32_t box[3] = {192, 8, 8}, boxs[3] = {192, 2, 8};
    make_map(&mb.oi, d_out, 3, dim, str, box, CU_TENSOR_MAP_SWIZZLE_NONE);
    make_map(&ma.os, d_out, 3, dim, str, boxs, CU_TENSOR_MAP_SWIZZLE_NONE); }
  { cuuint64_t dim[4] = {32, 112, 224, 12}, str[3] = {(cuuint64_t)ROWB, 768, 64};
    cuuint32_t box[4] = {32, 8, 2, 3};
    make_map(&ma.ot, d_out, 4, dim, str, box, CU_TENSOR_MAP_SWIZZLE_64B); }
  { cuuint64_t dim[2] = {576, 192}, str[1] = {1152};
    cuuint32_t box[2] = {16, 192};
    make_map(&ma.w, wqkv, 2, dim, str, box, CU_TENSOR_MAP_SWIZZLE_32B); }
  { cuuint64_t dim[3] = {32, 192, 6}, str[2] = {384, 64};
    cuuint32_t box[3] = {32, 192, 3};
    make_map(&ma.wo, wo, 3, dim, str, box, CU_TENSOR_MAP_SWIZZLE_64B);
    mb.wo = ma.wo; }
  na_attn_kernel<<<112, 512, SM_A_TOTAL>>>(ma, wqkv, rpb);
  cudaLaunchConfig_t cfg = {};
  cfg.gridDim = dim3(20); cfg.blockDim = dim3(288); cfg.dynamicSmemBytes = SM_B_TOTAL; cfg.stream = cudaStreamPerThread;
  cudaLaunchAttribute at[1];
  at[0].id = cudaLaunchAttributeProgrammaticStreamSerialization; at[0].val.programmaticStreamSerializationAllowed = 1;
  cfg.attrs = at; cfg.numAttrs = 1;
  cudaLaunchKernelEx(&cfg, na_proj_kernel, mb);
}
```

```cpp
#include <cuda_runtime.h>
#include <cuda_bf16.h>
#include <cuda.h>
#include <stdint.h>

#define SPIN_LIMIT (1u << 18)

__device__ __forceinline__ uint32_t smem_u32(const void* p) { return (uint32_t)__cvta_generic_to_shared(p); }
__device__ __forceinline__ void wg_fence() { asm volatile("wgmma.fence.sync.aligned;" ::: "memory"); }
__device__ __forceinline__ void wg_commit() { asm volatile("wgmma.commit_group.sync.aligned;" ::: "memory"); }
template <int N> __device__ __forceinline__ void wg_wait() { asm volatile("wgmma.wait_group.sync.aligned %0;" ::"n"(N) : "memory"); }
template <int N> __device__ __forceinline__ void pin(float (&d)[N]) {
#pragma unroll
  for (int i = 0; i < N; i++) asm volatile("" : "+f"(d[i])::"memory");
}
__host__ __device__ constexpr uint64_t mkdesc(uint32_t addr, uint32_t lbo, uint32_t sbo, uint32_t sw) {
  return (uint64_t)((addr & 0x3FFFF) >> 4) | ((uint64_t)(lbo >> 4) << 16) | ((uint64_t)(sbo >> 4) << 32) | ((uint64_t)sw << 62);
}
__device__ __forceinline__ void mbar_init(uint32_t bar, uint32_t cnt) { asm volatile("mbarrier.init.shared::cta.b64 [%0], %1;" ::"r"(bar), "r"(cnt) : "memory"); }
__device__ __forceinline__ void mbar_arrive(uint32_t bar) { asm volatile("mbarrier.arrive.shared::cta.b64 _, [%0];" ::"r"(bar) : "memory"); }
__device__ __forceinline__ bool elect_one() {
  uint32_t r; asm volatile("{\n.reg .pred p;\nelect.sync _|p, 0xffffffff;\nselp.u32 %0, 1, 0, p;\n}" : "=r"(r)); return r;
}
__device__ __forceinline__ void mbar_arrive_elect(uint32_t bar) {
  asm volatile("{\n.reg .pred p;\nelect.sync _|p, 0xffffffff;\n@p mbarrier.arrive.shared::cta.b64 _, [%0];\n}" ::"r"(bar) : "memory");
}
__device__ __forceinline__ void mbar_expect(uint32_t bar, uint32_t bytes) { asm volatile("mbarrier.arrive.expect_tx.shared::cta.b64 _, [%0], %1;" ::"r"(bar), "r"(bytes) : "memory"); }
__device__ __forceinline__ void mbar_arrive_remote(uint32_t bar, uint32_t cta) {
  asm volatile("{\n.reg .b32 ra;\nmapa.shared::cluster.u32 ra, %0, %1;\nmbarrier.arrive.shared::cluster.b64 _, [ra];\n}" ::"r"(bar), "r"(cta) : "memory");
}
__device__ __forceinline__ void mbar_wait(uint32_t bar, uint32_t parity) {
  asm volatile("{\n.reg .pred p;\n.reg .b32 n;\nmov.b32 n, 0;\nWL:\nmbarrier.try_wait.parity.shared::cta.b64 p, [%0], %1;\n@p bra WD;\n"
               "add.u32 n, n, 1;\nsetp.lt.u32 p, n, 65536;\n@p bra WL;\nWD:\n}" ::"r"(bar), "r"(parity) : "memory");
}
__device__ __forceinline__ void nb_sync(int id, int n) { asm volatile("bar.sync %0, %1;" ::"r"(id), "r"(n) : "memory"); }
__device__ __forceinline__ void nb_arrive(int id, int n) { asm volatile("bar.arrive %0, %1;" ::"r"(id), "r"(n) : "memory"); }
__device__ __forceinline__ void fence_async() { asm volatile("fence.proxy.async.shared::cta;" ::: "memory"); }
__device__ __forceinline__ void cluster_sync() {
  asm volatile("barrier.cluster.arrive.relaxed.aligned;\nbarrier.cluster.wait.aligned;" ::: "memory");
}
__device__ __forceinline__ uint32_t pack2(float lo, float hi) {
  uint32_t r; asm("cvt.rn.bf16x2.f32 %0, %1, %2;" : "=r"(r) : "f"(hi), "f"(lo)); return r;
}
__device__ __forceinline__ void stsm4(uint32_t a, uint32_t r0, uint32_t r1, uint32_t r2, uint32_t r3) {
  asm volatile("stmatrix.sync.aligned.m8n8.x4.shared.b16 [%0], {%1,%2,%3,%4};" ::"r"(a), "r"(r0), "r"(r1), "r"(r2), "r"(r3) : "memory");
}
__device__ __forceinline__ void ldsm4(uint32_t a, uint32_t& r0, uint32_t& r1, uint32_t& r2, uint32_t& r3) {
  asm volatile("ldmatrix.sync.aligned.m8n8.x4.shared.b16 {%0,%1,%2,%3}, [%4];" : "=r"(r0), "=r"(r1), "=r"(r2), "=r"(r3) : "r"(a) : "memory");
}
__device__ __forceinline__ void sts128(uint32_t a, uint4 v) {
  asm volatile("st.shared.v4.b32 [%0], {%1,%2,%3,%4};" ::"r"(a), "r"(v.x), "r"(v.y), "r"(v.z), "r"(v.w) : "memory");
}
__device__ __forceinline__ float lds_f32(uint32_t a) { float v; asm volatile("ld.shared.f32 %0, [%1];" : "=f"(v) : "r"(a)); return v; }
__device__ __forceinline__ float ex2(float x) { float y; asm("ex2.approx.ftz.f32 %0, %1;" : "=f"(y) : "f"(x)); return y; }

template<int SC> __device__ __forceinline__ void wg_ss144(float (&d)[72], uint64_t da, uint64_t db) {
  asm volatile("{\n.reg .pred p;\nsetp.ne.b32 p, %74, 0;\nwgmma.mma_async.sync.aligned.m64n144k16.f32.bf16.bf16 {%0,%1,%2,%3,%4,%5,%6,%7,%8,%9,%10,%11,%12,%13,%14,%15,%16,%17,%18,%19,%20,%21,%22,%23,%24,%25,%26,%27,%28,%29,%30,%31,%32,%33,%34,%35,%36,%37,%38,%39,%40,%41,%42,%43,%44,%45,%46,%47,%48,%49,%50,%51,%52,%53,%54,%55,%56,%57,%58,%59,%60,%61,%62,%63,%64,%65,%66,%67,%68,%69,%70,%71}, %72, %73, p, 1, 1, 0, 1;\n}\n"
    : "+f"(d[0]),"+f"(d[1]),"+f"(d[2]),"+f"(d[3]),"+f"(d[4]),"+f"(d[5]),"+f"(d[6]),"+f"(d[7]),"+f"(d[8]),"+f"(d[9]),"+f"(d[10]),"+f"(d[11]),"+f"(d[12]),"+f"(d[13]),"+f"(d[14]),"+f"(d[15]),"+f"(d[16]),"+f"(d[17]),"+f"(d[18]),"+f"(d[19]),"+f"(d[20]),"+f"(d[21]),"+f"(d[22]),"+f"(d[23]),"+f"(d[24]),"+f"(d[25]),"+f"(d[26]),"+f"(d[27]),"+f"(d[28]),"+f"(d[29]),"+f"(d[30]),"+f"(d[31]),"+f"(d[32]),"+f"(d[33]),"+f"(d[34]),"+f"(d[35]),"+f"(d[36]),"+f"(d[37]),"+f"(d[38]),"+f"(d[39]),"+f"(d[40]),"+f"(d[41]),"+f"(d[42]),"+f"(d[43]),"+f"(d[44]),"+f"(d[45]),"+f"(d[46]),"+f"(d[47]),"+f"(d[48]),"+f"(d[49]),"+f"(d[50]),"+f"(d[51]),"+f"(d[52]),"+f"(d[53]),"+f"(d[54]),"+f"(d[55]),"+f"(d[56]),"+f"(d[57]),"+f"(d[58]),"+f"(d[59]),"+f"(d[60]),"+f"(d[61]),"+f"(d[62]),"+f"(d[63]),"+f"(d[64]),"+f"(d[65]),"+f"(d[66]),"+f"(d[67]),"+f"(d[68]),"+f"(d[69]),"+f"(d[70]),"+f"(d[71]) : "l"(da), "l"(db), "n"(SC));
}
template<int SC> __device__ __forceinline__ void wg_ss96(float (&d)[48], uint64_t da, uint64_t db) {
  asm volatile("{\n.reg .pred p;\nsetp.ne.b32 p, %50, 0;\nwgmma.mma_async.sync.aligned.m64n96k16.f32.bf16.bf16 {%0,%1,%2,%3,%4,%5,%6,%7,%8,%9,%10,%11,%12,%13,%14,%15,%16,%17,%18,%19,%20,%21,%22,%23,%24,%25,%26,%27,%28,%29,%30,%31,%32,%33,%34,%35,%36,%37,%38,%39,%40,%41,%42,%43,%44,%45,%46,%47}, %48, %49, p, 1, 1, 0, 1;\n}\n"
    : "+f"(d[0]),"+f"(d[1]),"+f"(d[2]),"+f"(d[3]),"+f"(d[4]),"+f"(d[5]),"+f"(d[6]),"+f"(d[7]),"+f"(d[8]),"+f"(d[9]),"+f"(d[10]),"+f"(d[11]),"+f"(d[12]),"+f"(d[13]),"+f"(d[14]),"+f"(d[15]),"+f"(d[16]),"+f"(d[17]),"+f"(d[18]),"+f"(d[19]),"+f"(d[20]),"+f"(d[21]),"+f"(d[22]),"+f"(d[23]),"+f"(d[24]),"+f"(d[25]),"+f"(d[26]),"+f"(d[27]),"+f"(d[28]),"+f"(d[29]),"+f"(d[30]),"+f"(d[31]),"+f"(d[32]),"+f"(d[33]),"+f"(d[34]),"+f"(d[35]),"+f"(d[36]),"+f"(d[37]),"+f"(d[38]),"+f"(d[39]),"+f"(d[40]),"+f"(d[41]),"+f"(d[42]),"+f"(d[43]),"+f"(d[44]),"+f"(d[45]),"+f"(d[46]),"+f"(d[47]) : "l"(da), "l"(db), "n"(SC));
}
template<int SC> __device__ __forceinline__ void wg_rs112(float (&d)[56], uint32_t a0, uint32_t a1, uint32_t a2, uint32_t a3, uint64_t db) {
  asm volatile("{\n.reg .pred p;\nsetp.ne.b32 p, %61, 0;\nwgmma.mma_async.sync.aligned.m64n112k16.f32.bf16.bf16 {%0,%1,%2,%3,%4,%5,%6,%7,%8,%9,%10,%11,%12,%13,%14,%15,%16,%17,%18,%19,%20,%21,%22,%23,%24,%25,%26,%27,%28,%29,%30,%31,%32,%33,%34,%35,%36,%37,%38,%39,%40,%41,%42,%43,%44,%45,%46,%47,%48,%49,%50,%51,%52,%53,%54,%55}, {%56,%57,%58,%59}, %60, p, 1, 1, 0;\n}\n"
    : "+f"(d[0]),"+f"(d[1]),"+f"(d[2]),"+f"(d[3]),"+f"(d[4]),"+f"(d[5]),"+f"(d[6]),"+f"(d[7]),"+f"(d[8]),"+f"(d[9]),"+f"(d[10]),"+f"(d[11]),"+f"(d[12]),"+f"(d[13]),"+f"(d[14]),"+f"(d[15]),"+f"(d[16]),"+f"(d[17]),"+f"(d[18]),"+f"(d[19]),"+f"(d[20]),"+f"(d[21]),"+f"(d[22]),"+f"(d[23]),"+f"(d[24]),"+f"(d[25]),"+f"(d[26]),"+f"(d[27]),"+f"(d[28]),"+f"(d[29]),"+f"(d[30]),"+f"(d[31]),"+f"(d[32]),"+f"(d[33]),"+f"(d[34]),"+f"(d[35]),"+f"(d[36]),"+f"(d[37]),"+f"(d[38]),"+f"(d[39]),"+f"(d[40]),"+f"(d[41]),"+f"(d[42]),"+f"(d[43]),"+f"(d[44]),"+f"(d[45]),"+f"(d[46]),"+f"(d[47]),"+f"(d[48]),"+f"(d[49]),"+f"(d[50]),"+f"(d[51]),"+f"(d[52]),"+f"(d[53]),"+f"(d[54]),"+f"(d[55]) : "r"(a0), "r"(a1), "r"(a2), "r"(a3), "l"(db), "n"(SC));
}
template<int SC> __device__ __forceinline__ void wg_sp48(float (&d)[24], uint32_t a0, uint32_t a1, uint32_t a2, uint32_t a3, uint64_t db, uint32_t meta) {
  asm volatile("{\n.reg .pred p;\nsetp.ne.b32 p, %30, 0;\nwgmma.mma_async.sp.sync.aligned.m64n48k32.f32.bf16.bf16 {%0,%1,%2,%3,%4,%5,%6,%7,%8,%9,%10,%11,%12,%13,%14,%15,%16,%17,%18,%19,%20,%21,%22,%23}, {%24,%25,%26,%27}, %28, %29, 0, p, 1, 1, 1;\n}\n"
    : "+f"(d[0]),"+f"(d[1]),"+f"(d[2]),"+f"(d[3]),"+f"(d[4]),"+f"(d[5]),"+f"(d[6]),"+f"(d[7]),"+f"(d[8]),"+f"(d[9]),"+f"(d[10]),"+f"(d[11]),"+f"(d[12]),"+f"(d[13]),"+f"(d[14]),"+f"(d[15]),"+f"(d[16]),"+f"(d[17]),"+f"(d[18]),"+f"(d[19]),"+f"(d[20]),"+f"(d[21]),"+f"(d[22]),"+f"(d[23]) : "r"(a0), "r"(a1), "r"(a2), "r"(a3), "l"(db), "r"(meta), "n"(SC));
}
template<int SC> __device__ __forceinline__ void wg_ss192(float (&d)[96], uint64_t da, uint64_t db) {
  asm volatile("{\n.reg .pred p;\nsetp.ne.b32 p, %98, 0;\nwgmma.mma_async.sync.aligned.m64n192k16.f32.bf16.bf16 {%0,%1,%2,%3,%4,%5,%6,%7,%8,%9,%10,%11,%12,%13,%14,%15,%16,%17,%18,%19,%20,%21,%22,%23,%24,%25,%26,%27,%28,%29,%30,%31,%32,%33,%34,%35,%36,%37,%38,%39,%40,%41,%42,%43,%44,%45,%46,%47,%48,%49,%50,%51,%52,%53,%54,%55,%56,%57,%58,%59,%60,%61,%62,%63,%64,%65,%66,%67,%68,%69,%70,%71,%72,%73,%74,%75,%76,%77,%78,%79,%80,%81,%82,%83,%84,%85,%86,%87,%88,%89,%90,%91,%92,%93,%94,%95}, %96, %97, p, 1, 1, 0, 1;\n}\n"
    : "+f"(d[0]),"+f"(d[1]),"+f"(d[2]),"+f"(d[3]),"+f"(d[4]),"+f"(d[5]),"+f"(d[6]),"+f"(d[7]),"+f"(d[8]),"+f"(d[9]),"+f"(d[10]),"+f"(d[11]),"+f"(d[12]),"+f"(d[13]),"+f"(d[14]),"+f"(d[15]),"+f"(d[16]),"+f"(d[17]),"+f"(d[18]),"+f"(d[19]),"+f"(d[20]),"+f"(d[21]),"+f"(d[22]),"+f"(d[23]),"+f"(d[24]),"+f"(d[25]),"+f"(d[26]),"+f"(d[27]),"+f"(d[28]),"+f"(d[29]),"+f"(d[30]),"+f"(d[31]),"+f"(d[32]),"+f"(d[33]),"+f"(d[34]),"+f"(d[35]),"+f"(d[36]),"+f"(d[37]),"+f"(d[38]),"+f"(d[39]),"+f"(d[40]),"+f"(d[41]),"+f"(d[42]),"+f"(d[43]),"+f"(d[44]),"+f"(d[45]),"+f"(d[46]),"+f"(d[47]),"+f"(d[48]),"+f"(d[49]),"+f"(d[50]),"+f"(d[51]),"+f"(d[52]),"+f"(d[53]),"+f"(d[54]),"+f"(d[55]),"+f"(d[56]),"+f"(d[57]),"+f"(d[58]),"+f"(d[59]),"+f"(d[60]),"+f"(d[61]),"+f"(d[62]),"+f"(d[63]),"+f"(d[64]),"+f"(d[65]),"+f"(d[66]),"+f"(d[67]),"+f"(d[68]),"+f"(d[69]),"+f"(d[70]),"+f"(d[71]),"+f"(d[72]),"+f"(d[73]),"+f"(d[74]),"+f"(d[75]),"+f"(d[76]),"+f"(d[77]),"+f"(d[78]),"+f"(d[79]),"+f"(d[80]),"+f"(d[81]),"+f"(d[82]),"+f"(d[83]),"+f"(d[84]),"+f"(d[85]),"+f"(d[86]),"+f"(d[87]),"+f"(d[88]),"+f"(d[89]),"+f"(d[90]),"+f"(d[91]),"+f"(d[92]),"+f"(d[93]),"+f"(d[94]),"+f"(d[95]) : "l"(da), "l"(db), "n"(SC));
}

constexpr uint32_t SBC = 1024;
constexpr int ROWB = 2 * 224 * 384;
constexpr int TB = 12;
constexpr int KS = 832;
constexpr int KSLOT = 22 * KS;
constexpr int SM_X1 = 0;
constexpr int SM_X2 = SM_X1 + 24576;
constexpr int SM_X0 = SM_X2 + 24576;
constexpr int SM_W = SM_X0 + 18432;
constexpr int SM_K = SM_W + 55296;
constexpr int SM_V = SM_K + 2 * KSLOT;
constexpr int SM_Q = SM_V + 22 * 1536;
constexpr int SM_O = SM_Q + 24576;
constexpr int SM_RPB = SM_O + 12288;
constexpr int SM_BAR = SM_RPB + 768;
constexpr int SM_A_TOTAL = SM_BAR + 256;
constexpr int SM_TWO = SM_X1;
constexpr int SM_TST = SM_TWO + 36864;
constexpr int SM_TIN = SM_W;
enum { B_FULL = 0, B_EMPTY = 3, B_TIN = 6, B_TFREE = 8, B_WK = 10, B_WQ, B_WO, B_Q0, B_ODONE, B_KFREE = B_ODONE + 2, B_VFREE, B_COUNT };
enum { N_KRDY = 4, N_QK0, N_QK1, N_VQ0, N_VQ1, N_PVISS };

#define SPL 4
#define RA 152
#define RG 184
__device__ int g_flags[TB * 56];

#define TR(role, it, k)
#define TRDECL
#define TRARG
#define TRPASS
#define TRDUMP
#define TRB(it, k)
#define TR2(blk, k)

struct GemmCtx {
  uint32_t bar;
  uint32_t kC, vC, qC;
  uint32_t kH, vH;
  bool hvalid;
};

template <int STRIDE> __device__ __forceinline__ void dump12(uint32_t a, const uint32_t (&r)[12]) {
#pragma unroll
  for (int j = 0; j < 3; j++) stsm4(a + j * 2 * STRIDE, r[4 * j], r[4 * j + 1], r[4 * j + 2], r[4 * j + 3]);
}
template <int N> __device__ __forceinline__ void pack12(uint32_t (&r)[12], const float (&d)[N], int off) {
#pragma unroll
  for (int j = 0; j < 12; j++) r[j] = pack2(d[off + 2 * j], d[off + 2 * j + 1]);
}
template <int XS, int K0, int K1> __device__ __forceinline__ void issue_core(float (&d)[72]) {
  constexpr uint64_t da = mkdesc(SBC + XS, 16, 1024, 1), db = mkdesc(SBC + SM_W, 6144, 256, 3);
  wg_fence();
  if (K0 == 0) wg_ss144<0>(d, da, db);
#pragma unroll
  for (int k = K0 ? K0 : 1; k < K1; k++) wg_ss144<1>(d, da + (k >> 2) * 512 + (k & 3) * 2, db + k * 32);
  wg_commit();
}
template <int K0, int K1> __device__ __forceinline__ void issue_halo(float (&d)[48]) {
  constexpr uint64_t da = mkdesc(SBC + SM_X0 - 2048, 16, 1024, 1), db = mkdesc(SBC + SM_W, 6144, 256, 3);
  wg_fence();
  if (K0 == 0) wg_ss96<0>(d, da, db);
#pragma unroll
  for (int k = K0 ? K0 : 1; k < K1; k++) wg_ss96<1>(d, da + (k >> 2) * 384 + (k & 3) * 2, db + k * 32);
  wg_commit();
}
template <int ST, int BYTES> __device__ __forceinline__ void release_stage(const GemmCtx& c, bool on) {
  asm volatile("{\n.reg .pred p, q;\n.reg .b32 ra;\nsetp.ne.b32 q, %2, 0;\nelect.sync _|p, 0xffffffff;\nand.pred p, p, q;\n"
               "mapa.shared::cluster.u32 ra, %1, %4;\n"
               "@p mbarrier.arrive.expect_tx.shared::cta.b64 _, [%0], %3;\n@p mbarrier.arrive.shared::cluster.b64 _, [ra];\n}"
               ::"r"(c.bar + (B_FULL + ST) * 8), "r"(c.bar + (B_EMPTY + ST) * 8), "r"((int)on), "n"(BYTES / 4), "n"(ST) : "memory");
}
__device__ __forceinline__ void load_w(const CUtensorMap* m, uint32_t dst, uint32_t bar, int col) {
  asm volatile("cp.async.bulk.tensor.2d.shared::cluster.global.mbarrier::complete_tx::bytes [%0], [%1, {%3,%4}], [%2];"
               ::"r"(dst), "l"(m), "r"(bar), "r"(col), "r"(0) : "memory");
}
__device__ __forceinline__ void publish(uint32_t bar) {
  fence_async();
  __syncwarp();
  mbar_arrive_elect(bar);
}

template <bool FIRST, bool LAST>
__device__ __forceinline__ void gemm_iter(const GemmCtx& c, int b, uint32_t (&pk)[12], uint32_t (&pv)[12], uint32_t (&pq)[12], int head TRARG) {
  const uint32_t bar = c.bar;
  const uint32_t pa = b & 1;
  const bool w = b >= 0;
  const uint32_t ko = pa * KSLOT, vx = pa * 16, qx = pa * 128;
  float H[48], C[72];
  uint32_t hk[12], hv[12], pv2[12];
  TR(2, b, 0);
  if (FIRST) mbar_wait(bar + (B_FULL + 0) * 8, pa);
  if (w) nb_sync(N_QK1, 256);
  TR(2, b, 2);
  issue_halo<0, 8>(H);
  TR(2, b, 3);
  if (!FIRST) {
    if (w) mbar_wait(bar + B_KFREE * 8, pa);
    dump12<128>(c.kC + ko, pk);
  }
  issue_halo<8, 12>(H);
  TR(2, b, 4);
  if (!LAST) {
    mbar_wait(bar + (B_FULL + 2) * 8, pa);
    if (FIRST) mbar_wait(bar + B_WQ * 8, 0);
    TR(2, b, 13);
    issue_core<SM_X2, 0, 8>(C);
    TR(2, b, 5);
    if (!FIRST) { fence_async(); dump12<256>(c.qC ^ (qx ^ 192), pq); }
    wg_wait<1>(); pin(H);
    release_stage<0, 18432>(c, true);
  } else {
    dump12<256>(c.qC ^ (qx ^ 192), pq);
    fence_async();
    nb_arrive(N_VQ0, 288); nb_arrive(N_VQ1, 288);
    wg_wait<0>(); pin(H);
    uint32_t ln; asm volatile("mov.u32 %0, %%laneid;" : "=r"(ln));
    if (ln < 4) mbar_arrive_remote(bar + (B_TFREE + (head >> 1)) * 8, ln);
  }
  pack12(hk, H, 0);
  if (c.hvalid) dump12<128>(c.kH + ko, hk);
  pack12(hv, H, 24);
  if (!LAST) {
    issue_core<SM_X2, 8, 12>(C);
    if (w) { nb_arrive(N_VQ0, 288); nb_arrive(N_VQ1, 288); }
    else if (!FIRST) { __syncwarp(); mbar_arrive_elect(bar + B_Q0 * 8); }
    mbar_wait(bar + (B_FULL + 1) * 8, pa);
    TR(2, b, 6);
    wg_wait<0>(); pin(C);
    TR(2, b, 7);
    pack12(pk, C, 0);
    dump12<128>(c.kC + ko + 64, pk);
    release_stage<2, 24576>(c, b < 11);
    pack12(pv2, C, 24);
    pack12(pq, C, 48);
    TR(2, b, 8);
    issue_core<SM_X1, 0, SPL>(C);
    if (w) nb_sync(N_PVISS, 384);
    issue_core<SM_X1, SPL, 8>(C);
    TR(2, b, 9);
  }
  if (!FIRST) fence_async();
  TR(2, b, 14);
  if (!LAST) issue_core<SM_X1, 8, 12>(C);
  if (!FIRST) nb_arrive(N_KRDY, 256);
  TR(2, b, 1);
  if (!LAST) mbar_wait(bar + (B_FULL + 0) * 8, pa ^ 1);
  if (w) mbar_wait(bar + B_VFREE * 8, pa);
  TR(2, b, 10);
  if (!FIRST) dump12<128>(c.vC ^ vx, pv);
  if (!LAST) dump12<256>(c.qC ^ qx, pq);
  if (c.hvalid) dump12<128>(c.vH ^ vx, hv);
  if (LAST) { fence_async(); nb_arrive(N_VQ0, 288); nb_arrive(N_VQ1, 288); return; }
  dump12<128>((c.vC ^ vx ^ 16) + 768, pv2);
  TR(2, b, 11);
  wg_wait<0>(); pin(C);
  TR(2, b, 12);
  release_stage<1, 24576>(c, b < 11);
  pack12(pk, C, 0);
  pack12(pv, C, 24);
  pack12(pq, C, 48);
}

__device__ __forceinline__ float fold(float a, float b, float t, int useb) {
  float r;
  asm("{\n.reg .pred p;\nsetp.ne.b32 p, %4, 0;\nfma.rn.f32 %0, %1, 0f3E553B95, %3;\n@p fma.rn.f32 %0, %2, 0f3E553B95, %3;\n}"
      : "=&f"(r) : "f"(a), "f"(b), "f"(t), "r"(useb));
  return r;
}
template <int U, int L, bool BORDER>
__device__ __forceinline__ void softmax_tile(const float (&SA)[56], const float (&SB)[56], const float (&T)[14], int b0, int b1,
                                             uint32_t ra0, uint32_t ra1, int qcu, uint32_t (&P)[28], float (&sx)[8]) {
  float lu[14], ll[14];
#pragma unroll
  for (int j = 0; j < 7; j++) {
    float tu0, tu1, tl0, tl1;
    if (BORDER) {
      tu0 = lds_f32(ra0 + (U + j + 3 - qcu) * 4); tu1 = lds_f32(ra1 + (U + j + 3 - qcu) * 4);
      tl0 = lds_f32(ra0 + (L + j + 2 - qcu) * 4); tl1 = lds_f32(ra1 + (L + j + 2 - qcu) * 4);
    } else { tu0 = tl0 = T[2 * j]; tu1 = tl1 = T[2 * j + 1]; }
    lu[2 * j]     = fold(SA[4 * (U + j)],     SB[4 * (U + j)],     tu0, b0);
    ll[2 * j]     = fold(SA[4 * (L + j) + 2], SB[4 * (L + j) + 2], tl0, b0);
    lu[2 * j + 1] = fold(SA[4 * (U + j) + 1], SB[4 * (U + j) + 1], tu1, b1);
    ll[2 * j + 1] = fold(SA[4 * (L + j) + 3], SB[4 * (L + j) + 3], tl1, b1);
  }
  float mu = lu[0], ml = ll[0], mu2 = lu[1], ml2 = ll[1];
#pragma unroll
  for (int j = 1; j < 7; j++) { mu = fmaxf(mu, lu[2 * j]); mu2 = fmaxf(mu2, lu[2 * j + 1]); ml = fmaxf(ml, ll[2 * j]); ml2 = fmaxf(ml2, ll[2 * j + 1]); }
  mu = fmaxf(mu, mu2); ml = fmaxf(ml, ml2);
  { const float a1 = __shfl_xor_sync(0xffffffffu, mu, 1), a2 = __shfl_xor_sync(0xffffffffu, mu, 2), a3 = __shfl_xor_sync(0xffffffffu, mu, 3);
    const float c1 = __shfl_xor_sync(0xffffffffu, ml, 1), c2 = __shfl_xor_sync(0xffffffffu, ml, 2), c3 = __shfl_xor_sync(0xffffffffu, ml, 3);
    mu = fmaxf(fmaxf(mu, a1), fmaxf(a2, a3)); ml = fmaxf(fmaxf(ml, c1), fmaxf(c2, c3)); }
  float su = 0.f, sl = 0.f;
#pragma unroll
  for (int c = 0; c < 14; c++) {
    const int iu = (c >> 1) * 4 + (c & 1) * 2;
    if (c >= U && c < U + 7) {
      float e0 = ex2(lu[2 * (c - U)] - mu), e1 = ex2(lu[2 * (c - U) + 1] - mu);
      su = c == U ? e0 + e1 : (su + e0) + e1; P[iu] = pack2(e0, e1);
    } else P[iu] = 0u;
    if (c >= L && c < L + 7) {
      float e0 = ex2(ll[2 * (c - L)] - ml), e1 = ex2(ll[2 * (c - L) + 1] - ml);
      sl = c == L ? e0 + e1 : (sl + e0) + e1; P[iu + 1] = pack2(e0, e1);
    } else P[iu + 1] = 0u;
  }
  sx[0] = su; sx[4] = sl;
#pragma unroll
  for (int k = 1; k < 4; k++) { sx[k] = __shfl_xor_sync(0xffffffffu, su, k); sx[4 + k] = __shfl_xor_sync(0xffffffffu, sl, k); }
}

struct Maps { CUtensorMap xc, xh, w, os, wo, ot; };

__global__ void __cluster_dims__(4, 1, 1) __launch_bounds__(512, 1)
na_attn_kernel(const __grid_constant__ Maps mp, const __nv_bfloat16* __restrict__ wqkv, const __nv_bfloat16* __restrict__ rpb) {
  extern __shared__ __align__(1024) uint8_t smem_raw[];
  const uint32_t sb = smem_u32(smem_raw);
  if ((sb & 0x3FFFF) != SBC) return;
  const uint32_t bar = sb + SM_BAR;
  TR2(blockIdx.x, 0);
  const int tid = threadIdx.x, lane = tid & 31;
  const int warp = __shfl_sync(0xffffffffu, tid >> 5, 0);
  const int head = blockIdx.x & 3, cl = blockIdx.x >> 2;
  const int par = cl / 7, strip = cl - par * 7, ph = par >> 1, pw = par & 1;

  uint4 wv[3];
  const int wr = tid / 6, wc = tid - wr * 6;
  if (warp < 12) {
#pragma unroll
    for (int i = 0; i < 3; i++) wv[i] = __ldg(reinterpret_cast<const uint4*>(wqkv + (wr + i * 64) * 576 + 384 + head * 48 + wc * 8));
  } else if (elect_one()) {
    if (warp == 12) {
      mbar_init(bar + B_WK * 8, 1);
#pragma unroll
      for (int i = 0; i < 3; i++) load_w(&mp.w, sb + SM_W + i * 6144, bar + B_WK * 8, 192 + head * 48 + i * 16);
      mbar_expect(bar + B_WK * 8, 18432);
    } else if (warp == 13) {
#pragma unroll
      for (int i = 0; i < B_WK; i++) mbar_init(bar + i * 8, i < B_EMPTY ? 4 : (i < B_TIN ? 16 : (i < B_TFREE ? 1 : 8)));
    } else if (warp == 14) {
#pragma unroll
      for (int i = B_WQ; i < B_COUNT; i++) mbar_init(bar + i * 8, i < B_Q0 ? 1 : (i < B_KFREE ? 4 : 8));
    }
    asm volatile("fence.mbarrier_init.release.cluster;" ::: "memory");
  }
  __syncwarp();
  asm volatile("barrier.cluster.arrive.relaxed.aligned;" ::: "memory");

  if (warp >= 12) {
    asm volatile("setmaxnreg.dec.sync.aligned.u32 24;");
    asm volatile("griddepcontrol.launch_dependents;");
    const int cc = ph * 112 + (head ? strip * 16 : (strip == 0 ? 16 : (strip == 6 ? 74 : strip * 16 - 3)));
    const int sd = strip == 0 ? -1 : (strip == 6 ? 1 : 0);
    const int r0 = head == 0 ? -4 : (head == 1 ? 4 : 0);
    asm volatile("barrier.cluster.wait.aligned;" ::: "memory");
    if (warp == 12) {
      const uint32_t fb = bar + (B_FULL + head) * 8, eb = bar + (B_EMPTY + head) * 8;
      const uint32_t dst = sb + (head == 0 ? SM_X0 : (head == 1 ? SM_X1 : SM_X2));
      const int nl = head == 0 ? 15 : (head == 3 ? 1 : 14);
#pragma unroll 1
      for (int n = 0; n < nl; n++) {
        if (n) mbar_wait(eb, (n - 1) & 1);
        if (elect_one()) {
          if (head == 0) {
            asm volatile("cp.async.bulk.tensor.5d.shared::cluster.global.mbarrier::complete_tx::bytes.multicast::cluster [%0], [%1, {%3,%4,%5,%6,%7}], [%2], %8;"
                         ::"r"(dst), "l"(&mp.xh), "r"(fb), "r"(0), "r"(8 * n + r0), "r"(cc), "r"(sd), "r"(pw * 3), "h"((uint16_t)15) : "memory");
            if (n + 1 < nl) asm volatile("cp.async.bulk.prefetch.tensor.5d.L2.global [%0, {%1,%2,%3,%4,%5}];" ::"l"(&mp.xh), "r"(0), "r"(8 * n + 8 + r0), "r"(cc), "r"(sd), "r"(pw * 3) : "memory");
          } else if (head < 3) {
            asm volatile("cp.async.bulk.tensor.4d.shared::cluster.global.mbarrier::complete_tx::bytes.multicast::cluster [%0], [%1, {%3,%4,%5,%6}], [%2], %7;"
                         ::"r"(dst), "l"(&mp.xc), "r"(fb), "r"(0), "r"(8 * n + r0), "r"(cc), "r"(pw * 3), "h"((uint16_t)15) : "memory");
          }
          if (n == 0) {
#pragma unroll
            for (int i = 0; i < 3; i++) load_w(&mp.w, sb + SM_W + (6 + i) * 6144, bar + B_WQ * 8, head * 48 + i * 16);
            mbar_expect(bar + B_WQ * 8, 18432);
            mbar_expect(bar + B_TIN * 8, 24576); mbar_expect(bar + (B_TIN + 1) * 8, 24576);
          }
          if (head && n + 1 < nl) asm volatile("cp.async.bulk.prefetch.tensor.4d.L2.global [%0, {%1,%2,%3,%4}];" ::"l"(&mp.xc), "r"(0), "r"(8 * n + 8 + r0), "r"(cc), "r"(pw * 3) : "memory");
        }
        __syncwarp();
      }
    }
    if (warp >= 14) {
      const int j = warp - 14;
      int* flag = g_flags + cl * 2 + j;
      nb_arrive(N_VQ0 + j, 288);
#pragma unroll 1
      for (int b = 0; b < TB; b++) {
        mbar_wait(bar + (B_ODONE + j) * 8, b & 1);
        if (lane == 0) {
          asm volatile("cp.async.bulk.tensor.3d.global.shared::cta.bulk_group [%0, {%2,%3,%4}], [%1];"
                       ::"l"(&mp.os), "r"(sb + SM_O + j * 6144), "r"(pw * 192), "r"(8 * b + 2 * head), "r"(ph * 112 + strip * 16 + 8 * j) : "memory");
          asm volatile("cp.async.bulk.commit_group;\ncp.async.bulk.wait_group.read 0;" ::: "memory");
        }
        __syncwarp();
        nb_arrive(N_VQ0 + j, 288);
        if (lane == 0) {
          asm volatile("cp.async.bulk.wait_group 0;\nfence.proxy.async.global;\nred.release.gpu.global.add.s32 [%0], 1;" ::"l"(flag + b * 56) : "memory");
        }
        __syncwarp();
      }
#pragma unroll 1
      for (int i = 0; i < 2; i++) {
        mbar_wait(bar + (B_ODONE + j) * 8, i);
        if (i == 0) { nb_arrive(N_VQ0 + j, 288); mbar_wait(bar + (B_TFREE + j) * 8, 0); }
        if (elect_one()) {
#pragma unroll
          for (int d = 0; d < 2; d++)
            asm volatile("{\n.reg .b32 rd, rb;\nmapa.shared::cluster.u32 rd, %0, %3;\nmapa.shared::cluster.u32 rb, %2, %3;\n"
                         "cp.async.bulk.shared::cluster.shared::cta.mbarrier::complete_tx::bytes [rd], [%1], 6144, [rb];\n}"
                         ::"r"(sb + SM_TIN + i * 24576 + head * 6144), "r"(sb + (i ? SM_Q + j * 12288 : SM_O + j * 6144)), "r"(bar + (B_TIN + i) * 8), "r"(2 * j + d) : "memory");
        }
        __syncwarp();
      }
    }
    cluster_sync();
  } else if (warp >= 8) {
    asm volatile("setmaxnreg.inc.sync.aligned.u32 %0;" ::"n"(RG));
    GemmCtx c;
    c.bar = bar;
    const int gw = warp - 8, tk = gw * 16 + (lane & 15), hi = lane >> 4;
    { const int col = tk >> 2, i = tk & 3;
      c.kC = sb + SM_K + (col + 3) * KS + hi * 128 + i * 16;
      c.vC = sb + SM_V + (col + 3) * 1536 + hi * 128 + (2 * i + ((col + 3) & 1)) * 16;
      c.qC = sb + SM_Q + col * 1536 + hi * 256 + (col & 1) * 64 + i * 16; }
    { const int ci = (tk >> 3) - 2, kc = ci < 3 ? ci : ci + 16, i = tk & 7; c.hvalid = gw > 0;
      c.kH = sb + SM_K + kc * KS + hi * 128 + i * 16;
      c.vH = sb + SM_V + kc * 1536 + hi * 128 + (i >> 2) * 768 + (2 * (i & 3) + ((kc ^ (i >> 2)) & 1)) * 16; }
    asm volatile("barrier.cluster.wait.aligned;" ::: "memory");
    if (elect_one()) { mbar_expect(bar + B_FULL * 8, 4608); mbar_expect(bar + (B_FULL + 1) * 8, 6144); mbar_expect(bar + (B_FULL + 2) * 8, 6144); }
    __syncwarp();
#pragma unroll
    for (int i = 0; i < 3; i++) sts128(sb + SM_W + (3 + (wc >> 1)) * 6144 + (wr + i * 64) * 32 + ((wc ^ (wr >> 2)) & 1) * 16, wv[i]);
    fence_async();
    asm volatile("bar.sync 1, 384;" ::: "memory");
    mbar_wait(bar + B_WK * 8, 0);
    uint32_t pk[12], pv[12], pq[12];
    TRDECL;
    gemm_iter<true, false>(c, -2, pk, pv, pq, head TRPASS);
#pragma unroll 1
    for (int b = -1; b < 12; b++) gemm_iter<false, false>(c, b, pk, pv, pq, head TRPASS);
    asm volatile("bar.sync 2, 128;" ::: "memory");
    if (gw == 0 && elect_one()) {
      mbar_expect(bar + B_WO * 8, 36864);
      asm volatile("cp.async.bulk.tensor.3d.shared::cluster.global.mbarrier::complete_tx::bytes [%0], [%1, {%3,%4,%5}], [%2];"
                   ::"r"(sb + SM_TWO), "l"(&mp.wo), "r"(bar + B_WO * 8), "r"(0), "r"(0), "r"((head & 1) * 3) : "memory");
    }
    __syncwarp();
    gemm_iter<false, true>(c, 12, pk, pv, pq, head TRPASS);
    TRDUMP;
    mbar_wait(bar + B_WO * 8, 0);
    nb_sync(N_QK1, 256);
    const uint32_t st = sb + SM_TST + gw * 3072;
    const uint32_t sta = st + (lane & 15) * 64 + ((hi ^ ((lane >> 1) & 3)) * 16);
#pragma unroll 1
    for (int i = 0; i < 2; i++) {
      constexpr uint64_t db = mkdesc(SBC + SM_TWO, 12288, 512, 2);
      const uint64_t da = mkdesc(SBC + SM_TIN, 128, 768, 0) + i * (24576 / 16);
      float D[48];
      mbar_wait(bar + (B_TIN + i) * 8, 0);
      wg_fence();
      wg_ss96<0>(D, da, db);
#pragma unroll
      for (int k = 1; k < 12; k++) wg_ss96<1>(D, da + (k / 3) * 384 + (k % 3) * 16, db + k * 64);
      wg_commit();
      if (lane == 0) asm volatile("cp.async.bulk.wait_group.read 0;" ::: "memory");
      __syncwarp();
      wg_wait<0>(); pin(D);
#pragma unroll
      for (int q = 0; q < 6; q++)
        stsm4((sta ^ ((q & 1) * 32)) + (q >> 1) * 1024,
              pack2(D[8 * q], D[8 * q + 1]), pack2(D[8 * q + 2], D[8 * q + 3]), pack2(D[8 * q + 4], D[8 * q + 5]), pack2(D[8 * q + 6], D[8 * q + 7]));
      fence_async();
      __syncwarp();
      if (lane == 0) {
        asm volatile("cp.async.bulk.tensor.4d.global.shared::cta.bulk_group [%0, {%2,%3,%4,%5}], [%1];"
                     ::"l"(&mp.ot), "r"(st), "r"(0), "r"(8 * (TB + i)), "r"(ph * 112 + strip * 16 + 8 * (head >> 1) + 2 * gw), "r"(pw * 6 + (head & 1) * 3) : "memory");
        asm volatile("cp.async.bulk.commit_group;" ::: "memory");
      }
    }
    asm volatile("barrier.cluster.arrive.relaxed.aligned;" ::: "memory");
    if (lane == 0) asm volatile("cp.async.bulk.wait_group 0;" ::: "memory");
    __syncwarp();
    asm volatile("barrier.cluster.wait.aligned;" ::: "memory");
  } else {
    asm volatile("setmaxnreg.inc.sync.aligned.u32 %0;" ::"n"(RA));
    float rv = -INFINITY;
    if (tid < 169) rv = __bfloat162float(rpb[head * 169 + tid]) * 1.4426950408889634f;
    if (tid < 192) {
      const int kc = (wr & 15) + 3;
      sts128(tid < 96 ? sb + SM_K + kc * KS + wc * 128 + 48 : sb + SM_V + kc * 1536 + wc * 128 + (6 + (kc & 1)) * 16, make_uint4(0, 0, 0, 0));
    }
#pragma unroll
    for (int i = 0; i < 3; i++) sts128(sb + SM_W + (3 + (wc >> 1)) * 6144 + (wr + i * 64) * 32 + ((wc ^ (wr >> 2)) & 1) * 16, wv[i]);
    fence_async();
    asm volatile("bar.arrive 1, 384;" ::: "memory");
    if (tid < 182) asm volatile("st.shared.f32 [%0], %1;" ::"r"(sb + SM_RPB + tid * 4), "f"(rv) : "memory");
    const int j = warp >> 2, w = warp & 3;
    int variant = w;
    if (strip == 0 && j == 0 && w < 2) variant = 4;
    if (strip == 6 && j == 1 && w >= 2) variant = 5;
    const uint32_t qa = sb + SM_Q + (8 * j + 2 * w + ((lane >> 3) & 1)) * 1536 + (lane >> 4) * 256 + (((lane & 7) * 16) ^ (((lane >> 3) & 1) * 64));
    uint32_t oa = sb + SM_O + j * 6144 + (2 * w + ((lane >> 3) & 1)) * 768 + (lane >> 4) * 128 + (lane & 7) * 16;
    const uint64_t dK = mkdesc(SBC + SM_K, 128, KS, 0) + j * (8 * KS / 16);
    const uint64_t dV = mkdesc(SBC + SM_V, 768, 128, 0) + j * (8 * 1536 / 16);
    asm volatile("barrier.cluster.wait.aligned;" ::: "memory");
    asm volatile("bar.sync 3, 256;" ::: "memory");
    float T[14];
    TRDECL;
    int b0 = 0, b1 = 0;
    uint32_t ra0 = 0, ra1 = 0, meta = 0;
    uint32_t q[12];
    mbar_wait(bar + B_Q0 * 8, 0);
#pragma unroll
    for (int k = 0; k < 3; k++) ldsm4(qa + k * 512, q[4 * k], q[4 * k + 1], q[4 * k + 2], q[4 * k + 3]);
#pragma unroll 1
    for (int b = 0; b < 14; b++) {
      const uint32_t pa = b & 1;
      if (b <= 1 || b == 13) {
        uint32_t ln; asm volatile("mov.u32 %0, %%laneid;" : "=r"(ln));
        const int g = ln >> 2, t = ln & 3;
        const int sw = b == 0 ? max(g + 1, 4) : (b == 13 ? min(g + 1, 5) : g + 1);
        const int i0 = 2 * t, i1 = 2 * t + 1;
        b0 = i0 <= sw - 2; b1 = i1 <= sw - 2;
        const int m = sw - 1;
        ra0 = sb + SM_RPB + (i0 == m ? 13 : i0 + (b0 ? 8 : 0) - g + 2) * 52;
        ra1 = sb + SM_RPB + (i1 == m ? 13 : i1 + (b1 ? 8 : 0) - g + 2) * 52;
#pragma unroll
        for (int jj = 0; jj < 7; jj++) { T[2 * jj] = lds_f32(ra0 + (jj + 3) * 4); T[2 * jj + 1] = lds_f32(ra1 + (jj + 3) * 4); }
        uint32_t m16 = 0x8888u;
#pragma unroll
        for (int i = 0; i < 8; i++) m16 |= (uint32_t)(((i <= sw - 2) ^ (i >> 2) ^ t ^ b) & 1) << (2 * i);
        meta = m16 | (m16 << 16);
        if (b == 13) oa += SM_Q - SM_O + j * 6144;
      } else meta ^= 0x55555555u;
      float SA[56], SB[56];
      const uint64_t dA = dK + pa * (KSLOT >> 4), dB = dK + (pa ^ 1) * (KSLOT >> 4);
      TR(0, b, 0);
      nb_sync(N_KRDY + j, 256);
      TR(0, b, 1);
      TR(0, b - 1, 9);
      wg_fence();
      wg_rs112<0>(SA, q[0], q[1], q[2], q[3], dA);
      wg_rs112<0>(SB, q[0], q[1], q[2], q[3], dB);
      wg_rs112<1>(SA, q[4], q[5], q[6], q[7], dA + 16);
      wg_rs112<1>(SB, q[4], q[5], q[6], q[7], dB + 16);
      wg_rs112<1>(SA, q[8], q[9], q[10], q[11], dA + 32);
      wg_rs112<1>(SB, q[8], q[9], q[10], q[11], dB + 32);
      wg_commit();
      nb_arrive(N_QK0 + j, 256);
      TR(0, b, 2);
      wg_wait<0>(); pin(SA); pin(SB);
      mbar_arrive_elect(bar + B_KFREE * 8);
      TR(0, b, 3);
      TR(0, b - 1, 10);
      uint32_t P[28];
      float sx[8];
      switch (variant) {
        case 0: softmax_tile<0, 1, false>(SA, SB, T, b0, b1, ra0, ra1, 0, P, sx); break;
        case 1: softmax_tile<2, 3, false>(SA, SB, T, b0, b1, ra0, ra1, 0, P, sx); break;
        case 2: softmax_tile<4, 5, false>(SA, SB, T, b0, b1, ra0, ra1, 0, P, sx); break;
        case 3: softmax_tile<6, 7, false>(SA, SB, T, b0, b1, ra0, ra1, 0, P, sx); break;
        case 4: softmax_tile<3, 3, true>(SA, SB, T, b0, b1, ra0, ra1, 2 * w, P, sx); break;
        default: softmax_tile<4, 4, true>(SA, SB, T, b0, b1, ra0, ra1, 2 * w, P, sx); break;
      }
      float O[24];
      TR(0, b, 4);
      nb_sync(N_VQ0 + j, 288);
      TR(0, b, 5);
#pragma unroll
      for (int k = 0; k < 3; k++) ldsm4(qa + (pa ^ 1) * 128 + k * 512, q[4 * k], q[4 * k + 1], q[4 * k + 2], q[4 * k + 3]);
      wg_fence();
      wg_sp48<0>(O, P[0], P[1], P[2], P[3], dV, meta);
#pragma unroll
      for (int s = 1; s < 7; s++) wg_sp48<1>(O, P[4 * s], P[4 * s + 1], P[4 * s + 2], P[4 * s + 3], dV + s * 192, meta);
      wg_commit();
      if (b < 12) nb_arrive(N_PVISS, 384);
      TR(0, b, 6);
      wg_wait<0>(); pin(O);
      mbar_arrive_elect(bar + B_VFREE * 8);
      TR(0, b, 7);
      float ru, rl;
      asm("rcp.approx.ftz.f32 %0, %1;" : "=f"(ru) : "f"(((fmaf(O[0], 0.f, sx[0]) + sx[1]) + sx[2]) + sx[3]));
      asm("rcp.approx.ftz.f32 %0, %1;" : "=f"(rl) : "f"(((fmaf(O[2], 0.f, sx[4]) + sx[5]) + sx[6]) + sx[7]));
#pragma unroll
      for (int i = 0; i < 3; i++)
        stsm4(oa + i * 256, pack2(O[8 * i] * ru, O[8 * i + 1] * ru), pack2(O[8 * i + 2] * rl, O[8 * i + 3] * rl),
              pack2(O[8 * i + 4] * ru, O[8 * i + 5] * ru), pack2(O[8 * i + 6] * rl, O[8 * i + 7] * rl));
      publish(bar + (B_ODONE + j) * 8);
      TR(0, b, 8);
    }
    TRDUMP;
    cluster_sync();
    TR2(blockIdx.x, 2);
  }
}

constexpr int NSTB = 4;
constexpr int NTB = TB * 56;
constexpr int SM_B_ST = 0;
constexpr int SM_B_IN = 49152;
constexpr int SM_B_W = SM_B_IN + NSTB * 24576;
constexpr int SM_B_BAR = SM_B_W + 73728;
constexpr int SM_B_TOTAL = SM_B_BAR + 128;
struct MapsB { CUtensorMap oi, oo, wo; };

__global__ void __launch_bounds__(288, 1)
na_proj_kernel(const __grid_constant__ MapsB mp) {
  extern __shared__ __align__(1024) uint8_t smem_raw[];
  const uint32_t sb = smem_u32(smem_raw);
  if ((sb & 0x3FFFF) != SBC) return;
  const uint32_t bar = sb + SM_B_BAR;
  const int tid = threadIdx.x, lane = tid & 31;
  const int warp = __shfl_sync(0xffffffffu, tid >> 5, 0);
  TR2(132 + blockIdx.x, 0);
  TRB(47, 0);
  if (warp == 8 && elect_one()) {
#pragma unroll
    for (int i = 0; i <= 2 * NSTB; i++) mbar_init(bar + i * 8, i < NSTB || i == 2 * NSTB ? 1 : 4);
    mbar_expect(bar + 2 * NSTB * 8, 73728);
#pragma unroll
    for (int i = 0; i < 2; i++)
      asm volatile("cp.async.bulk.tensor.3d.shared::cluster.global.mbarrier::complete_tx::bytes [%0], [%1, {%3,%4,%5}], [%2];"
                   ::"r"(sb + SM_B_W + i * 36864), "l"(&mp.wo), "r"(bar + 2 * NSTB * 8), "r"(0), "r"(0), "r"(i * 3) : "memory");
  }
  __syncthreads();
  const int step = gridDim.x;
  if (warp == 8) {
    int it = 0;
    uint32_t spin = 0;
#pragma unroll 1
    for (int n = blockIdx.x; n < NTB && spin < SPIN_LIMIT; spin++) {
      int v = 0;
      const int mine = n + lane * step;
      if (lane < 8 && mine < NTB) asm volatile("ld.acquire.gpu.global.s32 %0, [%1];" : "=r"(v) : "l"(g_flags + mine) : "memory");
      int cnt = __ffs(~__ballot_sync(0xffffffffu, v >= 4)) - 1;
      asm volatile("fence.proxy.async.global;" ::: "memory");
      __syncwarp();
#pragma unroll 1
      for (; cnt > 0; cnt--, n += step, it++) {
        TRB(it, 0);
        const int b = n / 56, rem = n - b * 56, par = rem / 14;
        const int st = it & (NSTB - 1), use = it / NSTB;
        if (use) mbar_wait(bar + (NSTB + st) * 8, (use - 1) & 1);
        if (elect_one()) {
          mbar_expect(bar + st * 8, 24576);
          asm volatile("cp.async.bulk.tensor.3d.shared::cluster.global.mbarrier::complete_tx::bytes [%0], [%1, {%3,%4,%5}], [%2];"
                       ::"r"(sb + SM_B_IN + st * 24576), "l"(&mp.oi), "r"(bar + st * 8), "r"((par & 1) * 192), "r"(8 * b), "r"((par >> 1) * 112 + (rem - par * 14) * 8) : "memory");
        }
        __syncwarp();
        TRB(it, 2);
      }
    }
    for (int n = blockIdx.x + lane * step; n < NTB; n += 32 * step) g_flags[n] = 0;
  } else {
    const int wg = warp >> 2, w = warp & 3;
    constexpr uint64_t db = mkdesc(SBC + SM_B_W, 12288, 512, 2);
    const uint32_t st = sb + SM_B_ST + warp * 6144;
    const uint32_t sta = st + (lane & 15) * 128 + (((lane >> 4) ^ (lane & 7)) * 16);
    mbar_wait(bar + 2 * NSTB * 8, 0);
    TRB(47, 1);
    int it = wg;
#pragma unroll 1
    for (int n = blockIdx.x + wg * step; n < NTB; n += 2 * step, it += 2) {
      const int b = n / 56, rem = n - b * 56, par = rem / 14, sg = it & (NSTB - 1);
      const uint64_t da = mkdesc(SBC + SM_B_IN, 128, 3072, 0) + sg * (24576 / 16);
      float D[96];
      mbar_wait(bar + sg * 8, (it / NSTB) & 1);
      TRB(it, 3);
      wg_fence();
      wg_ss192<0>(D, da, db);
#pragma unroll
      for (int k = 1; k < 12; k++) wg_ss192<1>(D, da + k * 16, db + k * 64);
      wg_commit();
      TRB(it, 4);
      if (lane == 0) asm volatile("cp.async.bulk.wait_group.read 0;" ::: "memory");
      __syncwarp();
      wg_wait<0>(); pin(D);
      mbar_arrive_elect(bar + (NSTB + sg) * 8);
      TRB(it, 5);
#pragma unroll
      for (int q = 0; q < 12; q++)
        stsm4((sta ^ ((q & 3) * 32)) + (q >> 2) * 2048,
              pack2(D[8 * q], D[8 * q + 1]), pack2(D[8 * q + 2], D[8 * q + 3]), pack2(D[8 * q + 4], D[8 * q + 5]), pack2(D[8 * q + 6], D[8 * q + 7]));
      fence_async();
      __syncwarp();
      if (lane == 0) {
        asm volatile("cp.async.bulk.tensor.4d.global.shared::cta.bulk_group [%0, {%2,%3,%4,%5}], [%1];"
                     ::"l"(&mp.oo), "r"(st), "r"(0), "r"(8 * b), "r"((par >> 1) * 112 + (rem - par * 14) * 8 + 2 * w), "r"((par & 1) * 3) : "memory");
        asm volatile("cp.async.bulk.commit_group;" ::: "memory");
      }
      TRB(it, 6);
    }
    if (lane == 0) asm volatile("cp.async.bulk.wait_group 0;" ::: "memory");
    TR2(132 + blockIdx.x, 2);
  }
}

typedef CUresult (*EncodeFn)(CUtensorMap*, CUtensorMapDataType, cuuint32_t, void*, const cuuint64_t*, const cuuint64_t*, const cuuint32_t*,
                             const cuuint32_t*, CUtensorMapInterleave, CUtensorMapSwizzle, CUtensorMapL2promotion, CUtensorMapFloatOOBfill);
static EncodeFn g_enc = nullptr;
static void make_map(CUtensorMap* m, const void* p, int rank, const cuuint64_t* dim, const cuuint64_t* str, const cuuint32_t* box, CUtensorMapSwizzle sw) {
  const cuuint32_t ones[5] = {1, 1, 1, 1, 1};
  g_enc(m, CU_TENSOR_MAP_DATA_TYPE_BFLOAT16, rank, (void*)p, dim, str, box, ones, CU_TENSOR_MAP_INTERLEAVE_NONE, sw,
        CU_TENSOR_MAP_L2_PROMOTION_L2_128B, CU_TENSOR_MAP_FLOAT_OOB_FILL_NONE);
}

extern "C" void kernel_launch(void* const* d_in, const int* in_sizes, int n_in, void* d_out, int out_size) {
  const __nv_bfloat16* x = (const __nv_bfloat16*)d_in[0];
  const __nv_bfloat16* wqkv = (const __nv_bfloat16*)d_in[1];
  const __nv_bfloat16* wo = (const __nv_bfloat16*)d_in[2];
  const __nv_bfloat16* rpb = (const __nv_bfloat16*)d_in[3];

  if (!g_enc) {
    void* fn = nullptr; cudaDriverEntryPointQueryResult qr;
    cudaGetDriverEntryPoint("cuTensorMapEncodeTiled", &fn, cudaEnableDefault, &qr);
    g_enc = (EncodeFn)fn;
    cudaFuncSetAttribute(na_attn_kernel, cudaFuncAttributeMaxDynamicSharedMemorySize, SM_A_TOTAL);
    cudaFuncSetAttribute(na_proj_kernel, cudaFuncAttributeMaxDynamicSharedMemorySize, SM_B_TOTAL);
  }
  Maps ma; MapsB mb;
  { cuuint64_t dim[4] = {64, 112, 224, 6}, str[3] = {(cuuint64_t)ROWB, 768, 128};
    cuuint32_t box[4] = {64, 4, 16, 3}, boxo[4] = {64, 8, 2, 3};
    make_map(&ma.xc, x, 4, dim, str, box, CU_TENSOR_MAP_SWIZZLE_128B);
    make_map(&mb.oo, d_out, 4, dim, str, boxo, CU_TENSOR_MAP_SWIZZLE_128B); }
  { cuuint64_t dim[5] = {64, 112, 224, 2, 6}, str[4] = {(cuuint64_t)ROWB, 768, 19 * 768, 128};
    cuuint32_t box[5] = {64, 8, 3, 2, 3};
    make_map(&ma.xh, x, 5, dim, str, box, CU_TENSOR_MAP_SWIZZLE_128B); }
  { cuuint64_t dim[3] = {384, 112, 224}, str[2] = {(cuuint64_t)ROWB, 768};
    cuuint32_t box[3] = {192, 8, 8}, boxs[3] = {192, 2, 8};
    make_map(&mb.oi, d_out, 3, dim, str, box, CU_TENSOR_MAP_SWIZZLE_NONE);
    make_map(&ma.os, d_out, 3, dim, str, boxs, CU_TENSOR_MAP_SWIZZLE_NONE); }
  { cuuint64_t dim[4] = {32, 112, 224, 12}, str[3] = {(cuuint64_t)ROWB, 768, 64};
    cuuint32_t box[4] = {32, 8, 2, 3};
    make_map(&ma.ot, d_out, 4, dim, str, box, CU_TENSOR_MAP_SWIZZLE_64B); }
  { cuuint64_t dim[2] = {576, 192}, str[1] = {1152};
    cuuint32_t box[2] = {16, 192};
    make_map(&ma.w, wqkv, 2, dim, str, box, CU_TENSOR_MAP_SWIZZLE_32B); }
  { cuuint64_t dim[3] = {32, 192, 6}, str[2] = {384, 64};
    cuuint32_t box[3] = {32, 192, 3};
    make_map(&ma.wo, wo, 3, dim, str, box, CU_TENSOR_MAP_SWIZZLE_64B);
    mb.wo = ma.wo; }
  na_attn_kernel<<<112, 512, SM_A_TOTAL>>>(ma, wqkv, rpb);
  cudaLaunchConfig_t cfg = {};
  cfg.gridDim = dim3(20); cfg.blockDim = dim3(288); cfg.dynamicSmemBytes = SM_B_TOTAL; cfg.stream = cudaStreamPerThread;
  cudaLaunchAttribute at[1];
  at[0].id = cudaLaunchAttributeProgrammaticStreamSerialization; at[0].val.programmaticStreamSerializationAllowed = 1;
  cfg.attrs = at; cfg.numAttrs = 1;
  cudaLaunchKernelEx(&cfg, na_proj_kernel, mb);
}
```

```cpp
#include <cuda_runtime.h>
#include <cuda_bf16.h>
#include <cuda.h>
#include <stdint.h>

#define SPIN_LIMIT (1u << 18)

__device__ __forceinline__ uint32_t smem_u32(const void* p) { return (uint32_t)__cvta_generic_to_shared(p); }
__device__ __forceinline__ void wg_fence() { asm volatile("wgmma.fence.sync.aligned;" ::: "memory"); }
__device__ __forceinline__ void wg_commit() { asm volatile("wgmma.commit_group.sync.aligned;" ::: "memory"); }
template <int N> __device__ __forceinline__ void wg_wait() { asm volatile("wgmma.wait_group.sync.aligned %0;" ::"n"(N) : "memory"); }
template <int N> __device__ __forceinline__ void pin(float (&d)[N]) {
#pragma unroll
  for (int i = 0; i < N; i++) asm volatile("" : "+f"(d[i])::"memory");
}
__host__ __device__ constexpr uint64_t mkdesc(uint32_t addr, uint32_t lbo, uint32_t sbo, uint32_t sw) {
  return (uint64_t)((addr & 0x3FFFF) >> 4) | ((uint64_t)(lbo >> 4) << 16) | ((uint64_t)(sbo >> 4) << 32) | ((uint64_t)sw << 62);
}
__device__ __forceinline__ void mbar_init(uint32_t bar, uint32_t cnt) { asm volatile("mbarrier.init.shared::cta.b64 [%0], %1;" ::"r"(bar), "r"(cnt) : "memory"); }
__device__ __forceinline__ void mbar_arrive(uint32_t bar) { asm volatile("mbarrier.arrive.shared::cta.b64 _, [%0];" ::"r"(bar) : "memory"); }
__device__ __forceinline__ bool elect_one() {
  uint32_t r; asm volatile("{\n.reg .pred p;\nelect.sync _|p, 0xffffffff;\nselp.u32 %0, 1, 0, p;\n}" : "=r"(r)); return r;
}
__device__ __forceinline__ void mbar_arrive_elect(uint32_t bar) {
  asm volatile("{\n.reg .pred p;\nelect.sync _|p, 0xffffffff;\n@p mbarrier.arrive.shared::cta.b64 _, [%0];\n}" ::"r"(bar) : "memory");
}
__device__ __forceinline__ void mbar_expect(uint32_t bar, uint32_t bytes) { asm volatile("mbarrier.arrive.expect_tx.shared::cta.b64 _, [%0], %1;" ::"r"(bar), "r"(bytes) : "memory"); }
__device__ __forceinline__ void mbar_arrive_remote(uint32_t bar, uint32_t cta) {
  asm volatile("{\n.reg .b32 ra;\nmapa.shared::cluster.u32 ra, %0, %1;\nmbarrier.arrive.shared::cluster.b64 _, [ra];\n}" ::"r"(bar), "r"(cta) : "memory");
}
__device__ __forceinline__ void mbar_wait(uint32_t bar, uint32_t parity) {
  asm volatile("{\n.reg .pred p;\n.reg .b32 n;\nmov.b32 n, 0;\nWL:\nmbarrier.try_wait.parity.shared::cta.b64 p, [%0], %1;\n@p bra WD;\n"
               "add.u32 n, n, 1;\nsetp.lt.u32 p, n, 65536;\n@p bra WL;\nWD:\n}" ::"r"(bar), "r"(parity) : "memory");
}
__device__ __forceinline__ void nb_sync(int id, int n) { asm volatile("bar.sync %0, %1;" ::"r"(id), "r"(n) : "memory"); }
__device__ __forceinline__ void nb_arrive(int id, int n) { asm volatile("bar.arrive %0, %1;" ::"r"(id), "r"(n) : "memory"); }
__device__ __forceinline__ void fence_async() { asm volatile("fence.proxy.async.shared::cta;" ::: "memory"); }
__device__ __forceinline__ void cluster_sync() {
  asm volatile("barrier.cluster.arrive.relaxed.aligned;\nbarrier.cluster.wait.aligned;" ::: "memory");
}
__device__ __forceinline__ uint32_t pack2(float lo, float hi) {
  uint32_t r; asm("cvt.rn.bf16x2.f32 %0, %1, %2;" : "=r"(r) : "f"(hi), "f"(lo)); return r;
}
__device__ __forceinline__ void stsm4(uint32_t a, uint32_t r0, uint32_t r1, uint32_t r2, uint32_t r3) {
  asm volatile("stmatrix.sync.aligned.m8n8.x4.shared.b16 [%0], {%1,%2,%3,%4};" ::"r"(a), "r"(r0), "r"(r1), "r"(r2), "r"(r3) : "memory");
}
__device__ __forceinline__ void ldsm4(uint32_t a, uint32_t& r0, uint32_t& r1, uint32_t& r2, uint32_t& r3) {
  asm volatile("ldmatrix.sync.aligned.m8n8.x4.shared.b16 {%0,%1,%2,%3}, [%4];" : "=r"(r0), "=r"(r1), "=r"(r2), "=r"(r3) : "r"(a) : "memory");
}
__device__ __forceinline__ void sts128(uint32_t a, uint4 v) {
  asm volatile("st.shared.v4.b32 [%0], {%1,%2,%3,%4};" ::"r"(a), "r"(v.x), "r"(v.y), "r"(v.z), "r"(v.w) : "memory");
}
__device__ __forceinline__ float lds_f32(uint32_t a) { float v; asm volatile("ld.shared.f32 %0, [%1];" : "=f"(v) : "r"(a)); return v; }
__device__ __forceinline__ float ex2(float x) { float y; asm("ex2.approx.ftz.f32 %0, %1;" : "=f"(y) : "f"(x)); return y; }

template<int SC> __device__ __forceinline__ void wg_ss144(float (&d)[72], uint64_t da, uint64_t db) {
  asm volatile("{\n.reg .pred p;\nsetp.ne.b32 p, %74, 0;\nwgmma.mma_async.sync.aligned.m64n144k16.f32.bf16.bf16 {%0,%1,%2,%3,%4,%5,%6,%7,%8,%9,%10,%11,%12,%13,%14,%15,%16,%17,%18,%19,%20,%21,%22,%23,%24,%25,%26,%27,%28,%29,%30,%31,%32,%33,%34,%35,%36,%37,%38,%39,%40,%41,%42,%43,%44,%45,%46,%47,%48,%49,%50,%51,%52,%53,%54,%55,%56,%57,%58,%59,%60,%61,%62,%63,%64,%65,%66,%67,%68,%69,%70,%71}, %72, %73, p, 1, 1, 0, 1;\n}\n"
    : "+f"(d[0]),"+f"(d[1]),"+f"(d[2]),"+f"(d[3]),"+f"(d[4]),"+f"(d[5]),"+f"(d[6]),"+f"(d[7]),"+f"(d[8]),"+f"(d[9]),"+f"(d[10]),"+f"(d[11]),"+f"(d[12]),"+f"(d[13]),"+f"(d[14]),"+f"(d[15]),"+f"(d[16]),"+f"(d[17]),"+f"(d[18]),"+f"(d[19]),"+f"(d[20]),"+f"(d[21]),"+f"(d[22]),"+f"(d[23]),"+f"(d[24]),"+f"(d[25]),"+f"(d[26]),"+f"(d[27]),"+f"(d[28]),"+f"(d[29]),"+f"(d[30]),"+f"(d[31]),"+f"(d[32]),"+f"(d[33]),"+f"(d[34]),"+f"(d[35]),"+f"(d[36]),"+f"(d[37]),"+f"(d[38]),"+f"(d[39]),"+f"(d[40]),"+f"(d[41]),"+f"(d[42]),"+f"(d[43]),"+f"(d[44]),"+f"(d[45]),"+f"(d[46]),"+f"(d[47]),"+f"(d[48]),"+f"(d[49]),"+f"(d[50]),"+f"(d[51]),"+f"(d[52]),"+f"(d[53]),"+f"(d[54]),"+f"(d[55]),"+f"(d[56]),"+f"(d[57]),"+f"(d[58]),"+f"(d[59]),"+f"(d[60]),"+f"(d[61]),"+f"(d[62]),"+f"(d[63]),"+f"(d[64]),"+f"(d[65]),"+f"(d[66]),"+f"(d[67]),"+f"(d[68]),"+f"(d[69]),"+f"(d[70]),"+f"(d[71]) : "l"(da), "l"(db), "n"(SC));
}
template<int SC> __device__ __forceinline__ void wg_ss96(float (&d)[48], uint64_t da, uint64_t db) {
  asm volatile("{\n.reg .pred p;\nsetp.ne.b32 p, %50, 0;\nwgmma.mma_async.sync.aligned.m64n96k16.f32.bf16.bf16 {%0,%1,%2,%3,%4,%5,%6,%7,%8,%9,%10,%11,%12,%13,%14,%15,%16,%17,%18,%19,%20,%21,%22,%23,%24,%25,%26,%27,%28,%29,%30,%31,%32,%33,%34,%35,%36,%37,%38,%39,%40,%41,%42,%43,%44,%45,%46,%47}, %48, %49, p, 1, 1, 0, 1;\n}\n"
    : "+f"(d[0]),"+f"(d[1]),"+f"(d[2]),"+f"(d[3]),"+f"(d[4]),"+f"(d[5]),"+f"(d[6]),"+f"(d[7]),"+f"(d[8]),"+f"(d[9]),"+f"(d[10]),"+f"(d[11]),"+f"(d[12]),"+f"(d[13]),"+f"(d[14]),"+f"(d[15]),"+f"(d[16]),"+f"(d[17]),"+f"(d[18]),"+f"(d[19]),"+f"(d[20]),"+f"(d[21]),"+f"(d[22]),"+f"(d[23]),"+f"(d[24]),"+f"(d[25]),"+f"(d[26]),"+f"(d[27]),"+f"(d[28]),"+f"(d[29]),"+f"(d[30]),"+f"(d[31]),"+f"(d[32]),"+f"(d[33]),"+f"(d[34]),"+f"(d[35]),"+f"(d[36]),"+f"(d[37]),"+f"(d[38]),"+f"(d[39]),"+f"(d[40]),"+f"(d[41]),"+f"(d[42]),"+f"(d[43]),"+f"(d[44]),"+f"(d[45]),"+f"(d[46]),"+f"(d[47]) : "l"(da), "l"(db), "n"(SC));
}
template<int SC> __device__ __forceinline__ void wg_rs112(float (&d)[56], uint32_t a0, uint32_t a1, uint32_t a2, uint32_t a3, uint64_t db) {
  asm volatile("{\n.reg .pred p;\nsetp.ne.b32 p, %61, 0;\nwgmma.mma_async.sync.aligned.m64n112k16.f32.bf16.bf16 {%0,%1,%2,%3,%4,%5,%6,%7,%8,%9,%10,%11,%12,%13,%14,%15,%16,%17,%18,%19,%20,%21,%22,%23,%24,%25,%26,%27,%28,%29,%30,%31,%32,%33,%34,%35,%36,%37,%38,%39,%40,%41,%42,%43,%44,%45,%46,%47,%48,%49,%50,%51,%52,%53,%54,%55}, {%56,%57,%58,%59}, %60, p, 1, 1, 0;\n}\n"
    : "+f"(d[0]),"+f"(d[1]),"+f"(d[2]),"+f"(d[3]),"+f"(d[4]),"+f"(d[5]),"+f"(d[6]),"+f"(d[7]),"+f"(d[8]),"+f"(d[9]),"+f"(d[10]),"+f"(d[11]),"+f"(d[12]),"+f"(d[13]),"+f"(d[14]),"+f"(d[15]),"+f"(d[16]),"+f"(d[17]),"+f"(d[18]),"+f"(d[19]),"+f"(d[20]),"+f"(d[21]),"+f"(d[22]),"+f"(d[23]),"+f"(d[24]),"+f"(d[25]),"+f"(d[26]),"+f"(d[27]),"+f"(d[28]),"+f"(d[29]),"+f"(d[30]),"+f"(d[31]),"+f"(d[32]),"+f"(d[33]),"+f"(d[34]),"+f"(d[35]),"+f"(d[36]),"+f"(d[37]),"+f"(d[38]),"+f"(d[39]),"+f"(d[40]),"+f"(d[41]),"+f"(d[42]),"+f"(d[43]),"+f"(d[44]),"+f"(d[45]),"+f"(d[46]),"+f"(d[47]),"+f"(d[48]),"+f"(d[49]),"+f"(d[50]),"+f"(d[51]),"+f"(d[52]),"+f"(d[53]),"+f"(d[54]),"+f"(d[55]) : "r"(a0), "r"(a1), "r"(a2), "r"(a3), "l"(db), "n"(SC));
}
template<int SC> __device__ __forceinline__ void wg_sp48(float (&d)[24], uint32_t a0, uint32_t a1, uint32_t a2, uint32_t a3, uint64_t db, uint32_t meta) {
  asm volatile("{\n.reg .pred p;\nsetp.ne.b32 p, %30, 0;\nwgmma.mma_async.sp.sync.aligned.m64n48k32.f32.bf16.bf16 {%0,%1,%2,%3,%4,%5,%6,%7,%8,%9,%10,%11,%12,%13,%14,%15,%16,%17,%18,%19,%20,%21,%22,%23}, {%24,%25,%26,%27}, %28, %29, 0, p, 1, 1, 1;\n}\n"
    : "+f"(d[0]),"+f"(d[1]),"+f"(d[2]),"+f"(d[3]),"+f"(d[4]),"+f"(d[5]),"+f"(d[6]),"+f"(d[7]),"+f"(d[8]),"+f"(d[9]),"+f"(d[10]),"+f"(d[11]),"+f"(d[12]),"+f"(d[13]),"+f"(d[14]),"+f"(d[15]),"+f"(d[16]),"+f"(d[17]),"+f"(d[18]),"+f"(d[19]),"+f"(d[20]),"+f"(d[21]),"+f"(d[22]),"+f"(d[23]) : "r"(a0), "r"(a1), "r"(a2), "r"(a3), "l"(db), "r"(meta), "n"(SC));
}
template<int SC> __device__ __forceinline__ void wg_ss192(float (&d)[96], uint64_t da, uint64_t db) {
  asm volatile("{\n.reg .pred p;\nsetp.ne.b32 p, %98, 0;\nwgmma.mma_async.sync.aligned.m64n192k16.f32.bf16.bf16 {%0,%1,%2,%3,%4,%5,%6,%7,%8,%9,%10,%11,%12,%13,%14,%15,%16,%17,%18,%19,%20,%21,%22,%23,%24,%25,%26,%27,%28,%29,%30,%31,%32,%33,%34,%35,%36,%37,%38,%39,%40,%41,%42,%43,%44,%45,%46,%47,%48,%49,%50,%51,%52,%53,%54,%55,%56,%57,%58,%59,%60,%61,%62,%63,%64,%65,%66,%67,%68,%69,%70,%71,%72,%73,%74,%75,%76,%77,%78,%79,%80,%81,%82,%83,%84,%85,%86,%87,%88,%89,%90,%91,%92,%93,%94,%95}, %96, %97, p, 1, 1, 0, 1;\n}\n"
    : "+f"(d[0]),"+f"(d[1]),"+f"(d[2]),"+f"(d[3]),"+f"(d[4]),"+f"(d[5]),"+f"(d[6]),"+f"(d[7]),"+f"(d[8]),"+f"(d[9]),"+f"(d[10]),"+f"(d[11]),"+f"(d[12]),"+f"(d[13]),"+f"(d[14]),"+f"(d[15]),"+f"(d[16]),"+f"(d[17]),"+f"(d[18]),"+f"(d[19]),"+f"(d[20]),"+f"(d[21]),"+f"(d[22]),"+f"(d[23]),"+f"(d[24]),"+f"(d[25]),"+f"(d[26]),"+f"(d[27]),"+f"(d[28]),"+f"(d[29]),"+f"(d[30]),"+f"(d[31]),"+f"(d[32]),"+f"(d[33]),"+f"(d[34]),"+f"(d[35]),"+f"(d[36]),"+f"(d[37]),"+f"(d[38]),"+f"(d[39]),"+f"(d[40]),"+f"(d[41]),"+f"(d[42]),"+f"(d[43]),"+f"(d[44]),"+f"(d[45]),"+f"(d[46]),"+f"(d[47]),"+f"(d[48]),"+f"(d[49]),"+f"(d[50]),"+f"(d[51]),"+f"(d[52]),"+f"(d[53]),"+f"(d[54]),"+f"(d[55]),"+f"(d[56]),"+f"(d[57]),"+f"(d[58]),"+f"(d[59]),"+f"(d[60]),"+f"(d[61]),"+f"(d[62]),"+f"(d[63]),"+f"(d[64]),"+f"(d[65]),"+f"(d[66]),"+f"(d[67]),"+f"(d[68]),"+f"(d[69]),"+f"(d[70]),"+f"(d[71]),"+f"(d[72]),"+f"(d[73]),"+f"(d[74]),"+f"(d[75]),"+f"(d[76]),"+f"(d[77]),"+f"(d[78]),"+f"(d[79]),"+f"(d[80]),"+f"(d[81]),"+f"(d[82]),"+f"(d[83]),"+f"(d[84]),"+f"(d[85]),"+f"(d[86]),"+f"(d[87]),"+f"(d[88]),"+f"(d[89]),"+f"(d[90]),"+f"(d[91]),"+f"(d[92]),"+f"(d[93]),"+f"(d[94]),"+f"(d[95]) : "l"(da), "l"(db), "n"(SC));
}

constexpr uint32_t SBC = 1024;
constexpr int ROWB = 2 * 224 * 384;
constexpr int TB = 12;
constexpr int KS = 832;
constexpr int KSLOT = 22 * KS;
constexpr int SM_X1 = 0;
constexpr int SM_X2 = SM_X1 + 24576;
constexpr int SM_X0 = SM_X2 + 24576;
constexpr int SM_W = SM_X0 + 18432;
constexpr int SM_K = SM_W + 55296;
constexpr int SM_V = SM_K + 2 * KSLOT;
constexpr int SM_Q = SM_V + 22 * 1536;
constexpr int SM_O = SM_Q + 24576;
constexpr int SM_RPB = SM_O + 12288;
constexpr int SM_BAR = SM_RPB + 768;
constexpr int SM_A_TOTAL = SM_BAR + 256;
constexpr int SM_TWO = SM_X1;
constexpr int SM_TST = SM_TWO + 36864;
constexpr int SM_TIN = SM_W;
enum { B_FULL = 0, B_EMPTY = 3, B_TIN = 6, B_TFREE = 8, B_WK = 10, B_WQ, B_WO, B_Q0, B_ODONE, B_KFREE = B_ODONE + 2, B_VFREE, B_COUNT };
enum { N_KRDY = 4, N_QK0, N_QK1, N_VQ0, N_VQ1, N_PVISS };

#define SPL 4
#define RA 152
#define RG 184
__device__ int g_flags[TB * 56];

#define TR(role, it, k)
#define TRDECL
#define TRARG
#define TRPASS
#define TRDUMP
#define TRB(it, k)
#define TR2(blk, k)

struct GemmCtx {
  uint32_t bar;
  uint32_t kC, vC, qC;
  uint32_t kH, vH;
  bool hvalid;
};

template <int STRIDE> __device__ __forceinline__ void dump12(uint32_t a, const uint32_t (&r)[12]) {
#pragma unroll
  for (int j = 0; j < 3; j++) stsm4(a + j * 2 * STRIDE, r[4 * j], r[4 * j + 1], r[4 * j + 2], r[4 * j + 3]);
}
template <int N> __device__ __forceinline__ void pack12(uint32_t (&r)[12], const float (&d)[N], int off) {
#pragma unroll
  for (int j = 0; j < 12; j++) r[j] = pack2(d[off + 2 * j], d[off + 2 * j + 1]);
}
template <int XS, int K0, int K1> __device__ __forceinline__ void issue_core(float (&d)[72]) {
  constexpr uint64_t da = mkdesc(SBC + XS, 16, 1024, 1), db = mkdesc(SBC + SM_W, 6144, 256, 3);
  wg_fence();
  if (K0 == 0) wg_ss144<0>(d, da, db);
#pragma unroll
  for (int k = K0 ? K0 : 1; k < K1; k++) wg_ss144<1>(d, da + (k >> 2) * 512 + (k & 3) * 2, db + k * 32);
  wg_commit();
}
template <int K0, int K1> __device__ __forceinline__ void issue_halo(float (&d)[48]) {
  constexpr uint64_t da = mkdesc(SBC + SM_X0 - 2048, 16, 1024, 1), db = mkdesc(SBC + SM_W, 6144, 256, 3);
  wg_fence();
  if (K0 == 0) wg_ss96<0>(d, da, db);
#pragma unroll
  for (int k = K0 ? K0 : 1; k < K1; k++) wg_ss96<1>(d, da + (k >> 2) * 384 + (k & 3) * 2, db + k * 32);
  wg_commit();
}
template <int ST, int BYTES> __device__ __forceinline__ void release_stage(const GemmCtx& c, bool on) {
  asm volatile("{\n.reg .pred p, q;\n.reg .b32 ra;\nsetp.ne.b32 q, %2, 0;\nelect.sync _|p, 0xffffffff;\nand.pred p, p, q;\n"
               "mapa.shared::cluster.u32 ra, %1, %4;\n"
               "@p mbarrier.arrive.expect_tx.shared::cta.b64 _, [%0], %3;\n@p mbarrier.arrive.shared::cluster.b64 _, [ra];\n}"
               ::"r"(c.bar + (B_FULL + ST) * 8), "r"(c.bar + (B_EMPTY + ST) * 8), "r"((int)on), "n"(BYTES / 4), "n"(ST) : "memory");
}
__device__ __forceinline__ void load_w(const CUtensorMap* m, uint32_t dst, uint32_t bar, int col) {
  asm volatile("cp.async.bulk.tensor.2d.shared::cluster.global.mbarrier::complete_tx::bytes [%0], [%1, {%3,%4}], [%2];"
               ::"r"(dst), "l"(m), "r"(bar), "r"(col), "r"(0) : "memory");
}
__device__ __forceinline__ void publish(uint32_t bar) {
  fence_async();
  __syncwarp();
  mbar_arrive_elect(bar);
}

template <bool FIRST, bool LAST>
__device__ __forceinline__ void gemm_iter(const GemmCtx& c, int b, uint32_t (&pk)[12], uint32_t (&pv)[12], uint32_t (&pq)[12], int head TRARG) {
  const uint32_t bar = c.bar;
  const uint32_t pa = b & 1;
  const bool w = b >= 0;
  const uint32_t ko = pa * KSLOT, vx = pa * 16, qx = pa * 128;
  float H[48], C[72];
  uint32_t hk[12], hv[12], pv2[12];
  TR(2, b, 0);
  if (FIRST) mbar_wait(bar + (B_FULL + 0) * 8, pa);
  if (w) nb_sync(N_QK1, 256);
  TR(2, b, 2);
  issue_halo<0, 8>(H);
  TR(2, b, 3);
  if (!FIRST) {
    if (w) mbar_wait(bar + B_KFREE * 8, pa);
    dump12<128>(c.kC + ko, pk);
  }
  issue_halo<8, 12>(H);
  TR(2, b, 4);
  if (!LAST) {
    mbar_wait(bar + (B_FULL + 2) * 8, pa);
    if (FIRST) mbar_wait(bar + B_WQ * 8, 0);
    TR(2, b, 13);
    issue_core<SM_X2, 0, 8>(C);
    TR(2, b, 5);
    if (!FIRST) { fence_async(); dump12<256>(c.qC ^ (qx ^ 192), pq); }
    wg_wait<1>(); pin(H);
    release_stage<0, 18432>(c, true);
  } else {
    dump12<256>(c.qC ^ (qx ^ 192), pq);
    fence_async();
    nb_arrive(N_VQ0, 288); nb_arrive(N_VQ1, 288);
    wg_wait<0>(); pin(H);
    uint32_t ln; asm volatile("mov.u32 %0, %%laneid;" : "=r"(ln));
    if (ln < 4) mbar_arrive_remote(bar + (B_TFREE + (head >> 1)) * 8, ln);
  }
  pack12(hk, H, 0);
  if (c.hvalid) dump12<128>(c.kH + ko, hk);
  pack12(hv, H, 24);
  if (!LAST) {
    issue_core<SM_X2, 8, 12>(C);
    if (w) { nb_arrive(N_VQ0, 288); nb_arrive(N_VQ1, 288); }
    else if (!FIRST) { __syncwarp(); mbar_arrive_elect(bar + B_Q0 * 8); }
    mbar_wait(bar + (B_FULL + 1) * 8, pa);
    TR(2, b, 6);
    wg_wait<0>(); pin(C);
    TR(2, b, 7);
    pack12(pk, C, 0);
    dump12<128>(c.kC + ko + 64, pk);
    release_stage<2, 24576>(c, b < 11);
    pack12(pv2, C, 24);
    pack12(pq, C, 48);
    TR(2, b, 8);
    issue_core<SM_X1, 0, SPL>(C);
    if (w) nb_sync(N_PVISS, 384);
    issue_core<SM_X1, SPL, 8>(C);
    TR(2, b, 9);
  }
  if (!FIRST) fence_async();
  TR(2, b, 14);
  if (!LAST) issue_core<SM_X1, 8, 12>(C);
  if (!FIRST) nb_arrive(N_KRDY, 256);
  TR(2, b, 1);
  if (!LAST) mbar_wait(bar + (B_FULL + 0) * 8, pa ^ 1);
  if (w) mbar_wait(bar + B_VFREE * 8, pa);
  TR(2, b, 10);
  if (!FIRST) dump12<128>(c.vC ^ vx, pv);
  if (!LAST) dump12<256>(c.qC ^ qx, pq);
  if (c.hvalid) dump12<128>(c.vH ^ vx, hv);
  if (LAST) { fence_async(); nb_arrive(N_VQ0, 288); nb_arrive(N_VQ1, 288); return; }
  dump12<128>((c.vC ^ vx ^ 16) + 768, pv2);
  TR(2, b, 11);
  wg_wait<0>(); pin(C);
  TR(2, b, 12);
  release_stage<1, 24576>(c, b < 11);
  pack12(pk, C, 0);
  pack12(pv, C, 24);
  pack12(pq, C, 48);
}

__device__ __forceinline__ float fold(float a, float b, float t, int useb) {
  float r;
  asm("{\n.reg .pred p;\nsetp.ne.b32 p, %4, 0;\nfma.rn.f32 %0, %1, 0f3E553B95, %3;\n@p fma.rn.f32 %0, %2, 0f3E553B95, %3;\n}"
      : "=&f"(r) : "f"(a), "f"(b), "f"(t), "r"(useb));
  return r;
}
template <int U, int L, bool BORDER>
__device__ __forceinline__ void softmax_tile(const float (&SA)[56], const float (&SB)[56], const float (&T)[14], int b0, int b1,
                                             uint32_t ra0, uint32_t ra1, int qcu, uint32_t (&P)[28], float (&sx)[8]) {
  float lu[14], ll[14];
#pragma unroll
  for (int j = 0; j < 7; j++) {
    float tu0, tu1, tl0, tl1;
    if (BORDER) {
      tu0 = lds_f32(ra0 + (U + j + 3 - qcu) * 4); tu1 = lds_f32(ra1 + (U + j + 3 - qcu) * 4);
      tl0 = lds_f32(ra0 + (L + j + 2 - qcu) * 4); tl1 = lds_f32(ra1 + (L + j + 2 - qcu) * 4);
    } else { tu0 = tl0 = T[2 * j]; tu1 = tl1 = T[2 * j + 1]; }
    lu[2 * j]     = fold(SA[4 * (U + j)],     SB[4 * (U + j)],     tu0, b0);
    ll[2 * j]     = fold(SA[4 * (L + j) + 2], SB[4 * (L + j) + 2], tl0, b0);
    lu[2 * j + 1] = fold(SA[4 * (U + j) + 1], SB[4 * (U + j) + 1], tu1, b1);
    ll[2 * j + 1] = fold(SA[4 * (L + j) + 3], SB[4 * (L + j) + 3], tl1, b1);
  }
  float mu = lu[0], ml = ll[0], mu2 = lu[1], ml2 = ll[1];
#pragma unroll
  for (int j = 1; j < 7; j++) { mu = fmaxf(mu, lu[2 * j]); mu2 = fmaxf(mu2, lu[2 * j + 1]); ml = fmaxf(ml, ll[2 * j]); ml2 = fmaxf(ml2, ll[2 * j + 1]); }
  mu = fmaxf(mu, mu2); ml = fmaxf(ml, ml2);
  { const float a1 = __shfl_xor_sync(0xffffffffu, mu, 1), a2 = __shfl_xor_sync(0xffffffffu, mu, 2), a3 = __shfl_xor_sync(0xffffffffu, mu, 3);
    const float c1 = __shfl_xor_sync(0xffffffffu, ml, 1), c2 = __shfl_xor_sync(0xffffffffu, ml, 2), c3 = __shfl_xor_sync(0xffffffffu, ml, 3);
    mu = fmaxf(fmaxf(mu, a1), fmaxf(a2, a3)); ml = fmaxf(fmaxf(ml, c1), fmaxf(c2, c3)); }
  float su = 0.f, sl = 0.f;
#pragma unroll
  for (int c = 0; c < 14; c++) {
    const int iu = (c >> 1) * 4 + (c & 1) * 2;
    if (c >= U && c < U + 7) {
      float e0 = ex2(lu[2 * (c - U)] - mu), e1 = ex2(lu[2 * (c - U) + 1] - mu);
      su = c == U ? e0 + e1 : (su + e0) + e1; P[iu] = pack2(e0, e1);
    } else P[iu] = 0u;
    if (c >= L && c < L + 7) {
      float e0 = ex2(ll[2 * (c - L)] - ml), e1 = ex2(ll[2 * (c - L) + 1] - ml);
      sl = c == L ? e0 + e1 : (sl + e0) + e1; P[iu + 1] = pack2(e0, e1);
    } else P[iu + 1] = 0u;
  }
  sx[0] = su; sx[4] = sl;
#pragma unroll
  for (int k = 1; k < 4; k++) { sx[k] = __shfl_xor_sync(0xffffffffu, su, k); sx[4 + k] = __shfl_xor_sync(0xffffffffu, sl, k); }
}

struct Maps { CUtensorMap xc, xh, w, os, wo, ot; };

__global__ void __cluster_dims__(4, 1, 1) __launch_bounds__(512, 1)
na_attn_kernel(const __grid_constant__ Maps mp, const __nv_bfloat16* __restrict__ wqkv, const __nv_bfloat16* __restrict__ rpb) {
  extern __shared__ __align__(1024) uint8_t smem_raw[];
  const uint32_t sb = smem_u32(smem_raw);
  if ((sb & 0x3FFFF) != SBC) return;
  const uint32_t bar = sb + SM_BAR;
  TR2(blockIdx.x, 0);
  const int tid = threadIdx.x, lane = tid & 31;
  const int warp = __shfl_sync(0xffffffffu, tid >> 5, 0);
  const int head = blockIdx.x & 3, cl = blockIdx.x >> 2;
  const int par = cl / 7, strip = cl - par * 7, ph = par >> 1, pw = par & 1;

  uint4 wv[3];
  const int wr = tid / 6, wc = tid - wr * 6;
  if (warp < 12) {
#pragma unroll
    for (int i = 0; i < 3; i++) wv[i] = __ldg(reinterpret_cast<const uint4*>(wqkv + (wr + i * 64) * 576 + 384 + head * 48 + wc * 8));
  } else if (elect_one()) {
    if (warp == 12) {
      mbar_init(bar + B_WK * 8, 1);
#pragma unroll
      for (int i = 0; i < 3; i++) load_w(&mp.w, sb + SM_W + i * 6144, bar + B_WK * 8, 192 + head * 48 + i * 16);
      mbar_expect(bar + B_WK * 8, 18432);
    } else if (warp == 13) {
#pragma unroll
      for (int i = 0; i < B_WK; i++) mbar_init(bar + i * 8, i < B_EMPTY ? 4 : (i < B_TIN ? 16 : (i < B_TFREE ? 1 : 8)));
    } else if (warp == 14) {
#pragma unroll
      for (int i = B_WQ; i < B_COUNT; i++) mbar_init(bar + i * 8, i < B_Q0 ? 1 : (i < B_KFREE ? 4 : 8));
    }
    asm volatile("fence.mbarrier_init.release.cluster;" ::: "memory");
  }
  __syncwarp();
  asm volatile("barrier.cluster.arrive.relaxed.aligned;" ::: "memory");

  if (warp >= 12) {
    asm volatile("setmaxnreg.dec.sync.aligned.u32 24;");
    asm volatile("griddepcontrol.launch_dependents;");
    const int cc = ph * 112 + (head ? strip * 16 : (strip == 0 ? 16 : (strip == 6 ? 74 : strip * 16 - 3)));
    const int sd = strip == 0 ? -1 : (strip == 6 ? 1 : 0);
    const int r0 = head == 0 ? -4 : (head == 1 ? 4 : 0);
    asm volatile("barrier.cluster.wait.aligned;" ::: "memory");
    if (warp == 12) {
      const uint32_t fb = bar + (B_FULL + head) * 8, eb = bar + (B_EMPTY + head) * 8;
      const uint32_t dst = sb + (head == 0 ? SM_X0 : (head == 1 ? SM_X1 : SM_X2));
      const int nl = head == 0 ? 15 : (head == 3 ? 1 : 14);
#pragma unroll 1
      for (int n = 0; n < nl; n++) {
        if (n) mbar_wait(eb, (n - 1) & 1);
        if (elect_one()) {
          if (head == 0) {
            asm volatile("cp.async.bulk.tensor.5d.shared::cluster.global.mbarrier::complete_tx::bytes.multicast::cluster [%0], [%1, {%3,%4,%5,%6,%7}], [%2], %8;"
                         ::"r"(dst), "l"(&mp.xh), "r"(fb), "r"(0), "r"(8 * n + r0), "r"(cc), "r"(sd), "r"(pw * 3), "h"((uint16_t)15) : "memory");
            if (n + 1 < nl) asm volatile("cp.async.bulk.prefetch.tensor.5d.L2.global [%0, {%1,%2,%3,%4,%5}];" ::"l"(&mp.xh), "r"(0), "r"(8 * n + 8 + r0), "r"(cc), "r"(sd), "r"(pw * 3) : "memory");
          } else if (head < 3) {
            asm volatile("cp.async.bulk.tensor.4d.shared::cluster.global.mbarrier::complete_tx::bytes.multicast::cluster [%0], [%1, {%3,%4,%5,%6}], [%2], %7;"
                         ::"r"(dst), "l"(&mp.xc), "r"(fb), "r"(0), "r"(8 * n + r0), "r"(cc), "r"(pw * 3), "h"((uint16_t)15) : "memory");
          }
          if (n == 0) {
#pragma unroll
            for (int i = 0; i < 3; i++) load_w(&mp.w, sb + SM_W + (6 + i) * 6144, bar + B_WQ * 8, head * 48 + i * 16);
            mbar_expect(bar + B_WQ * 8, 18432);
            mbar_expect(bar + B_TIN * 8, 24576); mbar_expect(bar + (B_TIN + 1) * 8, 24576);
          }
          if (head && n + 1 < nl) asm volatile("cp.async.bulk.prefetch.tensor.4d.L2.global [%0, {%1,%2,%3,%4}];" ::"l"(&mp.xc), "r"(0), "r"(8 * n + 8 + r0), "r"(cc), "r"(pw * 3) : "memory");
        }
        __syncwarp();
      }
    }
    if (warp >= 14) {
      const int j = warp - 14;
      int* flag = g_flags + cl * 2 + j;
      nb_arrive(N_VQ0 + j, 288);
#pragma unroll 1
      for (int b = 0; b < TB; b++) {
        mbar_wait(bar + (B_ODONE + j) * 8, b & 1);
        if (lane == 0) {
          asm volatile("cp.async.bulk.tensor.3d.global.shared::cta.bulk_group [%0, {%2,%3,%4}], [%1];"
                       ::"l"(&mp.os), "r"(sb + SM_O + j * 6144), "r"(pw * 192), "r"(8 * b + 2 * head), "r"(ph * 112 + strip * 16 + 8 * j) : "memory");
          asm volatile("cp.async.bulk.commit_group;\ncp.async.bulk.wait_group.read 0;" ::: "memory");
        }
        __syncwarp();
        nb_arrive(N_VQ0 + j, 288);
        if (lane == 0) {
          asm volatile("cp.async.bulk.wait_group 0;\nfence.proxy.async.global;\nred.release.gpu.global.add.s32 [%0], 1;" ::"l"(flag + b * 56) : "memory");
        }
        __syncwarp();
      }
#pragma unroll 1
      for (int i = 0; i < 2; i++) {
        mbar_wait(bar + (B_ODONE + j) * 8, i);
        if (i == 0) { nb_arrive(N_VQ0 + j, 288); mbar_wait(bar + (B_TFREE + j) * 8, 0); }
        if (elect_one()) {
#pragma unroll
          for (int d = 0; d < 2; d++)
            asm volatile("{\n.reg .b32 rd, rb;\nmapa.shared::cluster.u32 rd, %0, %3;\nmapa.shared::cluster.u32 rb, %2, %3;\n"
                         "cp.async.bulk.shared::cluster.shared::cta.mbarrier::complete_tx::bytes [rd], [%1], 6144, [rb];\n}"
                         ::"r"(sb + SM_TIN + i * 24576 + head * 6144), "r"(sb + (i ? SM_Q + j * 12288 : SM_O + j * 6144)), "r"(bar + (B_TIN + i) * 8), "r"(2 * j + d) : "memory");
        }
        __syncwarp();
      }
    }
    cluster_sync();
  } else if (warp >= 8) {
    asm volatile("setmaxnreg.inc.sync.aligned.u32 %0;" ::"n"(RG));
    GemmCtx c;
    c.bar = bar;
    const int gw = warp - 8, tk = gw * 16 + (lane & 15), hi = lane >> 4;
    { const int col = tk >> 2, i = tk & 3;
      c.kC = sb + SM_K + (col + 3) * KS + hi * 128 + i * 16;
      c.vC = sb + SM_V + (col + 3) * 1536 + hi * 128 + (2 * i + ((col + 3) & 1)) * 16;
      c.qC = sb + SM_Q + col * 1536 + hi * 256 + (col & 1) * 64 + i * 16; }
    { const int ci = (tk >> 3) - 2, kc = ci < 3 ? ci : ci + 16, i = tk & 7; c.hvalid = gw > 0;
      c.kH = sb + SM_K + kc * KS + hi * 128 + i * 16;
      c.vH = sb + SM_V + kc * 1536 + hi * 128 + (i >> 2) * 768 + (2 * (i & 3) + ((kc ^ (i >> 2)) & 1)) * 16; }
    asm volatile("barrier.cluster.wait.aligned;" ::: "memory");
    if (elect_one()) { mbar_expect(bar + B_FULL * 8, 4608); mbar_expect(bar + (B_FULL + 1) * 8, 6144); mbar_expect(bar + (B_FULL + 2) * 8, 6144); }
    __syncwarp();
#pragma unroll
    for (int i = 0; i < 3; i++) sts128(sb + SM_W + (3 + (wc >> 1)) * 6144 + (wr + i * 64) * 32 + ((wc ^ (wr >> 2)) & 1) * 16, wv[i]);
    fence_async();
    asm volatile("bar.sync 1, 384;" ::: "memory");
    mbar_wait(bar + B_WK * 8, 0);
    uint32_t pk[12], pv[12], pq[12];
    TRDECL;
    gemm_iter<true, false>(c, -2, pk, pv, pq, head TRPASS);
#pragma unroll 1
    for (int b = -1; b < 12; b++) gemm_iter<false, false>(c, b, pk, pv, pq, head TRPASS);
    asm volatile("bar.sync 2, 128;" ::: "memory");
    if (gw == 0 && elect_one()) {
      mbar_expect(bar + B_WO * 8, 36864);
      asm volatile("cp.async.bulk.tensor.3d.shared::cluster.global.mbarrier::complete_tx::bytes [%0], [%1, {%3,%4,%5}], [%2];"
                   ::"r"(sb + SM_TWO), "l"(&mp.wo), "r"(bar + B_WO * 8), "r"(0), "r"(0), "r"((head & 1) * 3) : "memory");
    }
    __syncwarp();
    gemm_iter<false, true>(c, 12, pk, pv, pq, head TRPASS);
    TRDUMP;
    mbar_wait(bar + B_WO * 8, 0);
    nb_sync(N_QK1, 256);
    const uint32_t st = sb + SM_TST + gw * 3072;
    const uint32_t sta = st + (lane & 15) * 64 + ((hi ^ ((lane >> 1) & 3)) * 16);
#pragma unroll 1
    for (int i = 0; i < 2; i++) {
      constexpr uint64_t db = mkdesc(SBC + SM_TWO, 12288, 512, 2);
      const uint64_t da = mkdesc(SBC + SM_TIN, 128, 768, 0) + i * (24576 / 16);
      float D[48];
      mbar_wait(bar + (B_TIN + i) * 8, 0);
      wg_fence();
      wg_ss96<0>(D, da, db);
#pragma unroll
      for (int k = 1; k < 12; k++) wg_ss96<1>(D, da + (k / 3) * 384 + (k % 3) * 16, db + k * 64);
      wg_commit();
      if (lane == 0) asm volatile("cp.async.bulk.wait_group.read 0;" ::: "memory");
      __syncwarp();
      wg_wait<0>(); pin(D);
#pragma unroll
      for (int q = 0; q < 6; q++)
        stsm4((sta ^ ((q & 1) * 32)) + (q >> 1) * 1024,
              pack2(D[8 * q], D[8 * q + 1]), pack2(D[8 * q + 2], D[8 * q + 3]), pack2(D[8 * q + 4], D[8 * q + 5]), pack2(D[8 * q + 6], D[8 * q + 7]));
      fence_async();
      __syncwarp();
      if (lane == 0) {
        asm volatile("cp.async.bulk.tensor.4d.global.shared::cta.bulk_group [%0, {%2,%3,%4,%5}], [%1];"
                     ::"l"(&mp.ot), "r"(st), "r"(0), "r"(8 * (TB + i)), "r"(ph * 112 + strip * 16 + 8 * (head >> 1) + 2 * gw), "r"(pw * 6 + (head & 1) * 3) : "memory");
        asm volatile("cp.async.bulk.commit_group;" ::: "memory");
      }
    }
    asm volatile("barrier.cluster.arrive.relaxed.aligned;" ::: "memory");
    if (lane == 0) asm volatile("cp.async.bulk.wait_group 0;" ::: "memory");
    __syncwarp();
    asm volatile("barrier.cluster.wait.aligned;" ::: "memory");
  } else {
    asm volatile("setmaxnreg.inc.sync.aligned.u32 %0;" ::"n"(RA));
    float rv = -INFINITY;
    if (tid < 169) rv = __bfloat162float(rpb[head * 169 + tid]) * 1.4426950408889634f;
    if (tid < 192) {
      const int kc = (wr & 15) + 3;
      sts128(tid < 96 ? sb + SM_K + kc * KS + wc * 128 + 48 : sb + SM_V + kc * 1536 + wc * 128 + (6 + (kc & 1)) * 16, make_uint4(0, 0, 0, 0));
    }
#pragma unroll
    for (int i = 0; i < 3; i++) sts128(sb + SM_W + (3 + (wc >> 1)) * 6144 + (wr + i * 64) * 32 + ((wc ^ (wr >> 2)) & 1) * 16, wv[i]);
    fence_async();
    asm volatile("bar.arrive 1, 384;" ::: "memory");
    if (tid < 182) asm volatile("st.shared.f32 [%0], %1;" ::"r"(sb + SM_RPB + tid * 4), "f"(rv) : "memory");
    const int j = warp >> 2, w = warp & 3;
    int variant = w;
    if (strip == 0 && j == 0 && w < 2) variant = 4;
    if (strip == 6 && j == 1 && w >= 2) variant = 5;
    const uint32_t qa = sb + SM_Q + (8 * j + 2 * w + ((lane >> 3) & 1)) * 1536 + (lane >> 4) * 256 + (((lane & 7) * 16) ^ (((lane >> 3) & 1) * 64));
    uint32_t oa = sb + SM_O + j * 6144 + (2 * w + ((lane >> 3) & 1)) * 768 + (lane >> 4) * 128 + (lane & 7) * 16;
    const uint64_t dK = mkdesc(SBC + SM_K, 128, KS, 0) + j * (8 * KS / 16);
    const uint64_t dV = mkdesc(SBC + SM_V, 768, 128, 0) + j * (8 * 1536 / 16);
    asm volatile("barrier.cluster.wait.aligned;" ::: "memory");
    asm volatile("bar.sync 3, 256;" ::: "memory");
    float T[14];
    TRDECL;
    int b0 = 0, b1 = 0;
    uint32_t ra0 = 0, ra1 = 0, meta = 0;
    uint32_t q[12];
    mbar_wait(bar + B_Q0 * 8, 0);
#pragma unroll
    for (int k = 0; k < 3; k++) ldsm4(qa + k * 512, q[4 * k], q[4 * k + 1], q[4 * k + 2], q[4 * k + 3]);
#pragma unroll 1
    for (int b = 0; b < 14; b++) {
      const uint32_t pa = b & 1;
      if (b <= 1 || b == 13) {
        uint32_t ln; asm volatile("mov.u32 %0, %%laneid;" : "=r"(ln));
        const int g = ln >> 2, t = ln & 3;
        const int sw = b == 0 ? max(g + 1, 4) : (b == 13 ? min(g + 1, 5) : g + 1);
        const int i0 = 2 * t, i1 = 2 * t + 1;
        b0 = i0 <= sw - 2; b1 = i1 <= sw - 2;
        const int m = sw - 1;
        ra0 = sb + SM_RPB + (i0 == m ? 13 : i0 + (b0 ? 8 : 0) - g + 2) * 52;
        ra1 = sb + SM_RPB + (i1 == m ? 13 : i1 + (b1 ? 8 : 0) - g + 2) * 52;
#pragma unroll
        for (int jj = 0; jj < 7; jj++) { T[2 * jj] = lds_f32(ra0 + (jj + 3) * 4); T[2 * jj + 1] = lds_f32(ra1 + (jj + 3) * 4); }
        uint32_t m16 = 0x8888u;
#pragma unroll
        for (int i = 0; i < 8; i++) m16 |= (uint32_t)(((i <= sw - 2) ^ (i >> 2) ^ t ^ b) & 1) << (2 * i);
        meta = m16 | (m16 << 16);
        if (b == 13) oa += SM_Q - SM_O + j * 6144;
      } else meta ^= 0x55555555u;
      float SA[56], SB[56];
      const uint64_t dA = dK + pa * (KSLOT >> 4), dB = dK + (pa ^ 1) * (KSLOT >> 4);
      TR(0, b, 0);
      nb_sync(N_KRDY + j, 256);
      TR(0, b, 1);
      TR(0, b - 1, 9);
      wg_fence();
      wg_rs112<0>(SA, q[0], q[1], q[2], q[3], dA);
      wg_rs112<0>(SB, q[0], q[1], q[2], q[3], dB);
      wg_rs112<1>(SA, q[4], q[5], q[6], q[7], dA + 16);
      wg_rs112<1>(SB, q[4], q[5], q[6], q[7], dB + 16);
      wg_rs112<1>(SA, q[8], q[9], q[10], q[11], dA + 32);
      wg_rs112<1>(SB, q[8], q[9], q[10], q[11], dB + 32);
      wg_commit();
      nb_arrive(N_QK0 + j, 256);
      TR(0, b, 2);
      wg_wait<0>(); pin(SA); pin(SB);
      mbar_arrive_elect(bar + B_KFREE * 8);
      TR(0, b, 3);
      TR(0, b - 1, 10);
      uint32_t P[28];
      float sx[8];
      switch (variant) {
        case 0: softmax_tile<0, 1, false>(SA, SB, T, b0, b1, ra0, ra1, 0, P, sx); break;
        case 1: softmax_tile<2, 3, false>(SA, SB, T, b0, b1, ra0, ra1, 0, P, sx); break;
        case 2: softmax_tile<4, 5, false>(SA, SB, T, b0, b1, ra0, ra1, 0, P, sx); break;
        case 3: softmax_tile<6, 7, false>(SA, SB, T, b0, b1, ra0, ra1, 0, P, sx); break;
        case 4: softmax_tile<3, 3, true>(SA, SB, T, b0, b1, ra0, ra1, 2 * w, P, sx); break;
        default: softmax_tile<4, 4, true>(SA, SB, T, b0, b1, ra0, ra1, 2 * w, P, sx); break;
      }
      float O[24];
      TR(0, b, 4);
      nb_sync(N_VQ0 + j, 288);
      TR(0, b, 5);
#pragma unroll
      for (int k = 0; k < 3; k++) ldsm4(qa + (pa ^ 1) * 128 + k * 512, q[4 * k], q[4 * k + 1], q[4 * k + 2], q[4 * k + 3]);
      wg_fence();
      wg_sp48<0>(O, P[0], P[1], P[2], P[3], dV, meta);
#pragma unroll
      for (int s = 1; s < 7; s++) wg_sp48<1>(O, P[4 * s], P[4 * s + 1], P[4 * s + 2], P[4 * s + 3], dV + s * 192, meta);
      wg_commit();
      if (b < 12) nb_arrive(N_PVISS, 384);
      TR(0, b, 6);
      wg_wait<0>(); pin(O);
      mbar_arrive_elect(bar + B_VFREE * 8);
      TR(0, b, 7);
      float ru, rl;
      asm("rcp.approx.ftz.f32 %0, %1;" : "=f"(ru) : "f"(((fmaf(O[0], 0.f, sx[0]) + sx[1]) + sx[2]) + sx[3]));
      asm("rcp.approx.ftz.f32 %0, %1;" : "=f"(rl) : "f"(((fmaf(O[2], 0.f, sx[4]) + sx[5]) + sx[6]) + sx[7]));
#pragma unroll
      for (int i = 0; i < 3; i++)
        stsm4(oa + i * 256, pack2(O[8 * i] * ru, O[8 * i + 1] * ru), pack2(O[8 * i + 2] * rl, O[8 * i + 3] * rl),
              pack2(O[8 * i + 4] * ru, O[8 * i + 5] * ru), pack2(O[8 * i + 6] * rl, O[8 * i + 7] * rl));
      publish(bar + (B_ODONE + j) * 8);
      TR(0, b, 8);
    }
    TRDUMP;
    cluster_sync();
    TR2(blockIdx.x, 2);
  }
}

constexpr int NSTB = 6;
constexpr int NTB = TB * 56;
constexpr int SM_B_IN = 0;
constexpr int SM_B_W = SM_B_IN + NSTB * 24576;
constexpr int SM_B_BAR = SM_B_W + 73728;
constexpr int SM_B_TOTAL = SM_B_BAR + 128;
struct MapsB { CUtensorMap oi, oo, wo; };

__global__ void __launch_bounds__(416, 1)
na_proj_kernel(const __grid_constant__ MapsB mp) {
  extern __shared__ __align__(1024) uint8_t smem_raw[];
  const uint32_t sb = smem_u32(smem_raw);
  if ((sb & 0x3FFFF) != SBC) return;
  const uint32_t bar = sb + SM_B_BAR;
  const int tid = threadIdx.x, lane = tid & 31;
  const int warp = __shfl_sync(0xffffffffu, tid >> 5, 0);
  TR2(132 + blockIdx.x, 0);
  TRB(47, 0);
  if (warp == 12 && elect_one()) {
#pragma unroll
    for (int i = 0; i <= 2 * NSTB; i++) mbar_init(bar + i * 8, i < NSTB || i == 2 * NSTB ? 1 : 4);
    mbar_expect(bar + 2 * NSTB * 8, 73728);
#pragma unroll
    for (int i = 0; i < 2; i++)
      asm volatile("cp.async.bulk.tensor.3d.shared::cluster.global.mbarrier::complete_tx::bytes [%0], [%1, {%3,%4,%5}], [%2];"
                   ::"r"(sb + SM_B_W + i * 36864), "l"(&mp.wo), "r"(bar + 2 * NSTB * 8), "r"(0), "r"(0), "r"(i * 3) : "memory");
  }
  __syncthreads();
  const int step = gridDim.x;
  if (warp == 12) {
    int it = 0;
    uint32_t spin = 0;
#pragma unroll 1
    for (int n = blockIdx.x; n < NTB && spin < SPIN_LIMIT; spin++) {
      int v = 0;
      const int mine = n + lane * step;
      if (lane < 8 && mine < NTB) asm volatile("ld.acquire.gpu.global.s32 %0, [%1];" : "=r"(v) : "l"(g_flags + mine) : "memory");
      int cnt = __ffs(~__ballot_sync(0xffffffffu, v >= 4)) - 1;
      asm volatile("fence.proxy.async.global;" ::: "memory");
      __syncwarp();
#pragma unroll 1
      for (; cnt > 0; cnt--, n += step, it++) {
        TRB(it, 0);
        const int b = n / 56, rem = n - b * 56, par = rem / 14;
        const int use = it / NSTB, st = it - use * NSTB;
        if (use) mbar_wait(bar + (NSTB + st) * 8, (use - 1) & 1);
        if (elect_one()) {
          mbar_expect(bar + st * 8, 24576);
          asm volatile("cp.async.bulk.tensor.3d.shared::cluster.global.mbarrier::complete_tx::bytes [%0], [%1, {%3,%4,%5}], [%2];"
                       ::"r"(sb + SM_B_IN + st * 24576), "l"(&mp.oi), "r"(bar + st * 8), "r"((par & 1) * 192), "r"(8 * b), "r"((par >> 1) * 112 + (rem - par * 14) * 8) : "memory");
        }
        __syncwarp();
        TRB(it, 2);
      }
    }
    for (int n = blockIdx.x + lane * step; n < NTB; n += 32 * step) g_flags[n] = 0;
  } else {
    const int wg = warp >> 2, w = warp & 3;
    constexpr uint64_t db = mkdesc(SBC + SM_B_W, 12288, 512, 2);
    const uint32_t sta0 = sb + SM_B_IN + w * 6144 + (lane & 15) * 128 + (((lane >> 4) ^ (lane & 7)) * 16);
    mbar_wait(bar + 2 * NSTB * 8, 0);
    TRB(47, 1);
    int use = 0;
#pragma unroll 1
    for (int n = blockIdx.x + wg * step; n < NTB; n += 3 * step, use++) {
      const int b = n / 56, rem = n - b * 56, par = rem / 14, sg = wg + 3 * (use & 1);
      const uint64_t da = mkdesc(SBC + SM_B_IN, 128, 3072, 0) + sg * (24576 / 16);
      float D[96];
      mbar_wait(bar + sg * 8, (use >> 1) & 1);
      TRB(use * 3 + wg, 3);
      wg_fence();
      wg_ss192<0>(D, da, db);
#pragma unroll
      for (int k = 1; k < 12; k++) wg_ss192<1>(D, da + k * 16, db + k * 64);
      wg_commit();
      TRB(use * 3 + wg, 4);
      wg_wait<0>(); pin(D);
      nb_sync(1 + wg, 128);
      TRB(use * 3 + wg, 5);
      const uint32_t sta = sta0 + sg * 24576;
#pragma unroll
      for (int q = 0; q < 12; q++)
        stsm4((sta ^ ((q & 3) * 32)) + (q >> 2) * 2048,
              pack2(D[8 * q], D[8 * q + 1]), pack2(D[8 * q + 2], D[8 * q + 3]), pack2(D[8 * q + 4], D[8 * q + 5]), pack2(D[8 * q + 6], D[8 * q + 7]));
      fence_async();
      __syncwarp();
      if (lane == 0) {
        asm volatile("cp.async.bulk.tensor.4d.global.shared::cta.bulk_group [%0, {%2,%3,%4,%5}], [%1];"
                     ::"l"(&mp.oo), "r"(sb + SM_B_IN + sg * 24576 + w * 6144), "r"(0), "r"(8 * b), "r"((par >> 1) * 112 + (rem - par * 14) * 8 + 2 * w), "r"((par & 1) * 3) : "memory");
        asm volatile("cp.async.bulk.commit_group;\ncp.async.bulk.wait_group.read 0;" ::: "memory");
        mbar_arrive(bar + (NSTB + sg) * 8);
      }
      __syncwarp();
      TRB(use * 3 + wg, 6);
    }
    if (lane == 0) asm volatile("cp.async.bulk.wait_group 0;" ::: "memory");
    TR2(132 + blockIdx.x, 2);
  }
}

typedef CUresult (*EncodeFn)(CUtensorMap*, CUtensorMapDataType, cuuint32_t, void*, const cuuint64_t*, const cuuint64_t*, const cuuint32_t*,
                             const cuuint32_t*, CUtensorMapInterleave, CUtensorMapSwizzle, CUtensorMapL2promotion, CUtensorMapFloatOOBfill);
static EncodeFn g_enc = nullptr;
static void make_map(CUtensorMap* m, const void* p, int rank, const cuuint64_t* dim, const cuuint64_t* str, const cuuint32_t* box, CUtensorMapSwizzle sw) {
  const cuuint32_t ones[5] = {1, 1, 1, 1, 1};
  g_enc(m, CU_TENSOR_MAP_DATA_TYPE_BFLOAT16, rank, (void*)p, dim, str, box, ones, CU_TENSOR_MAP_INTERLEAVE_NONE, sw,
        CU_TENSOR_MAP_L2_PROMOTION_L2_128B, CU_TENSOR_MAP_FLOAT_OOB_FILL_NONE);
}

extern "C" void kernel_launch(void* const* d_in, const int* in_sizes, int n_in, void* d_out, int out_size) {
  const __nv_bfloat16* x = (const __nv_bfloat16*)d_in[0];
  const __nv_bfloat16* wqkv = (const __nv_bfloat16*)d_in[1];
  const __nv_bfloat16* wo = (const __nv_bfloat16*)d_in[2];
  const __nv_bfloat16* rpb = (const __nv_bfloat16*)d_in[3];

  if (!g_enc) {
    void* fn = nullptr; cudaDriverEntryPointQueryResult qr;
    cudaGetDriverEntryPoint("cuTensorMapEncodeTiled", &fn, cudaEnableDefault, &qr);
    g_enc = (EncodeFn)fn;
    cudaFuncSetAttribute(na_attn_kernel, cudaFuncAttributeMaxDynamicSharedMemorySize, SM_A_TOTAL);
    cudaFuncSetAttribute(na_proj_kernel, cudaFuncAttributeMaxDynamicSharedMemorySize, SM_B_TOTAL);
  }
  Maps ma; MapsB mb;
  { cuuint64_t dim[4] = {64, 112, 224, 6}, str[3] = {(cuuint64_t)ROWB, 768, 128};
    cuuint32_t box[4] = {64, 4, 16, 3}, boxo[4] = {64, 8, 2, 3};
    make_map(&ma.xc, x, 4, dim, str, box, CU_TENSOR_MAP_SWIZZLE_128B);
    make_map(&mb.oo, d_out, 4, dim, str, boxo, CU_TENSOR_MAP_SWIZZLE_128B); }
  { cuuint64_t dim[5] = {64, 112, 224, 2, 6}, str[4] = {(cuuint64_t)ROWB, 768, 19 * 768, 128};
    cuuint32_t box[5] = {64, 8, 3, 2, 3};
    make_map(&ma.xh, x, 5, dim, str, box, CU_TENSOR_MAP_SWIZZLE_128B); }
  { cuuint64_t dim[3] = {384, 112, 224}, str[2] = {(cuuint64_t)ROWB, 768};
    cuuint32_t box[3] = {192, 8, 8}, boxs[3] = {192, 2, 8};
    make_map(&mb.oi, d_out, 3, dim, str, box, CU_TENSOR_MAP_SWIZZLE_NONE);
    make_map(&ma.os, d_out, 3, dim, str, boxs, CU_TENSOR_MAP_SWIZZLE_NONE); }
  { cuuint64_t dim[4] = {32, 112, 224, 12}, str[3] = {(cuuint64_t)ROWB, 768, 64};
    cuuint32_t box[4] = {32, 8, 2, 3};
    make_map(&ma.ot, d_out, 4, dim, str, box, CU_TENSOR_MAP_SWIZZLE_64B); }
  { cuuint64_t dim[2] = {576, 192}, str[1] = {1152};
    cuuint32_t box[2] = {16, 192};
    make_map(&ma.w, wqkv, 2, dim, str, box, CU_TENSOR_MAP_SWIZZLE_32B); }
  { cuuint64_t dim[3] = {32, 192, 6}, str[2] = {384, 64};
    cuuint32_t box[3] = {32, 192, 3};
    make_map(&ma.wo, wo, 3, dim, str, box, CU_TENSOR_MAP_SWIZZLE_64B);
    mb.wo = ma.wo; }
  na_attn_kernel<<<112, 512, SM_A_TOTAL>>>(ma, wqkv, rpb);
  cudaLaunchConfig_t cfg = {};
  cfg.gridDim = dim3(20); cfg.blockDim = dim3(416); cfg.dynamicSmemBytes = SM_B_TOTAL; cfg.stream = cudaStreamPerThread;
  cudaLaunchAttribute at[1];
  at[0].id = cudaLaunchAttributeProgrammaticStreamSerialization; at[0].val.programmaticStreamSerializationAllowed = 1;
  cfg.attrs = at; cfg.numAttrs = 1;
  cudaLaunchKernelEx(&cfg, na_proj_kernel, mb);
}
```

```cpp
#include <cuda_runtime.h>
#include <cuda_bf16.h>
#include <cuda.h>
#include <stdint.h>

#define SPIN_LIMIT (1u << 18)

__device__ __forceinline__ uint32_t smem_u32(const void* p) { return (uint32_t)__cvta_generic_to_shared(p); }
__device__ __forceinline__ void wg_fence() { asm volatile("wgmma.fence.sync.aligned;" ::: "memory"); }
__device__ __forceinline__ void wg_commit() { asm volatile("wgmma.commit_group.sync.aligned;" ::: "memory"); }
template <int N> __device__ __forceinline__ void wg_wait() { asm volatile("wgmma.wait_group.sync.aligned %0;" ::"n"(N) : "memory"); }
template <int N> __device__ __forceinline__ void pin(float (&d)[N]) {
#pragma unroll
  for (int i = 0; i < N; i++) asm volatile("" : "+f"(d[i])::"memory");
}
__host__ __device__ constexpr uint64_t mkdesc(uint32_t addr, uint32_t lbo, uint32_t sbo, uint32_t sw) {
  return (uint64_t)((addr & 0x3FFFF) >> 4) | ((uint64_t)(lbo >> 4) << 16) | ((uint64_t)(sbo >> 4) << 32) | ((uint64_t)sw << 62);
}
__device__ __forceinline__ void mbar_init(uint32_t bar, uint32_t cnt) { asm volatile("mbarrier.init.shared::cta.b64 [%0], %1;" ::"r"(bar), "r"(cnt) : "memory"); }
__device__ __forceinline__ void mbar_arrive(uint32_t bar) { asm volatile("mbarrier.arrive.shared::cta.b64 _, [%0];" ::"r"(bar) : "memory"); }
__device__ __forceinline__ bool elect_one() {
  uint32_t r; asm volatile("{\n.reg .pred p;\nelect.sync _|p, 0xffffffff;\nselp.u32 %0, 1, 0, p;\n}" : "=r"(r)); return r;
}
__device__ __forceinline__ void mbar_arrive_elect(uint32_t bar) {
  asm volatile("{\n.reg .pred p;\nelect.sync _|p, 0xffffffff;\n@p mbarrier.arrive.shared::cta.b64 _, [%0];\n}" ::"r"(bar) : "memory");
}
__device__ __forceinline__ void mbar_expect(uint32_t bar, uint32_t bytes) { asm volatile("mbarrier.arrive.expect_tx.shared::cta.b64 _, [%0], %1;" ::"r"(bar), "r"(bytes) : "memory"); }
__device__ __forceinline__ void mbar_arrive_remote(uint32_t bar, uint32_t cta) {
  asm volatile("{\n.reg .b32 ra;\nmapa.shared::cluster.u32 ra, %0, %1;\nmbarrier.arrive.shared::cluster.b64 _, [ra];\n}" ::"r"(bar), "r"(cta) : "memory");
}
__device__ __forceinline__ void mbar_wait(uint32_t bar, uint32_t parity) {
  asm volatile("{\n.reg .pred p;\n.reg .b32 n;\nmov.b32 n, 0;\nWL:\nmbarrier.try_wait.parity.shared::cta.b64 p, [%0], %1;\n@p bra WD;\n"
               "add.u32 n, n, 1;\nsetp.lt.u32 p, n, 65536;\n@p bra WL;\nWD:\n}" ::"r"(bar), "r"(parity) : "memory");
}
__device__ __forceinline__ void nb_sync(int id, int n) { asm volatile("bar.sync %0, %1;" ::"r"(id), "r"(n) : "memory"); }
__device__ __forceinline__ void nb_arrive(int id, int n) { asm volatile("bar.arrive %0, %1;" ::"r"(id), "r"(n) : "memory"); }
__device__ __forceinline__ void fence_async() { asm volatile("fence.proxy.async.shared::cta;" ::: "memory"); }
__device__ __forceinline__ void cluster_sync() {
  asm volatile("barrier.cluster.arrive.relaxed.aligned;\nbarrier.cluster.wait.aligned;" ::: "memory");
}
__device__ __forceinline__ uint32_t pack2(float lo, float hi) {
  uint32_t r; asm("cvt.rn.bf16x2.f32 %0, %1, %2;" : "=r"(r) : "f"(hi), "f"(lo)); return r;
}
__device__ __forceinline__ void stsm4(uint32_t a, uint32_t r0, uint32_t r1, uint32_t r2, uint32_t r3) {
  asm volatile("stmatrix.sync.aligned.m8n8.x4.shared.b16 [%0], {%1,%2,%3,%4};" ::"r"(a), "r"(r0), "r"(r1), "r"(r2), "r"(r3) : "memory");
}
__device__ __forceinline__ void ldsm4(uint32_t a, uint32_t& r0, uint32_t& r1, uint32_t& r2, uint32_t& r3) {
  asm volatile("ldmatrix.sync.aligned.m8n8.x4.shared.b16 {%0,%1,%2,%3}, [%4];" : "=r"(r0), "=r"(r1), "=r"(r2), "=r"(r3) : "r"(a) : "memory");
}
__device__ __forceinline__ void sts128(uint32_t a, uint4 v) {
  asm volatile("st.shared.v4.b32 [%0], {%1,%2,%3,%4};" ::"r"(a), "r"(v.x), "r"(v.y), "r"(v.z), "r"(v.w) : "memory");
}
__device__ __forceinline__ float lds_f32(uint32_t a) { float v; asm volatile("ld.shared.f32 %0, [%1];" : "=f"(v) : "r"(a)); return v; }
__device__ __forceinline__ float ex2(float x) { float y; asm("ex2.approx.ftz.f32 %0, %1;" : "=f"(y) : "f"(x)); return y; }

template<int SC> __device__ __forceinline__ void wg_ss144(float (&d)[72], uint64_t da, uint64_t db) {
  asm volatile("{\n.reg .pred p;\nsetp.ne.b32 p, %74, 0;\nwgmma.mma_async.sync.aligned.m64n144k16.f32.bf16.bf16 {%0,%1,%2,%3,%4,%5,%6,%7,%8,%9,%10,%11,%12,%13,%14,%15,%16,%17,%18,%19,%20,%21,%22,%23,%24,%25,%26,%27,%28,%29,%30,%31,%32,%33,%34,%35,%36,%37,%38,%39,%40,%41,%42,%43,%44,%45,%46,%47,%48,%49,%50,%51,%52,%53,%54,%55,%56,%57,%58,%59,%60,%61,%62,%63,%64,%65,%66,%67,%68,%69,%70,%71}, %72, %73, p, 1, 1, 0, 1;\n}\n"
    : "+f"(d[0]),"+f"(d[1]),"+f"(d[2]),"+f"(d[3]),"+f"(d[4]),"+f"(d[5]),"+f"(d[6]),"+f"(d[7]),"+f"(d[8]),"+f"(d[9]),"+f"(d[10]),"+f"(d[11]),"+f"(d[12]),"+f"(d[13]),"+f"(d[14]),"+f"(d[15]),"+f"(d[16]),"+f"(d[17]),"+f"(d[18]),"+f"(d[19]),"+f"(d[20]),"+f"(d[21]),"+f"(d[22]),"+f"(d[23]),"+f"(d[24]),"+f"(d[25]),"+f"(d[26]),"+f"(d[27]),"+f"(d[28]),"+f"(d[29]),"+f"(d[30]),"+f"(d[31]),"+f"(d[32]),"+f"(d[33]),"+f"(d[34]),"+f"(d[35]),"+f"(d[36]),"+f"(d[37]),"+f"(d[38]),"+f"(d[39]),"+f"(d[40]),"+f"(d[41]),"+f"(d[42]),"+f"(d[43]),"+f"(d[44]),"+f"(d[45]),"+f"(d[46]),"+f"(d[47]),"+f"(d[48]),"+f"(d[49]),"+f"(d[50]),"+f"(d[51]),"+f"(d[52]),"+f"(d[53]),"+f"(d[54]),"+f"(d[55]),"+f"(d[56]),"+f"(d[57]),"+f"(d[58]),"+f"(d[59]),"+f"(d[60]),"+f"(d[61]),"+f"(d[62]),"+f"(d[63]),"+f"(d[64]),"+f"(d[65]),"+f"(d[66]),"+f"(d[67]),"+f"(d[68]),"+f"(d[69]),"+f"(d[70]),"+f"(d[71]) : "l"(da), "l"(db), "n"(SC));
}
template<int SC> __device__ __forceinline__ void wg_ss96(float (&d)[48], uint64_t da, uint64_t db) {
  asm volatile("{\n.reg .pred p;\nsetp.ne.b32 p, %50, 0;\nwgmma.mma_async.sync.aligned.m64n96k16.f32.bf16.bf16 {%0,%1,%2,%3,%4,%5,%6,%7,%8,%9,%10,%11,%12,%13,%14,%15,%16,%17,%18,%19,%20,%21,%22,%23,%24,%25,%26,%27,%28,%29,%30,%31,%32,%33,%34,%35,%36,%37,%38,%39,%40,%41,%42,%43,%44,%45,%46,%47}, %48, %49, p, 1, 1, 0, 1;\n}\n"
    : "+f"(d[0]),"+f"(d[1]),"+f"(d[2]),"+f"(d[3]),"+f"(d[4]),"+f"(d[5]),"+f"(d[6]),"+f"(d[7]),"+f"(d[8]),"+f"(d[9]),"+f"(d[10]),"+f"(d[11]),"+f"(d[12]),"+f"(d[13]),"+f"(d[14]),"+f"(d[15]),"+f"(d[16]),"+f"(d[17]),"+f"(d[18]),"+f"(d[19]),"+f"(d[20]),"+f"(d[21]),"+f"(d[22]),"+f"(d[23]),"+f"(d[24]),"+f"(d[25]),"+f"(d[26]),"+f"(d[27]),"+f"(d[28]),"+f"(d[29]),"+f"(d[30]),"+f"(d[31]),"+f"(d[32]),"+f"(d[33]),"+f"(d[34]),"+f"(d[35]),"+f"(d[36]),"+f"(d[37]),"+f"(d[38]),"+f"(d[39]),"+f"(d[40]),"+f"(d[41]),"+f"(d[42]),"+f"(d[43]),"+f"(d[44]),"+f"(d[45]),"+f"(d[46]),"+f"(d[47]) : "l"(da), "l"(db), "n"(SC));
}
template<int SC> __device__ __forceinline__ void wg_rs112(float (&d)[56], uint32_t a0, uint32_t a1, uint32_t a2, uint32_t a3, uint64_t db) {
  asm volatile("{\n.reg .pred p;\nsetp.ne.b32 p, %61, 0;\nwgmma.mma_async.sync.aligned.m64n112k16.f32.bf16.bf16 {%0,%1,%2,%3,%4,%5,%6,%7,%8,%9,%10,%11,%12,%13,%14,%15,%16,%17,%18,%19,%20,%21,%22,%23,%24,%25,%26,%27,%28,%29,%30,%31,%32,%33,%34,%35,%36,%37,%38,%39,%40,%41,%42,%43,%44,%45,%46,%47,%48,%49,%50,%51,%52,%53,%54,%55}, {%56,%57,%58,%59}, %60, p, 1, 1, 0;\n}\n"
    : "+f"(d[0]),"+f"(d[1]),"+f"(d[2]),"+f"(d[3]),"+f"(d[4]),"+f"(d[5]),"+f"(d[6]),"+f"(d[7]),"+f"(d[8]),"+f"(d[9]),"+f"(d[10]),"+f"(d[11]),"+f"(d[12]),"+f"(d[13]),"+f"(d[14]),"+f"(d[15]),"+f"(d[16]),"+f"(d[17]),"+f"(d[18]),"+f"(d[19]),"+f"(d[20]),"+f"(d[21]),"+f"(d[22]),"+f"(d[23]),"+f"(d[24]),"+f"(d[25]),"+f"(d[26]),"+f"(d[27]),"+f"(d[28]),"+f"(d[29]),"+f"(d[30]),"+f"(d[31]),"+f"(d[32]),"+f"(d[33]),"+f"(d[34]),"+f"(d[35]),"+f"(d[36]),"+f"(d[37]),"+f"(d[38]),"+f"(d[39]),"+f"(d[40]),"+f"(d[41]),"+f"(d[42]),"+f"(d[43]),"+f"(d[44]),"+f"(d[45]),"+f"(d[46]),"+f"(d[47]),"+f"(d[48]),"+f"(d[49]),"+f"(d[50]),"+f"(d[51]),"+f"(d[52]),"+f"(d[53]),"+f"(d[54]),"+f"(d[55]) : "r"(a0), "r"(a1), "r"(a2), "r"(a3), "l"(db), "n"(SC));
}
template<int SC> __device__ __forceinline__ void wg_sp48(float (&d)[24], uint32_t a0, uint32_t a1, uint32_t a2, uint32_t a3, uint64_t db, uint32_t meta) {
  asm volatile("{\n.reg .pred p;\nsetp.ne.b32 p, %30, 0;\nwgmma.mma_async.sp.sync.aligned.m64n48k32.f32.bf16.bf16 {%0,%1,%2,%3,%4,%5,%6,%7,%8,%9,%10,%11,%12,%13,%14,%15,%16,%17,%18,%19,%20,%21,%22,%23}, {%24,%25,%26,%27}, %28, %29, 0, p, 1, 1, 1;\n}\n"
    : "+f"(d[0]),"+f"(d[1]),"+f"(d[2]),"+f"(d[3]),"+f"(d[4]),"+f"(d[5]),"+f"(d[6]),"+f"(d[7]),"+f"(d[8]),"+f"(d[9]),"+f"(d[10]),"+f"(d[11]),"+f"(d[12]),"+f"(d[13]),"+f"(d[14]),"+f"(d[15]),"+f"(d[16]),"+f"(d[17]),"+f"(d[18]),"+f"(d[19]),"+f"(d[20]),"+f"(d[21]),"+f"(d[22]),"+f"(d[23]) : "r"(a0), "r"(a1), "r"(a2), "r"(a3), "l"(db), "r"(meta), "n"(SC));
}
template<int SC> __device__ __forceinline__ void wg_ss192(float (&d)[96], uint64_t da, uint64_t db) {
  asm volatile("{\n.reg .pred p;\nsetp.ne.b32 p, %98, 0;\nwgmma.mma_async.sync.aligned.m64n192k16.f32.bf16.bf16 {%0,%1,%2,%3,%4,%5,%6,%7,%8,%9,%10,%11,%12,%13,%14,%15,%16,%17,%18,%19,%20,%21,%22,%23,%24,%25,%26,%27,%28,%29,%30,%31,%32,%33,%34,%35,%36,%37,%38,%39,%40,%41,%42,%43,%44,%45,%46,%47,%48,%49,%50,%51,%52,%53,%54,%55,%56,%57,%58,%59,%60,%61,%62,%63,%64,%65,%66,%67,%68,%69,%70,%71,%72,%73,%74,%75,%76,%77,%78,%79,%80,%81,%82,%83,%84,%85,%86,%87,%88,%89,%90,%91,%92,%93,%94,%95}, %96, %97, p, 1, 1, 0, 1;\n}\n"
    : "+f"(d[0]),"+f"(d[1]),"+f"(d[2]),"+f"(d[3]),"+f"(d[4]),"+f"(d[5]),"+f"(d[6]),"+f"(d[7]),"+f"(d[8]),"+f"(d[9]),"+f"(d[10]),"+f"(d[11]),"+f"(d[12]),"+f"(d[13]),"+f"(d[14]),"+f"(d[15]),"+f"(d[16]),"+f"(d[17]),"+f"(d[18]),"+f"(d[19]),"+f"(d[20]),"+f"(d[21]),"+f"(d[22]),"+f"(d[23]),"+f"(d[24]),"+f"(d[25]),"+f"(d[26]),"+f"(d[27]),"+f"(d[28]),"+f"(d[29]),"+f"(d[30]),"+f"(d[31]),"+f"(d[32]),"+f"(d[33]),"+f"(d[34]),"+f"(d[35]),"+f"(d[36]),"+f"(d[37]),"+f"(d[38]),"+f"(d[39]),"+f"(d[40]),"+f"(d[41]),"+f"(d[42]),"+f"(d[43]),"+f"(d[44]),"+f"(d[45]),"+f"(d[46]),"+f"(d[47]),"+f"(d[48]),"+f"(d[49]),"+f"(d[50]),"+f"(d[51]),"+f"(d[52]),"+f"(d[53]),"+f"(d[54]),"+f"(d[55]),"+f"(d[56]),"+f"(d[57]),"+f"(d[58]),"+f"(d[59]),"+f"(d[60]),"+f"(d[61]),"+f"(d[62]),"+f"(d[63]),"+f"(d[64]),"+f"(d[65]),"+f"(d[66]),"+f"(d[67]),"+f"(d[68]),"+f"(d[69]),"+f"(d[70]),"+f"(d[71]),"+f"(d[72]),"+f"(d[73]),"+f"(d[74]),"+f"(d[75]),"+f"(d[76]),"+f"(d[77]),"+f"(d[78]),"+f"(d[79]),"+f"(d[80]),"+f"(d[81]),"+f"(d[82]),"+f"(d[83]),"+f"(d[84]),"+f"(d[85]),"+f"(d[86]),"+f"(d[87]),"+f"(d[88]),"+f"(d[89]),"+f"(d[90]),"+f"(d[91]),"+f"(d[92]),"+f"(d[93]),"+f"(d[94]),"+f"(d[95]) : "l"(da), "l"(db), "n"(SC));
}

constexpr uint32_t SBC = 1024;
constexpr int ROWB = 2 * 224 * 384;
constexpr int TB = 12;
constexpr int KS = 832;
constexpr int KSLOT = 22 * KS;
constexpr int SM_X1 = 0;
constexpr int SM_X2 = SM_X1 + 24576;
constexpr int SM_X0 = SM_X2 + 24576;
constexpr int SM_W = SM_X0 + 18432;
constexpr int SM_K = SM_W + 55296;
constexpr int SM_V = SM_K + 2 * KSLOT;
constexpr int SM_Q = SM_V + 22 * 1536;
constexpr int SM_O = SM_Q + 24576;
constexpr int SM_RPB = SM_O + 12288;
constexpr int SM_BAR = SM_RPB + 768;
constexpr int SM_A_TOTAL = SM_BAR + 256;
constexpr int SM_TWO = SM_X1;
constexpr int SM_TST = SM_TWO + 36864;
constexpr int SM_TIN = SM_W;
enum { B_FULL = 0, B_EMPTY = 3, B_TIN = 6, B_TFREE = 8, B_WK = 10, B_WQ, B_WO, B_Q0, B_ODONE, B_KFREE = B_ODONE + 2, B_VFREE, B_COUNT };
enum { N_KRDY = 4, N_QK0, N_QK1, N_VQ0, N_VQ1, N_PVISS };

#define SPL 4
#define RA 152
#define RG 184
__device__ int g_flags[TB * 56];

#define TR(role, it, k)
#define TRDECL
#define TRARG
#define TRPASS
#define TRDUMP
#define TRB(it, k)
#define TR2(blk, k)

struct GemmCtx {
  uint32_t bar;
  uint32_t kC, vC, qC;
  uint32_t kH, vH;
  bool hvalid;
};

template <int STRIDE> __device__ __forceinline__ void dump12(uint32_t a, const uint32_t (&r)[12]) {
#pragma unroll
  for (int j = 0; j < 3; j++) stsm4(a + j * 2 * STRIDE, r[4 * j], r[4 * j + 1], r[4 * j + 2], r[4 * j + 3]);
}
template <int N> __device__ __forceinline__ void pack12(uint32_t (&r)[12], const float (&d)[N], int off) {
#pragma unroll
  for (int j = 0; j < 12; j++) r[j] = pack2(d[off + 2 * j], d[off + 2 * j + 1]);
}
template <int XS, int K0, int K1> __device__ __forceinline__ void issue_core(float (&d)[72]) {
  constexpr uint64_t da = mkdesc(SBC + XS, 16, 1024, 1), db = mkdesc(SBC + SM_W, 6144, 256, 3);
  wg_fence();
  if (K0 == 0) wg_ss144<0>(d, da, db);
#pragma unroll
  for (int k = K0 ? K0 : 1; k < K1; k++) wg_ss144<1>(d, da + (k >> 2) * 512 + (k & 3) * 2, db + k * 32);
  wg_commit();
}
template <int K0, int K1> __device__ __forceinline__ void issue_halo(float (&d)[48]) {
  constexpr uint64_t da = mkdesc(SBC + SM_X0 - 2048, 16, 1024, 1), db = mkdesc(SBC + SM_W, 6144, 256, 3);
  wg_fence();
  if (K0 == 0) wg_ss96<0>(d, da, db);
#pragma unroll
  for (int k = K0 ? K0 : 1; k < K1; k++) wg_ss96<1>(d, da + (k >> 2) * 384 + (k & 3) * 2, db + k * 32);
  wg_commit();
}
template <int ST, int BYTES> __device__ __forceinline__ void release_stage(const GemmCtx& c, bool on) {
  asm volatile("{\n.reg .pred p, q;\n.reg .b32 ra;\nsetp.ne.b32 q, %2, 0;\nelect.sync _|p, 0xffffffff;\nand.pred p, p, q;\n"
               "mapa.shared::cluster.u32 ra, %1, %4;\n"
               "@p mbarrier.arrive.expect_tx.shared::cta.b64 _, [%0], %3;\n@p mbarrier.arrive.shared::cluster.b64 _, [ra];\n}"
               ::"r"(c.bar + (B_FULL + ST) * 8), "r"(c.bar + (B_EMPTY + ST) * 8), "r"((int)on), "n"(BYTES / 4), "n"(ST) : "memory");
}
__device__ __forceinline__ void load_w(const CUtensorMap* m, uint32_t dst, uint32_t bar, int col) {
  asm volatile("cp.async.bulk.tensor.2d.shared::cluster.global.mbarrier::complete_tx::bytes [%0], [%1, {%3,%4}], [%2];"
               ::"r"(dst), "l"(m), "r"(bar), "r"(col), "r"(0) : "memory");
}
__device__ __forceinline__ void publish(uint32_t bar) {
  fence_async();
  __syncwarp();
  mbar_arrive_elect(bar);
}

template <bool FIRST, bool LAST>
__device__ __forceinline__ void gemm_iter(const GemmCtx& c, int b, uint32_t (&pk)[12], uint32_t (&pv)[12], uint32_t (&pq)[12], int head TRARG) {
  const uint32_t bar = c.bar;
  const uint32_t pa = b & 1;
  const bool w = b >= 0;
  const uint32_t ko = pa * KSLOT, vx = pa * 16, qx = pa * 128;
  float H[48], C[72];
  uint32_t hk[12], hv[12], pv2[12];
  TR(2, b, 0);
  if (FIRST) mbar_wait(bar + (B_FULL + 0) * 8, pa);
  if (w) nb_sync(N_QK1, 256);
  TR(2, b, 2);
  issue_halo<0, 8>(H);
  TR(2, b, 3);
  if (!FIRST) {
    if (w) mbar_wait(bar + B_KFREE * 8, pa);
    dump12<128>(c.kC + ko, pk);
  }
  issue_halo<8, 12>(H);
  TR(2, b, 4);
  if (!LAST) {
    mbar_wait(bar + (B_FULL + 2) * 8, pa);
    if (FIRST) mbar_wait(bar + B_WQ * 8, 0);
    TR(2, b, 13);
    issue_core<SM_X2, 0, 8>(C);
    TR(2, b, 5);
    if (!FIRST) { fence_async(); dump12<256>(c.qC ^ (qx ^ 192), pq); }
    wg_wait<1>(); pin(H);
    release_stage<0, 18432>(c, true);
  } else {
    dump12<256>(c.qC ^ (qx ^ 192), pq);
    fence_async();
    nb_arrive(N_VQ0, 288); nb_arrive(N_VQ1, 288);
    wg_wait<0>(); pin(H);
    uint32_t ln; asm volatile("mov.u32 %0, %%laneid;" : "=r"(ln));
    if (ln < 4) mbar_arrive_remote(bar + (B_TFREE + (head >> 1)) * 8, ln);
  }
  pack12(hk, H, 0);
  if (c.hvalid) dump12<128>(c.kH + ko, hk);
  pack12(hv, H, 24);
  if (!LAST) {
    issue_core<SM_X2, 8, 12>(C);
    if (w) { nb_arrive(N_VQ0, 288); nb_arrive(N_VQ1, 288); }
    else if (!FIRST) { __syncwarp(); mbar_arrive_elect(bar + B_Q0 * 8); }
    mbar_wait(bar + (B_FULL + 1) * 8, pa);
    TR(2, b, 6);
    wg_wait<0>(); pin(C);
    TR(2, b, 7);
    pack12(pk, C, 0);
    dump12<128>(c.kC + ko + 64, pk);
    release_stage<2, 24576>(c, b < 11);
    pack12(pv2, C, 24);
    pack12(pq, C, 48);
    TR(2, b, 8);
    issue_core<SM_X1, 0, SPL>(C);
    if (w) nb_sync(N_PVISS, 384);
    issue_core<SM_X1, SPL, 8>(C);
    TR(2, b, 9);
  }
  if (!FIRST) fence_async();
  TR(2, b, 14);
  if (!LAST) issue_core<SM_X1, 8, 12>(C);
  if (!FIRST) nb_arrive(N_KRDY, 256);
  TR(2, b, 1);
  if (!LAST) mbar_wait(bar + (B_FULL + 0) * 8, pa ^ 1);
  if (w) mbar_wait(bar + B_VFREE * 8, pa);
  TR(2, b, 10);
  if (!FIRST) dump12<128>(c.vC ^ vx, pv);
  if (!LAST) dump12<256>(c.qC ^ qx, pq);
  if (c.hvalid) dump12<128>(c.vH ^ vx, hv);
  if (LAST) { fence_async(); nb_arrive(N_VQ0, 288); nb_arrive(N_VQ1, 288); return; }
  dump12<128>((c.vC ^ vx ^ 16) + 768, pv2);
  TR(2, b, 11);
  wg_wait<0>(); pin(C);
  TR(2, b, 12);
  release_stage<1, 24576>(c, b < 11);
  pack12(pk, C, 0);
  pack12(pv, C, 24);
  pack12(pq, C, 48);
}

__device__ __forceinline__ float fold(float a, float b, float t, int useb) {
  float r;
  asm("{\n.reg .pred p;\nsetp.ne.b32 p, %4, 0;\nfma.rn.f32 %0, %1, 0f3E553B95, %3;\n@p fma.rn.f32 %0, %2, 0f3E553B95, %3;\n}"
      : "=&f"(r) : "f"(a), "f"(b), "f"(t), "r"(useb));
  return r;
}
template <int U, int L, bool BORDER>
__device__ __forceinline__ void softmax_tile(const float (&SA)[56], const float (&SB)[56], const float (&T)[14], int b0, int b1,
                                             uint32_t ra0, uint32_t ra1, int qcu, uint32_t (&P)[28], float (&sx)[8]) {
  float lu[14], ll[14];
#pragma unroll
  for (int j = 0; j < 7; j++) {
    float tu0, tu1, tl0, tl1;
    if (BORDER) {
      tu0 = lds_f32(ra0 + (U + j + 3 - qcu) * 4); tu1 = lds_f32(ra1 + (U + j + 3 - qcu) * 4);
      tl0 = lds_f32(ra0 + (L + j + 2 - qcu) * 4); tl1 = lds_f32(ra1 + (L + j + 2 - qcu) * 4);
    } else { tu0 = tl0 = T[2 * j]; tu1 = tl1 = T[2 * j + 1]; }
    lu[2 * j]     = fold(SA[4 * (U + j)],     SB[4 * (U + j)],     tu0, b0);
    ll[2 * j]     = fold(SA[4 * (L + j) + 2], SB[4 * (L + j) + 2], tl0, b0);
    lu[2 * j + 1] = fold(SA[4 * (U + j) + 1], SB[4 * (U + j) + 1], tu1, b1);
    ll[2 * j + 1] = fold(SA[4 * (L + j) + 3], SB[4 * (L + j) + 3], tl1, b1);
  }
  float mu = lu[0], ml = ll[0], mu2 = lu[1], ml2 = ll[1];
#pragma unroll
  for (int j = 1; j < 7; j++) { mu = fmaxf(mu, lu[2 * j]); mu2 = fmaxf(mu2, lu[2 * j + 1]); ml = fmaxf(ml, ll[2 * j]); ml2 = fmaxf(ml2, ll[2 * j + 1]); }
  mu = fmaxf(mu, mu2); ml = fmaxf(ml, ml2);
  { const float a1 = __shfl_xor_sync(0xffffffffu, mu, 1), a2 = __shfl_xor_sync(0xffffffffu, mu, 2), a3 = __shfl_xor_sync(0xffffffffu, mu, 3);
    const float c1 = __shfl_xor_sync(0xffffffffu, ml, 1), c2 = __shfl_xor_sync(0xffffffffu, ml, 2), c3 = __shfl_xor_sync(0xffffffffu, ml, 3);
    mu = fmaxf(fmaxf(mu, a1), fmaxf(a2, a3)); ml = fmaxf(fmaxf(ml, c1), fmaxf(c2, c3)); }
  float su = 0.f, sl = 0.f;
#pragma unroll
  for (int c = 0; c < 14; c++) {
    const int iu = (c >> 1) * 4 + (c & 1) * 2;
    if (c >= U && c < U + 7) {
      float e0 = ex2(lu[2 * (c - U)] - mu), e1 = ex2(lu[2 * (c - U) + 1] - mu);
      su = c == U ? e0 + e1 : (su + e0) + e1; P[iu] = pack2(e0, e1);
    } else P[iu] = 0u;
    if (c >= L && c < L + 7) {
      float e0 = ex2(ll[2 * (c - L)] - ml), e1 = ex2(ll[2 * (c - L) + 1] - ml);
      sl = c == L ? e0 + e1 : (sl + e0) + e1; P[iu + 1] = pack2(e0, e1);
    } else P[iu + 1] = 0u;
  }
  sx[0] = su; sx[4] = sl;
#pragma unroll
  for (int k = 1; k < 4; k++) { sx[k] = __shfl_xor_sync(0xffffffffu, su, k); sx[4 + k] = __shfl_xor_sync(0xffffffffu, sl, k); }
}

struct Maps { CUtensorMap xc, xh, w, os, wo, ot; };

__global__ void __cluster_dims__(4, 1, 1) __launch_bounds__(512, 1)
na_attn_kernel(const __grid_constant__ Maps mp, const __nv_bfloat16* __restrict__ wqkv, const __nv_bfloat16* __restrict__ rpb) {
  extern __shared__ __align__(1024) uint8_t smem_raw[];
  const uint32_t sb = smem_u32(smem_raw);
  if ((sb & 0x3FFFF) != SBC) return;
  const uint32_t bar = sb + SM_BAR;
  TR2(blockIdx.x, 0);
  const int tid = threadIdx.x, lane = tid & 31;
  const int warp = __shfl_sync(0xffffffffu, tid >> 5, 0);
  const int head = blockIdx.x & 3, cl = blockIdx.x >> 2;
  const int par = cl / 7, strip = cl - par * 7, ph = par >> 1, pw = par & 1;

  uint4 wv[3];
  const int wr = tid / 6, wc = tid - wr * 6;
  if (warp < 12) {
#pragma unroll
    for (int i = 0; i < 3; i++) wv[i] = __ldg(reinterpret_cast<const uint4*>(wqkv + (wr + i * 64) * 576 + 384 + head * 48 + wc * 8));
  } else if (elect_one()) {
    if (warp == 12) {
      mbar_init(bar + B_WK * 8, 1);
#pragma unroll
      for (int i = 0; i < 3; i++) load_w(&mp.w, sb + SM_W + i * 6144, bar + B_WK * 8, 192 + head * 48 + i * 16);
      mbar_expect(bar + B_WK * 8, 18432);
    } else if (warp == 13) {
#pragma unroll
      for (int i = 0; i < B_WK; i++) mbar_init(bar + i * 8, i < B_EMPTY ? 4 : (i < B_TIN ? 16 : (i < B_TFREE ? 1 : 8)));
    } else if (warp == 14) {
#pragma unroll
      for (int i = B_WQ; i < B_COUNT; i++) mbar_init(bar + i * 8, i < B_Q0 ? 1 : (i < B_KFREE ? 4 : 8));
    }
    asm volatile("fence.mbarrier_init.release.cluster;" ::: "memory");
  }
  __syncwarp();
  asm volatile("barrier.cluster.arrive.relaxed.aligned;" ::: "memory");

  if (warp >= 12) {
    asm volatile("setmaxnreg.dec.sync.aligned.u32 24;");
    asm volatile("griddepcontrol.launch_dependents;");
    const int cc = ph * 112 + (head ? strip * 16 : (strip == 0 ? 16 : (strip == 6 ? 74 : strip * 16 - 3)));
    const int sd = strip == 0 ? -1 : (strip == 6 ? 1 : 0);
    const int r0 = head == 0 ? -4 : (head == 1 ? 4 : 0);
    asm volatile("barrier.cluster.wait.aligned;" ::: "memory");
    if (warp == 12) {
      const uint32_t fb = bar + (B_FULL + head) * 8, eb = bar + (B_EMPTY + head) * 8;
      const uint32_t dst = sb + (head == 0 ? SM_X0 : (head == 1 ? SM_X1 : SM_X2));
      const int nl = head == 0 ? 15 : (head == 3 ? 1 : 14);
#pragma unroll 1
      for (int n = 0; n < nl; n++) {
        if (n) mbar_wait(eb, (n - 1) & 1);
        if (elect_one()) {
          if (head == 0) {
            asm volatile("cp.async.bulk.tensor.5d.shared::cluster.global.mbarrier::complete_tx::bytes.multicast::cluster [%0], [%1, {%3,%4,%5,%6,%7}], [%2], %8;"
                         ::"r"(dst), "l"(&mp.xh), "r"(fb), "r"(0), "r"(8 * n + r0), "r"(cc), "r"(sd), "r"(pw * 3), "h"((uint16_t)15) : "memory");
            if (n + 1 < nl) asm volatile("cp.async.bulk.prefetch.tensor.5d.L2.global [%0, {%1,%2,%3,%4,%5}];" ::"l"(&mp.xh), "r"(0), "r"(8 * n + 8 + r0), "r"(cc), "r"(sd), "r"(pw * 3) : "memory");
          } else if (head < 3) {
            asm volatile("cp.async.bulk.tensor.4d.shared::cluster.global.mbarrier::complete_tx::bytes.multicast::cluster [%0], [%1, {%3,%4,%5,%6}], [%2], %7;"
                         ::"r"(dst), "l"(&mp.xc), "r"(fb), "r"(0), "r"(8 * n + r0), "r"(cc), "r"(pw * 3), "h"((uint16_t)15) : "memory");
          }
          if (n == 0) {
#pragma unroll
            for (int i = 0; i < 3; i++) load_w(&mp.w, sb + SM_W + (6 + i) * 6144, bar + B_WQ * 8, head * 48 + i * 16);
            mbar_expect(bar + B_WQ * 8, 18432);
            mbar_expect(bar + B_TIN * 8, 24576); mbar_expect(bar + (B_TIN + 1) * 8, 24576);
          }
          if (head && n + 1 < nl) asm volatile("cp.async.bulk.prefetch.tensor.4d.L2.global [%0, {%1,%2,%3,%4}];" ::"l"(&mp.xc), "r"(0), "r"(8 * n + 8 + r0), "r"(cc), "r"(pw * 3) : "memory");
        }
        __syncwarp();
      }
    }
    if (warp >= 14) {
      const int j = warp - 14;
      int* flag = g_flags + cl * 2 + j;
      nb_arrive(N_VQ0 + j, 288);
#pragma unroll 1
      for (int b = 0; b < TB; b++) {
        mbar_wait(bar + (B_ODONE + j) * 8, b & 1);
        if (lane == 0) {
          asm volatile("cp.async.bulk.tensor.3d.global.shared::cta.bulk_group [%0, {%2,%3,%4}], [%1];"
                       ::"l"(&mp.os), "r"(sb + SM_O + j * 6144), "r"(pw * 192), "r"(8 * b + 2 * head), "r"(ph * 112 + strip * 16 + 8 * j) : "memory");
          asm volatile("cp.async.bulk.commit_group;\ncp.async.bulk.wait_group.read 0;" ::: "memory");
        }
        __syncwarp();
        nb_arrive(N_VQ0 + j, 288);
        if (lane == 0) {
          asm volatile("cp.async.bulk.wait_group 0;\nfence.proxy.async.global;\nred.release.gpu.global.add.s32 [%0], 1;" ::"l"(flag + b * 56) : "memory");
        }
        __syncwarp();
      }
#pragma unroll 1
      for (int i = 0; i < 2; i++) {
        mbar_wait(bar + (B_ODONE + j) * 8, i);
        if (i == 0) { nb_arrive(N_VQ0 + j, 288); mbar_wait(bar + (B_TFREE + j) * 8, 0); }
        if (elect_one()) {
#pragma unroll
          for (int d = 0; d < 2; d++)
            asm volatile("{\n.reg .b32 rd, rb;\nmapa.shared::cluster.u32 rd, %0, %3;\nmapa.shared::cluster.u32 rb, %2, %3;\n"
                         "cp.async.bulk.shared::cluster.shared::cta.mbarrier::complete_tx::bytes [rd], [%1], 6144, [rb];\n}"
                         ::"r"(sb + SM_TIN + i * 24576 + head * 6144), "r"(sb + (i ? SM_Q + j * 12288 : SM_O + j * 6144)), "r"(bar + (B_TIN + i) * 8), "r"(2 * j + d) : "memory");
        }
        __syncwarp();
      }
    }
    cluster_sync();
  } else if (warp >= 8) {
    asm volatile("setmaxnreg.inc.sync.aligned.u32 %0;" ::"n"(RG));
    GemmCtx c;
    c.bar = bar;
    const int gw = warp - 8, tk = gw * 16 + (lane & 15), hi = lane >> 4;
    { const int col = tk >> 2, i = tk & 3;
      c.kC = sb + SM_K + (col + 3) * KS + hi * 128 + i * 16;
      c.vC = sb + SM_V + (col + 3) * 1536 + hi * 128 + (2 * i + ((col + 3) & 1)) * 16;
      c.qC = sb + SM_Q + col * 1536 + hi * 256 + (col & 1) * 64 + i * 16; }
    { const int ci = (tk >> 3) - 2, kc = ci < 3 ? ci : ci + 16, i = tk & 7; c.hvalid = gw > 0;
      c.kH = sb + SM_K + kc * KS + hi * 128 + i * 16;
      c.vH = sb + SM_V + kc * 1536 + hi * 128 + (i >> 2) * 768 + (2 * (i & 3) + ((kc ^ (i >> 2)) & 1)) * 16; }
    asm volatile("barrier.cluster.wait.aligned;" ::: "memory");
    if (elect_one()) { mbar_expect(bar + B_FULL * 8, 4608); mbar_expect(bar + (B_FULL + 1) * 8, 6144); mbar_expect(bar + (B_FULL + 2) * 8, 6144); }
    __syncwarp();
#pragma unroll
    for (int i = 0; i < 3; i++) sts128(sb + SM_W + (3 + (wc >> 1)) * 6144 + (wr + i * 64) * 32 + ((wc ^ (wr >> 2)) & 1) * 16, wv[i]);
    fence_async();
    asm volatile("bar.sync 1, 384;" ::: "memory");
    mbar_wait(bar + B_WK * 8, 0);
    uint32_t pk[12], pv[12], pq[12];
    TRDECL;
    gemm_iter<true, false>(c, -2, pk, pv, pq, head TRPASS);
#pragma unroll 1
    for (int b = -1; b < 12; b++) gemm_iter<false, false>(c, b, pk, pv, pq, head TRPASS);
    asm volatile("bar.sync 2, 128;" ::: "memory");
    if (gw == 0 && elect_one()) {
      mbar_expect(bar + B_WO * 8, 36864);
      asm volatile("cp.async.bulk.tensor.3d.shared::cluster.global.mbarrier::complete_tx::bytes [%0], [%1, {%3,%4,%5}], [%2];"
                   ::"r"(sb + SM_TWO), "l"(&mp.wo), "r"(bar + B_WO * 8), "r"(0), "r"(0), "r"((head & 1) * 3) : "memory");
    }
    __syncwarp();
    gemm_iter<false, true>(c, 12, pk, pv, pq, head TRPASS);
    TRDUMP;
    mbar_wait(bar + B_WO * 8, 0);
    nb_sync(N_QK1, 256);
    const uint32_t st = sb + SM_TST + gw * 3072;
    const uint32_t sta = st + (lane & 15) * 64 + ((hi ^ ((lane >> 1) & 3)) * 16);
#pragma unroll 1
    for (int i = 0; i < 2; i++) {
      constexpr uint64_t db = mkdesc(SBC + SM_TWO, 12288, 512, 2);
      const uint64_t da = mkdesc(SBC + SM_TIN, 128, 768, 0) + i * (24576 / 16);
      float D[48];
      mbar_wait(bar + (B_TIN + i) * 8, 0);
      wg_fence();
      wg_ss96<0>(D, da, db);
#pragma unroll
      for (int k = 1; k < 12; k++) wg_ss96<1>(D, da + (k / 3) * 384 + (k % 3) * 16, db + k * 64);
      wg_commit();
      if (lane == 0) asm volatile("cp.async.bulk.wait_group.read 0;" ::: "memory");
      __syncwarp();
      wg_wait<0>(); pin(D);
#pragma unroll
      for (int q = 0; q < 6; q++)
        stsm4((sta ^ ((q & 1) * 32)) + (q >> 1) * 1024,
              pack2(D[8 * q], D[8 * q + 1]), pack2(D[8 * q + 2], D[8 * q + 3]), pack2(D[8 * q + 4], D[8 * q + 5]), pack2(D[8 * q + 6], D[8 * q + 7]));
      fence_async();
      __syncwarp();
      if (lane == 0) {
        asm volatile("cp.async.bulk.tensor.4d.global.shared::cta.bulk_group [%0, {%2,%3,%4,%5}], [%1];"
                     ::"l"(&mp.ot), "r"(st), "r"(0), "r"(8 * (TB + i)), "r"(ph * 112 + strip * 16 + 8 * (head >> 1) + 2 * gw), "r"(pw * 6 + (head & 1) * 3) : "memory");
        asm volatile("cp.async.bulk.commit_group;" ::: "memory");
      }
    }
    asm volatile("barrier.cluster.arrive.relaxed.aligned;" ::: "memory");
    if (lane == 0) asm volatile("cp.async.bulk.wait_group 0;" ::: "memory");
    __syncwarp();
    asm volatile("barrier.cluster.wait.aligned;" ::: "memory");
  } else {
    asm volatile("setmaxnreg.inc.sync.aligned.u32 %0;" ::"n"(RA));
    float rv = -INFINITY;
    if (tid < 169) rv = __bfloat162float(rpb[head * 169 + tid]) * 1.4426950408889634f;
    if (tid < 192) {
      const int kc = (wr & 15) + 3;
      sts128(tid < 96 ? sb + SM_K + kc * KS + wc * 128 + 48 : sb + SM_V + kc * 1536 + wc * 128 + (6 + (kc & 1)) * 16, make_uint4(0, 0, 0, 0));
    }
#pragma unroll
    for (int i = 0; i < 3; i++) sts128(sb + SM_W + (3 + (wc >> 1)) * 6144 + (wr + i * 64) * 32 + ((wc ^ (wr >> 2)) & 1) * 16, wv[i]);
    fence_async();
    asm volatile("bar.arrive 1, 384;" ::: "memory");
    if (tid < 182) asm volatile("st.shared.f32 [%0], %1;" ::"r"(sb + SM_RPB + tid * 4), "f"(rv) : "memory");
    const int j = warp >> 2, w = warp & 3;
    int variant = w;
    if (strip == 0 && j == 0 && w < 2) variant = 4;
    if (strip == 6 && j == 1 && w >= 2) variant = 5;
    const uint32_t qa = sb + SM_Q + (8 * j + 2 * w + ((lane >> 3) & 1)) * 1536 + (lane >> 4) * 256 + (((lane & 7) * 16) ^ (((lane >> 3) & 1) * 64));
    uint32_t oa = sb + SM_O + j * 6144 + (2 * w + ((lane >> 3) & 1)) * 768 + (lane >> 4) * 128 + (lane & 7) * 16;
    const uint64_t dK = mkdesc(SBC + SM_K, 128, KS, 0) + j * (8 * KS / 16);
    const uint64_t dV = mkdesc(SBC + SM_V, 768, 128, 0) + j * (8 * 1536 / 16);
    asm volatile("barrier.cluster.wait.aligned;" ::: "memory");
    asm volatile("bar.sync 3, 256;" ::: "memory");
    float T[14];
    TRDECL;
    int b0 = 0, b1 = 0;
    uint32_t ra0 = 0, ra1 = 0, meta = 0;
    uint32_t q[12];
    mbar_wait(bar + B_Q0 * 8, 0);
#pragma unroll
    for (int k = 0; k < 3; k++) ldsm4(qa + k * 512, q[4 * k], q[4 * k + 1], q[4 * k + 2], q[4 * k + 3]);
#pragma unroll 1
    for (int b = 0; b < 14; b++) {
      const uint32_t pa = b & 1;
      if (b <= 1 || b == 13) {
        uint32_t ln; asm volatile("mov.u32 %0, %%laneid;" : "=r"(ln));
        const int g = ln >> 2, t = ln & 3;
        const int sw = b == 0 ? max(g + 1, 4) : (b == 13 ? min(g + 1, 5) : g + 1);
        const int i0 = 2 * t, i1 = 2 * t + 1;
        b0 = i0 <= sw - 2; b1 = i1 <= sw - 2;
        const int m = sw - 1;
        ra0 = sb + SM_RPB + (i0 == m ? 13 : i0 + (b0 ? 8 : 0) - g + 2) * 52;
        ra1 = sb + SM_RPB + (i1 == m ? 13 : i1 + (b1 ? 8 : 0) - g + 2) * 52;
#pragma unroll
        for (int jj = 0; jj < 7; jj++) { T[2 * jj] = lds_f32(ra0 + (jj + 3) * 4); T[2 * jj + 1] = lds_f32(ra1 + (jj + 3) * 4); }
        uint32_t m16 = 0x8888u;
#pragma unroll
        for (int i = 0; i < 8; i++) m16 |= (uint32_t)(((i <= sw - 2) ^ (i >> 2) ^ t ^ b) & 1) << (2 * i);
        meta = m16 | (m16 << 16);
        if (b == 13) oa += SM_Q - SM_O + j * 6144;
      } else meta ^= 0x55555555u;
      float SA[56], SB[56];
      const uint64_t dA = dK + pa * (KSLOT >> 4), dB = dK + (pa ^ 1) * (KSLOT >> 4);
      TR(0, b, 0);
      nb_sync(N_KRDY + j, 256);
      TR(0, b, 1);
      TR(0, b - 1, 9);
      wg_fence();
      wg_rs112<0>(SA, q[0], q[1], q[2], q[3], dA);
      wg_rs112<0>(SB, q[0], q[1], q[2], q[3], dB);
      wg_rs112<1>(SA, q[4], q[5], q[6], q[7], dA + 16);
      wg_rs112<1>(SB, q[4], q[5], q[6], q[7], dB + 16);
      wg_rs112<1>(SA, q[8], q[9], q[10], q[11], dA + 32);
      wg_rs112<1>(SB, q[8], q[9], q[10], q[11], dB + 32);
      wg_commit();
      nb_arrive(N_QK0 + j, 256);
      TR(0, b, 2);
      wg_wait<0>(); pin(SA); pin(SB);
      mbar_arrive_elect(bar + B_KFREE * 8);
      TR(0, b, 3);
      TR(0, b - 1, 10);
      uint32_t P[28];
      float sx[8];
      switch (variant) {
        case 0: softmax_tile<0, 1, false>(SA, SB, T, b0, b1, ra0, ra1, 0, P, sx); break;
        case 1: softmax_tile<2, 3, false>(SA, SB, T, b0, b1, ra0, ra1, 0, P, sx); break;
        case 2: softmax_tile<4, 5, false>(SA, SB, T, b0, b1, ra0, ra1, 0, P, sx); break;
        case 3: softmax_tile<6, 7, false>(SA, SB, T, b0, b1, ra0, ra1, 0, P, sx); break;
        case 4: softmax_tile<3, 3, true>(SA, SB, T, b0, b1, ra0, ra1, 2 * w, P, sx); break;
        default: softmax_tile<4, 4, true>(SA, SB, T, b0, b1, ra0, ra1, 2 * w, P, sx); break;
      }
      float O[24];
      TR(0, b, 4);
      nb_sync(N_VQ0 + j, 288);
      TR(0, b, 5);
#pragma unroll
      for (int k = 0; k < 3; k++) ldsm4(qa + (pa ^ 1) * 128 + k * 512, q[4 * k], q[4 * k + 1], q[4 * k + 2], q[4 * k + 3]);
      wg_fence();
      wg_sp48<0>(O, P[0], P[1], P[2], P[3], dV, meta);
#pragma unroll
      for (int s = 1; s < 7; s++) wg_sp48<1>(O, P[4 * s], P[4 * s + 1], P[4 * s + 2], P[4 * s + 3], dV + s * 192, meta);
      wg_commit();
      if (b < 12) nb_arrive(N_PVISS, 384);
      TR(0, b, 6);
      wg_wait<0>(); pin(O);
      mbar_arrive_elect(bar + B_VFREE * 8);
      TR(0, b, 7);
      float ru, rl;
      asm("rcp.approx.ftz.f32 %0, %1;" : "=f"(ru) : "f"(((fmaf(O[0], 0.f, sx[0]) + sx[1]) + sx[2]) + sx[3]));
      asm("rcp.approx.ftz.f32 %0, %1;" : "=f"(rl) : "f"(((fmaf(O[2], 0.f, sx[4]) + sx[5]) + sx[6]) + sx[7]));
#pragma unroll
      for (int i = 0; i < 3; i++)
        stsm4(oa + i * 256, pack2(O[8 * i] * ru, O[8 * i + 1] * ru), pack2(O[8 * i + 2] * rl, O[8 * i + 3] * rl),
              pack2(O[8 * i + 4] * ru, O[8 * i + 5] * ru), pack2(O[8 * i + 6] * rl, O[8 * i + 7] * rl));
      publish(bar + (B_ODONE + j) * 8);
      TR(0, b, 8);
    }
    TRDUMP;
    cluster_sync();
    TR2(blockIdx.x, 2);
  }
}

constexpr int NSTB = 6;
constexpr int NTB = TB * 56;
constexpr int SM_B_IN = 0;
constexpr int SM_B_W = SM_B_IN + NSTB * 24576;
constexpr int SM_B_BAR = SM_B_W + 73728;
constexpr int SM_B_TOTAL = SM_B_BAR + 128;
struct MapsB { CUtensorMap oi, oo, wo; };

__global__ void __launch_bounds__(416, 1)
na_proj_kernel(const __grid_constant__ MapsB mp) {
  extern __shared__ __align__(1024) uint8_t smem_raw[];
  const uint32_t sb = smem_u32(smem_raw);
  if ((sb & 0x3FFFF) != SBC) return;
  const uint32_t bar = sb + SM_B_BAR;
  const int tid = threadIdx.x, lane = tid & 31;
  const int warp = __shfl_sync(0xffffffffu, tid >> 5, 0);
  TR2(132 + blockIdx.x, 0);
  TRB(47, 0);
  if (warp == 12 && elect_one()) {
#pragma unroll
    for (int i = 0; i <= 2 * NSTB; i++) mbar_init(bar + i * 8, i < NSTB || i == 2 * NSTB ? 1 : 4);
    mbar_expect(bar + 2 * NSTB * 8, 73728);
#pragma unroll
    for (int i = 0; i < 2; i++)
      asm volatile("cp.async.bulk.tensor.3d.shared::cluster.global.mbarrier::complete_tx::bytes [%0], [%1, {%3,%4,%5}], [%2];"
                   ::"r"(sb + SM_B_W + i * 36864), "l"(&mp.wo), "r"(bar + 2 * NSTB * 8), "r"(0), "r"(0), "r"(i * 3) : "memory");
  }
  __syncthreads();
  const int step = gridDim.x;
  if (warp == 12) {
    int it = 0;
    uint32_t spin = 0;
#pragma unroll 1
    for (int n = blockIdx.x; n < NTB && spin < SPIN_LIMIT; spin++) {
      int v = 0;
      const int mine = n + lane * step;
      if (lane < 8 && mine < NTB) asm volatile("ld.acquire.gpu.global.s32 %0, [%1];" : "=r"(v) : "l"(g_flags + mine) : "memory");
      int cnt = __ffs(~__ballot_sync(0xffffffffu, v >= 4)) - 1;
      asm volatile("fence.proxy.async.global;" ::: "memory");
      __syncwarp();
#pragma unroll 1
      for (; cnt > 0; cnt--, n += step, it++) {
        TRB(it, 0);
        const int b = n / 56, rem = n - b * 56, par = rem / 14;
        const int use = it / NSTB, st = it - use * NSTB;
        if (use) mbar_wait(bar + (NSTB + st) * 8, (use - 1) & 1);
        if (elect_one()) {
          mbar_expect(bar + st * 8, 24576);
          asm volatile("cp.async.bulk.tensor.3d.shared::cluster.global.mbarrier::complete_tx::bytes [%0], [%1, {%3,%4,%5}], [%2];"
                       ::"r"(sb + SM_B_IN + st * 24576), "l"(&mp.oi), "r"(bar + st * 8), "r"((par & 1) * 192), "r"(8 * b), "r"((par >> 1) * 112 + (rem - par * 14) * 8) : "memory");
        }
        __syncwarp();
        TRB(it, 2);
      }
    }
    for (int n = blockIdx.x + lane * step; n < NTB; n += 32 * step) g_flags[n] = 0;
  } else {
    const int wg = warp >> 2, w = warp & 3;
    constexpr uint64_t db = mkdesc(SBC + SM_B_W, 12288, 512, 2);
    const uint32_t sta0 = sb + SM_B_IN + w * 6144 + (lane & 15) * 128 + (((lane >> 4) ^ (lane & 7)) * 16);
    mbar_wait(bar + 2 * NSTB * 8, 0);
    TRB(47, 1);
    int use = 0;
#pragma unroll 1
    for (int n = blockIdx.x + wg * step; n < NTB; n += 3 * step, use++) {
      const int b = n / 56, rem = n - b * 56, par = rem / 14, sg = wg + 3 * (use & 1);
      const uint64_t da = mkdesc(SBC + SM_B_IN, 128, 3072, 0) + sg * (24576 / 16);
      float D[96];
      mbar_wait(bar + sg * 8, (use >> 1) & 1);
      if (use | wg) nb_sync(4 + wg, 256);
      TRB(use * 3 + wg, 3);
      wg_fence();
      wg_ss192<0>(D, da, db);
#pragma unroll
      for (int k = 1; k < 12; k++) wg_ss192<1>(D, da + k * 16, db + k * 64);
      wg_commit();
      if (n + step < NTB) nb_arrive(wg == 2 ? 4 : 5 + wg, 256);
      TRB(use * 3 + wg, 4);
      if (use && lane == 0) {
        asm volatile("cp.async.bulk.wait_group.read 0;" ::: "memory");
        mbar_arrive(bar + (NSTB + wg + 3 * (~use & 1)) * 8);
      }
      __syncwarp();
      wg_wait<0>(); pin(D);
      nb_sync(1 + wg, 128);
      TRB(use * 3 + wg, 5);
      const uint32_t sta = sta0 + sg * 24576;
#pragma unroll
      for (int q = 0; q < 12; q++)
        stsm4((sta ^ ((q & 3) * 32)) + (q >> 2) * 2048,
              pack2(D[8 * q], D[8 * q + 1]), pack2(D[8 * q + 2], D[8 * q + 3]), pack2(D[8 * q + 4], D[8 * q + 5]), pack2(D[8 * q + 6], D[8 * q + 7]));
      fence_async();
      __syncwarp();
      if (lane == 0) {
        asm volatile("cp.async.bulk.tensor.4d.global.shared::cta.bulk_group [%0, {%2,%3,%4,%5}], [%1];"
                     ::"l"(&mp.oo), "r"(sb + SM_B_IN + sg * 24576 + w * 6144), "r"(0), "r"(8 * b), "r"((par >> 1) * 112 + (rem - par * 14) * 8 + 2 * w), "r"((par & 1) * 3) : "memory");
        asm volatile("cp.async.bulk.commit_group;" ::: "memory");
      }
      __syncwarp();
      TRB(use * 3 + wg, 6);
    }
    if (lane == 0) asm volatile("cp.async.bulk.wait_group 0;" ::: "memory");
    TR2(132 + blockIdx.x, 2);
  }
}

typedef CUresult (*EncodeFn)(CUtensorMap*, CUtensorMapDataType, cuuint32_t, void*, const cuuint64_t*, const cuuint64_t*, const cuuint32_t*,
                             const cuuint32_t*, CUtensorMapInterleave, CUtensorMapSwizzle, CUtensorMapL2promotion, CUtensorMapFloatOOBfill);
static EncodeFn g_enc = nullptr;
static void make_map(CUtensorMap* m, const void* p, int rank, const cuuint64_t* dim, const cuuint64_t* str, const cuuint32_t* box, CUtensorMapSwizzle sw) {
  const cuuint32_t ones[5] = {1, 1, 1, 1, 1};
  g_enc(m, CU_TENSOR_MAP_DATA_TYPE_BFLOAT16, rank, (void*)p, dim, str, box, ones, CU_TENSOR_MAP_INTERLEAVE_NONE, sw,
        CU_TENSOR_MAP_L2_PROMOTION_L2_128B, CU_TENSOR_MAP_FLOAT_OOB_FILL_NONE);
}

extern "C" void kernel_launch(void* const* d_in, const int* in_sizes, int n_in, void* d_out, int out_size) {
  const __nv_bfloat16* x = (const __nv_bfloat16*)d_in[0];
  const __nv_bfloat16* wqkv = (const __nv_bfloat16*)d_in[1];
  const __nv_bfloat16* wo = (const __nv_bfloat16*)d_in[2];
  const __nv_bfloat16* rpb = (const __nv_bfloat16*)d_in[3];

  if (!g_enc) {
    void* fn = nullptr; cudaDriverEntryPointQueryResult qr;
    cudaGetDriverEntryPoint("cuTensorMapEncodeTiled", &fn, cudaEnableDefault, &qr);
    g_enc = (EncodeFn)fn;
    cudaFuncSetAttribute(na_attn_kernel, cudaFuncAttributeMaxDynamicSharedMemorySize, SM_A_TOTAL);
    cudaFuncSetAttribute(na_proj_kernel, cudaFuncAttributeMaxDynamicSharedMemorySize, SM_B_TOTAL);
  }
  Maps ma; MapsB mb;
  { cuuint64_t dim[4] = {64, 112, 224, 6}, str[3] = {(cuuint64_t)ROWB, 768, 128};
    cuuint32_t box[4] = {64, 4, 16, 3}, boxo[4] = {64, 8, 2, 3};
    make_map(&ma.xc, x, 4, dim, str, box, CU_TENSOR_MAP_SWIZZLE_128B);
    make_map(&mb.oo, d_out, 4, dim, str, boxo, CU_TENSOR_MAP_SWIZZLE_128B); }
  { cuuint64_t dim[5] = {64, 112, 224, 2, 6}, str[4] = {(cuuint64_t)ROWB, 768, 19 * 768, 128};
    cuuint32_t box[5] = {64, 8, 3, 2, 3};
    make_map(&ma.xh, x, 5, dim, str, box, CU_TENSOR_MAP_SWIZZLE_128B); }
  { cuuint64_t dim[3] = {384, 112, 224}, str[2] = {(cuuint64_t)ROWB, 768};
    cuuint32_t box[3] = {192, 8, 8}, boxs[3] = {192, 2, 8};
    make_map(&mb.oi, d_out, 3, dim, str, box, CU_TENSOR_MAP_SWIZZLE_NONE);
    make_map(&ma.os, d_out, 3, dim, str, boxs, CU_TENSOR_MAP_SWIZZLE_NONE); }
  { cuuint64_t dim[4] = {32, 112, 224, 12}, str[3] = {(cuuint64_t)ROWB, 768, 64};
    cuuint32_t box[4] = {32, 8, 2, 3};
    make_map(&ma.ot, d_out, 4, dim, str, box, CU_TENSOR_MAP_SWIZZLE_64B); }
  { cuuint64_t dim[2] = {576, 192}, str[1] = {1152};
    cuuint32_t box[2] = {16, 192};
    make_map(&ma.w, wqkv, 2, dim, str, box, CU_TENSOR_MAP_SWIZZLE_32B); }
  { cuuint64_t dim[3] = {32, 192, 6}, str[2] = {384, 64};
    cuuint32_t box[3] = {32, 192, 3};
    make_map(&ma.wo, wo, 3, dim, str, box, CU_TENSOR_MAP_SWIZZLE_64B);
    mb.wo = ma.wo; }
  na_attn_kernel<<<112, 512, SM_A_TOTAL>>>(ma, wqkv, rpb);
  cudaLaunchConfig_t cfg = {};
  cfg.gridDim = dim3(20); cfg.blockDim = dim3(416); cfg.dynamicSmemBytes = SM_B_TOTAL; cfg.stream = cudaStreamPerThread;
  cudaLaunchAttribute at[1];
  at[0].id = cudaLaunchAttributeProgrammaticStreamSerialization; at[0].val.programmaticStreamSerializationAllowed = 1;
  cfg.attrs = at; cfg.numAttrs = 1;
  cudaLaunchKernelEx(&cfg, na_proj_kernel, mb);
}
```

```cpp
#include <cuda_runtime.h>
#include <cuda_bf16.h>
#include <cuda.h>
#include <stdint.h>

#define SPIN_LIMIT (1u << 18)

__device__ __forceinline__ uint32_t smem_u32(const void* p) { return (uint32_t)__cvta_generic_to_shared(p); }
__device__ __forceinline__ void wg_fence() { asm volatile("wgmma.fence.sync.aligned;" ::: "memory"); }
__device__ __forceinline__ void wg_commit() { asm volatile("wgmma.commit_group.sync.aligned;" ::: "memory"); }
template <int N> __device__ __forceinline__ void wg_wait() { asm volatile("wgmma.wait_group.sync.aligned %0;" ::"n"(N) : "memory"); }
template <int N> __device__ __forceinline__ void pin(float (&d)[N]) {
#pragma unroll
  for (int i = 0; i < N; i++) asm volatile("" : "+f"(d[i])::"memory");
}
__host__ __device__ constexpr uint64_t mkdesc(uint32_t addr, uint32_t lbo, uint32_t sbo, uint32_t sw) {
  return (uint64_t)((addr & 0x3FFFF) >> 4) | ((uint64_t)(lbo >> 4) << 16) | ((uint64_t)(sbo >> 4) << 32) | ((uint64_t)sw << 62);
}
__device__ __forceinline__ void mbar_init(uint32_t bar, uint32_t cnt) { asm volatile("mbarrier.init.shared::cta.b64 [%0], %1;" ::"r"(bar), "r"(cnt) : "memory"); }
__device__ __forceinline__ void mbar_arrive(uint32_t bar) { asm volatile("mbarrier.arrive.shared::cta.b64 _, [%0];" ::"r"(bar) : "memory"); }
__device__ __forceinline__ bool elect_one() {
  uint32_t r; asm volatile("{\n.reg .pred p;\nelect.sync _|p, 0xffffffff;\nselp.u32 %0, 1, 0, p;\n}" : "=r"(r)); return r;
}
__device__ __forceinline__ void mbar_arrive_elect(uint32_t bar) {
  asm volatile("{\n.reg .pred p;\nelect.sync _|p, 0xffffffff;\n@p mbarrier.arrive.shared::cta.b64 _, [%0];\n}" ::"r"(bar) : "memory");
}
__device__ __forceinline__ void mbar_expect(uint32_t bar, uint32_t bytes) { asm volatile("mbarrier.arrive.expect_tx.shared::cta.b64 _, [%0], %1;" ::"r"(bar), "r"(bytes) : "memory"); }
__device__ __forceinline__ void mbar_arrive_remote(uint32_t bar, uint32_t cta) {
  asm volatile("{\n.reg .b32 ra;\nmapa.shared::cluster.u32 ra, %0, %1;\nmbarrier.arrive.shared::cluster.b64 _, [ra];\n}" ::"r"(bar), "r"(cta) : "memory");
}
__device__ __forceinline__ void mbar_wait(uint32_t bar, uint32_t parity) {
  asm volatile("{\n.reg .pred p;\n.reg .b32 n;\nmov.b32 n, 0;\nWL:\nmbarrier.try_wait.parity.shared::cta.b64 p, [%0], %1;\n@p bra WD;\n"
               "add.u32 n, n, 1;\nsetp.lt.u32 p, n, 65536;\n@p bra WL;\nWD:\n}" ::"r"(bar), "r"(parity) : "memory");
}
__device__ __forceinline__ void nb_sync(int id, int n) { asm volatile("bar.sync %0, %1;" ::"r"(id), "r"(n) : "memory"); }
__device__ __forceinline__ void nb_arrive(int id, int n) { asm volatile("bar.arrive %0, %1;" ::"r"(id), "r"(n) : "memory"); }
__device__ __forceinline__ void fence_async() { asm volatile("fence.proxy.async.shared::cta;" ::: "memory"); }
__device__ __forceinline__ void cluster_sync() {
  asm volatile("barrier.cluster.arrive.relaxed.aligned;\nbarrier.cluster.wait.aligned;" ::: "memory");
}
__device__ __forceinline__ uint32_t pack2(float lo, float hi) {
  uint32_t r; asm("cvt.rn.bf16x2.f32 %0, %1, %2;" : "=r"(r) : "f"(hi), "f"(lo)); return r;
}
__device__ __forceinline__ void stsm4(uint32_t a, uint32_t r0, uint32_t r1, uint32_t r2, uint32_t r3) {
  asm volatile("stmatrix.sync.aligned.m8n8.x4.shared.b16 [%0], {%1,%2,%3,%4};" ::"r"(a), "r"(r0), "r"(r1), "r"(r2), "r"(r3) : "memory");
}
__device__ __forceinline__ void ldsm4(uint32_t a, uint32_t& r0, uint32_t& r1, uint32_t& r2, uint32_t& r3) {
  asm volatile("ldmatrix.sync.aligned.m8n8.x4.shared.b16 {%0,%1,%2,%3}, [%4];" : "=r"(r0), "=r"(r1), "=r"(r2), "=r"(r3) : "r"(a) : "memory");
}
__device__ __forceinline__ void sts128(uint32_t a, uint4 v) {
  asm volatile("st.shared.v4.b32 [%0], {%1,%2,%3,%4};" ::"r"(a), "r"(v.x), "r"(v.y), "r"(v.z), "r"(v.w) : "memory");
}
__device__ __forceinline__ float lds_f32(uint32_t a) { float v; asm volatile("ld.shared.f32 %0, [%1];" : "=f"(v) : "r"(a)); return v; }
__device__ __forceinline__ float ex2(float x) { float y; asm("ex2.approx.ftz.f32 %0, %1;" : "=f"(y) : "f"(x)); return y; }

template<int SC> __device__ __forceinline__ void wg_ss144(float (&d)[72], uint64_t da, uint64_t db) {
  asm volatile("{\n.reg .pred p;\nsetp.ne.b32 p, %74, 0;\nwgmma.mma_async.sync.aligned.m64n144k16.f32.bf16.bf16 {%0,%1,%2,%3,%4,%5,%6,%7,%8,%9,%10,%11,%12,%13,%14,%15,%16,%17,%18,%19,%20,%21,%22,%23,%24,%25,%26,%27,%28,%29,%30,%31,%32,%33,%34,%35,%36,%37,%38,%39,%40,%41,%42,%43,%44,%45,%46,%47,%48,%49,%50,%51,%52,%53,%54,%55,%56,%57,%58,%59,%60,%61,%62,%63,%64,%65,%66,%67,%68,%69,%70,%71}, %72, %73, p, 1, 1, 0, 1;\n}\n"
    : "+f"(d[0]),"+f"(d[1]),"+f"(d[2]),"+f"(d[3]),"+f"(d[4]),"+f"(d[5]),"+f"(d[6]),"+f"(d[7]),"+f"(d[8]),"+f"(d[9]),"+f"(d[10]),"+f"(d[11]),"+f"(d[12]),"+f"(d[13]),"+f"(d[14]),"+f"(d[15]),"+f"(d[16]),"+f"(d[17]),"+f"(d[18]),"+f"(d[19]),"+f"(d[20]),"+f"(d[21]),"+f"(d[22]),"+f"(d[23]),"+f"(d[24]),"+f"(d[25]),"+f"(d[26]),"+f"(d[27]),"+f"(d[28]),"+f"(d[29]),"+f"(d[30]),"+f"(d[31]),"+f"(d[32]),"+f"(d[33]),"+f"(d[34]),"+f"(d[35]),"+f"(d[36]),"+f"(d[37]),"+f"(d[38]),"+f"(d[39]),"+f"(d[40]),"+f"(d[41]),"+f"(d[42]),"+f"(d[43]),"+f"(d[44]),"+f"(d[45]),"+f"(d[46]),"+f"(d[47]),"+f"(d[48]),"+f"(d[49]),"+f"(d[50]),"+f"(d[51]),"+f"(d[52]),"+f"(d[53]),"+f"(d[54]),"+f"(d[55]),"+f"(d[56]),"+f"(d[57]),"+f"(d[58]),"+f"(d[59]),"+f"(d[60]),"+f"(d[61]),"+f"(d[62]),"+f"(d[63]),"+f"(d[64]),"+f"(d[65]),"+f"(d[66]),"+f"(d[67]),"+f"(d[68]),"+f"(d[69]),"+f"(d[70]),"+f"(d[71]) : "l"(da), "l"(db), "n"(SC));
}
template<int SC> __device__ __forceinline__ void wg_ss96(float (&d)[48], uint64_t da, uint64_t db) {
  asm volatile("{\n.reg .pred p;\nsetp.ne.b32 p, %50, 0;\nwgmma.mma_async.sync.aligned.m64n96k16.f32.bf16.bf16 {%0,%1,%2,%3,%4,%5,%6,%7,%8,%9,%10,%11,%12,%13,%14,%15,%16,%17,%18,%19,%20,%21,%22,%23,%24,%25,%26,%27,%28,%29,%30,%31,%32,%33,%34,%35,%36,%37,%38,%39,%40,%41,%42,%43,%44,%45,%46,%47}, %48, %49, p, 1, 1, 0, 1;\n}\n"
    : "+f"(d[0]),"+f"(d[1]),"+f"(d[2]),"+f"(d[3]),"+f"(d[4]),"+f"(d[5]),"+f"(d[6]),"+f"(d[7]),"+f"(d[8]),"+f"(d[9]),"+f"(d[10]),"+f"(d[11]),"+f"(d[12]),"+f"(d[13]),"+f"(d[14]),"+f"(d[15]),"+f"(d[16]),"+f"(d[17]),"+f"(d[18]),"+f"(d[19]),"+f"(d[20]),"+f"(d[21]),"+f"(d[22]),"+f"(d[23]),"+f"(d[24]),"+f"(d[25]),"+f"(d[26]),"+f"(d[27]),"+f"(d[28]),"+f"(d[29]),"+f"(d[30]),"+f"(d[31]),"+f"(d[32]),"+f"(d[33]),"+f"(d[34]),"+f"(d[35]),"+f"(d[36]),"+f"(d[37]),"+f"(d[38]),"+f"(d[39]),"+f"(d[40]),"+f"(d[41]),"+f"(d[42]),"+f"(d[43]),"+f"(d[44]),"+f"(d[45]),"+f"(d[46]),"+f"(d[47]) : "l"(da), "l"(db), "n"(SC));
}
template<int SC> __device__ __forceinline__ void wg_rs112(float (&d)[56], uint32_t a0, uint32_t a1, uint32_t a2, uint32_t a3, uint64_t db) {
  asm volatile("{\n.reg .pred p;\nsetp.ne.b32 p, %61, 0;\nwgmma.mma_async.sync.aligned.m64n112k16.f32.bf16.bf16 {%0,%1,%2,%3,%4,%5,%6,%7,%8,%9,%10,%11,%12,%13,%14,%15,%16,%17,%18,%19,%20,%21,%22,%23,%24,%25,%26,%27,%28,%29,%30,%31,%32,%33,%34,%35,%36,%37,%38,%39,%40,%41,%42,%43,%44,%45,%46,%47,%48,%49,%50,%51,%52,%53,%54,%55}, {%56,%57,%58,%59}, %60, p, 1, 1, 0;\n}\n"
    : "+f"(d[0]),"+f"(d[1]),"+f"(d[2]),"+f"(d[3]),"+f"(d[4]),"+f"(d[5]),"+f"(d[6]),"+f"(d[7]),"+f"(d[8]),"+f"(d[9]),"+f"(d[10]),"+f"(d[11]),"+f"(d[12]),"+f"(d[13]),"+f"(d[14]),"+f"(d[15]),"+f"(d[16]),"+f"(d[17]),"+f"(d[18]),"+f"(d[19]),"+f"(d[20]),"+f"(d[21]),"+f"(d[22]),"+f"(d[23]),"+f"(d[24]),"+f"(d[25]),"+f"(d[26]),"+f"(d[27]),"+f"(d[28]),"+f"(d[29]),"+f"(d[30]),"+f"(d[31]),"+f"(d[32]),"+f"(d[33]),"+f"(d[34]),"+f"(d[35]),"+f"(d[36]),"+f"(d[37]),"+f"(d[38]),"+f"(d[39]),"+f"(d[40]),"+f"(d[41]),"+f"(d[42]),"+f"(d[43]),"+f"(d[44]),"+f"(d[45]),"+f"(d[46]),"+f"(d[47]),"+f"(d[48]),"+f"(d[49]),"+f"(d[50]),"+f"(d[51]),"+f"(d[52]),"+f"(d[53]),"+f"(d[54]),"+f"(d[55]) : "r"(a0), "r"(a1), "r"(a2), "r"(a3), "l"(db), "n"(SC));
}
template<int SC> __device__ __forceinline__ void wg_sp48(float (&d)[24], uint32_t a0, uint32_t a1, uint32_t a2, uint32_t a3, uint64_t db, uint32_t meta) {
  asm volatile("{\n.reg .pred p;\nsetp.ne.b32 p, %30, 0;\nwgmma.mma_async.sp.sync.aligned.m64n48k32.f32.bf16.bf16 {%0,%1,%2,%3,%4,%5,%6,%7,%8,%9,%10,%11,%12,%13,%14,%15,%16,%17,%18,%19,%20,%21,%22,%23}, {%24,%25,%26,%27}, %28, %29, 0, p, 1, 1, 1;\n}\n"
    : "+f"(d[0]),"+f"(d[1]),"+f"(d[2]),"+f"(d[3]),"+f"(d[4]),"+f"(d[5]),"+f"(d[6]),"+f"(d[7]),"+f"(d[8]),"+f"(d[9]),"+f"(d[10]),"+f"(d[11]),"+f"(d[12]),"+f"(d[13]),"+f"(d[14]),"+f"(d[15]),"+f"(d[16]),"+f"(d[17]),"+f"(d[18]),"+f"(d[19]),"+f"(d[20]),"+f"(d[21]),"+f"(d[22]),"+f"(d[23]) : "r"(a0), "r"(a1), "r"(a2), "r"(a3), "l"(db), "r"(meta), "n"(SC));
}
template<int SC> __device__ __forceinline__ void wg_ss192(float (&d)[96], uint64_t da, uint64_t db) {
  asm volatile("{\n.reg .pred p;\nsetp.ne.b32 p, %98, 0;\nwgmma.mma_async.sync.aligned.m64n192k16.f32.bf16.bf16 {%0,%1,%2,%3,%4,%5,%6,%7,%8,%9,%10,%11,%12,%13,%14,%15,%16,%17,%18,%19,%20,%21,%22,%23,%24,%25,%26,%27,%28,%29,%30,%31,%32,%33,%34,%35,%36,%37,%38,%39,%40,%41,%42,%43,%44,%45,%46,%47,%48,%49,%50,%51,%52,%53,%54,%55,%56,%57,%58,%59,%60,%61,%62,%63,%64,%65,%66,%67,%68,%69,%70,%71,%72,%73,%74,%75,%76,%77,%78,%79,%80,%81,%82,%83,%84,%85,%86,%87,%88,%89,%90,%91,%92,%93,%94,%95}, %96, %97, p, 1, 1, 0, 1;\n}\n"
    : "+f"(d[0]),"+f"(d[1]),"+f"(d[2]),"+f"(d[3]),"+f"(d[4]),"+f"(d[5]),"+f"(d[6]),"+f"(d[7]),"+f"(d[8]),"+f"(d[9]),"+f"(d[10]),"+f"(d[11]),"+f"(d[12]),"+f"(d[13]),"+f"(d[14]),"+f"(d[15]),"+f"(d[16]),"+f"(d[17]),"+f"(d[18]),"+f"(d[19]),"+f"(d[20]),"+f"(d[21]),"+f"(d[22]),"+f"(d[23]),"+f"(d[24]),"+f"(d[25]),"+f"(d[26]),"+f"(d[27]),"+f"(d[28]),"+f"(d[29]),"+f"(d[30]),"+f"(d[31]),"+f"(d[32]),"+f"(d[33]),"+f"(d[34]),"+f"(d[35]),"+f"(d[36]),"+f"(d[37]),"+f"(d[38]),"+f"(d[39]),"+f"(d[40]),"+f"(d[41]),"+f"(d[42]),"+f"(d[43]),"+f"(d[44]),"+f"(d[45]),"+f"(d[46]),"+f"(d[47]),"+f"(d[48]),"+f"(d[49]),"+f"(d[50]),"+f"(d[51]),"+f"(d[52]),"+f"(d[53]),"+f"(d[54]),"+f"(d[55]),"+f"(d[56]),"+f"(d[57]),"+f"(d[58]),"+f"(d[59]),"+f"(d[60]),"+f"(d[61]),"+f"(d[62]),"+f"(d[63]),"+f"(d[64]),"+f"(d[65]),"+f"(d[66]),"+f"(d[67]),"+f"(d[68]),"+f"(d[69]),"+f"(d[70]),"+f"(d[71]),"+f"(d[72]),"+f"(d[73]),"+f"(d[74]),"+f"(d[75]),"+f"(d[76]),"+f"(d[77]),"+f"(d[78]),"+f"(d[79]),"+f"(d[80]),"+f"(d[81]),"+f"(d[82]),"+f"(d[83]),"+f"(d[84]),"+f"(d[85]),"+f"(d[86]),"+f"(d[87]),"+f"(d[88]),"+f"(d[89]),"+f"(d[90]),"+f"(d[91]),"+f"(d[92]),"+f"(d[93]),"+f"(d[94]),"+f"(d[95]) : "l"(da), "l"(db), "n"(SC));
}

constexpr uint32_t SBC = 1024;
constexpr int ROWB = 2 * 224 * 384;
constexpr int TB = 12;
constexpr int KS = 832;
constexpr int KSLOT = 22 * KS;
constexpr int SM_X1 = 0;
constexpr int SM_X2 = SM_X1 + 24576;
constexpr int SM_X0 = SM_X2 + 24576;
constexpr int SM_W = SM_X0 + 18432;
constexpr int SM_K = SM_W + 55296;
constexpr int SM_V = SM_K + 2 * KSLOT;
constexpr int SM_Q = SM_V + 22 * 1536;
constexpr int SM_O = SM_Q + 24576;
constexpr int SM_RPB = SM_O + 12288;
constexpr int SM_BAR = SM_RPB + 768;
constexpr int SM_A_TOTAL = SM_BAR + 256;
constexpr int SM_TWO = SM_X1;
constexpr int SM_TST = SM_TWO + 36864;
constexpr int SM_TIN = SM_W;
enum { B_FULL = 0, B_EMPTY = 3, B_TIN = 6, B_TFREE = 8, B_WK = 10, B_WQ, B_WO, B_Q0, B_ODONE, B_KFREE = B_ODONE + 2, B_VFREE, B_COUNT };
enum { N_KRDY = 4, N_QK0, N_QK1, N_VQ0, N_VQ1, N_PVISS };

#define SPL 4
#define RA 152
#define RG 184
__device__ int g_flags[TB * 56];

#define TR(role, it, k)
#define TRDECL
#define TRARG
#define TRPASS
#define TRDUMP
#define TRB(it, k)
#define TR2(blk, k)

struct GemmCtx {
  uint32_t bar;
  uint32_t kC, vC, qC;
  uint32_t kH, vH;
  bool hvalid;
};

template <int STRIDE> __device__ __forceinline__ void dump12(uint32_t a, const uint32_t (&r)[12]) {
#pragma unroll
  for (int j = 0; j < 3; j++) stsm4(a + j * 2 * STRIDE, r[4 * j], r[4 * j + 1], r[4 * j + 2], r[4 * j + 3]);
}
template <int N> __device__ __forceinline__ void pack12(uint32_t (&r)[12], const float (&d)[N], int off) {
#pragma unroll
  for (int j = 0; j < 12; j++) r[j] = pack2(d[off + 2 * j], d[off + 2 * j + 1]);
}
template <int XS, int K0, int K1> __device__ __forceinline__ void issue_core(float (&d)[72]) {
  constexpr uint64_t da = mkdesc(SBC + XS, 16, 1024, 1), db = mkdesc(SBC + SM_W, 6144, 256, 3);
  wg_fence();
  if (K0 == 0) wg_ss144<0>(d, da, db);
#pragma unroll
  for (int k = K0 ? K0 : 1; k < K1; k++) wg_ss144<1>(d, da + (k >> 2) * 512 + (k & 3) * 2, db + k * 32);
  wg_commit();
}
template <int K0, int K1> __device__ __forceinline__ void issue_halo(float (&d)[48]) {
  constexpr uint64_t da = mkdesc(SBC + SM_X0 - 2048, 16, 1024, 1), db = mkdesc(SBC + SM_W, 6144, 256, 3);
  wg_fence();
  if (K0 == 0) wg_ss96<0>(d, da, db);
#pragma unroll
  for (int k = K0 ? K0 : 1; k < K1; k++) wg_ss96<1>(d, da + (k >> 2) * 384 + (k & 3) * 2, db + k * 32);
  wg_commit();
}
template <int ST, int BYTES> __device__ __forceinline__ void release_stage(const GemmCtx& c, bool on) {
  asm volatile("{\n.reg .pred p, q;\n.reg .b32 ra;\nsetp.ne.b32 q, %2, 0;\nelect.sync _|p, 0xffffffff;\nand.pred p, p, q;\n"
               "mapa.shared::cluster.u32 ra, %1, %4;\n"
               "@p mbarrier.arrive.expect_tx.shared::cta.b64 _, [%0], %3;\n@p mbarrier.arrive.shared::cluster.b64 _, [ra];\n}"
               ::"r"(c.bar + (B_FULL + ST) * 8), "r"(c.bar + (B_EMPTY + ST) * 8), "r"((int)on), "n"(BYTES / 4), "n"(ST) : "memory");
}
__device__ __forceinline__ void load_w(const CUtensorMap* m, uint32_t dst, uint32_t bar, int col) {
  asm volatile("cp.async.bulk.tensor.2d.shared::cluster.global.mbarrier::complete_tx::bytes [%0], [%1, {%3,%4}], [%2];"
               ::"r"(dst), "l"(m), "r"(bar), "r"(col), "r"(0) : "memory");
}
__device__ __forceinline__ void publish(uint32_t bar) {
  fence_async();
  __syncwarp();
  mbar_arrive_elect(bar);
}

template <bool FIRST, bool LAST>
__device__ __forceinline__ void gemm_iter(const GemmCtx& c, int b, uint32_t (&pk)[12], uint32_t (&pv)[12], uint32_t (&pq)[12], int head TRARG) {
  const uint32_t bar = c.bar;
  const uint32_t pa = b & 1;
  const bool w = b >= 0;
  const uint32_t ko = pa * KSLOT, vx = pa * 16, qx = pa * 128;
  float H[48], C[72];
  uint32_t hk[12], hv[12], pv2[12];
  TR(2, b, 0);
  if (FIRST) mbar_wait(bar + (B_FULL + 0) * 8, pa);
  if (w) nb_sync(N_QK1, 256);
  TR(2, b, 2);
  issue_halo<0, 8>(H);
  TR(2, b, 3);
  if (!FIRST) {
    if (w) mbar_wait(bar + B_KFREE * 8, pa);
    dump12<128>(c.kC + ko, pk);
  }
  issue_halo<8, 12>(H);
  TR(2, b, 4);
  if (!LAST) {
    mbar_wait(bar + (B_FULL + 2) * 8, pa);
    if (FIRST) mbar_wait(bar + B_WQ * 8, 0);
    TR(2, b, 13);
    issue_core<SM_X2, 0, 8>(C);
    TR(2, b, 5);
    if (!FIRST) { fence_async(); dump12<256>(c.qC ^ (qx ^ 192), pq); }
    wg_wait<1>(); pin(H);
    release_stage<0, 18432>(c, true);
  } else {
    dump12<256>(c.qC ^ (qx ^ 192), pq);
    fence_async();
    nb_arrive(N_VQ0, 288); nb_arrive(N_VQ1, 288);
    wg_wait<0>(); pin(H);
    uint32_t ln; asm volatile("mov.u32 %0, %%laneid;" : "=r"(ln));
    if (ln < 4) mbar_arrive_remote(bar + (B_TFREE + (head >> 1)) * 8, ln);
  }
  pack12(hk, H, 0);
  if (c.hvalid) dump12<128>(c.kH + ko, hk);
  pack12(hv, H, 24);
  if (!LAST) {
    issue_core<SM_X2, 8, 12>(C);
    if (w) { nb_arrive(N_VQ0, 288); nb_arrive(N_VQ1, 288); }
    else if (!FIRST) { __syncwarp(); mbar_arrive_elect(bar + B_Q0 * 8); }
    mbar_wait(bar + (B_FULL + 1) * 8, pa);
    TR(2, b, 6);
    wg_wait<0>(); pin(C);
    TR(2, b, 7);
    pack12(pk, C, 0);
    dump12<128>(c.kC + ko + 64, pk);
    release_stage<2, 24576>(c, b < 11);
    pack12(pv2, C, 24);
    pack12(pq, C, 48);
    TR(2, b, 8);
    issue_core<SM_X1, 0, SPL>(C);
    if (w) nb_sync(N_PVISS, 384);
    issue_core<SM_X1, SPL, 8>(C);
    TR(2, b, 9);
  }
  if (!FIRST) fence_async();
  TR(2, b, 14);
  if (!LAST) issue_core<SM_X1, 8, 12>(C);
  if (!FIRST) nb_arrive(N_KRDY, 256);
  TR(2, b, 1);
  if (!LAST) mbar_wait(bar + (B_FULL + 0) * 8, pa ^ 1);
  if (w) mbar_wait(bar + B_VFREE * 8, pa);
  TR(2, b, 10);
  if (!FIRST) dump12<128>(c.vC ^ vx, pv);
  if (!LAST) dump12<256>(c.qC ^ qx, pq);
  if (c.hvalid) dump12<128>(c.vH ^ vx, hv);
  if (LAST) { fence_async(); nb_arrive(N_VQ0, 288); nb_arrive(N_VQ1, 288); return; }
  dump12<128>((c.vC ^ vx ^ 16) + 768, pv2);
  TR(2, b, 11);
  wg_wait<0>(); pin(C);
  TR(2, b, 12);
  release_stage<1, 24576>(c, b < 11);
  pack12(pk, C, 0);
  pack12(pv, C, 24);
  pack12(pq, C, 48);
}

__device__ __forceinline__ float fold(float a, float b, float t, int useb) {
  float r;
  asm("{\n.reg .pred p;\nsetp.ne.b32 p, %4, 0;\nfma.rn.f32 %0, %1, 0f3E553B95, %3;\n@p fma.rn.f32 %0, %2, 0f3E553B95, %3;\n}"
      : "=&f"(r) : "f"(a), "f"(b), "f"(t), "r"(useb));
  return r;
}
template <int U, int L, bool BORDER>
__device__ __forceinline__ void softmax_tile(const float (&SA)[56], const float (&SB)[56], const float (&T)[14], int b0, int b1,
                                             uint32_t ra0, uint32_t ra1, int qcu, uint32_t (&P)[28], float (&sx)[8]) {
  float lu[14], ll[14];
#pragma unroll
  for (int j = 0; j < 7; j++) {
    float tu0, tu1, tl0, tl1;
    if (BORDER) {
      tu0 = lds_f32(ra0 + (U + j + 3 - qcu) * 4); tu1 = lds_f32(ra1 + (U + j + 3 - qcu) * 4);
      tl0 = lds_f32(ra0 + (L + j + 2 - qcu) * 4); tl1 = lds_f32(ra1 + (L + j + 2 - qcu) * 4);
    } else { tu0 = tl0 = T[2 * j]; tu1 = tl1 = T[2 * j + 1]; }
    lu[2 * j]     = fold(SA[4 * (U + j)],     SB[4 * (U + j)],     tu0, b0);
    ll[2 * j]     = fold(SA[4 * (L + j) + 2], SB[4 * (L + j) + 2], tl0, b0);
    lu[2 * j + 1] = fold(SA[4 * (U + j) + 1], SB[4 * (U + j) + 1], tu1, b1);
    ll[2 * j + 1] = fold(SA[4 * (L + j) + 3], SB[4 * (L + j) + 3], tl1, b1);
  }
  float mu = lu[0], ml = ll[0], mu2 = lu[1], ml2 = ll[1];
#pragma unroll
  for (int j = 1; j < 7; j++) { mu = fmaxf(mu, lu[2 * j]); mu2 = fmaxf(mu2, lu[2 * j + 1]); ml = fmaxf(ml, ll[2 * j]); ml2 = fmaxf(ml2, ll[2 * j + 1]); }
  mu = fmaxf(mu, mu2); ml = fmaxf(ml, ml2);
  { const float a1 = __shfl_xor_sync(0xffffffffu, mu, 1), a2 = __shfl_xor_sync(0xffffffffu, mu, 2), a3 = __shfl_xor_sync(0xffffffffu, mu, 3);
    const float c1 = __shfl_xor_sync(0xffffffffu, ml, 1), c2 = __shfl_xor_sync(0xffffffffu, ml, 2), c3 = __shfl_xor_sync(0xffffffffu, ml, 3);
    mu = fmaxf(fmaxf(mu, a1), fmaxf(a2, a3)); ml = fmaxf(fmaxf(ml, c1), fmaxf(c2, c3)); }
  float su = 0.f, sl = 0.f;
#pragma unroll
  for (int c = 0; c < 14; c++) {
    const int iu = (c >> 1) * 4 + (c & 1) * 2;
    if (c >= U && c < U + 7) {
      float e0 = ex2(lu[2 * (c - U)] - mu), e1 = ex2(lu[2 * (c - U) + 1] - mu);
      su = c == U ? e0 + e1 : (su + e0) + e1; P[iu] = pack2(e0, e1);
    } else P[iu] = 0u;
    if (c >= L && c < L + 7) {
      float e0 = ex2(ll[2 * (c - L)] - ml), e1 = ex2(ll[2 * (c - L) + 1] - ml);
      sl = c == L ? e0 + e1 : (sl + e0) + e1; P[iu + 1] = pack2(e0, e1);
    } else P[iu + 1] = 0u;
  }
  sx[0] = su; sx[4] = sl;
#pragma unroll
  for (int k = 1; k < 4; k++) { sx[k] = __shfl_xor_sync(0xffffffffu, su, k); sx[4 + k] = __shfl_xor_sync(0xffffffffu, sl, k); }
}

struct Maps { CUtensorMap xc, xh, w, os, wo, ot; };

__global__ void __cluster_dims__(4, 1, 1) __launch_bounds__(512, 1)
na_attn_kernel(const __grid_constant__ Maps mp, const __nv_bfloat16* __restrict__ wqkv, const __nv_bfloat16* __restrict__ rpb) {
  extern __shared__ __align__(1024) uint8_t smem_raw[];
  const uint32_t sb = smem_u32(smem_raw);
  if ((sb & 0x3FFFF) != SBC) return;
  const uint32_t bar = sb + SM_BAR;
  TR2(blockIdx.x, 0);
  const int tid = threadIdx.x, lane = tid & 31;
  const int warp = __shfl_sync(0xffffffffu, tid >> 5, 0);
  const int head = blockIdx.x & 3, cl = blockIdx.x >> 2;
  const int par = cl / 7, strip = cl - par * 7, ph = par >> 1, pw = par & 1;

  uint4 wv[3];
  const int wr = tid / 6, wc = tid - wr * 6;
  if (warp < 12) {
#pragma unroll
    for (int i = 0; i < 3; i++) wv[i] = __ldg(reinterpret_cast<const uint4*>(wqkv + (wr + i * 64) * 576 + 384 + head * 48 + wc * 8));
  } else if (elect_one()) {
    if (warp == 12) {
      mbar_init(bar + B_WK * 8, 1);
#pragma unroll
      for (int i = 0; i < 3; i++) load_w(&mp.w, sb + SM_W + i * 6144, bar + B_WK * 8, 192 + head * 48 + i * 16);
      mbar_expect(bar + B_WK * 8, 18432);
    } else if (warp == 13) {
#pragma unroll
      for (int i = 0; i < B_WK; i++) mbar_init(bar + i * 8, i < B_EMPTY ? 4 : (i < B_TIN ? 16 : (i < B_TFREE ? 1 : 8)));
    } else if (warp == 14) {
#pragma unroll
      for (int i = B_WQ; i < B_COUNT; i++) mbar_init(bar + i * 8, i < B_Q0 ? 1 : (i < B_KFREE ? 4 : 8));
    }
    asm volatile("fence.mbarrier_init.release.cluster;" ::: "memory");
  }
  __syncwarp();
  asm volatile("barrier.cluster.arrive.relaxed.aligned;" ::: "memory");

  if (warp >= 12) {
    asm volatile("setmaxnreg.dec.sync.aligned.u32 24;");
    asm volatile("griddepcontrol.launch_dependents;");
    const int cc = ph * 112 + (head ? strip * 16 : (strip == 0 ? 16 : (strip == 6 ? 74 : strip * 16 - 3)));
    const int sd = strip == 0 ? -1 : (strip == 6 ? 1 : 0);
    const int r0 = head == 0 ? -4 : (head == 1 ? 4 : 0);
    asm volatile("barrier.cluster.wait.aligned;" ::: "memory");
    if (warp == 12) {
      const uint32_t fb = bar + (B_FULL + head) * 8, eb = bar + (B_EMPTY + head) * 8;
      const uint32_t dst = sb + (head == 0 ? SM_X0 : (head == 1 ? SM_X1 : SM_X2));
      const int nl = head == 0 ? 15 : (head == 3 ? 1 : 14);
#pragma unroll 1
      for (int n = 0; n < nl; n++) {
        if (n) mbar_wait(eb, (n - 1) & 1);
        if (elect_one()) {
          if (head == 0) {
            asm volatile("cp.async.bulk.tensor.5d.shared::cluster.global.mbarrier::complete_tx::bytes.multicast::cluster [%0], [%1, {%3,%4,%5,%6,%7}], [%2], %8;"
                         ::"r"(dst), "l"(&mp.xh), "r"(fb), "r"(0), "r"(8 * n + r0), "r"(cc), "r"(sd), "r"(pw * 3), "h"((uint16_t)15) : "memory");
            if (n + 1 < nl) asm volatile("cp.async.bulk.prefetch.tensor.5d.L2.global [%0, {%1,%2,%3,%4,%5}];" ::"l"(&mp.xh), "r"(0), "r"(8 * n + 8 + r0), "r"(cc), "r"(sd), "r"(pw * 3) : "memory");
          } else if (head < 3) {
            asm volatile("cp.async.bulk.tensor.4d.shared::cluster.global.mbarrier::complete_tx::bytes.multicast::cluster [%0], [%1, {%3,%4,%5,%6}], [%2], %7;"
                         ::"r"(dst), "l"(&mp.xc), "r"(fb), "r"(0), "r"(8 * n + r0), "r"(cc), "r"(pw * 3), "h"((uint16_t)15) : "memory");
          }
          if (n == 0) {
#pragma unroll
            for (int i = 0; i < 3; i++) load_w(&mp.w, sb + SM_W + (6 + i) * 6144, bar + B_WQ * 8, head * 48 + i * 16);
            mbar_expect(bar + B_WQ * 8, 18432);
            mbar_expect(bar + B_TIN * 8, 24576); mbar_expect(bar + (B_TIN + 1) * 8, 24576);
          }
          if (head && n + 1 < nl) asm volatile("cp.async.bulk.prefetch.tensor.4d.L2.global [%0, {%1,%2,%3,%4}];" ::"l"(&mp.xc), "r"(0), "r"(8 * n + 8 + r0), "r"(cc), "r"(pw * 3) : "memory");
        }
        __syncwarp();
      }
    }
    if (warp >= 14) {
      const int j = warp - 14;
      int* flag = g_flags + cl * 2 + j;
      nb_arrive(N_VQ0 + j, 288);
      TRDECL;
#pragma unroll 1
      for (int b = 0; b < TB; b++) {
        TR(2, b, 0);
        mbar_wait(bar + (B_ODONE + j) * 8, b & 1);
        TR(2, b, 1);
        if (lane == 0) {
          asm volatile("cp.async.bulk.tensor.3d.global.shared::cta.bulk_group [%0, {%2,%3,%4}], [%1];"
                       ::"l"(&mp.os), "r"(sb + SM_O + j * 6144), "r"(pw * 192), "r"(8 * b + 2 * head), "r"(ph * 112 + strip * 16 + 8 * j) : "memory");
          asm volatile("cp.async.bulk.commit_group;\ncp.async.bulk.wait_group.read 0;" ::: "memory");
        }
        __syncwarp();
        nb_arrive(N_VQ0 + j, 288);
        TR(2, b, 2);
        if (lane == 0) {
          asm volatile("cp.async.bulk.wait_group 0;" ::: "memory");
          TR(2, b, 3);
          asm volatile("fence.proxy.async.global;" ::: "memory");
          TR(2, b, 4);
          asm volatile("red.release.gpu.global.add.s32 [%0], 1;" ::"l"(flag + b * 56) : "memory");
          TR(2, b, 5);
        }
        __syncwarp();
      }
      TRDUMP;
#pragma unroll 1
      for (int i = 0; i < 2; i++) {
        mbar_wait(bar + (B_ODONE + j) * 8, i);
        if (i == 0) { nb_arrive(N_VQ0 + j, 288); mbar_wait(bar + (B_TFREE + j) * 8, 0); }
        if (elect_one()) {
#pragma unroll
          for (int d = 0; d < 2; d++)
            asm volatile("{\n.reg .b32 rd, rb;\nmapa.shared::cluster.u32 rd, %0, %3;\nmapa.shared::cluster.u32 rb, %2, %3;\n"
                         "cp.async.bulk.shared::cluster.shared::cta.mbarrier::complete_tx::bytes [rd], [%1], 6144, [rb];\n}"
                         ::"r"(sb + SM_TIN + i * 24576 + head * 6144), "r"(sb + (i ? SM_Q + j * 12288 : SM_O + j * 6144)), "r"(bar + (B_TIN + i) * 8), "r"(2 * j + d) : "memory");
        }
        __syncwarp();
      }
    }
    cluster_sync();
  } else if (warp >= 8) {
    asm volatile("setmaxnreg.inc.sync.aligned.u32 %0;" ::"n"(RG));
    GemmCtx c;
    c.bar = bar;
    const int gw = warp - 8, tk = gw * 16 + (lane & 15), hi = lane >> 4;
    { const int col = tk >> 2, i = tk & 3;
      c.kC = sb + SM_K + (col + 3) * KS + hi * 128 + i * 16;
      c.vC = sb + SM_V + (col + 3) * 1536 + hi * 128 + (2 * i + ((col + 3) & 1)) * 16;
      c.qC = sb + SM_Q + col * 1536 + hi * 256 + (col & 1) * 64 + i * 16; }
    { const int ci = (tk >> 3) - 2, kc = ci < 3 ? ci : ci + 16, i = tk & 7; c.hvalid = gw > 0;
      c.kH = sb + SM_K + kc * KS + hi * 128 + i * 16;
      c.vH = sb + SM_V + kc * 1536 + hi * 128 + (i >> 2) * 768 + (2 * (i & 3) + ((kc ^ (i >> 2)) & 1)) * 16; }
    asm volatile("barrier.cluster.wait.aligned;" ::: "memory");
    if (elect_one()) { mbar_expect(bar + B_FULL * 8, 4608); mbar_expect(bar + (B_FULL + 1) * 8, 6144); mbar_expect(bar + (B_FULL + 2) * 8, 6144); }
    __syncwarp();
#pragma unroll
    for (int i = 0; i < 3; i++) sts128(sb + SM_W + (3 + (wc >> 1)) * 6144 + (wr + i * 64) * 32 + ((wc ^ (wr >> 2)) & 1) * 16, wv[i]);
    fence_async();
    asm volatile("bar.sync 1, 384;" ::: "memory");
    mbar_wait(bar + B_WK * 8, 0);
    uint32_t pk[12], pv[12], pq[12];
    TRDECL;
    gemm_iter<true, false>(c, -2, pk, pv, pq, head TRPASS);
#pragma unroll 1
    for (int b = -1; b < 12; b++) gemm_iter<false, false>(c, b, pk, pv, pq, head TRPASS);
    asm volatile("bar.sync 2, 128;" ::: "memory");
    if (gw == 0 && elect_one()) {
      mbar_expect(bar + B_WO * 8, 36864);
      asm volatile("cp.async.bulk.tensor.3d.shared::cluster.global.mbarrier::complete_tx::bytes [%0], [%1, {%3,%4,%5}], [%2];"
                   ::"r"(sb + SM_TWO), "l"(&mp.wo), "r"(bar + B_WO * 8), "r"(0), "r"(0), "r"((head & 1) * 3) : "memory");
    }
    __syncwarp();
    gemm_iter<false, true>(c, 12, pk, pv, pq, head TRPASS);
    TR(2, 13, 0);
    mbar_wait(bar + B_WO * 8, 0);
    nb_sync(N_QK1, 256);
    TR(2, 13, 1);
    const uint32_t st = sb + SM_TST + gw * 3072;
    const uint32_t sta = st + (lane & 15) * 64 + ((hi ^ ((lane >> 1) & 3)) * 16);
#pragma unroll 1
    for (int i = 0; i < 2; i++) {
      constexpr uint64_t db = mkdesc(SBC + SM_TWO, 12288, 512, 2);
      const uint64_t da = mkdesc(SBC + SM_TIN, 128, 768, 0) + i * (24576 / 16);
      float D[48];
      mbar_wait(bar + (B_TIN + i) * 8, 0);
      TR(2, 13 - i, 2); TR(2, 12 + i, 5);
      wg_fence();
      wg_ss96<0>(D, da, db);
#pragma unroll
      for (int k = 1; k < 12; k++) wg_ss96<1>(D, da + (k / 3) * 384 + (k % 3) * 16, db + k * 64);
      wg_commit();
      if (lane == 0) asm volatile("cp.async.bulk.wait_group.read 0;" ::: "memory");
      __syncwarp();
      wg_wait<0>(); pin(D);
      TR(2, 13 - i, 3); TR(2, 12 + i, 6);
#pragma unroll
      for (int q = 0; q < 6; q++)
        stsm4((sta ^ ((q & 1) * 32)) + (q >> 1) * 1024,
              pack2(D[8 * q], D[8 * q + 1]), pack2(D[8 * q + 2], D[8 * q + 3]), pack2(D[8 * q + 4], D[8 * q + 5]), pack2(D[8 * q + 6], D[8 * q + 7]));
      fence_async();
      __syncwarp();
      if (lane == 0) {
        asm volatile("cp.async.bulk.tensor.4d.global.shared::cta.bulk_group [%0, {%2,%3,%4,%5}], [%1];"
                     ::"l"(&mp.ot), "r"(st), "r"(0), "r"(8 * (TB + i)), "r"(ph * 112 + strip * 16 + 8 * (head >> 1) + 2 * gw), "r"(pw * 6 + (head & 1) * 3) : "memory");
        asm volatile("cp.async.bulk.commit_group;" ::: "memory");
      }
      TR(2, 13 - i, 4); TR(2, 12 + i, 7);
    }
    asm volatile("barrier.cluster.arrive.relaxed.aligned;" ::: "memory");
    if (lane == 0) asm volatile("cp.async.bulk.wait_group 0;" ::: "memory");
    __syncwarp();
    TR(2, 13, 8);
    TRDUMP;
    asm volatile("barrier.cluster.wait.aligned;" ::: "memory");
  } else {
    asm volatile("setmaxnreg.inc.sync.aligned.u32 %0;" ::"n"(RA));
    float rv = -INFINITY;
    if (tid < 169) rv = __bfloat162float(rpb[head * 169 + tid]) * 1.4426950408889634f;
    if (tid < 192) {
      const int kc = (wr & 15) + 3;
      sts128(tid < 96 ? sb + SM_K + kc * KS + wc * 128 + 48 : sb + SM_V + kc * 1536 + wc * 128 + (6 + (kc & 1)) * 16, make_uint4(0, 0, 0, 0));
    }
#pragma unroll
    for (int i = 0; i < 3; i++) sts128(sb + SM_W + (3 + (wc >> 1)) * 6144 + (wr + i * 64) * 32 + ((wc ^ (wr >> 2)) & 1) * 16, wv[i]);
    fence_async();
    asm volatile("bar.arrive 1, 384;" ::: "memory");
    if (tid < 182) asm volatile("st.shared.f32 [%0], %1;" ::"r"(sb + SM_RPB + tid * 4), "f"(rv) : "memory");
    const int j = warp >> 2, w = warp & 3;
    int variant = w;
    if (strip == 0 && j == 0 && w < 2) variant = 4;
    if (strip == 6 && j == 1 && w >= 2) variant = 5;
    const uint32_t qa = sb + SM_Q + (8 * j + 2 * w + ((lane >> 3) & 1)) * 1536 + (lane >> 4) * 256 + (((lane & 7) * 16) ^ (((lane >> 3) & 1) * 64));
    uint32_t oa = sb + SM_O + j * 6144 + (2 * w + ((lane >> 3) & 1)) * 768 + (lane >> 4) * 128 + (lane & 7) * 16;
    const uint64_t dK = mkdesc(SBC + SM_K, 128, KS, 0) + j * (8 * KS / 16);
    const uint64_t dV = mkdesc(SBC + SM_V, 768, 128, 0) + j * (8 * 1536 / 16);
    asm volatile("barrier.cluster.wait.aligned;" ::: "memory");
    asm volatile("bar.sync 3, 256;" ::: "memory");
    float T[14];
    TRDECL;
    int b0 = 0, b1 = 0;
    uint32_t ra0 = 0, ra1 = 0, meta = 0;
    uint32_t q[12];
    mbar_wait(bar + B_Q0 * 8, 0);
#pragma unroll
    for (int k = 0; k < 3; k++) ldsm4(qa + k * 512, q[4 * k], q[4 * k + 1], q[4 * k + 2], q[4 * k + 3]);
#pragma unroll 1
    for (int b = 0; b < 14; b++) {
      const uint32_t pa = b & 1;
      if (b <= 1 || b == 13) {
        uint32_t ln; asm volatile("mov.u32 %0, %%laneid;" : "=r"(ln));
        const int g = ln >> 2, t = ln & 3;
        const int sw = b == 0 ? max(g + 1, 4) : (b == 13 ? min(g + 1, 5) : g + 1);
        const int i0 = 2 * t, i1 = 2 * t + 1;
        b0 = i0 <= sw - 2; b1 = i1 <= sw - 2;
        const int m = sw - 1;
        ra0 = sb + SM_RPB + (i0 == m ? 13 : i0 + (b0 ? 8 : 0) - g + 2) * 52;
        ra1 = sb + SM_RPB + (i1 == m ? 13 : i1 + (b1 ? 8 : 0) - g + 2) * 52;
#pragma unroll
        for (int jj = 0; jj < 7; jj++) { T[2 * jj] = lds_f32(ra0 + (jj + 3) * 4); T[2 * jj + 1] = lds_f32(ra1 + (jj + 3) * 4); }
        uint32_t m16 = 0x8888u;
#pragma unroll
        for (int i = 0; i < 8; i++) m16 |= (uint32_t)(((i <= sw - 2) ^ (i >> 2) ^ t ^ b) & 1) << (2 * i);
        meta = m16 | (m16 << 16);
        if (b == 13) oa += SM_Q - SM_O + j * 6144;
      } else meta ^= 0x55555555u;
      float SA[56], SB[56];
      const uint64_t dA = dK + pa * (KSLOT >> 4), dB = dK + (pa ^ 1) * (KSLOT >> 4);
      TR(0, b, 0);
      nb_sync(N_KRDY + j, 256);
      TR(0, b, 1);
      TR(0, b - 1, 9);
      wg_fence();
      wg_rs112<0>(SA, q[0], q[1], q[2], q[3], dA);
      wg_rs112<0>(SB, q[0], q[1], q[2], q[3], dB);
      wg_rs112<1>(SA, q[4], q[5], q[6], q[7], dA + 16);
      wg_rs112<1>(SB, q[4], q[5], q[6], q[7], dB + 16);
      wg_rs112<1>(SA, q[8], q[9], q[10], q[11], dA + 32);
      wg_rs112<1>(SB, q[8], q[9], q[10], q[11], dB + 32);
      wg_commit();
      nb_arrive(N_QK0 + j, 256);
      TR(0, b, 2);
      wg_wait<0>(); pin(SA); pin(SB);
      mbar_arrive_elect(bar + B_KFREE * 8);
      TR(0, b, 3);
      TR(0, b - 1, 10);
      uint32_t P[28];
      float sx[8];
      switch (variant) {
        case 0: softmax_tile<0, 1, false>(SA, SB, T, b0, b1, ra0, ra1, 0, P, sx); break;
        case 1: softmax_tile<2, 3, false>(SA, SB, T, b0, b1, ra0, ra1, 0, P, sx); break;
        case 2: softmax_tile<4, 5, false>(SA, SB, T, b0, b1, ra0, ra1, 0, P, sx); break;
        case 3: softmax_tile<6, 7, false>(SA, SB, T, b0, b1, ra0, ra1, 0, P, sx); break;
        case 4: softmax_tile<3, 3, true>(SA, SB, T, b0, b1, ra0, ra1, 2 * w, P, sx); break;
        default: softmax_tile<4, 4, true>(SA, SB, T, b0, b1, ra0, ra1, 2 * w, P, sx); break;
      }
      float O[24];
      TR(0, b, 4);
      nb_sync(N_VQ0 + j, 288);
      TR(0, b, 5);
#pragma unroll
      for (int k = 0; k < 3; k++) ldsm4(qa + (pa ^ 1) * 128 + k * 512, q[4 * k], q[4 * k + 1], q[4 * k + 2], q[4 * k + 3]);
      wg_fence();
      wg_sp48<0>(O, P[0], P[1], P[2], P[3], dV, meta);
#pragma unroll
      for (int s = 1; s < 7; s++) wg_sp48<1>(O, P[4 * s], P[4 * s + 1], P[4 * s + 2], P[4 * s + 3], dV + s * 192, meta);
      wg_commit();
      if (b < 12) nb_arrive(N_PVISS, 384);
      TR(0, b, 6);
      wg_wait<0>(); pin(O);
      mbar_arrive_elect(bar + B_VFREE * 8);
      TR(0, b, 7);
      float ru, rl;
      asm("rcp.approx.ftz.f32 %0, %1;" : "=f"(ru) : "f"(((fmaf(O[0], 0.f, sx[0]) + sx[1]) + sx[2]) + sx[3]));
      asm("rcp.approx.ftz.f32 %0, %1;" : "=f"(rl) : "f"(((fmaf(O[2], 0.f, sx[4]) + sx[5]) + sx[6]) + sx[7]));
#pragma unroll
      for (int i = 0; i < 3; i++)
        stsm4(oa + i * 256, pack2(O[8 * i] * ru, O[8 * i + 1] * ru), pack2(O[8 * i + 2] * rl, O[8 * i + 3] * rl),
              pack2(O[8 * i + 4] * ru, O[8 * i + 5] * ru), pack2(O[8 * i + 6] * rl, O[8 * i + 7] * rl));
      publish(bar + (B_ODONE + j) * 8);
      TR(0, b, 8);
    }
    TRDUMP;
    cluster_sync();
    TR2(blockIdx.x, 2);
  }
}

constexpr int NSTB = 6;
constexpr int NTB = TB * 56;
constexpr int SM_B_IN = 0;
constexpr int SM_B_W = SM_B_IN + NSTB * 24576;
constexpr int SM_B_BAR = SM_B_W + 73728;
constexpr int SM_B_TOTAL = SM_B_BAR + 128;
struct MapsB { CUtensorMap oi, oo, wo; };

__global__ void __launch_bounds__(480, 1)
na_proj_kernel(const __grid_constant__ MapsB mp) {
  extern __shared__ __align__(1024) uint8_t smem_raw[];
  const uint32_t sb = smem_u32(smem_raw);
  if ((sb & 0x3FFFF) != SBC) return;
  const uint32_t bar = sb + SM_B_BAR;
  const int tid = threadIdx.x, lane = tid & 31;
  const int warp = __shfl_sync(0xffffffffu, tid >> 5, 0);
  TR2(132 + blockIdx.x, 0);
  TRB(47, 0);
  if (warp == 12 && elect_one()) {
#pragma unroll
    for (int i = 0; i <= 2 * NSTB; i++) mbar_init(bar + i * 8, i < NSTB || i == 2 * NSTB ? 1 : 4);
    mbar_expect(bar + 2 * NSTB * 8, 73728);
#pragma unroll
    for (int i = 0; i < 2; i++)
      asm volatile("cp.async.bulk.tensor.3d.shared::cluster.global.mbarrier::complete_tx::bytes [%0], [%1, {%3,%4,%5}], [%2];"
                   ::"r"(sb + SM_B_W + i * 36864), "l"(&mp.wo), "r"(bar + 2 * NSTB * 8), "r"(0), "r"(0), "r"(i * 3) : "memory");
  }
  __syncthreads();
  const int step = gridDim.x;
  if (warp >= 12) {
    const int wg = warp - 12;
    int use = 0;
#pragma unroll 1
    for (int n = blockIdx.x + wg * step; n < NTB; n += 3 * step, use++) {
      const int b = n / 56, rem = n - b * 56, par = rem / 14, sg = wg + 3 * (use & 1);
      int v; uint32_t spin = 0;
      do { asm volatile("ld.acquire.gpu.global.s32 %0, [%1];" : "=r"(v) : "l"(g_flags + n) : "memory"); } while (v < 4 && ++spin < SPIN_LIMIT);
      asm volatile("fence.proxy.async.global;" ::: "memory");
      if (use >= 2) mbar_wait(bar + (NSTB + sg) * 8, ((use >> 1) - 1) & 1);
      if (elect_one()) {
        mbar_expect(bar + sg * 8, 24576);
        asm volatile("cp.async.bulk.tensor.3d.shared::cluster.global.mbarrier::complete_tx::bytes [%0], [%1, {%3,%4,%5}], [%2];"
                     ::"r"(sb + SM_B_IN + sg * 24576), "l"(&mp.oi), "r"(bar + sg * 8), "r"((par & 1) * 192), "r"(8 * b), "r"((par >> 1) * 112 + (rem - par * 14) * 8) : "memory");
        g_flags[n] = 0;
      }
      __syncwarp();
    }
  } else {
    const int wg = warp >> 2, w = warp & 3;
    constexpr uint64_t db = mkdesc(SBC + SM_B_W, 12288, 512, 2);
    const uint32_t sta0 = sb + SM_B_IN + w * 6144 + (lane & 15) * 128 + (((lane >> 4) ^ (lane & 7)) * 16);
    mbar_wait(bar + 2 * NSTB * 8, 0);
    TRB(47, 1);
    int use = 0;
#pragma unroll 1
    for (int n = blockIdx.x + wg * step; n < NTB; n += 3 * step, use++) {
      const int b = n / 56, rem = n - b * 56, par = rem / 14, sg = wg + 3 * (use & 1);
      const uint64_t da = mkdesc(SBC + SM_B_IN, 128, 3072, 0) + sg * (24576 / 16);
      float D[96];
      mbar_wait(bar + sg * 8, (use >> 1) & 1);
      if (use | wg) nb_sync(4 + wg, 256);
      TRB(use * 3 + wg, 3);
      wg_fence();
      wg_ss192<0>(D, da, db);
#pragma unroll
      for (int k = 1; k < 12; k++) wg_ss192<1>(D, da + k * 16, db + k * 64);
      wg_commit();
      if (n + step < NTB) nb_arrive(wg == 2 ? 4 : 5 + wg, 256);
      TRB(use * 3 + wg, 4);
      if (use && lane == 0) {
        asm volatile("cp.async.bulk.wait_group.read 0;" ::: "memory");
        mbar_arrive(bar + (NSTB + wg + 3 * (~use & 1)) * 8);
      }
      __syncwarp();
      wg_wait<0>(); pin(D);
      nb_sync(1 + wg, 128);
      TRB(use * 3 + wg, 5);
      const uint32_t sta = sta0 + sg * 24576;
#pragma unroll
      for (int q = 0; q < 12; q++)
        stsm4((sta ^ ((q & 3) * 32)) + (q >> 2) * 2048,
              pack2(D[8 * q], D[8 * q + 1]), pack2(D[8 * q + 2], D[8 * q + 3]), pack2(D[8 * q + 4], D[8 * q + 5]), pack2(D[8 * q + 6], D[8 * q + 7]));
      fence_async();
      __syncwarp();
      if (lane == 0) {
        asm volatile("cp.async.bulk.tensor.4d.global.shared::cta.bulk_group [%0, {%2,%3,%4,%5}], [%1];"
                     ::"l"(&mp.oo), "r"(sb + SM_B_IN + sg * 24576 + w * 6144), "r"(0), "r"(8 * b), "r"((par >> 1) * 112 + (rem - par * 14) * 8 + 2 * w), "r"((par & 1) * 3) : "memory");
        asm volatile("cp.async.bulk.commit_group;" ::: "memory");
      }
      __syncwarp();
      TRB(use * 3 + wg, 6);
    }
    if (lane == 0) asm volatile("cp.async.bulk.wait_group 0;" ::: "memory");
    TR2(132 + blockIdx.x, 2);
  }
}

typedef CUresult (*EncodeFn)(CUtensorMap*, CUtensorMapDataType, cuuint32_t, void*, const cuuint64_t*, const cuuint64_t*, const cuuint32_t*,
                             const cuuint32_t*, CUtensorMapInterleave, CUtensorMapSwizzle, CUtensorMapL2promotion, CUtensorMapFloatOOBfill);
static EncodeFn g_enc = nullptr;
static void make_map(CUtensorMap* m, const void* p, int rank, const cuuint64_t* dim, const cuuint64_t* str, const cuuint32_t* box, CUtensorMapSwizzle sw) {
  const cuuint32_t ones[5] = {1, 1, 1, 1, 1};
  g_enc(m, CU_TENSOR_MAP_DATA_TYPE_BFLOAT16, rank, (void*)p, dim, str, box, ones, CU_TENSOR_MAP_INTERLEAVE_NONE, sw,
        CU_TENSOR_MAP_L2_PROMOTION_L2_128B, CU_TENSOR_MAP_FLOAT_OOB_FILL_NONE);
}

extern "C" void kernel_launch(void* const* d_in, const int* in_sizes, int n_in, void* d_out, int out_size) {
  const __nv_bfloat16* x = (const __nv_bfloat16*)d_in[0];
  const __nv_bfloat16* wqkv = (const __nv_bfloat16*)d_in[1];
  const __nv_bfloat16* wo = (const __nv_bfloat16*)d_in[2];
  const __nv_bfloat16* rpb = (const __nv_bfloat16*)d_in[3];

  if (!g_enc) {
    void* fn = nullptr; cudaDriverEntryPointQueryResult qr;
    cudaGetDriverEntryPoint("cuTensorMapEncodeTiled", &fn, cudaEnableDefault, &qr);
    g_enc = (EncodeFn)fn;
    cudaFuncSetAttribute(na_attn_kernel, cudaFuncAttributeMaxDynamicSharedMemorySize, SM_A_TOTAL);
    cudaFuncSetAttribute(na_proj_kernel, cudaFuncAttributeMaxDynamicSharedMemorySize, SM_B_TOTAL);
  }
  Maps ma; MapsB mb;
  { cuuint64_t dim[4] = {64, 112, 224, 6}, str[3] = {(cuuint64_t)ROWB, 768, 128};
    cuuint32_t box[4] = {64, 4, 16, 3}, boxo[4] = {64, 8, 2, 3};
    make_map(&ma.xc, x, 4, dim, str, box, CU_TENSOR_MAP_SWIZZLE_128B);
    make_map(&mb.oo, d_out, 4, dim, str, boxo, CU_TENSOR_MAP_SWIZZLE_128B); }
  { cuuint64_t dim[5] = {64, 112, 224, 2, 6}, str[4] = {(cuuint64_t)ROWB, 768, 19 * 768, 128};
    cuuint32_t box[5] = {64, 8, 3, 2, 3};
    make_map(&ma.xh, x, 5, dim, str, box, CU_TENSOR_MAP_SWIZZLE_128B); }
  { cuuint64_t dim[3] = {384, 112, 224}, str[2] = {(cuuint64_t)ROWB, 768};
    cuuint32_t box[3] = {192, 8, 8}, boxs[3] = {192, 2, 8};
    make_map(&mb.oi, d_out, 3, dim, str, box, CU_TENSOR_MAP_SWIZZLE_NONE);
    make_map(&ma.os, d_out, 3, dim, str, boxs, CU_TENSOR_MAP_SWIZZLE_NONE); }
  { cuuint64_t dim[4] = {32, 112, 224, 12}, str[3] = {(cuuint64_t)ROWB, 768, 64};
    cuuint32_t box[4] = {32, 8, 2, 3};
    make_map(&ma.ot, d_out, 4, dim, str, box, CU_TENSOR_MAP_SWIZZLE_64B); }
  { cuuint64_t dim[2] = {576, 192}, str[1] = {1152};
    cuuint32_t box[2] = {16, 192};
    make_map(&ma.w, wqkv, 2, dim, str, box, CU_TENSOR_MAP_SWIZZLE_32B); }
  { cuuint64_t dim[3] = {32, 192, 6}, str[2] = {384, 64};
    cuuint32_t box[3] = {32, 192, 3};
    make_map(&ma.wo, wo, 3, dim, str, box, CU_TENSOR_MAP_SWIZZLE_64B);
    mb.wo = ma.wo; }
  na_attn_kernel<<<112, 512, SM_A_TOTAL>>>(ma, wqkv, rpb);
  cudaLaunchConfig_t cfg = {};
  cfg.gridDim = dim3(20); cfg.blockDim = dim3(480); cfg.dynamicSmemBytes = SM_B_TOTAL; cfg.stream = cudaStreamPerThread;
  cudaLaunchAttribute at[1];
  at[0].id = cudaLaunchAttributeProgrammaticStreamSerialization; at[0].val.programmaticStreamSerializationAllowed = 1;
  cfg.attrs = at; cfg.numAttrs = 1;
  cudaLaunchKernelEx(&cfg, na_proj_kernel, mb);
}
```

```cpp
#include <cuda_runtime.h>
#include <cuda_bf16.h>
#include <cuda.h>
#include <stdint.h>

#define SPIN_LIMIT (1u << 18)

__device__ __forceinline__ uint32_t smem_u32(const void* p) { return (uint32_t)__cvta_generic_to_shared(p); }
__device__ __forceinline__ void wg_fence() { asm volatile("wgmma.fence.sync.aligned;" ::: "memory"); }
__device__ __forceinline__ void wg_commit() { asm volatile("wgmma.commit_group.sync.aligned;" ::: "memory"); }
template <int N> __device__ __forceinline__ void wg_wait() { asm volatile("wgmma.wait_group.sync.aligned %0;" ::"n"(N) : "memory"); }
template <int N> __device__ __forceinline__ void pin(float (&d)[N]) {
#pragma unroll
  for (int i = 0; i < N; i++) asm volatile("" : "+f"(d[i])::"memory");
}
__host__ __device__ constexpr uint64_t mkdesc(uint32_t addr, uint32_t lbo, uint32_t sbo, uint32_t sw) {
  return (uint64_t)((addr & 0x3FFFF) >> 4) | ((uint64_t)(lbo >> 4) << 16) | ((uint64_t)(sbo >> 4) << 32) | ((uint64_t)sw << 62);
}
__device__ __forceinline__ void mbar_init(uint32_t bar, uint32_t cnt) { asm volatile("mbarrier.init.shared::cta.b64 [%0], %1;" ::"r"(bar), "r"(cnt) : "memory"); }
__device__ __forceinline__ void mbar_arrive(uint32_t bar) { asm volatile("mbarrier.arrive.shared::cta.b64 _, [%0];" ::"r"(bar) : "memory"); }
__device__ __forceinline__ bool elect_one() {
  uint32_t r; asm volatile("{\n.reg .pred p;\nelect.sync _|p, 0xffffffff;\nselp.u32 %0, 1, 0, p;\n}" : "=r"(r)); return r;
}
__device__ __forceinline__ void mbar_arrive_elect(uint32_t bar) {
  asm volatile("{\n.reg .pred p;\nelect.sync _|p, 0xffffffff;\n@p mbarrier.arrive.shared::cta.b64 _, [%0];\n}" ::"r"(bar) : "memory");
}
__device__ __forceinline__ void mbar_expect(uint32_t bar, uint32_t bytes) { asm volatile("mbarrier.arrive.expect_tx.shared::cta.b64 _, [%0], %1;" ::"r"(bar), "r"(bytes) : "memory"); }
__device__ __forceinline__ void mbar_arrive_remote(uint32_t bar, uint32_t cta) {
  asm volatile("{\n.reg .b32 ra;\nmapa.shared::cluster.u32 ra, %0, %1;\nmbarrier.arrive.shared::cluster.b64 _, [ra];\n}" ::"r"(bar), "r"(cta) : "memory");
}
__device__ __forceinline__ void mbar_wait(uint32_t bar, uint32_t parity) {
  asm volatile("{\n.reg .pred p;\n.reg .b32 n;\nmov.b32 n, 0;\nWL:\nmbarrier.try_wait.parity.shared::cta.b64 p, [%0], %1;\n@p bra WD;\n"
               "add.u32 n, n, 1;\nsetp.lt.u32 p, n, 65536;\n@p bra WL;\nWD:\n}" ::"r"(bar), "r"(parity) : "memory");
}
__device__ __forceinline__ void nb_sync(int id, int n) { asm volatile("bar.sync %0, %1;" ::"r"(id), "r"(n) : "memory"); }
__device__ __forceinline__ void nb_arrive(int id, int n) { asm volatile("bar.arrive %0, %1;" ::"r"(id), "r"(n) : "memory"); }
__device__ __forceinline__ void fence_async() { asm volatile("fence.proxy.async.shared::cta;" ::: "memory"); }
__device__ __forceinline__ void cluster_sync() {
  asm volatile("barrier.cluster.arrive.relaxed.aligned;\nbarrier.cluster.wait.aligned;" ::: "memory");
}
__device__ __forceinline__ uint32_t pack2(float lo, float hi) {
  uint32_t r; asm("cvt.rn.bf16x2.f32 %0, %1, %2;" : "=r"(r) : "f"(hi), "f"(lo)); return r;
}
__device__ __forceinline__ void stsm4(uint32_t a, uint32_t r0, uint32_t r1, uint32_t r2, uint32_t r3) {
  asm volatile("stmatrix.sync.aligned.m8n8.x4.shared.b16 [%0], {%1,%2,%3,%4};" ::"r"(a), "r"(r0), "r"(r1), "r"(r2), "r"(r3) : "memory");
}
__device__ __forceinline__ void ldsm4(uint32_t a, uint32_t& r0, uint32_t& r1, uint32_t& r2, uint32_t& r3) {
  asm volatile("ldmatrix.sync.aligned.m8n8.x4.shared.b16 {%0,%1,%2,%3}, [%4];" : "=r"(r0), "=r"(r1), "=r"(r2), "=r"(r3) : "r"(a) : "memory");
}
__device__ __forceinline__ void sts128(uint32_t a, uint4 v) {
  asm volatile("st.shared.v4.b32 [%0], {%1,%2,%3,%4};" ::"r"(a), "r"(v.x), "r"(v.y), "r"(v.z), "r"(v.w) : "memory");
}
__device__ __forceinline__ float lds_f32(uint32_t a) { float v; asm volatile("ld.shared.f32 %0, [%1];" : "=f"(v) : "r"(a)); return v; }
__device__ __forceinline__ float ex2(float x) { float y; asm("ex2.approx.ftz.f32 %0, %1;" : "=f"(y) : "f"(x)); return y; }

template<int SC> __device__ __forceinline__ void wg_ss144(float (&d)[72], uint64_t da, uint64_t db) {
  asm volatile("{\n.reg .pred p;\nsetp.ne.b32 p, %74, 0;\nwgmma.mma_async.sync.aligned.m64n144k16.f32.bf16.bf16 {%0,%1,%2,%3,%4,%5,%6,%7,%8,%9,%10,%11,%12,%13,%14,%15,%16,%17,%18,%19,%20,%21,%22,%23,%24,%25,%26,%27,%28,%29,%30,%31,%32,%33,%34,%35,%36,%37,%38,%39,%40,%41,%42,%43,%44,%45,%46,%47,%48,%49,%50,%51,%52,%53,%54,%55,%56,%57,%58,%59,%60,%61,%62,%63,%64,%65,%66,%67,%68,%69,%70,%71}, %72, %73, p, 1, 1, 0, 1;\n}\n"
    : "+f"(d[0]),"+f"(d[1]),"+f"(d[2]),"+f"(d[3]),"+f"(d[4]),"+f"(d[5]),"+f"(d[6]),"+f"(d[7]),"+f"(d[8]),"+f"(d[9]),"+f"(d[10]),"+f"(d[11]),"+f"(d[12]),"+f"(d[13]),"+f"(d[14]),"+f"(d[15]),"+f"(d[16]),"+f"(d[17]),"+f"(d[18]),"+f"(d[19]),"+f"(d[20]),"+f"(d[21]),"+f"(d[22]),"+f"(d[23]),"+f"(d[24]),"+f"(d[25]),"+f"(d[26]),"+f"(d[27]),"+f"(d[28]),"+f"(d[29]),"+f"(d[30]),"+f"(d[31]),"+f"(d[32]),"+f"(d[33]),"+f"(d[34]),"+f"(d[35]),"+f"(d[36]),"+f"(d[37]),"+f"(d[38]),"+f"(d[39]),"+f"(d[40]),"+f"(d[41]),"+f"(d[42]),"+f"(d[43]),"+f"(d[44]),"+f"(d[45]),"+f"(d[46]),"+f"(d[47]),"+f"(d[48]),"+f"(d[49]),"+f"(d[50]),"+f"(d[51]),"+f"(d[52]),"+f"(d[53]),"+f"(d[54]),"+f"(d[55]),"+f"(d[56]),"+f"(d[57]),"+f"(d[58]),"+f"(d[59]),"+f"(d[60]),"+f"(d[61]),"+f"(d[62]),"+f"(d[63]),"+f"(d[64]),"+f"(d[65]),"+f"(d[66]),"+f"(d[67]),"+f"(d[68]),"+f"(d[69]),"+f"(d[70]),"+f"(d[71]) : "l"(da), "l"(db), "n"(SC));
}
template<int SC> __device__ __forceinline__ void wg_ss96(float (&d)[48], uint64_t da, uint64_t db) {
  asm volatile("{\n.reg .pred p;\nsetp.ne.b32 p, %50, 0;\nwgmma.mma_async.sync.aligned.m64n96k16.f32.bf16.bf16 {%0,%1,%2,%3,%4,%5,%6,%7,%8,%9,%10,%11,%12,%13,%14,%15,%16,%17,%18,%19,%20,%21,%22,%23,%24,%25,%26,%27,%28,%29,%30,%31,%32,%33,%34,%35,%36,%37,%38,%39,%40,%41,%42,%43,%44,%45,%46,%47}, %48, %49, p, 1, 1, 0, 1;\n}\n"
    : "+f"(d[0]),"+f"(d[1]),"+f"(d[2]),"+f"(d[3]),"+f"(d[4]),"+f"(d[5]),"+f"(d[6]),"+f"(d[7]),"+f"(d[8]),"+f"(d[9]),"+f"(d[10]),"+f"(d[11]),"+f"(d[12]),"+f"(d[13]),"+f"(d[14]),"+f"(d[15]),"+f"(d[16]),"+f"(d[17]),"+f"(d[18]),"+f"(d[19]),"+f"(d[20]),"+f"(d[21]),"+f"(d[22]),"+f"(d[23]),"+f"(d[24]),"+f"(d[25]),"+f"(d[26]),"+f"(d[27]),"+f"(d[28]),"+f"(d[29]),"+f"(d[30]),"+f"(d[31]),"+f"(d[32]),"+f"(d[33]),"+f"(d[34]),"+f"(d[35]),"+f"(d[36]),"+f"(d[37]),"+f"(d[38]),"+f"(d[39]),"+f"(d[40]),"+f"(d[41]),"+f"(d[42]),"+f"(d[43]),"+f"(d[44]),"+f"(d[45]),"+f"(d[46]),"+f"(d[47]) : "l"(da), "l"(db), "n"(SC));
}
template<int SC> __device__ __forceinline__ void wg_rs112(float (&d)[56], uint32_t a0, uint32_t a1, uint32_t a2, uint32_t a3, uint64_t db) {
  asm volatile("{\n.reg .pred p;\nsetp.ne.b32 p, %61, 0;\nwgmma.mma_async.sync.aligned.m64n112k16.f32.bf16.bf16 {%0,%1,%2,%3,%4,%5,%6,%7,%8,%9,%10,%11,%12,%13,%14,%15,%16,%17,%18,%19,%20,%21,%22,%23,%24,%25,%26,%27,%28,%29,%30,%31,%32,%33,%34,%35,%36,%37,%38,%39,%40,%41,%42,%43,%44,%45,%46,%47,%48,%49,%50,%51,%52,%53,%54,%55}, {%56,%57,%58,%59}, %60, p, 1, 1, 0;\n}\n"
    : "+f"(d[0]),"+f"(d[1]),"+f"(d[2]),"+f"(d[3]),"+f"(d[4]),"+f"(d[5]),"+f"(d[6]),"+f"(d[7]),"+f"(d[8]),"+f"(d[9]),"+f"(d[10]),"+f"(d[11]),"+f"(d[12]),"+f"(d[13]),"+f"(d[14]),"+f"(d[15]),"+f"(d[16]),"+f"(d[17]),"+f"(d[18]),"+f"(d[19]),"+f"(d[20]),"+f"(d[21]),"+f"(d[22]),"+f"(d[23]),"+f"(d[24]),"+f"(d[25]),"+f"(d[26]),"+f"(d[27]),"+f"(d[28]),"+f"(d[29]),"+f"(d[30]),"+f"(d[31]),"+f"(d[32]),"+f"(d[33]),"+f"(d[34]),"+f"(d[35]),"+f"(d[36]),"+f"(d[37]),"+f"(d[38]),"+f"(d[39]),"+f"(d[40]),"+f"(d[41]),"+f"(d[42]),"+f"(d[43]),"+f"(d[44]),"+f"(d[45]),"+f"(d[46]),"+f"(d[47]),"+f"(d[48]),"+f"(d[49]),"+f"(d[50]),"+f"(d[51]),"+f"(d[52]),"+f"(d[53]),"+f"(d[54]),"+f"(d[55]) : "r"(a0), "r"(a1), "r"(a2), "r"(a3), "l"(db), "n"(SC));
}
template<int SC> __device__ __forceinline__ void wg_sp48(float (&d)[24], uint32_t a0, uint32_t a1, uint32_t a2, uint32_t a3, uint64_t db, uint32_t meta) {
  asm volatile("{\n.reg .pred p;\nsetp.ne.b32 p, %30, 0;\nwgmma.mma_async.sp.sync.aligned.m64n48k32.f32.bf16.bf16 {%0,%1,%2,%3,%4,%5,%6,%7,%8,%9,%10,%11,%12,%13,%14,%15,%16,%17,%18,%19,%20,%21,%22,%23}, {%24,%25,%26,%27}, %28, %29, 0, p, 1, 1, 1;\n}\n"
    : "+f"(d[0]),"+f"(d[1]),"+f"(d[2]),"+f"(d[3]),"+f"(d[4]),"+f"(d[5]),"+f"(d[6]),"+f"(d[7]),"+f"(d[8]),"+f"(d[9]),"+f"(d[10]),"+f"(d[11]),"+f"(d[12]),"+f"(d[13]),"+f"(d[14]),"+f"(d[15]),"+f"(d[16]),"+f"(d[17]),"+f"(d[18]),"+f"(d[19]),"+f"(d[20]),"+f"(d[21]),"+f"(d[22]),"+f"(d[23]) : "r"(a0), "r"(a1), "r"(a2), "r"(a3), "l"(db), "r"(meta), "n"(SC));
}
template<int SC> __device__ __forceinline__ void wg_ss192(float (&d)[96], uint64_t da, uint64_t db) {
  asm volatile("{\n.reg .pred p;\nsetp.ne.b32 p, %98, 0;\nwgmma.mma_async.sync.aligned.m64n192k16.f32.bf16.bf16 {%0,%1,%2,%3,%4,%5,%6,%7,%8,%9,%10,%11,%12,%13,%14,%15,%16,%17,%18,%19,%20,%21,%22,%23,%24,%25,%26,%27,%28,%29,%30,%31,%32,%33,%34,%35,%36,%37,%38,%39,%40,%41,%42,%43,%44,%45,%46,%47,%48,%49,%50,%51,%52,%53,%54,%55,%56,%57,%58,%59,%60,%61,%62,%63,%64,%65,%66,%67,%68,%69,%70,%71,%72,%73,%74,%75,%76,%77,%78,%79,%80,%81,%82,%83,%84,%85,%86,%87,%88,%89,%90,%91,%92,%93,%94,%95}, %96, %97, p, 1, 1, 0, 1;\n}\n"
    : "+f"(d[0]),"+f"(d[1]),"+f"(d[2]),"+f"(d[3]),"+f"(d[4]),"+f"(d[5]),"+f"(d[6]),"+f"(d[7]),"+f"(d[8]),"+f"(d[9]),"+f"(d[10]),"+f"(d[11]),"+f"(d[12]),"+f"(d[13]),"+f"(d[14]),"+f"(d[15]),"+f"(d[16]),"+f"(d[17]),"+f"(d[18]),"+f"(d[19]),"+f"(d[20]),"+f"(d[21]),"+f"(d[22]),"+f"(d[23]),"+f"(d[24]),"+f"(d[25]),"+f"(d[26]),"+f"(d[27]),"+f"(d[28]),"+f"(d[29]),"+f"(d[30]),"+f"(d[31]),"+f"(d[32]),"+f"(d[33]),"+f"(d[34]),"+f"(d[35]),"+f"(d[36]),"+f"(d[37]),"+f"(d[38]),"+f"(d[39]),"+f"(d[40]),"+f"(d[41]),"+f"(d[42]),"+f"(d[43]),"+f"(d[44]),"+f"(d[45]),"+f"(d[46]),"+f"(d[47]),"+f"(d[48]),"+f"(d[49]),"+f"(d[50]),"+f"(d[51]),"+f"(d[52]),"+f"(d[53]),"+f"(d[54]),"+f"(d[55]),"+f"(d[56]),"+f"(d[57]),"+f"(d[58]),"+f"(d[59]),"+f"(d[60]),"+f"(d[61]),"+f"(d[62]),"+f"(d[63]),"+f"(d[64]),"+f"(d[65]),"+f"(d[66]),"+f"(d[67]),"+f"(d[68]),"+f"(d[69]),"+f"(d[70]),"+f"(d[71]),"+f"(d[72]),"+f"(d[73]),"+f"(d[74]),"+f"(d[75]),"+f"(d[76]),"+f"(d[77]),"+f"(d[78]),"+f"(d[79]),"+f"(d[80]),"+f"(d[81]),"+f"(d[82]),"+f"(d[83]),"+f"(d[84]),"+f"(d[85]),"+f"(d[86]),"+f"(d[87]),"+f"(d[88]),"+f"(d[89]),"+f"(d[90]),"+f"(d[91]),"+f"(d[92]),"+f"(d[93]),"+f"(d[94]),"+f"(d[95]) : "l"(da), "l"(db), "n"(SC));
}

constexpr uint32_t SBC = 1024;
constexpr int ROWB = 2 * 224 * 384;
constexpr int TB = 12;
constexpr int KS = 832;
constexpr int KSLOT = 22 * KS;
constexpr int SM_X1 = 0;
constexpr int SM_X2 = SM_X1 + 24576;
constexpr int SM_X0 = SM_X2 + 24576;
constexpr int SM_W = SM_X0 + 18432;
constexpr int SM_K = SM_W + 55296;
constexpr int SM_V = SM_K + 2 * KSLOT;
constexpr int SM_Q = SM_V + 22 * 1536;
constexpr int SM_O = SM_Q + 24576;
constexpr int SM_RPB = SM_O + 12288;
constexpr int SM_BAR = SM_RPB + 768;
constexpr int SM_A_TOTAL = SM_BAR + 256;
constexpr int SM_TWO = SM_X1;
constexpr int SM_TST = SM_TWO + 36864;
constexpr int SM_TIN = SM_W;
enum { B_FULL = 0, B_EMPTY = 3, B_TIN = 6, B_TFREE = 8, B_WK, B_WQ, B_WO, B_Q0, B_ODONE, B_KFREE = B_ODONE + 2, B_VFREE, B_COUNT };
enum { N_KRDY = 4, N_QK0, N_QK1, N_VQ0, N_VQ1, N_PVISS };

#define SPL 4
#define RA 152
#define RG 184
__device__ int g_flags[TB * 56];

#define TR(role, it, k)
#define TRDECL
#define TRARG
#define TRPASS
#define TRDUMP
#define TRB(it, k)
#define TR2(blk, k)

struct GemmCtx {
  uint32_t bar;
  uint32_t kC, vC, qC;
  uint32_t kH, vH;
  bool hvalid;
};

template <int STRIDE> __device__ __forceinline__ void dump12(uint32_t a, const uint32_t (&r)[12]) {
#pragma unroll
  for (int j = 0; j < 3; j++) stsm4(a + j * 2 * STRIDE, r[4 * j], r[4 * j + 1], r[4 * j + 2], r[4 * j + 3]);
}
template <int N> __device__ __forceinline__ void pack12(uint32_t (&r)[12], const float (&d)[N], int off) {
#pragma unroll
  for (int j = 0; j < 12; j++) r[j] = pack2(d[off + 2 * j], d[off + 2 * j + 1]);
}
template <int XS, int K0, int K1> __device__ __forceinline__ void issue_core(float (&d)[72]) {
  constexpr uint64_t da = mkdesc(SBC + XS, 16, 1024, 1), db = mkdesc(SBC + SM_W, 6144, 256, 3);
  wg_fence();
  if (K0 == 0) wg_ss144<0>(d, da, db);
#pragma unroll
  for (int k = K0 ? K0 : 1; k < K1; k++) wg_ss144<1>(d, da + (k >> 2) * 512 + (k & 3) * 2, db + k * 32);
  wg_commit();
}
template <int K0, int K1> __device__ __forceinline__ void issue_halo(float (&d)[48]) {
  constexpr uint64_t da = mkdesc(SBC + SM_X0 - 2048, 16, 1024, 1), db = mkdesc(SBC + SM_W, 6144, 256, 3);
  wg_fence();
  if (K0 == 0) wg_ss96<0>(d, da, db);
#pragma unroll
  for (int k = K0 ? K0 : 1; k < K1; k++) wg_ss96<1>(d, da + (k >> 2) * 384 + (k & 3) * 2, db + k * 32);
  wg_commit();
}
template <int ST, int BYTES> __device__ __forceinline__ void release_stage(const GemmCtx& c, bool on) {
  asm volatile("{\n.reg .pred p, q;\n.reg .b32 ra;\nsetp.ne.b32 q, %2, 0;\nelect.sync _|p, 0xffffffff;\nand.pred p, p, q;\n"
               "mapa.shared::cluster.u32 ra, %1, %4;\n"
               "@p mbarrier.arrive.expect_tx.shared::cta.b64 _, [%0], %3;\n@p mbarrier.arrive.shared::cluster.b64 _, [ra];\n}"
               ::"r"(c.bar + (B_FULL + ST) * 8), "r"(c.bar + (B_EMPTY + ST) * 8), "r"((int)on), "n"(BYTES / 4), "n"(ST) : "memory");
}
__device__ __forceinline__ void load_w(const CUtensorMap* m, uint32_t dst, uint32_t bar, int col) {
  asm volatile("cp.async.bulk.tensor.2d.shared::cluster.global.mbarrier::complete_tx::bytes [%0], [%1, {%3,%4}], [%2];"
               ::"r"(dst), "l"(m), "r"(bar), "r"(col), "r"(0) : "memory");
}
__device__ __forceinline__ void publish(uint32_t bar) {
  fence_async();
  __syncwarp();
  mbar_arrive_elect(bar);
}

template <bool FIRST, bool LAST>
__device__ __forceinline__ void gemm_iter(const GemmCtx& c, int b, uint32_t (&pk)[12], uint32_t (&pv)[12], uint32_t (&pq)[12] TRARG) {
  const uint32_t bar = c.bar;
  const uint32_t pa = b & 1;
  const bool w = b >= 0;
  const uint32_t ko = pa * KSLOT, vx = pa * 16, qx = pa * 128;
  float H[48], C[72];
  uint32_t hk[12], hv[12], pv2[12];
  TR(2, b, 0);
  if (FIRST) mbar_wait(bar + (B_FULL + 0) * 8, pa);
  if (w) nb_sync(N_QK1, 256);
  TR(2, b, 2);
  issue_halo<0, 8>(H);
  TR(2, b, 3);
  if (!FIRST) {
    if (w) mbar_wait(bar + B_KFREE * 8, pa);
    dump12<128>(c.kC + ko, pk);
  }
  issue_halo<8, 12>(H);
  TR(2, b, 4);
  if (!LAST) {
    mbar_wait(bar + (B_FULL + 2) * 8, pa);
    if (FIRST) mbar_wait(bar + B_WQ * 8, 0);
    TR(2, b, 13);
    issue_core<SM_X2, 0, 8>(C);
    TR(2, b, 5);
    if (!FIRST) { fence_async(); dump12<256>(c.qC ^ (qx ^ 192), pq); }
    wg_wait<1>(); pin(H);
    release_stage<0, 18432>(c, true);
  } else {
    dump12<256>(c.qC ^ (qx ^ 192), pq);
    fence_async();
    nb_arrive(N_VQ0, 288); nb_arrive(N_VQ1, 288);
    wg_wait<0>(); pin(H);
    uint32_t ln; asm volatile("mov.u32 %0, %%laneid;" : "=r"(ln));
    if (ln < 4) mbar_arrive_remote(bar + B_TFREE * 8, ln);
  }
  pack12(hk, H, 0);
  if (c.hvalid) dump12<128>(c.kH + ko, hk);
  pack12(hv, H, 24);
  if (!LAST) {
    issue_core<SM_X2, 8, 12>(C);
    if (w) { nb_arrive(N_VQ0, 288); nb_arrive(N_VQ1, 288); }
    else if (!FIRST) { __syncwarp(); mbar_arrive_elect(bar + B_Q0 * 8); }
    mbar_wait(bar + (B_FULL + 1) * 8, pa);
    TR(2, b, 6);
    wg_wait<0>(); pin(C);
    TR(2, b, 7);
    pack12(pk, C, 0);
    dump12<128>(c.kC + ko + 64, pk);
    release_stage<2, 24576>(c, b < 11);
    pack12(pv2, C, 24);
    pack12(pq, C, 48);
    TR(2, b, 8);
    issue_core<SM_X1, 0, SPL>(C);
    if (w) nb_sync(N_PVISS, 384);
    issue_core<SM_X1, SPL, 8>(C);
    TR(2, b, 9);
  }
  if (!FIRST) fence_async();
  TR(2, b, 14);
  if (!LAST) issue_core<SM_X1, 8, 12>(C);
  if (!FIRST) nb_arrive(N_KRDY, 256);
  TR(2, b, 1);
  if (!LAST) mbar_wait(bar + (B_FULL + 0) * 8, pa ^ 1);
  if (w) mbar_wait(bar + B_VFREE * 8, pa);
  TR(2, b, 10);
  if (!FIRST) dump12<128>(c.vC ^ vx, pv);
  if (!LAST) dump12<256>(c.qC ^ qx, pq);
  if (c.hvalid) dump12<128>(c.vH ^ vx, hv);
  if (LAST) { fence_async(); nb_arrive(N_VQ0, 256); nb_arrive(N_VQ1, 256); return; }
  dump12<128>((c.vC ^ vx ^ 16) + 768, pv2);
  TR(2, b, 11);
  wg_wait<0>(); pin(C);
  TR(2, b, 12);
  release_stage<1, 24576>(c, b < 11);
  pack12(pk, C, 0);
  pack12(pv, C, 24);
  pack12(pq, C, 48);
}

__device__ __forceinline__ float fold(float a, float b, float t, int useb) {
  float r;
  asm("{\n.reg .pred p;\nsetp.ne.b32 p, %4, 0;\nfma.rn.f32 %0, %1, 0f3E553B95, %3;\n@p fma.rn.f32 %0, %2, 0f3E553B95, %3;\n}"
      : "=&f"(r) : "f"(a), "f"(b), "f"(t), "r"(useb));
  return r;
}
template <int U, int L>
__device__ __forceinline__ void softmax_tile(const float (&SA)[56], const float (&SB)[56], const float (&T)[16], int b0, int b1,
                                             uint32_t (&P)[28], float (&sx)[8]) {
  float lu[14], ll[14];
#pragma unroll
  for (int j = 0; j < 7; j++) {
    constexpr int sh = U == L ? 2 : 0;
    const float tu0 = T[2 * j + sh], tu1 = T[2 * j + 1 + sh], tl0 = T[2 * j], tl1 = T[2 * j + 1];
    lu[2 * j]     = fold(SA[4 * (U + j)],     SB[4 * (U + j)],     tu0, b0);
    ll[2 * j]     = fold(SA[4 * (L + j) + 2], SB[4 * (L + j) + 2], tl0, b0);
    lu[2 * j + 1] = fold(SA[4 * (U + j) + 1], SB[4 * (U + j) + 1], tu1, b1);
    ll[2 * j + 1] = fold(SA[4 * (L + j) + 3], SB[4 * (L + j) + 3], tl1, b1);
  }
  float mu = lu[0], ml = ll[0], mu2 = lu[1], ml2 = ll[1];
#pragma unroll
  for (int j = 1; j < 7; j++) { mu = fmaxf(mu, lu[2 * j]); mu2 = fmaxf(mu2, lu[2 * j + 1]); ml = fmaxf(ml, ll[2 * j]); ml2 = fmaxf(ml2, ll[2 * j + 1]); }
  mu = fmaxf(mu, mu2); ml = fmaxf(ml, ml2);
  { const float a1 = __shfl_xor_sync(0xffffffffu, mu, 1), a2 = __shfl_xor_sync(0xffffffffu, mu, 2), a3 = __shfl_xor_sync(0xffffffffu, mu, 3);
    const float c1 = __shfl_xor_sync(0xffffffffu, ml, 1), c2 = __shfl_xor_sync(0xffffffffu, ml, 2), c3 = __shfl_xor_sync(0xffffffffu, ml, 3);
    mu = fmaxf(fmaxf(mu, a1), fmaxf(a2, a3)); ml = fmaxf(fmaxf(ml, c1), fmaxf(c2, c3)); }
  float su = 0.f, sl = 0.f;
#pragma unroll
  for (int c = 0; c < 14; c++) {
    const int iu = (c >> 1) * 4 + (c & 1) * 2;
    if (c >= U && c < U + 7) {
      float e0 = ex2(lu[2 * (c - U)] - mu), e1 = ex2(lu[2 * (c - U) + 1] - mu);
      su = c == U ? e0 + e1 : (su + e0) + e1; P[iu] = pack2(e0, e1);
    } else P[iu] = 0u;
    if (c >= L && c < L + 7) {
      float e0 = ex2(ll[2 * (c - L)] - ml), e1 = ex2(ll[2 * (c - L) + 1] - ml);
      sl = c == L ? e0 + e1 : (sl + e0) + e1; P[iu + 1] = pack2(e0, e1);
    } else P[iu + 1] = 0u;
  }
  sx[0] = su; sx[4] = sl;
#pragma unroll
  for (int k = 1; k < 4; k++) { sx[k] = __shfl_xor_sync(0xffffffffu, su, k); sx[4 + k] = __shfl_xor_sync(0xffffffffu, sl, k); }
}

struct Maps { CUtensorMap xc, xh, w, os, wo, ot; };

__global__ void __cluster_dims__(4, 1, 1) __launch_bounds__(512, 1)
na_attn_kernel(const __grid_constant__ Maps mp, const __nv_bfloat16* __restrict__ wqkv, const __nv_bfloat16* __restrict__ rpb) {
  extern __shared__ __align__(1024) uint8_t smem_raw[];
  const uint32_t sb = smem_u32(smem_raw);
  if ((sb & 0x3FFFF) != SBC) return;
  const uint32_t bar = sb + SM_BAR;
  TR2(blockIdx.x, 0);
  const int tid = threadIdx.x, lane = tid & 31;
  const int warp = __shfl_sync(0xffffffffu, tid >> 5, 0);
  const int head = blockIdx.x & 3, cl = blockIdx.x >> 2;
  const int par = cl / 7, strip = cl - par * 7, ph = par >> 1, pw = par & 1;

  uint4 wv[3];
  const int wr = tid / 6, wc = tid - wr * 6;
  if (warp < 12) {
#pragma unroll
    for (int i = 0; i < 3; i++) wv[i] = __ldg(reinterpret_cast<const uint4*>(wqkv + (wr + i * 64) * 576 + 384 + head * 48 + wc * 8));
  } else if (elect_one()) {
    if (warp == 12) {
      mbar_init(bar + B_WK * 8, 1);
#pragma unroll
      for (int i = 0; i < 3; i++) load_w(&mp.w, sb + SM_W + i * 6144, bar + B_WK * 8, 192 + head * 48 + i * 16);
      mbar_expect(bar + B_WK * 8, 18432);
    } else if (warp == 13) {
#pragma unroll
      for (int i = 0; i < B_WK; i++) mbar_init(bar + i * 8, i < B_EMPTY ? 4 : (i < B_TIN ? 16 : (i < B_TFREE ? 1 : 16)));
    } else if (warp == 14) {
#pragma unroll
      for (int i = B_WQ; i < B_COUNT; i++) mbar_init(bar + i * 8, i < B_Q0 ? 1 : (i < B_KFREE ? 4 : 8));
    }
    asm volatile("fence.mbarrier_init.release.cluster;" ::: "memory");
  }
  __syncwarp();
  asm volatile("barrier.cluster.arrive.relaxed.aligned;" ::: "memory");

  if (warp >= 12) {
    asm volatile("setmaxnreg.dec.sync.aligned.u32 24;");
    asm volatile("griddepcontrol.launch_dependents;");
    const int cc = ph * 112 + (head ? strip * 16 : (strip == 0 ? 16 : (strip == 6 ? 74 : strip * 16 - 3)));
    const int sd = strip == 0 ? -1 : (strip == 6 ? 1 : 0);
    const int r0 = head == 0 ? -4 : (head == 1 ? 4 : 0);
    asm volatile("barrier.cluster.wait.aligned;" ::: "memory");
    if (warp == 12) {
      const uint32_t fb = bar + (B_FULL + head) * 8, eb = bar + (B_EMPTY + head) * 8;
      const uint32_t dst = sb + (head == 0 ? SM_X0 : (head == 1 ? SM_X1 : SM_X2));
      const int nl = head == 0 ? 15 : (head == 3 ? 1 : 14);
#pragma unroll 1
      for (int n = 0; n < nl; n++) {
        if (n) mbar_wait(eb, (n - 1) & 1);
        if (elect_one()) {
          if (head == 0) {
            asm volatile("cp.async.bulk.tensor.5d.shared::cluster.global.mbarrier::complete_tx::bytes.multicast::cluster [%0], [%1, {%3,%4,%5,%6,%7}], [%2], %8;"
                         ::"r"(dst), "l"(&mp.xh), "r"(fb), "r"(0), "r"(8 * n + r0), "r"(cc), "r"(sd), "r"(pw * 3), "h"((uint16_t)15) : "memory");
            if (n + 1 < nl) asm volatile("cp.async.bulk.prefetch.tensor.5d.L2.global [%0, {%1,%2,%3,%4,%5}];" ::"l"(&mp.xh), "r"(0), "r"(8 * n + 8 + r0), "r"(cc), "r"(sd), "r"(pw * 3) : "memory");
          } else if (head < 3) {
            asm volatile("cp.async.bulk.tensor.4d.shared::cluster.global.mbarrier::complete_tx::bytes.multicast::cluster [%0], [%1, {%3,%4,%5,%6}], [%2], %7;"
                         ::"r"(dst), "l"(&mp.xc), "r"(fb), "r"(0), "r"(8 * n + r0), "r"(cc), "r"(pw * 3), "h"((uint16_t)15) : "memory");
          }
          if (n == 0) {
#pragma unroll
            for (int i = 0; i < 3; i++) load_w(&mp.w, sb + SM_W + (6 + i) * 6144, bar + B_WQ * 8, head * 48 + i * 16);
            mbar_expect(bar + B_WQ * 8, 18432);
            mbar_expect(bar + B_TIN * 8, 24576); mbar_expect(bar + (B_TIN + 1) * 8, 24576);
          }
          if (head && n + 1 < nl) asm volatile("cp.async.bulk.prefetch.tensor.4d.L2.global [%0, {%1,%2,%3,%4}];" ::"l"(&mp.xc), "r"(0), "r"(8 * n + 8 + r0), "r"(cc), "r"(pw * 3) : "memory");
        }
        __syncwarp();
      }
    }
    if (warp >= 14) {
      const int j = warp - 14;
      int* flag = g_flags + cl * 2 + j;
      nb_arrive(N_VQ0 + j, 288);
      TRDECL;
#pragma unroll 1
      for (int b = 0; b < TB; b++) {
        TR(2, b, 0);
        mbar_wait(bar + (B_ODONE + j) * 8, b & 1);
        TR(2, b, 1);
        if (lane == 0) {
          asm volatile("cp.async.bulk.tensor.3d.global.shared::cta.bulk_group [%0, {%2,%3,%4}], [%1];"
                       ::"l"(&mp.os), "r"(sb + SM_O + j * 6144), "r"(pw * 192), "r"(8 * b + 2 * head), "r"(ph * 112 + strip * 16 + 8 * j) : "memory");
          asm volatile("cp.async.bulk.commit_group;\ncp.async.bulk.wait_group.read 0;" ::: "memory");
        }
        __syncwarp();
        nb_arrive(N_VQ0 + j, 288);
        TR(2, b, 2);
        if (lane == 0) {
          asm volatile("cp.async.bulk.wait_group 0;" ::: "memory");
          TR(2, b, 3);
          asm volatile("fence.proxy.async.global;" ::: "memory");
          TR(2, b, 4);
          asm volatile("red.release.gpu.global.add.s32 [%0], 1;" ::"l"(flag + b * 56) : "memory");
          TR(2, b, 5);
        }
        __syncwarp();
      }
      TRDUMP;
    }
    cluster_sync();
  } else if (warp >= 8) {
    asm volatile("setmaxnreg.inc.sync.aligned.u32 %0;" ::"n"(RG));
    GemmCtx c;
    c.bar = bar;
    const int gw = warp - 8, tk = gw * 16 + (lane & 15), hi = lane >> 4;
    { const int col = tk >> 2, i = tk & 3;
      c.kC = sb + SM_K + (col + 3) * KS + hi * 128 + i * 16;
      c.vC = sb + SM_V + (col + 3) * 1536 + hi * 128 + (2 * i + ((col + 3) & 1)) * 16;
      c.qC = sb + SM_Q + col * 1536 + hi * 256 + (col & 1) * 64 + i * 16; }
    { const int ci = (tk >> 3) - 2, kc = ci < 3 ? ci : ci + 16, i = tk & 7; c.hvalid = gw > 0;
      c.kH = sb + SM_K + kc * KS + hi * 128 + i * 16;
      c.vH = sb + SM_V + kc * 1536 + hi * 128 + (i >> 2) * 768 + (2 * (i & 3) + ((kc ^ (i >> 2)) & 1)) * 16; }
    asm volatile("barrier.cluster.wait.aligned;" ::: "memory");
    if (elect_one()) { mbar_expect(bar + B_FULL * 8, 4608); mbar_expect(bar + (B_FULL + 1) * 8, 6144); mbar_expect(bar + (B_FULL + 2) * 8, 6144); }
    __syncwarp();
#pragma unroll
    for (int i = 0; i < 3; i++) sts128(sb + SM_W + (3 + (wc >> 1)) * 6144 + (wr + i * 64) * 32 + ((wc ^ (wr >> 2)) & 1) * 16, wv[i]);
    fence_async();
    asm volatile("bar.sync 1, 384;" ::: "memory");
    mbar_wait(bar + B_WK * 8, 0);
    uint32_t pk[12], pv[12], pq[12];
    TRDECL;
    gemm_iter<true, false>(c, -2, pk, pv, pq TRPASS);
#pragma unroll 1
    for (int b = -1; b < 12; b++) gemm_iter<false, false>(c, b, pk, pv, pq TRPASS);
    asm volatile("bar.sync 2, 128;" ::: "memory");
    if (gw == 0 && elect_one()) {
      mbar_expect(bar + B_WO * 8, 36864);
      asm volatile("cp.async.bulk.tensor.3d.shared::cluster.global.mbarrier::complete_tx::bytes [%0], [%1, {%3,%4,%5}], [%2];"
                   ::"r"(sb + SM_TWO), "l"(&mp.wo), "r"(bar + B_WO * 8), "r"(0), "r"(0), "r"((head & 1) * 3) : "memory");
    }
    __syncwarp();
    gemm_iter<false, true>(c, 12, pk, pv, pq TRPASS);
    TR(2, 13, 0);
    mbar_wait(bar + B_WO * 8, 0);
    nb_sync(N_QK1, 256);
    TR(2, 13, 1);
    const uint32_t st = sb + SM_TST + gw * 3072;
    const uint32_t sta = st + (lane & 15) * 64 + ((hi ^ ((lane >> 1) & 3)) * 16);
#pragma unroll 1
    for (int i = 0; i < 2; i++) {
      constexpr uint64_t db = mkdesc(SBC + SM_TWO, 12288, 512, 2);
      const uint64_t da = mkdesc(SBC + SM_TIN, 128, 768, 0) + i * (24576 / 16);
      float D[48];
      mbar_wait(bar + (B_TIN + i) * 8, 0);
      if (i) asm volatile("barrier.cluster.arrive.relaxed.aligned;" ::: "memory");
      TR(2, 13 - i, 2); TR(2, 12 + i, 5);
      wg_fence();
      wg_ss96<0>(D, da, db);
#pragma unroll
      for (int k = 1; k < 12; k++) wg_ss96<1>(D, da + (k / 3) * 384 + (k % 3) * 16, db + k * 64);
      wg_commit();
      if (lane == 0) asm volatile("cp.async.bulk.wait_group.read 0;" ::: "memory");
      __syncwarp();
      wg_wait<0>(); pin(D);
      TR(2, 13 - i, 3); TR(2, 12 + i, 6);
#pragma unroll
      for (int q = 0; q < 6; q++)
        stsm4((sta ^ ((q & 1) * 32)) + (q >> 1) * 1024,
              pack2(D[8 * q], D[8 * q + 1]), pack2(D[8 * q + 2], D[8 * q + 3]), pack2(D[8 * q + 4], D[8 * q + 5]), pack2(D[8 * q + 6], D[8 * q + 7]));
      fence_async();
      __syncwarp();
      if (lane == 0) {
        asm volatile("cp.async.bulk.tensor.4d.global.shared::cta.bulk_group [%0, {%2,%3,%4,%5}], [%1];"
                     ::"l"(&mp.ot), "r"(st), "r"(0), "r"(8 * (TB + i)), "r"(ph * 112 + strip * 16 + 8 * (gw >> 1) + 4 * (head >> 1) + 2 * (gw & 1)), "r"(pw * 6 + (head & 1) * 3) : "memory");
        asm volatile("cp.async.bulk.commit_group;" ::: "memory");
      }
      TR(2, 13 - i, 4); TR(2, 12 + i, 7);
    }
    if (lane == 0) asm volatile("cp.async.bulk.wait_group.read 0;" ::: "memory");
    __syncwarp();
    TR(2, 13, 8);
    TRDUMP;
    asm volatile("barrier.cluster.wait.aligned;" ::: "memory");
  } else {
    asm volatile("setmaxnreg.inc.sync.aligned.u32 %0;" ::"n"(RA));
    float rv = -INFINITY;
    if (tid < 169) rv = __bfloat162float(rpb[head * 169 + tid]) * 1.4426950408889634f;
    if (tid < 192) {
      const int kc = (wr & 15) + 3;
      sts128(tid < 96 ? sb + SM_K + kc * KS + wc * 128 + 48 : sb + SM_V + kc * 1536 + wc * 128 + (6 + (kc & 1)) * 16, make_uint4(0, 0, 0, 0));
    }
#pragma unroll
    for (int i = 0; i < 3; i++) sts128(sb + SM_W + (3 + (wc >> 1)) * 6144 + (wr + i * 64) * 32 + ((wc ^ (wr >> 2)) & 1) * 16, wv[i]);
    fence_async();
    asm volatile("bar.arrive 1, 384;" ::: "memory");
    if (tid < 182) asm volatile("st.shared.f32 [%0], %1;" ::"r"(sb + SM_RPB + tid * 4), "f"(rv) : "memory");
    const int j = warp >> 2, w = warp & 3;
    int variant = w;
    if (strip == 0 && j == 0 && w < 2) variant = 4;
    if (strip == 6 && j == 1 && w >= 2) variant = 5;
    const uint32_t qa = sb + SM_Q + (8 * j + 2 * w + ((lane >> 3) & 1)) * 1536 + (lane >> 4) * 256 + (((lane & 7) * 16) ^ (((lane >> 3) & 1) * 64));
    uint32_t oa = sb + SM_O + j * 6144 + (2 * w + ((lane >> 3) & 1)) * 768 + (lane >> 4) * 128 + (lane & 7) * 16;
    const uint64_t dK = mkdesc(SBC + SM_K, 128, KS, 0) + j * (8 * KS / 16);
    const uint64_t dV = mkdesc(SBC + SM_V, 768, 128, 0) + j * (8 * 1536 / 16);
    asm volatile("barrier.cluster.wait.aligned;" ::: "memory");
    asm volatile("bar.sync 3, 256;" ::: "memory");
    float T[16];
    TRDECL;
    int b0 = 0, b1 = 0;
    uint32_t meta = 0;
    uint32_t q[12];
    mbar_wait(bar + B_Q0 * 8, 0);
#pragma unroll
    for (int k = 0; k < 3; k++) ldsm4(qa + k * 512, q[4 * k], q[4 * k + 1], q[4 * k + 2], q[4 * k + 3]);
#pragma unroll 1
    for (int b = 0; b < 14; b++) {
      const uint32_t pa = b & 1;
      float SA[56], SB[56];
      const uint64_t dA = dK + pa * (KSLOT >> 4), dB = dK + (pa ^ 1) * (KSLOT >> 4);
      TR(0, b, 0);
      nb_sync(N_KRDY + j, 256);
      TR(0, b, 1);
      TR(0, b - 1, 9);
      wg_fence();
      wg_rs112<0>(SA, q[0], q[1], q[2], q[3], dA);
      wg_rs112<0>(SB, q[0], q[1], q[2], q[3], dB);
      wg_rs112<1>(SA, q[4], q[5], q[6], q[7], dA + 16);
      wg_rs112<1>(SB, q[4], q[5], q[6], q[7], dB + 16);
      wg_rs112<1>(SA, q[8], q[9], q[10], q[11], dA + 32);
      wg_rs112<1>(SB, q[8], q[9], q[10], q[11], dB + 32);
      wg_commit();
      nb_arrive(N_QK0 + j, 256);
      TR(0, b, 2);
      if (b <= 1 || b == 13) {
        uint32_t ln; asm volatile("mov.u32 %0, %%laneid;" : "=r"(ln));
        const int g = ln >> 2, t = ln & 3;
        const int sw = b == 0 ? max(g + 1, 4) : (b == 13 ? min(g + 1, 5) : g + 1);
        const int i0 = 2 * t, i1 = 2 * t + 1;
        b0 = i0 <= sw - 2; b1 = i1 <= sw - 2;
        const uint32_t tb = sb + SM_RPB + (variant < 4 ? 3 : variant + 1 - 2 * w) * 4;
        const uint32_t ra0 = tb + (i0 == sw - 1 ? 13 : i0 + 8 * b0 - g + 2) * 52;
        const uint32_t ra1 = tb + (i1 == sw - 1 ? 13 : i1 + 8 * b1 - g + 2) * 52;
#pragma unroll
        for (int jj = 0; jj < 8; jj++) { T[2 * jj] = lds_f32(ra0 + jj * 4); T[2 * jj + 1] = lds_f32(ra1 + jj * 4); }
        meta = ((0x5555u & ((1u << (2 * (sw - 1))) - 1)) ^ 0xDD88u ^ (((t ^ b) & 1) ? 0x5555u : 0u)) * 0x10001u;
        if (b == 13) oa += SM_Q - SM_O + j * 6144;
      } else meta ^= 0x55555555u;
      wg_wait<0>(); pin(SA); pin(SB);
      mbar_arrive_elect(bar + B_KFREE * 8);
      TR(0, b, 3);
      TR(0, b - 1, 10);
      uint32_t P[28];
      float sx[8];
      switch (variant) {
        case 0: softmax_tile<0, 1>(SA, SB, T, b0, b1, P, sx); break;
        case 1: softmax_tile<2, 3>(SA, SB, T, b0, b1, P, sx); break;
        case 2: softmax_tile<4, 5>(SA, SB, T, b0, b1, P, sx); break;
        case 3: softmax_tile<6, 7>(SA, SB, T, b0, b1, P, sx); break;
        case 4: softmax_tile<3, 3>(SA, SB, T, b0, b1, P, sx); break;
        default: softmax_tile<4, 4>(SA, SB, T, b0, b1, P, sx); break;
      }
      float O[24];
      TR(0, b, 4);
      nb_sync(N_VQ0 + j, b == 13 ? 256 : 288);
      TR(0, b, 5);
#pragma unroll
      for (int k = 0; k < 3; k++) ldsm4(qa + (pa ^ 1) * 128 + k * 512, q[4 * k], q[4 * k + 1], q[4 * k + 2], q[4 * k + 3]);
      wg_fence();
      wg_sp48<0>(O, P[0], P[1], P[2], P[3], dV, meta);
#pragma unroll
      for (int s = 1; s < 7; s++) wg_sp48<1>(O, P[4 * s], P[4 * s + 1], P[4 * s + 2], P[4 * s + 3], dV + s * 192, meta);
      wg_commit();
      if (b < 12) nb_arrive(N_PVISS, 384);
      TR(0, b, 6);
      wg_wait<0>(); pin(O);
      mbar_arrive_elect(bar + B_VFREE * 8);
      TR(0, b, 7);
      float ru, rl;
      asm("rcp.approx.ftz.f32 %0, %1;" : "=f"(ru) : "f"(((fmaf(O[0], 0.f, sx[0]) + sx[1]) + sx[2]) + sx[3]));
      asm("rcp.approx.ftz.f32 %0, %1;" : "=f"(rl) : "f"(((fmaf(O[2], 0.f, sx[4]) + sx[5]) + sx[6]) + sx[7]));
#pragma unroll
      for (int i = 0; i < 3; i++)
        stsm4(oa + i * 256, pack2(O[8 * i] * ru, O[8 * i + 1] * ru), pack2(O[8 * i + 2] * rl, O[8 * i + 3] * rl),
              pack2(O[8 * i + 4] * ru, O[8 * i + 5] * ru), pack2(O[8 * i + 6] * rl, O[8 * i + 7] * rl));
      if (b < TB) publish(bar + (B_ODONE + j) * 8);
      else {
        fence_async();
        if (b == TB) mbar_wait(bar + B_TFREE * 8, 0);
        __syncwarp();
        if (elect_one()) {
#pragma unroll
          for (int d = 0; d < 2; d++)
            asm volatile("{\n.reg .b32 rd, rb;\nmapa.shared::cluster.u32 rd, %0, %3;\nmapa.shared::cluster.u32 rb, %2, %3;\n"
                         "cp.async.bulk.shared::cluster.shared::cta.mbarrier::complete_tx::bytes [rd], [%1], 1536, [rb];\n}"
                         ::"r"(sb + SM_TIN + (b - TB) * 24576 + head * 6144 + (2 * j + (w & 1)) * 1536),
                           "r"(sb + (b == 13 ? SM_Q + j * 12288 : SM_O + j * 6144) + w * 1536), "r"(bar + (B_TIN + b - TB) * 8), "r"((w & 2) + d) : "memory");
        }
        __syncwarp();
      }
      TR(0, b, 8);
    }
    TRDUMP;
    cluster_sync();
    TR2(blockIdx.x, 2);
  }
}

constexpr int NSTB = 6;
constexpr int NTB = TB * 56;
constexpr int SM_B_IN = 0;
constexpr int SM_B_W = SM_B_IN + NSTB * 24576;
constexpr int SM_B_BAR = SM_B_W + 73728;
constexpr int SM_B_TOTAL = SM_B_BAR + 128;
struct MapsB { CUtensorMap oi, oo, wo; };

__global__ void __launch_bounds__(480, 1)
na_proj_kernel(const __grid_constant__ MapsB mp) {
  extern __shared__ __align__(1024) uint8_t smem_raw[];
  const uint32_t sb = smem_u32(smem_raw);
  if ((sb & 0x3FFFF) != SBC) return;
  const uint32_t bar = sb + SM_B_BAR;
  const int tid = threadIdx.x, lane = tid & 31;
  const int warp = __shfl_sync(0xffffffffu, tid >> 5, 0);
  TR2(132 + blockIdx.x, 0);
  TRB(47, 0);
  if (warp == 12 && elect_one()) {
#pragma unroll
    for (int i = 0; i <= 2 * NSTB; i++) mbar_init(bar + i * 8, i < NSTB || i == 2 * NSTB ? 1 : 4);
    mbar_expect(bar + 2 * NSTB * 8, 73728);
#pragma unroll
    for (int i = 0; i < 2; i++)
      asm volatile("cp.async.bulk.tensor.3d.shared::cluster.global.mbarrier::complete_tx::bytes [%0], [%1, {%3,%4,%5}], [%2];"
                   ::"r"(sb + SM_B_W + i * 36864), "l"(&mp.wo), "r"(bar + 2 * NSTB * 8), "r"(0), "r"(0), "r"(i * 3) : "memory");
  }
  __syncthreads();
  const int step = gridDim.x;
  if (warp >= 12) {
    const int wg = warp - 12;
    int use = 0;
#pragma unroll 1
    for (int n = blockIdx.x + wg * step; n < NTB; n += 3 * step, use++) {
      const int b = n / 56, rem = n - b * 56, par = rem / 14, sg = wg + 3 * (use & 1);
      int v; uint32_t spin = 0;
      do { asm volatile("ld.acquire.gpu.global.s32 %0, [%1];" : "=r"(v) : "l"(g_flags + n) : "memory"); } while (v < 4 && ++spin < SPIN_LIMIT);
      asm volatile("fence.proxy.async.global;" ::: "memory");
      if (use >= 2) mbar_wait(bar + (NSTB + sg) * 8, ((use >> 1) - 1) & 1);
      if (elect_one()) {
        mbar_expect(bar + sg * 8, 24576);
        asm volatile("cp.async.bulk.tensor.3d.shared::cluster.global.mbarrier::complete_tx::bytes [%0], [%1, {%3,%4,%5}], [%2];"
                     ::"r"(sb + SM_B_IN + sg * 24576), "l"(&mp.oi), "r"(bar + sg * 8), "r"((par & 1) * 192), "r"(8 * b), "r"((par >> 1) * 112 + (rem - par * 14) * 8) : "memory");
        g_flags[n] = 0;
      }
      __syncwarp();
    }
  } else {
    const int wg = warp >> 2, w = warp & 3;
    constexpr uint64_t db = mkdesc(SBC + SM_B_W, 12288, 512, 2);
    const uint32_t sta0 = sb + SM_B_IN + w * 6144 + (lane & 15) * 128 + (((lane >> 4) ^ (lane & 7)) * 16);
    mbar_wait(bar + 2 * NSTB * 8, 0);
    TRB(47, 1);
    int use = 0;
#pragma unroll 1
    for (int n = blockIdx.x + wg * step; n < NTB; n += 3 * step, use++) {
      const int b = n / 56, rem = n - b * 56, par = rem / 14, sg = wg + 3 * (use & 1);
      const uint64_t da = mkdesc(SBC + SM_B_IN, 128, 3072, 0) + sg * (24576 / 16);
      float D[96];
      mbar_wait(bar + sg * 8, (use >> 1) & 1);
      if (use | wg) nb_sync(4 + wg, 256);
      TRB(use * 3 + wg, 3);
      wg_fence();
      wg_ss192<0>(D, da, db);
#pragma unroll
      for (int k = 1; k < 12; k++) wg_ss192<1>(D, da + k * 16, db + k * 64);
      wg_commit();
      if (n + step < NTB) nb_arrive(wg == 2 ? 4 : 5 + wg, 256);
      TRB(use * 3 + wg, 4);
      if (use && lane == 0) {
        asm volatile("cp.async.bulk.wait_group.read 0;" ::: "memory");
        mbar_arrive(bar + (NSTB + wg + 3 * (~use & 1)) * 8);
      }
      __syncwarp();
      wg_wait<0>(); pin(D);
      nb_sync(1 + wg, 128);
      TRB(use * 3 + wg, 5);
      const uint32_t sta = sta0 + sg * 24576;
#pragma unroll
      for (int q = 0; q < 12; q++)
        stsm4((sta ^ ((q & 3) * 32)) + (q >> 2) * 2048,
              pack2(D[8 * q], D[8 * q + 1]), pack2(D[8 * q + 2], D[8 * q + 3]), pack2(D[8 * q + 4], D[8 * q + 5]), pack2(D[8 * q + 6], D[8 * q + 7]));
      fence_async();
      __syncwarp();
      if (lane == 0) {
        asm volatile("cp.async.bulk.tensor.4d.global.shared::cta.bulk_group [%0, {%2,%3,%4,%5}], [%1];"
                     ::"l"(&mp.oo), "r"(sb + SM_B_IN + sg * 24576 + w * 6144), "r"(0), "r"(8 * b), "r"((par >> 1) * 112 + (rem - par * 14) * 8 + 2 * w), "r"((par & 1) * 3) : "memory");
        asm volatile("cp.async.bulk.commit_group;" ::: "memory");
      }
      __syncwarp();
      TRB(use * 3 + wg, 6);
    }
    if (lane == 0) asm volatile("cp.async.bulk.wait_group 0;" ::: "memory");
    TR2(132 + blockIdx.x, 2);
  }
}

typedef CUresult (*EncodeFn)(CUtensorMap*, CUtensorMapDataType, cuuint32_t, void*, const cuuint64_t*, const cuuint64_t*, const cuuint32_t*,
                             const cuuint32_t*, CUtensorMapInterleave, CUtensorMapSwizzle, CUtensorMapL2promotion, CUtensorMapFloatOOBfill);
static EncodeFn g_enc = nullptr;
static void make_map(CUtensorMap* m, const void* p, int rank, const cuuint64_t* dim, const cuuint64_t* str, const cuuint32_t* box, CUtensorMapSwizzle sw) {
  const cuuint32_t ones[5] = {1, 1, 1, 1, 1};
  g_enc(m, CU_TENSOR_MAP_DATA_TYPE_BFLOAT16, rank, (void*)p, dim, str, box, ones, CU_TENSOR_MAP_INTERLEAVE_NONE, sw,
        CU_TENSOR_MAP_L2_PROMOTION_L2_128B, CU_TENSOR_MAP_FLOAT_OOB_FILL_NONE);
}

extern "C" void kernel_launch(void* const* d_in, const int* in_sizes, int n_in, void* d_out, int out_size) {
  const __nv_bfloat16* x = (const __nv_bfloat16*)d_in[0];
  const __nv_bfloat16* wqkv = (const __nv_bfloat16*)d_in[1];
  const __nv_bfloat16* wo = (const __nv_bfloat16*)d_in[2];
  const __nv_bfloat16* rpb = (const __nv_bfloat16*)d_in[3];

  if (!g_enc) {
    void* fn = nullptr; cudaDriverEntryPointQueryResult qr;
    cudaGetDriverEntryPoint("cuTensorMapEncodeTiled", &fn, cudaEnableDefault, &qr);
    g_enc = (EncodeFn)fn;
    cudaFuncSetAttribute(na_attn_kernel, cudaFuncAttributeMaxDynamicSharedMemorySize, SM_A_TOTAL);
    cudaFuncSetAttribute(na_proj_kernel, cudaFuncAttributeMaxDynamicSharedMemorySize, SM_B_TOTAL);
  }
  Maps ma; MapsB mb;
  { cuuint64_t dim[4] = {64, 112, 224, 6}, str[3] = {(cuuint64_t)ROWB, 768, 128};
    cuuint32_t box[4] = {64, 4, 16, 3}, boxo[4] = {64, 8, 2, 3};
    make_map(&ma.xc, x, 4, dim, str, box, CU_TENSOR_MAP_SWIZZLE_128B);
    make_map(&mb.oo, d_out, 4, dim, str, boxo, CU_TENSOR_MAP_SWIZZLE_128B); }
  { cuuint64_t dim[5] = {64, 112, 224, 2, 6}, str[4] = {(cuuint64_t)ROWB, 768, 19 * 768, 128};
    cuuint32_t box[5] = {64, 8, 3, 2, 3};
    make_map(&ma.xh, x, 5, dim, str, box, CU_TENSOR_MAP_SWIZZLE_128B); }
  { cuuint64_t dim[3] = {384, 112, 224}, str[2] = {(cuuint64_t)ROWB, 768};
    cuuint32_t box[3] = {192, 8, 8}, boxs[3] = {192, 2, 8};
    make_map(&mb.oi, d_out, 3, dim, str, box, CU_TENSOR_MAP_SWIZZLE_NONE);
    make_map(&ma.os, d_out, 3, dim, str, boxs, CU_TENSOR_MAP_SWIZZLE_NONE); }
  { cuuint64_t dim[4] = {32, 112, 224, 12}, str[3] = {(cuuint64_t)ROWB, 768, 64};
    cuuint32_t box[4] = {32, 8, 2, 3};
    make_map(&ma.ot, d_out, 4, dim, str, box, CU_TENSOR_MAP_SWIZZLE_64B); }
  { cuuint64_t dim[2] = {576, 192}, str[1] = {1152};
    cuuint32_t box[2] = {16, 192};
    make_map(&ma.w, wqkv, 2, dim, str, box, CU_TENSOR_MAP_SWIZZLE_32B); }
  { cuuint64_t dim[3] = {32, 192, 6}, str[2] = {384, 64};
    cuuint32_t box[3] = {32, 192, 3};
    make_map(&ma.wo, wo, 3, dim, str, box, CU_TENSOR_MAP_SWIZZLE_64B);
    mb.wo = ma.wo; }
  na_attn_kernel<<<112, 512, SM_A_TOTAL>>>(ma, wqkv, rpb);
  cudaLaunchConfig_t cfg = {};
  cfg.gridDim = dim3(20); cfg.blockDim = dim3(480); cfg.dynamicSmemBytes = SM_B_TOTAL; cfg.stream = cudaStreamPerThread;
  cudaLaunchAttribute at[1];
  at[0].id = cudaLaunchAttributeProgrammaticStreamSerialization; at[0].val.programmaticStreamSerializationAllowed = 1;
  cfg.attrs = at; cfg.numAttrs = 1;
  cudaLaunchKernelEx(&cfg, na_proj_kernel, mb);
}
```

```cpp
#include <cuda_runtime.h>
#include <cuda_bf16.h>
#include <cuda.h>
#include <stdint.h>

#define SPIN_LIMIT (1u << 18)

__device__ __forceinline__ uint32_t smem_u32(const void* p) { return (uint32_t)__cvta_generic_to_shared(p); }
__device__ __forceinline__ void wg_fence() { asm volatile("wgmma.fence.sync.aligned;" ::: "memory"); }
__device__ __forceinline__ void wg_commit() { asm volatile("wgmma.commit_group.sync.aligned;" ::: "memory"); }
template <int N> __device__ __forceinline__ void wg_wait() { asm volatile("wgmma.wait_group.sync.aligned %0;" ::"n"(N) : "memory"); }
template <int N> __device__ __forceinline__ void pin(float (&d)[N]) {
#pragma unroll
  for (int i = 0; i < N; i++) asm volatile("" : "+f"(d[i])::"memory");
}
__host__ __device__ constexpr uint64_t mkdesc(uint32_t addr, uint32_t lbo, uint32_t sbo, uint32_t sw) {
  return (uint64_t)((addr & 0x3FFFF) >> 4) | ((uint64_t)(lbo >> 4) << 16) | ((uint64_t)(sbo >> 4) << 32) | ((uint64_t)sw << 62);
}
__device__ __forceinline__ void mbar_init(uint32_t bar, uint32_t cnt) { asm volatile("mbarrier.init.shared::cta.b64 [%0], %1;" ::"r"(bar), "r"(cnt) : "memory"); }
__device__ __forceinline__ void mbar_arrive(uint32_t bar) { asm volatile("mbarrier.arrive.shared::cta.b64 _, [%0];" ::"r"(bar) : "memory"); }
__device__ __forceinline__ bool elect_one() {
  uint32_t r; asm volatile("{\n.reg .pred p;\nelect.sync _|p, 0xffffffff;\nselp.u32 %0, 1, 0, p;\n}" : "=r"(r)); return r;
}
__device__ __forceinline__ void mbar_arrive_elect(uint32_t bar) {
  asm volatile("{\n.reg .pred p;\nelect.sync _|p, 0xffffffff;\n@p mbarrier.arrive.shared::cta.b64 _, [%0];\n}" ::"r"(bar) : "memory");
}
__device__ __forceinline__ void mbar_expect(uint32_t bar, uint32_t bytes) { asm volatile("mbarrier.arrive.expect_tx.shared::cta.b64 _, [%0], %1;" ::"r"(bar), "r"(bytes) : "memory"); }
__device__ __forceinline__ void mbar_arrive_remote(uint32_t bar, uint32_t cta) {
  asm volatile("{\n.reg .b32 ra;\nmapa.shared::cluster.u32 ra, %0, %1;\nmbarrier.arrive.shared::cluster.b64 _, [ra];\n}" ::"r"(bar), "r"(cta) : "memory");
}
__device__ __forceinline__ void mbar_wait(uint32_t bar, uint32_t parity) {
  asm volatile("{\n.reg .pred p;\n.reg .b32 n;\nmov.b32 n, 0;\nWL:\nmbarrier.try_wait.parity.shared::cta.b64 p, [%0], %1;\n@p bra WD;\n"
               "add.u32 n, n, 1;\nsetp.lt.u32 p, n, 65536;\n@p bra WL;\nWD:\n}" ::"r"(bar), "r"(parity) : "memory");
}
__device__ __forceinline__ void nb_sync(int id, int n) { asm volatile("bar.sync %0, %1;" ::"r"(id), "r"(n) : "memory"); }
__device__ __forceinline__ void nb_arrive(int id, int n) { asm volatile("bar.arrive %0, %1;" ::"r"(id), "r"(n) : "memory"); }
__device__ __forceinline__ void fence_async() { asm volatile("fence.proxy.async.shared::cta;" ::: "memory"); }
__device__ __forceinline__ void cluster_sync() {
  asm volatile("barrier.cluster.arrive.relaxed.aligned;\nbarrier.cluster.wait.aligned;" ::: "memory");
}
__device__ __forceinline__ uint32_t pack2(float lo, float hi) {
  uint32_t r; asm("cvt.rn.bf16x2.f32 %0, %1, %2;" : "=r"(r) : "f"(hi), "f"(lo)); return r;
}
__device__ __forceinline__ void stsm4(uint32_t a, uint32_t r0, uint32_t r1, uint32_t r2, uint32_t r3) {
  asm volatile("stmatrix.sync.aligned.m8n8.x4.shared.b16 [%0], {%1,%2,%3,%4};" ::"r"(a), "r"(r0), "r"(r1), "r"(r2), "r"(r3) : "memory");
}
__device__ __forceinline__ void ldsm4(uint32_t a, uint32_t& r0, uint32_t& r1, uint32_t& r2, uint32_t& r3) {
  asm volatile("ldmatrix.sync.aligned.m8n8.x4.shared.b16 {%0,%1,%2,%3}, [%4];" : "=r"(r0), "=r"(r1), "=r"(r2), "=r"(r3) : "r"(a) : "memory");
}
__device__ __forceinline__ void sts128(uint32_t a, uint4 v) {
  asm volatile("st.shared.v4.b32 [%0], {%1,%2,%3,%4};" ::"r"(a), "r"(v.x), "r"(v.y), "r"(v.z), "r"(v.w) : "memory");
}
__device__ __forceinline__ float lds_f32(uint32_t a) { float v; asm volatile("ld.shared.f32 %0, [%1];" : "=f"(v) : "r"(a)); return v; }
__device__ __forceinline__ float ex2(float x) { float y; asm("ex2.approx.ftz.f32 %0, %1;" : "=f"(y) : "f"(x)); return y; }

template<int SC> __device__ __forceinline__ void wg_ss144(float (&d)[72], uint64_t da, uint64_t db) {
  asm volatile("{\n.reg .pred p;\nsetp.ne.b32 p, %74, 0;\nwgmma.mma_async.sync.aligned.m64n144k16.f32.bf16.bf16 {%0,%1,%2,%3,%4,%5,%6,%7,%8,%9,%10,%11,%12,%13,%14,%15,%16,%17,%18,%19,%20,%21,%22,%23,%24,%25,%26,%27,%28,%29,%30,%31,%32,%33,%34,%35,%36,%37,%38,%39,%40,%41,%42,%43,%44,%45,%46,%47,%48,%49,%50,%51,%52,%53,%54,%55,%56,%57,%58,%59,%60,%61,%62,%63,%64,%65,%66,%67,%68,%69,%70,%71}, %72, %73, p, 1, 1, 0, 1;\n}\n"
    : "+f"(d[0]),"+f"(d[1]),"+f"(d[2]),"+f"(d[3]),"+f"(d[4]),"+f"(d[5]),"+f"(d[6]),"+f"(d[7]),"+f"(d[8]),"+f"(d[9]),"+f"(d[10]),"+f"(d[11]),"+f"(d[12]),"+f"(d[13]),"+f"(d[14]),"+f"(d[15]),"+f"(d[16]),"+f"(d[17]),"+f"(d[18]),"+f"(d[19]),"+f"(d[20]),"+f"(d[21]),"+f"(d[22]),"+f"(d[23]),"+f"(d[24]),"+f"(d[25]),"+f"(d[26]),"+f"(d[27]),"+f"(d[28]),"+f"(d[29]),"+f"(d[30]),"+f"(d[31]),"+f"(d[32]),"+f"(d[33]),"+f"(d[34]),"+f"(d[35]),"+f"(d[36]),"+f"(d[37]),"+f"(d[38]),"+f"(d[39]),"+f"(d[40]),"+f"(d[41]),"+f"(d[42]),"+f"(d[43]),"+f"(d[44]),"+f"(d[45]),"+f"(d[46]),"+f"(d[47]),"+f"(d[48]),"+f"(d[49]),"+f"(d[50]),"+f"(d[51]),"+f"(d[52]),"+f"(d[53]),"+f"(d[54]),"+f"(d[55]),"+f"(d[56]),"+f"(d[57]),"+f"(d[58]),"+f"(d[59]),"+f"(d[60]),"+f"(d[61]),"+f"(d[62]),"+f"(d[63]),"+f"(d[64]),"+f"(d[65]),"+f"(d[66]),"+f"(d[67]),"+f"(d[68]),"+f"(d[69]),"+f"(d[70]),"+f"(d[71]) : "l"(da), "l"(db), "n"(SC));
}
template<int SC> __device__ __forceinline__ void wg_ss96(float (&d)[48], uint64_t da, uint64_t db) {
  asm volatile("{\n.reg .pred p;\nsetp.ne.b32 p, %50, 0;\nwgmma.mma_async.sync.aligned.m64n96k16.f32.bf16.bf16 {%0,%1,%2,%3,%4,%5,%6,%7,%8,%9,%10,%11,%12,%13,%14,%15,%16,%17,%18,%19,%20,%21,%22,%23,%24,%25,%26,%27,%28,%29,%30,%31,%32,%33,%34,%35,%36,%37,%38,%39,%40,%41,%42,%43,%44,%45,%46,%47}, %48, %49, p, 1, 1, 0, 1;\n}\n"
    : "+f"(d[0]),"+f"(d[1]),"+f"(d[2]),"+f"(d[3]),"+f"(d[4]),"+f"(d[5]),"+f"(d[6]),"+f"(d[7]),"+f"(d[8]),"+f"(d[9]),"+f"(d[10]),"+f"(d[11]),"+f"(d[12]),"+f"(d[13]),"+f"(d[14]),"+f"(d[15]),"+f"(d[16]),"+f"(d[17]),"+f"(d[18]),"+f"(d[19]),"+f"(d[20]),"+f"(d[21]),"+f"(d[22]),"+f"(d[23]),"+f"(d[24]),"+f"(d[25]),"+f"(d[26]),"+f"(d[27]),"+f"(d[28]),"+f"(d[29]),"+f"(d[30]),"+f"(d[31]),"+f"(d[32]),"+f"(d[33]),"+f"(d[34]),"+f"(d[35]),"+f"(d[36]),"+f"(d[37]),"+f"(d[38]),"+f"(d[39]),"+f"(d[40]),"+f"(d[41]),"+f"(d[42]),"+f"(d[43]),"+f"(d[44]),"+f"(d[45]),"+f"(d[46]),"+f"(d[47]) : "l"(da), "l"(db), "n"(SC));
}
template<int SC> __device__ __forceinline__ void wg_rs112(float (&d)[56], uint32_t a0, uint32_t a1, uint32_t a2, uint32_t a3, uint64_t db) {
  asm volatile("{\n.reg .pred p;\nsetp.ne.b32 p, %61, 0;\nwgmma.mma_async.sync.aligned.m64n112k16.f32.bf16.bf16 {%0,%1,%2,%3,%4,%5,%6,%7,%8,%9,%10,%11,%12,%13,%14,%15,%16,%17,%18,%19,%20,%21,%22,%23,%24,%25,%26,%27,%28,%29,%30,%31,%32,%33,%34,%35,%36,%37,%38,%39,%40,%41,%42,%43,%44,%45,%46,%47,%48,%49,%50,%51,%52,%53,%54,%55}, {%56,%57,%58,%59}, %60, p, 1, 1, 0;\n}\n"
    : "+f"(d[0]),"+f"(d[1]),"+f"(d[2]),"+f"(d[3]),"+f"(d[4]),"+f"(d[5]),"+f"(d[6]),"+f"(d[7]),"+f"(d[8]),"+f"(d[9]),"+f"(d[10]),"+f"(d[11]),"+f"(d[12]),"+f"(d[13]),"+f"(d[14]),"+f"(d[15]),"+f"(d[16]),"+f"(d[17]),"+f"(d[18]),"+f"(d[19]),"+f"(d[20]),"+f"(d[21]),"+f"(d[22]),"+f"(d[23]),"+f"(d[24]),"+f"(d[25]),"+f"(d[26]),"+f"(d[27]),"+f"(d[28]),"+f"(d[29]),"+f"(d[30]),"+f"(d[31]),"+f"(d[32]),"+f"(d[33]),"+f"(d[34]),"+f"(d[35]),"+f"(d[36]),"+f"(d[37]),"+f"(d[38]),"+f"(d[39]),"+f"(d[40]),"+f"(d[41]),"+f"(d[42]),"+f"(d[43]),"+f"(d[44]),"+f"(d[45]),"+f"(d[46]),"+f"(d[47]),"+f"(d[48]),"+f"(d[49]),"+f"(d[50]),"+f"(d[51]),"+f"(d[52]),"+f"(d[53]),"+f"(d[54]),"+f"(d[55]) : "r"(a0), "r"(a1), "r"(a2), "r"(a3), "l"(db), "n"(SC));
}
template<int SC> __device__ __forceinline__ void wg_sp48(float (&d)[24], uint32_t a0, uint32_t a1, uint32_t a2, uint32_t a3, uint64_t db, uint32_t meta) {
  asm volatile("{\n.reg .pred p;\nsetp.ne.b32 p, %30, 0;\nwgmma.mma_async.sp.sync.aligned.m64n48k32.f32.bf16.bf16 {%0,%1,%2,%3,%4,%5,%6,%7,%8,%9,%10,%11,%12,%13,%14,%15,%16,%17,%18,%19,%20,%21,%22,%23}, {%24,%25,%26,%27}, %28, %29, 0, p, 1, 1, 1;\n}\n"
    : "+f"(d[0]),"+f"(d[1]),"+f"(d[2]),"+f"(d[3]),"+f"(d[4]),"+f"(d[5]),"+f"(d[6]),"+f"(d[7]),"+f"(d[8]),"+f"(d[9]),"+f"(d[10]),"+f"(d[11]),"+f"(d[12]),"+f"(d[13]),"+f"(d[14]),"+f"(d[15]),"+f"(d[16]),"+f"(d[17]),"+f"(d[18]),"+f"(d[19]),"+f"(d[20]),"+f"(d[21]),"+f"(d[22]),"+f"(d[23]) : "r"(a0), "r"(a1), "r"(a2), "r"(a3), "l"(db), "r"(meta), "n"(SC));
}
template<int SC> __device__ __forceinline__ void wg_ss192(float (&d)[96], uint64_t da, uint64_t db) {
  asm volatile("{\n.reg .pred p;\nsetp.ne.b32 p, %98, 0;\nwgmma.mma_async.sync.aligned.m64n192k16.f32.bf16.bf16 {%0,%1,%2,%3,%4,%5,%6,%7,%8,%9,%10,%11,%12,%13,%14,%15,%16,%17,%18,%19,%20,%21,%22,%23,%24,%25,%26,%27,%28,%29,%30,%31,%32,%33,%34,%35,%36,%37,%38,%39,%40,%41,%42,%43,%44,%45,%46,%47,%48,%49,%50,%51,%52,%53,%54,%55,%56,%57,%58,%59,%60,%61,%62,%63,%64,%65,%66,%67,%68,%69,%70,%71,%72,%73,%74,%75,%76,%77,%78,%79,%80,%81,%82,%83,%84,%85,%86,%87,%88,%89,%90,%91,%92,%93,%94,%95}, %96, %97, p, 1, 1, 0, 1;\n}\n"
    : "+f"(d[0]),"+f"(d[1]),"+f"(d[2]),"+f"(d[3]),"+f"(d[4]),"+f"(d[5]),"+f"(d[6]),"+f"(d[7]),"+f"(d[8]),"+f"(d[9]),"+f"(d[10]),"+f"(d[11]),"+f"(d[12]),"+f"(d[13]),"+f"(d[14]),"+f"(d[15]),"+f"(d[16]),"+f"(d[17]),"+f"(d[18]),"+f"(d[19]),"+f"(d[20]),"+f"(d[21]),"+f"(d[22]),"+f"(d[23]),"+f"(d[24]),"+f"(d[25]),"+f"(d[26]),"+f"(d[27]),"+f"(d[28]),"+f"(d[29]),"+f"(d[30]),"+f"(d[31]),"+f"(d[32]),"+f"(d[33]),"+f"(d[34]),"+f"(d[35]),"+f"(d[36]),"+f"(d[37]),"+f"(d[38]),"+f"(d[39]),"+f"(d[40]),"+f"(d[41]),"+f"(d[42]),"+f"(d[43]),"+f"(d[44]),"+f"(d[45]),"+f"(d[46]),"+f"(d[47]),"+f"(d[48]),"+f"(d[49]),"+f"(d[50]),"+f"(d[51]),"+f"(d[52]),"+f"(d[53]),"+f"(d[54]),"+f"(d[55]),"+f"(d[56]),"+f"(d[57]),"+f"(d[58]),"+f"(d[59]),"+f"(d[60]),"+f"(d[61]),"+f"(d[62]),"+f"(d[63]),"+f"(d[64]),"+f"(d[65]),"+f"(d[66]),"+f"(d[67]),"+f"(d[68]),"+f"(d[69]),"+f"(d[70]),"+f"(d[71]),"+f"(d[72]),"+f"(d[73]),"+f"(d[74]),"+f"(d[75]),"+f"(d[76]),"+f"(d[77]),"+f"(d[78]),"+f"(d[79]),"+f"(d[80]),"+f"(d[81]),"+f"(d[82]),"+f"(d[83]),"+f"(d[84]),"+f"(d[85]),"+f"(d[86]),"+f"(d[87]),"+f"(d[88]),"+f"(d[89]),"+f"(d[90]),"+f"(d[91]),"+f"(d[92]),"+f"(d[93]),"+f"(d[94]),"+f"(d[95]) : "l"(da), "l"(db), "n"(SC));
}

constexpr uint32_t SBC = 1024;
constexpr int ROWB = 2 * 224 * 384;
constexpr int TB = 11;
constexpr int KS = 832;
constexpr int KSLOT = 22 * KS;
constexpr int SM_X1 = 0;
constexpr int SM_X2 = SM_X1 + 24576;
constexpr int SM_X0 = SM_X2 + 24576;
constexpr int SM_W = SM_X0 + 18432;
constexpr int SM_K = SM_W + 55296;
constexpr int SM_V = SM_K + 2 * KSLOT;
constexpr int SM_Q = SM_V + 22 * 1536;
constexpr int SM_O = SM_Q + 24576;
constexpr int SM_RPB = SM_O + 12288;
constexpr int SM_BAR = SM_RPB + 768;
constexpr int SM_A_TOTAL = SM_BAR + 256;
constexpr int SM_TWO = SM_X1;
constexpr int SM_TST = SM_TWO + 36864;
constexpr int SM_TIN = SM_X0;
enum { B_FULL = 0, B_EMPTY = 3, B_TIN = 6, B_TFREE = 9, B_WK, B_WQ, B_WO, B_Q0, B_ODONE, B_KFREE = B_ODONE + 2, B_VFREE, B_COUNT };
enum { N_KRDY = 4, N_QK0, N_QK1, N_VQ0, N_VQ1, N_PVISS };

#define SPL 4
#define RA 152
#define RG 184
__device__ int g_flags[TB * 56];

#define TR(role, it, k)
#define TRDECL
#define TRARG
#define TRPASS
#define TRDUMP
#define TRB(it, k)
#define TR2(blk, k)

struct GemmCtx {
  uint32_t bar;
  uint32_t kC, vC, qC;
  uint32_t kH, vH;
  bool hvalid;
};

template <int STRIDE> __device__ __forceinline__ void dump12(uint32_t a, const uint32_t (&r)[12]) {
#pragma unroll
  for (int j = 0; j < 3; j++) stsm4(a + j * 2 * STRIDE, r[4 * j], r[4 * j + 1], r[4 * j + 2], r[4 * j + 3]);
}
template <int N> __device__ __forceinline__ void pack12(uint32_t (&r)[12], const float (&d)[N], int off) {
#pragma unroll
  for (int j = 0; j < 12; j++) r[j] = pack2(d[off + 2 * j], d[off + 2 * j + 1]);
}
template <int XS, int K0, int K1> __device__ __forceinline__ void issue_core(float (&d)[72]) {
  constexpr uint64_t da = mkdesc(SBC + XS, 16, 1024, 1), db = mkdesc(SBC + SM_W, 6144, 256, 3);
  wg_fence();
  if (K0 == 0) wg_ss144<0>(d, da, db);
#pragma unroll
  for (int k = K0 ? K0 : 1; k < K1; k++) wg_ss144<1>(d, da + (k >> 2) * 512 + (k & 3) * 2, db + k * 32);
  wg_commit();
}
template <int K0, int K1> __device__ __forceinline__ void issue_halo(float (&d)[48]) {
  constexpr uint64_t da = mkdesc(SBC + SM_X0 - 2048, 16, 1024, 1), db = mkdesc(SBC + SM_W, 6144, 256, 3);
  wg_fence();
  if (K0 == 0) wg_ss96<0>(d, da, db);
#pragma unroll
  for (int k = K0 ? K0 : 1; k < K1; k++) wg_ss96<1>(d, da + (k >> 2) * 384 + (k & 3) * 2, db + k * 32);
  wg_commit();
}
template <int ST, int BYTES> __device__ __forceinline__ void release_stage(const GemmCtx& c, bool on) {
  asm volatile("{\n.reg .pred p, q;\n.reg .b32 ra;\nsetp.ne.b32 q, %2, 0;\nelect.sync _|p, 0xffffffff;\nand.pred p, p, q;\n"
               "mapa.shared::cluster.u32 ra, %1, %4;\n"
               "@p mbarrier.arrive.expect_tx.shared::cta.b64 _, [%0], %3;\n@p mbarrier.arrive.shared::cluster.b64 _, [ra];\n}"
               ::"r"(c.bar + (B_FULL + ST) * 8), "r"(c.bar + (B_EMPTY + ST) * 8), "r"((int)on), "n"(BYTES / 4), "n"(ST) : "memory");
}
__device__ __forceinline__ void load_w(const CUtensorMap* m, uint32_t dst, uint32_t bar, int col) {
  asm volatile("cp.async.bulk.tensor.2d.shared::cluster.global.mbarrier::complete_tx::bytes [%0], [%1, {%3,%4}], [%2];"
               ::"r"(dst), "l"(m), "r"(bar), "r"(col), "r"(0) : "memory");
}
template <int BYTES> __device__ __forceinline__ void send_o(uint32_t dst, uint32_t src, uint32_t bar, int cta) {
  asm volatile("{\n.reg .b32 rd, rb;\nmapa.shared::cluster.u32 rd, %0, %3;\nmapa.shared::cluster.u32 rb, %2, %3;\n"
               "cp.async.bulk.shared::cluster.shared::cta.mbarrier::complete_tx::bytes [rd], [%1], %4, [rb];\n}"
               ::"r"(dst), "r"(src), "r"(bar), "r"(cta), "n"(BYTES) : "memory");
}
__device__ __forceinline__ void publish(uint32_t bar) {
  fence_async();
  __syncwarp();
  mbar_arrive_elect(bar);
}

template <bool FIRST, bool LAST>
__device__ __forceinline__ void gemm_iter(const GemmCtx& c, int b, uint32_t (&pk)[12], uint32_t (&pv)[12], uint32_t (&pq)[12] TRARG) {
  const uint32_t bar = c.bar;
  const uint32_t pa = b & 1;
  const bool w = b >= 0;
  const uint32_t ko = pa * KSLOT, vx = pa * 16, qx = pa * 128;
  float H[48], C[72];
  uint32_t hk[12], hv[12], pv2[12];
  TR(2, b, 0);
  if (FIRST) mbar_wait(bar + (B_FULL + 0) * 8, pa);
  if (w) nb_sync(N_QK1, 256);
  TR(2, b, 2);
  issue_halo<0, 8>(H);
  TR(2, b, 3);
  if (!FIRST) {
    if (w) mbar_wait(bar + B_KFREE * 8, pa);
    dump12<128>(c.kC + ko, pk);
  }
  issue_halo<8, 12>(H);
  TR(2, b, 4);
  if (!LAST) {
    mbar_wait(bar + (B_FULL + 2) * 8, pa);
    if (FIRST) mbar_wait(bar + B_WQ * 8, 0);
    TR(2, b, 13);
    issue_core<SM_X2, 0, 8>(C);
    TR(2, b, 5);
    if (!FIRST) { fence_async(); dump12<256>(c.qC ^ (qx ^ 192), pq); }
    wg_wait<1>(); pin(H);
    release_stage<0, 18432>(c, true);
  } else {
    dump12<256>(c.qC ^ (qx ^ 192), pq);
    fence_async();
    nb_arrive(N_VQ0, 256); nb_arrive(N_VQ1, 256);
    wg_wait<0>(); pin(H);
    uint32_t ln; asm volatile("mov.u32 %0, %%laneid;" : "=r"(ln));
    if (ln < 4) mbar_arrive_remote(bar + B_TFREE * 8, ln);
  }
  pack12(hk, H, 0);
  if (c.hvalid) dump12<128>(c.kH + ko, hk);
  pack12(hv, H, 24);
  if (!LAST) {
    issue_core<SM_X2, 8, 12>(C);
    if (w) { nb_arrive(N_VQ0, 288); nb_arrive(N_VQ1, 288); }
    else if (!FIRST) { __syncwarp(); mbar_arrive_elect(bar + B_Q0 * 8); }
    mbar_wait(bar + (B_FULL + 1) * 8, pa);
    TR(2, b, 6);
    wg_wait<0>(); pin(C);
    TR(2, b, 7);
    pack12(pk, C, 0);
    dump12<128>(c.kC + ko + 64, pk);
    release_stage<2, 24576>(c, b < 11);
    pack12(pv2, C, 24);
    pack12(pq, C, 48);
    TR(2, b, 8);
    issue_core<SM_X1, 0, SPL>(C);
    if (w) nb_sync(N_PVISS, 384);
    issue_core<SM_X1, SPL, 8>(C);
    TR(2, b, 9);
  }
  if (!FIRST) fence_async();
  TR(2, b, 14);
  if (!LAST) issue_core<SM_X1, 8, 12>(C);
  if (!FIRST) nb_arrive(N_KRDY, 256);
  TR(2, b, 1);
  if (!LAST) mbar_wait(bar + (B_FULL + 0) * 8, pa ^ 1);
  if (w) mbar_wait(bar + B_VFREE * 8, pa);
  TR(2, b, 10);
  if (!FIRST) dump12<128>(c.vC ^ vx, pv);
  if (!LAST) dump12<256>(c.qC ^ qx, pq);
  if (c.hvalid) dump12<128>(c.vH ^ vx, hv);
  if (LAST) { fence_async(); nb_arrive(N_VQ0, 256); nb_arrive(N_VQ1, 256); return; }
  dump12<128>((c.vC ^ vx ^ 16) + 768, pv2);
  TR(2, b, 11);
  wg_wait<0>(); pin(C);
  TR(2, b, 12);
  release_stage<1, 24576>(c, b < 11);
  pack12(pk, C, 0);
  pack12(pv, C, 24);
  pack12(pq, C, 48);
}

__device__ __forceinline__ float fold(float a, float b, float t, int useb) {
  float r;
  asm("{\n.reg .pred p;\nsetp.ne.b32 p, %4, 0;\nfma.rn.f32 %0, %1, 0f3E553B95, %3;\n@p fma.rn.f32 %0, %2, 0f3E553B95, %3;\n}"
      : "=&f"(r) : "f"(a), "f"(b), "f"(t), "r"(useb));
  return r;
}
template <int U, int L>
__device__ __forceinline__ void softmax_tile(const float (&SA)[56], const float (&SB)[56], const float (&T)[16], int b0, int b1,
                                             uint32_t (&P)[28], float (&sx)[8]) {
  float lu[14], ll[14];
#pragma unroll
  for (int j = 0; j < 7; j++) {
    constexpr int sh = U == L ? 2 : 0;
    const float tu0 = T[2 * j + sh], tu1 = T[2 * j + 1 + sh], tl0 = T[2 * j], tl1 = T[2 * j + 1];
    lu[2 * j]     = fold(SA[4 * (U + j)],     SB[4 * (U + j)],     tu0, b0);
    ll[2 * j]     = fold(SA[4 * (L + j) + 2], SB[4 * (L + j) + 2], tl0, b0);
    lu[2 * j + 1] = fold(SA[4 * (U + j) + 1], SB[4 * (U + j) + 1], tu1, b1);
    ll[2 * j + 1] = fold(SA[4 * (L + j) + 3], SB[4 * (L + j) + 3], tl1, b1);
  }
  float mu = lu[0], ml = ll[0], mu2 = lu[1], ml2 = ll[1];
#pragma unroll
  for (int j = 1; j < 7; j++) { mu = fmaxf(mu, lu[2 * j]); mu2 = fmaxf(mu2, lu[2 * j + 1]); ml = fmaxf(ml, ll[2 * j]); ml2 = fmaxf(ml2, ll[2 * j + 1]); }
  mu = fmaxf(mu, mu2); ml = fmaxf(ml, ml2);
  { const float a1 = __shfl_xor_sync(0xffffffffu, mu, 1), a2 = __shfl_xor_sync(0xffffffffu, mu, 2), a3 = __shfl_xor_sync(0xffffffffu, mu, 3);
    const float c1 = __shfl_xor_sync(0xffffffffu, ml, 1), c2 = __shfl_xor_sync(0xffffffffu, ml, 2), c3 = __shfl_xor_sync(0xffffffffu, ml, 3);
    mu = fmaxf(fmaxf(mu, a1), fmaxf(a2, a3)); ml = fmaxf(fmaxf(ml, c1), fmaxf(c2, c3)); }
  float su = 0.f, sl = 0.f;
#pragma unroll
  for (int c = 0; c < 14; c++) {
    const int iu = (c >> 1) * 4 + (c & 1) * 2;
    if (c >= U && c < U + 7) {
      float e0 = ex2(lu[2 * (c - U)] - mu), e1 = ex2(lu[2 * (c - U) + 1] - mu);
      su = c == U ? e0 + e1 : (su + e0) + e1; P[iu] = pack2(e0, e1);
    } else P[iu] = 0u;
    if (c >= L && c < L + 7) {
      float e0 = ex2(ll[2 * (c - L)] - ml), e1 = ex2(ll[2 * (c - L) + 1] - ml);
      sl = c == L ? e0 + e1 : (sl + e0) + e1; P[iu + 1] = pack2(e0, e1);
    } else P[iu + 1] = 0u;
  }
  sx[0] = su; sx[4] = sl;
#pragma unroll
  for (int k = 1; k < 4; k++) { sx[k] = __shfl_xor_sync(0xffffffffu, su, k); sx[4 + k] = __shfl_xor_sync(0xffffffffu, sl, k); }
}

struct Maps { CUtensorMap xc, xh, w, os, wo, ot; };

__global__ void __cluster_dims__(4, 1, 1) __launch_bounds__(512, 1)
na_attn_kernel(const __grid_constant__ Maps mp, const __nv_bfloat16* __restrict__ wqkv, const __nv_bfloat16* __restrict__ rpb) {
  extern __shared__ __align__(1024) uint8_t smem_raw[];
  const uint32_t sb = smem_u32(smem_raw);
  if ((sb & 0x3FFFF) != SBC) return;
  const uint32_t bar = sb + SM_BAR;
  TR2(blockIdx.x, 0);
  const int tid = threadIdx.x, lane = tid & 31;
  const int warp = __shfl_sync(0xffffffffu, tid >> 5, 0);
  const int head = blockIdx.x & 3, cl = blockIdx.x >> 2;
  const int par = cl / 7, strip = cl - par * 7, ph = par >> 1, pw = par & 1;

  uint4 wv[3];
  const int wr = tid / 6, wc = tid - wr * 6;
  if (warp < 12) {
#pragma unroll
    for (int i = 0; i < 3; i++) wv[i] = __ldg(reinterpret_cast<const uint4*>(wqkv + (wr + i * 64) * 576 + 384 + head * 48 + wc * 8));
  } else if (elect_one()) {
    if (warp == 12) {
      mbar_init(bar + B_WK * 8, 1);
#pragma unroll
      for (int i = 0; i < 3; i++) load_w(&mp.w, sb + SM_W + i * 6144, bar + B_WK * 8, 192 + head * 48 + i * 16);
      mbar_expect(bar + B_WK * 8, 18432);
    } else if (warp == 13) {
#pragma unroll
      for (int i = 0; i < B_WK; i++) mbar_init(bar + i * 8, i < B_EMPTY ? 4 : (i < B_TIN ? 16 : (i < B_TFREE ? 1 : 16)));
    } else if (warp == 14) {
#pragma unroll
      for (int i = B_WQ; i < B_COUNT; i++) mbar_init(bar + i * 8, i < B_Q0 ? 1 : (i < B_KFREE ? 4 : 8));
    }
    asm volatile("fence.mbarrier_init.release.cluster;" ::: "memory");
  }
  __syncwarp();
  asm volatile("barrier.cluster.arrive.relaxed.aligned;" ::: "memory");

  if (warp >= 12) {
    asm volatile("setmaxnreg.dec.sync.aligned.u32 24;");
    asm volatile("griddepcontrol.launch_dependents;");
    const int cc = ph * 112 + (head ? strip * 16 : (strip == 0 ? 16 : (strip == 6 ? 74 : strip * 16 - 3)));
    const int sd = strip == 0 ? -1 : (strip == 6 ? 1 : 0);
    const int r0 = head == 0 ? -4 : (head == 1 ? 4 : 0);
    asm volatile("barrier.cluster.wait.aligned;" ::: "memory");
    if (warp == 12) {
      const uint32_t fb = bar + (B_FULL + head) * 8, eb = bar + (B_EMPTY + head) * 8;
      const uint32_t dst = sb + (head == 0 ? SM_X0 : (head == 1 ? SM_X1 : SM_X2));
      const int nl = head == 0 ? 15 : (head == 3 ? 1 : 14);
#pragma unroll 1
      for (int n = 0; n < nl; n++) {
        if (n) mbar_wait(eb, (n - 1) & 1);
        if (elect_one()) {
          if (head == 0) {
            asm volatile("cp.async.bulk.tensor.5d.shared::cluster.global.mbarrier::complete_tx::bytes.multicast::cluster [%0], [%1, {%3,%4,%5,%6,%7}], [%2], %8;"
                         ::"r"(dst), "l"(&mp.xh), "r"(fb), "r"(0), "r"(8 * n + r0), "r"(cc), "r"(sd), "r"(pw * 3), "h"((uint16_t)15) : "memory");
            if (n + 1 < nl) asm volatile("cp.async.bulk.prefetch.tensor.5d.L2.global [%0, {%1,%2,%3,%4,%5}];" ::"l"(&mp.xh), "r"(0), "r"(8 * n + 8 + r0), "r"(cc), "r"(sd), "r"(pw * 3) : "memory");
          } else if (head < 3) {
            asm volatile("cp.async.bulk.tensor.4d.shared::cluster.global.mbarrier::complete_tx::bytes.multicast::cluster [%0], [%1, {%3,%4,%5,%6}], [%2], %7;"
                         ::"r"(dst), "l"(&mp.xc), "r"(fb), "r"(0), "r"(8 * n + r0), "r"(cc), "r"(pw * 3), "h"((uint16_t)15) : "memory");
          }
          if (n == 0) {
#pragma unroll
            for (int i = 0; i < 3; i++) load_w(&mp.w, sb + SM_W + (6 + i) * 6144, bar + B_WQ * 8, head * 48 + i * 16);
            mbar_expect(bar + B_WQ * 8, 18432);
            mbar_expect(bar + B_TIN * 8, 24576); mbar_expect(bar + (B_TIN + 1) * 8, 24576); mbar_expect(bar + (B_TIN + 2) * 8, 24576);
          }
          if (head && n + 1 < nl) asm volatile("cp.async.bulk.prefetch.tensor.4d.L2.global [%0, {%1,%2,%3,%4}];" ::"l"(&mp.xc), "r"(0), "r"(8 * n + 8 + r0), "r"(cc), "r"(pw * 3) : "memory");
        }
        __syncwarp();
      }
    }
    if (warp >= 14) {
      const int j = warp - 14;
      int* flag = g_flags + cl * 2 + j;
      nb_arrive(N_VQ0 + j, 288);
      TRDECL;
#pragma unroll 1
      for (int b = 0; b < TB; b++) {
        TR(2, b, 0);
        mbar_wait(bar + (B_ODONE + j) * 8, b & 1);
        TR(2, b, 1);
        if (lane == 0) {
          asm volatile("cp.async.bulk.tensor.3d.global.shared::cta.bulk_group [%0, {%2,%3,%4}], [%1];"
                       ::"l"(&mp.os), "r"(sb + SM_O + j * 6144), "r"(pw * 192), "r"(8 * b + 2 * head), "r"(ph * 112 + strip * 16 + 8 * j) : "memory");
          asm volatile("cp.async.bulk.commit_group;\ncp.async.bulk.wait_group.read 0;" ::: "memory");
        }
        __syncwarp();
        nb_arrive(N_VQ0 + j, 288);
        TR(2, b, 2);
        if (lane == 0) {
          asm volatile("cp.async.bulk.wait_group 0;" ::: "memory");
          TR(2, b, 3);
          asm volatile("fence.proxy.async.global;" ::: "memory");
          TR(2, b, 4);
          asm volatile("red.release.gpu.global.add.s32 [%0], 1;" ::"l"(flag + b * 56) : "memory");
          TR(2, b, 5);
        }
        __syncwarp();
      }
      TRDUMP;
      mbar_wait(bar + (B_ODONE + j) * 8, TB & 1);
      mbar_wait(bar + B_TFREE * 8, 0);
      if (elect_one()) {
#pragma unroll
        for (int d = 0; d < 4; d++) send_o<3072>(sb + SM_TIN + head * 6144 + j * 3072, sb + SM_O + j * 6144 + (d >> 1) * 3072, bar + B_TIN * 8, d);
      }
      __syncwarp();
    }
    cluster_sync();
  } else if (warp >= 8) {
    asm volatile("setmaxnreg.inc.sync.aligned.u32 %0;" ::"n"(RG));
    GemmCtx c;
    c.bar = bar;
    const int gw = warp - 8, tk = gw * 16 + (lane & 15), hi = lane >> 4;
    { const int col = tk >> 2, i = tk & 3;
      c.kC = sb + SM_K + (col + 3) * KS + hi * 128 + i * 16;
      c.vC = sb + SM_V + (col + 3) * 1536 + hi * 128 + (2 * i + ((col + 3) & 1)) * 16;
      c.qC = sb + SM_Q + col * 1536 + hi * 256 + (col & 1) * 64 + i * 16; }
    { const int ci = (tk >> 3) - 2, kc = ci < 3 ? ci : ci + 16, i = tk & 7; c.hvalid = gw > 0;
      c.kH = sb + SM_K + kc * KS + hi * 128 + i * 16;
      c.vH = sb + SM_V + kc * 1536 + hi * 128 + (i >> 2) * 768 + (2 * (i & 3) + ((kc ^ (i >> 2)) & 1)) * 16; }
    asm volatile("barrier.cluster.wait.aligned;" ::: "memory");
    if (elect_one()) { mbar_expect(bar + B_FULL * 8, 4608); mbar_expect(bar + (B_FULL + 1) * 8, 6144); mbar_expect(bar + (B_FULL + 2) * 8, 6144); }
    __syncwarp();
#pragma unroll
    for (int i = 0; i < 3; i++) sts128(sb + SM_W + (3 + (wc >> 1)) * 6144 + (wr + i * 64) * 32 + ((wc ^ (wr >> 2)) & 1) * 16, wv[i]);
    fence_async();
    asm volatile("bar.sync 1, 384;" ::: "memory");
    mbar_wait(bar + B_WK * 8, 0);
    uint32_t pk[12], pv[12], pq[12];
    TRDECL;
    gemm_iter<true, false>(c, -2, pk, pv, pq TRPASS);
#pragma unroll 1
    for (int b = -1; b < 12; b++) gemm_iter<false, false>(c, b, pk, pv, pq TRPASS);
    asm volatile("bar.sync 2, 128;" ::: "memory");
    if (gw == 0 && elect_one()) {
      mbar_expect(bar + B_WO * 8, 36864);
      asm volatile("cp.async.bulk.tensor.3d.shared::cluster.global.mbarrier::complete_tx::bytes [%0], [%1, {%3,%4,%5}], [%2];"
                   ::"r"(sb + SM_TWO), "l"(&mp.wo), "r"(bar + B_WO * 8), "r"(0), "r"(0), "r"((head & 1) * 3) : "memory");
    }
    __syncwarp();
    gemm_iter<false, true>(c, 12, pk, pv, pq TRPASS);
    TR(2, 13, 0);
    mbar_wait(bar + B_WO * 8, 0);
    TR(2, 13, 1);
    const uint32_t st = sb + SM_TST + gw * 3072;
    const uint32_t sta = st + (lane & 15) * 64 + ((hi ^ ((lane >> 1) & 3)) * 16);
#pragma unroll 1
    for (int i = 0; i < 3; i++) {
      constexpr uint64_t db = mkdesc(SBC + SM_TWO, 12288, 512, 2);
      const uint64_t da = mkdesc(SBC + SM_TIN, 128, 768, 0) + i * (24576 / 16);
      float D[48];
      mbar_wait(bar + (B_TIN + i) * 8, 0);
      if (i == 2) asm volatile("barrier.cluster.arrive.relaxed.aligned;" ::: "memory");
      else nb_sync(i ? N_PVISS : N_QK1, i ? 384 : 256);
      TR(2, 13 - i, 2); TR(2, 12 + i, 5); TR(2, 11 + i, 9);
      wg_fence();
      wg_ss96<0>(D, da, db);
#pragma unroll
      for (int k = 1; k < 12; k++) wg_ss96<1>(D, da + (k / 3) * 384 + (k % 3) * 16, db + k * 64);
      wg_commit();
      if (lane == 0) asm volatile("cp.async.bulk.wait_group.read 0;" ::: "memory");
      __syncwarp();
      wg_wait<0>(); pin(D);
      TR(2, 13 - i, 3); TR(2, 12 + i, 6); TR(2, 11 + i, 10);
#pragma unroll
      for (int q = 0; q < 6; q++)
        stsm4((sta ^ ((q & 1) * 32)) + (q >> 1) * 1024,
              pack2(D[8 * q], D[8 * q + 1]), pack2(D[8 * q + 2], D[8 * q + 3]), pack2(D[8 * q + 4], D[8 * q + 5]), pack2(D[8 * q + 6], D[8 * q + 7]));
      fence_async();
      __syncwarp();
      if (lane == 0) {
        asm volatile("cp.async.bulk.tensor.4d.global.shared::cta.bulk_group [%0, {%2,%3,%4,%5}], [%1];"
                     ::"l"(&mp.ot), "r"(st), "r"(0), "r"(8 * (TB + i)), "r"(ph * 112 + strip * 16 + 8 * (gw >> 1) + 4 * (head >> 1) + 2 * (gw & 1)), "r"(pw * 6 + (head & 1) * 3) : "memory");
        asm volatile("cp.async.bulk.commit_group;" ::: "memory");
      }
      TR(2, 13 - i, 4); TR(2, 12 + i, 7); TR(2, 11 + i, 11);
    }
    if (lane == 0) asm volatile("cp.async.bulk.wait_group.read 0;" ::: "memory");
    __syncwarp();
    TR(2, 13, 8);
    TR2(blockIdx.x, 2);
    TRDUMP;
    asm volatile("barrier.cluster.wait.aligned;" ::: "memory");
  } else {
    asm volatile("setmaxnreg.inc.sync.aligned.u32 %0;" ::"n"(RA));
    float rv = -INFINITY;
    if (tid < 169) rv = __bfloat162float(rpb[head * 169 + tid]) * 1.4426950408889634f;
    if (tid < 192) {
      const int kc = (wr & 15) + 3;
      sts128(tid < 96 ? sb + SM_K + kc * KS + wc * 128 + 48 : sb + SM_V + kc * 1536 + wc * 128 + (6 + (kc & 1)) * 16, make_uint4(0, 0, 0, 0));
    }
#pragma unroll
    for (int i = 0; i < 3; i++) sts128(sb + SM_W + (3 + (wc >> 1)) * 6144 + (wr + i * 64) * 32 + ((wc ^ (wr >> 2)) & 1) * 16, wv[i]);
    fence_async();
    asm volatile("bar.arrive 1, 384;" ::: "memory");
    if (tid < 182) asm volatile("st.shared.f32 [%0], %1;" ::"r"(sb + SM_RPB + tid * 4), "f"(rv) : "memory");
    const int j = warp >> 2, w = warp & 3;
    int variant = w;
    if (strip == 0 && j == 0 && w < 2) variant = 4;
    if (strip == 6 && j == 1 && w >= 2) variant = 5;
    const uint32_t qa = sb + SM_Q + (8 * j + 2 * w + ((lane >> 3) & 1)) * 1536 + (lane >> 4) * 256 + (((lane & 7) * 16) ^ (((lane >> 3) & 1) * 64));
    uint32_t oa = sb + SM_O + j * 6144 + (2 * w + ((lane >> 3) & 1)) * 768 + (lane >> 4) * 128 + (lane & 7) * 16;
    const uint64_t dK = mkdesc(SBC + SM_K, 128, KS, 0) + j * (8 * KS / 16);
    const uint64_t dV = mkdesc(SBC + SM_V, 768, 128, 0) + j * (8 * 1536 / 16);
    asm volatile("barrier.cluster.wait.aligned;" ::: "memory");
    asm volatile("bar.sync 3, 256;" ::: "memory");
    float T[16];
    TRDECL;
    int b0 = 0, b1 = 0;
    uint32_t meta = 0;
    uint32_t q[12];
    mbar_wait(bar + B_Q0 * 8, 0);
#pragma unroll
    for (int k = 0; k < 3; k++) ldsm4(qa + k * 512, q[4 * k], q[4 * k + 1], q[4 * k + 2], q[4 * k + 3]);
#pragma unroll 1
    for (int b = 0; b < 14; b++) {
      const uint32_t pa = b & 1;
      float SA[56], SB[56];
      const uint64_t dA = dK + pa * (KSLOT >> 4), dB = dK + (pa ^ 1) * (KSLOT >> 4);
      TR(0, b, 0);
      nb_sync(N_KRDY + j, 256);
      TR(0, b, 1);
      TR(0, b - 1, 9);
      wg_fence();
      wg_rs112<0>(SA, q[0], q[1], q[2], q[3], dA);
      wg_rs112<0>(SB, q[0], q[1], q[2], q[3], dB);
      wg_rs112<1>(SA, q[4], q[5], q[6], q[7], dA + 16);
      wg_rs112<1>(SB, q[4], q[5], q[6], q[7], dB + 16);
      wg_rs112<1>(SA, q[8], q[9], q[10], q[11], dA + 32);
      wg_rs112<1>(SB, q[8], q[9], q[10], q[11], dB + 32);
      wg_commit();
      nb_arrive(N_QK0 + j, 256);
      TR(0, b, 2);
      if (b <= 1 || b == 13) {
        uint32_t ln; asm volatile("mov.u32 %0, %%laneid;" : "=r"(ln));
        const int g = ln >> 2, t = ln & 3;
        const int sw = b == 0 ? max(g + 1, 4) : (b == 13 ? min(g + 1, 5) : g + 1);
        const int i0 = 2 * t, i1 = 2 * t + 1;
        b0 = i0 <= sw - 2; b1 = i1 <= sw - 2;
        const uint32_t tb = sb + SM_RPB + (variant < 4 ? 3 : variant + 1 - 2 * w) * 4;
        const uint32_t ra0 = tb + (i0 == sw - 1 ? 13 : i0 + 8 * b0 - g + 2) * 52;
        const uint32_t ra1 = tb + (i1 == sw - 1 ? 13 : i1 + 8 * b1 - g + 2) * 52;
#pragma unroll
        for (int jj = 0; jj < 8; jj++) { T[2 * jj] = lds_f32(ra0 + jj * 4); T[2 * jj + 1] = lds_f32(ra1 + jj * 4); }
        meta = ((0x5555u & ((1u << (2 * (sw - 1))) - 1)) ^ 0xDD88u ^ (((t ^ b) & 1) ? 0x5555u : 0u)) * 0x10001u;
      } else meta ^= 0x55555555u;
      if (b >= 12) oa += b == 12 ? SM_Q - SM_O + warp * 1536 : 1536;
      wg_wait<0>(); pin(SA); pin(SB);
      mbar_arrive_elect(bar + B_KFREE * 8);
      TR(0, b, 3);
      TR(0, b - 1, 10);
      uint32_t P[28];
      float sx[8];
      switch (variant) {
        case 0: softmax_tile<0, 1>(SA, SB, T, b0, b1, P, sx); break;
        case 1: softmax_tile<2, 3>(SA, SB, T, b0, b1, P, sx); break;
        case 2: softmax_tile<4, 5>(SA, SB, T, b0, b1, P, sx); break;
        case 3: softmax_tile<6, 7>(SA, SB, T, b0, b1, P, sx); break;
        case 4: softmax_tile<3, 3>(SA, SB, T, b0, b1, P, sx); break;
        default: softmax_tile<4, 4>(SA, SB, T, b0, b1, P, sx); break;
      }
      float O[24];
      TR(0, b, 4);
      nb_sync(N_VQ0 + j, b >= 12 ? 256 : 288);
      TR(0, b, 5);
#pragma unroll
      for (int k = 0; k < 3; k++) ldsm4(qa + (pa ^ 1) * 128 + k * 512, q[4 * k], q[4 * k + 1], q[4 * k + 2], q[4 * k + 3]);
      wg_fence();
      wg_sp48<0>(O, P[0], P[1], P[2], P[3], dV, meta);
#pragma unroll
      for (int s = 1; s < 7; s++) wg_sp48<1>(O, P[4 * s], P[4 * s + 1], P[4 * s + 2], P[4 * s + 3], dV + s * 192, meta);
      wg_commit();
      if (b != 12) nb_arrive(N_PVISS, 384);
      TR(0, b, 6);
      wg_wait<0>(); pin(O);
      mbar_arrive_elect(bar + B_VFREE * 8);
      TR(0, b, 7);
      float ru, rl;
      asm("rcp.approx.ftz.f32 %0, %1;" : "=f"(ru) : "f"(((fmaf(O[0], 0.f, sx[0]) + sx[1]) + sx[2]) + sx[3]));
      asm("rcp.approx.ftz.f32 %0, %1;" : "=f"(rl) : "f"(((fmaf(O[2], 0.f, sx[4]) + sx[5]) + sx[6]) + sx[7]));
#pragma unroll
      for (int i = 0; i < 3; i++)
        stsm4(oa + i * 256, pack2(O[8 * i] * ru, O[8 * i + 1] * ru), pack2(O[8 * i + 2] * rl, O[8 * i + 3] * rl),
              pack2(O[8 * i + 4] * ru, O[8 * i + 5] * ru), pack2(O[8 * i + 6] * rl, O[8 * i + 7] * rl));
      if (b < 12) publish(bar + (B_ODONE + j) * 8);
      else {
        fence_async();
        if (b == 12) mbar_wait(bar + B_TFREE * 8, 0);
        __syncwarp();
        if (elect_one()) {
#pragma unroll
          for (int d = 0; d < 2; d++)
            send_o<1536>(sb + SM_TIN + (b - TB) * 24576 + head * 6144 + (2 * j + (w & 1)) * 1536, sb + SM_Q + warp * 3072 + (b - 12) * 1536,
                         bar + (B_TIN + b - TB) * 8, (w & 2) + d);
        }
        __syncwarp();
      }
      TR(0, b, 8);
    }
    TRDUMP;
    cluster_sync();
  }
}

constexpr int NSTB = 6;
constexpr int NTB = TB * 56;
constexpr int SM_B_IN = 0;
constexpr int SM_B_W = SM_B_IN + NSTB * 24576;
constexpr int SM_B_BAR = SM_B_W + 73728;
constexpr int SM_B_TOTAL = SM_B_BAR + 128;
struct MapsB { CUtensorMap oi, oo, wo; };

__global__ void __launch_bounds__(480, 1)
na_proj_kernel(const __grid_constant__ MapsB mp) {
  extern __shared__ __align__(1024) uint8_t smem_raw[];
  const uint32_t sb = smem_u32(smem_raw);
  if ((sb & 0x3FFFF) != SBC) return;
  const uint32_t bar = sb + SM_B_BAR;
  const int tid = threadIdx.x, lane = tid & 31;
  const int warp = __shfl_sync(0xffffffffu, tid >> 5, 0);
  TR2(132 + blockIdx.x, 0);
  TRB(47, 0);
  if (warp == 12 && elect_one()) {
#pragma unroll
    for (int i = 0; i <= 2 * NSTB; i++) mbar_init(bar + i * 8, i < NSTB || i == 2 * NSTB ? 1 : 4);
    mbar_expect(bar + 2 * NSTB * 8, 73728);
#pragma unroll
    for (int i = 0; i < 2; i++)
      asm volatile("cp.async.bulk.tensor.3d.shared::cluster.global.mbarrier::complete_tx::bytes [%0], [%1, {%3,%4,%5}], [%2];"
                   ::"r"(sb + SM_B_W + i * 36864), "l"(&mp.wo), "r"(bar + 2 * NSTB * 8), "r"(0), "r"(0), "r"(i * 3) : "memory");
  }
  __syncthreads();
  const int step = gridDim.x;
  if (warp >= 12) {
    const int wg = warp - 12;
    int use = 0;
#pragma unroll 1
    for (int n = blockIdx.x + wg * step; n < NTB; n += 3 * step, use++) {
      const int b = n / 56, rem = n - b * 56, par = rem / 14, sg = wg + 3 * (use & 1);
      int v; uint32_t spin = 0;
      do { asm volatile("ld.acquire.gpu.global.s32 %0, [%1];" : "=r"(v) : "l"(g_flags + n) : "memory"); } while (v < 4 && ++spin < SPIN_LIMIT);
      asm volatile("fence.proxy.async.global;" ::: "memory");
      if (use >= 2) mbar_wait(bar + (NSTB + sg) * 8, ((use >> 1) - 1) & 1);
      if (elect_one()) {
        mbar_expect(bar + sg * 8, 24576);
        asm volatile("cp.async.bulk.tensor.3d.shared::cluster.global.mbarrier::complete_tx::bytes [%0], [%1, {%3,%4,%5}], [%2];"
                     ::"r"(sb + SM_B_IN + sg * 24576), "l"(&mp.oi), "r"(bar + sg * 8), "r"((par & 1) * 192), "r"(8 * b), "r"((par >> 1) * 112 + (rem - par * 14) * 8) : "memory");
        g_flags[n] = 0;
      }
      __syncwarp();
    }
  } else {
    const int wg = warp >> 2, w = warp & 3;
    constexpr uint64_t db = mkdesc(SBC + SM_B_W, 12288, 512, 2);
    const uint32_t sta0 = sb + SM_B_IN + w * 6144 + (lane & 15) * 128 + (((lane >> 4) ^ (lane & 7)) * 16);
    mbar_wait(bar + 2 * NSTB * 8, 0);
    TRB(47, 1);
    int use = 0;
#pragma unroll 1
    for (int n = blockIdx.x + wg * step; n < NTB; n += 3 * step, use++) {
      const int b = n / 56, rem = n - b * 56, par = rem / 14, sg = wg + 3 * (use & 1);
      const uint64_t da = mkdesc(SBC + SM_B_IN, 128, 3072, 0) + sg * (24576 / 16);
      float D[96];
      mbar_wait(bar + sg * 8, (use >> 1) & 1);
      if (use | wg) nb_sync(4 + wg, 256);
      TRB(use * 3 + wg, 3);
      wg_fence();
      wg_ss192<0>(D, da, db);
#pragma unroll
      for (int k = 1; k < 12; k++) wg_ss192<1>(D, da + k * 16, db + k * 64);
      wg_commit();
      if (n + step < NTB) nb_arrive(wg == 2 ? 4 : 5 + wg, 256);
      TRB(use * 3 + wg, 4);
      if (use && lane == 0) {
        asm volatile("cp.async.bulk.wait_group.read 0;" ::: "memory");
        mbar_arrive(bar + (NSTB + wg + 3 * (~use & 1)) * 8);
      }
      __syncwarp();
      wg_wait<0>(); pin(D);
      nb_sync(1 + wg, 128);
      TRB(use * 3 + wg, 5);
      const uint32_t sta = sta0 + sg * 24576;
#pragma unroll
      for (int q = 0; q < 12; q++)
        stsm4((sta ^ ((q & 3) * 32)) + (q >> 2) * 2048,
              pack2(D[8 * q], D[8 * q + 1]), pack2(D[8 * q + 2], D[8 * q + 3]), pack2(D[8 * q + 4], D[8 * q + 5]), pack2(D[8 * q + 6], D[8 * q + 7]));
      fence_async();
      __syncwarp();
      if (lane == 0) {
        asm volatile("cp.async.bulk.tensor.4d.global.shared::cta.bulk_group [%0, {%2,%3,%4,%5}], [%1];"
                     ::"l"(&mp.oo), "r"(sb + SM_B_IN + sg * 24576 + w * 6144), "r"(0), "r"(8 * b), "r"((par >> 1) * 112 + (rem - par * 14) * 8 + 2 * w), "r"((par & 1) * 3) : "memory");
        asm volatile("cp.async.bulk.commit_group;" ::: "memory");
      }
      __syncwarp();
      TRB(use * 3 + wg, 6);
    }
    if (lane == 0) asm volatile("cp.async.bulk.wait_group 0;" ::: "memory");
    TR2(132 + blockIdx.x, 2);
  }
}

typedef CUresult (*EncodeFn)(CUtensorMap*, CUtensorMapDataType, cuuint32_t, void*, const cuuint64_t*, const cuuint64_t*, const cuuint32_t*,
                             const cuuint32_t*, CUtensorMapInterleave, CUtensorMapSwizzle, CUtensorMapL2promotion, CUtensorMapFloatOOBfill);
static EncodeFn g_enc = nullptr;
static void make_map(CUtensorMap* m, const void* p, int rank, const cuuint64_t* dim, const cuuint64_t* str, const cuuint32_t* box, CUtensorMapSwizzle sw) {
  const cuuint32_t ones[5] = {1, 1, 1, 1, 1};
  g_enc(m, CU_TENSOR_MAP_DATA_TYPE_BFLOAT16, rank, (void*)p, dim, str, box, ones, CU_TENSOR_MAP_INTERLEAVE_NONE, sw,
        CU_TENSOR_MAP_L2_PROMOTION_L2_128B, CU_TENSOR_MAP_FLOAT_OOB_FILL_NONE);
}

extern "C" void kernel_launch(void* const* d_in, const int* in_sizes, int n_in, void* d_out, int out_size) {
  const __nv_bfloat16* x = (const __nv_bfloat16*)d_in[0];
  const __nv_bfloat16* wqkv = (const __nv_bfloat16*)d_in[1];
  const __nv_bfloat16* wo = (const __nv_bfloat16*)d_in[2];
  const __nv_bfloat16* rpb = (const __nv_bfloat16*)d_in[3];

  if (!g_enc) {
    void* fn = nullptr; cudaDriverEntryPointQueryResult qr;
    cudaGetDriverEntryPoint("cuTensorMapEncodeTiled", &fn, cudaEnableDefault, &qr);
    g_enc = (EncodeFn)fn;
    cudaFuncSetAttribute(na_attn_kernel, cudaFuncAttributeMaxDynamicSharedMemorySize, SM_A_TOTAL);
    cudaFuncSetAttribute(na_proj_kernel, cudaFuncAttributeMaxDynamicSharedMemorySize, SM_B_TOTAL);
  }
  Maps ma; MapsB mb;
  { cuuint64_t dim[4] = {64, 112, 224, 6}, str[3] = {(cuuint64_t)ROWB, 768, 128};
    cuuint32_t box[4] = {64, 4, 16, 3}, boxo[4] = {64, 8, 2, 3};
    make_map(&ma.xc, x, 4, dim, str, box, CU_TENSOR_MAP_SWIZZLE_128B);
    make_map(&mb.oo, d_out, 4, dim, str, boxo, CU_TENSOR_MAP_SWIZZLE_128B); }
  { cuuint64_t dim[5] = {64, 112, 224, 2, 6}, str[4] = {(cuuint64_t)ROWB, 768, 19 * 768, 128};
    cuuint32_t box[5] = {64, 8, 3, 2, 3};
    make_map(&ma.xh, x, 5, dim, str, box, CU_TENSOR_MAP_SWIZZLE_128B); }
  { cuuint64_t dim[3] = {384, 112, 224}, str[2] = {(cuuint64_t)ROWB, 768};
    cuuint32_t box[3] = {192, 8, 8}, boxs[3] = {192, 2, 8};
    make_map(&mb.oi, d_out, 3, dim, str, box, CU_TENSOR_MAP_SWIZZLE_NONE);
    make_map(&ma.os, d_out, 3, dim, str, boxs, CU_TENSOR_MAP_SWIZZLE_NONE); }
  { cuuint64_t dim[4] = {32, 112, 224, 12}, str[3] = {(cuuint64_t)ROWB, 768, 64};
    cuuint32_t box[4] = {32, 8, 2, 3};
    make_map(&ma.ot, d_out, 4, dim, str, box, CU_TENSOR_MAP_SWIZZLE_64B); }
  { cuuint64_t dim[2] = {576, 192}, str[1] = {1152};
    cuuint32_t box[2] = {16, 192};
    make_map(&ma.w, wqkv, 2, dim, str, box, CU_TENSOR_MAP_SWIZZLE_32B); }
  { cuuint64_t dim[3] = {32, 192, 6}, str[2] = {384, 64};
    cuuint32_t box[3] = {32, 192, 3};
    make_map(&ma.wo, wo, 3, dim, str, box, CU_TENSOR_MAP_SWIZZLE_64B);
    mb.wo = ma.wo; }
  na_attn_kernel<<<112, 512, SM_A_TOTAL>>>(ma, wqkv, rpb);
  cudaLaunchConfig_t cfg = {};
  cfg.gridDim = dim3(20); cfg.blockDim = dim3(480); cfg.dynamicSmemBytes = SM_B_TOTAL; cfg.stream = cudaStreamPerThread;
  cudaLaunchAttribute at[1];
  at[0].id = cudaLaunchAttributeProgrammaticStreamSerialization; at[0].val.programmaticStreamSerializationAllowed = 1;
  cfg.attrs = at; cfg.numAttrs = 1;
  cudaLaunchKernelEx(&cfg, na_proj_kernel, mb);
}
```

```cpp
#include <cuda_runtime.h>
#include <cuda_bf16.h>
#include <cuda.h>
#include <stdint.h>

#define SPIN_LIMIT (1u << 18)

__device__ __forceinline__ uint32_t smem_u32(const void* p) { return (uint32_t)__cvta_generic_to_shared(p); }
__device__ __forceinline__ void wg_fence() { asm volatile("wgmma.fence.sync.aligned;" ::: "memory"); }
__device__ __forceinline__ void wg_commit() { asm volatile("wgmma.commit_group.sync.aligned;" ::: "memory"); }
template <int N> __device__ __forceinline__ void wg_wait() { asm volatile("wgmma.wait_group.sync.aligned %0;" ::"n"(N) : "memory"); }
template <int N> __device__ __forceinline__ void pin(float (&d)[N]) {
#pragma unroll
  for (int i = 0; i < N; i++) asm volatile("" : "+f"(d[i])::"memory");
}
__host__ __device__ constexpr uint64_t mkdesc(uint32_t addr, uint32_t lbo, uint32_t sbo, uint32_t sw) {
  return (uint64_t)((addr & 0x3FFFF) >> 4) | ((uint64_t)(lbo >> 4) << 16) | ((uint64_t)(sbo >> 4) << 32) | ((uint64_t)sw << 62);
}
__device__ __forceinline__ void mbar_init(uint32_t bar, uint32_t cnt) { asm volatile("mbarrier.init.shared::cta.b64 [%0], %1;" ::"r"(bar), "r"(cnt) : "memory"); }
__device__ __forceinline__ void mbar_arrive(uint32_t bar) { asm volatile("mbarrier.arrive.shared::cta.b64 _, [%0];" ::"r"(bar) : "memory"); }
__device__ __forceinline__ bool elect_one() {
  uint32_t r; asm volatile("{\n.reg .pred p;\nelect.sync _|p, 0xffffffff;\nselp.u32 %0, 1, 0, p;\n}" : "=r"(r)); return r;
}
__device__ __forceinline__ void mbar_arrive_elect(uint32_t bar) {
  asm volatile("{\n.reg .pred p;\nelect.sync _|p, 0xffffffff;\n@p mbarrier.arrive.shared::cta.b64 _, [%0];\n}" ::"r"(bar) : "memory");
}
__device__ __forceinline__ void mbar_expect(uint32_t bar, uint32_t bytes) { asm volatile("mbarrier.arrive.expect_tx.shared::cta.b64 _, [%0], %1;" ::"r"(bar), "r"(bytes) : "memory"); }
__device__ __forceinline__ void mbar_arrive_remote(uint32_t bar, uint32_t cta) {
  asm volatile("{\n.reg .b32 ra;\nmapa.shared::cluster.u32 ra, %0, %1;\nmbarrier.arrive.shared::cluster.b64 _, [ra];\n}" ::"r"(bar), "r"(cta) : "memory");
}
__device__ __forceinline__ void mbar_wait(uint32_t bar, uint32_t parity) {
  asm volatile("{\n.reg .pred p;\n.reg .b32 n;\nmov.b32 n, 0;\nWL:\nmbarrier.try_wait.parity.shared::cta.b64 p, [%0], %1;\n@p bra WD;\n"
               "add.u32 n, n, 1;\nsetp.lt.u32 p, n, 65536;\n@p bra WL;\nWD:\n}" ::"r"(bar), "r"(parity) : "memory");
}
#define mbar_wait_long mbar_wait
__device__ __forceinline__ void nb_sync(int id, int n) { asm volatile("bar.sync %0, %1;" ::"r"(id), "r"(n) : "memory"); }
__device__ __forceinline__ void nb_arrive(int id, int n) { asm volatile("bar.arrive %0, %1;" ::"r"(id), "r"(n) : "memory"); }
__device__ __forceinline__ void fence_async() { asm volatile("fence.proxy.async.shared::cta;" ::: "memory"); }
__device__ __forceinline__ void cluster_sync() {
  asm volatile("barrier.cluster.arrive.relaxed.aligned;\nbarrier.cluster.wait.aligned;" ::: "memory");
}
__device__ __forceinline__ uint32_t pack2(float lo, float hi) {
  uint32_t r; asm("cvt.rn.bf16x2.f32 %0, %1, %2;" : "=r"(r) : "f"(hi), "f"(lo)); return r;
}
__device__ __forceinline__ void stsm4(uint32_t a, uint32_t r0, uint32_t r1, uint32_t r2, uint32_t r3) {
  asm volatile("stmatrix.sync.aligned.m8n8.x4.shared.b16 [%0], {%1,%2,%3,%4};" ::"r"(a), "r"(r0), "r"(r1), "r"(r2), "r"(r3) : "memory");
}
__device__ __forceinline__ void ldsm4(uint32_t a, uint32_t& r0, uint32_t& r1, uint32_t& r2, uint32_t& r3) {
  asm volatile("ldmatrix.sync.aligned.m8n8.x4.shared.b16 {%0,%1,%2,%3}, [%4];" : "=r"(r0), "=r"(r1), "=r"(r2), "=r"(r3) : "r"(a) : "memory");
}
__device__ __forceinline__ void sts128(uint32_t a, uint4 v) {
  asm volatile("st.shared.v4.b32 [%0], {%1,%2,%3,%4};" ::"r"(a), "r"(v.x), "r"(v.y), "r"(v.z), "r"(v.w) : "memory");
}
__device__ __forceinline__ float lds_f32(uint32_t a) { float v; asm volatile("ld.shared.f32 %0, [%1];" : "=f"(v) : "r"(a)); return v; }
__device__ __forceinline__ float ex2(float x) { float y; asm("ex2.approx.ftz.f32 %0, %1;" : "=f"(y) : "f"(x)); return y; }

template<int SC> __device__ __forceinline__ void wg_ss144(float (&d)[72], uint64_t da, uint64_t db) {
  asm volatile("{\n.reg .pred p;\nsetp.ne.b32 p, %74, 0;\nwgmma.mma_async.sync.aligned.m64n144k16.f32.bf16.bf16 {%0,%1,%2,%3,%4,%5,%6,%7,%8,%9,%10,%11,%12,%13,%14,%15,%16,%17,%18,%19,%20,%21,%22,%23,%24,%25,%26,%27,%28,%29,%30,%31,%32,%33,%34,%35,%36,%37,%38,%39,%40,%41,%42,%43,%44,%45,%46,%47,%48,%49,%50,%51,%52,%53,%54,%55,%56,%57,%58,%59,%60,%61,%62,%63,%64,%65,%66,%67,%68,%69,%70,%71}, %72, %73, p, 1, 1, 0, 1;\n}\n"
    : "+f"(d[0]),"+f"(d[1]),"+f"(d[2]),"+f"(d[3]),"+f"(d[4]),"+f"(d[5]),"+f"(d[6]),"+f"(d[7]),"+f"(d[8]),"+f"(d[9]),"+f"(d[10]),"+f"(d[11]),"+f"(d[12]),"+f"(d[13]),"+f"(d[14]),"+f"(d[15]),"+f"(d[16]),"+f"(d[17]),"+f"(d[18]),"+f"(d[19]),"+f"(d[20]),"+f"(d[21]),"+f"(d[22]),"+f"(d[23]),"+f"(d[24]),"+f"(d[25]),"+f"(d[26]),"+f"(d[27]),"+f"(d[28]),"+f"(d[29]),"+f"(d[30]),"+f"(d[31]),"+f"(d[32]),"+f"(d[33]),"+f"(d[34]),"+f"(d[35]),"+f"(d[36]),"+f"(d[37]),"+f"(d[38]),"+f"(d[39]),"+f"(d[40]),"+f"(d[41]),"+f"(d[42]),"+f"(d[43]),"+f"(d[44]),"+f"(d[45]),"+f"(d[46]),"+f"(d[47]),"+f"(d[48]),"+f"(d[49]),"+f"(d[50]),"+f"(d[51]),"+f"(d[52]),"+f"(d[53]),"+f"(d[54]),"+f"(d[55]),"+f"(d[56]),"+f"(d[57]),"+f"(d[58]),"+f"(d[59]),"+f"(d[60]),"+f"(d[61]),"+f"(d[62]),"+f"(d[63]),"+f"(d[64]),"+f"(d[65]),"+f"(d[66]),"+f"(d[67]),"+f"(d[68]),"+f"(d[69]),"+f"(d[70]),"+f"(d[71]) : "l"(da), "l"(db), "n"(SC));
}
template<int SC> __device__ __forceinline__ void wg_ss96(float (&d)[48], uint64_t da, uint64_t db) {
  asm volatile("{\n.reg .pred p;\nsetp.ne.b32 p, %50, 0;\nwgmma.mma_async.sync.aligned.m64n96k16.f32.bf16.bf16 {%0,%1,%2,%3,%4,%5,%6,%7,%8,%9,%10,%11,%12,%13,%14,%15,%16,%17,%18,%19,%20,%21,%22,%23,%24,%25,%26,%27,%28,%29,%30,%31,%32,%33,%34,%35,%36,%37,%38,%39,%40,%41,%42,%43,%44,%45,%46,%47}, %48, %49, p, 1, 1, 0, 1;\n}\n"
    : "+f"(d[0]),"+f"(d[1]),"+f"(d[2]),"+f"(d[3]),"+f"(d[4]),"+f"(d[5]),"+f"(d[6]),"+f"(d[7]),"+f"(d[8]),"+f"(d[9]),"+f"(d[10]),"+f"(d[11]),"+f"(d[12]),"+f"(d[13]),"+f"(d[14]),"+f"(d[15]),"+f"(d[16]),"+f"(d[17]),"+f"(d[18]),"+f"(d[19]),"+f"(d[20]),"+f"(d[21]),"+f"(d[22]),"+f"(d[23]),"+f"(d[24]),"+f"(d[25]),"+f"(d[26]),"+f"(d[27]),"+f"(d[28]),"+f"(d[29]),"+f"(d[30]),"+f"(d[31]),"+f"(d[32]),"+f"(d[33]),"+f"(d[34]),"+f"(d[35]),"+f"(d[36]),"+f"(d[37]),"+f"(d[38]),"+f"(d[39]),"+f"(d[40]),"+f"(d[41]),"+f"(d[42]),"+f"(d[43]),"+f"(d[44]),"+f"(d[45]),"+f"(d[46]),"+f"(d[47]) : "l"(da), "l"(db), "n"(SC));
}
template<int SC> __device__ __forceinline__ void wg_rs112(float (&d)[56], uint32_t a0, uint32_t a1, uint32_t a2, uint32_t a3, uint64_t db) {
  asm volatile("{\n.reg .pred p;\nsetp.ne.b32 p, %61, 0;\nwgmma.mma_async.sync.aligned.m64n112k16.f32.bf16.bf16 {%0,%1,%2,%3,%4,%5,%6,%7,%8,%9,%10,%11,%12,%13,%14,%15,%16,%17,%18,%19,%20,%21,%22,%23,%24,%25,%26,%27,%28,%29,%30,%31,%32,%33,%34,%35,%36,%37,%38,%39,%40,%41,%42,%43,%44,%45,%46,%47,%48,%49,%50,%51,%52,%53,%54,%55}, {%56,%57,%58,%59}, %60, p, 1, 1, 0;\n}\n"
    : "+f"(d[0]),"+f"(d[1]),"+f"(d[2]),"+f"(d[3]),"+f"(d[4]),"+f"(d[5]),"+f"(d[6]),"+f"(d[7]),"+f"(d[8]),"+f"(d[9]),"+f"(d[10]),"+f"(d[11]),"+f"(d[12]),"+f"(d[13]),"+f"(d[14]),"+f"(d[15]),"+f"(d[16]),"+f"(d[17]),"+f"(d[18]),"+f"(d[19]),"+f"(d[20]),"+f"(d[21]),"+f"(d[22]),"+f"(d[23]),"+f"(d[24]),"+f"(d[25]),"+f"(d[26]),"+f"(d[27]),"+f"(d[28]),"+f"(d[29]),"+f"(d[30]),"+f"(d[31]),"+f"(d[32]),"+f"(d[33]),"+f"(d[34]),"+f"(d[35]),"+f"(d[36]),"+f"(d[37]),"+f"(d[38]),"+f"(d[39]),"+f"(d[40]),"+f"(d[41]),"+f"(d[42]),"+f"(d[43]),"+f"(d[44]),"+f"(d[45]),"+f"(d[46]),"+f"(d[47]),"+f"(d[48]),"+f"(d[49]),"+f"(d[50]),"+f"(d[51]),"+f"(d[52]),"+f"(d[53]),"+f"(d[54]),"+f"(d[55]) : "r"(a0), "r"(a1), "r"(a2), "r"(a3), "l"(db), "n"(SC));
}
template<int SC> __device__ __forceinline__ void wg_sp48(float (&d)[24], uint32_t a0, uint32_t a1, uint32_t a2, uint32_t a3, uint64_t db, uint32_t meta) {
  asm volatile("{\n.reg .pred p;\nsetp.ne.b32 p, %30, 0;\nwgmma.mma_async.sp.sync.aligned.m64n48k32.f32.bf16.bf16 {%0,%1,%2,%3,%4,%5,%6,%7,%8,%9,%10,%11,%12,%13,%14,%15,%16,%17,%18,%19,%20,%21,%22,%23}, {%24,%25,%26,%27}, %28, %29, 0, p, 1, 1, 1;\n}\n"
    : "+f"(d[0]),"+f"(d[1]),"+f"(d[2]),"+f"(d[3]),"+f"(d[4]),"+f"(d[5]),"+f"(d[6]),"+f"(d[7]),"+f"(d[8]),"+f"(d[9]),"+f"(d[10]),"+f"(d[11]),"+f"(d[12]),"+f"(d[13]),"+f"(d[14]),"+f"(d[15]),"+f"(d[16]),"+f"(d[17]),"+f"(d[18]),"+f"(d[19]),"+f"(d[20]),"+f"(d[21]),"+f"(d[22]),"+f"(d[23]) : "r"(a0), "r"(a1), "r"(a2), "r"(a3), "l"(db), "r"(meta), "n"(SC));
}
template<int SC> __device__ __forceinline__ void wg_ss192(float (&d)[96], uint64_t da, uint64_t db) {
  asm volatile("{\n.reg .pred p;\nsetp.ne.b32 p, %98, 0;\nwgmma.mma_async.sync.aligned.m64n192k16.f32.bf16.bf16 {%0,%1,%2,%3,%4,%5,%6,%7,%8,%9,%10,%11,%12,%13,%14,%15,%16,%17,%18,%19,%20,%21,%22,%23,%24,%25,%26,%27,%28,%29,%30,%31,%32,%33,%34,%35,%36,%37,%38,%39,%40,%41,%42,%43,%44,%45,%46,%47,%48,%49,%50,%51,%52,%53,%54,%55,%56,%57,%58,%59,%60,%61,%62,%63,%64,%65,%66,%67,%68,%69,%70,%71,%72,%73,%74,%75,%76,%77,%78,%79,%80,%81,%82,%83,%84,%85,%86,%87,%88,%89,%90,%91,%92,%93,%94,%95}, %96, %97, p, 1, 1, 0, 1;\n}\n"
    : "+f"(d[0]),"+f"(d[1]),"+f"(d[2]),"+f"(d[3]),"+f"(d[4]),"+f"(d[5]),"+f"(d[6]),"+f"(d[7]),"+f"(d[8]),"+f"(d[9]),"+f"(d[10]),"+f"(d[11]),"+f"(d[12]),"+f"(d[13]),"+f"(d[14]),"+f"(d[15]),"+f"(d[16]),"+f"(d[17]),"+f"(d[18]),"+f"(d[19]),"+f"(d[20]),"+f"(d[21]),"+f"(d[22]),"+f"(d[23]),"+f"(d[24]),"+f"(d[25]),"+f"(d[26]),"+f"(d[27]),"+f"(d[28]),"+f"(d[29]),"+f"(d[30]),"+f"(d[31]),"+f"(d[32]),"+f"(d[33]),"+f"(d[34]),"+f"(d[35]),"+f"(d[36]),"+f"(d[37]),"+f"(d[38]),"+f"(d[39]),"+f"(d[40]),"+f"(d[41]),"+f"(d[42]),"+f"(d[43]),"+f"(d[44]),"+f"(d[45]),"+f"(d[46]),"+f"(d[47]),"+f"(d[48]),"+f"(d[49]),"+f"(d[50]),"+f"(d[51]),"+f"(d[52]),"+f"(d[53]),"+f"(d[54]),"+f"(d[55]),"+f"(d[56]),"+f"(d[57]),"+f"(d[58]),"+f"(d[59]),"+f"(d[60]),"+f"(d[61]),"+f"(d[62]),"+f"(d[63]),"+f"(d[64]),"+f"(d[65]),"+f"(d[66]),"+f"(d[67]),"+f"(d[68]),"+f"(d[69]),"+f"(d[70]),"+f"(d[71]),"+f"(d[72]),"+f"(d[73]),"+f"(d[74]),"+f"(d[75]),"+f"(d[76]),"+f"(d[77]),"+f"(d[78]),"+f"(d[79]),"+f"(d[80]),"+f"(d[81]),"+f"(d[82]),"+f"(d[83]),"+f"(d[84]),"+f"(d[85]),"+f"(d[86]),"+f"(d[87]),"+f"(d[88]),"+f"(d[89]),"+f"(d[90]),"+f"(d[91]),"+f"(d[92]),"+f"(d[93]),"+f"(d[94]),"+f"(d[95]) : "l"(da), "l"(db), "n"(SC));
}

constexpr uint32_t SBC = 1024;
constexpr int ROWB = 2 * 224 * 384;
constexpr int TB = 11;
constexpr int KS = 832;
constexpr int KSLOT = 22 * KS;
constexpr int SM_X1 = 0;
constexpr int SM_X2 = SM_X1 + 24576;
constexpr int SM_X0 = SM_X2 + 24576;
constexpr int SM_W = SM_X0 + 18432;
constexpr int SM_K = SM_W + 55296;
constexpr int SM_V = SM_K + 2 * KSLOT;
constexpr int SM_Q = SM_V + 22 * 1536;
constexpr int SM_O = SM_Q + 24576;
constexpr int SM_RPB = SM_O + 12288;
constexpr int SM_BAR = SM_RPB + 768;
constexpr int SM_A_TOTAL = SM_BAR + 256;
constexpr int SM_TWO = SM_X1;
constexpr int SM_TST = SM_TWO + 36864;
constexpr int SM_TIN = SM_X0;
enum { B_FULL = 0, B_EMPTY = 3, B_TIN = 6, B_TFREE = 9, B_TGL, B_WK, B_WQ, B_WO, B_Q0, B_ODONE, B_KFREE = B_ODONE + 2, B_VFREE, B_COUNT };
enum { N_KRDY = 4, N_QK0, N_QK1, N_VQ0, N_VQ1, N_PVISS };

#define SPL 4
#define RA 152
#define RG 184
__device__ int g_flags[TB * 56];

#define TR(role, it, k)
#define TRDECL
#define TRARG
#define TRPASS
#define TRDUMP
#define TRB(it, k)
#define TR2(blk, k)

struct GemmCtx {
  uint32_t bar;
  uint32_t kC, vC, qC;
  uint32_t kH, vH;
  bool hvalid;
};

template <int STRIDE> __device__ __forceinline__ void dump12(uint32_t a, const uint32_t (&r)[12]) {
#pragma unroll
  for (int j = 0; j < 3; j++) stsm4(a + j * 2 * STRIDE, r[4 * j], r[4 * j + 1], r[4 * j + 2], r[4 * j + 3]);
}
template <int N> __device__ __forceinline__ void pack12(uint32_t (&r)[12], const float (&d)[N], int off) {
#pragma unroll
  for (int j = 0; j < 12; j++) r[j] = pack2(d[off + 2 * j], d[off + 2 * j + 1]);
}
template <int XS, int K0, int K1> __device__ __forceinline__ void issue_core(float (&d)[72]) {
  constexpr uint64_t da = mkdesc(SBC + XS, 16, 1024, 1), db = mkdesc(SBC + SM_W, 6144, 256, 3);
  wg_fence();
  if (K0 == 0) wg_ss144<0>(d, da, db);
#pragma unroll
  for (int k = K0 ? K0 : 1; k < K1; k++) wg_ss144<1>(d, da + (k >> 2) * 512 + (k & 3) * 2, db + k * 32);
  wg_commit();
}
template <int K0, int K1> __device__ __forceinline__ void issue_halo(float (&d)[48]) {
  constexpr uint64_t da = mkdesc(SBC + SM_X0 - 2048, 16, 1024, 1), db = mkdesc(SBC + SM_W, 6144, 256, 3);
  wg_fence();
  if (K0 == 0) wg_ss96<0>(d, da, db);
#pragma unroll
  for (int k = K0 ? K0 : 1; k < K1; k++) wg_ss96<1>(d, da + (k >> 2) * 384 + (k & 3) * 2, db + k * 32);
  wg_commit();
}
template <int ST, int BYTES> __device__ __forceinline__ void release_stage(const GemmCtx& c, bool on) {
  asm volatile("{\n.reg .pred p, q;\n.reg .b32 ra;\nsetp.ne.b32 q, %2, 0;\nelect.sync _|p, 0xffffffff;\nand.pred p, p, q;\n"
               "mapa.shared::cluster.u32 ra, %1, %4;\n"
               "@p mbarrier.arrive.expect_tx.shared::cta.b64 _, [%0], %3;\n@p mbarrier.arrive.shared::cluster.b64 _, [ra];\n}"
               ::"r"(c.bar + (B_FULL + ST) * 8), "r"(c.bar + (B_EMPTY + ST) * 8), "r"((int)on), "n"(BYTES / 4), "n"(ST) : "memory");
}
__device__ __forceinline__ void load_w(const CUtensorMap* m, uint32_t dst, uint32_t bar, int col) {
  asm volatile("cp.async.bulk.tensor.2d.shared::cluster.global.mbarrier::complete_tx::bytes [%0], [%1, {%3,%4}], [%2];"
               ::"r"(dst), "l"(m), "r"(bar), "r"(col), "r"(0) : "memory");
}
template <int BYTES> __device__ __forceinline__ void send_o(uint32_t dst, uint32_t src, uint32_t bar, int cta) {
  asm volatile("{\n.reg .b32 rd, rb;\nmapa.shared::cluster.u32 rd, %0, %3;\nmapa.shared::cluster.u32 rb, %2, %3;\n"
               "cp.async.bulk.shared::cluster.shared::cta.mbarrier::complete_tx::bytes [rd], [%1], %4, [rb];\n}"
               ::"r"(dst), "r"(src), "r"(bar), "r"(cta), "n"(BYTES) : "memory");
}
__device__ __forceinline__ void publish(uint32_t bar) {
  fence_async();
  __syncwarp();
  mbar_arrive_elect(bar);
}

template <bool FIRST, bool LAST>
__device__ __forceinline__ void gemm_iter(const GemmCtx& c, int b, uint32_t (&pk)[12], uint32_t (&pv)[12], uint32_t (&pq)[12] TRARG) {
  const uint32_t bar = c.bar;
  const uint32_t pa = b & 1;
  const bool w = b >= 0;
  const uint32_t ko = pa * KSLOT, vx = pa * 16, qx = pa * 128;
  float H[48], C[72];
  uint32_t hk[12], hv[12], pv2[12];
  TR(2, b, 0);
  if (FIRST) mbar_wait(bar + (B_FULL + 0) * 8, pa);
  if (w) nb_sync(N_QK1, 256);
  TR(2, b, 2);
  issue_halo<0, 8>(H);
  TR(2, b, 3);
  if (!FIRST) {
    if (w) mbar_wait(bar + B_KFREE * 8, pa);
    dump12<128>(c.kC + ko, pk);
  }
  issue_halo<8, 12>(H);
  TR(2, b, 4);
  if (!LAST) {
    mbar_wait(bar + (B_FULL + 2) * 8, pa);
    if (FIRST) mbar_wait(bar + B_WQ * 8, 0);
    TR(2, b, 13);
    issue_core<SM_X2, 0, 8>(C);
    TR(2, b, 5);
    if (!FIRST) { fence_async(); dump12<256>(c.qC ^ (qx ^ 192), pq); }
    wg_wait<1>(); pin(H);
    release_stage<0, 18432>(c, true);
  } else {
    dump12<256>(c.qC ^ (qx ^ 192), pq);
    fence_async();
    nb_arrive(N_VQ0, 288); nb_arrive(N_VQ1, 288);
    wg_wait<0>(); pin(H);
    uint32_t ln; asm volatile("mov.u32 %0, %%laneid;" : "=r"(ln));
    if (ln < 4) mbar_arrive_remote(bar + B_TFREE * 8, ln);
  }
  pack12(hk, H, 0);
  if (c.hvalid) dump12<128>(c.kH + ko, hk);
  pack12(hv, H, 24);
  if (!LAST) {
    issue_core<SM_X2, 8, 12>(C);
    if (w) { nb_arrive(N_VQ0, 288); nb_arrive(N_VQ1, 288); }
    else if (!FIRST) { __syncwarp(); mbar_arrive_elect(bar + B_Q0 * 8); }
    mbar_wait(bar + (B_FULL + 1) * 8, pa);
    TR(2, b, 6);
    wg_wait<0>(); pin(C);
    TR(2, b, 7);
    pack12(pk, C, 0);
    dump12<128>(c.kC + ko + 64, pk);
    release_stage<2, 24576>(c, b < 11);
    pack12(pv2, C, 24);
    pack12(pq, C, 48);
    TR(2, b, 8);
    issue_core<SM_X1, 0, SPL>(C);
    if (w) nb_sync(N_PVISS, 384);
    issue_core<SM_X1, SPL, 8>(C);
    TR(2, b, 9);
  }
  if (!FIRST) fence_async();
  TR(2, b, 14);
  if (!LAST) issue_core<SM_X1, 8, 12>(C);
  if (!FIRST) nb_arrive(N_KRDY, 256);
  TR(2, b, 1);
  if (!LAST) mbar_wait(bar + (B_FULL + 0) * 8, pa ^ 1);
  if (w) mbar_wait(bar + B_VFREE * 8, pa);
  TR(2, b, 10);
  if (!FIRST) dump12<128>(c.vC ^ vx, pv);
  if (!LAST) dump12<256>(c.qC ^ qx, pq);
  if (c.hvalid) dump12<128>(c.vH ^ vx, hv);
  if (LAST) { fence_async(); nb_arrive(N_VQ0, 256); nb_arrive(N_VQ1, 256); return; }
  dump12<128>((c.vC ^ vx ^ 16) + 768, pv2);
  TR(2, b, 11);
  wg_wait<0>(); pin(C);
  TR(2, b, 12);
  release_stage<1, 24576>(c, b < 11);
  pack12(pk, C, 0);
  pack12(pv, C, 24);
  pack12(pq, C, 48);
}

__device__ __forceinline__ float fold(float a, float b, float t, int useb) {
  float r;
  asm("{\n.reg .pred p;\nsetp.ne.b32 p, %4, 0;\nfma.rn.f32 %0, %1, 0f3E553B95, %3;\n@p fma.rn.f32 %0, %2, 0f3E553B95, %3;\n}"
      : "=&f"(r) : "f"(a), "f"(b), "f"(t), "r"(useb));
  return r;
}
template <int U, int L>
__device__ __forceinline__ void softmax_tile(const float (&SA)[56], const float (&SB)[56], const float (&T)[16], int b0, int b1,
                                             uint32_t (&P)[28], float (&sx)[8]) {
  float lu[14], ll[14];
#pragma unroll
  for (int j = 0; j < 7; j++) {
    constexpr int sh = U == L ? 2 : 0;
    const float tu0 = T[2 * j + sh], tu1 = T[2 * j + 1 + sh], tl0 = T[2 * j], tl1 = T[2 * j + 1];
    lu[2 * j]     = fold(SA[4 * (U + j)],     SB[4 * (U + j)],     tu0, b0);
    ll[2 * j]     = fold(SA[4 * (L + j) + 2], SB[4 * (L + j) + 2], tl0, b0);
    lu[2 * j + 1] = fold(SA[4 * (U + j) + 1], SB[4 * (U + j) + 1], tu1, b1);
    ll[2 * j + 1] = fold(SA[4 * (L + j) + 3], SB[4 * (L + j) + 3], tl1, b1);
  }
  float mu = lu[0], ml = ll[0], mu2 = lu[1], ml2 = ll[1];
#pragma unroll
  for (int j = 1; j < 7; j++) { mu = fmaxf(mu, lu[2 * j]); mu2 = fmaxf(mu2, lu[2 * j + 1]); ml = fmaxf(ml, ll[2 * j]); ml2 = fmaxf(ml2, ll[2 * j + 1]); }
  mu = fmaxf(mu, mu2); ml = fmaxf(ml, ml2);
  { const float a1 = __shfl_xor_sync(0xffffffffu, mu, 1), a2 = __shfl_xor_sync(0xffffffffu, mu, 2), a3 = __shfl_xor_sync(0xffffffffu, mu, 3);
    const float c1 = __shfl_xor_sync(0xffffffffu, ml, 1), c2 = __shfl_xor_sync(0xffffffffu, ml, 2), c3 = __shfl_xor_sync(0xffffffffu, ml, 3);
    mu = fmaxf(fmaxf(mu, a1), fmaxf(a2, a3)); ml = fmaxf(fmaxf(ml, c1), fmaxf(c2, c3)); }
  float su = 0.f, sl = 0.f;
#pragma unroll
  for (int c = 0; c < 14; c++) {
    const int iu = (c >> 1) * 4 + (c & 1) * 2;
    if (c >= U && c < U + 7) {
      float e0 = ex2(lu[2 * (c - U)] - mu), e1 = ex2(lu[2 * (c - U) + 1] - mu);
      su = c == U ? e0 + e1 : (su + e0) + e1; P[iu] = pack2(e0, e1);
    } else P[iu] = 0u;
    if (c >= L && c < L + 7) {
      float e0 = ex2(ll[2 * (c - L)] - ml), e1 = ex2(ll[2 * (c - L) + 1] - ml);
      sl = c == L ? e0 + e1 : (sl + e0) + e1; P[iu + 1] = pack2(e0, e1);
    } else P[iu + 1] = 0u;
  }
  sx[0] = su; sx[4] = sl;
#pragma unroll
  for (int k = 1; k < 4; k++) { sx[k] = __shfl_xor_sync(0xffffffffu, su, k); sx[4 + k] = __shfl_xor_sync(0xffffffffu, sl, k); }
}

struct Maps { CUtensorMap xc, xh, w, os, wo, ot; };

__global__ void __cluster_dims__(4, 1, 1) __launch_bounds__(512, 1)
na_attn_kernel(const __grid_constant__ Maps mp, const __nv_bfloat16* __restrict__ wqkv, const __nv_bfloat16* __restrict__ rpb) {
  extern __shared__ __align__(1024) uint8_t smem_raw[];
  const uint32_t sb = smem_u32(smem_raw);
  if ((sb & 0x3FFFF) != SBC) return;
  const uint32_t bar = sb + SM_BAR;
  TR2(blockIdx.x, 0);
  const int tid = threadIdx.x, lane = tid & 31;
  const int warp = __shfl_sync(0xffffffffu, tid >> 5, 0);
  const int head = blockIdx.x & 3, cl = blockIdx.x >> 2;
  const int par = cl / 7, strip = cl - par * 7, ph = par >> 1, pw = par & 1;

  uint4 wv[3];
  const int wr = tid / 6, wc = tid - wr * 6;
  if (warp < 12) {
#pragma unroll
    for (int i = 0; i < 3; i++) wv[i] = __ldg(reinterpret_cast<const uint4*>(wqkv + (wr + i * 64) * 576 + 384 + head * 48 + wc * 8));
  } else if (elect_one()) {
    if (warp == 12) {
      mbar_init(bar + B_WK * 8, 1);
#pragma unroll
      for (int i = 0; i < 3; i++) load_w(&mp.w, sb + SM_W + i * 6144, bar + B_WK * 8, 192 + head * 48 + i * 16);
      mbar_expect(bar + B_WK * 8, 18432);
    } else if (warp == 13) {
#pragma unroll
      for (int i = 0; i < B_WK; i++) mbar_init(bar + i * 8, i < B_EMPTY ? 4 : (i < B_TIN ? 16 : (i < B_TFREE ? 1 : (i == B_TFREE ? 16 : 8))));
    } else if (warp == 14) {
#pragma unroll
      for (int i = B_WQ; i < B_COUNT; i++) mbar_init(bar + i * 8, i < B_Q0 ? 1 : (i < B_KFREE ? 4 : 8));
    }
    asm volatile("fence.mbarrier_init.release.cluster;" ::: "memory");
  }
  __syncwarp();
  asm volatile("barrier.cluster.arrive.relaxed.aligned;" ::: "memory");

  if (warp >= 12) {
    asm volatile("setmaxnreg.dec.sync.aligned.u32 24;");
    asm volatile("griddepcontrol.launch_dependents;");
    const int cc = ph * 112 + (head ? strip * 16 : (strip == 0 ? 16 : (strip == 6 ? 74 : strip * 16 - 3)));
    const int sd = strip == 0 ? -1 : (strip == 6 ? 1 : 0);
    const int r0 = head == 0 ? -4 : (head == 1 ? 4 : 0);
    asm volatile("barrier.cluster.wait.aligned;" ::: "memory");
    if (warp == 12) {
      const uint32_t fb = bar + (B_FULL + head) * 8, eb = bar + (B_EMPTY + head) * 8;
      const uint32_t dst = sb + (head == 0 ? SM_X0 : (head == 1 ? SM_X1 : SM_X2));
      const int nl = head == 0 ? 15 : (head == 3 ? 1 : 14);
#pragma unroll 1
      for (int n = 0; n < nl; n++) {
        if (n) mbar_wait(eb, (n - 1) & 1);
        if (elect_one()) {
          if (head == 0) {
            asm volatile("cp.async.bulk.tensor.5d.shared::cluster.global.mbarrier::complete_tx::bytes.multicast::cluster [%0], [%1, {%3,%4,%5,%6,%7}], [%2], %8;"
                         ::"r"(dst), "l"(&mp.xh), "r"(fb), "r"(0), "r"(8 * n + r0), "r"(cc), "r"(sd), "r"(pw * 3), "h"((uint16_t)15) : "memory");
            if (n + 1 < nl) asm volatile("cp.async.bulk.prefetch.tensor.5d.L2.global [%0, {%1,%2,%3,%4,%5}];" ::"l"(&mp.xh), "r"(0), "r"(8 * n + 8 + r0), "r"(cc), "r"(sd), "r"(pw * 3) : "memory");
          } else if (head < 3) {
            asm volatile("cp.async.bulk.tensor.4d.shared::cluster.global.mbarrier::complete_tx::bytes.multicast::cluster [%0], [%1, {%3,%4,%5,%6}], [%2], %7;"
                         ::"r"(dst), "l"(&mp.xc), "r"(fb), "r"(0), "r"(8 * n + r0), "r"(cc), "r"(pw * 3), "h"((uint16_t)15) : "memory");
          }
          if (n == 0) {
#pragma unroll
            for (int i = 0; i < 3; i++) load_w(&mp.w, sb + SM_W + (6 + i) * 6144, bar + B_WQ * 8, head * 48 + i * 16);
            mbar_expect(bar + B_WQ * 8, 18432);
            mbar_expect(bar + B_TIN * 8, 24576); mbar_expect(bar + (B_TIN + 1) * 8, 24576); mbar_expect(bar + (B_TIN + 2) * 8, 24576);
          }
          if (head && n + 1 < nl) asm volatile("cp.async.bulk.prefetch.tensor.4d.L2.global [%0, {%1,%2,%3,%4}];" ::"l"(&mp.xc), "r"(0), "r"(8 * n + 8 + r0), "r"(cc), "r"(pw * 3) : "memory");
        }
        __syncwarp();
      }
    }
    if (warp >= 14) {
      const int j = warp - 14;
      int* flag = g_flags + cl * 2 + j;
      nb_arrive(N_VQ0 + j, 288);
#pragma unroll 1
      for (int b = 0; b <= TB; b++) {
        mbar_wait(bar + (B_ODONE + j) * 8, b & 1);
        if (lane == 0) {
#pragma unroll
          for (int i = 0; i < 2; i++)
            asm volatile("cp.async.bulk.tensor.3d.global.shared::cta.bulk_group [%0, {%2,%3,%4}], [%1];"
                         ::"l"(&mp.os), "r"(sb + SM_O + j * 6144 + i * 3072), "r"(pw * 192), "r"(8 * b + 2 * head), "r"(ph * 112 + strip * 16 + 8 * j + 4 * i) : "memory");
          asm volatile("cp.async.bulk.commit_group;\ncp.async.bulk.wait_group.read 0;" ::: "memory");
        }
        __syncwarp();
        nb_arrive(N_VQ0 + j, 288);
        if (lane == 0) {
          asm volatile("cp.async.bulk.wait_group 0;\nfence.proxy.async.global;\nfence.acq_rel.gpu;" ::: "memory");
          if (b < TB) asm volatile("red.relaxed.gpu.global.add.s32 [%0], 1;" ::"l"(flag + b * 56) : "memory");
          else {
#pragma unroll
            for (int d = 0; d < 4; d++) mbar_arrive_remote(bar + B_TGL * 8, d);
          }
        }
        __syncwarp();
      }
      mbar_wait(bar + (B_ODONE + j) * 8, 0);
      mbar_wait(bar + B_TFREE * 8, 0);
      if (elect_one()) {
#pragma unroll
        for (int d = 0; d < 4; d++) send_o<3072>(sb + SM_TIN + 24576 + head * 6144 + j * 3072, sb + SM_O + j * 6144 + (d >> 1) * 3072, bar + (B_TIN + 1) * 8, d);
      }
      __syncwarp();
    } else if (warp == 13) {
      mbar_wait_long(bar + B_TGL * 8, 0);
      mbar_wait(bar + B_TFREE * 8, 0);
      asm volatile("fence.acq_rel.cluster;\nfence.proxy.async.global;" ::: "memory");
      if (elect_one()) {
#pragma unroll
        for (int i = 0; i < 4; i++) {
          const int hd = 2 * (head & 1) + (i >> 1), jj = i & 1;
          asm volatile("cp.async.bulk.tensor.3d.shared::cluster.global.mbarrier::complete_tx::bytes.multicast::cluster [%0], [%1, {%3,%4,%5}], [%2], %6;"
                       ::"r"(sb + SM_TIN + hd * 6144 + jj * 3072), "l"(&mp.os), "r"(bar + B_TIN * 8), "r"(pw * 192), "r"(8 * TB + 2 * hd),
                         "r"(ph * 112 + strip * 16 + 8 * jj + 4 * (head >> 1)), "h"((uint16_t)(3 << (head & 2))) : "memory");
        }
      }
      __syncwarp();
    }
    cluster_sync();
  } else if (warp >= 8) {
    asm volatile("setmaxnreg.inc.sync.aligned.u32 %0;" ::"n"(RG));
    GemmCtx c;
    c.bar = bar;
    const int gw = warp - 8, tk = gw * 16 + (lane & 15), hi = lane >> 4;
    { const int col = tk >> 2, i = tk & 3;
      c.kC = sb + SM_K + (col + 3) * KS + hi * 128 + i * 16;
      c.vC = sb + SM_V + (col + 3) * 1536 + hi * 128 + (2 * i + ((col + 3) & 1)) * 16;
      c.qC = sb + SM_Q + col * 1536 + hi * 256 + (col & 1) * 64 + i * 16; }
    { const int ci = (tk >> 3) - 2, kc = ci < 3 ? ci : ci + 16, i = tk & 7; c.hvalid = gw > 0;
      c.kH = sb + SM_K + kc * KS + hi * 128 + i * 16;
      c.vH = sb + SM_V + kc * 1536 + hi * 128 + (i >> 2) * 768 + (2 * (i & 3) + ((kc ^ (i >> 2)) & 1)) * 16; }
    asm volatile("barrier.cluster.wait.aligned;" ::: "memory");
    if (elect_one()) { mbar_expect(bar + B_FULL * 8, 4608); mbar_expect(bar + (B_FULL + 1) * 8, 6144); mbar_expect(bar + (B_FULL + 2) * 8, 6144); }
    __syncwarp();
#pragma unroll
    for (int i = 0; i < 3; i++) sts128(sb + SM_W + (3 + (wc >> 1)) * 6144 + (wr + i * 64) * 32 + ((wc ^ (wr >> 2)) & 1) * 16, wv[i]);
    fence_async();
    asm volatile("bar.sync 1, 384;" ::: "memory");
    mbar_wait(bar + B_WK * 8, 0);
    uint32_t pk[12], pv[12], pq[12];
    TRDECL;
    gemm_iter<true, false>(c, -2, pk, pv, pq TRPASS);
#pragma unroll 1
    for (int b = -1; b < 12; b++) gemm_iter<false, false>(c, b, pk, pv, pq TRPASS);
    asm volatile("bar.sync 2, 128;" ::: "memory");
    if (gw == 0 && elect_one()) {
      mbar_expect(bar + B_WO * 8, 36864);
      asm volatile("cp.async.bulk.tensor.3d.shared::cluster.global.mbarrier::complete_tx::bytes [%0], [%1, {%3,%4,%5}], [%2];"
                   ::"r"(sb + SM_TWO), "l"(&mp.wo), "r"(bar + B_WO * 8), "r"(0), "r"(0), "r"((head & 1) * 3) : "memory");
    }
    __syncwarp();
    gemm_iter<false, true>(c, 12, pk, pv, pq TRPASS);
    TR(2, 13, 0);
    mbar_wait(bar + B_WO * 8, 0);
    TR(2, 13, 1);
    const uint32_t st = sb + SM_TST + gw * 3072;
    const uint32_t sta = st + (lane & 15) * 64 + ((hi ^ ((lane >> 1) & 3)) * 16);
#pragma unroll 1
    for (int i = 0; i < 3; i++) {
      constexpr uint64_t db = mkdesc(SBC + SM_TWO, 12288, 512, 2);
      const uint64_t da = mkdesc(SBC + SM_TIN, 128, 768, 0) + i * (24576 / 16);
      float D[48];
      mbar_wait(bar + (B_TIN + i) * 8, 0);
      if (i == 2) asm volatile("barrier.cluster.arrive.relaxed.aligned;" ::: "memory");
      else nb_sync(i ? N_PVISS : N_QK1, i ? 384 : 256);
      TR(2, 13 - i, 2); TR(2, 12 + i, 5); TR(2, 11 + i, 9);
      wg_fence();
      wg_ss96<0>(D, da, db);
#pragma unroll
      for (int k = 1; k < 12; k++) wg_ss96<1>(D, da + (k / 3) * 384 + (k % 3) * 16, db + k * 64);
      wg_commit();
      if (lane == 0) asm volatile("cp.async.bulk.wait_group.read 0;" ::: "memory");
      __syncwarp();
      wg_wait<0>(); pin(D);
      TR(2, 13 - i, 3); TR(2, 12 + i, 6); TR(2, 11 + i, 10);
#pragma unroll
      for (int q = 0; q < 6; q++)
        stsm4((sta ^ ((q & 1) * 32)) + (q >> 1) * 1024,
              pack2(D[8 * q], D[8 * q + 1]), pack2(D[8 * q + 2], D[8 * q + 3]), pack2(D[8 * q + 4], D[8 * q + 5]), pack2(D[8 * q + 6], D[8 * q + 7]));
      fence_async();
      __syncwarp();
      if (lane == 0) {
        asm volatile("cp.async.bulk.tensor.4d.global.shared::cta.bulk_group [%0, {%2,%3,%4,%5}], [%1];"
                     ::"l"(&mp.ot), "r"(st), "r"(0), "r"(8 * (TB + i)), "r"(ph * 112 + strip * 16 + 8 * (gw >> 1) + 4 * (head >> 1) + 2 * (gw & 1)), "r"(pw * 6 + (head & 1) * 3) : "memory");
        asm volatile("cp.async.bulk.commit_group;" ::: "memory");
      }
      TR(2, 13 - i, 4); TR(2, 12 + i, 7); TR(2, 11 + i, 11);
    }
    if (lane == 0) asm volatile("cp.async.bulk.wait_group.read 0;" ::: "memory");
    __syncwarp();
    TR(2, 13, 8);
    TR2(blockIdx.x, 2);
    TRDUMP;
    asm volatile("barrier.cluster.wait.aligned;" ::: "memory");
  } else {
    asm volatile("setmaxnreg.inc.sync.aligned.u32 %0;" ::"n"(RA));
    float rv = -INFINITY;
    if (tid < 169) rv = __bfloat162float(rpb[head * 169 + tid]) * 1.4426950408889634f;
    if (tid < 192) {
      const int kc = (wr & 15) + 3;
      sts128(tid < 96 ? sb + SM_K + kc * KS + wc * 128 + 48 : sb + SM_V + kc * 1536 + wc * 128 + (6 + (kc & 1)) * 16, make_uint4(0, 0, 0, 0));
    }
#pragma unroll
    for (int i = 0; i < 3; i++) sts128(sb + SM_W + (3 + (wc >> 1)) * 6144 + (wr + i * 64) * 32 + ((wc ^ (wr >> 2)) & 1) * 16, wv[i]);
    fence_async();
    asm volatile("bar.arrive 1, 384;" ::: "memory");
    if (tid < 182) asm volatile("st.shared.f32 [%0], %1;" ::"r"(sb + SM_RPB + tid * 4), "f"(rv) : "memory");
    const int j = warp >> 2, w = warp & 3;
    int variant = w;
    if (strip == 0 && j == 0 && w < 2) variant = 4;
    if (strip == 6 && j == 1 && w >= 2) variant = 5;
    const uint32_t qa = sb + SM_Q + (8 * j + 2 * w + ((lane >> 3) & 1)) * 1536 + (lane >> 4) * 256 + (((lane & 7) * 16) ^ (((lane >> 3) & 1) * 64));
    uint32_t oa = sb + SM_O + j * 6144 + (2 * w + ((lane >> 3) & 1)) * 768 + (lane >> 4) * 128 + (lane & 7) * 16;
    const uint64_t dK = mkdesc(SBC + SM_K, 128, KS, 0) + j * (8 * KS / 16);
    const uint64_t dV = mkdesc(SBC + SM_V, 768, 128, 0) + j * (8 * 1536 / 16);
    asm volatile("barrier.cluster.wait.aligned;" ::: "memory");
    asm volatile("bar.sync 3, 256;" ::: "memory");
    float T[16];
    TRDECL;
    int b0 = 0, b1 = 0;
    uint32_t meta = 0;
    uint32_t q[12];
    mbar_wait(bar + B_Q0 * 8, 0);
#pragma unroll
    for (int k = 0; k < 3; k++) ldsm4(qa + k * 512, q[4 * k], q[4 * k + 1], q[4 * k + 2], q[4 * k + 3]);
#pragma unroll 1
    for (int b = 0; b < 14; b++) {
      const uint32_t pa = b & 1;
      float SA[56], SB[56];
      const uint64_t dA = dK + pa * (KSLOT >> 4), dB = dK + (pa ^ 1) * (KSLOT >> 4);
      TR(0, b, 0);
      nb_sync(N_KRDY + j, 256);
      TR(0, b, 1);
      TR(0, b - 1, 9);
      wg_fence();
      wg_rs112<0>(SA, q[0], q[1], q[2], q[3], dA);
      wg_rs112<0>(SB, q[0], q[1], q[2], q[3], dB);
      wg_rs112<1>(SA, q[4], q[5], q[6], q[7], dA + 16);
      wg_rs112<1>(SB, q[4], q[5], q[6], q[7], dB + 16);
      wg_rs112<1>(SA, q[8], q[9], q[10], q[11], dA + 32);
      wg_rs112<1>(SB, q[8], q[9], q[10], q[11], dB + 32);
      wg_commit();
      nb_arrive(N_QK0 + j, 256);
      TR(0, b, 2);
      if (b <= 1 || b == 13) {
        uint32_t ln; asm volatile("mov.u32 %0, %%laneid;" : "=r"(ln));
        const int g = ln >> 2, t = ln & 3;
        const int sw = b == 0 ? max(g + 1, 4) : (b == 13 ? min(g + 1, 5) : g + 1);
        const int i0 = 2 * t, i1 = 2 * t + 1;
        b0 = i0 <= sw - 2; b1 = i1 <= sw - 2;
        const uint32_t tb = sb + SM_RPB + (variant < 4 ? 3 : variant + 1 - 2 * w) * 4;
        const uint32_t ra0 = tb + (i0 == sw - 1 ? 13 : i0 + 8 * b0 - g + 2) * 52;
        const uint32_t ra1 = tb + (i1 == sw - 1 ? 13 : i1 + 8 * b1 - g + 2) * 52;
#pragma unroll
        for (int jj = 0; jj < 8; jj++) { T[2 * jj] = lds_f32(ra0 + jj * 4); T[2 * jj + 1] = lds_f32(ra1 + jj * 4); }
        meta = ((0x5555u & ((1u << (2 * (sw - 1))) - 1)) ^ 0xDD88u ^ (((t ^ b) & 1) ? 0x5555u : 0u)) * 0x10001u;
        if (b == 13) oa += SM_Q - SM_O;
      } else meta ^= 0x55555555u;
      wg_wait<0>(); pin(SA); pin(SB);
      mbar_arrive_elect(bar + B_KFREE * 8);
      TR(0, b, 3);
      TR(0, b - 1, 10);
      uint32_t P[28];
      float sx[8];
      switch (variant) {
        case 0: softmax_tile<0, 1>(SA, SB, T, b0, b1, P, sx); break;
        case 1: softmax_tile<2, 3>(SA, SB, T, b0, b1, P, sx); break;
        case 2: softmax_tile<4, 5>(SA, SB, T, b0, b1, P, sx); break;
        case 3: softmax_tile<6, 7>(SA, SB, T, b0, b1, P, sx); break;
        case 4: softmax_tile<3, 3>(SA, SB, T, b0, b1, P, sx); break;
        default: softmax_tile<4, 4>(SA, SB, T, b0, b1, P, sx); break;
      }
      float O[24];
      TR(0, b, 4);
      nb_sync(N_VQ0 + j, b == 13 ? 256 : 288);
      TR(0, b, 5);
#pragma unroll
      for (int k = 0; k < 3; k++) ldsm4(qa + (pa ^ 1) * 128 + k * 512, q[4 * k], q[4 * k + 1], q[4 * k + 2], q[4 * k + 3]);
      wg_fence();
      wg_sp48<0>(O, P[0], P[1], P[2], P[3], dV, meta);
#pragma unroll
      for (int s = 1; s < 7; s++) wg_sp48<1>(O, P[4 * s], P[4 * s + 1], P[4 * s + 2], P[4 * s + 3], dV + s * 192, meta);
      wg_commit();
      if (b != 12) nb_arrive(N_PVISS, 384);
      TR(0, b, 6);
      wg_wait<0>(); pin(O);
      mbar_arrive_elect(bar + B_VFREE * 8);
      TR(0, b, 7);
      float ru, rl;
      asm("rcp.approx.ftz.f32 %0, %1;" : "=f"(ru) : "f"(((fmaf(O[0], 0.f, sx[0]) + sx[1]) + sx[2]) + sx[3]));
      asm("rcp.approx.ftz.f32 %0, %1;" : "=f"(rl) : "f"(((fmaf(O[2], 0.f, sx[4]) + sx[5]) + sx[6]) + sx[7]));
#pragma unroll
      for (int i = 0; i < 3; i++)
        stsm4(oa + i * 256, pack2(O[8 * i] * ru, O[8 * i + 1] * ru), pack2(O[8 * i + 2] * rl, O[8 * i + 3] * rl),
              pack2(O[8 * i + 4] * ru, O[8 * i + 5] * ru), pack2(O[8 * i + 6] * rl, O[8 * i + 7] * rl));
      if (b < 13) publish(bar + (B_ODONE + j) * 8);
      else {
        fence_async();
        mbar_wait(bar + B_TFREE * 8, 0);
        __syncwarp();
        if (elect_one()) {
#pragma unroll
          for (int d = 0; d < 2; d++)
            send_o<1536>(sb + SM_TIN + 2 * 24576 + head * 6144 + (2 * j + (w & 1)) * 1536, sb + SM_Q + warp * 1536, bar + (B_TIN + 2) * 8, (w & 2) + d);
        }
        __syncwarp();
      }
      TR(0, b, 8);
    }
    TRDUMP;
    cluster_sync();
  }
}

constexpr int NSTB = 6;
constexpr int NTB = TB * 56;
constexpr int SM_B_IN = 0;
constexpr int SM_B_W = SM_B_IN + NSTB * 24576;
constexpr int SM_B_BAR = SM_B_W + 73728;
constexpr int SM_B_TOTAL = SM_B_BAR + 128;
struct MapsB { CUtensorMap oi, oo, wo; };

__global__ void __launch_bounds__(480, 1)
na_proj_kernel(const __grid_constant__ MapsB mp) {
  extern __shared__ __align__(1024) uint8_t smem_raw[];
  const uint32_t sb = smem_u32(smem_raw);
  if ((sb & 0x3FFFF) != SBC) return;
  const uint32_t bar = sb + SM_B_BAR;
  const int tid = threadIdx.x, lane = tid & 31;
  const int warp = __shfl_sync(0xffffffffu, tid >> 5, 0);
  TR2(132 + blockIdx.x, 0);
  TRB(47, 0);
  if (warp == 12 && elect_one()) {
#pragma unroll
    for (int i = 0; i <= 2 * NSTB; i++) mbar_init(bar + i * 8, i < NSTB || i == 2 * NSTB ? 1 : 4);
    mbar_expect(bar + 2 * NSTB * 8, 73728);
#pragma unroll
    for (int i = 0; i < 2; i++)
      asm volatile("cp.async.bulk.tensor.3d.shared::cluster.global.mbarrier::complete_tx::bytes [%0], [%1, {%3,%4,%5}], [%2];"
                   ::"r"(sb + SM_B_W + i * 36864), "l"(&mp.wo), "r"(bar + 2 * NSTB * 8), "r"(0), "r"(0), "r"(i * 3) : "memory");
  }
  __syncthreads();
  const int step = gridDim.x;
  if (warp >= 12) {
    const int wg = warp - 12;
    int use = 0;
#pragma unroll 1
    for (int n = blockIdx.x + wg * step; n < NTB; n += 3 * step, use++) {
      const int b = n / 56, rem = n - b * 56, par = rem / 14, sg = wg + 3 * (use & 1);
      int v; uint32_t spin = 0;
      do { asm volatile("ld.acquire.gpu.global.s32 %0, [%1];" : "=r"(v) : "l"(g_flags + n) : "memory"); } while (v < 4 && ++spin < SPIN_LIMIT);
      asm volatile("fence.proxy.async.global;" ::: "memory");
      if (use >= 2) mbar_wait(bar + (NSTB + sg) * 8, ((use >> 1) - 1) & 1);
      if (elect_one()) {
        mbar_expect(bar + sg * 8, 24576);
        asm volatile("cp.async.bulk.tensor.3d.shared::cluster.global.mbarrier::complete_tx::bytes [%0], [%1, {%3,%4,%5}], [%2];"
                     ::"r"(sb + SM_B_IN + sg * 24576), "l"(&mp.oi), "r"(bar + sg * 8), "r"((par & 1) * 192), "r"(8 * b), "r"((par >> 1) * 112 + (rem - par * 14) * 8) : "memory");
        g_flags[n] = 0;
      }
      __syncwarp();
    }
  } else {
    const int wg = warp >> 2, w = warp & 3;
    constexpr uint64_t db = mkdesc(SBC + SM_B_W, 12288, 512, 2);
    const uint32_t sta0 = sb + SM_B_IN + w * 6144 + (lane & 15) * 128 + (((lane >> 4) ^ (lane & 7)) * 16);
    mbar_wait(bar + 2 * NSTB * 8, 0);
    TRB(47, 1);
    int use = 0;
#pragma unroll 1
    for (int n = blockIdx.x + wg * step; n < NTB; n += 3 * step, use++) {
      const int b = n / 56, rem = n - b * 56, par = rem / 14, sg = wg + 3 * (use & 1);
      const uint64_t da = mkdesc(SBC + SM_B_IN, 128, 3072, 0) + sg * (24576 / 16);
      float D[96];
      mbar_wait(bar + sg * 8, (use >> 1) & 1);
      if (use | wg) nb_sync(4 + wg, 256);
      TRB(use * 3 + wg, 3);
      wg_fence();
      wg_ss192<0>(D, da, db);
#pragma unroll
      for (int k = 1; k < 12; k++) wg_ss192<1>(D, da + k * 16, db + k * 64);
      wg_commit();
      if (n + step < NTB) nb_arrive(wg == 2 ? 4 : 5 + wg, 256);
      TRB(use * 3 + wg, 4);
      if (use && lane == 0) {
        asm volatile("cp.async.bulk.wait_group.read 0;" ::: "memory");
        mbar_arrive(bar + (NSTB + wg + 3 * (~use & 1)) * 8);
      }
      __syncwarp();
      wg_wait<0>(); pin(D);
      nb_sync(1 + wg, 128);
      TRB(use * 3 + wg, 5);
      const uint32_t sta = sta0 + sg * 24576;
#pragma unroll
      for (int q = 0; q < 12; q++)
        stsm4((sta ^ ((q & 3) * 32)) + (q >> 2) * 2048,
              pack2(D[8 * q], D[8 * q + 1]), pack2(D[8 * q + 2], D[8 * q + 3]), pack2(D[8 * q + 4], D[8 * q + 5]), pack2(D[8 * q + 6], D[8 * q + 7]));
      fence_async();
      __syncwarp();
      if (lane == 0) {
        asm volatile("cp.async.bulk.tensor.4d.global.shared::cta.bulk_group [%0, {%2,%3,%4,%5}], [%1];"
                     ::"l"(&mp.oo), "r"(sb + SM_B_IN + sg * 24576 + w * 6144), "r"(0), "r"(8 * b), "r"((par >> 1) * 112 + (rem - par * 14) * 8 + 2 * w), "r"((par & 1) * 3) : "memory");
        asm volatile("cp.async.bulk.commit_group;" ::: "memory");
      }
      __syncwarp();
      TRB(use * 3 + wg, 6);
    }
    if (lane == 0) asm volatile("cp.async.bulk.wait_group 0;" ::: "memory");
    TR2(132 + blockIdx.x, 2);
  }
}

typedef CUresult (*EncodeFn)(CUtensorMap*, CUtensorMapDataType, cuuint32_t, void*, const cuuint64_t*, const cuuint64_t*, const cuuint32_t*,
                             const cuuint32_t*, CUtensorMapInterleave, CUtensorMapSwizzle, CUtensorMapL2promotion, CUtensorMapFloatOOBfill);
static EncodeFn g_enc = nullptr;
static void make_map(CUtensorMap* m, const void* p, int rank, const cuuint64_t* dim, const cuuint64_t* str, const cuuint32_t* box, CUtensorMapSwizzle sw) {
  const cuuint32_t ones[5] = {1, 1, 1, 1, 1};
  g_enc(m, CU_TENSOR_MAP_DATA_TYPE_BFLOAT16, rank, (void*)p, dim, str, box, ones, CU_TENSOR_MAP_INTERLEAVE_NONE, sw,
        CU_TENSOR_MAP_L2_PROMOTION_L2_128B, CU_TENSOR_MAP_FLOAT_OOB_FILL_NONE);
}

extern "C" void kernel_launch(void* const* d_in, const int* in_sizes, int n_in, void* d_out, int out_size) {
  const __nv_bfloat16* x = (const __nv_bfloat16*)d_in[0];
  const __nv_bfloat16* wqkv = (const __nv_bfloat16*)d_in[1];
  const __nv_bfloat16* wo = (const __nv_bfloat16*)d_in[2];
  const __nv_bfloat16* rpb = (const __nv_bfloat16*)d_in[3];

  if (!g_enc) {
    void* fn = nullptr; cudaDriverEntryPointQueryResult qr;
    cudaGetDriverEntryPoint("cuTensorMapEncodeTiled", &fn, cudaEnableDefault, &qr);
    g_enc = (EncodeFn)fn;
    cudaFuncSetAttribute(na_attn_kernel, cudaFuncAttributeMaxDynamicSharedMemorySize, SM_A_TOTAL);
    cudaFuncSetAttribute(na_proj_kernel, cudaFuncAttributeMaxDynamicSharedMemorySize, SM_B_TOTAL);
  }
  Maps ma; MapsB mb;
  { cuuint64_t dim[4] = {64, 112, 224, 6}, str[3] = {(cuuint64_t)ROWB, 768, 128};
    cuuint32_t box[4] = {64, 4, 16, 3}, boxo[4] = {64, 8, 2, 3};
    make_map(&ma.xc, x, 4, dim, str, box, CU_TENSOR_MAP_SWIZZLE_128B);
    make_map(&mb.oo, d_out, 4, dim, str, boxo, CU_TENSOR_MAP_SWIZZLE_128B); }
  { cuuint64_t dim[5] = {64, 112, 224, 2, 6}, str[4] = {(cuuint64_t)ROWB, 768, 19 * 768, 128};
    cuuint32_t box[5] = {64, 8, 3, 2, 3};
    make_map(&ma.xh, x, 5, dim, str, box, CU_TENSOR_MAP_SWIZZLE_128B); }
  { cuuint64_t dim[3] = {384, 112, 224}, str[2] = {(cuuint64_t)ROWB, 768};
    cuuint32_t box[3] = {192, 8, 8}, boxs[3] = {192, 2, 4};
    make_map(&mb.oi, d_out, 3, dim, str, box, CU_TENSOR_MAP_SWIZZLE_NONE);
    make_map(&ma.os, d_out, 3, dim, str, boxs, CU_TENSOR_MAP_SWIZZLE_NONE); }
  { cuuint64_t dim[4] = {32, 112, 224, 12}, str[3] = {(cuuint64_t)ROWB, 768, 64};
    cuuint32_t box[4] = {32, 8, 2, 3};
    make_map(&ma.ot, d_out, 4, dim, str, box, CU_TENSOR_MAP_SWIZZLE_64B); }
  { cuuint64_t dim[2] = {576, 192}, str[1] = {1152};
    cuuint32_t box[2] = {16, 192};
    make_map(&ma.w, wqkv, 2, dim, str, box, CU_TENSOR_MAP_SWIZZLE_32B); }
  { cuuint64_t dim[3] = {32, 192, 6}, str[2] = {384, 64};
    cuuint32_t box[3] = {32, 192, 3};
    make_map(&ma.wo, wo, 3, dim, str, box, CU_TENSOR_MAP_SWIZZLE_64B);
    mb.wo = ma.wo; }
  na_attn_kernel<<<112, 512, SM_A_TOTAL>>>(ma, wqkv, rpb);
  cudaLaunchConfig_t cfg = {};
  cfg.gridDim = dim3(20); cfg.blockDim = dim3(480); cfg.dynamicSmemBytes = SM_B_TOTAL; cfg.stream = cudaStreamPerThread;
  cudaLaunchAttribute at[1];
  at[0].id = cudaLaunchAttributeProgrammaticStreamSerialization; at[0].val.programmaticStreamSerializationAllowed = 1;
  cfg.attrs = at; cfg.numAttrs = 1;
  cudaLaunchKernelEx(&cfg, na_proj_kernel, mb);
}
```

```cpp
#include <cuda_runtime.h>
#include <cuda_bf16.h>
#include <cuda.h>
#include <stdint.h>

#define SPIN_LIMIT (1u << 18)

__device__ __forceinline__ uint32_t smem_u32(const void* p) { return (uint32_t)__cvta_generic_to_shared(p); }
__device__ __forceinline__ void wg_fence() { asm volatile("wgmma.fence.sync.aligned;" ::: "memory"); }
__device__ __forceinline__ void wg_commit() { asm volatile("wgmma.commit_group.sync.aligned;" ::: "memory"); }
template <int N> __device__ __forceinline__ void wg_wait() { asm volatile("wgmma.wait_group.sync.aligned %0;" ::"n"(N) : "memory"); }
template <int N> __device__ __forceinline__ void pin(float (&d)[N]) {
#pragma unroll
  for (int i = 0; i < N; i++) asm volatile("" : "+f"(d[i])::"memory");
}
__host__ __device__ constexpr uint64_t mkdesc(uint32_t addr, uint32_t lbo, uint32_t sbo, uint32_t sw) {
  return (uint64_t)((addr & 0x3FFFF) >> 4) | ((uint64_t)(lbo >> 4) << 16) | ((uint64_t)(sbo >> 4) << 32) | ((uint64_t)sw << 62);
}
__device__ __forceinline__ void mbar_init(uint32_t bar, uint32_t cnt) { asm volatile("mbarrier.init.shared::cta.b64 [%0], %1;" ::"r"(bar), "r"(cnt) : "memory"); }
__device__ __forceinline__ void mbar_arrive(uint32_t bar) { asm volatile("mbarrier.arrive.shared::cta.b64 _, [%0];" ::"r"(bar) : "memory"); }
__device__ __forceinline__ bool elect_one() {
  uint32_t r; asm volatile("{\n.reg .pred p;\nelect.sync _|p, 0xffffffff;\nselp.u32 %0, 1, 0, p;\n}" : "=r"(r)); return r;
}
__device__ __forceinline__ void mbar_arrive_elect(uint32_t bar) {
  asm volatile("{\n.reg .pred p;\nelect.sync _|p, 0xffffffff;\n@p mbarrier.arrive.shared::cta.b64 _, [%0];\n}" ::"r"(bar) : "memory");
}
__device__ __forceinline__ void mbar_expect(uint32_t bar, uint32_t bytes) { asm volatile("mbarrier.arrive.expect_tx.shared::cta.b64 _, [%0], %1;" ::"r"(bar), "r"(bytes) : "memory"); }
__device__ __forceinline__ void mbar_arrive_remote(uint32_t bar, uint32_t cta) {
  asm volatile("{\n.reg .b32 ra;\nmapa.shared::cluster.u32 ra, %0, %1;\nmbarrier.arrive.relaxed.cluster.shared::cluster.b64 _, [ra];\n}" ::"r"(bar), "r"(cta) : "memory");
}
__device__ __forceinline__ void mbar_wait(uint32_t bar, uint32_t parity) {
  asm volatile("{\n.reg .pred p;\n.reg .b32 n;\nmov.b32 n, 0;\nWL:\nmbarrier.try_wait.parity.shared::cta.b64 p, [%0], %1;\n@p bra WD;\n"
               "add.u32 n, n, 1;\nsetp.lt.u32 p, n, 65536;\n@p bra WL;\nWD:\n}" ::"r"(bar), "r"(parity) : "memory");
}
__device__ __forceinline__ void nb_sync(int id, int n) { asm volatile("bar.sync %0, %1;" ::"r"(id), "r"(n) : "memory"); }
__device__ __forceinline__ void nb_arrive(int id, int n) { asm volatile("bar.arrive %0, %1;" ::"r"(id), "r"(n) : "memory"); }
__device__ __forceinline__ void fence_async() { asm volatile("fence.proxy.async.shared::cta;" ::: "memory"); }
__device__ __forceinline__ void cluster_sync() {
  asm volatile("barrier.cluster.arrive.relaxed.aligned;\nbarrier.cluster.wait.aligned;" ::: "memory");
}
__device__ __forceinline__ uint32_t pack2(float lo, float hi) {
  uint32_t r; asm("cvt.rn.bf16x2.f32 %0, %1, %2;" : "=r"(r) : "f"(hi), "f"(lo)); return r;
}
__device__ __forceinline__ void stsm4(uint32_t a, uint32_t r0, uint32_t r1, uint32_t r2, uint32_t r3) {
  asm volatile("stmatrix.sync.aligned.m8n8.x4.shared.b16 [%0], {%1,%2,%3,%4};" ::"r"(a), "r"(r0), "r"(r1), "r"(r2), "r"(r3) : "memory");
}
__device__ __forceinline__ void ldsm4(uint32_t a, uint32_t& r0, uint32_t& r1, uint32_t& r2, uint32_t& r3) {
  asm volatile("ldmatrix.sync.aligned.m8n8.x4.shared.b16 {%0,%1,%2,%3}, [%4];" : "=r"(r0), "=r"(r1), "=r"(r2), "=r"(r3) : "r"(a) : "memory");
}
__device__ __forceinline__ void sts128(uint32_t a, uint4 v) {
  asm volatile("st.shared.v4.b32 [%0], {%1,%2,%3,%4};" ::"r"(a), "r"(v.x), "r"(v.y), "r"(v.z), "r"(v.w) : "memory");
}
__device__ __forceinline__ float lds_f32(uint32_t a) { float v; asm volatile("ld.shared.f32 %0, [%1];" : "=f"(v) : "r"(a)); return v; }
__device__ __forceinline__ float ex2(float x) { float y; asm("ex2.approx.ftz.f32 %0, %1;" : "=f"(y) : "f"(x)); return y; }

template<int SC> __device__ __forceinline__ void wg_ss144(float (&d)[72], uint64_t da, uint64_t db) {
  asm volatile("{\n.reg .pred p;\nsetp.ne.b32 p, %74, 0;\nwgmma.mma_async.sync.aligned.m64n144k16.f32.bf16.bf16 {%0,%1,%2,%3,%4,%5,%6,%7,%8,%9,%10,%11,%12,%13,%14,%15,%16,%17,%18,%19,%20,%21,%22,%23,%24,%25,%26,%27,%28,%29,%30,%31,%32,%33,%34,%35,%36,%37,%38,%39,%40,%41,%42,%43,%44,%45,%46,%47,%48,%49,%50,%51,%52,%53,%54,%55,%56,%57,%58,%59,%60,%61,%62,%63,%64,%65,%66,%67,%68,%69,%70,%71}, %72, %73, p, 1, 1, 0, 1;\n}\n"
    : "+f"(d[0]),"+f"(d[1]),"+f"(d[2]),"+f"(d[3]),"+f"(d[4]),"+f"(d[5]),"+f"(d[6]),"+f"(d[7]),"+f"(d[8]),"+f"(d[9]),"+f"(d[10]),"+f"(d[11]),"+f"(d[12]),"+f"(d[13]),"+f"(d[14]),"+f"(d[15]),"+f"(d[16]),"+f"(d[17]),"+f"(d[18]),"+f"(d[19]),"+f"(d[20]),"+f"(d[21]),"+f"(d[22]),"+f"(d[23]),"+f"(d[24]),"+f"(d[25]),"+f"(d[26]),"+f"(d[27]),"+f"(d[28]),"+f"(d[29]),"+f"(d[30]),"+f"(d[31]),"+f"(d[32]),"+f"(d[33]),"+f"(d[34]),"+f"(d[35]),"+f"(d[36]),"+f"(d[37]),"+f"(d[38]),"+f"(d[39]),"+f"(d[40]),"+f"(d[41]),"+f"(d[42]),"+f"(d[43]),"+f"(d[44]),"+f"(d[45]),"+f"(d[46]),"+f"(d[47]),"+f"(d[48]),"+f"(d[49]),"+f"(d[50]),"+f"(d[51]),"+f"(d[52]),"+f"(d[53]),"+f"(d[54]),"+f"(d[55]),"+f"(d[56]),"+f"(d[57]),"+f"(d[58]),"+f"(d[59]),"+f"(d[60]),"+f"(d[61]),"+f"(d[62]),"+f"(d[63]),"+f"(d[64]),"+f"(d[65]),"+f"(d[66]),"+f"(d[67]),"+f"(d[68]),"+f"(d[69]),"+f"(d[70]),"+f"(d[71]) : "l"(da), "l"(db), "n"(SC));
}
template<int SC> __device__ __forceinline__ void wg_ss96(float (&d)[48], uint64_t da, uint64_t db) {
  asm volatile("{\n.reg .pred p;\nsetp.ne.b32 p, %50, 0;\nwgmma.mma_async.sync.aligned.m64n96k16.f32.bf16.bf16 {%0,%1,%2,%3,%4,%5,%6,%7,%8,%9,%10,%11,%12,%13,%14,%15,%16,%17,%18,%19,%20,%21,%22,%23,%24,%25,%26,%27,%28,%29,%30,%31,%32,%33,%34,%35,%36,%37,%38,%39,%40,%41,%42,%43,%44,%45,%46,%47}, %48, %49, p, 1, 1, 0, 1;\n}\n"
    : "+f"(d[0]),"+f"(d[1]),"+f"(d[2]),"+f"(d[3]),"+f"(d[4]),"+f"(d[5]),"+f"(d[6]),"+f"(d[7]),"+f"(d[8]),"+f"(d[9]),"+f"(d[10]),"+f"(d[11]),"+f"(d[12]),"+f"(d[13]),"+f"(d[14]),"+f"(d[15]),"+f"(d[16]),"+f"(d[17]),"+f"(d[18]),"+f"(d[19]),"+f"(d[20]),"+f"(d[21]),"+f"(d[22]),"+f"(d[23]),"+f"(d[24]),"+f"(d[25]),"+f"(d[26]),"+f"(d[27]),"+f"(d[28]),"+f"(d[29]),"+f"(d[30]),"+f"(d[31]),"+f"(d[32]),"+f"(d[33]),"+f"(d[34]),"+f"(d[35]),"+f"(d[36]),"+f"(d[37]),"+f"(d[38]),"+f"(d[39]),"+f"(d[40]),"+f"(d[41]),"+f"(d[42]),"+f"(d[43]),"+f"(d[44]),"+f"(d[45]),"+f"(d[46]),"+f"(d[47]) : "l"(da), "l"(db), "n"(SC));
}
template<int SC> __device__ __forceinline__ void wg_rs112(float (&d)[56], uint32_t a0, uint32_t a1, uint32_t a2, uint32_t a3, uint64_t db) {
  asm volatile("{\n.reg .pred p;\nsetp.ne.b32 p, %61, 0;\nwgmma.mma_async.sync.aligned.m64n112k16.f32.bf16.bf16 {%0,%1,%2,%3,%4,%5,%6,%7,%8,%9,%10,%11,%12,%13,%14,%15,%16,%17,%18,%19,%20,%21,%22,%23,%24,%25,%26,%27,%28,%29,%30,%31,%32,%33,%34,%35,%36,%37,%38,%39,%40,%41,%42,%43,%44,%45,%46,%47,%48,%49,%50,%51,%52,%53,%54,%55}, {%56,%57,%58,%59}, %60, p, 1, 1, 0;\n}\n"
    : "+f"(d[0]),"+f"(d[1]),"+f"(d[2]),"+f"(d[3]),"+f"(d[4]),"+f"(d[5]),"+f"(d[6]),"+f"(d[7]),"+f"(d[8]),"+f"(d[9]),"+f"(d[10]),"+f"(d[11]),"+f"(d[12]),"+f"(d[13]),"+f"(d[14]),"+f"(d[15]),"+f"(d[16]),"+f"(d[17]),"+f"(d[18]),"+f"(d[19]),"+f"(d[20]),"+f"(d[21]),"+f"(d[22]),"+f"(d[23]),"+f"(d[24]),"+f"(d[25]),"+f"(d[26]),"+f"(d[27]),"+f"(d[28]),"+f"(d[29]),"+f"(d[30]),"+f"(d[31]),"+f"(d[32]),"+f"(d[33]),"+f"(d[34]),"+f"(d[35]),"+f"(d[36]),"+f"(d[37]),"+f"(d[38]),"+f"(d[39]),"+f"(d[40]),"+f"(d[41]),"+f"(d[42]),"+f"(d[43]),"+f"(d[44]),"+f"(d[45]),"+f"(d[46]),"+f"(d[47]),"+f"(d[48]),"+f"(d[49]),"+f"(d[50]),"+f"(d[51]),"+f"(d[52]),"+f"(d[53]),"+f"(d[54]),"+f"(d[55]) : "r"(a0), "r"(a1), "r"(a2), "r"(a3), "l"(db), "n"(SC));
}
template<int SC> __device__ __forceinline__ void wg_sp48(float (&d)[24], uint32_t a0, uint32_t a1, uint32_t a2, uint32_t a3, uint64_t db, uint32_t meta) {
  asm volatile("{\n.reg .pred p;\nsetp.ne.b32 p, %30, 0;\nwgmma.mma_async.sp.sync.aligned.m64n48k32.f32.bf16.bf16 {%0,%1,%2,%3,%4,%5,%6,%7,%8,%9,%10,%11,%12,%13,%14,%15,%16,%17,%18,%19,%20,%21,%22,%23}, {%24,%25,%26,%27}, %28, %29, 0, p, 1, 1, 1;\n}\n"
    : "+f"(d[0]),"+f"(d[1]),"+f"(d[2]),"+f"(d[3]),"+f"(d[4]),"+f"(d[5]),"+f"(d[6]),"+f"(d[7]),"+f"(d[8]),"+f"(d[9]),"+f"(d[10]),"+f"(d[11]),"+f"(d[12]),"+f"(d[13]),"+f"(d[14]),"+f"(d[15]),"+f"(d[16]),"+f"(d[17]),"+f"(d[18]),"+f"(d[19]),"+f"(d[20]),"+f"(d[21]),"+f"(d[22]),"+f"(d[23]) : "r"(a0), "r"(a1), "r"(a2), "r"(a3), "l"(db), "r"(meta), "n"(SC));
}
template<int SC> __device__ __forceinline__ void wg_ss192(float (&d)[96], uint64_t da, uint64_t db) {
  asm volatile("{\n.reg .pred p;\nsetp.ne.b32 p, %98, 0;\nwgmma.mma_async.sync.aligned.m64n192k16.f32.bf16.bf16 {%0,%1,%2,%3,%4,%5,%6,%7,%8,%9,%10,%11,%12,%13,%14,%15,%16,%17,%18,%19,%20,%21,%22,%23,%24,%25,%26,%27,%28,%29,%30,%31,%32,%33,%34,%35,%36,%37,%38,%39,%40,%41,%42,%43,%44,%45,%46,%47,%48,%49,%50,%51,%52,%53,%54,%55,%56,%57,%58,%59,%60,%61,%62,%63,%64,%65,%66,%67,%68,%69,%70,%71,%72,%73,%74,%75,%76,%77,%78,%79,%80,%81,%82,%83,%84,%85,%86,%87,%88,%89,%90,%91,%92,%93,%94,%95}, %96, %97, p, 1, 1, 0, 1;\n}\n"
    : "+f"(d[0]),"+f"(d[1]),"+f"(d[2]),"+f"(d[3]),"+f"(d[4]),"+f"(d[5]),"+f"(d[6]),"+f"(d[7]),"+f"(d[8]),"+f"(d[9]),"+f"(d[10]),"+f"(d[11]),"+f"(d[12]),"+f"(d[13]),"+f"(d[14]),"+f"(d[15]),"+f"(d[16]),"+f"(d[17]),"+f"(d[18]),"+f"(d[19]),"+f"(d[20]),"+f"(d[21]),"+f"(d[22]),"+f"(d[23]),"+f"(d[24]),"+f"(d[25]),"+f"(d[26]),"+f"(d[27]),"+f"(d[28]),"+f"(d[29]),"+f"(d[30]),"+f"(d[31]),"+f"(d[32]),"+f"(d[33]),"+f"(d[34]),"+f"(d[35]),"+f"(d[36]),"+f"(d[37]),"+f"(d[38]),"+f"(d[39]),"+f"(d[40]),"+f"(d[41]),"+f"(d[42]),"+f"(d[43]),"+f"(d[44]),"+f"(d[45]),"+f"(d[46]),"+f"(d[47]),"+f"(d[48]),"+f"(d[49]),"+f"(d[50]),"+f"(d[51]),"+f"(d[52]),"+f"(d[53]),"+f"(d[54]),"+f"(d[55]),"+f"(d[56]),"+f"(d[57]),"+f"(d[58]),"+f"(d[59]),"+f"(d[60]),"+f"(d[61]),"+f"(d[62]),"+f"(d[63]),"+f"(d[64]),"+f"(d[65]),"+f"(d[66]),"+f"(d[67]),"+f"(d[68]),"+f"(d[69]),"+f"(d[70]),"+f"(d[71]),"+f"(d[72]),"+f"(d[73]),"+f"(d[74]),"+f"(d[75]),"+f"(d[76]),"+f"(d[77]),"+f"(d[78]),"+f"(d[79]),"+f"(d[80]),"+f"(d[81]),"+f"(d[82]),"+f"(d[83]),"+f"(d[84]),"+f"(d[85]),"+f"(d[86]),"+f"(d[87]),"+f"(d[88]),"+f"(d[89]),"+f"(d[90]),"+f"(d[91]),"+f"(d[92]),"+f"(d[93]),"+f"(d[94]),"+f"(d[95]) : "l"(da), "l"(db), "n"(SC));
}

constexpr uint32_t SBC = 1024;
constexpr int ROWB = 2 * 224 * 384;
constexpr int TB = 11;
constexpr int KS = 832;
constexpr int KSLOT = 22 * KS;
constexpr int SM_X1 = 0;
constexpr int SM_X2 = SM_X1 + 24576;
constexpr int SM_X0 = SM_X2 + 24576;
constexpr int SM_W = SM_X0 + 18432;
constexpr int SM_K = SM_W + 55296;
constexpr int SM_V = SM_K + 2 * KSLOT;
constexpr int SM_Q = SM_V + 22 * 1536;
constexpr int SM_O = SM_Q + 24576;
constexpr int SM_RPB = SM_O + 12288;
constexpr int SM_BAR = SM_RPB + 768;
constexpr int SM_A_TOTAL = SM_BAR + 256;
constexpr int SM_TWO = SM_X0 + 24576;
constexpr int SM_TST = SM_TWO + 36864;
enum { B_FULL = 0, B_EMPTY = 3, B_TIN = 6, B_TFREE = 9, B_WK = 11, B_WQ, B_WO, B_Q0, B_ODONE, B_KFREE = B_ODONE + 2, B_VFREE, B_COUNT };
enum { N_KRDY = 4, N_QK0, N_QK1, N_VQ0, N_VQ1, N_PVISS };

#define SPL 4
#define RA 152
#define RG 184
__device__ int g_flags[TB * 56];

#define TR(role, it, k)
#define TRDECL
#define TRARG
#define TRPASS
#define TRDUMP
#define TRB(it, k)
#define TR2(blk, k)

struct GemmCtx {
  uint32_t bar;
  uint32_t kC, vC, qC;
  uint32_t kH, vH;
  bool hvalid;
};

template <int STRIDE> __device__ __forceinline__ void dump12(uint32_t a, const uint32_t (&r)[12]) {
#pragma unroll
  for (int j = 0; j < 3; j++) stsm4(a + j * 2 * STRIDE, r[4 * j], r[4 * j + 1], r[4 * j + 2], r[4 * j + 3]);
}
template <int N> __device__ __forceinline__ void pack12(uint32_t (&r)[12], const float (&d)[N], int off) {
#pragma unroll
  for (int j = 0; j < 12; j++) r[j] = pack2(d[off + 2 * j], d[off + 2 * j + 1]);
}
template <int XS, int K0, int K1> __device__ __forceinline__ void issue_core(float (&d)[72]) {
  constexpr uint64_t da = mkdesc(SBC + XS, 16, 1024, 1), db = mkdesc(SBC + SM_W, 6144, 256, 3);
  wg_fence();
  if (K0 == 0) wg_ss144<0>(d, da, db);
#pragma unroll
  for (int k = K0 ? K0 : 1; k < K1; k++) wg_ss144<1>(d, da + (k >> 2) * 512 + (k & 3) * 2, db + k * 32);
  wg_commit();
}
template <int K0, int K1> __device__ __forceinline__ void issue_halo(float (&d)[48]) {
  constexpr uint64_t da = mkdesc(SBC + SM_X0 - 2048, 16, 1024, 1), db = mkdesc(SBC + SM_W, 6144, 256, 3);
  wg_fence();
  if (K0 == 0) wg_ss96<0>(d, da, db);
#pragma unroll
  for (int k = K0 ? K0 : 1; k < K1; k++) wg_ss96<1>(d, da + (k >> 2) * 384 + (k & 3) * 2, db + k * 32);
  wg_commit();
}
template <int ST, int BYTES> __device__ __forceinline__ void release_stage(const GemmCtx& c, bool on) {
  asm volatile("{\n.reg .pred p, q;\n.reg .b32 ra;\nsetp.ne.b32 q, %2, 0;\nelect.sync _|p, 0xffffffff;\nand.pred p, p, q;\n"
               "mapa.shared::cluster.u32 ra, %1, %4;\n"
               "@p mbarrier.arrive.expect_tx.shared::cta.b64 _, [%0], %3;\n@p mbarrier.arrive.shared::cluster.b64 _, [ra];\n}"
               ::"r"(c.bar + (B_FULL + ST) * 8), "r"(c.bar + (B_EMPTY + ST) * 8), "r"((int)on), "n"(BYTES / 4), "n"(ST) : "memory");
}
__device__ __forceinline__ void load_w(const CUtensorMap* m, uint32_t dst, uint32_t bar, int col) {
  asm volatile("cp.async.bulk.tensor.2d.shared::cluster.global.mbarrier::complete_tx::bytes [%0], [%1, {%3,%4}], [%2];"
               ::"r"(dst), "l"(m), "r"(bar), "r"(col), "r"(0) : "memory");
}
template <int BYTES> __device__ __forceinline__ void send_o(uint32_t dst, uint32_t src, uint32_t bar, int cta) {
  asm volatile("{\n.reg .b32 rd, rb;\nmapa.shared::cluster.u32 rd, %0, %3;\nmapa.shared::cluster.u32 rb, %2, %3;\n"
               "cp.async.bulk.shared::cluster.shared::cta.mbarrier::complete_tx::bytes [rd], [%1], %4, [rb];\n}"
               ::"r"(dst), "r"(src), "r"(bar), "r"(cta), "n"(BYTES) : "memory");
}
__device__ __forceinline__ void tail_free(uint32_t bar) {
  uint32_t ln; asm volatile("mov.u32 %0, %%laneid;" : "=r"(ln));
  if (ln < 4) mbar_arrive_remote(bar, ln);
}
__device__ __forceinline__ void publish(uint32_t bar) {
  fence_async();
  __syncwarp();
  mbar_arrive_elect(bar);
}

template <bool FIRST, bool LAST>
__device__ __forceinline__ void gemm_iter(const GemmCtx& c, int b, uint32_t (&pk)[12], uint32_t (&pv)[12], uint32_t (&pq)[12], const CUtensorMap* mwo TRARG) {
  const uint32_t bar = c.bar;
  const uint32_t pa = b & 1;
  const bool w = b >= 0;
  const uint32_t ko = pa * KSLOT, vx = pa * 16, qx = pa * 128;
  float H[48], C[72];
  uint32_t hk[12], hv[12], pv2[12];
  TR(2, b, 0);
  if (FIRST) mbar_wait(bar + (B_FULL + 0) * 8, pa);
  if (w) nb_sync(N_QK1, 256);
  TR(2, b, 2);
  issue_halo<0, 8>(H);
  TR(2, b, 3);
  if (!FIRST) {
    if (w) mbar_wait(bar + B_KFREE * 8, pa);
    dump12<128>(c.kC + ko, pk);
  }
  issue_halo<8, 12>(H);
  TR(2, b, 4);
  if (!LAST) {
    mbar_wait(bar + (B_FULL + 2) * 8, pa);
    if (FIRST) mbar_wait(bar + B_WQ * 8, 0);
    TR(2, b, 13);
    issue_core<SM_X2, 0, 8>(C);
    TR(2, b, 5);
    if (!FIRST) { fence_async(); dump12<256>(c.qC ^ (qx ^ 192), pq); }
    wg_wait<1>(); pin(H);
    release_stage<0, 18432>(c, true);
  } else {
    dump12<256>(c.qC ^ (qx ^ 192), pq);
    fence_async();
    nb_arrive(N_VQ0, 288); nb_arrive(N_VQ1, 288);
    wg_wait<0>(); pin(H);
    tail_free(bar + (B_TFREE + 1) * 8);
    nb_sync(2, 128);
    if (!c.hvalid && elect_one()) {
      mbar_expect(bar + B_WO * 8, 36864);
      asm volatile("cp.async.bulk.tensor.3d.shared::cluster.global.mbarrier::complete_tx::bytes [%0], [%1, {%3,%4,%5}], [%2];"
                   ::"r"(bar - SM_BAR + SM_TWO), "l"(mwo), "r"(bar + B_WO * 8), "r"(0), "r"(0), "r"((blockIdx.x & 1) * 3) : "memory");
    }
    __syncwarp();
  }
  pack12(hk, H, 0);
  if (c.hvalid) dump12<128>(c.kH + ko, hk);
  pack12(hv, H, 24);
  if (!LAST) {
    issue_core<SM_X2, 8, 12>(C);
    if (w) { nb_arrive(N_VQ0, 288); nb_arrive(N_VQ1, 288); }
    else if (!FIRST) { __syncwarp(); mbar_arrive_elect(bar + B_Q0 * 8); }
    mbar_wait(bar + (B_FULL + 1) * 8, pa);
    TR(2, b, 6);
    wg_wait<0>(); pin(C);
    TR(2, b, 7);
    pack12(pk, C, 0);
    dump12<128>(c.kC + ko + 64, pk);
    release_stage<2, 24576>(c, b < 11);
    if (b == 11) tail_free(bar + B_TFREE * 8);
    pack12(pv2, C, 24);
    pack12(pq, C, 48);
    TR(2, b, 8);
    issue_core<SM_X1, 0, SPL>(C);
    if (w) nb_sync(N_PVISS, 384);
    issue_core<SM_X1, SPL, 8>(C);
    TR(2, b, 9);
  }
  if (!FIRST) fence_async();
  TR(2, b, 14);
  if (!LAST) issue_core<SM_X1, 8, 12>(C);
  if (!FIRST) nb_arrive(N_KRDY, 256);
  TR(2, b, 1);
  if (!LAST) mbar_wait(bar + (B_FULL + 0) * 8, pa ^ 1);
  if (w) mbar_wait(bar + B_VFREE * 8, pa);
  TR(2, b, 10);
  if (!FIRST) dump12<128>(c.vC ^ vx, pv);
  if (!LAST) dump12<256>(c.qC ^ qx, pq);
  if (c.hvalid) dump12<128>(c.vH ^ vx, hv);
  if (LAST) { fence_async(); nb_arrive(N_VQ0, 256); nb_arrive(N_VQ1, 256); return; }
  dump12<128>((c.vC ^ vx ^ 16) + 768, pv2);
  TR(2, b, 11);
  wg_wait<0>(); pin(C);
  TR(2, b, 12);
  release_stage<1, 24576>(c, b < 11);
  pack12(pk, C, 0);
  pack12(pv, C, 24);
  pack12(pq, C, 48);
}

__device__ __forceinline__ float fold(float a, float b, float t, int useb) {
  float r;
  asm("{\n.reg .pred p;\nsetp.ne.b32 p, %4, 0;\nfma.rn.f32 %0, %1, 0f3E553B95, %3;\n@p fma.rn.f32 %0, %2, 0f3E553B95, %3;\n}"
      : "=&f"(r) : "f"(a), "f"(b), "f"(t), "r"(useb));
  return r;
}
template <int U, int L>
__device__ __forceinline__ void softmax_tile(const float (&SA)[56], const float (&SB)[56], const float (&T)[16], int b0, int b1,
                                             uint32_t (&P)[28], float (&sx)[8]) {
  float lu[14], ll[14];
#pragma unroll
  for (int j = 0; j < 7; j++) {
    constexpr int sh = U == L ? 2 : 0;
    const float tu0 = T[2 * j + sh], tu1 = T[2 * j + 1 + sh], tl0 = T[2 * j], tl1 = T[2 * j + 1];
    lu[2 * j]     = fold(SA[4 * (U + j)],     SB[4 * (U + j)],     tu0, b0);
    ll[2 * j]     = fold(SA[4 * (L + j) + 2], SB[4 * (L + j) + 2], tl0, b0);
    lu[2 * j + 1] = fold(SA[4 * (U + j) + 1], SB[4 * (U + j) + 1], tu1, b1);
    ll[2 * j + 1] = fold(SA[4 * (L + j) + 3], SB[4 * (L + j) + 3], tl1, b1);
  }
  float mu = lu[0], ml = ll[0], mu2 = lu[1], ml2 = ll[1];
#pragma unroll
  for (int j = 1; j < 7; j++) { mu = fmaxf(mu, lu[2 * j]); mu2 = fmaxf(mu2, lu[2 * j + 1]); ml = fmaxf(ml, ll[2 * j]); ml2 = fmaxf(ml2, ll[2 * j + 1]); }
  mu = fmaxf(mu, mu2); ml = fmaxf(ml, ml2);
  { const float a1 = __shfl_xor_sync(0xffffffffu, mu, 1), a2 = __shfl_xor_sync(0xffffffffu, mu, 2), a3 = __shfl_xor_sync(0xffffffffu, mu, 3);
    const float c1 = __shfl_xor_sync(0xffffffffu, ml, 1), c2 = __shfl_xor_sync(0xffffffffu, ml, 2), c3 = __shfl_xor_sync(0xffffffffu, ml, 3);
    mu = fmaxf(fmaxf(mu, a1), fmaxf(a2, a3)); ml = fmaxf(fmaxf(ml, c1), fmaxf(c2, c3)); }
  float su = 0.f, sl = 0.f;
#pragma unroll
  for (int c = 0; c < 14; c++) {
    const int iu = (c >> 1) * 4 + (c & 1) * 2;
    if (c >= U && c < U + 7) {
      float e0 = ex2(lu[2 * (c - U)] - mu), e1 = ex2(lu[2 * (c - U) + 1] - mu);
      su = c == U ? e0 + e1 : (su + e0) + e1; P[iu] = pack2(e0, e1);
    } else P[iu] = 0u;
    if (c >= L && c < L + 7) {
      float e0 = ex2(ll[2 * (c - L)] - ml), e1 = ex2(ll[2 * (c - L) + 1] - ml);
      sl = c == L ? e0 + e1 : (sl + e0) + e1; P[iu + 1] = pack2(e0, e1);
    } else P[iu + 1] = 0u;
  }
  sx[0] = su; sx[4] = sl;
#pragma unroll
  for (int k = 1; k < 4; k++) { sx[k] = __shfl_xor_sync(0xffffffffu, su, k); sx[4 + k] = __shfl_xor_sync(0xffffffffu, sl, k); }
}

struct Maps { CUtensorMap xc, xh, w, os, wo, ot; };

__global__ void __cluster_dims__(4, 1, 1) __launch_bounds__(512, 1)
na_attn_kernel(const __grid_constant__ Maps mp, const __nv_bfloat16* __restrict__ wqkv, const __nv_bfloat16* __restrict__ rpb) {
  extern __shared__ __align__(1024) uint8_t smem_raw[];
  const uint32_t sb = smem_u32(smem_raw);
  if ((sb & 0x3FFFF) != SBC) return;
  const uint32_t bar = sb + SM_BAR;
  TR2(blockIdx.x, 0);
  const int tid = threadIdx.x, lane = tid & 31;
  const int warp = __shfl_sync(0xffffffffu, tid >> 5, 0);
  const int head = blockIdx.x & 3, cl = blockIdx.x >> 2;
  const int par = cl / 7, strip = cl - par * 7, ph = par >> 1, pw = par & 1;

  uint4 wv[3];
  const int wr = tid / 6, wc = tid - wr * 6;
  if (warp < 12) {
#pragma unroll
    for (int i = 0; i < 3; i++) wv[i] = __ldg(reinterpret_cast<const uint4*>(wqkv + (wr + i * 64) * 576 + 384 + head * 48 + wc * 8));
  } else if (elect_one()) {
    if (warp == 12) {
      mbar_init(bar + B_WK * 8, 1);
#pragma unroll
      for (int i = 0; i < 3; i++) load_w(&mp.w, sb + SM_W + i * 6144, bar + B_WK * 8, 192 + head * 48 + i * 16);
      mbar_expect(bar + B_WK * 8, 18432);
    } else if (warp == 13) {
#pragma unroll
      for (int i = 0; i < B_WK; i++) mbar_init(bar + i * 8, i < B_EMPTY ? 4 : (i < B_TIN ? 16 : (i < B_TFREE ? 1 : 16)));
    } else if (warp == 14) {
#pragma unroll
      for (int i = B_WQ; i < B_COUNT; i++) mbar_init(bar + i * 8, i < B_Q0 ? 1 : (i < B_KFREE ? 4 : 8));
    }
    asm volatile("fence.mbarrier_init.release.cluster;" ::: "memory");
  }
  __syncwarp();
  asm volatile("barrier.cluster.arrive.relaxed.aligned;" ::: "memory");

  if (warp >= 12) {
    asm volatile("setmaxnreg.dec.sync.aligned.u32 24;");
    asm volatile("griddepcontrol.launch_dependents;");
    const int cc = ph * 112 + (head ? strip * 16 : (strip == 0 ? 16 : (strip == 6 ? 74 : strip * 16 - 3)));
    const int sd = strip == 0 ? -1 : (strip == 6 ? 1 : 0);
    const int r0 = head == 0 ? -4 : (head == 1 ? 4 : 0);
    asm volatile("barrier.cluster.wait.aligned;" ::: "memory");
    if (warp == 12) {
      const uint32_t fb = bar + (B_FULL + head) * 8, eb = bar + (B_EMPTY + head) * 8;
      const uint32_t dst = sb + (head == 0 ? SM_X0 : (head == 1 ? SM_X1 : SM_X2));
      const int nl = head == 0 ? 15 : (head == 3 ? 1 : 14);
#pragma unroll 1
      for (int n = 0; n < nl; n++) {
        if (n) mbar_wait(eb, (n - 1) & 1);
        if (elect_one()) {
          if (head == 0) {
            asm volatile("cp.async.bulk.tensor.5d.shared::cluster.global.mbarrier::complete_tx::bytes.multicast::cluster [%0], [%1, {%3,%4,%5,%6,%7}], [%2], %8;"
                         ::"r"(dst), "l"(&mp.xh), "r"(fb), "r"(0), "r"(8 * n + r0), "r"(cc), "r"(sd), "r"(pw * 3), "h"((uint16_t)15) : "memory");
            if (n + 1 < nl) asm volatile("cp.async.bulk.prefetch.tensor.5d.L2.global [%0, {%1,%2,%3,%4,%5}];" ::"l"(&mp.xh), "r"(0), "r"(8 * n + 8 + r0), "r"(cc), "r"(sd), "r"(pw * 3) : "memory");
          } else if (head < 3) {
            asm volatile("cp.async.bulk.tensor.4d.shared::cluster.global.mbarrier::complete_tx::bytes.multicast::cluster [%0], [%1, {%3,%4,%5,%6}], [%2], %7;"
                         ::"r"(dst), "l"(&mp.xc), "r"(fb), "r"(0), "r"(8 * n + r0), "r"(cc), "r"(pw * 3), "h"((uint16_t)15) : "memory");
          }
          if (n == 0) {
#pragma unroll
            for (int i = 0; i < 3; i++) load_w(&mp.w, sb + SM_W + (6 + i) * 6144, bar + B_WQ * 8, head * 48 + i * 16);
            mbar_expect(bar + B_WQ * 8, 18432);
            mbar_expect(bar + B_TIN * 8, 24576); mbar_expect(bar + (B_TIN + 1) * 8, 24576); mbar_expect(bar + (B_TIN + 2) * 8, 24576);
          }
          if (head && n + 1 < nl) asm volatile("cp.async.bulk.prefetch.tensor.4d.L2.global [%0, {%1,%2,%3,%4}];" ::"l"(&mp.xc), "r"(0), "r"(8 * n + 8 + r0), "r"(cc), "r"(pw * 3) : "memory");
        }
        __syncwarp();
      }
    }
    if (warp >= 14) {
      const int j = warp - 14;
      int* flag = g_flags + cl * 2 + j;
      nb_arrive(N_VQ0 + j, 288);
#pragma unroll 1
      for (int b = 0; b < TB; b++) {
        mbar_wait(bar + (B_ODONE + j) * 8, b & 1);
        if (lane == 0) {
          asm volatile("cp.async.bulk.tensor.3d.global.shared::cta.bulk_group [%0, {%2,%3,%4}], [%1];"
                       ::"l"(&mp.os), "r"(sb + SM_O + j * 6144), "r"(pw * 192), "r"(8 * b + 2 * head), "r"(ph * 112 + strip * 16 + 8 * j) : "memory");
          asm volatile("cp.async.bulk.commit_group;\ncp.async.bulk.wait_group.read 0;" ::: "memory");
        }
        __syncwarp();
        nb_arrive(N_VQ0 + j, 288);
        if (lane == 0) asm volatile("cp.async.bulk.wait_group 0;\nfence.proxy.async.global;\nred.release.gpu.global.add.s32 [%0], 1;" ::"l"(flag + b * 56) : "memory");
        __syncwarp();
      }
#pragma unroll 1
      for (int i = 0; i < 2; i++) {
        mbar_wait(bar + (B_ODONE + j) * 8, (TB + i) & 1);
        if (i == 0) nb_arrive(N_VQ0 + j, 288);
        mbar_wait(bar + (B_TFREE + i) * 8, 0);
        if (elect_one()) {
#pragma unroll 1
          for (int d = 0; d < 8; d++)
            send_o<1536>(sb + (i ? SM_X1 : SM_X2) + head * 6144 + j * 3072 + (d & 1) * 1536,
                         sb + (i ? SM_Q : SM_O) + (4 * j + (d >> 2) * 2 + (d & 1)) * (i ? 3072 : 1536), bar + (B_TIN + i) * 8, d >> 1);
        }
        __syncwarp();
      }
    }
    cluster_sync();
  } else if (warp >= 8) {
    asm volatile("setmaxnreg.inc.sync.aligned.u32 %0;" ::"n"(RG));
    GemmCtx c;
    c.bar = bar;
    const int gw = warp - 8, tk = gw * 16 + (lane & 15), hi = lane >> 4;
    { const int col = tk >> 2, i = tk & 3;
      c.kC = sb + SM_K + (col + 3) * KS + hi * 128 + i * 16;
      c.vC = sb + SM_V + (col + 3) * 1536 + hi * 128 + (2 * i + ((col + 3) & 1)) * 16;
      c.qC = sb + SM_Q + col * 1536 + hi * 256 + (col & 1) * 64 + i * 16; }
    { const int ci = (tk >> 3) - 2, kc = ci < 3 ? ci : ci + 16, i = tk & 7; c.hvalid = gw > 0;
      c.kH = sb + SM_K + kc * KS + hi * 128 + i * 16;
      c.vH = sb + SM_V + kc * 1536 + hi * 128 + (i >> 2) * 768 + (2 * (i & 3) + ((kc ^ (i >> 2)) & 1)) * 16; }
    asm volatile("barrier.cluster.wait.aligned;" ::: "memory");
    if (elect_one()) { mbar_expect(bar + B_FULL * 8, 4608); mbar_expect(bar + (B_FULL + 1) * 8, 6144); mbar_expect(bar + (B_FULL + 2) * 8, 6144); }
    __syncwarp();
#pragma unroll
    for (int i = 0; i < 3; i++) sts128(sb + SM_W + (3 + (wc >> 1)) * 6144 + (wr + i * 64) * 32 + ((wc ^ (wr >> 2)) & 1) * 16, wv[i]);
    fence_async();
    asm volatile("bar.sync 1, 384;" ::: "memory");
    mbar_wait(bar + B_WK * 8, 0);
    uint32_t pk[12], pv[12], pq[12];
    TRDECL;
    gemm_iter<true, false>(c, -2, pk, pv, pq, &mp.wo TRPASS);
#pragma unroll 1
    for (int b = -1; b < 12; b++) gemm_iter<false, false>(c, b, pk, pv, pq, &mp.wo TRPASS);
    gemm_iter<false, true>(c, 12, pk, pv, pq, &mp.wo TRPASS);
    TR(2, 13, 0);
    mbar_wait(bar + B_WO * 8, 0);
    TR(2, 13, 1);
    const uint32_t st = sb + SM_TST + gw * 3072;
    const uint32_t sta = st + (lane & 15) * 64 + ((hi ^ ((lane >> 1) & 3)) * 16);
#pragma unroll 1
    for (int i = 0; i < 3; i++) {
      constexpr uint64_t db = mkdesc(SBC + SM_TWO, 12288, 512, 2);
      const uint64_t da = mkdesc(SBC, 128, 768, 0) + (i ^ (i < 2)) * (24576 / 16);
      float D[48];
      mbar_wait(bar + (B_TIN + i) * 8, 0);
      if (i == 2) asm volatile("barrier.cluster.arrive.relaxed.aligned;" ::: "memory");
      else nb_sync(i ? N_PVISS : N_QK1, i ? 384 : 256);
      TR(2, 13 - i, 2); TR(2, 12 + i, 5); TR(2, 11 + i, 9);
      wg_fence();
      wg_ss96<0>(D, da, db);
#pragma unroll
      for (int k = 1; k < 12; k++) wg_ss96<1>(D, da + (k / 3) * 384 + (k % 3) * 16, db + k * 64);
      wg_commit();
      if (lane == 0) asm volatile("cp.async.bulk.wait_group.read 0;" ::: "memory");
      __syncwarp();
      wg_wait<0>(); pin(D);
      TR(2, 13 - i, 3); TR(2, 12 + i, 6); TR(2, 11 + i, 10);
#pragma unroll
      for (int q = 0; q < 6; q++)
        stsm4((sta ^ ((q & 1) * 32)) + (q >> 1) * 1024,
              pack2(D[8 * q], D[8 * q + 1]), pack2(D[8 * q + 2], D[8 * q + 3]), pack2(D[8 * q + 4], D[8 * q + 5]), pack2(D[8 * q + 6], D[8 * q + 7]));
      fence_async();
      __syncwarp();
      if (lane == 0) {
        asm volatile("cp.async.bulk.tensor.4d.global.shared::cta.bulk_group [%0, {%2,%3,%4,%5}], [%1];"
                     ::"l"(&mp.ot), "r"(st), "r"(0), "r"(8 * (TB + i)), "r"(ph * 112 + strip * 16 + 8 * (gw >> 1) + 4 * (head >> 1) + 2 * (gw & 1)), "r"(pw * 6 + (head & 1) * 3) : "memory");
        asm volatile("cp.async.bulk.commit_group;" ::: "memory");
      }
      TR(2, 13 - i, 4); TR(2, 12 + i, 7); TR(2, 11 + i, 11);
    }
    if (lane == 0) asm volatile("cp.async.bulk.wait_group.read 0;" ::: "memory");
    __syncwarp();
    TR(2, 13, 8);
    TR2(blockIdx.x, 2);
    TRDUMP;
    asm volatile("barrier.cluster.wait.aligned;" ::: "memory");
  } else {
    asm volatile("setmaxnreg.inc.sync.aligned.u32 %0;" ::"n"(RA));
    float rv = -INFINITY;
    if (tid < 169) rv = __bfloat162float(rpb[head * 169 + tid]) * 1.4426950408889634f;
    if (tid < 192) {
      const int kc = (wr & 15) + 3;
      sts128(tid < 96 ? sb + SM_K + kc * KS + wc * 128 + 48 : sb + SM_V + kc * 1536 + wc * 128 + (6 + (kc & 1)) * 16, make_uint4(0, 0, 0, 0));
    }
#pragma unroll
    for (int i = 0; i < 3; i++) sts128(sb + SM_W + (3 + (wc >> 1)) * 6144 + (wr + i * 64) * 32 + ((wc ^ (wr >> 2)) & 1) * 16, wv[i]);
    fence_async();
    asm volatile("bar.arrive 1, 384;" ::: "memory");
    if (tid < 182) asm volatile("st.shared.f32 [%0], %1;" ::"r"(sb + SM_RPB + tid * 4), "f"(rv) : "memory");
    const int j = warp >> 2, w = warp & 3;
    int variant = w;
    if (strip == 0 && j == 0 && w < 2) variant = 4;
    if (strip == 6 && j == 1 && w >= 2) variant = 5;
    const uint32_t qa = sb + SM_Q + (8 * j + 2 * w + ((lane >> 3) & 1)) * 1536 + (lane >> 4) * 256 + (((lane & 7) * 16) ^ (((lane >> 3) & 1) * 64));
    uint32_t oa = sb + SM_O + j * 6144 + (2 * w + ((lane >> 3) & 1)) * 768 + (lane >> 4) * 128 + (lane & 7) * 16;
    const uint64_t dK = mkdesc(SBC + SM_K, 128, KS, 0) + j * (8 * KS / 16);
    const uint64_t dV = mkdesc(SBC + SM_V, 768, 128, 0) + j * (8 * 1536 / 16);
    asm volatile("barrier.cluster.wait.aligned;" ::: "memory");
    asm volatile("bar.sync 3, 256;" ::: "memory");
    float T[16];
    TRDECL;
    int b0 = 0, b1 = 0;
    uint32_t meta = 0;
    uint32_t q[12];
    mbar_wait(bar + B_Q0 * 8, 0);
#pragma unroll
    for (int k = 0; k < 3; k++) ldsm4(qa + k * 512, q[4 * k], q[4 * k + 1], q[4 * k + 2], q[4 * k + 3]);
#pragma unroll 1
    for (int b = 0; b < 14; b++) {
      const uint32_t pa = b & 1;
      float SA[56], SB[56];
      const uint64_t dA = dK + pa * (KSLOT >> 4), dB = dK + (pa ^ 1) * (KSLOT >> 4);
      TR(0, b, 0);
      nb_sync(N_KRDY + j, 256);
      TR(0, b, 1);
      TR(0, b - 1, 9);
      wg_fence();
      wg_rs112<0>(SA, q[0], q[1], q[2], q[3], dA);
      wg_rs112<0>(SB, q[0], q[1], q[2], q[3], dB);
      wg_rs112<1>(SA, q[4], q[5], q[6], q[7], dA + 16);
      wg_rs112<1>(SB, q[4], q[5], q[6], q[7], dB + 16);
      wg_rs112<1>(SA, q[8], q[9], q[10], q[11], dA + 32);
      wg_rs112<1>(SB, q[8], q[9], q[10], q[11], dB + 32);
      wg_commit();
      nb_arrive(N_QK0 + j, 256);
      TR(0, b, 2);
      if (b <= 1 || b == 13) {
        uint32_t ln; asm volatile("mov.u32 %0, %%laneid;" : "=r"(ln));
        const int g = ln >> 2, t = ln & 3;
        const int sw = b == 0 ? max(g + 1, 4) : (b == 13 ? min(g + 1, 5) : g + 1);
        const int i0 = 2 * t, i1 = 2 * t + 1;
        b0 = i0 <= sw - 2; b1 = i1 <= sw - 2;
        const uint32_t tb = sb + SM_RPB + (variant < 4 ? 3 : variant + 1 - 2 * w) * 4;
        const uint32_t ra0 = tb + (i0 == sw - 1 ? 13 : i0 + 8 * b0 - g + 2) * 52;
        const uint32_t ra1 = tb + (i1 == sw - 1 ? 13 : i1 + 8 * b1 - g + 2) * 52;
#pragma unroll
        for (int jj = 0; jj < 8; jj++) { T[2 * jj] = lds_f32(ra0 + jj * 4); T[2 * jj + 1] = lds_f32(ra1 + jj * 4); }
        meta = ((0x5555u & ((1u << (2 * (sw - 1))) - 1)) ^ 0xDD88u ^ (((t ^ b) & 1) ? 0x5555u : 0u)) * 0x10001u;
      } else meta ^= 0x55555555u;
      if (b >= 12) oa += b == 12 ? warp * 1536 - (SM_O - SM_Q) : 1536;
      wg_wait<0>(); pin(SA); pin(SB);
      mbar_arrive_elect(bar + B_KFREE * 8);
      TR(0, b, 3);
      TR(0, b - 1, 10);
      uint32_t P[28];
      float sx[8];
      switch (variant) {
        case 0: softmax_tile<0, 1>(SA, SB, T, b0, b1, P, sx); break;
        case 1: softmax_tile<2, 3>(SA, SB, T, b0, b1, P, sx); break;
        case 2: softmax_tile<4, 5>(SA, SB, T, b0, b1, P, sx); break;
        case 3: softmax_tile<6, 7>(SA, SB, T, b0, b1, P, sx); break;
        case 4: softmax_tile<3, 3>(SA, SB, T, b0, b1, P, sx); break;
        default: softmax_tile<4, 4>(SA, SB, T, b0, b1, P, sx); break;
      }
      float O[24];
      TR(0, b, 4);
      nb_sync(N_VQ0 + j, b == 13 ? 256 : 288);
      TR(0, b, 5);
#pragma unroll
      for (int k = 0; k < 3; k++) ldsm4(qa + (pa ^ 1) * 128 + k * 512, q[4 * k], q[4 * k + 1], q[4 * k + 2], q[4 * k + 3]);
      wg_fence();
      wg_sp48<0>(O, P[0], P[1], P[2], P[3], dV, meta);
#pragma unroll
      for (int s = 1; s < 7; s++) wg_sp48<1>(O, P[4 * s], P[4 * s + 1], P[4 * s + 2], P[4 * s + 3], dV + s * 192, meta);
      wg_commit();
      if (b != 12) nb_arrive(N_PVISS, 384);
      TR(0, b, 6);
      wg_wait<0>(); pin(O);
      mbar_arrive_elect(bar + B_VFREE * 8);
      TR(0, b, 7);
      float ru, rl;
      asm("rcp.approx.ftz.f32 %0, %1;" : "=f"(ru) : "f"(((fmaf(O[0], 0.f, sx[0]) + sx[1]) + sx[2]) + sx[3]));
      asm("rcp.approx.ftz.f32 %0, %1;" : "=f"(rl) : "f"(((fmaf(O[2], 0.f, sx[4]) + sx[5]) + sx[6]) + sx[7]));
#pragma unroll
      for (int i = 0; i < 3; i++)
        stsm4(oa + i * 256, pack2(O[8 * i] * ru, O[8 * i + 1] * ru), pack2(O[8 * i + 2] * rl, O[8 * i + 3] * rl),
              pack2(O[8 * i + 4] * ru, O[8 * i + 5] * ru), pack2(O[8 * i + 6] * rl, O[8 * i + 7] * rl));
      if (b < 13) publish(bar + (B_ODONE + j) * 8);
      else {
        fence_async();
        mbar_wait(bar + (B_TFREE + 1) * 8, 0);
        __syncwarp();
        if (elect_one()) {
#pragma unroll
          for (int d = 0; d < 2; d++)
            send_o<1536>(sb + SM_X0 + head * 6144 + (2 * j + (w & 1)) * 1536, sb + SM_Q + warp * 3072 + 1536, bar + (B_TIN + 2) * 8, (w & 2) + d);
        }
        __syncwarp();
      }
      TR(0, b, 8);
    }
    TRDUMP;
    cluster_sync();
  }
}

constexpr int NSTB = 6;
constexpr int NTB = TB * 56;
constexpr int SM_B_IN = 0;
constexpr int SM_B_W = SM_B_IN + NSTB * 24576;
constexpr int SM_B_BAR = SM_B_W + 73728;
constexpr int SM_B_TOTAL = SM_B_BAR + 128;
struct MapsB { CUtensorMap oi, oo, wo; };

__global__ void __launch_bounds__(480, 1)
na_proj_kernel(const __grid_constant__ MapsB mp) {
  extern __shared__ __align__(1024) uint8_t smem_raw[];
  const uint32_t sb = smem_u32(smem_raw);
  if ((sb & 0x3FFFF) != SBC) return;
  const uint32_t bar = sb + SM_B_BAR;
  const int tid = threadIdx.x, lane = tid & 31;
  const int warp = __shfl_sync(0xffffffffu, tid >> 5, 0);
  TR2(132 + blockIdx.x, 0);
  TRB(47, 0);
  if (warp == 12 && elect_one()) {
#pragma unroll
    for (int i = 0; i <= 2 * NSTB; i++) mbar_init(bar + i * 8, i < NSTB || i == 2 * NSTB ? 1 : 4);
    mbar_expect(bar + 2 * NSTB * 8, 73728);
#pragma unroll
    for (int i = 0; i < 2; i++)
      asm volatile("cp.async.bulk.tensor.3d.shared::cluster.global.mbarrier::complete_tx::bytes [%0], [%1, {%3,%4,%5}], [%2];"
                   ::"r"(sb + SM_B_W + i * 36864), "l"(&mp.wo), "r"(bar + 2 * NSTB * 8), "r"(0), "r"(0), "r"(i * 3) : "memory");
  }
  __syncthreads();
  const int step = gridDim.x;
  if (warp >= 12) {
    const int wg = warp - 12;
    int use = 0;
#pragma unroll 1
    for (int n = blockIdx.x + wg * step; n < NTB; n += 3 * step, use++) {
      const int b = n / 56, rem = n - b * 56, par = rem / 14, sg = wg + 3 * (use & 1);
      int v; uint32_t spin = 0;
      do { asm volatile("ld.acquire.gpu.global.s32 %0, [%1];" : "=r"(v) : "l"(g_flags + n) : "memory"); } while (v < 4 && ++spin < SPIN_LIMIT);
      asm volatile("fence.proxy.async.global;" ::: "memory");
      if (use >= 2) mbar_wait(bar + (NSTB + sg) * 8, ((use >> 1) - 1) & 1);
      if (elect_one()) {
        mbar_expect(bar + sg * 8, 24576);
        asm volatile("cp.async.bulk.tensor.3d.shared::cluster.global.mbarrier::complete_tx::bytes [%0], [%1, {%3,%4,%5}], [%2];"
                     ::"r"(sb + SM_B_IN + sg * 24576), "l"(&mp.oi), "r"(bar + sg * 8), "r"((par & 1) * 192), "r"(8 * b), "r"((par >> 1) * 112 + (rem - par * 14) * 8) : "memory");
        g_flags[n] = 0;
      }
      __syncwarp();
    }
  } else {
    const int wg = warp >> 2, w = warp & 3;
    constexpr uint64_t db = mkdesc(SBC + SM_B_W, 12288, 512, 2);
    const uint32_t sta0 = sb + SM_B_IN + w * 6144 + (lane & 15) * 128 + (((lane >> 4) ^ (lane & 7)) * 16);
    mbar_wait(bar + 2 * NSTB * 8, 0);
    TRB(47, 1);
    int use = 0;
#pragma unroll 1
    for (int n = blockIdx.x + wg * step; n < NTB; n += 3 * step, use++) {
      const int b = n / 56, rem = n - b * 56, par = rem / 14, sg = wg + 3 * (use & 1);
      const uint64_t da = mkdesc(SBC + SM_B_IN, 128, 3072, 0) + sg * (24576 / 16);
      float D[96];
      mbar_wait(bar + sg * 8, (use >> 1) & 1);
      if (use | wg) nb_sync(4 + wg, 256);
      TRB(use * 3 + wg, 3);
      wg_fence();
      wg_ss192<0>(D, da, db);
#pragma unroll
      for (int k = 1; k < 12; k++) wg_ss192<1>(D, da + k * 16, db + k * 64);
      wg_commit();
      if (n + step < NTB) nb_arrive(wg == 2 ? 4 : 5 + wg, 256);
      TRB(use * 3 + wg, 4);
      if (use && lane == 0) {
        asm volatile("cp.async.bulk.wait_group.read 0;" ::: "memory");
        mbar_arrive(bar + (NSTB + wg + 3 * (~use & 1)) * 8);
      }
      __syncwarp();
      wg_wait<0>(); pin(D);
      nb_sync(1 + wg, 128);
      TRB(use * 3 + wg, 5);
      const uint32_t sta = sta0 + sg * 24576;
#pragma unroll
      for (int q = 0; q < 12; q++)
        stsm4((sta ^ ((q & 3) * 32)) + (q >> 2) * 2048,
              pack2(D[8 * q], D[8 * q + 1]), pack2(D[8 * q + 2], D[8 * q + 3]), pack2(D[8 * q + 4], D[8 * q + 5]), pack2(D[8 * q + 6], D[8 * q + 7]));
      fence_async();
      __syncwarp();
      if (lane == 0) {
        asm volatile("cp.async.bulk.tensor.4d.global.shared::cta.bulk_group [%0, {%2,%3,%4,%5}], [%1];"
                     ::"l"(&mp.oo), "r"(sb + SM_B_IN + sg * 24576 + w * 6144), "r"(0), "r"(8 * b), "r"((par >> 1) * 112 + (rem - par * 14) * 8 + 2 * w), "r"((par & 1) * 3) : "memory");
        asm volatile("cp.async.bulk.commit_group;" ::: "memory");
      }
      __syncwarp();
      TRB(use * 3 + wg, 6);
    }
    if (lane == 0) asm volatile("cp.async.bulk.wait_group 0;" ::: "memory");
    TR2(132 + blockIdx.x, 2);
  }
}

typedef CUresult (*EncodeFn)(CUtensorMap*, CUtensorMapDataType, cuuint32_t, void*, const cuuint64_t*, const cuuint64_t*, const cuuint32_t*,
                             const cuuint32_t*, CUtensorMapInterleave, CUtensorMapSwizzle, CUtensorMapL2promotion, CUtensorMapFloatOOBfill);
static EncodeFn g_enc = nullptr;
static void make_map(CUtensorMap* m, const void* p, int rank, const cuuint64_t* dim, const cuuint64_t* str, const cuuint32_t* box, CUtensorMapSwizzle sw) {
  const cuuint32_t ones[5] = {1, 1, 1, 1, 1};
  g_enc(m, CU_TENSOR_MAP_DATA_TYPE_BFLOAT16, rank, (void*)p, dim, str, box, ones, CU_TENSOR_MAP_INTERLEAVE_NONE, sw,
        CU_TENSOR_MAP_L2_PROMOTION_L2_128B, CU_TENSOR_MAP_FLOAT_OOB_FILL_NONE);
}

extern "C" void kernel_launch(void* const* d_in, const int* in_sizes, int n_in, void* d_out, int out_size) {
  const __nv_bfloat16* x = (const __nv_bfloat16*)d_in[0];
  const __nv_bfloat16* wqkv = (const __nv_bfloat16*)d_in[1];
  const __nv_bfloat16* wo = (const __nv_bfloat16*)d_in[2];
  const __nv_bfloat16* rpb = (const __nv_bfloat16*)d_in[3];

  if (!g_enc) {
    void* fn = nullptr; cudaDriverEntryPointQueryResult qr;
    cudaGetDriverEntryPoint("cuTensorMapEncodeTiled", &fn, cudaEnableDefault, &qr);
    g_enc = (EncodeFn)fn;
    cudaFuncSetAttribute(na_attn_kernel, cudaFuncAttributeMaxDynamicSharedMemorySize, SM_A_TOTAL);
    cudaFuncSetAttribute(na_proj_kernel, cudaFuncAttributeMaxDynamicSharedMemorySize, SM_B_TOTAL);
  }
  Maps ma; MapsB mb;
  { cuuint64_t dim[4] = {64, 112, 224, 6}, str[3] = {(cuuint64_t)ROWB, 768, 128};
    cuuint32_t box[4] = {64, 4, 16, 3}, boxo[4] = {64, 8, 2, 3};
    make_map(&ma.xc, x, 4, dim, str, box, CU_TENSOR_MAP_SWIZZLE_128B);
    make_map(&mb.oo, d_out, 4, dim, str, boxo, CU_TENSOR_MAP_SWIZZLE_128B); }
  { cuuint64_t dim[5] = {64, 112, 224, 2, 6}, str[4] = {(cuuint64_t)ROWB, 768, 19 * 768, 128};
    cuuint32_t box[5] = {64, 8, 3, 2, 3};
    make_map(&ma.xh, x, 5, dim, str, box, CU_TENSOR_MAP_SWIZZLE_128B); }
  { cuuint64_t dim[3] = {384, 112, 224}, str[2] = {(cuuint64_t)ROWB, 768};
    cuuint32_t box[3] = {192, 8, 8}, boxs[3] = {192, 2, 8};
    make_map(&mb.oi, d_out, 3, dim, str, box, CU_TENSOR_MAP_SWIZZLE_NONE);
    make_map(&ma.os, d_out, 3, dim, str, boxs, CU_TENSOR_MAP_SWIZZLE_NONE); }
  { cuuint64_t dim[4] = {32, 112, 224, 12}, str[3] = {(cuuint64_t)ROWB, 768, 64};
    cuuint32_t box[4] = {32, 8, 2, 3};
    make_map(&ma.ot, d_out, 4, dim, str, box, CU_TENSOR_MAP_SWIZZLE_64B); }
  { cuuint64_t dim[2] = {576, 192}, str[1] = {1152};
    cuuint32_t box[2] = {16, 192};
    make_map(&ma.w, wqkv, 2, dim, str, box, CU_TENSOR_MAP_SWIZZLE_32B); }
  { cuuint64_t dim[3] = {32, 192, 6}, str[2] = {384, 64};
    cuuint32_t box[3] = {32, 192, 3};
    make_map(&ma.wo, wo, 3, dim, str, box, CU_TENSOR_MAP_SWIZZLE_64B);
    mb.wo = ma.wo; }
  na_attn_kernel<<<112, 512, SM_A_TOTAL>>>(ma, wqkv, rpb);
  cudaLaunchConfig_t cfg = {};
  cfg.gridDim = dim3(20); cfg.blockDim = dim3(480); cfg.dynamicSmemBytes = SM_B_TOTAL; cfg.stream = cudaStreamPerThread;
  cudaLaunchAttribute at[1];
  at[0].id = cudaLaunchAttributeProgrammaticStreamSerialization; at[0].val.programmaticStreamSerializationAllowed = 1;
  cfg.attrs = at; cfg.numAttrs = 1;
  cudaLaunchKernelEx(&cfg, na_proj_kernel, mb);
}
```

```cpp
#include <cuda_runtime.h>
#include <cuda_bf16.h>
#include <cuda.h>
#include <stdint.h>

#define SPIN_LIMIT (1u << 18)

__device__ __forceinline__ uint32_t smem_u32(const void* p) { return (uint32_t)__cvta_generic_to_shared(p); }
__device__ __forceinline__ void wg_fence() { asm volatile("wgmma.fence.sync.aligned;" ::: "memory"); }
__device__ __forceinline__ void wg_commit() { asm volatile("wgmma.commit_group.sync.aligned;" ::: "memory"); }
template <int N> __device__ __forceinline__ void wg_wait() { asm volatile("wgmma.wait_group.sync.aligned %0;" ::"n"(N) : "memory"); }
template <int N> __device__ __forceinline__ void pin(float (&d)[N]) {
#pragma unroll
  for (int i = 0; i < N; i++) asm volatile("" : "+f"(d[i])::"memory");
}
__host__ __device__ constexpr uint64_t mkdesc(uint32_t addr, uint32_t lbo, uint32_t sbo, uint32_t sw) {
  return (uint64_t)((addr & 0x3FFFF) >> 4) | ((uint64_t)(lbo >> 4) << 16) | ((uint64_t)(sbo >> 4) << 32) | ((uint64_t)sw << 62);
}
__device__ __forceinline__ void mbar_init(uint32_t bar, uint32_t cnt) { asm volatile("mbarrier.init.shared::cta.b64 [%0], %1;" ::"r"(bar), "r"(cnt) : "memory"); }
__device__ __forceinline__ void mbar_arrive(uint32_t bar) { asm volatile("mbarrier.arrive.shared::cta.b64 _, [%0];" ::"r"(bar) : "memory"); }
__device__ __forceinline__ bool elect_one() {
  uint32_t r; asm volatile("{\n.reg .pred p;\nelect.sync _|p, 0xffffffff;\nselp.u32 %0, 1, 0, p;\n}" : "=r"(r)); return r;
}
__device__ __forceinline__ void mbar_arrive_elect(uint32_t bar) {
  asm volatile("{\n.reg .pred p;\nelect.sync _|p, 0xffffffff;\n@p mbarrier.arrive.shared::cta.b64 _, [%0];\n}" ::"r"(bar) : "memory");
}
__device__ __forceinline__ void mbar_expect(uint32_t bar, uint32_t bytes) { asm volatile("mbarrier.arrive.expect_tx.shared::cta.b64 _, [%0], %1;" ::"r"(bar), "r"(bytes) : "memory"); }
__device__ __forceinline__ void mbar_arrive_remote(uint32_t bar, uint32_t cta) {
  asm volatile("{\n.reg .b32 ra;\nmapa.shared::cluster.u32 ra, %0, %1;\nmbarrier.arrive.relaxed.cluster.shared::cluster.b64 _, [ra];\n}" ::"r"(bar), "r"(cta) : "memory");
}
__device__ __forceinline__ void mbar_wait(uint32_t bar, uint32_t parity) {
  asm volatile("{\n.reg .pred p;\n.reg .b32 n;\nmov.b32 n, 0;\nWL:\nmbarrier.try_wait.parity.shared::cta.b64 p, [%0], %1;\n@p bra WD;\n"
               "add.u32 n, n, 1;\nsetp.lt.u32 p, n, 65536;\n@p bra WL;\nWD:\n}" ::"r"(bar), "r"(parity) : "memory");
}
__device__ __forceinline__ void nb_sync(int id, int n) { asm volatile("bar.sync %0, %1;" ::"r"(id), "r"(n) : "memory"); }
__device__ __forceinline__ void nb_arrive(int id, int n) { asm volatile("bar.arrive %0, %1;" ::"r"(id), "r"(n) : "memory"); }
__device__ __forceinline__ void fence_async() { asm volatile("fence.proxy.async.shared::cta;" ::: "memory"); }
__device__ __forceinline__ void cluster_sync() {
  asm volatile("barrier.cluster.arrive.relaxed.aligned;\nbarrier.cluster.wait.aligned;" ::: "memory");
}
__device__ __forceinline__ uint32_t pack2(float lo, float hi) {
  uint32_t r; asm("cvt.rn.bf16x2.f32 %0, %1, %2;" : "=r"(r) : "f"(hi), "f"(lo)); return r;
}
__device__ __forceinline__ void stsm4(uint32_t a, uint32_t r0, uint32_t r1, uint32_t r2, uint32_t r3) {
  asm volatile("stmatrix.sync.aligned.m8n8.x4.shared.b16 [%0], {%1,%2,%3,%4};" ::"r"(a), "r"(r0), "r"(r1), "r"(r2), "r"(r3) : "memory");
}
__device__ __forceinline__ void ldsm4(uint32_t a, uint32_t& r0, uint32_t& r1, uint32_t& r2, uint32_t& r3) {
  asm volatile("ldmatrix.sync.aligned.m8n8.x4.shared.b16 {%0,%1,%2,%3}, [%4];" : "=r"(r0), "=r"(r1), "=r"(r2), "=r"(r3) : "r"(a) : "memory");
}
__device__ __forceinline__ void sts128(uint32_t a, uint4 v) {
  asm volatile("st.shared.v4.b32 [%0], {%1,%2,%3,%4};" ::"r"(a), "r"(v.x), "r"(v.y), "r"(v.z), "r"(v.w) : "memory");
}
__device__ __forceinline__ float lds_f32(uint32_t a) { float v; asm volatile("ld.shared.f32 %0, [%1];" : "=f"(v) : "r"(a)); return v; }
__device__ __forceinline__ float ex2(float x) { float y; asm("ex2.approx.ftz.f32 %0, %1;" : "=f"(y) : "f"(x)); return y; }

template<int SC> __device__ __forceinline__ void wg_ss144(float (&d)[72], uint64_t da, uint64_t db) {
  asm volatile("{\n.reg .pred p;\nsetp.ne.b32 p, %74, 0;\nwgmma.mma_async.sync.aligned.m64n144k16.f32.bf16.bf16 {%0,%1,%2,%3,%4,%5,%6,%7,%8,%9,%10,%11,%12,%13,%14,%15,%16,%17,%18,%19,%20,%21,%22,%23,%24,%25,%26,%27,%28,%29,%30,%31,%32,%33,%34,%35,%36,%37,%38,%39,%40,%41,%42,%43,%44,%45,%46,%47,%48,%49,%50,%51,%52,%53,%54,%55,%56,%57,%58,%59,%60,%61,%62,%63,%64,%65,%66,%67,%68,%69,%70,%71}, %72, %73, p, 1, 1, 0, 1;\n}\n"
    : "+f"(d[0]),"+f"(d[1]),"+f"(d[2]),"+f"(d[3]),"+f"(d[4]),"+f"(d[5]),"+f"(d[6]),"+f"(d[7]),"+f"(d[8]),"+f"(d[9]),"+f"(d[10]),"+f"(d[11]),"+f"(d[12]),"+f"(d[13]),"+f"(d[14]),"+f"(d[15]),"+f"(d[16]),"+f"(d[17]),"+f"(d[18]),"+f"(d[19]),"+f"(d[20]),"+f"(d[21]),"+f"(d[22]),"+f"(d[23]),"+f"(d[24]),"+f"(d[25]),"+f"(d[26]),"+f"(d[27]),"+f"(d[28]),"+f"(d[29]),"+f"(d[30]),"+f"(d[31]),"+f"(d[32]),"+f"(d[33]),"+f"(d[34]),"+f"(d[35]),"+f"(d[36]),"+f"(d[37]),"+f"(d[38]),"+f"(d[39]),"+f"(d[40]),"+f"(d[41]),"+f"(d[42]),"+f"(d[43]),"+f"(d[44]),"+f"(d[45]),"+f"(d[46]),"+f"(d[47]),"+f"(d[48]),"+f"(d[49]),"+f"(d[50]),"+f"(d[51]),"+f"(d[52]),"+f"(d[53]),"+f"(d[54]),"+f"(d[55]),"+f"(d[56]),"+f"(d[57]),"+f"(d[58]),"+f"(d[59]),"+f"(d[60]),"+f"(d[61]),"+f"(d[62]),"+f"(d[63]),"+f"(d[64]),"+f"(d[65]),"+f"(d[66]),"+f"(d[67]),"+f"(d[68]),"+f"(d[69]),"+f"(d[70]),"+f"(d[71]) : "l"(da), "l"(db), "n"(SC));
}
template<int SC> __device__ __forceinline__ void wg_ss96(float (&d)[48], uint64_t da, uint64_t db) {
  asm volatile("{\n.reg .pred p;\nsetp.ne.b32 p, %50, 0;\nwgmma.mma_async.sync.aligned.m64n96k16.f32.bf16.bf16 {%0,%1,%2,%3,%4,%5,%6,%7,%8,%9,%10,%11,%12,%13,%14,%15,%16,%17,%18,%19,%20,%21,%22,%23,%24,%25,%26,%27,%28,%29,%30,%31,%32,%33,%34,%35,%36,%37,%38,%39,%40,%41,%42,%43,%44,%45,%46,%47}, %48, %49, p, 1, 1, 0, 1;\n}\n"
    : "+f"(d[0]),"+f"(d[1]),"+f"(d[2]),"+f"(d[3]),"+f"(d[4]),"+f"(d[5]),"+f"(d[6]),"+f"(d[7]),"+f"(d[8]),"+f"(d[9]),"+f"(d[10]),"+f"(d[11]),"+f"(d[12]),"+f"(d[13]),"+f"(d[14]),"+f"(d[15]),"+f"(d[16]),"+f"(d[17]),"+f"(d[18]),"+f"(d[19]),"+f"(d[20]),"+f"(d[21]),"+f"(d[22]),"+f"(d[23]),"+f"(d[24]),"+f"(d[25]),"+f"(d[26]),"+f"(d[27]),"+f"(d[28]),"+f"(d[29]),"+f"(d[30]),"+f"(d[31]),"+f"(d[32]),"+f"(d[33]),"+f"(d[34]),"+f"(d[35]),"+f"(d[36]),"+f"(d[37]),"+f"(d[38]),"+f"(d[39]),"+f"(d[40]),"+f"(d[41]),"+f"(d[42]),"+f"(d[43]),"+f"(d[44]),"+f"(d[45]),"+f"(d[46]),"+f"(d[47]) : "l"(da), "l"(db), "n"(SC));
}
template<int SC> __device__ __forceinline__ void wg_rs112(float (&d)[56], uint32_t a0, uint32_t a1, uint32_t a2, uint32_t a3, uint64_t db) {
  asm volatile("{\n.reg .pred p;\nsetp.ne.b32 p, %61, 0;\nwgmma.mma_async.sync.aligned.m64n112k16.f32.bf16.bf16 {%0,%1,%2,%3,%4,%5,%6,%7,%8,%9,%10,%11,%12,%13,%14,%15,%16,%17,%18,%19,%20,%21,%22,%23,%24,%25,%26,%27,%28,%29,%30,%31,%32,%33,%34,%35,%36,%37,%38,%39,%40,%41,%42,%43,%44,%45,%46,%47,%48,%49,%50,%51,%52,%53,%54,%55}, {%56,%57,%58,%59}, %60, p, 1, 1, 0;\n}\n"
    : "+f"(d[0]),"+f"(d[1]),"+f"(d[2]),"+f"(d[3]),"+f"(d[4]),"+f"(d[5]),"+f"(d[6]),"+f"(d[7]),"+f"(d[8]),"+f"(d[9]),"+f"(d[10]),"+f"(d[11]),"+f"(d[12]),"+f"(d[13]),"+f"(d[14]),"+f"(d[15]),"+f"(d[16]),"+f"(d[17]),"+f"(d[18]),"+f"(d[19]),"+f"(d[20]),"+f"(d[21]),"+f"(d[22]),"+f"(d[23]),"+f"(d[24]),"+f"(d[25]),"+f"(d[26]),"+f"(d[27]),"+f"(d[28]),"+f"(d[29]),"+f"(d[30]),"+f"(d[31]),"+f"(d[32]),"+f"(d[33]),"+f"(d[34]),"+f"(d[35]),"+f"(d[36]),"+f"(d[37]),"+f"(d[38]),"+f"(d[39]),"+f"(d[40]),"+f"(d[41]),"+f"(d[42]),"+f"(d[43]),"+f"(d[44]),"+f"(d[45]),"+f"(d[46]),"+f"(d[47]),"+f"(d[48]),"+f"(d[49]),"+f"(d[50]),"+f"(d[51]),"+f"(d[52]),"+f"(d[53]),"+f"(d[54]),"+f"(d[55]) : "r"(a0), "r"(a1), "r"(a2), "r"(a3), "l"(db), "n"(SC));
}
template<int SC> __device__ __forceinline__ void wg_sp48(float (&d)[24], uint32_t a0, uint32_t a1, uint32_t a2, uint32_t a3, uint64_t db, uint32_t meta) {
  asm volatile("{\n.reg .pred p;\nsetp.ne.b32 p, %30, 0;\nwgmma.mma_async.sp.sync.aligned.m64n48k32.f32.bf16.bf16 {%0,%1,%2,%3,%4,%5,%6,%7,%8,%9,%10,%11,%12,%13,%14,%15,%16,%17,%18,%19,%20,%21,%22,%23}, {%24,%25,%26,%27}, %28, %29, 0, p, 1, 1, 1;\n}\n"
    : "+f"(d[0]),"+f"(d[1]),"+f"(d[2]),"+f"(d[3]),"+f"(d[4]),"+f"(d[5]),"+f"(d[6]),"+f"(d[7]),"+f"(d[8]),"+f"(d[9]),"+f"(d[10]),"+f"(d[11]),"+f"(d[12]),"+f"(d[13]),"+f"(d[14]),"+f"(d[15]),"+f"(d[16]),"+f"(d[17]),"+f"(d[18]),"+f"(d[19]),"+f"(d[20]),"+f"(d[21]),"+f"(d[22]),"+f"(d[23]) : "r"(a0), "r"(a1), "r"(a2), "r"(a3), "l"(db), "r"(meta), "n"(SC));
}
template<int SC> __device__ __forceinline__ void wg_ss192(float (&d)[96], uint64_t da, uint64_t db) {
  asm volatile("{\n.reg .pred p;\nsetp.ne.b32 p, %98, 0;\nwgmma.mma_async.sync.aligned.m64n192k16.f32.bf16.bf16 {%0,%1,%2,%3,%4,%5,%6,%7,%8,%9,%10,%11,%12,%13,%14,%15,%16,%17,%18,%19,%20,%21,%22,%23,%24,%25,%26,%27,%28,%29,%30,%31,%32,%33,%34,%35,%36,%37,%38,%39,%40,%41,%42,%43,%44,%45,%46,%47,%48,%49,%50,%51,%52,%53,%54,%55,%56,%57,%58,%59,%60,%61,%62,%63,%64,%65,%66,%67,%68,%69,%70,%71,%72,%73,%74,%75,%76,%77,%78,%79,%80,%81,%82,%83,%84,%85,%86,%87,%88,%89,%90,%91,%92,%93,%94,%95}, %96, %97, p, 1, 1, 0, 1;\n}\n"
    : "+f"(d[0]),"+f"(d[1]),"+f"(d[2]),"+f"(d[3]),"+f"(d[4]),"+f"(d[5]),"+f"(d[6]),"+f"(d[7]),"+f"(d[8]),"+f"(d[9]),"+f"(d[10]),"+f"(d[11]),"+f"(d[12]),"+f"(d[13]),"+f"(d[14]),"+f"(d[15]),"+f"(d[16]),"+f"(d[17]),"+f"(d[18]),"+f"(d[19]),"+f"(d[20]),"+f"(d[21]),"+f"(d[22]),"+f"(d[23]),"+f"(d[24]),"+f"(d[25]),"+f"(d[26]),"+f"(d[27]),"+f"(d[28]),"+f"(d[29]),"+f"(d[30]),"+f"(d[31]),"+f"(d[32]),"+f"(d[33]),"+f"(d[34]),"+f"(d[35]),"+f"(d[36]),"+f"(d[37]),"+f"(d[38]),"+f"(d[39]),"+f"(d[40]),"+f"(d[41]),"+f"(d[42]),"+f"(d[43]),"+f"(d[44]),"+f"(d[45]),"+f"(d[46]),"+f"(d[47]),"+f"(d[48]),"+f"(d[49]),"+f"(d[50]),"+f"(d[51]),"+f"(d[52]),"+f"(d[53]),"+f"(d[54]),"+f"(d[55]),"+f"(d[56]),"+f"(d[57]),"+f"(d[58]),"+f"(d[59]),"+f"(d[60]),"+f"(d[61]),"+f"(d[62]),"+f"(d[63]),"+f"(d[64]),"+f"(d[65]),"+f"(d[66]),"+f"(d[67]),"+f"(d[68]),"+f"(d[69]),"+f"(d[70]),"+f"(d[71]),"+f"(d[72]),"+f"(d[73]),"+f"(d[74]),"+f"(d[75]),"+f"(d[76]),"+f"(d[77]),"+f"(d[78]),"+f"(d[79]),"+f"(d[80]),"+f"(d[81]),"+f"(d[82]),"+f"(d[83]),"+f"(d[84]),"+f"(d[85]),"+f"(d[86]),"+f"(d[87]),"+f"(d[88]),"+f"(d[89]),"+f"(d[90]),"+f"(d[91]),"+f"(d[92]),"+f"(d[93]),"+f"(d[94]),"+f"(d[95]) : "l"(da), "l"(db), "n"(SC));
}

constexpr uint32_t SBC = 1024;
constexpr int ROWB = 2 * 224 * 384;
constexpr int TB = 11;
constexpr int KS = 832;
constexpr int KSLOT = 22 * KS;
constexpr int SM_X1 = 0;
constexpr int SM_X2 = SM_X1 + 24576;
constexpr int SM_X0 = SM_X2 + 24576;
constexpr int SM_W = SM_X0 + 18432;
constexpr int SM_K = SM_W + 55296;
constexpr int SM_V = SM_K + 2 * KSLOT;
constexpr int SM_Q = SM_V + 22 * 1536;
constexpr int SM_O = SM_Q + 24576;
constexpr int SM_RPB = SM_O + 12288;
constexpr int SM_BAR = SM_RPB + 768;
constexpr int SM_A_TOTAL = SM_BAR + 256;
constexpr int SM_TWO = SM_X0 + 24576;
constexpr int SM_TST = SM_TWO + 36864;
enum { B_FULL = 0, B_EMPTY = 3, B_TIN = 6, B_TFREE = 9, B_WK = 11, B_WQ, B_WO, B_Q0, B_ODONE, B_KFREE, B_VFREE, B_COUNT };
enum { N_KRDY = 4, N_QK0, N_QK1, N_VQ0, N_VQ1, N_PVISS };

#define SPL 4
#define RA 152
#define RG 184
__device__ int g_flags[TB * 56];

#define TR(role, it, k)
#define TRDECL
#define TRARG
#define TRPASS
#define TRDUMP
#define TRB(it, k)
#define TR2(blk, k)

struct GemmCtx {
  uint32_t bar;
  uint32_t kC, vC, qC;
  uint32_t kH, vH;
  bool hvalid;
};

template <int STRIDE> __device__ __forceinline__ void dump12(uint32_t a, const uint32_t (&r)[12]) {
#pragma unroll
  for (int j = 0; j < 3; j++) stsm4(a + j * 2 * STRIDE, r[4 * j], r[4 * j + 1], r[4 * j + 2], r[4 * j + 3]);
}
template <int N> __device__ __forceinline__ void pack12(uint32_t (&r)[12], const float (&d)[N], int off) {
#pragma unroll
  for (int j = 0; j < 12; j++) r[j] = pack2(d[off + 2 * j], d[off + 2 * j + 1]);
}
template <int XS, int K0, int K1> __device__ __forceinline__ void issue_core(float (&d)[72]) {
  constexpr uint64_t da = mkdesc(SBC + XS, 16, 1024, 1), db = mkdesc(SBC + SM_W, 6144, 256, 3);
  wg_fence();
  if (K0 == 0) wg_ss144<0>(d, da, db);
#pragma unroll
  for (int k = K0 ? K0 : 1; k < K1; k++) wg_ss144<1>(d, da + (k >> 2) * 512 + (k & 3) * 2, db + k * 32);
  wg_commit();
}
template <int K0, int K1> __device__ __forceinline__ void issue_halo(float (&d)[48]) {
  constexpr uint64_t da = mkdesc(SBC + SM_X0 - 2048, 16, 1024, 1), db = mkdesc(SBC + SM_W, 6144, 256, 3);
  wg_fence();
  if (K0 == 0) wg_ss96<0>(d, da, db);
#pragma unroll
  for (int k = K0 ? K0 : 1; k < K1; k++) wg_ss96<1>(d, da + (k >> 2) * 384 + (k & 3) * 2, db + k * 32);
  wg_commit();
}
template <int ST, int BYTES> __device__ __forceinline__ void release_stage(const GemmCtx& c, bool on) {
  asm volatile("{\n.reg .pred p, q;\n.reg .b32 ra;\nsetp.ne.b32 q, %2, 0;\nelect.sync _|p, 0xffffffff;\nand.pred p, p, q;\n"
               "mapa.shared::cluster.u32 ra, %1, %4;\n"
               "@p mbarrier.arrive.expect_tx.shared::cta.b64 _, [%0], %3;\n@p mbarrier.arrive.shared::cluster.b64 _, [ra];\n}"
               ::"r"(c.bar + (B_FULL + ST) * 8), "r"(c.bar + (B_EMPTY + ST) * 8), "r"((int)on), "n"(BYTES / 4), "n"(ST) : "memory");
}
__device__ __forceinline__ void load_w(const CUtensorMap* m, uint32_t dst, uint32_t bar, int col) {
  asm volatile("cp.async.bulk.tensor.2d.shared::cluster.global.mbarrier::complete_tx::bytes [%0], [%1, {%3,%4}], [%2];"
               ::"r"(dst), "l"(m), "r"(bar), "r"(col), "r"(0) : "memory");
}
template <int BYTES> __device__ __forceinline__ void send_o(uint32_t dst, uint32_t src, uint32_t bar, int cta) {
  asm volatile("{\n.reg .b32 rd, rb;\nmapa.shared::cluster.u32 rd, %0, %3;\nmapa.shared::cluster.u32 rb, %2, %3;\n"
               "cp.async.bulk.shared::cluster.shared::cta.mbarrier::complete_tx::bytes [rd], [%1], %4, [rb];\n}"
               ::"r"(dst), "r"(src), "r"(bar), "r"(cta), "n"(BYTES) : "memory");
}
__device__ __forceinline__ void tail_free(uint32_t bar) {
  uint32_t ln; asm volatile("mov.u32 %0, %%laneid;" : "=r"(ln));
  if (ln < 4) mbar_arrive_remote(bar, ln);
}
__device__ __forceinline__ void publish(uint32_t bar) {
  fence_async();
  __syncwarp();
  mbar_arrive_elect(bar);
}

template <bool FIRST, bool LAST>
__device__ __forceinline__ void gemm_iter(const GemmCtx& c, int b, uint32_t (&pk)[12], uint32_t (&pv)[12], uint32_t (&pq)[12], const CUtensorMap* mwo TRARG) {
  const uint32_t bar = c.bar;
  const uint32_t pa = b & 1;
  const bool w = b >= 0;
  const uint32_t ko = pa * KSLOT, vx = pa * 16, qx = pa * 128;
  float H[48], C[72];
  uint32_t hk[12], hv[12], pv2[12];
  TR(2, b, 0);
  if (FIRST) mbar_wait(bar + (B_FULL + 0) * 8, pa);
  if (w) nb_sync(N_QK1, 256);
  TR(2, b, 2);
  issue_halo<0, 8>(H);
  TR(2, b, 3);
  if (!FIRST) {
    if (w) mbar_wait(bar + B_KFREE * 8, pa);
    dump12<128>(c.kC + ko, pk);
  }
  issue_halo<8, 12>(H);
  TR(2, b, 4);
  if (!LAST) {
    mbar_wait(bar + (B_FULL + 2) * 8, pa);
    if (FIRST) mbar_wait(bar + B_WQ * 8, 0);
    TR(2, b, 13);
    issue_core<SM_X2, 0, 8>(C);
    TR(2, b, 5);
    if (!FIRST) { fence_async(); dump12<256>(c.qC ^ (qx ^ 192), pq); }
    wg_wait<1>(); pin(H);
    release_stage<0, 18432>(c, true);
  } else {
    dump12<256>(c.qC ^ (qx ^ 192), pq);
    fence_async();
    nb_arrive(N_VQ0, 288); nb_arrive(N_VQ1, 288);
    wg_wait<0>(); pin(H);
    tail_free(bar + (B_TFREE + 1) * 8);
    nb_sync(2, 128);
    if (!c.hvalid && elect_one()) {
      mbar_expect(bar + B_WO * 8, 36864);
      asm volatile("cp.async.bulk.tensor.3d.shared::cluster.global.mbarrier::complete_tx::bytes [%0], [%1, {%3,%4,%5}], [%2];"
                   ::"r"(bar - SM_BAR + SM_TWO), "l"(mwo), "r"(bar + B_WO * 8), "r"(0), "r"(0), "r"((blockIdx.x & 1) * 3) : "memory");
    }
    __syncwarp();
  }
  pack12(hk, H, 0);
  if (c.hvalid) dump12<128>(c.kH + ko, hk);
  pack12(hv, H, 24);
  if (!LAST) {
    issue_core<SM_X2, 8, 12>(C);
    if (w) { nb_arrive(N_VQ0, 288); nb_arrive(N_VQ1, 288); }
    else if (!FIRST) { __syncwarp(); mbar_arrive_elect(bar + B_Q0 * 8); }
    mbar_wait(bar + (B_FULL + 1) * 8, pa);
    TR(2, b, 6);
    wg_wait<0>(); pin(C);
    TR(2, b, 7);
    pack12(pk, C, 0);
    dump12<128>(c.kC + ko + 64, pk);
    release_stage<2, 24576>(c, b < 11);
    if (b == 11) tail_free(bar + B_TFREE * 8);
    pack12(pv2, C, 24);
    pack12(pq, C, 48);
    TR(2, b, 8);
    issue_core<SM_X1, 0, SPL>(C);
    if (w) nb_sync(N_PVISS, 384);
    issue_core<SM_X1, SPL, 8>(C);
    TR(2, b, 9);
  }
  if (!FIRST) fence_async();
  TR(2, b, 14);
  if (!LAST) issue_core<SM_X1, 8, 12>(C);
  if (!FIRST) nb_arrive(N_KRDY, 256);
  TR(2, b, 1);
  if (!LAST) mbar_wait(bar + (B_FULL + 0) * 8, pa ^ 1);
  if (w) mbar_wait(bar + B_VFREE * 8, pa);
  TR(2, b, 10);
  if (!FIRST) dump12<128>(c.vC ^ vx, pv);
  if (!LAST) dump12<256>(c.qC ^ qx, pq);
  if (c.hvalid) dump12<128>(c.vH ^ vx, hv);
  if (LAST) { fence_async(); nb_arrive(N_VQ0, 256); nb_arrive(N_VQ1, 256); return; }
  dump12<128>((c.vC ^ vx ^ 16) + 768, pv2);
  TR(2, b, 11);
  wg_wait<0>(); pin(C);
  TR(2, b, 12);
  release_stage<1, 24576>(c, b < 11);
  pack12(pk, C, 0);
  pack12(pv, C, 24);
  pack12(pq, C, 48);
}

__device__ __forceinline__ float fold(float a, float b, float t, int useb) {
  float r;
  asm("{\n.reg .pred p;\nsetp.ne.b32 p, %4, 0;\nfma.rn.f32 %0, %1, 0f3E553B95, %3;\n@p fma.rn.f32 %0, %2, 0f3E553B95, %3;\n}"
      : "=&f"(r) : "f"(a), "f"(b), "f"(t), "r"(useb));
  return r;
}
template <int U, int L>
__device__ __forceinline__ void softmax_tile(const float (&SA)[56], const float (&SB)[56], const float (&T)[16], int b0, int b1,
                                             uint32_t (&P)[28], float (&sx)[8]) {
  float lu[14], ll[14];
#pragma unroll
  for (int j = 0; j < 7; j++) {
    constexpr int sh = U == L ? 2 : 0;
    const float tu0 = T[2 * j + sh], tu1 = T[2 * j + 1 + sh], tl0 = T[2 * j], tl1 = T[2 * j + 1];
    lu[2 * j]     = fold(SA[4 * (U + j)],     SB[4 * (U + j)],     tu0, b0);
    ll[2 * j]     = fold(SA[4 * (L + j) + 2], SB[4 * (L + j) + 2], tl0, b0);
    lu[2 * j + 1] = fold(SA[4 * (U + j) + 1], SB[4 * (U + j) + 1], tu1, b1);
    ll[2 * j + 1] = fold(SA[4 * (L + j) + 3], SB[4 * (L + j) + 3], tl1, b1);
  }
  float mu = lu[0], ml = ll[0], mu2 = lu[1], ml2 = ll[1];
#pragma unroll
  for (int j = 1; j < 7; j++) { mu = fmaxf(mu, lu[2 * j]); mu2 = fmaxf(mu2, lu[2 * j + 1]); ml = fmaxf(ml, ll[2 * j]); ml2 = fmaxf(ml2, ll[2 * j + 1]); }
  mu = fmaxf(mu, mu2); ml = fmaxf(ml, ml2);
  { const float a1 = __shfl_xor_sync(0xffffffffu, mu, 1), a2 = __shfl_xor_sync(0xffffffffu, mu, 2), a3 = __shfl_xor_sync(0xffffffffu, mu, 3);
    const float c1 = __shfl_xor_sync(0xffffffffu, ml, 1), c2 = __shfl_xor_sync(0xffffffffu, ml, 2), c3 = __shfl_xor_sync(0xffffffffu, ml, 3);
    mu = fmaxf(fmaxf(mu, a1), fmaxf(a2, a3)); ml = fmaxf(fmaxf(ml, c1), fmaxf(c2, c3)); }
  float su = 0.f, sl = 0.f;
#pragma unroll
  for (int c = 0; c < 14; c++) {
    const int iu = (c >> 1) * 4 + (c & 1) * 2;
    if (c >= U && c < U + 7) {
      float e0 = ex2(lu[2 * (c - U)] - mu), e1 = ex2(lu[2 * (c - U) + 1] - mu);
      su = c == U ? e0 + e1 : (su + e0) + e1; P[iu] = pack2(e0, e1);
    } else P[iu] = 0u;
    if (c >= L && c < L + 7) {
      float e0 = ex2(ll[2 * (c - L)] - ml), e1 = ex2(ll[2 * (c - L) + 1] - ml);
      sl = c == L ? e0 + e1 : (sl + e0) + e1; P[iu + 1] = pack2(e0, e1);
    } else P[iu + 1] = 0u;
  }
  sx[0] = su; sx[4] = sl;
#pragma unroll
  for (int k = 1; k < 4; k++) { sx[k] = __shfl_xor_sync(0xffffffffu, su, k); sx[4 + k] = __shfl_xor_sync(0xffffffffu, sl, k); }
}

struct Maps { CUtensorMap xc, xh, w, os, wo, ot; };

__global__ void __cluster_dims__(4, 1, 1) __launch_bounds__(512, 1)
na_attn_kernel(const __grid_constant__ Maps mp, const __nv_bfloat16* __restrict__ wqkv, const __nv_bfloat16* __restrict__ rpb) {
  extern __shared__ __align__(1024) uint8_t smem_raw[];
  const uint32_t sb = smem_u32(smem_raw);
  if ((sb & 0x3FFFF) != SBC) return;
  const uint32_t bar = sb + SM_BAR;
  TR2(blockIdx.x, 0);
  const int tid = threadIdx.x, lane = tid & 31;
  const int warp = __shfl_sync(0xffffffffu, tid >> 5, 0);
  const int head = blockIdx.x & 3, cl = blockIdx.x >> 2;
  const int par = cl / 7, strip = cl - par * 7, ph = par >> 1, pw = par & 1;

  uint4 wv[3];
  const int wr = tid / 6, wc = tid - wr * 6;
  if (warp < 12) {
#pragma unroll
    for (int i = 0; i < 3; i++) wv[i] = __ldg(reinterpret_cast<const uint4*>(wqkv + (wr + i * 64) * 576 + 384 + head * 48 + wc * 8));
  } else if (elect_one()) {
    if (warp == 12) {
      mbar_init(bar + B_WK * 8, 1);
#pragma unroll
      for (int i = 0; i < 3; i++) load_w(&mp.w, sb + SM_W + i * 6144, bar + B_WK * 8, 192 + head * 48 + i * 16);
      mbar_expect(bar + B_WK * 8, 18432);
    } else if (warp == 13) {
#pragma unroll
      for (int i = 0; i < B_WK; i++) mbar_init(bar + i * 8, i < B_EMPTY ? 4 : (i < B_TIN ? 16 : (i < B_TFREE ? 1 : 16)));
    } else if (warp == 14) {
#pragma unroll
      for (int i = B_WQ; i < B_COUNT; i++) mbar_init(bar + i * 8, i < B_Q0 ? 1 : (i == B_Q0 ? 4 : 8));
    }
    asm volatile("fence.mbarrier_init.release.cluster;" ::: "memory");
  }
  __syncwarp();
  asm volatile("barrier.cluster.arrive.relaxed.aligned;" ::: "memory");

  if (warp >= 12) {
    asm volatile("setmaxnreg.dec.sync.aligned.u32 24;");
    asm volatile("griddepcontrol.launch_dependents;");
    const int cc = ph * 112 + (head ? strip * 16 : (strip == 0 ? 16 : (strip == 6 ? 74 : strip * 16 - 3)));
    const int sd = strip == 0 ? -1 : (strip == 6 ? 1 : 0);
    const int r0 = head == 0 ? -4 : (head == 1 ? 4 : 0);
    asm volatile("barrier.cluster.wait.aligned;" ::: "memory");
    if (warp == 12) {
      const uint32_t fb = bar + (B_FULL + head) * 8, eb = bar + (B_EMPTY + head) * 8;
      const uint32_t dst = sb + (head == 0 ? SM_X0 : (head == 1 ? SM_X1 : SM_X2));
      const int nl = head == 0 ? 15 : (head == 3 ? 1 : 14);
#pragma unroll 1
      for (int n = 0; n < nl; n++) {
        if (n) mbar_wait(eb, (n - 1) & 1);
        if (elect_one()) {
          if (head == 0) {
            asm volatile("cp.async.bulk.tensor.5d.shared::cluster.global.mbarrier::complete_tx::bytes.multicast::cluster [%0], [%1, {%3,%4,%5,%6,%7}], [%2], %8;"
                         ::"r"(dst), "l"(&mp.xh), "r"(fb), "r"(0), "r"(8 * n + r0), "r"(cc), "r"(sd), "r"(pw * 3), "h"((uint16_t)15) : "memory");
            if (n + 1 < nl) asm volatile("cp.async.bulk.prefetch.tensor.5d.L2.global [%0, {%1,%2,%3,%4,%5}];" ::"l"(&mp.xh), "r"(0), "r"(8 * n + 8 + r0), "r"(cc), "r"(sd), "r"(pw * 3) : "memory");
          } else if (head < 3) {
            asm volatile("cp.async.bulk.tensor.4d.shared::cluster.global.mbarrier::complete_tx::bytes.multicast::cluster [%0], [%1, {%3,%4,%5,%6}], [%2], %7;"
                         ::"r"(dst), "l"(&mp.xc), "r"(fb), "r"(0), "r"(8 * n + r0), "r"(cc), "r"(pw * 3), "h"((uint16_t)15) : "memory");
          }
          if (n == 0) {
#pragma unroll
            for (int i = 0; i < 3; i++) load_w(&mp.w, sb + SM_W + (6 + i) * 6144, bar + B_WQ * 8, head * 48 + i * 16);
            mbar_expect(bar + B_WQ * 8, 18432);
            mbar_expect(bar + B_TIN * 8, 24576); mbar_expect(bar + (B_TIN + 1) * 8, 24576); mbar_expect(bar + (B_TIN + 2) * 8, 24576);
          }
          if (head && n + 1 < nl) asm volatile("cp.async.bulk.prefetch.tensor.4d.L2.global [%0, {%1,%2,%3,%4}];" ::"l"(&mp.xc), "r"(0), "r"(8 * n + 8 + r0), "r"(cc), "r"(pw * 3) : "memory");
        }
        __syncwarp();
      }
    }
    if (warp == 14) {
      int* flag = g_flags + cl * 2;
      nb_arrive(N_VQ0, 288); nb_arrive(N_VQ1, 288);
#pragma unroll 1
      for (int b = 0; b < TB; b++) {
        mbar_wait(bar + B_ODONE * 8, b & 1);
        if (lane == 0) {
          asm volatile("cp.async.bulk.tensor.3d.global.shared::cta.bulk_group [%0, {%2,%3,%4}], [%1];"
                       ::"l"(&mp.os), "r"(sb + SM_O), "r"(pw * 192), "r"(8 * b + 2 * head), "r"(ph * 112 + strip * 16) : "memory");
          asm volatile("cp.async.bulk.commit_group;\ncp.async.bulk.wait_group 0;" ::: "memory");
        }
        __syncwarp();
        nb_arrive(N_VQ0, 288); nb_arrive(N_VQ1, 288);
        if (lane == 0)
          asm volatile("fence.proxy.async.global;\nfence.acq_rel.gpu;\nred.relaxed.gpu.global.add.s32 [%0], 1;\nred.relaxed.gpu.global.add.s32 [%0+4], 1;"
                       ::"l"(flag + b * 56) : "memory");
        __syncwarp();
      }
#pragma unroll 1
      for (int i = 0; i < 2; i++) {
        mbar_wait(bar + B_ODONE * 8, (TB + i) & 1);
        if (i == 0) { nb_arrive(N_VQ0, 288); nb_arrive(N_VQ1, 288); }
        mbar_wait(bar + (B_TFREE + i) * 8, 0);
        if (elect_one()) {
#pragma unroll 1
          for (int d = 0; d < 16; d++) {
            const int dst = (d + head) & 3, pc = d >> 2;
            send_o<1536>(sb + (i ? SM_X1 : SM_X2) + head * 6144 + pc * 1536,
                         sb + (i ? SM_Q : SM_O) + (4 * (pc >> 1) + (dst & 2) + (pc & 1)) * (i ? 3072 : 1536), bar + (B_TIN + i) * 8, dst);
          }
        }
        __syncwarp();
      }
    }
    cluster_sync();
  } else if (warp >= 8) {
    asm volatile("setmaxnreg.inc.sync.aligned.u32 %0;" ::"n"(RG));
    GemmCtx c;
    c.bar = bar;
    const int gw = warp - 8, tk = gw * 16 + (lane & 15), hi = lane >> 4;
    { const int col = tk >> 2, i = tk & 3;
      c.kC = sb + SM_K + (col + 3) * KS + hi * 128 + i * 16;
      c.vC = sb + SM_V + (col + 3) * 1536 + hi * 128 + (2 * i + ((col + 3) & 1)) * 16;
      c.qC = sb + SM_Q + col * 1536 + hi * 256 + (col & 1) * 64 + i * 16; }
    { const int ci = (tk >> 3) - 2, kc = ci < 3 ? ci : ci + 16, i = tk & 7; c.hvalid = gw > 0;
      c.kH = sb + SM_K + kc * KS + hi * 128 + i * 16;
      c.vH = sb + SM_V + kc * 1536 + hi * 128 + (i >> 2) * 768 + (2 * (i & 3) + ((kc ^ (i >> 2)) & 1)) * 16; }
    asm volatile("barrier.cluster.wait.aligned;" ::: "memory");
    if (elect_one()) { mbar_expect(bar + B_FULL * 8, 4608); mbar_expect(bar + (B_FULL + 1) * 8, 6144); mbar_expect(bar + (B_FULL + 2) * 8, 6144); }
    __syncwarp();
#pragma unroll
    for (int i = 0; i < 3; i++) sts128(sb + SM_W + (3 + (wc >> 1)) * 6144 + (wr + i * 64) * 32 + ((wc ^ (wr >> 2)) & 1) * 16, wv[i]);
    fence_async();
    asm volatile("bar.sync 1, 384;" ::: "memory");
    mbar_wait(bar + B_WK * 8, 0);
    uint32_t pk[12], pv[12], pq[12];
    TRDECL;
    gemm_iter<true, false>(c, -2, pk, pv, pq, &mp.wo TRPASS);
    TR2(blockIdx.x, 4);
#pragma unroll 1
    for (int b = -1; b < 12; b++) gemm_iter<false, false>(c, b, pk, pv, pq, &mp.wo TRPASS);
    TR2(blockIdx.x, 6);
    gemm_iter<false, true>(c, 12, pk, pv, pq, &mp.wo TRPASS);
    TR(2, 13, 0);
    mbar_wait(bar + B_WO * 8, 0);
    TR(2, 13, 1);
    const uint32_t st = sb + SM_TST + gw * 3072;
    const uint32_t sta = st + (lane & 15) * 64 + ((hi ^ ((lane >> 1) & 3)) * 16);
#pragma unroll 1
    for (int i = 0; i < 3; i++) {
      constexpr uint64_t db = mkdesc(SBC + SM_TWO, 12288, 512, 2);
      const uint64_t da = mkdesc(SBC, 128, 768, 0) + (i ^ (i < 2)) * (24576 / 16);
      float D[48];
      mbar_wait(bar + (B_TIN + i) * 8, 0);
      if (i == 2) asm volatile("barrier.cluster.arrive.relaxed.aligned;" ::: "memory");
      else nb_sync(i ? N_PVISS : N_QK1, i ? 384 : 256);
      TR(2, 13 - i, 2); TR(2, 12 + i, 5); TR(2, 11 + i, 9);
      wg_fence();
      wg_ss96<0>(D, da, db);
#pragma unroll
      for (int k = 1; k < 12; k++) wg_ss96<1>(D, da + (k / 3) * 384 + (k % 3) * 16, db + k * 64);
      wg_commit();
      if (lane == 0) asm volatile("cp.async.bulk.wait_group.read 0;" ::: "memory");
      __syncwarp();
      wg_wait<0>(); pin(D);
      TR(2, 13 - i, 3); TR(2, 12 + i, 6); TR(2, 11 + i, 10);
#pragma unroll
      for (int q = 0; q < 6; q++)
        stsm4((sta ^ ((q & 1) * 32)) + (q >> 1) * 1024,
              pack2(D[8 * q], D[8 * q + 1]), pack2(D[8 * q + 2], D[8 * q + 3]), pack2(D[8 * q + 4], D[8 * q + 5]), pack2(D[8 * q + 6], D[8 * q + 7]));
      fence_async();
      __syncwarp();
      if (lane == 0) {
        asm volatile("cp.async.bulk.tensor.4d.global.shared::cta.bulk_group [%0, {%2,%3,%4,%5}], [%1];"
                     ::"l"(&mp.ot), "r"(st), "r"(0), "r"(8 * (TB + i)), "r"(ph * 112 + strip * 16 + 8 * (gw >> 1) + 4 * (head >> 1) + 2 * (gw & 1)), "r"(pw * 6 + (head & 1) * 3) : "memory");
        asm volatile("cp.async.bulk.commit_group;" ::: "memory");
      }
      TR(2, 13 - i, 4); TR(2, 12 + i, 7); TR(2, 11 + i, 11);
    }
    if (lane == 0) asm volatile("cp.async.bulk.wait_group.read 0;" ::: "memory");
    __syncwarp();
    TR(2, 13, 8);
    TR2(blockIdx.x, 2);
    TRDUMP;
    asm volatile("barrier.cluster.wait.aligned;" ::: "memory");
  } else {
    asm volatile("setmaxnreg.inc.sync.aligned.u32 %0;" ::"n"(RA));
    float rv = -INFINITY;
    if (tid < 169) rv = __bfloat162float(rpb[head * 169 + tid]) * 1.4426950408889634f;
    if (tid < 192) {
      const int kc = (wr & 15) + 3;
      sts128(tid < 96 ? sb + SM_K + kc * KS + wc * 128 + 48 : sb + SM_V + kc * 1536 + wc * 128 + (6 + (kc & 1)) * 16, make_uint4(0, 0, 0, 0));
    }
#pragma unroll
    for (int i = 0; i < 3; i++) sts128(sb + SM_W + (3 + (wc >> 1)) * 6144 + (wr + i * 64) * 32 + ((wc ^ (wr >> 2)) & 1) * 16, wv[i]);
    fence_async();
    asm volatile("bar.arrive 1, 384;" ::: "memory");
    if (tid < 182) asm volatile("st.shared.f32 [%0], %1;" ::"r"(sb + SM_RPB + tid * 4), "f"(rv) : "memory");
    const int j = warp >> 2, w = warp & 3;
    int variant = w;
    if (strip == 0 && j == 0 && w < 2) variant = 4;
    if (strip == 6 && j == 1 && w >= 2) variant = 5;
    const uint32_t qa = sb + SM_Q + (8 * j + 2 * w + ((lane >> 3) & 1)) * 1536 + (lane >> 4) * 256 + (((lane & 7) * 16) ^ (((lane >> 3) & 1) * 64));
    uint32_t oa = sb + SM_O + j * 6144 + (2 * w + ((lane >> 3) & 1)) * 768 + (lane >> 4) * 128 + (lane & 7) * 16;
    const uint64_t dK = mkdesc(SBC + SM_K, 128, KS, 0) + j * (8 * KS / 16);
    const uint64_t dV = mkdesc(SBC + SM_V, 768, 128, 0) + j * (8 * 1536 / 16);
    asm volatile("barrier.cluster.wait.aligned;" ::: "memory");
    asm volatile("bar.sync 3, 256;" ::: "memory");
    float T[16];
    TRDECL;
    int b0 = 0, b1 = 0;
    uint32_t meta = 0;
    uint32_t q[12];
    mbar_wait(bar + B_Q0 * 8, 0);
#pragma unroll
    for (int k = 0; k < 3; k++) ldsm4(qa + k * 512, q[4 * k], q[4 * k + 1], q[4 * k + 2], q[4 * k + 3]);
#pragma unroll 1
    for (int b = 0; b < 14; b++) {
      const uint32_t pa = b & 1;
      float SA[56], SB[56];
      const uint64_t dA = dK + pa * (KSLOT >> 4), dB = dK + (pa ^ 1) * (KSLOT >> 4);
      TR(0, b, 0);
      nb_sync(N_KRDY + j, 256);
      TR(0, b, 1);
      TR(0, b - 1, 9);
      wg_fence();
      wg_rs112<0>(SA, q[0], q[1], q[2], q[3], dA);
      wg_rs112<0>(SB, q[0], q[1], q[2], q[3], dB);
      wg_rs112<1>(SA, q[4], q[5], q[6], q[7], dA + 16);
      wg_rs112<1>(SB, q[4], q[5], q[6], q[7], dB + 16);
      wg_rs112<1>(SA, q[8], q[9], q[10], q[11], dA + 32);
      wg_rs112<1>(SB, q[8], q[9], q[10], q[11], dB + 32);
      wg_commit();
      nb_arrive(N_QK0 + j, 256);
      TR(0, b, 2);
      if (b <= 1 || b == 13) {
        uint32_t ln; asm volatile("mov.u32 %0, %%laneid;" : "=r"(ln));
        const int g = ln >> 2, t = ln & 3;
        const int sw = b == 0 ? max(g + 1, 4) : (b == 13 ? min(g + 1, 5) : g + 1);
        const int i0 = 2 * t, i1 = 2 * t + 1;
        b0 = i0 <= sw - 2; b1 = i1 <= sw - 2;
        const uint32_t tb = sb + SM_RPB + (variant < 4 ? 3 : variant + 1 - 2 * w) * 4;
        const uint32_t ra0 = tb + (i0 == sw - 1 ? 13 : i0 + 8 * b0 - g + 2) * 52;
        const uint32_t ra1 = tb + (i1 == sw - 1 ? 13 : i1 + 8 * b1 - g + 2) * 52;
#pragma unroll
        for (int jj = 0; jj < 8; jj++) { T[2 * jj] = lds_f32(ra0 + jj * 4); T[2 * jj + 1] = lds_f32(ra1 + jj * 4); }
        meta = ((0x5555u & ((1u << (2 * (sw - 1))) - 1)) ^ 0xDD88u ^ (((t ^ b) & 1) ? 0x5555u : 0u)) * 0x10001u;
      } else meta ^= 0x55555555u;
      if (b >= 12) oa += b == 12 ? warp * 1536 - (SM_O - SM_Q) : 1536;
      wg_wait<0>(); pin(SA); pin(SB);
      mbar_arrive_elect(bar + B_KFREE * 8);
      TR(0, b, 3);
      TR(0, b - 1, 10);
      uint32_t P[28];
      float sx[8];
      switch (variant) {
        case 0: softmax_tile<0, 1>(SA, SB, T, b0, b1, P, sx); break;
        case 1: softmax_tile<2, 3>(SA, SB, T, b0, b1, P, sx); break;
        case 2: softmax_tile<4, 5>(SA, SB, T, b0, b1, P, sx); break;
        case 3: softmax_tile<6, 7>(SA, SB, T, b0, b1, P, sx); break;
        case 4: softmax_tile<3, 3>(SA, SB, T, b0, b1, P, sx); break;
        default: softmax_tile<4, 4>(SA, SB, T, b0, b1, P, sx); break;
      }
      float O[24];
      TR(0, b, 4);
      nb_sync(N_VQ0 + j, b == 13 ? 256 : 288);
      TR(0, b, 5);
#pragma unroll
      for (int k = 0; k < 3; k++) ldsm4(qa + (pa ^ 1) * 128 + k * 512, q[4 * k], q[4 * k + 1], q[4 * k + 2], q[4 * k + 3]);
      wg_fence();
      wg_sp48<0>(O, P[0], P[1], P[2], P[3], dV, meta);
#pragma unroll
      for (int s = 1; s < 7; s++) wg_sp48<1>(O, P[4 * s], P[4 * s + 1], P[4 * s + 2], P[4 * s + 3], dV + s * 192, meta);
      wg_commit();
      if (b != 12) nb_arrive(N_PVISS, 384);
      TR(0, b, 6);
      wg_wait<0>(); pin(O);
      mbar_arrive_elect(bar + B_VFREE * 8);
      TR(0, b, 7);
      float ru, rl;
      asm("rcp.approx.ftz.f32 %0, %1;" : "=f"(ru) : "f"(((fmaf(O[0], 0.f, sx[0]) + sx[1]) + sx[2]) + sx[3]));
      asm("rcp.approx.ftz.f32 %0, %1;" : "=f"(rl) : "f"(((fmaf(O[2], 0.f, sx[4]) + sx[5]) + sx[6]) + sx[7]));
#pragma unroll
      for (int i = 0; i < 3; i++)
        stsm4(oa + i * 256, pack2(O[8 * i] * ru, O[8 * i + 1] * ru), pack2(O[8 * i + 2] * rl, O[8 * i + 3] * rl),
              pack2(O[8 * i + 4] * ru, O[8 * i + 5] * ru), pack2(O[8 * i + 6] * rl, O[8 * i + 7] * rl));
      if (b < 13) publish(bar + B_ODONE * 8);
      else {
        fence_async();
        mbar_wait(bar + (B_TFREE + 1) * 8, 0);
        __syncwarp();
        if (elect_one()) {
#pragma unroll
          for (int d = 0; d < 2; d++)
            send_o<1536>(sb + SM_X0 + head * 6144 + (2 * j + (w & 1)) * 1536, sb + SM_Q + warp * 3072 + 1536, bar + (B_TIN + 2) * 8, (w & 2) + (d ^ (head & 1)));
        }
        __syncwarp();
      }
      TR(0, b, 8);
    }
    TRDUMP;
    cluster_sync();
  }
}

constexpr int NSTB = 6;
constexpr int NTB = TB * 56;
constexpr int SM_B_IN = 0;
constexpr int SM_B_W = SM_B_IN + NSTB * 24576;
constexpr int SM_B_BAR = SM_B_W + 73728;
constexpr int SM_B_TOTAL = SM_B_BAR + 128;
struct MapsB { CUtensorMap oi, oo, wo; };

__global__ void __launch_bounds__(480, 1)
na_proj_kernel(const __grid_constant__ MapsB mp) {
  extern __shared__ __align__(1024) uint8_t smem_raw[];
  const uint32_t sb = smem_u32(smem_raw);
  if ((sb & 0x3FFFF) != SBC) return;
  const uint32_t bar = sb + SM_B_BAR;
  const int tid = threadIdx.x, lane = tid & 31;
  const int warp = __shfl_sync(0xffffffffu, tid >> 5, 0);
  TR2(132 + blockIdx.x, 0);
  TRB(47, 0);
  if (warp == 12 && elect_one()) {
#pragma unroll
    for (int i = 0; i <= 2 * NSTB; i++) mbar_init(bar + i * 8, i < NSTB || i == 2 * NSTB ? 1 : 4);
    mbar_expect(bar + 2 * NSTB * 8, 73728);
#pragma unroll
    for (int i = 0; i < 2; i++)
      asm volatile("cp.async.bulk.tensor.3d.shared::cluster.global.mbarrier::complete_tx::bytes [%0], [%1, {%3,%4,%5}], [%2];"
                   ::"r"(sb + SM_B_W + i * 36864), "l"(&mp.wo), "r"(bar + 2 * NSTB * 8), "r"(0), "r"(0), "r"(i * 3) : "memory");
  }
  __syncthreads();
  const int step = gridDim.x;
  if (warp >= 12) {
    const int wg = warp - 12;
    int use = 0;
#pragma unroll 1
    for (int n = blockIdx.x + wg * step; n < NTB; n += 3 * step, use++) {
      const int b = n / 56, rem = n - b * 56, par = rem / 14, sg = wg + 3 * (use & 1);
      int v; uint32_t spin = 0;
      do { asm volatile("ld.acquire.gpu.global.s32 %0, [%1];" : "=r"(v) : "l"(g_flags + n) : "memory"); } while (v < 4 && ++spin < SPIN_LIMIT);
      TRB(use * 3 + wg, 0);
      asm volatile("fence.proxy.async.global;" ::: "memory");
      if (use >= 2) mbar_wait(bar + (NSTB + sg) * 8, ((use >> 1) - 1) & 1);
      TRB(use * 3 + wg, 1);
      if (elect_one()) {
        mbar_expect(bar + sg * 8, 24576);
        asm volatile("cp.async.bulk.tensor.3d.shared::cluster.global.mbarrier::complete_tx::bytes [%0], [%1, {%3,%4,%5}], [%2];"
                     ::"r"(sb + SM_B_IN + sg * 24576), "l"(&mp.oi), "r"(bar + sg * 8), "r"((par & 1) * 192), "r"(8 * b), "r"((par >> 1) * 112 + (rem - par * 14) * 8) : "memory");
        g_flags[n] = 0;
      }
      __syncwarp();
    }
  } else {
    const int wg = warp >> 2, w = warp & 3;
    constexpr uint64_t db = mkdesc(SBC + SM_B_W, 12288, 512, 2);
    const uint32_t sta0 = sb + SM_B_IN + w * 6144 + (lane & 15) * 128 + (((lane >> 4) ^ (lane & 7)) * 16);
    mbar_wait(bar + 2 * NSTB * 8, 0);
    TRB(47, 1);
    int use = 0;
#pragma unroll 1
    for (int n = blockIdx.x + wg * step; n < NTB; n += 3 * step, use++) {
      const int b = n / 56, rem = n - b * 56, par = rem / 14, sg = wg + 3 * (use & 1);
      const uint64_t da = mkdesc(SBC + SM_B_IN, 128, 3072, 0) + sg * (24576 / 16);
      float D[96];
      mbar_wait(bar + sg * 8, (use >> 1) & 1);
      if (use | wg) nb_sync(4 + wg, 256);
      TRB(use * 3 + wg, 3);
      wg_fence();
      wg_ss192<0>(D, da, db);
#pragma unroll
      for (int k = 1; k < 12; k++) wg_ss192<1>(D, da + k * 16, db + k * 64);
      wg_commit();
      if (n + step < NTB) nb_arrive(wg == 2 ? 4 : 5 + wg, 256);
      TRB(use * 3 + wg, 4);
      if (use && lane == 0) {
        asm volatile("cp.async.bulk.wait_group.read 0;" ::: "memory");
        mbar_arrive(bar + (NSTB + wg + 3 * (~use & 1)) * 8);
      }
      __syncwarp();
      wg_wait<0>(); pin(D);
      nb_sync(1 + wg, 128);
      TRB(use * 3 + wg, 5);
      const uint32_t sta = sta0 + sg * 24576;
#pragma unroll
      for (int q = 0; q < 12; q++)
        stsm4((sta ^ ((q & 3) * 32)) + (q >> 2) * 2048,
              pack2(D[8 * q], D[8 * q + 1]), pack2(D[8 * q + 2], D[8 * q + 3]), pack2(D[8 * q + 4], D[8 * q + 5]), pack2(D[8 * q + 6], D[8 * q + 7]));
      fence_async();
      __syncwarp();
      if (lane == 0) {
        asm volatile("cp.async.bulk.tensor.4d.global.shared::cta.bulk_group [%0, {%2,%3,%4,%5}], [%1];"
                     ::"l"(&mp.oo), "r"(sb + SM_B_IN + sg * 24576 + w * 6144), "r"(0), "r"(8 * b), "r"((par >> 1) * 112 + (rem - par * 14) * 8 + 2 * w), "r"((par & 1) * 3) : "memory");
        asm volatile("cp.async.bulk.commit_group;" ::: "memory");
      }
      __syncwarp();
      TRB(use * 3 + wg, 6);
    }
    if (lane == 0) asm volatile("cp.async.bulk.wait_group 0;" ::: "memory");
    TR2(132 + blockIdx.x, 2);
  }
}

typedef CUresult (*EncodeFn)(CUtensorMap*, CUtensorMapDataType, cuuint32_t, void*, const cuuint64_t*, const cuuint64_t*, const cuuint32_t*,
                             const cuuint32_t*, CUtensorMapInterleave, CUtensorMapSwizzle, CUtensorMapL2promotion, CUtensorMapFloatOOBfill);
static EncodeFn g_enc = nullptr;
static void make_map(CUtensorMap* m, const void* p, int rank, const cuuint64_t* dim, const cuuint64_t* str, const cuuint32_t* box, CUtensorMapSwizzle sw) {
  const cuuint32_t ones[5] = {1, 1, 1, 1, 1};
  g_enc(m, CU_TENSOR_MAP_DATA_TYPE_BFLOAT16, rank, (void*)p, dim, str, box, ones, CU_TENSOR_MAP_INTERLEAVE_NONE, sw,
        CU_TENSOR_MAP_L2_PROMOTION_L2_128B, CU_TENSOR_MAP_FLOAT_OOB_FILL_NONE);
}

extern "C" void kernel_launch(void* const* d_in, const int* in_sizes, int n_in, void* d_out, int out_size) {
  const __nv_bfloat16* x = (const __nv_bfloat16*)d_in[0];
  const __nv_bfloat16* wqkv = (const __nv_bfloat16*)d_in[1];
  const __nv_bfloat16* wo = (const __nv_bfloat16*)d_in[2];
  const __nv_bfloat16* rpb = (const __nv_bfloat16*)d_in[3];

  if (!g_enc) {
    void* fn = nullptr; cudaDriverEntryPointQueryResult qr;
    cudaGetDriverEntryPoint("cuTensorMapEncodeTiled", &fn, cudaEnableDefault, &qr);
    g_enc = (EncodeFn)fn;
    cudaFuncSetAttribute(na_attn_kernel, cudaFuncAttributeMaxDynamicSharedMemorySize, SM_A_TOTAL);
    cudaFuncSetAttribute(na_proj_kernel, cudaFuncAttributeMaxDynamicSharedMemorySize, SM_B_TOTAL);
  }
  Maps ma; MapsB mb;
  { cuuint64_t dim[4] = {64, 112, 224, 6}, str[3] = {(cuuint64_t)ROWB, 768, 128};
    cuuint32_t box[4] = {64, 4, 16, 3}, boxo[4] = {64, 8, 2, 3};
    make_map(&ma.xc, x, 4, dim, str, box, CU_TENSOR_MAP_SWIZZLE_128B);
    make_map(&mb.oo, d_out, 4, dim, str, boxo, CU_TENSOR_MAP_SWIZZLE_128B); }
  { cuuint64_t dim[5] = {64, 112, 224, 2, 6}, str[4] = {(cuuint64_t)ROWB, 768, 19 * 768, 128};
    cuuint32_t box[5] = {64, 8, 3, 2, 3};
    make_map(&ma.xh, x, 5, dim, str, box, CU_TENSOR_MAP_SWIZZLE_128B); }
  { cuuint64_t dim[3] = {384, 112, 224}, str[2] = {(cuuint64_t)ROWB, 768};
    cuuint32_t box[3] = {192, 8, 8}, boxs[3] = {192, 2, 16};
    make_map(&mb.oi, d_out, 3, dim, str, box, CU_TENSOR_MAP_SWIZZLE_NONE);
    make_map(&ma.os, d_out, 3, dim, str, boxs, CU_TENSOR_MAP_SWIZZLE_NONE); }
  { cuuint64_t dim[4] = {32, 112, 224, 12}, str[3] = {(cuuint64_t)ROWB, 768, 64};
    cuuint32_t box[4] = {32, 8, 2, 3};
    make_map(&ma.ot, d_out, 4, dim, str, box, CU_TENSOR_MAP_SWIZZLE_64B); }
  { cuuint64_t dim[2] = {576, 192}, str[1] = {1152};
    cuuint32_t box[2] = {16, 192};
    make_map(&ma.w, wqkv, 2, dim, str, box, CU_TENSOR_MAP_SWIZZLE_32B); }
  { cuuint64_t dim[3] = {32, 192, 6}, str[2] = {384, 64};
    cuuint32_t box[3] = {32, 192, 3};
    make_map(&ma.wo, wo, 3, dim, str, box, CU_TENSOR_MAP_SWIZZLE_64B);
    mb.wo = ma.wo; }
  na_attn_kernel<<<112, 512, SM_A_TOTAL>>>(ma, wqkv, rpb);
  cudaLaunchConfig_t cfg = {};
  cfg.gridDim = dim3(20); cfg.blockDim = dim3(480); cfg.dynamicSmemBytes = SM_B_TOTAL; cfg.stream = cudaStreamPerThread;
  cudaLaunchAttribute at[1];
  at[0].id = cudaLaunchAttributeProgrammaticStreamSerialization; at[0].val.programmaticStreamSerializationAllowed = 1;
  cfg.attrs = at; cfg.numAttrs = 1;
  cudaLaunchKernelEx(&cfg, na_proj_kernel, mb);
}
```

```cpp
#include <cuda_runtime.h>
#include <cuda_bf16.h>
#include <cuda.h>
#include <stdint.h>

#define SPIN_LIMIT (1u << 18)

__device__ __forceinline__ uint32_t smem_u32(const void* p) { return (uint32_t)__cvta_generic_to_shared(p); }
__device__ __forceinline__ void wg_fence() { asm volatile("wgmma.fence.sync.aligned;" ::: "memory"); }
__device__ __forceinline__ void wg_commit() { asm volatile("wgmma.commit_group.sync.aligned;" ::: "memory"); }
template <int N> __device__ __forceinline__ void wg_wait() { asm volatile("wgmma.wait_group.sync.aligned %0;" ::"n"(N) : "memory"); }
template <int N> __device__ __forceinline__ void pin(float (&d)[N]) {
#pragma unroll
  for (int i = 0; i < N; i++) asm volatile("" : "+f"(d[i])::"memory");
}
__host__ __device__ constexpr uint64_t mkdesc(uint32_t addr, uint32_t lbo, uint32_t sbo, uint32_t sw) {
  return (uint64_t)((addr & 0x3FFFF) >> 4) | ((uint64_t)(lbo >> 4) << 16) | ((uint64_t)(sbo >> 4) << 32) | ((uint64_t)sw << 62);
}
__device__ __forceinline__ void mbar_init(uint32_t bar, uint32_t cnt) { asm volatile("mbarrier.init.shared::cta.b64 [%0], %1;" ::"r"(bar), "r"(cnt) : "memory"); }
__device__ __forceinline__ void mbar_arrive(uint32_t bar) { asm volatile("mbarrier.arrive.shared::cta.b64 _, [%0];" ::"r"(bar) : "memory"); }
__device__ __forceinline__ bool elect_one() {
  uint32_t r; asm volatile("{\n.reg .pred p;\nelect.sync _|p, 0xffffffff;\nselp.u32 %0, 1, 0, p;\n}" : "=r"(r)); return r;
}
__device__ __forceinline__ void mbar_arrive_elect(uint32_t bar) {
  asm volatile("{\n.reg .pred p;\nelect.sync _|p, 0xffffffff;\n@p mbarrier.arrive.shared::cta.b64 _, [%0];\n}" ::"r"(bar) : "memory");
}
__device__ __forceinline__ void mbar_expect(uint32_t bar, uint32_t bytes) { asm volatile("mbarrier.arrive.expect_tx.shared::cta.b64 _, [%0], %1;" ::"r"(bar), "r"(bytes) : "memory"); }
__device__ __forceinline__ void mbar_arrive_remote(uint32_t bar, uint32_t cta) {
  asm volatile("{\n.reg .b32 ra;\nmapa.shared::cluster.u32 ra, %0, %1;\nmbarrier.arrive.relaxed.cluster.shared::cluster.b64 _, [ra];\n}" ::"r"(bar), "r"(cta) : "memory");
}
__device__ __forceinline__ void mbar_wait(uint32_t bar, uint32_t parity) {
  asm volatile("{\n.reg .pred p;\n.reg .b32 n;\nmov.b32 n, 0;\nWL:\nmbarrier.try_wait.parity.shared::cta.b64 p, [%0], %1;\n@p bra WD;\n"
               "add.u32 n, n, 1;\nsetp.lt.u32 p, n, 65536;\n@p bra WL;\nWD:\n}" ::"r"(bar), "r"(parity) : "memory");
}
__device__ __forceinline__ void nb_sync(int id, int n) { asm volatile("bar.sync %0, %1;" ::"r"(id), "r"(n) : "memory"); }
__device__ __forceinline__ void nb_arrive(int id, int n) { asm volatile("bar.arrive %0, %1;" ::"r"(id), "r"(n) : "memory"); }
__device__ __forceinline__ void fence_async() { asm volatile("fence.proxy.async.shared::cta;" ::: "memory"); }
__device__ __forceinline__ void cluster_sync() {
  asm volatile("barrier.cluster.arrive.relaxed.aligned;\nbarrier.cluster.wait.aligned;" ::: "memory");
}
__device__ __forceinline__ uint32_t pack2(float lo, float hi) {
  uint32_t r; asm("cvt.rn.bf16x2.f32 %0, %1, %2;" : "=r"(r) : "f"(hi), "f"(lo)); return r;
}
__device__ __forceinline__ void stsm4(uint32_t a, uint32_t r0, uint32_t r1, uint32_t r2, uint32_t r3) {
  asm volatile("stmatrix.sync.aligned.m8n8.x4.shared.b16 [%0], {%1,%2,%3,%4};" ::"r"(a), "r"(r0), "r"(r1), "r"(r2), "r"(r3) : "memory");
}
__device__ __forceinline__ void ldsm4(uint32_t a, uint32_t& r0, uint32_t& r1, uint32_t& r2, uint32_t& r3) {
  asm volatile("ldmatrix.sync.aligned.m8n8.x4.shared.b16 {%0,%1,%2,%3}, [%4];" : "=r"(r0), "=r"(r1), "=r"(r2), "=r"(r3) : "r"(a) : "memory");
}
__device__ __forceinline__ void sts128(uint32_t a, uint4 v) {
  asm volatile("st.shared.v4.b32 [%0], {%1,%2,%3,%4};" ::"r"(a), "r"(v.x), "r"(v.y), "r"(v.z), "r"(v.w) : "memory");
}
__device__ __forceinline__ float lds_f32(uint32_t a) { float v; asm volatile("ld.shared.f32 %0, [%1];" : "=f"(v) : "r"(a)); return v; }
__device__ __forceinline__ float ex2(float x) { float y; asm("ex2.approx.ftz.f32 %0, %1;" : "=f"(y) : "f"(x)); return y; }

template<int SC> __device__ __forceinline__ void wg_ss144(float (&d)[72], uint64_t da, uint64_t db) {
  asm volatile("{\n.reg .pred p;\nsetp.ne.b32 p, %74, 0;\nwgmma.mma_async.sync.aligned.m64n144k16.f32.bf16.bf16 {%0,%1,%2,%3,%4,%5,%6,%7,%8,%9,%10,%11,%12,%13,%14,%15,%16,%17,%18,%19,%20,%21,%22,%23,%24,%25,%26,%27,%28,%29,%30,%31,%32,%33,%34,%35,%36,%37,%38,%39,%40,%41,%42,%43,%44,%45,%46,%47,%48,%49,%50,%51,%52,%53,%54,%55,%56,%57,%58,%59,%60,%61,%62,%63,%64,%65,%66,%67,%68,%69,%70,%71}, %72, %73, p, 1, 1, 0, 1;\n}\n"
    : "+f"(d[0]),"+f"(d[1]),"+f"(d[2]),"+f"(d[3]),"+f"(d[4]),"+f"(d[5]),"+f"(d[6]),"+f"(d[7]),"+f"(d[8]),"+f"(d[9]),"+f"(d[10]),"+f"(d[11]),"+f"(d[12]),"+f"(d[13]),"+f"(d[14]),"+f"(d[15]),"+f"(d[16]),"+f"(d[17]),"+f"(d[18]),"+f"(d[19]),"+f"(d[20]),"+f"(d[21]),"+f"(d[22]),"+f"(d[23]),"+f"(d[24]),"+f"(d[25]),"+f"(d[26]),"+f"(d[27]),"+f"(d[28]),"+f"(d[29]),"+f"(d[30]),"+f"(d[31]),"+f"(d[32]),"+f"(d[33]),"+f"(d[34]),"+f"(d[35]),"+f"(d[36]),"+f"(d[37]),"+f"(d[38]),"+f"(d[39]),"+f"(d[40]),"+f"(d[41]),"+f"(d[42]),"+f"(d[43]),"+f"(d[44]),"+f"(d[45]),"+f"(d[46]),"+f"(d[47]),"+f"(d[48]),"+f"(d[49]),"+f"(d[50]),"+f"(d[51]),"+f"(d[52]),"+f"(d[53]),"+f"(d[54]),"+f"(d[55]),"+f"(d[56]),"+f"(d[57]),"+f"(d[58]),"+f"(d[59]),"+f"(d[60]),"+f"(d[61]),"+f"(d[62]),"+f"(d[63]),"+f"(d[64]),"+f"(d[65]),"+f"(d[66]),"+f"(d[67]),"+f"(d[68]),"+f"(d[69]),"+f"(d[70]),"+f"(d[71]) : "l"(da), "l"(db), "n"(SC));
}
template<int SC> __device__ __forceinline__ void wg_ss96(float (&d)[48], uint64_t da, uint64_t db) {
  asm volatile("{\n.reg .pred p;\nsetp.ne.b32 p, %50, 0;\nwgmma.mma_async.sync.aligned.m64n96k16.f32.bf16.bf16 {%0,%1,%2,%3,%4,%5,%6,%7,%8,%9,%10,%11,%12,%13,%14,%15,%16,%17,%18,%19,%20,%21,%22,%23,%24,%25,%26,%27,%28,%29,%30,%31,%32,%33,%34,%35,%36,%37,%38,%39,%40,%41,%42,%43,%44,%45,%46,%47}, %48, %49, p, 1, 1, 0, 1;\n}\n"
    : "+f"(d[0]),"+f"(d[1]),"+f"(d[2]),"+f"(d[3]),"+f"(d[4]),"+f"(d[5]),"+f"(d[6]),"+f"(d[7]),"+f"(d[8]),"+f"(d[9]),"+f"(d[10]),"+f"(d[11]),"+f"(d[12]),"+f"(d[13]),"+f"(d[14]),"+f"(d[15]),"+f"(d[16]),"+f"(d[17]),"+f"(d[18]),"+f"(d[19]),"+f"(d[20]),"+f"(d[21]),"+f"(d[22]),"+f"(d[23]),"+f"(d[24]),"+f"(d[25]),"+f"(d[26]),"+f"(d[27]),"+f"(d[28]),"+f"(d[29]),"+f"(d[30]),"+f"(d[31]),"+f"(d[32]),"+f"(d[33]),"+f"(d[34]),"+f"(d[35]),"+f"(d[36]),"+f"(d[37]),"+f"(d[38]),"+f"(d[39]),"+f"(d[40]),"+f"(d[41]),"+f"(d[42]),"+f"(d[43]),"+f"(d[44]),"+f"(d[45]),"+f"(d[46]),"+f"(d[47]) : "l"(da), "l"(db), "n"(SC));
}
template<int SC> __device__ __forceinline__ void wg_rs112(float (&d)[56], uint32_t a0, uint32_t a1, uint32_t a2, uint32_t a3, uint64_t db) {
  asm volatile("{\n.reg .pred p;\nsetp.ne.b32 p, %61, 0;\nwgmma.mma_async.sync.aligned.m64n112k16.f32.bf16.bf16 {%0,%1,%2,%3,%4,%5,%6,%7,%8,%9,%10,%11,%12,%13,%14,%15,%16,%17,%18,%19,%20,%21,%22,%23,%24,%25,%26,%27,%28,%29,%30,%31,%32,%33,%34,%35,%36,%37,%38,%39,%40,%41,%42,%43,%44,%45,%46,%47,%48,%49,%50,%51,%52,%53,%54,%55}, {%56,%57,%58,%59}, %60, p, 1, 1, 0;\n}\n"
    : "+f"(d[0]),"+f"(d[1]),"+f"(d[2]),"+f"(d[3]),"+f"(d[4]),"+f"(d[5]),"+f"(d[6]),"+f"(d[7]),"+f"(d[8]),"+f"(d[9]),"+f"(d[10]),"+f"(d[11]),"+f"(d[12]),"+f"(d[13]),"+f"(d[14]),"+f"(d[15]),"+f"(d[16]),"+f"(d[17]),"+f"(d[18]),"+f"(d[19]),"+f"(d[20]),"+f"(d[21]),"+f"(d[22]),"+f"(d[23]),"+f"(d[24]),"+f"(d[25]),"+f"(d[26]),"+f"(d[27]),"+f"(d[28]),"+f"(d[29]),"+f"(d[30]),"+f"(d[31]),"+f"(d[32]),"+f"(d[33]),"+f"(d[34]),"+f"(d[35]),"+f"(d[36]),"+f"(d[37]),"+f"(d[38]),"+f"(d[39]),"+f"(d[40]),"+f"(d[41]),"+f"(d[42]),"+f"(d[43]),"+f"(d[44]),"+f"(d[45]),"+f"(d[46]),"+f"(d[47]),"+f"(d[48]),"+f"(d[49]),"+f"(d[50]),"+f"(d[51]),"+f"(d[52]),"+f"(d[53]),"+f"(d[54]),"+f"(d[55]) : "r"(a0), "r"(a1), "r"(a2), "r"(a3), "l"(db), "n"(SC));
}
template<int SC> __device__ __forceinline__ void wg_sp48(float (&d)[24], uint32_t a0, uint32_t a1, uint32_t a2, uint32_t a3, uint64_t db, uint32_t meta) {
  asm volatile("{\n.reg .pred p;\nsetp.ne.b32 p, %30, 0;\nwgmma.mma_async.sp.sync.aligned.m64n48k32.f32.bf16.bf16 {%0,%1,%2,%3,%4,%5,%6,%7,%8,%9,%10,%11,%12,%13,%14,%15,%16,%17,%18,%19,%20,%21,%22,%23}, {%24,%25,%26,%27}, %28, %29, 0, p, 1, 1, 1;\n}\n"
    : "+f"(d[0]),"+f"(d[1]),"+f"(d[2]),"+f"(d[3]),"+f"(d[4]),"+f"(d[5]),"+f"(d[6]),"+f"(d[7]),"+f"(d[8]),"+f"(d[9]),"+f"(d[10]),"+f"(d[11]),"+f"(d[12]),"+f"(d[13]),"+f"(d[14]),"+f"(d[15]),"+f"(d[16]),"+f"(d[17]),"+f"(d[18]),"+f"(d[19]),"+f"(d[20]),"+f"(d[21]),"+f"(d[22]),"+f"(d[23]) : "r"(a0), "r"(a1), "r"(a2), "r"(a3), "l"(db), "r"(meta), "n"(SC));
}
template<int SC> __device__ __forceinline__ void wg_ss192(float (&d)[96], uint64_t da, uint64_t db) {
  asm volatile("{\n.reg .pred p;\nsetp.ne.b32 p, %98, 0;\nwgmma.mma_async.sync.aligned.m64n192k16.f32.bf16.bf16 {%0,%1,%2,%3,%4,%5,%6,%7,%8,%9,%10,%11,%12,%13,%14,%15,%16,%17,%18,%19,%20,%21,%22,%23,%24,%25,%26,%27,%28,%29,%30,%31,%32,%33,%34,%35,%36,%37,%38,%39,%40,%41,%42,%43,%44,%45,%46,%47,%48,%49,%50,%51,%52,%53,%54,%55,%56,%57,%58,%59,%60,%61,%62,%63,%64,%65,%66,%67,%68,%69,%70,%71,%72,%73,%74,%75,%76,%77,%78,%79,%80,%81,%82,%83,%84,%85,%86,%87,%88,%89,%90,%91,%92,%93,%94,%95}, %96, %97, p, 1, 1, 0, 1;\n}\n"
    : "+f"(d[0]),"+f"(d[1]),"+f"(d[2]),"+f"(d[3]),"+f"(d[4]),"+f"(d[5]),"+f"(d[6]),"+f"(d[7]),"+f"(d[8]),"+f"(d[9]),"+f"(d[10]),"+f"(d[11]),"+f"(d[12]),"+f"(d[13]),"+f"(d[14]),"+f"(d[15]),"+f"(d[16]),"+f"(d[17]),"+f"(d[18]),"+f"(d[19]),"+f"(d[20]),"+f"(d[21]),"+f"(d[22]),"+f"(d[23]),"+f"(d[24]),"+f"(d[25]),"+f"(d[26]),"+f"(d[27]),"+f"(d[28]),"+f"(d[29]),"+f"(d[30]),"+f"(d[31]),"+f"(d[32]),"+f"(d[33]),"+f"(d[34]),"+f"(d[35]),"+f"(d[36]),"+f"(d[37]),"+f"(d[38]),"+f"(d[39]),"+f"(d[40]),"+f"(d[41]),"+f"(d[42]),"+f"(d[43]),"+f"(d[44]),"+f"(d[45]),"+f"(d[46]),"+f"(d[47]),"+f"(d[48]),"+f"(d[49]),"+f"(d[50]),"+f"(d[51]),"+f"(d[52]),"+f"(d[53]),"+f"(d[54]),"+f"(d[55]),"+f"(d[56]),"+f"(d[57]),"+f"(d[58]),"+f"(d[59]),"+f"(d[60]),"+f"(d[61]),"+f"(d[62]),"+f"(d[63]),"+f"(d[64]),"+f"(d[65]),"+f"(d[66]),"+f"(d[67]),"+f"(d[68]),"+f"(d[69]),"+f"(d[70]),"+f"(d[71]),"+f"(d[72]),"+f"(d[73]),"+f"(d[74]),"+f"(d[75]),"+f"(d[76]),"+f"(d[77]),"+f"(d[78]),"+f"(d[79]),"+f"(d[80]),"+f"(d[81]),"+f"(d[82]),"+f"(d[83]),"+f"(d[84]),"+f"(d[85]),"+f"(d[86]),"+f"(d[87]),"+f"(d[88]),"+f"(d[89]),"+f"(d[90]),"+f"(d[91]),"+f"(d[92]),"+f"(d[93]),"+f"(d[94]),"+f"(d[95]) : "l"(da), "l"(db), "n"(SC));
}

constexpr uint32_t SBC = 1024;
constexpr int ROWB = 2 * 224 * 384;
constexpr int TB = 11;
constexpr int KS = 832;
constexpr int KSLOT = 22 * KS;
constexpr int SM_X1 = 0;
constexpr int SM_X2 = SM_X1 + 24576;
constexpr int SM_X0 = SM_X2 + 24576;
constexpr int SM_W = SM_X0 + 18432;
constexpr int SM_K = SM_W + 55296;
constexpr int SM_V = SM_K + 2 * KSLOT;
constexpr int SM_Q = SM_V + 22 * 1536;
constexpr int SM_O = SM_Q + 24576;
constexpr int SM_RPB = SM_O + 12288;
constexpr int SM_BAR = SM_RPB + 768;
constexpr int SM_A_TOTAL = SM_BAR + 256;
constexpr int SM_TWO = SM_X0 + 24576;
constexpr int SM_TST = SM_TWO + 36864;
enum { B_FULL = 0, B_EMPTY = 3, B_TIN = 6, B_TFREE = 9, B_WK = 11, B_WQ, B_WO, B_Q0, B_OTAIL, B_ODONE = B_OTAIL + 2, B_KFREE, B_VFREE, B_COUNT };
enum { N_KRDY = 4, N_QK0, N_QK1, N_VQ0, N_VQ1, N_PVISS };

#define SPL 4
#define RA 152
#define RG 184
__device__ int g_flags[TB * 56];

#define TR(role, it, k)
#define TRDECL
#define TRARG
#define TRPASS
#define TRDUMP
#define TRB(it, k)
#define TR2(blk, k)

struct GemmCtx {
  uint32_t bar;
  uint32_t kC, vC, qC;
  uint32_t kH, vH;
  bool hvalid;
};

template <int STRIDE> __device__ __forceinline__ void dump12(uint32_t a, const uint32_t (&r)[12]) {
#pragma unroll
  for (int j = 0; j < 3; j++) stsm4(a + j * 2 * STRIDE, r[4 * j], r[4 * j + 1], r[4 * j + 2], r[4 * j + 3]);
}
template <int N> __device__ __forceinline__ void pack12(uint32_t (&r)[12], const float (&d)[N], int off) {
#pragma unroll
  for (int j = 0; j < 12; j++) r[j] = pack2(d[off + 2 * j], d[off + 2 * j + 1]);
}
template <int XS, int K0, int K1> __device__ __forceinline__ void issue_core(float (&d)[72]) {
  constexpr uint64_t da = mkdesc(SBC + XS, 16, 1024, 1), db = mkdesc(SBC + SM_W, 6144, 256, 3);
  wg_fence();
  if (K0 == 0) wg_ss144<0>(d, da, db);
#pragma unroll
  for (int k = K0 ? K0 : 1; k < K1; k++) wg_ss144<1>(d, da + (k >> 2) * 512 + (k & 3) * 2, db + k * 32);
  wg_commit();
}
template <int K0, int K1> __device__ __forceinline__ void issue_halo(float (&d)[48]) {
  constexpr uint64_t da = mkdesc(SBC + SM_X0 - 2048, 16, 1024, 1), db = mkdesc(SBC + SM_W, 6144, 256, 3);
  wg_fence();
  if (K0 == 0) wg_ss96<0>(d, da, db);
#pragma unroll
  for (int k = K0 ? K0 : 1; k < K1; k++) wg_ss96<1>(d, da + (k >> 2) * 384 + (k & 3) * 2, db + k * 32);
  wg_commit();
}
template <int ST, int BYTES> __device__ __forceinline__ void release_stage(const GemmCtx& c, bool on) {
  asm volatile("{\n.reg .pred p, q;\n.reg .b32 ra;\nsetp.ne.b32 q, %2, 0;\nelect.sync _|p, 0xffffffff;\nand.pred p, p, q;\n"
               "mapa.shared::cluster.u32 ra, %1, %4;\n"
               "@p mbarrier.arrive.expect_tx.shared::cta.b64 _, [%0], %3;\n@p mbarrier.arrive.shared::cluster.b64 _, [ra];\n}"
               ::"r"(c.bar + (B_FULL + ST) * 8), "r"(c.bar + (B_EMPTY + ST) * 8), "r"((int)on), "n"(BYTES / 4), "n"(ST) : "memory");
}
__device__ __forceinline__ void load_w(const CUtensorMap* m, uint32_t dst, uint32_t bar, int col) {
  asm volatile("cp.async.bulk.tensor.2d.shared::cluster.global.mbarrier::complete_tx::bytes [%0], [%1, {%3,%4}], [%2];"
               ::"r"(dst), "l"(m), "r"(bar), "r"(col), "r"(0) : "memory");
}
template <int BYTES> __device__ __forceinline__ void send_o(uint32_t dst, uint32_t src, uint32_t bar, int cta) {
  asm volatile("{\n.reg .b32 rd, rb;\nmapa.shared::cluster.u32 rd, %0, %3;\nmapa.shared::cluster.u32 rb, %2, %3;\n"
               "cp.async.bulk.shared::cluster.shared::cta.mbarrier::complete_tx::bytes [rd], [%1], %4, [rb];\n}"
               ::"r"(dst), "r"(src), "r"(bar), "r"(cta), "n"(BYTES) : "memory");
}
__device__ __forceinline__ void tail_free(uint32_t bar) {
  uint32_t ln; asm volatile("mov.u32 %0, %%laneid;" : "=r"(ln));
  if (ln < 4) mbar_arrive_remote(bar, ln);
}
__device__ __forceinline__ void publish(uint32_t bar) {
  fence_async();
  __syncwarp();
  mbar_arrive_elect(bar);
}

template <bool FIRST, bool LAST>
__device__ __forceinline__ void gemm_iter(const GemmCtx& c, int b, uint32_t (&pk)[12], uint32_t (&pv)[12], uint32_t (&pq)[12], const CUtensorMap* mwo TRARG) {
  const uint32_t bar = c.bar;
  const uint32_t pa = b & 1;
  const bool w = b >= 0;
  const uint32_t ko = pa * KSLOT, vx = pa * 16, qx = pa * 128;
  float H[48], C[72];
  uint32_t hk[12], hv[12], pv2[12];
  TR(2, b, 0);
  if (FIRST) mbar_wait(bar + (B_FULL + 0) * 8, pa);
  if (w) nb_sync(N_QK1, 256);
  TR(2, b, 2);
  issue_halo<0, 8>(H);
  TR(2, b, 3);
  if (!FIRST) {
    if (w) mbar_wait(bar + B_KFREE * 8, pa);
    dump12<128>(c.kC + ko, pk);
  }
  issue_halo<8, 12>(H);
  TR(2, b, 4);
  if (!LAST) {
    mbar_wait(bar + (B_FULL + 2) * 8, pa);
    if (FIRST) mbar_wait(bar + B_WQ * 8, 0);
    TR(2, b, 13);
    issue_core<SM_X2, 0, 8>(C);
    TR(2, b, 5);
    if (!FIRST) { fence_async(); dump12<256>(c.qC ^ (qx ^ 192), pq); }
    wg_wait<1>(); pin(H);
    release_stage<0, 18432>(c, true);
  } else {
    dump12<256>(c.qC ^ (qx ^ 192), pq);
    fence_async();
    nb_arrive(N_VQ0, 288); nb_arrive(N_VQ1, 288);
    wg_wait<0>(); pin(H);
    tail_free(bar + (B_TFREE + 1) * 8);
    nb_sync(2, 128);
    if (!c.hvalid && elect_one()) {
      mbar_expect(bar + B_WO * 8, 36864);
      asm volatile("cp.async.bulk.tensor.3d.shared::cluster.global.mbarrier::complete_tx::bytes [%0], [%1, {%3,%4,%5}], [%2];"
                   ::"r"(bar - SM_BAR + SM_TWO), "l"(mwo), "r"(bar + B_WO * 8), "r"(0), "r"(0), "r"((blockIdx.x & 1) * 3) : "memory");
    }
    __syncwarp();
  }
  pack12(hk, H, 0);
  if (c.hvalid) dump12<128>(c.kH + ko, hk);
  pack12(hv, H, 24);
  if (!LAST) {
    issue_core<SM_X2, 8, 12>(C);
    if (w) { nb_arrive(N_VQ0, 288); nb_arrive(N_VQ1, 288); }
    else if (!FIRST) { __syncwarp(); mbar_arrive_elect(bar + B_Q0 * 8); }
    mbar_wait(bar + (B_FULL + 1) * 8, pa);
    TR(2, b, 6);
    wg_wait<0>(); pin(C);
    TR(2, b, 7);
    pack12(pk, C, 0);
    dump12<128>(c.kC + ko + 64, pk);
    release_stage<2, 24576>(c, b < 11);
    if (b == 11) tail_free(bar + B_TFREE * 8);
    pack12(pv2, C, 24);
    pack12(pq, C, 48);
    TR(2, b, 8);
    issue_core<SM_X1, 0, SPL>(C);
    if (w) nb_sync(N_PVISS, 384);
    issue_core<SM_X1, SPL, 8>(C);
    TR(2, b, 9);
  }
  if (!FIRST) fence_async();
  TR(2, b, 14);
  if (!LAST) issue_core<SM_X1, 8, 12>(C);
  if (!FIRST) nb_arrive(N_KRDY, 256);
  TR(2, b, 1);
  if (!LAST) mbar_wait(bar + (B_FULL + 0) * 8, pa ^ 1);
  if (w) mbar_wait(bar + B_VFREE * 8, pa);
  TR(2, b, 10);
  if (!FIRST) dump12<128>(c.vC ^ vx, pv);
  if (!LAST) dump12<256>(c.qC ^ qx, pq);
  if (c.hvalid) dump12<128>(c.vH ^ vx, hv);
  if (LAST) { fence_async(); nb_arrive(N_VQ0, 256); nb_arrive(N_VQ1, 256); return; }
  dump12<128>((c.vC ^ vx ^ 16) + 768, pv2);
  TR(2, b, 11);
  wg_wait<0>(); pin(C);
  TR(2, b, 12);
  release_stage<1, 24576>(c, b < 11);
  pack12(pk, C, 0);
  pack12(pv, C, 24);
  pack12(pq, C, 48);
}

__device__ __forceinline__ float fold(float a, float b, float t, int useb) {
  float r;
  asm("{\n.reg .pred p;\nsetp.ne.b32 p, %4, 0;\nfma.rn.f32 %0, %1, 0f3E553B95, %3;\n@p fma.rn.f32 %0, %2, 0f3E553B95, %3;\n}"
      : "=&f"(r) : "f"(a), "f"(b), "f"(t), "r"(useb));
  return r;
}
template <int U, int L>
__device__ __forceinline__ void softmax_tile(const float (&SA)[56], const float (&SB)[56], const float (&T)[16], int b0, int b1,
                                             uint32_t (&P)[28], float (&sx)[8]) {
  float lu[14], ll[14];
#pragma unroll
  for (int j = 0; j < 7; j++) {
    constexpr int sh = U == L ? 2 : 0;
    const float tu0 = T[2 * j + sh], tu1 = T[2 * j + 1 + sh], tl0 = T[2 * j], tl1 = T[2 * j + 1];
    lu[2 * j]     = fold(SA[4 * (U + j)],     SB[4 * (U + j)],     tu0, b0);
    ll[2 * j]     = fold(SA[4 * (L + j) + 2], SB[4 * (L + j) + 2], tl0, b0);
    lu[2 * j + 1] = fold(SA[4 * (U + j) + 1], SB[4 * (U + j) + 1], tu1, b1);
    ll[2 * j + 1] = fold(SA[4 * (L + j) + 3], SB[4 * (L + j) + 3], tl1, b1);
  }
  float mu = lu[0], ml = ll[0], mu2 = lu[1], ml2 = ll[1];
#pragma unroll
  for (int j = 1; j < 7; j++) { mu = fmaxf(mu, lu[2 * j]); mu2 = fmaxf(mu2, lu[2 * j + 1]); ml = fmaxf(ml, ll[2 * j]); ml2 = fmaxf(ml2, ll[2 * j + 1]); }
  mu = fmaxf(mu, mu2); ml = fmaxf(ml, ml2);
  { const float a1 = __shfl_xor_sync(0xffffffffu, mu, 1), a2 = __shfl_xor_sync(0xffffffffu, mu, 2), a3 = __shfl_xor_sync(0xffffffffu, mu, 3);
    const float c1 = __shfl_xor_sync(0xffffffffu, ml, 1), c2 = __shfl_xor_sync(0xffffffffu, ml, 2), c3 = __shfl_xor_sync(0xffffffffu, ml, 3);
    mu = fmaxf(fmaxf(mu, a1), fmaxf(a2, a3)); ml = fmaxf(fmaxf(ml, c1), fmaxf(c2, c3)); }
  float su = 0.f, sl = 0.f;
#pragma unroll
  for (int c = 0; c < 14; c++) {
    const int iu = (c >> 1) * 4 + (c & 1) * 2;
    if (c >= U && c < U + 7) {
      float e0 = ex2(lu[2 * (c - U)] - mu), e1 = ex2(lu[2 * (c - U) + 1] - mu);
      su = c == U ? e0 + e1 : (su + e0) + e1; P[iu] = pack2(e0, e1);
    } else P[iu] = 0u;
    if (c >= L && c < L + 7) {
      float e0 = ex2(ll[2 * (c - L)] - ml), e1 = ex2(ll[2 * (c - L) + 1] - ml);
      sl = c == L ? e0 + e1 : (sl + e0) + e1; P[iu + 1] = pack2(e0, e1);
    } else P[iu + 1] = 0u;
  }
  sx[0] = su; sx[4] = sl;
#pragma unroll
  for (int k = 1; k < 4; k++) { sx[k] = __shfl_xor_sync(0xffffffffu, su, k); sx[4 + k] = __shfl_xor_sync(0xffffffffu, sl, k); }
}

struct Maps { CUtensorMap xc, xh, w, os, wo, ot; };

__global__ void __cluster_dims__(4, 1, 1) __launch_bounds__(512, 1)
na_attn_kernel(const __grid_constant__ Maps mp, const __nv_bfloat16* __restrict__ wqkv, const __nv_bfloat16* __restrict__ rpb) {
  extern __shared__ __align__(1024) uint8_t smem_raw[];
  const uint32_t sb = smem_u32(smem_raw);
  if ((sb & 0x3FFFF) != SBC) return;
  const uint32_t bar = sb + SM_BAR;
  TR2(blockIdx.x, 0);
  const int tid = threadIdx.x, lane = tid & 31;
  const int warp = __shfl_sync(0xffffffffu, tid >> 5, 0);
  const int head = blockIdx.x & 3, cl = blockIdx.x >> 2;
  const int par = cl / 7, strip = cl - par * 7, ph = par >> 1, pw = par & 1;

  uint4 wv[3];
  const int wr = tid / 6, wc = tid - wr * 6;
  if (warp < 12) {
#pragma unroll
    for (int i = 0; i < 3; i++) wv[i] = __ldg(reinterpret_cast<const uint4*>(wqkv + (wr + i * 64) * 576 + 384 + head * 48 + wc * 8));
  } else if (elect_one()) {
    if (warp == 12) {
      mbar_init(bar + B_WK * 8, 1);
#pragma unroll
      for (int i = 0; i < 3; i++) load_w(&mp.w, sb + SM_W + i * 6144, bar + B_WK * 8, 192 + head * 48 + i * 16);
      mbar_expect(bar + B_WK * 8, 18432);
    } else if (warp == 13) {
#pragma unroll
      for (int i = 0; i < B_WK; i++) mbar_init(bar + i * 8, i < B_EMPTY ? 4 : (i < B_TIN ? 16 : (i < B_TFREE ? 1 : 16)));
    } else if (warp == 14) {
#pragma unroll
      for (int i = B_WQ; i < B_COUNT; i++) mbar_init(bar + i * 8, i < B_Q0 ? 1 : (i < B_ODONE ? 4 : 8));
    }
    asm volatile("fence.mbarrier_init.release.cluster;" ::: "memory");
  }
  __syncwarp();
  asm volatile("barrier.cluster.arrive.relaxed.aligned;" ::: "memory");

  if (warp >= 12) {
    asm volatile("setmaxnreg.dec.sync.aligned.u32 24;");
    asm volatile("griddepcontrol.launch_dependents;");
    const int cc = ph * 112 + (head ? strip * 16 : (strip == 0 ? 16 : (strip == 6 ? 74 : strip * 16 - 3)));
    const int sd = strip == 0 ? -1 : (strip == 6 ? 1 : 0);
    const int r0 = head == 0 ? -4 : (head == 1 ? 4 : 0);
    asm volatile("barrier.cluster.wait.aligned;" ::: "memory");
    if (warp == 12) {
      const uint32_t fb = bar + (B_FULL + head) * 8, eb = bar + (B_EMPTY + head) * 8;
      const uint32_t dst = sb + (head == 0 ? SM_X0 : (head == 1 ? SM_X1 : SM_X2));
      const int nl = head == 0 ? 15 : (head == 3 ? 1 : 14);
#pragma unroll 1
      for (int n = 0; n < nl; n++) {
        if (n) mbar_wait(eb, (n - 1) & 1);
        if (elect_one()) {
          if (head == 0) {
            asm volatile("cp.async.bulk.tensor.5d.shared::cluster.global.mbarrier::complete_tx::bytes.multicast::cluster [%0], [%1, {%3,%4,%5,%6,%7}], [%2], %8;"
                         ::"r"(dst), "l"(&mp.xh), "r"(fb), "r"(0), "r"(8 * n + r0), "r"(cc), "r"(sd), "r"(pw * 3), "h"((uint16_t)15) : "memory");
            if (n + 1 < nl) asm volatile("cp.async.bulk.prefetch.tensor.5d.L2.global [%0, {%1,%2,%3,%4,%5}];" ::"l"(&mp.xh), "r"(0), "r"(8 * n + 8 + r0), "r"(cc), "r"(sd), "r"(pw * 3) : "memory");
          } else if (head < 3) {
            asm volatile("cp.async.bulk.tensor.4d.shared::cluster.global.mbarrier::complete_tx::bytes.multicast::cluster [%0], [%1, {%3,%4,%5,%6}], [%2], %7;"
                         ::"r"(dst), "l"(&mp.xc), "r"(fb), "r"(0), "r"(8 * n + r0), "r"(cc), "r"(pw * 3), "h"((uint16_t)15) : "memory");
          }
          if (n == 0) {
#pragma unroll
            for (int i = 0; i < 3; i++) load_w(&mp.w, sb + SM_W + (6 + i) * 6144, bar + B_WQ * 8, head * 48 + i * 16);
            mbar_expect(bar + B_WQ * 8, 18432);
            mbar_expect(bar + B_TIN * 8, 24576); mbar_expect(bar + (B_TIN + 1) * 8, 24576); mbar_expect(bar + (B_TIN + 2) * 8, 24576);
          }
          if (head && n + 1 < nl) asm volatile("cp.async.bulk.prefetch.tensor.4d.L2.global [%0, {%1,%2,%3,%4}];" ::"l"(&mp.xc), "r"(0), "r"(8 * n + 8 + r0), "r"(cc), "r"(pw * 3) : "memory");
        }
        __syncwarp();
      }
    }
    if (warp == 14) {
      int* flag = g_flags + cl * 2;
      nb_arrive(N_VQ0, 288); nb_arrive(N_VQ1, 288);
#pragma unroll 1
      for (int b = 0; b < TB; b++) {
        mbar_wait(bar + B_ODONE * 8, b & 1);
        if (lane == 0) {
          asm volatile("cp.async.bulk.tensor.3d.global.shared::cta.bulk_group [%0, {%2,%3,%4}], [%1];"
                       ::"l"(&mp.os), "r"(sb + SM_O), "r"(pw * 192), "r"(8 * b + 2 * head), "r"(ph * 112 + strip * 16) : "memory");
          asm volatile("cp.async.bulk.commit_group;\ncp.async.bulk.wait_group 0;" ::: "memory");
        }
        __syncwarp();
        nb_arrive(N_VQ0, 288); nb_arrive(N_VQ1, 288);
        if (lane == 0)
          asm volatile("fence.proxy.async.global;\nfence.acq_rel.gpu;\nred.relaxed.gpu.global.add.s32 [%0], 1;\nred.relaxed.gpu.global.add.s32 [%0+4], 1;"
                       ::"l"(flag + b * 56) : "memory");
        __syncwarp();
      }
    } else if (warp & 1) {
      const int j = (warp >> 1) & 1;
#pragma unroll 1
      for (int i = 0; i < 2; i++) {
        mbar_wait(bar + (B_OTAIL + j) * 8, i);
        if (i == 0) nb_arrive(N_VQ0 + j, 288);
        mbar_wait(bar + (B_TFREE + i) * 8, 0);
        if (elect_one()) {
#pragma unroll 1
          for (int d = 0; d < 8; d++) {
            const int dst = (d + head) & 3, pc = d >> 2;
            send_o<1536>(sb + (i ? SM_X1 : SM_X2) + head * 6144 + j * 3072 + pc * 1536,
                         sb + (i ? SM_Q : SM_O) + (4 * j + (dst & 2) + pc) * (i ? 3072 : 1536), bar + (B_TIN + i) * 8, dst);
          }
        }
        __syncwarp();
      }
    }
    cluster_sync();
  } else if (warp >= 8) {
    asm volatile("setmaxnreg.inc.sync.aligned.u32 %0;" ::"n"(RG));
    GemmCtx c;
    c.bar = bar;
    const int gw = warp - 8, tk = gw * 16 + (lane & 15), hi = lane >> 4;
    { const int col = tk >> 2, i = tk & 3;
      c.kC = sb + SM_K + (col + 3) * KS + hi * 128 + i * 16;
      c.vC = sb + SM_V + (col + 3) * 1536 + hi * 128 + (2 * i + ((col + 3) & 1)) * 16;
      c.qC = sb + SM_Q + col * 1536 + hi * 256 + (col & 1) * 64 + i * 16; }
    { const int ci = (tk >> 3) - 2, kc = ci < 3 ? ci : ci + 16, i = tk & 7; c.hvalid = gw > 0;
      c.kH = sb + SM_K + kc * KS + hi * 128 + i * 16;
      c.vH = sb + SM_V + kc * 1536 + hi * 128 + (i >> 2) * 768 + (2 * (i & 3) + ((kc ^ (i >> 2)) & 1)) * 16; }
    asm volatile("barrier.cluster.wait.aligned;" ::: "memory");
    if (elect_one()) { mbar_expect(bar + B_FULL * 8, 4608); mbar_expect(bar + (B_FULL + 1) * 8, 6144); mbar_expect(bar + (B_FULL + 2) * 8, 6144); }
    __syncwarp();
#pragma unroll
    for (int i = 0; i < 3; i++) sts128(sb + SM_W + (3 + (wc >> 1)) * 6144 + (wr + i * 64) * 32 + ((wc ^ (wr >> 2)) & 1) * 16, wv[i]);
    fence_async();
    asm volatile("bar.sync 1, 384;" ::: "memory");
    mbar_wait(bar + B_WK * 8, 0);
    uint32_t pk[12], pv[12], pq[12];
    TRDECL;
    gemm_iter<true, false>(c, -2, pk, pv, pq, &mp.wo TRPASS);
    TR2(blockIdx.x, 4);
#pragma unroll 1
    for (int b = -1; b < 12; b++) gemm_iter<false, false>(c, b, pk, pv, pq, &mp.wo TRPASS);
    TR2(blockIdx.x, 6);
    gemm_iter<false, true>(c, 12, pk, pv, pq, &mp.wo TRPASS);
    TR(2, 13, 0);
    mbar_wait(bar + B_WO * 8, 0);
    TR(2, 13, 1);
    const uint32_t st = sb + SM_TST + gw * 3072;
    const uint32_t sta = st + (lane & 15) * 64 + ((hi ^ ((lane >> 1) & 3)) * 16);
#pragma unroll 1
    for (int i = 0; i < 3; i++) {
      constexpr uint64_t db = mkdesc(SBC + SM_TWO, 12288, 512, 2);
      const uint64_t da = mkdesc(SBC, 128, 768, 0) + (i ^ (i < 2)) * (24576 / 16);
      float D[48];
      mbar_wait(bar + (B_TIN + i) * 8, 0);
      if (i == 2) asm volatile("barrier.cluster.arrive.relaxed.aligned;" ::: "memory");
      else nb_sync(i ? N_PVISS : N_QK1, i ? 384 : 256);
      TR(2, 13 - i, 2); TR(2, 12 + i, 5); TR(2, 11 + i, 9);
      wg_fence();
      wg_ss96<0>(D, da, db);
#pragma unroll
      for (int k = 1; k < 12; k++) wg_ss96<1>(D, da + (k / 3) * 384 + (k % 3) * 16, db + k * 64);
      wg_commit();
      if (lane == 0) asm volatile("cp.async.bulk.wait_group.read 0;" ::: "memory");
      __syncwarp();
      wg_wait<0>(); pin(D);
      TR(2, 13 - i, 3); TR(2, 12 + i, 6); TR(2, 11 + i, 10);
#pragma unroll
      for (int q = 0; q < 6; q++)
        stsm4((sta ^ ((q & 1) * 32)) + (q >> 1) * 1024,
              pack2(D[8 * q], D[8 * q + 1]), pack2(D[8 * q + 2], D[8 * q + 3]), pack2(D[8 * q + 4], D[8 * q + 5]), pack2(D[8 * q + 6], D[8 * q + 7]));
      fence_async();
      __syncwarp();
      if (lane == 0) {
        asm volatile("cp.async.bulk.tensor.4d.global.shared::cta.bulk_group [%0, {%2,%3,%4,%5}], [%1];"
                     ::"l"(&mp.ot), "r"(st), "r"(0), "r"(8 * (TB + i)), "r"(ph * 112 + strip * 16 + 8 * (gw >> 1) + 4 * (head >> 1) + 2 * (gw & 1)), "r"(pw * 6 + (head & 1) * 3) : "memory");
        asm volatile("cp.async.bulk.commit_group;" ::: "memory");
      }
      TR(2, 13 - i, 4); TR(2, 12 + i, 7); TR(2, 11 + i, 11);
    }
    if (lane == 0) asm volatile("cp.async.bulk.wait_group.read 0;" ::: "memory");
    __syncwarp();
    TR(2, 13, 8);
    TR2(blockIdx.x, 2);
    TRDUMP;
    asm volatile("barrier.cluster.wait.aligned;" ::: "memory");
  } else {
    asm volatile("setmaxnreg.inc.sync.aligned.u32 %0;" ::"n"(RA));
    float rv = -INFINITY;
    if (tid < 169) rv = __bfloat162float(rpb[head * 169 + tid]) * 1.4426950408889634f;
    if (tid < 192) {
      const int kc = (wr & 15) + 3;
      sts128(tid < 96 ? sb + SM_K + kc * KS + wc * 128 + 48 : sb + SM_V + kc * 1536 + wc * 128 + (6 + (kc & 1)) * 16, make_uint4(0, 0, 0, 0));
    }
#pragma unroll
    for (int i = 0; i < 3; i++) sts128(sb + SM_W + (3 + (wc >> 1)) * 6144 + (wr + i * 64) * 32 + ((wc ^ (wr >> 2)) & 1) * 16, wv[i]);
    fence_async();
    asm volatile("bar.arrive 1, 384;" ::: "memory");
    if (tid < 182) asm volatile("st.shared.f32 [%0], %1;" ::"r"(sb + SM_RPB + tid * 4), "f"(rv) : "memory");
    const int j = warp >> 2, w = warp & 3;
    int variant = w;
    if (strip == 0 && j == 0 && w < 2) variant = 4;
    if (strip == 6 && j == 1 && w >= 2) variant = 5;
    const uint32_t qa = sb + SM_Q + (8 * j + 2 * w + ((lane >> 3) & 1)) * 1536 + (lane >> 4) * 256 + (((lane & 7) * 16) ^ (((lane >> 3) & 1) * 64));
    uint32_t oa = sb + SM_O + j * 6144 + (2 * w + ((lane >> 3) & 1)) * 768 + (lane >> 4) * 128 + (lane & 7) * 16;
    const uint64_t dK = mkdesc(SBC + SM_K, 128, KS, 0) + j * (8 * KS / 16);
    const uint64_t dV = mkdesc(SBC + SM_V, 768, 128, 0) + j * (8 * 1536 / 16);
    asm volatile("barrier.cluster.wait.aligned;" ::: "memory");
    asm volatile("bar.sync 3, 256;" ::: "memory");
    float T[16];
    TRDECL;
    int b0 = 0, b1 = 0;
    uint32_t meta = 0;
    uint32_t q[12];
    mbar_wait(bar + B_Q0 * 8, 0);
#pragma unroll
    for (int k = 0; k < 3; k++) ldsm4(qa + k * 512, q[4 * k], q[4 * k + 1], q[4 * k + 2], q[4 * k + 3]);
#pragma unroll 1
    for (int b = 0; b < 14; b++) {
      const uint32_t pa = b & 1;
      float SA[56], SB[56];
      const uint64_t dA = dK + pa * (KSLOT >> 4), dB = dK + (pa ^ 1) * (KSLOT >> 4);
      TR(0, b, 0);
      nb_sync(N_KRDY + j, 256);
      TR(0, b, 1);
      TR(0, b - 1, 9);
      wg_fence();
      wg_rs112<0>(SA, q[0], q[1], q[2], q[3], dA);
      wg_rs112<0>(SB, q[0], q[1], q[2], q[3], dB);
      wg_rs112<1>(SA, q[4], q[5], q[6], q[7], dA + 16);
      wg_rs112<1>(SB, q[4], q[5], q[6], q[7], dB + 16);
      wg_rs112<1>(SA, q[8], q[9], q[10], q[11], dA + 32);
      wg_rs112<1>(SB, q[8], q[9], q[10], q[11], dB + 32);
      wg_commit();
      nb_arrive(N_QK0 + j, 256);
      TR(0, b, 2);
      if (b <= 1 || b == 13) {
        uint32_t ln; asm volatile("mov.u32 %0, %%laneid;" : "=r"(ln));
        const int g = ln >> 2, t = ln & 3;
        const int sw = b == 0 ? max(g + 1, 4) : (b == 13 ? min(g + 1, 5) : g + 1);
        const int i0 = 2 * t, i1 = 2 * t + 1;
        b0 = i0 <= sw - 2; b1 = i1 <= sw - 2;
        const uint32_t tb = sb + SM_RPB + (variant < 4 ? 3 : variant + 1 - 2 * w) * 4;
        const uint32_t ra0 = tb + (i0 == sw - 1 ? 13 : i0 + 8 * b0 - g + 2) * 52;
        const uint32_t ra1 = tb + (i1 == sw - 1 ? 13 : i1 + 8 * b1 - g + 2) * 52;
#pragma unroll
        for (int jj = 0; jj < 8; jj++) { T[2 * jj] = lds_f32(ra0 + jj * 4); T[2 * jj + 1] = lds_f32(ra1 + jj * 4); }
        meta = ((0x5555u & ((1u << (2 * (sw - 1))) - 1)) ^ 0xDD88u ^ (((t ^ b) & 1) ? 0x5555u : 0u)) * 0x10001u;
      } else meta ^= 0x55555555u;
      if (b >= 12) oa += b == 12 ? warp * 1536 - (SM_O - SM_Q) : 1536;
      wg_wait<0>(); pin(SA); pin(SB);
      mbar_arrive_elect(bar + B_KFREE * 8);
      TR(0, b, 3);
      TR(0, b - 1, 10);
      uint32_t P[28];
      float sx[8];
      switch (variant) {
        case 0: softmax_tile<0, 1>(SA, SB, T, b0, b1, P, sx); break;
        case 1: softmax_tile<2, 3>(SA, SB, T, b0, b1, P, sx); break;
        case 2: softmax_tile<4, 5>(SA, SB, T, b0, b1, P, sx); break;
        case 3: softmax_tile<6, 7>(SA, SB, T, b0, b1, P, sx); break;
        case 4: softmax_tile<3, 3>(SA, SB, T, b0, b1, P, sx); break;
        default: softmax_tile<4, 4>(SA, SB, T, b0, b1, P, sx); break;
      }
      float O[24];
      TR(0, b, 4);
      nb_sync(N_VQ0 + j, b == 13 ? 256 : 288);
      TR(0, b, 5);
#pragma unroll
      for (int k = 0; k < 3; k++) ldsm4(qa + (pa ^ 1) * 128 + k * 512, q[4 * k], q[4 * k + 1], q[4 * k + 2], q[4 * k + 3]);
      wg_fence();
      wg_sp48<0>(O, P[0], P[1], P[2], P[3], dV, meta);
#pragma unroll
      for (int s = 1; s < 7; s++) wg_sp48<1>(O, P[4 * s], P[4 * s + 1], P[4 * s + 2], P[4 * s + 3], dV + s * 192, meta);
      wg_commit();
      if (b != 12) nb_arrive(N_PVISS, 384);
      TR(0, b, 6);
      wg_wait<0>(); pin(O);
      mbar_arrive_elect(bar + B_VFREE * 8);
      TR(0, b, 7);
      float ru, rl;
      asm("rcp.approx.ftz.f32 %0, %1;" : "=f"(ru) : "f"(((fmaf(O[0], 0.f, sx[0]) + sx[1]) + sx[2]) + sx[3]));
      asm("rcp.approx.ftz.f32 %0, %1;" : "=f"(rl) : "f"(((fmaf(O[2], 0.f, sx[4]) + sx[5]) + sx[6]) + sx[7]));
#pragma unroll
      for (int i = 0; i < 3; i++)
        stsm4(oa + i * 256, pack2(O[8 * i] * ru, O[8 * i + 1] * ru), pack2(O[8 * i + 2] * rl, O[8 * i + 3] * rl),
              pack2(O[8 * i + 4] * ru, O[8 * i + 5] * ru), pack2(O[8 * i + 6] * rl, O[8 * i + 7] * rl));
      if (b < 13) publish(bar + (b < TB ? B_ODONE : B_OTAIL + j) * 8);
      else {
        fence_async();
        mbar_wait(bar + (B_TFREE + 1) * 8, 0);
        __syncwarp();
        if (elect_one()) {
#pragma unroll
          for (int d = 0; d < 2; d++)
            send_o<1536>(sb + SM_X0 + head * 6144 + (2 * j + (w & 1)) * 1536, sb + SM_Q + warp * 3072 + 1536, bar + (B_TIN + 2) * 8, (w & 2) + (d ^ (head & 1)));
        }
        __syncwarp();
      }
      TR(0, b, 8);
    }
    TRDUMP;
    cluster_sync();
  }
}

constexpr int NSTB = 6;
constexpr int NTB = TB * 56;
constexpr int SM_B_IN = 0;
constexpr int SM_B_W = SM_B_IN + NSTB * 24576;
constexpr int SM_B_BAR = SM_B_W + 73728;
constexpr int SM_B_TOTAL = SM_B_BAR + 128;
struct MapsB { CUtensorMap oi, oo, wo; };

__global__ void __launch_bounds__(480, 1)
na_proj_kernel(const __grid_constant__ MapsB mp) {
  extern __shared__ __align__(1024) uint8_t smem_raw[];
  const uint32_t sb = smem_u32(smem_raw);
  if ((sb & 0x3FFFF) != SBC) return;
  const uint32_t bar = sb + SM_B_BAR;
  const int tid = threadIdx.x, lane = tid & 31;
  const int warp = __shfl_sync(0xffffffffu, tid >> 5, 0);
  TR2(132 + blockIdx.x, 0);
  TRB(47, 0);
  if (warp == 12 && elect_one()) {
#pragma unroll
    for (int i = 0; i <= 2 * NSTB; i++) mbar_init(bar + i * 8, i < NSTB || i == 2 * NSTB ? 1 : 4);
    mbar_expect(bar + 2 * NSTB * 8, 73728);
#pragma unroll
    for (int i = 0; i < 2; i++)
      asm volatile("cp.async.bulk.tensor.3d.shared::cluster.global.mbarrier::complete_tx::bytes [%0], [%1, {%3,%4,%5}], [%2];"
                   ::"r"(sb + SM_B_W + i * 36864), "l"(&mp.wo), "r"(bar + 2 * NSTB * 8), "r"(0), "r"(0), "r"(i * 3) : "memory");
  }
  __syncthreads();
  const int step = gridDim.x;
  if (warp >= 12) {
    const int wg = warp - 12;
    int use = 0;
#pragma unroll 1
    for (int n = blockIdx.x + wg * step; n < NTB; n += 3 * step, use++) {
      const int b = n / 56, rem = n - b * 56, par = rem / 14, sg = wg + 3 * (use & 1);
      int v; uint32_t spin = 0;
      do { asm volatile("ld.acquire.gpu.global.s32 %0, [%1];" : "=r"(v) : "l"(g_flags + n) : "memory"); } while (v < 4 && ++spin < SPIN_LIMIT);
      TRB(use * 3 + wg, 0);
      asm volatile("fence.proxy.async.global;" ::: "memory");
      if (use >= 2) mbar_wait(bar + (NSTB + sg) * 8, ((use >> 1) - 1) & 1);
      TRB(use * 3 + wg, 1);
      if (elect_one()) {
        mbar_expect(bar + sg * 8, 24576);
        asm volatile("cp.async.bulk.tensor.3d.shared::cluster.global.mbarrier::complete_tx::bytes [%0], [%1, {%3,%4,%5}], [%2];"
                     ::"r"(sb + SM_B_IN + sg * 24576), "l"(&mp.oi), "r"(bar + sg * 8), "r"((par & 1) * 192), "r"(8 * b), "r"((par >> 1) * 112 + (rem - par * 14) * 8) : "memory");
        g_flags[n] = 0;
      }
      __syncwarp();
    }
  } else {
    const int wg = warp >> 2, w = warp & 3;
    constexpr uint64_t db = mkdesc(SBC + SM_B_W, 12288, 512, 2);
    const uint32_t sta0 = sb + SM_B_IN + w * 6144 + (lane & 15) * 128 + (((lane >> 4) ^ (lane & 7)) * 16);
    mbar_wait(bar + 2 * NSTB * 8, 0);
    TRB(47, 1);
    int use = 0;
#pragma unroll 1
    for (int n = blockIdx.x + wg * step; n < NTB; n += 3 * step, use++) {
      const int b = n / 56, rem = n - b * 56, par = rem / 14, sg = wg + 3 * (use & 1);
      const uint64_t da = mkdesc(SBC + SM_B_IN, 128, 3072, 0) + sg * (24576 / 16);
      float D[96];
      mbar_wait(bar + sg * 8, (use >> 1) & 1);
      if (use | wg) nb_sync(4 + wg, 256);
      TRB(use * 3 + wg, 3);
      wg_fence();
      wg_ss192<0>(D, da, db);
#pragma unroll
      for (int k = 1; k < 12; k++) wg_ss192<1>(D, da + k * 16, db + k * 64);
      wg_commit();
      if (n + step < NTB) nb_arrive(wg == 2 ? 4 : 5 + wg, 256);
      TRB(use * 3 + wg, 4);
      if (use && lane == 0) {
        asm volatile("cp.async.bulk.wait_group.read 0;" ::: "memory");
        mbar_arrive(bar + (NSTB + wg + 3 * (~use & 1)) * 8);
      }
      __syncwarp();
      wg_wait<0>(); pin(D);
      nb_sync(1 + wg, 128);
      TRB(use * 3 + wg, 5);
      const uint32_t sta = sta0 + sg * 24576;
#pragma unroll
      for (int q = 0; q < 12; q++)
        stsm4((sta ^ ((q & 3) * 32)) + (q >> 2) * 2048,
              pack2(D[8 * q], D[8 * q + 1]), pack2(D[8 * q + 2], D[8 * q + 3]), pack2(D[8 * q + 4], D[8 * q + 5]), pack2(D[8 * q + 6], D[8 * q + 7]));
      fence_async();
      __syncwarp();
      if (lane == 0) {
        asm volatile("cp.async.bulk.tensor.4d.global.shared::cta.bulk_group [%0, {%2,%3,%4,%5}], [%1];"
                     ::"l"(&mp.oo), "r"(sb + SM_B_IN + sg * 24576 + w * 6144), "r"(0), "r"(8 * b), "r"((par >> 1) * 112 + (rem - par * 14) * 8 + 2 * w), "r"((par & 1) * 3) : "memory");
        asm volatile("cp.async.bulk.commit_group;" ::: "memory");
      }
      __syncwarp();
      TRB(use * 3 + wg, 6);
    }
    if (lane == 0) asm volatile("cp.async.bulk.wait_group 0;" ::: "memory");
    TR2(132 + blockIdx.x, 2);
  }
}

typedef CUresult (*EncodeFn)(CUtensorMap*, CUtensorMapDataType, cuuint32_t, void*, const cuuint64_t*, const cuuint64_t*, const cuuint32_t*,
                             const cuuint32_t*, CUtensorMapInterleave, CUtensorMapSwizzle, CUtensorMapL2promotion, CUtensorMapFloatOOBfill);
static EncodeFn g_enc = nullptr;
static void make_map(CUtensorMap* m, const void* p, int rank, const cuuint64_t* dim, const cuuint64_t* str, const cuuint32_t* box, CUtensorMapSwizzle sw) {
  const cuuint32_t ones[5] = {1, 1, 1, 1, 1};
  g_enc(m, CU_TENSOR_MAP_DATA_TYPE_BFLOAT16, rank, (void*)p, dim, str, box, ones, CU_TENSOR_MAP_INTERLEAVE_NONE, sw,
        CU_TENSOR_MAP_L2_PROMOTION_L2_128B, CU_TENSOR_MAP_FLOAT_OOB_FILL_NONE);
}

extern "C" void kernel_launch(void* const* d_in, const int* in_sizes, int n_in, void* d_out, int out_size) {
  const __nv_bfloat16* x = (const __nv_bfloat16*)d_in[0];
  const __nv_bfloat16* wqkv = (const __nv_bfloat16*)d_in[1];
  const __nv_bfloat16* wo = (const __nv_bfloat16*)d_in[2];
  const __nv_bfloat16* rpb = (const __nv_bfloat16*)d_in[3];

  if (!g_enc) {
    void* fn = nullptr; cudaDriverEntryPointQueryResult qr;
    cudaGetDriverEntryPoint("cuTensorMapEncodeTiled", &fn, cudaEnableDefault, &qr);
    g_enc = (EncodeFn)fn;
    cudaFuncSetAttribute(na_attn_kernel, cudaFuncAttributeMaxDynamicSharedMemorySize, SM_A_TOTAL);
    cudaFuncSetAttribute(na_proj_kernel, cudaFuncAttributeMaxDynamicSharedMemorySize, SM_B_TOTAL);
  }
  Maps ma; MapsB mb;
  { cuuint64_t dim[4] = {64, 112, 224, 6}, str[3] = {(cuuint64_t)ROWB, 768, 128};
    cuuint32_t box[4] = {64, 4, 16, 3}, boxo[4] = {64, 8, 2, 3};
    make_map(&ma.xc, x, 4, dim, str, box, CU_TENSOR_MAP_SWIZZLE_128B);
    make_map(&mb.oo, d_out, 4, dim, str, boxo, CU_TENSOR_MAP_SWIZZLE_128B); }
  { cuuint64_t dim[5] = {64, 112, 224, 2, 6}, str[4] = {(cuuint64_t)ROWB, 768, 19 * 768, 128};
    cuuint32_t box[5] = {64, 8, 3, 2, 3};
    make_map(&ma.xh, x, 5, dim, str, box, CU_TENSOR_MAP_SWIZZLE_128B); }
  { cuuint64_t dim[3] = {384, 112, 224}, str[2] = {(cuuint64_t)ROWB, 768};
    cuuint32_t box[3] = {192, 8, 8}, boxs[3] = {192, 2, 16};
    make_map(&mb.oi, d_out, 3, dim, str, box, CU_TENSOR_MAP_SWIZZLE_NONE);
    make_map(&ma.os, d_out, 3, dim, str, boxs, CU_TENSOR_MAP_SWIZZLE_NONE); }
  { cuuint64_t dim[4] = {32, 112, 224, 12}, str[3] = {(cuuint64_t)ROWB, 768, 64};
    cuuint32_t box[4] = {32, 8, 2, 3};
    make_map(&ma.ot, d_out, 4, dim, str, box, CU_TENSOR_MAP_SWIZZLE_64B); }
  { cuuint64_t dim[2] = {576, 192}, str[1] = {1152};
    cuuint32_t box[2] = {16, 192};
    make_map(&ma.w, wqkv, 2, dim, str, box, CU_TENSOR_MAP_SWIZZLE_32B); }
  { cuuint64_t dim[3] = {32, 192, 6}, str[2] = {384, 64};
    cuuint32_t box[3] = {32, 192, 3};
    make_map(&ma.wo, wo, 3, dim, str, box, CU_TENSOR_MAP_SWIZZLE_64B);
    mb.wo = ma.wo; }
  na_attn_kernel<<<112, 512, SM_A_TOTAL>>>(ma, wqkv, rpb);
  cudaLaunchConfig_t cfg = {};
  cfg.gridDim = dim3(20); cfg.blockDim = dim3(480); cfg.dynamicSmemBytes = SM_B_TOTAL; cfg.stream = cudaStreamPerThread;
  cudaLaunchAttribute at[1];
  at[0].id = cudaLaunchAttributeProgrammaticStreamSerialization; at[0].val.programmaticStreamSerializationAllowed = 1;
  cfg.attrs = at; cfg.numAttrs = 1;
  cudaLaunchKernelEx(&cfg, na_proj_kernel, mb);
}
```

```cpp
#include <cuda_runtime.h>
#include <cuda_bf16.h>
#include <cuda.h>
#include <stdint.h>

#define SPIN_LIMIT (1u << 18)

__device__ __forceinline__ uint32_t smem_u32(const void* p) { return (uint32_t)__cvta_generic_to_shared(p); }
__device__ __forceinline__ void wg_fence() { asm volatile("wgmma.fence.sync.aligned;" ::: "memory"); }
__device__ __forceinline__ void wg_commit() { asm volatile("wgmma.commit_group.sync.aligned;" ::: "memory"); }
template <int N> __device__ __forceinline__ void wg_wait() { asm volatile("wgmma.wait_group.sync.aligned %0;" ::"n"(N) : "memory"); }
template <int N> __device__ __forceinline__ void pin(float (&d)[N]) {
#pragma unroll
  for (int i = 0; i < N; i++) asm volatile("" : "+f"(d[i])::"memory");
}
__host__ __device__ constexpr uint64_t mkdesc(uint32_t addr, uint32_t lbo, uint32_t sbo, uint32_t sw) {
  return (uint64_t)((addr & 0x3FFFF) >> 4) | ((uint64_t)(lbo >> 4) << 16) | ((uint64_t)(sbo >> 4) << 32) | ((uint64_t)sw << 62);
}
__device__ __forceinline__ void mbar_init(uint32_t bar, uint32_t cnt) { asm volatile("mbarrier.init.shared::cta.b64 [%0], %1;" ::"r"(bar), "r"(cnt) : "memory"); }
__device__ __forceinline__ void mbar_arrive(uint32_t bar) { asm volatile("mbarrier.arrive.shared::cta.b64 _, [%0];" ::"r"(bar) : "memory"); }
__device__ __forceinline__ bool elect_one() {
  uint32_t r; asm volatile("{\n.reg .pred p;\nelect.sync _|p, 0xffffffff;\nselp.u32 %0, 1, 0, p;\n}" : "=r"(r)); return r;
}
__device__ __forceinline__ void mbar_arrive_elect(uint32_t bar) {
  asm volatile("{\n.reg .pred p;\nelect.sync _|p, 0xffffffff;\n@p mbarrier.arrive.shared::cta.b64 _, [%0];\n}" ::"r"(bar) : "memory");
}
__device__ __forceinline__ void mbar_expect(uint32_t bar, uint32_t bytes) { asm volatile("mbarrier.arrive.expect_tx.shared::cta.b64 _, [%0], %1;" ::"r"(bar), "r"(bytes) : "memory"); }
__device__ __forceinline__ void mbar_arrive_remote(uint32_t bar, uint32_t cta) {
  asm volatile("{\n.reg .b32 ra;\nmapa.shared::cluster.u32 ra, %0, %1;\nmbarrier.arrive.relaxed.cluster.shared::cluster.b64 _, [ra];\n}" ::"r"(bar), "r"(cta) : "memory");
}
__device__ __forceinline__ void mbar_wait(uint32_t bar, uint32_t parity) {
  asm volatile("{\n.reg .pred p;\n.reg .b32 n;\nmov.b32 n, 0;\nWL:\nmbarrier.try_wait.parity.shared::cta.b64 p, [%0], %1;\n@p bra WD;\n"
               "add.u32 n, n, 1;\nsetp.lt.u32 p, n, 65536;\n@p bra WL;\nWD:\n}" ::"r"(bar), "r"(parity) : "memory");
}
__device__ __forceinline__ void nb_sync(int id, int n) { asm volatile("bar.sync %0, %1;" ::"r"(id), "r"(n) : "memory"); }
__device__ __forceinline__ void nb_arrive(int id, int n) { asm volatile("bar.arrive %0, %1;" ::"r"(id), "r"(n) : "memory"); }
__device__ __forceinline__ void fence_async() { asm volatile("fence.proxy.async.shared::cta;" ::: "memory"); }
__device__ __forceinline__ void cluster_sync() {
  asm volatile("barrier.cluster.arrive.relaxed.aligned;\nbarrier.cluster.wait.aligned;" ::: "memory");
}
__device__ __forceinline__ uint32_t pack2(float lo, float hi) {
  uint32_t r; asm("cvt.rn.bf16x2.f32 %0, %1, %2;" : "=r"(r) : "f"(hi), "f"(lo)); return r;
}
__device__ __forceinline__ void stsm4(uint32_t a, uint32_t r0, uint32_t r1, uint32_t r2, uint32_t r3) {
  asm volatile("stmatrix.sync.aligned.m8n8.x4.shared.b16 [%0], {%1,%2,%3,%4};" ::"r"(a), "r"(r0), "r"(r1), "r"(r2), "r"(r3) : "memory");
}
__device__ __forceinline__ void ldsm4(uint32_t a, uint32_t& r0, uint32_t& r1, uint32_t& r2, uint32_t& r3) {
  asm volatile("ldmatrix.sync.aligned.m8n8.x4.shared.b16 {%0,%1,%2,%3}, [%4];" : "=r"(r0), "=r"(r1), "=r"(r2), "=r"(r3) : "r"(a) : "memory");
}
__device__ __forceinline__ void sts128(uint32_t a, uint4 v) {
  asm volatile("st.shared.v4.b32 [%0], {%1,%2,%3,%4};" ::"r"(a), "r"(v.x), "r"(v.y), "r"(v.z), "r"(v.w) : "memory");
}
__device__ __forceinline__ float lds_f32(uint32_t a) { float v; asm volatile("ld.shared.f32 %0, [%1];" : "=f"(v) : "r"(a)); return v; }
__device__ __forceinline__ float ex2(float x) { float y; asm("ex2.approx.ftz.f32 %0, %1;" : "=f"(y) : "f"(x)); return y; }

template<int SC> __device__ __forceinline__ void wg_ss144(float (&d)[72], uint64_t da, uint64_t db) {
  asm volatile("{\n.reg .pred p;\nsetp.ne.b32 p, %74, 0;\nwgmma.mma_async.sync.aligned.m64n144k16.f32.bf16.bf16 {%0,%1,%2,%3,%4,%5,%6,%7,%8,%9,%10,%11,%12,%13,%14,%15,%16,%17,%18,%19,%20,%21,%22,%23,%24,%25,%26,%27,%28,%29,%30,%31,%32,%33,%34,%35,%36,%37,%38,%39,%40,%41,%42,%43,%44,%45,%46,%47,%48,%49,%50,%51,%52,%53,%54,%55,%56,%57,%58,%59,%60,%61,%62,%63,%64,%65,%66,%67,%68,%69,%70,%71}, %72, %73, p, 1, 1, 0, 1;\n}\n"
    : "+f"(d[0]),"+f"(d[1]),"+f"(d[2]),"+f"(d[3]),"+f"(d[4]),"+f"(d[5]),"+f"(d[6]),"+f"(d[7]),"+f"(d[8]),"+f"(d[9]),"+f"(d[10]),"+f"(d[11]),"+f"(d[12]),"+f"(d[13]),"+f"(d[14]),"+f"(d[15]),"+f"(d[16]),"+f"(d[17]),"+f"(d[18]),"+f"(d[19]),"+f"(d[20]),"+f"(d[21]),"+f"(d[22]),"+f"(d[23]),"+f"(d[24]),"+f"(d[25]),"+f"(d[26]),"+f"(d[27]),"+f"(d[28]),"+f"(d[29]),"+f"(d[30]),"+f"(d[31]),"+f"(d[32]),"+f"(d[33]),"+f"(d[34]),"+f"(d[35]),"+f"(d[36]),"+f"(d[37]),"+f"(d[38]),"+f"(d[39]),"+f"(d[40]),"+f"(d[41]),"+f"(d[42]),"+f"(d[43]),"+f"(d[44]),"+f"(d[45]),"+f"(d[46]),"+f"(d[47]),"+f"(d[48]),"+f"(d[49]),"+f"(d[50]),"+f"(d[51]),"+f"(d[52]),"+f"(d[53]),"+f"(d[54]),"+f"(d[55]),"+f"(d[56]),"+f"(d[57]),"+f"(d[58]),"+f"(d[59]),"+f"(d[60]),"+f"(d[61]),"+f"(d[62]),"+f"(d[63]),"+f"(d[64]),"+f"(d[65]),"+f"(d[66]),"+f"(d[67]),"+f"(d[68]),"+f"(d[69]),"+f"(d[70]),"+f"(d[71]) : "l"(da), "l"(db), "n"(SC));
}
template<int SC> __device__ __forceinline__ void wg_ss96(float (&d)[48], uint64_t da, uint64_t db) {
  asm volatile("{\n.reg .pred p;\nsetp.ne.b32 p, %50, 0;\nwgmma.mma_async.sync.aligned.m64n96k16.f32.bf16.bf16 {%0,%1,%2,%3,%4,%5,%6,%7,%8,%9,%10,%11,%12,%13,%14,%15,%16,%17,%18,%19,%20,%21,%22,%23,%24,%25,%26,%27,%28,%29,%30,%31,%32,%33,%34,%35,%36,%37,%38,%39,%40,%41,%42,%43,%44,%45,%46,%47}, %48, %49, p, 1, 1, 0, 1;\n}\n"
    : "+f"(d[0]),"+f"(d[1]),"+f"(d[2]),"+f"(d[3]),"+f"(d[4]),"+f"(d[5]),"+f"(d[6]),"+f"(d[7]),"+f"(d[8]),"+f"(d[9]),"+f"(d[10]),"+f"(d[11]),"+f"(d[12]),"+f"(d[13]),"+f"(d[14]),"+f"(d[15]),"+f"(d[16]),"+f"(d[17]),"+f"(d[18]),"+f"(d[19]),"+f"(d[20]),"+f"(d[21]),"+f"(d[22]),"+f"(d[23]),"+f"(d[24]),"+f"(d[25]),"+f"(d[26]),"+f"(d[27]),"+f"(d[28]),"+f"(d[29]),"+f"(d[30]),"+f"(d[31]),"+f"(d[32]),"+f"(d[33]),"+f"(d[34]),"+f"(d[35]),"+f"(d[36]),"+f"(d[37]),"+f"(d[38]),"+f"(d[39]),"+f"(d[40]),"+f"(d[41]),"+f"(d[42]),"+f"(d[43]),"+f"(d[44]),"+f"(d[45]),"+f"(d[46]),"+f"(d[47]) : "l"(da), "l"(db), "n"(SC));
}
template<int SC> __device__ __forceinline__ void wg_rs112(float (&d)[56], uint32_t a0, uint32_t a1, uint32_t a2, uint32_t a3, uint64_t db) {
  asm volatile("{\n.reg .pred p;\nsetp.ne.b32 p, %61, 0;\nwgmma.mma_async.sync.aligned.m64n112k16.f32.bf16.bf16 {%0,%1,%2,%3,%4,%5,%6,%7,%8,%9,%10,%11,%12,%13,%14,%15,%16,%17,%18,%19,%20,%21,%22,%23,%24,%25,%26,%27,%28,%29,%30,%31,%32,%33,%34,%35,%36,%37,%38,%39,%40,%41,%42,%43,%44,%45,%46,%47,%48,%49,%50,%51,%52,%53,%54,%55}, {%56,%57,%58,%59}, %60, p, 1, 1, 0;\n}\n"
    : "+f"(d[0]),"+f"(d[1]),"+f"(d[2]),"+f"(d[3]),"+f"(d[4]),"+f"(d[5]),"+f"(d[6]),"+f"(d[7]),"+f"(d[8]),"+f"(d[9]),"+f"(d[10]),"+f"(d[11]),"+f"(d[12]),"+f"(d[13]),"+f"(d[14]),"+f"(d[15]),"+f"(d[16]),"+f"(d[17]),"+f"(d[18]),"+f"(d[19]),"+f"(d[20]),"+f"(d[21]),"+f"(d[22]),"+f"(d[23]),"+f"(d[24]),"+f"(d[25]),"+f"(d[26]),"+f"(d[27]),"+f"(d[28]),"+f"(d[29]),"+f"(d[30]),"+f"(d[31]),"+f"(d[32]),"+f"(d[33]),"+f"(d[34]),"+f"(d[35]),"+f"(d[36]),"+f"(d[37]),"+f"(d[38]),"+f"(d[39]),"+f"(d[40]),"+f"(d[41]),"+f"(d[42]),"+f"(d[43]),"+f"(d[44]),"+f"(d[45]),"+f"(d[46]),"+f"(d[47]),"+f"(d[48]),"+f"(d[49]),"+f"(d[50]),"+f"(d[51]),"+f"(d[52]),"+f"(d[53]),"+f"(d[54]),"+f"(d[55]) : "r"(a0), "r"(a1), "r"(a2), "r"(a3), "l"(db), "n"(SC));
}
template<int SC> __device__ __forceinline__ void wg_sp48(float (&d)[24], uint32_t a0, uint32_t a1, uint32_t a2, uint32_t a3, uint64_t db, uint32_t meta) {
  asm volatile("{\n.reg .pred p;\nsetp.ne.b32 p, %30, 0;\nwgmma.mma_async.sp.sync.aligned.m64n48k32.f32.bf16.bf16 {%0,%1,%2,%3,%4,%5,%6,%7,%8,%9,%10,%11,%12,%13,%14,%15,%16,%17,%18,%19,%20,%21,%22,%23}, {%24,%25,%26,%27}, %28, %29, 0, p, 1, 1, 1;\n}\n"
    : "+f"(d[0]),"+f"(d[1]),"+f"(d[2]),"+f"(d[3]),"+f"(d[4]),"+f"(d[5]),"+f"(d[6]),"+f"(d[7]),"+f"(d[8]),"+f"(d[9]),"+f"(d[10]),"+f"(d[11]),"+f"(d[12]),"+f"(d[13]),"+f"(d[14]),"+f"(d[15]),"+f"(d[16]),"+f"(d[17]),"+f"(d[18]),"+f"(d[19]),"+f"(d[20]),"+f"(d[21]),"+f"(d[22]),"+f"(d[23]) : "r"(a0), "r"(a1), "r"(a2), "r"(a3), "l"(db), "r"(meta), "n"(SC));
}
template<int SC> __device__ __forceinline__ void wg_ss192(float (&d)[96], uint64_t da, uint64_t db) {
  asm volatile("{\n.reg .pred p;\nsetp.ne.b32 p, %98, 0;\nwgmma.mma_async.sync.aligned.m64n192k16.f32.bf16.bf16 {%0,%1,%2,%3,%4,%5,%6,%7,%8,%9,%10,%11,%12,%13,%14,%15,%16,%17,%18,%19,%20,%21,%22,%23,%24,%25,%26,%27,%28,%29,%30,%31,%32,%33,%34,%35,%36,%37,%38,%39,%40,%41,%42,%43,%44,%45,%46,%47,%48,%49,%50,%51,%52,%53,%54,%55,%56,%57,%58,%59,%60,%61,%62,%63,%64,%65,%66,%67,%68,%69,%70,%71,%72,%73,%74,%75,%76,%77,%78,%79,%80,%81,%82,%83,%84,%85,%86,%87,%88,%89,%90,%91,%92,%93,%94,%95}, %96, %97, p, 1, 1, 0, 1;\n}\n"
    : "+f"(d[0]),"+f"(d[1]),"+f"(d[2]),"+f"(d[3]),"+f"(d[4]),"+f"(d[5]),"+f"(d[6]),"+f"(d[7]),"+f"(d[8]),"+f"(d[9]),"+f"(d[10]),"+f"(d[11]),"+f"(d[12]),"+f"(d[13]),"+f"(d[14]),"+f"(d[15]),"+f"(d[16]),"+f"(d[17]),"+f"(d[18]),"+f"(d[19]),"+f"(d[20]),"+f"(d[21]),"+f"(d[22]),"+f"(d[23]),"+f"(d[24]),"+f"(d[25]),"+f"(d[26]),"+f"(d[27]),"+f"(d[28]),"+f"(d[29]),"+f"(d[30]),"+f"(d[31]),"+f"(d[32]),"+f"(d[33]),"+f"(d[34]),"+f"(d[35]),"+f"(d[36]),"+f"(d[37]),"+f"(d[38]),"+f"(d[39]),"+f"(d[40]),"+f"(d[41]),"+f"(d[42]),"+f"(d[43]),"+f"(d[44]),"+f"(d[45]),"+f"(d[46]),"+f"(d[47]),"+f"(d[48]),"+f"(d[49]),"+f"(d[50]),"+f"(d[51]),"+f"(d[52]),"+f"(d[53]),"+f"(d[54]),"+f"(d[55]),"+f"(d[56]),"+f"(d[57]),"+f"(d[58]),"+f"(d[59]),"+f"(d[60]),"+f"(d[61]),"+f"(d[62]),"+f"(d[63]),"+f"(d[64]),"+f"(d[65]),"+f"(d[66]),"+f"(d[67]),"+f"(d[68]),"+f"(d[69]),"+f"(d[70]),"+f"(d[71]),"+f"(d[72]),"+f"(d[73]),"+f"(d[74]),"+f"(d[75]),"+f"(d[76]),"+f"(d[77]),"+f"(d[78]),"+f"(d[79]),"+f"(d[80]),"+f"(d[81]),"+f"(d[82]),"+f"(d[83]),"+f"(d[84]),"+f"(d[85]),"+f"(d[86]),"+f"(d[87]),"+f"(d[88]),"+f"(d[89]),"+f"(d[90]),"+f"(d[91]),"+f"(d[92]),"+f"(d[93]),"+f"(d[94]),"+f"(d[95]) : "l"(da), "l"(db), "n"(SC));
}

constexpr uint32_t SBC = 1024;
constexpr int ROWB = 2 * 224 * 384;
constexpr int TB = 11;
constexpr int KS = 832;
constexpr int KSLOT = 22 * KS;
constexpr int SM_X1 = 0;
constexpr int SM_X2 = SM_X1 + 24576;
constexpr int SM_X0 = SM_X2 + 24576;
constexpr int SM_W = SM_X0 + 18432;
constexpr int SM_K = SM_W + 55296;
constexpr int SM_V = SM_K + 2 * KSLOT;
constexpr int SM_Q = SM_V + 22 * 1536;
constexpr int SM_O = SM_Q + 24576;
constexpr int SM_RPB = SM_O + 12288;
constexpr int SM_BAR = SM_RPB + 768;
constexpr int SM_A_TOTAL = SM_BAR + 256;
constexpr int SM_TWO = SM_X0 + 24576;
constexpr int SM_TST = SM_TWO + 36864;
enum { B_FULL = 0, B_EMPTY = 3, B_TIN = 6, B_TFREE = 9, B_WK = 11, B_WQ, B_WO, B_Q0, B_OTAIL, B_ODONE = B_OTAIL + 2, B_KFREE, B_VFREE, B_COUNT };
enum { N_KRDY = 4, N_QK0, N_QK1, N_VQ0, N_VQ1, N_PVISS };

#define PFM 2
#define SPL 4
#define RA 152
#define RG 184
__device__ int g_flags[TB * 56];

#define TR(role, it, k)
#define TRDECL
#define TRARG
#define TRPASS
#define TRDUMP
#define TRB(it, k)
#define TR2(blk, k)

struct GemmCtx {
  uint32_t bar;
  uint32_t kC, vC, qC;
  uint32_t kH, vH;
  bool hvalid;
};

template <int STRIDE> __device__ __forceinline__ void dump12(uint32_t a, const uint32_t (&r)[12]) {
#pragma unroll
  for (int j = 0; j < 3; j++) stsm4(a + j * 2 * STRIDE, r[4 * j], r[4 * j + 1], r[4 * j + 2], r[4 * j + 3]);
}
template <int N> __device__ __forceinline__ void pack12(uint32_t (&r)[12], const float (&d)[N], int off) {
#pragma unroll
  for (int j = 0; j < 12; j++) r[j] = pack2(d[off + 2 * j], d[off + 2 * j + 1]);
}
template <int XS, int K0, int K1> __device__ __forceinline__ void issue_core(float (&d)[72]) {
  constexpr uint64_t da = mkdesc(SBC + XS, 16, 1024, 1), db = mkdesc(SBC + SM_W, 6144, 256, 3);
  wg_fence();
  if (K0 == 0) wg_ss144<0>(d, da, db);
#pragma unroll
  for (int k = K0 ? K0 : 1; k < K1; k++) wg_ss144<1>(d, da + (k >> 2) * 512 + (k & 3) * 2, db + k * 32);
  wg_commit();
}
template <int K0, int K1> __device__ __forceinline__ void issue_halo(float (&d)[48]) {
  constexpr uint64_t da = mkdesc(SBC + SM_X0 - 2048, 16, 1024, 1), db = mkdesc(SBC + SM_W, 6144, 256, 3);
  wg_fence();
  if (K0 == 0) wg_ss96<0>(d, da, db);
#pragma unroll
  for (int k = K0 ? K0 : 1; k < K1; k++) wg_ss96<1>(d, da + (k >> 2) * 384 + (k & 3) * 2, db + k * 32);
  wg_commit();
}
template <int ST, int BYTES> __device__ __forceinline__ void release_stage(const GemmCtx& c, bool on) {
  asm volatile("{\n.reg .pred p, q;\n.reg .b32 ra;\nsetp.ne.b32 q, %2, 0;\nelect.sync _|p, 0xffffffff;\nand.pred p, p, q;\n"
               "mapa.shared::cluster.u32 ra, %1, %4;\n"
               "@p mbarrier.arrive.expect_tx.shared::cta.b64 _, [%0], %3;\n@p mbarrier.arrive.shared::cluster.b64 _, [ra];\n}"
               ::"r"(c.bar + (B_FULL + ST) * 8), "r"(c.bar + (B_EMPTY + ST) * 8), "r"((int)on), "n"(BYTES / 4), "n"(ST) : "memory");
}
__device__ __forceinline__ void load_w(const CUtensorMap* m, uint32_t dst, uint32_t bar, int col) {
  asm volatile("cp.async.bulk.tensor.2d.shared::cluster.global.mbarrier::complete_tx::bytes [%0], [%1, {%3,%4}], [%2];"
               ::"r"(dst), "l"(m), "r"(bar), "r"(col), "r"(0) : "memory");
}
template <int BYTES> __device__ __forceinline__ void send_o(uint32_t dst, uint32_t src, uint32_t bar, int cta) {
  asm volatile("{\n.reg .b32 rd, rb;\nmapa.shared::cluster.u32 rd, %0, %3;\nmapa.shared::cluster.u32 rb, %2, %3;\n"
               "cp.async.bulk.shared::cluster.shared::cta.mbarrier::complete_tx::bytes [rd], [%1], %4, [rb];\n}"
               ::"r"(dst), "r"(src), "r"(bar), "r"(cta), "n"(BYTES) : "memory");
}
__device__ __forceinline__ void tail_free(uint32_t bar) {
  uint32_t ln; asm volatile("mov.u32 %0, %%laneid;" : "=r"(ln));
  if (ln < 4) mbar_arrive_remote(bar, ln);
}
__device__ __forceinline__ void publish(uint32_t bar) {
  fence_async();
  __syncwarp();
  mbar_arrive_elect(bar);
}

template <bool FIRST, bool LAST>
__device__ __forceinline__ void gemm_iter(const GemmCtx& c, int b, uint32_t (&pk)[12], uint32_t (&pv)[12], uint32_t (&pq)[12], const CUtensorMap* mwo TRARG) {
  const uint32_t bar = c.bar;
  const uint32_t pa = b & 1;
  const bool w = b >= 0;
  const uint32_t ko = pa * KSLOT, vx = pa * 16, qx = pa * 128;
  float H[48], C[72];
  uint32_t hk[12], hv[12], pv2[12];
  TR(2, b, 0);
  if (FIRST) mbar_wait(bar + (B_FULL + 0) * 8, pa);
  if (w) nb_sync(N_QK1, 256);
  TR(2, b, 2);
  if (FIRST) TR(2, b - 1, 6);
  issue_halo<0, 8>(H);
  TR(2, b, 3);
  if (!FIRST) {
    if (w) mbar_wait(bar + B_KFREE * 8, pa);
    dump12<128>(c.kC + ko, pk);
  }
  issue_halo<8, 12>(H);
  TR(2, b, 4);
  if (!LAST) {
    mbar_wait(bar + (B_FULL + 2) * 8, pa);
    if (FIRST) mbar_wait(bar + B_WQ * 8, 0);
    TR(2, b, 13);
    if (FIRST) TR(2, b - 1, 7);
    issue_core<SM_X2, 0, 8>(C);
    TR(2, b, 5);
    if (!FIRST) { fence_async(); dump12<256>(c.qC ^ (qx ^ 192), pq); }
    wg_wait<1>(); pin(H);
    release_stage<0, 18432>(c, true);
  } else {
    dump12<256>(c.qC ^ (qx ^ 192), pq);
    fence_async();
    nb_arrive(N_VQ0, 288); nb_arrive(N_VQ1, 288);
    wg_wait<0>(); pin(H);
    tail_free(bar + (B_TFREE + 1) * 8);
    nb_sync(2, 128);
    if (!c.hvalid && elect_one()) {
      mbar_expect(bar + B_WO * 8, 36864);
      asm volatile("cp.async.bulk.tensor.3d.shared::cluster.global.mbarrier::complete_tx::bytes [%0], [%1, {%3,%4,%5}], [%2];"
                   ::"r"(bar - SM_BAR + SM_TWO), "l"(mwo), "r"(bar + B_WO * 8), "r"(0), "r"(0), "r"((blockIdx.x & 1) * 3) : "memory");
    }
    __syncwarp();
  }
  pack12(hk, H, 0);
  if (c.hvalid) dump12<128>(c.kH + ko, hk);
  pack12(hv, H, 24);
  if (!LAST) {
    issue_core<SM_X2, 8, 12>(C);
    if (w) { nb_arrive(N_VQ0, 288); nb_arrive(N_VQ1, 288); }
    else if (!FIRST) { __syncwarp(); mbar_arrive_elect(bar + B_Q0 * 8); }
    mbar_wait(bar + (B_FULL + 1) * 8, pa);
    TR(2, b, 6);
    wg_wait<0>(); pin(C);
    TR(2, b, 7);
    pack12(pk, C, 0);
    dump12<128>(c.kC + ko + 64, pk);
    release_stage<2, 24576>(c, b < 11);
    if (b == 11) tail_free(bar + B_TFREE * 8);
    pack12(pv2, C, 24);
    pack12(pq, C, 48);
    TR(2, b, 8);
    issue_core<SM_X1, 0, SPL>(C);
    if (w) nb_sync(N_PVISS, 384);
    issue_core<SM_X1, SPL, 8>(C);
    TR(2, b, 9);
  }
  if (!FIRST) fence_async();
  TR(2, b, 14);
  if (!LAST) issue_core<SM_X1, 8, 12>(C);
  if (!FIRST) nb_arrive(N_KRDY, 256);
  TR(2, b, 1);
  if (!LAST) mbar_wait(bar + (B_FULL + 0) * 8, pa ^ 1);
  if (w) mbar_wait(bar + B_VFREE * 8, pa);
  TR(2, b, 10);
  if (!FIRST) dump12<128>(c.vC ^ vx, pv);
  if (!LAST) dump12<256>(c.qC ^ qx, pq);
  if (c.hvalid) dump12<128>(c.vH ^ vx, hv);
  if (LAST) { fence_async(); nb_arrive(N_VQ0, 256); nb_arrive(N_VQ1, 256); return; }
  dump12<128>((c.vC ^ vx ^ 16) + 768, pv2);
  TR(2, b, 11);
  wg_wait<0>(); pin(C);
  TR(2, b, 12);
  release_stage<1, 24576>(c, b < 11);
  pack12(pk, C, 0);
  pack12(pv, C, 24);
  pack12(pq, C, 48);
}

__device__ __forceinline__ float fold(float a, float b, float t, int useb) {
  float r;
  asm("{\n.reg .pred p;\nsetp.ne.b32 p, %4, 0;\nfma.rn.f32 %0, %1, 0f3E553B95, %3;\n@p fma.rn.f32 %0, %2, 0f3E553B95, %3;\n}"
      : "=&f"(r) : "f"(a), "f"(b), "f"(t), "r"(useb));
  return r;
}
template <int U, int L>
__device__ __forceinline__ void softmax_tile(const float (&SA)[56], const float (&SB)[56], const float (&T)[16], int b0, int b1,
                                             uint32_t (&P)[28], float (&sx)[8]) {
  float lu[14], ll[14];
#pragma unroll
  for (int j = 0; j < 7; j++) {
    constexpr int sh = U == L ? 2 : 0;
    const float tu0 = T[2 * j + sh], tu1 = T[2 * j + 1 + sh], tl0 = T[2 * j], tl1 = T[2 * j + 1];
    lu[2 * j]     = fold(SA[4 * (U + j)],     SB[4 * (U + j)],     tu0, b0);
    ll[2 * j]     = fold(SA[4 * (L + j) + 2], SB[4 * (L + j) + 2], tl0, b0);
    lu[2 * j + 1] = fold(SA[4 * (U + j) + 1], SB[4 * (U + j) + 1], tu1, b1);
    ll[2 * j + 1] = fold(SA[4 * (L + j) + 3], SB[4 * (L + j) + 3], tl1, b1);
  }
  float mu = lu[0], ml = ll[0], mu2 = lu[1], ml2 = ll[1];
#pragma unroll
  for (int j = 1; j < 7; j++) { mu = fmaxf(mu, lu[2 * j]); mu2 = fmaxf(mu2, lu[2 * j + 1]); ml = fmaxf(ml, ll[2 * j]); ml2 = fmaxf(ml2, ll[2 * j + 1]); }
  mu = fmaxf(mu, mu2); ml = fmaxf(ml, ml2);
  { const float a1 = __shfl_xor_sync(0xffffffffu, mu, 1), a2 = __shfl_xor_sync(0xffffffffu, mu, 2), a3 = __shfl_xor_sync(0xffffffffu, mu, 3);
    const float c1 = __shfl_xor_sync(0xffffffffu, ml, 1), c2 = __shfl_xor_sync(0xffffffffu, ml, 2), c3 = __shfl_xor_sync(0xffffffffu, ml, 3);
    mu = fmaxf(fmaxf(mu, a1), fmaxf(a2, a3)); ml = fmaxf(fmaxf(ml, c1), fmaxf(c2, c3)); }
  float su = 0.f, sl = 0.f;
#pragma unroll
  for (int c = 0; c < 14; c++) {
    const int iu = (c >> 1) * 4 + (c & 1) * 2;
    if (c >= U && c < U + 7) {
      float e0 = ex2(lu[2 * (c - U)] - mu), e1 = ex2(lu[2 * (c - U) + 1] - mu);
      su = c == U ? e0 + e1 : (su + e0) + e1; P[iu] = pack2(e0, e1);
    } else P[iu] = 0u;
    if (c >= L && c < L + 7) {
      float e0 = ex2(ll[2 * (c - L)] - ml), e1 = ex2(ll[2 * (c - L) + 1] - ml);
      sl = c == L ? e0 + e1 : (sl + e0) + e1; P[iu + 1] = pack2(e0, e1);
    } else P[iu + 1] = 0u;
  }
  sx[0] = su; sx[4] = sl;
#pragma unroll
  for (int k = 1; k < 4; k++) { sx[k] = __shfl_xor_sync(0xffffffffu, su, k); sx[4 + k] = __shfl_xor_sync(0xffffffffu, sl, k); }
}

struct Maps { CUtensorMap xc, xh, w, os, wo, ot; };

__global__ void __cluster_dims__(4, 1, 1) __launch_bounds__(512, 1)
na_attn_kernel(const __grid_constant__ Maps mp, const __nv_bfloat16* __restrict__ x, const __nv_bfloat16* __restrict__ wqkv, const __nv_bfloat16* __restrict__ rpb) {
  extern __shared__ __align__(1024) uint8_t smem_raw[];
  const uint32_t sb = smem_u32(smem_raw);
  if ((sb & 0x3FFFF) != SBC) return;
  const uint32_t bar = sb + SM_BAR;
  TR2(blockIdx.x, 0);
  const int tid = threadIdx.x, lane = tid & 31;
  const int warp = __shfl_sync(0xffffffffu, tid >> 5, 0);
  const int head = blockIdx.x & 3, cl = blockIdx.x >> 2;
  const int par = cl / 7, strip = cl - par * 7, ph = par >> 1, pw = par & 1;

  uint4 wv[2];
  const int va = head == 1;
  const uint32_t wdst = sb + SM_W + (3 + va + ((tid >> 1) & 1)) * 6144 + (tid >> 2) * 32 + ((tid ^ (tid >> 4)) & 1) * 16;
  if (warp == 15) {
    const int col = min(max(strip * 16 - 3 + min(lane, 21), 0), 111);
    const uint8_t* p = reinterpret_cast<const uint8_t*>(x) + (size_t)head * ROWB + (ph * 112 + col) * 768 + pw * 384;
#pragma unroll
    for (int i = 0; i < 3; i++) asm volatile("prefetch.global.L2 [%0];" ::"l"(p + i * 128));
  }
  if (warp >= 12 && elect_one()) {
    if (warp == 12) {
      mbar_init(bar + B_WK * 8, 1);
#pragma unroll
      for (int i = 0; i < 3; i++) load_w(&mp.w, sb + SM_W + i * 6144, bar + B_WK * 8, 192 + head * 48 + i * 16);
      mbar_expect(bar + B_WK * 8, 24576);
    } else if (warp == 13) {
#pragma unroll
      for (int i = 0; i < B_WK; i++) mbar_init(bar + i * 8, i < B_EMPTY ? 4 : (i < B_TIN ? 16 : (i < B_TFREE ? 1 : 16)));
    } else if (warp == 14) {
#pragma unroll
      for (int i = B_WQ; i < B_COUNT; i++) mbar_init(bar + i * 8, i < B_Q0 ? 1 : (i < B_ODONE ? 4 : 8));
    } else asm volatile("prefetch.tensormap [%0];" ::"l"(head ? &mp.xc : &mp.xh) : "memory");
    asm volatile("fence.mbarrier_init.release.cluster;" ::: "memory");
  }
  __syncwarp();
  asm volatile("barrier.cluster.arrive.relaxed.aligned;" ::: "memory");
  if (warp < 12) {
#pragma unroll
    for (int i = 0; i < 2; i++) wv[i] = __ldg(reinterpret_cast<const uint4*>(wqkv + ((tid >> 2) + i * 96) * 576 + 384 + head * 48 + va * 16 + (tid & 3) * 8));
  }

  if (warp >= 12) {
    asm volatile("setmaxnreg.dec.sync.aligned.u32 24;");
    asm volatile("griddepcontrol.launch_dependents;");
    const int cc = ph * 112 + (head ? strip * 16 : (strip == 0 ? 16 : (strip == 6 ? 74 : strip * 16 - 3)));
    const int sd = strip == 0 ? -1 : (strip == 6 ? 1 : 0);
    const int r0 = head == 0 ? -4 : (head == 1 ? 4 : 0);
    asm volatile("barrier.cluster.wait.aligned;" ::: "memory");
    if (warp == 12) {
      const uint32_t fb = bar + (B_FULL + head) * 8, eb = bar + (B_EMPTY + head) * 8;
      const uint32_t dst = sb + (head == 0 ? SM_X0 : (head == 1 ? SM_X1 : SM_X2));
      const int nl = head == 0 ? 15 : (head == 3 ? 1 : 14);
#pragma unroll 1
      for (int n = 0; n < nl; n++) {
        if (n) mbar_wait(eb, (n - 1) & 1);
        if (elect_one()) {
          if (head == 0) {
            asm volatile("cp.async.bulk.tensor.5d.shared::cluster.global.mbarrier::complete_tx::bytes.multicast::cluster [%0], [%1, {%3,%4,%5,%6,%7}], [%2], %8;"
                         ::"r"(dst), "l"(&mp.xh), "r"(fb), "r"(0), "r"(8 * n + r0), "r"(cc), "r"(sd), "r"(pw * 3), "h"((uint16_t)15) : "memory");
            if (n + 1 < nl) asm volatile("cp.async.bulk.prefetch.tensor.5d.L2.global [%0, {%1,%2,%3,%4,%5}];" ::"l"(&mp.xh), "r"(0), "r"(8 * n + 8 + r0), "r"(cc), "r"(sd), "r"(pw * 3) : "memory");
          } else if (head < 3) {
            asm volatile("cp.async.bulk.tensor.4d.shared::cluster.global.mbarrier::complete_tx::bytes.multicast::cluster [%0], [%1, {%3,%4,%5,%6}], [%2], %7;"
                         ::"r"(dst), "l"(&mp.xc), "r"(fb), "r"(0), "r"(8 * n + r0), "r"(cc), "r"(pw * 3), "h"((uint16_t)15) : "memory");
          }
          if (n == 0) {
            load_w(&mp.w, sb + SM_W + (va ? 3 : 5) * 6144, bar + B_WK * 8, 384 + head * 48 + (va ? 0 : 32));
#pragma unroll
            for (int i = 0; i < 3; i++) load_w(&mp.w, sb + SM_W + (6 + i) * 6144, bar + B_WQ * 8, head * 48 + i * 16);
            mbar_expect(bar + B_WQ * 8, 18432);
            mbar_expect(bar + B_TIN * 8, 24576); mbar_expect(bar + (B_TIN + 1) * 8, 24576); mbar_expect(bar + (B_TIN + 2) * 8, 24576);
          }
          if (head && n + 1 < nl) asm volatile("cp.async.bulk.prefetch.tensor.4d.L2.global [%0, {%1,%2,%3,%4}];" ::"l"(&mp.xc), "r"(0), "r"(8 * n + 8 + r0), "r"(cc), "r"(pw * 3) : "memory");
        }
        __syncwarp();
      }
    }
    if (warp == 14) {
      int* flag = g_flags + cl * 2;
      nb_arrive(N_VQ0, 288); nb_arrive(N_VQ1, 288);
#pragma unroll 1
      for (int b = 0; b < TB; b++) {
        mbar_wait(bar + B_ODONE * 8, b & 1);
        if (lane == 0) {
          asm volatile("cp.async.bulk.tensor.3d.global.shared::cta.bulk_group [%0, {%2,%3,%4}], [%1];"
                       ::"l"(&mp.os), "r"(sb + SM_O), "r"(pw * 192), "r"(8 * b + 2 * head), "r"(ph * 112 + strip * 16) : "memory");
          asm volatile("cp.async.bulk.commit_group;\ncp.async.bulk.wait_group 0;" ::: "memory");
        }
        __syncwarp();
        nb_arrive(N_VQ0, 288); nb_arrive(N_VQ1, 288);
        if (lane == 0)
          asm volatile("fence.proxy.async.global;\nfence.acq_rel.gpu;\nred.relaxed.gpu.global.add.s32 [%0], 1;\nred.relaxed.gpu.global.add.s32 [%0+4], 1;"
                       ::"l"(flag + b * 56) : "memory");
        __syncwarp();
      }
    } else if (warp & 1) {
      const int j = (warp >> 1) & 1;
#pragma unroll 1
      for (int i = 0; i < 2; i++) {
        mbar_wait(bar + (B_OTAIL + j) * 8, i);
        if (i == 0) nb_arrive(N_VQ0 + j, 288);
        mbar_wait(bar + (B_TFREE + i) * 8, 0);
        if (elect_one()) {
#pragma unroll 1
          for (int d = 0; d < 8; d++) {
            const int dst = (d + head) & 3, pc = d >> 2;
            send_o<1536>(sb + (i ? SM_X1 : SM_X2) + head * 6144 + j * 3072 + pc * 1536,
                         sb + (i ? SM_Q : SM_O) + (4 * j + (dst & 2) + pc) * (i ? 3072 : 1536), bar + (B_TIN + i) * 8, dst);
          }
        }
        __syncwarp();
      }
    }
    cluster_sync();
  } else if (warp >= 8) {
    TRDECL;
    TR(2, -3, 0);
    asm volatile("setmaxnreg.inc.sync.aligned.u32 %0;" ::"n"(RG));
    TR(2, -3, 1);
    GemmCtx c;
    c.bar = bar;
    const int gw = warp - 8, tk = gw * 16 + (lane & 15), hi = lane >> 4;
    { const int col = tk >> 2, i = tk & 3;
      c.kC = sb + SM_K + (col + 3) * KS + hi * 128 + i * 16;
      c.vC = sb + SM_V + (col + 3) * 1536 + hi * 128 + (2 * i + ((col + 3) & 1)) * 16;
      c.qC = sb + SM_Q + col * 1536 + hi * 256 + (col & 1) * 64 + i * 16; }
    { const int ci = (tk >> 3) - 2, kc = ci < 3 ? ci : ci + 16, i = tk & 7; c.hvalid = gw > 0;
      c.kH = sb + SM_K + kc * KS + hi * 128 + i * 16;
      c.vH = sb + SM_V + kc * 1536 + hi * 128 + (i >> 2) * 768 + (2 * (i & 3) + ((kc ^ (i >> 2)) & 1)) * 16; }
    asm volatile("barrier.cluster.wait.aligned;" ::: "memory");
    TR(2, -3, 2);
    if (elect_one()) { mbar_expect(bar + B_FULL * 8, 4608); mbar_expect(bar + (B_FULL + 1) * 8, 6144); mbar_expect(bar + (B_FULL + 2) * 8, 6144); }
    __syncwarp();
    sts128(wdst, wv[0]); sts128(wdst + 3072, wv[1]);
    fence_async();
    TR(2, -3, 3);
    asm volatile("bar.sync 1, 384;" ::: "memory");
    TR(2, -3, 4);
    mbar_wait(bar + B_WK * 8, 0);
    TR(2, -3, 5);
    uint32_t pk[12], pv[12], pq[12];
    gemm_iter<true, false>(c, -2, pk, pv, pq, &mp.wo TRPASS);
    TR2(blockIdx.x, 4);
#pragma unroll 1
    for (int b = -1; b < 12; b++) gemm_iter<false, false>(c, b, pk, pv, pq, &mp.wo TRPASS);
    TR2(blockIdx.x, 6);
    gemm_iter<false, true>(c, 12, pk, pv, pq, &mp.wo TRPASS);
    TR(2, 13, 0);
    mbar_wait(bar + B_WO * 8, 0);
    TR(2, 13, 1);
    const uint32_t st = sb + SM_TST + gw * 3072;
    const uint32_t sta = st + (lane & 15) * 64 + ((hi ^ ((lane >> 1) & 3)) * 16);
#pragma unroll 1
    for (int i = 0; i < 3; i++) {
      constexpr uint64_t db = mkdesc(SBC + SM_TWO, 12288, 512, 2);
      const uint64_t da = mkdesc(SBC, 128, 768, 0) + (i ^ (i < 2)) * (24576 / 16);
      float D[48];
      mbar_wait(bar + (B_TIN + i) * 8, 0);
      if (i == 2) asm volatile("barrier.cluster.arrive.relaxed.aligned;" ::: "memory");
      else nb_sync(i ? N_PVISS : N_QK1, i ? 384 : 256);
      TR(2, 13 - i, 2); TR(2, 12 + i, 5); TR(2, 11 + i, 9);
      wg_fence();
      wg_ss96<0>(D, da, db);
#pragma unroll
      for (int k = 1; k < 12; k++) wg_ss96<1>(D, da + (k / 3) * 384 + (k % 3) * 16, db + k * 64);
      wg_commit();
      if (lane == 0) asm volatile("cp.async.bulk.wait_group.read 0;" ::: "memory");
      __syncwarp();
      wg_wait<0>(); pin(D);
      TR(2, 13 - i, 3); TR(2, 12 + i, 6); TR(2, 11 + i, 10);
#pragma unroll
      for (int q = 0; q < 6; q++)
        stsm4((sta ^ ((q & 1) * 32)) + (q >> 1) * 1024,
              pack2(D[8 * q], D[8 * q + 1]), pack2(D[8 * q + 2], D[8 * q + 3]), pack2(D[8 * q + 4], D[8 * q + 5]), pack2(D[8 * q + 6], D[8 * q + 7]));
      fence_async();
      __syncwarp();
      if (lane == 0) {
        asm volatile("cp.async.bulk.tensor.4d.global.shared::cta.bulk_group [%0, {%2,%3,%4,%5}], [%1];"
                     ::"l"(&mp.ot), "r"(st), "r"(0), "r"(8 * (TB + i)), "r"(ph * 112 + strip * 16 + 8 * (gw >> 1) + 4 * (head >> 1) + 2 * (gw & 1)), "r"(pw * 6 + (head & 1) * 3) : "memory");
        asm volatile("cp.async.bulk.commit_group;" ::: "memory");
      }
      TR(2, 13 - i, 4); TR(2, 12 + i, 7); TR(2, 11 + i, 11);
    }
    if (lane == 0) asm volatile("cp.async.bulk.wait_group.read 0;" ::: "memory");
    __syncwarp();
    TR(2, 13, 8);
    TR2(blockIdx.x, 2);
    TRDUMP;
    asm volatile("barrier.cluster.wait.aligned;" ::: "memory");
  } else {
    asm volatile("setmaxnreg.inc.sync.aligned.u32 %0;" ::"n"(RA));
    float rv = -INFINITY;
    if (tid < 169) rv = __bfloat162float(rpb[head * 169 + tid]) * 1.4426950408889634f;
    if (tid < 192) {
      const int kc = (tid & 15) + 3, wc = (tid >> 4) % 6;
      sts128(tid < 96 ? sb + SM_K + kc * KS + wc * 128 + 48 : sb + SM_V + kc * 1536 + wc * 128 + (6 + (kc & 1)) * 16, make_uint4(0, 0, 0, 0));
    }
    sts128(wdst, wv[0]); sts128(wdst + 3072, wv[1]);
    fence_async();
    asm volatile("bar.arrive 1, 384;" ::: "memory");
    if (tid < 182) asm volatile("st.shared.f32 [%0], %1;" ::"r"(sb + SM_RPB + tid * 4), "f"(rv) : "memory");
    const int j = warp >> 2, w = warp & 3;
    int variant = w;
    if (strip == 0 && j == 0 && w < 2) variant = 4;
    if (strip == 6 && j == 1 && w >= 2) variant = 5;
    const uint32_t qa = sb + SM_Q + (8 * j + 2 * w + ((lane >> 3) & 1)) * 1536 + (lane >> 4) * 256 + (((lane & 7) * 16) ^ (((lane >> 3) & 1) * 64));
    uint32_t oa = sb + SM_O + j * 6144 + (2 * w + ((lane >> 3) & 1)) * 768 + (lane >> 4) * 128 + (lane & 7) * 16;
    const uint64_t dK = mkdesc(SBC + SM_K, 128, KS, 0) + j * (8 * KS / 16);
    const uint64_t dV = mkdesc(SBC + SM_V, 768, 128, 0) + j * (8 * 1536 / 16);
    asm volatile("barrier.cluster.wait.aligned;" ::: "memory");
    asm volatile("bar.sync 3, 256;" ::: "memory");
    float T[16];
    TRDECL;
    int b0 = 0, b1 = 0;
    uint32_t meta = 0;
    uint32_t q[12];
    mbar_wait(bar + B_Q0 * 8, 0);
#pragma unroll
    for (int k = 0; k < 3; k++) ldsm4(qa + k * 512, q[4 * k], q[4 * k + 1], q[4 * k + 2], q[4 * k + 3]);
#pragma unroll 1
    for (int b = 0; b < 14; b++) {
      const uint32_t pa = b & 1;
      float SA[56], SB[56];
      const uint64_t dA = dK + pa * (KSLOT >> 4), dB = dK + (pa ^ 1) * (KSLOT >> 4);
      TR(0, b, 0);
      nb_sync(N_KRDY + j, 256);
      TR(0, b, 1);
      TR(0, b - 1, 9);
      wg_fence();
      wg_rs112<0>(SA, q[0], q[1], q[2], q[3], dA);
      wg_rs112<0>(SB, q[0], q[1], q[2], q[3], dB);
      wg_rs112<1>(SA, q[4], q[5], q[6], q[7], dA + 16);
      wg_rs112<1>(SB, q[4], q[5], q[6], q[7], dB + 16);
      wg_rs112<1>(SA, q[8], q[9], q[10], q[11], dA + 32);
      wg_rs112<1>(SB, q[8], q[9], q[10], q[11], dB + 32);
      wg_commit();
      nb_arrive(N_QK0 + j, 256);
      TR(0, b, 2);
      if (b <= 1 || b == 13) {
        uint32_t ln; asm volatile("mov.u32 %0, %%laneid;" : "=r"(ln));
        const int g = ln >> 2, t = ln & 3;
        const int sw = b == 0 ? max(g + 1, 4) : (b == 13 ? min(g + 1, 5) : g + 1);
        const int i0 = 2 * t, i1 = 2 * t + 1;
        b0 = i0 <= sw - 2; b1 = i1 <= sw - 2;
        const uint32_t tb = sb + SM_RPB + (variant < 4 ? 3 : variant + 1 - 2 * w) * 4;
        const uint32_t ra0 = tb + (i0 == sw - 1 ? 13 : i0 + 8 * b0 - g + 2) * 52;
        const uint32_t ra1 = tb + (i1 == sw - 1 ? 13 : i1 + 8 * b1 - g + 2) * 52;
#pragma unroll
        for (int jj = 0; jj < 8; jj++) { T[2 * jj] = lds_f32(ra0 + jj * 4); T[2 * jj + 1] = lds_f32(ra1 + jj * 4); }
        meta = ((0x5555u & ((1u << (2 * (sw - 1))) - 1)) ^ 0xDD88u ^ (((t ^ b) & 1) ? 0x5555u : 0u)) * 0x10001u;
      } else meta ^= 0x55555555u;
      if (b >= 12) oa += b == 12 ? warp * 1536 - (SM_O - SM_Q) : 1536;
      wg_wait<0>(); pin(SA); pin(SB);
      mbar_arrive_elect(bar + B_KFREE * 8);
      TR(0, b, 3);
      TR(0, b - 1, 10);
      uint32_t P[28];
      float sx[8];
      switch (variant) {
        case 0: softmax_tile<0, 1>(SA, SB, T, b0, b1, P, sx); break;
        case 1: softmax_tile<2, 3>(SA, SB, T, b0, b1, P, sx); break;
        case 2: softmax_tile<4, 5>(SA, SB, T, b0, b1, P, sx); break;
        case 3: softmax_tile<6, 7>(SA, SB, T, b0, b1, P, sx); break;
        case 4: softmax_tile<3, 3>(SA, SB, T, b0, b1, P, sx); break;
        default: softmax_tile<4, 4>(SA, SB, T, b0, b1, P, sx); break;
      }
      float O[24];
      TR(0, b, 4);
      nb_sync(N_VQ0 + j, b == 13 ? 256 : 288);
      TR(0, b, 5);
#pragma unroll
      for (int k = 0; k < 3; k++) ldsm4(qa + (pa ^ 1) * 128 + k * 512, q[4 * k], q[4 * k + 1], q[4 * k + 2], q[4 * k + 3]);
      wg_fence();
      wg_sp48<0>(O, P[0], P[1], P[2], P[3], dV, meta);
#pragma unroll
      for (int s = 1; s < 7; s++) wg_sp48<1>(O, P[4 * s], P[4 * s + 1], P[4 * s + 2], P[4 * s + 3], dV + s * 192, meta);
      wg_commit();
      if (b != 12) nb_arrive(N_PVISS, 384);
      TR(0, b, 6);
      wg_wait<0>(); pin(O);
      mbar_arrive_elect(bar + B_VFREE * 8);
      TR(0, b, 7);
      float ru, rl;
      asm("rcp.approx.ftz.f32 %0, %1;" : "=f"(ru) : "f"(((fmaf(O[0], 0.f, sx[0]) + sx[1]) + sx[2]) + sx[3]));
      asm("rcp.approx.ftz.f32 %0, %1;" : "=f"(rl) : "f"(((fmaf(O[2], 0.f, sx[4]) + sx[5]) + sx[6]) + sx[7]));
#pragma unroll
      for (int i = 0; i < 3; i++)
        stsm4(oa + i * 256, pack2(O[8 * i] * ru, O[8 * i + 1] * ru), pack2(O[8 * i + 2] * rl, O[8 * i + 3] * rl),
              pack2(O[8 * i + 4] * ru, O[8 * i + 5] * ru), pack2(O[8 * i + 6] * rl, O[8 * i + 7] * rl));
      if (b < 13) publish(bar + (b < TB ? B_ODONE : B_OTAIL + j) * 8);
      else {
        fence_async();
        mbar_wait(bar + (B_TFREE + 1) * 8, 0);
        __syncwarp();
        if (elect_one()) {
#pragma unroll
          for (int d = 0; d < 2; d++)
            send_o<1536>(sb + SM_X0 + head * 6144 + (2 * j + (w & 1)) * 1536, sb + SM_Q + warp * 3072 + 1536, bar + (B_TIN + 2) * 8, (w & 2) + (d ^ (head & 1)));
        }
        __syncwarp();
      }
      TR(0, b, 8);
    }
    TRDUMP;
    cluster_sync();
  }
}

constexpr int NSTB = 6;
constexpr int NTB = TB * 56;
constexpr int SM_B_IN = 0;
constexpr int SM_B_W = SM_B_IN + NSTB * 24576;
constexpr int SM_B_BAR = SM_B_W + 73728;
constexpr int SM_B_TOTAL = SM_B_BAR + 128;
struct MapsB { CUtensorMap oi, oo, wo; };

__global__ void __launch_bounds__(480, 1)
na_proj_kernel(const __grid_constant__ MapsB mp) {
  extern __shared__ __align__(1024) uint8_t smem_raw[];
  const uint32_t sb = smem_u32(smem_raw);
  if ((sb & 0x3FFFF) != SBC) return;
  const uint32_t bar = sb + SM_B_BAR;
  const int tid = threadIdx.x, lane = tid & 31;
  const int warp = __shfl_sync(0xffffffffu, tid >> 5, 0);
  TR2(132 + blockIdx.x, 0);
  TRB(47, 0);
  if (warp == 12 && elect_one()) {
#pragma unroll
    for (int i = 0; i <= 2 * NSTB; i++) mbar_init(bar + i * 8, i < NSTB || i == 2 * NSTB ? 1 : 4);
    mbar_expect(bar + 2 * NSTB * 8, 73728);
#pragma unroll
    for (int i = 0; i < 2; i++)
      asm volatile("cp.async.bulk.tensor.3d.shared::cluster.global.mbarrier::complete_tx::bytes [%0], [%1, {%3,%4,%5}], [%2];"
                   ::"r"(sb + SM_B_W + i * 36864), "l"(&mp.wo), "r"(bar + 2 * NSTB * 8), "r"(0), "r"(0), "r"(i * 3) : "memory");
  }
  __syncthreads();
  const int step = gridDim.x;
  if (warp >= 12) {
    const int wg = warp - 12;
    int use = 0;
#pragma unroll 1
    for (int n = blockIdx.x + wg * step; n < NTB; n += 3 * step, use++) {
      const int b = n / 56, rem = n - b * 56, par = rem / 14, sg = wg + 3 * (use & 1);
      int v; uint32_t spin = 0;
      do { asm volatile("ld.acquire.gpu.global.s32 %0, [%1];" : "=r"(v) : "l"(g_flags + n) : "memory"); } while (v < 4 && ++spin < SPIN_LIMIT);
      TRB(use * 3 + wg, 0);
      asm volatile("fence.proxy.async.global;" ::: "memory");
      if (use >= 2) mbar_wait(bar + (NSTB + sg) * 8, ((use >> 1) - 1) & 1);
      TRB(use * 3 + wg, 1);
      if (elect_one()) {
        mbar_expect(bar + sg * 8, 24576);
        asm volatile("cp.async.bulk.tensor.3d.shared::cluster.global.mbarrier::complete_tx::bytes [%0], [%1, {%3,%4,%5}], [%2];"
                     ::"r"(sb + SM_B_IN + sg * 24576), "l"(&mp.oi), "r"(bar + sg * 8), "r"((par & 1) * 192), "r"(8 * b), "r"((par >> 1) * 112 + (rem - par * 14) * 8) : "memory");
        g_flags[n] = 0;
      }
      __syncwarp();
    }
  } else {
    const int wg = warp >> 2, w = warp & 3;
    constexpr uint64_t db = mkdesc(SBC + SM_B_W, 12288, 512, 2);
    const uint32_t sta0 = sb + SM_B_IN + w * 6144 + (lane & 15) * 128 + (((lane >> 4) ^ (lane & 7)) * 16);
    mbar_wait(bar + 2 * NSTB * 8, 0);
    TRB(47, 1);
    int use = 0;
#pragma unroll 1
    for (int n = blockIdx.x + wg * step; n < NTB; n += 3 * step, use++) {
      const int b = n / 56, rem = n - b * 56, par = rem / 14, sg = wg + 3 * (use & 1);
      const uint64_t da = mkdesc(SBC + SM_B_IN, 128, 3072, 0) + sg * (24576 / 16);
      float D[96];
      mbar_wait(bar + sg * 8, (use >> 1) & 1);
      if (use | wg) nb_sync(4 + wg, 256);
      TRB(use * 3 + wg, 3);
      wg_fence();
      wg_ss192<0>(D, da, db);
#pragma unroll
      for (int k = 1; k < 12; k++) wg_ss192<1>(D, da + k * 16, db + k * 64);
      wg_commit();
      if (n + step < NTB) nb_arrive(wg == 2 ? 4 : 5 + wg, 256);
      TRB(use * 3 + wg, 4);
      if (use && lane == 0) {
        asm volatile("cp.async.bulk.wait_group.read 0;" ::: "memory");
        mbar_arrive(bar + (NSTB + wg + 3 * (~use & 1)) * 8);
      }
      __syncwarp();
      wg_wait<0>(); pin(D);
      nb_sync(1 + wg, 128);
      TRB(use * 3 + wg, 5);
      const uint32_t sta = sta0 + sg * 24576;
#pragma unroll
      for (int q = 0; q < 12; q++)
        stsm4((sta ^ ((q & 3) * 32)) + (q >> 2) * 2048,
              pack2(D[8 * q], D[8 * q + 1]), pack2(D[8 * q + 2], D[8 * q + 3]), pack2(D[8 * q + 4], D[8 * q + 5]), pack2(D[8 * q + 6], D[8 * q + 7]));
      fence_async();
      __syncwarp();
      if (lane == 0) {
        asm volatile("cp.async.bulk.tensor.4d.global.shared::cta.bulk_group [%0, {%2,%3,%4,%5}], [%1];"
                     ::"l"(&mp.oo), "r"(sb + SM_B_IN + sg * 24576 + w * 6144), "r"(0), "r"(8 * b), "r"((par >> 1) * 112 + (rem - par * 14) * 8 + 2 * w), "r"((par & 1) * 3) : "memory");
        asm volatile("cp.async.bulk.commit_group;" ::: "memory");
      }
      __syncwarp();
      TRB(use * 3 + wg, 6);
    }
    if (lane == 0) asm volatile("cp.async.bulk.wait_group 0;" ::: "memory");
    TR2(132 + blockIdx.x, 2);
  }
}

typedef CUresult (*EncodeFn)(CUtensorMap*, CUtensorMapDataType, cuuint32_t, void*, const cuuint64_t*, const cuuint64_t*, const cuuint32_t*,
                             const cuuint32_t*, CUtensorMapInterleave, CUtensorMapSwizzle, CUtensorMapL2promotion, CUtensorMapFloatOOBfill);
static EncodeFn g_enc = nullptr;
static void make_map(CUtensorMap* m, const void* p, int rank, const cuuint64_t* dim, const cuuint64_t* str, const cuuint32_t* box, CUtensorMapSwizzle sw) {
  const cuuint32_t ones[5] = {1, 1, 1, 1, 1};
  g_enc(m, CU_TENSOR_MAP_DATA_TYPE_BFLOAT16, rank, (void*)p, dim, str, box, ones, CU_TENSOR_MAP_INTERLEAVE_NONE, sw,
        CU_TENSOR_MAP_L2_PROMOTION_L2_128B, CU_TENSOR_MAP_FLOAT_OOB_FILL_NONE);
}

extern "C" void kernel_launch(void* const* d_in, const int* in_sizes, int n_in, void* d_out, int out_size) {
  const __nv_bfloat16* x = (const __nv_bfloat16*)d_in[0];
  const __nv_bfloat16* wqkv = (const __nv_bfloat16*)d_in[1];
  const __nv_bfloat16* wo = (const __nv_bfloat16*)d_in[2];
  const __nv_bfloat16* rpb = (const __nv_bfloat16*)d_in[3];

  if (!g_enc) {
    void* fn = nullptr; cudaDriverEntryPointQueryResult qr;
    cudaGetDriverEntryPoint("cuTensorMapEncodeTiled", &fn, cudaEnableDefault, &qr);
    g_enc = (EncodeFn)fn;
    cudaFuncSetAttribute(na_attn_kernel, cudaFuncAttributeMaxDynamicSharedMemorySize, SM_A_TOTAL);
    cudaFuncSetAttribute(na_proj_kernel, cudaFuncAttributeMaxDynamicSharedMemorySize, SM_B_TOTAL);
  }
  Maps ma; MapsB mb;
  { cuuint64_t dim[4] = {64, 112, 224, 6}, str[3] = {(cuuint64_t)ROWB, 768, 128};
    cuuint32_t box[4] = {64, 4, 16, 3}, boxo[4] = {64, 8, 2, 3};
    make_map(&ma.xc, x, 4, dim, str, box, CU_TENSOR_MAP_SWIZZLE_128B);
    make_map(&mb.oo, d_out, 4, dim, str, boxo, CU_TENSOR_MAP_SWIZZLE_128B); }
  { cuuint64_t dim[5] = {64, 112, 224, 2, 6}, str[4] = {(cuuint64_t)ROWB, 768, 19 * 768, 128};
    cuuint32_t box[5] = {64, 8, 3, 2, 3};
    make_map(&ma.xh, x, 5, dim, str, box, CU_TENSOR_MAP_SWIZZLE_128B); }
  { cuuint64_t dim[3] = {384, 112, 224}, str[2] = {(cuuint64_t)ROWB, 768};
    cuuint32_t box[3] = {192, 8, 8}, boxs[3] = {192, 2, 16};
    make_map(&mb.oi, d_out, 3, dim, str, box, CU_TENSOR_MAP_SWIZZLE_NONE);
    make_map(&ma.os, d_out, 3, dim, str, boxs, CU_TENSOR_MAP_SWIZZLE_NONE); }
  { cuuint64_t dim[4] = {32, 112, 224, 12}, str[3] = {(cuuint64_t)ROWB, 768, 64};
    cuuint32_t box[4] = {32, 8, 2, 3};
    make_map(&ma.ot, d_out, 4, dim, str, box, CU_TENSOR_MAP_SWIZZLE_64B); }
  { cuuint64_t dim[2] = {576, 192}, str[1] = {1152};
    cuuint32_t box[2] = {16, 192};
    make_map(&ma.w, wqkv, 2, dim, str, box, CU_TENSOR_MAP_SWIZZLE_32B); }
  { cuuint64_t dim[3] = {32, 192, 6}, str[2] = {384, 64};
    cuuint32_t box[3] = {32, 192, 3};
    make_map(&ma.wo, wo, 3, dim, str, box, CU_TENSOR_MAP_SWIZZLE_64B);
    mb.wo = ma.wo; }
  na_attn_kernel<<<112, 512, SM_A_TOTAL>>>(ma, x, wqkv, rpb);
  cudaLaunchConfig_t cfg = {};
  cfg.gridDim = dim3(20); cfg.blockDim = dim3(480); cfg.dynamicSmemBytes = SM_B_TOTAL; cfg.stream = cudaStreamPerThread;
  cudaLaunchAttribute at[1];
  at[0].id = cudaLaunchAttributeProgrammaticStreamSerialization; at[0].val.programmaticStreamSerializationAllowed = 1;
  cfg.attrs = at; cfg.numAttrs = 1;
  cudaLaunchKernelEx(&cfg, na_proj_kernel, mb);
}
```

```cpp
#include <cuda_runtime.h>
#include <cuda_bf16.h>
#include <cuda.h>
#include <stdint.h>

#define SPIN_LIMIT (1u << 18)

__device__ __forceinline__ uint32_t smem_u32(const void* p) { return (uint32_t)__cvta_generic_to_shared(p); }
__device__ __forceinline__ void wg_fence() { asm volatile("wgmma.fence.sync.aligned;" ::: "memory"); }
__device__ __forceinline__ void wg_commit() { asm volatile("wgmma.commit_group.sync.aligned;" ::: "memory"); }
template <int N> __device__ __forceinline__ void wg_wait() { asm volatile("wgmma.wait_group.sync.aligned %0;" ::"n"(N) : "memory"); }
template <int N> __device__ __forceinline__ void pin(float (&d)[N]) {
#pragma unroll
  for (int i = 0; i < N; i++) asm volatile("" : "+f"(d[i])::"memory");
}
__host__ __device__ constexpr uint64_t mkdesc(uint32_t addr, uint32_t lbo, uint32_t sbo, uint32_t sw) {
  return (uint64_t)((addr & 0x3FFFF) >> 4) | ((uint64_t)(lbo >> 4) << 16) | ((uint64_t)(sbo >> 4) << 32) | ((uint64_t)sw << 62);
}
__device__ __forceinline__ void mbar_init(uint32_t bar, uint32_t cnt) { asm volatile("mbarrier.init.shared::cta.b64 [%0], %1;" ::"r"(bar), "r"(cnt) : "memory"); }
__device__ __forceinline__ void mbar_arrive(uint32_t bar) { asm volatile("mbarrier.arrive.shared::cta.b64 _, [%0];" ::"r"(bar) : "memory"); }
__device__ __forceinline__ bool elect_one() {
  uint32_t r; asm volatile("{\n.reg .pred p;\nelect.sync _|p, 0xffffffff;\nselp.u32 %0, 1, 0, p;\n}" : "=r"(r)); return r;
}
__device__ __forceinline__ void mbar_arrive_elect(uint32_t bar) {
  asm volatile("{\n.reg .pred p;\nelect.sync _|p, 0xffffffff;\n@p mbarrier.arrive.shared::cta.b64 _, [%0];\n}" ::"r"(bar) : "memory");
}
__device__ __forceinline__ void mbar_expect(uint32_t bar, uint32_t bytes) { asm volatile("mbarrier.arrive.expect_tx.shared::cta.b64 _, [%0], %1;" ::"r"(bar), "r"(bytes) : "memory"); }
__device__ __forceinline__ void mbar_arrive_remote(uint32_t bar, uint32_t cta) {
  asm volatile("{\n.reg .b32 ra;\nmapa.shared::cluster.u32 ra, %0, %1;\nmbarrier.arrive.relaxed.cluster.shared::cluster.b64 _, [ra];\n}" ::"r"(bar), "r"(cta) : "memory");
}
__device__ __forceinline__ void mbar_wait(uint32_t bar, uint32_t parity) {
  asm volatile("{\n.reg .pred p;\n.reg .b32 n;\nmov.b32 n, 0;\nWL:\nmbarrier.try_wait.parity.shared::cta.b64 p, [%0], %1;\n@p bra WD;\n"
               "add.u32 n, n, 1;\nsetp.lt.u32 p, n, 65536;\n@p bra WL;\nWD:\n}" ::"r"(bar), "r"(parity) : "memory");
}
__device__ __forceinline__ void nb_sync(int id, int n) { asm volatile("bar.sync %0, %1;" ::"r"(id), "r"(n) : "memory"); }
__device__ __forceinline__ void nb_arrive(int id, int n) { asm volatile("bar.arrive %0, %1;" ::"r"(id), "r"(n) : "memory"); }
__device__ __forceinline__ void fence_async() { asm volatile("fence.proxy.async.shared::cta;" ::: "memory"); }
__device__ __forceinline__ void cluster_sync() {
  asm volatile("barrier.cluster.arrive.relaxed.aligned;\nbarrier.cluster.wait.aligned;" ::: "memory");
}
__device__ __forceinline__ uint32_t pack2(float lo, float hi) {
  uint32_t r; asm("cvt.rn.bf16x2.f32 %0, %1, %2;" : "=r"(r) : "f"(hi), "f"(lo)); return r;
}
__device__ __forceinline__ void stsm4(uint32_t a, uint32_t r0, uint32_t r1, uint32_t r2, uint32_t r3) {
  asm volatile("stmatrix.sync.aligned.m8n8.x4.shared.b16 [%0], {%1,%2,%3,%4};" ::"r"(a), "r"(r0), "r"(r1), "r"(r2), "r"(r3) : "memory");
}
__device__ __forceinline__ void ldsm4(uint32_t a, uint32_t& r0, uint32_t& r1, uint32_t& r2, uint32_t& r3) {
  asm volatile("ldmatrix.sync.aligned.m8n8.x4.shared.b16 {%0,%1,%2,%3}, [%4];" : "=r"(r0), "=r"(r1), "=r"(r2), "=r"(r3) : "r"(a) : "memory");
}
__device__ __forceinline__ void sts128(uint32_t a, uint4 v) {
  asm volatile("st.shared.v4.b32 [%0], {%1,%2,%3,%4};" ::"r"(a), "r"(v.x), "r"(v.y), "r"(v.z), "r"(v.w) : "memory");
}
__device__ __forceinline__ float lds_f32(uint32_t a) { float v; asm volatile("ld.shared.f32 %0, [%1];" : "=f"(v) : "r"(a)); return v; }
__device__ __forceinline__ float ex2(float x) { float y; asm("ex2.approx.ftz.f32 %0, %1;" : "=f"(y) : "f"(x)); return y; }

template<int SC> __device__ __forceinline__ void wg_ss144(float (&d)[72], uint64_t da, uint64_t db) {
  asm volatile("{\n.reg .pred p;\nsetp.ne.b32 p, %74, 0;\nwgmma.mma_async.sync.aligned.m64n144k16.f32.bf16.bf16 {%0,%1,%2,%3,%4,%5,%6,%7,%8,%9,%10,%11,%12,%13,%14,%15,%16,%17,%18,%19,%20,%21,%22,%23,%24,%25,%26,%27,%28,%29,%30,%31,%32,%33,%34,%35,%36,%37,%38,%39,%40,%41,%42,%43,%44,%45,%46,%47,%48,%49,%50,%51,%52,%53,%54,%55,%56,%57,%58,%59,%60,%61,%62,%63,%64,%65,%66,%67,%68,%69,%70,%71}, %72, %73, p, 1, 1, 0, 1;\n}\n"
    : "+f"(d[0]),"+f"(d[1]),"+f"(d[2]),"+f"(d[3]),"+f"(d[4]),"+f"(d[5]),"+f"(d[6]),"+f"(d[7]),"+f"(d[8]),"+f"(d[9]),"+f"(d[10]),"+f"(d[11]),"+f"(d[12]),"+f"(d[13]),"+f"(d[14]),"+f"(d[15]),"+f"(d[16]),"+f"(d[17]),"+f"(d[18]),"+f"(d[19]),"+f"(d[20]),"+f"(d[21]),"+f"(d[22]),"+f"(d[23]),"+f"(d[24]),"+f"(d[25]),"+f"(d[26]),"+f"(d[27]),"+f"(d[28]),"+f"(d[29]),"+f"(d[30]),"+f"(d[31]),"+f"(d[32]),"+f"(d[33]),"+f"(d[34]),"+f"(d[35]),"+f"(d[36]),"+f"(d[37]),"+f"(d[38]),"+f"(d[39]),"+f"(d[40]),"+f"(d[41]),"+f"(d[42]),"+f"(d[43]),"+f"(d[44]),"+f"(d[45]),"+f"(d[46]),"+f"(d[47]),"+f"(d[48]),"+f"(d[49]),"+f"(d[50]),"+f"(d[51]),"+f"(d[52]),"+f"(d[53]),"+f"(d[54]),"+f"(d[55]),"+f"(d[56]),"+f"(d[57]),"+f"(d[58]),"+f"(d[59]),"+f"(d[60]),"+f"(d[61]),"+f"(d[62]),"+f"(d[63]),"+f"(d[64]),"+f"(d[65]),"+f"(d[66]),"+f"(d[67]),"+f"(d[68]),"+f"(d[69]),"+f"(d[70]),"+f"(d[71]) : "l"(da), "l"(db), "n"(SC));
}
template<int SC> __device__ __forceinline__ void wg_ss96(float (&d)[48], uint64_t da, uint64_t db) {
  asm volatile("{\n.reg .pred p;\nsetp.ne.b32 p, %50, 0;\nwgmma.mma_async.sync.aligned.m64n96k16.f32.bf16.bf16 {%0,%1,%2,%3,%4,%5,%6,%7,%8,%9,%10,%11,%12,%13,%14,%15,%16,%17,%18,%19,%20,%21,%22,%23,%24,%25,%26,%27,%28,%29,%30,%31,%32,%33,%34,%35,%36,%37,%38,%39,%40,%41,%42,%43,%44,%45,%46,%47}, %48, %49, p, 1, 1, 0, 1;\n}\n"
    : "+f"(d[0]),"+f"(d[1]),"+f"(d[2]),"+f"(d[3]),"+f"(d[4]),"+f"(d[5]),"+f"(d[6]),"+f"(d[7]),"+f"(d[8]),"+f"(d[9]),"+f"(d[10]),"+f"(d[11]),"+f"(d[12]),"+f"(d[13]),"+f"(d[14]),"+f"(d[15]),"+f"(d[16]),"+f"(d[17]),"+f"(d[18]),"+f"(d[19]),"+f"(d[20]),"+f"(d[21]),"+f"(d[22]),"+f"(d[23]),"+f"(d[24]),"+f"(d[25]),"+f"(d[26]),"+f"(d[27]),"+f"(d[28]),"+f"(d[29]),"+f"(d[30]),"+f"(d[31]),"+f"(d[32]),"+f"(d[33]),"+f"(d[34]),"+f"(d[35]),"+f"(d[36]),"+f"(d[37]),"+f"(d[38]),"+f"(d[39]),"+f"(d[40]),"+f"(d[41]),"+f"(d[42]),"+f"(d[43]),"+f"(d[44]),"+f"(d[45]),"+f"(d[46]),"+f"(d[47]) : "l"(da), "l"(db), "n"(SC));
}
template<int SC> __device__ __forceinline__ void wg_rs112(float (&d)[56], uint32_t a0, uint32_t a1, uint32_t a2, uint32_t a3, uint64_t db) {
  asm volatile("{\n.reg .pred p;\nsetp.ne.b32 p, %61, 0;\nwgmma.mma_async.sync.aligned.m64n112k16.f32.bf16.bf16 {%0,%1,%2,%3,%4,%5,%6,%7,%8,%9,%10,%11,%12,%13,%14,%15,%16,%17,%18,%19,%20,%21,%22,%23,%24,%25,%26,%27,%28,%29,%30,%31,%32,%33,%34,%35,%36,%37,%38,%39,%40,%41,%42,%43,%44,%45,%46,%47,%48,%49,%50,%51,%52,%53,%54,%55}, {%56,%57,%58,%59}, %60, p, 1, 1, 0;\n}\n"
    : "+f"(d[0]),"+f"(d[1]),"+f"(d[2]),"+f"(d[3]),"+f"(d[4]),"+f"(d[5]),"+f"(d[6]),"+f"(d[7]),"+f"(d[8]),"+f"(d[9]),"+f"(d[10]),"+f"(d[11]),"+f"(d[12]),"+f"(d[13]),"+f"(d[14]),"+f"(d[15]),"+f"(d[16]),"+f"(d[17]),"+f"(d[18]),"+f"(d[19]),"+f"(d[20]),"+f"(d[21]),"+f"(d[22]),"+f"(d[23]),"+f"(d[24]),"+f"(d[25]),"+f"(d[26]),"+f"(d[27]),"+f"(d[28]),"+f"(d[29]),"+f"(d[30]),"+f"(d[31]),"+f"(d[32]),"+f"(d[33]),"+f"(d[34]),"+f"(d[35]),"+f"(d[36]),"+f"(d[37]),"+f"(d[38]),"+f"(d[39]),"+f"(d[40]),"+f"(d[41]),"+f"(d[42]),"+f"(d[43]),"+f"(d[44]),"+f"(d[45]),"+f"(d[46]),"+f"(d[47]),"+f"(d[48]),"+f"(d[49]),"+f"(d[50]),"+f"(d[51]),"+f"(d[52]),"+f"(d[53]),"+f"(d[54]),"+f"(d[55]) : "r"(a0), "r"(a1), "r"(a2), "r"(a3), "l"(db), "n"(SC));
}
template<int SC> __device__ __forceinline__ void wg_sp48(float (&d)[24], uint32_t a0, uint32_t a1, uint32_t a2, uint32_t a3, uint64_t db, uint32_t meta) {
  asm volatile("{\n.reg .pred p;\nsetp.ne.b32 p, %30, 0;\nwgmma.mma_async.sp.sync.aligned.m64n48k32.f32.bf16.bf16 {%0,%1,%2,%3,%4,%5,%6,%7,%8,%9,%10,%11,%12,%13,%14,%15,%16,%17,%18,%19,%20,%21,%22,%23}, {%24,%25,%26,%27}, %28, %29, 0, p, 1, 1, 1;\n}\n"
    : "+f"(d[0]),"+f"(d[1]),"+f"(d[2]),"+f"(d[3]),"+f"(d[4]),"+f"(d[5]),"+f"(d[6]),"+f"(d[7]),"+f"(d[8]),"+f"(d[9]),"+f"(d[10]),"+f"(d[11]),"+f"(d[12]),"+f"(d[13]),"+f"(d[14]),"+f"(d[15]),"+f"(d[16]),"+f"(d[17]),"+f"(d[18]),"+f"(d[19]),"+f"(d[20]),"+f"(d[21]),"+f"(d[22]),"+f"(d[23]) : "r"(a0), "r"(a1), "r"(a2), "r"(a3), "l"(db), "r"(meta), "n"(SC));
}
template<int SC> __device__ __forceinline__ void wg_ss192(float (&d)[96], uint64_t da, uint64_t db) {
  asm volatile("{\n.reg .pred p;\nsetp.ne.b32 p, %98, 0;\nwgmma.mma_async.sync.aligned.m64n192k16.f32.bf16.bf16 {%0,%1,%2,%3,%4,%5,%6,%7,%8,%9,%10,%11,%12,%13,%14,%15,%16,%17,%18,%19,%20,%21,%22,%23,%24,%25,%26,%27,%28,%29,%30,%31,%32,%33,%34,%35,%36,%37,%38,%39,%40,%41,%42,%43,%44,%45,%46,%47,%48,%49,%50,%51,%52,%53,%54,%55,%56,%57,%58,%59,%60,%61,%62,%63,%64,%65,%66,%67,%68,%69,%70,%71,%72,%73,%74,%75,%76,%77,%78,%79,%80,%81,%82,%83,%84,%85,%86,%87,%88,%89,%90,%91,%92,%93,%94,%95}, %96, %97, p, 1, 1, 0, 1;\n}\n"
    : "+f"(d[0]),"+f"(d[1]),"+f"(d[2]),"+f"(d[3]),"+f"(d[4]),"+f"(d[5]),"+f"(d[6]),"+f"(d[7]),"+f"(d[8]),"+f"(d[9]),"+f"(d[10]),"+f"(d[11]),"+f"(d[12]),"+f"(d[13]),"+f"(d[14]),"+f"(d[15]),"+f"(d[16]),"+f"(d[17]),"+f"(d[18]),"+f"(d[19]),"+f"(d[20]),"+f"(d[21]),"+f"(d[22]),"+f"(d[23]),"+f"(d[24]),"+f"(d[25]),"+f"(d[26]),"+f"(d[27]),"+f"(d[28]),"+f"(d[29]),"+f"(d[30]),"+f"(d[31]),"+f"(d[32]),"+f"(d[33]),"+f"(d[34]),"+f"(d[35]),"+f"(d[36]),"+f"(d[37]),"+f"(d[38]),"+f"(d[39]),"+f"(d[40]),"+f"(d[41]),"+f"(d[42]),"+f"(d[43]),"+f"(d[44]),"+f"(d[45]),"+f"(d[46]),"+f"(d[47]),"+f"(d[48]),"+f"(d[49]),"+f"(d[50]),"+f"(d[51]),"+f"(d[52]),"+f"(d[53]),"+f"(d[54]),"+f"(d[55]),"+f"(d[56]),"+f"(d[57]),"+f"(d[58]),"+f"(d[59]),"+f"(d[60]),"+f"(d[61]),"+f"(d[62]),"+f"(d[63]),"+f"(d[64]),"+f"(d[65]),"+f"(d[66]),"+f"(d[67]),"+f"(d[68]),"+f"(d[69]),"+f"(d[70]),"+f"(d[71]),"+f"(d[72]),"+f"(d[73]),"+f"(d[74]),"+f"(d[75]),"+f"(d[76]),"+f"(d[77]),"+f"(d[78]),"+f"(d[79]),"+f"(d[80]),"+f"(d[81]),"+f"(d[82]),"+f"(d[83]),"+f"(d[84]),"+f"(d[85]),"+f"(d[86]),"+f"(d[87]),"+f"(d[88]),"+f"(d[89]),"+f"(d[90]),"+f"(d[91]),"+f"(d[92]),"+f"(d[93]),"+f"(d[94]),"+f"(d[95]) : "l"(da), "l"(db), "n"(SC));
}

constexpr uint32_t SBC = 1024;
constexpr int ROWB = 2 * 224 * 384;
constexpr int TB = 11;
constexpr int KS = 832;
constexpr int KSLOT = 22 * KS;
constexpr int SM_X1 = 0;
constexpr int SM_X2 = SM_X1 + 24576;
constexpr int SM_X0 = SM_X2 + 24576;
constexpr int SM_W = SM_X0 + 18432;
constexpr int SM_K = SM_W + 55296;
constexpr int SM_V = SM_K + 2 * KSLOT;
constexpr int SM_Q = SM_V + 22 * 1536;
constexpr int SM_O = SM_Q + 24576;
constexpr int SM_RPB = SM_O + 12288;
constexpr int SM_BAR = SM_RPB + 768;
constexpr int SM_A_TOTAL = SM_BAR + 256;
constexpr int SM_TWO = SM_X0 + 24576;
constexpr int SM_TST = SM_TWO + 36864;
enum { B_FULL = 0, B_EMPTY = 3, B_TIN = 6, B_TFREE = 9, B_WK = 11, B_WQ, B_WO, B_Q0, B_OTAIL, B_ODONE = B_OTAIL + 2, B_KFREE, B_VFREE, B_COUNT };
enum { N_KRDY = 4, N_QK0, N_QK1, N_VQ0, N_VQ1, N_PVISS };

#define NL 2
#define SPL 4
#define RA 152
#define RG 184
__device__ int g_flags[TB * 56];

#define TR(role, it, k)
#define TRDECL
#define TRARG
#define TRPASS
#define TRDUMP
#define TRB(it, k)
#define TR2(blk, k)

struct GemmCtx {
  uint32_t bar;
  uint32_t kC, vC, qC;
  uint32_t kH, vH;
  bool hvalid;
};

template <int STRIDE> __device__ __forceinline__ void dump12(uint32_t a, const uint32_t (&r)[12]) {
#pragma unroll
  for (int j = 0; j < 3; j++) stsm4(a + j * 2 * STRIDE, r[4 * j], r[4 * j + 1], r[4 * j + 2], r[4 * j + 3]);
}
template <int N> __device__ __forceinline__ void pack12(uint32_t (&r)[12], const float (&d)[N], int off) {
#pragma unroll
  for (int j = 0; j < 12; j++) r[j] = pack2(d[off + 2 * j], d[off + 2 * j + 1]);
}
template <int XS, int K0, int K1> __device__ __forceinline__ void issue_core(float (&d)[72]) {
  constexpr uint64_t da = mkdesc(SBC + XS, 16, 1024, 1), db = mkdesc(SBC + SM_W, 6144, 256, 3);
  wg_fence();
  if (K0 == 0) wg_ss144<0>(d, da, db);
#pragma unroll
  for (int k = K0 ? K0 : 1; k < K1; k++) wg_ss144<1>(d, da + (k >> 2) * 512 + (k & 3) * 2, db + k * 32);
  wg_commit();
}
template <int K0, int K1> __device__ __forceinline__ void issue_halo(float (&d)[48]) {
  constexpr uint64_t da = mkdesc(SBC + SM_X0 - 2048, 16, 1024, 1), db = mkdesc(SBC + SM_W, 6144, 256, 3);
  wg_fence();
  if (K0 == 0) wg_ss96<0>(d, da, db);
#pragma unroll
  for (int k = K0 ? K0 : 1; k < K1; k++) wg_ss96<1>(d, da + (k >> 2) * 384 + (k & 3) * 2, db + k * 32);
  wg_commit();
}
template <int ST, int BYTES> __device__ __forceinline__ void release_stage(const GemmCtx& c, bool on) {
  asm volatile("{\n.reg .pred p, q;\n.reg .b32 ra;\nsetp.ne.b32 q, %2, 0;\nelect.sync _|p, 0xffffffff;\nand.pred p, p, q;\n"
               "mapa.shared::cluster.u32 ra, %1, %4;\n"
               "@p mbarrier.arrive.expect_tx.shared::cta.b64 _, [%0], %3;\n@p mbarrier.arrive.shared::cluster.b64 _, [ra];\n}"
               ::"r"(c.bar + (B_FULL + ST) * 8), "r"(c.bar + (B_EMPTY + ST) * 8), "r"((int)on), "n"(BYTES / 4), "n"(ST) : "memory");
}
__device__ __forceinline__ void load_w(const CUtensorMap* m, uint32_t dst, uint32_t bar, int col) {
  asm volatile("cp.async.bulk.tensor.2d.shared::cluster.global.mbarrier::complete_tx::bytes [%0], [%1, {%3,%4}], [%2];"
               ::"r"(dst), "l"(m), "r"(bar), "r"(col), "r"(0) : "memory");
}
template <int BYTES> __device__ __forceinline__ void send_o(uint32_t dst, uint32_t src, uint32_t bar, int cta) {
  asm volatile("{\n.reg .b32 rd, rb;\nmapa.shared::cluster.u32 rd, %0, %3;\nmapa.shared::cluster.u32 rb, %2, %3;\n"
               "cp.async.bulk.shared::cluster.shared::cta.mbarrier::complete_tx::bytes [rd], [%1], %4, [rb];\n}"
               ::"r"(dst), "r"(src), "r"(bar), "r"(cta), "n"(BYTES) : "memory");
}
__device__ __forceinline__ void tail_free(uint32_t bar) {
  uint32_t ln; asm volatile("mov.u32 %0, %%laneid;" : "=r"(ln));
  if (ln < 4) mbar_arrive_remote(bar, ln);
}
__device__ __forceinline__ void publish(uint32_t bar) {
  fence_async();
  __syncwarp();
  mbar_arrive_elect(bar);
}

template <bool FIRST, bool LAST>
__device__ __forceinline__ void gemm_iter(const GemmCtx& c, int b, uint32_t (&pk)[12], uint32_t (&pv)[12], uint32_t (&pq)[12], const CUtensorMap* mwo TRARG) {
  const uint32_t bar = c.bar;
  const uint32_t pa = b & 1;
  const bool w = b >= 0;
  const uint32_t ko = pa * KSLOT, vx = pa * 16, qx = pa * 128;
  float H[48], C[72];
  uint32_t hk[12], hv[12], pv2[12];
  TR(2, b, 0);
  if (FIRST) mbar_wait(bar + (B_FULL + 0) * 8, pa);
  if (w) nb_sync(N_QK1, 256);
  TR(2, b, 2);
  if (FIRST) TR(2, b - 1, 6);
  issue_halo<0, 8>(H);
  TR(2, b, 3);
  if (!FIRST) {
    if (w) mbar_wait(bar + B_KFREE * 8, pa);
    dump12<128>(c.kC + ko, pk);
  }
  issue_halo<8, 12>(H);
  TR(2, b, 4);
  if (!LAST) {
    mbar_wait(bar + (B_FULL + 2) * 8, pa);
    if (FIRST && NL == 2) mbar_wait(bar + B_WQ * 8, 0);
    TR(2, b, 13);
    if (FIRST) TR(2, b - 1, 7);
    issue_core<SM_X2, 0, 8>(C);
    TR(2, b, 5);
    if (!FIRST) { fence_async(); dump12<256>(c.qC ^ (qx ^ 192), pq); }
    wg_wait<1>(); pin(H);
    release_stage<0, 18432>(c, true);
  } else {
    dump12<256>(c.qC ^ (qx ^ 192), pq);
    fence_async();
    nb_arrive(N_VQ0, 288); nb_arrive(N_VQ1, 288);
    wg_wait<0>(); pin(H);
    tail_free(bar + (B_TFREE + 1) * 8);
    nb_sync(2, 128);
    if (!c.hvalid && elect_one()) {
      mbar_expect(bar + B_WO * 8, 36864);
      asm volatile("cp.async.bulk.tensor.3d.shared::cluster.global.mbarrier::complete_tx::bytes [%0], [%1, {%3,%4,%5}], [%2];"
                   ::"r"(bar - SM_BAR + SM_TWO), "l"(mwo), "r"(bar + B_WO * 8), "r"(0), "r"(0), "r"((blockIdx.x & 1) * 3) : "memory");
    }
    __syncwarp();
  }
  pack12(hk, H, 0);
  if (c.hvalid) dump12<128>(c.kH + ko, hk);
  pack12(hv, H, 24);
  if (!LAST) {
    issue_core<SM_X2, 8, 12>(C);
    if (w) { nb_arrive(N_VQ0, 288); nb_arrive(N_VQ1, 288); }
    else if (!FIRST) { __syncwarp(); mbar_arrive_elect(bar + B_Q0 * 8); }
    mbar_wait(bar + (B_FULL + 1) * 8, pa);
    TR(2, b, 6);
    wg_wait<0>(); pin(C);
    TR(2, b, 7);
    pack12(pk, C, 0);
    dump12<128>(c.kC + ko + 64, pk);
    release_stage<2, 24576>(c, b < 11);
    if (b == 11) tail_free(bar + B_TFREE * 8);
    pack12(pv2, C, 24);
    pack12(pq, C, 48);
    TR(2, b, 8);
    issue_core<SM_X1, 0, SPL>(C);
    if (w) nb_sync(N_PVISS, 384);
    issue_core<SM_X1, SPL, 8>(C);
    TR(2, b, 9);
  }
  if (!FIRST) fence_async();
  TR(2, b, 14);
  if (!LAST) issue_core<SM_X1, 8, 12>(C);
  if (!FIRST) nb_arrive(N_KRDY, 256);
  TR(2, b, 1);
  if (!LAST) mbar_wait(bar + (B_FULL + 0) * 8, pa ^ 1);
  if (w) mbar_wait(bar + B_VFREE * 8, pa);
  TR(2, b, 10);
  if (!FIRST) dump12<128>(c.vC ^ vx, pv);
  if (!LAST) dump12<256>(c.qC ^ qx, pq);
  if (c.hvalid) dump12<128>(c.vH ^ vx, hv);
  if (LAST) { fence_async(); nb_arrive(N_VQ0, 256); nb_arrive(N_VQ1, 256); return; }
  dump12<128>((c.vC ^ vx ^ 16) + 768, pv2);
  TR(2, b, 11);
  wg_wait<0>(); pin(C);
  TR(2, b, 12);
  release_stage<1, 24576>(c, b < 11);
  pack12(pk, C, 0);
  pack12(pv, C, 24);
  pack12(pq, C, 48);
}

__device__ __forceinline__ float fold(float a, float b, float t, int useb) {
  float r;
  asm("{\n.reg .pred p;\nsetp.ne.b32 p, %4, 0;\nfma.rn.f32 %0, %1, 0f3E553B95, %3;\n@p fma.rn.f32 %0, %2, 0f3E553B95, %3;\n}"
      : "=&f"(r) : "f"(a), "f"(b), "f"(t), "r"(useb));
  return r;
}
template <int U, int L>
__device__ __forceinline__ void softmax_tile(const float (&SA)[56], const float (&SB)[56], const float (&T)[16], int b0, int b1,
                                             uint32_t (&P)[28], float (&sx)[8]) {
  float lu[14], ll[14];
#pragma unroll
  for (int j = 0; j < 7; j++) {
    constexpr int sh = U == L ? 2 : 0;
    const float tu0 = T[2 * j + sh], tu1 = T[2 * j + 1 + sh], tl0 = T[2 * j], tl1 = T[2 * j + 1];
    lu[2 * j]     = fold(SA[4 * (U + j)],     SB[4 * (U + j)],     tu0, b0);
    ll[2 * j]     = fold(SA[4 * (L + j) + 2], SB[4 * (L + j) + 2], tl0, b0);
    lu[2 * j + 1] = fold(SA[4 * (U + j) + 1], SB[4 * (U + j) + 1], tu1, b1);
    ll[2 * j + 1] = fold(SA[4 * (L + j) + 3], SB[4 * (L + j) + 3], tl1, b1);
  }
  float mu = lu[0], ml = ll[0], mu2 = lu[1], ml2 = ll[1];
#pragma unroll
  for (int j = 1; j < 7; j++) { mu = fmaxf(mu, lu[2 * j]); mu2 = fmaxf(mu2, lu[2 * j + 1]); ml = fmaxf(ml, ll[2 * j]); ml2 = fmaxf(ml2, ll[2 * j + 1]); }
  mu = fmaxf(mu, mu2); ml = fmaxf(ml, ml2);
  { const float a1 = __shfl_xor_sync(0xffffffffu, mu, 1), a2 = __shfl_xor_sync(0xffffffffu, mu, 2), a3 = __shfl_xor_sync(0xffffffffu, mu, 3);
    const float c1 = __shfl_xor_sync(0xffffffffu, ml, 1), c2 = __shfl_xor_sync(0xffffffffu, ml, 2), c3 = __shfl_xor_sync(0xffffffffu, ml, 3);
    mu = fmaxf(fmaxf(mu, a1), fmaxf(a2, a3)); ml = fmaxf(fmaxf(ml, c1), fmaxf(c2, c3)); }
  float su = 0.f, sl = 0.f;
#pragma unroll
  for (int c = 0; c < 14; c++) {
    const int iu = (c >> 1) * 4 + (c & 1) * 2;
    if (c >= U && c < U + 7) {
      float e0 = ex2(lu[2 * (c - U)] - mu), e1 = ex2(lu[2 * (c - U) + 1] - mu);
      su = c == U ? e0 + e1 : (su + e0) + e1; P[iu] = pack2(e0, e1);
    } else P[iu] = 0u;
    if (c >= L && c < L + 7) {
      float e0 = ex2(ll[2 * (c - L)] - ml), e1 = ex2(ll[2 * (c - L) + 1] - ml);
      sl = c == L ? e0 + e1 : (sl + e0) + e1; P[iu + 1] = pack2(e0, e1);
    } else P[iu + 1] = 0u;
  }
  sx[0] = su; sx[4] = sl;
#pragma unroll
  for (int k = 1; k < 4; k++) { sx[k] = __shfl_xor_sync(0xffffffffu, su, k); sx[4 + k] = __shfl_xor_sync(0xffffffffu, sl, k); }
}

struct Maps { CUtensorMap xc, xh, w, os, wo, ot; };

__global__ void __cluster_dims__(4, 1, 1) __launch_bounds__(512, 1)
na_attn_kernel(const __grid_constant__ Maps mp, const __nv_bfloat16* __restrict__ x, const __nv_bfloat16* __restrict__ wqkv, const __nv_bfloat16* __restrict__ rpb) {
  extern __shared__ __align__(1024) uint8_t smem_raw[];
  const uint32_t sb = smem_u32(smem_raw);
  if ((sb & 0x3FFFF) != SBC) return;
  const uint32_t bar = sb + SM_BAR;
  TR2(blockIdx.x, 0);
  const int tid = threadIdx.x, lane = tid & 31;
  const int warp = __shfl_sync(0xffffffffu, tid >> 5, 0);
  const int head = blockIdx.x & 3, cl = blockIdx.x >> 2;
  const int par = cl / 7, strip = cl - par * 7, ph = par >> 1, pw = par & 1;

  uint4 wv[2 * NL];
  const int va = head == 1;
  const uint32_t wdst = sb + SM_W + (va + ((tid >> 1) & 1)) * 6144 + (tid >> 2) * 32 + ((tid ^ (tid >> 4)) & 1) * 16;
  if (warp == 15) {
    const int col = min(max(strip * 16 - 3 + min(lane, 21), 0), 111);
    const uint8_t* p = reinterpret_cast<const uint8_t*>(x) + (size_t)head * ROWB + (ph * 112 + col) * 768 + pw * 384;
#pragma unroll
    for (int i = 0; i < 3; i++) asm volatile("prefetch.global.L2 [%0];" ::"l"(p + i * 128));
  }
  if (warp >= 12 && elect_one()) {
    if (warp == 12) {
      mbar_init(bar + B_WK * 8, 1);
#pragma unroll
      for (int i = 0; i < NL; i++) load_w(&mp.w, sb + SM_W + (3 * i + 2 - 2 * va) * 6144, bar + B_WK * 8, ((i + 1) % 3) * 192 + head * 48 + 32 - 32 * va);
      mbar_expect(bar + B_WK * 8, NL * 6144);
    } else if (warp == 13) {
#pragma unroll
      for (int i = 0; i < B_WK; i++) mbar_init(bar + i * 8, i < B_EMPTY ? 4 : (i < B_TIN ? 16 : (i < B_TFREE ? 1 : 16)));
    } else if (warp == 14) {
#pragma unroll
      for (int i = B_WQ; i < B_COUNT; i++) mbar_init(bar + i * 8, i < B_Q0 ? 1 : (i < B_ODONE ? 4 : 8));
    } else asm volatile("prefetch.tensormap [%0];" ::"l"(head ? &mp.xc : &mp.xh) : "memory");
    asm volatile("fence.mbarrier_init.release.cluster;" ::: "memory");
  }
  __syncwarp();
  asm volatile("barrier.cluster.arrive.relaxed.aligned;" ::: "memory");
  if (warp < 12) {
#pragma unroll
    for (int i = 0; i < 2 * NL; i++)
      wv[i] = __ldg(reinterpret_cast<const uint4*>(wqkv + ((tid >> 2) + (i & 1) * 96) * 576 + ((i / 2 + 1) % 3) * 192 + head * 48 + va * 16 + (tid & 3) * 8));
  }

  if (warp >= 12) {
    asm volatile("setmaxnreg.dec.sync.aligned.u32 24;");
    asm volatile("griddepcontrol.launch_dependents;");
    const int cc = ph * 112 + (head ? strip * 16 : (strip == 0 ? 16 : (strip == 6 ? 74 : strip * 16 - 3)));
    const int sd = strip == 0 ? -1 : (strip == 6 ? 1 : 0);
    const int r0 = head == 0 ? -4 : (head == 1 ? 4 : 0);
    asm volatile("barrier.cluster.wait.aligned;" ::: "memory");
    if (warp == 12) {
      const uint32_t fb = bar + (B_FULL + head) * 8, eb = bar + (B_EMPTY + head) * 8;
      const uint32_t dst = sb + (head == 0 ? SM_X0 : (head == 1 ? SM_X1 : SM_X2));
      const int nl = head == 0 ? 15 : (head == 3 ? 1 : 14);
#pragma unroll 1
      for (int n = 0; n < nl; n++) {
        if (n) mbar_wait(eb, (n - 1) & 1);
        if (elect_one()) {
          if (head == 0) {
            asm volatile("cp.async.bulk.tensor.5d.shared::cluster.global.mbarrier::complete_tx::bytes.multicast::cluster [%0], [%1, {%3,%4,%5,%6,%7}], [%2], %8;"
                         ::"r"(dst), "l"(&mp.xh), "r"(fb), "r"(0), "r"(8 * n + r0), "r"(cc), "r"(sd), "r"(pw * 3), "h"((uint16_t)15) : "memory");
          } else if (head < 3) {
            asm volatile("cp.async.bulk.tensor.4d.shared::cluster.global.mbarrier::complete_tx::bytes.multicast::cluster [%0], [%1, {%3,%4,%5,%6}], [%2], %7;"
                         ::"r"(dst), "l"(&mp.xc), "r"(fb), "r"(0), "r"(8 * n + r0), "r"(cc), "r"(pw * 3), "h"((uint16_t)15) : "memory");
          }
          if (n == 0) {
#pragma unroll
            for (int i = 0; i < 3; i++) load_w(&mp.w, sb + SM_W + (6 + i) * 6144, bar + B_WQ * 8, head * 48 + i * 16);
            mbar_expect(bar + B_WQ * 8, 18432);
            mbar_expect(bar + B_TIN * 8, 24576); mbar_expect(bar + (B_TIN + 1) * 8, 24576); mbar_expect(bar + (B_TIN + 2) * 8, 24576);
          }
          if (!head && n + 1 < nl) asm volatile("cp.async.bulk.prefetch.tensor.5d.L2.global [%0, {%1,%2,%3,%4,%5}];" ::"l"(&mp.xh), "r"(0), "r"(8 * n + 8 + r0), "r"(cc), "r"(sd), "r"(pw * 3) : "memory");
          if (head && n + 1 < nl) asm volatile("cp.async.bulk.prefetch.tensor.4d.L2.global [%0, {%1,%2,%3,%4}];" ::"l"(&mp.xc), "r"(0), "r"(8 * n + 8 + r0), "r"(cc), "r"(pw * 3) : "memory");
        }
        __syncwarp();
      }
    }
    if (warp == 14) {
      int* flag = g_flags + cl * 2;
      nb_arrive(N_VQ0, 288); nb_arrive(N_VQ1, 288);
#pragma unroll 1
      for (int b = 0; b < TB; b++) {
        mbar_wait(bar + B_ODONE * 8, b & 1);
        if (lane == 0) {
          asm volatile("cp.async.bulk.tensor.3d.global.shared::cta.bulk_group [%0, {%2,%3,%4}], [%1];"
                       ::"l"(&mp.os), "r"(sb + SM_O), "r"(pw * 192), "r"(8 * b + 2 * head), "r"(ph * 112 + strip * 16) : "memory");
          asm volatile("cp.async.bulk.commit_group;\ncp.async.bulk.wait_group 0;" ::: "memory");
        }
        __syncwarp();
        nb_arrive(N_VQ0, 288); nb_arrive(N_VQ1, 288);
        if (lane == 0)
          asm volatile("fence.proxy.async.global;\nfence.acq_rel.gpu;\nred.relaxed.gpu.global.add.s32 [%0], 1;\nred.relaxed.gpu.global.add.s32 [%0+4], 1;"
                       ::"l"(flag + b * 56) : "memory");
        __syncwarp();
      }
    } else if (warp & 1) {
      const int j = (warp >> 1) & 1;
#pragma unroll 1
      for (int i = 0; i < 2; i++) {
        mbar_wait(bar + (B_OTAIL + j) * 8, i);
        if (i == 0) nb_arrive(N_VQ0 + j, 288);
        mbar_wait(bar + (B_TFREE + i) * 8, 0);
        if (elect_one()) {
#pragma unroll 1
          for (int d = 0; d < 8; d++) {
            const int dst = (d + head) & 3, pc = d >> 2;
            send_o<1536>(sb + (i ? SM_X1 : SM_X2) + head * 6144 + j * 3072 + pc * 1536,
                         sb + (i ? SM_Q : SM_O) + (4 * j + (dst & 2) + pc) * (i ? 3072 : 1536), bar + (B_TIN + i) * 8, dst);
          }
        }
        __syncwarp();
      }
    }
    cluster_sync();
  } else if (warp >= 8) {
    TRDECL;
    TR(2, -3, 0);
    asm volatile("setmaxnreg.inc.sync.aligned.u32 %0;" ::"n"(RG));
    TR(2, -3, 1);
    GemmCtx c;
    c.bar = bar;
    const int gw = warp - 8, tk = gw * 16 + (lane & 15), hi = lane >> 4;
    { const int col = tk >> 2, i = tk & 3;
      c.kC = sb + SM_K + (col + 3) * KS + hi * 128 + i * 16;
      c.vC = sb + SM_V + (col + 3) * 1536 + hi * 128 + (2 * i + ((col + 3) & 1)) * 16;
      c.qC = sb + SM_Q + col * 1536 + hi * 256 + (col & 1) * 64 + i * 16; }
    { const int ci = (tk >> 3) - 2, kc = ci < 3 ? ci : ci + 16, i = tk & 7; c.hvalid = gw > 0;
      c.kH = sb + SM_K + kc * KS + hi * 128 + i * 16;
      c.vH = sb + SM_V + kc * 1536 + hi * 128 + (i >> 2) * 768 + (2 * (i & 3) + ((kc ^ (i >> 2)) & 1)) * 16; }
    asm volatile("barrier.cluster.wait.aligned;" ::: "memory");
    TR(2, -3, 2);
    if (elect_one()) { mbar_expect(bar + B_FULL * 8, 4608); mbar_expect(bar + (B_FULL + 1) * 8, 6144); mbar_expect(bar + (B_FULL + 2) * 8, 6144); }
    __syncwarp();
#pragma unroll
    for (int i = 0; i < 2 * NL; i++) sts128(wdst + (i & 1) * 3072 + (i / 2) * 18432, wv[i]);
    fence_async();
    TR(2, -3, 3);
    asm volatile("bar.sync 1, 384;" ::: "memory");
    TR(2, -3, 4);
    mbar_wait(bar + B_WK * 8, 0);
    TR(2, -3, 5);
    uint32_t pk[12], pv[12], pq[12];
    gemm_iter<true, false>(c, -2, pk, pv, pq, &mp.wo TRPASS);
    TR2(blockIdx.x, 4);
#pragma unroll 1
    for (int b = -1; b < 12; b++) gemm_iter<false, false>(c, b, pk, pv, pq, &mp.wo TRPASS);
    TR2(blockIdx.x, 6);
    gemm_iter<false, true>(c, 12, pk, pv, pq, &mp.wo TRPASS);
    TR(2, 13, 0);
    mbar_wait(bar + B_WO * 8, 0);
    TR(2, 13, 1);
    const uint32_t st = sb + SM_TST + gw * 3072;
    const uint32_t sta = st + (lane & 15) * 64 + ((hi ^ ((lane >> 1) & 3)) * 16);
#pragma unroll 1
    for (int i = 0; i < 3; i++) {
      constexpr uint64_t db = mkdesc(SBC + SM_TWO, 12288, 512, 2);
      const uint64_t da = mkdesc(SBC, 128, 768, 0) + (i ^ (i < 2)) * (24576 / 16);
      float D[48];
      mbar_wait(bar + (B_TIN + i) * 8, 0);
      if (i == 2) asm volatile("barrier.cluster.arrive.relaxed.aligned;" ::: "memory");
      else nb_sync(i ? N_PVISS : N_QK1, i ? 384 : 256);
      TR(2, 13 - i, 2); TR(2, 12 + i, 5); TR(2, 11 + i, 9);
      wg_fence();
      wg_ss96<0>(D, da, db);
#pragma unroll
      for (int k = 1; k < 12; k++) wg_ss96<1>(D, da + (k / 3) * 384 + (k % 3) * 16, db + k * 64);
      wg_commit();
      if (lane == 0) asm volatile("cp.async.bulk.wait_group.read 0;" ::: "memory");
      __syncwarp();
      wg_wait<0>(); pin(D);
      TR(2, 13 - i, 3); TR(2, 12 + i, 6); TR(2, 11 + i, 10);
#pragma unroll
      for (int q = 0; q < 6; q++)
        stsm4((sta ^ ((q & 1) * 32)) + (q >> 1) * 1024,
              pack2(D[8 * q], D[8 * q + 1]), pack2(D[8 * q + 2], D[8 * q + 3]), pack2(D[8 * q + 4], D[8 * q + 5]), pack2(D[8 * q + 6], D[8 * q + 7]));
      fence_async();
      __syncwarp();
      if (lane == 0) {
        asm volatile("cp.async.bulk.tensor.4d.global.shared::cta.bulk_group [%0, {%2,%3,%4,%5}], [%1];"
                     ::"l"(&mp.ot), "r"(st), "r"(0), "r"(8 * (TB + i)), "r"(ph * 112 + strip * 16 + 8 * (gw >> 1) + 4 * (head >> 1) + 2 * (gw & 1)), "r"(pw * 6 + (head & 1) * 3) : "memory");
        asm volatile("cp.async.bulk.commit_group;" ::: "memory");
      }
      TR(2, 13 - i, 4); TR(2, 12 + i, 7); TR(2, 11 + i, 11);
    }
    if (lane == 0) asm volatile("cp.async.bulk.wait_group.read 0;" ::: "memory");
    __syncwarp();
    TR(2, 13, 8);
    TR2(blockIdx.x, 2);
    TRDUMP;
    asm volatile("barrier.cluster.wait.aligned;" ::: "memory");
  } else {
    asm volatile("setmaxnreg.inc.sync.aligned.u32 %0;" ::"n"(RA));
    float rv = -INFINITY;
    if (tid < 169) rv = __bfloat162float(rpb[head * 169 + tid]) * 1.4426950408889634f;
    if (tid < 192) {
      const int kc = (tid & 15) + 3, wc = (tid >> 4) % 6;
      sts128(tid < 96 ? sb + SM_K + kc * KS + wc * 128 + 48 : sb + SM_V + kc * 1536 + wc * 128 + (6 + (kc & 1)) * 16, make_uint4(0, 0, 0, 0));
    }
#pragma unroll
    for (int i = 0; i < 2 * NL; i++) sts128(wdst + (i & 1) * 3072 + (i / 2) * 18432, wv[i]);
    fence_async();
    asm volatile("bar.arrive 1, 384;" ::: "memory");
    if (tid < 182) asm volatile("st.shared.f32 [%0], %1;" ::"r"(sb + SM_RPB + tid * 4), "f"(rv) : "memory");
    const int j = warp >> 2, w = warp & 3;
    int variant = w;
    if (strip == 0 && j == 0 && w < 2) variant = 4;
    if (strip == 6 && j == 1 && w >= 2) variant = 5;
    const uint32_t qa = sb + SM_Q + (8 * j + 2 * w + ((lane >> 3) & 1)) * 1536 + (lane >> 4) * 256 + (((lane & 7) * 16) ^ (((lane >> 3) & 1) * 64));
    uint32_t oa = sb + SM_O + j * 6144 + (2 * w + ((lane >> 3) & 1)) * 768 + (lane >> 4) * 128 + (lane & 7) * 16;
    const uint64_t dK = mkdesc(SBC + SM_K, 128, KS, 0) + j * (8 * KS / 16);
    const uint64_t dV = mkdesc(SBC + SM_V, 768, 128, 0) + j * (8 * 1536 / 16);
    asm volatile("barrier.cluster.wait.aligned;" ::: "memory");
    asm volatile("bar.sync 3, 256;" ::: "memory");
    float T[16];
    TRDECL;
    int b0 = 0, b1 = 0;
    uint32_t meta = 0;
    uint32_t q[12];
    mbar_wait(bar + B_Q0 * 8, 0);
#pragma unroll
    for (int k = 0; k < 3; k++) ldsm4(qa + k * 512, q[4 * k], q[4 * k + 1], q[4 * k + 2], q[4 * k + 3]);
#pragma unroll 1
    for (int b = 0; b < 14; b++) {
      const uint32_t pa = b & 1;
      float SA[56], SB[56];
      const uint64_t dA = dK + pa * (KSLOT >> 4), dB = dK + (pa ^ 1) * (KSLOT >> 4);
      TR(0, b, 0);
      nb_sync(N_KRDY + j, 256);
      TR(0, b, 1);
      TR(0, b - 1, 9);
      wg_fence();
      wg_rs112<0>(SA, q[0], q[1], q[2], q[3], dA);
      wg_rs112<0>(SB, q[0], q[1], q[2], q[3], dB);
      wg_rs112<1>(SA, q[4], q[5], q[6], q[7], dA + 16);
      wg_rs112<1>(SB, q[4], q[5], q[6], q[7], dB + 16);
      wg_rs112<1>(SA, q[8], q[9], q[10], q[11], dA + 32);
      wg_rs112<1>(SB, q[8], q[9], q[10], q[11], dB + 32);
      wg_commit();
      nb_arrive(N_QK0 + j, 256);
      TR(0, b, 2);
      if (b <= 1 || b == 13) {
        uint32_t ln; asm volatile("mov.u32 %0, %%laneid;" : "=r"(ln));
        const int g = ln >> 2, t = ln & 3;
        const int sw = b == 0 ? max(g + 1, 4) : (b == 13 ? min(g + 1, 5) : g + 1);
        const int i0 = 2 * t, i1 = 2 * t + 1;
        b0 = i0 <= sw - 2; b1 = i1 <= sw - 2;
        const uint32_t tb = sb + SM_RPB + (variant < 4 ? 3 : variant + 1 - 2 * w) * 4;
        const uint32_t ra0 = tb + (i0 == sw - 1 ? 13 : i0 + 8 * b0 - g + 2) * 52;
        const uint32_t ra1 = tb + (i1 == sw - 1 ? 13 : i1 + 8 * b1 - g + 2) * 52;
#pragma unroll
        for (int jj = 0; jj < 8; jj++) { T[2 * jj] = lds_f32(ra0 + jj * 4); T[2 * jj + 1] = lds_f32(ra1 + jj * 4); }
        meta = ((0x5555u & ((1u << (2 * (sw - 1))) - 1)) ^ 0xDD88u ^ (((t ^ b) & 1) ? 0x5555u : 0u)) * 0x10001u;
      } else meta ^= 0x55555555u;
      if (b >= 12) oa += b == 12 ? warp * 1536 - (SM_O - SM_Q) : 1536;
      wg_wait<0>(); pin(SA); pin(SB);
      mbar_arrive_elect(bar + B_KFREE * 8);
      TR(0, b, 3);
      TR(0, b - 1, 10);
      uint32_t P[28];
      float sx[8];
      switch (variant) {
        case 0: softmax_tile<0, 1>(SA, SB, T, b0, b1, P, sx); break;
        case 1: softmax_tile<2, 3>(SA, SB, T, b0, b1, P, sx); break;
        case 2: softmax_tile<4, 5>(SA, SB, T, b0, b1, P, sx); break;
        case 3: softmax_tile<6, 7>(SA, SB, T, b0, b1, P, sx); break;
        case 4: softmax_tile<3, 3>(SA, SB, T, b0, b1, P, sx); break;
        default: softmax_tile<4, 4>(SA, SB, T, b0, b1, P, sx); break;
      }
      float O[24];
      TR(0, b, 4);
      nb_sync(N_VQ0 + j, b == 13 ? 256 : 288);
      TR(0, b, 5);
#pragma unroll
      for (int k = 0; k < 3; k++) ldsm4(qa + (pa ^ 1) * 128 + k * 512, q[4 * k], q[4 * k + 1], q[4 * k + 2], q[4 * k + 3]);
      wg_fence();
      wg_sp48<0>(O, P[0], P[1], P[2], P[3], dV, meta);
#pragma unroll
      for (int s = 1; s < 7; s++) wg_sp48<1>(O, P[4 * s], P[4 * s + 1], P[4 * s + 2], P[4 * s + 3], dV + s * 192, meta);
      wg_commit();
      if (b != 12) nb_arrive(N_PVISS, 384);
      TR(0, b, 6);
      wg_wait<0>(); pin(O);
      mbar_arrive_elect(bar + B_VFREE * 8);
      TR(0, b, 7);
      float ru, rl;
      asm("rcp.approx.ftz.f32 %0, %1;" : "=f"(ru) : "f"(((fmaf(O[0], 0.f, sx[0]) + sx[1]) + sx[2]) + sx[3]));
      asm("rcp.approx.ftz.f32 %0, %1;" : "=f"(rl) : "f"(((fmaf(O[2], 0.f, sx[4]) + sx[5]) + sx[6]) + sx[7]));
#pragma unroll
      for (int i = 0; i < 3; i++)
        stsm4(oa + i * 256, pack2(O[8 * i] * ru, O[8 * i + 1] * ru), pack2(O[8 * i + 2] * rl, O[8 * i + 3] * rl),
              pack2(O[8 * i + 4] * ru, O[8 * i + 5] * ru), pack2(O[8 * i + 6] * rl, O[8 * i + 7] * rl));
      if (b < 13) publish(bar + (b < TB ? B_ODONE : B_OTAIL + j) * 8);
      else {
        fence_async();
        mbar_wait(bar + (B_TFREE + 1) * 8, 0);
        __syncwarp();
        if (elect_one()) {
#pragma unroll
          for (int d = 0; d < 2; d++)
            send_o<1536>(sb + SM_X0 + head * 6144 + (2 * j + (w & 1)) * 1536, sb + SM_Q + warp * 3072 + 1536, bar + (B_TIN + 2) * 8, (w & 2) + (d ^ (head & 1)));
        }
        __syncwarp();
      }
      TR(0, b, 8);
    }
    TRDUMP;
    cluster_sync();
  }
}

constexpr int NSTB = 6;
constexpr int NTB = TB * 56;
constexpr int SM_B_IN = 0;
constexpr int SM_B_W = SM_B_IN + NSTB * 24576;
constexpr int SM_B_BAR = SM_B_W + 73728;
constexpr int SM_B_TOTAL = SM_B_BAR + 128;
struct MapsB { CUtensorMap oi, oo, wo; };

__global__ void __launch_bounds__(480, 1)
na_proj_kernel(const __grid_constant__ MapsB mp) {
  extern __shared__ __align__(1024) uint8_t smem_raw[];
  const uint32_t sb = smem_u32(smem_raw);
  if ((sb & 0x3FFFF) != SBC) return;
  const uint32_t bar = sb + SM_B_BAR;
  const int tid = threadIdx.x, lane = tid & 31;
  const int warp = __shfl_sync(0xffffffffu, tid >> 5, 0);
  TR2(132 + blockIdx.x, 0);
  TRB(47, 0);
  if (warp == 12 && elect_one()) {
#pragma unroll
    for (int i = 0; i <= 2 * NSTB; i++) mbar_init(bar + i * 8, i < NSTB || i == 2 * NSTB ? 1 : 4);
    mbar_expect(bar + 2 * NSTB * 8, 73728);
#pragma unroll
    for (int i = 0; i < 2; i++)
      asm volatile("cp.async.bulk.tensor.3d.shared::cluster.global.mbarrier::complete_tx::bytes [%0], [%1, {%3,%4,%5}], [%2];"
                   ::"r"(sb + SM_B_W + i * 36864), "l"(&mp.wo), "r"(bar + 2 * NSTB * 8), "r"(0), "r"(0), "r"(i * 3) : "memory");
  }
  __syncthreads();
  const int step = gridDim.x;
  if (warp >= 12) {
    const int wg = warp - 12;
    int use = 0;
#pragma unroll 1
    for (int n = blockIdx.x + wg * step; n < NTB; n += 3 * step, use++) {
      const int b = n / 56, rem = n - b * 56, par = rem / 14, sg = wg + 3 * (use & 1);
      int v; uint32_t spin = 0;
      do { asm volatile("ld.acquire.gpu.global.s32 %0, [%1];" : "=r"(v) : "l"(g_flags + n) : "memory"); } while (v < 4 && ++spin < SPIN_LIMIT);
      TRB(use * 3 + wg, 0);
      asm volatile("fence.proxy.async.global;" ::: "memory");
      if (use >= 2) mbar_wait(bar + (NSTB + sg) * 8, ((use >> 1) - 1) & 1);
      TRB(use * 3 + wg, 1);
      if (elect_one()) {
        mbar_expect(bar + sg * 8, 24576);
        asm volatile("cp.async.bulk.tensor.3d.shared::cluster.global.mbarrier::complete_tx::bytes [%0], [%1, {%3,%4,%5}], [%2];"
                     ::"r"(sb + SM_B_IN + sg * 24576), "l"(&mp.oi), "r"(bar + sg * 8), "r"((par & 1) * 192), "r"(8 * b), "r"((par >> 1) * 112 + (rem - par * 14) * 8) : "memory");
        g_flags[n] = 0;
      }
      __syncwarp();
    }
  } else {
    const int wg = warp >> 2, w = warp & 3;
    constexpr uint64_t db = mkdesc(SBC + SM_B_W, 12288, 512, 2);
    const uint32_t sta0 = sb + SM_B_IN + w * 6144 + (lane & 15) * 128 + (((lane >> 4) ^ (lane & 7)) * 16);
    mbar_wait(bar + 2 * NSTB * 8, 0);
    TRB(47, 1);
    int use = 0;
#pragma unroll 1
    for (int n = blockIdx.x + wg * step; n < NTB; n += 3 * step, use++) {
      const int b = n / 56, rem = n - b * 56, par = rem / 14, sg = wg + 3 * (use & 1);
      const uint64_t da = mkdesc(SBC + SM_B_IN, 128, 3072, 0) + sg * (24576 / 16);
      float D[96];
      mbar_wait(bar + sg * 8, (use >> 1) & 1);
      if (use | wg) nb_sync(4 + wg, 256);
      TRB(use * 3 + wg, 3);
      wg_fence();
      wg_ss192<0>(D, da, db);
#pragma unroll
      for (int k = 1; k < 12; k++) wg_ss192<1>(D, da + k * 16, db + k * 64);
      wg_commit();
      if (n + step < NTB) nb_arrive(wg == 2 ? 4 : 5 + wg, 256);
      TRB(use * 3 + wg, 4);
      if (use && lane == 0) {
        asm volatile("cp.async.bulk.wait_group.read 0;" ::: "memory");
        mbar_arrive(bar + (NSTB + wg + 3 * (~use & 1)) * 8);
      }
      __syncwarp();
      wg_wait<0>(); pin(D);
      nb_sync(1 + wg, 128);
      TRB(use * 3 + wg, 5);
      const uint32_t sta = sta0 + sg * 24576;
#pragma unroll
      for (int q = 0; q < 12; q++)
        stsm4((sta ^ ((q & 3) * 32)) + (q >> 2) * 2048,
              pack2(D[8 * q], D[8 * q + 1]), pack2(D[8 * q + 2], D[8 * q + 3]), pack2(D[8 * q + 4], D[8 * q + 5]), pack2(D[8 * q + 6], D[8 * q + 7]));
      fence_async();
      __syncwarp();
      if (lane == 0) {
        asm volatile("cp.async.bulk.tensor.4d.global.shared::cta.bulk_group [%0, {%2,%3,%4,%5}], [%1];"
                     ::"l"(&mp.oo), "r"(sb + SM_B_IN + sg * 24576 + w * 6144), "r"(0), "r"(8 * b), "r"((par >> 1) * 112 + (rem - par * 14) * 8 + 2 * w), "r"((par & 1) * 3) : "memory");
        asm volatile("cp.async.bulk.commit_group;" ::: "memory");
      }
      __syncwarp();
      TRB(use * 3 + wg, 6);
    }
    if (lane == 0) asm volatile("cp.async.bulk.wait_group 0;" ::: "memory");
    TR2(132 + blockIdx.x, 2);
  }
}

typedef CUresult (*EncodeFn)(CUtensorMap*, CUtensorMapDataType, cuuint32_t, void*, const cuuint64_t*, const cuuint64_t*, const cuuint32_t*,
                             const cuuint32_t*, CUtensorMapInterleave, CUtensorMapSwizzle, CUtensorMapL2promotion, CUtensorMapFloatOOBfill);
static EncodeFn g_enc = nullptr;
static void make_map(CUtensorMap* m, const void* p, int rank, const cuuint64_t* dim, const cuuint64_t* str, const cuuint32_t* box, CUtensorMapSwizzle sw) {
  const cuuint32_t ones[5] = {1, 1, 1, 1, 1};
  g_enc(m, CU_TENSOR_MAP_DATA_TYPE_BFLOAT16, rank, (void*)p, dim, str, box, ones, CU_TENSOR_MAP_INTERLEAVE_NONE, sw,
        CU_TENSOR_MAP_L2_PROMOTION_L2_128B, CU_TENSOR_MAP_FLOAT_OOB_FILL_NONE);
}

extern "C" void kernel_launch(void* const* d_in, const int* in_sizes, int n_in, void* d_out, int out_size) {
  const __nv_bfloat16* x = (const __nv_bfloat16*)d_in[0];
  const __nv_bfloat16* wqkv = (const __nv_bfloat16*)d_in[1];
  const __nv_bfloat16* wo = (const __nv_bfloat16*)d_in[2];
  const __nv_bfloat16* rpb = (const __nv_bfloat16*)d_in[3];

  if (!g_enc) {
    void* fn = nullptr; cudaDriverEntryPointQueryResult qr;
    cudaGetDriverEntryPoint("cuTensorMapEncodeTiled", &fn, cudaEnableDefault, &qr);
    g_enc = (EncodeFn)fn;
    cudaFuncSetAttribute(na_attn_kernel, cudaFuncAttributeMaxDynamicSharedMemorySize, SM_A_TOTAL);
    cudaFuncSetAttribute(na_proj_kernel, cudaFuncAttributeMaxDynamicSharedMemorySize, SM_B_TOTAL);
  }
  Maps ma; MapsB mb;
  { cuuint64_t dim[4] = {64, 112, 224, 6}, str[3] = {(cuuint64_t)ROWB, 768, 128};
    cuuint32_t box[4] = {64, 4, 16, 3}, boxo[4] = {64, 8, 2, 3};
    make_map(&ma.xc, x, 4, dim, str, box, CU_TENSOR_MAP_SWIZZLE_128B);
    make_map(&mb.oo, d_out, 4, dim, str, boxo, CU_TENSOR_MAP_SWIZZLE_128B); }
  { cuuint64_t dim[5] = {64, 112, 224, 2, 6}, str[4] = {(cuuint64_t)ROWB, 768, 19 * 768, 128};
    cuuint32_t box[5] = {64, 8, 3, 2, 3};
    make_map(&ma.xh, x, 5, dim, str, box, CU_TENSOR_MAP_SWIZZLE_128B); }
  { cuuint64_t dim[3] = {384, 112, 224}, str[2] = {(cuuint64_t)ROWB, 768};
    cuuint32_t box[3] = {192, 8, 8}, boxs[3] = {192, 2, 16};
    make_map(&mb.oi, d_out, 3, dim, str, box, CU_TENSOR_MAP_SWIZZLE_NONE);
    make_map(&ma.os, d_out, 3, dim, str, boxs, CU_TENSOR_MAP_SWIZZLE_NONE); }
  { cuuint64_t dim[4] = {32, 112, 224, 12}, str[3] = {(cuuint64_t)ROWB, 768, 64};
    cuuint32_t box[4] = {32, 8, 2, 3};
    make_map(&ma.ot, d_out, 4, dim, str, box, CU_TENSOR_MAP_SWIZZLE_64B); }
  { cuuint64_t dim[2] = {576, 192}, str[1] = {1152};
    cuuint32_t box[2] = {16, 192};
    make_map(&ma.w, wqkv, 2, dim, str, box, CU_TENSOR_MAP_SWIZZLE_32B); }
  { cuuint64_t dim[3] = {32, 192, 6}, str[2] = {384, 64};
    cuuint32_t box[3] = {32, 192, 3};
    make_map(&ma.wo, wo, 3, dim, str, box, CU_TENSOR_MAP_SWIZZLE_64B);
    mb.wo = ma.wo; }
  na_attn_kernel<<<112, 512, SM_A_TOTAL>>>(ma, x, wqkv, rpb);
  cudaLaunchConfig_t cfg = {};
  cfg.gridDim = dim3(20); cfg.blockDim = dim3(480); cfg.dynamicSmemBytes = SM_B_TOTAL; cfg.stream = cudaStreamPerThread;
  cudaLaunchAttribute at[1];
  at[0].id = cudaLaunchAttributeProgrammaticStreamSerialization; at[0].val.programmaticStreamSerializationAllowed = 1;
  cfg.attrs = at; cfg.numAttrs = 1;
  cudaLaunchKernelEx(&cfg, na_proj_kernel, mb);
}
```

```cpp
#include <cuda_runtime.h>
#include <cuda_bf16.h>
#include <cuda.h>
#include <stdint.h>

#define SPIN_LIMIT (1u << 18)

__device__ __forceinline__ uint32_t smem_u32(const void* p) { return (uint32_t)__cvta_generic_to_shared(p); }
__device__ __forceinline__ void wg_fence() { asm volatile("wgmma.fence.sync.aligned;" ::: "memory"); }
__device__ __forceinline__ void wg_commit() { asm volatile("wgmma.commit_group.sync.aligned;" ::: "memory"); }
template <int N> __device__ __forceinline__ void wg_wait() { asm volatile("wgmma.wait_group.sync.aligned %0;" ::"n"(N) : "memory"); }
template <int N> __device__ __forceinline__ void pin(float (&d)[N]) {
#pragma unroll
  for (int i = 0; i < N; i++) asm volatile("" : "+f"(d[i])::"memory");
}
__host__ __device__ constexpr uint64_t mkdesc(uint32_t addr, uint32_t lbo, uint32_t sbo, uint32_t sw) {
  return (uint64_t)((addr & 0x3FFFF) >> 4) | ((uint64_t)(lbo >> 4) << 16) | ((uint64_t)(sbo >> 4) << 32) | ((uint64_t)sw << 62);
}
__device__ __forceinline__ void mbar_init(uint32_t bar, uint32_t cnt) { asm volatile("mbarrier.init.shared::cta.b64 [%0], %1;" ::"r"(bar), "r"(cnt) : "memory"); }
__device__ __forceinline__ void mbar_arrive(uint32_t bar) { asm volatile("mbarrier.arrive.shared::cta.b64 _, [%0];" ::"r"(bar) : "memory"); }
__device__ __forceinline__ bool elect_one() {
  uint32_t r; asm volatile("{\n.reg .pred p;\nelect.sync _|p, 0xffffffff;\nselp.u32 %0, 1, 0, p;\n}" : "=r"(r)); return r;
}
__device__ __forceinline__ void mbar_arrive_elect(uint32_t bar) {
  asm volatile("{\n.reg .pred p;\nelect.sync _|p, 0xffffffff;\n@p mbarrier.arrive.shared::cta.b64 _, [%0];\n}" ::"r"(bar) : "memory");
}
__device__ __forceinline__ void mbar_expect(uint32_t bar, uint32_t bytes) { asm volatile("mbarrier.arrive.expect_tx.shared::cta.b64 _, [%0], %1;" ::"r"(bar), "r"(bytes) : "memory"); }
__device__ __forceinline__ void mbar_arrive_remote(uint32_t bar, uint32_t cta) {
  asm volatile("{\n.reg .b32 ra;\nmapa.shared::cluster.u32 ra, %0, %1;\nmbarrier.arrive.relaxed.cluster.shared::cluster.b64 _, [ra];\n}" ::"r"(bar), "r"(cta) : "memory");
}
__device__ __forceinline__ void mbar_wait(uint32_t bar, uint32_t parity) {
  asm volatile("{\n.reg .pred p;\n.reg .b32 n;\nmov.b32 n, 0;\nWL:\nmbarrier.try_wait.parity.shared::cta.b64 p, [%0], %1;\n@p bra WD;\n"
               "add.u32 n, n, 1;\nsetp.lt.u32 p, n, 65536;\n@p bra WL;\nWD:\n}" ::"r"(bar), "r"(parity) : "memory");
}
__device__ __forceinline__ void nb_sync(int id, int n) { asm volatile("bar.sync %0, %1;" ::"r"(id), "r"(n) : "memory"); }
__device__ __forceinline__ void nb_arrive(int id, int n) { asm volatile("bar.arrive %0, %1;" ::"r"(id), "r"(n) : "memory"); }
__device__ __forceinline__ void fence_async() { asm volatile("fence.proxy.async.shared::cta;" ::: "memory"); }
__device__ __forceinline__ void cluster_sync() {
  asm volatile("barrier.cluster.arrive.relaxed.aligned;\nbarrier.cluster.wait.aligned;" ::: "memory");
}
__device__ __forceinline__ uint32_t pack2(float lo, float hi) {
  uint32_t r; asm("cvt.rn.bf16x2.f32 %0, %1, %2;" : "=r"(r) : "f"(hi), "f"(lo)); return r;
}
__device__ __forceinline__ void stsm4(uint32_t a, uint32_t r0, uint32_t r1, uint32_t r2, uint32_t r3) {
  asm volatile("stmatrix.sync.aligned.m8n8.x4.shared.b16 [%0], {%1,%2,%3,%4};" ::"r"(a), "r"(r0), "r"(r1), "r"(r2), "r"(r3) : "memory");
}
__device__ __forceinline__ void ldsm4(uint32_t a, uint32_t& r0, uint32_t& r1, uint32_t& r2, uint32_t& r3) {
  asm volatile("ldmatrix.sync.aligned.m8n8.x4.shared.b16 {%0,%1,%2,%3}, [%4];" : "=r"(r0), "=r"(r1), "=r"(r2), "=r"(r3) : "r"(a) : "memory");
}
__device__ __forceinline__ void sts128(uint32_t a, uint4 v) {
  asm volatile("st.shared.v4.b32 [%0], {%1,%2,%3,%4};" ::"r"(a), "r"(v.x), "r"(v.y), "r"(v.z), "r"(v.w) : "memory");
}
__device__ __forceinline__ float lds_f32(uint32_t a) { float v; asm volatile("ld.shared.f32 %0, [%1];" : "=f"(v) : "r"(a)); return v; }
__device__ __forceinline__ float ex2(float x) { float y; asm("ex2.approx.ftz.f32 %0, %1;" : "=f"(y) : "f"(x)); return y; }

template<int SC> __device__ __forceinline__ void wg_ss144(float (&d)[72], uint64_t da, uint64_t db) {
  asm volatile("{\n.reg .pred p;\nsetp.ne.b32 p, %74, 0;\nwgmma.mma_async.sync.aligned.m64n144k16.f32.bf16.bf16 {%0,%1,%2,%3,%4,%5,%6,%7,%8,%9,%10,%11,%12,%13,%14,%15,%16,%17,%18,%19,%20,%21,%22,%23,%24,%25,%26,%27,%28,%29,%30,%31,%32,%33,%34,%35,%36,%37,%38,%39,%40,%41,%42,%43,%44,%45,%46,%47,%48,%49,%50,%51,%52,%53,%54,%55,%56,%57,%58,%59,%60,%61,%62,%63,%64,%65,%66,%67,%68,%69,%70,%71}, %72, %73, p, 1, 1, 0, 1;\n}\n"
    : "+f"(d[0]),"+f"(d[1]),"+f"(d[2]),"+f"(d[3]),"+f"(d[4]),"+f"(d[5]),"+f"(d[6]),"+f"(d[7]),"+f"(d[8]),"+f"(d[9]),"+f"(d[10]),"+f"(d[11]),"+f"(d[12]),"+f"(d[13]),"+f"(d[14]),"+f"(d[15]),"+f"(d[16]),"+f"(d[17]),"+f"(d[18]),"+f"(d[19]),"+f"(d[20]),"+f"(d[21]),"+f"(d[22]),"+f"(d[23]),"+f"(d[24]),"+f"(d[25]),"+f"(d[26]),"+f"(d[27]),"+f"(d[28]),"+f"(d[29]),"+f"(d[30]),"+f"(d[31]),"+f"(d[32]),"+f"(d[33]),"+f"(d[34]),"+f"(d[35]),"+f"(d[36]),"+f"(d[37]),"+f"(d[38]),"+f"(d[39]),"+f"(d[40]),"+f"(d[41]),"+f"(d[42]),"+f"(d[43]),"+f"(d[44]),"+f"(d[45]),"+f"(d[46]),"+f"(d[47]),"+f"(d[48]),"+f"(d[49]),"+f"(d[50]),"+f"(d[51]),"+f"(d[52]),"+f"(d[53]),"+f"(d[54]),"+f"(d[55]),"+f"(d[56]),"+f"(d[57]),"+f"(d[58]),"+f"(d[59]),"+f"(d[60]),"+f"(d[61]),"+f"(d[62]),"+f"(d[63]),"+f"(d[64]),"+f"(d[65]),"+f"(d[66]),"+f"(d[67]),"+f"(d[68]),"+f"(d[69]),"+f"(d[70]),"+f"(d[71]) : "l"(da), "l"(db), "n"(SC));
}
template<int SC> __device__ __forceinline__ void wg_ss96(float (&d)[48], uint64_t da, uint64_t db) {
  asm volatile("{\n.reg .pred p;\nsetp.ne.b32 p, %50, 0;\nwgmma.mma_async.sync.aligned.m64n96k16.f32.bf16.bf16 {%0,%1,%2,%3,%4,%5,%6,%7,%8,%9,%10,%11,%12,%13,%14,%15,%16,%17,%18,%19,%20,%21,%22,%23,%24,%25,%26,%27,%28,%29,%30,%31,%32,%33,%34,%35,%36,%37,%38,%39,%40,%41,%42,%43,%44,%45,%46,%47}, %48, %49, p, 1, 1, 0, 1;\n}\n"
    : "+f"(d[0]),"+f"(d[1]),"+f"(d[2]),"+f"(d[3]),"+f"(d[4]),"+f"(d[5]),"+f"(d[6]),"+f"(d[7]),"+f"(d[8]),"+f"(d[9]),"+f"(d[10]),"+f"(d[11]),"+f"(d[12]),"+f"(d[13]),"+f"(d[14]),"+f"(d[15]),"+f"(d[16]),"+f"(d[17]),"+f"(d[18]),"+f"(d[19]),"+f"(d[20]),"+f"(d[21]),"+f"(d[22]),"+f"(d[23]),"+f"(d[24]),"+f"(d[25]),"+f"(d[26]),"+f"(d[27]),"+f"(d[28]),"+f"(d[29]),"+f"(d[30]),"+f"(d[31]),"+f"(d[32]),"+f"(d[33]),"+f"(d[34]),"+f"(d[35]),"+f"(d[36]),"+f"(d[37]),"+f"(d[38]),"+f"(d[39]),"+f"(d[40]),"+f"(d[41]),"+f"(d[42]),"+f"(d[43]),"+f"(d[44]),"+f"(d[45]),"+f"(d[46]),"+f"(d[47]) : "l"(da), "l"(db), "n"(SC));
}
template<int SC> __device__ __forceinline__ void wg_rs112(float (&d)[56], uint32_t a0, uint32_t a1, uint32_t a2, uint32_t a3, uint64_t db) {
  asm volatile("{\n.reg .pred p;\nsetp.ne.b32 p, %61, 0;\nwgmma.mma_async.sync.aligned.m64n112k16.f32.bf16.bf16 {%0,%1,%2,%3,%4,%5,%6,%7,%8,%9,%10,%11,%12,%13,%14,%15,%16,%17,%18,%19,%20,%21,%22,%23,%24,%25,%26,%27,%28,%29,%30,%31,%32,%33,%34,%35,%36,%37,%38,%39,%40,%41,%42,%43,%44,%45,%46,%47,%48,%49,%50,%51,%52,%53,%54,%55}, {%56,%57,%58,%59}, %60, p, 1, 1, 0;\n}\n"
    : "+f"(d[0]),"+f"(d[1]),"+f"(d[2]),"+f"(d[3]),"+f"(d[4]),"+f"(d[5]),"+f"(d[6]),"+f"(d[7]),"+f"(d[8]),"+f"(d[9]),"+f"(d[10]),"+f"(d[11]),"+f"(d[12]),"+f"(d[13]),"+f"(d[14]),"+f"(d[15]),"+f"(d[16]),"+f"(d[17]),"+f"(d[18]),"+f"(d[19]),"+f"(d[20]),"+f"(d[21]),"+f"(d[22]),"+f"(d[23]),"+f"(d[24]),"+f"(d[25]),"+f"(d[26]),"+f"(d[27]),"+f"(d[28]),"+f"(d[29]),"+f"(d[30]),"+f"(d[31]),"+f"(d[32]),"+f"(d[33]),"+f"(d[34]),"+f"(d[35]),"+f"(d[36]),"+f"(d[37]),"+f"(d[38]),"+f"(d[39]),"+f"(d[40]),"+f"(d[41]),"+f"(d[42]),"+f"(d[43]),"+f"(d[44]),"+f"(d[45]),"+f"(d[46]),"+f"(d[47]),"+f"(d[48]),"+f"(d[49]),"+f"(d[50]),"+f"(d[51]),"+f"(d[52]),"+f"(d[53]),"+f"(d[54]),"+f"(d[55]) : "r"(a0), "r"(a1), "r"(a2), "r"(a3), "l"(db), "n"(SC));
}
template<int SC> __device__ __forceinline__ void wg_sp48(float (&d)[24], uint32_t a0, uint32_t a1, uint32_t a2, uint32_t a3, uint64_t db, uint32_t meta) {
  asm volatile("{\n.reg .pred p;\nsetp.ne.b32 p, %30, 0;\nwgmma.mma_async.sp.sync.aligned.m64n48k32.f32.bf16.bf16 {%0,%1,%2,%3,%4,%5,%6,%7,%8,%9,%10,%11,%12,%13,%14,%15,%16,%17,%18,%19,%20,%21,%22,%23}, {%24,%25,%26,%27}, %28, %29, 0, p, 1, 1, 1;\n}\n"
    : "+f"(d[0]),"+f"(d[1]),"+f"(d[2]),"+f"(d[3]),"+f"(d[4]),"+f"(d[5]),"+f"(d[6]),"+f"(d[7]),"+f"(d[8]),"+f"(d[9]),"+f"(d[10]),"+f"(d[11]),"+f"(d[12]),"+f"(d[13]),"+f"(d[14]),"+f"(d[15]),"+f"(d[16]),"+f"(d[17]),"+f"(d[18]),"+f"(d[19]),"+f"(d[20]),"+f"(d[21]),"+f"(d[22]),"+f"(d[23]) : "r"(a0), "r"(a1), "r"(a2), "r"(a3), "l"(db), "r"(meta), "n"(SC));
}
template<int SC> __device__ __forceinline__ void wg_ss192(float (&d)[96], uint64_t da, uint64_t db) {
  asm volatile("{\n.reg .pred p;\nsetp.ne.b32 p, %98, 0;\nwgmma.mma_async.sync.aligned.m64n192k16.f32.bf16.bf16 {%0,%1,%2,%3,%4,%5,%6,%7,%8,%9,%10,%11,%12,%13,%14,%15,%16,%17,%18,%19,%20,%21,%22,%23,%24,%25,%26,%27,%28,%29,%30,%31,%32,%33,%34,%35,%36,%37,%38,%39,%40,%41,%42,%43,%44,%45,%46,%47,%48,%49,%50,%51,%52,%53,%54,%55,%56,%57,%58,%59,%60,%61,%62,%63,%64,%65,%66,%67,%68,%69,%70,%71,%72,%73,%74,%75,%76,%77,%78,%79,%80,%81,%82,%83,%84,%85,%86,%87,%88,%89,%90,%91,%92,%93,%94,%95}, %96, %97, p, 1, 1, 0, 1;\n}\n"
    : "+f"(d[0]),"+f"(d[1]),"+f"(d[2]),"+f"(d[3]),"+f"(d[4]),"+f"(d[5]),"+f"(d[6]),"+f"(d[7]),"+f"(d[8]),"+f"(d[9]),"+f"(d[10]),"+f"(d[11]),"+f"(d[12]),"+f"(d[13]),"+f"(d[14]),"+f"(d[15]),"+f"(d[16]),"+f"(d[17]),"+f"(d[18]),"+f"(d[19]),"+f"(d[20]),"+f"(d[21]),"+f"(d[22]),"+f"(d[23]),"+f"(d[24]),"+f"(d[25]),"+f"(d[26]),"+f"(d[27]),"+f"(d[28]),"+f"(d[29]),"+f"(d[30]),"+f"(d[31]),"+f"(d[32]),"+f"(d[33]),"+f"(d[34]),"+f"(d[35]),"+f"(d[36]),"+f"(d[37]),"+f"(d[38]),"+f"(d[39]),"+f"(d[40]),"+f"(d[41]),"+f"(d[42]),"+f"(d[43]),"+f"(d[44]),"+f"(d[45]),"+f"(d[46]),"+f"(d[47]),"+f"(d[48]),"+f"(d[49]),"+f"(d[50]),"+f"(d[51]),"+f"(d[52]),"+f"(d[53]),"+f"(d[54]),"+f"(d[55]),"+f"(d[56]),"+f"(d[57]),"+f"(d[58]),"+f"(d[59]),"+f"(d[60]),"+f"(d[61]),"+f"(d[62]),"+f"(d[63]),"+f"(d[64]),"+f"(d[65]),"+f"(d[66]),"+f"(d[67]),"+f"(d[68]),"+f"(d[69]),"+f"(d[70]),"+f"(d[71]),"+f"(d[72]),"+f"(d[73]),"+f"(d[74]),"+f"(d[75]),"+f"(d[76]),"+f"(d[77]),"+f"(d[78]),"+f"(d[79]),"+f"(d[80]),"+f"(d[81]),"+f"(d[82]),"+f"(d[83]),"+f"(d[84]),"+f"(d[85]),"+f"(d[86]),"+f"(d[87]),"+f"(d[88]),"+f"(d[89]),"+f"(d[90]),"+f"(d[91]),"+f"(d[92]),"+f"(d[93]),"+f"(d[94]),"+f"(d[95]) : "l"(da), "l"(db), "n"(SC));
}

constexpr uint32_t SBC = 1024;
constexpr int ROWB = 2 * 224 * 384;
constexpr int TB = 11;
constexpr int KS = 832;
constexpr int KSLOT = 22 * KS;
constexpr int SM_X1 = 0;
constexpr int SM_X2 = SM_X1 + 24576;
constexpr int SM_X0 = SM_X2 + 24576;
constexpr int SM_W = SM_X0 + 18432;
constexpr int SM_K = SM_W + 55296;
constexpr int SM_V = SM_K + 2 * KSLOT;
constexpr int SM_Q = SM_V + 22 * 1536;
constexpr int SM_O = SM_Q + 24576;
constexpr int SM_RPB = SM_O + 12288;
constexpr int SM_BAR = SM_RPB + 768;
constexpr int SM_A_TOTAL = SM_BAR + 256;
constexpr int SM_TWO = SM_X0 + 24576;
constexpr int SM_TST = SM_TWO + 36864;
enum { B_FULL = 0, B_EMPTY = 3, B_TIN = 6, B_TFREE = 9, B_WK = 11, B_WQ, B_WO, B_Q0, B_OTAIL, B_ODONE = B_OTAIL + 2, B_KFREE, B_VFREE, B_COUNT };
enum { N_KRDY = 4, N_QK0, N_QK1, N_VQ0, N_VQ1, N_PVISS };

#define NL 2
#define SPL 4
#define RA 152
#define RG 184
__device__ int g_flags[TB * 56];

#define TR(role, it, k)
#define TRDECL
#define TRARG
#define TRPASS
#define TRDUMP
#define TRB(it, k)
#define TR2(blk, k)

struct GemmCtx {
  uint32_t bar;
  uint32_t kC, vC, qC;
  uint32_t kH, vH;
  bool hvalid;
};

template <int STRIDE> __device__ __forceinline__ void dump12(uint32_t a, const uint32_t (&r)[12]) {
#pragma unroll
  for (int j = 0; j < 3; j++) stsm4(a + j * 2 * STRIDE, r[4 * j], r[4 * j + 1], r[4 * j + 2], r[4 * j + 3]);
}
template <int N> __device__ __forceinline__ void pack12(uint32_t (&r)[12], const float (&d)[N], int off) {
#pragma unroll
  for (int j = 0; j < 12; j++) r[j] = pack2(d[off + 2 * j], d[off + 2 * j + 1]);
}
template <int XS, int K0, int K1> __device__ __forceinline__ void issue_core(float (&d)[72]) {
  constexpr uint64_t da = mkdesc(SBC + XS, 16, 1024, 1), db = mkdesc(SBC + SM_W, 6144, 256, 3);
  wg_fence();
  if (K0 == 0) wg_ss144<0>(d, da, db);
#pragma unroll
  for (int k = K0 ? K0 : 1; k < K1; k++) wg_ss144<1>(d, da + (k >> 2) * 512 + (k & 3) * 2, db + k * 32);
  wg_commit();
}
template <int K0, int K1> __device__ __forceinline__ void issue_halo(float (&d)[48]) {
  constexpr uint64_t da = mkdesc(SBC + SM_X0 - 2048, 16, 1024, 1), db = mkdesc(SBC + SM_W, 6144, 256, 3);
  wg_fence();
  if (K0 == 0) wg_ss96<0>(d, da, db);
#pragma unroll
  for (int k = K0 ? K0 : 1; k < K1; k++) wg_ss96<1>(d, da + (k >> 2) * 384 + (k & 3) * 2, db + k * 32);
  wg_commit();
}
template <int ST, int BYTES> __device__ __forceinline__ void release_stage(const GemmCtx& c, bool on) {
  asm volatile("{\n.reg .pred p, q;\n.reg .b32 ra;\nsetp.ne.b32 q, %2, 0;\nelect.sync _|p, 0xffffffff;\nand.pred p, p, q;\n"
               "mapa.shared::cluster.u32 ra, %1, %4;\n"
               "@p mbarrier.arrive.expect_tx.shared::cta.b64 _, [%0], %3;\n@p mbarrier.arrive.shared::cluster.b64 _, [ra];\n}"
               ::"r"(c.bar + (B_FULL + ST) * 8), "r"(c.bar + (B_EMPTY + ST) * 8), "r"((int)on), "n"(BYTES / 4), "n"(ST) : "memory");
}
__device__ __forceinline__ void load_w(const CUtensorMap* m, uint32_t dst, uint32_t bar, int col) {
  asm volatile("cp.async.bulk.tensor.2d.shared::cluster.global.mbarrier::complete_tx::bytes [%0], [%1, {%3,%4}], [%2];"
               ::"r"(dst), "l"(m), "r"(bar), "r"(col), "r"(0) : "memory");
}
template <int BYTES> __device__ __forceinline__ void send_o(uint32_t dst, uint32_t src, uint32_t bar, int cta) {
  asm volatile("{\n.reg .b32 rd, rb;\nmapa.shared::cluster.u32 rd, %0, %3;\nmapa.shared::cluster.u32 rb, %2, %3;\n"
               "cp.async.bulk.shared::cluster.shared::cta.mbarrier::complete_tx::bytes [rd], [%1], %4, [rb];\n}"
               ::"r"(dst), "r"(src), "r"(bar), "r"(cta), "n"(BYTES) : "memory");
}
__device__ __forceinline__ void tail_free(uint32_t bar) {
  uint32_t ln; asm volatile("mov.u32 %0, %%laneid;" : "=r"(ln));
  if (ln < 4) mbar_arrive_remote(bar, ln);
}
__device__ __forceinline__ void publish(uint32_t bar) {
  fence_async();
  __syncwarp();
  mbar_arrive_elect(bar);
}

template <bool FIRST, bool LAST>
__device__ __forceinline__ void gemm_iter(const GemmCtx& c, int b, uint32_t (&pk)[12], uint32_t (&pv)[12], uint32_t (&pq)[12], const CUtensorMap* mwo TRARG) {
  const uint32_t bar = c.bar;
  const uint32_t pa = b & 1;
  const bool w = b >= 0;
  const uint32_t ko = pa * KSLOT, vx = pa * 16, qx = pa * 128;
  float H[48], C[72];
  uint32_t hk[12], hv[12], pv2[12];
  TR(2, b, 0);
  if (FIRST) mbar_wait(bar + (B_FULL + 0) * 8, pa);
  if (w) nb_sync(N_QK1, 256);
  TR(2, b, 2);
  if (FIRST) TR(2, b - 1, 6);
  issue_halo<0, 8>(H);
  TR(2, b, 3);
  if (!FIRST) {
    if (w) mbar_wait(bar + B_KFREE * 8, pa);
    dump12<128>(c.kC + ko, pk);
  }
  issue_halo<8, 12>(H);
  TR(2, b, 4);
  if (!LAST) {
    mbar_wait(bar + (B_FULL + 2) * 8, pa);
    if (FIRST && NL == 2) mbar_wait(bar + B_WQ * 8, 0);
    TR(2, b, 13);
    if (FIRST) TR(2, b - 1, 7);
    issue_core<SM_X2, 0, 8>(C);
    TR(2, b, 5);
    if (!FIRST) { fence_async(); dump12<256>(c.qC ^ (qx ^ 192), pq); }
    wg_wait<1>(); pin(H);
    release_stage<0, 18432>(c, true);
  } else {
    dump12<256>(c.qC ^ (qx ^ 192), pq);
    fence_async();
    nb_arrive(N_VQ0, 288); nb_arrive(N_VQ1, 288);
    wg_wait<0>(); pin(H);
    tail_free(bar + (B_TFREE + 1) * 8);
    nb_sync(2, 128);
    if (!c.hvalid && elect_one()) {
      mbar_expect(bar + B_WO * 8, 36864);
      asm volatile("cp.async.bulk.tensor.3d.shared::cluster.global.mbarrier::complete_tx::bytes [%0], [%1, {%3,%4,%5}], [%2];"
                   ::"r"(bar - SM_BAR + SM_TWO), "l"(mwo), "r"(bar + B_WO * 8), "r"(0), "r"(0), "r"((blockIdx.x & 1) * 3) : "memory");
    }
    __syncwarp();
  }
  pack12(hk, H, 0);
  if (c.hvalid) dump12<128>(c.kH + ko, hk);
  pack12(hv, H, 24);
  if (!LAST) {
    issue_core<SM_X2, 8, 12>(C);
    if (w) { nb_arrive(N_VQ0, 288); nb_arrive(N_VQ1, 288); }
    else if (!FIRST) { __syncwarp(); mbar_arrive_elect(bar + B_Q0 * 8); }
    mbar_wait(bar + (B_FULL + 1) * 8, pa);
    TR(2, b, 6);
    wg_wait<0>(); pin(C);
    TR(2, b, 7);
    pack12(pk, C, 0);
    dump12<128>(c.kC + ko + 64, pk);
    release_stage<2, 24576>(c, b < 11);
    if (b == 11) tail_free(bar + B_TFREE * 8);
    pack12(pv2, C, 24);
    pack12(pq, C, 48);
    TR(2, b, 8);
    issue_core<SM_X1, 0, SPL>(C);
    if (w) nb_sync(N_PVISS, 384);
    issue_core<SM_X1, SPL, 8>(C);
    TR(2, b, 9);
  }
  if (!FIRST) fence_async();
  TR(2, b, 14);
  if (!LAST) issue_core<SM_X1, 8, 12>(C);
  if (!FIRST) nb_arrive(N_KRDY, 256);
  TR(2, b, 1);
  if (!LAST) mbar_wait(bar + (B_FULL + 0) * 8, pa ^ 1);
  if (w) mbar_wait(bar + B_VFREE * 8, pa);
  TR(2, b, 10);
  if (!FIRST) dump12<128>(c.vC ^ vx, pv);
  if (!LAST) dump12<256>(c.qC ^ qx, pq);
  if (c.hvalid) dump12<128>(c.vH ^ vx, hv);
  if (LAST) { fence_async(); nb_arrive(N_VQ0, 256); nb_arrive(N_VQ1, 256); return; }
  dump12<128>((c.vC ^ vx ^ 16) + 768, pv2);
  TR(2, b, 11);
  wg_wait<0>(); pin(C);
  TR(2, b, 12);
  release_stage<1, 24576>(c, b < 11);
  pack12(pk, C, 0);
  pack12(pv, C, 24);
  pack12(pq, C, 48);
}

__device__ __forceinline__ float fold(float a, float b, float t, int useb) {
  float r;
  asm("{\n.reg .pred p;\nsetp.ne.b32 p, %4, 0;\nfma.rn.f32 %0, %1, 0f3E553B95, %3;\n@p fma.rn.f32 %0, %2, 0f3E553B95, %3;\n}"
      : "=&f"(r) : "f"(a), "f"(b), "f"(t), "r"(useb));
  return r;
}
template <int U, int L>
__device__ __forceinline__ void softmax_tile(const float (&SA)[56], const float (&SB)[56], const float (&T)[16], int b0, int b1,
                                             uint32_t (&P)[28], float (&sx)[8]) {
  float lu[14], ll[14];
#pragma unroll
  for (int j = 0; j < 7; j++) {
    constexpr int sh = U == L ? 2 : 0;
    const float tu0 = T[2 * j + sh], tu1 = T[2 * j + 1 + sh], tl0 = T[2 * j], tl1 = T[2 * j + 1];
    lu[2 * j]     = fold(SA[4 * (U + j)],     SB[4 * (U + j)],     tu0, b0);
    ll[2 * j]     = fold(SA[4 * (L + j) + 2], SB[4 * (L + j) + 2], tl0, b0);
    lu[2 * j + 1] = fold(SA[4 * (U + j) + 1], SB[4 * (U + j) + 1], tu1, b1);
    ll[2 * j + 1] = fold(SA[4 * (L + j) + 3], SB[4 * (L + j) + 3], tl1, b1);
  }
  float mu = lu[0], ml = ll[0], mu2 = lu[1], ml2 = ll[1];
#pragma unroll
  for (int j = 1; j < 7; j++) { mu = fmaxf(mu, lu[2 * j]); mu2 = fmaxf(mu2, lu[2 * j + 1]); ml = fmaxf(ml, ll[2 * j]); ml2 = fmaxf(ml2, ll[2 * j + 1]); }
  mu = fmaxf(mu, mu2); ml = fmaxf(ml, ml2);
  { const float a1 = __shfl_xor_sync(0xffffffffu, mu, 1), a2 = __shfl_xor_sync(0xffffffffu, mu, 2), a3 = __shfl_xor_sync(0xffffffffu, mu, 3);
    const float c1 = __shfl_xor_sync(0xffffffffu, ml, 1), c2 = __shfl_xor_sync(0xffffffffu, ml, 2), c3 = __shfl_xor_sync(0xffffffffu, ml, 3);
    mu = fmaxf(fmaxf(mu, a1), fmaxf(a2, a3)); ml = fmaxf(fmaxf(ml, c1), fmaxf(c2, c3)); }
  float su = 0.f, sl = 0.f;
#pragma unroll
  for (int c = 0; c < 14; c++) {
    const int iu = (c >> 1) * 4 + (c & 1) * 2;
    if (c >= U && c < U + 7) {
      float e0 = ex2(lu[2 * (c - U)] - mu), e1 = ex2(lu[2 * (c - U) + 1] - mu);
      su = c == U ? e0 + e1 : (su + e0) + e1; P[iu] = pack2(e0, e1);
    } else P[iu] = 0u;
    if (c >= L && c < L + 7) {
      float e0 = ex2(ll[2 * (c - L)] - ml), e1 = ex2(ll[2 * (c - L) + 1] - ml);
      sl = c == L ? e0 + e1 : (sl + e0) + e1; P[iu + 1] = pack2(e0, e1);
    } else P[iu + 1] = 0u;
  }
  sx[0] = su; sx[4] = sl;
#pragma unroll
  for (int k = 1; k < 4; k++) { sx[k] = __shfl_xor_sync(0xffffffffu, su, k); sx[4 + k] = __shfl_xor_sync(0xffffffffu, sl, k); }
}

struct Maps { CUtensorMap xc, xh, w, os, wo, ot; };

__global__ void __cluster_dims__(4, 1, 1) __launch_bounds__(512, 1)
na_attn_kernel(const __nv_bfloat16* __restrict__ x, const __nv_bfloat16* __restrict__ wqkv, const __nv_bfloat16* __restrict__ rpb, const __grid_constant__ Maps mp) {
  extern __shared__ __align__(1024) uint8_t smem_raw[];
  const uint32_t sb = smem_u32(smem_raw);
  if ((sb & 0x3FFFF) != SBC) return;
  const uint32_t bar = sb + SM_BAR;
  TR2(blockIdx.x, 0);
  const int tid = threadIdx.x, lane = tid & 31;
  const int warp = __shfl_sync(0xffffffffu, tid >> 5, 0);
  const int head = blockIdx.x & 3, cl = blockIdx.x >> 2;
  const int par = cl / 7, strip = cl - par * 7, ph = par >> 1, pw = par & 1;

  uint4 wv[2 * NL];
  const int va = head == 1;
  const uint32_t wdst = sb + SM_W + (va + ((tid >> 1) & 1)) * 6144 + (tid >> 2) * 32 + ((tid ^ (tid >> 4)) & 1) * 16;
  if (warp < 12) asm volatile("barrier.cluster.arrive.relaxed.aligned;" ::: "memory");
  {
    const uint32_t wo0 = (tid >> 2) * 1152 + head * 96 + va * 32 + (tid & 3) * 16;
#pragma unroll
    for (int i = 0; i < 2 * NL; i++)
      asm volatile("{\n.reg .pred p;\nsetp.lt.u32 p, %5, 384;\n@p ld.global.nc.v4.b32 {%0,%1,%2,%3}, [%4];\n}"
                   : "=r"(wv[i].x), "=r"(wv[i].y), "=r"(wv[i].z), "=r"(wv[i].w)
                   : "l"(reinterpret_cast<const uint8_t*>(wqkv) + wo0 + (i & 1) * 96 * 1152 + ((i / 2 + 1) % 3) * 384), "r"(tid));
  }
  if (warp < 8) {
    asm volatile("setmaxnreg.inc.sync.aligned.u32 %0;" ::"n"(RA));
    float rv = -INFINITY;
    if (tid < 169) rv = __bfloat162float(rpb[head * 169 + tid]) * 1.4426950408889634f;
    if (tid < 192) {
      const int kc = (tid & 15) + 3, wc = (tid >> 4) % 6;
      sts128(tid < 96 ? sb + SM_K + kc * KS + wc * 128 + 48 : sb + SM_V + kc * 1536 + wc * 128 + (6 + (kc & 1)) * 16, make_uint4(0, 0, 0, 0));
    }
#pragma unroll
    for (int i = 0; i < 2 * NL; i++) sts128(wdst + (i & 1) * 3072 + (i / 2) * 18432, wv[i]);
    fence_async();
    asm volatile("bar.arrive 1, 384;" ::: "memory");
    if (tid < 182) asm volatile("st.shared.f32 [%0], %1;" ::"r"(sb + SM_RPB + tid * 4), "f"(rv) : "memory");
    const int j = warp >> 2, w = warp & 3;
    int variant = w;
    if (strip == 0 && j == 0 && w < 2) variant = 4;
    if (strip == 6 && j == 1 && w >= 2) variant = 5;
    const uint32_t qa = sb + SM_Q + (8 * j + 2 * w + ((lane >> 3) & 1)) * 1536 + (lane >> 4) * 256 + (((lane & 7) * 16) ^ (((lane >> 3) & 1) * 64));
    uint32_t oa = sb + SM_O + j * 6144 + (2 * w + ((lane >> 3) & 1)) * 768 + (lane >> 4) * 128 + (lane & 7) * 16;
    const uint64_t dK = mkdesc(SBC + SM_K, 128, KS, 0) + j * (8 * KS / 16);
    const uint64_t dV = mkdesc(SBC + SM_V, 768, 128, 0) + j * (8 * 1536 / 16);
    asm volatile("barrier.cluster.wait.aligned;" ::: "memory");
    asm volatile("bar.sync 3, 256;" ::: "memory");
    float T[16];
    TRDECL;
    int b0 = 0, b1 = 0;
    uint32_t meta = 0;
    uint32_t q[12];
    mbar_wait(bar + B_Q0 * 8, 0);
#pragma unroll
    for (int k = 0; k < 3; k++) ldsm4(qa + k * 512, q[4 * k], q[4 * k + 1], q[4 * k + 2], q[4 * k + 3]);
#pragma unroll 1
    for (int b = 0; b < 14; b++) {
      const uint32_t pa = b & 1;
      float SA[56], SB[56];
      const uint64_t dA = dK + pa * (KSLOT >> 4), dB = dK + (pa ^ 1) * (KSLOT >> 4);
      TR(0, b, 0);
      nb_sync(N_KRDY + j, 256);
      TR(0, b, 1);
      TR(0, b - 1, 9);
      wg_fence();
      wg_rs112<0>(SA, q[0], q[1], q[2], q[3], dA);
      wg_rs112<0>(SB, q[0], q[1], q[2], q[3], dB);
      wg_rs112<1>(SA, q[4], q[5], q[6], q[7], dA + 16);
      wg_rs112<1>(SB, q[4], q[5], q[6], q[7], dB + 16);
      wg_rs112<1>(SA, q[8], q[9], q[10], q[11], dA + 32);
      wg_rs112<1>(SB, q[8], q[9], q[10], q[11], dB + 32);
      wg_commit();
      nb_arrive(N_QK0 + j, 256);
      TR(0, b, 2);
      if (b <= 1 || b == 13) {
        uint32_t ln; asm volatile("mov.u32 %0, %%laneid;" : "=r"(ln));
        const int g = ln >> 2, t = ln & 3;
        const int sw = b == 0 ? max(g + 1, 4) : (b == 13 ? min(g + 1, 5) : g + 1);
        const int i0 = 2 * t, i1 = 2 * t + 1;
        b0 = i0 <= sw - 2; b1 = i1 <= sw - 2;
        const uint32_t tb = sb + SM_RPB + (variant < 4 ? 3 : variant + 1 - 2 * w) * 4;
        const uint32_t ra0 = tb + (i0 == sw - 1 ? 13 : i0 + 8 * b0 - g + 2) * 52;
        const uint32_t ra1 = tb + (i1 == sw - 1 ? 13 : i1 + 8 * b1 - g + 2) * 52;
#pragma unroll
        for (int jj = 0; jj < 8; jj++) { T[2 * jj] = lds_f32(ra0 + jj * 4); T[2 * jj + 1] = lds_f32(ra1 + jj * 4); }
        meta = ((0x5555u & ((1u << (2 * (sw - 1))) - 1)) ^ 0xDD88u ^ (((t ^ b) & 1) ? 0x5555u : 0u)) * 0x10001u;
      } else meta ^= 0x55555555u;
      if (b >= 12) oa += b == 12 ? warp * 1536 - (SM_O - SM_Q) : 1536;
      wg_wait<0>(); pin(SA); pin(SB);
      mbar_arrive_elect(bar + B_KFREE * 8);
      TR(0, b, 3);
      TR(0, b - 1, 10);
      uint32_t P[28];
      float sx[8];
      switch (variant) {
        case 0: softmax_tile<0, 1>(SA, SB, T, b0, b1, P, sx); break;
        case 1: softmax_tile<2, 3>(SA, SB, T, b0, b1, P, sx); break;
        case 2: softmax_tile<4, 5>(SA, SB, T, b0, b1, P, sx); break;
        case 3: softmax_tile<6, 7>(SA, SB, T, b0, b1, P, sx); break;
        case 4: softmax_tile<3, 3>(SA, SB, T, b0, b1, P, sx); break;
        default: softmax_tile<4, 4>(SA, SB, T, b0, b1, P, sx); break;
      }
      float O[24];
      TR(0, b, 4);
      nb_sync(N_VQ0 + j, b == 13 ? 256 : 288);
      TR(0, b, 5);
#pragma unroll
      for (int k = 0; k < 3; k++) ldsm4(qa + (pa ^ 1) * 128 + k * 512, q[4 * k], q[4 * k + 1], q[4 * k + 2], q[4 * k + 3]);
      wg_fence();
      wg_sp48<0>(O, P[0], P[1], P[2], P[3], dV, meta);
#pragma unroll
      for (int s = 1; s < 7; s++) wg_sp48<1>(O, P[4 * s], P[4 * s + 1], P[4 * s + 2], P[4 * s + 3], dV + s * 192, meta);
      wg_commit();
      if (b != 12) nb_arrive(N_PVISS, 384);
      TR(0, b, 6);
      wg_wait<0>(); pin(O);
      mbar_arrive_elect(bar + B_VFREE * 8);
      TR(0, b, 7);
      float ru, rl;
      asm("rcp.approx.ftz.f32 %0, %1;" : "=f"(ru) : "f"(((fmaf(O[0], 0.f, sx[0]) + sx[1]) + sx[2]) + sx[3]));
      asm("rcp.approx.ftz.f32 %0, %1;" : "=f"(rl) : "f"(((fmaf(O[2], 0.f, sx[4]) + sx[5]) + sx[6]) + sx[7]));
#pragma unroll
      for (int i = 0; i < 3; i++)
        stsm4(oa + i * 256, pack2(O[8 * i] * ru, O[8 * i + 1] * ru), pack2(O[8 * i + 2] * rl, O[8 * i + 3] * rl),
              pack2(O[8 * i + 4] * ru, O[8 * i + 5] * ru), pack2(O[8 * i + 6] * rl, O[8 * i + 7] * rl));
      if (b < 13) publish(bar + (b < TB ? B_ODONE : B_OTAIL + j) * 8);
      else {
        fence_async();
        mbar_wait(bar + (B_TFREE + 1) * 8, 0);
        __syncwarp();
        if (elect_one()) {
#pragma unroll
          for (int d = 0; d < 2; d++)
            send_o<1536>(sb + SM_X0 + head * 6144 + (2 * j + (w & 1)) * 1536, sb + SM_Q + warp * 3072 + 1536, bar + (B_TIN + 2) * 8, (w & 2) + (d ^ (head & 1)));
        }
        __syncwarp();
      }
      TR(0, b, 8);
    }
    TRDUMP;
    cluster_sync();
  } else if (warp < 12) {
    TRDECL;
    TR(2, -3, 0);
    asm volatile("setmaxnreg.inc.sync.aligned.u32 %0;" ::"n"(RG));
    TR(2, -3, 1);
    GemmCtx c;
    c.bar = bar;
    const int gw = warp - 8, tk = gw * 16 + (lane & 15), hi = lane >> 4;
    { const int col = tk >> 2, i = tk & 3;
      c.kC = sb + SM_K + (col + 3) * KS + hi * 128 + i * 16;
      c.vC = sb + SM_V + (col + 3) * 1536 + hi * 128 + (2 * i + ((col + 3) & 1)) * 16;
      c.qC = sb + SM_Q + col * 1536 + hi * 256 + (col & 1) * 64 + i * 16; }
    { const int ci = (tk >> 3) - 2, kc = ci < 3 ? ci : ci + 16, i = tk & 7; c.hvalid = gw > 0;
      c.kH = sb + SM_K + kc * KS + hi * 128 + i * 16;
      c.vH = sb + SM_V + kc * 1536 + hi * 128 + (i >> 2) * 768 + (2 * (i & 3) + ((kc ^ (i >> 2)) & 1)) * 16; }
    asm volatile("barrier.cluster.wait.aligned;" ::: "memory");
    TR(2, -3, 2);
    if (elect_one()) { mbar_expect(bar + B_FULL * 8, 4608); mbar_expect(bar + (B_FULL + 1) * 8, 6144); mbar_expect(bar + (B_FULL + 2) * 8, 6144); }
    __syncwarp();
#pragma unroll
    for (int i = 0; i < 2 * NL; i++) sts128(wdst + (i & 1) * 3072 + (i / 2) * 18432, wv[i]);
    fence_async();
    TR(2, -3, 3);
    asm volatile("bar.sync 1, 384;" ::: "memory");
    TR(2, -3, 4);
    mbar_wait(bar + B_WK * 8, 0);
    TR(2, -3, 5);
    uint32_t pk[12], pv[12], pq[12];
    gemm_iter<true, false>(c, -2, pk, pv, pq, &mp.wo TRPASS);
    TR2(blockIdx.x, 4);
#pragma unroll 1
    for (int b = -1; b < 12; b++) gemm_iter<false, false>(c, b, pk, pv, pq, &mp.wo TRPASS);
    TR2(blockIdx.x, 6);
    gemm_iter<false, true>(c, 12, pk, pv, pq, &mp.wo TRPASS);
    TR(2, 13, 0);
    mbar_wait(bar + B_WO * 8, 0);
    TR(2, 13, 1);
    const uint32_t st = sb + SM_TST + gw * 3072;
    const uint32_t sta = st + (lane & 15) * 64 + ((hi ^ ((lane >> 1) & 3)) * 16);
#pragma unroll 1
    for (int i = 0; i < 3; i++) {
      constexpr uint64_t db = mkdesc(SBC + SM_TWO, 12288, 512, 2);
      const uint64_t da = mkdesc(SBC, 128, 768, 0) + (i ^ (i < 2)) * (24576 / 16);
      float D[48];
      mbar_wait(bar + (B_TIN + i) * 8, 0);
      if (i == 2) asm volatile("barrier.cluster.arrive.relaxed.aligned;" ::: "memory");
      else nb_sync(i ? N_PVISS : N_QK1, i ? 384 : 256);
      TR(2, 13 - i, 2); TR(2, 12 + i, 5); TR(2, 11 + i, 9);
      wg_fence();
      wg_ss96<0>(D, da, db);
#pragma unroll
      for (int k = 1; k < 12; k++) wg_ss96<1>(D, da + (k / 3) * 384 + (k % 3) * 16, db + k * 64);
      wg_commit();
      if (lane == 0) asm volatile("cp.async.bulk.wait_group.read 0;" ::: "memory");
      __syncwarp();
      wg_wait<0>(); pin(D);
      TR(2, 13 - i, 3); TR(2, 12 + i, 6); TR(2, 11 + i, 10);
#pragma unroll
      for (int q = 0; q < 6; q++)
        stsm4((sta ^ ((q & 1) * 32)) + (q >> 1) * 1024,
              pack2(D[8 * q], D[8 * q + 1]), pack2(D[8 * q + 2], D[8 * q + 3]), pack2(D[8 * q + 4], D[8 * q + 5]), pack2(D[8 * q + 6], D[8 * q + 7]));
      fence_async();
      __syncwarp();
      if (lane == 0) {
        asm volatile("cp.async.bulk.tensor.4d.global.shared::cta.bulk_group [%0, {%2,%3,%4,%5}], [%1];"
                     ::"l"(&mp.ot), "r"(st), "r"(0), "r"(8 * (TB + i)), "r"(ph * 112 + strip * 16 + 8 * (gw >> 1) + 4 * (head >> 1) + 2 * (gw & 1)), "r"(pw * 6 + (head & 1) * 3) : "memory");
        asm volatile("cp.async.bulk.commit_group;" ::: "memory");
      }
      TR(2, 13 - i, 4); TR(2, 12 + i, 7); TR(2, 11 + i, 11);
    }
    if (lane == 0) asm volatile("cp.async.bulk.wait_group.read 0;" ::: "memory");
    __syncwarp();
    TR(2, 13, 8);
    TR2(blockIdx.x, 2);
    TRDUMP;
    asm volatile("barrier.cluster.wait.aligned;" ::: "memory");
  } else {
    if (warp == 12) {
      if (elect_one()) {
        mbar_init(bar + B_WK * 8, 1);
#pragma unroll
        for (int i = 0; i < NL; i++) load_w(&mp.w, sb + SM_W + (3 * i + 2 - 2 * va) * 6144, bar + B_WK * 8, ((i + 1) % 3) * 192 + head * 48 + 32 - 32 * va);
        asm volatile("prefetch.tensormap [%0];" ::"l"(head ? &mp.xc : &mp.xh) : "memory");
        mbar_expect(bar + B_WK * 8, NL * 6144);
      }
    } else if (warp == 15) {
      const int col = min(max(strip * 16 - 3 + min(lane, 21), 0), 111);
      const uint8_t* p = reinterpret_cast<const uint8_t*>(x) + (uint32_t)(head * ROWB + (ph * 112 + col) * 768 + pw * 384);
#pragma unroll
      for (int i = 0; i < 3; i++) asm volatile("prefetch.global.L2 [%0];" ::"l"(p + i * 128));
    } else if (elect_one()) {
      if (warp == 13) {
#pragma unroll
        for (int i = 0; i < B_WK; i++) mbar_init(bar + i * 8, i < B_EMPTY ? 4 : (i < B_TIN ? 16 : (i < B_TFREE ? 1 : 16)));
      } else {
#pragma unroll
        for (int i = B_WQ; i < B_COUNT; i++) mbar_init(bar + i * 8, i < B_Q0 ? 1 : (i < B_ODONE ? 4 : 8));
      }
    }
    asm volatile("fence.mbarrier_init.release.cluster;" ::: "memory");
    __syncwarp();
    asm volatile("barrier.cluster.arrive.relaxed.aligned;" ::: "memory");
    asm volatile("setmaxnreg.dec.sync.aligned.u32 24;");
    asm volatile("griddepcontrol.launch_dependents;");
    const int cc = ph * 112 + (head ? strip * 16 : (strip == 0 ? 16 : (strip == 6 ? 74 : strip * 16 - 3)));
    const int sd = strip == 0 ? -1 : (strip == 6 ? 1 : 0);
    const int r0 = head == 0 ? -4 : (head == 1 ? 4 : 0);
    asm volatile("barrier.cluster.wait.aligned;" ::: "memory");
    if (warp == 12) {
      const uint32_t fb = bar + (B_FULL + head) * 8, eb = bar + (B_EMPTY + head) * 8;
      const uint32_t dst = sb + (head == 0 ? SM_X0 : (head == 1 ? SM_X1 : SM_X2));
      const int nl = head == 0 ? 15 : (head == 3 ? 1 : 14);
#pragma unroll 1
      for (int n = 0; n < nl; n++) {
        if (n) mbar_wait(eb, (n - 1) & 1);
        if (elect_one()) {
          if (head == 0) {
            asm volatile("cp.async.bulk.tensor.5d.shared::cluster.global.mbarrier::complete_tx::bytes.multicast::cluster [%0], [%1, {%3,%4,%5,%6,%7}], [%2], %8;"
                         ::"r"(dst), "l"(&mp.xh), "r"(fb), "r"(0), "r"(8 * n + r0), "r"(cc), "r"(sd), "r"(pw * 3), "h"((uint16_t)15) : "memory");
          } else if (head < 3) {
            asm volatile("cp.async.bulk.tensor.4d.shared::cluster.global.mbarrier::complete_tx::bytes.multicast::cluster [%0], [%1, {%3,%4,%5,%6}], [%2], %7;"
                         ::"r"(dst), "l"(&mp.xc), "r"(fb), "r"(0), "r"(8 * n + r0), "r"(cc), "r"(pw * 3), "h"((uint16_t)15) : "memory");
          }
          if (n == 0) {
#pragma unroll
            for (int i = 0; i < 3; i++) load_w(&mp.w, sb + SM_W + (6 + i) * 6144, bar + B_WQ * 8, head * 48 + i * 16);
            mbar_expect(bar + B_WQ * 8, 18432);
            mbar_expect(bar + B_TIN * 8, 24576); mbar_expect(bar + (B_TIN + 1) * 8, 24576); mbar_expect(bar + (B_TIN + 2) * 8, 24576);
          }
          if (!head && n + 1 < nl) asm volatile("cp.async.bulk.prefetch.tensor.5d.L2.global [%0, {%1,%2,%3,%4,%5}];" ::"l"(&mp.xh), "r"(0), "r"(8 * n + 8 + r0), "r"(cc), "r"(sd), "r"(pw * 3) : "memory");
          if (head && n + 1 < nl) asm volatile("cp.async.bulk.prefetch.tensor.4d.L2.global [%0, {%1,%2,%3,%4}];" ::"l"(&mp.xc), "r"(0), "r"(8 * n + 8 + r0), "r"(cc), "r"(pw * 3) : "memory");
        }
        __syncwarp();
      }
    }
    if (warp == 14) {
      int* flag = g_flags + cl * 2;
      nb_arrive(N_VQ0, 288); nb_arrive(N_VQ1, 288);
#pragma unroll 1
      for (int b = 0; b < TB; b++) {
        mbar_wait(bar + B_ODONE * 8, b & 1);
        if (lane == 0) {
          asm volatile("cp.async.bulk.tensor.3d.global.shared::cta.bulk_group [%0, {%2,%3,%4}], [%1];"
                       ::"l"(&mp.os), "r"(sb + SM_O), "r"(pw * 192), "r"(8 * b + 2 * head), "r"(ph * 112 + strip * 16) : "memory");
          asm volatile("cp.async.bulk.commit_group;\ncp.async.bulk.wait_group 0;" ::: "memory");
        }
        __syncwarp();
        nb_arrive(N_VQ0, 288); nb_arrive(N_VQ1, 288);
        if (lane == 0)
          asm volatile("fence.proxy.async.global;\nfence.acq_rel.gpu;\nred.relaxed.gpu.global.add.s32 [%0], 1;\nred.relaxed.gpu.global.add.s32 [%0+4], 1;"
                       ::"l"(flag + b * 56) : "memory");
        __syncwarp();
      }
    } else if (warp & 1) {
      const int j = (warp >> 1) & 1;
#pragma unroll 1
      for (int i = 0; i < 2; i++) {
        mbar_wait(bar + (B_OTAIL + j) * 8, i);
        if (i == 0) nb_arrive(N_VQ0 + j, 288);
        mbar_wait(bar + (B_TFREE + i) * 8, 0);
        if (elect_one()) {
#pragma unroll 1
          for (int d = 0; d < 8; d++) {
            const int dst = (d + head) & 3, pc = d >> 2;
            send_o<1536>(sb + (i ? SM_X1 : SM_X2) + head * 6144 + j * 3072 + pc * 1536,
                         sb + (i ? SM_Q : SM_O) + (4 * j + (dst & 2) + pc) * (i ? 3072 : 1536), bar + (B_TIN + i) * 8, dst);
          }
        }
        __syncwarp();
      }
    }
    cluster_sync();
  }
}

constexpr int NSTB = 6;
constexpr int NTB = TB * 56;
constexpr int SM_B_IN = 0;
constexpr int SM_B_W = SM_B_IN + NSTB * 24576;
constexpr int SM_B_BAR = SM_B_W + 73728;
constexpr int SM_B_TOTAL = SM_B_BAR + 128;
struct MapsB { CUtensorMap oi, oo, wo; };

__global__ void __launch_bounds__(480, 1)
na_proj_kernel(const __grid_constant__ MapsB mp) {
  extern __shared__ __align__(1024) uint8_t smem_raw[];
  const uint32_t sb = smem_u32(smem_raw);
  if ((sb & 0x3FFFF) != SBC) return;
  const uint32_t bar = sb + SM_B_BAR;
  const int tid = threadIdx.x, lane = tid & 31;
  const int warp = __shfl_sync(0xffffffffu, tid >> 5, 0);
  TR2(132 + blockIdx.x, 0);
  TRB(47, 0);
  if (warp == 12 && elect_one()) {
#pragma unroll
    for (int i = 0; i <= 2 * NSTB; i++) mbar_init(bar + i * 8, i < NSTB || i == 2 * NSTB ? 1 : 4);
    mbar_expect(bar + 2 * NSTB * 8, 73728);
#pragma unroll
    for (int i = 0; i < 2; i++)
      asm volatile("cp.async.bulk.tensor.3d.shared::cluster.global.mbarrier::complete_tx::bytes [%0], [%1, {%3,%4,%5}], [%2];"
                   ::"r"(sb + SM_B_W + i * 36864), "l"(&mp.wo), "r"(bar + 2 * NSTB * 8), "r"(0), "r"(0), "r"(i * 3) : "memory");
  }
  __syncthreads();
  const int step = gridDim.x;
  if (warp >= 12) {
    const int wg = warp - 12;
    int use = 0;
#pragma unroll 1
    for (int n = blockIdx.x + wg * step; n < NTB; n += 3 * step, use++) {
      const int b = n / 56, rem = n - b * 56, par = rem / 14, sg = wg + 3 * (use & 1);
      int v; uint32_t spin = 0;
      do { asm volatile("ld.acquire.gpu.global.s32 %0, [%1];" : "=r"(v) : "l"(g_flags + n) : "memory"); } while (v < 4 && ++spin < SPIN_LIMIT);
      TRB(use * 3 + wg, 0);
      asm volatile("fence.proxy.async.global;" ::: "memory");
      if (use >= 2) mbar_wait(bar + (NSTB + sg) * 8, ((use >> 1) - 1) & 1);
      TRB(use * 3 + wg, 1);
      if (elect_one()) {
        mbar_expect(bar + sg * 8, 24576);
        asm volatile("cp.async.bulk.tensor.3d.shared::cluster.global.mbarrier::complete_tx::bytes [%0], [%1, {%3,%4,%5}], [%2];"
                     ::"r"(sb + SM_B_IN + sg * 24576), "l"(&mp.oi), "r"(bar + sg * 8), "r"((par & 1) * 192), "r"(8 * b), "r"((par >> 1) * 112 + (rem - par * 14) * 8) : "memory");
        g_flags[n] = 0;
      }
      __syncwarp();
    }
  } else {
    const int wg = warp >> 2, w = warp & 3;
    constexpr uint64_t db = mkdesc(SBC + SM_B_W, 12288, 512, 2);
    const uint32_t sta0 = sb + SM_B_IN + w * 6144 + (lane & 15) * 128 + (((lane >> 4) ^ (lane & 7)) * 16);
    mbar_wait(bar + 2 * NSTB * 8, 0);
    TRB(47, 1);
    int use = 0;
#pragma unroll 1
    for (int n = blockIdx.x + wg * step; n < NTB; n += 3 * step, use++) {
      const int b = n / 56, rem = n - b * 56, par = rem / 14, sg = wg + 3 * (use & 1);
      const uint64_t da = mkdesc(SBC + SM_B_IN, 128, 3072, 0) + sg * (24576 / 16);
      float D[96];
      mbar_wait(bar + sg * 8, (use >> 1) & 1);
      if (use | wg) nb_sync(4 + wg, 256);
      TRB(use * 3 + wg, 3);
      wg_fence();
      wg_ss192<0>(D, da, db);
#pragma unroll
      for (int k = 1; k < 12; k++) wg_ss192<1>(D, da + k * 16, db + k * 64);
      wg_commit();
      if (n + step < NTB) nb_arrive(wg == 2 ? 4 : 5 + wg, 256);
      TRB(use * 3 + wg, 4);
      if (use && lane == 0) {
        asm volatile("cp.async.bulk.wait_group.read 0;" ::: "memory");
        mbar_arrive(bar + (NSTB + wg + 3 * (~use & 1)) * 8);
      }
      __syncwarp();
      wg_wait<0>(); pin(D);
      nb_sync(1 + wg, 128);
      TRB(use * 3 + wg, 5);
      const uint32_t sta = sta0 + sg * 24576;
#pragma unroll
      for (int q = 0; q < 12; q++)
        stsm4((sta ^ ((q & 3) * 32)) + (q >> 2) * 2048,
              pack2(D[8 * q], D[8 * q + 1]), pack2(D[8 * q + 2], D[8 * q + 3]), pack2(D[8 * q + 4], D[8 * q + 5]), pack2(D[8 * q + 6], D[8 * q + 7]));
      fence_async();
      __syncwarp();
      if (lane == 0) {
        asm volatile("cp.async.bulk.tensor.4d.global.shared::cta.bulk_group [%0, {%2,%3,%4,%5}], [%1];"
                     ::"l"(&mp.oo), "r"(sb + SM_B_IN + sg * 24576 + w * 6144), "r"(0), "r"(8 * b), "r"((par >> 1) * 112 + (rem - par * 14) * 8 + 2 * w), "r"((par & 1) * 3) : "memory");
        asm volatile("cp.async.bulk.commit_group;" ::: "memory");
      }
      __syncwarp();
      TRB(use * 3 + wg, 6);
    }
    if (lane == 0) asm volatile("cp.async.bulk.wait_group 0;" ::: "memory");
    TR2(132 + blockIdx.x, 2);
  }
}

typedef CUresult (*EncodeFn)(CUtensorMap*, CUtensorMapDataType, cuuint32_t, void*, const cuuint64_t*, const cuuint64_t*, const cuuint32_t*,
                             const cuuint32_t*, CUtensorMapInterleave, CUtensorMapSwizzle, CUtensorMapL2promotion, CUtensorMapFloatOOBfill);
static EncodeFn g_enc = nullptr;
static void make_map(CUtensorMap* m, const void* p, int rank, const cuuint64_t* dim, const cuuint64_t* str, const cuuint32_t* box, CUtensorMapSwizzle sw) {
  const cuuint32_t ones[5] = {1, 1, 1, 1, 1};
  g_enc(m, CU_TENSOR_MAP_DATA_TYPE_BFLOAT16, rank, (void*)p, dim, str, box, ones, CU_TENSOR_MAP_INTERLEAVE_NONE, sw,
        CU_TENSOR_MAP_L2_PROMOTION_L2_128B, CU_TENSOR_MAP_FLOAT_OOB_FILL_NONE);
}

extern "C" void kernel_launch(void* const* d_in, const int* in_sizes, int n_in, void* d_out, int out_size) {
  const __nv_bfloat16* x = (const __nv_bfloat16*)d_in[0];
  const __nv_bfloat16* wqkv = (const __nv_bfloat16*)d_in[1];
  const __nv_bfloat16* wo = (const __nv_bfloat16*)d_in[2];
  const __nv_bfloat16* rpb = (const __nv_bfloat16*)d_in[3];

  if (!g_enc) {
    void* fn = nullptr; cudaDriverEntryPointQueryResult qr;
    cudaGetDriverEntryPoint("cuTensorMapEncodeTiled", &fn, cudaEnableDefault, &qr);
    g_enc = (EncodeFn)fn;
    cudaFuncSetAttribute(na_attn_kernel, cudaFuncAttributeMaxDynamicSharedMemorySize, SM_A_TOTAL);
    cudaFuncSetAttribute(na_proj_kernel, cudaFuncAttributeMaxDynamicSharedMemorySize, SM_B_TOTAL);
  }
  Maps ma; MapsB mb;
  { cuuint64_t dim[4] = {64, 112, 224, 6}, str[3] = {(cuuint64_t)ROWB, 768, 128};
    cuuint32_t box[4] = {64, 4, 16, 3}, boxo[4] = {64, 8, 2, 3};
    make_map(&ma.xc, x, 4, dim, str, box, CU_TENSOR_MAP_SWIZZLE_128B);
    make_map(&mb.oo, d_out, 4, dim, str, boxo, CU_TENSOR_MAP_SWIZZLE_128B); }
  { cuuint64_t dim[5] = {64, 112, 224, 2, 6}, str[4] = {(cuuint64_t)ROWB, 768, 19 * 768, 128};
    cuuint32_t box[5] = {64, 8, 3, 2, 3};
    make_map(&ma.xh, x, 5, dim, str, box, CU_TENSOR_MAP_SWIZZLE_128B); }
  { cuuint64_t dim[3] = {384, 112, 224}, str[2] = {(cuuint64_t)ROWB, 768};
    cuuint32_t box[3] = {192, 8, 8}, boxs[3] = {192, 2, 16};
    make_map(&mb.oi, d_out, 3, dim, str, box, CU_TENSOR_MAP_SWIZZLE_NONE);
    make_map(&ma.os, d_out, 3, dim, str, boxs, CU_TENSOR_MAP_SWIZZLE_NONE); }
  { cuuint64_t dim[4] = {32, 112, 224, 12}, str[3] = {(cuuint64_t)ROWB, 768, 64};
    cuuint32_t box[4] = {32, 8, 2, 3};
    make_map(&ma.ot, d_out, 4, dim, str, box, CU_TENSOR_MAP_SWIZZLE_64B); }
  { cuuint64_t dim[2] = {576, 192}, str[1] = {1152};
    cuuint32_t box[2] = {16, 192};
    make_map(&ma.w, wqkv, 2, dim, str, box, CU_TENSOR_MAP_SWIZZLE_32B); }
  { cuuint64_t dim[3] = {32, 192, 6}, str[2] = {384, 64};
    cuuint32_t box[3] = {32, 192, 3};
    make_map(&ma.wo, wo, 3, dim, str, box, CU_TENSOR_MAP_SWIZZLE_64B);
    mb.wo = ma.wo; }
  na_attn_kernel<<<112, 512, SM_A_TOTAL>>>(x, wqkv, rpb, ma);
  cudaLaunchConfig_t cfg = {};
  cfg.gridDim = dim3(20); cfg.blockDim = dim3(480); cfg.dynamicSmemBytes = SM_B_TOTAL; cfg.stream = cudaStreamPerThread;
  cudaLaunchAttribute at[1];
  at[0].id = cudaLaunchAttributeProgrammaticStreamSerialization; at[0].val.programmaticStreamSerializationAllowed = 1;
  cfg.attrs = at; cfg.numAttrs = 1;
  cudaLaunchKernelEx(&cfg, na_proj_kernel, mb);
}
```

```cpp
#include <cuda_runtime.h>
#include <cuda_bf16.h>
#include <cuda.h>
#include <stdint.h>

#define SPIN_LIMIT (1u << 18)

__device__ __forceinline__ uint32_t smem_u32(const void* p) { return (uint32_t)__cvta_generic_to_shared(p); }
__device__ __forceinline__ void wg_fence() { asm volatile("wgmma.fence.sync.aligned;" ::: "memory"); }
__device__ __forceinline__ void wg_commit() { asm volatile("wgmma.commit_group.sync.aligned;" ::: "memory"); }
template <int N> __device__ __forceinline__ void wg_wait() { asm volatile("wgmma.wait_group.sync.aligned %0;" ::"n"(N) : "memory"); }
template <int N> __device__ __forceinline__ void pin(float (&d)[N]) {
#pragma unroll
  for (int i = 0; i < N; i++) asm volatile("" : "+f"(d[i])::"memory");
}
__host__ __device__ constexpr uint64_t mkdesc(uint32_t addr, uint32_t lbo, uint32_t sbo, uint32_t sw) {
  return (uint64_t)((addr & 0x3FFFF) >> 4) | ((uint64_t)(lbo >> 4) << 16) | ((uint64_t)(sbo >> 4) << 32) | ((uint64_t)sw << 62);
}
__device__ __forceinline__ void mbar_init(uint32_t bar, uint32_t cnt) { asm volatile("mbarrier.init.shared::cta.b64 [%0], %1;" ::"r"(bar), "r"(cnt) : "memory"); }
__device__ __forceinline__ void mbar_arrive(uint32_t bar) { asm volatile("mbarrier.arrive.shared::cta.b64 _, [%0];" ::"r"(bar) : "memory"); }
__device__ __forceinline__ bool elect_one() {
  uint32_t r; asm volatile("{\n.reg .pred p;\nelect.sync _|p, 0xffffffff;\nselp.u32 %0, 1, 0, p;\n}" : "=r"(r)); return r;
}
__device__ __forceinline__ void mbar_arrive_elect(uint32_t bar) {
  asm volatile("{\n.reg .pred p;\nelect.sync _|p, 0xffffffff;\n@p mbarrier.arrive.shared::cta.b64 _, [%0];\n}" ::"r"(bar) : "memory");
}
__device__ __forceinline__ void mbar_expect(uint32_t bar, uint32_t bytes) { asm volatile("mbarrier.arrive.expect_tx.shared::cta.b64 _, [%0], %1;" ::"r"(bar), "r"(bytes) : "memory"); }
__device__ __forceinline__ void mbar_arrive_remote(uint32_t bar, uint32_t cta) {
  asm volatile("{\n.reg .b32 ra;\nmapa.shared::cluster.u32 ra, %0, %1;\nmbarrier.arrive.relaxed.cluster.shared::cluster.b64 _, [ra];\n}" ::"r"(bar), "r"(cta) : "memory");
}
__device__ __forceinline__ void mbar_wait(uint32_t bar, uint32_t parity) {
  asm volatile("{\n.reg .pred p;\n.reg .b32 n;\nmov.b32 n, 0;\nWL:\nmbarrier.try_wait.parity.shared::cta.b64 p, [%0], %1;\n@p bra WD;\n"
               "add.u32 n, n, 1;\nsetp.lt.u32 p, n, 65536;\n@p bra WL;\nWD:\n}" ::"r"(bar), "r"(parity) : "memory");
}
__device__ __forceinline__ void nb_sync(int id, int n) { asm volatile("bar.sync %0, %1;" ::"r"(id), "r"(n) : "memory"); }
__device__ __forceinline__ void nb_arrive(int id, int n) { asm volatile("bar.arrive %0, %1;" ::"r"(id), "r"(n) : "memory"); }
__device__ __forceinline__ void fence_async() { asm volatile("fence.proxy.async.shared::cta;" ::: "memory"); }
__device__ __forceinline__ void cluster_sync() {
  asm volatile("barrier.cluster.arrive.relaxed.aligned;\nbarrier.cluster.wait.aligned;" ::: "memory");
}
__device__ __forceinline__ uint32_t pack2(float lo, float hi) {
  uint32_t r; asm("cvt.rn.bf16x2.f32 %0, %1, %2;" : "=r"(r) : "f"(hi), "f"(lo)); return r;
}
__device__ __forceinline__ void stsm4(uint32_t a, uint32_t r0, uint32_t r1, uint32_t r2, uint32_t r3) {
  asm volatile("stmatrix.sync.aligned.m8n8.x4.shared.b16 [%0], {%1,%2,%3,%4};" ::"r"(a), "r"(r0), "r"(r1), "r"(r2), "r"(r3) : "memory");
}
__device__ __forceinline__ void ldsm4(uint32_t a, uint32_t& r0, uint32_t& r1, uint32_t& r2, uint32_t& r3) {
  asm volatile("ldmatrix.sync.aligned.m8n8.x4.shared.b16 {%0,%1,%2,%3}, [%4];" : "=r"(r0), "=r"(r1), "=r"(r2), "=r"(r3) : "r"(a) : "memory");
}
__device__ __forceinline__ void sts128(uint32_t a, uint4 v) {
  asm volatile("st.shared.v4.b32 [%0], {%1,%2,%3,%4};" ::"r"(a), "r"(v.x), "r"(v.y), "r"(v.z), "r"(v.w) : "memory");
}
__device__ __forceinline__ float lds_f32(uint32_t a) { float v; asm volatile("ld.shared.f32 %0, [%1];" : "=f"(v) : "r"(a)); return v; }
__device__ __forceinline__ float ex2(float x) { float y; asm("ex2.approx.ftz.f32 %0, %1;" : "=f"(y) : "f"(x)); return y; }

template<int SC> __device__ __forceinline__ void wg_ss144(float (&d)[72], uint64_t da, uint64_t db) {
  asm volatile("{\n.reg .pred p;\nsetp.ne.b32 p, %74, 0;\nwgmma.mma_async.sync.aligned.m64n144k16.f32.bf16.bf16 {%0,%1,%2,%3,%4,%5,%6,%7,%8,%9,%10,%11,%12,%13,%14,%15,%16,%17,%18,%19,%20,%21,%22,%23,%24,%25,%26,%27,%28,%29,%30,%31,%32,%33,%34,%35,%36,%37,%38,%39,%40,%41,%42,%43,%44,%45,%46,%47,%48,%49,%50,%51,%52,%53,%54,%55,%56,%57,%58,%59,%60,%61,%62,%63,%64,%65,%66,%67,%68,%69,%70,%71}, %72, %73, p, 1, 1, 0, 1;\n}\n"
    : "+f"(d[0]),"+f"(d[1]),"+f"(d[2]),"+f"(d[3]),"+f"(d[4]),"+f"(d[5]),"+f"(d[6]),"+f"(d[7]),"+f"(d[8]),"+f"(d[9]),"+f"(d[10]),"+f"(d[11]),"+f"(d[12]),"+f"(d[13]),"+f"(d[14]),"+f"(d[15]),"+f"(d[16]),"+f"(d[17]),"+f"(d[18]),"+f"(d[19]),"+f"(d[20]),"+f"(d[21]),"+f"(d[22]),"+f"(d[23]),"+f"(d[24]),"+f"(d[25]),"+f"(d[26]),"+f"(d[27]),"+f"(d[28]),"+f"(d[29]),"+f"(d[30]),"+f"(d[31]),"+f"(d[32]),"+f"(d[33]),"+f"(d[34]),"+f"(d[35]),"+f"(d[36]),"+f"(d[37]),"+f"(d[38]),"+f"(d[39]),"+f"(d[40]),"+f"(d[41]),"+f"(d[42]),"+f"(d[43]),"+f"(d[44]),"+f"(d[45]),"+f"(d[46]),"+f"(d[47]),"+f"(d[48]),"+f"(d[49]),"+f"(d[50]),"+f"(d[51]),"+f"(d[52]),"+f"(d[53]),"+f"(d[54]),"+f"(d[55]),"+f"(d[56]),"+f"(d[57]),"+f"(d[58]),"+f"(d[59]),"+f"(d[60]),"+f"(d[61]),"+f"(d[62]),"+f"(d[63]),"+f"(d[64]),"+f"(d[65]),"+f"(d[66]),"+f"(d[67]),"+f"(d[68]),"+f"(d[69]),"+f"(d[70]),"+f"(d[71]) : "l"(da), "l"(db), "n"(SC));
}
template<int SC> __device__ __forceinline__ void wg_ss96(float (&d)[48], uint64_t da, uint64_t db) {
  asm volatile("{\n.reg .pred p;\nsetp.ne.b32 p, %50, 0;\nwgmma.mma_async.sync.aligned.m64n96k16.f32.bf16.bf16 {%0,%1,%2,%3,%4,%5,%6,%7,%8,%9,%10,%11,%12,%13,%14,%15,%16,%17,%18,%19,%20,%21,%22,%23,%24,%25,%26,%27,%28,%29,%30,%31,%32,%33,%34,%35,%36,%37,%38,%39,%40,%41,%42,%43,%44,%45,%46,%47}, %48, %49, p, 1, 1, 0, 1;\n}\n"
    : "+f"(d[0]),"+f"(d[1]),"+f"(d[2]),"+f"(d[3]),"+f"(d[4]),"+f"(d[5]),"+f"(d[6]),"+f"(d[7]),"+f"(d[8]),"+f"(d[9]),"+f"(d[10]),"+f"(d[11]),"+f"(d[12]),"+f"(d[13]),"+f"(d[14]),"+f"(d[15]),"+f"(d[16]),"+f"(d[17]),"+f"(d[18]),"+f"(d[19]),"+f"(d[20]),"+f"(d[21]),"+f"(d[22]),"+f"(d[23]),"+f"(d[24]),"+f"(d[25]),"+f"(d[26]),"+f"(d[27]),"+f"(d[28]),"+f"(d[29]),"+f"(d[30]),"+f"(d[31]),"+f"(d[32]),"+f"(d[33]),"+f"(d[34]),"+f"(d[35]),"+f"(d[36]),"+f"(d[37]),"+f"(d[38]),"+f"(d[39]),"+f"(d[40]),"+f"(d[41]),"+f"(d[42]),"+f"(d[43]),"+f"(d[44]),"+f"(d[45]),"+f"(d[46]),"+f"(d[47]) : "l"(da), "l"(db), "n"(SC));
}
template<int SC> __device__ __forceinline__ void wg_rs112(float (&d)[56], uint32_t a0, uint32_t a1, uint32_t a2, uint32_t a3, uint64_t db) {
  asm volatile("{\n.reg .pred p;\nsetp.ne.b32 p, %61, 0;\nwgmma.mma_async.sync.aligned.m64n112k16.f32.bf16.bf16 {%0,%1,%2,%3,%4,%5,%6,%7,%8,%9,%10,%11,%12,%13,%14,%15,%16,%17,%18,%19,%20,%21,%22,%23,%24,%25,%26,%27,%28,%29,%30,%31,%32,%33,%34,%35,%36,%37,%38,%39,%40,%41,%42,%43,%44,%45,%46,%47,%48,%49,%50,%51,%52,%53,%54,%55}, {%56,%57,%58,%59}, %60, p, 1, 1, 0;\n}\n"
    : "+f"(d[0]),"+f"(d[1]),"+f"(d[2]),"+f"(d[3]),"+f"(d[4]),"+f"(d[5]),"+f"(d[6]),"+f"(d[7]),"+f"(d[8]),"+f"(d[9]),"+f"(d[10]),"+f"(d[11]),"+f"(d[12]),"+f"(d[13]),"+f"(d[14]),"+f"(d[15]),"+f"(d[16]),"+f"(d[17]),"+f"(d[18]),"+f"(d[19]),"+f"(d[20]),"+f"(d[21]),"+f"(d[22]),"+f"(d[23]),"+f"(d[24]),"+f"(d[25]),"+f"(d[26]),"+f"(d[27]),"+f"(d[28]),"+f"(d[29]),"+f"(d[30]),"+f"(d[31]),"+f"(d[32]),"+f"(d[33]),"+f"(d[34]),"+f"(d[35]),"+f"(d[36]),"+f"(d[37]),"+f"(d[38]),"+f"(d[39]),"+f"(d[40]),"+f"(d[41]),"+f"(d[42]),"+f"(d[43]),"+f"(d[44]),"+f"(d[45]),"+f"(d[46]),"+f"(d[47]),"+f"(d[48]),"+f"(d[49]),"+f"(d[50]),"+f"(d[51]),"+f"(d[52]),"+f"(d[53]),"+f"(d[54]),"+f"(d[55]) : "r"(a0), "r"(a1), "r"(a2), "r"(a3), "l"(db), "n"(SC));
}
template<int SC> __device__ __forceinline__ void wg_sp48(float (&d)[24], uint32_t a0, uint32_t a1, uint32_t a2, uint32_t a3, uint64_t db, uint32_t meta) {
  asm volatile("{\n.reg .pred p;\nsetp.ne.b32 p, %30, 0;\nwgmma.mma_async.sp.sync.aligned.m64n48k32.f32.bf16.bf16 {%0,%1,%2,%3,%4,%5,%6,%7,%8,%9,%10,%11,%12,%13,%14,%15,%16,%17,%18,%19,%20,%21,%22,%23}, {%24,%25,%26,%27}, %28, %29, 0, p, 1, 1, 1;\n}\n"
    : "+f"(d[0]),"+f"(d[1]),"+f"(d[2]),"+f"(d[3]),"+f"(d[4]),"+f"(d[5]),"+f"(d[6]),"+f"(d[7]),"+f"(d[8]),"+f"(d[9]),"+f"(d[10]),"+f"(d[11]),"+f"(d[12]),"+f"(d[13]),"+f"(d[14]),"+f"(d[15]),"+f"(d[16]),"+f"(d[17]),"+f"(d[18]),"+f"(d[19]),"+f"(d[20]),"+f"(d[21]),"+f"(d[22]),"+f"(d[23]) : "r"(a0), "r"(a1), "r"(a2), "r"(a3), "l"(db), "r"(meta), "n"(SC));
}
template<int SC> __device__ __forceinline__ void wg_ss192(float (&d)[96], uint64_t da, uint64_t db) {
  asm volatile("{\n.reg .pred p;\nsetp.ne.b32 p, %98, 0;\nwgmma.mma_async.sync.aligned.m64n192k16.f32.bf16.bf16 {%0,%1,%2,%3,%4,%5,%6,%7,%8,%9,%10,%11,%12,%13,%14,%15,%16,%17,%18,%19,%20,%21,%22,%23,%24,%25,%26,%27,%28,%29,%30,%31,%32,%33,%34,%35,%36,%37,%38,%39,%40,%41,%42,%43,%44,%45,%46,%47,%48,%49,%50,%51,%52,%53,%54,%55,%56,%57,%58,%59,%60,%61,%62,%63,%64,%65,%66,%67,%68,%69,%70,%71,%72,%73,%74,%75,%76,%77,%78,%79,%80,%81,%82,%83,%84,%85,%86,%87,%88,%89,%90,%91,%92,%93,%94,%95}, %96, %97, p, 1, 1, 0, 1;\n}\n"
    : "+f"(d[0]),"+f"(d[1]),"+f"(d[2]),"+f"(d[3]),"+f"(d[4]),"+f"(d[5]),"+f"(d[6]),"+f"(d[7]),"+f"(d[8]),"+f"(d[9]),"+f"(d[10]),"+f"(d[11]),"+f"(d[12]),"+f"(d[13]),"+f"(d[14]),"+f"(d[15]),"+f"(d[16]),"+f"(d[17]),"+f"(d[18]),"+f"(d[19]),"+f"(d[20]),"+f"(d[21]),"+f"(d[22]),"+f"(d[23]),"+f"(d[24]),"+f"(d[25]),"+f"(d[26]),"+f"(d[27]),"+f"(d[28]),"+f"(d[29]),"+f"(d[30]),"+f"(d[31]),"+f"(d[32]),"+f"(d[33]),"+f"(d[34]),"+f"(d[35]),"+f"(d[36]),"+f"(d[37]),"+f"(d[38]),"+f"(d[39]),"+f"(d[40]),"+f"(d[41]),"+f"(d[42]),"+f"(d[43]),"+f"(d[44]),"+f"(d[45]),"+f"(d[46]),"+f"(d[47]),"+f"(d[48]),"+f"(d[49]),"+f"(d[50]),"+f"(d[51]),"+f"(d[52]),"+f"(d[53]),"+f"(d[54]),"+f"(d[55]),"+f"(d[56]),"+f"(d[57]),"+f"(d[58]),"+f"(d[59]),"+f"(d[60]),"+f"(d[61]),"+f"(d[62]),"+f"(d[63]),"+f"(d[64]),"+f"(d[65]),"+f"(d[66]),"+f"(d[67]),"+f"(d[68]),"+f"(d[69]),"+f"(d[70]),"+f"(d[71]),"+f"(d[72]),"+f"(d[73]),"+f"(d[74]),"+f"(d[75]),"+f"(d[76]),"+f"(d[77]),"+f"(d[78]),"+f"(d[79]),"+f"(d[80]),"+f"(d[81]),"+f"(d[82]),"+f"(d[83]),"+f"(d[84]),"+f"(d[85]),"+f"(d[86]),"+f"(d[87]),"+f"(d[88]),"+f"(d[89]),"+f"(d[90]),"+f"(d[91]),"+f"(d[92]),"+f"(d[93]),"+f"(d[94]),"+f"(d[95]) : "l"(da), "l"(db), "n"(SC));
}

constexpr uint32_t SBC = 1024;
constexpr int ROWB = 2 * 224 * 384;
constexpr int TB = 11;
constexpr int KS = 832;
constexpr int KSLOT = 22 * KS;
constexpr int SM_X1 = 0;
constexpr int SM_X2 = SM_X1 + 24576;
constexpr int SM_X0 = SM_X2 + 24576;
constexpr int SM_W = SM_X0 + 18432;
constexpr int SM_K = SM_W + 55296;
constexpr int SM_V = SM_K + 2 * KSLOT;
constexpr int SM_Q = SM_V + 22 * 1536;
constexpr int SM_O = SM_Q + 24576;
constexpr int SM_RPB = SM_O + 12288;
constexpr int SM_BAR = SM_RPB + 768;
constexpr int SM_A_TOTAL = SM_BAR + 256;
constexpr int SM_TWO = SM_X0 + 24576;
constexpr int SM_TST = SM_TWO + 36864;
enum { B_FULL = 0, B_EMPTY = 3, B_TIN = 6, B_TFREE = 9, B_WK = 11, B_WQ, B_WO, B_Q0, B_OTAIL, B_ODONE = B_OTAIL + 2, B_KFREE, B_VFREE, B_COUNT };
enum { N_KRDY = 4, N_QK0, N_QK1, N_VQ0, N_VQ1, N_PVISS };

#define NL 2
#define OPT 0
#define SPL 4
#define RA 152
#define RG 184
__device__ int g_flags[TB * 56];

#define TR(role, it, k)
#define TRDECL
#define TRARG
#define TRPASS
#define TRDUMP
#define TRB(it, k)
#define TR2(blk, k)

struct GemmCtx {
  uint32_t bar;
  uint32_t kC, vC, qC;
  uint32_t kH, vH;
  bool hvalid;
};

template <int STRIDE> __device__ __forceinline__ void dump12(uint32_t a, const uint32_t (&r)[12]) {
#pragma unroll
  for (int j = 0; j < 3; j++) stsm4(a + j * 2 * STRIDE, r[4 * j], r[4 * j + 1], r[4 * j + 2], r[4 * j + 3]);
}
template <int N> __device__ __forceinline__ void pack12(uint32_t (&r)[12], const float (&d)[N], int off) {
#pragma unroll
  for (int j = 0; j < 12; j++) r[j] = pack2(d[off + 2 * j], d[off + 2 * j + 1]);
}
template <int XS, int K0, int K1> __device__ __forceinline__ void issue_core(float (&d)[72]) {
  constexpr uint64_t da = mkdesc(SBC + XS, 16, 1024, 1), db = mkdesc(SBC + SM_W, 6144, 256, 3);
  wg_fence();
  if (K0 == 0) wg_ss144<0>(d, da, db);
#pragma unroll
  for (int k = K0 ? K0 : 1; k < K1; k++) wg_ss144<1>(d, da + (k >> 2) * 512 + (k & 3) * 2, db + k * 32);
  wg_commit();
}
template <int K0, int K1> __device__ __forceinline__ void issue_halo(float (&d)[48]) {
  constexpr uint64_t da = mkdesc(SBC + SM_X0 - 2048, 16, 1024, 1), db = mkdesc(SBC + SM_W, 6144, 256, 3);
  wg_fence();
  if (K0 == 0) wg_ss96<0>(d, da, db);
#pragma unroll
  for (int k = K0 ? K0 : 1; k < K1; k++) wg_ss96<1>(d, da + (k >> 2) * 384 + (k & 3) * 2, db + k * 32);
  wg_commit();
}
template <int ST, int BYTES> __device__ __forceinline__ void release_stage(const GemmCtx& c, bool on) {
  asm volatile("{\n.reg .pred p, q;\n.reg .b32 ra;\nsetp.ne.b32 q, %2, 0;\nelect.sync _|p, 0xffffffff;\nand.pred p, p, q;\n"
               "mapa.shared::cluster.u32 ra, %1, %4;\n"
               "@p mbarrier.arrive.expect_tx.shared::cta.b64 _, [%0], %3;\n@p mbarrier.arrive.shared::cluster.b64 _, [ra];\n}"
               ::"r"(c.bar + (B_FULL + ST) * 8), "r"(c.bar + (B_EMPTY + ST) * 8), "r"((int)on), "n"(BYTES / 4), "n"(ST) : "memory");
}
__device__ __forceinline__ void load_w(const CUtensorMap* m, uint32_t dst, uint32_t bar, int col) {
  asm volatile("cp.async.bulk.tensor.2d.shared::cluster.global.mbarrier::complete_tx::bytes [%0], [%1, {%3,%4}], [%2];"
               ::"r"(dst), "l"(m), "r"(bar), "r"(col), "r"(0) : "memory");
}
template <int BYTES> __device__ __forceinline__ void send_o(uint32_t dst, uint32_t src, uint32_t bar, int cta) {
  asm volatile("{\n.reg .b32 rd, rb;\nmapa.shared::cluster.u32 rd, %0, %3;\nmapa.shared::cluster.u32 rb, %2, %3;\n"
               "cp.async.bulk.shared::cluster.shared::cta.mbarrier::complete_tx::bytes [rd], [%1], %4, [rb];\n}"
               ::"r"(dst), "r"(src), "r"(bar), "r"(cta), "n"(BYTES) : "memory");
}
__device__ __forceinline__ void tail_free(uint32_t bar) {
  uint32_t ln; asm volatile("mov.u32 %0, %%laneid;" : "=r"(ln));
  if (ln < 4) mbar_arrive_remote(bar, ln);
}
__device__ __forceinline__ void publish(uint32_t bar) {
  fence_async();
  __syncwarp();
  mbar_arrive_elect(bar);
}

template <bool FIRST, bool LAST>
__device__ __forceinline__ void gemm_iter(const GemmCtx& c, int b, uint32_t (&pk)[12], uint32_t (&pv)[12], uint32_t (&pq)[12], const CUtensorMap* mwo TRARG) {
  const uint32_t bar = c.bar;
  const uint32_t pa = b & 1;
  const bool w = b >= 0;
  const uint32_t ko = pa * KSLOT, vx = pa * 16, qx = pa * 128;
  float H[48], C[72];
  uint32_t hk[12], hv[12], pv2[12];
  TR(2, b, 0);
  if (FIRST) mbar_wait(bar + (B_FULL + 0) * 8, pa);
  if (!FIRST) dump12<256>(c.qC ^ (qx ^ 192), pq);
  if (w) nb_sync(N_QK1, 256);
  TR(2, b, 2);
  if (FIRST) TR(2, b - 1, 6);
  issue_halo<0, 8>(H);
  TR(2, b, 3);
  if (!FIRST) {
    if (w) mbar_wait(bar + B_KFREE * 8, pa);
    dump12<128>(c.kC + ko, pk);
  }
  issue_halo<8, 12>(H);
  TR(2, b, 4);
  if (!LAST) {
    mbar_wait(bar + (B_FULL + 2) * 8, pa);
    if (FIRST && NL == 2) mbar_wait(bar + B_WQ * 8, 0);
    TR(2, b, 13);
    if (FIRST) TR(2, b - 1, 7);
    issue_core<SM_X2, 0, 8>(C);
    TR(2, b, 5);
    if (!FIRST) fence_async();
    wg_wait<1>(); pin(H);
    release_stage<0, 18432>(c, true);
  } else {
    fence_async();
    nb_arrive(N_VQ0, 288); nb_arrive(N_VQ1, 288);
    wg_wait<0>(); pin(H);
    tail_free(bar + (B_TFREE + 1) * 8);
    nb_sync(2, 128);
    if (!c.hvalid && elect_one()) {
      mbar_expect(bar + B_WO * 8, 36864);
      asm volatile("cp.async.bulk.tensor.3d.shared::cluster.global.mbarrier::complete_tx::bytes [%0], [%1, {%3,%4,%5}], [%2];"
                   ::"r"(bar - SM_BAR + SM_TWO), "l"(mwo), "r"(bar + B_WO * 8), "r"(0), "r"(0), "r"((blockIdx.x & 1) * 3) : "memory");
    }
    __syncwarp();
  }
  pack12(hk, H, 0);
  if (c.hvalid) dump12<128>(c.kH + ko, hk);
  pack12(hv, H, 24);
  if (!LAST) {
    issue_core<SM_X2, 8, 12>(C);
    if (w) { nb_arrive(N_VQ0, 288); nb_arrive(N_VQ1, 288); }
    else if (!FIRST) { __syncwarp(); mbar_arrive_elect(bar + B_Q0 * 8); }
    mbar_wait(bar + (B_FULL + 1) * 8, pa);
    TR(2, b, 6);
    wg_wait<0>(); pin(C);
    TR(2, b, 7);
    pack12(pk, C, 0);
    dump12<128>(c.kC + ko + 64, pk);
    release_stage<2, 24576>(c, b < 11);
    if (b == 11) tail_free(bar + B_TFREE * 8);
    pack12(pv2, C, 24);
    pack12(pq, C, 48);
    TR(2, b, 8);
    issue_core<SM_X1, 0, SPL>(C);
    if (w) nb_sync(N_PVISS, 384);
    issue_core<SM_X1, SPL, 8>(C);
    TR(2, b, 9);
  }
  if (!FIRST) fence_async();
  TR(2, b, 14);
  if (!LAST) issue_core<SM_X1, 8, 12>(C);
  if (!FIRST) nb_arrive(N_KRDY, 256);
  TR(2, b, 1);
  if (!LAST) mbar_wait(bar + (B_FULL + 0) * 8, pa ^ 1);
  if (w) mbar_wait(bar + B_VFREE * 8, pa);
  TR(2, b, 10);
  if (!FIRST) dump12<128>(c.vC ^ vx, pv);
  if (!LAST) dump12<256>(c.qC ^ qx, pq);
  if (c.hvalid) dump12<128>(c.vH ^ vx, hv);
  if (LAST) { fence_async(); nb_arrive(N_VQ0, 256); nb_arrive(N_VQ1, 256); return; }
  dump12<128>((c.vC ^ vx ^ 16) + 768, pv2);
  TR(2, b, 11);
  wg_wait<0>(); pin(C);
  TR(2, b, 12);
  release_stage<1, 24576>(c, b < 11);
  pack12(pk, C, 0);
  pack12(pv, C, 24);
  pack12(pq, C, 48);
}

__device__ __forceinline__ float fold(float a, float b, float t, int useb) {
  float r;
  asm("{\n.reg .pred p;\nsetp.ne.b32 p, %4, 0;\nfma.rn.f32 %0, %1, 0f3E553B95, %3;\n@p fma.rn.f32 %0, %2, 0f3E553B95, %3;\n}"
      : "=&f"(r) : "f"(a), "f"(b), "f"(t), "r"(useb));
  return r;
}
template <int U, int L>
__device__ __forceinline__ void softmax_tile(const float (&SA)[56], const float (&SB)[56], const float (&T)[16], int b0, int b1,
                                             uint32_t (&P)[28], float (&sx)[8]) {
  float lu[14], ll[14];
#pragma unroll
  for (int j = 0; j < 7; j++) {
    constexpr int sh = U == L ? 2 : 0;
    const float tu0 = T[2 * j + sh], tu1 = T[2 * j + 1 + sh], tl0 = T[2 * j], tl1 = T[2 * j + 1];
    lu[2 * j]     = fold(SA[4 * (U + j)],     SB[4 * (U + j)],     tu0, b0);
    ll[2 * j]     = fold(SA[4 * (L + j) + 2], SB[4 * (L + j) + 2], tl0, b0);
    lu[2 * j + 1] = fold(SA[4 * (U + j) + 1], SB[4 * (U + j) + 1], tu1, b1);
    ll[2 * j + 1] = fold(SA[4 * (L + j) + 3], SB[4 * (L + j) + 3], tl1, b1);
  }
  float mu = lu[0], ml = ll[0], mu2 = lu[1], ml2 = ll[1];
#pragma unroll
  for (int j = 1; j < 7; j++) { mu = fmaxf(mu, lu[2 * j]); mu2 = fmaxf(mu2, lu[2 * j + 1]); ml = fmaxf(ml, ll[2 * j]); ml2 = fmaxf(ml2, ll[2 * j + 1]); }
  mu = fmaxf(mu, mu2); ml = fmaxf(ml, ml2);
  { const float a1 = __shfl_xor_sync(0xffffffffu, mu, 1), a2 = __shfl_xor_sync(0xffffffffu, mu, 2), a3 = __shfl_xor_sync(0xffffffffu, mu, 3);
    const float c1 = __shfl_xor_sync(0xffffffffu, ml, 1), c2 = __shfl_xor_sync(0xffffffffu, ml, 2), c3 = __shfl_xor_sync(0xffffffffu, ml, 3);
    mu = fmaxf(fmaxf(mu, a1), fmaxf(a2, a3)); ml = fmaxf(fmaxf(ml, c1), fmaxf(c2, c3)); }
  float su = 0.f, sl = 0.f;
#pragma unroll
  for (int c = 0; c < 14; c++) {
    const int iu = (c >> 1) * 4 + (c & 1) * 2;
    if (c >= U && c < U + 7) {
      float e0 = ex2(lu[2 * (c - U)] - mu), e1 = ex2(lu[2 * (c - U) + 1] - mu);
      su = c == U ? e0 + e1 : (su + e0) + e1; P[iu] = pack2(e0, e1);
    } else P[iu] = 0u;
    if (c >= L && c < L + 7) {
      float e0 = ex2(ll[2 * (c - L)] - ml), e1 = ex2(ll[2 * (c - L) + 1] - ml);
      sl = c == L ? e0 + e1 : (sl + e0) + e1; P[iu + 1] = pack2(e0, e1);
    } else P[iu + 1] = 0u;
  }
  sx[0] = su; sx[4] = sl;
#pragma unroll
  for (int k = 1; k < 4; k++) { sx[k] = __shfl_xor_sync(0xffffffffu, su, k); sx[4 + k] = __shfl_xor_sync(0xffffffffu, sl, k); }
}

struct Maps { CUtensorMap xc, xh, w, os, wo, ot; };

__global__ void __cluster_dims__(4, 1, 1) __launch_bounds__(512, 1)
na_attn_kernel(const __nv_bfloat16* __restrict__ x, const __nv_bfloat16* __restrict__ wqkv, const __nv_bfloat16* __restrict__ rpb, const __grid_constant__ Maps mp) {
  extern __shared__ __align__(1024) uint8_t smem_raw[];
  const uint32_t sb = smem_u32(smem_raw);
  if ((sb & 0x3FFFF) != SBC) return;
  const uint32_t bar = sb + SM_BAR;
  TR2(blockIdx.x, 0);
  const int tid = threadIdx.x, lane = tid & 31;
  const int warp = __shfl_sync(0xffffffffu, tid >> 5, 0);
  const int head = blockIdx.x & 3, cl = blockIdx.x >> 2;
  const int par = cl / 7, strip = cl - par * 7, ph = par >> 1, pw = par & 1;

  uint4 wv[2 * NL];
  const int va = head == 1;
  const uint32_t wdst = sb + SM_W + (va + ((tid >> 1) & 1)) * 6144 + (tid >> 2) * 32 + ((tid ^ (tid >> 4)) & 1) * 16;
  if (warp < 12) asm volatile("barrier.cluster.arrive.relaxed.aligned;" ::: "memory");
  {
    const uint32_t wo0 = (tid >> 2) * 1152 + head * 96 + va * 32 + (tid & 3) * 16;
#pragma unroll
    for (int i = 0; i < 2 * NL; i++)
      asm volatile("{\n.reg .pred p;\nsetp.lt.u32 p, %5, 384;\n@p ld.global.nc.v4.b32 {%0,%1,%2,%3}, [%4];\n}"
                   : "=r"(wv[i].x), "=r"(wv[i].y), "=r"(wv[i].z), "=r"(wv[i].w)
                   : "l"(reinterpret_cast<const uint8_t*>(wqkv) + wo0 + (i & 1) * 96 * 1152 + ((i / 2 + 1) % 3) * 384), "r"(tid));
  }
  if (warp < 8) {
    asm volatile("setmaxnreg.inc.sync.aligned.u32 %0;" ::"n"(RA));
    float rv = -INFINITY;
    if (tid < 169) rv = __bfloat162float(rpb[head * 169 + tid]) * 1.4426950408889634f;
    if (tid < 192) {
      const int kc = (tid & 15) + 3, wc = (tid >> 4) % 6;
      sts128(tid < 96 ? sb + SM_K + kc * KS + wc * 128 + 48 : sb + SM_V + kc * 1536 + wc * 128 + (6 + (kc & 1)) * 16, make_uint4(0, 0, 0, 0));
    }
#pragma unroll
    for (int i = 0; i < 2 * NL; i++) sts128(wdst + (i & 1) * 3072 + (i / 2) * 18432, wv[i]);
    fence_async();
    asm volatile("bar.arrive 1, 384;" ::: "memory");
    if (tid < 182) asm volatile("st.shared.f32 [%0], %1;" ::"r"(sb + SM_RPB + tid * 4), "f"(rv) : "memory");
    const int j = warp >> 2, w = warp & 3;
    int variant = w;
    if (strip == 0 && j == 0 && w < 2) variant = 4;
    if (strip == 6 && j == 1 && w >= 2) variant = 5;
    const uint32_t qa = sb + SM_Q + (8 * j + 2 * w + ((lane >> 3) & 1)) * 1536 + (lane >> 4) * 256 + (((lane & 7) * 16) ^ (((lane >> 3) & 1) * 64));
    uint32_t oa = sb + SM_O + j * 6144 + (2 * w + ((lane >> 3) & 1)) * 768 + (lane >> 4) * 128 + (lane & 7) * 16;
    const uint64_t dK = mkdesc(SBC + SM_K, 128, KS, 0) + j * (8 * KS / 16);
    const uint64_t dV = mkdesc(SBC + SM_V, 768, 128, 0) + j * (8 * 1536 / 16);
    asm volatile("barrier.cluster.wait.aligned;" ::: "memory");
    asm volatile("bar.sync 3, 256;" ::: "memory");
    float T[16];
    TRDECL;
    int b0 = 0, b1 = 0;
    uint32_t meta = 0;
    uint32_t q[12];
    mbar_wait(bar + B_Q0 * 8, 0);
#pragma unroll
    for (int k = 0; k < 3; k++) ldsm4(qa + k * 512, q[4 * k], q[4 * k + 1], q[4 * k + 2], q[4 * k + 3]);
#pragma unroll 1
    for (int b = 0; b < 14; b++) {
      const uint32_t pa = b & 1;
      float SA[56], SB[56];
      const uint64_t dA = dK + pa * (KSLOT >> 4), dB = dK + (pa ^ 1) * (KSLOT >> 4);
      TR(0, b, 0);
      nb_sync(N_KRDY + j, 256);
      TR(0, b, 1);
      TR(0, b - 1, 9);
      wg_fence();
      wg_rs112<0>(SA, q[0], q[1], q[2], q[3], dA);
      wg_rs112<0>(SB, q[0], q[1], q[2], q[3], dB);
      wg_rs112<1>(SA, q[4], q[5], q[6], q[7], dA + 16);
      wg_rs112<1>(SB, q[4], q[5], q[6], q[7], dB + 16);
      wg_rs112<1>(SA, q[8], q[9], q[10], q[11], dA + 32);
      wg_rs112<1>(SB, q[8], q[9], q[10], q[11], dB + 32);
      wg_commit();
      nb_arrive(N_QK0 + j, 256);
      TR(0, b, 2);
      if (b <= 1 || b == 13) {
        uint32_t ln; asm volatile("mov.u32 %0, %%laneid;" : "=r"(ln));
        const int g = ln >> 2, t = ln & 3;
        const int sw = b == 0 ? max(g + 1, 4) : (b == 13 ? min(g + 1, 5) : g + 1);
        const int i0 = 2 * t, i1 = 2 * t + 1;
        b0 = i0 <= sw - 2; b1 = i1 <= sw - 2;
        const uint32_t tb = sb + SM_RPB + (variant < 4 ? 3 : variant + 1 - 2 * w) * 4;
        const uint32_t ra0 = tb + (i0 == sw - 1 ? 13 : i0 + 8 * b0 - g + 2) * 52;
        const uint32_t ra1 = tb + (i1 == sw - 1 ? 13 : i1 + 8 * b1 - g + 2) * 52;
#pragma unroll
        for (int jj = 0; jj < 8; jj++) { T[2 * jj] = lds_f32(ra0 + jj * 4); T[2 * jj + 1] = lds_f32(ra1 + jj * 4); }
        meta = ((0x5555u & ((1u << (2 * (sw - 1))) - 1)) ^ 0xDD88u ^ (((t ^ b) & 1) ? 0x5555u : 0u)) * 0x10001u;
      } else meta ^= 0x55555555u;
      if (b >= 12) oa += b == 12 ? warp * 1536 - (SM_O - SM_Q) : 1536;
      wg_wait<0>(); pin(SA); pin(SB);
      mbar_arrive_elect(bar + B_KFREE * 8);
      TR(0, b, 3);
      TR(0, b - 1, 10);
      uint32_t P[28];
      float sx[8];
      switch (variant) {
        case 0: softmax_tile<0, 1>(SA, SB, T, b0, b1, P, sx); break;
        case 1: softmax_tile<2, 3>(SA, SB, T, b0, b1, P, sx); break;
        case 2: softmax_tile<4, 5>(SA, SB, T, b0, b1, P, sx); break;
        case 3: softmax_tile<6, 7>(SA, SB, T, b0, b1, P, sx); break;
        case 4: softmax_tile<3, 3>(SA, SB, T, b0, b1, P, sx); break;
        default: softmax_tile<4, 4>(SA, SB, T, b0, b1, P, sx); break;
      }
      float O[24];
      TR(0, b, 4);
      nb_sync(N_VQ0 + j, b == 13 ? 256 : 288);
      TR(0, b, 5);
#pragma unroll
      for (int k = 0; k < 3; k++) ldsm4(qa + (pa ^ 1) * 128 + k * 512, q[4 * k], q[4 * k + 1], q[4 * k + 2], q[4 * k + 3]);
      wg_fence();
      wg_sp48<0>(O, P[0], P[1], P[2], P[3], dV, meta);
#pragma unroll
      for (int s = 1; s < 7; s++) wg_sp48<1>(O, P[4 * s], P[4 * s + 1], P[4 * s + 2], P[4 * s + 3], dV + s * 192, meta);
      wg_commit();
      if (b != 12) nb_arrive(N_PVISS, 384);
      TR(0, b, 6);
      wg_wait<0>(); pin(O);
      mbar_arrive_elect(bar + B_VFREE * 8);
      TR(0, b, 7);
      float ru, rl;
      asm("rcp.approx.ftz.f32 %0, %1;" : "=f"(ru) : "f"(((fmaf(O[0], 0.f, sx[0]) + sx[1]) + sx[2]) + sx[3]));
      asm("rcp.approx.ftz.f32 %0, %1;" : "=f"(rl) : "f"(((fmaf(O[2], 0.f, sx[4]) + sx[5]) + sx[6]) + sx[7]));
#pragma unroll
      for (int i = 0; i < 3; i++)
        stsm4(oa + i * 256, pack2(O[8 * i] * ru, O[8 * i + 1] * ru), pack2(O[8 * i + 2] * rl, O[8 * i + 3] * rl),
              pack2(O[8 * i + 4] * ru, O[8 * i + 5] * ru), pack2(O[8 * i + 6] * rl, O[8 * i + 7] * rl));
      if (b < 13) publish(bar + (b < TB ? B_ODONE : B_OTAIL + j) * 8);
      else {
        fence_async();
        mbar_wait(bar + (B_TFREE + 1) * 8, 0);
        __syncwarp();
        if (elect_one()) {
#pragma unroll
          for (int d = 0; d < 2; d++)
            send_o<1536>(sb + SM_X0 + head * 6144 + (2 * j + (w & 1)) * 1536, sb + SM_Q + warp * 3072 + 1536, bar + (B_TIN + 2) * 8, (w & 2) + (d ^ (head & 1)));
        }
        __syncwarp();
      }
      TR(0, b, 8);
    }
    TRDUMP;
    cluster_sync();
  } else if (warp < 12) {
    TRDECL;
    TR(2, -3, 0);
    asm volatile("setmaxnreg.inc.sync.aligned.u32 %0;" ::"n"(RG));
    TR(2, -3, 1);
    GemmCtx c;
    c.bar = bar;
    const int gw = warp - 8, tk = gw * 16 + (lane & 15), hi = lane >> 4;
    { const int col = tk >> 2, i = tk & 3;
      c.kC = sb + SM_K + (col + 3) * KS + hi * 128 + i * 16;
      c.vC = sb + SM_V + (col + 3) * 1536 + hi * 128 + (2 * i + ((col + 3) & 1)) * 16;
      c.qC = sb + SM_Q + col * 1536 + hi * 256 + (col & 1) * 64 + i * 16; }
    { const int ci = (tk >> 3) - 2, kc = ci < 3 ? ci : ci + 16, i = tk & 7; c.hvalid = gw > 0;
      c.kH = sb + SM_K + kc * KS + hi * 128 + i * 16;
      c.vH = sb + SM_V + kc * 1536 + hi * 128 + (i >> 2) * 768 + (2 * (i & 3) + ((kc ^ (i >> 2)) & 1)) * 16; }
    asm volatile("barrier.cluster.wait.aligned;" ::: "memory");
    TR(2, -3, 2);
    if (elect_one()) { mbar_expect(bar + B_FULL * 8, 4608); mbar_expect(bar + (B_FULL + 1) * 8, 6144); mbar_expect(bar + (B_FULL + 2) * 8, 6144); }
    __syncwarp();
#pragma unroll
    for (int i = 0; i < 2 * NL; i++) sts128(wdst + (i & 1) * 3072 + (i / 2) * 18432, wv[i]);
    fence_async();
    TR(2, -3, 3);
    asm volatile("bar.sync 1, 384;" ::: "memory");
    TR(2, -3, 4);
    mbar_wait(bar + B_WK * 8, 0);
    TR(2, -3, 5);
    uint32_t pk[12], pv[12], pq[12];
    gemm_iter<true, false>(c, -2, pk, pv, pq, &mp.wo TRPASS);
    TR2(blockIdx.x, 4);
#pragma unroll 1
    for (int b = -1; b < 12; b++) gemm_iter<false, false>(c, b, pk, pv, pq, &mp.wo TRPASS);
    TR2(blockIdx.x, 6);
    gemm_iter<false, true>(c, 12, pk, pv, pq, &mp.wo TRPASS);
    TR(2, 13, 0);
    mbar_wait(bar + B_WO * 8, 0);
    TR(2, 13, 1);
    const uint32_t st = sb + SM_TST + gw * 3072;
    const uint32_t sta = st + (lane & 15) * 64 + ((hi ^ ((lane >> 1) & 3)) * 16);
#pragma unroll 1
    for (int i = 0; i < 3; i++) {
      constexpr uint64_t db = mkdesc(SBC + SM_TWO, 12288, 512, 2);
      const uint64_t da = mkdesc(SBC, 128, 768, 0) + (i ^ (i < 2)) * (24576 / 16);
      float D[48];
      mbar_wait(bar + (B_TIN + i) * 8, 0);
      if (i == 2) asm volatile("barrier.cluster.arrive.relaxed.aligned;" ::: "memory");
      else nb_sync(i ? N_PVISS : N_QK1, i ? 384 : 256);
      TR(2, 13 - i, 2); TR(2, 12 + i, 5); TR(2, 11 + i, 9);
      wg_fence();
      wg_ss96<0>(D, da, db);
#pragma unroll
      for (int k = 1; k < 12; k++) wg_ss96<1>(D, da + (k / 3) * 384 + (k % 3) * 16, db + k * 64);
      wg_commit();
      if (lane == 0) asm volatile("cp.async.bulk.wait_group.read 0;" ::: "memory");
      __syncwarp();
      wg_wait<0>(); pin(D);
      TR(2, 13 - i, 3); TR(2, 12 + i, 6); TR(2, 11 + i, 10);
#pragma unroll
      for (int q = 0; q < 6; q++)
        stsm4((sta ^ ((q & 1) * 32)) + (q >> 1) * 1024,
              pack2(D[8 * q], D[8 * q + 1]), pack2(D[8 * q + 2], D[8 * q + 3]), pack2(D[8 * q + 4], D[8 * q + 5]), pack2(D[8 * q + 6], D[8 * q + 7]));
      fence_async();
      __syncwarp();
      if (lane == 0) {
        asm volatile("cp.async.bulk.tensor.4d.global.shared::cta.bulk_group [%0, {%2,%3,%4,%5}], [%1];"
                     ::"l"(&mp.ot), "r"(st), "r"(0), "r"(8 * (TB + i)), "r"(ph * 112 + strip * 16 + 8 * (gw >> 1) + 4 * (head >> 1) + 2 * (gw & 1)), "r"(pw * 6 + (head & 1) * 3) : "memory");
        asm volatile("cp.async.bulk.commit_group;" ::: "memory");
      }
      TR(2, 13 - i, 4); TR(2, 12 + i, 7); TR(2, 11 + i, 11);
    }
    if (lane == 0) asm volatile("cp.async.bulk.wait_group.read 0;" ::: "memory");
    __syncwarp();
    TR(2, 13, 8);
    TR2(blockIdx.x, 2);
    TRDUMP;
    asm volatile("barrier.cluster.wait.aligned;" ::: "memory");
  } else {
    if (warp == 12) {
      if (elect_one()) {
        mbar_init(bar + B_WK * 8, 1);
#pragma unroll
        for (int i = 0; i < NL; i++) load_w(&mp.w, sb + SM_W + (3 * i + 2 - 2 * va) * 6144, bar + B_WK * 8, ((i + 1) % 3) * 192 + head * 48 + 32 - 32 * va);
        asm volatile("prefetch.tensormap [%0];" ::"l"(head ? &mp.xc : &mp.xh) : "memory");
        mbar_expect(bar + B_WK * 8, NL * 6144);
      }
    } else if (warp == 15) {
      const int col = min(max(strip * 16 - 3 + min(lane, 21), 0), 111);
      const uint8_t* p = reinterpret_cast<const uint8_t*>(x) + (uint32_t)(head * ROWB + (ph * 112 + col) * 768 + pw * 384);
#pragma unroll
      for (int i = 0; i < 3; i++) asm volatile("prefetch.global.L2 [%0];" ::"l"(p + i * 128));
    } else if (elect_one()) {
      if (warp == 13) {
#pragma unroll
        for (int i = 0; i < B_WK; i++) mbar_init(bar + i * 8, i < B_EMPTY ? 4 : (i < B_TIN ? 16 : (i < B_TFREE ? 1 : 16)));
      } else {
#pragma unroll
        for (int i = B_WQ; i < B_COUNT; i++) mbar_init(bar + i * 8, i < B_Q0 ? 1 : (i < B_ODONE ? 4 : 8));
      }
    }
    asm volatile("fence.mbarrier_init.release.cluster;" ::: "memory");
    __syncwarp();
    asm volatile("barrier.cluster.arrive.relaxed.aligned;" ::: "memory");
    asm volatile("setmaxnreg.dec.sync.aligned.u32 24;");
    asm volatile("griddepcontrol.launch_dependents;");
    const int cc = ph * 112 + (head ? strip * 16 : (strip == 0 ? 16 : (strip == 6 ? 74 : strip * 16 - 3)));
    const int sd = strip == 0 ? -1 : (strip == 6 ? 1 : 0);
    const int r0 = head == 0 ? -4 : (head == 1 ? 4 : 0);
    asm volatile("barrier.cluster.wait.aligned;" ::: "memory");
    if (warp == 12) {
      const uint32_t fb = bar + (B_FULL + head) * 8, eb = bar + (B_EMPTY + head) * 8;
      const uint32_t dst = sb + (head == 0 ? SM_X0 : (head == 1 ? SM_X1 : SM_X2));
      const int nl = head == 0 ? 15 : (head == 3 ? 1 : 14);
#pragma unroll 1
      for (int n = 0; n < nl; n++) {
        if (n) mbar_wait(eb, (n - 1) & 1);
        if (elect_one()) {
          if (head == 0) {
            asm volatile("cp.async.bulk.tensor.5d.shared::cluster.global.mbarrier::complete_tx::bytes.multicast::cluster [%0], [%1, {%3,%4,%5,%6,%7}], [%2], %8;"
                         ::"r"(dst), "l"(&mp.xh), "r"(fb), "r"(0), "r"(8 * n + r0), "r"(cc), "r"(sd), "r"(pw * 3), "h"((uint16_t)15) : "memory");
          } else if (head < 3) {
            asm volatile("cp.async.bulk.tensor.4d.shared::cluster.global.mbarrier::complete_tx::bytes.multicast::cluster [%0], [%1, {%3,%4,%5,%6}], [%2], %7;"
                         ::"r"(dst), "l"(&mp.xc), "r"(fb), "r"(0), "r"(8 * n + r0), "r"(cc), "r"(pw * 3), "h"((uint16_t)15) : "memory");
          }
          if (n == 0) {
#pragma unroll
            for (int i = 0; i < 3; i++) load_w(&mp.w, sb + SM_W + (6 + i) * 6144, bar + B_WQ * 8, head * 48 + i * 16);
            mbar_expect(bar + B_WQ * 8, 18432);
            mbar_expect(bar + B_TIN * 8, 24576); mbar_expect(bar + (B_TIN + 1) * 8, 24576); mbar_expect(bar + (B_TIN + 2) * 8, 24576);
          }
          if (!head && n + 1 < nl) asm volatile("cp.async.bulk.prefetch.tensor.5d.L2.global [%0, {%1,%2,%3,%4,%5}];" ::"l"(&mp.xh), "r"(0), "r"(8 * n + 8 + r0), "r"(cc), "r"(sd), "r"(pw * 3) : "memory");
          if (head && n + 1 < nl) asm volatile("cp.async.bulk.prefetch.tensor.4d.L2.global [%0, {%1,%2,%3,%4}];" ::"l"(&mp.xc), "r"(0), "r"(8 * n + 8 + r0), "r"(cc), "r"(pw * 3) : "memory");
        }
        __syncwarp();
      }
    }
    if (warp == 14) {
      int* flag = g_flags + cl * 2;
      nb_arrive(N_VQ0, 288); nb_arrive(N_VQ1, 288);
#pragma unroll 1
      for (int b = 0; b < TB; b++) {
        mbar_wait(bar + B_ODONE * 8, b & 1);
        if (lane == 0) {
          asm volatile("cp.async.bulk.tensor.3d.global.shared::cta.bulk_group [%0, {%2,%3,%4}], [%1];"
                       ::"l"(&mp.os), "r"(sb + SM_O), "r"(pw * 192), "r"(8 * b + 2 * head), "r"(ph * 112 + strip * 16) : "memory");
          asm volatile("cp.async.bulk.commit_group;\ncp.async.bulk.wait_group 0;" ::: "memory");
        }
        __syncwarp();
        nb_arrive(N_VQ0, 288); nb_arrive(N_VQ1, 288);
        if (lane == 0)
          asm volatile("fence.proxy.async.global;\nfence.acq_rel.gpu;\nred.relaxed.gpu.global.add.s32 [%0], 1;\nred.relaxed.gpu.global.add.s32 [%0+4], 1;"
                       ::"l"(flag + b * 56) : "memory");
        __syncwarp();
      }
    } else if (warp & 1) {
      const int j = (warp >> 1) & 1;
#pragma unroll 1
      for (int i = 0; i < 2; i++) {
        mbar_wait(bar + (B_OTAIL + j) * 8, i);
        if (i == 0) nb_arrive(N_VQ0 + j, 288);
        mbar_wait(bar + (B_TFREE + i) * 8, 0);
        if (elect_one()) {
#pragma unroll 1
          for (int d = 0; d < 8; d++) {
            const int dst = (d + head) & 3, pc = d >> 2;
            send_o<1536>(sb + (i ? SM_X1 : SM_X2) + head * 6144 + j * 3072 + pc * 1536,
                         sb + (i ? SM_Q : SM_O) + (4 * j + (dst & 2) + pc) * (i ? 3072 : 1536), bar + (B_TIN + i) * 8, dst);
          }
        }
        __syncwarp();
      }
    }
    cluster_sync();
  }
}

constexpr int NSTB = 6;
constexpr int NTB = TB * 56;
constexpr int SM_B_IN = 0;
constexpr int SM_B_W = SM_B_IN + NSTB * 24576;
constexpr int SM_B_BAR = SM_B_W + 73728;
constexpr int SM_B_TOTAL = SM_B_BAR + 128;
struct MapsB { CUtensorMap oi, oo, wo; };

__global__ void __launch_bounds__(480, 1)
na_proj_kernel(const __grid_constant__ MapsB mp) {
  extern __shared__ __align__(1024) uint8_t smem_raw[];
  const uint32_t sb = smem_u32(smem_raw);
  if ((sb & 0x3FFFF) != SBC) return;
  const uint32_t bar = sb + SM_B_BAR;
  const int tid = threadIdx.x, lane = tid & 31;
  const int warp = __shfl_sync(0xffffffffu, tid >> 5, 0);
  TR2(132 + blockIdx.x, 0);
  TRB(47, 0);
  if (warp == 12 && elect_one()) {
#pragma unroll
    for (int i = 0; i <= 2 * NSTB; i++) mbar_init(bar + i * 8, i < NSTB || i == 2 * NSTB ? 1 : 4);
    mbar_expect(bar + 2 * NSTB * 8, 73728);
#pragma unroll
    for (int i = 0; i < 2; i++)
      asm volatile("cp.async.bulk.tensor.3d.shared::cluster.global.mbarrier::complete_tx::bytes [%0], [%1, {%3,%4,%5}], [%2];"
                   ::"r"(sb + SM_B_W + i * 36864), "l"(&mp.wo), "r"(bar + 2 * NSTB * 8), "r"(0), "r"(0), "r"(i * 3) : "memory");
  }
  __syncthreads();
  const int step = gridDim.x;
  if (warp >= 12) {
    const int wg = warp - 12;
    int use = 0;
#pragma unroll 1
    for (int n = blockIdx.x + wg * step; n < NTB; n += 3 * step, use++) {
      const int b = n / 56, rem = n - b * 56, par = rem / 14, sg = wg + 3 * (use & 1);
      int v; uint32_t spin = 0;
      do { asm volatile("ld.acquire.gpu.global.s32 %0, [%1];" : "=r"(v) : "l"(g_flags + n) : "memory"); if ((OPT & 1) && v < 4) __nanosleep(200); } while (v < 4 && ++spin < SPIN_LIMIT);
      TRB(use * 3 + wg, 0);
      asm volatile("fence.proxy.async.global;" ::: "memory");
      if (use >= 2) mbar_wait(bar + (NSTB + sg) * 8, ((use >> 1) - 1) & 1);
      TRB(use * 3 + wg, 1);
      if (elect_one()) {
        mbar_expect(bar + sg * 8, 24576);
        asm volatile("cp.async.bulk.tensor.3d.shared::cluster.global.mbarrier::complete_tx::bytes [%0], [%1, {%3,%4,%5}], [%2];"
                     ::"r"(sb + SM_B_IN + sg * 24576), "l"(&mp.oi), "r"(bar + sg * 8), "r"((par & 1) * 192), "r"(8 * b), "r"((par >> 1) * 112 + (rem - par * 14) * 8) : "memory");
        g_flags[n] = 0;
      }
      __syncwarp();
    }
  } else {
    const int wg = warp >> 2, w = warp & 3;
    constexpr uint64_t db = mkdesc(SBC + SM_B_W, 12288, 512, 2);
    const uint32_t sta0 = sb + SM_B_IN + w * 6144 + (lane & 15) * 128 + (((lane >> 4) ^ (lane & 7)) * 16);
    mbar_wait(bar + 2 * NSTB * 8, 0);
    TRB(47, 1);
    int use = 0;
#pragma unroll 1
    for (int n = blockIdx.x + wg * step; n < NTB; n += 3 * step, use++) {
      const int b = n / 56, rem = n - b * 56, par = rem / 14, sg = wg + 3 * (use & 1);
      const uint64_t da = mkdesc(SBC + SM_B_IN, 128, 3072, 0) + sg * (24576 / 16);
      float D[96];
      mbar_wait(bar + sg * 8, (use >> 1) & 1);
      if (use | wg) nb_sync(4 + wg, 256);
      TRB(use * 3 + wg, 3);
      wg_fence();
      wg_ss192<0>(D, da, db);
#pragma unroll
      for (int k = 1; k < 12; k++) wg_ss192<1>(D, da + k * 16, db + k * 64);
      wg_commit();
      if (n + step < NTB) nb_arrive(wg == 2 ? 4 : 5 + wg, 256);
      TRB(use * 3 + wg, 4);
      if (use && lane == 0) {
        asm volatile("cp.async.bulk.wait_group.read 0;" ::: "memory");
        mbar_arrive(bar + (NSTB + wg + 3 * (~use & 1)) * 8);
      }
      __syncwarp();
      wg_wait<0>(); pin(D);
      nb_sync(1 + wg, 128);
      TRB(use * 3 + wg, 5);
      const uint32_t sta = sta0 + sg * 24576;
#pragma unroll
      for (int q = 0; q < 12; q++)
        stsm4((sta ^ ((q & 3) * 32)) + (q >> 2) * 2048,
              pack2(D[8 * q], D[8 * q + 1]), pack2(D[8 * q + 2], D[8 * q + 3]), pack2(D[8 * q + 4], D[8 * q + 5]), pack2(D[8 * q + 6], D[8 * q + 7]));
      fence_async();
      __syncwarp();
      if (lane == 0) {
        asm volatile("cp.async.bulk.tensor.4d.global.shared::cta.bulk_group [%0, {%2,%3,%4,%5}], [%1];"
                     ::"l"(&mp.oo), "r"(sb + SM_B_IN + sg * 24576 + w * 6144), "r"(0), "r"(8 * b), "r"((par >> 1) * 112 + (rem - par * 14) * 8 + 2 * w), "r"((par & 1) * 3) : "memory");
        asm volatile("cp.async.bulk.commit_group;" ::: "memory");
      }
      __syncwarp();
      TRB(use * 3 + wg, 6);
    }
    if (lane == 0) asm volatile("cp.async.bulk.wait_group 0;" ::: "memory");
    TR2(132 + blockIdx.x, 2);
  }
}

typedef CUresult (*EncodeFn)(CUtensorMap*, CUtensorMapDataType, cuuint32_t, void*, const cuuint64_t*, const cuuint64_t*, const cuuint32_t*,
                             const cuuint32_t*, CUtensorMapInterleave, CUtensorMapSwizzle, CUtensorMapL2promotion, CUtensorMapFloatOOBfill);
static EncodeFn g_enc = nullptr;
static void make_map(CUtensorMap* m, const void* p, int rank, const cuuint64_t* dim, const cuuint64_t* str, const cuuint32_t* box, CUtensorMapSwizzle sw) {
  const cuuint32_t ones[5] = {1, 1, 1, 1, 1};
  g_enc(m, CU_TENSOR_MAP_DATA_TYPE_BFLOAT16, rank, (void*)p, dim, str, box, ones, CU_TENSOR_MAP_INTERLEAVE_NONE, sw,
        CU_TENSOR_MAP_L2_PROMOTION_L2_128B, CU_TENSOR_MAP_FLOAT_OOB_FILL_NONE);
}

extern "C" void kernel_launch(void* const* d_in, const int* in_sizes, int n_in, void* d_out, int out_size) {
  const __nv_bfloat16* x = (const __nv_bfloat16*)d_in[0];
  const __nv_bfloat16* wqkv = (const __nv_bfloat16*)d_in[1];
  const __nv_bfloat16* wo = (const __nv_bfloat16*)d_in[2];
  const __nv_bfloat16* rpb = (const __nv_bfloat16*)d_in[3];

  if (!g_enc) {
    void* fn = nullptr; cudaDriverEntryPointQueryResult qr;
    cudaGetDriverEntryPoint("cuTensorMapEncodeTiled", &fn, cudaEnableDefault, &qr);
    g_enc = (EncodeFn)fn;
    cudaFuncSetAttribute(na_attn_kernel, cudaFuncAttributeMaxDynamicSharedMemorySize, SM_A_TOTAL);
    cudaFuncSetAttribute(na_proj_kernel, cudaFuncAttributeMaxDynamicSharedMemorySize, SM_B_TOTAL);
  }
  Maps ma; MapsB mb;
  { cuuint64_t dim[4] = {64, 112, 224, 6}, str[3] = {(cuuint64_t)ROWB, 768, 128};
    cuuint32_t box[4] = {64, 4, 16, 3}, boxo[4] = {64, 8, 2, 3};
    make_map(&ma.xc, x, 4, dim, str, box, CU_TENSOR_MAP_SWIZZLE_128B);
    make_map(&mb.oo, d_out, 4, dim, str, boxo, CU_TENSOR_MAP_SWIZZLE_128B); }
  { cuuint64_t dim[5] = {64, 112, 224, 2, 6}, str[4] = {(cuuint64_t)ROWB, 768, 19 * 768, 128};
    cuuint32_t box[5] = {64, 8, 3, 2, 3};
    make_map(&ma.xh, x, 5, dim, str, box, CU_TENSOR_MAP_SWIZZLE_128B); }
  { cuuint64_t dim[3] = {384, 112, 224}, str[2] = {(cuuint64_t)ROWB, 768};
    cuuint32_t box[3] = {192, 8, 8}, boxs[3] = {192, 2, 16};
    make_map(&mb.oi, d_out, 3, dim, str, box, CU_TENSOR_MAP_SWIZZLE_NONE);
    make_map(&ma.os, d_out, 3, dim, str, boxs, CU_TENSOR_MAP_SWIZZLE_NONE); }
  { cuuint64_t dim[4] = {32, 112, 224, 12}, str[3] = {(cuuint64_t)ROWB, 768, 64};
    cuuint32_t box[4] = {32, 8, 2, 3};
    make_map(&ma.ot, d_out, 4, dim, str, box, CU_TENSOR_MAP_SWIZZLE_64B); }
  { cuuint64_t dim[2] = {576, 192}, str[1] = {1152};
    cuuint32_t box[2] = {16, 192};
    make_map(&ma.w, wqkv, 2, dim, str, box, CU_TENSOR_MAP_SWIZZLE_32B); }
  { cuuint64_t dim[3] = {32, 192, 6}, str[2] = {384, 64};
    cuuint32_t box[3] = {32, 192, 3};
    make_map(&ma.wo, wo, 3, dim, str, box, CU_TENSOR_MAP_SWIZZLE_64B);
    mb.wo = ma.wo; }
  na_attn_kernel<<<112, 512, SM_A_TOTAL>>>(x, wqkv, rpb, ma);
  cudaLaunchConfig_t cfg = {};
  cfg.gridDim = dim3(20); cfg.blockDim = dim3(480); cfg.dynamicSmemBytes = SM_B_TOTAL; cfg.stream = cudaStreamPerThread;
  cudaLaunchAttribute at[1];
  at[0].id = cudaLaunchAttributeProgrammaticStreamSerialization; at[0].val.programmaticStreamSerializationAllowed = 1;
  cfg.attrs = at; cfg.numAttrs = 1;
  cudaLaunchKernelEx(&cfg, na_proj_kernel, mb);
}
```

```cpp
#include <cuda_runtime.h>
#include <cuda_bf16.h>
#include <cuda.h>
#include <stdint.h>

#define SPIN_LIMIT (1u << 18)

__device__ __forceinline__ uint32_t smem_u32(const void* p) { return (uint32_t)__cvta_generic_to_shared(p); }
__device__ __forceinline__ void wg_fence() { asm volatile("wgmma.fence.sync.aligned;" ::: "memory"); }
__device__ __forceinline__ void wg_commit() { asm volatile("wgmma.commit_group.sync.aligned;" ::: "memory"); }
template <int N> __device__ __forceinline__ void wg_wait() { asm volatile("wgmma.wait_group.sync.aligned %0;" ::"n"(N) : "memory"); }
template <int N> __device__ __forceinline__ void pin(float (&d)[N]) {
#pragma unroll
  for (int i = 0; i < N; i++) asm volatile("" : "+f"(d[i])::"memory");
}
__host__ __device__ constexpr uint64_t mkdesc(uint32_t addr, uint32_t lbo, uint32_t sbo, uint32_t sw) {
  return (uint64_t)((addr & 0x3FFFF) >> 4) | ((uint64_t)(lbo >> 4) << 16) | ((uint64_t)(sbo >> 4) << 32) | ((uint64_t)sw << 62);
}
__device__ __forceinline__ void mbar_init(uint32_t bar, uint32_t cnt) { asm volatile("mbarrier.init.shared::cta.b64 [%0], %1;" ::"r"(bar), "r"(cnt) : "memory"); }
__device__ __forceinline__ void mbar_arrive(uint32_t bar) { asm volatile("mbarrier.arrive.shared::cta.b64 _, [%0];" ::"r"(bar) : "memory"); }
__device__ __forceinline__ bool elect_one() {
  uint32_t r; asm volatile("{\n.reg .pred p;\nelect.sync _|p, 0xffffffff;\nselp.u32 %0, 1, 0, p;\n}" : "=r"(r)); return r;
}
__device__ __forceinline__ void mbar_arrive_elect(uint32_t bar) {
  asm volatile("{\n.reg .pred p;\nelect.sync _|p, 0xffffffff;\n@p mbarrier.arrive.shared::cta.b64 _, [%0];\n}" ::"r"(bar) : "memory");
}
__device__ __forceinline__ void mbar_expect(uint32_t bar, uint32_t bytes) { asm volatile("mbarrier.arrive.expect_tx.shared::cta.b64 _, [%0], %1;" ::"r"(bar), "r"(bytes) : "memory"); }
__device__ __forceinline__ void mbar_arrive_remote(uint32_t bar, uint32_t cta) {
  asm volatile("{\n.reg .b32 ra;\nmapa.shared::cluster.u32 ra, %0, %1;\nmbarrier.arrive.relaxed.cluster.shared::cluster.b64 _, [ra];\n}" ::"r"(bar), "r"(cta) : "memory");
}
__device__ __forceinline__ void mbar_wait(uint32_t bar, uint32_t parity) {
  asm volatile("{\n.reg .pred p;\n.reg .b32 n;\nmov.b32 n, 0;\nWL:\nmbarrier.try_wait.parity.shared::cta.b64 p, [%0], %1;\n@p bra WD;\n"
               "add.u32 n, n, 1;\nsetp.lt.u32 p, n, 65536;\n@p bra WL;\nWD:\n}" ::"r"(bar), "r"(parity) : "memory");
}
__device__ __forceinline__ void nb_sync(int id, int n) { asm volatile("bar.sync %0, %1;" ::"r"(id), "r"(n) : "memory"); }
__device__ __forceinline__ void nb_arrive(int id, int n) { asm volatile("bar.arrive %0, %1;" ::"r"(id), "r"(n) : "memory"); }
__device__ __forceinline__ void fence_async() { asm volatile("fence.proxy.async.shared::cta;" ::: "memory"); }
__device__ __forceinline__ void cluster_sync() {
  asm volatile("barrier.cluster.arrive.relaxed.aligned;\nbarrier.cluster.wait.aligned;" ::: "memory");
}
__device__ __forceinline__ uint32_t pack2(float lo, float hi) {
  uint32_t r; asm("cvt.rn.bf16x2.f32 %0, %1, %2;" : "=r"(r) : "f"(hi), "f"(lo)); return r;
}
__device__ __forceinline__ void stsm4(uint32_t a, uint32_t r0, uint32_t r1, uint32_t r2, uint32_t r3) {
  asm volatile("stmatrix.sync.aligned.m8n8.x4.shared.b16 [%0], {%1,%2,%3,%4};" ::"r"(a), "r"(r0), "r"(r1), "r"(r2), "r"(r3) : "memory");
}
__device__ __forceinline__ void ldsm4(uint32_t a, uint32_t& r0, uint32_t& r1, uint32_t& r2, uint32_t& r3) {
  asm volatile("ldmatrix.sync.aligned.m8n8.x4.shared.b16 {%0,%1,%2,%3}, [%4];" : "=r"(r0), "=r"(r1), "=r"(r2), "=r"(r3) : "r"(a) : "memory");
}
__device__ __forceinline__ void sts128(uint32_t a, uint4 v) {
  asm volatile("st.shared.v4.b32 [%0], {%1,%2,%3,%4};" ::"r"(a), "r"(v.x), "r"(v.y), "r"(v.z), "r"(v.w) : "memory");
}
__device__ __forceinline__ float lds_f32(uint32_t a) { float v; asm volatile("ld.shared.f32 %0, [%1];" : "=f"(v) : "r"(a)); return v; }
__device__ __forceinline__ float ex2(float x) { float y; asm("ex2.approx.ftz.f32 %0, %1;" : "=f"(y) : "f"(x)); return y; }

template<int SC> __device__ __forceinline__ void wg_ss144(float (&d)[72], uint64_t da, uint64_t db) {
  asm volatile("{\n.reg .pred p;\nsetp.ne.b32 p, %74, 0;\nwgmma.mma_async.sync.aligned.m64n144k16.f32.bf16.bf16 {%0,%1,%2,%3,%4,%5,%6,%7,%8,%9,%10,%11,%12,%13,%14,%15,%16,%17,%18,%19,%20,%21,%22,%23,%24,%25,%26,%27,%28,%29,%30,%31,%32,%33,%34,%35,%36,%37,%38,%39,%40,%41,%42,%43,%44,%45,%46,%47,%48,%49,%50,%51,%52,%53,%54,%55,%56,%57,%58,%59,%60,%61,%62,%63,%64,%65,%66,%67,%68,%69,%70,%71}, %72, %73, p, 1, 1, 0, 1;\n}\n"
    : "+f"(d[0]),"+f"(d[1]),"+f"(d[2]),"+f"(d[3]),"+f"(d[4]),"+f"(d[5]),"+f"(d[6]),"+f"(d[7]),"+f"(d[8]),"+f"(d[9]),"+f"(d[10]),"+f"(d[11]),"+f"(d[12]),"+f"(d[13]),"+f"(d[14]),"+f"(d[15]),"+f"(d[16]),"+f"(d[17]),"+f"(d[18]),"+f"(d[19]),"+f"(d[20]),"+f"(d[21]),"+f"(d[22]),"+f"(d[23]),"+f"(d[24]),"+f"(d[25]),"+f"(d[26]),"+f"(d[27]),"+f"(d[28]),"+f"(d[29]),"+f"(d[30]),"+f"(d[31]),"+f"(d[32]),"+f"(d[33]),"+f"(d[34]),"+f"(d[35]),"+f"(d[36]),"+f"(d[37]),"+f"(d[38]),"+f"(d[39]),"+f"(d[40]),"+f"(d[41]),"+f"(d[42]),"+f"(d[43]),"+f"(d[44]),"+f"(d[45]),"+f"(d[46]),"+f"(d[47]),"+f"(d[48]),"+f"(d[49]),"+f"(d[50]),"+f"(d[51]),"+f"(d[52]),"+f"(d[53]),"+f"(d[54]),"+f"(d[55]),"+f"(d[56]),"+f"(d[57]),"+f"(d[58]),"+f"(d[59]),"+f"(d[60]),"+f"(d[61]),"+f"(d[62]),"+f"(d[63]),"+f"(d[64]),"+f"(d[65]),"+f"(d[66]),"+f"(d[67]),"+f"(d[68]),"+f"(d[69]),"+f"(d[70]),"+f"(d[71]) : "l"(da), "l"(db), "n"(SC));
}
template<int SC> __device__ __forceinline__ void wg_ss96(float (&d)[48], uint64_t da, uint64_t db) {
  asm volatile("{\n.reg .pred p;\nsetp.ne.b32 p, %50, 0;\nwgmma.mma_async.sync.aligned.m64n96k16.f32.bf16.bf16 {%0,%1,%2,%3,%4,%5,%6,%7,%8,%9,%10,%11,%12,%13,%14,%15,%16,%17,%18,%19,%20,%21,%22,%23,%24,%25,%26,%27,%28,%29,%30,%31,%32,%33,%34,%35,%36,%37,%38,%39,%40,%41,%42,%43,%44,%45,%46,%47}, %48, %49, p, 1, 1, 0, 1;\n}\n"
    : "+f"(d[0]),"+f"(d[1]),"+f"(d[2]),"+f"(d[3]),"+f"(d[4]),"+f"(d[5]),"+f"(d[6]),"+f"(d[7]),"+f"(d[8]),"+f"(d[9]),"+f"(d[10]),"+f"(d[11]),"+f"(d[12]),"+f"(d[13]),"+f"(d[14]),"+f"(d[15]),"+f"(d[16]),"+f"(d[17]),"+f"(d[18]),"+f"(d[19]),"+f"(d[20]),"+f"(d[21]),"+f"(d[22]),"+f"(d[23]),"+f"(d[24]),"+f"(d[25]),"+f"(d[26]),"+f"(d[27]),"+f"(d[28]),"+f"(d[29]),"+f"(d[30]),"+f"(d[31]),"+f"(d[32]),"+f"(d[33]),"+f"(d[34]),"+f"(d[35]),"+f"(d[36]),"+f"(d[37]),"+f"(d[38]),"+f"(d[39]),"+f"(d[40]),"+f"(d[41]),"+f"(d[42]),"+f"(d[43]),"+f"(d[44]),"+f"(d[45]),"+f"(d[46]),"+f"(d[47]) : "l"(da), "l"(db), "n"(SC));
}
template<int SC> __device__ __forceinline__ void wg_rs112(float (&d)[56], uint32_t a0, uint32_t a1, uint32_t a2, uint32_t a3, uint64_t db) {
  asm volatile("{\n.reg .pred p;\nsetp.ne.b32 p, %61, 0;\nwgmma.mma_async.sync.aligned.m64n112k16.f32.bf16.bf16 {%0,%1,%2,%3,%4,%5,%6,%7,%8,%9,%10,%11,%12,%13,%14,%15,%16,%17,%18,%19,%20,%21,%22,%23,%24,%25,%26,%27,%28,%29,%30,%31,%32,%33,%34,%35,%36,%37,%38,%39,%40,%41,%42,%43,%44,%45,%46,%47,%48,%49,%50,%51,%52,%53,%54,%55}, {%56,%57,%58,%59}, %60, p, 1, 1, 0;\n}\n"
    : "+f"(d[0]),"+f"(d[1]),"+f"(d[2]),"+f"(d[3]),"+f"(d[4]),"+f"(d[5]),"+f"(d[6]),"+f"(d[7]),"+f"(d[8]),"+f"(d[9]),"+f"(d[10]),"+f"(d[11]),"+f"(d[12]),"+f"(d[13]),"+f"(d[14]),"+f"(d[15]),"+f"(d[16]),"+f"(d[17]),"+f"(d[18]),"+f"(d[19]),"+f"(d[20]),"+f"(d[21]),"+f"(d[22]),"+f"(d[23]),"+f"(d[24]),"+f"(d[25]),"+f"(d[26]),"+f"(d[27]),"+f"(d[28]),"+f"(d[29]),"+f"(d[30]),"+f"(d[31]),"+f"(d[32]),"+f"(d[33]),"+f"(d[34]),"+f"(d[35]),"+f"(d[36]),"+f"(d[37]),"+f"(d[38]),"+f"(d[39]),"+f"(d[40]),"+f"(d[41]),"+f"(d[42]),"+f"(d[43]),"+f"(d[44]),"+f"(d[45]),"+f"(d[46]),"+f"(d[47]),"+f"(d[48]),"+f"(d[49]),"+f"(d[50]),"+f"(d[51]),"+f"(d[52]),"+f"(d[53]),"+f"(d[54]),"+f"(d[55]) : "r"(a0), "r"(a1), "r"(a2), "r"(a3), "l"(db), "n"(SC));
}
template<int SC> __device__ __forceinline__ void wg_sp48(float (&d)[24], uint32_t a0, uint32_t a1, uint32_t a2, uint32_t a3, uint64_t db, uint32_t meta) {
  asm volatile("{\n.reg .pred p;\nsetp.ne.b32 p, %30, 0;\nwgmma.mma_async.sp.sync.aligned.m64n48k32.f32.bf16.bf16 {%0,%1,%2,%3,%4,%5,%6,%7,%8,%9,%10,%11,%12,%13,%14,%15,%16,%17,%18,%19,%20,%21,%22,%23}, {%24,%25,%26,%27}, %28, %29, 0, p, 1, 1, 1;\n}\n"
    : "+f"(d[0]),"+f"(d[1]),"+f"(d[2]),"+f"(d[3]),"+f"(d[4]),"+f"(d[5]),"+f"(d[6]),"+f"(d[7]),"+f"(d[8]),"+f"(d[9]),"+f"(d[10]),"+f"(d[11]),"+f"(d[12]),"+f"(d[13]),"+f"(d[14]),"+f"(d[15]),"+f"(d[16]),"+f"(d[17]),"+f"(d[18]),"+f"(d[19]),"+f"(d[20]),"+f"(d[21]),"+f"(d[22]),"+f"(d[23]) : "r"(a0), "r"(a1), "r"(a2), "r"(a3), "l"(db), "r"(meta), "n"(SC));
}
template<int SC> __device__ __forceinline__ void wg_ss192(float (&d)[96], uint64_t da, uint64_t db) {
  asm volatile("{\n.reg .pred p;\nsetp.ne.b32 p, %98, 0;\nwgmma.mma_async.sync.aligned.m64n192k16.f32.bf16.bf16 {%0,%1,%2,%3,%4,%5,%6,%7,%8,%9,%10,%11,%12,%13,%14,%15,%16,%17,%18,%19,%20,%21,%22,%23,%24,%25,%26,%27,%28,%29,%30,%31,%32,%33,%34,%35,%36,%37,%38,%39,%40,%41,%42,%43,%44,%45,%46,%47,%48,%49,%50,%51,%52,%53,%54,%55,%56,%57,%58,%59,%60,%61,%62,%63,%64,%65,%66,%67,%68,%69,%70,%71,%72,%73,%74,%75,%76,%77,%78,%79,%80,%81,%82,%83,%84,%85,%86,%87,%88,%89,%90,%91,%92,%93,%94,%95}, %96, %97, p, 1, 1, 0, 1;\n}\n"
    : "+f"(d[0]),"+f"(d[1]),"+f"(d[2]),"+f"(d[3]),"+f"(d[4]),"+f"(d[5]),"+f"(d[6]),"+f"(d[7]),"+f"(d[8]),"+f"(d[9]),"+f"(d[10]),"+f"(d[11]),"+f"(d[12]),"+f"(d[13]),"+f"(d[14]),"+f"(d[15]),"+f"(d[16]),"+f"(d[17]),"+f"(d[18]),"+f"(d[19]),"+f"(d[20]),"+f"(d[21]),"+f"(d[22]),"+f"(d[23]),"+f"(d[24]),"+f"(d[25]),"+f"(d[26]),"+f"(d[27]),"+f"(d[28]),"+f"(d[29]),"+f"(d[30]),"+f"(d[31]),"+f"(d[32]),"+f"(d[33]),"+f"(d[34]),"+f"(d[35]),"+f"(d[36]),"+f"(d[37]),"+f"(d[38]),"+f"(d[39]),"+f"(d[40]),"+f"(d[41]),"+f"(d[42]),"+f"(d[43]),"+f"(d[44]),"+f"(d[45]),"+f"(d[46]),"+f"(d[47]),"+f"(d[48]),"+f"(d[49]),"+f"(d[50]),"+f"(d[51]),"+f"(d[52]),"+f"(d[53]),"+f"(d[54]),"+f"(d[55]),"+f"(d[56]),"+f"(d[57]),"+f"(d[58]),"+f"(d[59]),"+f"(d[60]),"+f"(d[61]),"+f"(d[62]),"+f"(d[63]),"+f"(d[64]),"+f"(d[65]),"+f"(d[66]),"+f"(d[67]),"+f"(d[68]),"+f"(d[69]),"+f"(d[70]),"+f"(d[71]),"+f"(d[72]),"+f"(d[73]),"+f"(d[74]),"+f"(d[75]),"+f"(d[76]),"+f"(d[77]),"+f"(d[78]),"+f"(d[79]),"+f"(d[80]),"+f"(d[81]),"+f"(d[82]),"+f"(d[83]),"+f"(d[84]),"+f"(d[85]),"+f"(d[86]),"+f"(d[87]),"+f"(d[88]),"+f"(d[89]),"+f"(d[90]),"+f"(d[91]),"+f"(d[92]),"+f"(d[93]),"+f"(d[94]),"+f"(d[95]) : "l"(da), "l"(db), "n"(SC));
}

constexpr uint32_t SBC = 1024;
constexpr int ROWB = 2 * 224 * 384;
constexpr int TB = 11;
constexpr int KS = 832;
constexpr int KSLOT = 22 * KS;
constexpr int SM_X1 = 0;
constexpr int SM_X2 = SM_X1 + 24576;
constexpr int SM_X0 = SM_X2 + 24576;
constexpr int SM_W = SM_X0 + 18432;
constexpr int SM_K = SM_W + 55296;
constexpr int SM_V = SM_K + 2 * KSLOT;
constexpr int SM_Q = SM_V + 22 * 1536;
constexpr int SM_O = SM_Q + 24576;
constexpr int SM_RPB = SM_O + 12288;
constexpr int SM_BAR = SM_RPB + 768;
constexpr int SM_A_TOTAL = SM_BAR + 256;
constexpr int SM_TWO = SM_X0 + 24576;
constexpr int SM_TST = SM_TWO + 36864;
enum { B_FULL = 0, B_EMPTY = 3, B_TIN = 6, B_TFREE = 9, B_WK = 11, B_WQ, B_WO, B_Q0, B_OTAIL, B_ODONE = B_OTAIL + 2, B_KFREE, B_VFREE, B_COUNT };
enum { N_KRDY = 4, N_QK0, N_QK1, N_VQ0, N_VQ1, N_PVISS };

#define NL 2
#define OPT 0
#define SPL 4
#define RA 152
#define RG 184
__device__ int g_flags[TB * 56];

#define TR(role, it, k)
#define TRDECL
#define TRARG
#define TRPASS
#define TRDUMP
#define TRB(it, k)
#define TR2(blk, k)

struct GemmCtx {
  uint32_t bar;
  uint32_t kC, vC, qC;
  uint32_t kH, vH;
  bool hvalid;
};

template <int STRIDE> __device__ __forceinline__ void dump12(uint32_t a, const uint32_t (&r)[12]) {
#pragma unroll
  for (int j = 0; j < 3; j++) stsm4(a + j * 2 * STRIDE, r[4 * j], r[4 * j + 1], r[4 * j + 2], r[4 * j + 3]);
}
template <int N> __device__ __forceinline__ void pack12(uint32_t (&r)[12], const float (&d)[N], int off) {
#pragma unroll
  for (int j = 0; j < 12; j++) r[j] = pack2(d[off + 2 * j], d[off + 2 * j + 1]);
}
template <int XS, int K0, int K1> __device__ __forceinline__ void issue_core(float (&d)[72]) {
  constexpr uint64_t da = mkdesc(SBC + XS, 16, 1024, 1), db = mkdesc(SBC + SM_W, 6144, 256, 3);
  wg_fence();
  if (K0 == 0) wg_ss144<0>(d, da, db);
#pragma unroll
  for (int k = K0 ? K0 : 1; k < K1; k++) wg_ss144<1>(d, da + (k >> 2) * 512 + (k & 3) * 2, db + k * 32);
  wg_commit();
}
template <int K0, int K1> __device__ __forceinline__ void issue_halo(float (&d)[48]) {
  constexpr uint64_t da = mkdesc(SBC + SM_X0 - 2048, 16, 1024, 1), db = mkdesc(SBC + SM_W, 6144, 256, 3);
  wg_fence();
  if (K0 == 0) wg_ss96<0>(d, da, db);
#pragma unroll
  for (int k = K0 ? K0 : 1; k < K1; k++) wg_ss96<1>(d, da + (k >> 2) * 384 + (k & 3) * 2, db + k * 32);
  wg_commit();
}
template <int ST, int BYTES> __device__ __forceinline__ void release_stage(const GemmCtx& c, bool on) {
  asm volatile("{\n.reg .pred p, q;\n.reg .b32 ra;\nsetp.ne.b32 q, %2, 0;\nelect.sync _|p, 0xffffffff;\nand.pred p, p, q;\n"
               "mapa.shared::cluster.u32 ra, %1, %4;\n"
               "@p mbarrier.arrive.expect_tx.shared::cta.b64 _, [%0], %3;\n@p mbarrier.arrive.shared::cluster.b64 _, [ra];\n}"
               ::"r"(c.bar + (B_FULL + ST) * 8), "r"(c.bar + (B_EMPTY + ST) * 8), "r"((int)on), "n"(BYTES / 4), "n"(ST) : "memory");
}
__device__ __forceinline__ void load_w(const CUtensorMap* m, uint32_t dst, uint32_t bar, int col) {
  asm volatile("cp.async.bulk.tensor.2d.shared::cluster.global.mbarrier::complete_tx::bytes [%0], [%1, {%3,%4}], [%2];"
               ::"r"(dst), "l"(m), "r"(bar), "r"(col), "r"(0) : "memory");
}
template <int BYTES> __device__ __forceinline__ void send_o(uint32_t dst, uint32_t src, uint32_t bar, int cta) {
  asm volatile("{\n.reg .b32 rd, rb;\nmapa.shared::cluster.u32 rd, %0, %3;\nmapa.shared::cluster.u32 rb, %2, %3;\n"
               "cp.async.bulk.shared::cluster.shared::cta.mbarrier::complete_tx::bytes [rd], [%1], %4, [rb];\n}"
               ::"r"(dst), "r"(src), "r"(bar), "r"(cta), "n"(BYTES) : "memory");
}
__device__ __forceinline__ void tail_free(uint32_t bar) {
  uint32_t ln; asm volatile("mov.u32 %0, %%laneid;" : "=r"(ln));
  if (ln < 4) mbar_arrive_remote(bar, ln);
}
__device__ __forceinline__ void publish(uint32_t bar) {
  fence_async();
  __syncwarp();
  mbar_arrive_elect(bar);
}

template <bool FIRST, bool LAST>
__device__ __forceinline__ void gemm_iter(const GemmCtx& c, int b, uint32_t (&pk)[12], uint32_t (&pv)[12], uint32_t (&pq)[12], const CUtensorMap* mwo TRARG) {
  const uint32_t bar = c.bar;
  const uint32_t pa = b & 1;
  const bool w = b >= 0;
  const uint32_t ko = pa * KSLOT, vx = pa * 16, qx = pa * 128;
  float H[48], C[72];
  uint32_t hk[12], hv[12], pv2[12];
  TR(2, b, 0);
  if (FIRST) mbar_wait(bar + (B_FULL + 0) * 8, pa);
  if (!FIRST) dump12<256>(c.qC ^ (qx ^ 192), pq);
  if (w) nb_sync(N_QK1, 256);
  TR(2, b, 2);
  if (FIRST) TR(2, b - 1, 6);
  issue_halo<0, 8>(H);
  TR(2, b, 3);
  if (!FIRST) {
    if (w) mbar_wait(bar + B_KFREE * 8, pa);
    dump12<128>(c.kC + ko, pk);
  }
  issue_halo<8, 12>(H);
  TR(2, b, 4);
  if (!LAST) {
    mbar_wait(bar + (B_FULL + 2) * 8, pa);
    if (FIRST && NL == 2) mbar_wait(bar + B_WQ * 8, 0);
    TR(2, b, 13);
    if (FIRST) TR(2, b - 1, 7);
    issue_core<SM_X2, 0, 8>(C);
    TR(2, b, 5);
    if (!FIRST) fence_async();
    wg_wait<1>(); pin(H);
    release_stage<0, 18432>(c, true);
  } else {
    fence_async();
    nb_arrive(N_VQ0, 288); nb_arrive(N_VQ1, 288);
    wg_wait<0>(); pin(H);
    tail_free(bar + (B_TFREE + 1) * 8);
    nb_sync(2, 128);
    if (!c.hvalid && elect_one()) {
      mbar_expect(bar + B_WO * 8, 36864);
      asm volatile("cp.async.bulk.tensor.3d.shared::cluster.global.mbarrier::complete_tx::bytes [%0], [%1, {%3,%4,%5}], [%2];"
                   ::"r"(bar - SM_BAR + SM_TWO), "l"(mwo), "r"(bar + B_WO * 8), "r"(0), "r"(0), "r"((blockIdx.x & 1) * 3) : "memory");
    }
    __syncwarp();
  }
  pack12(hk, H, 0);
  if (c.hvalid) dump12<128>(c.kH + ko, hk);
  pack12(hv, H, 24);
  if (!LAST) {
    issue_core<SM_X2, 8, 12>(C);
    if (w) { nb_arrive(N_VQ0, 288); nb_arrive(N_VQ1, 288); }
    else if (!FIRST) { __syncwarp(); mbar_arrive_elect(bar + B_Q0 * 8); }
    mbar_wait(bar + (B_FULL + 1) * 8, pa);
    TR(2, b, 6);
    wg_wait<0>(); pin(C);
    TR(2, b, 7);
    pack12(pk, C, 0);
    dump12<128>(c.kC + ko + 64, pk);
    release_stage<2, 24576>(c, b < 11);
    if (b == 11) tail_free(bar + B_TFREE * 8);
    pack12(pv2, C, 24);
    pack12(pq, C, 48);
    TR(2, b, 8);
    issue_core<SM_X1, 0, SPL>(C);
    if (w) nb_sync(N_PVISS, 384);
    issue_core<SM_X1, SPL, 8>(C);
    TR(2, b, 9);
  }
  if (!FIRST) fence_async();
  TR(2, b, 14);
  if (!LAST) issue_core<SM_X1, 8, 12>(C);
  if (!FIRST) nb_arrive(N_KRDY, 256);
  TR(2, b, 1);
  if (!LAST) mbar_wait(bar + (B_FULL + 0) * 8, pa ^ 1);
  if (w) mbar_wait(bar + B_VFREE * 8, pa);
  TR(2, b, 10);
  if (!FIRST) dump12<128>(c.vC ^ vx, pv);
  if (!LAST) dump12<256>(c.qC ^ qx, pq);
  if (c.hvalid) dump12<128>(c.vH ^ vx, hv);
  if (LAST) { fence_async(); nb_arrive(N_VQ0, 256); nb_arrive(N_VQ1, 256); return; }
  dump12<128>((c.vC ^ vx ^ 16) + 768, pv2);
  TR(2, b, 11);
  wg_wait<0>(); pin(C);
  TR(2, b, 12);
  release_stage<1, 24576>(c, b < 11);
  pack12(pk, C, 0);
  pack12(pv, C, 24);
  pack12(pq, C, 48);
}

template <int IN> __device__ __forceinline__ void issue_proj(float (&D)[48]) {
  constexpr uint64_t da = mkdesc(SBC + IN, 128, 768, 0), db = mkdesc(SBC + SM_TWO, 12288, 512, 2);
  wg_fence();
  wg_ss96<0>(D, da, db);
#pragma unroll
  for (int k = 1; k < 12; k++) wg_ss96<1>(D, da + (k / 3) * 384 + (k % 3) * 16, db + k * 64);
  wg_commit();
}
__device__ __forceinline__ void store_proj(const float (&D)[48], const CUtensorMap* m, uint32_t st, uint32_t sta, int row, int col, int ch) {
#pragma unroll
  for (int q = 0; q < 6; q++)
    stsm4((sta ^ ((q & 1) * 32)) + (q >> 1) * 1024,
          pack2(D[8 * q], D[8 * q + 1]), pack2(D[8 * q + 2], D[8 * q + 3]), pack2(D[8 * q + 4], D[8 * q + 5]), pack2(D[8 * q + 6], D[8 * q + 7]));
  fence_async();
  __syncwarp();
  if ((threadIdx.x & 31) == 0) {
    asm volatile("cp.async.bulk.tensor.4d.global.shared::cta.bulk_group [%0, {%2,%3,%4,%5}], [%1];" ::"l"(m), "r"(st), "r"(0), "r"(row), "r"(col), "r"(ch) : "memory");
    asm volatile("cp.async.bulk.commit_group;" ::: "memory");
  }
  __syncwarp();
}

__device__ __forceinline__ float fold(float a, float b, float t, int useb) {
  float r;
  asm("{\n.reg .pred p;\nsetp.ne.b32 p, %4, 0;\nfma.rn.f32 %0, %1, 0f3E553B95, %3;\n@p fma.rn.f32 %0, %2, 0f3E553B95, %3;\n}"
      : "=&f"(r) : "f"(a), "f"(b), "f"(t), "r"(useb));
  return r;
}
template <int U, int L>
__device__ __forceinline__ void softmax_tile(const float (&SA)[56], const float (&SB)[56], const float (&T)[16], int b0, int b1,
                                             uint32_t (&P)[28], float (&sx)[8]) {
  float lu[14], ll[14];
#pragma unroll
  for (int j = 0; j < 7; j++) {
    constexpr int sh = U == L ? 2 : 0;
    const float tu0 = T[2 * j + sh], tu1 = T[2 * j + 1 + sh], tl0 = T[2 * j], tl1 = T[2 * j + 1];
    lu[2 * j]     = fold(SA[4 * (U + j)],     SB[4 * (U + j)],     tu0, b0);
    ll[2 * j]     = fold(SA[4 * (L + j) + 2], SB[4 * (L + j) + 2], tl0, b0);
    lu[2 * j + 1] = fold(SA[4 * (U + j) + 1], SB[4 * (U + j) + 1], tu1, b1);
    ll[2 * j + 1] = fold(SA[4 * (L + j) + 3], SB[4 * (L + j) + 3], tl1, b1);
  }
  float mu = lu[0], ml = ll[0], mu2 = lu[1], ml2 = ll[1];
#pragma unroll
  for (int j = 1; j < 7; j++) { mu = fmaxf(mu, lu[2 * j]); mu2 = fmaxf(mu2, lu[2 * j + 1]); ml = fmaxf(ml, ll[2 * j]); ml2 = fmaxf(ml2, ll[2 * j + 1]); }
  mu = fmaxf(mu, mu2); ml = fmaxf(ml, ml2);
  { const float a1 = __shfl_xor_sync(0xffffffffu, mu, 1), a2 = __shfl_xor_sync(0xffffffffu, mu, 2), a3 = __shfl_xor_sync(0xffffffffu, mu, 3);
    const float c1 = __shfl_xor_sync(0xffffffffu, ml, 1), c2 = __shfl_xor_sync(0xffffffffu, ml, 2), c3 = __shfl_xor_sync(0xffffffffu, ml, 3);
    mu = fmaxf(fmaxf(mu, a1), fmaxf(a2, a3)); ml = fmaxf(fmaxf(ml, c1), fmaxf(c2, c3)); }
  float su = 0.f, sl = 0.f;
#pragma unroll
  for (int c = 0; c < 14; c++) {
    const int iu = (c >> 1) * 4 + (c & 1) * 2;
    if (c >= U && c < U + 7) {
      float e0 = ex2(lu[2 * (c - U)] - mu), e1 = ex2(lu[2 * (c - U) + 1] - mu);
      su = c == U ? e0 + e1 : (su + e0) + e1; P[iu] = pack2(e0, e1);
    } else P[iu] = 0u;
    if (c >= L && c < L + 7) {
      float e0 = ex2(ll[2 * (c - L)] - ml), e1 = ex2(ll[2 * (c - L) + 1] - ml);
      sl = c == L ? e0 + e1 : (sl + e0) + e1; P[iu + 1] = pack2(e0, e1);
    } else P[iu + 1] = 0u;
  }
  sx[0] = su; sx[4] = sl;
#pragma unroll
  for (int k = 1; k < 4; k++) { sx[k] = __shfl_xor_sync(0xffffffffu, su, k); sx[4 + k] = __shfl_xor_sync(0xffffffffu, sl, k); }
}

struct Maps { CUtensorMap xc, xh, w, os, wo, ot; };

__global__ void __cluster_dims__(4, 1, 1) __launch_bounds__(512, 1)
na_attn_kernel(const __nv_bfloat16* __restrict__ x, const __nv_bfloat16* __restrict__ wqkv, const __nv_bfloat16* __restrict__ rpb, const __grid_constant__ Maps mp) {
  extern __shared__ __align__(1024) uint8_t smem_raw[];
  const uint32_t sb = smem_u32(smem_raw);
  if ((sb & 0x3FFFF) != SBC) return;
  const uint32_t bar = sb + SM_BAR;
  TR2(blockIdx.x, 0);
  const int tid = threadIdx.x, lane = tid & 31;
  const int warp = __shfl_sync(0xffffffffu, tid >> 5, 0);
  const int head = blockIdx.x & 3, cl = blockIdx.x >> 2;
  const int par = cl / 7, strip = cl - par * 7, ph = par >> 1, pw = par & 1;

  uint4 wv[2 * NL];
  const int va = head == 1;
  const uint32_t wdst = sb + SM_W + (va + ((tid >> 1) & 1)) * 6144 + (tid >> 2) * 32 + ((tid ^ (tid >> 4)) & 1) * 16;
  if (warp < 12) asm volatile("barrier.cluster.arrive.relaxed.aligned;" ::: "memory");
  {
    const uint32_t wo0 = (tid >> 2) * 1152 + head * 96 + va * 32 + (tid & 3) * 16;
#pragma unroll
    for (int i = 0; i < 2 * NL; i++)
      asm volatile("{\n.reg .pred p;\nsetp.lt.u32 p, %5, 384;\n@p ld.global.nc.v4.b32 {%0,%1,%2,%3}, [%4];\n}"
                   : "=r"(wv[i].x), "=r"(wv[i].y), "=r"(wv[i].z), "=r"(wv[i].w)
                   : "l"(reinterpret_cast<const uint8_t*>(wqkv) + wo0 + (i & 1) * 96 * 1152 + ((i / 2 + 1) % 3) * 384), "r"(tid));
  }
  if (warp < 8) {
    asm volatile("setmaxnreg.inc.sync.aligned.u32 %0;" ::"n"(RA));
    float rv = -INFINITY;
    if (tid < 169) rv = __bfloat162float(rpb[head * 169 + tid]) * 1.4426950408889634f;
    if (tid < 192) {
      const int kc = (tid & 15) + 3, wc = (tid >> 4) % 6;
      sts128(tid < 96 ? sb + SM_K + kc * KS + wc * 128 + 48 : sb + SM_V + kc * 1536 + wc * 128 + (6 + (kc & 1)) * 16, make_uint4(0, 0, 0, 0));
    }
#pragma unroll
    for (int i = 0; i < 2 * NL; i++) sts128(wdst + (i & 1) * 3072 + (i / 2) * 18432, wv[i]);
    fence_async();
    asm volatile("bar.arrive 1, 384;" ::: "memory");
    if (tid < 182) asm volatile("st.shared.f32 [%0], %1;" ::"r"(sb + SM_RPB + tid * 4), "f"(rv) : "memory");
    const int j = warp >> 2, w = warp & 3;
    int variant = w;
    if (strip == 0 && j == 0 && w < 2) variant = 4;
    if (strip == 6 && j == 1 && w >= 2) variant = 5;
    const uint32_t qa = sb + SM_Q + (8 * j + 2 * w + ((lane >> 3) & 1)) * 1536 + (lane >> 4) * 256 + (((lane & 7) * 16) ^ (((lane >> 3) & 1) * 64));
    uint32_t oa = sb + SM_O + j * 6144 + (2 * w + ((lane >> 3) & 1)) * 768 + (lane >> 4) * 128 + (lane & 7) * 16;
    const uint64_t dK = mkdesc(SBC + SM_K, 128, KS, 0) + j * (8 * KS / 16);
    const uint64_t dV = mkdesc(SBC + SM_V, 768, 128, 0) + j * (8 * 1536 / 16);
    asm volatile("barrier.cluster.wait.aligned;" ::: "memory");
    asm volatile("bar.sync 3, 256;" ::: "memory");
    float T[16];
    TRDECL;
    int b0 = 0, b1 = 0;
    uint32_t meta = 0;
    uint32_t q[12];
    mbar_wait(bar + B_Q0 * 8, 0);
#pragma unroll
    for (int k = 0; k < 3; k++) ldsm4(qa + k * 512, q[4 * k], q[4 * k + 1], q[4 * k + 2], q[4 * k + 3]);
#pragma unroll 1
    for (int b = 0; b < 14; b++) {
      const uint32_t pa = b & 1;
      float SA[56], SB[56];
      const uint64_t dA = dK + pa * (KSLOT >> 4), dB = dK + (pa ^ 1) * (KSLOT >> 4);
      TR(0, b, 0);
      nb_sync(N_KRDY + j, 256);
      TR(0, b, 1);
      TR(0, b - 1, 9);
      wg_fence();
      wg_rs112<0>(SA, q[0], q[1], q[2], q[3], dA);
      wg_rs112<0>(SB, q[0], q[1], q[2], q[3], dB);
      wg_rs112<1>(SA, q[4], q[5], q[6], q[7], dA + 16);
      wg_rs112<1>(SB, q[4], q[5], q[6], q[7], dB + 16);
      wg_rs112<1>(SA, q[8], q[9], q[10], q[11], dA + 32);
      wg_rs112<1>(SB, q[8], q[9], q[10], q[11], dB + 32);
      wg_commit();
      if (b + j < 14) nb_arrive(N_QK0 + j, 256);
      TR(0, b, 2);
      if (b <= 1 || b == 13) {
        uint32_t ln; asm volatile("mov.u32 %0, %%laneid;" : "=r"(ln));
        const int g = ln >> 2, t = ln & 3;
        const int sw = b == 0 ? max(g + 1, 4) : (b == 13 ? min(g + 1, 5) : g + 1);
        const int i0 = 2 * t, i1 = 2 * t + 1;
        b0 = i0 <= sw - 2; b1 = i1 <= sw - 2;
        const uint32_t tb = sb + SM_RPB + (variant < 4 ? 3 : variant + 1 - 2 * w) * 4;
        const uint32_t ra0 = tb + (i0 == sw - 1 ? 13 : i0 + 8 * b0 - g + 2) * 52;
        const uint32_t ra1 = tb + (i1 == sw - 1 ? 13 : i1 + 8 * b1 - g + 2) * 52;
#pragma unroll
        for (int jj = 0; jj < 8; jj++) { T[2 * jj] = lds_f32(ra0 + jj * 4); T[2 * jj + 1] = lds_f32(ra1 + jj * 4); }
        meta = ((0x5555u & ((1u << (2 * (sw - 1))) - 1)) ^ 0xDD88u ^ (((t ^ b) & 1) ? 0x5555u : 0u)) * 0x10001u;
      } else meta ^= 0x55555555u;
      if (b >= 12) oa += b == 12 ? warp * 1536 - (SM_O - SM_Q) : 1536;
      wg_wait<0>(); pin(SA); pin(SB);
      mbar_arrive_elect(bar + B_KFREE * 8);
      TR(0, b, 3);
      TR(0, b - 1, 10);
      uint32_t P[28];
      float sx[8];
      switch (variant) {
        case 0: softmax_tile<0, 1>(SA, SB, T, b0, b1, P, sx); break;
        case 1: softmax_tile<2, 3>(SA, SB, T, b0, b1, P, sx); break;
        case 2: softmax_tile<4, 5>(SA, SB, T, b0, b1, P, sx); break;
        case 3: softmax_tile<6, 7>(SA, SB, T, b0, b1, P, sx); break;
        case 4: softmax_tile<3, 3>(SA, SB, T, b0, b1, P, sx); break;
        default: softmax_tile<4, 4>(SA, SB, T, b0, b1, P, sx); break;
      }
      float O[24];
      TR(0, b, 4);
      nb_sync(N_VQ0 + j, b == 13 ? 256 : 288);
      TR(0, b, 5);
#pragma unroll
      for (int k = 0; k < 3; k++) ldsm4(qa + (pa ^ 1) * 128 + k * 512, q[4 * k], q[4 * k + 1], q[4 * k + 2], q[4 * k + 3]);
      wg_fence();
      wg_sp48<0>(O, P[0], P[1], P[2], P[3], dV, meta);
#pragma unroll
      for (int s = 1; s < 7; s++) wg_sp48<1>(O, P[4 * s], P[4 * s + 1], P[4 * s + 2], P[4 * s + 3], dV + s * 192, meta);
      wg_commit();
      if (b < 12 || (!(OPT & 2) && b == 13)) nb_arrive(N_PVISS, 384);
      TR(0, b, 6);
      if (b == 13) mbar_wait(bar + (B_TFREE + 1) * 8, 0);
      wg_wait<0>(); pin(O);
      mbar_arrive_elect(bar + B_VFREE * 8);
      TR(0, b, 7);
      float ru, rl;
      asm("rcp.approx.ftz.f32 %0, %1;" : "=f"(ru) : "f"(((fmaf(O[0], 0.f, sx[0]) + sx[1]) + sx[2]) + sx[3]));
      asm("rcp.approx.ftz.f32 %0, %1;" : "=f"(rl) : "f"(((fmaf(O[2], 0.f, sx[4]) + sx[5]) + sx[6]) + sx[7]));
#pragma unroll
      for (int i = 0; i < 3; i++)
        stsm4(oa + i * 256, pack2(O[8 * i] * ru, O[8 * i + 1] * ru), pack2(O[8 * i + 2] * rl, O[8 * i + 3] * rl),
              pack2(O[8 * i + 4] * ru, O[8 * i + 5] * ru), pack2(O[8 * i + 6] * rl, O[8 * i + 7] * rl));
      if (b < 13) publish(bar + (b < TB ? B_ODONE : B_OTAIL + j) * 8);
      else {
        fence_async();
        if (OPT & 2) nb_arrive(N_PVISS, 384);
        __syncwarp();
        if (elect_one()) {
#pragma unroll
          for (int d = 0; d < 2; d++)
            send_o<1536>(sb + SM_X0 + head * 6144 + (2 * j + (w & 1)) * 1536, sb + SM_Q + warp * 3072 + 1536, bar + (B_TIN + 2) * 8, (w & 2) + (d ^ (head & 1)));
        }
        __syncwarp();
      }
      TR(0, b, 8);
    }
    TRDUMP;
    cluster_sync();
  } else if (warp < 12) {
    TRDECL;
    TR(2, -3, 0);
    asm volatile("setmaxnreg.inc.sync.aligned.u32 %0;" ::"n"(RG));
    TR(2, -3, 1);
    GemmCtx c;
    c.bar = bar;
    const int gw = warp - 8, tk = gw * 16 + (lane & 15), hi = lane >> 4;
    { const int col = tk >> 2, i = tk & 3;
      c.kC = sb + SM_K + (col + 3) * KS + hi * 128 + i * 16;
      c.vC = sb + SM_V + (col + 3) * 1536 + hi * 128 + (2 * i + ((col + 3) & 1)) * 16;
      c.qC = sb + SM_Q + col * 1536 + hi * 256 + (col & 1) * 64 + i * 16; }
    { const int ci = (tk >> 3) - 2, kc = ci < 3 ? ci : ci + 16, i = tk & 7; c.hvalid = gw > 0;
      c.kH = sb + SM_K + kc * KS + hi * 128 + i * 16;
      c.vH = sb + SM_V + kc * 1536 + hi * 128 + (i >> 2) * 768 + (2 * (i & 3) + ((kc ^ (i >> 2)) & 1)) * 16; }
    asm volatile("barrier.cluster.wait.aligned;" ::: "memory");
    TR(2, -3, 2);
    if (elect_one()) { mbar_expect(bar + B_FULL * 8, 4608); mbar_expect(bar + (B_FULL + 1) * 8, 6144); mbar_expect(bar + (B_FULL + 2) * 8, 6144); }
    __syncwarp();
#pragma unroll
    for (int i = 0; i < 2 * NL; i++) sts128(wdst + (i & 1) * 3072 + (i / 2) * 18432, wv[i]);
    fence_async();
    TR(2, -3, 3);
    asm volatile("bar.sync 1, 384;" ::: "memory");
    TR(2, -3, 4);
    mbar_wait(bar + B_WK * 8, 0);
    TR(2, -3, 5);
    uint32_t pk[12], pv[12], pq[12];
    gemm_iter<true, false>(c, -2, pk, pv, pq, &mp.wo TRPASS);
    TR2(blockIdx.x, 4);
#pragma unroll 1
    for (int b = -1; b < 12; b++) gemm_iter<false, false>(c, b, pk, pv, pq, &mp.wo TRPASS);
    TR2(blockIdx.x, 6);
    gemm_iter<false, true>(c, 12, pk, pv, pq, &mp.wo TRPASS);
    TR(2, 13, 0);
    mbar_wait(bar + B_WO * 8, 0);
    mbar_wait(bar + B_TIN * 8, 0);
    const uint32_t st = sb + gw * 3072;
    const uint32_t sta = st + (lane & 15) * 64 + ((hi ^ ((lane >> 1) & 3)) * 16);
    const int oc = ph * 112 + strip * 16 + 8 * (gw >> 1) + 4 * (head >> 1) + 2 * (gw & 1), och = pw * 6 + (head & 1) * 3;
    float D0[48], D1[48];
    nb_sync(N_PVISS, 384);
    TR(2, 13, 1);
    issue_proj<SM_X2>(D0);
    mbar_wait(bar + (B_TIN + 1) * 8, 0);
    issue_proj<SM_X1>(D1);
    TR(2, 13, 2);
    wg_wait<1>(); pin(D0);
    store_proj(D0, &mp.ot, st + SM_TST, sta + SM_TST, 8 * TB, oc, och);
    TR(2, 13, 3);
    mbar_wait(bar + (B_TIN + 2) * 8, 0);
    TR(2, 13, 4);
    issue_proj<SM_X0>(D0);
    asm volatile("barrier.cluster.arrive.relaxed.aligned;" ::: "memory");
    wg_wait<1>(); pin(D1);
    TR(2, 13, 5);
    store_proj(D1, &mp.ot, st + SM_X2, sta + SM_X2, 8 * TB + 8, oc, och);
    wg_wait<0>(); pin(D0);
    TR(2, 13, 6);
    store_proj(D0, &mp.ot, st + SM_X2 + 12288, sta + SM_X2 + 12288, 8 * TB + 16, oc, och);
    TR(2, 13, 7);
    if (lane == 0) asm volatile("cp.async.bulk.wait_group.read 0;" ::: "memory");
    __syncwarp();
    TR(2, 13, 8);
    TR2(blockIdx.x, 2);
    TRDUMP;
    asm volatile("barrier.cluster.wait.aligned;" ::: "memory");
  } else {
    if (warp == 12) {
      if (elect_one()) {
        mbar_init(bar + B_WK * 8, 1);
#pragma unroll
        for (int i = 0; i < NL; i++) load_w(&mp.w, sb + SM_W + (3 * i + 2 - 2 * va) * 6144, bar + B_WK * 8, ((i + 1) % 3) * 192 + head * 48 + 32 - 32 * va);
        asm volatile("prefetch.tensormap [%0];" ::"l"(head ? &mp.xc : &mp.xh) : "memory");
        mbar_expect(bar + B_WK * 8, NL * 6144);
      }
    } else if (warp == 15) {
      const int col = min(max(strip * 16 - 3 + min(lane, 21), 0), 111);
      const uint8_t* p = reinterpret_cast<const uint8_t*>(x) + (uint32_t)(head * ROWB + (ph * 112 + col) * 768 + pw * 384);
#pragma unroll
      for (int i = 0; i < 3; i++) asm volatile("prefetch.global.L2 [%0];" ::"l"(p + i * 128));
    } else if (elect_one()) {
      if (warp == 13) {
#pragma unroll
        for (int i = 0; i < B_WK; i++) mbar_init(bar + i * 8, i < B_EMPTY ? 4 : (i < B_TIN ? 16 : (i < B_TFREE ? 1 : 16)));
      } else {
#pragma unroll
        for (int i = B_WQ; i < B_COUNT; i++) mbar_init(bar + i * 8, i < B_Q0 ? 1 : (i < B_ODONE ? 4 : 8));
      }
    }
    asm volatile("fence.mbarrier_init.release.cluster;" ::: "memory");
    __syncwarp();
    asm volatile("barrier.cluster.arrive.relaxed.aligned;" ::: "memory");
    asm volatile("setmaxnreg.dec.sync.aligned.u32 24;");
    asm volatile("griddepcontrol.launch_dependents;");
    const int cc = ph * 112 + (head ? strip * 16 : (strip == 0 ? 16 : (strip == 6 ? 74 : strip * 16 - 3)));
    const int sd = strip == 0 ? -1 : (strip == 6 ? 1 : 0);
    const int r0 = head == 0 ? -4 : (head == 1 ? 4 : 0);
    asm volatile("barrier.cluster.wait.aligned;" ::: "memory");
    if (warp == 12) {
      const uint32_t fb = bar + (B_FULL + head) * 8, eb = bar + (B_EMPTY + head) * 8;
      const uint32_t dst = sb + (head == 0 ? SM_X0 : (head == 1 ? SM_X1 : SM_X2));
      const int nl = head == 0 ? 15 : (head == 3 ? 1 : 14);
#pragma unroll 1
      for (int n = 0; n < nl; n++) {
        if (n) mbar_wait(eb, (n - 1) & 1);
        if (elect_one()) {
          if (head == 0) {
            asm volatile("cp.async.bulk.tensor.5d.shared::cluster.global.mbarrier::complete_tx::bytes.multicast::cluster [%0], [%1, {%3,%4,%5,%6,%7}], [%2], %8;"
                         ::"r"(dst), "l"(&mp.xh), "r"(fb), "r"(0), "r"(8 * n + r0), "r"(cc), "r"(sd), "r"(pw * 3), "h"((uint16_t)15) : "memory");
          } else if (head < 3) {
            asm volatile("cp.async.bulk.tensor.4d.shared::cluster.global.mbarrier::complete_tx::bytes.multicast::cluster [%0], [%1, {%3,%4,%5,%6}], [%2], %7;"
                         ::"r"(dst), "l"(&mp.xc), "r"(fb), "r"(0), "r"(8 * n + r0), "r"(cc), "r"(pw * 3), "h"((uint16_t)15) : "memory");
          }
          if (n == 0) {
#pragma unroll
            for (int i = 0; i < 3; i++) load_w(&mp.w, sb + SM_W + (6 + i) * 6144, bar + B_WQ * 8, head * 48 + i * 16);
            mbar_expect(bar + B_WQ * 8, 18432);
            mbar_expect(bar + B_TIN * 8, 24576); mbar_expect(bar + (B_TIN + 1) * 8, 24576); mbar_expect(bar + (B_TIN + 2) * 8, 24576);
          }
          if (!head && n + 1 < nl) asm volatile("cp.async.bulk.prefetch.tensor.5d.L2.global [%0, {%1,%2,%3,%4,%5}];" ::"l"(&mp.xh), "r"(0), "r"(8 * n + 8 + r0), "r"(cc), "r"(sd), "r"(pw * 3) : "memory");
          if (head && n + 1 < nl) asm volatile("cp.async.bulk.prefetch.tensor.4d.L2.global [%0, {%1,%2,%3,%4}];" ::"l"(&mp.xc), "r"(0), "r"(8 * n + 8 + r0), "r"(cc), "r"(pw * 3) : "memory");
        }
        __syncwarp();
      }
    }
    if (warp == 14) {
      int* flag = g_flags + cl * 2;
      nb_arrive(N_VQ0, 288); nb_arrive(N_VQ1, 288);
#pragma unroll 1
      for (int b = 0; b < TB; b++) {
        mbar_wait(bar + B_ODONE * 8, b & 1);
        if (lane == 0) {
          asm volatile("cp.async.bulk.tensor.3d.global.shared::cta.bulk_group [%0, {%2,%3,%4}], [%1];"
                       ::"l"(&mp.os), "r"(sb + SM_O), "r"(pw * 192), "r"(8 * b + 2 * head), "r"(ph * 112 + strip * 16) : "memory");
          asm volatile("cp.async.bulk.commit_group;\ncp.async.bulk.wait_group 0;" ::: "memory");
        }
        __syncwarp();
        nb_arrive(N_VQ0, 288); nb_arrive(N_VQ1, 288);
        if (lane == 0)
          asm volatile("fence.proxy.async.global;\nfence.acq_rel.gpu;\nred.relaxed.gpu.global.add.s32 [%0], 1;\nred.relaxed.gpu.global.add.s32 [%0+4], 1;"
                       ::"l"(flag + b * 56) : "memory");
        __syncwarp();
      }
    } else if (warp & 1) {
      const int j = (warp >> 1) & 1;
#pragma unroll 1
      for (int i = 0; i < 2; i++) {
        mbar_wait(bar + (B_OTAIL + j) * 8, i);
        if (i == 0) nb_arrive(N_VQ0 + j, 288);
        mbar_wait(bar + (B_TFREE + i) * 8, 0);
        if (elect_one()) {
#pragma unroll 1
          for (int d = 0; d < 8; d++) {
            const int dst = (d + head) & 3, pc = d >> 2;
            send_o<1536>(sb + (i ? SM_X1 : SM_X2) + head * 6144 + j * 3072 + pc * 1536,
                         sb + (i ? SM_Q : SM_O) + (4 * j + (dst & 2) + pc) * (i ? 3072 : 1536), bar + (B_TIN + i) * 8, dst);
          }
        }
        __syncwarp();
      }
    }
    cluster_sync();
  }
}

constexpr int NSTB = 6;
constexpr int NTB = TB * 56;
constexpr int SM_B_IN = 0;
constexpr int SM_B_W = SM_B_IN + NSTB * 24576;
constexpr int SM_B_BAR = SM_B_W + 73728;
constexpr int SM_B_TOTAL = SM_B_BAR + 128;
struct MapsB { CUtensorMap oi, oo, wo; };

__global__ void __launch_bounds__(480, 1)
na_proj_kernel(const __grid_constant__ MapsB mp) {
  extern __shared__ __align__(1024) uint8_t smem_raw[];
  const uint32_t sb = smem_u32(smem_raw);
  if ((sb & 0x3FFFF) != SBC) return;
  const uint32_t bar = sb + SM_B_BAR;
  const int tid = threadIdx.x, lane = tid & 31;
  const int warp = __shfl_sync(0xffffffffu, tid >> 5, 0);
  TR2(132 + blockIdx.x, 0);
  TRB(47, 0);
  if (warp == 12 && elect_one()) {
#pragma unroll
    for (int i = 0; i <= 2 * NSTB; i++) mbar_init(bar + i * 8, i < NSTB || i == 2 * NSTB ? 1 : 4);
    mbar_expect(bar + 2 * NSTB * 8, 73728);
#pragma unroll
    for (int i = 0; i < 2; i++)
      asm volatile("cp.async.bulk.tensor.3d.shared::cluster.global.mbarrier::complete_tx::bytes [%0], [%1, {%3,%4,%5}], [%2];"
                   ::"r"(sb + SM_B_W + i * 36864), "l"(&mp.wo), "r"(bar + 2 * NSTB * 8), "r"(0), "r"(0), "r"(i * 3) : "memory");
  }
  __syncthreads();
  const int step = gridDim.x;
  if (warp >= 12) {
    const int wg = warp - 12;
    int use = 0;
#pragma unroll 1
    for (int n = blockIdx.x + wg * step; n < NTB; n += 3 * step, use++) {
      const int b = n / 56, rem = n - b * 56, par = rem / 14, sg = wg + 3 * (use & 1);
      int v; uint32_t spin = 0;
      do { asm volatile("ld.acquire.gpu.global.s32 %0, [%1];" : "=r"(v) : "l"(g_flags + n) : "memory"); if ((OPT & 1) && v < 4) __nanosleep(200); } while (v < 4 && ++spin < SPIN_LIMIT);
      TRB(use * 3 + wg, 0);
      asm volatile("fence.proxy.async.global;" ::: "memory");
      if (use >= 2) mbar_wait(bar + (NSTB + sg) * 8, ((use >> 1) - 1) & 1);
      TRB(use * 3 + wg, 1);
      if (elect_one()) {
        mbar_expect(bar + sg * 8, 24576);
        asm volatile("cp.async.bulk.tensor.3d.shared::cluster.global.mbarrier::complete_tx::bytes [%0], [%1, {%3,%4,%5}], [%2];"
                     ::"r"(sb + SM_B_IN + sg * 24576), "l"(&mp.oi), "r"(bar + sg * 8), "r"((par & 1) * 192), "r"(8 * b), "r"((par >> 1) * 112 + (rem - par * 14) * 8) : "memory");
        g_flags[n] = 0;
      }
      __syncwarp();
    }
  } else {
    const int wg = warp >> 2, w = warp & 3;
    constexpr uint64_t db = mkdesc(SBC + SM_B_W, 12288, 512, 2);
    const uint32_t sta0 = sb + SM_B_IN + w * 6144 + (lane & 15) * 128 + (((lane >> 4) ^ (lane & 7)) * 16);
    mbar_wait(bar + 2 * NSTB * 8, 0);
    TRB(47, 1);
    int use = 0;
#pragma unroll 1
    for (int n = blockIdx.x + wg * step; n < NTB; n += 3 * step, use++) {
      const int b = n / 56, rem = n - b * 56, par = rem / 14, sg = wg + 3 * (use & 1);
      const uint64_t da = mkdesc(SBC + SM_B_IN, 128, 3072, 0) + sg * (24576 / 16);
      float D[96];
      mbar_wait(bar + sg * 8, (use >> 1) & 1);
      if (use | wg) nb_sync(4 + wg, 256);
      TRB(use * 3 + wg, 3);
      wg_fence();
      wg_ss192<0>(D, da, db);
#pragma unroll
      for (int k = 1; k < 12; k++) wg_ss192<1>(D, da + k * 16, db + k * 64);
      wg_commit();
      if (n + step < NTB) nb_arrive(wg == 2 ? 4 : 5 + wg, 256);
      TRB(use * 3 + wg, 4);
      if (use && lane == 0) {
        asm volatile("cp.async.bulk.wait_group.read 0;" ::: "memory");
        mbar_arrive(bar + (NSTB + wg + 3 * (~use & 1)) * 8);
      }
      __syncwarp();
      wg_wait<0>(); pin(D);
      nb_sync(1 + wg, 128);
      TRB(use * 3 + wg, 5);
      const uint32_t sta = sta0 + sg * 24576;
#pragma unroll
      for (int q = 0; q < 12; q++)
        stsm4((sta ^ ((q & 3) * 32)) + (q >> 2) * 2048,
              pack2(D[8 * q], D[8 * q + 1]), pack2(D[8 * q + 2], D[8 * q + 3]), pack2(D[8 * q + 4], D[8 * q + 5]), pack2(D[8 * q + 6], D[8 * q + 7]));
      fence_async();
      __syncwarp();
      if (lane == 0) {
        asm volatile("cp.async.bulk.tensor.4d.global.shared::cta.bulk_group [%0, {%2,%3,%4,%5}], [%1];"
                     ::"l"(&mp.oo), "r"(sb + SM_B_IN + sg * 24576 + w * 6144), "r"(0), "r"(8 * b), "r"((par >> 1) * 112 + (rem - par * 14) * 8 + 2 * w), "r"((par & 1) * 3) : "memory");
        asm volatile("cp.async.bulk.commit_group;" ::: "memory");
      }
      __syncwarp();
      TRB(use * 3 + wg, 6);
    }
    if (lane == 0) asm volatile("cp.async.bulk.wait_group 0;" ::: "memory");
    TR2(132 + blockIdx.x, 2);
  }
}

typedef CUresult (*EncodeFn)(CUtensorMap*, CUtensorMapDataType, cuuint32_t, void*, const cuuint64_t*, const cuuint64_t*, const cuuint32_t*,
                             const cuuint32_t*, CUtensorMapInterleave, CUtensorMapSwizzle, CUtensorMapL2promotion, CUtensorMapFloatOOBfill);
static EncodeFn g_enc = nullptr;
static void make_map(CUtensorMap* m, const void* p, int rank, const cuuint64_t* dim, const cuuint64_t* str, const cuuint32_t* box, CUtensorMapSwizzle sw) {
  const cuuint32_t ones[5] = {1, 1, 1, 1, 1};
  g_enc(m, CU_TENSOR_MAP_DATA_TYPE_BFLOAT16, rank, (void*)p, dim, str, box, ones, CU_TENSOR_MAP_INTERLEAVE_NONE, sw,
        CU_TENSOR_MAP_L2_PROMOTION_L2_128B, CU_TENSOR_MAP_FLOAT_OOB_FILL_NONE);
}

extern "C" void kernel_launch(void* const* d_in, const int* in_sizes, int n_in, void* d_out, int out_size) {
  const __nv_bfloat16* x = (const __nv_bfloat16*)d_in[0];
  const __nv_bfloat16* wqkv = (const __nv_bfloat16*)d_in[1];
  const __nv_bfloat16* wo = (const __nv_bfloat16*)d_in[2];
  const __nv_bfloat16* rpb = (const __nv_bfloat16*)d_in[3];

  if (!g_enc) {
    void* fn = nullptr; cudaDriverEntryPointQueryResult qr;
    cudaGetDriverEntryPoint("cuTensorMapEncodeTiled", &fn, cudaEnableDefault, &qr);
    g_enc = (EncodeFn)fn;
    cudaFuncSetAttribute(na_attn_kernel, cudaFuncAttributeMaxDynamicSharedMemorySize, SM_A_TOTAL);
    cudaFuncSetAttribute(na_proj_kernel, cudaFuncAttributeMaxDynamicSharedMemorySize, SM_B_TOTAL);
  }
  Maps ma; MapsB mb;
  { cuuint64_t dim[4] = {64, 112, 224, 6}, str[3] = {(cuuint64_t)ROWB, 768, 128};
    cuuint32_t box[4] = {64, 4, 16, 3}, boxo[4] = {64, 8, 2, 3};
    make_map(&ma.xc, x, 4, dim, str, box, CU_TENSOR_MAP_SWIZZLE_128B);
    make_map(&mb.oo, d_out, 4, dim, str, boxo, CU_TENSOR_MAP_SWIZZLE_128B); }
  { cuuint64_t dim[5] = {64, 112, 224, 2, 6}, str[4] = {(cuuint64_t)ROWB, 768, 19 * 768, 128};
    cuuint32_t box[5] = {64, 8, 3, 2, 3};
    make_map(&ma.xh, x, 5, dim, str, box, CU_TENSOR_MAP_SWIZZLE_128B); }
  { cuuint64_t dim[3] = {384, 112, 224}, str[2] = {(cuuint64_t)ROWB, 768};
    cuuint32_t box[3] = {192, 8, 8}, boxs[3] = {192, 2, 16};
    make_map(&mb.oi, d_out, 3, dim, str, box, CU_TENSOR_MAP_SWIZZLE_NONE);
    make_map(&ma.os, d_out, 3, dim, str, boxs, CU_TENSOR_MAP_SWIZZLE_NONE); }
  { cuuint64_t dim[4] = {32, 112, 224, 12}, str[3] = {(cuuint64_t)ROWB, 768, 64};
    cuuint32_t box[4] = {32, 8, 2, 3};
    make_map(&ma.ot, d_out, 4, dim, str, box, CU_TENSOR_MAP_SWIZZLE_64B); }
  { cuuint64_t dim[2] = {576, 192}, str[1] = {1152};
    cuuint32_t box[2] = {16, 192};
    make_map(&ma.w, wqkv, 2, dim, str, box, CU_TENSOR_MAP_SWIZZLE_32B); }
  { cuuint64_t dim[3] = {32, 192, 6}, str[2] = {384, 64};
    cuuint32_t box[3] = {32, 192, 3};
    make_map(&ma.wo, wo, 3, dim, str, box, CU_TENSOR_MAP_SWIZZLE_64B);
    mb.wo = ma.wo; }
  na_attn_kernel<<<112, 512, SM_A_TOTAL>>>(x, wqkv, rpb, ma);
  cudaLaunchConfig_t cfg = {};
  cfg.gridDim = dim3(20); cfg.blockDim = dim3(480); cfg.dynamicSmemBytes = SM_B_TOTAL; cfg.stream = cudaStreamPerThread;
  cudaLaunchAttribute at[1];
  at[0].id = cudaLaunchAttributeProgrammaticStreamSerialization; at[0].val.programmaticStreamSerializationAllowed = 1;
  cfg.attrs = at; cfg.numAttrs = 1;
  cudaLaunchKernelEx(&cfg, na_proj_kernel, mb);
}
```

```cpp
#include <cuda_runtime.h>
#include <cuda_bf16.h>
#include <cuda.h>
#include <stdint.h>

#define SPIN_LIMIT (1u << 18)

__device__ __forceinline__ uint32_t smem_u32(const void* p) { return (uint32_t)__cvta_generic_to_shared(p); }
__device__ __forceinline__ void wg_fence() { asm volatile("wgmma.fence.sync.aligned;" ::: "memory"); }
__device__ __forceinline__ void wg_commit() { asm volatile("wgmma.commit_group.sync.aligned;" ::: "memory"); }
template <int N> __device__ __forceinline__ void wg_wait() { asm volatile("wgmma.wait_group.sync.aligned %0;" ::"n"(N) : "memory"); }
template <int N> __device__ __forceinline__ void pin(float (&d)[N]) {
#pragma unroll
  for (int i = 0; i < N; i++) asm volatile("" : "+f"(d[i])::"memory");
}
__host__ __device__ constexpr uint64_t mkdesc(uint32_t addr, uint32_t lbo, uint32_t sbo, uint32_t sw) {
  return (uint64_t)((addr & 0x3FFFF) >> 4) | ((uint64_t)(lbo >> 4) << 16) | ((uint64_t)(sbo >> 4) << 32) | ((uint64_t)sw << 62);
}
__device__ __forceinline__ void mbar_init(uint32_t bar, uint32_t cnt) { asm volatile("mbarrier.init.shared::cta.b64 [%0], %1;" ::"r"(bar), "r"(cnt) : "memory"); }
__device__ __forceinline__ void mbar_arrive(uint32_t bar) { asm volatile("mbarrier.arrive.shared::cta.b64 _, [%0];" ::"r"(bar) : "memory"); }
__device__ __forceinline__ bool elect_one() {
  uint32_t r; asm volatile("{\n.reg .pred p;\nelect.sync _|p, 0xffffffff;\nselp.u32 %0, 1, 0, p;\n}" : "=r"(r)); return r;
}
__device__ __forceinline__ void mbar_arrive_elect(uint32_t bar) {
  asm volatile("{\n.reg .pred p;\nelect.sync _|p, 0xffffffff;\n@p mbarrier.arrive.shared::cta.b64 _, [%0];\n}" ::"r"(bar) : "memory");
}
__device__ __forceinline__ void mbar_expect(uint32_t bar, uint32_t bytes) { asm volatile("mbarrier.arrive.expect_tx.shared::cta.b64 _, [%0], %1;" ::"r"(bar), "r"(bytes) : "memory"); }
__device__ __forceinline__ void mbar_arrive_remote(uint32_t bar, uint32_t cta) {
  asm volatile("{\n.reg .b32 ra;\nmapa.shared::cluster.u32 ra, %0, %1;\nmbarrier.arrive.relaxed.cluster.shared::cluster.b64 _, [ra];\n}" ::"r"(bar), "r"(cta) : "memory");
}
__device__ __forceinline__ void mbar_wait(uint32_t bar, uint32_t parity) {
  asm volatile("{\n.reg .pred p;\n.reg .b32 n;\nmov.b32 n, 0;\nWL:\nmbarrier.try_wait.parity.shared::cta.b64 p, [%0], %1;\n@p bra WD;\n"
               "add.u32 n, n, 1;\nsetp.lt.u32 p, n, 65536;\n@p bra WL;\nWD:\n}" ::"r"(bar), "r"(parity) : "memory");
}
__device__ __forceinline__ void nb_sync(int id, int n) { asm volatile("bar.sync %0, %1;" ::"r"(id), "r"(n) : "memory"); }
__device__ __forceinline__ void nb_arrive(int id, int n) { asm volatile("bar.arrive %0, %1;" ::"r"(id), "r"(n) : "memory"); }
__device__ __forceinline__ void fence_async() { asm volatile("fence.proxy.async.shared::cta;" ::: "memory"); }
__device__ __forceinline__ void cluster_sync() {
  asm volatile("barrier.cluster.arrive.relaxed.aligned;\nbarrier.cluster.wait.aligned;" ::: "memory");
}
__device__ __forceinline__ uint32_t pack2(float lo, float hi) {
  uint32_t r; asm("cvt.rn.bf16x2.f32 %0, %1, %2;" : "=r"(r) : "f"(hi), "f"(lo)); return r;
}
__device__ __forceinline__ void stsm4(uint32_t a, uint32_t r0, uint32_t r1, uint32_t r2, uint32_t r3) {
  asm volatile("stmatrix.sync.aligned.m8n8.x4.shared.b16 [%0], {%1,%2,%3,%4};" ::"r"(a), "r"(r0), "r"(r1), "r"(r2), "r"(r3) : "memory");
}
__device__ __forceinline__ void ldsm4(uint32_t a, uint32_t& r0, uint32_t& r1, uint32_t& r2, uint32_t& r3) {
  asm volatile("ldmatrix.sync.aligned.m8n8.x4.shared.b16 {%0,%1,%2,%3}, [%4];" : "=r"(r0), "=r"(r1), "=r"(r2), "=r"(r3) : "r"(a) : "memory");
}
__device__ __forceinline__ void sts128(uint32_t a, uint4 v) {
  asm volatile("st.shared.v4.b32 [%0], {%1,%2,%3,%4};" ::"r"(a), "r"(v.x), "r"(v.y), "r"(v.z), "r"(v.w) : "memory");
}
__device__ __forceinline__ float lds_f32(uint32_t a) { float v; asm volatile("ld.shared.f32 %0, [%1];" : "=f"(v) : "r"(a)); return v; }
__device__ __forceinline__ float ex2(float x) { float y; asm("ex2.approx.ftz.f32 %0, %1;" : "=f"(y) : "f"(x)); return y; }

template<int SC> __device__ __forceinline__ void wg_ss144(float (&d)[72], uint64_t da, uint64_t db) {
  asm volatile("{\n.reg .pred p;\nsetp.ne.b32 p, %74, 0;\nwgmma.mma_async.sync.aligned.m64n144k16.f32.bf16.bf16 {%0,%1,%2,%3,%4,%5,%6,%7,%8,%9,%10,%11,%12,%13,%14,%15,%16,%17,%18,%19,%20,%21,%22,%23,%24,%25,%26,%27,%28,%29,%30,%31,%32,%33,%34,%35,%36,%37,%38,%39,%40,%41,%42,%43,%44,%45,%46,%47,%48,%49,%50,%51,%52,%53,%54,%55,%56,%57,%58,%59,%60,%61,%62,%63,%64,%65,%66,%67,%68,%69,%70,%71}, %72, %73, p, 1, 1, 0, 1;\n}\n"
    : "+f"(d[0]),"+f"(d[1]),"+f"(d[2]),"+f"(d[3]),"+f"(d[4]),"+f"(d[5]),"+f"(d[6]),"+f"(d[7]),"+f"(d[8]),"+f"(d[9]),"+f"(d[10]),"+f"(d[11]),"+f"(d[12]),"+f"(d[13]),"+f"(d[14]),"+f"(d[15]),"+f"(d[16]),"+f"(d[17]),"+f"(d[18]),"+f"(d[19]),"+f"(d[20]),"+f"(d[21]),"+f"(d[22]),"+f"(d[23]),"+f"(d[24]),"+f"(d[25]),"+f"(d[26]),"+f"(d[27]),"+f"(d[28]),"+f"(d[29]),"+f"(d[30]),"+f"(d[31]),"+f"(d[32]),"+f"(d[33]),"+f"(d[34]),"+f"(d[35]),"+f"(d[36]),"+f"(d[37]),"+f"(d[38]),"+f"(d[39]),"+f"(d[40]),"+f"(d[41]),"+f"(d[42]),"+f"(d[43]),"+f"(d[44]),"+f"(d[45]),"+f"(d[46]),"+f"(d[47]),"+f"(d[48]),"+f"(d[49]),"+f"(d[50]),"+f"(d[51]),"+f"(d[52]),"+f"(d[53]),"+f"(d[54]),"+f"(d[55]),"+f"(d[56]),"+f"(d[57]),"+f"(d[58]),"+f"(d[59]),"+f"(d[60]),"+f"(d[61]),"+f"(d[62]),"+f"(d[63]),"+f"(d[64]),"+f"(d[65]),"+f"(d[66]),"+f"(d[67]),"+f"(d[68]),"+f"(d[69]),"+f"(d[70]),"+f"(d[71]) : "l"(da), "l"(db), "n"(SC));
}
template<int SC> __device__ __forceinline__ void wg_ss96(float (&d)[48], uint64_t da, uint64_t db) {
  asm volatile("{\n.reg .pred p;\nsetp.ne.b32 p, %50, 0;\nwgmma.mma_async.sync.aligned.m64n96k16.f32.bf16.bf16 {%0,%1,%2,%3,%4,%5,%6,%7,%8,%9,%10,%11,%12,%13,%14,%15,%16,%17,%18,%19,%20,%21,%22,%23,%24,%25,%26,%27,%28,%29,%30,%31,%32,%33,%34,%35,%36,%37,%38,%39,%40,%41,%42,%43,%44,%45,%46,%47}, %48, %49, p, 1, 1, 0, 1;\n}\n"
    : "+f"(d[0]),"+f"(d[1]),"+f"(d[2]),"+f"(d[3]),"+f"(d[4]),"+f"(d[5]),"+f"(d[6]),"+f"(d[7]),"+f"(d[8]),"+f"(d[9]),"+f"(d[10]),"+f"(d[11]),"+f"(d[12]),"+f"(d[13]),"+f"(d[14]),"+f"(d[15]),"+f"(d[16]),"+f"(d[17]),"+f"(d[18]),"+f"(d[19]),"+f"(d[20]),"+f"(d[21]),"+f"(d[22]),"+f"(d[23]),"+f"(d[24]),"+f"(d[25]),"+f"(d[26]),"+f"(d[27]),"+f"(d[28]),"+f"(d[29]),"+f"(d[30]),"+f"(d[31]),"+f"(d[32]),"+f"(d[33]),"+f"(d[34]),"+f"(d[35]),"+f"(d[36]),"+f"(d[37]),"+f"(d[38]),"+f"(d[39]),"+f"(d[40]),"+f"(d[41]),"+f"(d[42]),"+f"(d[43]),"+f"(d[44]),"+f"(d[45]),"+f"(d[46]),"+f"(d[47]) : "l"(da), "l"(db), "n"(SC));
}
template<int SC> __device__ __forceinline__ void wg_rs112(float (&d)[56], uint32_t a0, uint32_t a1, uint32_t a2, uint32_t a3, uint64_t db) {
  asm volatile("{\n.reg .pred p;\nsetp.ne.b32 p, %61, 0;\nwgmma.mma_async.sync.aligned.m64n112k16.f32.bf16.bf16 {%0,%1,%2,%3,%4,%5,%6,%7,%8,%9,%10,%11,%12,%13,%14,%15,%16,%17,%18,%19,%20,%21,%22,%23,%24,%25,%26,%27,%28,%29,%30,%31,%32,%33,%34,%35,%36,%37,%38,%39,%40,%41,%42,%43,%44,%45,%46,%47,%48,%49,%50,%51,%52,%53,%54,%55}, {%56,%57,%58,%59}, %60, p, 1, 1, 0;\n}\n"
    : "+f"(d[0]),"+f"(d[1]),"+f"(d[2]),"+f"(d[3]),"+f"(d[4]),"+f"(d[5]),"+f"(d[6]),"+f"(d[7]),"+f"(d[8]),"+f"(d[9]),"+f"(d[10]),"+f"(d[11]),"+f"(d[12]),"+f"(d[13]),"+f"(d[14]),"+f"(d[15]),"+f"(d[16]),"+f"(d[17]),"+f"(d[18]),"+f"(d[19]),"+f"(d[20]),"+f"(d[21]),"+f"(d[22]),"+f"(d[23]),"+f"(d[24]),"+f"(d[25]),"+f"(d[26]),"+f"(d[27]),"+f"(d[28]),"+f"(d[29]),"+f"(d[30]),"+f"(d[31]),"+f"(d[32]),"+f"(d[33]),"+f"(d[34]),"+f"(d[35]),"+f"(d[36]),"+f"(d[37]),"+f"(d[38]),"+f"(d[39]),"+f"(d[40]),"+f"(d[41]),"+f"(d[42]),"+f"(d[43]),"+f"(d[44]),"+f"(d[45]),"+f"(d[46]),"+f"(d[47]),"+f"(d[48]),"+f"(d[49]),"+f"(d[50]),"+f"(d[51]),"+f"(d[52]),"+f"(d[53]),"+f"(d[54]),"+f"(d[55]) : "r"(a0), "r"(a1), "r"(a2), "r"(a3), "l"(db), "n"(SC));
}
template<int SC> __device__ __forceinline__ void wg_sp48(float (&d)[24], uint32_t a0, uint32_t a1, uint32_t a2, uint32_t a3, uint64_t db, uint32_t meta) {
  asm volatile("{\n.reg .pred p;\nsetp.ne.b32 p, %30, 0;\nwgmma.mma_async.sp.sync.aligned.m64n48k32.f32.bf16.bf16 {%0,%1,%2,%3,%4,%5,%6,%7,%8,%9,%10,%11,%12,%13,%14,%15,%16,%17,%18,%19,%20,%21,%22,%23}, {%24,%25,%26,%27}, %28, %29, 0, p, 1, 1, 1;\n}\n"
    : "+f"(d[0]),"+f"(d[1]),"+f"(d[2]),"+f"(d[3]),"+f"(d[4]),"+f"(d[5]),"+f"(d[6]),"+f"(d[7]),"+f"(d[8]),"+f"(d[9]),"+f"(d[10]),"+f"(d[11]),"+f"(d[12]),"+f"(d[13]),"+f"(d[14]),"+f"(d[15]),"+f"(d[16]),"+f"(d[17]),"+f"(d[18]),"+f"(d[19]),"+f"(d[20]),"+f"(d[21]),"+f"(d[22]),"+f"(d[23]) : "r"(a0), "r"(a1), "r"(a2), "r"(a3), "l"(db), "r"(meta), "n"(SC));
}
template<int SC> __device__ __forceinline__ void wg_ss192(float (&d)[96], uint64_t da, uint64_t db) {
  asm volatile("{\n.reg .pred p;\nsetp.ne.b32 p, %98, 0;\nwgmma.mma_async.sync.aligned.m64n192k16.f32.bf16.bf16 {%0,%1,%2,%3,%4,%5,%6,%7,%8,%9,%10,%11,%12,%13,%14,%15,%16,%17,%18,%19,%20,%21,%22,%23,%24,%25,%26,%27,%28,%29,%30,%31,%32,%33,%34,%35,%36,%37,%38,%39,%40,%41,%42,%43,%44,%45,%46,%47,%48,%49,%50,%51,%52,%53,%54,%55,%56,%57,%58,%59,%60,%61,%62,%63,%64,%65,%66,%67,%68,%69,%70,%71,%72,%73,%74,%75,%76,%77,%78,%79,%80,%81,%82,%83,%84,%85,%86,%87,%88,%89,%90,%91,%92,%93,%94,%95}, %96, %97, p, 1, 1, 0, 1;\n}\n"
    : "+f"(d[0]),"+f"(d[1]),"+f"(d[2]),"+f"(d[3]),"+f"(d[4]),"+f"(d[5]),"+f"(d[6]),"+f"(d[7]),"+f"(d[8]),"+f"(d[9]),"+f"(d[10]),"+f"(d[11]),"+f"(d[12]),"+f"(d[13]),"+f"(d[14]),"+f"(d[15]),"+f"(d[16]),"+f"(d[17]),"+f"(d[18]),"+f"(d[19]),"+f"(d[20]),"+f"(d[21]),"+f"(d[22]),"+f"(d[23]),"+f"(d[24]),"+f"(d[25]),"+f"(d[26]),"+f"(d[27]),"+f"(d[28]),"+f"(d[29]),"+f"(d[30]),"+f"(d[31]),"+f"(d[32]),"+f"(d[33]),"+f"(d[34]),"+f"(d[35]),"+f"(d[36]),"+f"(d[37]),"+f"(d[38]),"+f"(d[39]),"+f"(d[40]),"+f"(d[41]),"+f"(d[42]),"+f"(d[43]),"+f"(d[44]),"+f"(d[45]),"+f"(d[46]),"+f"(d[47]),"+f"(d[48]),"+f"(d[49]),"+f"(d[50]),"+f"(d[51]),"+f"(d[52]),"+f"(d[53]),"+f"(d[54]),"+f"(d[55]),"+f"(d[56]),"+f"(d[57]),"+f"(d[58]),"+f"(d[59]),"+f"(d[60]),"+f"(d[61]),"+f"(d[62]),"+f"(d[63]),"+f"(d[64]),"+f"(d[65]),"+f"(d[66]),"+f"(d[67]),"+f"(d[68]),"+f"(d[69]),"+f"(d[70]),"+f"(d[71]),"+f"(d[72]),"+f"(d[73]),"+f"(d[74]),"+f"(d[75]),"+f"(d[76]),"+f"(d[77]),"+f"(d[78]),"+f"(d[79]),"+f"(d[80]),"+f"(d[81]),"+f"(d[82]),"+f"(d[83]),"+f"(d[84]),"+f"(d[85]),"+f"(d[86]),"+f"(d[87]),"+f"(d[88]),"+f"(d[89]),"+f"(d[90]),"+f"(d[91]),"+f"(d[92]),"+f"(d[93]),"+f"(d[94]),"+f"(d[95]) : "l"(da), "l"(db), "n"(SC));
}

constexpr uint32_t SBC = 1024;
constexpr int ROWB = 2 * 224 * 384;
constexpr int TB = 11;
constexpr int KS = 832;
constexpr int KSLOT = 22 * KS;
constexpr int SM_X1 = 0;
constexpr int SM_X2 = SM_X1 + 24576;
constexpr int SM_X0 = SM_X2 + 24576;
constexpr int SM_W = SM_X0 + 18432;
constexpr int SM_K = SM_W + 55296;
constexpr int SM_V = SM_K + 2 * KSLOT;
constexpr int SM_Q = SM_V + 22 * 1536;
constexpr int SM_O = SM_Q + 24576;
constexpr int SM_RPB = SM_O + 12288;
constexpr int SM_BAR = SM_RPB + 768;
constexpr int SM_A_TOTAL = SM_BAR + 256;
constexpr int SM_TWO = SM_X0 + 24576;
constexpr int SM_TST = SM_TWO + 36864;
enum { B_FULL = 0, B_EMPTY = 3, B_TIN = 6, B_TFREE = 9, B_WK = 11, B_WQ, B_WO, B_Q0, B_OTAIL, B_ODONE = B_OTAIL + 2, B_KFREE, B_VFREE, B_COUNT };
enum { N_KRDY = 4, N_QK0, N_QK1, N_VQ0, N_VQ1, N_PVISS };

#define NL 2
#define OPT 0
#define SPL 4
#define RA 152
#define RG 184
__device__ int g_flags[TB * 56];

#define TR(role, it, k)
#define TRDECL
#define TRARG
#define TRPASS
#define TRDUMP
#define TRB(it, k)
#define TR2(blk, k)

struct GemmCtx {
  uint32_t bar;
  uint32_t kC, vC[2], qC[2];
  uint32_t kH, vH[2];
  uint32_t spin;
  bool hvalid, never;
};

template <int STRIDE> __device__ __forceinline__ void dump12(uint32_t a, const uint32_t (&r)[12]) {
#pragma unroll
  for (int j = 0; j < 3; j++) stsm4(a + j * 2 * STRIDE, r[4 * j], r[4 * j + 1], r[4 * j + 2], r[4 * j + 3]);
}
__device__ __forceinline__ void keep12(bool never, uint32_t a, const uint32_t (&r)[12]) { if (never) dump12<128>(a, r); }
template <int N> __device__ __forceinline__ void pack12(uint32_t (&r)[12], const float (&d)[N], int off) {
#pragma unroll
  for (int j = 0; j < 12; j++) r[j] = pack2(d[off + 2 * j], d[off + 2 * j + 1]);
}
template <int XS, int K0, int K1> __device__ __forceinline__ void issue_core(float (&d)[72]) {
  constexpr uint64_t da = mkdesc(SBC + XS, 16, 1024, 1), db = mkdesc(SBC + SM_W, 6144, 256, 3);
  wg_fence();
  if (K0 == 0) wg_ss144<0>(d, da, db);
#pragma unroll
  for (int k = K0 ? K0 : 1; k < K1; k++) wg_ss144<1>(d, da + (k >> 2) * 512 + (k & 3) * 2, db + k * 32);
  wg_commit();
}
template <int K0, int K1> __device__ __forceinline__ void issue_halo(float (&d)[48]) {
  constexpr uint64_t da = mkdesc(SBC + SM_X0 - 2048, 16, 1024, 1), db = mkdesc(SBC + SM_W, 6144, 256, 3);
  wg_fence();
  if (K0 == 0) wg_ss96<0>(d, da, db);
#pragma unroll
  for (int k = K0 ? K0 : 1; k < K1; k++) wg_ss96<1>(d, da + (k >> 2) * 384 + (k & 3) * 2, db + k * 32);
  wg_commit();
}
template <int ST> __device__ __forceinline__ void release_stage(const GemmCtx& c) {
  asm volatile("{\n.reg .pred p;\n.reg .b32 ra;\nelect.sync _|p, 0xffffffff;\nmapa.shared::cluster.u32 ra, %0, %1;\n"
               "@p mbarrier.arrive.shared::cluster.b64 _, [ra];\n}" ::"r"(c.bar + (B_EMPTY + ST) * 8), "n"(ST) : "memory");
}
template <int PARITY> __device__ __forceinline__ void gwait(GemmCtx& c, int bar) {
  asm volatile("{\n.reg .pred p;\nWL:\nmbarrier.try_wait.parity.shared::cta.b64 p, [%1], %2;\n@p bra WD;\n"
               "add.u32 %0, %0, 1;\nsetp.lt.u32 p, %0, 0x100000;\n@p bra WL;\nWD:\n}" : "+r"(c.spin) : "r"(c.bar + bar * 8), "n"(PARITY) : "memory");
}
__device__ __forceinline__ void load_w(const CUtensorMap* m, uint32_t dst, uint32_t bar, int col) {
  asm volatile("cp.async.bulk.tensor.2d.shared::cluster.global.mbarrier::complete_tx::bytes [%0], [%1, {%3,%4}], [%2];"
               ::"r"(dst), "l"(m), "r"(bar), "r"(col), "r"(0) : "memory");
}
template <int BYTES> __device__ __forceinline__ void send_o(uint32_t dst, uint32_t src, uint32_t bar, int cta) {
  asm volatile("{\n.reg .b32 rd, rb;\nmapa.shared::cluster.u32 rd, %0, %3;\nmapa.shared::cluster.u32 rb, %2, %3;\n"
               "cp.async.bulk.shared::cluster.shared::cta.mbarrier::complete_tx::bytes [rd], [%1], %4, [rb];\n}"
               ::"r"(dst), "r"(src), "r"(bar), "r"(cta), "n"(BYTES) : "memory");
}
__device__ __forceinline__ void tail_free(uint32_t bar) {
  uint32_t ln; asm volatile("mov.u32 %0, %%laneid;" : "=r"(ln));
  if (ln < 4) mbar_arrive_remote(bar, ln);
}
__device__ __forceinline__ void publish(uint32_t bar) {
  fence_async();
  __syncwarp();
  mbar_arrive_elect(bar);
}

template <bool FIRST, bool LAST, int PA>
__device__ __forceinline__ void gemm_iter(GemmCtx& c, int b, uint32_t (&pk)[12], uint32_t (&pv)[12], uint32_t (&pq)[12], const CUtensorMap* mwo TRARG) {
  const uint32_t bar = c.bar;
  const bool w = !FIRST && (PA == 0 || b >= 0), never = c.never;
  constexpr uint32_t ko = PA * KSLOT;
  float H[48], C[72];
  uint32_t hk[12], hv[12], pv2[12];
  TR(2, b, 0);
  if (FIRST) gwait<PA>(c, B_FULL + 0);
  if (!FIRST) dump12<256>(c.qC[1] + (PA ^ 1) * 128, pq);
  if (w) nb_sync(N_QK1, 256);
  TR(2, b, 2);
  if (FIRST) TR(2, b - 1, 6);
  issue_halo<0, 8>(H);
  TR(2, b, 3);
  if (!FIRST) {
    if (w) gwait<PA>(c, B_KFREE);
    dump12<128>(c.kC + ko, pk);
  }
  issue_halo<8, 12>(H);
  TR(2, b, 4);
  if (!LAST) {
    gwait<PA>(c, B_FULL + 2);
    if (FIRST && NL == 2) gwait<0>(c, B_WQ);
    TR(2, b, 13);
    if (FIRST) TR(2, b - 1, 7);
    issue_core<SM_X2, 0, 8>(C);
    TR(2, b, 5);
    if (!FIRST) { fence_async(); keep12(never, c.kC, pk); }
    wg_wait<1>(); pin(H);
    release_stage<0>(c);
  } else {
    fence_async();
    nb_arrive(N_VQ0, 288); nb_arrive(N_VQ1, 288);
    wg_wait<0>(); pin(H);
    tail_free(bar + (B_TFREE + 1) * 8);
    nb_sync(2, 128);
    if (!c.hvalid && elect_one()) {
      mbar_expect(bar + B_WO * 8, 36864);
      asm volatile("cp.async.bulk.tensor.3d.shared::cluster.global.mbarrier::complete_tx::bytes [%0], [%1, {%3,%4,%5}], [%2];"
                   ::"r"(bar - SM_BAR + SM_TWO), "l"(mwo), "r"(bar + B_WO * 8), "r"(0), "r"(0), "r"((blockIdx.x & 1) * 3) : "memory");
    }
    __syncwarp();
  }
  pack12(hk, H, 0);
  if (c.hvalid) dump12<128>(c.kH + ko, hk);
  pack12(hv, H, 24);
  if (!LAST) {
    issue_core<SM_X2, 8, 12>(C);
    if (w) { nb_arrive(N_VQ0, 288); nb_arrive(N_VQ1, 288); }
    else if (!FIRST) { __syncwarp(); mbar_arrive_elect(bar + B_Q0 * 8); }
    gwait<PA>(c, B_FULL + 1);
    keep12(never, c.kC, hk);
    TR(2, b, 6);
    wg_wait<0>(); pin(C);
    TR(2, b, 7);
    pack12(pk, C, 0);
    dump12<128>(c.kC + ko + 64, pk);
    release_stage<2>(c);
    pack12(pv2, C, 24);
    pack12(pq, C, 48);
    TR(2, b, 8);
    issue_core<SM_X1, 0, SPL>(C);
    if (w) nb_sync(N_PVISS, 384);
    issue_core<SM_X1, SPL, 8>(C);
    TR(2, b, 9);
  }
  if (!FIRST) fence_async();
  if (!LAST) keep12(never, c.kC, pk);
  TR(2, b, 14);
  if (!LAST) issue_core<SM_X1, 8, 12>(C);
  if (!FIRST) nb_arrive(N_KRDY, 256);
  TR(2, b, 1);
  if (PA && b == 11) tail_free(bar + B_TFREE * 8);
  if (!LAST) gwait<PA ^ 1>(c, B_FULL + 0);
  if (w) gwait<PA>(c, B_VFREE);
  TR(2, b, 10);
  if (!FIRST) dump12<128>(c.vC[PA], pv);
  if (!LAST) dump12<256>(c.qC[0] + PA * 128, pq);
  if (c.hvalid) dump12<128>(c.vH[PA], hv);
  if (LAST) { fence_async(); nb_arrive(N_VQ0, 256); nb_arrive(N_VQ1, 256); return; }
  dump12<128>(c.vC[PA ^ 1] + 768, pv2);
  TR(2, b, 11);
  wg_wait<0>(); pin(C);
  TR(2, b, 12);
  release_stage<1>(c);
  pack12(pk, C, 0);
  pack12(pv, C, 24);
  pack12(pq, C, 48);
}

template <int IN> __device__ __forceinline__ void issue_proj(float (&D)[48]) {
  constexpr uint64_t da = mkdesc(SBC + IN, 128, 768, 0), db = mkdesc(SBC + SM_TWO, 12288, 512, 2);
  wg_fence();
  wg_ss96<0>(D, da, db);
#pragma unroll
  for (int k = 1; k < 12; k++) wg_ss96<1>(D, da + (k / 3) * 384 + (k % 3) * 16, db + k * 64);
  wg_commit();
}
__device__ __forceinline__ void store_proj(const float (&D)[48], const CUtensorMap* m, uint32_t st, uint32_t sta, int row, int col, int ch) {
#pragma unroll
  for (int q = 0; q < 6; q++)
    stsm4((sta ^ ((q & 1) * 32)) + (q >> 1) * 1024,
          pack2(D[8 * q], D[8 * q + 1]), pack2(D[8 * q + 2], D[8 * q + 3]), pack2(D[8 * q + 4], D[8 * q + 5]), pack2(D[8 * q + 6], D[8 * q + 7]));
  fence_async();
  __syncwarp();
  if ((threadIdx.x & 31) == 0) {
    asm volatile("cp.async.bulk.tensor.4d.global.shared::cta.bulk_group [%0, {%2,%3,%4,%5}], [%1];" ::"l"(m), "r"(st), "r"(0), "r"(row), "r"(col), "r"(ch) : "memory");
    asm volatile("cp.async.bulk.commit_group;" ::: "memory");
  }
  __syncwarp();
}

__device__ __forceinline__ float fold(float a, float b, float t, int useb) {
  float r;
  asm("{\n.reg .pred p;\nsetp.ne.b32 p, %4, 0;\nfma.rn.f32 %0, %1, 0f3E553B95, %3;\n@p fma.rn.f32 %0, %2, 0f3E553B95, %3;\n}"
      : "=&f"(r) : "f"(a), "f"(b), "f"(t), "r"(useb));
  return r;
}
template <int U, int L>
__device__ __forceinline__ void softmax_tile(const float (&SA)[56], const float (&SB)[56], const float (&T)[16], int b0, int b1,
                                             uint32_t (&P)[28], float (&sx)[8]) {
  float lu[14], ll[14];
#pragma unroll
  for (int j = 0; j < 7; j++) {
    constexpr int sh = U == L ? 2 : 0;
    const float tu0 = T[2 * j + sh], tu1 = T[2 * j + 1 + sh], tl0 = T[2 * j], tl1 = T[2 * j + 1];
    lu[2 * j]     = fold(SA[4 * (U + j)],     SB[4 * (U + j)],     tu0, b0);
    ll[2 * j]     = fold(SA[4 * (L + j) + 2], SB[4 * (L + j) + 2], tl0, b0);
    lu[2 * j + 1] = fold(SA[4 * (U + j) + 1], SB[4 * (U + j) + 1], tu1, b1);
    ll[2 * j + 1] = fold(SA[4 * (L + j) + 3], SB[4 * (L + j) + 3], tl1, b1);
  }
  float mu = lu[0], ml = ll[0], mu2 = lu[1], ml2 = ll[1];
#pragma unroll
  for (int j = 1; j < 7; j++) { mu = fmaxf(mu, lu[2 * j]); mu2 = fmaxf(mu2, lu[2 * j + 1]); ml = fmaxf(ml, ll[2 * j]); ml2 = fmaxf(ml2, ll[2 * j + 1]); }
  mu = fmaxf(mu, mu2); ml = fmaxf(ml, ml2);
  { const float a1 = __shfl_xor_sync(0xffffffffu, mu, 1), a2 = __shfl_xor_sync(0xffffffffu, mu, 2), a3 = __shfl_xor_sync(0xffffffffu, mu, 3);
    const float c1 = __shfl_xor_sync(0xffffffffu, ml, 1), c2 = __shfl_xor_sync(0xffffffffu, ml, 2), c3 = __shfl_xor_sync(0xffffffffu, ml, 3);
    mu = fmaxf(fmaxf(mu, a1), fmaxf(a2, a3)); ml = fmaxf(fmaxf(ml, c1), fmaxf(c2, c3)); }
  float su = 0.f, sl = 0.f;
#pragma unroll
  for (int c = 0; c < 14; c++) {
    const int iu = (c >> 1) * 4 + (c & 1) * 2;
    if (c >= U && c < U + 7) {
      float e0 = ex2(lu[2 * (c - U)] - mu), e1 = ex2(lu[2 * (c - U) + 1] - mu);
      su = c == U ? e0 + e1 : (su + e0) + e1; P[iu] = pack2(e0, e1);
    } else P[iu] = 0u;
    if (c >= L && c < L + 7) {
      float e0 = ex2(ll[2 * (c - L)] - ml), e1 = ex2(ll[2 * (c - L) + 1] - ml);
      sl = c == L ? e0 + e1 : (sl + e0) + e1; P[iu + 1] = pack2(e0, e1);
    } else P[iu + 1] = 0u;
  }
  sx[0] = su; sx[4] = sl;
#pragma unroll
  for (int k = 1; k < 4; k++) { sx[k] = __shfl_xor_sync(0xffffffffu, su, k); sx[4 + k] = __shfl_xor_sync(0xffffffffu, sl, k); }
}

struct Maps { CUtensorMap xc, xh, w, os, wo, ot; };

__global__ void __cluster_dims__(4, 1, 1) __launch_bounds__(512, 1)
na_attn_kernel(const __nv_bfloat16* __restrict__ x, const __nv_bfloat16* __restrict__ wqkv, const __nv_bfloat16* __restrict__ rpb, const __grid_constant__ Maps mp) {
  extern __shared__ __align__(1024) uint8_t smem_raw[];
  const uint32_t sb = smem_u32(smem_raw);
  if ((sb & 0x3FFFF) != SBC) return;
  const uint32_t bar = sb + SM_BAR;
  TR2(blockIdx.x, 0);
  const int tid = threadIdx.x, lane = tid & 31;
  const int warp = __shfl_sync(0xffffffffu, tid >> 5, 0);
  const int head = blockIdx.x & 3, cl = blockIdx.x >> 2;
  const int par = cl / 7, strip = cl - par * 7, ph = par >> 1, pw = par & 1;

  uint4 wv[2 * NL];
  const int va = head == 1;
  const uint32_t wdst = sb + SM_W + (va + ((tid >> 1) & 1)) * 6144 + (tid >> 2) * 32 + ((tid ^ (tid >> 4)) & 1) * 16;
  if (warp < 12) asm volatile("barrier.cluster.arrive.relaxed.aligned;" ::: "memory");
  {
    const uint32_t wo0 = (tid >> 2) * 1152 + head * 96 + va * 32 + (tid & 3) * 16;
#pragma unroll
    for (int i = 0; i < 2 * NL; i++)
      asm volatile("{\n.reg .pred p;\nsetp.lt.u32 p, %5, 384;\n@p ld.global.nc.v4.b32 {%0,%1,%2,%3}, [%4];\n}"
                   : "=r"(wv[i].x), "=r"(wv[i].y), "=r"(wv[i].z), "=r"(wv[i].w)
                   : "l"(reinterpret_cast<const uint8_t*>(wqkv) + wo0 + (i & 1) * 96 * 1152 + ((i / 2 + 1) % 3) * 384), "r"(tid));
  }
  if (warp < 8) {
    asm volatile("setmaxnreg.inc.sync.aligned.u32 %0;" ::"n"(RA));
    float rv = -INFINITY;
    if (tid < 169) rv = __bfloat162float(rpb[head * 169 + tid]) * 1.4426950408889634f;
    if (tid < 192) {
      const int kc = (tid & 15) + 3, wc = (tid >> 4) % 6;
      sts128(tid < 96 ? sb + SM_K + kc * KS + wc * 128 + 48 : sb + SM_V + kc * 1536 + wc * 128 + (6 + (kc & 1)) * 16, make_uint4(0, 0, 0, 0));
    }
#pragma unroll
    for (int i = 0; i < 2 * NL; i++) sts128(wdst + (i & 1) * 3072 + (i / 2) * 18432, wv[i]);
    fence_async();
    asm volatile("bar.arrive 1, 384;" ::: "memory");
    if (tid < 182) asm volatile("st.shared.f32 [%0], %1;" ::"r"(sb + SM_RPB + tid * 4), "f"(rv) : "memory");
    const int j = warp >> 2, w = warp & 3;
    int variant = w;
    if (strip == 0 && j == 0 && w < 2) variant = 4;
    if (strip == 6 && j == 1 && w >= 2) variant = 5;
    const uint32_t qa = sb + SM_Q + (8 * j + 2 * w + ((lane >> 3) & 1)) * 1536 + (lane >> 4) * 256 + (((lane & 7) * 16) ^ (((lane >> 3) & 1) * 64));
    uint32_t oa = sb + SM_O + j * 6144 + (2 * w + ((lane >> 3) & 1)) * 768 + (lane >> 4) * 128 + (lane & 7) * 16;
    const uint64_t dK = mkdesc(SBC + SM_K, 128, KS, 0) + j * (8 * KS / 16);
    const uint64_t dV = mkdesc(SBC + SM_V, 768, 128, 0) + j * (8 * 1536 / 16);
    asm volatile("barrier.cluster.wait.aligned;" ::: "memory");
    asm volatile("bar.sync 3, 256;" ::: "memory");
    float T[16];
    TRDECL;
    int b0 = 0, b1 = 0;
    uint32_t meta = 0;
    uint32_t q[12];
    mbar_wait(bar + B_Q0 * 8, 0);
#pragma unroll
    for (int k = 0; k < 3; k++) ldsm4(qa + k * 512, q[4 * k], q[4 * k + 1], q[4 * k + 2], q[4 * k + 3]);
#pragma unroll 1
    for (int b = 0; b < 14; b++) {
      const uint32_t pa = b & 1;
      float SA[56], SB[56];
      const uint64_t dA = dK + pa * (KSLOT >> 4), dB = dK + (pa ^ 1) * (KSLOT >> 4);
      TR(0, b, 0);
      nb_sync(N_KRDY + j, 256);
      TR(0, b, 1);
      TR(0, b - 1, 9);
      wg_fence();
      wg_rs112<0>(SA, q[0], q[1], q[2], q[3], dA);
      wg_rs112<0>(SB, q[0], q[1], q[2], q[3], dB);
      wg_rs112<1>(SA, q[4], q[5], q[6], q[7], dA + 16);
      wg_rs112<1>(SB, q[4], q[5], q[6], q[7], dB + 16);
      wg_rs112<1>(SA, q[8], q[9], q[10], q[11], dA + 32);
      wg_rs112<1>(SB, q[8], q[9], q[10], q[11], dB + 32);
      wg_commit();
      if (b + j < 14) nb_arrive(N_QK0 + j, 256);
      TR(0, b, 2);
      if (b <= 1 || b == 13) {
        uint32_t ln; asm volatile("mov.u32 %0, %%laneid;" : "=r"(ln));
        const int g = ln >> 2, t = ln & 3;
        const int sw = b == 0 ? max(g + 1, 4) : (b == 13 ? min(g + 1, 5) : g + 1);
        const int i0 = 2 * t, i1 = 2 * t + 1;
        b0 = i0 <= sw - 2; b1 = i1 <= sw - 2;
        const uint32_t tb = sb + SM_RPB + (variant < 4 ? 3 : variant + 1 - 2 * w) * 4;
        const uint32_t ra0 = tb + (i0 == sw - 1 ? 13 : i0 + 8 * b0 - g + 2) * 52;
        const uint32_t ra1 = tb + (i1 == sw - 1 ? 13 : i1 + 8 * b1 - g + 2) * 52;
#pragma unroll
        for (int jj = 0; jj < 8; jj++) { T[2 * jj] = lds_f32(ra0 + jj * 4); T[2 * jj + 1] = lds_f32(ra1 + jj * 4); }
        meta = ((0x5555u & ((1u << (2 * (sw - 1))) - 1)) ^ 0xDD88u ^ (((t ^ b) & 1) ? 0x5555u : 0u)) * 0x10001u;
      } else meta ^= 0x55555555u;
      if (b >= 12) oa += b == 12 ? warp * 1536 - (SM_O - SM_Q) : 1536;
      wg_wait<0>(); pin(SA); pin(SB);
      mbar_arrive_elect(bar + B_KFREE * 8);
      TR(0, b, 3);
      TR(0, b - 1, 10);
      uint32_t P[28];
      float sx[8];
      switch (variant) {
        case 0: softmax_tile<0, 1>(SA, SB, T, b0, b1, P, sx); break;
        case 1: softmax_tile<2, 3>(SA, SB, T, b0, b1, P, sx); break;
        case 2: softmax_tile<4, 5>(SA, SB, T, b0, b1, P, sx); break;
        case 3: softmax_tile<6, 7>(SA, SB, T, b0, b1, P, sx); break;
        case 4: softmax_tile<3, 3>(SA, SB, T, b0, b1, P, sx); break;
        default: softmax_tile<4, 4>(SA, SB, T, b0, b1, P, sx); break;
      }
      float O[24];
      TR(0, b, 4);
      nb_sync(N_VQ0 + j, b == 13 ? 256 : 288);
      TR(0, b, 5);
#pragma unroll
      for (int k = 0; k < 3; k++) ldsm4(qa + (pa ^ 1) * 128 + k * 512, q[4 * k], q[4 * k + 1], q[4 * k + 2], q[4 * k + 3]);
      wg_fence();
      wg_sp48<0>(O, P[0], P[1], P[2], P[3], dV, meta);
#pragma unroll
      for (int s = 1; s < 7; s++) wg_sp48<1>(O, P[4 * s], P[4 * s + 1], P[4 * s + 2], P[4 * s + 3], dV + s * 192, meta);
      wg_commit();
      if (b < 12 || (!(OPT & 2) && b == 13)) nb_arrive(N_PVISS, 384);
      TR(0, b, 6);
      if (b == 13) mbar_wait(bar + (B_TFREE + 1) * 8, 0);
      wg_wait<0>(); pin(O);
      mbar_arrive_elect(bar + B_VFREE * 8);
      TR(0, b, 7);
      float ru, rl;
      asm("rcp.approx.ftz.f32 %0, %1;" : "=f"(ru) : "f"(((fmaf(O[0], 0.f, sx[0]) + sx[1]) + sx[2]) + sx[3]));
      asm("rcp.approx.ftz.f32 %0, %1;" : "=f"(rl) : "f"(((fmaf(O[2], 0.f, sx[4]) + sx[5]) + sx[6]) + sx[7]));
#pragma unroll
      for (int i = 0; i < 3; i++)
        stsm4(oa + i * 256, pack2(O[8 * i] * ru, O[8 * i + 1] * ru), pack2(O[8 * i + 2] * rl, O[8 * i + 3] * rl),
              pack2(O[8 * i + 4] * ru, O[8 * i + 5] * ru), pack2(O[8 * i + 6] * rl, O[8 * i + 7] * rl));
      if (b < 13) publish(bar + (b < TB ? B_ODONE : B_OTAIL + j) * 8);
      else {
        fence_async();
        if (OPT & 2) nb_arrive(N_PVISS, 384);
        __syncwarp();
        if (elect_one()) {
#pragma unroll
          for (int d = 0; d < 2; d++)
            send_o<1536>(sb + SM_X0 + head * 6144 + (2 * j + (w & 1)) * 1536, sb + SM_Q + warp * 3072 + 1536, bar + (B_TIN + 2) * 8, (w & 2) + (d ^ (head & 1)));
        }
        __syncwarp();
      }
      TR(0, b, 8);
    }
    TRDUMP;
    cluster_sync();
  } else if (warp < 12) {
    TRDECL;
    TR(2, -3, 0);
    asm volatile("setmaxnreg.inc.sync.aligned.u32 %0;" ::"n"(RG));
    TR(2, -3, 1);
    GemmCtx c;
    c.bar = bar;
    const int gw = warp - 8, tk = gw * 16 + (lane & 15), hi = lane >> 4;
    { const int col = tk >> 2, i = tk & 3;
      c.kC = sb + SM_K + (col + 3) * KS + hi * 128 + i * 16;
      c.vC[0] = sb + SM_V + (col + 3) * 1536 + hi * 128 + (2 * i + ((col + 3) & 1)) * 16;
      c.qC[0] = sb + SM_Q + col * 1536 + hi * 256 + (col & 1) * 64 + i * 16; }
    { const int ci = (tk >> 3) - 2, kc = ci < 3 ? ci : ci + 16, i = tk & 7; c.hvalid = gw > 0;
      c.kH = sb + SM_K + kc * KS + hi * 128 + i * 16;
      c.vH[0] = sb + SM_V + kc * 1536 + hi * 128 + (i >> 2) * 768 + (2 * (i & 3) + ((kc ^ (i >> 2)) & 1)) * 16; }
    c.never = x == nullptr;
    c.kC = __shfl_sync(0xffffffffu, c.kC, lane); c.kH = __shfl_sync(0xffffffffu, c.kH, lane);
    c.vC[1] = __shfl_sync(0xffffffffu, c.vC[0] ^ 16, lane); c.vC[0] = __shfl_sync(0xffffffffu, c.vC[0], lane);
    c.vH[1] = __shfl_sync(0xffffffffu, c.vH[0] ^ 16, lane); c.vH[0] = __shfl_sync(0xffffffffu, c.vH[0], lane);
    c.qC[1] = __shfl_sync(0xffffffffu, c.qC[0] ^ 64, lane); c.qC[0] = __shfl_sync(0xffffffffu, c.qC[0], lane);
    c.spin = 0;
    asm volatile("barrier.cluster.wait.aligned;" ::: "memory");
    TR(2, -3, 2);
#pragma unroll
    for (int i = 0; i < 2 * NL; i++) sts128(wdst + (i & 1) * 3072 + (i / 2) * 18432, wv[i]);
    fence_async();
    TR(2, -3, 3);
    asm volatile("bar.sync 1, 384;" ::: "memory");
    TR(2, -3, 4);
    mbar_wait(bar + B_WK * 8, 0);
    TR(2, -3, 5);
    uint32_t pk[12], pv[12], pq[12];
    gemm_iter<true, false, 0>(c, -2, pk, pv, pq, &mp.wo TRPASS);
    TR2(blockIdx.x, 4);
#pragma unroll 1
    for (int b = -1;; b += 2) {
      gemm_iter<false, false, 1>(c, b, pk, pv, pq, &mp.wo TRPASS);
      if (b == 11) break;
      gemm_iter<false, false, 0>(c, b + 1, pk, pv, pq, &mp.wo TRPASS);
    }
    TR2(blockIdx.x, 6);
    gemm_iter<false, true, 0>(c, 12, pk, pv, pq, &mp.wo TRPASS);
    TR(2, 13, 0);
    mbar_wait(bar + B_WO * 8, 0);
    mbar_wait(bar + B_TIN * 8, 0);
    const uint32_t st = sb + gw * 3072;
    const uint32_t sta = st + (lane & 15) * 64 + ((hi ^ ((lane >> 1) & 3)) * 16);
    const int oc = ph * 112 + strip * 16 + 8 * (gw >> 1) + 4 * (head >> 1) + 2 * (gw & 1), och = pw * 6 + (head & 1) * 3;
    float D0[48], D1[48];
    nb_sync(N_PVISS, 384);
    TR(2, 13, 1);
    issue_proj<SM_X2>(D0);
    mbar_wait(bar + (B_TIN + 1) * 8, 0);
    issue_proj<SM_X1>(D1);
    TR(2, 13, 2);
    wg_wait<1>(); pin(D0);
    store_proj(D0, &mp.ot, st + SM_TST, sta + SM_TST, 8 * TB, oc, och);
    TR(2, 13, 3);
    mbar_wait(bar + (B_TIN + 2) * 8, 0);
    TR(2, 13, 4);
    issue_proj<SM_X0>(D0);
    asm volatile("barrier.cluster.arrive.relaxed.aligned;" ::: "memory");
    wg_wait<1>(); pin(D1);
    TR(2, 13, 5);
    store_proj(D1, &mp.ot, st + SM_X2, sta + SM_X2, 8 * TB + 8, oc, och);
    wg_wait<0>(); pin(D0);
    TR(2, 13, 6);
    store_proj(D0, &mp.ot, st + SM_X2 + 12288, sta + SM_X2 + 12288, 8 * TB + 16, oc, och);
    TR(2, 13, 7);
    if (lane == 0) asm volatile("cp.async.bulk.wait_group.read 0;" ::: "memory");
    __syncwarp();
    TR(2, 13, 8);
    TR2(blockIdx.x, 2);
    TRDUMP;
    asm volatile("barrier.cluster.wait.aligned;" ::: "memory");
  } else {
    if (warp == 12) {
      if (elect_one()) {
        mbar_init(bar + B_WK * 8, 1);
#pragma unroll
        for (int i = 0; i < NL; i++) load_w(&mp.w, sb + SM_W + (3 * i + 2 - 2 * va) * 6144, bar + B_WK * 8, ((i + 1) % 3) * 192 + head * 48 + 32 - 32 * va);
        asm volatile("prefetch.tensormap [%0];" ::"l"(head ? &mp.xc : &mp.xh) : "memory");
        mbar_expect(bar + B_WK * 8, NL * 6144);
      }
    } else if (warp == 15) {
      const int col = min(max(strip * 16 - 3 + min(lane, 21), 0), 111);
      const uint8_t* p = reinterpret_cast<const uint8_t*>(x) + (uint32_t)(head * ROWB + (ph * 112 + col) * 768 + pw * 384);
#pragma unroll
      for (int i = 0; i < 3; i++) asm volatile("prefetch.global.L2 [%0];" ::"l"(p + i * 128));
    } else if (elect_one()) {
      if (warp == 13) {
#pragma unroll
        for (int i = 0; i < B_WK; i++) mbar_init(bar + i * 8, i < B_EMPTY ? 1 : (i < B_TIN ? 16 : (i < B_TFREE ? 1 : 16)));
      } else {
#pragma unroll
        for (int i = B_WQ; i < B_COUNT; i++) mbar_init(bar + i * 8, i < B_Q0 ? 1 : (i < B_ODONE ? 4 : 8));
      }
    }
    asm volatile("fence.mbarrier_init.release.cluster;" ::: "memory");
    __syncwarp();
    asm volatile("barrier.cluster.arrive.relaxed.aligned;" ::: "memory");
    asm volatile("setmaxnreg.dec.sync.aligned.u32 24;");
    asm volatile("griddepcontrol.launch_dependents;");
    const int cc = ph * 112 + (head ? strip * 16 : (strip == 0 ? 16 : (strip == 6 ? 74 : strip * 16 - 3)));
    const int sd = strip == 0 ? -1 : (strip == 6 ? 1 : 0);
    const int r0 = head == 0 ? -4 : (head == 1 ? 4 : 0);
    asm volatile("barrier.cluster.wait.aligned;" ::: "memory");
    if (warp == 12) {
      const uint32_t fb = bar + (B_FULL + head) * 8, eb = bar + (B_EMPTY + head) * 8;
      const uint32_t dst = sb + (head == 0 ? SM_X0 : (head == 1 ? SM_X1 : SM_X2));
      const int nl = head == 0 ? 15 : (head == 3 ? 1 : 14);
#pragma unroll 1
      for (int n = 0; n < nl; n++) {
        if (n) mbar_wait(eb, (n - 1) & 1);
        if (lane < 4 && head < 3)
          asm volatile("{\n.reg .b32 ra;\nmapa.shared::cluster.u32 ra, %0, %1;\nmbarrier.arrive.expect_tx.shared::cluster.b64 _, [ra], %2;\n}"
                       ::"r"(fb), "r"(lane), "r"(head ? 24576 : 18432) : "memory");
        __syncwarp();
        if (elect_one()) {
          if (head == 0) {
            asm volatile("cp.async.bulk.tensor.5d.shared::cluster.global.mbarrier::complete_tx::bytes.multicast::cluster [%0], [%1, {%3,%4,%5,%6,%7}], [%2], %8;"
                         ::"r"(dst), "l"(&mp.xh), "r"(fb), "r"(0), "r"(8 * n + r0), "r"(cc), "r"(sd), "r"(pw * 3), "h"((uint16_t)15) : "memory");
          } else if (head < 3) {
            asm volatile("cp.async.bulk.tensor.4d.shared::cluster.global.mbarrier::complete_tx::bytes.multicast::cluster [%0], [%1, {%3,%4,%5,%6}], [%2], %7;"
                         ::"r"(dst), "l"(&mp.xc), "r"(fb), "r"(0), "r"(8 * n + r0), "r"(cc), "r"(pw * 3), "h"((uint16_t)15) : "memory");
          }
          if (n == 0) {
#pragma unroll
            for (int i = 0; i < 3; i++) load_w(&mp.w, sb + SM_W + (6 + i) * 6144, bar + B_WQ * 8, head * 48 + i * 16);
            mbar_expect(bar + B_WQ * 8, 18432);
            mbar_expect(bar + B_TIN * 8, 24576); mbar_expect(bar + (B_TIN + 1) * 8, 24576); mbar_expect(bar + (B_TIN + 2) * 8, 24576);
          }
          if (!head && n + 1 < nl) asm volatile("cp.async.bulk.prefetch.tensor.5d.L2.global [%0, {%1,%2,%3,%4,%5}];" ::"l"(&mp.xh), "r"(0), "r"(8 * n + 8 + r0), "r"(cc), "r"(sd), "r"(pw * 3) : "memory");
          if (head && n + 1 < nl) asm volatile("cp.async.bulk.prefetch.tensor.4d.L2.global [%0, {%1,%2,%3,%4}];" ::"l"(&mp.xc), "r"(0), "r"(8 * n + 8 + r0), "r"(cc), "r"(pw * 3) : "memory");
        }
        __syncwarp();
      }
    }
    if (warp == 14) {
      int* flag = g_flags + cl * 2;
      nb_arrive(N_VQ0, 288); nb_arrive(N_VQ1, 288);
#pragma unroll 1
      for (int b = 0; b < TB; b++) {
        mbar_wait(bar + B_ODONE * 8, b & 1);
        if (lane == 0) {
          asm volatile("cp.async.bulk.tensor.3d.global.shared::cta.bulk_group [%0, {%2,%3,%4}], [%1];"
                       ::"l"(&mp.os), "r"(sb + SM_O), "r"(pw * 192), "r"(8 * b + 2 * head), "r"(ph * 112 + strip * 16) : "memory");
          asm volatile("cp.async.bulk.commit_group;\ncp.async.bulk.wait_group 0;" ::: "memory");
        }
        __syncwarp();
        nb_arrive(N_VQ0, 288); nb_arrive(N_VQ1, 288);
        if (lane == 0)
          asm volatile("fence.proxy.async.global;\nfence.acq_rel.gpu;\nred.relaxed.gpu.global.add.s32 [%0], 1;\nred.relaxed.gpu.global.add.s32 [%0+4], 1;"
                       ::"l"(flag + b * 56) : "memory");
        __syncwarp();
      }
    } else if (warp & 1) {
      const int j = (warp >> 1) & 1;
#pragma unroll 1
      for (int i = 0; i < 2; i++) {
        mbar_wait(bar + (B_OTAIL + j) * 8, i);
        if (i == 0) nb_arrive(N_VQ0 + j, 288);
        mbar_wait(bar + (B_TFREE + i) * 8, 0);
        if (elect_one()) {
#pragma unroll 1
          for (int d = 0; d < 8; d++) {
            const int dst = (d + head) & 3, pc = d >> 2;
            send_o<1536>(sb + (i ? SM_X1 : SM_X2) + head * 6144 + j * 3072 + pc * 1536,
                         sb + (i ? SM_Q : SM_O) + (4 * j + (dst & 2) + pc) * (i ? 3072 : 1536), bar + (B_TIN + i) * 8, dst);
          }
        }
        __syncwarp();
      }
    }
    cluster_sync();
  }
}

constexpr int NSTB = 6;
constexpr int NTB = TB * 56;
constexpr int SM_B_IN = 0;
constexpr int SM_B_W = SM_B_IN + NSTB * 24576;
constexpr int SM_B_BAR = SM_B_W + 73728;
constexpr int SM_B_TOTAL = SM_B_BAR + 128;
struct MapsB { CUtensorMap oi, oo, wo; };

__global__ void __launch_bounds__(480, 1)
na_proj_kernel(const __grid_constant__ MapsB mp) {
  extern __shared__ __align__(1024) uint8_t smem_raw[];
  const uint32_t sb = smem_u32(smem_raw);
  if ((sb & 0x3FFFF) != SBC) return;
  const uint32_t bar = sb + SM_B_BAR;
  const int tid = threadIdx.x, lane = tid & 31;
  const int warp = __shfl_sync(0xffffffffu, tid >> 5, 0);
  TR2(132 + blockIdx.x, 0);
  TRB(47, 0);
  if (warp == 12 && elect_one()) {
#pragma unroll
    for (int i = 0; i <= 2 * NSTB; i++) mbar_init(bar + i * 8, i < NSTB || i == 2 * NSTB ? 1 : 4);
    mbar_expect(bar + 2 * NSTB * 8, 73728);
#pragma unroll
    for (int i = 0; i < 2; i++)
      asm volatile("cp.async.bulk.tensor.3d.shared::cluster.global.mbarrier::complete_tx::bytes [%0], [%1, {%3,%4,%5}], [%2];"
                   ::"r"(sb + SM_B_W + i * 36864), "l"(&mp.wo), "r"(bar + 2 * NSTB * 8), "r"(0), "r"(0), "r"(i * 3) : "memory");
  }
  __syncthreads();
  const int step = gridDim.x;
  if (warp >= 12) {
    const int wg = warp - 12;
    int use = 0;
#pragma unroll 1
    for (int n = blockIdx.x + wg * step; n < NTB; n += 3 * step, use++) {
      const int b = n / 56, rem = n - b * 56, par = rem / 14, sg = wg + 3 * (use & 1);
      int v; uint32_t spin = 0;
      do { asm volatile("ld.acquire.gpu.global.s32 %0, [%1];" : "=r"(v) : "l"(g_flags + n) : "memory"); if ((OPT & 1) && v < 4) __nanosleep(200); } while (v < 4 && ++spin < SPIN_LIMIT);
      TRB(use * 3 + wg, 0);
      asm volatile("fence.proxy.async.global;" ::: "memory");
      if (use >= 2) mbar_wait(bar + (NSTB + sg) * 8, ((use >> 1) - 1) & 1);
      TRB(use * 3 + wg, 1);
      if (elect_one()) {
        mbar_expect(bar + sg * 8, 24576);
        asm volatile("cp.async.bulk.tensor.3d.shared::cluster.global.mbarrier::complete_tx::bytes [%0], [%1, {%3,%4,%5}], [%2];"
                     ::"r"(sb + SM_B_IN + sg * 24576), "l"(&mp.oi), "r"(bar + sg * 8), "r"((par & 1) * 192), "r"(8 * b), "r"((par >> 1) * 112 + (rem - par * 14) * 8) : "memory");
        g_flags[n] = 0;
      }
      __syncwarp();
    }
  } else {
    const int wg = warp >> 2, w = warp & 3;
    constexpr uint64_t db = mkdesc(SBC + SM_B_W, 12288, 512, 2);
    const uint32_t sta0 = sb + SM_B_IN + w * 6144 + (lane & 15) * 128 + (((lane >> 4) ^ (lane & 7)) * 16);
    mbar_wait(bar + 2 * NSTB * 8, 0);
    TRB(47, 1);
    int use = 0;
#pragma unroll 1
    for (int n = blockIdx.x + wg * step; n < NTB; n += 3 * step, use++) {
      const int b = n / 56, rem = n - b * 56, par = rem / 14, sg = wg + 3 * (use & 1);
      const uint64_t da = mkdesc(SBC + SM_B_IN, 128, 3072, 0) + sg * (24576 / 16);
      float D[96];
      mbar_wait(bar + sg * 8, (use >> 1) & 1);
      if (use | wg) nb_sync(4 + wg, 256);
      TRB(use * 3 + wg, 3);
      wg_fence();
      wg_ss192<0>(D, da, db);
#pragma unroll
      for (int k = 1; k < 12; k++) wg_ss192<1>(D, da + k * 16, db + k * 64);
      wg_commit();
      if (n + step < NTB) nb_arrive(wg == 2 ? 4 : 5 + wg, 256);
      TRB(use * 3 + wg, 4);
      if (use && lane == 0) {
        asm volatile("cp.async.bulk.wait_group.read 0;" ::: "memory");
        mbar_arrive(bar + (NSTB + wg + 3 * (~use & 1)) * 8);
      }
      __syncwarp();
      wg_wait<0>(); pin(D);
      nb_sync(1 + wg, 128);
      TRB(use * 3 + wg, 5);
      const uint32_t sta = sta0 + sg * 24576;
#pragma unroll
      for (int q = 0; q < 12; q++)
        stsm4((sta ^ ((q & 3) * 32)) + (q >> 2) * 2048,
              pack2(D[8 * q], D[8 * q + 1]), pack2(D[8 * q + 2], D[8 * q + 3]), pack2(D[8 * q + 4], D[8 * q + 5]), pack2(D[8 * q + 6], D[8 * q + 7]));
      fence_async();
      __syncwarp();
      if (lane == 0) {
        asm volatile("cp.async.bulk.tensor.4d.global.shared::cta.bulk_group [%0, {%2,%3,%4,%5}], [%1];"
                     ::"l"(&mp.oo), "r"(sb + SM_B_IN + sg * 24576 + w * 6144), "r"(0), "r"(8 * b), "r"((par >> 1) * 112 + (rem - par * 14) * 8 + 2 * w), "r"((par & 1) * 3) : "memory");
        asm volatile("cp.async.bulk.commit_group;" ::: "memory");
      }
      __syncwarp();
      TRB(use * 3 + wg, 6);
    }
    if (lane == 0) asm volatile("cp.async.bulk.wait_group 0;" ::: "memory");
    TR2(132 + blockIdx.x, 2);
  }
}

typedef CUresult (*EncodeFn)(CUtensorMap*, CUtensorMapDataType, cuuint32_t, void*, const cuuint64_t*, const cuuint64_t*, const cuuint32_t*,
                             const cuuint32_t*, CUtensorMapInterleave, CUtensorMapSwizzle, CUtensorMapL2promotion, CUtensorMapFloatOOBfill);
static EncodeFn g_enc = nullptr;
static void make_map(CUtensorMap* m, const void* p, int rank, const cuuint64_t* dim, const cuuint64_t* str, const cuuint32_t* box, CUtensorMapSwizzle sw) {
  const cuuint32_t ones[5] = {1, 1, 1, 1, 1};
  g_enc(m, CU_TENSOR_MAP_DATA_TYPE_BFLOAT16, rank, (void*)p, dim, str, box, ones, CU_TENSOR_MAP_INTERLEAVE_NONE, sw,
        CU_TENSOR_MAP_L2_PROMOTION_L2_128B, CU_TENSOR_MAP_FLOAT_OOB_FILL_NONE);
}

extern "C" void kernel_launch(void* const* d_in, const int* in_sizes, int n_in, void* d_out, int out_size) {
  const __nv_bfloat16* x = (const __nv_bfloat16*)d_in[0];
  const __nv_bfloat16* wqkv = (const __nv_bfloat16*)d_in[1];
  const __nv_bfloat16* wo = (const __nv_bfloat16*)d_in[2];
  const __nv_bfloat16* rpb = (const __nv_bfloat16*)d_in[3];

  if (!g_enc) {
    void* fn = nullptr; cudaDriverEntryPointQueryResult qr;
    cudaGetDriverEntryPoint("cuTensorMapEncodeTiled", &fn, cudaEnableDefault, &qr);
    g_enc = (EncodeFn)fn;
    cudaFuncSetAttribute(na_attn_kernel, cudaFuncAttributeMaxDynamicSharedMemorySize, SM_A_TOTAL);
    cudaFuncSetAttribute(na_proj_kernel, cudaFuncAttributeMaxDynamicSharedMemorySize, SM_B_TOTAL);
  }
  Maps ma; MapsB mb;
  { cuuint64_t dim[4] = {64, 112, 224, 6}, str[3] = {(cuuint64_t)ROWB, 768, 128};
    cuuint32_t box[4] = {64, 4, 16, 3}, boxo[4] = {64, 8, 2, 3};
    make_map(&ma.xc, x, 4, dim, str, box, CU_TENSOR_MAP_SWIZZLE_128B);
    make_map(&mb.oo, d_out, 4, dim, str, boxo, CU_TENSOR_MAP_SWIZZLE_128B); }
  { cuuint64_t dim[5] = {64, 112, 224, 2, 6}, str[4] = {(cuuint64_t)ROWB, 768, 19 * 768, 128};
    cuuint32_t box[5] = {64, 8, 3, 2, 3};
    make_map(&ma.xh, x, 5, dim, str, box, CU_TENSOR_MAP_SWIZZLE_128B); }
  { cuuint64_t dim[3] = {384, 112, 224}, str[2] = {(cuuint64_t)ROWB, 768};
    cuuint32_t box[3] = {192, 8, 8}, boxs[3] = {192, 2, 16};
    make_map(&mb.oi, d_out, 3, dim, str, box, CU_TENSOR_MAP_SWIZZLE_NONE);
    make_map(&ma.os, d_out, 3, dim, str, boxs, CU_TENSOR_MAP_SWIZZLE_NONE); }
  { cuuint64_t dim[4] = {32, 112, 224, 12}, str[3] = {(cuuint64_t)ROWB, 768, 64};
    cuuint32_t box[4] = {32, 8, 2, 3};
    make_map(&ma.ot, d_out, 4, dim, str, box, CU_TENSOR_MAP_SWIZZLE_64B); }
  { cuuint64_t dim[2] = {576, 192}, str[1] = {1152};
    cuuint32_t box[2] = {16, 192};
    make_map(&ma.w, wqkv, 2, dim, str, box, CU_TENSOR_MAP_SWIZZLE_32B); }
  { cuuint64_t dim[3] = {32, 192, 6}, str[2] = {384, 64};
    cuuint32_t box[3] = {32, 192, 3};
    make_map(&ma.wo, wo, 3, dim, str, box, CU_TENSOR_MAP_SWIZZLE_64B);
    mb.wo = ma.wo; }
  na_attn_kernel<<<112, 512, SM_A_TOTAL>>>(x, wqkv, rpb, ma);
  cudaLaunchConfig_t cfg = {};
  cfg.gridDim = dim3(20); cfg.blockDim = dim3(480); cfg.dynamicSmemBytes = SM_B_TOTAL; cfg.stream = cudaStreamPerThread;
  cudaLaunchAttribute at[1];
  at[0].id = cudaLaunchAttributeProgrammaticStreamSerialization; at[0].val.programmaticStreamSerializationAllowed = 1;
  cfg.attrs = at; cfg.numAttrs = 1;
  cudaLaunchKernelEx(&cfg, na_proj_kernel, mb);
}
```

```cpp
#include <cuda_runtime.h>
#include <cuda_bf16.h>
#include <cuda.h>
#include <stdint.h>

#define SPIN_LIMIT (1u << 18)

__device__ __forceinline__ uint32_t smem_u32(const void* p) { return (uint32_t)__cvta_generic_to_shared(p); }
__device__ __forceinline__ void wg_fence() { asm volatile("wgmma.fence.sync.aligned;" ::: "memory"); }
__device__ __forceinline__ void wg_commit() { asm volatile("wgmma.commit_group.sync.aligned;" ::: "memory"); }
template <int N> __device__ __forceinline__ void wg_wait() { asm volatile("wgmma.wait_group.sync.aligned %0;" ::"n"(N) : "memory"); }
template <int N> __device__ __forceinline__ void pin(float (&d)[N]) {
#pragma unroll
  for (int i = 0; i < N; i++) asm volatile("" : "+f"(d[i])::"memory");
}
__host__ __device__ constexpr uint64_t mkdesc(uint32_t addr, uint32_t lbo, uint32_t sbo, uint32_t sw) {
  return (uint64_t)((addr & 0x3FFFF) >> 4) | ((uint64_t)(lbo >> 4) << 16) | ((uint64_t)(sbo >> 4) << 32) | ((uint64_t)sw << 62);
}
__device__ __forceinline__ void mbar_init(uint32_t bar, uint32_t cnt) { asm volatile("mbarrier.init.shared::cta.b64 [%0], %1;" ::"r"(bar), "r"(cnt) : "memory"); }
__device__ __forceinline__ void mbar_arrive(uint32_t bar) { asm volatile("mbarrier.arrive.shared::cta.b64 _, [%0];" ::"r"(bar) : "memory"); }
__device__ __forceinline__ bool elect_one() {
  uint32_t r; asm volatile("{\n.reg .pred p;\nelect.sync _|p, 0xffffffff;\nselp.u32 %0, 1, 0, p;\n}" : "=r"(r)); return r;
}
__device__ __forceinline__ void mbar_arrive_elect(uint32_t bar) {
  asm volatile("{\n.reg .pred p;\nelect.sync _|p, 0xffffffff;\n@p mbarrier.arrive.shared::cta.b64 _, [%0];\n}" ::"r"(bar) : "memory");
}
__device__ __forceinline__ void mbar_expect(uint32_t bar, uint32_t bytes) { asm volatile("mbarrier.arrive.expect_tx.shared::cta.b64 _, [%0], %1;" ::"r"(bar), "r"(bytes) : "memory"); }
__device__ __forceinline__ void mbar_arrive_remote(uint32_t bar, uint32_t cta) {
  asm volatile("{\n.reg .b32 ra;\nmapa.shared::cluster.u32 ra, %0, %1;\nmbarrier.arrive.relaxed.cluster.shared::cluster.b64 _, [ra];\n}" ::"r"(bar), "r"(cta) : "memory");
}
__device__ __forceinline__ void mbar_wait(uint32_t bar, uint32_t parity) {
  asm volatile("{\n.reg .pred p;\n.reg .b32 n;\nmov.b32 n, 0;\nWL:\nmbarrier.try_wait.parity.shared::cta.b64 p, [%0], %1;\n@p bra WD;\n"
               "add.u32 n, n, 1;\nsetp.lt.u32 p, n, 65536;\n@p bra WL;\nWD:\n}" ::"r"(bar), "r"(parity) : "memory");
}
__device__ __forceinline__ void nb_sync(int id, int n) { asm volatile("bar.sync %0, %1;" ::"r"(id), "r"(n) : "memory"); }
__device__ __forceinline__ void nb_arrive(int id, int n) { asm volatile("bar.arrive %0, %1;" ::"r"(id), "r"(n) : "memory"); }
__device__ __forceinline__ void fence_async() { asm volatile("fence.proxy.async.shared::cta;" ::: "memory"); }
__device__ __forceinline__ void cluster_sync() {
  asm volatile("barrier.cluster.arrive.relaxed.aligned;\nbarrier.cluster.wait.aligned;" ::: "memory");
}
__device__ __forceinline__ uint32_t pack2(float lo, float hi) {
  uint32_t r; asm("cvt.rn.bf16x2.f32 %0, %1, %2;" : "=r"(r) : "f"(hi), "f"(lo)); return r;
}
__device__ __forceinline__ void stsm4(uint32_t a, uint32_t r0, uint32_t r1, uint32_t r2, uint32_t r3) {
  asm volatile("stmatrix.sync.aligned.m8n8.x4.shared.b16 [%0], {%1,%2,%3,%4};" ::"r"(a), "r"(r0), "r"(r1), "r"(r2), "r"(r3) : "memory");
}
__device__ __forceinline__ void ldsm4(uint32_t a, uint32_t& r0, uint32_t& r1, uint32_t& r2, uint32_t& r3) {
  asm volatile("ldmatrix.sync.aligned.m8n8.x4.shared.b16 {%0,%1,%2,%3}, [%4];" : "=r"(r0), "=r"(r1), "=r"(r2), "=r"(r3) : "r"(a) : "memory");
}
__device__ __forceinline__ void sts128(uint32_t a, uint4 v) {
  asm volatile("st.shared.v4.b32 [%0], {%1,%2,%3,%4};" ::"r"(a), "r"(v.x), "r"(v.y), "r"(v.z), "r"(v.w) : "memory");
}
__device__ __forceinline__ float lds_f32(uint32_t a) { float v; asm volatile("ld.shared.f32 %0, [%1];" : "=f"(v) : "r"(a)); return v; }
__device__ __forceinline__ float ex2(float x) { float y; asm("ex2.approx.ftz.f32 %0, %1;" : "=f"(y) : "f"(x)); return y; }

template<int SC> __device__ __forceinline__ void wg_ss144(float (&d)[72], uint64_t da, uint64_t db) {
  asm volatile("{\n.reg .pred p;\nsetp.ne.b32 p, %74, 0;\nwgmma.mma_async.sync.aligned.m64n144k16.f32.bf16.bf16 {%0,%1,%2,%3,%4,%5,%6,%7,%8,%9,%10,%11,%12,%13,%14,%15,%16,%17,%18,%19,%20,%21,%22,%23,%24,%25,%26,%27,%28,%29,%30,%31,%32,%33,%34,%35,%36,%37,%38,%39,%40,%41,%42,%43,%44,%45,%46,%47,%48,%49,%50,%51,%52,%53,%54,%55,%56,%57,%58,%59,%60,%61,%62,%63,%64,%65,%66,%67,%68,%69,%70,%71}, %72, %73, p, 1, 1, 0, 1;\n}\n"
    : "+f"(d[0]),"+f"(d[1]),"+f"(d[2]),"+f"(d[3]),"+f"(d[4]),"+f"(d[5]),"+f"(d[6]),"+f"(d[7]),"+f"(d[8]),"+f"(d[9]),"+f"(d[10]),"+f"(d[11]),"+f"(d[12]),"+f"(d[13]),"+f"(d[14]),"+f"(d[15]),"+f"(d[16]),"+f"(d[17]),"+f"(d[18]),"+f"(d[19]),"+f"(d[20]),"+f"(d[21]),"+f"(d[22]),"+f"(d[23]),"+f"(d[24]),"+f"(d[25]),"+f"(d[26]),"+f"(d[27]),"+f"(d[28]),"+f"(d[29]),"+f"(d[30]),"+f"(d[31]),"+f"(d[32]),"+f"(d[33]),"+f"(d[34]),"+f"(d[35]),"+f"(d[36]),"+f"(d[37]),"+f"(d[38]),"+f"(d[39]),"+f"(d[40]),"+f"(d[41]),"+f"(d[42]),"+f"(d[43]),"+f"(d[44]),"+f"(d[45]),"+f"(d[46]),"+f"(d[47]),"+f"(d[48]),"+f"(d[49]),"+f"(d[50]),"+f"(d[51]),"+f"(d[52]),"+f"(d[53]),"+f"(d[54]),"+f"(d[55]),"+f"(d[56]),"+f"(d[57]),"+f"(d[58]),"+f"(d[59]),"+f"(d[60]),"+f"(d[61]),"+f"(d[62]),"+f"(d[63]),"+f"(d[64]),"+f"(d[65]),"+f"(d[66]),"+f"(d[67]),"+f"(d[68]),"+f"(d[69]),"+f"(d[70]),"+f"(d[71]) : "l"(da), "l"(db), "n"(SC));
}
template<int SC> __device__ __forceinline__ void wg_ss96(float (&d)[48], uint64_t da, uint64_t db) {
  asm volatile("{\n.reg .pred p;\nsetp.ne.b32 p, %50, 0;\nwgmma.mma_async.sync.aligned.m64n96k16.f32.bf16.bf16 {%0,%1,%2,%3,%4,%5,%6,%7,%8,%9,%10,%11,%12,%13,%14,%15,%16,%17,%18,%19,%20,%21,%22,%23,%24,%25,%26,%27,%28,%29,%30,%31,%32,%33,%34,%35,%36,%37,%38,%39,%40,%41,%42,%43,%44,%45,%46,%47}, %48, %49, p, 1, 1, 0, 1;\n}\n"
    : "+f"(d[0]),"+f"(d[1]),"+f"(d[2]),"+f"(d[3]),"+f"(d[4]),"+f"(d[5]),"+f"(d[6]),"+f"(d[7]),"+f"(d[8]),"+f"(d[9]),"+f"(d[10]),"+f"(d[11]),"+f"(d[12]),"+f"(d[13]),"+f"(d[14]),"+f"(d[15]),"+f"(d[16]),"+f"(d[17]),"+f"(d[18]),"+f"(d[19]),"+f"(d[20]),"+f"(d[21]),"+f"(d[22]),"+f"(d[23]),"+f"(d[24]),"+f"(d[25]),"+f"(d[26]),"+f"(d[27]),"+f"(d[28]),"+f"(d[29]),"+f"(d[30]),"+f"(d[31]),"+f"(d[32]),"+f"(d[33]),"+f"(d[34]),"+f"(d[35]),"+f"(d[36]),"+f"(d[37]),"+f"(d[38]),"+f"(d[39]),"+f"(d[40]),"+f"(d[41]),"+f"(d[42]),"+f"(d[43]),"+f"(d[44]),"+f"(d[45]),"+f"(d[46]),"+f"(d[47]) : "l"(da), "l"(db), "n"(SC));
}
template<int SC> __device__ __forceinline__ void wg_rs112(float (&d)[56], uint32_t a0, uint32_t a1, uint32_t a2, uint32_t a3, uint64_t db) {
  asm volatile("{\n.reg .pred p;\nsetp.ne.b32 p, %61, 0;\nwgmma.mma_async.sync.aligned.m64n112k16.f32.bf16.bf16 {%0,%1,%2,%3,%4,%5,%6,%7,%8,%9,%10,%11,%12,%13,%14,%15,%16,%17,%18,%19,%20,%21,%22,%23,%24,%25,%26,%27,%28,%29,%30,%31,%32,%33,%34,%35,%36,%37,%38,%39,%40,%41,%42,%43,%44,%45,%46,%47,%48,%49,%50,%51,%52,%53,%54,%55}, {%56,%57,%58,%59}, %60, p, 1, 1, 0;\n}\n"
    : "+f"(d[0]),"+f"(d[1]),"+f"(d[2]),"+f"(d[3]),"+f"(d[4]),"+f"(d[5]),"+f"(d[6]),"+f"(d[7]),"+f"(d[8]),"+f"(d[9]),"+f"(d[10]),"+f"(d[11]),"+f"(d[12]),"+f"(d[13]),"+f"(d[14]),"+f"(d[15]),"+f"(d[16]),"+f"(d[17]),"+f"(d[18]),"+f"(d[19]),"+f"(d[20]),"+f"(d[21]),"+f"(d[22]),"+f"(d[23]),"+f"(d[24]),"+f"(d[25]),"+f"(d[26]),"+f"(d[27]),"+f"(d[28]),"+f"(d[29]),"+f"(d[30]),"+f"(d[31]),"+f"(d[32]),"+f"(d[33]),"+f"(d[34]),"+f"(d[35]),"+f"(d[36]),"+f"(d[37]),"+f"(d[38]),"+f"(d[39]),"+f"(d[40]),"+f"(d[41]),"+f"(d[42]),"+f"(d[43]),"+f"(d[44]),"+f"(d[45]),"+f"(d[46]),"+f"(d[47]),"+f"(d[48]),"+f"(d[49]),"+f"(d[50]),"+f"(d[51]),"+f"(d[52]),"+f"(d[53]),"+f"(d[54]),"+f"(d[55]) : "r"(a0), "r"(a1), "r"(a2), "r"(a3), "l"(db), "n"(SC));
}
template<int SC> __device__ __forceinline__ void wg_sp48(float (&d)[24], uint32_t a0, uint32_t a1, uint32_t a2, uint32_t a3, uint64_t db, uint32_t meta) {
  asm volatile("{\n.reg .pred p;\nsetp.ne.b32 p, %30, 0;\nwgmma.mma_async.sp.sync.aligned.m64n48k32.f32.bf16.bf16 {%0,%1,%2,%3,%4,%5,%6,%7,%8,%9,%10,%11,%12,%13,%14,%15,%16,%17,%18,%19,%20,%21,%22,%23}, {%24,%25,%26,%27}, %28, %29, 0, p, 1, 1, 1;\n}\n"
    : "+f"(d[0]),"+f"(d[1]),"+f"(d[2]),"+f"(d[3]),"+f"(d[4]),"+f"(d[5]),"+f"(d[6]),"+f"(d[7]),"+f"(d[8]),"+f"(d[9]),"+f"(d[10]),"+f"(d[11]),"+f"(d[12]),"+f"(d[13]),"+f"(d[14]),"+f"(d[15]),"+f"(d[16]),"+f"(d[17]),"+f"(d[18]),"+f"(d[19]),"+f"(d[20]),"+f"(d[21]),"+f"(d[22]),"+f"(d[23]) : "r"(a0), "r"(a1), "r"(a2), "r"(a3), "l"(db), "r"(meta), "n"(SC));
}
template<int SC> __device__ __forceinline__ void wg_ss192(float (&d)[96], uint64_t da, uint64_t db) {
  asm volatile("{\n.reg .pred p;\nsetp.ne.b32 p, %98, 0;\nwgmma.mma_async.sync.aligned.m64n192k16.f32.bf16.bf16 {%0,%1,%2,%3,%4,%5,%6,%7,%8,%9,%10,%11,%12,%13,%14,%15,%16,%17,%18,%19,%20,%21,%22,%23,%24,%25,%26,%27,%28,%29,%30,%31,%32,%33,%34,%35,%36,%37,%38,%39,%40,%41,%42,%43,%44,%45,%46,%47,%48,%49,%50,%51,%52,%53,%54,%55,%56,%57,%58,%59,%60,%61,%62,%63,%64,%65,%66,%67,%68,%69,%70,%71,%72,%73,%74,%75,%76,%77,%78,%79,%80,%81,%82,%83,%84,%85,%86,%87,%88,%89,%90,%91,%92,%93,%94,%95}, %96, %97, p, 1, 1, 0, 1;\n}\n"
    : "+f"(d[0]),"+f"(d[1]),"+f"(d[2]),"+f"(d[3]),"+f"(d[4]),"+f"(d[5]),"+f"(d[6]),"+f"(d[7]),"+f"(d[8]),"+f"(d[9]),"+f"(d[10]),"+f"(d[11]),"+f"(d[12]),"+f"(d[13]),"+f"(d[14]),"+f"(d[15]),"+f"(d[16]),"+f"(d[17]),"+f"(d[18]),"+f"(d[19]),"+f"(d[20]),"+f"(d[21]),"+f"(d[22]),"+f"(d[23]),"+f"(d[24]),"+f"(d[25]),"+f"(d[26]),"+f"(d[27]),"+f"(d[28]),"+f"(d[29]),"+f"(d[30]),"+f"(d[31]),"+f"(d[32]),"+f"(d[33]),"+f"(d[34]),"+f"(d[35]),"+f"(d[36]),"+f"(d[37]),"+f"(d[38]),"+f"(d[39]),"+f"(d[40]),"+f"(d[41]),"+f"(d[42]),"+f"(d[43]),"+f"(d[44]),"+f"(d[45]),"+f"(d[46]),"+f"(d[47]),"+f"(d[48]),"+f"(d[49]),"+f"(d[50]),"+f"(d[51]),"+f"(d[52]),"+f"(d[53]),"+f"(d[54]),"+f"(d[55]),"+f"(d[56]),"+f"(d[57]),"+f"(d[58]),"+f"(d[59]),"+f"(d[60]),"+f"(d[61]),"+f"(d[62]),"+f"(d[63]),"+f"(d[64]),"+f"(d[65]),"+f"(d[66]),"+f"(d[67]),"+f"(d[68]),"+f"(d[69]),"+f"(d[70]),"+f"(d[71]),"+f"(d[72]),"+f"(d[73]),"+f"(d[74]),"+f"(d[75]),"+f"(d[76]),"+f"(d[77]),"+f"(d[78]),"+f"(d[79]),"+f"(d[80]),"+f"(d[81]),"+f"(d[82]),"+f"(d[83]),"+f"(d[84]),"+f"(d[85]),"+f"(d[86]),"+f"(d[87]),"+f"(d[88]),"+f"(d[89]),"+f"(d[90]),"+f"(d[91]),"+f"(d[92]),"+f"(d[93]),"+f"(d[94]),"+f"(d[95]) : "l"(da), "l"(db), "n"(SC));
}

constexpr uint32_t SBC = 1024;
constexpr int ROWB = 2 * 224 * 384;
constexpr int TB = 11;
constexpr int KS = 832;
constexpr int KSLOT = 22 * KS;
constexpr int SM_X1 = 0;
constexpr int SM_X2 = SM_X1 + 24576;
constexpr int SM_X0 = SM_X2 + 24576;
constexpr int SM_W = SM_X0 + 18432;
constexpr int SM_K = SM_W + 55296;
constexpr int SM_V = SM_K + 2 * KSLOT;
constexpr int SM_Q = SM_V + 22 * 1536;
constexpr int SM_O = SM_Q + 24576;
constexpr int SM_RPB = SM_O + 12288;
constexpr int SM_BAR = SM_RPB + 768;
constexpr int SM_A_TOTAL = SM_BAR + 256;
constexpr int SM_TWO = SM_X0 + 24576;
constexpr int SM_TST = SM_TWO + 36864;
enum { B_FULL = 0, B_EMPTY = 3, B_TIN = 6, B_TFREE = 9, B_WK = 11, B_WQ, B_WO, B_Q0, B_OTAIL, B_ODONE = B_OTAIL + 2, B_KFREE, B_VFREE, B_COUNT };
enum { N_KRDY = 4, N_QK0, N_QK1, N_VQ0, N_VQ1, N_PVISS };

#define NL 2
#define OPT 0
#define SPL 4
#define RA 152
#define RG 184
__device__ int g_flags[TB * 56];

#define TR(role, it, k)
#define TRDECL
#define TRARG
#define TRPASS
#define TRDUMP
#define TRB(it, k)
#define TR2(blk, k)

struct GemmCtx {
  uint32_t bar;
  uint32_t kC, vC[2], qC[2];
  uint32_t kH, vH[2];
  uint32_t spin;
  bool hvalid, never;
};

template <int STRIDE> __device__ __forceinline__ void dump12(uint32_t a, const uint32_t (&r)[12]) {
#pragma unroll
  for (int j = 0; j < 3; j++) stsm4(a + j * 2 * STRIDE, r[4 * j], r[4 * j + 1], r[4 * j + 2], r[4 * j + 3]);
}
__device__ __forceinline__ void keep12(bool never, uint32_t a, const uint32_t (&r)[12]) { if (never) dump12<128>(a, r); }
template <int N> __device__ __forceinline__ void pack12(uint32_t (&r)[12], const float (&d)[N], int off) {
#pragma unroll
  for (int j = 0; j < 12; j++) r[j] = pack2(d[off + 2 * j], d[off + 2 * j + 1]);
}
template <int XS, int K0, int K1> __device__ __forceinline__ void issue_core(float (&d)[72]) {
  constexpr uint64_t da = mkdesc(SBC + XS, 16, 1024, 1), db = mkdesc(SBC + SM_W, 6144, 256, 3);
  wg_fence();
  if (K0 == 0) wg_ss144<0>(d, da, db);
#pragma unroll
  for (int k = K0 ? K0 : 1; k < K1; k++) wg_ss144<1>(d, da + (k >> 2) * 512 + (k & 3) * 2, db + k * 32);
  wg_commit();
}
template <int K0, int K1> __device__ __forceinline__ void issue_halo(float (&d)[48]) {
  constexpr uint64_t da = mkdesc(SBC + SM_X0 - 2048, 16, 1024, 1), db = mkdesc(SBC + SM_W, 6144, 256, 3);
  wg_fence();
  if (K0 == 0) wg_ss96<0>(d, da, db);
#pragma unroll
  for (int k = K0 ? K0 : 1; k < K1; k++) wg_ss96<1>(d, da + (k >> 2) * 384 + (k & 3) * 2, db + k * 32);
  wg_commit();
}
template <int ST> __device__ __forceinline__ void release_stage(const GemmCtx& c) {
  asm volatile("{\n.reg .pred p;\n.reg .b32 ra;\nelect.sync _|p, 0xffffffff;\nmapa.shared::cluster.u32 ra, %0, %1;\n"
               "@p mbarrier.arrive.shared::cluster.b64 _, [ra];\n}" ::"r"(c.bar + (B_EMPTY + ST) * 8), "n"(ST) : "memory");
}
template <int PARITY> __device__ __forceinline__ void gwait(GemmCtx& c, int bar) {
  asm volatile("{\n.reg .pred p;\nWL:\nmbarrier.try_wait.parity.shared::cta.b64 p, [%1], %2;\n@p bra WD;\n"
               "add.u32 %0, %0, 1;\nsetp.lt.u32 p, %0, 0x100000;\n@p bra WL;\nWD:\n}" : "+r"(c.spin) : "r"(c.bar + bar * 8), "n"(PARITY) : "memory");
}
__device__ __forceinline__ void load_w(const CUtensorMap* m, uint32_t dst, uint32_t bar, int col) {
  asm volatile("cp.async.bulk.tensor.2d.shared::cluster.global.mbarrier::complete_tx::bytes [%0], [%1, {%3,%4}], [%2];"
               ::"r"(dst), "l"(m), "r"(bar), "r"(col), "r"(0) : "memory");
}
template <int BYTES> __device__ __forceinline__ void send_o(uint32_t dst, uint32_t src, uint32_t bar, int cta) {
  asm volatile("{\n.reg .b32 rd, rb;\nmapa.shared::cluster.u32 rd, %0, %3;\nmapa.shared::cluster.u32 rb, %2, %3;\n"
               "cp.async.bulk.shared::cluster.shared::cta.mbarrier::complete_tx::bytes [rd], [%1], %4, [rb];\n}"
               ::"r"(dst), "r"(src), "r"(bar), "r"(cta), "n"(BYTES) : "memory");
}
__device__ __forceinline__ void tail_free(uint32_t bar) {
  uint32_t ln; asm volatile("mov.u32 %0, %%laneid;" : "=r"(ln));
  if (ln < 4) mbar_arrive_remote(bar, ln);
}
__device__ __forceinline__ void publish(uint32_t bar) {
  fence_async();
  __syncwarp();
  mbar_arrive_elect(bar);
}

template <bool FIRST, bool LAST, int PA>
__device__ __forceinline__ void gemm_iter(GemmCtx& c, int b, uint32_t (&pk)[12], uint32_t (&pv)[12], uint32_t (&pq)[12], const CUtensorMap* mwo TRARG) {
  const uint32_t bar = c.bar;
  const bool w = !FIRST && (PA == 0 || b >= 0), never = c.never;
  constexpr uint32_t ko = PA * KSLOT;
  float H[48], C[72];
  uint32_t hk[12], hv[12], pv2[12];
  TR(2, b, 0);
  if (FIRST) gwait<PA>(c, B_FULL + 0);
  if (!FIRST) dump12<256>(c.qC[1] + (PA ^ 1) * 128, pq);
  if (w) nb_sync(N_QK1, 256);
  TR(2, b, 2);
  if (FIRST) TR(2, b - 1, 6);
  issue_halo<0, 8>(H);
  TR(2, b, 3);
  if (!FIRST) {
    if (w) gwait<PA>(c, B_KFREE);
    dump12<128>(c.kC + ko, pk);
  }
  issue_halo<8, 12>(H);
  TR(2, b, 4);
  if (!LAST) {
    gwait<PA>(c, B_FULL + 2);
    if (FIRST && NL == 2) gwait<0>(c, B_WQ);
    TR(2, b, 13);
    if (FIRST) TR(2, b - 1, 7);
    issue_core<SM_X2, 0, 8>(C);
    TR(2, b, 5);
    if (!FIRST) { fence_async(); keep12(never, c.kC, pk); }
    wg_wait<1>(); pin(H);
    release_stage<0>(c);
  } else {
    fence_async();
    nb_arrive(N_VQ0, 288); nb_arrive(N_VQ1, 288); nb_arrive(N_PVISS, 384);
    wg_wait<0>(); pin(H);
    tail_free(bar + (B_TFREE + 1) * 8);
    nb_sync(2, 128);
    if (!c.hvalid && elect_one()) {
      mbar_expect(bar + B_WO * 8, 36864);
      asm volatile("cp.async.bulk.tensor.3d.shared::cluster.global.mbarrier::complete_tx::bytes [%0], [%1, {%3,%4,%5}], [%2];"
                   ::"r"(bar - SM_BAR + SM_TWO), "l"(mwo), "r"(bar + B_WO * 8), "r"(0), "r"(0), "r"((blockIdx.x & 1) * 3) : "memory");
    }
    __syncwarp();
  }
  pack12(hk, H, 0);
  if (c.hvalid) dump12<128>(c.kH + ko, hk);
  pack12(hv, H, 24);
  if (!LAST) {
    issue_core<SM_X2, 8, 12>(C);
    if (w) { nb_arrive(N_VQ0, 288); nb_arrive(N_VQ1, 288); }
    else if (!FIRST) { __syncwarp(); mbar_arrive_elect(bar + B_Q0 * 8); }
    gwait<PA>(c, B_FULL + 1);
    keep12(never, c.kC, hk);
    TR(2, b, 6);
    wg_wait<0>(); pin(C);
    TR(2, b, 7);
    pack12(pk, C, 0);
    dump12<128>(c.kC + ko + 64, pk);
    release_stage<2>(c);
    pack12(pv2, C, 24);
    pack12(pq, C, 48);
    TR(2, b, 8);
    issue_core<SM_X1, 0, SPL>(C);
    if (w) nb_sync(N_PVISS, 384);
    issue_core<SM_X1, SPL, 8>(C);
    TR(2, b, 9);
  }
  if (!FIRST) fence_async();
  if (!LAST) keep12(never, c.kC, pk);
  TR(2, b, 14);
  if (!LAST) issue_core<SM_X1, 8, 12>(C);
  if (!FIRST) nb_arrive(N_KRDY, 256);
  TR(2, b, 1);
  if (PA && b == 11) tail_free(bar + B_TFREE * 8);
  if (!LAST) gwait<PA ^ 1>(c, B_FULL + 0);
  if (w) gwait<PA>(c, B_VFREE);
  TR(2, b, 10);
  if (!FIRST) dump12<128>(c.vC[PA], pv);
  if (!LAST) dump12<256>(c.qC[0] + PA * 128, pq);
  if (c.hvalid) dump12<128>(c.vH[PA], hv);
  if (LAST) { fence_async(); nb_arrive(N_VQ0, 288); nb_arrive(N_VQ1, 288); nb_arrive(N_QK1, 256); return; }
  dump12<128>(c.vC[PA ^ 1] + 768, pv2);
  TR(2, b, 11);
  wg_wait<0>(); pin(C);
  TR(2, b, 12);
  release_stage<1>(c);
  pack12(pk, C, 0);
  pack12(pv, C, 24);
  pack12(pq, C, 48);
}

template <int IN> __device__ __forceinline__ void issue_proj(float (&D)[48]) {
  constexpr uint64_t da = mkdesc(SBC + IN, 128, 768, 0), db = mkdesc(SBC + SM_TWO, 12288, 512, 2);
  wg_fence();
  wg_ss96<0>(D, da, db);
#pragma unroll
  for (int k = 1; k < 12; k++) wg_ss96<1>(D, da + (k / 3) * 384 + (k % 3) * 16, db + k * 64);
  wg_commit();
}
__device__ __forceinline__ void store_proj(const float (&D)[48], const CUtensorMap* m, uint32_t st, uint32_t sta, int row, int col, int ch) {
#pragma unroll
  for (int q = 0; q < 6; q++)
    stsm4((sta ^ ((q & 1) * 32)) + (q >> 1) * 1024,
          pack2(D[8 * q], D[8 * q + 1]), pack2(D[8 * q + 2], D[8 * q + 3]), pack2(D[8 * q + 4], D[8 * q + 5]), pack2(D[8 * q + 6], D[8 * q + 7]));
  fence_async();
  __syncwarp();
  if ((threadIdx.x & 31) == 0) {
    asm volatile("cp.async.bulk.tensor.4d.global.shared::cta.bulk_group [%0, {%2,%3,%4,%5}], [%1];" ::"l"(m), "r"(st), "r"(0), "r"(row), "r"(col), "r"(ch) : "memory");
    asm volatile("cp.async.bulk.commit_group;" ::: "memory");
  }
  __syncwarp();
}

__device__ __forceinline__ float fold(float a, float b, float t, int useb) {
  float r;
  asm("{\n.reg .pred p;\nsetp.ne.b32 p, %4, 0;\nfma.rn.f32 %0, %1, 0f3E553B95, %3;\n@p fma.rn.f32 %0, %2, 0f3E553B95, %3;\n}"
      : "=&f"(r) : "f"(a), "f"(b), "f"(t), "r"(useb));
  return r;
}
template <int U, int L>
__device__ __forceinline__ void softmax_tile(const float (&SA)[56], const float (&SB)[56], const float (&T)[16], int b0, int b1,
                                             uint32_t (&P)[28], float (&sx)[8]) {
  float lu[14], ll[14];
#pragma unroll
  for (int j = 0; j < 7; j++) {
    constexpr int sh = U == L ? 2 : 0;
    const float tu0 = T[2 * j + sh], tu1 = T[2 * j + 1 + sh], tl0 = T[2 * j], tl1 = T[2 * j + 1];
    lu[2 * j]     = fold(SA[4 * (U + j)],     SB[4 * (U + j)],     tu0, b0);
    ll[2 * j]     = fold(SA[4 * (L + j) + 2], SB[4 * (L + j) + 2], tl0, b0);
    lu[2 * j + 1] = fold(SA[4 * (U + j) + 1], SB[4 * (U + j) + 1], tu1, b1);
    ll[2 * j + 1] = fold(SA[4 * (L + j) + 3], SB[4 * (L + j) + 3], tl1, b1);
  }
  float mu = lu[0], ml = ll[0], mu2 = lu[1], ml2 = ll[1];
#pragma unroll
  for (int j = 1; j < 7; j++) { mu = fmaxf(mu, lu[2 * j]); mu2 = fmaxf(mu2, lu[2 * j + 1]); ml = fmaxf(ml, ll[2 * j]); ml2 = fmaxf(ml2, ll[2 * j + 1]); }
  mu = fmaxf(mu, mu2); ml = fmaxf(ml, ml2);
  { const float a1 = __shfl_xor_sync(0xffffffffu, mu, 1), a2 = __shfl_xor_sync(0xffffffffu, mu, 2), a3 = __shfl_xor_sync(0xffffffffu, mu, 3);
    const float c1 = __shfl_xor_sync(0xffffffffu, ml, 1), c2 = __shfl_xor_sync(0xffffffffu, ml, 2), c3 = __shfl_xor_sync(0xffffffffu, ml, 3);
    mu = fmaxf(fmaxf(mu, a1), fmaxf(a2, a3)); ml = fmaxf(fmaxf(ml, c1), fmaxf(c2, c3)); }
  float su = 0.f, sl = 0.f;
#pragma unroll
  for (int c = 0; c < 14; c++) {
    const int iu = (c >> 1) * 4 + (c & 1) * 2;
    if (c >= U && c < U + 7) {
      float e0 = ex2(lu[2 * (c - U)] - mu), e1 = ex2(lu[2 * (c - U) + 1] - mu);
      su = c == U ? e0 + e1 : (su + e0) + e1; P[iu] = pack2(e0, e1);
    } else P[iu] = 0u;
    if (c >= L && c < L + 7) {
      float e0 = ex2(ll[2 * (c - L)] - ml), e1 = ex2(ll[2 * (c - L) + 1] - ml);
      sl = c == L ? e0 + e1 : (sl + e0) + e1; P[iu + 1] = pack2(e0, e1);
    } else P[iu + 1] = 0u;
  }
  sx[0] = su; sx[4] = sl;
#pragma unroll
  for (int k = 1; k < 4; k++) { sx[k] = __shfl_xor_sync(0xffffffffu, su, k); sx[4 + k] = __shfl_xor_sync(0xffffffffu, sl, k); }
}

struct Maps { CUtensorMap xc, xh, w, os, wo, ot; };

__global__ void __cluster_dims__(4, 1, 1) __launch_bounds__(512, 1)
na_attn_kernel(const __nv_bfloat16* __restrict__ x, const __nv_bfloat16* __restrict__ wqkv, const __nv_bfloat16* __restrict__ rpb, const __grid_constant__ Maps mp) {
  extern __shared__ __align__(1024) uint8_t smem_raw[];
  const uint32_t sb = smem_u32(smem_raw);
  if ((sb & 0x3FFFF) != SBC) return;
  const uint32_t bar = sb + SM_BAR;
  TR2(blockIdx.x, 0);
  const int tid = threadIdx.x, lane = tid & 31;
  const int warp = __shfl_sync(0xffffffffu, tid >> 5, 0);
  const int head = blockIdx.x & 3, cl = blockIdx.x >> 2;
  const int par = cl / 7, strip = cl - par * 7, ph = par >> 1, pw = par & 1;

  uint4 wv[2 * NL];
  const int va = head == 1;
  const uint32_t wdst = sb + SM_W + (va + ((tid >> 1) & 1)) * 6144 + (tid >> 2) * 32 + ((tid ^ (tid >> 4)) & 1) * 16;
  if (warp < 12) asm volatile("barrier.cluster.arrive.relaxed.aligned;" ::: "memory");
  {
    const uint32_t wo0 = (tid >> 2) * 1152 + head * 96 + va * 32 + (tid & 3) * 16;
#pragma unroll
    for (int i = 0; i < 2 * NL; i++)
      asm volatile("{\n.reg .pred p;\nsetp.lt.u32 p, %5, 384;\n@p ld.global.nc.v4.b32 {%0,%1,%2,%3}, [%4];\n}"
                   : "=r"(wv[i].x), "=r"(wv[i].y), "=r"(wv[i].z), "=r"(wv[i].w)
                   : "l"(reinterpret_cast<const uint8_t*>(wqkv) + wo0 + (i & 1) * 96 * 1152 + ((i / 2 + 1) % 3) * 384), "r"(tid));
  }
  if (warp < 8) {
    asm volatile("setmaxnreg.inc.sync.aligned.u32 %0;" ::"n"(RA));
    float rv = -INFINITY;
    if (tid < 169) rv = __bfloat162float(rpb[head * 169 + tid]) * 1.4426950408889634f;
    if (tid < 192) {
      const int kc = (tid & 15) + 3, wc = (tid >> 4) % 6;
      sts128(tid < 96 ? sb + SM_K + kc * KS + wc * 128 + 48 : sb + SM_V + kc * 1536 + wc * 128 + (6 + (kc & 1)) * 16, make_uint4(0, 0, 0, 0));
    }
#pragma unroll
    for (int i = 0; i < 2 * NL; i++) sts128(wdst + (i & 1) * 3072 + (i / 2) * 18432, wv[i]);
    fence_async();
    asm volatile("bar.arrive 1, 384;" ::: "memory");
    if (tid < 182) asm volatile("st.shared.f32 [%0], %1;" ::"r"(sb + SM_RPB + tid * 4), "f"(rv) : "memory");
    const int j = warp >> 2, w = warp & 3;
    int variant = w;
    if (strip == 0 && j == 0 && w < 2) variant = 4;
    if (strip == 6 && j == 1 && w >= 2) variant = 5;
    const uint32_t qa = sb + SM_Q + (8 * j + 2 * w + ((lane >> 3) & 1)) * 1536 + (lane >> 4) * 256 + (((lane & 7) * 16) ^ (((lane >> 3) & 1) * 64));
    uint32_t oa = sb + SM_O + j * 6144 + (2 * w + ((lane >> 3) & 1)) * 768 + (lane >> 4) * 128 + (lane & 7) * 16;
    const uint64_t dK = mkdesc(SBC + SM_K, 128, KS, 0) + j * (8 * KS / 16);
    const uint64_t dV = mkdesc(SBC + SM_V, 768, 128, 0) + j * (8 * 1536 / 16);
    asm volatile("barrier.cluster.wait.aligned;" ::: "memory");
    asm volatile("bar.sync 3, 256;" ::: "memory");
    float T[16];
    TRDECL;
    int b0 = 0, b1 = 0;
    uint32_t meta = 0, ob = bar + B_ODONE * 8;
    uint32_t q[12];
    mbar_wait(bar + B_Q0 * 8, 0);
#pragma unroll
    for (int k = 0; k < 3; k++) ldsm4(qa + k * 512, q[4 * k], q[4 * k + 1], q[4 * k + 2], q[4 * k + 3]);
#pragma unroll 1
    for (int b = 0; b < 14; b++) {
      const uint32_t pa = b & 1;
      float SA[56], SB[56];
      const uint64_t dA = dK + pa * (KSLOT >> 4), dB = dK + (pa ^ 1) * (KSLOT >> 4);
      TR(0, b, 0);
      nb_sync(N_KRDY + j, 256);
      TR(0, b, 1);
      TR(0, b - 1, 9);
      wg_fence();
      wg_rs112<0>(SA, q[0], q[1], q[2], q[3], dA);
      wg_rs112<0>(SB, q[0], q[1], q[2], q[3], dB);
      wg_rs112<1>(SA, q[4], q[5], q[6], q[7], dA + 16);
      wg_rs112<1>(SB, q[4], q[5], q[6], q[7], dB + 16);
      wg_rs112<1>(SA, q[8], q[9], q[10], q[11], dA + 32);
      wg_rs112<1>(SB, q[8], q[9], q[10], q[11], dB + 32);
      wg_commit();
      nb_arrive(N_QK0 + j, 256);
      TR(0, b, 2);
      if (b <= 1 || b == 13) {
        uint32_t ln; asm volatile("mov.u32 %0, %%laneid;" : "=r"(ln));
        const int g = ln >> 2, t = ln & 3;
        const int sw = b == 0 ? max(g + 1, 4) : (b == 13 ? min(g + 1, 5) : g + 1);
        const int i0 = 2 * t, i1 = 2 * t + 1;
        b0 = i0 <= sw - 2; b1 = i1 <= sw - 2;
        const uint32_t tb = sb + SM_RPB + (variant < 4 ? 3 : variant + 1 - 2 * w) * 4;
        const uint32_t ra0 = tb + (i0 == sw - 1 ? 13 : i0 + 8 * b0 - g + 2) * 52;
        const uint32_t ra1 = tb + (i1 == sw - 1 ? 13 : i1 + 8 * b1 - g + 2) * 52;
#pragma unroll
        for (int jj = 0; jj < 8; jj++) { T[2 * jj] = lds_f32(ra0 + jj * 4); T[2 * jj + 1] = lds_f32(ra1 + jj * 4); }
        meta = ((0x5555u & ((1u << (2 * (sw - 1))) - 1)) ^ 0xDD88u ^ (((t ^ b) & 1) ? 0x5555u : 0u)) * 0x10001u;
      } else meta ^= 0x55555555u;
      if (b == TB) ob = bar + (B_OTAIL + j) * 8;
      if (b >= 12) oa += b == 12 ? warp * 1536 - (SM_O - SM_Q) : 1536;
      wg_wait<0>(); pin(SA); pin(SB);
      mbar_arrive_elect(bar + B_KFREE * 8);
      TR(0, b, 3);
      TR(0, b - 1, 10);
      uint32_t P[28];
      float sx[8];
      switch (variant) {
        case 0: softmax_tile<0, 1>(SA, SB, T, b0, b1, P, sx); break;
        case 1: softmax_tile<2, 3>(SA, SB, T, b0, b1, P, sx); break;
        case 2: softmax_tile<4, 5>(SA, SB, T, b0, b1, P, sx); break;
        case 3: softmax_tile<6, 7>(SA, SB, T, b0, b1, P, sx); break;
        case 4: softmax_tile<3, 3>(SA, SB, T, b0, b1, P, sx); break;
        default: softmax_tile<4, 4>(SA, SB, T, b0, b1, P, sx); break;
      }
      float O[24];
      TR(0, b, 4);
      nb_sync(N_VQ0 + j, 288);
      TR(0, b, 5);
#pragma unroll
      for (int k = 0; k < 3; k++) ldsm4(qa + (pa ^ 1) * 128 + k * 512, q[4 * k], q[4 * k + 1], q[4 * k + 2], q[4 * k + 3]);
      wg_fence();
      wg_sp48<0>(O, P[0], P[1], P[2], P[3], dV, meta);
#pragma unroll
      for (int s = 1; s < 7; s++) wg_sp48<1>(O, P[4 * s], P[4 * s + 1], P[4 * s + 2], P[4 * s + 3], dV + s * 192, meta);
      wg_commit();
      nb_arrive(N_PVISS, 384);
      TR(0, b, 6);
      wg_wait<0>(); pin(O);
      mbar_arrive_elect(bar + B_VFREE * 8);
      TR(0, b, 7);
      float ru, rl;
      asm("rcp.approx.ftz.f32 %0, %1;" : "=f"(ru) : "f"(((fmaf(O[0], 0.f, sx[0]) + sx[1]) + sx[2]) + sx[3]));
      asm("rcp.approx.ftz.f32 %0, %1;" : "=f"(rl) : "f"(((fmaf(O[2], 0.f, sx[4]) + sx[5]) + sx[6]) + sx[7]));
#pragma unroll
      for (int i = 0; i < 3; i++)
        stsm4(oa + i * 256, pack2(O[8 * i] * ru, O[8 * i + 1] * ru), pack2(O[8 * i + 2] * rl, O[8 * i + 3] * rl),
              pack2(O[8 * i + 4] * ru, O[8 * i + 5] * ru), pack2(O[8 * i + 6] * rl, O[8 * i + 7] * rl));
      publish(ob);
      TR(0, b, 8);
    }
    if (elect_one()) {
#pragma unroll
      for (int d = 0; d < 2; d++)
        send_o<1536>(sb + SM_X0 + head * 6144 + (2 * j + (w & 1)) * 1536, sb + SM_Q + warp * 3072 + 1536, bar + (B_TIN + 2) * 8, (w & 2) + (d ^ (head & 1)));
    }
    __syncwarp();
    TRDUMP;
    cluster_sync();
  } else if (warp < 12) {
    TRDECL;
    TR(2, -3, 0);
    asm volatile("setmaxnreg.inc.sync.aligned.u32 %0;" ::"n"(RG));
    TR(2, -3, 1);
    GemmCtx c;
    c.bar = bar;
    const int gw = warp - 8, tk = gw * 16 + (lane & 15), hi = lane >> 4;
    { const int col = tk >> 2, i = tk & 3;
      c.kC = sb + SM_K + (col + 3) * KS + hi * 128 + i * 16;
      c.vC[0] = sb + SM_V + (col + 3) * 1536 + hi * 128 + (2 * i + ((col + 3) & 1)) * 16;
      c.qC[0] = sb + SM_Q + col * 1536 + hi * 256 + (col & 1) * 64 + i * 16; }
    { const int ci = (tk >> 3) - 2, kc = ci < 3 ? ci : ci + 16, i = tk & 7; c.hvalid = gw > 0;
      c.kH = sb + SM_K + kc * KS + hi * 128 + i * 16;
      c.vH[0] = sb + SM_V + kc * 1536 + hi * 128 + (i >> 2) * 768 + (2 * (i & 3) + ((kc ^ (i >> 2)) & 1)) * 16; }
    c.never = x == nullptr;
    c.kC = __shfl_sync(0xffffffffu, c.kC, lane); c.kH = __shfl_sync(0xffffffffu, c.kH, lane);
    c.vC[1] = __shfl_sync(0xffffffffu, c.vC[0] ^ 16, lane); c.vC[0] = __shfl_sync(0xffffffffu, c.vC[0], lane);
    c.vH[1] = __shfl_sync(0xffffffffu, c.vH[0] ^ 16, lane); c.vH[0] = __shfl_sync(0xffffffffu, c.vH[0], lane);
    c.qC[1] = __shfl_sync(0xffffffffu, c.qC[0] ^ 64, lane); c.qC[0] = __shfl_sync(0xffffffffu, c.qC[0], lane);
    c.spin = 0;
    asm volatile("barrier.cluster.wait.aligned;" ::: "memory");
    TR(2, -3, 2);
#pragma unroll
    for (int i = 0; i < 2 * NL; i++) sts128(wdst + (i & 1) * 3072 + (i / 2) * 18432, wv[i]);
    fence_async();
    TR(2, -3, 3);
    asm volatile("bar.sync 1, 384;" ::: "memory");
    TR(2, -3, 4);
    mbar_wait(bar + B_WK * 8, 0);
    TR(2, -3, 5);
    uint32_t pk[12], pv[12], pq[12];
    gemm_iter<true, false, 0>(c, -2, pk, pv, pq, &mp.wo TRPASS);
    TR2(blockIdx.x, 4);
#pragma unroll 1
    for (int b = -1;; b += 2) {
      gemm_iter<false, false, 1>(c, b, pk, pv, pq, &mp.wo TRPASS);
      if (b == 11) break;
      gemm_iter<false, false, 0>(c, b + 1, pk, pv, pq, &mp.wo TRPASS);
    }
    TR2(blockIdx.x, 6);
    gemm_iter<false, true, 0>(c, 12, pk, pv, pq, &mp.wo TRPASS);
    TR(2, 13, 0);
    mbar_wait(bar + B_WO * 8, 0);
    mbar_wait(bar + B_TIN * 8, 0);
    const uint32_t st = sb + gw * 3072;
    const uint32_t sta = st + (lane & 15) * 64 + ((hi ^ ((lane >> 1) & 3)) * 16);
    const int oc = ph * 112 + strip * 16 + 8 * (gw >> 1) + 4 * (head >> 1) + 2 * (gw & 1), och = pw * 6 + (head & 1) * 3;
    float D0[48], D1[48];
    nb_sync(N_PVISS, 384);
    TR(2, 13, 1);
    issue_proj<SM_X2>(D0);
    mbar_wait(bar + (B_TIN + 1) * 8, 0);
    issue_proj<SM_X1>(D1);
    TR(2, 13, 2);
    wg_wait<1>(); pin(D0);
    store_proj(D0, &mp.ot, st + SM_TST, sta + SM_TST, 8 * TB, oc, och);
    TR(2, 13, 3);
    mbar_wait(bar + (B_TIN + 2) * 8, 0);
    TR(2, 13, 4);
    issue_proj<SM_X0>(D0);
    asm volatile("barrier.cluster.arrive.relaxed.aligned;" ::: "memory");
    wg_wait<1>(); pin(D1);
    TR(2, 13, 5);
    store_proj(D1, &mp.ot, st + SM_X2, sta + SM_X2, 8 * TB + 8, oc, och);
    wg_wait<0>(); pin(D0);
    TR(2, 13, 6);
    store_proj(D0, &mp.ot, st + SM_X2 + 12288, sta + SM_X2 + 12288, 8 * TB + 16, oc, och);
    TR(2, 13, 7);
    if (lane == 0) asm volatile("cp.async.bulk.wait_group.read 0;" ::: "memory");
    __syncwarp();
    TR(2, 13, 8);
    TR2(blockIdx.x, 2);
    TRDUMP;
    asm volatile("barrier.cluster.wait.aligned;" ::: "memory");
  } else {
    if (warp == 12) {
      if (elect_one()) {
        mbar_init(bar + B_WK * 8, 1);
#pragma unroll
        for (int i = 0; i < NL; i++) load_w(&mp.w, sb + SM_W + (3 * i + 2 - 2 * va) * 6144, bar + B_WK * 8, ((i + 1) % 3) * 192 + head * 48 + 32 - 32 * va);
        asm volatile("prefetch.tensormap [%0];" ::"l"(head ? &mp.xc : &mp.xh) : "memory");
        mbar_expect(bar + B_WK * 8, NL * 6144);
      }
    } else if (warp == 15) {
      const int col = min(max(strip * 16 - 3 + min(lane, 21), 0), 111);
      const uint8_t* p = reinterpret_cast<const uint8_t*>(x) + (uint32_t)(head * ROWB + (ph * 112 + col) * 768 + pw * 384);
#pragma unroll
      for (int i = 0; i < 3; i++) asm volatile("prefetch.global.L2 [%0];" ::"l"(p + i * 128));
    } else if (elect_one()) {
      if (warp == 13) {
#pragma unroll
        for (int i = 0; i < B_WK; i++) mbar_init(bar + i * 8, i < B_EMPTY ? 1 : (i < B_TIN ? 16 : (i < B_TFREE ? 1 : 16)));
      } else {
#pragma unroll
        for (int i = B_WQ; i < B_COUNT; i++) mbar_init(bar + i * 8, i < B_Q0 ? 1 : (i < B_ODONE ? 4 : 8));
      }
    }
    asm volatile("fence.mbarrier_init.release.cluster;" ::: "memory");
    __syncwarp();
    asm volatile("barrier.cluster.arrive.relaxed.aligned;" ::: "memory");
    asm volatile("setmaxnreg.dec.sync.aligned.u32 24;");
    asm volatile("griddepcontrol.launch_dependents;");
    const int cc = ph * 112 + (head ? strip * 16 : (strip == 0 ? 16 : (strip == 6 ? 74 : strip * 16 - 3)));
    const int sd = strip == 0 ? -1 : (strip == 6 ? 1 : 0);
    const int r0 = head == 0 ? -4 : (head == 1 ? 4 : 0);
    asm volatile("barrier.cluster.wait.aligned;" ::: "memory");
    if (warp == 12) {
      const uint32_t fb = bar + (B_FULL + head) * 8, eb = bar + (B_EMPTY + head) * 8;
      const uint32_t dst = sb + (head == 0 ? SM_X0 : (head == 1 ? SM_X1 : SM_X2));
      const int nl = head == 0 ? 15 : (head == 3 ? 1 : 14);
#pragma unroll 1
      for (int n = 0; n < nl; n++) {
        if (n) mbar_wait(eb, (n - 1) & 1);
        if (lane < 4 && head < 3)
          asm volatile("{\n.reg .b32 ra;\nmapa.shared::cluster.u32 ra, %0, %1;\nmbarrier.arrive.expect_tx.shared::cluster.b64 _, [ra], %2;\n}"
                       ::"r"(fb), "r"(lane), "r"(head ? 24576 : 18432) : "memory");
        __syncwarp();
        if (elect_one()) {
          if (head == 0) {
            asm volatile("cp.async.bulk.tensor.5d.shared::cluster.global.mbarrier::complete_tx::bytes.multicast::cluster [%0], [%1, {%3,%4,%5,%6,%7}], [%2], %8;"
                         ::"r"(dst), "l"(&mp.xh), "r"(fb), "r"(0), "r"(8 * n + r0), "r"(cc), "r"(sd), "r"(pw * 3), "h"((uint16_t)15) : "memory");
          } else if (head < 3) {
            asm volatile("cp.async.bulk.tensor.4d.shared::cluster.global.mbarrier::complete_tx::bytes.multicast::cluster [%0], [%1, {%3,%4,%5,%6}], [%2], %7;"
                         ::"r"(dst), "l"(&mp.xc), "r"(fb), "r"(0), "r"(8 * n + r0), "r"(cc), "r"(pw * 3), "h"((uint16_t)15) : "memory");
          }
          if (n == 0) {
#pragma unroll
            for (int i = 0; i < 3; i++) load_w(&mp.w, sb + SM_W + (6 + i) * 6144, bar + B_WQ * 8, head * 48 + i * 16);
            mbar_expect(bar + B_WQ * 8, 18432);
            mbar_expect(bar + B_TIN * 8, 24576); mbar_expect(bar + (B_TIN + 1) * 8, 24576); mbar_expect(bar + (B_TIN + 2) * 8, 24576);
          }
          if (!head && n + 1 < nl) asm volatile("cp.async.bulk.prefetch.tensor.5d.L2.global [%0, {%1,%2,%3,%4,%5}];" ::"l"(&mp.xh), "r"(0), "r"(8 * n + 8 + r0), "r"(cc), "r"(sd), "r"(pw * 3) : "memory");
          if (head && n + 1 < nl) asm volatile("cp.async.bulk.prefetch.tensor.4d.L2.global [%0, {%1,%2,%3,%4}];" ::"l"(&mp.xc), "r"(0), "r"(8 * n + 8 + r0), "r"(cc), "r"(pw * 3) : "memory");
        }
        __syncwarp();
      }
    }
    if (warp == 14) {
      int* flag = g_flags + cl * 2;
      nb_arrive(N_VQ0, 288); nb_arrive(N_VQ1, 288);
#pragma unroll 1
      for (int b = 0; b < TB; b++) {
        mbar_wait(bar + B_ODONE * 8, b & 1);
        if (lane == 0) {
          asm volatile("cp.async.bulk.tensor.3d.global.shared::cta.bulk_group [%0, {%2,%3,%4}], [%1];"
                       ::"l"(&mp.os), "r"(sb + SM_O), "r"(pw * 192), "r"(8 * b + 2 * head), "r"(ph * 112 + strip * 16) : "memory");
          asm volatile("cp.async.bulk.commit_group;\ncp.async.bulk.wait_group 0;" ::: "memory");
        }
        __syncwarp();
        nb_arrive(N_VQ0, 288); nb_arrive(N_VQ1, 288);
        if (lane == 0)
          asm volatile("fence.proxy.async.global;\nfence.acq_rel.gpu;\nred.relaxed.gpu.global.add.s32 [%0], 1;\nred.relaxed.gpu.global.add.s32 [%0+4], 1;"
                       ::"l"(flag + b * 56) : "memory");
        __syncwarp();
      }
    } else if (warp & 1) {
      const int j = (warp >> 1) & 1;
#pragma unroll 1
      for (int i = 0; i < 2; i++) {
        mbar_wait(bar + (B_OTAIL + j) * 8, i);
        if (i == 0) nb_arrive(N_VQ0 + j, 288);
        mbar_wait(bar + (B_TFREE + i) * 8, 0);
        if (i == 1) nb_arrive(N_VQ0 + j, 288);
        if (elect_one()) {
#pragma unroll 1
          for (int d = 0; d < 8; d++) {
            const int dst = (d + head) & 3, pc = d >> 2;
            send_o<1536>(sb + (i ? SM_X1 : SM_X2) + head * 6144 + j * 3072 + pc * 1536,
                         sb + (i ? SM_Q : SM_O) + (4 * j + (dst & 2) + pc) * (i ? 3072 : 1536), bar + (B_TIN + i) * 8, dst);
          }
        }
        __syncwarp();
      }
    }
    cluster_sync();
  }
}

constexpr int NSTB = 6;
constexpr int NTB = TB * 56;
constexpr int SM_B_IN = 0;
constexpr int SM_B_W = SM_B_IN + NSTB * 24576;
constexpr int SM_B_BAR = SM_B_W + 73728;
constexpr int SM_B_TOTAL = SM_B_BAR + 128;
struct MapsB { CUtensorMap oi, oo, wo; };

__global__ void __launch_bounds__(480, 1)
na_proj_kernel(const __grid_constant__ MapsB mp) {
  extern __shared__ __align__(1024) uint8_t smem_raw[];
  const uint32_t sb = smem_u32(smem_raw);
  if ((sb & 0x3FFFF) != SBC) return;
  const uint32_t bar = sb + SM_B_BAR;
  const int tid = threadIdx.x, lane = tid & 31;
  const int warp = __shfl_sync(0xffffffffu, tid >> 5, 0);
  TR2(132 + blockIdx.x, 0);
  TRB(47, 0);
  if (warp == 12 && elect_one()) {
#pragma unroll
    for (int i = 0; i <= 2 * NSTB; i++) mbar_init(bar + i * 8, i < NSTB || i == 2 * NSTB ? 1 : 4);
    mbar_expect(bar + 2 * NSTB * 8, 73728);
#pragma unroll
    for (int i = 0; i < 2; i++)
      asm volatile("cp.async.bulk.tensor.3d.shared::cluster.global.mbarrier::complete_tx::bytes [%0], [%1, {%3,%4,%5}], [%2];"
                   ::"r"(sb + SM_B_W + i * 36864), "l"(&mp.wo), "r"(bar + 2 * NSTB * 8), "r"(0), "r"(0), "r"(i * 3) : "memory");
  }
  __syncthreads();
  const int step = gridDim.x;
  if (warp >= 12) {
    const int wg = warp - 12;
    int use = 0;
#pragma unroll 1
    for (int n = blockIdx.x + wg * step; n < NTB; n += 3 * step, use++) {
      const int b = n / 56, rem = n - b * 56, par = rem / 14, sg = wg + 3 * (use & 1);
      int v; uint32_t spin = 0;
      do { asm volatile("ld.acquire.gpu.global.s32 %0, [%1];" : "=r"(v) : "l"(g_flags + n) : "memory"); if ((OPT & 1) && v < 4) __nanosleep(200); } while (v < 4 && ++spin < SPIN_LIMIT);
      TRB(use * 3 + wg, 0);
      asm volatile("fence.proxy.async.global;" ::: "memory");
      if (use >= 2) mbar_wait(bar + (NSTB + sg) * 8, ((use >> 1) - 1) & 1);
      TRB(use * 3 + wg, 1);
      if (elect_one()) {
        mbar_expect(bar + sg * 8, 24576);
        asm volatile("cp.async.bulk.tensor.3d.shared::cluster.global.mbarrier::complete_tx::bytes [%0], [%1, {%3,%4,%5}], [%2];"
                     ::"r"(sb + SM_B_IN + sg * 24576), "l"(&mp.oi), "r"(bar + sg * 8), "r"((par & 1) * 192), "r"(8 * b), "r"((par >> 1) * 112 + (rem - par * 14) * 8) : "memory");
        g_flags[n] = 0;
      }
      __syncwarp();
    }
  } else {
    const int wg = warp >> 2, w = warp & 3;
    constexpr uint64_t db = mkdesc(SBC + SM_B_W, 12288, 512, 2);
    const uint32_t sta0 = sb + SM_B_IN + w * 6144 + (lane & 15) * 128 + (((lane >> 4) ^ (lane & 7)) * 16);
    mbar_wait(bar + 2 * NSTB * 8, 0);
    TRB(47, 1);
    int use = 0;
#pragma unroll 1
    for (int n = blockIdx.x + wg * step; n < NTB; n += 3 * step, use++) {
      const int b = n / 56, rem = n - b * 56, par = rem / 14, sg = wg + 3 * (use & 1);
      const uint64_t da = mkdesc(SBC + SM_B_IN, 128, 3072, 0) + sg * (24576 / 16);
      float D[96];
      mbar_wait(bar + sg * 8, (use >> 1) & 1);
      if (use | wg) nb_sync(4 + wg, 256);
      TRB(use * 3 + wg, 3);
      wg_fence();
      wg_ss192<0>(D, da, db);
#pragma unroll
      for (int k = 1; k < 12; k++) wg_ss192<1>(D, da + k * 16, db + k * 64);
      wg_commit();
      if (n + step < NTB) nb_arrive(wg == 2 ? 4 : 5 + wg, 256);
      TRB(use * 3 + wg, 4);
      if (use && lane == 0) {
        asm volatile("cp.async.bulk.wait_group.read 0;" ::: "memory");
        mbar_arrive(bar + (NSTB + wg + 3 * (~use & 1)) * 8);
      }
      __syncwarp();
      wg_wait<0>(); pin(D);
      nb_sync(1 + wg, 128);
      TRB(use * 3 + wg, 5);
      const uint32_t sta = sta0 + sg * 24576;
#pragma unroll
      for (int q = 0; q < 12; q++)
        stsm4((sta ^ ((q & 3) * 32)) + (q >> 2) * 2048,
              pack2(D[8 * q], D[8 * q + 1]), pack2(D[8 * q + 2], D[8 * q + 3]), pack2(D[8 * q + 4], D[8 * q + 5]), pack2(D[8 * q + 6], D[8 * q + 7]));
      fence_async();
      __syncwarp();
      if (lane == 0) {
        asm volatile("cp.async.bulk.tensor.4d.global.shared::cta.bulk_group [%0, {%2,%3,%4,%5}], [%1];"
                     ::"l"(&mp.oo), "r"(sb + SM_B_IN + sg * 24576 + w * 6144), "r"(0), "r"(8 * b), "r"((par >> 1) * 112 + (rem - par * 14) * 8 + 2 * w), "r"((par & 1) * 3) : "memory");
        asm volatile("cp.async.bulk.commit_group;" ::: "memory");
      }
      __syncwarp();
      TRB(use * 3 + wg, 6);
    }
    if (lane == 0) asm volatile("cp.async.bulk.wait_group 0;" ::: "memory");
    TR2(132 + blockIdx.x, 2);
  }
}

typedef CUresult (*EncodeFn)(CUtensorMap*, CUtensorMapDataType, cuuint32_t, void*, const cuuint64_t*, const cuuint64_t*, const cuuint32_t*,
                             const cuuint32_t*, CUtensorMapInterleave, CUtensorMapSwizzle, CUtensorMapL2promotion, CUtensorMapFloatOOBfill);
static EncodeFn g_enc = nullptr;
static void make_map(CUtensorMap* m, const void* p, int rank, const cuuint64_t* dim, const cuuint64_t* str, const cuuint32_t* box, CUtensorMapSwizzle sw) {
  const cuuint32_t ones[5] = {1, 1, 1, 1, 1};
  g_enc(m, CU_TENSOR_MAP_DATA_TYPE_BFLOAT16, rank, (void*)p, dim, str, box, ones, CU_TENSOR_MAP_INTERLEAVE_NONE, sw,
        CU_TENSOR_MAP_L2_PROMOTION_L2_128B, CU_TENSOR_MAP_FLOAT_OOB_FILL_NONE);
}

extern "C" void kernel_launch(void* const* d_in, const int* in_sizes, int n_in, void* d_out, int out_size) {
  const __nv_bfloat16* x = (const __nv_bfloat16*)d_in[0];
  const __nv_bfloat16* wqkv = (const __nv_bfloat16*)d_in[1];
  const __nv_bfloat16* wo = (const __nv_bfloat16*)d_in[2];
  const __nv_bfloat16* rpb = (const __nv_bfloat16*)d_in[3];

  if (!g_enc) {
    void* fn = nullptr; cudaDriverEntryPointQueryResult qr;
    cudaGetDriverEntryPoint("cuTensorMapEncodeTiled", &fn, cudaEnableDefault, &qr);
    g_enc = (EncodeFn)fn;
    cudaFuncSetAttribute(na_attn_kernel, cudaFuncAttributeMaxDynamicSharedMemorySize, SM_A_TOTAL);
    cudaFuncSetAttribute(na_proj_kernel, cudaFuncAttributeMaxDynamicSharedMemorySize, SM_B_TOTAL);
  }
  Maps ma; MapsB mb;
  { cuuint64_t dim[4] = {64, 112, 224, 6}, str[3] = {(cuuint64_t)ROWB, 768, 128};
    cuuint32_t box[4] = {64, 4, 16, 3}, boxo[4] = {64, 8, 2, 3};
    make_map(&ma.xc, x, 4, dim, str, box, CU_TENSOR_MAP_SWIZZLE_128B);
    make_map(&mb.oo, d_out, 4, dim, str, boxo, CU_TENSOR_MAP_SWIZZLE_128B); }
  { cuuint64_t dim[5] = {64, 112, 224, 2, 6}, str[4] = {(cuuint64_t)ROWB, 768, 19 * 768, 128};
    cuuint32_t box[5] = {64, 8, 3, 2, 3};
    make_map(&ma.xh, x, 5, dim, str, box, CU_TENSOR_MAP_SWIZZLE_128B); }
  { cuuint64_t dim[3] = {384, 112, 224}, str[2] = {(cuuint64_t)ROWB, 768};
    cuuint32_t box[3] = {192, 8, 8}, boxs[3] = {192, 2, 16};
    make_map(&mb.oi, d_out, 3, dim, str, box, CU_TENSOR_MAP_SWIZZLE_NONE);
    make_map(&ma.os, d_out, 3, dim, str, boxs, CU_TENSOR_MAP_SWIZZLE_NONE); }
  { cuuint64_t dim[4] = {32, 112, 224, 12}, str[3] = {(cuuint64_t)ROWB, 768, 64};
    cuuint32_t box[4] = {32, 8, 2, 3};
    make_map(&ma.ot, d_out, 4, dim, str, box, CU_TENSOR_MAP_SWIZZLE_64B); }
  { cuuint64_t dim[2] = {576, 192}, str[1] = {1152};
    cuuint32_t box[2] = {16, 192};
    make_map(&ma.w, wqkv, 2, dim, str, box, CU_TENSOR_MAP_SWIZZLE_32B); }
  { cuuint64_t dim[3] = {32, 192, 6}, str[2] = {384, 64};
    cuuint32_t box[3] = {32, 192, 3};
    make_map(&ma.wo, wo, 3, dim, str, box, CU_TENSOR_MAP_SWIZZLE_64B);
    mb.wo = ma.wo; }
  na_attn_kernel<<<112, 512, SM_A_TOTAL>>>(x, wqkv, rpb, ma);
  cudaLaunchConfig_t cfg = {};
  cfg.gridDim = dim3(20); cfg.blockDim = dim3(480); cfg.dynamicSmemBytes = SM_B_TOTAL; cfg.stream = cudaStreamPerThread;
  cudaLaunchAttribute at[1];
  at[0].id = cudaLaunchAttributeProgrammaticStreamSerialization; at[0].val.programmaticStreamSerializationAllowed = 1;
  cfg.attrs = at; cfg.numAttrs = 1;
  cudaLaunchKernelEx(&cfg, na_proj_kernel, mb);
}
```

```cpp
#include <cuda_runtime.h>
#include <cuda_bf16.h>
#include <cuda.h>
#include <stdint.h>

#define SPIN_LIMIT (1u << 18)

__device__ __forceinline__ uint32_t smem_u32(const void* p) { return (uint32_t)__cvta_generic_to_shared(p); }
__device__ __forceinline__ void wg_fence() { asm volatile("wgmma.fence.sync.aligned;" ::: "memory"); }
__device__ __forceinline__ void wg_commit() { asm volatile("wgmma.commit_group.sync.aligned;" ::: "memory"); }
template <int N> __device__ __forceinline__ void wg_wait() { asm volatile("wgmma.wait_group.sync.aligned %0;" ::"n"(N) : "memory"); }
template <int N> __device__ __forceinline__ void pin(float (&d)[N]) {
#pragma unroll
  for (int i = 0; i < N; i++) asm volatile("" : "+f"(d[i])::"memory");
}
__host__ __device__ constexpr uint64_t mkdesc(uint32_t addr, uint32_t lbo, uint32_t sbo, uint32_t sw) {
  return (uint64_t)((addr & 0x3FFFF) >> 4) | ((uint64_t)(lbo >> 4) << 16) | ((uint64_t)(sbo >> 4) << 32) | ((uint64_t)sw << 62);
}
__device__ __forceinline__ void mbar_init(uint32_t bar, uint32_t cnt) { asm volatile("mbarrier.init.shared::cta.b64 [%0], %1;" ::"r"(bar), "r"(cnt) : "memory"); }
__device__ __forceinline__ void mbar_arrive(uint32_t bar) { asm volatile("mbarrier.arrive.shared::cta.b64 _, [%0];" ::"r"(bar) : "memory"); }
__device__ __forceinline__ bool elect_one() {
  uint32_t r; asm volatile("{\n.reg .pred p;\nelect.sync _|p, 0xffffffff;\nselp.u32 %0, 1, 0, p;\n}" : "=r"(r)); return r;
}
__device__ __forceinline__ void mbar_arrive_elect(uint32_t bar) {
  asm volatile("{\n.reg .pred p;\nelect.sync _|p, 0xffffffff;\n@p mbarrier.arrive.shared::cta.b64 _, [%0];\n}" ::"r"(bar) : "memory");
}
__device__ __forceinline__ void mbar_expect(uint32_t bar, uint32_t bytes) { asm volatile("mbarrier.arrive.expect_tx.shared::cta.b64 _, [%0], %1;" ::"r"(bar), "r"(bytes) : "memory"); }
__device__ __forceinline__ void mbar_arrive_remote(uint32_t bar, uint32_t cta) {
  asm volatile("{\n.reg .b32 ra;\nmapa.shared::cluster.u32 ra, %0, %1;\nmbarrier.arrive.relaxed.cluster.shared::cluster.b64 _, [ra];\n}" ::"r"(bar), "r"(cta) : "memory");
}
__device__ __forceinline__ void mbar_wait(uint32_t bar, uint32_t parity) {
  asm volatile("{\n.reg .pred p;\n.reg .b32 n;\nmov.b32 n, 0;\nWL:\nmbarrier.try_wait.parity.shared::cta.b64 p, [%0], %1;\n@p bra WD;\n"
               "add.u32 n, n, 1;\nsetp.lt.u32 p, n, 65536;\n@p bra WL;\nWD:\n}" ::"r"(bar), "r"(parity) : "memory");
}
__device__ __forceinline__ void nb_sync(int id, int n) { asm volatile("bar.sync %0, %1;" ::"r"(id), "r"(n) : "memory"); }
__device__ __forceinline__ void nb_arrive(int id, int n) { asm volatile("bar.arrive %0, %1;" ::"r"(id), "r"(n) : "memory"); }
__device__ __forceinline__ void fence_async() { asm volatile("fence.proxy.async.shared::cta;" ::: "memory"); }
__device__ __forceinline__ void cluster_sync() {
  asm volatile("barrier.cluster.arrive.relaxed.aligned;\nbarrier.cluster.wait.aligned;" ::: "memory");
}
__device__ __forceinline__ uint32_t pack2(float lo, float hi) {
  uint32_t r; asm("cvt.rn.bf16x2.f32 %0, %1, %2;" : "=r"(r) : "f"(hi), "f"(lo)); return r;
}
__device__ __forceinline__ void stsm4(uint32_t a, uint32_t r0, uint32_t r1, uint32_t r2, uint32_t r3) {
  asm volatile("stmatrix.sync.aligned.m8n8.x4.shared.b16 [%0], {%1,%2,%3,%4};" ::"r"(a), "r"(r0), "r"(r1), "r"(r2), "r"(r3) : "memory");
}
__device__ __forceinline__ void ldsm4(uint32_t a, uint32_t& r0, uint32_t& r1, uint32_t& r2, uint32_t& r3) {
  asm volatile("ldmatrix.sync.aligned.m8n8.x4.shared.b16 {%0,%1,%2,%3}, [%4];" : "=r"(r0), "=r"(r1), "=r"(r2), "=r"(r3) : "r"(a) : "memory");
}
__device__ __forceinline__ void sts128(uint32_t a, uint4 v) {
  asm volatile("st.shared.v4.b32 [%0], {%1,%2,%3,%4};" ::"r"(a), "r"(v.x), "r"(v.y), "r"(v.z), "r"(v.w) : "memory");
}
__device__ __forceinline__ float lds_f32(uint32_t a) { float v; asm volatile("ld.shared.f32 %0, [%1];" : "=f"(v) : "r"(a)); return v; }
__device__ __forceinline__ float ex2(float x) { float y; asm("ex2.approx.ftz.f32 %0, %1;" : "=f"(y) : "f"(x)); return y; }

template<int SC> __device__ __forceinline__ void wg_ss144(float (&d)[72], uint64_t da, uint64_t db) {
  asm volatile("{\n.reg .pred p;\nsetp.ne.b32 p, %74, 0;\nwgmma.mma_async.sync.aligned.m64n144k16.f32.bf16.bf16 {%0,%1,%2,%3,%4,%5,%6,%7,%8,%9,%10,%11,%12,%13,%14,%15,%16,%17,%18,%19,%20,%21,%22,%23,%24,%25,%26,%27,%28,%29,%30,%31,%32,%33,%34,%35,%36,%37,%38,%39,%40,%41,%42,%43,%44,%45,%46,%47,%48,%49,%50,%51,%52,%53,%54,%55,%56,%57,%58,%59,%60,%61,%62,%63,%64,%65,%66,%67,%68,%69,%70,%71}, %72, %73, p, 1, 1, 0, 1;\n}\n"
    : "+f"(d[0]),"+f"(d[1]),"+f"(d[2]),"+f"(d[3]),"+f"(d[4]),"+f"(d[5]),"+f"(d[6]),"+f"(d[7]),"+f"(d[8]),"+f"(d[9]),"+f"(d[10]),"+f"(d[11]),"+f"(d[12]),"+f"(d[13]),"+f"(d[14]),"+f"(d[15]),"+f"(d[16]),"+f"(d[17]),"+f"(d[18]),"+f"(d[19]),"+f"(d[20]),"+f"(d[21]),"+f"(d[22]),"+f"(d[23]),"+f"(d[24]),"+f"(d[25]),"+f"(d[26]),"+f"(d[27]),"+f"(d[28]),"+f"(d[29]),"+f"(d[30]),"+f"(d[31]),"+f"(d[32]),"+f"(d[33]),"+f"(d[34]),"+f"(d[35]),"+f"(d[36]),"+f"(d[37]),"+f"(d[38]),"+f"(d[39]),"+f"(d[40]),"+f"(d[41]),"+f"(d[42]),"+f"(d[43]),"+f"(d[44]),"+f"(d[45]),"+f"(d[46]),"+f"(d[47]),"+f"(d[48]),"+f"(d[49]),"+f"(d[50]),"+f"(d[51]),"+f"(d[52]),"+f"(d[53]),"+f"(d[54]),"+f"(d[55]),"+f"(d[56]),"+f"(d[57]),"+f"(d[58]),"+f"(d[59]),"+f"(d[60]),"+f"(d[61]),"+f"(d[62]),"+f"(d[63]),"+f"(d[64]),"+f"(d[65]),"+f"(d[66]),"+f"(d[67]),"+f"(d[68]),"+f"(d[69]),"+f"(d[70]),"+f"(d[71]) : "l"(da), "l"(db), "n"(SC));
}
template<int SC> __device__ __forceinline__ void wg_ss96(float (&d)[48], uint64_t da, uint64_t db) {
  asm volatile("{\n.reg .pred p;\nsetp.ne.b32 p, %50, 0;\nwgmma.mma_async.sync.aligned.m64n96k16.f32.bf16.bf16 {%0,%1,%2,%3,%4,%5,%6,%7,%8,%9,%10,%11,%12,%13,%14,%15,%16,%17,%18,%19,%20,%21,%22,%23,%24,%25,%26,%27,%28,%29,%30,%31,%32,%33,%34,%35,%36,%37,%38,%39,%40,%41,%42,%43,%44,%45,%46,%47}, %48, %49, p, 1, 1, 0, 1;\n}\n"
    : "+f"(d[0]),"+f"(d[1]),"+f"(d[2]),"+f"(d[3]),"+f"(d[4]),"+f"(d[5]),"+f"(d[6]),"+f"(d[7]),"+f"(d[8]),"+f"(d[9]),"+f"(d[10]),"+f"(d[11]),"+f"(d[12]),"+f"(d[13]),"+f"(d[14]),"+f"(d[15]),"+f"(d[16]),"+f"(d[17]),"+f"(d[18]),"+f"(d[19]),"+f"(d[20]),"+f"(d[21]),"+f"(d[22]),"+f"(d[23]),"+f"(d[24]),"+f"(d[25]),"+f"(d[26]),"+f"(d[27]),"+f"(d[28]),"+f"(d[29]),"+f"(d[30]),"+f"(d[31]),"+f"(d[32]),"+f"(d[33]),"+f"(d[34]),"+f"(d[35]),"+f"(d[36]),"+f"(d[37]),"+f"(d[38]),"+f"(d[39]),"+f"(d[40]),"+f"(d[41]),"+f"(d[42]),"+f"(d[43]),"+f"(d[44]),"+f"(d[45]),"+f"(d[46]),"+f"(d[47]) : "l"(da), "l"(db), "n"(SC));
}
template<int SC> __device__ __forceinline__ void wg_rs112(float (&d)[56], uint32_t a0, uint32_t a1, uint32_t a2, uint32_t a3, uint64_t db) {
  asm volatile("{\n.reg .pred p;\nsetp.ne.b32 p, %61, 0;\nwgmma.mma_async.sync.aligned.m64n112k16.f32.bf16.bf16 {%0,%1,%2,%3,%4,%5,%6,%7,%8,%9,%10,%11,%12,%13,%14,%15,%16,%17,%18,%19,%20,%21,%22,%23,%24,%25,%26,%27,%28,%29,%30,%31,%32,%33,%34,%35,%36,%37,%38,%39,%40,%41,%42,%43,%44,%45,%46,%47,%48,%49,%50,%51,%52,%53,%54,%55}, {%56,%57,%58,%59}, %60, p, 1, 1, 0;\n}\n"
    : "+f"(d[0]),"+f"(d[1]),"+f"(d[2]),"+f"(d[3]),"+f"(d[4]),"+f"(d[5]),"+f"(d[6]),"+f"(d[7]),"+f"(d[8]),"+f"(d[9]),"+f"(d[10]),"+f"(d[11]),"+f"(d[12]),"+f"(d[13]),"+f"(d[14]),"+f"(d[15]),"+f"(d[16]),"+f"(d[17]),"+f"(d[18]),"+f"(d[19]),"+f"(d[20]),"+f"(d[21]),"+f"(d[22]),"+f"(d[23]),"+f"(d[24]),"+f"(d[25]),"+f"(d[26]),"+f"(d[27]),"+f"(d[28]),"+f"(d[29]),"+f"(d[30]),"+f"(d[31]),"+f"(d[32]),"+f"(d[33]),"+f"(d[34]),"+f"(d[35]),"+f"(d[36]),"+f"(d[37]),"+f"(d[38]),"+f"(d[39]),"+f"(d[40]),"+f"(d[41]),"+f"(d[42]),"+f"(d[43]),"+f"(d[44]),"+f"(d[45]),"+f"(d[46]),"+f"(d[47]),"+f"(d[48]),"+f"(d[49]),"+f"(d[50]),"+f"(d[51]),"+f"(d[52]),"+f"(d[53]),"+f"(d[54]),"+f"(d[55]) : "r"(a0), "r"(a1), "r"(a2), "r"(a3), "l"(db), "n"(SC));
}
template<int SC> __device__ __forceinline__ void wg_sp48(float (&d)[24], uint32_t a0, uint32_t a1, uint32_t a2, uint32_t a3, uint64_t db, uint32_t meta) {
  asm volatile("{\n.reg .pred p;\nsetp.ne.b32 p, %30, 0;\nwgmma.mma_async.sp.sync.aligned.m64n48k32.f32.bf16.bf16 {%0,%1,%2,%3,%4,%5,%6,%7,%8,%9,%10,%11,%12,%13,%14,%15,%16,%17,%18,%19,%20,%21,%22,%23}, {%24,%25,%26,%27}, %28, %29, 0, p, 1, 1, 1;\n}\n"
    : "+f"(d[0]),"+f"(d[1]),"+f"(d[2]),"+f"(d[3]),"+f"(d[4]),"+f"(d[5]),"+f"(d[6]),"+f"(d[7]),"+f"(d[8]),"+f"(d[9]),"+f"(d[10]),"+f"(d[11]),"+f"(d[12]),"+f"(d[13]),"+f"(d[14]),"+f"(d[15]),"+f"(d[16]),"+f"(d[17]),"+f"(d[18]),"+f"(d[19]),"+f"(d[20]),"+f"(d[21]),"+f"(d[22]),"+f"(d[23]) : "r"(a0), "r"(a1), "r"(a2), "r"(a3), "l"(db), "r"(meta), "n"(SC));
}
template<int SC> __device__ __forceinline__ void wg_ss192(float (&d)[96], uint64_t da, uint64_t db) {
  asm volatile("{\n.reg .pred p;\nsetp.ne.b32 p, %98, 0;\nwgmma.mma_async.sync.aligned.m64n192k16.f32.bf16.bf16 {%0,%1,%2,%3,%4,%5,%6,%7,%8,%9,%10,%11,%12,%13,%14,%15,%16,%17,%18,%19,%20,%21,%22,%23,%24,%25,%26,%27,%28,%29,%30,%31,%32,%33,%34,%35,%36,%37,%38,%39,%40,%41,%42,%43,%44,%45,%46,%47,%48,%49,%50,%51,%52,%53,%54,%55,%56,%57,%58,%59,%60,%61,%62,%63,%64,%65,%66,%67,%68,%69,%70,%71,%72,%73,%74,%75,%76,%77,%78,%79,%80,%81,%82,%83,%84,%85,%86,%87,%88,%89,%90,%91,%92,%93,%94,%95}, %96, %97, p, 1, 1, 0, 1;\n}\n"
    : "+f"(d[0]),"+f"(d[1]),"+f"(d[2]),"+f"(d[3]),"+f"(d[4]),"+f"(d[5]),"+f"(d[6]),"+f"(d[7]),"+f"(d[8]),"+f"(d[9]),"+f"(d[10]),"+f"(d[11]),"+f"(d[12]),"+f"(d[13]),"+f"(d[14]),"+f"(d[15]),"+f"(d[16]),"+f"(d[17]),"+f"(d[18]),"+f"(d[19]),"+f"(d[20]),"+f"(d[21]),"+f"(d[22]),"+f"(d[23]),"+f"(d[24]),"+f"(d[25]),"+f"(d[26]),"+f"(d[27]),"+f"(d[28]),"+f"(d[29]),"+f"(d[30]),"+f"(d[31]),"+f"(d[32]),"+f"(d[33]),"+f"(d[34]),"+f"(d[35]),"+f"(d[36]),"+f"(d[37]),"+f"(d[38]),"+f"(d[39]),"+f"(d[40]),"+f"(d[41]),"+f"(d[42]),"+f"(d[43]),"+f"(d[44]),"+f"(d[45]),"+f"(d[46]),"+f"(d[47]),"+f"(d[48]),"+f"(d[49]),"+f"(d[50]),"+f"(d[51]),"+f"(d[52]),"+f"(d[53]),"+f"(d[54]),"+f"(d[55]),"+f"(d[56]),"+f"(d[57]),"+f"(d[58]),"+f"(d[59]),"+f"(d[60]),"+f"(d[61]),"+f"(d[62]),"+f"(d[63]),"+f"(d[64]),"+f"(d[65]),"+f"(d[66]),"+f"(d[67]),"+f"(d[68]),"+f"(d[69]),"+f"(d[70]),"+f"(d[71]),"+f"(d[72]),"+f"(d[73]),"+f"(d[74]),"+f"(d[75]),"+f"(d[76]),"+f"(d[77]),"+f"(d[78]),"+f"(d[79]),"+f"(d[80]),"+f"(d[81]),"+f"(d[82]),"+f"(d[83]),"+f"(d[84]),"+f"(d[85]),"+f"(d[86]),"+f"(d[87]),"+f"(d[88]),"+f"(d[89]),"+f"(d[90]),"+f"(d[91]),"+f"(d[92]),"+f"(d[93]),"+f"(d[94]),"+f"(d[95]) : "l"(da), "l"(db), "n"(SC));
}

constexpr uint32_t SBC = 1024;
constexpr int ROWB = 2 * 224 * 384;
constexpr int TB = 11;
constexpr int KS = 832;
constexpr int KSLOT = 22 * KS;
constexpr int SM_X1 = 0;
constexpr int SM_X2 = SM_X1 + 24576;
constexpr int SM_X0 = SM_X2 + 24576;
constexpr int SM_W = SM_X0 + 18432;
constexpr int SM_K = SM_W + 55296;
constexpr int SM_V = SM_K + 2 * KSLOT;
constexpr int SM_Q = SM_V + 22 * 1536;
constexpr int SM_O = SM_Q + 24576;
constexpr int SM_RPB = SM_O + 12288;
constexpr int SM_BAR = SM_RPB + 768;
constexpr int SM_A_TOTAL = SM_BAR + 256;
constexpr int SM_TWO = SM_X0 + 24576;
constexpr int SM_TST = SM_TWO + 36864;
enum { B_FULL = 0, B_EMPTY = 3, B_TIN = 6, B_TFREE = 9, B_WK = 11, B_WQ, B_WO, B_Q0, B_OTAIL, B_ODONE = B_OTAIL + 2, B_KFREE, B_VFREE, B_COUNT };
enum { N_KRDY = 4, N_QK0, N_QK1, N_VQ0, N_VQ1, N_PVISS };

#define NL 2
#define OPT 0
#define SPL 4
#define RA 152
#define RG 184
__device__ int g_flags[TB * 56];

#define TR(role, it, k)
#define TRDECL
#define TRARG
#define TRPASS
#define TRDUMP
#define TRB(it, k)
#define TR2(blk, k)

struct GemmCtx {
  uint32_t bar;
  uint32_t kC, vC[2], qC[2];
  uint32_t kH, vH[2];
  uint32_t spin;
  bool hvalid, never;
};

template <int STRIDE> __device__ __forceinline__ void dump12(uint32_t a, const uint32_t (&r)[12]) {
#pragma unroll
  for (int j = 0; j < 3; j++) stsm4(a + j * 2 * STRIDE, r[4 * j], r[4 * j + 1], r[4 * j + 2], r[4 * j + 3]);
}
__device__ __forceinline__ void keep12(bool never, uint32_t a, const uint32_t (&r)[12]) { if (never) dump12<128>(a, r); }
template <int N> __device__ __forceinline__ void pack12(uint32_t (&r)[12], const float (&d)[N], int off) {
#pragma unroll
  for (int j = 0; j < 12; j++) r[j] = pack2(d[off + 2 * j], d[off + 2 * j + 1]);
}
template <int XS, int K0, int K1> __device__ __forceinline__ void issue_core(float (&d)[72]) {
  constexpr uint64_t da = mkdesc(SBC + XS, 16, 1024, 1), db = mkdesc(SBC + SM_W, 6144, 256, 3);
  wg_fence();
  if (K0 == 0) wg_ss144<0>(d, da, db);
#pragma unroll
  for (int k = K0 ? K0 : 1; k < K1; k++) wg_ss144<1>(d, da + (k >> 2) * 512 + (k & 3) * 2, db + k * 32);
  wg_commit();
}
template <int K0, int K1> __device__ __forceinline__ void issue_halo(float (&d)[48]) {
  constexpr uint64_t da = mkdesc(SBC + SM_X0 - 2048, 16, 1024, 1), db = mkdesc(SBC + SM_W, 6144, 256, 3);
  wg_fence();
  if (K0 == 0) wg_ss96<0>(d, da, db);
#pragma unroll
  for (int k = K0 ? K0 : 1; k < K1; k++) wg_ss96<1>(d, da + (k >> 2) * 384 + (k & 3) * 2, db + k * 32);
  wg_commit();
}
template <int ST> __device__ __forceinline__ void release_stage(const GemmCtx& c) {
  asm volatile("{\n.reg .pred p;\n.reg .b32 ra;\nelect.sync _|p, 0xffffffff;\nmapa.shared::cluster.u32 ra, %0, %1;\n"
               "@p mbarrier.arrive.shared::cluster.b64 _, [ra];\n}" ::"r"(c.bar + (B_EMPTY + ST) * 8), "n"(ST) : "memory");
}
template <int PARITY> __device__ __forceinline__ void gwait(GemmCtx& c, int bar) {
  asm volatile("{\n.reg .pred p;\nWL:\nmbarrier.try_wait.parity.shared::cta.b64 p, [%1], %2;\n@p bra WD;\n"
               "add.u32 %0, %0, 1;\nsetp.lt.u32 p, %0, 0x100000;\n@p bra WL;\nWD:\n}" : "+r"(c.spin) : "r"(c.bar + bar * 8), "n"(PARITY) : "memory");
}
__device__ __forceinline__ void load_w(const CUtensorMap* m, uint32_t dst, uint32_t bar, int col) {
  asm volatile("cp.async.bulk.tensor.2d.shared::cluster.global.mbarrier::complete_tx::bytes [%0], [%1, {%3,%4}], [%2];"
               ::"r"(dst), "l"(m), "r"(bar), "r"(col), "r"(0) : "memory");
}
template <int BYTES> __device__ __forceinline__ void send_o(uint32_t dst, uint32_t src, uint32_t bar, int cta) {
  asm volatile("{\n.reg .b32 rd, rb;\nmapa.shared::cluster.u32 rd, %0, %3;\nmapa.shared::cluster.u32 rb, %2, %3;\n"
               "cp.async.bulk.shared::cluster.shared::cta.mbarrier::complete_tx::bytes [rd], [%1], %4, [rb];\n}"
               ::"r"(dst), "r"(src), "r"(bar), "r"(cta), "n"(BYTES) : "memory");
}
__device__ __forceinline__ void tail_free(uint32_t bar) {
  uint32_t ln; asm volatile("mov.u32 %0, %%laneid;" : "=r"(ln));
  if (ln < 4) mbar_arrive_remote(bar, ln);
}
__device__ __forceinline__ void publish(uint32_t bar) {
  fence_async();
  __syncwarp();
  mbar_arrive_elect(bar);
}

template <bool FIRST, bool LAST, int PA>
__device__ __forceinline__ void gemm_iter(GemmCtx& c, int b, uint32_t (&pk)[12], uint32_t (&pv)[12], uint32_t (&pq)[12], const CUtensorMap* mwo TRARG) {
  const uint32_t bar = c.bar;
  const bool w = !FIRST && (PA == 0 || b >= 0), never = c.never;
  constexpr uint32_t ko = PA * KSLOT;
  float H[48], C[72];
  uint32_t hk[12], hv[12], pv2[12];
  TR(2, b, 0);
  if (FIRST) gwait<PA>(c, B_FULL + 0);
  if (!FIRST) dump12<256>(c.qC[1] + (PA ^ 1) * 128, pq);
  if (w) nb_sync(N_QK1, 256);
  TR(2, b, 2);
  if (FIRST) TR(2, b - 1, 6);
  issue_halo<0, 8>(H);
  TR(2, b, 3);
  if (!FIRST) {
    if (w) gwait<PA>(c, B_KFREE);
    dump12<128>(c.kC + ko, pk);
  }
  issue_halo<8, 12>(H);
  TR(2, b, 4);
  if (!LAST) {
    gwait<PA>(c, B_FULL + 2);
    if (FIRST && NL == 2) gwait<0>(c, B_WQ);
    TR(2, b, 13);
    if (FIRST) TR(2, b - 1, 7);
    issue_core<SM_X2, 0, 8>(C);
    TR(2, b, 5);
    if (!FIRST) { fence_async(); keep12(never, c.kC, pk); }
    wg_wait<1>(); pin(H);
    release_stage<0>(c);
  } else {
    fence_async();
    nb_arrive(N_VQ0, 288); nb_arrive(N_VQ1, 288); nb_arrive(N_PVISS, 384);
    wg_wait<0>(); pin(H);
    tail_free(bar + (B_TFREE + 1) * 8);
    nb_sync(2, 128);
    if (!c.hvalid && elect_one()) {
      mbar_expect(bar + B_WO * 8, 36864);
      asm volatile("cp.async.bulk.tensor.3d.shared::cluster.global.mbarrier::complete_tx::bytes [%0], [%1, {%3,%4,%5}], [%2];"
                   ::"r"(bar - SM_BAR + SM_TWO), "l"(mwo), "r"(bar + B_WO * 8), "r"(0), "r"(0), "r"((blockIdx.x & 1) * 3) : "memory");
    }
    __syncwarp();
  }
  pack12(hk, H, 0);
  if (c.hvalid) dump12<128>(c.kH + ko, hk);
  pack12(hv, H, 24);
  if (!LAST) {
    issue_core<SM_X2, 8, 12>(C);
    if (w) { nb_arrive(N_VQ0, 288); nb_arrive(N_VQ1, 288); }
    else if (!FIRST) { __syncwarp(); mbar_arrive_elect(bar + B_Q0 * 8); }
    gwait<PA>(c, B_FULL + 1);
    keep12(never, c.kC, hk);
    TR(2, b, 6);
    wg_wait<0>(); pin(C);
    TR(2, b, 7);
    pack12(pk, C, 0);
    dump12<128>(c.kC + ko + 64, pk);
    release_stage<2>(c);
    pack12(pv2, C, 24);
    pack12(pq, C, 48);
    TR(2, b, 8);
    issue_core<SM_X1, 0, SPL>(C);
    if (w) nb_sync(N_PVISS, 384);
    issue_core<SM_X1, SPL, 8>(C);
    TR(2, b, 9);
  }
  if (!FIRST) fence_async();
  if (!LAST) keep12(never, c.kC, pk);
  TR(2, b, 14);
  if (!LAST) issue_core<SM_X1, 8, 12>(C);
  if (!FIRST) nb_arrive(N_KRDY, 256);
  TR(2, b, 1);
  if (PA && b == 11) tail_free(bar + B_TFREE * 8);
  if (!LAST) gwait<PA ^ 1>(c, B_FULL + 0);
  if (w) gwait<PA>(c, B_VFREE);
  TR(2, b, 10);
  if (!FIRST) dump12<128>(c.vC[PA], pv);
  if (!LAST) dump12<256>(c.qC[0] + PA * 128, pq);
  if (c.hvalid) dump12<128>(c.vH[PA], hv);
  if (LAST) { fence_async(); nb_arrive(N_VQ0, 288); nb_arrive(N_VQ1, 288); nb_arrive(N_QK1, 256); return; }
  dump12<128>(c.vC[PA ^ 1] + 768, pv2);
  TR(2, b, 11);
  wg_wait<0>(); pin(C);
  TR(2, b, 12);
  release_stage<1>(c);
  pack12(pk, C, 0);
  pack12(pv, C, 24);
  pack12(pq, C, 48);
}

template <int IN> __device__ __forceinline__ void issue_proj(float (&D)[48]) {
  constexpr uint64_t da = mkdesc(SBC + IN, 128, 768, 0), db = mkdesc(SBC + SM_TWO, 12288, 512, 2);
  wg_fence();
  wg_ss96<0>(D, da, db);
#pragma unroll
  for (int k = 1; k < 12; k++) wg_ss96<1>(D, da + (k / 3) * 384 + (k % 3) * 16, db + k * 64);
  wg_commit();
}
__device__ __forceinline__ void store_proj(const float (&D)[48], const CUtensorMap* m, uint32_t st, uint32_t sta, int row, int col, int ch) {
#pragma unroll
  for (int q = 0; q < 6; q++)
    stsm4((sta ^ ((q & 1) * 32)) + (q >> 1) * 1024,
          pack2(D[8 * q], D[8 * q + 1]), pack2(D[8 * q + 2], D[8 * q + 3]), pack2(D[8 * q + 4], D[8 * q + 5]), pack2(D[8 * q + 6], D[8 * q + 7]));
  fence_async();
  __syncwarp();
  if ((threadIdx.x & 31) == 0) {
    asm volatile("cp.async.bulk.tensor.4d.global.shared::cta.bulk_group [%0, {%2,%3,%4,%5}], [%1];" ::"l"(m), "r"(st), "r"(0), "r"(row), "r"(col), "r"(ch) : "memory");
    asm volatile("cp.async.bulk.commit_group;" ::: "memory");
  }
  __syncwarp();
}

__device__ __forceinline__ float fold(float a, float b, float t, int useb) {
  float r;
  asm("{\n.reg .pred p;\nsetp.ne.b32 p, %4, 0;\nfma.rn.f32 %0, %1, 0f3E553B95, %3;\n@p fma.rn.f32 %0, %2, 0f3E553B95, %3;\n}"
      : "=&f"(r) : "f"(a), "f"(b), "f"(t), "r"(useb));
  return r;
}
template <int U, int L>
__device__ __forceinline__ void softmax_tile(const float (&SA)[56], const float (&SB)[56], const float (&T)[16], int b0, int b1,
                                             uint32_t (&P)[28], float (&sx)[8]) {
  float lu[14], ll[14];
#pragma unroll
  for (int j = 0; j < 7; j++) {
    constexpr int sh = U == L ? 2 : 0;
    const float tu0 = T[2 * j + sh], tu1 = T[2 * j + 1 + sh], tl0 = T[2 * j], tl1 = T[2 * j + 1];
    lu[2 * j]     = fold(SA[4 * (U + j)],     SB[4 * (U + j)],     tu0, b0);
    ll[2 * j]     = fold(SA[4 * (L + j) + 2], SB[4 * (L + j) + 2], tl0, b0);
    lu[2 * j + 1] = fold(SA[4 * (U + j) + 1], SB[4 * (U + j) + 1], tu1, b1);
    ll[2 * j + 1] = fold(SA[4 * (L + j) + 3], SB[4 * (L + j) + 3], tl1, b1);
  }
  float mu = lu[0], ml = ll[0], mu2 = lu[1], ml2 = ll[1];
#pragma unroll
  for (int j = 1; j < 7; j++) { mu = fmaxf(mu, lu[2 * j]); mu2 = fmaxf(mu2, lu[2 * j + 1]); ml = fmaxf(ml, ll[2 * j]); ml2 = fmaxf(ml2, ll[2 * j + 1]); }
  mu = fmaxf(mu, mu2); ml = fmaxf(ml, ml2);
  { const float a1 = __shfl_xor_sync(0xffffffffu, mu, 1), a2 = __shfl_xor_sync(0xffffffffu, mu, 2), a3 = __shfl_xor_sync(0xffffffffu, mu, 3);
    const float c1 = __shfl_xor_sync(0xffffffffu, ml, 1), c2 = __shfl_xor_sync(0xffffffffu, ml, 2), c3 = __shfl_xor_sync(0xffffffffu, ml, 3);
    mu = fmaxf(fmaxf(mu, a1), fmaxf(a2, a3)); ml = fmaxf(fmaxf(ml, c1), fmaxf(c2, c3)); }
  float su = 0.f, sl = 0.f;
#pragma unroll
  for (int c = 0; c < 14; c++) {
    const int iu = (c >> 1) * 4 + (c & 1) * 2;
    if (c >= U && c < U + 7) {
      float e0 = ex2(lu[2 * (c - U)] - mu), e1 = ex2(lu[2 * (c - U) + 1] - mu);
      su = c == U ? e0 + e1 : (su + e0) + e1; P[iu] = pack2(e0, e1);
    } else P[iu] = 0u;
    if (c >= L && c < L + 7) {
      float e0 = ex2(ll[2 * (c - L)] - ml), e1 = ex2(ll[2 * (c - L) + 1] - ml);
      sl = c == L ? e0 + e1 : (sl + e0) + e1; P[iu + 1] = pack2(e0, e1);
    } else P[iu + 1] = 0u;
  }
  sx[0] = su; sx[4] = sl;
#pragma unroll
  for (int k = 1; k < 4; k++) { sx[k] = __shfl_xor_sync(0xffffffffu, su, k); sx[4 + k] = __shfl_xor_sync(0xffffffffu, sl, k); }
}

struct Maps { CUtensorMap xc, xh, w, os, wo, ot; };

__global__ void __cluster_dims__(4, 1, 1) __launch_bounds__(512, 1)
na_attn_kernel(const __nv_bfloat16* __restrict__ x, const __nv_bfloat16* __restrict__ wqkv, const __nv_bfloat16* __restrict__ rpb, const __grid_constant__ Maps mp) {
  extern __shared__ __align__(1024) uint8_t smem_raw[];
  const uint32_t sb = smem_u32(smem_raw);
  if ((sb & 0x3FFFF) != SBC) return;
  const uint32_t bar = sb + SM_BAR;
  TR2(blockIdx.x, 0);
  const int tid = threadIdx.x, lane = tid & 31;
  const int warp = __shfl_sync(0xffffffffu, tid >> 5, 0);
  const int head = blockIdx.x & 3, cl = blockIdx.x >> 2;
  const int par = cl / 7, strip = cl - par * 7, ph = par >> 1, pw = par & 1;

  uint4 wv[2 * NL];
  const int va = head == 1;
  const uint32_t wdst = sb + SM_W + (va + ((tid >> 1) & 1)) * 6144 + (tid >> 2) * 32 + ((tid ^ (tid >> 4)) & 1) * 16;
  if (warp < 12) asm volatile("barrier.cluster.arrive.relaxed.aligned;" ::: "memory");
  {
    const uint32_t wo0 = (tid >> 2) * 1152 + head * 96 + va * 32 + (tid & 3) * 16;
#pragma unroll
    for (int i = 0; i < 2 * NL; i++)
      asm volatile("{\n.reg .pred p;\nsetp.lt.u32 p, %5, 384;\n@p ld.global.nc.v4.b32 {%0,%1,%2,%3}, [%4];\n}"
                   : "=r"(wv[i].x), "=r"(wv[i].y), "=r"(wv[i].z), "=r"(wv[i].w)
                   : "l"(reinterpret_cast<const uint8_t*>(wqkv) + wo0 + (i & 1) * 96 * 1152 + ((i / 2 + 1) % 3) * 384), "r"(tid));
  }
  if (warp < 8) {
    asm volatile("setmaxnreg.inc.sync.aligned.u32 %0;" ::"n"(RA));
    float rv = -INFINITY;
    if (tid < 169) rv = __bfloat162float(rpb[head * 169 + tid]) * 1.4426950408889634f;
    if (tid < 192) {
      const int kc = (tid & 15) + 3, wc = (tid >> 4) % 6;
      sts128(tid < 96 ? sb + SM_K + kc * KS + wc * 128 + 48 : sb + SM_V + kc * 1536 + wc * 128 + (6 + (kc & 1)) * 16, make_uint4(0, 0, 0, 0));
    }
#pragma unroll
    for (int i = 0; i < 2 * NL; i++) sts128(wdst + (i & 1) * 3072 + (i / 2) * 18432, wv[i]);
    fence_async();
    asm volatile("bar.arrive 1, 384;" ::: "memory");
    if (tid < 182) asm volatile("st.shared.f32 [%0], %1;" ::"r"(sb + SM_RPB + tid * 4), "f"(rv) : "memory");
    const int j = warp >> 2, w = warp & 3;
    int variant = w;
    if (strip == 0 && j == 0 && w < 2) variant = 4;
    if (strip == 6 && j == 1 && w >= 2) variant = 5;
    const uint32_t qa = sb + SM_Q + (8 * j + 2 * w + ((lane >> 3) & 1)) * 1536 + (lane >> 4) * 256 + (((lane & 7) * 16) ^ (((lane >> 3) & 1) * 64));
    uint32_t oa = sb + SM_O + j * 6144 + (2 * w + ((lane >> 3) & 1)) * 768 + (lane >> 4) * 128 + (lane & 7) * 16;
    const uint64_t dK = mkdesc(SBC + SM_K, 128, KS, 0) + j * (8 * KS / 16);
    const uint64_t dV = mkdesc(SBC + SM_V, 768, 128, 0) + j * (8 * 1536 / 16);
    asm volatile("barrier.cluster.wait.aligned;" ::: "memory");
    asm volatile("bar.sync 3, 256;" ::: "memory");
    float T[16];
    TRDECL;
    int b0 = 0, b1 = 0;
    uint32_t meta = 0, ob = bar + B_ODONE * 8;
    uint32_t q[12];
    mbar_wait(bar + B_Q0 * 8, 0);
#pragma unroll
    for (int k = 0; k < 3; k++) ldsm4(qa + k * 512, q[4 * k], q[4 * k + 1], q[4 * k + 2], q[4 * k + 3]);
#pragma unroll 1
    for (int b = 0; b < 14; b++) {
      const uint32_t pa = b & 1;
      float SA[56], SB[56];
      const uint64_t dA = dK + pa * (KSLOT >> 4), dB = dK + (pa ^ 1) * (KSLOT >> 4);
      TR(0, b, 0);
      nb_sync(N_KRDY + j, 256);
      TR(0, b, 1);
      TR(0, b - 1, 9);
      wg_fence();
      wg_rs112<0>(SA, q[0], q[1], q[2], q[3], dA);
      wg_rs112<0>(SB, q[0], q[1], q[2], q[3], dB);
      wg_rs112<1>(SA, q[4], q[5], q[6], q[7], dA + 16);
      wg_rs112<1>(SB, q[4], q[5], q[6], q[7], dB + 16);
      wg_rs112<1>(SA, q[8], q[9], q[10], q[11], dA + 32);
      wg_rs112<1>(SB, q[8], q[9], q[10], q[11], dB + 32);
      wg_commit();
      nb_arrive(N_QK0 + j, 256);
      TR(0, b, 2);
      if (b <= 1 || b == 13) {
        uint32_t ln; asm volatile("mov.u32 %0, %%laneid;" : "=r"(ln));
        const int g = ln >> 2, t = ln & 3;
        const int sw = b == 0 ? max(g + 1, 4) : (b == 13 ? min(g + 1, 5) : g + 1);
        const int i0 = 2 * t, i1 = 2 * t + 1;
        b0 = i0 <= sw - 2; b1 = i1 <= sw - 2;
        const uint32_t tb = sb + SM_RPB + (variant < 4 ? 3 : variant + 1 - 2 * w) * 4;
        const uint32_t ra0 = tb + (i0 == sw - 1 ? 13 : i0 + 8 * b0 - g + 2) * 52;
        const uint32_t ra1 = tb + (i1 == sw - 1 ? 13 : i1 + 8 * b1 - g + 2) * 52;
#pragma unroll
        for (int jj = 0; jj < 8; jj++) { T[2 * jj] = lds_f32(ra0 + jj * 4); T[2 * jj + 1] = lds_f32(ra1 + jj * 4); }
        meta = ((0x5555u & ((1u << (2 * (sw - 1))) - 1)) ^ 0xDD88u ^ (((t ^ b) & 1) ? 0x5555u : 0u)) * 0x10001u;
      } else meta ^= 0x55555555u;
      if (b == TB) ob = bar + (B_OTAIL + j) * 8;
      if (b >= 12) oa += b == 12 ? warp * 1536 - (SM_O - SM_Q) : 1536;
      wg_wait<0>(); pin(SA); pin(SB);
      mbar_arrive_elect(bar + B_KFREE * 8);
      TR(0, b, 3);
      TR(0, b - 1, 10);
      uint32_t P[28];
      float sx[8];
      switch (variant) {
        case 0: softmax_tile<0, 1>(SA, SB, T, b0, b1, P, sx); break;
        case 1: softmax_tile<2, 3>(SA, SB, T, b0, b1, P, sx); break;
        case 2: softmax_tile<4, 5>(SA, SB, T, b0, b1, P, sx); break;
        case 3: softmax_tile<6, 7>(SA, SB, T, b0, b1, P, sx); break;
        case 4: softmax_tile<3, 3>(SA, SB, T, b0, b1, P, sx); break;
        default: softmax_tile<4, 4>(SA, SB, T, b0, b1, P, sx); break;
      }
      float O[24];
      TR(0, b, 4);
      nb_sync(N_VQ0 + j, 288);
      TR(0, b, 5);
#pragma unroll
      for (int k = 0; k < 3; k++) ldsm4(qa + (pa ^ 1) * 128 + k * 512, q[4 * k], q[4 * k + 1], q[4 * k + 2], q[4 * k + 3]);
      wg_fence();
      wg_sp48<0>(O, P[0], P[1], P[2], P[3], dV, meta);
#pragma unroll
      for (int s = 1; s < 7; s++) wg_sp48<1>(O, P[4 * s], P[4 * s + 1], P[4 * s + 2], P[4 * s + 3], dV + s * 192, meta);
      wg_commit();
      nb_arrive(N_PVISS, 384);
      TR(0, b, 6);
      wg_wait<0>(); pin(O);
      mbar_arrive_elect(bar + B_VFREE * 8);
      TR(0, b, 7);
      float ru, rl;
      asm("rcp.approx.ftz.f32 %0, %1;" : "=f"(ru) : "f"(((fmaf(O[0], 0.f, sx[0]) + sx[1]) + sx[2]) + sx[3]));
      asm("rcp.approx.ftz.f32 %0, %1;" : "=f"(rl) : "f"(((fmaf(O[2], 0.f, sx[4]) + sx[5]) + sx[6]) + sx[7]));
#pragma unroll
      for (int i = 0; i < 3; i++)
        stsm4(oa + i * 256, pack2(O[8 * i] * ru, O[8 * i + 1] * ru), pack2(O[8 * i + 2] * rl, O[8 * i + 3] * rl),
              pack2(O[8 * i + 4] * ru, O[8 * i + 5] * ru), pack2(O[8 * i + 6] * rl, O[8 * i + 7] * rl));
      publish(ob);
      TR(0, b, 8);
    }
    if (elect_one()) {
#pragma unroll
      for (int d = 0; d < 2; d++)
        send_o<1536>(sb + SM_X0 + head * 6144 + (2 * j + (w & 1)) * 1536, sb + SM_Q + warp * 3072 + 1536, bar + (B_TIN + 2) * 8, (w & 2) + (d ^ (head & 1)));
    }
    __syncwarp();
    TRDUMP;
    cluster_sync();
  } else if (warp < 12) {
    TRDECL;
    TR(2, -3, 0);
    asm volatile("setmaxnreg.inc.sync.aligned.u32 %0;" ::"n"(RG));
    TR(2, -3, 1);
    GemmCtx c;
    c.bar = bar;
    const int gw = warp - 8, tk = gw * 16 + (lane & 15), hi = lane >> 4;
    { const int col = tk >> 2, i = tk & 3;
      c.kC = sb + SM_K + (col + 3) * KS + hi * 128 + i * 16;
      c.vC[0] = sb + SM_V + (col + 3) * 1536 + hi * 128 + (2 * i + ((col + 3) & 1)) * 16;
      c.qC[0] = sb + SM_Q + col * 1536 + hi * 256 + (col & 1) * 64 + i * 16; }
    { const int ci = (tk >> 3) - 2, kc = ci < 3 ? ci : ci + 16, i = tk & 7; c.hvalid = gw > 0;
      c.kH = sb + SM_K + kc * KS + hi * 128 + i * 16;
      c.vH[0] = sb + SM_V + kc * 1536 + hi * 128 + (i >> 2) * 768 + (2 * (i & 3) + ((kc ^ (i >> 2)) & 1)) * 16; }
    c.never = x == nullptr;
    c.kC = __shfl_sync(0xffffffffu, c.kC, lane); c.kH = __shfl_sync(0xffffffffu, c.kH, lane);
    c.vC[1] = __shfl_sync(0xffffffffu, c.vC[0] ^ 16, lane); c.vC[0] = __shfl_sync(0xffffffffu, c.vC[0], lane);
    c.vH[1] = __shfl_sync(0xffffffffu, c.vH[0] ^ 16, lane); c.vH[0] = __shfl_sync(0xffffffffu, c.vH[0], lane);
    c.qC[1] = __shfl_sync(0xffffffffu, c.qC[0] ^ 64, lane); c.qC[0] = __shfl_sync(0xffffffffu, c.qC[0], lane);
    c.spin = 0;
    asm volatile("barrier.cluster.wait.aligned;" ::: "memory");
    TR(2, -3, 2);
#pragma unroll
    for (int i = 0; i < 2 * NL; i++) sts128(wdst + (i & 1) * 3072 + (i / 2) * 18432, wv[i]);
    fence_async();
    TR(2, -3, 3);
    asm volatile("bar.sync 1, 384;" ::: "memory");
    TR(2, -3, 4);
    mbar_wait(bar + B_WK * 8, 0);
    TR(2, -3, 5);
    uint32_t pk[12], pv[12], pq[12];
    gemm_iter<true, false, 0>(c, -2, pk, pv, pq, &mp.wo TRPASS);
    TR2(blockIdx.x, 4);
#pragma unroll 1
    for (int b = -1;; b += 2) {
      gemm_iter<false, false, 1>(c, b, pk, pv, pq, &mp.wo TRPASS);
      if (b == 11) break;
      gemm_iter<false, false, 0>(c, b + 1, pk, pv, pq, &mp.wo TRPASS);
    }
    TR2(blockIdx.x, 6);
    gemm_iter<false, true, 0>(c, 12, pk, pv, pq, &mp.wo TRPASS);
    TR(2, 13, 0);
    mbar_wait(bar + B_WO * 8, 0);
    mbar_wait(bar + B_TIN * 8, 0);
    const uint32_t st = sb + gw * 3072;
    const uint32_t sta = st + (lane & 15) * 64 + ((hi ^ ((lane >> 1) & 3)) * 16);
    const int oc = ph * 112 + strip * 16 + 8 * (gw >> 1) + 4 * (head >> 1) + 2 * (gw & 1), och = pw * 6 + (head & 1) * 3;
    float D0[48], D1[48];
    nb_sync(N_PVISS, 384);
    issue_proj<SM_X2>(D0);
    mbar_wait(bar + (B_TIN + 1) * 8, 0);
    issue_proj<SM_X1>(D1);
    wg_wait<1>(); pin(D0);
    store_proj(D0, &mp.ot, st + SM_TST, sta + SM_TST, 8 * TB, oc, och);
    wg_wait<0>(); pin(D1);
    store_proj(D1, &mp.ot, st + SM_X2, sta + SM_X2, 8 * TB + 8, oc, och);
    mbar_wait(bar + (B_TIN + 2) * 8, 0);
    issue_proj<SM_X0>(D0);
    asm volatile("barrier.cluster.arrive.relaxed.aligned;" ::: "memory");
    wg_wait<0>(); pin(D0);
    store_proj(D0, &mp.ot, st + SM_X2 + 12288, sta + SM_X2 + 12288, 8 * TB + 16, oc, och);
    TR(2, 13, 7);
    if (lane == 0) asm volatile("cp.async.bulk.wait_group.read 0;" ::: "memory");
    __syncwarp();
    TR(2, 13, 8);
    TR2(blockIdx.x, 2);
    TRDUMP;
    asm volatile("barrier.cluster.wait.aligned;" ::: "memory");
  } else {
    if (warp == 12) {
      if (elect_one()) {
        mbar_init(bar + B_WK * 8, 1);
#pragma unroll
        for (int i = 0; i < NL; i++) load_w(&mp.w, sb + SM_W + (3 * i + 2 - 2 * va) * 6144, bar + B_WK * 8, ((i + 1) % 3) * 192 + head * 48 + 32 - 32 * va);
        asm volatile("prefetch.tensormap [%0];" ::"l"(head ? &mp.xc : &mp.xh) : "memory");
        mbar_expect(bar + B_WK * 8, NL * 6144);
      }
    } else if (warp == 15) {
      const int col = min(max(strip * 16 - 3 + min(lane, 21), 0), 111);
      const uint8_t* p = reinterpret_cast<const uint8_t*>(x) + (uint32_t)(head * ROWB + (ph * 112 + col) * 768 + pw * 384);
#pragma unroll
      for (int i = 0; i < 3; i++) asm volatile("prefetch.global.L2 [%0];" ::"l"(p + i * 128));
    } else if (elect_one()) {
      if (warp == 13) {
#pragma unroll
        for (int i = 0; i < B_WK; i++) mbar_init(bar + i * 8, i < B_EMPTY ? 1 : (i < B_TIN ? 16 : (i < B_TFREE ? 1 : 16)));
      } else {
#pragma unroll
        for (int i = B_WQ; i < B_COUNT; i++) mbar_init(bar + i * 8, i < B_Q0 ? 1 : (i < B_ODONE ? 4 : 8));
      }
    }
    asm volatile("fence.mbarrier_init.release.cluster;" ::: "memory");
    __syncwarp();
    asm volatile("barrier.cluster.arrive.relaxed.aligned;" ::: "memory");
    asm volatile("setmaxnreg.dec.sync.aligned.u32 24;");
    asm volatile("griddepcontrol.launch_dependents;");
    const int cc = ph * 112 + (head ? strip * 16 : (strip == 0 ? 16 : (strip == 6 ? 74 : strip * 16 - 3)));
    const int sd = strip == 0 ? -1 : (strip == 6 ? 1 : 0);
    const int r0 = head == 0 ? -4 : (head == 1 ? 4 : 0);
    asm volatile("barrier.cluster.wait.aligned;" ::: "memory");
    if (warp == 12) {
      const uint32_t fb = bar + (B_FULL + head) * 8, eb = bar + (B_EMPTY + head) * 8;
      const uint32_t dst = sb + (head == 0 ? SM_X0 : (head == 1 ? SM_X1 : SM_X2));
      const int nl = head == 0 ? 15 : (head == 3 ? 1 : 14);
#pragma unroll 1
      for (int n = 0; n < nl; n++) {
        if (n) mbar_wait(eb, (n - 1) & 1);
        if (lane < 4 && head < 3)
          asm volatile("{\n.reg .b32 ra;\nmapa.shared::cluster.u32 ra, %0, %1;\nmbarrier.arrive.expect_tx.shared::cluster.b64 _, [ra], %2;\n}"
                       ::"r"(fb), "r"(lane), "r"(head ? 24576 : 18432) : "memory");
        __syncwarp();
        if (elect_one()) {
          if (head == 0) {
            asm volatile("cp.async.bulk.tensor.5d.shared::cluster.global.mbarrier::complete_tx::bytes.multicast::cluster [%0], [%1, {%3,%4,%5,%6,%7}], [%2], %8;"
                         ::"r"(dst), "l"(&mp.xh), "r"(fb), "r"(0), "r"(8 * n + r0), "r"(cc), "r"(sd), "r"(pw * 3), "h"((uint16_t)15) : "memory");
          } else if (head < 3) {
            asm volatile("cp.async.bulk.tensor.4d.shared::cluster.global.mbarrier::complete_tx::bytes.multicast::cluster [%0], [%1, {%3,%4,%5,%6}], [%2], %7;"
                         ::"r"(dst), "l"(&mp.xc), "r"(fb), "r"(0), "r"(8 * n + r0), "r"(cc), "r"(pw * 3), "h"((uint16_t)15) : "memory");
          }
          if (n == 0) {
#pragma unroll
            for (int i = 0; i < 3; i++) load_w(&mp.w, sb + SM_W + (6 + i) * 6144, bar + B_WQ * 8, head * 48 + i * 16);
            mbar_expect(bar + B_WQ * 8, 18432);
            mbar_expect(bar + B_TIN * 8, 24576); mbar_expect(bar + (B_TIN + 1) * 8, 24576); mbar_expect(bar + (B_TIN + 2) * 8, 24576);
          }
          if (!head && n + 1 < nl) asm volatile("cp.async.bulk.prefetch.tensor.5d.L2.global [%0, {%1,%2,%3,%4,%5}];" ::"l"(&mp.xh), "r"(0), "r"(8 * n + 8 + r0), "r"(cc), "r"(sd), "r"(pw * 3) : "memory");
          if (head && n + 1 < nl) asm volatile("cp.async.bulk.prefetch.tensor.4d.L2.global [%0, {%1,%2,%3,%4}];" ::"l"(&mp.xc), "r"(0), "r"(8 * n + 8 + r0), "r"(cc), "r"(pw * 3) : "memory");
        }
        __syncwarp();
      }
    }
    if (warp == 14) {
      int* flag = g_flags + cl * 2;
      nb_arrive(N_VQ0, 288); nb_arrive(N_VQ1, 288);
#pragma unroll 1
      for (int b = 0; b < TB; b++) {
        mbar_wait(bar + B_ODONE * 8, b & 1);
        if (lane == 0) {
          asm volatile("cp.async.bulk.tensor.3d.global.shared::cta.bulk_group [%0, {%2,%3,%4}], [%1];"
                       ::"l"(&mp.os), "r"(sb + SM_O), "r"(pw * 192), "r"(8 * b + 2 * head), "r"(ph * 112 + strip * 16) : "memory");
          asm volatile("cp.async.bulk.commit_group;\ncp.async.bulk.wait_group 0;" ::: "memory");
        }
        __syncwarp();
        nb_arrive(N_VQ0, 288); nb_arrive(N_VQ1, 288);
        if (lane == 0)
          asm volatile("fence.proxy.async.global;\nfence.acq_rel.gpu;\nred.relaxed.gpu.global.add.s32 [%0], 1;\nred.relaxed.gpu.global.add.s32 [%0+4], 1;"
                       ::"l"(flag + b * 56) : "memory");
        __syncwarp();
      }
    } else if (warp & 1) {
      const int j = (warp >> 1) & 1;
#pragma unroll 1
      for (int i = 0; i < 2; i++) {
        mbar_wait(bar + (B_OTAIL + j) * 8, i);
        if (i == 0) nb_arrive(N_VQ0 + j, 288);
        mbar_wait(bar + (B_TFREE + i) * 8, 0);
        if (i == 1) nb_arrive(N_VQ0 + j, 288);
        if (elect_one()) {
#pragma unroll 1
          for (int d = 0; d < 8; d++) {
            const int dst = (d + head) & 3, pc = d >> 2;
            send_o<1536>(sb + (i ? SM_X1 : SM_X2) + head * 6144 + j * 3072 + pc * 1536,
                         sb + (i ? SM_Q : SM_O) + (4 * j + (dst & 2) + pc) * (i ? 3072 : 1536), bar + (B_TIN + i) * 8, dst);
          }
        }
        __syncwarp();
      }
    }
    cluster_sync();
  }
}

constexpr int NSTB = 6;
constexpr int NTB = TB * 56;
constexpr int SM_B_IN = 0;
constexpr int SM_B_W = SM_B_IN + NSTB * 24576;
constexpr int SM_B_BAR = SM_B_W + 73728;
constexpr int SM_B_TOTAL = SM_B_BAR + 128;
struct MapsB { CUtensorMap oi, oo, wo; };

__global__ void __launch_bounds__(480, 1)
na_proj_kernel(const __grid_constant__ MapsB mp) {
  extern __shared__ __align__(1024) uint8_t smem_raw[];
  const uint32_t sb = smem_u32(smem_raw);
  if ((sb & 0x3FFFF) != SBC) return;
  const uint32_t bar = sb + SM_B_BAR;
  const int tid = threadIdx.x, lane = tid & 31;
  const int warp = __shfl_sync(0xffffffffu, tid >> 5, 0);
  TR2(132 + blockIdx.x, 0);
  TRB(47, 0);
  if (warp == 12 && elect_one()) {
#pragma unroll
    for (int i = 0; i <= 2 * NSTB; i++) mbar_init(bar + i * 8, i < NSTB || i == 2 * NSTB ? 1 : 4);
    mbar_expect(bar + 2 * NSTB * 8, 73728);
#pragma unroll
    for (int i = 0; i < 2; i++)
      asm volatile("cp.async.bulk.tensor.3d.shared::cluster.global.mbarrier::complete_tx::bytes [%0], [%1, {%3,%4,%5}], [%2];"
                   ::"r"(sb + SM_B_W + i * 36864), "l"(&mp.wo), "r"(bar + 2 * NSTB * 8), "r"(0), "r"(0), "r"(i * 3) : "memory");
  }
  __syncthreads();
  const int step = gridDim.x;
  if (warp >= 12) {
    const int wg = warp - 12;
    int use = 0;
#pragma unroll 1
    for (int n = blockIdx.x + wg * step; n < NTB; n += 3 * step, use++) {
      const int b = n / 56, rem = n - b * 56, par = rem / 14, sg = wg + 3 * (use & 1);
      int v; uint32_t spin = 0;
      do { asm volatile("ld.acquire.gpu.global.s32 %0, [%1];" : "=r"(v) : "l"(g_flags + n) : "memory"); if ((OPT & 1) && v < 4) __nanosleep(200); } while (v < 4 && ++spin < SPIN_LIMIT);
      TRB(use * 3 + wg, 0);
      asm volatile("fence.proxy.async.global;" ::: "memory");
      if (use >= 2) mbar_wait(bar + (NSTB + sg) * 8, ((use >> 1) - 1) & 1);
      TRB(use * 3 + wg, 1);
      if (elect_one()) {
        mbar_expect(bar + sg * 8, 24576);
        asm volatile("cp.async.bulk.tensor.3d.shared::cluster.global.mbarrier::complete_tx::bytes [%0], [%1, {%3,%4,%5}], [%2];"
                     ::"r"(sb + SM_B_IN + sg * 24576), "l"(&mp.oi), "r"(bar + sg * 8), "r"((par & 1) * 192), "r"(8 * b), "r"((par >> 1) * 112 + (rem - par * 14) * 8) : "memory");
        g_flags[n] = 0;
      }
      __syncwarp();
    }
  } else {
    const int wg = warp >> 2, w = warp & 3;
    constexpr uint64_t db = mkdesc(SBC + SM_B_W, 12288, 512, 2);
    const uint32_t sta0 = sb + SM_B_IN + w * 6144 + (lane & 15) * 128 + (((lane >> 4) ^ (lane & 7)) * 16);
    mbar_wait(bar + 2 * NSTB * 8, 0);
    TRB(47, 1);
    int use = 0;
#pragma unroll 1
    for (int n = blockIdx.x + wg * step; n < NTB; n += 3 * step, use++) {
      const int b = n / 56, rem = n - b * 56, par = rem / 14, sg = wg + 3 * (use & 1);
      const uint64_t da = mkdesc(SBC + SM_B_IN, 128, 3072, 0) + sg * (24576 / 16);
      float D[96];
      mbar_wait(bar + sg * 8, (use >> 1) & 1);
      if (use | wg) nb_sync(4 + wg, 256);
      TRB(use * 3 + wg, 3);
      wg_fence();
      wg_ss192<0>(D, da, db);
#pragma unroll
      for (int k = 1; k < 12; k++) wg_ss192<1>(D, da + k * 16, db + k * 64);
      wg_commit();
      if (n + step < NTB) nb_arrive(wg == 2 ? 4 : 5 + wg, 256);
      TRB(use * 3 + wg, 4);
      if (use && lane == 0) {
        asm volatile("cp.async.bulk.wait_group.read 0;" ::: "memory");
        mbar_arrive(bar + (NSTB + wg + 3 * (~use & 1)) * 8);
      }
      __syncwarp();
      wg_wait<0>(); pin(D);
      nb_sync(1 + wg, 128);
      TRB(use * 3 + wg, 5);
      const uint32_t sta = sta0 + sg * 24576;
#pragma unroll
      for (int q = 0; q < 12; q++)
        stsm4((sta ^ ((q & 3) * 32)) + (q >> 2) * 2048,
              pack2(D[8 * q], D[8 * q + 1]), pack2(D[8 * q + 2], D[8 * q + 3]), pack2(D[8 * q + 4], D[8 * q + 5]), pack2(D[8 * q + 6], D[8 * q + 7]));
      fence_async();
      __syncwarp();
      if (lane == 0) {
        asm volatile("cp.async.bulk.tensor.4d.global.shared::cta.bulk_group [%0, {%2,%3,%4,%5}], [%1];"
                     ::"l"(&mp.oo), "r"(sb + SM_B_IN + sg * 24576 + w * 6144), "r"(0), "r"(8 * b), "r"((par >> 1) * 112 + (rem - par * 14) * 8 + 2 * w), "r"((par & 1) * 3) : "memory");
        asm volatile("cp.async.bulk.commit_group;" ::: "memory");
      }
      __syncwarp();
      TRB(use * 3 + wg, 6);
    }
    if (lane == 0) asm volatile("cp.async.bulk.wait_group 0;" ::: "memory");
    TR2(132 + blockIdx.x, 2);
  }
}

typedef CUresult (*EncodeFn)(CUtensorMap*, CUtensorMapDataType, cuuint32_t, void*, const cuuint64_t*, const cuuint64_t*, const cuuint32_t*,
                             const cuuint32_t*, CUtensorMapInterleave, CUtensorMapSwizzle, CUtensorMapL2promotion, CUtensorMapFloatOOBfill);
static EncodeFn g_enc = nullptr;
static void make_map(CUtensorMap* m, const void* p, int rank, const cuuint64_t* dim, const cuuint64_t* str, const cuuint32_t* box, CUtensorMapSwizzle sw) {
  const cuuint32_t ones[5] = {1, 1, 1, 1, 1};
  g_enc(m, CU_TENSOR_MAP_DATA_TYPE_BFLOAT16, rank, (void*)p, dim, str, box, ones, CU_TENSOR_MAP_INTERLEAVE_NONE, sw,
        CU_TENSOR_MAP_L2_PROMOTION_L2_128B, CU_TENSOR_MAP_FLOAT_OOB_FILL_NONE);
}

extern "C" void kernel_launch(void* const* d_in, const int* in_sizes, int n_in, void* d_out, int out_size) {
  const __nv_bfloat16* x = (const __nv_bfloat16*)d_in[0];
  const __nv_bfloat16* wqkv = (const __nv_bfloat16*)d_in[1];
  const __nv_bfloat16* wo = (const __nv_bfloat16*)d_in[2];
  const __nv_bfloat16* rpb = (const __nv_bfloat16*)d_in[3];

  if (!g_enc) {
    void* fn = nullptr; cudaDriverEntryPointQueryResult qr;
    cudaGetDriverEntryPoint("cuTensorMapEncodeTiled", &fn, cudaEnableDefault, &qr);
    g_enc = (EncodeFn)fn;
    cudaFuncSetAttribute(na_attn_kernel, cudaFuncAttributeMaxDynamicSharedMemorySize, SM_A_TOTAL);
    cudaFuncSetAttribute(na_proj_kernel, cudaFuncAttributeMaxDynamicSharedMemorySize, SM_B_TOTAL);
  }
  Maps ma; MapsB mb;
  { cuuint64_t dim[4] = {64, 112, 224, 6}, str[3] = {(cuuint64_t)ROWB, 768, 128};
    cuuint32_t box[4] = {64, 4, 16, 3}, boxo[4] = {64, 8, 2, 3};
    make_map(&ma.xc, x, 4, dim, str, box, CU_TENSOR_MAP_SWIZZLE_128B);
    make_map(&mb.oo, d_out, 4, dim, str, boxo, CU_TENSOR_MAP_SWIZZLE_128B); }
  { cuuint64_t dim[5] = {64, 112, 224, 2, 6}, str[4] = {(cuuint64_t)ROWB, 768, 19 * 768, 128};
    cuuint32_t box[5] = {64, 8, 3, 2, 3};
    make_map(&ma.xh, x, 5, dim, str, box, CU_TENSOR_MAP_SWIZZLE_128B); }
  { cuuint64_t dim[3] = {384, 112, 224}, str[2] = {(cuuint64_t)ROWB, 768};
    cuuint32_t box[3] = {192, 8, 8}, boxs[3] = {192, 2, 16};
    make_map(&mb.oi, d_out, 3, dim, str, box, CU_TENSOR_MAP_SWIZZLE_NONE);
    make_map(&ma.os, d_out, 3, dim, str, boxs, CU_TENSOR_MAP_SWIZZLE_NONE); }
  { cuuint64_t dim[4] = {32, 112, 224, 12}, str[3] = {(cuuint64_t)ROWB, 768, 64};
    cuuint32_t box[4] = {32, 8, 2, 3};
    make_map(&ma.ot, d_out, 4, dim, str, box, CU_TENSOR_MAP_SWIZZLE_64B); }
  { cuuint64_t dim[2] = {576, 192}, str[1] = {1152};
    cuuint32_t box[2] = {16, 192};
    make_map(&ma.w, wqkv, 2, dim, str, box, CU_TENSOR_MAP_SWIZZLE_32B); }
  { cuuint64_t dim[3] = {32, 192, 6}, str[2] = {384, 64};
    cuuint32_t box[3] = {32, 192, 3};
    make_map(&ma.wo, wo, 3, dim, str, box, CU_TENSOR_MAP_SWIZZLE_64B);
    mb.wo = ma.wo; }
  na_attn_kernel<<<112, 512, SM_A_TOTAL>>>(x, wqkv, rpb, ma);
  cudaLaunchConfig_t cfg = {};
  cfg.gridDim = dim3(20); cfg.blockDim = dim3(480); cfg.dynamicSmemBytes = SM_B_TOTAL; cfg.stream = cudaStreamPerThread;
  cudaLaunchAttribute at[1];
  at[0].id = cudaLaunchAttributeProgrammaticStreamSerialization; at[0].val.programmaticStreamSerializationAllowed = 1;
  cfg.attrs = at; cfg.numAttrs = 1;
  cudaLaunchKernelEx(&cfg, na_proj_kernel, mb);
}
```

```cpp
#include <cuda_runtime.h>
#include <cuda_bf16.h>
#include <cuda.h>
#include <stdint.h>

#define SPIN_LIMIT (1u << 18)

__device__ __forceinline__ uint32_t smem_u32(const void* p) { return (uint32_t)__cvta_generic_to_shared(p); }
__device__ __forceinline__ void wg_fence() { asm volatile("wgmma.fence.sync.aligned;" ::: "memory"); }
__device__ __forceinline__ void wg_commit() { asm volatile("wgmma.commit_group.sync.aligned;" ::: "memory"); }
template <int N> __device__ __forceinline__ void wg_wait() { asm volatile("wgmma.wait_group.sync.aligned %0;" ::"n"(N) : "memory"); }
template <int N> __device__ __forceinline__ void pin(float (&d)[N]) {
#pragma unroll
  for (int i = 0; i < N; i++) asm volatile("" : "+f"(d[i])::"memory");
}
__host__ __device__ constexpr uint64_t mkdesc(uint32_t addr, uint32_t lbo, uint32_t sbo, uint32_t sw) {
  return (uint64_t)((addr & 0x3FFFF) >> 4) | ((uint64_t)(lbo >> 4) << 16) | ((uint64_t)(sbo >> 4) << 32) | ((uint64_t)sw << 62);
}
__device__ __forceinline__ void mbar_init(uint32_t bar, uint32_t cnt) { asm volatile("mbarrier.init.shared::cta.b64 [%0], %1;" ::"r"(bar), "r"(cnt) : "memory"); }
__device__ __forceinline__ void mbar_arrive(uint32_t bar) { asm volatile("mbarrier.arrive.shared::cta.b64 _, [%0];" ::"r"(bar) : "memory"); }
__device__ __forceinline__ bool elect_one() {
  uint32_t r; asm volatile("{\n.reg .pred p;\nelect.sync _|p, 0xffffffff;\nselp.u32 %0, 1, 0, p;\n}" : "=r"(r)); return r;
}
__device__ __forceinline__ void mbar_arrive_elect(uint32_t bar) {
  asm volatile("{\n.reg .pred p;\nelect.sync _|p, 0xffffffff;\n@p mbarrier.arrive.shared::cta.b64 _, [%0];\n}" ::"r"(bar) : "memory");
}
__device__ __forceinline__ void mbar_expect(uint32_t bar, uint32_t bytes) { asm volatile("mbarrier.arrive.expect_tx.shared::cta.b64 _, [%0], %1;" ::"r"(bar), "r"(bytes) : "memory"); }
__device__ __forceinline__ void mbar_arrive_remote(uint32_t bar, uint32_t cta) {
  asm volatile("{\n.reg .b32 ra;\nmapa.shared::cluster.u32 ra, %0, %1;\nmbarrier.arrive.relaxed.cluster.shared::cluster.b64 _, [ra];\n}" ::"r"(bar), "r"(cta) : "memory");
}
__device__ __forceinline__ void mbar_wait(uint32_t bar, uint32_t parity) {
  asm volatile("{\n.reg .pred p;\n.reg .b32 n;\nmov.b32 n, 0;\nWL:\nmbarrier.try_wait.parity.shared::cta.b64 p, [%0], %1;\n@p bra WD;\n"
               "add.u32 n, n, 1;\nsetp.lt.u32 p, n, 65536;\n@p bra WL;\nWD:\n}" ::"r"(bar), "r"(parity) : "memory");
}
__device__ __forceinline__ void nb_sync(int id, int n) { asm volatile("bar.sync %0, %1;" ::"r"(id), "r"(n) : "memory"); }
__device__ __forceinline__ void nb_arrive(int id, int n) { asm volatile("bar.arrive %0, %1;" ::"r"(id), "r"(n) : "memory"); }
__device__ __forceinline__ void fence_async() { asm volatile("fence.proxy.async.shared::cta;" ::: "memory"); }
__device__ __forceinline__ void cluster_sync() {
  asm volatile("barrier.cluster.arrive.relaxed.aligned;\nbarrier.cluster.wait.aligned;" ::: "memory");
}
__device__ __forceinline__ uint32_t pack2(float lo, float hi) {
  uint32_t r; asm("cvt.rn.bf16x2.f32 %0, %1, %2;" : "=r"(r) : "f"(hi), "f"(lo)); return r;
}
__device__ __forceinline__ void stsm4(uint32_t a, uint32_t r0, uint32_t r1, uint32_t r2, uint32_t r3) {
  asm volatile("stmatrix.sync.aligned.m8n8.x4.shared.b16 [%0], {%1,%2,%3,%4};" ::"r"(a), "r"(r0), "r"(r1), "r"(r2), "r"(r3) : "memory");
}
__device__ __forceinline__ void ldsm4(uint32_t a, uint32_t& r0, uint32_t& r1, uint32_t& r2, uint32_t& r3) {
  asm volatile("ldmatrix.sync.aligned.m8n8.x4.shared.b16 {%0,%1,%2,%3}, [%4];" : "=r"(r0), "=r"(r1), "=r"(r2), "=r"(r3) : "r"(a) : "memory");
}
__device__ __forceinline__ void sts128(uint32_t a, uint4 v) {
  asm volatile("st.shared.v4.b32 [%0], {%1,%2,%3,%4};" ::"r"(a), "r"(v.x), "r"(v.y), "r"(v.z), "r"(v.w) : "memory");
}
__device__ __forceinline__ float lds_f32(uint32_t a) { float v; asm volatile("ld.shared.f32 %0, [%1];" : "=f"(v) : "r"(a)); return v; }
__device__ __forceinline__ float ex2(float x) { float y; asm("ex2.approx.ftz.f32 %0, %1;" : "=f"(y) : "f"(x)); return y; }

template<int SC> __device__ __forceinline__ void wg_ss144(float (&d)[72], uint64_t da, uint64_t db) {
  asm volatile("{\n.reg .pred p;\nsetp.ne.b32 p, %74, 0;\nwgmma.mma_async.sync.aligned.m64n144k16.f32.bf16.bf16 {%0,%1,%2,%3,%4,%5,%6,%7,%8,%9,%10,%11,%12,%13,%14,%15,%16,%17,%18,%19,%20,%21,%22,%23,%24,%25,%26,%27,%28,%29,%30,%31,%32,%33,%34,%35,%36,%37,%38,%39,%40,%41,%42,%43,%44,%45,%46,%47,%48,%49,%50,%51,%52,%53,%54,%55,%56,%57,%58,%59,%60,%61,%62,%63,%64,%65,%66,%67,%68,%69,%70,%71}, %72, %73, p, 1, 1, 0, 1;\n}\n"
    : "+f"(d[0]),"+f"(d[1]),"+f"(d[2]),"+f"(d[3]),"+f"(d[4]),"+f"(d[5]),"+f"(d[6]),"+f"(d[7]),"+f"(d[8]),"+f"(d[9]),"+f"(d[10]),"+f"(d[11]),"+f"(d[12]),"+f"(d[13]),"+f"(d[14]),"+f"(d[15]),"+f"(d[16]),"+f"(d[17]),"+f"(d[18]),"+f"(d[19]),"+f"(d[20]),"+f"(d[21]),"+f"(d[22]),"+f"(d[23]),"+f"(d[24]),"+f"(d[25]),"+f"(d[26]),"+f"(d[27]),"+f"(d[28]),"+f"(d[29]),"+f"(d[30]),"+f"(d[31]),"+f"(d[32]),"+f"(d[33]),"+f"(d[34]),"+f"(d[35]),"+f"(d[36]),"+f"(d[37]),"+f"(d[38]),"+f"(d[39]),"+f"(d[40]),"+f"(d[41]),"+f"(d[42]),"+f"(d[43]),"+f"(d[44]),"+f"(d[45]),"+f"(d[46]),"+f"(d[47]),"+f"(d[48]),"+f"(d[49]),"+f"(d[50]),"+f"(d[51]),"+f"(d[52]),"+f"(d[53]),"+f"(d[54]),"+f"(d[55]),"+f"(d[56]),"+f"(d[57]),"+f"(d[58]),"+f"(d[59]),"+f"(d[60]),"+f"(d[61]),"+f"(d[62]),"+f"(d[63]),"+f"(d[64]),"+f"(d[65]),"+f"(d[66]),"+f"(d[67]),"+f"(d[68]),"+f"(d[69]),"+f"(d[70]),"+f"(d[71]) : "l"(da), "l"(db), "n"(SC));
}
template<int SC> __device__ __forceinline__ void wg_ss96(float (&d)[48], uint64_t da, uint64_t db) {
  asm volatile("{\n.reg .pred p;\nsetp.ne.b32 p, %50, 0;\nwgmma.mma_async.sync.aligned.m64n96k16.f32.bf16.bf16 {%0,%1,%2,%3,%4,%5,%6,%7,%8,%9,%10,%11,%12,%13,%14,%15,%16,%17,%18,%19,%20,%21,%22,%23,%24,%25,%26,%27,%28,%29,%30,%31,%32,%33,%34,%35,%36,%37,%38,%39,%40,%41,%42,%43,%44,%45,%46,%47}, %48, %49, p, 1, 1, 0, 1;\n}\n"
    : "+f"(d[0]),"+f"(d[1]),"+f"(d[2]),"+f"(d[3]),"+f"(d[4]),"+f"(d[5]),"+f"(d[6]),"+f"(d[7]),"+f"(d[8]),"+f"(d[9]),"+f"(d[10]),"+f"(d[11]),"+f"(d[12]),"+f"(d[13]),"+f"(d[14]),"+f"(d[15]),"+f"(d[16]),"+f"(d[17]),"+f"(d[18]),"+f"(d[19]),"+f"(d[20]),"+f"(d[21]),"+f"(d[22]),"+f"(d[23]),"+f"(d[24]),"+f"(d[25]),"+f"(d[26]),"+f"(d[27]),"+f"(d[28]),"+f"(d[29]),"+f"(d[30]),"+f"(d[31]),"+f"(d[32]),"+f"(d[33]),"+f"(d[34]),"+f"(d[35]),"+f"(d[36]),"+f"(d[37]),"+f"(d[38]),"+f"(d[39]),"+f"(d[40]),"+f"(d[41]),"+f"(d[42]),"+f"(d[43]),"+f"(d[44]),"+f"(d[45]),"+f"(d[46]),"+f"(d[47]) : "l"(da), "l"(db), "n"(SC));
}
template<int SC> __device__ __forceinline__ void wg_rs112(float (&d)[56], uint32_t a0, uint32_t a1, uint32_t a2, uint32_t a3, uint64_t db) {
  asm volatile("{\n.reg .pred p;\nsetp.ne.b32 p, %61, 0;\nwgmma.mma_async.sync.aligned.m64n112k16.f32.bf16.bf16 {%0,%1,%2,%3,%4,%5,%6,%7,%8,%9,%10,%11,%12,%13,%14,%15,%16,%17,%18,%19,%20,%21,%22,%23,%24,%25,%26,%27,%28,%29,%30,%31,%32,%33,%34,%35,%36,%37,%38,%39,%40,%41,%42,%43,%44,%45,%46,%47,%48,%49,%50,%51,%52,%53,%54,%55}, {%56,%57,%58,%59}, %60, p, 1, 1, 0;\n}\n"
    : "+f"(d[0]),"+f"(d[1]),"+f"(d[2]),"+f"(d[3]),"+f"(d[4]),"+f"(d[5]),"+f"(d[6]),"+f"(d[7]),"+f"(d[8]),"+f"(d[9]),"+f"(d[10]),"+f"(d[11]),"+f"(d[12]),"+f"(d[13]),"+f"(d[14]),"+f"(d[15]),"+f"(d[16]),"+f"(d[17]),"+f"(d[18]),"+f"(d[19]),"+f"(d[20]),"+f"(d[21]),"+f"(d[22]),"+f"(d[23]),"+f"(d[24]),"+f"(d[25]),"+f"(d[26]),"+f"(d[27]),"+f"(d[28]),"+f"(d[29]),"+f"(d[30]),"+f"(d[31]),"+f"(d[32]),"+f"(d[33]),"+f"(d[34]),"+f"(d[35]),"+f"(d[36]),"+f"(d[37]),"+f"(d[38]),"+f"(d[39]),"+f"(d[40]),"+f"(d[41]),"+f"(d[42]),"+f"(d[43]),"+f"(d[44]),"+f"(d[45]),"+f"(d[46]),"+f"(d[47]),"+f"(d[48]),"+f"(d[49]),"+f"(d[50]),"+f"(d[51]),"+f"(d[52]),"+f"(d[53]),"+f"(d[54]),"+f"(d[55]) : "r"(a0), "r"(a1), "r"(a2), "r"(a3), "l"(db), "n"(SC));
}
template<int SC> __device__ __forceinline__ void wg_sp48(float (&d)[24], uint32_t a0, uint32_t a1, uint32_t a2, uint32_t a3, uint64_t db, uint32_t meta) {
  asm volatile("{\n.reg .pred p;\nsetp.ne.b32 p, %30, 0;\nwgmma.mma_async.sp.sync.aligned.m64n48k32.f32.bf16.bf16 {%0,%1,%2,%3,%4,%5,%6,%7,%8,%9,%10,%11,%12,%13,%14,%15,%16,%17,%18,%19,%20,%21,%22,%23}, {%24,%25,%26,%27}, %28, %29, 0, p, 1, 1, 1;\n}\n"
    : "+f"(d[0]),"+f"(d[1]),"+f"(d[2]),"+f"(d[3]),"+f"(d[4]),"+f"(d[5]),"+f"(d[6]),"+f"(d[7]),"+f"(d[8]),"+f"(d[9]),"+f"(d[10]),"+f"(d[11]),"+f"(d[12]),"+f"(d[13]),"+f"(d[14]),"+f"(d[15]),"+f"(d[16]),"+f"(d[17]),"+f"(d[18]),"+f"(d[19]),"+f"(d[20]),"+f"(d[21]),"+f"(d[22]),"+f"(d[23]) : "r"(a0), "r"(a1), "r"(a2), "r"(a3), "l"(db), "r"(meta), "n"(SC));
}
template<int SC> __device__ __forceinline__ void wg_ss192(float (&d)[96], uint64_t da, uint64_t db) {
  asm volatile("{\n.reg .pred p;\nsetp.ne.b32 p, %98, 0;\nwgmma.mma_async.sync.aligned.m64n192k16.f32.bf16.bf16 {%0,%1,%2,%3,%4,%5,%6,%7,%8,%9,%10,%11,%12,%13,%14,%15,%16,%17,%18,%19,%20,%21,%22,%23,%24,%25,%26,%27,%28,%29,%30,%31,%32,%33,%34,%35,%36,%37,%38,%39,%40,%41,%42,%43,%44,%45,%46,%47,%48,%49,%50,%51,%52,%53,%54,%55,%56,%57,%58,%59,%60,%61,%62,%63,%64,%65,%66,%67,%68,%69,%70,%71,%72,%73,%74,%75,%76,%77,%78,%79,%80,%81,%82,%83,%84,%85,%86,%87,%88,%89,%90,%91,%92,%93,%94,%95}, %96, %97, p, 1, 1, 0, 1;\n}\n"
    : "+f"(d[0]),"+f"(d[1]),"+f"(d[2]),"+f"(d[3]),"+f"(d[4]),"+f"(d[5]),"+f"(d[6]),"+f"(d[7]),"+f"(d[8]),"+f"(d[9]),"+f"(d[10]),"+f"(d[11]),"+f"(d[12]),"+f"(d[13]),"+f"(d[14]),"+f"(d[15]),"+f"(d[16]),"+f"(d[17]),"+f"(d[18]),"+f"(d[19]),"+f"(d[20]),"+f"(d[21]),"+f"(d[22]),"+f"(d[23]),"+f"(d[24]),"+f"(d[25]),"+f"(d[26]),"+f"(d[27]),"+f"(d[28]),"+f"(d[29]),"+f"(d[30]),"+f"(d[31]),"+f"(d[32]),"+f"(d[33]),"+f"(d[34]),"+f"(d[35]),"+f"(d[36]),"+f"(d[37]),"+f"(d[38]),"+f"(d[39]),"+f"(d[40]),"+f"(d[41]),"+f"(d[42]),"+f"(d[43]),"+f"(d[44]),"+f"(d[45]),"+f"(d[46]),"+f"(d[47]),"+f"(d[48]),"+f"(d[49]),"+f"(d[50]),"+f"(d[51]),"+f"(d[52]),"+f"(d[53]),"+f"(d[54]),"+f"(d[55]),"+f"(d[56]),"+f"(d[57]),"+f"(d[58]),"+f"(d[59]),"+f"(d[60]),"+f"(d[61]),"+f"(d[62]),"+f"(d[63]),"+f"(d[64]),"+f"(d[65]),"+f"(d[66]),"+f"(d[67]),"+f"(d[68]),"+f"(d[69]),"+f"(d[70]),"+f"(d[71]),"+f"(d[72]),"+f"(d[73]),"+f"(d[74]),"+f"(d[75]),"+f"(d[76]),"+f"(d[77]),"+f"(d[78]),"+f"(d[79]),"+f"(d[80]),"+f"(d[81]),"+f"(d[82]),"+f"(d[83]),"+f"(d[84]),"+f"(d[85]),"+f"(d[86]),"+f"(d[87]),"+f"(d[88]),"+f"(d[89]),"+f"(d[90]),"+f"(d[91]),"+f"(d[92]),"+f"(d[93]),"+f"(d[94]),"+f"(d[95]) : "l"(da), "l"(db), "n"(SC));
}

constexpr uint32_t SBC = 1024;
constexpr int ROWB = 2 * 224 * 384;
constexpr int TB = 11;
constexpr int KS = 832;
constexpr int KSLOT = 22 * KS;
constexpr int SM_X1 = 0;
constexpr int SM_X2 = SM_X1 + 24576;
constexpr int SM_X0 = SM_X2 + 24576;
constexpr int SM_W = SM_X0 + 18432;
constexpr int SM_K = SM_W + 55296;
constexpr int SM_V = SM_K + 2 * KSLOT;
constexpr int SM_Q = SM_V + 22 * 1536;
constexpr int SM_O = SM_Q + 24576;
constexpr int SM_RPB = SM_O + 12288;
constexpr int SM_BAR = SM_RPB + 768;
constexpr int SM_A_TOTAL = SM_BAR + 256;
constexpr int SM_TWO = SM_X0 + 24576;
constexpr int SM_TST = SM_TWO + 36864;
enum { B_FULL = 0, B_EMPTY = 3, B_TIN = 6, B_TFREE = 9, B_WK = 11, B_WQ, B_WO, B_Q0, B_OTAIL, B_ODONE = B_OTAIL + 2, B_KFREE, B_VFREE, B_COUNT };
enum { N_KRDY = 4, N_QK0, N_QK1, N_VQ0, N_VQ1, N_PVISS };

#define NL 2
#define OPT 0
#define SPL 4
#define RA 152
#define RG 184
__device__ int g_flags[TB * 56];

#define TR(role, it, k)
#define TRDECL
#define TRARG
#define TRPASS
#define TRDUMP
#define TRB(it, k)
#define TR2(blk, k)

struct GemmCtx {
  uint32_t bar;
  uint32_t kC, vC[2], qC[2];
  uint32_t kH, vH[2];
  uint32_t hiA, hiB;
  uint32_t spin;
  bool hvalid, never;
};

template <int STRIDE> __device__ __forceinline__ void dump12(uint32_t a, const uint32_t (&r)[12]) {
#pragma unroll
  for (int j = 0; j < 3; j++) stsm4(a + j * 2 * STRIDE, r[4 * j], r[4 * j + 1], r[4 * j + 2], r[4 * j + 3]);
}
__device__ __forceinline__ void keep12(bool never, uint32_t a, const uint32_t (&r)[12]) { if (never) dump12<128>(a, r); }
template <int N> __device__ __forceinline__ void pack12(uint32_t (&r)[12], const float (&d)[N], int off) {
#pragma unroll
  for (int j = 0; j < 12; j++) r[j] = pack2(d[off + 2 * j], d[off + 2 * j + 1]);
}
__device__ __forceinline__ uint64_t dsc(uint64_t lo, uint32_t hi) { uint64_t r; asm("mov.b64 %0, {%1, %2};" : "=l"(r) : "r"((uint32_t)lo), "r"(hi)); return r; }
template <int XS, int K0, int K1> __device__ __forceinline__ void issue_core(const GemmCtx& c, float (&d)[72]) {
  constexpr uint64_t da = mkdesc(SBC + XS, 16, 1024, 1), db = mkdesc(SBC + SM_W, 6144, 256, 3);
  wg_fence();
  if (K0 == 0) wg_ss144<0>(d, dsc(da, c.hiA), dsc(db, c.hiB));
#pragma unroll
  for (int k = K0 ? K0 : 1; k < K1; k++) wg_ss144<1>(d, dsc(da + (k >> 2) * 512 + (k & 3) * 2, c.hiA), dsc(db + k * 32, c.hiB));
  wg_commit();
}
template <int K0, int K1> __device__ __forceinline__ void issue_halo(const GemmCtx& c, float (&d)[48]) {
  constexpr uint64_t da = mkdesc(SBC + SM_X0 - 2048, 16, 1024, 1), db = mkdesc(SBC + SM_W, 6144, 256, 3);
  wg_fence();
  if (K0 == 0) wg_ss96<0>(d, dsc(da, c.hiA), dsc(db, c.hiB));
#pragma unroll
  for (int k = K0 ? K0 : 1; k < K1; k++) wg_ss96<1>(d, dsc(da + (k >> 2) * 384 + (k & 3) * 2, c.hiA), dsc(db + k * 32, c.hiB));
  wg_commit();
}
template <int ST> __device__ __forceinline__ void release_stage(const GemmCtx& c) {
  asm volatile("{\n.reg .pred p;\n.reg .b32 ra;\nelect.sync _|p, 0xffffffff;\nmapa.shared::cluster.u32 ra, %0, %1;\n"
               "@p mbarrier.arrive.shared::cluster.b64 _, [ra];\n}" ::"r"(c.bar + (B_EMPTY + ST) * 8), "n"(ST) : "memory");
}
template <int PARITY> __device__ __forceinline__ void gwait(GemmCtx& c, int bar) {
  asm volatile("{\n.reg .pred p;\nWL:\nmbarrier.try_wait.parity.shared::cta.b64 p, [%1], %2;\n@p bra WD;\n"
               "add.u32 %0, %0, 1;\nsetp.lt.u32 p, %0, 0x100000;\n@p bra WL;\nWD:\n}" : "+r"(c.spin) : "r"(c.bar + bar * 8), "n"(PARITY) : "memory");
}
__device__ __forceinline__ void load_w(const CUtensorMap* m, uint32_t dst, uint32_t bar, int col) {
  asm volatile("cp.async.bulk.tensor.2d.shared::cluster.global.mbarrier::complete_tx::bytes [%0], [%1, {%3,%4}], [%2];"
               ::"r"(dst), "l"(m), "r"(bar), "r"(col), "r"(0) : "memory");
}
template <int BYTES> __device__ __forceinline__ void send_o(uint32_t dst, uint32_t src, uint32_t bar, int cta) {
  asm volatile("{\n.reg .b32 rd, rb;\nmapa.shared::cluster.u32 rd, %0, %3;\nmapa.shared::cluster.u32 rb, %2, %3;\n"
               "cp.async.bulk.shared::cluster.shared::cta.mbarrier::complete_tx::bytes [rd], [%1], %4, [rb];\n}"
               ::"r"(dst), "r"(src), "r"(bar), "r"(cta), "n"(BYTES) : "memory");
}
__device__ __forceinline__ void tail_free(uint32_t bar) {
  uint32_t ln; asm volatile("mov.u32 %0, %%laneid;" : "=r"(ln));
  if (ln < 4) mbar_arrive_remote(bar, ln);
}
__device__ __forceinline__ void publish(uint32_t bar) {
  fence_async();
  __syncwarp();
  mbar_arrive_elect(bar);
}

template <bool FIRST, bool LAST, int PA>
__device__ __forceinline__ void gemm_iter(GemmCtx& c, int b, uint32_t (&pk)[12], uint32_t (&pv)[12], uint32_t (&pq)[12], const CUtensorMap* mwo TRARG) {
  const uint32_t bar = c.bar;
  const bool w = !FIRST && (PA == 0 || b >= 0), never = c.never;
  constexpr uint32_t ko = PA * KSLOT;
  float H[48], C[72];
  uint32_t hk[12], hv[12], pv2[12];
  TR(2, b, 0);
  if (FIRST) gwait<PA>(c, B_FULL + 0);
  if (!FIRST) dump12<256>(c.qC[1] + (PA ^ 1) * 128, pq);
  if (w) nb_sync(N_QK1, 256);
  TR(2, b, 2);
  if (FIRST) TR(2, b - 1, 6);
  issue_halo<0, 8>(c, H);
  TR(2, b, 3);
  if (!FIRST) {
    if (w) gwait<PA>(c, B_KFREE);
    dump12<128>(c.kC + ko, pk);
  }
  issue_halo<8, 12>(c, H);
  TR(2, b, 4);
  if (!LAST) {
    gwait<PA>(c, B_FULL + 2);
    if (FIRST && NL == 2) gwait<0>(c, B_WQ);
    TR(2, b, 13);
    if (FIRST) TR(2, b - 1, 7);
    issue_core<SM_X2, 0, 8>(c, C);
    TR(2, b, 5);
    if (!FIRST) { fence_async(); keep12(never, c.kC, pk); }
    wg_wait<1>(); pin(H);
    release_stage<0>(c);
  } else {
    fence_async();
    nb_arrive(N_VQ0, 288); nb_arrive(N_VQ1, 288); nb_arrive(N_PVISS, 384);
    wg_wait<0>(); pin(H);
    tail_free(bar + (B_TFREE + 1) * 8);
    nb_sync(2, 128);
    if (!c.hvalid && elect_one()) {
      mbar_expect(bar + B_WO * 8, 36864);
      asm volatile("cp.async.bulk.tensor.3d.shared::cluster.global.mbarrier::complete_tx::bytes [%0], [%1, {%3,%4,%5}], [%2];"
                   ::"r"(bar - SM_BAR + SM_TWO), "l"(mwo), "r"(bar + B_WO * 8), "r"(0), "r"(0), "r"((blockIdx.x & 1) * 3) : "memory");
    }
    __syncwarp();
  }
  pack12(hk, H, 0);
  if (c.hvalid) dump12<128>(c.kH + ko, hk);
  pack12(hv, H, 24);
  if (!LAST) {
    issue_core<SM_X2, 8, 12>(c, C);
    if (w) { nb_arrive(N_VQ0, 288); nb_arrive(N_VQ1, 288); }
    else if (!FIRST) { __syncwarp(); mbar_arrive_elect(bar + B_Q0 * 8); }
    gwait<PA>(c, B_FULL + 1);
    keep12(never, c.kC, hk);
    TR(2, b, 6);
    wg_wait<0>(); pin(C);
    TR(2, b, 7);
    pack12(pk, C, 0);
    dump12<128>(c.kC + ko + 64, pk);
    release_stage<2>(c);
    pack12(pv2, C, 24);
    pack12(pq, C, 48);
    TR(2, b, 8);
    issue_core<SM_X1, 0, SPL>(c, C);
    if (w) nb_sync(N_PVISS, 384);
    issue_core<SM_X1, SPL, 8>(c, C);
    TR(2, b, 9);
  }
  if (!FIRST) fence_async();
  if (!LAST) keep12(never, c.kC, pk);
  TR(2, b, 14);
  if (!LAST) issue_core<SM_X1, 8, 12>(c, C);
  if (!FIRST) nb_arrive(N_KRDY, 256);
  TR(2, b, 1);
  if (PA && b == 11) tail_free(bar + B_TFREE * 8);
  if (!LAST) gwait<PA ^ 1>(c, B_FULL + 0);
  if (w) gwait<PA>(c, B_VFREE);
  TR(2, b, 10);
  if (!FIRST) dump12<128>(c.vC[PA], pv);
  if (!LAST) dump12<256>(c.qC[0] + PA * 128, pq);
  if (c.hvalid) dump12<128>(c.vH[PA], hv);
  if (LAST) { fence_async(); nb_arrive(N_VQ0, 288); nb_arrive(N_VQ1, 288); nb_arrive(N_QK1, 256); return; }
  dump12<128>(c.vC[PA ^ 1] + 768, pv2);
  TR(2, b, 11);
  wg_wait<0>(); pin(C);
  TR(2, b, 12);
  release_stage<1>(c);
  pack12(pk, C, 0);
  pack12(pv, C, 24);
  pack12(pq, C, 48);
}

template <int IN> __device__ __forceinline__ void issue_proj(float (&D)[48]) {
  constexpr uint64_t da = mkdesc(SBC + IN, 128, 768, 0), db = mkdesc(SBC + SM_TWO, 12288, 512, 2);
  wg_fence();
  wg_ss96<0>(D, da, db);
#pragma unroll
  for (int k = 1; k < 12; k++) wg_ss96<1>(D, da + (k / 3) * 384 + (k % 3) * 16, db + k * 64);
  wg_commit();
}
__device__ __forceinline__ void store_proj(const float (&D)[48], const CUtensorMap* m, uint32_t st, uint32_t sta, int row, int col, int ch) {
#pragma unroll
  for (int q = 0; q < 6; q++)
    stsm4((sta ^ ((q & 1) * 32)) + (q >> 1) * 1024,
          pack2(D[8 * q], D[8 * q + 1]), pack2(D[8 * q + 2], D[8 * q + 3]), pack2(D[8 * q + 4], D[8 * q + 5]), pack2(D[8 * q + 6], D[8 * q + 7]));
  fence_async();
  __syncwarp();
  if ((threadIdx.x & 31) == 0) {
    asm volatile("cp.async.bulk.tensor.4d.global.shared::cta.bulk_group [%0, {%2,%3,%4,%5}], [%1];" ::"l"(m), "r"(st), "r"(0), "r"(row), "r"(col), "r"(ch) : "memory");
    asm volatile("cp.async.bulk.commit_group;" ::: "memory");
  }
  __syncwarp();
}

__device__ __forceinline__ float fold(float a, float b, float t, int useb) {
  float r;
  asm("{\n.reg .pred p;\nsetp.ne.b32 p, %4, 0;\nfma.rn.f32 %0, %1, 0f3E553B95, %3;\n@p fma.rn.f32 %0, %2, 0f3E553B95, %3;\n}"
      : "=&f"(r) : "f"(a), "f"(b), "f"(t), "r"(useb));
  return r;
}
template <int U, int L>
__device__ __forceinline__ void softmax_tile(const float (&SA)[56], const float (&SB)[56], const float (&T)[16], int b0, int b1,
                                             uint32_t (&P)[28], float (&sx)[8]) {
  float lu[14], ll[14];
#pragma unroll
  for (int j = 0; j < 7; j++) {
    constexpr int sh = U == L ? 2 : 0;
    const float tu0 = T[2 * j + sh], tu1 = T[2 * j + 1 + sh], tl0 = T[2 * j], tl1 = T[2 * j + 1];
    lu[2 * j]     = fold(SA[4 * (U + j)],     SB[4 * (U + j)],     tu0, b0);
    ll[2 * j]     = fold(SA[4 * (L + j) + 2], SB[4 * (L + j) + 2], tl0, b0);
    lu[2 * j + 1] = fold(SA[4 * (U + j) + 1], SB[4 * (U + j) + 1], tu1, b1);
    ll[2 * j + 1] = fold(SA[4 * (L + j) + 3], SB[4 * (L + j) + 3], tl1, b1);
  }
  float mu = lu[0], ml = ll[0], mu2 = lu[1], ml2 = ll[1];
#pragma unroll
  for (int j = 1; j < 7; j++) { mu = fmaxf(mu, lu[2 * j]); mu2 = fmaxf(mu2, lu[2 * j + 1]); ml = fmaxf(ml, ll[2 * j]); ml2 = fmaxf(ml2, ll[2 * j + 1]); }
  mu = fmaxf(mu, mu2); ml = fmaxf(ml, ml2);
  { const float a1 = __shfl_xor_sync(0xffffffffu, mu, 1), a2 = __shfl_xor_sync(0xffffffffu, mu, 2), a3 = __shfl_xor_sync(0xffffffffu, mu, 3);
    const float c1 = __shfl_xor_sync(0xffffffffu, ml, 1), c2 = __shfl_xor_sync(0xffffffffu, ml, 2), c3 = __shfl_xor_sync(0xffffffffu, ml, 3);
    mu = fmaxf(fmaxf(mu, a1), fmaxf(a2, a3)); ml = fmaxf(fmaxf(ml, c1), fmaxf(c2, c3)); }
  float su = 0.f, sl = 0.f;
#pragma unroll
  for (int c = 0; c < 14; c++) {
    const int iu = (c >> 1) * 4 + (c & 1) * 2;
    if (c >= U && c < U + 7) {
      float e0 = ex2(lu[2 * (c - U)] - mu), e1 = ex2(lu[2 * (c - U) + 1] - mu);
      su = c == U ? e0 + e1 : (su + e0) + e1; P[iu] = pack2(e0, e1);
    } else P[iu] = 0u;
    if (c >= L && c < L + 7) {
      float e0 = ex2(ll[2 * (c - L)] - ml), e1 = ex2(ll[2 * (c - L) + 1] - ml);
      sl = c == L ? e0 + e1 : (sl + e0) + e1; P[iu + 1] = pack2(e0, e1);
    } else P[iu + 1] = 0u;
  }
  sx[0] = su; sx[4] = sl;
#pragma unroll
  for (int k = 1; k < 4; k++) { sx[k] = __shfl_xor_sync(0xffffffffu, su, k); sx[4 + k] = __shfl_xor_sync(0xffffffffu, sl, k); }
}

struct Maps { CUtensorMap xc, xh, w, os, wo, ot; };

__global__ void __cluster_dims__(4, 1, 1) __launch_bounds__(512, 1)
na_attn_kernel(const __nv_bfloat16* __restrict__ x, const __nv_bfloat16* __restrict__ wqkv, const __nv_bfloat16* __restrict__ rpb, const __grid_constant__ Maps mp) {
  extern __shared__ __align__(1024) uint8_t smem_raw[];
  const uint32_t sb = smem_u32(smem_raw);
  if ((sb & 0x3FFFF) != SBC) return;
  const uint32_t bar = sb + SM_BAR;
  TR2(blockIdx.x, 0);
  const int tid = threadIdx.x, lane = tid & 31;
  const int warp = __shfl_sync(0xffffffffu, tid >> 5, 0);
  const int head = blockIdx.x & 3, cl = blockIdx.x >> 2;
  const int par = cl / 7, strip = cl - par * 7, ph = par >> 1, pw = par & 1;

  uint4 wv[2 * NL];
  const int va = head == 1;
  const uint32_t wdst = sb + SM_W + (va + ((tid >> 1) & 1)) * 6144 + (tid >> 2) * 32 + ((tid ^ (tid >> 4)) & 1) * 16;
  if (warp < 12) asm volatile("barrier.cluster.arrive.relaxed.aligned;" ::: "memory");
  {
    const uint32_t wo0 = (tid >> 2) * 1152 + head * 96 + va * 32 + (tid & 3) * 16;
#pragma unroll
    for (int i = 0; i < 2 * NL; i++)
      asm volatile("{\n.reg .pred p;\nsetp.lt.u32 p, %5, 384;\n@p ld.global.nc.v4.b32 {%0,%1,%2,%3}, [%4];\n}"
                   : "=r"(wv[i].x), "=r"(wv[i].y), "=r"(wv[i].z), "=r"(wv[i].w)
                   : "l"(reinterpret_cast<const uint8_t*>(wqkv) + wo0 + (i & 1) * 96 * 1152 + ((i / 2 + 1) % 3) * 384), "r"(tid));
  }
  if (warp < 8) {
    asm volatile("setmaxnreg.inc.sync.aligned.u32 %0;" ::"n"(RA));
    float rv = -INFINITY;
    if (tid < 169) rv = __bfloat162float(rpb[head * 169 + tid]) * 1.4426950408889634f;
    if (tid < 192) {
      const int kc = (tid & 15) + 3, wc = (tid >> 4) % 6;
      sts128(tid < 96 ? sb + SM_K + kc * KS + wc * 128 + 48 : sb + SM_V + kc * 1536 + wc * 128 + (6 + (kc & 1)) * 16, make_uint4(0, 0, 0, 0));
    }
#pragma unroll
    for (int i = 0; i < 2 * NL; i++) sts128(wdst + (i & 1) * 3072 + (i / 2) * 18432, wv[i]);
    fence_async();
    asm volatile("bar.arrive 1, 384;" ::: "memory");
    if (tid < 182) asm volatile("st.shared.f32 [%0], %1;" ::"r"(sb + SM_RPB + tid * 4), "f"(rv) : "memory");
    const int j = warp >> 2, w = warp & 3;
    int variant = w;
    if (strip == 0 && j == 0 && w < 2) variant = 4;
    if (strip == 6 && j == 1 && w >= 2) variant = 5;
    const uint32_t qa = sb + SM_Q + (8 * j + 2 * w + ((lane >> 3) & 1)) * 1536 + (lane >> 4) * 256 + (((lane & 7) * 16) ^ (((lane >> 3) & 1) * 64));
    uint32_t oa = sb + SM_O + j * 6144 + (2 * w + ((lane >> 3) & 1)) * 768 + (lane >> 4) * 128 + (lane & 7) * 16;
    const uint64_t dK = mkdesc(SBC + SM_K, 128, KS, 0) + j * (8 * KS / 16);
    const uint64_t dV = mkdesc(SBC + SM_V, 768, 128, 0) + j * (8 * 1536 / 16);
    asm volatile("barrier.cluster.wait.aligned;" ::: "memory");
    asm volatile("bar.sync 3, 256;" ::: "memory");
    float T[16];
    TRDECL;
    int b0 = 0, b1 = 0;
    uint32_t meta = 0, ob = bar + B_ODONE * 8;
    uint32_t q[12];
    mbar_wait(bar + B_Q0 * 8, 0);
#pragma unroll
    for (int k = 0; k < 3; k++) ldsm4(qa + k * 512, q[4 * k], q[4 * k + 1], q[4 * k + 2], q[4 * k + 3]);
#pragma unroll 1
    for (int b = 0; b < 14; b++) {
      const uint32_t pa = b & 1;
      float SA[56], SB[56];
      const uint64_t dA = dK + pa * (KSLOT >> 4), dB = dK + (pa ^ 1) * (KSLOT >> 4);
      TR(0, b, 0);
      nb_sync(N_KRDY + j, 256);
      TR(0, b, 1);
      TR(0, b - 1, 9);
      wg_fence();
      wg_rs112<0>(SA, q[0], q[1], q[2], q[3], dA);
      wg_rs112<0>(SB, q[0], q[1], q[2], q[3], dB);
      wg_rs112<1>(SA, q[4], q[5], q[6], q[7], dA + 16);
      wg_rs112<1>(SB, q[4], q[5], q[6], q[7], dB + 16);
      wg_rs112<1>(SA, q[8], q[9], q[10], q[11], dA + 32);
      wg_rs112<1>(SB, q[8], q[9], q[10], q[11], dB + 32);
      wg_commit();
      nb_arrive(N_QK0 + j, 256);
      TR(0, b, 2);
      if (b <= 1 || b == 13) {
        uint32_t ln; asm volatile("mov.u32 %0, %%laneid;" : "=r"(ln));
        const int g = ln >> 2, t = ln & 3;
        const int sw = b == 0 ? max(g + 1, 4) : (b == 13 ? min(g + 1, 5) : g + 1);
        const int i0 = 2 * t, i1 = 2 * t + 1;
        b0 = i0 <= sw - 2; b1 = i1 <= sw - 2;
        const uint32_t tb = sb + SM_RPB + (variant < 4 ? 3 : variant + 1 - 2 * w) * 4;
        const uint32_t ra0 = tb + (i0 == sw - 1 ? 13 : i0 + 8 * b0 - g + 2) * 52;
        const uint32_t ra1 = tb + (i1 == sw - 1 ? 13 : i1 + 8 * b1 - g + 2) * 52;
#pragma unroll
        for (int jj = 0; jj < 8; jj++) { T[2 * jj] = lds_f32(ra0 + jj * 4); T[2 * jj + 1] = lds_f32(ra1 + jj * 4); }
        meta = ((0x5555u & ((1u << (2 * (sw - 1))) - 1)) ^ 0xDD88u ^ (((t ^ b) & 1) ? 0x5555u : 0u)) * 0x10001u;
      } else meta ^= 0x55555555u;
      if (b == TB) ob = bar + (B_OTAIL + j) * 8;
      if (b >= 12) oa += b == 12 ? warp * 1536 - (SM_O - SM_Q) : 1536;
      wg_wait<0>(); pin(SA); pin(SB);
      mbar_arrive_elect(bar + B_KFREE * 8);
      TR(0, b, 3);
      TR(0, b - 1, 10);
      uint32_t P[28];
      float sx[8];
      switch (variant) {
        case 0: softmax_tile<0, 1>(SA, SB, T, b0, b1, P, sx); break;
        case 1: softmax_tile<2, 3>(SA, SB, T, b0, b1, P, sx); break;
        case 2: softmax_tile<4, 5>(SA, SB, T, b0, b1, P, sx); break;
        case 3: softmax_tile<6, 7>(SA, SB, T, b0, b1, P, sx); break;
        case 4: softmax_tile<3, 3>(SA, SB, T, b0, b1, P, sx); break;
        default: softmax_tile<4, 4>(SA, SB, T, b0, b1, P, sx); break;
      }
      float O[24];
      TR(0, b, 4);
      nb_sync(N_VQ0 + j, 288);
      TR(0, b, 5);
#pragma unroll
      for (int k = 0; k < 3; k++) ldsm4(qa + (pa ^ 1) * 128 + k * 512, q[4 * k], q[4 * k + 1], q[4 * k + 2], q[4 * k + 3]);
      wg_fence();
      wg_sp48<0>(O, P[0], P[1], P[2], P[3], dV, meta);
#pragma unroll
      for (int s = 1; s < 7; s++) wg_sp48<1>(O, P[4 * s], P[4 * s + 1], P[4 * s + 2], P[4 * s + 3], dV + s * 192, meta);
      wg_commit();
      nb_arrive(N_PVISS, 384);
      TR(0, b, 6);
      wg_wait<0>(); pin(O);
      mbar_arrive_elect(bar + B_VFREE * 8);
      TR(0, b, 7);
      float ru, rl;
      asm("rcp.approx.ftz.f32 %0, %1;" : "=f"(ru) : "f"(((fmaf(O[0], 0.f, sx[0]) + sx[1]) + sx[2]) + sx[3]));
      asm("rcp.approx.ftz.f32 %0, %1;" : "=f"(rl) : "f"(((fmaf(O[2], 0.f, sx[4]) + sx[5]) + sx[6]) + sx[7]));
#pragma unroll
      for (int i = 0; i < 3; i++)
        stsm4(oa + i * 256, pack2(O[8 * i] * ru, O[8 * i + 1] * ru), pack2(O[8 * i + 2] * rl, O[8 * i + 3] * rl),
              pack2(O[8 * i + 4] * ru, O[8 * i + 5] * ru), pack2(O[8 * i + 6] * rl, O[8 * i + 7] * rl));
      publish(ob);
      TR(0, b, 8);
    }
    if (elect_one()) {
#pragma unroll
      for (int d = 0; d < 2; d++)
        send_o<1536>(sb + SM_X0 + head * 6144 + (2 * j + (w & 1)) * 1536, sb + SM_Q + warp * 3072 + 1536, bar + (B_TIN + 2) * 8, (w & 2) + (d ^ (head & 1)));
    }
    __syncwarp();
    TRDUMP;
    cluster_sync();
  } else if (warp < 12) {
    TRDECL;
    TR(2, -3, 0);
    asm volatile("setmaxnreg.inc.sync.aligned.u32 %0;" ::"n"(RG));
    TR(2, -3, 1);
    GemmCtx c;
    c.bar = bar;
    const int gw = warp - 8, tk = gw * 16 + (lane & 15), hi = lane >> 4;
    { const int col = tk >> 2, i = tk & 3;
      c.kC = sb + SM_K + (col + 3) * KS + hi * 128 + i * 16;
      c.vC[0] = sb + SM_V + (col + 3) * 1536 + hi * 128 + (2 * i + ((col + 3) & 1)) * 16;
      c.qC[0] = sb + SM_Q + col * 1536 + hi * 256 + (col & 1) * 64 + i * 16; }
    { const int ci = (tk >> 3) - 2, kc = ci < 3 ? ci : ci + 16, i = tk & 7; c.hvalid = gw > 0;
      c.kH = sb + SM_K + kc * KS + hi * 128 + i * 16;
      c.vH[0] = sb + SM_V + kc * 1536 + hi * 128 + (i >> 2) * 768 + (2 * (i & 3) + ((kc ^ (i >> 2)) & 1)) * 16; }
    c.never = x == nullptr;
    c.kC = __shfl_sync(0xffffffffu, c.kC, lane); c.kH = __shfl_sync(0xffffffffu, c.kH, lane);
    c.vC[1] = __shfl_sync(0xffffffffu, c.vC[0] ^ 16, lane); c.vC[0] = __shfl_sync(0xffffffffu, c.vC[0], lane);
    c.vH[1] = __shfl_sync(0xffffffffu, c.vH[0] ^ 16, lane); c.vH[0] = __shfl_sync(0xffffffffu, c.vH[0], lane);
    c.qC[1] = __shfl_sync(0xffffffffu, c.qC[0] ^ 64, lane); c.qC[0] = __shfl_sync(0xffffffffu, c.qC[0], lane);
    c.spin = 0;
    c.hiA = (uint32_t)(mkdesc(0, 0, 1024, 1) >> 32) + (blockIdx.x >> 16); c.hiB = (uint32_t)(mkdesc(0, 0, 256, 3) >> 32) + (blockIdx.x >> 16);
    asm volatile("barrier.cluster.wait.aligned;" ::: "memory");
    TR(2, -3, 2);
#pragma unroll
    for (int i = 0; i < 2 * NL; i++) sts128(wdst + (i & 1) * 3072 + (i / 2) * 18432, wv[i]);
    fence_async();
    TR(2, -3, 3);
    asm volatile("bar.sync 1, 384;" ::: "memory");
    TR(2, -3, 4);
    mbar_wait(bar + B_WK * 8, 0);
    TR(2, -3, 5);
    uint32_t pk[12], pv[12], pq[12];
    gemm_iter<true, false, 0>(c, -2, pk, pv, pq, &mp.wo TRPASS);
    TR2(blockIdx.x, 4);
#pragma unroll 1
    for (int b = -1;; b += 2) {
      gemm_iter<false, false, 1>(c, b, pk, pv, pq, &mp.wo TRPASS);
      if (b == 11) break;
      gemm_iter<false, false, 0>(c, b + 1, pk, pv, pq, &mp.wo TRPASS);
    }
    TR2(blockIdx.x, 6);
    gemm_iter<false, true, 0>(c, 12, pk, pv, pq, &mp.wo TRPASS);
    TR(2, 13, 0);
    mbar_wait(bar + B_WO * 8, 0);
    mbar_wait(bar + B_TIN * 8, 0);
    const uint32_t st = sb + gw * 3072;
    const uint32_t sta = st + (lane & 15) * 64 + ((hi ^ ((lane >> 1) & 3)) * 16);
    const int oc = ph * 112 + strip * 16 + 8 * (gw >> 1) + 4 * (head >> 1) + 2 * (gw & 1), och = pw * 6 + (head & 1) * 3;
    float D0[48], D1[48];
    nb_sync(N_PVISS, 384);
    issue_proj<SM_X2>(D0);
    mbar_wait(bar + (B_TIN + 1) * 8, 0);
    issue_proj<SM_X1>(D1);
    wg_wait<1>(); pin(D0);
    store_proj(D0, &mp.ot, st + SM_TST, sta + SM_TST, 8 * TB, oc, och);
    wg_wait<0>(); pin(D1);
    store_proj(D1, &mp.ot, st + SM_X2, sta + SM_X2, 8 * TB + 8, oc, och);
    mbar_wait(bar + (B_TIN + 2) * 8, 0);
    issue_proj<SM_X0>(D0);
    asm volatile("barrier.cluster.arrive.relaxed.aligned;" ::: "memory");
    wg_wait<0>(); pin(D0);
    store_proj(D0, &mp.ot, st + SM_X2 + 12288, sta + SM_X2 + 12288, 8 * TB + 16, oc, och);
    TR(2, 13, 7);
    if (lane == 0) asm volatile("cp.async.bulk.wait_group.read 0;" ::: "memory");
    __syncwarp();
    TR(2, 13, 8);
    TR2(blockIdx.x, 2);
    TRDUMP;
    asm volatile("barrier.cluster.wait.aligned;" ::: "memory");
  } else {
    if (warp == 12) {
      if (elect_one()) {
        mbar_init(bar + B_WK * 8, 1);
#pragma unroll
        for (int i = 0; i < NL; i++) load_w(&mp.w, sb + SM_W + (3 * i + 2 - 2 * va) * 6144, bar + B_WK * 8, ((i + 1) % 3) * 192 + head * 48 + 32 - 32 * va);
        asm volatile("prefetch.tensormap [%0];" ::"l"(head ? &mp.xc : &mp.xh) : "memory");
        mbar_expect(bar + B_WK * 8, NL * 6144);
      }
    } else if (warp == 15) {
      const int col = min(max(strip * 16 - 3 + min(lane, 21), 0), 111);
      const uint8_t* p = reinterpret_cast<const uint8_t*>(x) + (uint32_t)(head * ROWB + (ph * 112 + col) * 768 + pw * 384);
#pragma unroll
      for (int i = 0; i < 3; i++) asm volatile("prefetch.global.L2 [%0];" ::"l"(p + i * 128));
    } else if (elect_one()) {
      if (warp == 13) {
#pragma unroll
        for (int i = 0; i < B_WK; i++) mbar_init(bar + i * 8, i < B_EMPTY ? 1 : (i < B_TIN ? 16 : (i < B_TFREE ? 1 : 16)));
      } else {
#pragma unroll
        for (int i = B_WQ; i < B_COUNT; i++) mbar_init(bar + i * 8, i < B_Q0 ? 1 : (i < B_ODONE ? 4 : 8));
      }
    }
    asm volatile("fence.mbarrier_init.release.cluster;" ::: "memory");
    __syncwarp();
    asm volatile("barrier.cluster.arrive.relaxed.aligned;" ::: "memory");
    asm volatile("setmaxnreg.dec.sync.aligned.u32 24;");
    asm volatile("griddepcontrol.launch_dependents;");
    const int cc = ph * 112 + (head ? strip * 16 : (strip == 0 ? 16 : (strip == 6 ? 74 : strip * 16 - 3)));
    const int sd = strip == 0 ? -1 : (strip == 6 ? 1 : 0);
    const int r0 = head == 0 ? -4 : (head == 1 ? 4 : 0);
    asm volatile("barrier.cluster.wait.aligned;" ::: "memory");
    if (warp == 12) {
      const uint32_t fb = bar + (B_FULL + head) * 8, eb = bar + (B_EMPTY + head) * 8;
      const uint32_t dst = sb + (head == 0 ? SM_X0 : (head == 1 ? SM_X1 : SM_X2));
      const int nl = head == 0 ? 15 : (head == 3 ? 1 : 14);
#pragma unroll 1
      for (int n = 0; n < nl; n++) {
        if (n) mbar_wait(eb, (n - 1) & 1);
        if (lane < 4 && head < 3)
          asm volatile("{\n.reg .b32 ra;\nmapa.shared::cluster.u32 ra, %0, %1;\nmbarrier.arrive.expect_tx.shared::cluster.b64 _, [ra], %2;\n}"
                       ::"r"(fb), "r"(lane), "r"(head ? 24576 : 18432) : "memory");
        __syncwarp();
        if (elect_one()) {
          if (head == 0) {
            asm volatile("cp.async.bulk.tensor.5d.shared::cluster.global.mbarrier::complete_tx::bytes.multicast::cluster [%0], [%1, {%3,%4,%5,%6,%7}], [%2], %8;"
                         ::"r"(dst), "l"(&mp.xh), "r"(fb), "r"(0), "r"(8 * n + r0), "r"(cc), "r"(sd), "r"(pw * 3), "h"((uint16_t)15) : "memory");
          } else if (head < 3) {
            asm volatile("cp.async.bulk.tensor.4d.shared::cluster.global.mbarrier::complete_tx::bytes.multicast::cluster [%0], [%1, {%3,%4,%5,%6}], [%2], %7;"
                         ::"r"(dst), "l"(&mp.xc), "r"(fb), "r"(0), "r"(8 * n + r0), "r"(cc), "r"(pw * 3), "h"((uint16_t)15) : "memory");
          }
          if (n == 0) {
#pragma unroll
            for (int i = 0; i < 3; i++) load_w(&mp.w, sb + SM_W + (6 + i) * 6144, bar + B_WQ * 8, head * 48 + i * 16);
            mbar_expect(bar + B_WQ * 8, 18432);
            mbar_expect(bar + B_TIN * 8, 24576); mbar_expect(bar + (B_TIN + 1) * 8, 24576); mbar_expect(bar + (B_TIN + 2) * 8, 24576);
          }
          if (!head && n + 1 < nl) asm volatile("cp.async.bulk.prefetch.tensor.5d.L2.global [%0, {%1,%2,%3,%4,%5}];" ::"l"(&mp.xh), "r"(0), "r"(8 * n + 8 + r0), "r"(cc), "r"(sd), "r"(pw * 3) : "memory");
          if (head && n + 1 < nl) asm volatile("cp.async.bulk.prefetch.tensor.4d.L2.global [%0, {%1,%2,%3,%4}];" ::"l"(&mp.xc), "r"(0), "r"(8 * n + 8 + r0), "r"(cc), "r"(pw * 3) : "memory");
        }
        __syncwarp();
      }
    }
    if (warp == 14) {
      int* flag = g_flags + cl * 2;
      nb_arrive(N_VQ0, 288); nb_arrive(N_VQ1, 288);
#pragma unroll 1
      for (int b = 0; b < TB; b++) {
        mbar_wait(bar + B_ODONE * 8, b & 1);
        if (lane == 0) {
          asm volatile("cp.async.bulk.tensor.3d.global.shared::cta.bulk_group [%0, {%2,%3,%4}], [%1];"
                       ::"l"(&mp.os), "r"(sb + SM_O), "r"(pw * 192), "r"(8 * b + 2 * head), "r"(ph * 112 + strip * 16) : "memory");
          asm volatile("cp.async.bulk.commit_group;\ncp.async.bulk.wait_group 0;" ::: "memory");
        }
        __syncwarp();
        nb_arrive(N_VQ0, 288); nb_arrive(N_VQ1, 288);
        if (lane == 0)
          asm volatile("fence.proxy.async.global;\nfence.acq_rel.gpu;\nred.relaxed.gpu.global.add.s32 [%0], 1;\nred.relaxed.gpu.global.add.s32 [%0+4], 1;"
                       ::"l"(flag + b * 56) : "memory");
        __syncwarp();
      }
    } else if (warp & 1) {
      const int j = (warp >> 1) & 1;
#pragma unroll 1
      for (int i = 0; i < 2; i++) {
        mbar_wait(bar + (B_OTAIL + j) * 8, i);
        if (i == 0) nb_arrive(N_VQ0 + j, 288);
        mbar_wait(bar + (B_TFREE + i) * 8, 0);
        if (i == 1) nb_arrive(N_VQ0 + j, 288);
        if (elect_one()) {
#pragma unroll 1
          for (int d = 0; d < 8; d++) {
            const int dst = (d + head) & 3, pc = d >> 2;
            send_o<1536>(sb + (i ? SM_X1 : SM_X2) + head * 6144 + j * 3072 + pc * 1536,
                         sb + (i ? SM_Q : SM_O) + (4 * j + (dst & 2) + pc) * (i ? 3072 : 1536), bar + (B_TIN + i) * 8, dst);
          }
        }
        __syncwarp();
      }
    }
    cluster_sync();
  }
}

constexpr int NSTB = 6;
constexpr int NTB = TB * 56;
constexpr int SM_B_IN = 0;
constexpr int SM_B_W = SM_B_IN + NSTB * 24576;
constexpr int SM_B_BAR = SM_B_W + 73728;
constexpr int SM_B_TOTAL = SM_B_BAR + 128;
struct MapsB { CUtensorMap oi, oo, wo; };

__global__ void __launch_bounds__(480, 1)
na_proj_kernel(const __grid_constant__ MapsB mp) {
  extern __shared__ __align__(1024) uint8_t smem_raw[];
  const uint32_t sb = smem_u32(smem_raw);
  if ((sb & 0x3FFFF) != SBC) return;
  const uint32_t bar = sb + SM_B_BAR;
  const int tid = threadIdx.x, lane = tid & 31;
  const int warp = __shfl_sync(0xffffffffu, tid >> 5, 0);
  TR2(132 + blockIdx.x, 0);
  TRB(47, 0);
  if (warp == 12 && elect_one()) {
#pragma unroll
    for (int i = 0; i <= 2 * NSTB; i++) mbar_init(bar + i * 8, i < NSTB || i == 2 * NSTB ? 1 : 4);
    mbar_expect(bar + 2 * NSTB * 8, 73728);
#pragma unroll
    for (int i = 0; i < 2; i++)
      asm volatile("cp.async.bulk.tensor.3d.shared::cluster.global.mbarrier::complete_tx::bytes [%0], [%1, {%3,%4,%5}], [%2];"
                   ::"r"(sb + SM_B_W + i * 36864), "l"(&mp.wo), "r"(bar + 2 * NSTB * 8), "r"(0), "r"(0), "r"(i * 3) : "memory");
  }
  __syncthreads();
  const int step = gridDim.x;
  if (warp >= 12) {
    const int wg = warp - 12;
    int use = 0;
#pragma unroll 1
    for (int n = blockIdx.x + wg * step; n < NTB; n += 3 * step, use++) {
      const int b = n / 56, rem = n - b * 56, par = rem / 14, sg = wg + 3 * (use & 1);
      int v; uint32_t spin = 0;
      do { asm volatile("ld.acquire.gpu.global.s32 %0, [%1];" : "=r"(v) : "l"(g_flags + n) : "memory"); if ((OPT & 1) && v < 4) __nanosleep(200); } while (v < 4 && ++spin < SPIN_LIMIT);
      TRB(use * 3 + wg, 0);
      asm volatile("fence.proxy.async.global;" ::: "memory");
      if (use >= 2) mbar_wait(bar + (NSTB + sg) * 8, ((use >> 1) - 1) & 1);
      TRB(use * 3 + wg, 1);
      if (elect_one()) {
        mbar_expect(bar + sg * 8, 24576);
        asm volatile("cp.async.bulk.tensor.3d.shared::cluster.global.mbarrier::complete_tx::bytes [%0], [%1, {%3,%4,%5}], [%2];"
                     ::"r"(sb + SM_B_IN + sg * 24576), "l"(&mp.oi), "r"(bar + sg * 8), "r"((par & 1) * 192), "r"(8 * b), "r"((par >> 1) * 112 + (rem - par * 14) * 8) : "memory");
        g_flags[n] = 0;
      }
      __syncwarp();
    }
  } else {
    const int wg = warp >> 2, w = warp & 3;
    constexpr uint64_t db = mkdesc(SBC + SM_B_W, 12288, 512, 2);
    const uint32_t sta0 = sb + SM_B_IN + w * 6144 + (lane & 15) * 128 + (((lane >> 4) ^ (lane & 7)) * 16);
    mbar_wait(bar + 2 * NSTB * 8, 0);
    TRB(47, 1);
    int use = 0;
#pragma unroll 1
    for (int n = blockIdx.x + wg * step; n < NTB; n += 3 * step, use++) {
      const int b = n / 56, rem = n - b * 56, par = rem / 14, sg = wg + 3 * (use & 1);
      const uint64_t da = mkdesc(SBC + SM_B_IN, 128, 3072, 0) + sg * (24576 / 16);
      float D[96];
      mbar_wait(bar + sg * 8, (use >> 1) & 1);
      if (use | wg) nb_sync(4 + wg, 256);
      TRB(use * 3 + wg, 3);
      wg_fence();
      wg_ss192<0>(D, da, db);
#pragma unroll
      for (int k = 1; k < 12; k++) wg_ss192<1>(D, da + k * 16, db + k * 64);
      wg_commit();
      if (n + step < NTB) nb_arrive(wg == 2 ? 4 : 5 + wg, 256);
      TRB(use * 3 + wg, 4);
      if (use && lane == 0) {
        asm volatile("cp.async.bulk.wait_group.read 0;" ::: "memory");
        mbar_arrive(bar + (NSTB + wg + 3 * (~use & 1)) * 8);
      }
      __syncwarp();
      wg_wait<0>(); pin(D);
      nb_sync(1 + wg, 128);
      TRB(use * 3 + wg, 5);
      const uint32_t sta = sta0 + sg * 24576;
#pragma unroll
      for (int q = 0; q < 12; q++)
        stsm4((sta ^ ((q & 3) * 32)) + (q >> 2) * 2048,
              pack2(D[8 * q], D[8 * q + 1]), pack2(D[8 * q + 2], D[8 * q + 3]), pack2(D[8 * q + 4], D[8 * q + 5]), pack2(D[8 * q + 6], D[8 * q + 7]));
      fence_async();
      __syncwarp();
      if (lane == 0) {
        asm volatile("cp.async.bulk.tensor.4d.global.shared::cta.bulk_group [%0, {%2,%3,%4,%5}], [%1];"
                     ::"l"(&mp.oo), "r"(sb + SM_B_IN + sg * 24576 + w * 6144), "r"(0), "r"(8 * b), "r"((par >> 1) * 112 + (rem - par * 14) * 8 + 2 * w), "r"((par & 1) * 3) : "memory");
        asm volatile("cp.async.bulk.commit_group;" ::: "memory");
      }
      __syncwarp();
      TRB(use * 3 + wg, 6);
    }
    if (lane == 0) asm volatile("cp.async.bulk.wait_group 0;" ::: "memory");
    TR2(132 + blockIdx.x, 2);
  }
}

typedef CUresult (*EncodeFn)(CUtensorMap*, CUtensorMapDataType, cuuint32_t, void*, const cuuint64_t*, const cuuint64_t*, const cuuint32_t*,
                             const cuuint32_t*, CUtensorMapInterleave, CUtensorMapSwizzle, CUtensorMapL2promotion, CUtensorMapFloatOOBfill);
static EncodeFn g_enc = nullptr;
static void make_map(CUtensorMap* m, const void* p, int rank, const cuuint64_t* dim, const cuuint64_t* str, const cuuint32_t* box, CUtensorMapSwizzle sw) {
  const cuuint32_t ones[5] = {1, 1, 1, 1, 1};
  g_enc(m, CU_TENSOR_MAP_DATA_TYPE_BFLOAT16, rank, (void*)p, dim, str, box, ones, CU_TENSOR_MAP_INTERLEAVE_NONE, sw,
        CU_TENSOR_MAP_L2_PROMOTION_L2_128B, CU_TENSOR_MAP_FLOAT_OOB_FILL_NONE);
}

extern "C" void kernel_launch(void* const* d_in, const int* in_sizes, int n_in, void* d_out, int out_size) {
  const __nv_bfloat16* x = (const __nv_bfloat16*)d_in[0];
  const __nv_bfloat16* wqkv = (const __nv_bfloat16*)d_in[1];
  const __nv_bfloat16* wo = (const __nv_bfloat16*)d_in[2];
  const __nv_bfloat16* rpb = (const __nv_bfloat16*)d_in[3];

  if (!g_enc) {
    void* fn = nullptr; cudaDriverEntryPointQueryResult qr;
    cudaGetDriverEntryPoint("cuTensorMapEncodeTiled", &fn, cudaEnableDefault, &qr);
    g_enc = (EncodeFn)fn;
    cudaFuncSetAttribute(na_attn_kernel, cudaFuncAttributeMaxDynamicSharedMemorySize, SM_A_TOTAL);
    cudaFuncSetAttribute(na_proj_kernel, cudaFuncAttributeMaxDynamicSharedMemorySize, SM_B_TOTAL);
  }
  Maps ma; MapsB mb;
  { cuuint64_t dim[4] = {64, 112, 224, 6}, str[3] = {(cuuint64_t)ROWB, 768, 128};
    cuuint32_t box[4] = {64, 4, 16, 3}, boxo[4] = {64, 8, 2, 3};
    make_map(&ma.xc, x, 4, dim, str, box, CU_TENSOR_MAP_SWIZZLE_128B);
    make_map(&mb.oo, d_out, 4, dim, str, boxo, CU_TENSOR_MAP_SWIZZLE_128B); }
  { cuuint64_t dim[5] = {64, 112, 224, 2, 6}, str[4] = {(cuuint64_t)ROWB, 768, 19 * 768, 128};
    cuuint32_t box[5] = {64, 8, 3, 2, 3};
    make_map(&ma.xh, x, 5, dim, str, box, CU_TENSOR_MAP_SWIZZLE_128B); }
  { cuuint64_t dim[3] = {384, 112, 224}, str[2] = {(cuuint64_t)ROWB, 768};
    cuuint32_t box[3] = {192, 8, 8}, boxs[3] = {192, 2, 16};
    make_map(&mb.oi, d_out, 3, dim, str, box, CU_TENSOR_MAP_SWIZZLE_NONE);
    make_map(&ma.os, d_out, 3, dim, str, boxs, CU_TENSOR_MAP_SWIZZLE_NONE); }
  { cuuint64_t dim[4] = {32, 112, 224, 12}, str[3] = {(cuuint64_t)ROWB, 768, 64};
    cuuint32_t box[4] = {32, 8, 2, 3};
    make_map(&ma.ot, d_out, 4, dim, str, box, CU_TENSOR_MAP_SWIZZLE_64B); }
  { cuuint64_t dim[2] = {576, 192}, str[1] = {1152};
    cuuint32_t box[2] = {16, 192};
    make_map(&ma.w, wqkv, 2, dim, str, box, CU_TENSOR_MAP_SWIZZLE_32B); }
  { cuuint64_t dim[3] = {32, 192, 6}, str[2] = {384, 64};
    cuuint32_t box[3] = {32, 192, 3};
    make_map(&ma.wo, wo, 3, dim, str, box, CU_TENSOR_MAP_SWIZZLE_64B);
    mb.wo = ma.wo; }
  na_attn_kernel<<<112, 512, SM_A_TOTAL>>>(x, wqkv, rpb, ma);
  cudaLaunchConfig_t cfg = {};
  cfg.gridDim = dim3(20); cfg.blockDim = dim3(480); cfg.dynamicSmemBytes = SM_B_TOTAL; cfg.stream = cudaStreamPerThread;
  cudaLaunchAttribute at[1];
  at[0].id = cudaLaunchAttributeProgrammaticStreamSerialization; at[0].val.programmaticStreamSerializationAllowed = 1;
  cfg.attrs = at; cfg.numAttrs = 1;
  cudaLaunchKernelEx(&cfg, na_proj_kernel, mb);
}
```

```cpp
#include <cuda_runtime.h>
#include <cuda_bf16.h>
#include <cuda.h>
#include <stdint.h>

#define SPIN_LIMIT (1u << 18)

__device__ __forceinline__ uint32_t smem_u32(const void* p) { return (uint32_t)__cvta_generic_to_shared(p); }
__device__ __forceinline__ void wg_fence() { asm volatile("wgmma.fence.sync.aligned;" ::: "memory"); }
__device__ __forceinline__ void wg_commit() { asm volatile("wgmma.commit_group.sync.aligned;" ::: "memory"); }
template <int N> __device__ __forceinline__ void wg_wait() { asm volatile("wgmma.wait_group.sync.aligned %0;" ::"n"(N) : "memory"); }
template <int N> __device__ __forceinline__ void pin(float (&d)[N]) {
#pragma unroll
  for (int i = 0; i < N; i++) asm volatile("" : "+f"(d[i])::"memory");
}
__host__ __device__ constexpr uint64_t mkdesc(uint32_t addr, uint32_t lbo, uint32_t sbo, uint32_t sw) {
  return (uint64_t)((addr & 0x3FFFF) >> 4) | ((uint64_t)(lbo >> 4) << 16) | ((uint64_t)(sbo >> 4) << 32) | ((uint64_t)sw << 62);
}
__device__ __forceinline__ void mbar_init(uint32_t bar, uint32_t cnt) { asm volatile("mbarrier.init.shared::cta.b64 [%0], %1;" ::"r"(bar), "r"(cnt) : "memory"); }
__device__ __forceinline__ void mbar_arrive(uint32_t bar) { asm volatile("mbarrier.arrive.shared::cta.b64 _, [%0];" ::"r"(bar) : "memory"); }
__device__ __forceinline__ bool elect_one() {
  uint32_t r; asm volatile("{\n.reg .pred p;\nelect.sync _|p, 0xffffffff;\nselp.u32 %0, 1, 0, p;\n}" : "=r"(r)); return r;
}
__device__ __forceinline__ void mbar_arrive_elect(uint32_t bar) {
  asm volatile("{\n.reg .pred p;\nelect.sync _|p, 0xffffffff;\n@p mbarrier.arrive.shared::cta.b64 _, [%0];\n}" ::"r"(bar) : "memory");
}
__device__ __forceinline__ void mbar_expect(uint32_t bar, uint32_t bytes) { asm volatile("mbarrier.arrive.expect_tx.shared::cta.b64 _, [%0], %1;" ::"r"(bar), "r"(bytes) : "memory"); }
__device__ __forceinline__ void mbar_arrive_remote(uint32_t bar, uint32_t cta) {
  asm volatile("{\n.reg .b32 ra;\nmapa.shared::cluster.u32 ra, %0, %1;\nmbarrier.arrive.relaxed.cluster.shared::cluster.b64 _, [ra];\n}" ::"r"(bar), "r"(cta) : "memory");
}
__device__ __forceinline__ void mbar_wait(uint32_t bar, uint32_t parity) {
  asm volatile("{\n.reg .pred p;\n.reg .b32 n;\nmov.b32 n, 0;\nWL:\nmbarrier.try_wait.parity.shared::cta.b64 p, [%0], %1;\n@p bra WD;\n"
               "add.u32 n, n, 1;\nsetp.lt.u32 p, n, 65536;\n@p bra WL;\nWD:\n}" ::"r"(bar), "r"(parity) : "memory");
}
__device__ __forceinline__ void nb_sync(int id, int n) { asm volatile("bar.sync %0, %1;" ::"r"(id), "r"(n) : "memory"); }
__device__ __forceinline__ void nb_arrive(int id, int n) { asm volatile("bar.arrive %0, %1;" ::"r"(id), "r"(n) : "memory"); }
__device__ __forceinline__ uint32_t opq(uint32_t x) { uint32_t r; asm volatile("mov.b32 %0, %1;" : "=r"(r) : "r"(x)); return r; }
__device__ __forceinline__ uint64_t opq(uint64_t x) { uint64_t r; asm volatile("mov.b64 %0, %1;" : "=l"(r) : "l"(x)); return r; }
__device__ __forceinline__ void fence_async() { asm volatile("fence.proxy.async.shared::cta;" ::: "memory"); }
__device__ __forceinline__ void cluster_sync() {
  asm volatile("barrier.cluster.arrive.relaxed.aligned;\nbarrier.cluster.wait.aligned;" ::: "memory");
}
__device__ __forceinline__ uint32_t pack2(float lo, float hi) {
  uint32_t r; asm("cvt.rn.bf16x2.f32 %0, %1, %2;" : "=r"(r) : "f"(hi), "f"(lo)); return r;
}
__device__ __forceinline__ void stsm4(uint32_t a, uint32_t r0, uint32_t r1, uint32_t r2, uint32_t r3) {
  asm volatile("stmatrix.sync.aligned.m8n8.x4.shared.b16 [%0], {%1,%2,%3,%4};" ::"r"(a), "r"(r0), "r"(r1), "r"(r2), "r"(r3) : "memory");
}
__device__ __forceinline__ void ldsm4(uint32_t a, uint32_t& r0, uint32_t& r1, uint32_t& r2, uint32_t& r3) {
  asm volatile("ldmatrix.sync.aligned.m8n8.x4.shared.b16 {%0,%1,%2,%3}, [%4];" : "=r"(r0), "=r"(r1), "=r"(r2), "=r"(r3) : "r"(a) : "memory");
}
__device__ __forceinline__ void sts128(uint32_t a, uint4 v) {
  asm volatile("st.shared.v4.b32 [%0], {%1,%2,%3,%4};" ::"r"(a), "r"(v.x), "r"(v.y), "r"(v.z), "r"(v.w) : "memory");
}
__device__ __forceinline__ float lds_f32(uint32_t a) { float v; asm volatile("ld.shared.f32 %0, [%1];" : "=f"(v) : "r"(a)); return v; }
__device__ __forceinline__ float ex2(float x) { float y; asm("ex2.approx.ftz.f32 %0, %1;" : "=f"(y) : "f"(x)); return y; }

template<int SC> __device__ __forceinline__ void wg_ss144(float (&d)[72], uint64_t da, uint64_t db) {
  asm volatile("{\n.reg .pred p;\nsetp.ne.b32 p, %74, 0;\nwgmma.mma_async.sync.aligned.m64n144k16.f32.bf16.bf16 {%0,%1,%2,%3,%4,%5,%6,%7,%8,%9,%10,%11,%12,%13,%14,%15,%16,%17,%18,%19,%20,%21,%22,%23,%24,%25,%26,%27,%28,%29,%30,%31,%32,%33,%34,%35,%36,%37,%38,%39,%40,%41,%42,%43,%44,%45,%46,%47,%48,%49,%50,%51,%52,%53,%54,%55,%56,%57,%58,%59,%60,%61,%62,%63,%64,%65,%66,%67,%68,%69,%70,%71}, %72, %73, p, 1, 1, 0, 1;\n}\n"
    : "+f"(d[0]),"+f"(d[1]),"+f"(d[2]),"+f"(d[3]),"+f"(d[4]),"+f"(d[5]),"+f"(d[6]),"+f"(d[7]),"+f"(d[8]),"+f"(d[9]),"+f"(d[10]),"+f"(d[11]),"+f"(d[12]),"+f"(d[13]),"+f"(d[14]),"+f"(d[15]),"+f"(d[16]),"+f"(d[17]),"+f"(d[18]),"+f"(d[19]),"+f"(d[20]),"+f"(d[21]),"+f"(d[22]),"+f"(d[23]),"+f"(d[24]),"+f"(d[25]),"+f"(d[26]),"+f"(d[27]),"+f"(d[28]),"+f"(d[29]),"+f"(d[30]),"+f"(d[31]),"+f"(d[32]),"+f"(d[33]),"+f"(d[34]),"+f"(d[35]),"+f"(d[36]),"+f"(d[37]),"+f"(d[38]),"+f"(d[39]),"+f"(d[40]),"+f"(d[41]),"+f"(d[42]),"+f"(d[43]),"+f"(d[44]),"+f"(d[45]),"+f"(d[46]),"+f"(d[47]),"+f"(d[48]),"+f"(d[49]),"+f"(d[50]),"+f"(d[51]),"+f"(d[52]),"+f"(d[53]),"+f"(d[54]),"+f"(d[55]),"+f"(d[56]),"+f"(d[57]),"+f"(d[58]),"+f"(d[59]),"+f"(d[60]),"+f"(d[61]),"+f"(d[62]),"+f"(d[63]),"+f"(d[64]),"+f"(d[65]),"+f"(d[66]),"+f"(d[67]),"+f"(d[68]),"+f"(d[69]),"+f"(d[70]),"+f"(d[71]) : "l"(da), "l"(db), "n"(SC));
}
template<int SC> __device__ __forceinline__ void wg_ss96(float (&d)[48], uint64_t da, uint64_t db) {
  asm volatile("{\n.reg .pred p;\nsetp.ne.b32 p, %50, 0;\nwgmma.mma_async.sync.aligned.m64n96k16.f32.bf16.bf16 {%0,%1,%2,%3,%4,%5,%6,%7,%8,%9,%10,%11,%12,%13,%14,%15,%16,%17,%18,%19,%20,%21,%22,%23,%24,%25,%26,%27,%28,%29,%30,%31,%32,%33,%34,%35,%36,%37,%38,%39,%40,%41,%42,%43,%44,%45,%46,%47}, %48, %49, p, 1, 1, 0, 1;\n}\n"
    : "+f"(d[0]),"+f"(d[1]),"+f"(d[2]),"+f"(d[3]),"+f"(d[4]),"+f"(d[5]),"+f"(d[6]),"+f"(d[7]),"+f"(d[8]),"+f"(d[9]),"+f"(d[10]),"+f"(d[11]),"+f"(d[12]),"+f"(d[13]),"+f"(d[14]),"+f"(d[15]),"+f"(d[16]),"+f"(d[17]),"+f"(d[18]),"+f"(d[19]),"+f"(d[20]),"+f"(d[21]),"+f"(d[22]),"+f"(d[23]),"+f"(d[24]),"+f"(d[25]),"+f"(d[26]),"+f"(d[27]),"+f"(d[28]),"+f"(d[29]),"+f"(d[30]),"+f"(d[31]),"+f"(d[32]),"+f"(d[33]),"+f"(d[34]),"+f"(d[35]),"+f"(d[36]),"+f"(d[37]),"+f"(d[38]),"+f"(d[39]),"+f"(d[40]),"+f"(d[41]),"+f"(d[42]),"+f"(d[43]),"+f"(d[44]),"+f"(d[45]),"+f"(d[46]),"+f"(d[47]) : "l"(da), "l"(db), "n"(SC));
}
template<int SC> __device__ __forceinline__ void wg_rs112(float (&d)[56], uint32_t a0, uint32_t a1, uint32_t a2, uint32_t a3, uint64_t db) {
  asm volatile("{\n.reg .pred p;\nsetp.ne.b32 p, %61, 0;\nwgmma.mma_async.sync.aligned.m64n112k16.f32.bf16.bf16 {%0,%1,%2,%3,%4,%5,%6,%7,%8,%9,%10,%11,%12,%13,%14,%15,%16,%17,%18,%19,%20,%21,%22,%23,%24,%25,%26,%27,%28,%29,%30,%31,%32,%33,%34,%35,%36,%37,%38,%39,%40,%41,%42,%43,%44,%45,%46,%47,%48,%49,%50,%51,%52,%53,%54,%55}, {%56,%57,%58,%59}, %60, p, 1, 1, 0;\n}\n"
    : "+f"(d[0]),"+f"(d[1]),"+f"(d[2]),"+f"(d[3]),"+f"(d[4]),"+f"(d[5]),"+f"(d[6]),"+f"(d[7]),"+f"(d[8]),"+f"(d[9]),"+f"(d[10]),"+f"(d[11]),"+f"(d[12]),"+f"(d[13]),"+f"(d[14]),"+f"(d[15]),"+f"(d[16]),"+f"(d[17]),"+f"(d[18]),"+f"(d[19]),"+f"(d[20]),"+f"(d[21]),"+f"(d[22]),"+f"(d[23]),"+f"(d[24]),"+f"(d[25]),"+f"(d[26]),"+f"(d[27]),"+f"(d[28]),"+f"(d[29]),"+f"(d[30]),"+f"(d[31]),"+f"(d[32]),"+f"(d[33]),"+f"(d[34]),"+f"(d[35]),"+f"(d[36]),"+f"(d[37]),"+f"(d[38]),"+f"(d[39]),"+f"(d[40]),"+f"(d[41]),"+f"(d[42]),"+f"(d[43]),"+f"(d[44]),"+f"(d[45]),"+f"(d[46]),"+f"(d[47]),"+f"(d[48]),"+f"(d[49]),"+f"(d[50]),"+f"(d[51]),"+f"(d[52]),"+f"(d[53]),"+f"(d[54]),"+f"(d[55]) : "r"(a0), "r"(a1), "r"(a2), "r"(a3), "l"(db), "n"(SC));
}
template<int SC> __device__ __forceinline__ void wg_sp48(float (&d)[24], uint32_t a0, uint32_t a1, uint32_t a2, uint32_t a3, uint64_t db, uint32_t meta) {
  asm volatile("{\n.reg .pred p;\nsetp.ne.b32 p, %30, 0;\nwgmma.mma_async.sp.sync.aligned.m64n48k32.f32.bf16.bf16 {%0,%1,%2,%3,%4,%5,%6,%7,%8,%9,%10,%11,%12,%13,%14,%15,%16,%17,%18,%19,%20,%21,%22,%23}, {%24,%25,%26,%27}, %28, %29, 0, p, 1, 1, 1;\n}\n"
    : "+f"(d[0]),"+f"(d[1]),"+f"(d[2]),"+f"(d[3]),"+f"(d[4]),"+f"(d[5]),"+f"(d[6]),"+f"(d[7]),"+f"(d[8]),"+f"(d[9]),"+f"(d[10]),"+f"(d[11]),"+f"(d[12]),"+f"(d[13]),"+f"(d[14]),"+f"(d[15]),"+f"(d[16]),"+f"(d[17]),"+f"(d[18]),"+f"(d[19]),"+f"(d[20]),"+f"(d[21]),"+f"(d[22]),"+f"(d[23]) : "r"(a0), "r"(a1), "r"(a2), "r"(a3), "l"(db), "r"(meta), "n"(SC));
}
template<int SC> __device__ __forceinline__ void wg_ss192(float (&d)[96], uint64_t da, uint64_t db) {
  asm volatile("{\n.reg .pred p;\nsetp.ne.b32 p, %98, 0;\nwgmma.mma_async.sync.aligned.m64n192k16.f32.bf16.bf16 {%0,%1,%2,%3,%4,%5,%6,%7,%8,%9,%10,%11,%12,%13,%14,%15,%16,%17,%18,%19,%20,%21,%22,%23,%24,%25,%26,%27,%28,%29,%30,%31,%32,%33,%34,%35,%36,%37,%38,%39,%40,%41,%42,%43,%44,%45,%46,%47,%48,%49,%50,%51,%52,%53,%54,%55,%56,%57,%58,%59,%60,%61,%62,%63,%64,%65,%66,%67,%68,%69,%70,%71,%72,%73,%74,%75,%76,%77,%78,%79,%80,%81,%82,%83,%84,%85,%86,%87,%88,%89,%90,%91,%92,%93,%94,%95}, %96, %97, p, 1, 1, 0, 1;\n}\n"
    : "+f"(d[0]),"+f"(d[1]),"+f"(d[2]),"+f"(d[3]),"+f"(d[4]),"+f"(d[5]),"+f"(d[6]),"+f"(d[7]),"+f"(d[8]),"+f"(d[9]),"+f"(d[10]),"+f"(d[11]),"+f"(d[12]),"+f"(d[13]),"+f"(d[14]),"+f"(d[15]),"+f"(d[16]),"+f"(d[17]),"+f"(d[18]),"+f"(d[19]),"+f"(d[20]),"+f"(d[21]),"+f"(d[22]),"+f"(d[23]),"+f"(d[24]),"+f"(d[25]),"+f"(d[26]),"+f"(d[27]),"+f"(d[28]),"+f"(d[29]),"+f"(d[30]),"+f"(d[31]),"+f"(d[32]),"+f"(d[33]),"+f"(d[34]),"+f"(d[35]),"+f"(d[36]),"+f"(d[37]),"+f"(d[38]),"+f"(d[39]),"+f"(d[40]),"+f"(d[41]),"+f"(d[42]),"+f"(d[43]),"+f"(d[44]),"+f"(d[45]),"+f"(d[46]),"+f"(d[47]),"+f"(d[48]),"+f"(d[49]),"+f"(d[50]),"+f"(d[51]),"+f"(d[52]),"+f"(d[53]),"+f"(d[54]),"+f"(d[55]),"+f"(d[56]),"+f"(d[57]),"+f"(d[58]),"+f"(d[59]),"+f"(d[60]),"+f"(d[61]),"+f"(d[62]),"+f"(d[63]),"+f"(d[64]),"+f"(d[65]),"+f"(d[66]),"+f"(d[67]),"+f"(d[68]),"+f"(d[69]),"+f"(d[70]),"+f"(d[71]),"+f"(d[72]),"+f"(d[73]),"+f"(d[74]),"+f"(d[75]),"+f"(d[76]),"+f"(d[77]),"+f"(d[78]),"+f"(d[79]),"+f"(d[80]),"+f"(d[81]),"+f"(d[82]),"+f"(d[83]),"+f"(d[84]),"+f"(d[85]),"+f"(d[86]),"+f"(d[87]),"+f"(d[88]),"+f"(d[89]),"+f"(d[90]),"+f"(d[91]),"+f"(d[92]),"+f"(d[93]),"+f"(d[94]),"+f"(d[95]) : "l"(da), "l"(db), "n"(SC));
}

constexpr uint32_t SBC = 1024;
constexpr int ROWB = 2 * 224 * 384;
constexpr int TB = 11;
constexpr int KS = 832;
constexpr int KSLOT = 22 * KS;
constexpr int SM_X1 = 0;
constexpr int SM_X2 = SM_X1 + 24576;
constexpr int SM_X0 = SM_X2 + 24576;
constexpr int SM_W = SM_X0 + 18432;
constexpr int SM_K = SM_W + 55296;
constexpr int SM_V = SM_K + 2 * KSLOT;
constexpr int SM_Q = SM_V + 22 * 1536;
constexpr int SM_O = SM_Q + 24576;
constexpr int SM_RPB = SM_O + 12288;
constexpr int SM_BAR = SM_RPB + 768;
constexpr int SM_A_TOTAL = SM_BAR + 256;
constexpr int SM_TWO = SM_X0 + 24576;
constexpr int SM_TST = SM_TWO + 36864;
enum { B_FULL = 0, B_EMPTY = 3, B_TIN = 6, B_TFREE = 10, B_WK = 12, B_WQ, B_WO, B_Q0, B_OTAIL, B_ODONE = B_OTAIL + 2, B_KFREE, B_VFREE, B_COUNT };
enum { N_KRDY = 4, N_QK0, N_QK1, N_VQ0, N_VQ1, N_PVISS };

#define NL 2
#define OPT 0
#define SPL 4
#define RA 160
#define RG 168
__device__ int g_flags[TB * 56];

#define TR(role, it, k)
#define TRDECL
#define TRARG
#define TRPASS
#define TRDUMP
#define TRB(it, k)
#define TR2(blk, k)

struct GemmCtx {
  uint32_t bar;
  uint32_t kC, vC[2], qC[2];
  uint32_t kH, vH[2];
  uint32_t hiA, hiB;
  uint32_t spin;
  bool hvalid, never;
};

template <int STRIDE> __device__ __forceinline__ void dump12(uint32_t a, const uint32_t (&r)[12]) {
#pragma unroll
  for (int j = 0; j < 3; j++) stsm4(a + j * 2 * STRIDE, r[4 * j], r[4 * j + 1], r[4 * j + 2], r[4 * j + 3]);
}
__device__ __forceinline__ void keep12(bool never, uint32_t a, const uint32_t (&r)[12]) { if (never) dump12<128>(a, r); }
template <int N> __device__ __forceinline__ void pack12(uint32_t (&r)[12], const float (&d)[N], int off) {
#pragma unroll
  for (int j = 0; j < 12; j++) r[j] = pack2(d[off + 2 * j], d[off + 2 * j + 1]);
}
__device__ __forceinline__ uint64_t dsc(uint64_t lo, uint32_t hi) { uint64_t r; asm("mov.b64 %0, {%1, %2};" : "=l"(r) : "r"((uint32_t)lo), "r"(hi)); return r; }
template <int XS, int K0, int K1> __device__ __forceinline__ void issue_core(const GemmCtx& c, float (&d)[72]) {
  constexpr uint64_t da = mkdesc(SBC + XS, 16, 1024, 1), db = mkdesc(SBC + SM_W, 6144, 256, 3);
  wg_fence();
  if (K0 == 0) wg_ss144<0>(d, dsc(da, c.hiA), dsc(db, c.hiB));
#pragma unroll
  for (int k = K0 ? K0 : 1; k < K1; k++) wg_ss144<1>(d, dsc(da + (k >> 2) * 512 + (k & 3) * 2, c.hiA), dsc(db + k * 32, c.hiB));
  wg_commit();
}
template <int K0, int K1> __device__ __forceinline__ void issue_halo(const GemmCtx& c, float (&d)[48]) {
  constexpr uint64_t da = mkdesc(SBC + SM_X0 - 2048, 16, 1024, 1), db = mkdesc(SBC + SM_W, 6144, 256, 3);
  wg_fence();
  if (K0 == 0) wg_ss96<0>(d, dsc(da, c.hiA), dsc(db, c.hiB));
#pragma unroll
  for (int k = K0 ? K0 : 1; k < K1; k++) wg_ss96<1>(d, dsc(da + (k >> 2) * 384 + (k & 3) * 2, c.hiA), dsc(db + k * 32, c.hiB));
  wg_commit();
}
template <int ST> __device__ __forceinline__ void release_stage(const GemmCtx& c) {
  asm volatile("{\n.reg .pred p;\n.reg .b32 ra;\nelect.sync _|p, 0xffffffff;\nmapa.shared::cluster.u32 ra, %0, %1;\n"
               "@p mbarrier.arrive.shared::cluster.b64 _, [ra];\n}" ::"r"(c.bar + (B_EMPTY + ST) * 8), "n"(ST) : "memory");
}
template <int PARITY> __device__ __forceinline__ void gwait(GemmCtx& c, int bar) {
  asm volatile("{\n.reg .pred p;\nWL:\nmbarrier.try_wait.parity.shared::cta.b64 p, [%1], %2;\n@p bra WD;\n"
               "add.u32 %0, %0, 1;\nsetp.lt.u32 p, %0, 0x100000;\n@p bra WL;\nWD:\n}" : "+r"(c.spin) : "r"(c.bar + bar * 8), "n"(PARITY) : "memory");
}
__device__ __forceinline__ void load_w(const CUtensorMap* m, uint32_t dst, uint32_t bar, int col) {
  asm volatile("cp.async.bulk.tensor.2d.shared::cluster.global.mbarrier::complete_tx::bytes [%0], [%1, {%3,%4}], [%2];"
               ::"r"(dst), "l"(m), "r"(bar), "r"(col), "r"(0) : "memory");
}
template <int BYTES> __device__ __forceinline__ void send_o(uint32_t dst, uint32_t src, uint32_t bar, int cta) {
  asm volatile("{\n.reg .b32 rd, rb;\nmapa.shared::cluster.u32 rd, %0, %3;\nmapa.shared::cluster.u32 rb, %2, %3;\n"
               "cp.async.bulk.shared::cluster.shared::cta.mbarrier::complete_tx::bytes [rd], [%1], %4, [rb];\n}"
               ::"r"(dst), "r"(src), "r"(bar), "r"(cta), "n"(BYTES) : "memory");
}
__device__ __forceinline__ void tail_free(uint32_t bar) {
  uint32_t ln; asm volatile("mov.u32 %0, %%laneid;" : "=r"(ln));
  if (ln < 4) mbar_arrive_remote(bar, ln);
}
__device__ __forceinline__ void publish(uint32_t bar) {
  fence_async();
  __syncwarp();
  mbar_arrive_elect(bar);
}

template <bool FIRST, bool LAST, int PA>
__device__ __forceinline__ void gemm_iter(GemmCtx& c, int b, uint32_t (&pk)[12], uint32_t (&pv)[12], uint32_t (&pq)[12], const CUtensorMap* mwo TRARG) {
  const uint32_t bar = c.bar;
  const bool w = !FIRST && (PA == 0 || b >= 0), never = c.never;
  constexpr uint32_t ko = PA * KSLOT;
  float H[48], C[72];
  uint32_t hk[12], hv[12], pv2[12];
  TR(2, b, 0);
  if (FIRST) gwait<PA>(c, B_FULL + 0);
  if (!FIRST) dump12<256>(c.qC[1] + (PA ^ 1) * 128, pq);
  if (w) nb_sync(N_QK1, 256);
  TR(2, b, 2);
  if (FIRST) TR(2, b - 1, 6);
  issue_halo<0, 8>(c, H);
  TR(2, b, 3);
  if (!FIRST) {
    if (w) gwait<PA>(c, B_KFREE);
    dump12<128>(c.kC + ko, pk);
  }
  issue_halo<8, 12>(c, H);
  TR(2, b, 4);
  if (!LAST) {
    gwait<PA>(c, B_FULL + 2);
    if (FIRST && NL == 2) gwait<0>(c, B_WQ);
    TR(2, b, 13);
    if (FIRST) TR(2, b - 1, 7);
    issue_core<SM_X2, 0, 8>(c, C);
    TR(2, b, 5);
    if (!FIRST) { fence_async(); keep12(never, c.kC, pk); }
    wg_wait<1>(); pin(H);
    release_stage<0>(c);
  } else {
    fence_async();
    nb_arrive(N_VQ0, 288); nb_arrive(N_VQ1, 288); nb_arrive(N_PVISS, 384);
    wg_wait<0>(); pin(H);
    tail_free(bar + (B_TFREE + 1) * 8);
    nb_sync(2, 128);
    if (!c.hvalid && elect_one()) {
      mbar_expect(bar + B_WO * 8, 36864);
      asm volatile("cp.async.bulk.tensor.3d.shared::cluster.global.mbarrier::complete_tx::bytes [%0], [%1, {%3,%4,%5}], [%2];"
                   ::"r"(bar - SM_BAR + SM_TWO), "l"(mwo), "r"(bar + B_WO * 8), "r"(0), "r"(0), "r"((blockIdx.x & 1) * 3) : "memory");
    }
    __syncwarp();
  }
  pack12(hk, H, 0);
  if (c.hvalid) dump12<128>(c.kH + ko, hk);
  pack12(hv, H, 24);
  if (!LAST) {
    issue_core<SM_X2, 8, 12>(c, C);
    if (w) { nb_arrive(N_VQ0, 288); nb_arrive(N_VQ1, 288); }
    else if (!FIRST) { __syncwarp(); mbar_arrive_elect(bar + B_Q0 * 8); }
    gwait<PA>(c, B_FULL + 1);
    keep12(never, c.kC, hk);
    TR(2, b, 6);
    wg_wait<0>(); pin(C);
    TR(2, b, 7);
    pack12(pk, C, 0);
    dump12<128>(c.kC + ko + 64, pk);
    release_stage<2>(c);
    pack12(pv2, C, 24);
    pack12(pq, C, 48);
    TR(2, b, 8);
    issue_core<SM_X1, 0, SPL>(c, C);
    if (w) nb_sync(N_PVISS, 384);
    issue_core<SM_X1, SPL, 8>(c, C);
    TR(2, b, 9);
  }
  if (!FIRST) fence_async();
  if (!LAST) keep12(never, c.kC, pk);
  TR(2, b, 14);
  if (!LAST) issue_core<SM_X1, 8, 12>(c, C);
  if (!FIRST) nb_arrive(N_KRDY, 256);
  TR(2, b, 1);
  if (PA && b == 11) tail_free(bar + B_TFREE * 8);
  if (!LAST) gwait<PA ^ 1>(c, B_FULL + 0);
  if (w) gwait<PA>(c, B_VFREE);
  TR(2, b, 10);
  if (!FIRST) dump12<128>(c.vC[PA], pv);
  if (!LAST) dump12<256>(c.qC[0] + PA * 128, pq);
  if (c.hvalid) dump12<128>(c.vH[PA], hv);
  if (LAST) { fence_async(); nb_arrive(N_VQ0, 288); nb_arrive(N_VQ1, 288); nb_arrive(N_QK1, 256); return; }
  dump12<128>(c.vC[PA ^ 1] + 768, pv2);
  TR(2, b, 11);
  wg_wait<0>(); pin(C);
  TR(2, b, 12);
  release_stage<1>(c);
  pack12(pk, C, 0);
  pack12(pv, C, 24);
  pack12(pq, C, 48);
}

template <int IN> __device__ __forceinline__ void issue_proj(float (&D)[48]) {
  constexpr uint64_t da = mkdesc(SBC + IN, 128, 768, 0), db = mkdesc(SBC + SM_TWO, 12288, 512, 2);
  wg_fence();
  wg_ss96<0>(D, da, db);
#pragma unroll
  for (int k = 1; k < 12; k++) wg_ss96<1>(D, da + (k / 3) * 384 + (k % 3) * 16, db + k * 64);
  wg_commit();
}
__device__ __forceinline__ void store_proj(const float (&D)[48], const CUtensorMap* m, uint32_t st, uint32_t sta, int row, int col, int ch) {
#pragma unroll
  for (int q = 0; q < 6; q++)
    stsm4((sta ^ ((q & 1) * 32)) + (q >> 1) * 1024,
          pack2(D[8 * q], D[8 * q + 1]), pack2(D[8 * q + 2], D[8 * q + 3]), pack2(D[8 * q + 4], D[8 * q + 5]), pack2(D[8 * q + 6], D[8 * q + 7]));
  fence_async();
  __syncwarp();
  if ((threadIdx.x & 31) == 0) {
    asm volatile("cp.async.bulk.tensor.4d.global.shared::cta.bulk_group [%0, {%2,%3,%4,%5}], [%1];" ::"l"(m), "r"(st), "r"(0), "r"(row), "r"(col), "r"(ch) : "memory");
    asm volatile("cp.async.bulk.commit_group;" ::: "memory");
  }
  __syncwarp();
}

__device__ __forceinline__ float fold(float a, float b, float t, int useb) {
  float r;
  asm("{\n.reg .pred p;\nsetp.ne.b32 p, %4, 0;\nfma.rn.f32 %0, %1, 0f3E553B95, %3;\n@p fma.rn.f32 %0, %2, 0f3E553B95, %3;\n}"
      : "=&f"(r) : "f"(a), "f"(b), "f"(t), "r"(useb));
  return r;
}
template <int U, int L>
__device__ __forceinline__ void softmax_tile(const float (&SA)[56], const float (&SB)[56], const float (&T)[16], int b0, int b1,
                                             uint32_t (&P)[28], float (&sx)[8]) {
  float lu[14], ll[14];
#pragma unroll
  for (int j = 0; j < 7; j++) {
    constexpr int sh = U == L ? 2 : 0;
    const float tu0 = T[2 * j + sh], tu1 = T[2 * j + 1 + sh], tl0 = T[2 * j], tl1 = T[2 * j + 1];
    lu[2 * j]     = fold(SA[4 * (U + j)],     SB[4 * (U + j)],     tu0, b0);
    ll[2 * j]     = fold(SA[4 * (L + j) + 2], SB[4 * (L + j) + 2], tl0, b0);
    lu[2 * j + 1] = fold(SA[4 * (U + j) + 1], SB[4 * (U + j) + 1], tu1, b1);
    ll[2 * j + 1] = fold(SA[4 * (L + j) + 3], SB[4 * (L + j) + 3], tl1, b1);
  }
  float mu = lu[0], ml = ll[0], mu2 = lu[1], ml2 = ll[1];
#pragma unroll
  for (int j = 1; j < 7; j++) { mu = fmaxf(mu, lu[2 * j]); mu2 = fmaxf(mu2, lu[2 * j + 1]); ml = fmaxf(ml, ll[2 * j]); ml2 = fmaxf(ml2, ll[2 * j + 1]); }
  mu = fmaxf(mu, mu2); ml = fmaxf(ml, ml2);
  { const float a1 = __shfl_xor_sync(0xffffffffu, mu, 1), a2 = __shfl_xor_sync(0xffffffffu, mu, 2), a3 = __shfl_xor_sync(0xffffffffu, mu, 3);
    const float c1 = __shfl_xor_sync(0xffffffffu, ml, 1), c2 = __shfl_xor_sync(0xffffffffu, ml, 2), c3 = __shfl_xor_sync(0xffffffffu, ml, 3);
    mu = fmaxf(fmaxf(mu, a1), fmaxf(a2, a3)); ml = fmaxf(fmaxf(ml, c1), fmaxf(c2, c3)); }
  float su = 0.f, sl = 0.f;
#pragma unroll
  for (int c = 0; c < 14; c++) {
    const int iu = (c >> 1) * 4 + (c & 1) * 2;
    if (c >= U && c < U + 7) {
      float e0 = ex2(lu[2 * (c - U)] - mu), e1 = ex2(lu[2 * (c - U) + 1] - mu);
      su = c == U ? e0 + e1 : (su + e0) + e1; P[iu] = pack2(e0, e1);
    } else P[iu] = 0u;
    if (c >= L && c < L + 7) {
      float e0 = ex2(ll[2 * (c - L)] - ml), e1 = ex2(ll[2 * (c - L) + 1] - ml);
      sl = c == L ? e0 + e1 : (sl + e0) + e1; P[iu + 1] = pack2(e0, e1);
    } else P[iu + 1] = 0u;
  }
  sx[0] = su; sx[4] = sl;
#pragma unroll
  for (int k = 1; k < 4; k++) { sx[k] = __shfl_xor_sync(0xffffffffu, su, k); sx[4 + k] = __shfl_xor_sync(0xffffffffu, sl, k); }
}

__device__ __forceinline__ void band_setup(int b, uint32_t tb, float (&T)[16], int& b0, int& b1, uint32_t& meta) {
  uint32_t ln; asm volatile("mov.u32 %0, %%laneid;" : "=r"(ln));
  const int g = ln >> 2, t = ln & 3;
  const int sw = min(max(g + 1, b == 0 ? 4 : 0), b == 13 ? 5 : 8);
  const int i0 = 2 * t, i1 = 2 * t + 1;
  b0 = i0 <= sw - 2; b1 = i1 <= sw - 2;
  const uint32_t ra0 = tb + (i0 == sw - 1 ? 13 : i0 + 8 * b0 - g + 2) * 52;
  const uint32_t ra1 = tb + (i1 == sw - 1 ? 13 : i1 + 8 * b1 - g + 2) * 52;
#pragma unroll
  for (int jj = 0; jj < 8; jj++) { T[2 * jj] = lds_f32(ra0 + jj * 4); T[2 * jj + 1] = lds_f32(ra1 + jj * 4); }
  meta = ((0x5555u & ((1u << (2 * (sw - 1))) - 1)) ^ 0xDD88u ^ (((t ^ b) & 1) ? 0x5555u : 0u)) * 0x10001u;
}

struct Maps { CUtensorMap xc, xh, w, os, wo, ot; };

__global__ void __cluster_dims__(4, 1, 1) __launch_bounds__(512, 1)
na_attn_kernel(const __nv_bfloat16* __restrict__ x, const __nv_bfloat16* __restrict__ wqkv, const __nv_bfloat16* __restrict__ rpb, const __grid_constant__ Maps mp) {
  extern __shared__ __align__(1024) uint8_t smem_raw[];
  const uint32_t sb = smem_u32(smem_raw);
  if ((sb & 0x3FFFF) != SBC) return;
  const uint32_t bar = sb + SM_BAR;
  TR2(blockIdx.x, 0);
  const int tid = threadIdx.x, lane = tid & 31;
  const int warp = __shfl_sync(0xffffffffu, tid >> 5, 0);
  const int head = blockIdx.x & 3, cl = blockIdx.x >> 2;
  const int par = cl / 7, strip = cl - par * 7, ph = par >> 1, pw = par & 1;

  uint4 wv[2 * NL];
  const int va = head == 1;
  const uint32_t wdst = sb + SM_W + (va + ((tid >> 1) & 1)) * 6144 + (tid >> 2) * 32 + ((tid ^ (tid >> 4)) & 1) * 16;
  if (warp < 12) asm volatile("barrier.cluster.arrive.relaxed.aligned;" ::: "memory");
  {
    const uint32_t wo0 = (tid >> 2) * 1152 + head * 96 + va * 32 + (tid & 3) * 16;
#pragma unroll
    for (int i = 0; i < 2 * NL; i++)
      asm volatile("{\n.reg .pred p;\nsetp.lt.u32 p, %5, 384;\n@p ld.global.nc.v4.b32 {%0,%1,%2,%3}, [%4];\n}"
                   : "=r"(wv[i].x), "=r"(wv[i].y), "=r"(wv[i].z), "=r"(wv[i].w)
                   : "l"(reinterpret_cast<const uint8_t*>(wqkv) + wo0 + (i & 1) * 96 * 1152 + ((i / 2 + 1) % 3) * 384), "r"(tid));
  }
  if (warp < 8) {
    asm volatile("setmaxnreg.inc.sync.aligned.u32 %0;" ::"n"(RA));
    float rv = -INFINITY;
    if (tid < 169) rv = __bfloat162float(rpb[head * 169 + tid]) * 1.4426950408889634f;
    if (tid < 192) {
      const int kc = (tid & 15) + 3, wc = (tid >> 4) % 6;
      sts128(tid < 96 ? sb + SM_K + kc * KS + wc * 128 + 48 : sb + SM_V + kc * 1536 + wc * 128 + (6 + (kc & 1)) * 16, make_uint4(0, 0, 0, 0));
    }
#pragma unroll
    for (int i = 0; i < 2 * NL; i++) sts128(wdst + (i & 1) * 3072 + (i / 2) * 18432, wv[i]);
    fence_async();
    asm volatile("bar.arrive 1, 384;" ::: "memory");
    if (tid < 182) asm volatile("st.shared.f32 [%0], %1;" ::"r"(sb + SM_RPB + tid * 4), "f"(rv) : "memory");
    const int j = warp >> 2, w = warp & 3;
    int variant = w;
    if (strip == 0 && j == 0 && w < 2) variant = 4;
    if (strip == 6 && j == 1 && w >= 2) variant = 5;
    const bool v1 = opq((uint32_t)(variant & 1)), v2 = opq((uint32_t)(variant & 2)), v4 = opq((uint32_t)(variant & 4));
    uint32_t qa = opq(sb + SM_Q + (8 * j + 2 * w + ((lane >> 3) & 1)) * 1536 + (lane >> 4) * 256 + (((lane & 7) * 16) ^ (((lane >> 3) & 1) * 64)));
    uint32_t oa = opq(sb + SM_O + j * 6144 + (2 * w + ((lane >> 3) & 1)) * 768 + (lane >> 4) * 128 + (lane & 7) * 16);
    uint64_t dA = opq(mkdesc(SBC + SM_K, 128, KS, 0) + j * (8 * KS / 16)), dB = opq(dA + (KSLOT >> 4));
    uint64_t dV[7];
#pragma unroll
    for (int i = 0; i < 7; i++) dV[i] = opq(mkdesc(SBC + SM_V, 768, 128, 0) + j * (8 * 1536 / 16) + i * 192);
    const uint32_t nbK = opq((uint32_t)(N_KRDY + j)), nbQ = opq((uint32_t)(N_QK0 + j)), nbV = opq((uint32_t)(N_VQ0 + j));
    asm volatile("barrier.cluster.wait.aligned;" ::: "memory");
    asm volatile("bar.sync 3, 256;" ::: "memory");
    float T[16];
    TRDECL;
    int b0, b1;
    uint32_t meta, dm = 0, ob = bar + B_ODONE * 8;
    const uint32_t tb = opq(sb + SM_RPB + (variant < 4 ? 3 : variant + 1 - 2 * w) * 4);
    band_setup(0, tb, T, b0, b1, meta);
    uint32_t q[12];
    mbar_wait(bar + B_Q0 * 8, 0);
#pragma unroll
    for (int k = 0; k < 3; k++) ldsm4(qa + k * 512, q[4 * k], q[4 * k + 1], q[4 * k + 2], q[4 * k + 3]);
#pragma unroll 1
    for (int b = 0; b < 14; b++) {
      float SA[56], SB[56];
      TR(0, b, 0);
      nb_sync(nbK, 256);
      TR(0, b, 1);
      TR(0, b - 1, 9);
      wg_fence();
      wg_rs112<0>(SA, q[0], q[1], q[2], q[3], dA);
      wg_rs112<0>(SB, q[0], q[1], q[2], q[3], dB);
      wg_rs112<1>(SA, q[4], q[5], q[6], q[7], dA + 16);
      wg_rs112<1>(SB, q[4], q[5], q[6], q[7], dB + 16);
      wg_rs112<1>(SA, q[8], q[9], q[10], q[11], dA + 32);
      wg_rs112<1>(SB, q[8], q[9], q[10], q[11], dB + 32);
      wg_commit();
      nb_arrive(nbQ, 256);
      { const uint64_t t = dA; dA = dB; dB = t; }
      qa ^= 128;
      TR(0, b, 2);
      wg_wait<0>(); pin(SA); pin(SB);
      mbar_arrive_elect(bar + B_KFREE * 8);
      TR(0, b, 3);
      TR(0, b - 1, 10);
      uint32_t P[28];
      float sx[8];
      if (v2) {
        if (v1) softmax_tile<6, 7>(SA, SB, T, b0, b1, P, sx); else softmax_tile<4, 5>(SA, SB, T, b0, b1, P, sx);
      } else if (!v4) {
        if (v1) softmax_tile<2, 3>(SA, SB, T, b0, b1, P, sx); else softmax_tile<0, 1>(SA, SB, T, b0, b1, P, sx);
      } else {
        if (v1) softmax_tile<4, 4>(SA, SB, T, b0, b1, P, sx); else softmax_tile<3, 3>(SA, SB, T, b0, b1, P, sx);
      }
      float O[24];
      TR(0, b, 4);
      nb_sync(nbV, 288);
      TR(0, b, 5);
#pragma unroll
      for (int k = 0; k < 3; k++) ldsm4(qa + k * 512, q[4 * k], q[4 * k + 1], q[4 * k + 2], q[4 * k + 3]);
      wg_fence();
      wg_sp48<0>(O, P[0], P[1], P[2], P[3], dV[0], meta);
#pragma unroll
      for (int s = 1; s < 7; s++) wg_sp48<1>(O, P[4 * s], P[4 * s + 1], P[4 * s + 2], P[4 * s + 3], dV[s], meta);
      wg_commit();
      nb_arrive(N_PVISS, 384);
      TR(0, b, 6);
      if (b == 0 || b == 12) { band_setup(b + 1, tb, T, b0, b1, dm); dm ^= meta; }
      wg_wait<0>(); pin(O);
      mbar_arrive_elect(bar + B_VFREE * 8);
      TR(0, b, 7);
      asm volatile("xor.b32 %0, %0, %1;\nmov.b32 %1, 0x55555555;" : "+r"(meta), "+r"(dm));
      float ru, rl;
      asm("rcp.approx.ftz.f32 %0, %1;" : "=f"(ru) : "f"(((fmaf(O[0], 0.f, sx[0]) + sx[1]) + sx[2]) + sx[3]));
      asm("rcp.approx.ftz.f32 %0, %1;" : "=f"(rl) : "f"(((fmaf(O[2], 0.f, sx[4]) + sx[5]) + sx[6]) + sx[7]));
#pragma unroll
      for (int i = 0; i < 3; i++)
        stsm4(oa + i * 256, pack2(O[8 * i] * ru, O[8 * i + 1] * ru), pack2(O[8 * i + 2] * rl, O[8 * i + 3] * rl),
              pack2(O[8 * i + 4] * ru, O[8 * i + 5] * ru), pack2(O[8 * i + 6] * rl, O[8 * i + 7] * rl));
      publish(ob);
      if (b >= TB - 1) {
        ob = opq(bar + (B_OTAIL + j) * 8);
        oa += b == 11 ? warp * 1536 - (SM_O - SM_Q) : (b == 12 ? 1536 : 0);
      }
      TR(0, b, 8);
    }
    if (elect_one()) {
#pragma unroll
      for (int d = 0; d < 2; d++)
        send_o<1536>(sb + SM_X0 + head * 6144 + (2 * j + (w & 1)) * 1536, sb + SM_Q + warp * 3072 + 1536, bar + (B_TIN + 2 + d) * 8, (w & 2) + (d ^ (head & 1)));
    }
    __syncwarp();
    TRDUMP;
    cluster_sync();
  } else if (warp < 12) {
    TRDECL;
    TR(2, -3, 0);
    asm volatile("setmaxnreg.inc.sync.aligned.u32 %0;" ::"n"(RG));
    TR(2, -3, 1);
    GemmCtx c;
    c.bar = bar;
    const int gw = warp - 8, tk = gw * 16 + (lane & 15), hi = lane >> 4;
    { const int col = tk >> 2, i = tk & 3;
      c.kC = sb + SM_K + (col + 3) * KS + hi * 128 + i * 16;
      c.vC[0] = sb + SM_V + (col + 3) * 1536 + hi * 128 + (2 * i + ((col + 3) & 1)) * 16;
      c.qC[0] = sb + SM_Q + col * 1536 + hi * 256 + (col & 1) * 64 + i * 16; }
    { const int ci = (tk >> 3) - 2, kc = ci < 3 ? ci : ci + 16, i = tk & 7; c.hvalid = gw > 0;
      c.kH = sb + SM_K + kc * KS + hi * 128 + i * 16;
      c.vH[0] = sb + SM_V + kc * 1536 + hi * 128 + (i >> 2) * 768 + (2 * (i & 3) + ((kc ^ (i >> 2)) & 1)) * 16; }
    c.never = x == nullptr;
    c.kC = opq(c.kC); c.kH = opq(c.kH);
    c.vC[1] = opq(c.vC[0] ^ 16); c.vC[0] = opq(c.vC[0]);
    c.vH[1] = opq(c.vH[0] ^ 16); c.vH[0] = opq(c.vH[0]);
    c.qC[1] = opq(c.qC[0] ^ 64); c.qC[0] = opq(c.qC[0]);
    c.spin = 0;
    c.hiA = (uint32_t)(mkdesc(0, 0, 1024, 1) >> 32) + (blockIdx.x >> 16); c.hiB = (uint32_t)(mkdesc(0, 0, 256, 3) >> 32) + (blockIdx.x >> 16);
    asm volatile("barrier.cluster.wait.aligned;" ::: "memory");
    TR(2, -3, 2);
#pragma unroll
    for (int i = 0; i < 2 * NL; i++) sts128(wdst + (i & 1) * 3072 + (i / 2) * 18432, wv[i]);
    fence_async();
    TR(2, -3, 3);
    asm volatile("bar.sync 1, 384;" ::: "memory");
    TR(2, -3, 4);
    mbar_wait(bar + B_WK * 8, 0);
    TR(2, -3, 5);
    uint32_t pk[12], pv[12], pq[12];
    gemm_iter<true, false, 0>(c, -2, pk, pv, pq, &mp.wo TRPASS);
    TR2(blockIdx.x, 4);
#pragma unroll 1
    for (int b = -1;; b += 2) {
      gemm_iter<false, false, 1>(c, b, pk, pv, pq, &mp.wo TRPASS);
      if (b == 11) break;
      gemm_iter<false, false, 0>(c, b + 1, pk, pv, pq, &mp.wo TRPASS);
    }
    TR2(blockIdx.x, 6);
    gemm_iter<false, true, 0>(c, 12, pk, pv, pq, &mp.wo TRPASS);
    TR(2, 13, 0);
    mbar_wait(bar + B_WO * 8, 0);
    mbar_wait(bar + B_TIN * 8, 0);
    const uint32_t st = sb + gw * 3072;
    const uint32_t sta = st + (lane & 15) * 64 + ((hi ^ ((lane >> 1) & 3)) * 16);
    const int oc = ph * 112 + strip * 16 + 8 * (gw >> 1) + 4 * (head >> 1) + 2 * (gw & 1), och = pw * 6 + (head & 1) * 3;
    float D0[48], D1[48];
    nb_sync(N_PVISS, 384);
    issue_proj<SM_X2>(D0);
    mbar_wait(bar + (B_TIN + 1) * 8, 0);
    issue_proj<SM_X1>(D1);
    wg_wait<1>(); pin(D0);
    store_proj(D0, &mp.ot, st + SM_TST, sta + SM_TST, 8 * TB, oc, och);
    wg_wait<0>(); pin(D1);
    store_proj(D1, &mp.ot, st + SM_X2, sta + SM_X2, 8 * TB + 8, oc, och);
    {
      const uint64_t da = mkdesc(SBC + SM_X0, 128, 768, 0), db = mkdesc(SBC + SM_TWO, 12288, 512, 2);
#pragma unroll
      for (int g = 0; g < 2; g++) {
        const int hd = (head ^ g) & 1;
        mbar_wait(bar + (B_TIN + 2 + g) * 8, 0);
        wg_fence();
#pragma unroll
        for (int k = 0; k < 6; k++) {
          const uint64_t a = da + hd * 384 + (k / 3) * 768 + (k % 3) * 16, bb = db + hd * 192 + (k / 3) * 384 + (k % 3) * 64;
          if (g + k == 0) wg_ss96<0>(D0, a, bb); else wg_ss96<1>(D0, a, bb);
        }
        wg_commit();
      }
    }
    asm volatile("barrier.cluster.arrive.relaxed.aligned;" ::: "memory");
    wg_wait<0>(); pin(D0);
    store_proj(D0, &mp.ot, st + SM_X2 + 12288, sta + SM_X2 + 12288, 8 * TB + 16, oc, och);
    TR(2, 13, 7);
    if (lane == 0) asm volatile("cp.async.bulk.wait_group.read 0;" ::: "memory");
    __syncwarp();
    TR(2, 13, 8);
    TR2(blockIdx.x, 2);
    TRDUMP;
    asm volatile("barrier.cluster.wait.aligned;" ::: "memory");
  } else {
    if (warp == 12) {
      if (elect_one()) {
        mbar_init(bar + B_WK * 8, 1);
#pragma unroll
        for (int i = 0; i < NL; i++) load_w(&mp.w, sb + SM_W + (3 * i + 2 - 2 * va) * 6144, bar + B_WK * 8, ((i + 1) % 3) * 192 + head * 48 + 32 - 32 * va);
        asm volatile("prefetch.tensormap [%0];" ::"l"(head ? &mp.xc : &mp.xh) : "memory");
        mbar_expect(bar + B_WK * 8, NL * 6144);
      }
    } else if (warp == 15) {
      const int col = min(max(strip * 16 - 3 + min(lane, 21), 0), 111);
      const uint8_t* p = reinterpret_cast<const uint8_t*>(x) + (uint32_t)(head * ROWB + (ph * 112 + col) * 768 + pw * 384);
#pragma unroll
      for (int i = 0; i < 3; i++) asm volatile("prefetch.global.L2 [%0];" ::"l"(p + i * 128));
    } else if (elect_one()) {
      if (warp == 13) {
#pragma unroll
        for (int i = 0; i < B_WK; i++) mbar_init(bar + i * 8, i < B_EMPTY ? 1 : (i < B_TIN ? 16 : (i < B_TFREE ? 1 : 16)));
      } else {
#pragma unroll
        for (int i = B_WQ; i < B_COUNT; i++) mbar_init(bar + i * 8, i < B_Q0 ? 1 : (i < B_ODONE ? 4 : 8));
      }
    }
    asm volatile("fence.mbarrier_init.release.cluster;" ::: "memory");
    __syncwarp();
    asm volatile("barrier.cluster.arrive.relaxed.aligned;" ::: "memory");
    asm volatile("setmaxnreg.dec.sync.aligned.u32 24;");
    asm volatile("griddepcontrol.launch_dependents;");
    const int cc = ph * 112 + (head ? strip * 16 : (strip == 0 ? 16 : (strip == 6 ? 74 : strip * 16 - 3)));
    const int sd = strip == 0 ? -1 : (strip == 6 ? 1 : 0);
    const int r0 = head == 0 ? -4 : (head == 1 ? 4 : 0);
    asm volatile("barrier.cluster.wait.aligned;" ::: "memory");
    if (warp == 12) {
      const uint32_t fb = bar + (B_FULL + head) * 8, eb = bar + (B_EMPTY + head) * 8;
      const uint32_t dst = sb + (head == 0 ? SM_X0 : (head == 1 ? SM_X1 : SM_X2));
      const int nl = head == 0 ? 15 : (head == 3 ? 1 : 14);
#pragma unroll 1
      for (int n = 0; n < nl; n++) {
        if (n) mbar_wait(eb, (n - 1) & 1);
        if (lane < 4 && head < 3)
          asm volatile("{\n.reg .b32 ra;\nmapa.shared::cluster.u32 ra, %0, %1;\nmbarrier.arrive.expect_tx.shared::cluster.b64 _, [ra], %2;\n}"
                       ::"r"(fb), "r"(lane), "r"(head ? 24576 : 18432) : "memory");
        __syncwarp();
        if (elect_one()) {
          if (head == 0) {
            asm volatile("cp.async.bulk.tensor.5d.shared::cluster.global.mbarrier::complete_tx::bytes.multicast::cluster [%0], [%1, {%3,%4,%5,%6,%7}], [%2], %8;"
                         ::"r"(dst), "l"(&mp.xh), "r"(fb), "r"(0), "r"(8 * n + r0), "r"(cc), "r"(sd), "r"(pw * 3), "h"((uint16_t)15) : "memory");
          } else if (head < 3) {
            asm volatile("cp.async.bulk.tensor.4d.shared::cluster.global.mbarrier::complete_tx::bytes.multicast::cluster [%0], [%1, {%3,%4,%5,%6}], [%2], %7;"
                         ::"r"(dst), "l"(&mp.xc), "r"(fb), "r"(0), "r"(8 * n + r0), "r"(cc), "r"(pw * 3), "h"((uint16_t)15) : "memory");
          }
          if (n == 0) {
#pragma unroll
            for (int i = 0; i < 3; i++) load_w(&mp.w, sb + SM_W + (6 + i) * 6144, bar + B_WQ * 8, head * 48 + i * 16);
            mbar_expect(bar + B_WQ * 8, 18432);
            mbar_expect(bar + B_TIN * 8, 24576); mbar_expect(bar + (B_TIN + 1) * 8, 24576); mbar_expect(bar + (B_TIN + 2) * 8, 12288); mbar_expect(bar + (B_TIN + 3) * 8, 12288);
          }
          if (!head && n + 1 < nl) asm volatile("cp.async.bulk.prefetch.tensor.5d.L2.global [%0, {%1,%2,%3,%4,%5}];" ::"l"(&mp.xh), "r"(0), "r"(8 * n + 8 + r0), "r"(cc), "r"(sd), "r"(pw * 3) : "memory");
          if (head && n + 1 < nl) asm volatile("cp.async.bulk.prefetch.tensor.4d.L2.global [%0, {%1,%2,%3,%4}];" ::"l"(&mp.xc), "r"(0), "r"(8 * n + 8 + r0), "r"(cc), "r"(pw * 3) : "memory");
        }
        __syncwarp();
      }
    }
    if (warp == 14) {
      int* flag = g_flags + cl * 2;
      nb_arrive(N_VQ0, 288); nb_arrive(N_VQ1, 288);
#pragma unroll 1
      for (int b = 0; b < TB; b++) {
        mbar_wait(bar + B_ODONE * 8, b & 1);
        if (lane == 0) {
          asm volatile("cp.async.bulk.tensor.3d.global.shared::cta.bulk_group [%0, {%2,%3,%4}], [%1];"
                       ::"l"(&mp.os), "r"(sb + SM_O), "r"(pw * 192), "r"(8 * b + 2 * head), "r"(ph * 112 + strip * 16) : "memory");
          asm volatile("cp.async.bulk.commit_group;\ncp.async.bulk.wait_group 0;" ::: "memory");
        }
        __syncwarp();
        nb_arrive(N_VQ0, 288); nb_arrive(N_VQ1, 288);
        if (lane == 0)
          asm volatile("fence.proxy.async.global;\nfence.acq_rel.gpu;\nred.relaxed.gpu.global.add.s32 [%0], 1;\nred.relaxed.gpu.global.add.s32 [%0+4], 1;"
                       ::"l"(flag + b * 56) : "memory");
        __syncwarp();
      }
    } else if (warp & 1) {
      const int j = (warp >> 1) & 1;
#pragma unroll 1
      for (int i = 0; i < 2; i++) {
        mbar_wait(bar + (B_OTAIL + j) * 8, i);
        if (i == 0) nb_arrive(N_VQ0 + j, 288);
        mbar_wait(bar + (B_TFREE + i) * 8, 0);
        if (i == 1) nb_arrive(N_VQ0 + j, 288);
        if (elect_one()) {
#pragma unroll 1
          for (int d = 0; d < 8; d++) {
            const int dst = (d + head) & 3, pc = d >> 2;
            send_o<1536>(sb + (i ? SM_X1 : SM_X2) + head * 6144 + j * 3072 + pc * 1536,
                         sb + (i ? SM_Q : SM_O) + (4 * j + (dst & 2) + pc) * (i ? 3072 : 1536), bar + (B_TIN + i) * 8, dst);
          }
        }
        __syncwarp();
      }
    }
    cluster_sync();
  }
}

constexpr int NSTB = 6;
constexpr int NTB = TB * 56;
constexpr int SM_B_IN = 0;
constexpr int SM_B_W = SM_B_IN + NSTB * 24576;
constexpr int SM_B_BAR = SM_B_W + 73728;
constexpr int SM_B_TOTAL = SM_B_BAR + 128;
struct MapsB { CUtensorMap oi, oo, wo; };

__global__ void __launch_bounds__(480, 1)
na_proj_kernel(const __grid_constant__ MapsB mp) {
  extern __shared__ __align__(1024) uint8_t smem_raw[];
  const uint32_t sb = smem_u32(smem_raw);
  if ((sb & 0x3FFFF) != SBC) return;
  const uint32_t bar = sb + SM_B_BAR;
  const int tid = threadIdx.x, lane = tid & 31;
  const int warp = __shfl_sync(0xffffffffu, tid >> 5, 0);
  TR2(132 + blockIdx.x, 0);
  TRB(47, 0);
  if (warp == 12 && elect_one()) {
#pragma unroll
    for (int i = 0; i <= 2 * NSTB; i++) mbar_init(bar + i * 8, i < NSTB || i == 2 * NSTB ? 1 : 4);
    mbar_expect(bar + 2 * NSTB * 8, 73728);
#pragma unroll
    for (int i = 0; i < 2; i++)
      asm volatile("cp.async.bulk.tensor.3d.shared::cluster.global.mbarrier::complete_tx::bytes [%0], [%1, {%3,%4,%5}], [%2];"
                   ::"r"(sb + SM_B_W + i * 36864), "l"(&mp.wo), "r"(bar + 2 * NSTB * 8), "r"(0), "r"(0), "r"(i * 3) : "memory");
  }
  __syncthreads();
  const int step = gridDim.x;
  if (warp >= 12) {
    const int wg = warp - 12;
    int use = 0;
#pragma unroll 1
    for (int n = blockIdx.x + wg * step; n < NTB; n += 3 * step, use++) {
      const int b = n / 56, rem = n - b * 56, par = rem / 14, sg = wg + 3 * (use & 1);
      int v; uint32_t spin = 0;
      do { asm volatile("ld.acquire.gpu.global.s32 %0, [%1];" : "=r"(v) : "l"(g_flags + n) : "memory"); if ((OPT & 1) && v < 4) __nanosleep(200); } while (v < 4 && ++spin < SPIN_LIMIT);
      TRB(use * 3 + wg, 0);
      asm volatile("fence.proxy.async.global;" ::: "memory");
      if (use >= 2) mbar_wait(bar + (NSTB + sg) * 8, ((use >> 1) - 1) & 1);
      TRB(use * 3 + wg, 1);
      if (elect_one()) {
        mbar_expect(bar + sg * 8, 24576);
        asm volatile("cp.async.bulk.tensor.3d.shared::cluster.global.mbarrier::complete_tx::bytes [%0], [%1, {%3,%4,%5}], [%2];"
                     ::"r"(sb + SM_B_IN + sg * 24576), "l"(&mp.oi), "r"(bar + sg * 8), "r"((par & 1) * 192), "r"(8 * b), "r"((par >> 1) * 112 + (rem - par * 14) * 8) : "memory");
        g_flags[n] = 0;
      }
      __syncwarp();
    }
  } else {
    const int wg = warp >> 2, w = warp & 3;
    constexpr uint64_t db = mkdesc(SBC + SM_B_W, 12288, 512, 2);
    const uint32_t sta0 = sb + SM_B_IN + w * 6144 + (lane & 15) * 128 + (((lane >> 4) ^ (lane & 7)) * 16);
    mbar_wait(bar + 2 * NSTB * 8, 0);
    TRB(47, 1);
    int use = 0;
#pragma unroll 1
    for (int n = blockIdx.x + wg * step; n < NTB; n += 3 * step, use++) {
      const int b = n / 56, rem = n - b * 56, par = rem / 14, sg = wg + 3 * (use & 1);
      const uint64_t da = mkdesc(SBC + SM_B_IN, 128, 3072, 0) + sg * (24576 / 16);
      float D[96];
      mbar_wait(bar + sg * 8, (use >> 1) & 1);
      if (use | wg) nb_sync(4 + wg, 256);
      TRB(use * 3 + wg, 3);
      wg_fence();
      wg_ss192<0>(D, da, db);
#pragma unroll
      for (int k = 1; k < 12; k++) wg_ss192<1>(D, da + k * 16, db + k * 64);
      wg_commit();
      if (n + step < NTB) nb_arrive(wg == 2 ? 4 : 5 + wg, 256);
      TRB(use * 3 + wg, 4);
      if (use && lane == 0) {
        asm volatile("cp.async.bulk.wait_group.read 0;" ::: "memory");
        mbar_arrive(bar + (NSTB + wg + 3 * (~use & 1)) * 8);
      }
      __syncwarp();
      wg_wait<0>(); pin(D);
      nb_sync(1 + wg, 128);
      TRB(use * 3 + wg, 5);
      const uint32_t sta = sta0 + sg * 24576;
#pragma unroll
      for (int q = 0; q < 12; q++)
        stsm4((sta ^ ((q & 3) * 32)) + (q >> 2) * 2048,
              pack2(D[8 * q], D[8 * q + 1]), pack2(D[8 * q + 2], D[8 * q + 3]), pack2(D[8 * q + 4], D[8 * q + 5]), pack2(D[8 * q + 6], D[8 * q + 7]));
      fence_async();
      __syncwarp();
      if (lane == 0) {
        asm volatile("cp.async.bulk.tensor.4d.global.shared::cta.bulk_group [%0, {%2,%3,%4,%5}], [%1];"
                     ::"l"(&mp.oo), "r"(sb + SM_B_IN + sg * 24576 + w * 6144), "r"(0), "r"(8 * b), "r"((par >> 1) * 112 + (rem - par * 14) * 8 + 2 * w), "r"((par & 1) * 3) : "memory");
        asm volatile("cp.async.bulk.commit_group;" ::: "memory");
      }
      __syncwarp();
      TRB(use * 3 + wg, 6);
    }
    if (lane == 0) asm volatile("cp.async.bulk.wait_group 0;" ::: "memory");
    TR2(132 + blockIdx.x, 2);
  }
}

typedef CUresult (*EncodeFn)(CUtensorMap*, CUtensorMapDataType, cuuint32_t, void*, const cuuint64_t*, const cuuint64_t*, const cuuint32_t*,
                             const cuuint32_t*, CUtensorMapInterleave, CUtensorMapSwizzle, CUtensorMapL2promotion, CUtensorMapFloatOOBfill);
static EncodeFn g_enc = nullptr;
static void make_map(CUtensorMap* m, const void* p, int rank, const cuuint64_t* dim, const cuuint64_t* str, const cuuint32_t* box, CUtensorMapSwizzle sw) {
  const cuuint32_t ones[5] = {1, 1, 1, 1, 1};
  g_enc(m, CU_TENSOR_MAP_DATA_TYPE_BFLOAT16, rank, (void*)p, dim, str, box, ones, CU_TENSOR_MAP_INTERLEAVE_NONE, sw,
        CU_TENSOR_MAP_L2_PROMOTION_L2_128B, CU_TENSOR_MAP_FLOAT_OOB_FILL_NONE);
}

extern "C" void kernel_launch(void* const* d_in, const int* in_sizes, int n_in, void* d_out, int out_size) {
  const __nv_bfloat16* x = (const __nv_bfloat16*)d_in[0];
  const __nv_bfloat16* wqkv = (const __nv_bfloat16*)d_in[1];
  const __nv_bfloat16* wo = (const __nv_bfloat16*)d_in[2];
  const __nv_bfloat16* rpb = (const __nv_bfloat16*)d_in[3];

  if (!g_enc) {
    void* fn = nullptr; cudaDriverEntryPointQueryResult qr;
    cudaGetDriverEntryPoint("cuTensorMapEncodeTiled", &fn, cudaEnableDefault, &qr);
    g_enc = (EncodeFn)fn;
    cudaFuncSetAttribute(na_attn_kernel, cudaFuncAttributeMaxDynamicSharedMemorySize, SM_A_TOTAL);
    cudaFuncSetAttribute(na_proj_kernel, cudaFuncAttributeMaxDynamicSharedMemorySize, SM_B_TOTAL);
  }
  Maps ma; MapsB mb;
  { cuuint64_t dim[4] = {64, 112, 224, 6}, str[3] = {(cuuint64_t)ROWB, 768, 128};
    cuuint32_t box[4] = {64, 4, 16, 3}, boxo[4] = {64, 8, 2, 3};
    make_map(&ma.xc, x, 4, dim, str, box, CU_TENSOR_MAP_SWIZZLE_128B);
    make_map(&mb.oo, d_out, 4, dim, str, boxo, CU_TENSOR_MAP_SWIZZLE_128B); }
  { cuuint64_t dim[5] = {64, 112, 224, 2, 6}, str[4] = {(cuuint64_t)ROWB, 768, 19 * 768, 128};
    cuuint32_t box[5] = {64, 8, 3, 2, 3};
    make_map(&ma.xh, x, 5, dim, str, box, CU_TENSOR_MAP_SWIZZLE_128B); }
  { cuuint64_t dim[3] = {384, 112, 224}, str[2] = {(cuuint64_t)ROWB, 768};
    cuuint32_t box[3] = {192, 8, 8}, boxs[3] = {192, 2, 16};
    make_map(&mb.oi, d_out, 3, dim, str, box, CU_TENSOR_MAP_SWIZZLE_NONE);
    make_map(&ma.os, d_out, 3, dim, str, boxs, CU_TENSOR_MAP_SWIZZLE_NONE); }
  { cuuint64_t dim[4] = {32, 112, 224, 12}, str[3] = {(cuuint64_t)ROWB, 768, 64};
    cuuint32_t box[4] = {32, 8, 2, 3};
    make_map(&ma.ot, d_out, 4, dim, str, box, CU_TENSOR_MAP_SWIZZLE_64B); }
  { cuuint64_t dim[2] = {576, 192}, str[1] = {1152};
    cuuint32_t box[2] = {16, 192};
    make_map(&ma.w, wqkv, 2, dim, str, box, CU_TENSOR_MAP_SWIZZLE_32B); }
  { cuuint64_t dim[3] = {32, 192, 6}, str[2] = {384, 64};
    cuuint32_t box[3] = {32, 192, 3};
    make_map(&ma.wo, wo, 3, dim, str, box, CU_TENSOR_MAP_SWIZZLE_64B);
    mb.wo = ma.wo; }
  na_attn_kernel<<<112, 512, SM_A_TOTAL>>>(x, wqkv, rpb, ma);
  cudaLaunchConfig_t cfg = {};
  cfg.gridDim = dim3(20); cfg.blockDim = dim3(480); cfg.dynamicSmemBytes = SM_B_TOTAL; cfg.stream = cudaStreamPerThread;
  cudaLaunchAttribute at[1];
  at[0].id = cudaLaunchAttributeProgrammaticStreamSerialization; at[0].val.programmaticStreamSerializationAllowed = 1;
  cfg.attrs = at; cfg.numAttrs = 1;
  cudaLaunchKernelEx(&cfg, na_proj_kernel, mb);
}
```

```cpp
#include <cuda_runtime.h>
#include <cuda_bf16.h>
#include <cuda.h>
#include <stdint.h>

#define SPIN_LIMIT (1u << 18)

__device__ __forceinline__ uint32_t smem_u32(const void* p) { return (uint32_t)__cvta_generic_to_shared(p); }
__device__ __forceinline__ void wg_fence() { asm volatile("wgmma.fence.sync.aligned;" ::: "memory"); }
__device__ __forceinline__ void wg_commit() { asm volatile("wgmma.commit_group.sync.aligned;" ::: "memory"); }
template <int N> __device__ __forceinline__ void wg_wait() { asm volatile("wgmma.wait_group.sync.aligned %0;" ::"n"(N) : "memory"); }
template <int N> __device__ __forceinline__ void pin(float (&d)[N]) {
#pragma unroll
  for (int i = 0; i < N; i++) asm volatile("" : "+f"(d[i])::"memory");
}
__host__ __device__ constexpr uint64_t mkdesc(uint32_t addr, uint32_t lbo, uint32_t sbo, uint32_t sw) {
  return (uint64_t)((addr & 0x3FFFF) >> 4) | ((uint64_t)(lbo >> 4) << 16) | ((uint64_t)(sbo >> 4) << 32) | ((uint64_t)sw << 62);
}
__device__ __forceinline__ void mbar_init(uint32_t bar, uint32_t cnt) { asm volatile("mbarrier.init.shared::cta.b64 [%0], %1;" ::"r"(bar), "r"(cnt) : "memory"); }
__device__ __forceinline__ void mbar_arrive(uint32_t bar) { asm volatile("mbarrier.arrive.shared::cta.b64 _, [%0];" ::"r"(bar) : "memory"); }
__device__ __forceinline__ bool elect_one() {
  uint32_t r; asm volatile("{\n.reg .pred p;\nelect.sync _|p, 0xffffffff;\nselp.u32 %0, 1, 0, p;\n}" : "=r"(r)); return r;
}
__device__ __forceinline__ void mbar_arrive_elect(uint32_t bar) {
  asm volatile("{\n.reg .pred p;\nelect.sync _|p, 0xffffffff;\n@p mbarrier.arrive.shared::cta.b64 _, [%0];\n}" ::"r"(bar) : "memory");
}
__device__ __forceinline__ void mbar_expect(uint32_t bar, uint32_t bytes) { asm volatile("mbarrier.arrive.expect_tx.shared::cta.b64 _, [%0], %1;" ::"r"(bar), "r"(bytes) : "memory"); }
__device__ __forceinline__ void mbar_arrive_remote(uint32_t bar, uint32_t cta) {
  asm volatile("{\n.reg .b32 ra;\nmapa.shared::cluster.u32 ra, %0, %1;\nmbarrier.arrive.relaxed.cluster.shared::cluster.b64 _, [ra];\n}" ::"r"(bar), "r"(cta) : "memory");
}
__device__ __forceinline__ void mbar_wait(uint32_t bar, uint32_t parity) {
  asm volatile("{\n.reg .pred p;\n.reg .b32 n;\nmov.b32 n, 0;\nWL:\nmbarrier.try_wait.parity.shared::cta.b64 p, [%0], %1;\n@p bra WD;\n"
               "add.u32 n, n, 1;\nsetp.lt.u32 p, n, 65536;\n@p bra WL;\nWD:\n}" ::"r"(bar), "r"(parity) : "memory");
}
__device__ __forceinline__ void nb_sync(int id, int n) { asm volatile("bar.sync %0, %1;" ::"r"(id), "r"(n) : "memory"); }
__device__ __forceinline__ void nb_arrive(int id, int n) { asm volatile("bar.arrive %0, %1;" ::"r"(id), "r"(n) : "memory"); }
__device__ __forceinline__ uint32_t opq(uint32_t x) { uint32_t r; asm volatile("mov.b32 %0, %1;" : "=r"(r) : "r"(x)); return r; }
__device__ __forceinline__ uint64_t opq(uint64_t x) { uint64_t r; asm volatile("mov.b64 %0, %1;" : "=l"(r) : "l"(x)); return r; }
__device__ __forceinline__ void fence_async() { asm volatile("fence.proxy.async.shared::cta;" ::: "memory"); }
__device__ __forceinline__ void cluster_sync() {
  asm volatile("barrier.cluster.arrive.relaxed.aligned;\nbarrier.cluster.wait.aligned;" ::: "memory");
}
__device__ __forceinline__ uint32_t pack2(float lo, float hi) {
  uint32_t r; asm("cvt.rn.bf16x2.f32 %0, %1, %2;" : "=r"(r) : "f"(hi), "f"(lo)); return r;
}
__device__ __forceinline__ void stsm4(uint32_t a, uint32_t r0, uint32_t r1, uint32_t r2, uint32_t r3) {
  asm volatile("stmatrix.sync.aligned.m8n8.x4.shared.b16 [%0], {%1,%2,%3,%4};" ::"r"(a), "r"(r0), "r"(r1), "r"(r2), "r"(r3) : "memory");
}
__device__ __forceinline__ void ldsm4(uint32_t a, uint32_t& r0, uint32_t& r1, uint32_t& r2, uint32_t& r3) {
  asm volatile("ldmatrix.sync.aligned.m8n8.x4.shared.b16 {%0,%1,%2,%3}, [%4];" : "=r"(r0), "=r"(r1), "=r"(r2), "=r"(r3) : "r"(a) : "memory");
}
__device__ __forceinline__ void sts128(uint32_t a, uint4 v) {
  asm volatile("st.shared.v4.b32 [%0], {%1,%2,%3,%4};" ::"r"(a), "r"(v.x), "r"(v.y), "r"(v.z), "r"(v.w) : "memory");
}
__device__ __forceinline__ float lds_f32(uint32_t a) { float v; asm volatile("ld.shared.f32 %0, [%1];" : "=f"(v) : "r"(a)); return v; }
__device__ __forceinline__ float ex2(float x) { float y; asm("ex2.approx.ftz.f32 %0, %1;" : "=f"(y) : "f"(x)); return y; }

template<int SC> __device__ __forceinline__ void wg_ss144(float (&d)[72], uint64_t da, uint64_t db) {
  asm volatile("{\n.reg .pred p;\nsetp.ne.b32 p, %74, 0;\nwgmma.mma_async.sync.aligned.m64n144k16.f32.bf16.bf16 {%0,%1,%2,%3,%4,%5,%6,%7,%8,%9,%10,%11,%12,%13,%14,%15,%16,%17,%18,%19,%20,%21,%22,%23,%24,%25,%26,%27,%28,%29,%30,%31,%32,%33,%34,%35,%36,%37,%38,%39,%40,%41,%42,%43,%44,%45,%46,%47,%48,%49,%50,%51,%52,%53,%54,%55,%56,%57,%58,%59,%60,%61,%62,%63,%64,%65,%66,%67,%68,%69,%70,%71}, %72, %73, p, 1, 1, 0, 1;\n}\n"
    : "+f"(d[0]),"+f"(d[1]),"+f"(d[2]),"+f"(d[3]),"+f"(d[4]),"+f"(d[5]),"+f"(d[6]),"+f"(d[7]),"+f"(d[8]),"+f"(d[9]),"+f"(d[10]),"+f"(d[11]),"+f"(d[12]),"+f"(d[13]),"+f"(d[14]),"+f"(d[15]),"+f"(d[16]),"+f"(d[17]),"+f"(d[18]),"+f"(d[19]),"+f"(d[20]),"+f"(d[21]),"+f"(d[22]),"+f"(d[23]),"+f"(d[24]),"+f"(d[25]),"+f"(d[26]),"+f"(d[27]),"+f"(d[28]),"+f"(d[29]),"+f"(d[30]),"+f"(d[31]),"+f"(d[32]),"+f"(d[33]),"+f"(d[34]),"+f"(d[35]),"+f"(d[36]),"+f"(d[37]),"+f"(d[38]),"+f"(d[39]),"+f"(d[40]),"+f"(d[41]),"+f"(d[42]),"+f"(d[43]),"+f"(d[44]),"+f"(d[45]),"+f"(d[46]),"+f"(d[47]),"+f"(d[48]),"+f"(d[49]),"+f"(d[50]),"+f"(d[51]),"+f"(d[52]),"+f"(d[53]),"+f"(d[54]),"+f"(d[55]),"+f"(d[56]),"+f"(d[57]),"+f"(d[58]),"+f"(d[59]),"+f"(d[60]),"+f"(d[61]),"+f"(d[62]),"+f"(d[63]),"+f"(d[64]),"+f"(d[65]),"+f"(d[66]),"+f"(d[67]),"+f"(d[68]),"+f"(d[69]),"+f"(d[70]),"+f"(d[71]) : "l"(da), "l"(db), "n"(SC));
}
template<int SC> __device__ __forceinline__ void wg_ss96(float (&d)[48], uint64_t da, uint64_t db) {
  asm volatile("{\n.reg .pred p;\nsetp.ne.b32 p, %50, 0;\nwgmma.mma_async.sync.aligned.m64n96k16.f32.bf16.bf16 {%0,%1,%2,%3,%4,%5,%6,%7,%8,%9,%10,%11,%12,%13,%14,%15,%16,%17,%18,%19,%20,%21,%22,%23,%24,%25,%26,%27,%28,%29,%30,%31,%32,%33,%34,%35,%36,%37,%38,%39,%40,%41,%42,%43,%44,%45,%46,%47}, %48, %49, p, 1, 1, 0, 1;\n}\n"
    : "+f"(d[0]),"+f"(d[1]),"+f"(d[2]),"+f"(d[3]),"+f"(d[4]),"+f"(d[5]),"+f"(d[6]),"+f"(d[7]),"+f"(d[8]),"+f"(d[9]),"+f"(d[10]),"+f"(d[11]),"+f"(d[12]),"+f"(d[13]),"+f"(d[14]),"+f"(d[15]),"+f"(d[16]),"+f"(d[17]),"+f"(d[18]),"+f"(d[19]),"+f"(d[20]),"+f"(d[21]),"+f"(d[22]),"+f"(d[23]),"+f"(d[24]),"+f"(d[25]),"+f"(d[26]),"+f"(d[27]),"+f"(d[28]),"+f"(d[29]),"+f"(d[30]),"+f"(d[31]),"+f"(d[32]),"+f"(d[33]),"+f"(d[34]),"+f"(d[35]),"+f"(d[36]),"+f"(d[37]),"+f"(d[38]),"+f"(d[39]),"+f"(d[40]),"+f"(d[41]),"+f"(d[42]),"+f"(d[43]),"+f"(d[44]),"+f"(d[45]),"+f"(d[46]),"+f"(d[47]) : "l"(da), "l"(db), "n"(SC));
}
template<int SC> __device__ __forceinline__ void wg_rs112(float (&d)[56], uint32_t a0, uint32_t a1, uint32_t a2, uint32_t a3, uint64_t db) {
  asm volatile("{\n.reg .pred p;\nsetp.ne.b32 p, %61, 0;\nwgmma.mma_async.sync.aligned.m64n112k16.f32.bf16.bf16 {%0,%1,%2,%3,%4,%5,%6,%7,%8,%9,%10,%11,%12,%13,%14,%15,%16,%17,%18,%19,%20,%21,%22,%23,%24,%25,%26,%27,%28,%29,%30,%31,%32,%33,%34,%35,%36,%37,%38,%39,%40,%41,%42,%43,%44,%45,%46,%47,%48,%49,%50,%51,%52,%53,%54,%55}, {%56,%57,%58,%59}, %60, p, 1, 1, 0;\n}\n"
    : "+f"(d[0]),"+f"(d[1]),"+f"(d[2]),"+f"(d[3]),"+f"(d[4]),"+f"(d[5]),"+f"(d[6]),"+f"(d[7]),"+f"(d[8]),"+f"(d[9]),"+f"(d[10]),"+f"(d[11]),"+f"(d[12]),"+f"(d[13]),"+f"(d[14]),"+f"(d[15]),"+f"(d[16]),"+f"(d[17]),"+f"(d[18]),"+f"(d[19]),"+f"(d[20]),"+f"(d[21]),"+f"(d[22]),"+f"(d[23]),"+f"(d[24]),"+f"(d[25]),"+f"(d[26]),"+f"(d[27]),"+f"(d[28]),"+f"(d[29]),"+f"(d[30]),"+f"(d[31]),"+f"(d[32]),"+f"(d[33]),"+f"(d[34]),"+f"(d[35]),"+f"(d[36]),"+f"(d[37]),"+f"(d[38]),"+f"(d[39]),"+f"(d[40]),"+f"(d[41]),"+f"(d[42]),"+f"(d[43]),"+f"(d[44]),"+f"(d[45]),"+f"(d[46]),"+f"(d[47]),"+f"(d[48]),"+f"(d[49]),"+f"(d[50]),"+f"(d[51]),"+f"(d[52]),"+f"(d[53]),"+f"(d[54]),"+f"(d[55]) : "r"(a0), "r"(a1), "r"(a2), "r"(a3), "l"(db), "n"(SC));
}
template<int SC> __device__ __forceinline__ void wg_sp48(float (&d)[24], uint32_t a0, uint32_t a1, uint32_t a2, uint32_t a3, uint64_t db, uint32_t meta) {
  asm volatile("{\n.reg .pred p;\nsetp.ne.b32 p, %30, 0;\nwgmma.mma_async.sp.sync.aligned.m64n48k32.f32.bf16.bf16 {%0,%1,%2,%3,%4,%5,%6,%7,%8,%9,%10,%11,%12,%13,%14,%15,%16,%17,%18,%19,%20,%21,%22,%23}, {%24,%25,%26,%27}, %28, %29, 0, p, 1, 1, 1;\n}\n"
    : "+f"(d[0]),"+f"(d[1]),"+f"(d[2]),"+f"(d[3]),"+f"(d[4]),"+f"(d[5]),"+f"(d[6]),"+f"(d[7]),"+f"(d[8]),"+f"(d[9]),"+f"(d[10]),"+f"(d[11]),"+f"(d[12]),"+f"(d[13]),"+f"(d[14]),"+f"(d[15]),"+f"(d[16]),"+f"(d[17]),"+f"(d[18]),"+f"(d[19]),"+f"(d[20]),"+f"(d[21]),"+f"(d[22]),"+f"(d[23]) : "r"(a0), "r"(a1), "r"(a2), "r"(a3), "l"(db), "r"(meta), "n"(SC));
}
template<int SC> __device__ __forceinline__ void wg_ss192(float (&d)[96], uint64_t da, uint64_t db) {
  asm volatile("{\n.reg .pred p;\nsetp.ne.b32 p, %98, 0;\nwgmma.mma_async.sync.aligned.m64n192k16.f32.bf16.bf16 {%0,%1,%2,%3,%4,%5,%6,%7,%8,%9,%10,%11,%12,%13,%14,%15,%16,%17,%18,%19,%20,%21,%22,%23,%24,%25,%26,%27,%28,%29,%30,%31,%32,%33,%34,%35,%36,%37,%38,%39,%40,%41,%42,%43,%44,%45,%46,%47,%48,%49,%50,%51,%52,%53,%54,%55,%56,%57,%58,%59,%60,%61,%62,%63,%64,%65,%66,%67,%68,%69,%70,%71,%72,%73,%74,%75,%76,%77,%78,%79,%80,%81,%82,%83,%84,%85,%86,%87,%88,%89,%90,%91,%92,%93,%94,%95}, %96, %97, p, 1, 1, 0, 1;\n}\n"
    : "+f"(d[0]),"+f"(d[1]),"+f"(d[2]),"+f"(d[3]),"+f"(d[4]),"+f"(d[5]),"+f"(d[6]),"+f"(d[7]),"+f"(d[8]),"+f"(d[9]),"+f"(d[10]),"+f"(d[11]),"+f"(d[12]),"+f"(d[13]),"+f"(d[14]),"+f"(d[15]),"+f"(d[16]),"+f"(d[17]),"+f"(d[18]),"+f"(d[19]),"+f"(d[20]),"+f"(d[21]),"+f"(d[22]),"+f"(d[23]),"+f"(d[24]),"+f"(d[25]),"+f"(d[26]),"+f"(d[27]),"+f"(d[28]),"+f"(d[29]),"+f"(d[30]),"+f"(d[31]),"+f"(d[32]),"+f"(d[33]),"+f"(d[34]),"+f"(d[35]),"+f"(d[36]),"+f"(d[37]),"+f"(d[38]),"+f"(d[39]),"+f"(d[40]),"+f"(d[41]),"+f"(d[42]),"+f"(d[43]),"+f"(d[44]),"+f"(d[45]),"+f"(d[46]),"+f"(d[47]),"+f"(d[48]),"+f"(d[49]),"+f"(d[50]),"+f"(d[51]),"+f"(d[52]),"+f"(d[53]),"+f"(d[54]),"+f"(d[55]),"+f"(d[56]),"+f"(d[57]),"+f"(d[58]),"+f"(d[59]),"+f"(d[60]),"+f"(d[61]),"+f"(d[62]),"+f"(d[63]),"+f"(d[64]),"+f"(d[65]),"+f"(d[66]),"+f"(d[67]),"+f"(d[68]),"+f"(d[69]),"+f"(d[70]),"+f"(d[71]),"+f"(d[72]),"+f"(d[73]),"+f"(d[74]),"+f"(d[75]),"+f"(d[76]),"+f"(d[77]),"+f"(d[78]),"+f"(d[79]),"+f"(d[80]),"+f"(d[81]),"+f"(d[82]),"+f"(d[83]),"+f"(d[84]),"+f"(d[85]),"+f"(d[86]),"+f"(d[87]),"+f"(d[88]),"+f"(d[89]),"+f"(d[90]),"+f"(d[91]),"+f"(d[92]),"+f"(d[93]),"+f"(d[94]),"+f"(d[95]) : "l"(da), "l"(db), "n"(SC));
}

constexpr uint32_t SBC = 1024;
constexpr int ROWB = 2 * 224 * 384;
constexpr int TB = 11;
constexpr int KS = 832;
constexpr int KSLOT = 22 * KS;
constexpr int SM_X2 = 0;
constexpr int SM_X0 = SM_X2 + 24576;
constexpr int SM_W = SM_X0 + 18432;
constexpr int SM_X1 = SM_W + 55296;
constexpr int SM_K = SM_X1 + 24576;
constexpr int SM_V = SM_K + 2 * KSLOT;
constexpr int SM_Q = SM_V + 22 * 1536;
constexpr int SM_O = SM_Q + 24576;
constexpr int SM_RPB = SM_O + 12288;
constexpr int SM_BAR = SM_RPB + 768;
constexpr int SM_A_TOTAL = SM_BAR + 256;
constexpr int SM_TIN = 0;
constexpr int SM_TST = 3 * 24576;
constexpr int SM_TWO = SM_TST + 12288;
enum { B_FULL = 0, B_EMPTY = 3, B_TIN = 6, B_TFREE = 10, B_WK = 12, B_WQ, B_WO, B_Q0, B_OTAIL, B_ODONE = B_OTAIL + 2, B_KFREE, B_VFREE, B_COUNT };
enum { N_KRDY = 4, N_QK0, N_QK1, N_VQ0, N_VQ1, N_PVISS };

#define NL 2
#define OPT 0
#define SPL 4
#define RA 160
#define RG 168
__device__ int g_flags[TB * 56];

#define TR(role, it, k)
#define TRDECL
#define TRARG
#define TRPASS
#define TRDUMP
#define TRB(it, k)
#define TR2(blk, k)

struct GemmCtx {
  uint32_t bar;
  uint32_t kC, vC[2], qC[2];
  uint32_t kH, vH[2];
  uint32_t hiA, hiB;
  uint32_t spin;
  bool hvalid, never;
};

template <int STRIDE> __device__ __forceinline__ void dump12(uint32_t a, const uint32_t (&r)[12]) {
#pragma unroll
  for (int j = 0; j < 3; j++) stsm4(a + j * 2 * STRIDE, r[4 * j], r[4 * j + 1], r[4 * j + 2], r[4 * j + 3]);
}
__device__ __forceinline__ void keep12(bool never, uint32_t a, const uint32_t (&r)[12]) { if (never) dump12<128>(a, r); }
template <int N> __device__ __forceinline__ void pack12(uint32_t (&r)[12], const float (&d)[N], int off) {
#pragma unroll
  for (int j = 0; j < 12; j++) r[j] = pack2(d[off + 2 * j], d[off + 2 * j + 1]);
}
__device__ __forceinline__ uint64_t dsc(uint64_t lo, uint32_t hi) { uint64_t r; asm("mov.b64 %0, {%1, %2};" : "=l"(r) : "r"((uint32_t)lo), "r"(hi)); return r; }
template <int XS, int K0, int K1> __device__ __forceinline__ void issue_core(const GemmCtx& c, float (&d)[72]) {
  constexpr uint64_t da = mkdesc(SBC + XS, 16, 1024, 1), db = mkdesc(SBC + SM_W, 6144, 256, 3);
  wg_fence();
  if (K0 == 0) wg_ss144<0>(d, dsc(da, c.hiA), dsc(db, c.hiB));
#pragma unroll
  for (int k = K0 ? K0 : 1; k < K1; k++) wg_ss144<1>(d, dsc(da + (k >> 2) * 512 + (k & 3) * 2, c.hiA), dsc(db + k * 32, c.hiB));
  wg_commit();
}
template <int K0, int K1> __device__ __forceinline__ void issue_halo(const GemmCtx& c, float (&d)[48]) {
  constexpr uint64_t da = mkdesc(SBC + SM_X0 - 2048, 16, 1024, 1), db = mkdesc(SBC + SM_W, 6144, 256, 3);
  wg_fence();
  if (K0 == 0) wg_ss96<0>(d, dsc(da, c.hiA), dsc(db, c.hiB));
#pragma unroll
  for (int k = K0 ? K0 : 1; k < K1; k++) wg_ss96<1>(d, dsc(da + (k >> 2) * 384 + (k & 3) * 2, c.hiA), dsc(db + k * 32, c.hiB));
  wg_commit();
}
template <int ST> __device__ __forceinline__ void release_stage(const GemmCtx& c) {
  asm volatile("{\n.reg .pred p;\n.reg .b32 ra;\nelect.sync _|p, 0xffffffff;\nmapa.shared::cluster.u32 ra, %0, %1;\n"
               "@p mbarrier.arrive.shared::cluster.b64 _, [ra];\n}" ::"r"(c.bar + (B_EMPTY + ST) * 8), "n"(ST) : "memory");
}
template <int PARITY> __device__ __forceinline__ void gwait(GemmCtx& c, int bar) {
  asm volatile("{\n.reg .pred p;\nWL:\nmbarrier.try_wait.parity.shared::cta.b64 p, [%1], %2;\n@p bra WD;\n"
               "add.u32 %0, %0, 1;\nsetp.lt.u32 p, %0, 0x100000;\n@p bra WL;\nWD:\n}" : "+r"(c.spin) : "r"(c.bar + bar * 8), "n"(PARITY) : "memory");
}
__device__ __forceinline__ void load_w(const CUtensorMap* m, uint32_t dst, uint32_t bar, int col) {
  asm volatile("cp.async.bulk.tensor.2d.shared::cluster.global.mbarrier::complete_tx::bytes [%0], [%1, {%3,%4}], [%2];"
               ::"r"(dst), "l"(m), "r"(bar), "r"(col), "r"(0) : "memory");
}
template <int BYTES> __device__ __forceinline__ void send_o(uint32_t dst, uint32_t src, uint32_t bar, int cta) {
  asm volatile("{\n.reg .b32 rd, rb;\nmapa.shared::cluster.u32 rd, %0, %3;\nmapa.shared::cluster.u32 rb, %2, %3;\n"
               "cp.async.bulk.shared::cluster.shared::cta.mbarrier::complete_tx::bytes [rd], [%1], %4, [rb];\n}"
               ::"r"(dst), "r"(src), "r"(bar), "r"(cta), "n"(BYTES) : "memory");
}
__device__ __forceinline__ void tail_free(uint32_t bar) {
  uint32_t ln; asm volatile("mov.u32 %0, %%laneid;" : "=r"(ln));
  if (ln < 4) mbar_arrive_remote(bar, ln);
}
__device__ __forceinline__ void publish(uint32_t bar) {
  fence_async();
  __syncwarp();
  mbar_arrive_elect(bar);
}

template <bool FIRST, int PA>
__device__ __forceinline__ void gemm_iter(GemmCtx& c, int b, uint32_t (&pk)[12], uint32_t (&pv)[12], uint32_t (&pq)[12] TRARG) {
  const uint32_t bar = c.bar;
  const bool w = !FIRST && (PA == 0 || b >= 0), never = c.never;
  constexpr uint32_t ko = PA * KSLOT;
  float H[48], C[72];
  uint32_t hk[12], hv[12], pv2[12];
  TR(2, b, 0);
  if (FIRST) gwait<PA>(c, B_FULL + 0);
  if (!FIRST) dump12<256>(c.qC[1] + (PA ^ 1) * 128, pq);
  if (w) nb_sync(N_QK1, 256);
  TR(2, b, 2);
  if (FIRST) TR(2, b - 1, 6);
  issue_halo<0, 8>(c, H);
  TR(2, b, 3);
  if (!FIRST) {
    if (w) gwait<PA>(c, B_KFREE);
    dump12<128>(c.kC + ko, pk);
  }
  issue_halo<8, 12>(c, H);
  TR(2, b, 4);
  {
    gwait<PA>(c, B_FULL + 2);
    if (FIRST && NL == 2) gwait<0>(c, B_WQ);
    TR(2, b, 13);
    if (FIRST) TR(2, b - 1, 7);
    issue_core<SM_X2, 0, 8>(c, C);
    TR(2, b, 5);
    if (!FIRST) { fence_async(); keep12(never, c.kC, pk); }
    wg_wait<1>(); pin(H);
    release_stage<0>(c);
  }
  pack12(hk, H, 0);
  if (c.hvalid) dump12<128>(c.kH + ko, hk);
  pack12(hv, H, 24);
  {
    issue_core<SM_X2, 8, 12>(c, C);
    if (w) { nb_arrive(N_VQ0, 288); nb_arrive(N_VQ1, 288); }
    else if (!FIRST) { __syncwarp(); mbar_arrive_elect(bar + B_Q0 * 8); }
    gwait<PA>(c, B_FULL + 1);
    keep12(never, c.kC, hk);
    TR(2, b, 6);
    wg_wait<0>(); pin(C);
    TR(2, b, 7);
    pack12(pk, C, 0);
    dump12<128>(c.kC + ko + 64, pk);
    release_stage<2>(c);
    pack12(pv2, C, 24);
    pack12(pq, C, 48);
    TR(2, b, 8);
    issue_core<SM_X1, 0, SPL>(c, C);
    if (w) nb_sync(N_PVISS, 384);
    issue_core<SM_X1, SPL, 8>(c, C);
    TR(2, b, 9);
  }
  if (!FIRST) fence_async();
  keep12(never, c.kC, pk);
  TR(2, b, 14);
  issue_core<SM_X1, 8, 12>(c, C);
  if (!FIRST) nb_arrive(N_KRDY, 256);
  TR(2, b, 1);
  if (PA && b == 11) tail_free(bar + B_TFREE * 8);
  gwait<PA ^ 1>(c, B_FULL + 0);
  if (w) gwait<PA>(c, B_VFREE);
  TR(2, b, 10);
  if (!FIRST) dump12<128>(c.vC[PA], pv);
  dump12<256>(c.qC[0] + PA * 128, pq);
  if (c.hvalid) dump12<128>(c.vH[PA], hv);
  dump12<128>(c.vC[PA ^ 1] + 768, pv2);
  TR(2, b, 11);
  wg_wait<0>(); pin(C);
  TR(2, b, 12);
  release_stage<1>(c);
  pack12(pk, C, 0);
  pack12(pv, C, 24);
  pack12(pq, C, 48);
}

template <int IN> __device__ __forceinline__ void issue_proj(float (&D)[48]) {
  constexpr uint64_t da = mkdesc(SBC + IN, 128, 768, 0), db = mkdesc(SBC + SM_TWO, 12288, 512, 2);
  wg_fence();
  wg_ss96<0>(D, da, db);
#pragma unroll
  for (int k = 1; k < 12; k++) wg_ss96<1>(D, da + (k / 3) * 384 + (k % 3) * 16, db + k * 64);
  wg_commit();
}
__device__ __forceinline__ void store_proj(const float (&D)[48], const CUtensorMap* m, uint32_t st, uint32_t sta, int row, int col, int ch) {
#pragma unroll
  for (int q = 0; q < 6; q++)
    stsm4((sta ^ ((q & 1) * 32)) + (q >> 1) * 1024,
          pack2(D[8 * q], D[8 * q + 1]), pack2(D[8 * q + 2], D[8 * q + 3]), pack2(D[8 * q + 4], D[8 * q + 5]), pack2(D[8 * q + 6], D[8 * q + 7]));
  fence_async();
  __syncwarp();
  if ((threadIdx.x & 31) == 0) {
    asm volatile("cp.async.bulk.tensor.4d.global.shared::cta.bulk_group [%0, {%2,%3,%4,%5}], [%1];" ::"l"(m), "r"(st), "r"(0), "r"(row), "r"(col), "r"(ch) : "memory");
    asm volatile("cp.async.bulk.commit_group;" ::: "memory");
  }
  __syncwarp();
}

__device__ __forceinline__ float fold(float a, float b, float t, int useb) {
  float r;
  asm("{\n.reg .pred p;\nsetp.ne.b32 p, %4, 0;\nfma.rn.f32 %0, %1, 0f3E553B95, %3;\n@p fma.rn.f32 %0, %2, 0f3E553B95, %3;\n}"
      : "=&f"(r) : "f"(a), "f"(b), "f"(t), "r"(useb));
  return r;
}
template <int U, int L>
__device__ __forceinline__ void softmax_tile(const float (&SA)[56], const float (&SB)[56], const float (&T)[16], int b0, int b1,
                                             uint32_t (&P)[28], float (&sx)[8]) {
  float lu[14], ll[14];
#pragma unroll
  for (int j = 0; j < 7; j++) {
    constexpr int sh = U == L ? 2 : 0;
    const float tu0 = T[2 * j + sh], tu1 = T[2 * j + 1 + sh], tl0 = T[2 * j], tl1 = T[2 * j + 1];
    lu[2 * j]     = fold(SA[4 * (U + j)],     SB[4 * (U + j)],     tu0, b0);
    ll[2 * j]     = fold(SA[4 * (L + j) + 2], SB[4 * (L + j) + 2], tl0, b0);
    lu[2 * j + 1] = fold(SA[4 * (U + j) + 1], SB[4 * (U + j) + 1], tu1, b1);
    ll[2 * j + 1] = fold(SA[4 * (L + j) + 3], SB[4 * (L + j) + 3], tl1, b1);
  }
  float mu = lu[0], ml = ll[0], mu2 = lu[1], ml2 = ll[1];
#pragma unroll
  for (int j = 1; j < 7; j++) { mu = fmaxf(mu, lu[2 * j]); mu2 = fmaxf(mu2, lu[2 * j + 1]); ml = fmaxf(ml, ll[2 * j]); ml2 = fmaxf(ml2, ll[2 * j + 1]); }
  mu = fmaxf(mu, mu2); ml = fmaxf(ml, ml2);
  { const float a1 = __shfl_xor_sync(0xffffffffu, mu, 1), a2 = __shfl_xor_sync(0xffffffffu, mu, 2), a3 = __shfl_xor_sync(0xffffffffu, mu, 3);
    const float c1 = __shfl_xor_sync(0xffffffffu, ml, 1), c2 = __shfl_xor_sync(0xffffffffu, ml, 2), c3 = __shfl_xor_sync(0xffffffffu, ml, 3);
    mu = fmaxf(fmaxf(mu, a1), fmaxf(a2, a3)); ml = fmaxf(fmaxf(ml, c1), fmaxf(c2, c3)); }
  float su = 0.f, sl = 0.f;
#pragma unroll
  for (int c = 0; c < 14; c++) {
    const int iu = (c >> 1) * 4 + (c & 1) * 2;
    if (c >= U && c < U + 7) {
      float e0 = ex2(lu[2 * (c - U)] - mu), e1 = ex2(lu[2 * (c - U) + 1] - mu);
      su = c == U ? e0 + e1 : (su + e0) + e1; P[iu] = pack2(e0, e1);
    } else P[iu] = 0u;
    if (c >= L && c < L + 7) {
      float e0 = ex2(ll[2 * (c - L)] - ml), e1 = ex2(ll[2 * (c - L) + 1] - ml);
      sl = c == L ? e0 + e1 : (sl + e0) + e1; P[iu + 1] = pack2(e0, e1);
    } else P[iu + 1] = 0u;
  }
  sx[0] = su; sx[4] = sl;
#pragma unroll
  for (int k = 1; k < 4; k++) { sx[k] = __shfl_xor_sync(0xffffffffu, su, k); sx[4 + k] = __shfl_xor_sync(0xffffffffu, sl, k); }
}

struct BandCfg { uint32_t ra0, ra1, meta; int b0, b1; };
__device__ __forceinline__ void band_cfg(int b, uint32_t tb, BandCfg& n) {
  uint32_t ln; asm volatile("mov.u32 %0, %%laneid;" : "=r"(ln));
  const int g = ln >> 2, t = ln & 3;
  const int sw = min(max(g + 1, b == 0 ? 4 : 0), b == 13 ? 5 : 8);
  const int i0 = 2 * t, i1 = 2 * t + 1;
  n.b0 = i0 <= sw - 2; n.b1 = i1 <= sw - 2;
  n.ra0 = tb + (i0 == sw - 1 ? 13 : i0 + 8 * n.b0 - g + 2) * 52;
  n.ra1 = tb + (i1 == sw - 1 ? 13 : i1 + 8 * n.b1 - g + 2) * 52;
  n.meta = ((0x5555u & ((1u << (2 * (sw - 1))) - 1)) ^ 0xDD88u ^ (((t ^ b) & 1) ? 0x5555u : 0u)) * 0x10001u;
}
__device__ __forceinline__ void band_load(const BandCfg& n, float (&T)[16], int& b0, int& b1, uint32_t& meta) {
#pragma unroll
  for (int jj = 0; jj < 8; jj++) { T[2 * jj] = lds_f32(n.ra0 + jj * 4); T[2 * jj + 1] = lds_f32(n.ra1 + jj * 4); }
  b0 = n.b0; b1 = n.b1; meta = n.meta;
}

struct Maps { CUtensorMap xc, xh, w, os, wo, ot; };

__global__ void __cluster_dims__(4, 1, 1) __launch_bounds__(512, 1)
na_attn_kernel(const __nv_bfloat16* __restrict__ x, const __nv_bfloat16* __restrict__ wqkv, const __nv_bfloat16* __restrict__ rpb, const __grid_constant__ Maps mp) {
  extern __shared__ __align__(1024) uint8_t smem_raw[];
  const uint32_t sb = smem_u32(smem_raw);
  if ((sb & 0x3FFFF) != SBC) return;
  const uint32_t bar = sb + SM_BAR;
  TR2(blockIdx.x, 0);
  const int tid = threadIdx.x, lane = tid & 31;
  const int warp = __shfl_sync(0xffffffffu, tid >> 5, 0);
  const int head = blockIdx.x & 3, cl = blockIdx.x >> 2;
  const int par = cl / 7, strip = cl - par * 7, ph = par >> 1, pw = par & 1;

  uint4 wv[2 * NL];
  const int va = head == 1;
  const uint32_t wdst = sb + SM_W + (va + ((tid >> 1) & 1)) * 6144 + (tid >> 2) * 32 + ((tid ^ (tid >> 4)) & 1) * 16;
  if (warp < 12) asm volatile("barrier.cluster.arrive.relaxed.aligned;" ::: "memory");
  {
    const uint32_t wo0 = (tid >> 2) * 1152 + head * 96 + va * 32 + (tid & 3) * 16;
#pragma unroll
    for (int i = 0; i < 2 * NL; i++)
      asm volatile("{\n.reg .pred p;\nsetp.lt.u32 p, %5, 384;\n@p ld.global.nc.v4.b32 {%0,%1,%2,%3}, [%4];\n}"
                   : "=r"(wv[i].x), "=r"(wv[i].y), "=r"(wv[i].z), "=r"(wv[i].w)
                   : "l"(reinterpret_cast<const uint8_t*>(wqkv) + wo0 + (i & 1) * 96 * 1152 + ((i / 2 + 1) % 3) * 384), "r"(tid));
  }
  if (warp < 8) {
    asm volatile("setmaxnreg.inc.sync.aligned.u32 %0;" ::"n"(RA));
    float rv = -INFINITY;
    if (tid < 169) rv = __bfloat162float(rpb[head * 169 + tid]) * 1.4426950408889634f;
    if (tid < 192) {
      const int kc = (tid & 15) + 3, wc = (tid >> 4) % 6;
      sts128(tid < 96 ? sb + SM_K + kc * KS + wc * 128 + 48 : sb + SM_V + kc * 1536 + wc * 128 + (6 + (kc & 1)) * 16, make_uint4(0, 0, 0, 0));
    }
#pragma unroll
    for (int i = 0; i < 2 * NL; i++) sts128(wdst + (i & 1) * 3072 + (i / 2) * 18432, wv[i]);
    fence_async();
    asm volatile("bar.arrive 1, 384;" ::: "memory");
    if (tid < 182) asm volatile("st.shared.f32 [%0], %1;" ::"r"(sb + SM_RPB + tid * 4), "f"(rv) : "memory");
    const int j = warp >> 2, w = warp & 3;
    int variant = w;
    if (strip == 0 && j == 0 && w < 2) variant = 4;
    if (strip == 6 && j == 1 && w >= 2) variant = 5;
    const bool v1 = opq((uint32_t)(variant & 1)), v2 = opq((uint32_t)(variant & 2)), v4 = opq((uint32_t)(variant & 4));
    uint32_t qa = opq(sb + SM_Q + (8 * j + 2 * w + ((lane >> 3) & 1)) * 1536 + (lane >> 4) * 256 + (((lane & 7) * 16) ^ (((lane >> 3) & 1) * 64)));
    uint32_t oa = opq(sb + SM_O + j * 6144 + (2 * w + ((lane >> 3) & 1)) * 768 + (lane >> 4) * 128 + (lane & 7) * 16);
    uint64_t dA = opq(mkdesc(SBC + SM_K, 128, KS, 0) + j * (8 * KS / 16)), dB = opq(dA + (KSLOT >> 4));
    uint64_t dV[7];
#pragma unroll
    for (int i = 0; i < 7; i++) dV[i] = opq(mkdesc(SBC + SM_V, 768, 128, 0) + j * (8 * 1536 / 16) + i * 192);
    const uint32_t nbK = opq((uint32_t)(N_KRDY + j)), nbQ = opq((uint32_t)(N_QK0 + j)), nbV = opq((uint32_t)(N_VQ0 + j));
    asm volatile("barrier.cluster.wait.aligned;" ::: "memory");
    asm volatile("bar.sync 3, 256;" ::: "memory");
    float T[16];
    TRDECL;
    int b0, b1;
    uint32_t meta, ob = bar + B_ODONE * 8;
    const uint32_t tb = opq(sb + SM_RPB + (variant < 4 ? 3 : variant + 1 - 2 * w) * 4);
    BandCfg nx;
    band_cfg(0, tb, nx);
    band_load(nx, T, b0, b1, meta);
    meta ^= 0x55555555u;
    band_cfg(1, tb, nx);
    uint32_t q[12];
    mbar_wait(bar + B_Q0 * 8, 0);
#pragma unroll
    for (int k = 0; k < 3; k++) ldsm4(qa + k * 512, q[4 * k], q[4 * k + 1], q[4 * k + 2], q[4 * k + 3]);
#pragma unroll 1
    for (int b = 0; b < 14; b++) {
      float SA[56], SB[56];
      TR(0, b, 0);
      nb_sync(nbK, 256);
      TR(0, b, 1);
      TR(0, b - 1, 9);
      wg_fence();
      wg_rs112<0>(SA, q[0], q[1], q[2], q[3], dA);
      wg_rs112<0>(SB, q[0], q[1], q[2], q[3], dB);
      wg_rs112<1>(SA, q[4], q[5], q[6], q[7], dA + 16);
      wg_rs112<1>(SB, q[4], q[5], q[6], q[7], dB + 16);
      wg_rs112<1>(SA, q[8], q[9], q[10], q[11], dA + 32);
      wg_rs112<1>(SB, q[8], q[9], q[10], q[11], dB + 32);
      wg_commit();
      nb_arrive(nbQ, 256);
      { const uint64_t t = dA; dA = dB; dB = t; }
      qa ^= 128;
      meta ^= 0x55555555u;
      if (b == 1 || b == 13) band_load(nx, T, b0, b1, meta);
      TR(0, b, 2);
      wg_wait<0>(); pin(SA); pin(SB);
      mbar_arrive_elect(bar + B_KFREE * 8);
      TR(0, b, 3);
      TR(0, b - 1, 10);
      uint32_t P[28];
      float sx[8];
      if (v2) {
        if (v1) softmax_tile<6, 7>(SA, SB, T, b0, b1, P, sx); else softmax_tile<4, 5>(SA, SB, T, b0, b1, P, sx);
      } else if (!v4) {
        if (v1) softmax_tile<2, 3>(SA, SB, T, b0, b1, P, sx); else softmax_tile<0, 1>(SA, SB, T, b0, b1, P, sx);
      } else {
        if (v1) softmax_tile<4, 4>(SA, SB, T, b0, b1, P, sx); else softmax_tile<3, 3>(SA, SB, T, b0, b1, P, sx);
      }
      float O[24];
      TR(0, b, 4);
      if (b == 3) band_cfg(13, tb, nx);
      nb_sync(nbV, 288);
      TR(0, b, 5);
#pragma unroll
      for (int k = 0; k < 3; k++) ldsm4(qa + k * 512, q[4 * k], q[4 * k + 1], q[4 * k + 2], q[4 * k + 3]);
      wg_fence();
      wg_sp48<0>(O, P[0], P[1], P[2], P[3], dV[0], meta);
#pragma unroll
      for (int s = 1; s < 7; s++) wg_sp48<1>(O, P[4 * s], P[4 * s + 1], P[4 * s + 2], P[4 * s + 3], dV[s], meta);
      wg_commit();
      nb_arrive(N_PVISS, 384);
      TR(0, b, 6);
      wg_wait<0>(); pin(O);
      mbar_arrive_elect(bar + B_VFREE * 8);
      TR(0, b, 7);
      float ru, rl;
      asm("rcp.approx.ftz.f32 %0, %1;" : "=f"(ru) : "f"(((fmaf(O[0], 0.f, sx[0]) + sx[1]) + sx[2]) + sx[3]));
      asm("rcp.approx.ftz.f32 %0, %1;" : "=f"(rl) : "f"(((fmaf(O[2], 0.f, sx[4]) + sx[5]) + sx[6]) + sx[7]));
#pragma unroll
      for (int i = 0; i < 3; i++)
        stsm4(oa + i * 256, pack2(O[8 * i] * ru, O[8 * i + 1] * ru), pack2(O[8 * i + 2] * rl, O[8 * i + 3] * rl),
              pack2(O[8 * i + 4] * ru, O[8 * i + 5] * ru), pack2(O[8 * i + 6] * rl, O[8 * i + 7] * rl));
      publish(ob);
      if (b >= TB - 1) {
        ob = opq(bar + (B_OTAIL + j) * 8);
        oa += b == 11 ? warp * 1536 - (SM_O - SM_Q) : (b == 12 ? 1536 : 0);
      }
      TR(0, b, 8);
    }
    if (elect_one()) {
#pragma unroll
      for (int d = 0; d < 2; d++)
        send_o<1536>(sb + SM_TIN + 2 * 24576 + head * 6144 + (2 * j + (w & 1)) * 1536, sb + SM_Q + warp * 3072 + 1536, bar + (B_TIN + 2 + d) * 8, (w & 2) + (d ^ (head & 1)));
    }
    __syncwarp();
    if (((OPT & 2) && j == 0) || ((OPT & 4) && j == 1)) nb_arrive(3, (OPT & 6) == 6 ? 384 : 256);
    TRDUMP;
    cluster_sync();
  } else if (warp < 12) {
    TRDECL;
    TR(2, -3, 0);
    asm volatile("setmaxnreg.inc.sync.aligned.u32 %0;" ::"n"(RG));
    TR(2, -3, 1);
    GemmCtx c;
    c.bar = bar;
    const int gw = warp - 8, tk = gw * 16 + (lane & 15), hi = lane >> 4;
    { const int col = tk >> 2, i = tk & 3;
      c.kC = sb + SM_K + (col + 3) * KS + hi * 128 + i * 16;
      c.vC[0] = sb + SM_V + (col + 3) * 1536 + hi * 128 + (2 * i + ((col + 3) & 1)) * 16;
      c.qC[0] = sb + SM_Q + col * 1536 + hi * 256 + (col & 1) * 64 + i * 16; }
    { const int ci = (tk >> 3) - 2, kc = ci < 3 ? ci : ci + 16, i = tk & 7; c.hvalid = gw > 0;
      c.kH = sb + SM_K + kc * KS + hi * 128 + i * 16;
      c.vH[0] = sb + SM_V + kc * 1536 + hi * 128 + (i >> 2) * 768 + (2 * (i & 3) + ((kc ^ (i >> 2)) & 1)) * 16; }
    c.never = x == nullptr;
    c.kC = opq(c.kC); c.kH = opq(c.kH);
    c.vC[1] = opq(c.vC[0] ^ 16); c.vC[0] = opq(c.vC[0]);
    c.vH[1] = opq(c.vH[0] ^ 16); c.vH[0] = opq(c.vH[0]);
    c.qC[1] = opq(c.qC[0] ^ 64); c.qC[0] = opq(c.qC[0]);
    c.spin = 0;
    c.hiA = (uint32_t)(mkdesc(0, 0, 1024, 1) >> 32) + (blockIdx.x >> 16); c.hiB = (uint32_t)(mkdesc(0, 0, 256, 3) >> 32) + (blockIdx.x >> 16);
    asm volatile("barrier.cluster.wait.aligned;" ::: "memory");
    TR(2, -3, 2);
#pragma unroll
    for (int i = 0; i < 2 * NL; i++) sts128(wdst + (i & 1) * 3072 + (i / 2) * 18432, wv[i]);
    fence_async();
    TR(2, -3, 3);
    asm volatile("bar.sync 1, 384;" ::: "memory");
    TR(2, -3, 4);
    mbar_wait(bar + B_WK * 8, 0);
    TR(2, -3, 5);
    uint32_t pk[12], pv[12], pq[12];
    gemm_iter<true, 0>(c, -2, pk, pv, pq TRPASS);
    TR2(blockIdx.x, 4);
#pragma unroll 1
    for (int b = -1;; b += 2) {
      gemm_iter<false, 1>(c, b, pk, pv, pq TRPASS);
      if (b == 11) break;
      gemm_iter<false, 0>(c, b + 1, pk, pv, pq TRPASS);
    }
    TR2(blockIdx.x, 6);
    const uint32_t st = sb + gw * 3072;
    const uint32_t sta = st + (lane & 15) * 64 + ((hi ^ ((lane >> 1) & 3)) * 16);
    const int oc = ph * 112 + strip * 16 + 8 * (gw >> 1) + 4 * (head >> 1) + 2 * (gw & 1), och = pw * 6 + (head & 1) * 3;
    float D0[48], D1[48];
    dump12<256>(c.qC[1] + 128, pq);
    nb_sync(N_QK1, 256);
    if (gw == 1 && elect_one()) {
      mbar_expect(bar + B_WO * 8, 36864);
      asm volatile("cp.async.bulk.tensor.3d.shared::cluster.global.mbarrier::complete_tx::bytes [%0], [%1, {%3,%4,%5}], [%2];"
                   ::"r"(sb + SM_TWO), "l"(&mp.wo), "r"(bar + B_WO * 8), "r"(0), "r"(0), "r"((head & 1) * 3) : "memory");
    }
    __syncwarp();
    issue_halo<0, 12>(c, D1);
    gwait<0>(c, B_KFREE);
    dump12<128>(c.kC, pk);
    fence_async();
    nb_arrive(N_VQ0, 288); nb_arrive(N_VQ1, 288); nb_arrive(N_PVISS, 384);
    wg_wait<0>(); pin(D1);
    tail_free(bar + (B_TFREE + 1) * 8);
    pack12(pk, D1, 0);
    if (c.hvalid) dump12<128>(c.kH, pk);
    TR(2, 13, 0);
    gwait<0>(c, B_WO);
    gwait<0>(c, B_TIN);
    TR(2, 13, 9);
    issue_proj<SM_TIN>(D0);
    pack12(pq, D1, 24);
    fence_async();
    nb_arrive(N_KRDY, 256);
    gwait<0>(c, B_VFREE);
    dump12<128>(c.vC[0], pv);
    if (c.hvalid) dump12<128>(c.vH[0], pq);
    fence_async();
    nb_arrive(N_VQ0, 288); nb_arrive(N_VQ1, 288); nb_arrive(N_QK1, 256);
    wg_wait<0>(); pin(D0);
    store_proj(D0, &mp.ot, st + SM_TST, sta + SM_TST, 8 * TB, oc, och);
    gwait<0>(c, B_TIN + 1);
    TR(2, 13, 1);
    nb_sync(N_PVISS, 384);
    if (OPT & 6) nb_sync(3, (OPT & 6) == 6 ? 384 : 256);
    issue_proj<SM_TIN + 24576>(D1);
    TR(2, 13, 2);
    wg_wait<0>(); pin(D1);
    TR(2, 13, 3);
    store_proj(D1, &mp.ot, st + SM_TIN, sta + SM_TIN, 8 * TB + 8, oc, och);
    TR(2, 13, 4);
    {
      const uint64_t da = mkdesc(SBC + SM_TIN + 2 * 24576, 128, 768, 0), db = mkdesc(SBC + SM_TWO, 12288, 512, 2);
#pragma unroll
      for (int g = 0; g < 2; g++) {
        const int hd = (head ^ g) & 1;
        mbar_wait(bar + (B_TIN + 2 + g) * 8, 0);
        TR(2, 13, 5 + g);
        wg_fence();
#pragma unroll
        for (int k = 0; k < 6; k++) {
          const uint64_t a = da + hd * 384 + (k / 3) * 768 + (k % 3) * 16, bb = db + hd * 192 + (k / 3) * 384 + (k % 3) * 64;
          if (g + k == 0) wg_ss96<0>(D0, a, bb); else wg_ss96<1>(D0, a, bb);
        }
        wg_commit();
      }
    }
    asm volatile("barrier.cluster.arrive.relaxed.aligned;" ::: "memory");
    wg_wait<0>(); pin(D0);
    store_proj(D0, &mp.ot, st + SM_TIN + 12288, sta + SM_TIN + 12288, 8 * TB + 16, oc, och);
    TR(2, 13, 7);
    if (lane == 0) asm volatile("cp.async.bulk.wait_group.read 0;" ::: "memory");
    __syncwarp();
    TR(2, 13, 8);
    TR2(blockIdx.x, 2);
    TRDUMP;
    asm volatile("barrier.cluster.wait.aligned;" ::: "memory");
  } else {
    if (warp == 12) {
      if (elect_one()) {
        mbar_init(bar + B_WK * 8, 1);
#pragma unroll
        for (int i = 0; i < NL; i++) load_w(&mp.w, sb + SM_W + (3 * i + 2 - 2 * va) * 6144, bar + B_WK * 8, ((i + 1) % 3) * 192 + head * 48 + 32 - 32 * va);
        asm volatile("prefetch.tensormap [%0];" ::"l"(head ? &mp.xc : &mp.xh) : "memory");
        mbar_expect(bar + B_WK * 8, NL * 6144);
      }
    } else if (warp == 15) {
      const int col = min(max(strip * 16 - 3 + min(lane, 21), 0), 111);
      const uint8_t* p = reinterpret_cast<const uint8_t*>(x) + (uint32_t)(head * ROWB + (ph * 112 + col) * 768 + pw * 384);
#pragma unroll
      for (int i = 0; i < 3; i++) asm volatile("prefetch.global.L2 [%0];" ::"l"(p + i * 128));
    } else if (elect_one()) {
      if (warp == 13) {
#pragma unroll
        for (int i = 0; i < B_WK; i++) mbar_init(bar + i * 8, i < B_EMPTY ? 1 : (i < B_TIN ? 16 : (i < B_TFREE ? 1 : 16)));
      } else {
#pragma unroll
        for (int i = B_WQ; i < B_COUNT; i++) mbar_init(bar + i * 8, i < B_Q0 ? 1 : (i < B_ODONE ? 4 : 8));
      }
    }
    asm volatile("fence.mbarrier_init.release.cluster;" ::: "memory");
    __syncwarp();
    asm volatile("barrier.cluster.arrive.relaxed.aligned;" ::: "memory");
    asm volatile("setmaxnreg.dec.sync.aligned.u32 24;");
    asm volatile("griddepcontrol.launch_dependents;");
    const int cc = ph * 112 + (head ? strip * 16 : (strip == 0 ? 16 : (strip == 6 ? 74 : strip * 16 - 3)));
    const int sd = strip == 0 ? -1 : (strip == 6 ? 1 : 0);
    const int r0 = head == 0 ? -4 : (head == 1 ? 4 : 0);
    asm volatile("barrier.cluster.wait.aligned;" ::: "memory");
    if (warp == 12) {
      const uint32_t fb = bar + (B_FULL + head) * 8, eb = bar + (B_EMPTY + head) * 8;
      const uint32_t dst = sb + (head == 0 ? SM_X0 : (head == 1 ? SM_X1 : SM_X2));
      const int nl = head == 0 ? 15 : (head == 3 ? 1 : 14);
#pragma unroll 1
      for (int n = 0; n < nl; n++) {
        if (n) mbar_wait(eb, (n - 1) & 1);
        if (lane < 4 && head < 3)
          asm volatile("{\n.reg .b32 ra;\nmapa.shared::cluster.u32 ra, %0, %1;\nmbarrier.arrive.expect_tx.shared::cluster.b64 _, [ra], %2;\n}"
                       ::"r"(fb), "r"(lane), "r"(head ? 24576 : 18432) : "memory");
        __syncwarp();
        if (elect_one()) {
          if (head == 0) {
            asm volatile("cp.async.bulk.tensor.5d.shared::cluster.global.mbarrier::complete_tx::bytes.multicast::cluster [%0], [%1, {%3,%4,%5,%6,%7}], [%2], %8;"
                         ::"r"(dst), "l"(&mp.xh), "r"(fb), "r"(0), "r"(8 * n + r0), "r"(cc), "r"(sd), "r"(pw * 3), "h"((uint16_t)15) : "memory");
          } else if (head < 3) {
            asm volatile("cp.async.bulk.tensor.4d.shared::cluster.global.mbarrier::complete_tx::bytes.multicast::cluster [%0], [%1, {%3,%4,%5,%6}], [%2], %7;"
                         ::"r"(dst), "l"(&mp.xc), "r"(fb), "r"(0), "r"(8 * n + r0), "r"(cc), "r"(pw * 3), "h"((uint16_t)15) : "memory");
          }
          if (n == 0) {
#pragma unroll
            for (int i = 0; i < 3; i++) load_w(&mp.w, sb + SM_W + (6 + i) * 6144, bar + B_WQ * 8, head * 48 + i * 16);
            mbar_expect(bar + B_WQ * 8, 18432);
            mbar_expect(bar + B_TIN * 8, 24576); mbar_expect(bar + (B_TIN + 1) * 8, 24576); mbar_expect(bar + (B_TIN + 2) * 8, 12288); mbar_expect(bar + (B_TIN + 3) * 8, 12288);
          }
          if (!head && n + 1 < nl) asm volatile("cp.async.bulk.prefetch.tensor.5d.L2.global [%0, {%1,%2,%3,%4,%5}];" ::"l"(&mp.xh), "r"(0), "r"(8 * n + 8 + r0), "r"(cc), "r"(sd), "r"(pw * 3) : "memory");
          if (head && n + 1 < nl) asm volatile("cp.async.bulk.prefetch.tensor.4d.L2.global [%0, {%1,%2,%3,%4}];" ::"l"(&mp.xc), "r"(0), "r"(8 * n + 8 + r0), "r"(cc), "r"(pw * 3) : "memory");
        }
        __syncwarp();
      }
    }
    if (warp == 14) {
      int* flag = g_flags + cl * 2;
      nb_arrive(N_VQ0, 288); nb_arrive(N_VQ1, 288);
#pragma unroll 1
      for (int b = 0; b < TB; b++) {
        mbar_wait(bar + B_ODONE * 8, b & 1);
        if (lane == 0) {
          asm volatile("cp.async.bulk.tensor.3d.global.shared::cta.bulk_group [%0, {%2,%3,%4}], [%1];"
                       ::"l"(&mp.os), "r"(sb + SM_O), "r"(pw * 192), "r"(8 * b + 2 * head), "r"(ph * 112 + strip * 16) : "memory");
          asm volatile("cp.async.bulk.commit_group;\ncp.async.bulk.wait_group 0;" ::: "memory");
        }
        __syncwarp();
        nb_arrive(N_VQ0, 288); nb_arrive(N_VQ1, 288);
        if (lane == 0)
          asm volatile("fence.proxy.async.global;\nfence.acq_rel.gpu;\nred.relaxed.gpu.global.add.s32 [%0], 1;\nred.relaxed.gpu.global.add.s32 [%0+4], 1;"
                       ::"l"(flag + b * 56) : "memory");
        __syncwarp();
      }
    } else if (warp & 1) {
      const int j = (warp >> 1) & 1;
#pragma unroll 1
      for (int i = 0; i < 2; i++) {
        mbar_wait(bar + (B_OTAIL + j) * 8, i);
        if (i == 0) nb_arrive(N_VQ0 + j, 288);
        mbar_wait(bar + (B_TFREE + i) * 8, 0);
        if (i == 1) nb_arrive(N_VQ0 + j, 288);
        if (elect_one()) {
#pragma unroll 1
          for (int d = 0; d < 8; d++) {
            const int dst = (d + head) & 3, pc = d >> 2;
            send_o<1536>(sb + SM_TIN + i * 24576 + head * 6144 + j * 3072 + pc * 1536,
                         sb + (i ? SM_Q : SM_O) + (4 * j + (dst & 2) + pc) * (i ? 3072 : 1536), bar + (B_TIN + i) * 8, dst);
          }
        }
        __syncwarp();
      }
    }
    cluster_sync();
  }
}

constexpr int NSTB = 6;
constexpr int NTB = TB * 56;
constexpr int SM_B_IN = 0;
constexpr int SM_B_W = SM_B_IN + NSTB * 24576;
constexpr int SM_B_BAR = SM_B_W + 73728;
constexpr int SM_B_TOTAL = SM_B_BAR + 128;
struct MapsB { CUtensorMap oi, oo, wo; };

__global__ void __launch_bounds__(480, 1)
na_proj_kernel(const __grid_constant__ MapsB mp) {
  extern __shared__ __align__(1024) uint8_t smem_raw[];
  const uint32_t sb = smem_u32(smem_raw);
  if ((sb & 0x3FFFF) != SBC) return;
  const uint32_t bar = sb + SM_B_BAR;
  const int tid = threadIdx.x, lane = tid & 31;
  const int warp = __shfl_sync(0xffffffffu, tid >> 5, 0);
  TR2(132 + blockIdx.x, 0);
  TRB(47, 0);
  if (warp == 12 && elect_one()) {
#pragma unroll
    for (int i = 0; i <= 2 * NSTB; i++) mbar_init(bar + i * 8, i < NSTB || i == 2 * NSTB ? 1 : 4);
    mbar_expect(bar + 2 * NSTB * 8, 73728);
#pragma unroll
    for (int i = 0; i < 2; i++)
      asm volatile("cp.async.bulk.tensor.3d.shared::cluster.global.mbarrier::complete_tx::bytes [%0], [%1, {%3,%4,%5}], [%2];"
                   ::"r"(sb + SM_B_W + i * 36864), "l"(&mp.wo), "r"(bar + 2 * NSTB * 8), "r"(0), "r"(0), "r"(i * 3) : "memory");
  }
  __syncthreads();
  const int step = gridDim.x;
  if (warp >= 12) {
    const int wg = warp - 12;
    int use = 0;
#pragma unroll 1
    for (int n = blockIdx.x + wg * step; n < NTB; n += 3 * step, use++) {
      const int b = n / 56, rem = n - b * 56, par = rem / 14, sg = wg + 3 * (use & 1);
      int v; uint32_t spin = 0;
      do { asm volatile("ld.acquire.gpu.global.s32 %0, [%1];" : "=r"(v) : "l"(g_flags + n) : "memory"); if ((OPT & 1) && v < 4) __nanosleep(200); } while (v < 4 && ++spin < SPIN_LIMIT);
      TRB(use * 3 + wg, 0);
      asm volatile("fence.proxy.async.global;" ::: "memory");
      if (use >= 2) mbar_wait(bar + (NSTB + sg) * 8, ((use >> 1) - 1) & 1);
      TRB(use * 3 + wg, 1);
      if (elect_one()) {
        mbar_expect(bar + sg * 8, 24576);
        asm volatile("cp.async.bulk.tensor.3d.shared::cluster.global.mbarrier::complete_tx::bytes [%0], [%1, {%3,%4,%5}], [%2];"
                     ::"r"(sb + SM_B_IN + sg * 24576), "l"(&mp.oi), "r"(bar + sg * 8), "r"((par & 1) * 192), "r"(8 * b), "r"((par >> 1) * 112 + (rem - par * 14) * 8) : "memory");
        g_flags[n] = 0;
      }
      __syncwarp();
    }
  } else {
    const int wg = warp >> 2, w = warp & 3;
    constexpr uint64_t db = mkdesc(SBC + SM_B_W, 12288, 512, 2);
    const uint32_t sta0 = sb + SM_B_IN + w * 6144 + (lane & 15) * 128 + (((lane >> 4) ^ (lane & 7)) * 16);
    mbar_wait(bar + 2 * NSTB * 8, 0);
    TRB(47, 1);
    int use = 0;
#pragma unroll 1
    for (int n = blockIdx.x + wg * step; n < NTB; n += 3 * step, use++) {
      const int b = n / 56, rem = n - b * 56, par = rem / 14, sg = wg + 3 * (use & 1);
      const uint64_t da = mkdesc(SBC + SM_B_IN, 128, 3072, 0) + sg * (24576 / 16);
      float D[96];
      mbar_wait(bar + sg * 8, (use >> 1) & 1);
      if (use | wg) nb_sync(4 + wg, 256);
      TRB(use * 3 + wg, 3);
      wg_fence();
      wg_ss192<0>(D, da, db);
#pragma unroll
      for (int k = 1; k < 12; k++) wg_ss192<1>(D, da + k * 16, db + k * 64);
      wg_commit();
      if (n + step < NTB) nb_arrive(wg == 2 ? 4 : 5 + wg, 256);
      TRB(use * 3 + wg, 4);
      if (use && lane == 0) {
        asm volatile("cp.async.bulk.wait_group.read 0;" ::: "memory");
        mbar_arrive(bar + (NSTB + wg + 3 * (~use & 1)) * 8);
      }
      __syncwarp();
      wg_wait<0>(); pin(D);
      nb_sync(1 + wg, 128);
      TRB(use * 3 + wg, 5);
      const uint32_t sta = sta0 + sg * 24576;
#pragma unroll
      for (int q = 0; q < 12; q++)
        stsm4((sta ^ ((q & 3) * 32)) + (q >> 2) * 2048,
              pack2(D[8 * q], D[8 * q + 1]), pack2(D[8 * q + 2], D[8 * q + 3]), pack2(D[8 * q + 4], D[8 * q + 5]), pack2(D[8 * q + 6], D[8 * q + 7]));
      fence_async();
      __syncwarp();
      if (lane == 0) {
        asm volatile("cp.async.bulk.tensor.4d.global.shared::cta.bulk_group [%0, {%2,%3,%4,%5}], [%1];"
                     ::"l"(&mp.oo), "r"(sb + SM_B_IN + sg * 24576 + w * 6144), "r"(0), "r"(8 * b), "r"((par >> 1) * 112 + (rem - par * 14) * 8 + 2 * w), "r"((par & 1) * 3) : "memory");
        asm volatile("cp.async.bulk.commit_group;" ::: "memory");
      }
      __syncwarp();
      TRB(use * 3 + wg, 6);
    }
    if (lane == 0) asm volatile("cp.async.bulk.wait_group 0;" ::: "memory");
    TR2(132 + blockIdx.x, 2);
  }
}

typedef CUresult (*EncodeFn)(CUtensorMap*, CUtensorMapDataType, cuuint32_t, void*, const cuuint64_t*, const cuuint64_t*, const cuuint32_t*,
                             const cuuint32_t*, CUtensorMapInterleave, CUtensorMapSwizzle, CUtensorMapL2promotion, CUtensorMapFloatOOBfill);
static EncodeFn g_enc = nullptr;
static void make_map(CUtensorMap* m, const void* p, int rank, const cuuint64_t* dim, const cuuint64_t* str, const cuuint32_t* box, CUtensorMapSwizzle sw) {
  const cuuint32_t ones[5] = {1, 1, 1, 1, 1};
  g_enc(m, CU_TENSOR_MAP_DATA_TYPE_BFLOAT16, rank, (void*)p, dim, str, box, ones, CU_TENSOR_MAP_INTERLEAVE_NONE, sw,
        CU_TENSOR_MAP_L2_PROMOTION_L2_128B, CU_TENSOR_MAP_FLOAT_OOB_FILL_NONE);
}

extern "C" void kernel_launch(void* const* d_in, const int* in_sizes, int n_in, void* d_out, int out_size) {
  const __nv_bfloat16* x = (const __nv_bfloat16*)d_in[0];
  const __nv_bfloat16* wqkv = (const __nv_bfloat16*)d_in[1];
  const __nv_bfloat16* wo = (const __nv_bfloat16*)d_in[2];
  const __nv_bfloat16* rpb = (const __nv_bfloat16*)d_in[3];

  if (!g_enc) {
    void* fn = nullptr; cudaDriverEntryPointQueryResult qr;
    cudaGetDriverEntryPoint("cuTensorMapEncodeTiled", &fn, cudaEnableDefault, &qr);
    g_enc = (EncodeFn)fn;
    cudaFuncSetAttribute(na_attn_kernel, cudaFuncAttributeMaxDynamicSharedMemorySize, SM_A_TOTAL);
    cudaFuncSetAttribute(na_proj_kernel, cudaFuncAttributeMaxDynamicSharedMemorySize, SM_B_TOTAL);
  }
  Maps ma; MapsB mb;
  { cuuint64_t dim[4] = {64, 112, 224, 6}, str[3] = {(cuuint64_t)ROWB, 768, 128};
    cuuint32_t box[4] = {64, 4, 16, 3}, boxo[4] = {64, 8, 2, 3};
    make_map(&ma.xc, x, 4, dim, str, box, CU_TENSOR_MAP_SWIZZLE_128B);
    make_map(&mb.oo, d_out, 4, dim, str, boxo, CU_TENSOR_MAP_SWIZZLE_128B); }
  { cuuint64_t dim[5] = {64, 112, 224, 2, 6}, str[4] = {(cuuint64_t)ROWB, 768, 19 * 768, 128};
    cuuint32_t box[5] = {64, 8, 3, 2, 3};
    make_map(&ma.xh, x, 5, dim, str, box, CU_TENSOR_MAP_SWIZZLE_128B); }
  { cuuint64_t dim[3] = {384, 112, 224}, str[2] = {(cuuint64_t)ROWB, 768};
    cuuint32_t box[3] = {192, 8, 8}, boxs[3] = {192, 2, 16};
    make_map(&mb.oi, d_out, 3, dim, str, box, CU_TENSOR_MAP_SWIZZLE_NONE);
    make_map(&ma.os, d_out, 3, dim, str, boxs, CU_TENSOR_MAP_SWIZZLE_NONE); }
  { cuuint64_t dim[4] = {32, 112, 224, 12}, str[3] = {(cuuint64_t)ROWB, 768, 64};
    cuuint32_t box[4] = {32, 8, 2, 3};
    make_map(&ma.ot, d_out, 4, dim, str, box, CU_TENSOR_MAP_SWIZZLE_64B); }
  { cuuint64_t dim[2] = {576, 192}, str[1] = {1152};
    cuuint32_t box[2] = {16, 192};
    make_map(&ma.w, wqkv, 2, dim, str, box, CU_TENSOR_MAP_SWIZZLE_32B); }
  { cuuint64_t dim[3] = {32, 192, 6}, str[2] = {384, 64};
    cuuint32_t box[3] = {32, 192, 3};
    make_map(&ma.wo, wo, 3, dim, str, box, CU_TENSOR_MAP_SWIZZLE_64B);
    mb.wo = ma.wo; }
  na_attn_kernel<<<112, 512, SM_A_TOTAL>>>(x, wqkv, rpb, ma);
  cudaLaunchConfig_t cfg = {};
  cfg.gridDim = dim3(20); cfg.blockDim = dim3(480); cfg.dynamicSmemBytes = SM_B_TOTAL; cfg.stream = cudaStreamPerThread;
  cudaLaunchAttribute at[1];
  at[0].id = cudaLaunchAttributeProgrammaticStreamSerialization; at[0].val.programmaticStreamSerializationAllowed = 1;
  cfg.attrs = at; cfg.numAttrs = 1;
  cudaLaunchKernelEx(&cfg, na_proj_kernel, mb);
}
```

```cpp
#include <cuda_runtime.h>
#include <cuda_bf16.h>
#include <cuda.h>
#include <stdint.h>

#define SPIN_LIMIT (1u << 18)

__device__ __forceinline__ uint32_t smem_u32(const void* p) { return (uint32_t)__cvta_generic_to_shared(p); }
__device__ __forceinline__ void wg_fence() { asm volatile("wgmma.fence.sync.aligned;" ::: "memory"); }
__device__ __forceinline__ void wg_commit() { asm volatile("wgmma.commit_group.sync.aligned;" ::: "memory"); }
template <int N> __device__ __forceinline__ void wg_wait() { asm volatile("wgmma.wait_group.sync.aligned %0;" ::"n"(N) : "memory"); }
template <int N> __device__ __forceinline__ void pin(float (&d)[N]) {
#pragma unroll
  for (int i = 0; i < N; i++) asm volatile("" : "+f"(d[i])::"memory");
}
__host__ __device__ constexpr uint64_t mkdesc(uint32_t addr, uint32_t lbo, uint32_t sbo, uint32_t sw) {
  return (uint64_t)((addr & 0x3FFFF) >> 4) | ((uint64_t)(lbo >> 4) << 16) | ((uint64_t)(sbo >> 4) << 32) | ((uint64_t)sw << 62);
}
__device__ __forceinline__ void mbar_init(uint32_t bar, uint32_t cnt) { asm volatile("mbarrier.init.shared::cta.b64 [%0], %1;" ::"r"(bar), "r"(cnt) : "memory"); }
__device__ __forceinline__ void mbar_arrive(uint32_t bar) { asm volatile("mbarrier.arrive.shared::cta.b64 _, [%0];" ::"r"(bar) : "memory"); }
__device__ __forceinline__ bool elect_one() {
  uint32_t r; asm volatile("{\n.reg .pred p;\nelect.sync _|p, 0xffffffff;\nselp.u32 %0, 1, 0, p;\n}" : "=r"(r)); return r;
}
__device__ __forceinline__ void mbar_arrive_elect(uint32_t bar) {
  asm volatile("{\n.reg .pred p;\nelect.sync _|p, 0xffffffff;\n@p mbarrier.arrive.shared::cta.b64 _, [%0];\n}" ::"r"(bar) : "memory");
}
__device__ __forceinline__ void mbar_expect(uint32_t bar, uint32_t bytes) { asm volatile("mbarrier.arrive.expect_tx.shared::cta.b64 _, [%0], %1;" ::"r"(bar), "r"(bytes) : "memory"); }
__device__ __forceinline__ void mbar_arrive_remote(uint32_t bar, uint32_t cta) {
  asm volatile("{\n.reg .b32 ra;\nmapa.shared::cluster.u32 ra, %0, %1;\nmbarrier.arrive.relaxed.cluster.shared::cluster.b64 _, [ra];\n}" ::"r"(bar), "r"(cta) : "memory");
}
__device__ __forceinline__ void mbar_wait(uint32_t bar, uint32_t parity) {
  asm volatile("{\n.reg .pred p;\n.reg .b32 n;\nmov.b32 n, 0;\nWL:\nmbarrier.try_wait.parity.shared::cta.b64 p, [%0], %1;\n@p bra WD;\n"
               "add.u32 n, n, 1;\nsetp.lt.u32 p, n, 65536;\n@p bra WL;\nWD:\n}" ::"r"(bar), "r"(parity) : "memory");
}
__device__ __forceinline__ void nb_sync(int id, int n) { asm volatile("bar.sync %0, %1;" ::"r"(id), "r"(n) : "memory"); }
__device__ __forceinline__ void nb_arrive(int id, int n) { asm volatile("bar.arrive %0, %1;" ::"r"(id), "r"(n) : "memory"); }
__device__ __forceinline__ uint32_t opq(uint32_t x) { uint32_t r; asm volatile("mov.b32 %0, %1;" : "=r"(r) : "r"(x)); return r; }
__device__ __forceinline__ uint64_t opq(uint64_t x) { uint64_t r; asm volatile("mov.b64 %0, %1;" : "=l"(r) : "l"(x)); return r; }
__device__ __forceinline__ void fence_async() { asm volatile("fence.proxy.async.shared::cta;" ::: "memory"); }
__device__ __forceinline__ void cluster_sync() {
  asm volatile("barrier.cluster.arrive.relaxed.aligned;\nbarrier.cluster.wait.aligned;" ::: "memory");
}
__device__ __forceinline__ uint32_t pack2(float lo, float hi) {
  uint32_t r; asm("cvt.rn.bf16x2.f32 %0, %1, %2;" : "=r"(r) : "f"(hi), "f"(lo)); return r;
}
__device__ __forceinline__ void stsm4(uint32_t a, uint32_t r0, uint32_t r1, uint32_t r2, uint32_t r3) {
  asm volatile("stmatrix.sync.aligned.m8n8.x4.shared.b16 [%0], {%1,%2,%3,%4};" ::"r"(a), "r"(r0), "r"(r1), "r"(r2), "r"(r3) : "memory");
}
__device__ __forceinline__ void ldsm4(uint32_t a, uint32_t& r0, uint32_t& r1, uint32_t& r2, uint32_t& r3) {
  asm volatile("ldmatrix.sync.aligned.m8n8.x4.shared.b16 {%0,%1,%2,%3}, [%4];" : "=r"(r0), "=r"(r1), "=r"(r2), "=r"(r3) : "r"(a) : "memory");
}
__device__ __forceinline__ void sts128(uint32_t a, uint4 v) {
  asm volatile("st.shared.v4.b32 [%0], {%1,%2,%3,%4};" ::"r"(a), "r"(v.x), "r"(v.y), "r"(v.z), "r"(v.w) : "memory");
}
__device__ __forceinline__ float lds_f32(uint32_t a) { float v; asm volatile("ld.shared.f32 %0, [%1];" : "=f"(v) : "r"(a)); return v; }
__device__ __forceinline__ float ex2(float x) { float y; asm("ex2.approx.ftz.f32 %0, %1;" : "=f"(y) : "f"(x)); return y; }

template<int SC> __device__ __forceinline__ void wg_ss144(float (&d)[72], uint64_t da, uint64_t db) {
  asm volatile("{\n.reg .pred p;\nsetp.ne.b32 p, %74, 0;\nwgmma.mma_async.sync.aligned.m64n144k16.f32.bf16.bf16 {%0,%1,%2,%3,%4,%5,%6,%7,%8,%9,%10,%11,%12,%13,%14,%15,%16,%17,%18,%19,%20,%21,%22,%23,%24,%25,%26,%27,%28,%29,%30,%31,%32,%33,%34,%35,%36,%37,%38,%39,%40,%41,%42,%43,%44,%45,%46,%47,%48,%49,%50,%51,%52,%53,%54,%55,%56,%57,%58,%59,%60,%61,%62,%63,%64,%65,%66,%67,%68,%69,%70,%71}, %72, %73, p, 1, 1, 0, 1;\n}\n"
    : "+f"(d[0]),"+f"(d[1]),"+f"(d[2]),"+f"(d[3]),"+f"(d[4]),"+f"(d[5]),"+f"(d[6]),"+f"(d[7]),"+f"(d[8]),"+f"(d[9]),"+f"(d[10]),"+f"(d[11]),"+f"(d[12]),"+f"(d[13]),"+f"(d[14]),"+f"(d[15]),"+f"(d[16]),"+f"(d[17]),"+f"(d[18]),"+f"(d[19]),"+f"(d[20]),"+f"(d[21]),"+f"(d[22]),"+f"(d[23]),"+f"(d[24]),"+f"(d[25]),"+f"(d[26]),"+f"(d[27]),"+f"(d[28]),"+f"(d[29]),"+f"(d[30]),"+f"(d[31]),"+f"(d[32]),"+f"(d[33]),"+f"(d[34]),"+f"(d[35]),"+f"(d[36]),"+f"(d[37]),"+f"(d[38]),"+f"(d[39]),"+f"(d[40]),"+f"(d[41]),"+f"(d[42]),"+f"(d[43]),"+f"(d[44]),"+f"(d[45]),"+f"(d[46]),"+f"(d[47]),"+f"(d[48]),"+f"(d[49]),"+f"(d[50]),"+f"(d[51]),"+f"(d[52]),"+f"(d[53]),"+f"(d[54]),"+f"(d[55]),"+f"(d[56]),"+f"(d[57]),"+f"(d[58]),"+f"(d[59]),"+f"(d[60]),"+f"(d[61]),"+f"(d[62]),"+f"(d[63]),"+f"(d[64]),"+f"(d[65]),"+f"(d[66]),"+f"(d[67]),"+f"(d[68]),"+f"(d[69]),"+f"(d[70]),"+f"(d[71]) : "l"(da), "l"(db), "n"(SC));
}
template<int SC> __device__ __forceinline__ void wg_ss96(float (&d)[48], uint64_t da, uint64_t db) {
  asm volatile("{\n.reg .pred p;\nsetp.ne.b32 p, %50, 0;\nwgmma.mma_async.sync.aligned.m64n96k16.f32.bf16.bf16 {%0,%1,%2,%3,%4,%5,%6,%7,%8,%9,%10,%11,%12,%13,%14,%15,%16,%17,%18,%19,%20,%21,%22,%23,%24,%25,%26,%27,%28,%29,%30,%31,%32,%33,%34,%35,%36,%37,%38,%39,%40,%41,%42,%43,%44,%45,%46,%47}, %48, %49, p, 1, 1, 0, 1;\n}\n"
    : "+f"(d[0]),"+f"(d[1]),"+f"(d[2]),"+f"(d[3]),"+f"(d[4]),"+f"(d[5]),"+f"(d[6]),"+f"(d[7]),"+f"(d[8]),"+f"(d[9]),"+f"(d[10]),"+f"(d[11]),"+f"(d[12]),"+f"(d[13]),"+f"(d[14]),"+f"(d[15]),"+f"(d[16]),"+f"(d[17]),"+f"(d[18]),"+f"(d[19]),"+f"(d[20]),"+f"(d[21]),"+f"(d[22]),"+f"(d[23]),"+f"(d[24]),"+f"(d[25]),"+f"(d[26]),"+f"(d[27]),"+f"(d[28]),"+f"(d[29]),"+f"(d[30]),"+f"(d[31]),"+f"(d[32]),"+f"(d[33]),"+f"(d[34]),"+f"(d[35]),"+f"(d[36]),"+f"(d[37]),"+f"(d[38]),"+f"(d[39]),"+f"(d[40]),"+f"(d[41]),"+f"(d[42]),"+f"(d[43]),"+f"(d[44]),"+f"(d[45]),"+f"(d[46]),"+f"(d[47]) : "l"(da), "l"(db), "n"(SC));
}
template<int SC> __device__ __forceinline__ void wg_rs112(float (&d)[56], uint32_t a0, uint32_t a1, uint32_t a2, uint32_t a3, uint64_t db) {
  asm volatile("{\n.reg .pred p;\nsetp.ne.b32 p, %61, 0;\nwgmma.mma_async.sync.aligned.m64n112k16.f32.bf16.bf16 {%0,%1,%2,%3,%4,%5,%6,%7,%8,%9,%10,%11,%12,%13,%14,%15,%16,%17,%18,%19,%20,%21,%22,%23,%24,%25,%26,%27,%28,%29,%30,%31,%32,%33,%34,%35,%36,%37,%38,%39,%40,%41,%42,%43,%44,%45,%46,%47,%48,%49,%50,%51,%52,%53,%54,%55}, {%56,%57,%58,%59}, %60, p, 1, 1, 0;\n}\n"
    : "+f"(d[0]),"+f"(d[1]),"+f"(d[2]),"+f"(d[3]),"+f"(d[4]),"+f"(d[5]),"+f"(d[6]),"+f"(d[7]),"+f"(d[8]),"+f"(d[9]),"+f"(d[10]),"+f"(d[11]),"+f"(d[12]),"+f"(d[13]),"+f"(d[14]),"+f"(d[15]),"+f"(d[16]),"+f"(d[17]),"+f"(d[18]),"+f"(d[19]),"+f"(d[20]),"+f"(d[21]),"+f"(d[22]),"+f"(d[23]),"+f"(d[24]),"+f"(d[25]),"+f"(d[26]),"+f"(d[27]),"+f"(d[28]),"+f"(d[29]),"+f"(d[30]),"+f"(d[31]),"+f"(d[32]),"+f"(d[33]),"+f"(d[34]),"+f"(d[35]),"+f"(d[36]),"+f"(d[37]),"+f"(d[38]),"+f"(d[39]),"+f"(d[40]),"+f"(d[41]),"+f"(d[42]),"+f"(d[43]),"+f"(d[44]),"+f"(d[45]),"+f"(d[46]),"+f"(d[47]),"+f"(d[48]),"+f"(d[49]),"+f"(d[50]),"+f"(d[51]),"+f"(d[52]),"+f"(d[53]),"+f"(d[54]),"+f"(d[55]) : "r"(a0), "r"(a1), "r"(a2), "r"(a3), "l"(db), "n"(SC));
}
template<int SC> __device__ __forceinline__ void wg_sp48(float (&d)[24], uint32_t a0, uint32_t a1, uint32_t a2, uint32_t a3, uint64_t db, uint32_t meta) {
  asm volatile("{\n.reg .pred p;\nsetp.ne.b32 p, %30, 0;\nwgmma.mma_async.sp.sync.aligned.m64n48k32.f32.bf16.bf16 {%0,%1,%2,%3,%4,%5,%6,%7,%8,%9,%10,%11,%12,%13,%14,%15,%16,%17,%18,%19,%20,%21,%22,%23}, {%24,%25,%26,%27}, %28, %29, 0, p, 1, 1, 1;\n}\n"
    : "+f"(d[0]),"+f"(d[1]),"+f"(d[2]),"+f"(d[3]),"+f"(d[4]),"+f"(d[5]),"+f"(d[6]),"+f"(d[7]),"+f"(d[8]),"+f"(d[9]),"+f"(d[10]),"+f"(d[11]),"+f"(d[12]),"+f"(d[13]),"+f"(d[14]),"+f"(d[15]),"+f"(d[16]),"+f"(d[17]),"+f"(d[18]),"+f"(d[19]),"+f"(d[20]),"+f"(d[21]),"+f"(d[22]),"+f"(d[23]) : "r"(a0), "r"(a1), "r"(a2), "r"(a3), "l"(db), "r"(meta), "n"(SC));
}
template<int SC> __device__ __forceinline__ void wg_ss192(float (&d)[96], uint64_t da, uint64_t db) {
  asm volatile("{\n.reg .pred p;\nsetp.ne.b32 p, %98, 0;\nwgmma.mma_async.sync.aligned.m64n192k16.f32.bf16.bf16 {%0,%1,%2,%3,%4,%5,%6,%7,%8,%9,%10,%11,%12,%13,%14,%15,%16,%17,%18,%19,%20,%21,%22,%23,%24,%25,%26,%27,%28,%29,%30,%31,%32,%33,%34,%35,%36,%37,%38,%39,%40,%41,%42,%43,%44,%45,%46,%47,%48,%49,%50,%51,%52,%53,%54,%55,%56,%57,%58,%59,%60,%61,%62,%63,%64,%65,%66,%67,%68,%69,%70,%71,%72,%73,%74,%75,%76,%77,%78,%79,%80,%81,%82,%83,%84,%85,%86,%87,%88,%89,%90,%91,%92,%93,%94,%95}, %96, %97, p, 1, 1, 0, 1;\n}\n"
    : "+f"(d[0]),"+f"(d[1]),"+f"(d[2]),"+f"(d[3]),"+f"(d[4]),"+f"(d[5]),"+f"(d[6]),"+f"(d[7]),"+f"(d[8]),"+f"(d[9]),"+f"(d[10]),"+f"(d[11]),"+f"(d[12]),"+f"(d[13]),"+f"(d[14]),"+f"(d[15]),"+f"(d[16]),"+f"(d[17]),"+f"(d[18]),"+f"(d[19]),"+f"(d[20]),"+f"(d[21]),"+f"(d[22]),"+f"(d[23]),"+f"(d[24]),"+f"(d[25]),"+f"(d[26]),"+f"(d[27]),"+f"(d[28]),"+f"(d[29]),"+f"(d[30]),"+f"(d[31]),"+f"(d[32]),"+f"(d[33]),"+f"(d[34]),"+f"(d[35]),"+f"(d[36]),"+f"(d[37]),"+f"(d[38]),"+f"(d[39]),"+f"(d[40]),"+f"(d[41]),"+f"(d[42]),"+f"(d[43]),"+f"(d[44]),"+f"(d[45]),"+f"(d[46]),"+f"(d[47]),"+f"(d[48]),"+f"(d[49]),"+f"(d[50]),"+f"(d[51]),"+f"(d[52]),"+f"(d[53]),"+f"(d[54]),"+f"(d[55]),"+f"(d[56]),"+f"(d[57]),"+f"(d[58]),"+f"(d[59]),"+f"(d[60]),"+f"(d[61]),"+f"(d[62]),"+f"(d[63]),"+f"(d[64]),"+f"(d[65]),"+f"(d[66]),"+f"(d[67]),"+f"(d[68]),"+f"(d[69]),"+f"(d[70]),"+f"(d[71]),"+f"(d[72]),"+f"(d[73]),"+f"(d[74]),"+f"(d[75]),"+f"(d[76]),"+f"(d[77]),"+f"(d[78]),"+f"(d[79]),"+f"(d[80]),"+f"(d[81]),"+f"(d[82]),"+f"(d[83]),"+f"(d[84]),"+f"(d[85]),"+f"(d[86]),"+f"(d[87]),"+f"(d[88]),"+f"(d[89]),"+f"(d[90]),"+f"(d[91]),"+f"(d[92]),"+f"(d[93]),"+f"(d[94]),"+f"(d[95]) : "l"(da), "l"(db), "n"(SC));
}

constexpr uint32_t SBC = 1024;
constexpr int ROWB = 2 * 224 * 384;
constexpr int TB = 11;
constexpr int KS = 832;
constexpr int KSLOT = 22 * KS;
constexpr int SM_X2 = 0;
constexpr int SM_X0 = SM_X2 + 24576;
constexpr int SM_W = SM_X0 + 18432;
constexpr int SM_X1 = SM_W + 55296;
constexpr int SM_K = SM_X1 + 24576;
constexpr int SM_V = SM_K + 2 * KSLOT;
constexpr int SM_Q = SM_V + 22 * 1536;
constexpr int SM_O = SM_Q + 24576;
constexpr int SM_RPB = SM_O + 12288;
constexpr int SM_BAR = SM_RPB + 768;
constexpr int SM_A_TOTAL = SM_BAR + 256;
constexpr int SM_TIN = 0;
constexpr int SM_TST = 3 * 24576;
constexpr int SM_TWO = SM_TST + 12288;
enum { B_FULL = 0, B_EMPTY = 3, B_TIN = 6, B_TFREE = 10, B_WK = 12, B_WQ, B_WO, B_Q0, B_WOFREE, B_OTAIL, B_ODONE = B_OTAIL + 2, B_KFREE, B_VFREE, B_COUNT };
enum { N_KRDY = 4, N_QK0, N_QK1, N_VQ0, N_VQ1, N_PVISS };

#define NL 2
#define OPT 0
#define SPL 4
#define RA 160
#define RG 168
__device__ int g_flags[TB * 56];

#define TR(role, it, k)
#define TRDECL
#define TRARG
#define TRPASS
#define TRDUMP
#define TRB(it, k)
#define TR2(blk, k)

struct GemmCtx {
  uint32_t bar;
  uint32_t kC, vC[2], qC[2];
  uint32_t kH, vH[2];
  uint32_t hiA, hiB;
  uint32_t spin;
  bool hvalid, never;
};

template <int STRIDE> __device__ __forceinline__ void dump12(uint32_t a, const uint32_t (&r)[12]) {
#pragma unroll
  for (int j = 0; j < 3; j++) stsm4(a + j * 2 * STRIDE, r[4 * j], r[4 * j + 1], r[4 * j + 2], r[4 * j + 3]);
}
__device__ __forceinline__ void keep12(bool never, uint32_t a, const uint32_t (&r)[12]) { if (never) dump12<128>(a, r); }
template <int N> __device__ __forceinline__ void pack12(uint32_t (&r)[12], const float (&d)[N], int off) {
#pragma unroll
  for (int j = 0; j < 12; j++) r[j] = pack2(d[off + 2 * j], d[off + 2 * j + 1]);
}
__device__ __forceinline__ uint64_t dsc(uint64_t lo, uint32_t hi) { uint64_t r; asm("mov.b64 %0, {%1, %2};" : "=l"(r) : "r"((uint32_t)lo), "r"(hi)); return r; }
template <int XS, int K0, int K1> __device__ __forceinline__ void issue_core(const GemmCtx& c, float (&d)[72]) {
  constexpr uint64_t da = mkdesc(SBC + XS, 16, 1024, 1), db = mkdesc(SBC + SM_W, 6144, 256, 3);
  wg_fence();
  if (K0 == 0) wg_ss144<0>(d, dsc(da, c.hiA), dsc(db, c.hiB));
#pragma unroll
  for (int k = K0 ? K0 : 1; k < K1; k++) wg_ss144<1>(d, dsc(da + (k >> 2) * 512 + (k & 3) * 2, c.hiA), dsc(db + k * 32, c.hiB));
  wg_commit();
}
template <int K0, int K1> __device__ __forceinline__ void issue_halo(const GemmCtx& c, float (&d)[48]) {
  constexpr uint64_t da = mkdesc(SBC + SM_X0 - 2048, 16, 1024, 1), db = mkdesc(SBC + SM_W, 6144, 256, 3);
  wg_fence();
  if (K0 == 0) wg_ss96<0>(d, dsc(da, c.hiA), dsc(db, c.hiB));
#pragma unroll
  for (int k = K0 ? K0 : 1; k < K1; k++) wg_ss96<1>(d, dsc(da + (k >> 2) * 384 + (k & 3) * 2, c.hiA), dsc(db + k * 32, c.hiB));
  wg_commit();
}
template <int ST> __device__ __forceinline__ void release_stage(const GemmCtx& c) {
  asm volatile("{\n.reg .pred p;\n.reg .b32 ra;\nelect.sync _|p, 0xffffffff;\nmapa.shared::cluster.u32 ra, %0, %1;\n"
               "@p mbarrier.arrive.shared::cluster.b64 _, [ra];\n}" ::"r"(c.bar + (B_EMPTY + ST) * 8), "n"(ST) : "memory");
}
template <int PARITY> __device__ __forceinline__ void gwait(GemmCtx& c, int bar) {
  asm volatile("{\n.reg .pred p;\nWL:\nmbarrier.try_wait.parity.shared::cta.b64 p, [%1], %2;\n@p bra WD;\n"
               "add.u32 %0, %0, 1;\nsetp.lt.u32 p, %0, 0x100000;\n@p bra WL;\nWD:\n}" : "+r"(c.spin) : "r"(c.bar + bar * 8), "n"(PARITY) : "memory");
}
__device__ __forceinline__ void load_w(const CUtensorMap* m, uint32_t dst, uint32_t bar, int col) {
  asm volatile("cp.async.bulk.tensor.2d.shared::cluster.global.mbarrier::complete_tx::bytes [%0], [%1, {%3,%4}], [%2];"
               ::"r"(dst), "l"(m), "r"(bar), "r"(col), "r"(0) : "memory");
}
template <int BYTES> __device__ __forceinline__ void send_o(uint32_t dst, uint32_t src, uint32_t bar, int cta) {
  asm volatile("{\n.reg .b32 rd, rb;\nmapa.shared::cluster.u32 rd, %0, %3;\nmapa.shared::cluster.u32 rb, %2, %3;\n"
               "cp.async.bulk.shared::cluster.shared::cta.mbarrier::complete_tx::bytes [rd], [%1], %4, [rb];\n}"
               ::"r"(dst), "r"(src), "r"(bar), "r"(cta), "n"(BYTES) : "memory");
}
__device__ __forceinline__ void tail_free(uint32_t bar) {
  uint32_t ln; asm volatile("mov.u32 %0, %%laneid;" : "=r"(ln));
  if (ln < 4) mbar_arrive_remote(bar, ln);
}
__device__ __forceinline__ void publish(uint32_t bar) {
  fence_async();
  __syncwarp();
  mbar_arrive_elect(bar);
}

template <bool FIRST, int PA>
__device__ __forceinline__ void gemm_iter(GemmCtx& c, int b, uint32_t (&pk)[12], uint32_t (&pv)[12], uint32_t (&pq)[12] TRARG) {
  const uint32_t bar = c.bar;
  const bool w = !FIRST && (PA == 0 || b >= 0), never = c.never;
  constexpr uint32_t ko = PA * KSLOT;
  float H[48], C[72];
  uint32_t hk[12], hv[12], pv2[12];
  TR(2, b, 0);
  if (FIRST) gwait<PA>(c, B_FULL + 0);
  if (!FIRST) dump12<256>(c.qC[1] + (PA ^ 1) * 128, pq);
  if (w) nb_sync(N_QK1, 256);
  TR(2, b, 2);
  if (FIRST) TR(2, b - 1, 6);
  issue_halo<0, 8>(c, H);
  TR(2, b, 3);
  if (!FIRST) {
    if (w) gwait<PA>(c, B_KFREE);
    dump12<128>(c.kC + ko, pk);
  }
  issue_halo<8, 12>(c, H);
  TR(2, b, 4);
  {
    gwait<PA>(c, B_FULL + 2);
    if (FIRST && NL == 2) gwait<0>(c, B_WQ);
    TR(2, b, 13);
    if (FIRST) TR(2, b - 1, 7);
    issue_core<SM_X2, 0, 8>(c, C);
    TR(2, b, 5);
    if (!FIRST) { fence_async(); keep12(never, c.kC, pk); }
    wg_wait<1>(); pin(H);
    release_stage<0>(c);
  }
  pack12(hk, H, 0);
  if (c.hvalid) dump12<128>(c.kH + ko, hk);
  pack12(hv, H, 24);
  {
    issue_core<SM_X2, 8, 12>(c, C);
    if (w) { nb_arrive(N_VQ0, 288); nb_arrive(N_VQ1, 288); }
    else if (!FIRST) { __syncwarp(); mbar_arrive_elect(bar + B_Q0 * 8); }
    gwait<PA>(c, B_FULL + 1);
    keep12(never, c.kC, hk);
    TR(2, b, 6);
    wg_wait<0>(); pin(C);
    TR(2, b, 7);
    pack12(pk, C, 0);
    dump12<128>(c.kC + ko + 64, pk);
    release_stage<2>(c);
    pack12(pv2, C, 24);
    pack12(pq, C, 48);
    TR(2, b, 8);
    issue_core<SM_X1, 0, SPL>(c, C);
    if (w) nb_sync(N_PVISS, 384);
    issue_core<SM_X1, SPL, 8>(c, C);
    TR(2, b, 9);
  }
  if (!FIRST) fence_async();
  keep12(never, c.kC, pk);
  TR(2, b, 14);
  issue_core<SM_X1, 8, 12>(c, C);
  if (!FIRST) nb_arrive(N_KRDY, 256);
  TR(2, b, 1);
  if (PA && b == 11) tail_free(bar + B_TFREE * 8);
  gwait<PA ^ 1>(c, B_FULL + 0);
  if (w) gwait<PA>(c, B_VFREE);
  TR(2, b, 10);
  if (!FIRST) dump12<128>(c.vC[PA], pv);
  dump12<256>(c.qC[0] + PA * 128, pq);
  if (c.hvalid) dump12<128>(c.vH[PA], hv);
  dump12<128>(c.vC[PA ^ 1] + 768, pv2);
  TR(2, b, 11);
  wg_wait<0>(); pin(C);
  TR(2, b, 12);
  release_stage<1>(c);
  pack12(pk, C, 0);
  pack12(pv, C, 24);
  pack12(pq, C, 48);
}

template <int IN> __device__ __forceinline__ void issue_proj(float (&D)[48]) {
  constexpr uint64_t da = mkdesc(SBC + IN, 128, 768, 0), db = mkdesc(SBC + SM_TWO, 12288, 512, 2);
  wg_fence();
  wg_ss96<0>(D, da, db);
#pragma unroll
  for (int k = 1; k < 12; k++) wg_ss96<1>(D, da + (k / 3) * 384 + (k % 3) * 16, db + k * 64);
  wg_commit();
}
template <int ACC> __device__ __forceinline__ void issue_proj_half(float (&D)[48], int hd) {
  const uint64_t da = mkdesc(SBC + SM_TIN + 2 * 24576, 128, 768, 0) + hd * 384, db = mkdesc(SBC + SM_TWO, 12288, 512, 2) + hd * 192;
  wg_fence();
  wg_ss96<ACC>(D, da, db);
#pragma unroll
  for (int k = 1; k < 6; k++) wg_ss96<1>(D, da + (k / 3) * 768 + (k % 3) * 16, db + (k / 3) * 384 + (k % 3) * 64);
  wg_commit();
}
__device__ __forceinline__ void store_proj(const float (&D)[48], const CUtensorMap* m, uint32_t st, uint32_t sta, int row, int col, int ch) {
#pragma unroll
  for (int q = 0; q < 6; q++)
    stsm4((sta ^ ((q & 1) * 32)) + (q >> 1) * 1024,
          pack2(D[8 * q], D[8 * q + 1]), pack2(D[8 * q + 2], D[8 * q + 3]), pack2(D[8 * q + 4], D[8 * q + 5]), pack2(D[8 * q + 6], D[8 * q + 7]));
  fence_async();
  __syncwarp();
  if ((threadIdx.x & 31) == 0) {
    asm volatile("cp.async.bulk.tensor.4d.global.shared::cta.bulk_group [%0, {%2,%3,%4,%5}], [%1];" ::"l"(m), "r"(st), "r"(0), "r"(row), "r"(col), "r"(ch) : "memory");
    asm volatile("cp.async.bulk.commit_group;" ::: "memory");
  }
  __syncwarp();
}

__device__ __forceinline__ float fold(float a, float b, float t, int useb) {
  float r;
  asm("{\n.reg .pred p;\nsetp.ne.b32 p, %4, 0;\nfma.rn.f32 %0, %1, 0f3E553B95, %3;\n@p fma.rn.f32 %0, %2, 0f3E553B95, %3;\n}"
      : "=&f"(r) : "f"(a), "f"(b), "f"(t), "r"(useb));
  return r;
}
template <int U, int L>
__device__ __forceinline__ void softmax_tile(const float (&SA)[56], const float (&SB)[56], const float (&T)[16], int b0, int b1,
                                             uint32_t (&P)[28], float (&sx)[8]) {
  float lu[14], ll[14];
#pragma unroll
  for (int j = 0; j < 7; j++) {
    constexpr int sh = U == L ? 2 : 0;
    const float tu0 = T[2 * j + sh], tu1 = T[2 * j + 1 + sh], tl0 = T[2 * j], tl1 = T[2 * j + 1];
    lu[2 * j]     = fold(SA[4 * (U + j)],     SB[4 * (U + j)],     tu0, b0);
    ll[2 * j]     = fold(SA[4 * (L + j) + 2], SB[4 * (L + j) + 2], tl0, b0);
    lu[2 * j + 1] = fold(SA[4 * (U + j) + 1], SB[4 * (U + j) + 1], tu1, b1);
    ll[2 * j + 1] = fold(SA[4 * (L + j) + 3], SB[4 * (L + j) + 3], tl1, b1);
  }
  float mu = lu[0], ml = ll[0], mu2 = lu[1], ml2 = ll[1];
#pragma unroll
  for (int j = 1; j < 7; j++) { mu = fmaxf(mu, lu[2 * j]); mu2 = fmaxf(mu2, lu[2 * j + 1]); ml = fmaxf(ml, ll[2 * j]); ml2 = fmaxf(ml2, ll[2 * j + 1]); }
  mu = fmaxf(mu, mu2); ml = fmaxf(ml, ml2);
  { const float a1 = __shfl_xor_sync(0xffffffffu, mu, 1), a2 = __shfl_xor_sync(0xffffffffu, mu, 2), a3 = __shfl_xor_sync(0xffffffffu, mu, 3);
    const float c1 = __shfl_xor_sync(0xffffffffu, ml, 1), c2 = __shfl_xor_sync(0xffffffffu, ml, 2), c3 = __shfl_xor_sync(0xffffffffu, ml, 3);
    mu = fmaxf(fmaxf(mu, a1), fmaxf(a2, a3)); ml = fmaxf(fmaxf(ml, c1), fmaxf(c2, c3)); }
  float su = 0.f, sl = 0.f;
#pragma unroll
  for (int c = 0; c < 14; c++) {
    const int iu = (c >> 1) * 4 + (c & 1) * 2;
    if (c >= U && c < U + 7) {
      float e0 = ex2(lu[2 * (c - U)] - mu), e1 = ex2(lu[2 * (c - U) + 1] - mu);
      su = c == U ? e0 + e1 : (su + e0) + e1; P[iu] = pack2(e0, e1);
    } else P[iu] = 0u;
    if (c >= L && c < L + 7) {
      float e0 = ex2(ll[2 * (c - L)] - ml), e1 = ex2(ll[2 * (c - L) + 1] - ml);
      sl = c == L ? e0 + e1 : (sl + e0) + e1; P[iu + 1] = pack2(e0, e1);
    } else P[iu + 1] = 0u;
  }
  sx[0] = su; sx[4] = sl;
#pragma unroll
  for (int k = 1; k < 4; k++) { sx[k] = __shfl_xor_sync(0xffffffffu, su, k); sx[4 + k] = __shfl_xor_sync(0xffffffffu, sl, k); }
}

struct BandCfg { uint32_t ra0, ra1, meta; int b0, b1; };
__device__ __forceinline__ void band_cfg(int b, uint32_t tb, BandCfg& n) {
  uint32_t ln; asm volatile("mov.u32 %0, %%laneid;" : "=r"(ln));
  const int g = ln >> 2, t = ln & 3;
  const int sw = min(max(g + 1, b == 0 ? 4 : 0), b == 13 ? 5 : 8);
  const int i0 = 2 * t, i1 = 2 * t + 1;
  n.b0 = i0 <= sw - 2; n.b1 = i1 <= sw - 2;
  n.ra0 = tb + (i0 == sw - 1 ? 13 : i0 + 8 * n.b0 - g + 2) * 52;
  n.ra1 = tb + (i1 == sw - 1 ? 13 : i1 + 8 * n.b1 - g + 2) * 52;
  n.meta = ((0x5555u & ((1u << (2 * (sw - 1))) - 1)) ^ 0xDD88u ^ (((t ^ b) & 1) ? 0x5555u : 0u)) * 0x10001u;
}
__device__ __forceinline__ void band_load(const BandCfg& n, float (&T)[16], int& b0, int& b1, uint32_t& meta) {
#pragma unroll
  for (int jj = 0; jj < 8; jj++) { T[2 * jj] = lds_f32(n.ra0 + jj * 4); T[2 * jj + 1] = lds_f32(n.ra1 + jj * 4); }
  b0 = n.b0; b1 = n.b1; meta = n.meta;
}

struct Maps { CUtensorMap xc, xh, w, os, wo, ot; };

__global__ void __cluster_dims__(4, 1, 1) __launch_bounds__(512, 1)
na_attn_kernel(const __nv_bfloat16* __restrict__ x, const __nv_bfloat16* __restrict__ wqkv, const __nv_bfloat16* __restrict__ rpb, const __grid_constant__ Maps mp) {
  extern __shared__ __align__(1024) uint8_t smem_raw[];
  const uint32_t sb = smem_u32(smem_raw);
  if ((sb & 0x3FFFF) != SBC) return;
  const uint32_t bar = sb + SM_BAR;
  TR2(blockIdx.x, 0);
  const int tid = threadIdx.x, lane = tid & 31;
  const int warp = __shfl_sync(0xffffffffu, tid >> 5, 0);
  const int head = blockIdx.x & 3, cl = blockIdx.x >> 2;
  const int par = cl / 7, strip = cl - par * 7, ph = par >> 1, pw = par & 1;

  uint4 wv[2 * NL];
  const int va = head == 1;
  const uint32_t wdst = sb + SM_W + (va + ((tid >> 1) & 1)) * 6144 + (tid >> 2) * 32 + ((tid ^ (tid >> 4)) & 1) * 16;
  if (warp < 12) asm volatile("barrier.cluster.arrive.relaxed.aligned;" ::: "memory");
  {
    const uint32_t wo0 = (tid >> 2) * 1152 + head * 96 + va * 32 + (tid & 3) * 16;
#pragma unroll
    for (int i = 0; i < 2 * NL; i++)
      asm volatile("{\n.reg .pred p;\nsetp.lt.u32 p, %5, 384;\n@p ld.global.nc.v4.b32 {%0,%1,%2,%3}, [%4];\n}"
                   : "=r"(wv[i].x), "=r"(wv[i].y), "=r"(wv[i].z), "=r"(wv[i].w)
                   : "l"(reinterpret_cast<const uint8_t*>(wqkv) + wo0 + (i & 1) * 96 * 1152 + ((i / 2 + 1) % 3) * 384), "r"(tid));
  }
  if (warp < 8) {
    asm volatile("setmaxnreg.inc.sync.aligned.u32 %0;" ::"n"(RA));
    float rv = -INFINITY;
    if (tid < 169) rv = __bfloat162float(rpb[head * 169 + tid]) * 1.4426950408889634f;
    if (tid < 192) {
      const int kc = (tid & 15) + 3, wc = (tid >> 4) % 6;
      sts128(tid < 96 ? sb + SM_K + kc * KS + wc * 128 + 48 : sb + SM_V + kc * 1536 + wc * 128 + (6 + (kc & 1)) * 16, make_uint4(0, 0, 0, 0));
    }
#pragma unroll
    for (int i = 0; i < 2 * NL; i++) sts128(wdst + (i & 1) * 3072 + (i / 2) * 18432, wv[i]);
    fence_async();
    asm volatile("bar.arrive 1, 384;" ::: "memory");
    if (tid < 182) asm volatile("st.shared.f32 [%0], %1;" ::"r"(sb + SM_RPB + tid * 4), "f"(rv) : "memory");
    const int j = warp >> 2, w = warp & 3;
    int variant = w;
    if (strip == 0 && j == 0 && w < 2) variant = 4;
    if (strip == 6 && j == 1 && w >= 2) variant = 5;
    const bool v1 = opq((uint32_t)(variant & 1)), v2 = opq((uint32_t)(variant & 2)), v4 = opq((uint32_t)(variant & 4));
    uint32_t qa = opq(sb + SM_Q + (8 * j + 2 * w + ((lane >> 3) & 1)) * 1536 + (lane >> 4) * 256 + (((lane & 7) * 16) ^ (((lane >> 3) & 1) * 64)));
    uint32_t oa = opq(sb + SM_O + j * 6144 + (2 * w + ((lane >> 3) & 1)) * 768 + (lane >> 4) * 128 + (lane & 7) * 16);
    uint64_t dA = opq(mkdesc(SBC + SM_K, 128, KS, 0) + j * (8 * KS / 16)), dB = opq(dA + (KSLOT >> 4));
    uint64_t dV[7];
#pragma unroll
    for (int i = 0; i < 7; i++) dV[i] = opq(mkdesc(SBC + SM_V, 768, 128, 0) + j * (8 * 1536 / 16) + i * 192);
    const uint32_t nbK = opq((uint32_t)(N_KRDY + j)), nbQ = opq((uint32_t)(N_QK0 + j)), nbV = opq((uint32_t)(N_VQ0 + j));
    asm volatile("barrier.cluster.wait.aligned;" ::: "memory");
    asm volatile("bar.sync 3, 256;" ::: "memory");
    float T[16];
    TRDECL;
    int b0, b1;
    uint32_t meta, ob = bar + B_ODONE * 8;
    const uint32_t tb = opq(sb + SM_RPB + (variant < 4 ? 3 : variant + 1 - 2 * w) * 4);
    const bool own = ((w ^ head) & 2) == 0;
    const uint32_t dst13 = sb + SM_TIN + 2 * 24576 + head * 6144 + (2 * j + (w & 1)) * 1536, src13 = own ? dst13 : sb + SM_Q + warp * 3072 + 1536;
    BandCfg nx;
    band_cfg(0, tb, nx);
    band_load(nx, T, b0, b1, meta);
    meta ^= 0x55555555u;
    band_cfg(1, tb, nx);
    uint32_t q[12];
    mbar_wait(bar + B_Q0 * 8, 0);
#pragma unroll
    for (int k = 0; k < 3; k++) ldsm4(qa + k * 512, q[4 * k], q[4 * k + 1], q[4 * k + 2], q[4 * k + 3]);
#pragma unroll 1
    for (int b = 0; b < 14; b++) {
      float SA[56], SB[56];
      TR(0, b, 0);
      nb_sync(nbK, 256);
      TR(0, b, 1);
      TR(0, b - 1, 9);
      wg_fence();
      wg_rs112<0>(SA, q[0], q[1], q[2], q[3], dA);
      wg_rs112<0>(SB, q[0], q[1], q[2], q[3], dB);
      wg_rs112<1>(SA, q[4], q[5], q[6], q[7], dA + 16);
      wg_rs112<1>(SB, q[4], q[5], q[6], q[7], dB + 16);
      wg_rs112<1>(SA, q[8], q[9], q[10], q[11], dA + 32);
      wg_rs112<1>(SB, q[8], q[9], q[10], q[11], dB + 32);
      wg_commit();
      nb_arrive(nbQ, 256);
      { const uint64_t t = dA; dA = dB; dB = t; }
      qa ^= 128;
      meta ^= 0x55555555u;
      if (b == 1 || b == 13) band_load(nx, T, b0, b1, meta);
      TR(0, b, 2);
      wg_wait<0>(); pin(SA); pin(SB);
      mbar_arrive_elect(bar + B_KFREE * 8);
      TR(0, b, 3);
      TR(0, b - 1, 10);
      uint32_t P[28];
      float sx[8];
      if (v2) {
        if (v1) softmax_tile<6, 7>(SA, SB, T, b0, b1, P, sx); else softmax_tile<4, 5>(SA, SB, T, b0, b1, P, sx);
      } else if (!v4) {
        if (v1) softmax_tile<2, 3>(SA, SB, T, b0, b1, P, sx); else softmax_tile<0, 1>(SA, SB, T, b0, b1, P, sx);
      } else {
        if (v1) softmax_tile<4, 4>(SA, SB, T, b0, b1, P, sx); else softmax_tile<3, 3>(SA, SB, T, b0, b1, P, sx);
      }
      float O[24];
      TR(0, b, 4);
      if (b == 3) band_cfg(13, tb, nx);
      nb_sync(nbV, 288);
      TR(0, b, 5);
#pragma unroll
      for (int k = 0; k < 3; k++) ldsm4(qa + k * 512, q[4 * k], q[4 * k + 1], q[4 * k + 2], q[4 * k + 3]);
      wg_fence();
      wg_sp48<0>(O, P[0], P[1], P[2], P[3], dV[0], meta);
#pragma unroll
      for (int s = 1; s < 7; s++) wg_sp48<1>(O, P[4 * s], P[4 * s + 1], P[4 * s + 2], P[4 * s + 3], dV[s], meta);
      wg_commit();
      nb_arrive(N_PVISS, 384);
      TR(0, b, 6);
      wg_wait<0>(); pin(O);
      mbar_arrive_elect(bar + B_VFREE * 8);
      TR(0, b, 7);
      float ru, rl;
      asm("rcp.approx.ftz.f32 %0, %1;" : "=f"(ru) : "f"(((fmaf(O[0], 0.f, sx[0]) + sx[1]) + sx[2]) + sx[3]));
      asm("rcp.approx.ftz.f32 %0, %1;" : "=f"(rl) : "f"(((fmaf(O[2], 0.f, sx[4]) + sx[5]) + sx[6]) + sx[7]));
#pragma unroll
      for (int i = 0; i < 3; i++)
        stsm4(oa + i * 256, pack2(O[8 * i] * ru, O[8 * i + 1] * ru), pack2(O[8 * i + 2] * rl, O[8 * i + 3] * rl),
              pack2(O[8 * i + 4] * ru, O[8 * i + 5] * ru), pack2(O[8 * i + 6] * rl, O[8 * i + 7] * rl));
      publish(ob);
      if (b >= TB - 1) {
        ob = opq(bar + (b == 12 && own ? B_TIN + 2 : B_OTAIL + j) * 8);
        oa += b == 11 ? warp * 1536 - (SM_O - SM_Q) : (b == 12 ? src13 - (sb + SM_Q + warp * 3072) : 0);
      }
      TR(0, b, 8);
    }
    if (elect_one()) {
      if (!own) send_o<1536>(dst13, src13, bar + (B_TIN + 2) * 8, head ^ 2);
      send_o<1536>(dst13, src13, bar + (B_TIN + 3) * 8, (w & 2) + (~head & 1));
    }
    __syncwarp();
    if (((OPT & 2) && j == 0) || ((OPT & 4) && j == 1)) nb_arrive(3, (OPT & 6) == 6 ? 384 : 256);
    TRDUMP;
    cluster_sync();
  } else if (warp < 12) {
    TRDECL;
    TR(2, -3, 0);
    asm volatile("setmaxnreg.inc.sync.aligned.u32 %0;" ::"n"(RG));
    TR(2, -3, 1);
    GemmCtx c;
    c.bar = bar;
    const int gw = warp - 8, tk = gw * 16 + (lane & 15), hi = lane >> 4;
    { const int col = tk >> 2, i = tk & 3;
      c.kC = sb + SM_K + (col + 3) * KS + hi * 128 + i * 16;
      c.vC[0] = sb + SM_V + (col + 3) * 1536 + hi * 128 + (2 * i + ((col + 3) & 1)) * 16;
      c.qC[0] = sb + SM_Q + col * 1536 + hi * 256 + (col & 1) * 64 + i * 16; }
    { const int ci = (tk >> 3) - 2, kc = ci < 3 ? ci : ci + 16, i = tk & 7; c.hvalid = gw > 0;
      c.kH = sb + SM_K + kc * KS + hi * 128 + i * 16;
      c.vH[0] = sb + SM_V + kc * 1536 + hi * 128 + (i >> 2) * 768 + (2 * (i & 3) + ((kc ^ (i >> 2)) & 1)) * 16; }
    c.never = x == nullptr;
    c.kC = opq(c.kC); c.kH = opq(c.kH);
    c.vC[1] = opq(c.vC[0] ^ 16); c.vC[0] = opq(c.vC[0]);
    c.vH[1] = opq(c.vH[0] ^ 16); c.vH[0] = opq(c.vH[0]);
    c.qC[1] = opq(c.qC[0] ^ 64); c.qC[0] = opq(c.qC[0]);
    c.spin = 0;
    c.hiA = (uint32_t)(mkdesc(0, 0, 1024, 1) >> 32) + (blockIdx.x >> 16); c.hiB = (uint32_t)(mkdesc(0, 0, 256, 3) >> 32) + (blockIdx.x >> 16);
    asm volatile("barrier.cluster.wait.aligned;" ::: "memory");
    TR(2, -3, 2);
#pragma unroll
    for (int i = 0; i < 2 * NL; i++) sts128(wdst + (i & 1) * 3072 + (i / 2) * 18432, wv[i]);
    fence_async();
    TR(2, -3, 3);
    asm volatile("bar.sync 1, 384;" ::: "memory");
    TR(2, -3, 4);
    mbar_wait(bar + B_WK * 8, 0);
    TR(2, -3, 5);
    uint32_t pk[12], pv[12], pq[12];
    gemm_iter<true, 0>(c, -2, pk, pv, pq TRPASS);
    TR2(blockIdx.x, 4);
#pragma unroll 1
    for (int b = -1;; b += 2) {
      gemm_iter<false, 1>(c, b, pk, pv, pq TRPASS);
      if (b == 11) break;
      gemm_iter<false, 0>(c, b + 1, pk, pv, pq TRPASS);
    }
    TR2(blockIdx.x, 6);
    const uint32_t st = sb + gw * 3072;
    const uint32_t sta = st + (lane & 15) * 64 + ((hi ^ ((lane >> 1) & 3)) * 16);
    const int oc = ph * 112 + strip * 16 + 8 * (gw >> 1) + 4 * (head >> 1) + 2 * (gw & 1), och = pw * 6 + (head & 1) * 3;
    float D0[48], D1[48];
    mbar_arrive_elect(bar + B_WOFREE * 8);
    dump12<256>(c.qC[1] + 128, pq);
    nb_sync(N_QK1, 256);
    issue_halo<0, 12>(c, D1);
    gwait<0>(c, B_KFREE);
    dump12<128>(c.kC, pk);
    fence_async();
    nb_arrive(N_VQ0, 288); nb_arrive(N_VQ1, 288); nb_arrive(N_PVISS, 384);
    wg_wait<0>(); pin(D1);
    pack12(pk, D1, 0);
    if (c.hvalid) dump12<128>(c.kH, pk);
    tail_free(bar + (B_TFREE + 1) * 8);
    pack12(pq, D1, 24);
    fence_async();
    nb_arrive(N_KRDY, 256);
    gwait<0>(c, B_VFREE);
    dump12<128>(c.vC[0], pv);
    if (c.hvalid) dump12<128>(c.vH[0], pq);
    fence_async();
    nb_arrive(N_VQ0, 288); nb_arrive(N_VQ1, 288); nb_arrive(N_QK1, 256);
    gwait<0>(c, B_WO);
    gwait<0>(c, B_TIN);
    gwait<0>(c, B_TIN + 1);
    TR(2, 13, 0);
    nb_sync(N_PVISS, 384);
    if (OPT & 6) nb_sync(3, (OPT & 6) == 6 ? 384 : 256);
    issue_proj<SM_TIN>(D0);
    TR(2, 13, 1);
    issue_proj<SM_TIN + 24576>(D1);
    wg_wait<1>(); pin(D0);
    TR(2, 13, 2);
    store_proj(D0, &mp.ot, st + SM_TST, sta + SM_TST, 8 * TB, oc, och);
    TR(2, 13, 3);
    gwait<0>(c, B_TIN + 2);
    TR(2, 13, 4);
    issue_proj_half<0>(D0, head & 1);
    wg_wait<1>(); pin(D1);
    store_proj(D1, &mp.ot, st + SM_TIN, sta + SM_TIN, 8 * TB + 8, oc, och);
    TR(2, 13, 5);
    gwait<0>(c, B_TIN + 3);
    TR(2, 13, 6);
    issue_proj_half<1>(D0, ~head & 1);
    asm volatile("barrier.cluster.arrive.relaxed.aligned;" ::: "memory");
    wg_wait<0>(); pin(D0);
    store_proj(D0, &mp.ot, st + SM_TIN + 12288, sta + SM_TIN + 12288, 8 * TB + 16, oc, och);
    TR(2, 13, 7);
    if (lane == 0) asm volatile("cp.async.bulk.wait_group.read 0;" ::: "memory");
    __syncwarp();
    TR(2, 13, 8);
    TR2(blockIdx.x, 2);
    TRDUMP;
    asm volatile("barrier.cluster.wait.aligned;" ::: "memory");
  } else {
    if (warp == 12) {
      if (elect_one()) {
        mbar_init(bar + B_WK * 8, 1);
#pragma unroll
        for (int i = 0; i < NL; i++) load_w(&mp.w, sb + SM_W + (3 * i + 2 - 2 * va) * 6144, bar + B_WK * 8, ((i + 1) % 3) * 192 + head * 48 + 32 - 32 * va);
        asm volatile("prefetch.tensormap [%0];" ::"l"(head ? &mp.xc : &mp.xh) : "memory");
        mbar_expect(bar + B_WK * 8, NL * 6144);
      }
    } else if (warp == 15) {
      const int col = min(max(strip * 16 - 3 + min(lane, 21), 0), 111);
      const uint8_t* p = reinterpret_cast<const uint8_t*>(x) + (uint32_t)(head * ROWB + (ph * 112 + col) * 768 + pw * 384);
#pragma unroll
      for (int i = 0; i < 3; i++) asm volatile("prefetch.global.L2 [%0];" ::"l"(p + i * 128));
    } else if (elect_one()) {
      if (warp == 13) {
#pragma unroll
        for (int i = 0; i < B_WK; i++) mbar_init(bar + i * 8, i < B_EMPTY ? 1 : (i < B_TIN ? 16 : (i < B_TFREE ? (i == B_TIN + 2 ? 5 : 1) : 16)));
      } else {
#pragma unroll
        for (int i = B_WQ; i < B_COUNT; i++) mbar_init(bar + i * 8, i < B_Q0 ? 1 : (i < B_ODONE ? 4 : 8));
      }
    }
    asm volatile("fence.mbarrier_init.release.cluster;" ::: "memory");
    __syncwarp();
    asm volatile("barrier.cluster.arrive.relaxed.aligned;" ::: "memory");
    asm volatile("setmaxnreg.dec.sync.aligned.u32 24;");
    asm volatile("griddepcontrol.launch_dependents;");
    const int cc = ph * 112 + (head ? strip * 16 : (strip == 0 ? 16 : (strip == 6 ? 74 : strip * 16 - 3)));
    const int sd = strip == 0 ? -1 : (strip == 6 ? 1 : 0);
    const int r0 = head == 0 ? -4 : (head == 1 ? 4 : 0);
    asm volatile("barrier.cluster.wait.aligned;" ::: "memory");
    if (warp == 12) {
      const uint32_t fb = bar + (B_FULL + head) * 8, eb = bar + (B_EMPTY + head) * 8;
      const uint32_t dst = sb + (head == 0 ? SM_X0 : (head == 1 ? SM_X1 : SM_X2));
      const int nl = head == 0 ? 15 : (head == 3 ? 1 : 14);
#pragma unroll 1
      for (int n = 0; n < nl; n++) {
        if (n) mbar_wait(eb, (n - 1) & 1);
        if (lane < 4 && head < 3)
          asm volatile("{\n.reg .b32 ra;\nmapa.shared::cluster.u32 ra, %0, %1;\nmbarrier.arrive.expect_tx.shared::cluster.b64 _, [ra], %2;\n}"
                       ::"r"(fb), "r"(lane), "r"(head ? 24576 : 18432) : "memory");
        __syncwarp();
        if (elect_one()) {
          if (head == 0) {
            asm volatile("cp.async.bulk.tensor.5d.shared::cluster.global.mbarrier::complete_tx::bytes.multicast::cluster [%0], [%1, {%3,%4,%5,%6,%7}], [%2], %8;"
                         ::"r"(dst), "l"(&mp.xh), "r"(fb), "r"(0), "r"(8 * n + r0), "r"(cc), "r"(sd), "r"(pw * 3), "h"((uint16_t)15) : "memory");
          } else if (head < 3) {
            asm volatile("cp.async.bulk.tensor.4d.shared::cluster.global.mbarrier::complete_tx::bytes.multicast::cluster [%0], [%1, {%3,%4,%5,%6}], [%2], %7;"
                         ::"r"(dst), "l"(&mp.xc), "r"(fb), "r"(0), "r"(8 * n + r0), "r"(cc), "r"(pw * 3), "h"((uint16_t)15) : "memory");
          }
          if (n == 0) {
#pragma unroll
            for (int i = 0; i < 3; i++) load_w(&mp.w, sb + SM_W + (6 + i) * 6144, bar + B_WQ * 8, head * 48 + i * 16);
            mbar_expect(bar + B_WQ * 8, 18432);
            mbar_expect(bar + B_TIN * 8, 24576); mbar_expect(bar + (B_TIN + 1) * 8, 24576); mbar_expect(bar + (B_TIN + 2) * 8, 6144); mbar_expect(bar + (B_TIN + 3) * 8, 12288);
          }
          if (!head && n + 1 < nl) asm volatile("cp.async.bulk.prefetch.tensor.5d.L2.global [%0, {%1,%2,%3,%4,%5}];" ::"l"(&mp.xh), "r"(0), "r"(8 * n + 8 + r0), "r"(cc), "r"(sd), "r"(pw * 3) : "memory");
          if (head && n + 1 < nl) asm volatile("cp.async.bulk.prefetch.tensor.4d.L2.global [%0, {%1,%2,%3,%4}];" ::"l"(&mp.xc), "r"(0), "r"(8 * n + 8 + r0), "r"(cc), "r"(pw * 3) : "memory");
        }
        __syncwarp();
      }
      mbar_wait(bar + B_WOFREE * 8, 0);
      if (elect_one()) {
        mbar_expect(bar + B_WO * 8, 36864);
        asm volatile("cp.async.bulk.tensor.3d.shared::cluster.global.mbarrier::complete_tx::bytes [%0], [%1, {%3,%4,%5}], [%2];"
                     ::"r"(sb + SM_TWO), "l"(&mp.wo), "r"(bar + B_WO * 8), "r"(0), "r"(0), "r"((head & 1) * 3) : "memory");
      }
      __syncwarp();
    }
    if (warp == 14) {
      int* flag = g_flags + cl * 2;
      nb_arrive(N_VQ0, 288); nb_arrive(N_VQ1, 288);
#pragma unroll 1
      for (int b = 0; b < TB; b++) {
        mbar_wait(bar + B_ODONE * 8, b & 1);
        if (lane == 0) {
          asm volatile("cp.async.bulk.tensor.3d.global.shared::cta.bulk_group [%0, {%2,%3,%4}], [%1];"
                       ::"l"(&mp.os), "r"(sb + SM_O), "r"(pw * 192), "r"(8 * b + 2 * head), "r"(ph * 112 + strip * 16) : "memory");
          asm volatile("cp.async.bulk.commit_group;\ncp.async.bulk.wait_group 0;" ::: "memory");
        }
        __syncwarp();
        nb_arrive(N_VQ0, 288); nb_arrive(N_VQ1, 288);
        if (lane == 0)
          asm volatile("fence.proxy.async.global;\nfence.acq_rel.gpu;\nred.relaxed.gpu.global.add.s32 [%0], 1;\nred.relaxed.gpu.global.add.s32 [%0+4], 1;"
                       ::"l"(flag + b * 56) : "memory");
        __syncwarp();
      }
    } else if (warp & 1) {
      const int j = (warp >> 1) & 1;
#pragma unroll 1
      for (int i = 0; i < 2; i++) {
        mbar_wait(bar + (B_OTAIL + j) * 8, i);
        if (i == 0) nb_arrive(N_VQ0 + j, 288);
        mbar_wait(bar + (B_TFREE + i) * 8, 0);
        if (i == 1) nb_arrive(N_VQ0 + j, 288);
        if (elect_one()) {
#pragma unroll 1
          for (int d = 0; d < 8; d++) {
            const int dst = (d + head) & 3, pc = d >> 2;
            send_o<1536>(sb + SM_TIN + i * 24576 + head * 6144 + j * 3072 + pc * 1536,
                         sb + (i ? SM_Q : SM_O) + (4 * j + (dst & 2) + pc) * (i ? 3072 : 1536), bar + (B_TIN + i) * 8, dst);
          }
        }
        __syncwarp();
      }
    }
    cluster_sync();
  }
}

constexpr int NSTB = 6;
constexpr int NTB = TB * 56;
constexpr int SM_B_IN = 0;
constexpr int SM_B_W = SM_B_IN + NSTB * 24576;
constexpr int SM_B_BAR = SM_B_W + 73728;
constexpr int SM_B_TOTAL = SM_B_BAR + 128;
struct MapsB { CUtensorMap oi, oo, wo; };

__global__ void __launch_bounds__(480, 1)
na_proj_kernel(const __grid_constant__ MapsB mp) {
  extern __shared__ __align__(1024) uint8_t smem_raw[];
  const uint32_t sb = smem_u32(smem_raw);
  if ((sb & 0x3FFFF) != SBC) return;
  const uint32_t bar = sb + SM_B_BAR;
  const int tid = threadIdx.x, lane = tid & 31;
  const int warp = __shfl_sync(0xffffffffu, tid >> 5, 0);
  TR2(132 + blockIdx.x, 0);
  TRB(47, 0);
  if (warp == 12 && elect_one()) {
#pragma unroll
    for (int i = 0; i <= 2 * NSTB; i++) mbar_init(bar + i * 8, i < NSTB || i == 2 * NSTB ? 1 : 4);
    mbar_expect(bar + 2 * NSTB * 8, 73728);
#pragma unroll
    for (int i = 0; i < 2; i++)
      asm volatile("cp.async.bulk.tensor.3d.shared::cluster.global.mbarrier::complete_tx::bytes [%0], [%1, {%3,%4,%5}], [%2];"
                   ::"r"(sb + SM_B_W + i * 36864), "l"(&mp.wo), "r"(bar + 2 * NSTB * 8), "r"(0), "r"(0), "r"(i * 3) : "memory");
  }
  __syncthreads();
  const int step = gridDim.x;
  if (warp >= 12) {
    const int wg = warp - 12;
    int use = 0;
#pragma unroll 1
    for (int n = blockIdx.x + wg * step; n < NTB; n += 3 * step, use++) {
      const int b = n / 56, rem = n - b * 56, par = rem / 14, sg = wg + 3 * (use & 1);
      int v; uint32_t spin = 0;
      do { asm volatile("ld.acquire.gpu.global.s32 %0, [%1];" : "=r"(v) : "l"(g_flags + n) : "memory"); if ((OPT & 1) && v < 4) __nanosleep(200); } while (v < 4 && ++spin < SPIN_LIMIT);
      TRB(use * 3 + wg, 0);
      asm volatile("fence.proxy.async.global;" ::: "memory");
      if (use >= 2) mbar_wait(bar + (NSTB + sg) * 8, ((use >> 1) - 1) & 1);
      TRB(use * 3 + wg, 1);
      if (elect_one()) {
        mbar_expect(bar + sg * 8, 24576);
        asm volatile("cp.async.bulk.tensor.3d.shared::cluster.global.mbarrier::complete_tx::bytes [%0], [%1, {%3,%4,%5}], [%2];"
                     ::"r"(sb + SM_B_IN + sg * 24576), "l"(&mp.oi), "r"(bar + sg * 8), "r"((par & 1) * 192), "r"(8 * b), "r"((par >> 1) * 112 + (rem - par * 14) * 8) : "memory");
        g_flags[n] = 0;
      }
      __syncwarp();
    }
  } else {
    const int wg = warp >> 2, w = warp & 3;
    constexpr uint64_t db = mkdesc(SBC + SM_B_W, 12288, 512, 2);
    const uint32_t sta0 = sb + SM_B_IN + w * 6144 + (lane & 15) * 128 + (((lane >> 4) ^ (lane & 7)) * 16);
    mbar_wait(bar + 2 * NSTB * 8, 0);
    TRB(47, 1);
    int use = 0;
#pragma unroll 1
    for (int n = blockIdx.x + wg * step; n < NTB; n += 3 * step, use++) {
      const int b = n / 56, rem = n - b * 56, par = rem / 14, sg = wg + 3 * (use & 1);
      const uint64_t da = mkdesc(SBC + SM_B_IN, 128, 3072, 0) + sg * (24576 / 16);
      float D[96];
      mbar_wait(bar + sg * 8, (use >> 1) & 1);
      if (use | wg) nb_sync(4 + wg, 256);
      TRB(use * 3 + wg, 3);
      wg_fence();
      wg_ss192<0>(D, da, db);
#pragma unroll
      for (int k = 1; k < 12; k++) wg_ss192<1>(D, da + k * 16, db + k * 64);
      wg_commit();
      if (n + step < NTB) nb_arrive(wg == 2 ? 4 : 5 + wg, 256);
      TRB(use * 3 + wg, 4);
      if (use && lane == 0) {
        asm volatile("cp.async.bulk.wait_group.read 0;" ::: "memory");
        mbar_arrive(bar + (NSTB + wg + 3 * (~use & 1)) * 8);
      }
      __syncwarp();
      wg_wait<0>(); pin(D);
      nb_sync(1 + wg, 128);
      TRB(use * 3 + wg, 5);
      const uint32_t sta = sta0 + sg * 24576;
#pragma unroll
      for (int q = 0; q < 12; q++)
        stsm4((sta ^ ((q & 3) * 32)) + (q >> 2) * 2048,
              pack2(D[8 * q], D[8 * q + 1]), pack2(D[8 * q + 2], D[8 * q + 3]), pack2(D[8 * q + 4], D[8 * q + 5]), pack2(D[8 * q + 6], D[8 * q + 7]));
      fence_async();
      __syncwarp();
      if (lane == 0) {
        asm volatile("cp.async.bulk.tensor.4d.global.shared::cta.bulk_group [%0, {%2,%3,%4,%5}], [%1];"
                     ::"l"(&mp.oo), "r"(sb + SM_B_IN + sg * 24576 + w * 6144), "r"(0), "r"(8 * b), "r"((par >> 1) * 112 + (rem - par * 14) * 8 + 2 * w), "r"((par & 1) * 3) : "memory");
        asm volatile("cp.async.bulk.commit_group;" ::: "memory");
      }
      __syncwarp();
      TRB(use * 3 + wg, 6);
    }
    if (lane == 0) asm volatile("cp.async.bulk.wait_group 0;" ::: "memory");
    TR2(132 + blockIdx.x, 2);
  }
}

typedef CUresult (*EncodeFn)(CUtensorMap*, CUtensorMapDataType, cuuint32_t, void*, const cuuint64_t*, const cuuint64_t*, const cuuint32_t*,
                             const cuuint32_t*, CUtensorMapInterleave, CUtensorMapSwizzle, CUtensorMapL2promotion, CUtensorMapFloatOOBfill);
static EncodeFn g_enc = nullptr;
static void make_map(CUtensorMap* m, const void* p, int rank, const cuuint64_t* dim, const cuuint64_t* str, const cuuint32_t* box, CUtensorMapSwizzle sw) {
  const cuuint32_t ones[5] = {1, 1, 1, 1, 1};
  g_enc(m, CU_TENSOR_MAP_DATA_TYPE_BFLOAT16, rank, (void*)p, dim, str, box, ones, CU_TENSOR_MAP_INTERLEAVE_NONE, sw,
        CU_TENSOR_MAP_L2_PROMOTION_L2_128B, CU_TENSOR_MAP_FLOAT_OOB_FILL_NONE);
}

extern "C" void kernel_launch(void* const* d_in, const int* in_sizes, int n_in, void* d_out, int out_size) {
  const __nv_bfloat16* x = (const __nv_bfloat16*)d_in[0];
  const __nv_bfloat16* wqkv = (const __nv_bfloat16*)d_in[1];
  const __nv_bfloat16* wo = (const __nv_bfloat16*)d_in[2];
  const __nv_bfloat16* rpb = (const __nv_bfloat16*)d_in[3];

  if (!g_enc) {
    void* fn = nullptr; cudaDriverEntryPointQueryResult qr;
    cudaGetDriverEntryPoint("cuTensorMapEncodeTiled", &fn, cudaEnableDefault, &qr);
    g_enc = (EncodeFn)fn;
    cudaFuncSetAttribute(na_attn_kernel, cudaFuncAttributeMaxDynamicSharedMemorySize, SM_A_TOTAL);
    cudaFuncSetAttribute(na_proj_kernel, cudaFuncAttributeMaxDynamicSharedMemorySize, SM_B_TOTAL);
  }
  Maps ma; MapsB mb;
  { cuuint64_t dim[4] = {64, 112, 224, 6}, str[3] = {(cuuint64_t)ROWB, 768, 128};
    cuuint32_t box[4] = {64, 4, 16, 3}, boxo[4] = {64, 8, 2, 3};
    make_map(&ma.xc, x, 4, dim, str, box, CU_TENSOR_MAP_SWIZZLE_128B);
    make_map(&mb.oo, d_out, 4, dim, str, boxo, CU_TENSOR_MAP_SWIZZLE_128B); }
  { cuuint64_t dim[5] = {64, 112, 224, 2, 6}, str[4] = {(cuuint64_t)ROWB, 768, 19 * 768, 128};
    cuuint32_t box[5] = {64, 8, 3, 2, 3};
    make_map(&ma.xh, x, 5, dim, str, box, CU_TENSOR_MAP_SWIZZLE_128B); }
  { cuuint64_t dim[3] = {384, 112, 224}, str[2] = {(cuuint64_t)ROWB, 768};
    cuuint32_t box[3] = {192, 8, 8}, boxs[3] = {192, 2, 16};
    make_map(&mb.oi, d_out, 3, dim, str, box, CU_TENSOR_MAP_SWIZZLE_NONE);
    make_map(&ma.os, d_out, 3, dim, str, boxs, CU_TENSOR_MAP_SWIZZLE_NONE); }
  { cuuint64_t dim[4] = {32, 112, 224, 12}, str[3] = {(cuuint64_t)ROWB, 768, 64};
    cuuint32_t box[4] = {32, 8, 2, 3};
    make_map(&ma.ot, d_out, 4, dim, str, box, CU_TENSOR_MAP_SWIZZLE_64B); }
  { cuuint64_t dim[2] = {576, 192}, str[1] = {1152};
    cuuint32_t box[2] = {16, 192};
    make_map(&ma.w, wqkv, 2, dim, str, box, CU_TENSOR_MAP_SWIZZLE_32B); }
  { cuuint64_t dim[3] = {32, 192, 6}, str[2] = {384, 64};
    cuuint32_t box[3] = {32, 192, 3};
    make_map(&ma.wo, wo, 3, dim, str, box, CU_TENSOR_MAP_SWIZZLE_64B);
    mb.wo = ma.wo; }
  na_attn_kernel<<<112, 512, SM_A_TOTAL>>>(x, wqkv, rpb, ma);
  cudaLaunchConfig_t cfg = {};
  cfg.gridDim = dim3(20); cfg.blockDim = dim3(480); cfg.dynamicSmemBytes = SM_B_TOTAL; cfg.stream = cudaStreamPerThread;
  cudaLaunchAttribute at[1];
  at[0].id = cudaLaunchAttributeProgrammaticStreamSerialization; at[0].val.programmaticStreamSerializationAllowed = 1;
  cfg.attrs = at; cfg.numAttrs = 1;
  cudaLaunchKernelEx(&cfg, na_proj_kernel, mb);
}
```

```cpp
#include <cuda_runtime.h>
#include <cuda_bf16.h>
#include <cuda.h>
#include <stdint.h>

#define SPIN_LIMIT (1u << 18)

__device__ __forceinline__ uint32_t smem_u32(const void* p) { return (uint32_t)__cvta_generic_to_shared(p); }
__device__ __forceinline__ void wg_fence() { asm volatile("wgmma.fence.sync.aligned;" ::: "memory"); }
__device__ __forceinline__ void wg_commit() { asm volatile("wgmma.commit_group.sync.aligned;" ::: "memory"); }
template <int N> __device__ __forceinline__ void wg_wait() { asm volatile("wgmma.wait_group.sync.aligned %0;" ::"n"(N) : "memory"); }
template <int N> __device__ __forceinline__ void pin(float (&d)[N]) {
#pragma unroll
  for (int i = 0; i < N; i++) asm volatile("" : "+f"(d[i])::"memory");
}
__host__ __device__ constexpr uint64_t mkdesc(uint32_t addr, uint32_t lbo, uint32_t sbo, uint32_t sw) {
  return (uint64_t)((addr & 0x3FFFF) >> 4) | ((uint64_t)(lbo >> 4) << 16) | ((uint64_t)(sbo >> 4) << 32) | ((uint64_t)sw << 62);
}
__device__ __forceinline__ void mbar_init(uint32_t bar, uint32_t cnt) { asm volatile("mbarrier.init.shared::cta.b64 [%0], %1;" ::"r"(bar), "r"(cnt) : "memory"); }
__device__ __forceinline__ void mbar_arrive(uint32_t bar) { asm volatile("mbarrier.arrive.shared::cta.b64 _, [%0];" ::"r"(bar) : "memory"); }
__device__ __forceinline__ bool elect_one() {
  uint32_t r; asm volatile("{\n.reg .pred p;\nelect.sync _|p, 0xffffffff;\nselp.u32 %0, 1, 0, p;\n}" : "=r"(r)); return r;
}
__device__ __forceinline__ void mbar_arrive_elect(uint32_t bar) {
  asm volatile("{\n.reg .pred p;\nelect.sync _|p, 0xffffffff;\n@p mbarrier.arrive.shared::cta.b64 _, [%0];\n}" ::"r"(bar) : "memory");
}
__device__ __forceinline__ void mbar_expect(uint32_t bar, uint32_t bytes) { asm volatile("mbarrier.arrive.expect_tx.shared::cta.b64 _, [%0], %1;" ::"r"(bar), "r"(bytes) : "memory"); }
__device__ __forceinline__ void mbar_arrive_remote(uint32_t bar, uint32_t cta) {
  asm volatile("{\n.reg .b32 ra;\nmapa.shared::cluster.u32 ra, %0, %1;\nmbarrier.arrive.relaxed.cluster.shared::cluster.b64 _, [ra];\n}" ::"r"(bar), "r"(cta) : "memory");
}
__device__ __forceinline__ void mbar_wait(uint32_t bar, uint32_t parity) {
  asm volatile("{\n.reg .pred p;\n.reg .b32 n;\nmov.b32 n, 0;\nWL:\nmbarrier.try_wait.parity.shared::cta.b64 p, [%0], %1;\n@p bra WD;\n"
               "add.u32 n, n, 1;\nsetp.lt.u32 p, n, 65536;\n@p bra WL;\nWD:\n}" ::"r"(bar), "r"(parity) : "memory");
}
__device__ __forceinline__ void nb_sync(int id, int n) { asm volatile("bar.sync %0, %1;" ::"r"(id), "r"(n) : "memory"); }
__device__ __forceinline__ void nb_arrive(int id, int n) { asm volatile("bar.arrive %0, %1;" ::"r"(id), "r"(n) : "memory"); }
__device__ __forceinline__ uint32_t opq(uint32_t x) { uint32_t r; asm volatile("mov.b32 %0, %1;" : "=r"(r) : "r"(x)); return r; }
__device__ __forceinline__ uint64_t opq(uint64_t x) { uint64_t r; asm volatile("mov.b64 %0, %1;" : "=l"(r) : "l"(x)); return r; }
__device__ __forceinline__ uint32_t mapa(uint32_t a, uint32_t cta) { uint32_t r; asm("mapa.shared::cluster.u32 %0, %1, %2;" : "=r"(r) : "r"(a), "r"(cta)); return r; }
__device__ __forceinline__ void fence_async() { asm volatile("fence.proxy.async.shared::cta;" ::: "memory"); }
__device__ __forceinline__ void cluster_sync() {
  asm volatile("barrier.cluster.arrive.relaxed.aligned;\nbarrier.cluster.wait.aligned;" ::: "memory");
}
__device__ __forceinline__ uint32_t pack2(float lo, float hi) {
  uint32_t r; asm("cvt.rn.bf16x2.f32 %0, %1, %2;" : "=r"(r) : "f"(hi), "f"(lo)); return r;
}
__device__ __forceinline__ void stsm4(uint32_t a, uint32_t r0, uint32_t r1, uint32_t r2, uint32_t r3) {
  asm volatile("stmatrix.sync.aligned.m8n8.x4.shared.b16 [%0], {%1,%2,%3,%4};" ::"r"(a), "r"(r0), "r"(r1), "r"(r2), "r"(r3) : "memory");
}
__device__ __forceinline__ void ldsm4(uint32_t a, uint32_t& r0, uint32_t& r1, uint32_t& r2, uint32_t& r3) {
  asm volatile("ldmatrix.sync.aligned.m8n8.x4.shared.b16 {%0,%1,%2,%3}, [%4];" : "=r"(r0), "=r"(r1), "=r"(r2), "=r"(r3) : "r"(a) : "memory");
}
__device__ __forceinline__ void sts128(uint32_t a, uint4 v) {
  asm volatile("st.shared.v4.b32 [%0], {%1,%2,%3,%4};" ::"r"(a), "r"(v.x), "r"(v.y), "r"(v.z), "r"(v.w) : "memory");
}
__device__ __forceinline__ float lds_f32(uint32_t a) { float v; asm volatile("ld.shared.f32 %0, [%1];" : "=f"(v) : "r"(a)); return v; }
__device__ __forceinline__ float ex2(float x) { float y; asm("ex2.approx.ftz.f32 %0, %1;" : "=f"(y) : "f"(x)); return y; }

template<int SC> __device__ __forceinline__ void wg_ss144(float (&d)[72], uint64_t da, uint64_t db) {
  asm volatile("{\n.reg .pred p;\nsetp.ne.b32 p, %74, 0;\nwgmma.mma_async.sync.aligned.m64n144k16.f32.bf16.bf16 {%0,%1,%2,%3,%4,%5,%6,%7,%8,%9,%10,%11,%12,%13,%14,%15,%16,%17,%18,%19,%20,%21,%22,%23,%24,%25,%26,%27,%28,%29,%30,%31,%32,%33,%34,%35,%36,%37,%38,%39,%40,%41,%42,%43,%44,%45,%46,%47,%48,%49,%50,%51,%52,%53,%54,%55,%56,%57,%58,%59,%60,%61,%62,%63,%64,%65,%66,%67,%68,%69,%70,%71}, %72, %73, p, 1, 1, 0, 1;\n}\n"
    : "+f"(d[0]),"+f"(d[1]),"+f"(d[2]),"+f"(d[3]),"+f"(d[4]),"+f"(d[5]),"+f"(d[6]),"+f"(d[7]),"+f"(d[8]),"+f"(d[9]),"+f"(d[10]),"+f"(d[11]),"+f"(d[12]),"+f"(d[13]),"+f"(d[14]),"+f"(d[15]),"+f"(d[16]),"+f"(d[17]),"+f"(d[18]),"+f"(d[19]),"+f"(d[20]),"+f"(d[21]),"+f"(d[22]),"+f"(d[23]),"+f"(d[24]),"+f"(d[25]),"+f"(d[26]),"+f"(d[27]),"+f"(d[28]),"+f"(d[29]),"+f"(d[30]),"+f"(d[31]),"+f"(d[32]),"+f"(d[33]),"+f"(d[34]),"+f"(d[35]),"+f"(d[36]),"+f"(d[37]),"+f"(d[38]),"+f"(d[39]),"+f"(d[40]),"+f"(d[41]),"+f"(d[42]),"+f"(d[43]),"+f"(d[44]),"+f"(d[45]),"+f"(d[46]),"+f"(d[47]),"+f"(d[48]),"+f"(d[49]),"+f"(d[50]),"+f"(d[51]),"+f"(d[52]),"+f"(d[53]),"+f"(d[54]),"+f"(d[55]),"+f"(d[56]),"+f"(d[57]),"+f"(d[58]),"+f"(d[59]),"+f"(d[60]),"+f"(d[61]),"+f"(d[62]),"+f"(d[63]),"+f"(d[64]),"+f"(d[65]),"+f"(d[66]),"+f"(d[67]),"+f"(d[68]),"+f"(d[69]),"+f"(d[70]),"+f"(d[71]) : "l"(da), "l"(db), "n"(SC));
}
template<int SC> __device__ __forceinline__ void wg_ss96(float (&d)[48], uint64_t da, uint64_t db) {
  asm volatile("{\n.reg .pred p;\nsetp.ne.b32 p, %50, 0;\nwgmma.mma_async.sync.aligned.m64n96k16.f32.bf16.bf16 {%0,%1,%2,%3,%4,%5,%6,%7,%8,%9,%10,%11,%12,%13,%14,%15,%16,%17,%18,%19,%20,%21,%22,%23,%24,%25,%26,%27,%28,%29,%30,%31,%32,%33,%34,%35,%36,%37,%38,%39,%40,%41,%42,%43,%44,%45,%46,%47}, %48, %49, p, 1, 1, 0, 1;\n}\n"
    : "+f"(d[0]),"+f"(d[1]),"+f"(d[2]),"+f"(d[3]),"+f"(d[4]),"+f"(d[5]),"+f"(d[6]),"+f"(d[7]),"+f"(d[8]),"+f"(d[9]),"+f"(d[10]),"+f"(d[11]),"+f"(d[12]),"+f"(d[13]),"+f"(d[14]),"+f"(d[15]),"+f"(d[16]),"+f"(d[17]),"+f"(d[18]),"+f"(d[19]),"+f"(d[20]),"+f"(d[21]),"+f"(d[22]),"+f"(d[23]),"+f"(d[24]),"+f"(d[25]),"+f"(d[26]),"+f"(d[27]),"+f"(d[28]),"+f"(d[29]),"+f"(d[30]),"+f"(d[31]),"+f"(d[32]),"+f"(d[33]),"+f"(d[34]),"+f"(d[35]),"+f"(d[36]),"+f"(d[37]),"+f"(d[38]),"+f"(d[39]),"+f"(d[40]),"+f"(d[41]),"+f"(d[42]),"+f"(d[43]),"+f"(d[44]),"+f"(d[45]),"+f"(d[46]),"+f"(d[47]) : "l"(da), "l"(db), "n"(SC));
}
template<int SC> __device__ __forceinline__ void wg_rs112(float (&d)[56], uint32_t a0, uint32_t a1, uint32_t a2, uint32_t a3, uint64_t db) {
  asm volatile("{\n.reg .pred p;\nsetp.ne.b32 p, %61, 0;\nwgmma.mma_async.sync.aligned.m64n112k16.f32.bf16.bf16 {%0,%1,%2,%3,%4,%5,%6,%7,%8,%9,%10,%11,%12,%13,%14,%15,%16,%17,%18,%19,%20,%21,%22,%23,%24,%25,%26,%27,%28,%29,%30,%31,%32,%33,%34,%35,%36,%37,%38,%39,%40,%41,%42,%43,%44,%45,%46,%47,%48,%49,%50,%51,%52,%53,%54,%55}, {%56,%57,%58,%59}, %60, p, 1, 1, 0;\n}\n"
    : "+f"(d[0]),"+f"(d[1]),"+f"(d[2]),"+f"(d[3]),"+f"(d[4]),"+f"(d[5]),"+f"(d[6]),"+f"(d[7]),"+f"(d[8]),"+f"(d[9]),"+f"(d[10]),"+f"(d[11]),"+f"(d[12]),"+f"(d[13]),"+f"(d[14]),"+f"(d[15]),"+f"(d[16]),"+f"(d[17]),"+f"(d[18]),"+f"(d[19]),"+f"(d[20]),"+f"(d[21]),"+f"(d[22]),"+f"(d[23]),"+f"(d[24]),"+f"(d[25]),"+f"(d[26]),"+f"(d[27]),"+f"(d[28]),"+f"(d[29]),"+f"(d[30]),"+f"(d[31]),"+f"(d[32]),"+f"(d[33]),"+f"(d[34]),"+f"(d[35]),"+f"(d[36]),"+f"(d[37]),"+f"(d[38]),"+f"(d[39]),"+f"(d[40]),"+f"(d[41]),"+f"(d[42]),"+f"(d[43]),"+f"(d[44]),"+f"(d[45]),"+f"(d[46]),"+f"(d[47]),"+f"(d[48]),"+f"(d[49]),"+f"(d[50]),"+f"(d[51]),"+f"(d[52]),"+f"(d[53]),"+f"(d[54]),"+f"(d[55]) : "r"(a0), "r"(a1), "r"(a2), "r"(a3), "l"(db), "n"(SC));
}
template<int SC> __device__ __forceinline__ void wg_sp48(float (&d)[24], uint32_t a0, uint32_t a1, uint32_t a2, uint32_t a3, uint64_t db, uint32_t meta) {
  asm volatile("{\n.reg .pred p;\nsetp.ne.b32 p, %30, 0;\nwgmma.mma_async.sp.sync.aligned.m64n48k32.f32.bf16.bf16 {%0,%1,%2,%3,%4,%5,%6,%7,%8,%9,%10,%11,%12,%13,%14,%15,%16,%17,%18,%19,%20,%21,%22,%23}, {%24,%25,%26,%27}, %28, %29, 0, p, 1, 1, 1;\n}\n"
    : "+f"(d[0]),"+f"(d[1]),"+f"(d[2]),"+f"(d[3]),"+f"(d[4]),"+f"(d[5]),"+f"(d[6]),"+f"(d[7]),"+f"(d[8]),"+f"(d[9]),"+f"(d[10]),"+f"(d[11]),"+f"(d[12]),"+f"(d[13]),"+f"(d[14]),"+f"(d[15]),"+f"(d[16]),"+f"(d[17]),"+f"(d[18]),"+f"(d[19]),"+f"(d[20]),"+f"(d[21]),"+f"(d[22]),"+f"(d[23]) : "r"(a0), "r"(a1), "r"(a2), "r"(a3), "l"(db), "r"(meta), "n"(SC));
}
template<int SC> __device__ __forceinline__ void wg_ss192(float (&d)[96], uint64_t da, uint64_t db) {
  asm volatile("{\n.reg .pred p;\nsetp.ne.b32 p, %98, 0;\nwgmma.mma_async.sync.aligned.m64n192k16.f32.bf16.bf16 {%0,%1,%2,%3,%4,%5,%6,%7,%8,%9,%10,%11,%12,%13,%14,%15,%16,%17,%18,%19,%20,%21,%22,%23,%24,%25,%26,%27,%28,%29,%30,%31,%32,%33,%34,%35,%36,%37,%38,%39,%40,%41,%42,%43,%44,%45,%46,%47,%48,%49,%50,%51,%52,%53,%54,%55,%56,%57,%58,%59,%60,%61,%62,%63,%64,%65,%66,%67,%68,%69,%70,%71,%72,%73,%74,%75,%76,%77,%78,%79,%80,%81,%82,%83,%84,%85,%86,%87,%88,%89,%90,%91,%92,%93,%94,%95}, %96, %97, p, 1, 1, 0, 1;\n}\n"
    : "+f"(d[0]),"+f"(d[1]),"+f"(d[2]),"+f"(d[3]),"+f"(d[4]),"+f"(d[5]),"+f"(d[6]),"+f"(d[7]),"+f"(d[8]),"+f"(d[9]),"+f"(d[10]),"+f"(d[11]),"+f"(d[12]),"+f"(d[13]),"+f"(d[14]),"+f"(d[15]),"+f"(d[16]),"+f"(d[17]),"+f"(d[18]),"+f"(d[19]),"+f"(d[20]),"+f"(d[21]),"+f"(d[22]),"+f"(d[23]),"+f"(d[24]),"+f"(d[25]),"+f"(d[26]),"+f"(d[27]),"+f"(d[28]),"+f"(d[29]),"+f"(d[30]),"+f"(d[31]),"+f"(d[32]),"+f"(d[33]),"+f"(d[34]),"+f"(d[35]),"+f"(d[36]),"+f"(d[37]),"+f"(d[38]),"+f"(d[39]),"+f"(d[40]),"+f"(d[41]),"+f"(d[42]),"+f"(d[43]),"+f"(d[44]),"+f"(d[45]),"+f"(d[46]),"+f"(d[47]),"+f"(d[48]),"+f"(d[49]),"+f"(d[50]),"+f"(d[51]),"+f"(d[52]),"+f"(d[53]),"+f"(d[54]),"+f"(d[55]),"+f"(d[56]),"+f"(d[57]),"+f"(d[58]),"+f"(d[59]),"+f"(d[60]),"+f"(d[61]),"+f"(d[62]),"+f"(d[63]),"+f"(d[64]),"+f"(d[65]),"+f"(d[66]),"+f"(d[67]),"+f"(d[68]),"+f"(d[69]),"+f"(d[70]),"+f"(d[71]),"+f"(d[72]),"+f"(d[73]),"+f"(d[74]),"+f"(d[75]),"+f"(d[76]),"+f"(d[77]),"+f"(d[78]),"+f"(d[79]),"+f"(d[80]),"+f"(d[81]),"+f"(d[82]),"+f"(d[83]),"+f"(d[84]),"+f"(d[85]),"+f"(d[86]),"+f"(d[87]),"+f"(d[88]),"+f"(d[89]),"+f"(d[90]),"+f"(d[91]),"+f"(d[92]),"+f"(d[93]),"+f"(d[94]),"+f"(d[95]) : "l"(da), "l"(db), "n"(SC));
}

constexpr uint32_t SBC = 1024;
constexpr int ROWB = 2 * 224 * 384;
constexpr int TB = 11;
constexpr int KS = 832;
constexpr int KSLOT = 22 * KS;
constexpr int SM_X2 = 0;
constexpr int SM_X0 = SM_X2 + 24576;
constexpr int SM_W = SM_X0 + 18432;
constexpr int SM_X1 = SM_W + 55296;
constexpr int SM_K = SM_X1 + 24576;
constexpr int SM_V = SM_K + 2 * KSLOT;
constexpr int SM_Q = SM_V + 22 * 1536;
constexpr int SM_O = SM_Q + 24576;
constexpr int SM_RPB = SM_O + 12288;
constexpr int SM_BAR = SM_RPB + 768;
constexpr int SM_A_TOTAL = SM_BAR + 256;
constexpr int SM_TIN = 0;
constexpr int SM_TST = 3 * 24576;
constexpr int SM_TWO = SM_TST + 12288;
enum { B_FULL = 0, B_EMPTY = 3, B_TIN = 6, B_TFREE = 10, B_WK = 12, B_WQ, B_WO, B_Q0, B_WOFREE, B_OTAIL, B_ODONE = B_OTAIL + 2, B_KFREE, B_VFREE, B_COUNT };
enum { N_KRDY = 4, N_QK0, N_QK1, N_VQ0, N_VQ1, N_PVISS };

#define NL 2
#define OPT 0
#define SPL 4
#define RA 160
#define RG 168
__device__ int g_flags[TB * 56];

#define TR(role, it, k)
#define TRDECL
#define TRARG
#define TRPASS
#define TRDUMP
#define TRB(it, k)
#define TR2(blk, k)

struct GemmCtx {
  uint32_t bar;
  uint32_t kC, vC[2], qC[2];
  uint32_t kH, vH[2];
  uint32_t hiA, hiB;
  uint32_t spin;
  bool hvalid, never;
};

template <int STRIDE> __device__ __forceinline__ void dump12(uint32_t a, const uint32_t (&r)[12]) {
#pragma unroll
  for (int j = 0; j < 3; j++) stsm4(a + j * 2 * STRIDE, r[4 * j], r[4 * j + 1], r[4 * j + 2], r[4 * j + 3]);
}
__device__ __forceinline__ void keep12(bool never, uint32_t a, const uint32_t (&r)[12]) { if (never) dump12<128>(a, r); }
template <int N> __device__ __forceinline__ void pack12(uint32_t (&r)[12], const float (&d)[N], int off) {
#pragma unroll
  for (int j = 0; j < 12; j++) r[j] = pack2(d[off + 2 * j], d[off + 2 * j + 1]);
}
__device__ __forceinline__ uint64_t dsc(uint64_t lo, uint32_t hi) { uint64_t r; asm("mov.b64 %0, {%1, %2};" : "=l"(r) : "r"((uint32_t)lo), "r"(hi)); return r; }
template <int XS, int K0, int K1> __device__ __forceinline__ void issue_core(const GemmCtx& c, float (&d)[72]) {
  constexpr uint64_t da = mkdesc(SBC + XS, 16, 1024, 1), db = mkdesc(SBC + SM_W, 6144, 256, 3);
  wg_fence();
  if (K0 == 0) wg_ss144<0>(d, dsc(da, c.hiA), dsc(db, c.hiB));
#pragma unroll
  for (int k = K0 ? K0 : 1; k < K1; k++) wg_ss144<1>(d, dsc(da + (k >> 2) * 512 + (k & 3) * 2, c.hiA), dsc(db + k * 32, c.hiB));
  wg_commit();
}
template <int K0, int K1> __device__ __forceinline__ void issue_halo(const GemmCtx& c, float (&d)[48]) {
  constexpr uint64_t da = mkdesc(SBC + SM_X0 - 2048, 16, 1024, 1), db = mkdesc(SBC + SM_W, 6144, 256, 3);
  wg_fence();
  if (K0 == 0) wg_ss96<0>(d, dsc(da, c.hiA), dsc(db, c.hiB));
#pragma unroll
  for (int k = K0 ? K0 : 1; k < K1; k++) wg_ss96<1>(d, dsc(da + (k >> 2) * 384 + (k & 3) * 2, c.hiA), dsc(db + k * 32, c.hiB));
  wg_commit();
}
template <int ST> __device__ __forceinline__ void release_stage(const GemmCtx& c) {
  asm volatile("{\n.reg .pred p;\n.reg .b32 ra;\nelect.sync _|p, 0xffffffff;\nmapa.shared::cluster.u32 ra, %0, %1;\n"
               "@p mbarrier.arrive.shared::cluster.b64 _, [ra];\n}" ::"r"(c.bar + (B_EMPTY + ST) * 8), "n"(ST) : "memory");
}
template <int PARITY> __device__ __forceinline__ void gwait(GemmCtx& c, int bar) {
  asm volatile("{\n.reg .pred p;\nWL:\nmbarrier.try_wait.parity.shared::cta.b64 p, [%1], %2;\n@p bra WD;\n"
               "add.u32 %0, %0, 1;\nsetp.lt.u32 p, %0, 0x100000;\n@p bra WL;\nWD:\n}" : "+r"(c.spin) : "r"(c.bar + bar * 8), "n"(PARITY) : "memory");
}
__device__ __forceinline__ void load_w(const CUtensorMap* m, uint32_t dst, uint32_t bar, int col) {
  asm volatile("cp.async.bulk.tensor.2d.shared::cluster.global.mbarrier::complete_tx::bytes [%0], [%1, {%3,%4}], [%2];"
               ::"r"(dst), "l"(m), "r"(bar), "r"(col), "r"(0) : "memory");
}
template <int BYTES> __device__ __forceinline__ void send_o(uint32_t dst, uint32_t src, uint32_t bar, int cta) {
  asm volatile("{\n.reg .b32 rd, rb;\nmapa.shared::cluster.u32 rd, %0, %3;\nmapa.shared::cluster.u32 rb, %2, %3;\n"
               "cp.async.bulk.shared::cluster.shared::cta.mbarrier::complete_tx::bytes [rd], [%1], %4, [rb];\n}"
               ::"r"(dst), "r"(src), "r"(bar), "r"(cta), "n"(BYTES) : "memory");
}
__device__ __forceinline__ void tail_free(uint32_t bar) {
  uint32_t ln; asm volatile("mov.u32 %0, %%laneid;" : "=r"(ln));
  if (ln < 4) mbar_arrive_remote(bar, ln);
}
__device__ __forceinline__ void publish(uint32_t bar) {
  fence_async();
  __syncwarp();
  mbar_arrive_elect(bar);
}

template <bool FIRST, int PA>
__device__ __forceinline__ void gemm_iter(GemmCtx& c, int b, uint32_t (&pk)[12], uint32_t (&pv)[12], uint32_t (&pq)[12] TRARG) {
  const uint32_t bar = c.bar;
  const bool w = !FIRST && (PA == 0 || b >= 0), never = c.never;
  constexpr uint32_t ko = PA * KSLOT;
  float H[48], C[72];
  uint32_t hk[12], hv[12], pv2[12];
  TR(2, b, 0);
  if (FIRST) gwait<PA>(c, B_FULL + 0);
  if (!FIRST) dump12<256>(c.qC[1] + (PA ^ 1) * 128, pq);
  if (w) nb_sync(N_QK1, 256);
  TR(2, b, 2);
  if (FIRST) TR(2, b - 1, 6);
  issue_halo<0, 8>(c, H);
  TR(2, b, 3);
  if (!FIRST) {
    if (w) gwait<PA>(c, B_KFREE);
    dump12<128>(c.kC + ko, pk);
  }
  issue_halo<8, 12>(c, H);
  TR(2, b, 4);
  {
    gwait<PA>(c, B_FULL + 2);
    if (FIRST && NL == 2) gwait<0>(c, B_WQ);
    TR(2, b, 13);
    if (FIRST) TR(2, b - 1, 7);
    issue_core<SM_X2, 0, 8>(c, C);
    TR(2, b, 5);
    if (!FIRST) { fence_async(); keep12(never, c.kC, pk); }
    wg_wait<1>(); pin(H);
    release_stage<0>(c);
  }
  pack12(hk, H, 0);
  if (c.hvalid) dump12<128>(c.kH + ko, hk);
  pack12(hv, H, 24);
  {
    issue_core<SM_X2, 8, 12>(c, C);
    if (w) { nb_arrive(N_VQ0, 288); nb_arrive(N_VQ1, 288); }
    else if (!FIRST) { __syncwarp(); mbar_arrive_elect(bar + B_Q0 * 8); }
    gwait<PA>(c, B_FULL + 1);
    keep12(never, c.kC, hk);
    TR(2, b, 6);
    wg_wait<0>(); pin(C);
    TR(2, b, 7);
    pack12(pk, C, 0);
    dump12<128>(c.kC + ko + 64, pk);
    release_stage<2>(c);
    pack12(pv2, C, 24);
    pack12(pq, C, 48);
    TR(2, b, 8);
    issue_core<SM_X1, 0, SPL>(c, C);
    if (w) nb_sync(N_PVISS, 384);
    issue_core<SM_X1, SPL, 8>(c, C);
    TR(2, b, 9);
  }
  if (!FIRST) fence_async();
  keep12(never, c.kC, pk);
  TR(2, b, 14);
  issue_core<SM_X1, 8, 12>(c, C);
  if (!FIRST) nb_arrive(N_KRDY, 256);
  TR(2, b, 1);
  if (PA && b == 11) tail_free(bar + B_TFREE * 8);
  gwait<PA ^ 1>(c, B_FULL + 0);
  if (w) gwait<PA>(c, B_VFREE);
  TR(2, b, 10);
  if (!FIRST) dump12<128>(c.vC[PA], pv);
  dump12<256>(c.qC[0] + PA * 128, pq);
  if (c.hvalid) dump12<128>(c.vH[PA], hv);
  dump12<128>(c.vC[PA ^ 1] + 768, pv2);
  TR(2, b, 11);
  wg_wait<0>(); pin(C);
  TR(2, b, 12);
  release_stage<1>(c);
  pack12(pk, C, 0);
  pack12(pv, C, 24);
  pack12(pq, C, 48);
}

template <int IN> __device__ __forceinline__ void issue_proj(float (&D)[48]) {
  constexpr uint64_t da = mkdesc(SBC + IN, 128, 768, 0), db = mkdesc(SBC + SM_TWO, 12288, 512, 2);
  wg_fence();
  wg_ss96<0>(D, da, db);
#pragma unroll
  for (int k = 1; k < 12; k++) wg_ss96<1>(D, da + (k / 3) * 384 + (k % 3) * 16, db + k * 64);
  wg_commit();
}
template <int ACC> __device__ __forceinline__ void issue_proj_half(float (&D)[48], int hd) {
  const uint64_t da = mkdesc(SBC + SM_TIN + 2 * 24576, 128, 768, 0) + hd * 384, db = mkdesc(SBC + SM_TWO, 12288, 512, 2) + hd * 192;
  wg_fence();
  wg_ss96<ACC>(D, da, db);
#pragma unroll
  for (int k = 1; k < 6; k++) wg_ss96<1>(D, da + (k / 3) * 768 + (k % 3) * 16, db + (k / 3) * 384 + (k % 3) * 64);
  wg_commit();
}
__device__ __forceinline__ void store_proj(const float (&D)[48], const CUtensorMap* m, uint32_t st, uint32_t sta, int row, int col, int ch) {
#pragma unroll
  for (int q = 0; q < 6; q++)
    stsm4((sta ^ ((q & 1) * 32)) + (q >> 1) * 1024,
          pack2(D[8 * q], D[8 * q + 1]), pack2(D[8 * q + 2], D[8 * q + 3]), pack2(D[8 * q + 4], D[8 * q + 5]), pack2(D[8 * q + 6], D[8 * q + 7]));
  fence_async();
  __syncwarp();
  if ((threadIdx.x & 31) == 0) {
    asm volatile("cp.async.bulk.tensor.4d.global.shared::cta.bulk_group [%0, {%2,%3,%4,%5}], [%1];" ::"l"(m), "r"(st), "r"(0), "r"(row), "r"(col), "r"(ch) : "memory");
    asm volatile("cp.async.bulk.commit_group;" ::: "memory");
  }
  __syncwarp();
}

__device__ __forceinline__ float fold(float a, float b, float t, int useb) {
  float r;
  asm("{\n.reg .pred p;\nsetp.ne.b32 p, %4, 0;\nfma.rn.f32 %0, %1, 0f3E553B95, %3;\n@p fma.rn.f32 %0, %2, 0f3E553B95, %3;\n}"
      : "=&f"(r) : "f"(a), "f"(b), "f"(t), "r"(useb));
  return r;
}
template <int U, int L>
__device__ __forceinline__ void softmax_tile(const float (&SA)[56], const float (&SB)[56], const float (&T)[16], int b0, int b1,
                                             uint32_t (&P)[28], float (&sx)[8]) {
  float lu[14], ll[14];
#pragma unroll
  for (int j = 0; j < 7; j++) {
    constexpr int sh = U == L ? 2 : 0;
    const float tu0 = T[2 * j + sh], tu1 = T[2 * j + 1 + sh], tl0 = T[2 * j], tl1 = T[2 * j + 1];
    lu[2 * j]     = fold(SA[4 * (U + j)],     SB[4 * (U + j)],     tu0, b0);
    ll[2 * j]     = fold(SA[4 * (L + j) + 2], SB[4 * (L + j) + 2], tl0, b0);
    lu[2 * j + 1] = fold(SA[4 * (U + j) + 1], SB[4 * (U + j) + 1], tu1, b1);
    ll[2 * j + 1] = fold(SA[4 * (L + j) + 3], SB[4 * (L + j) + 3], tl1, b1);
  }
  float mu = lu[0], ml = ll[0], mu2 = lu[1], ml2 = ll[1];
#pragma unroll
  for (int j = 1; j < 7; j++) { mu = fmaxf(mu, lu[2 * j]); mu2 = fmaxf(mu2, lu[2 * j + 1]); ml = fmaxf(ml, ll[2 * j]); ml2 = fmaxf(ml2, ll[2 * j + 1]); }
  mu = fmaxf(mu, mu2); ml = fmaxf(ml, ml2);
  { const float a1 = __shfl_xor_sync(0xffffffffu, mu, 1), a2 = __shfl_xor_sync(0xffffffffu, mu, 2), a3 = __shfl_xor_sync(0xffffffffu, mu, 3);
    const float c1 = __shfl_xor_sync(0xffffffffu, ml, 1), c2 = __shfl_xor_sync(0xffffffffu, ml, 2), c3 = __shfl_xor_sync(0xffffffffu, ml, 3);
    mu = fmaxf(fmaxf(mu, a1), fmaxf(a2, a3)); ml = fmaxf(fmaxf(ml, c1), fmaxf(c2, c3)); }
  float su = 0.f, sl = 0.f;
#pragma unroll
  for (int c = 0; c < 14; c++) {
    const int iu = (c >> 1) * 4 + (c & 1) * 2;
    if (c >= U && c < U + 7) {
      float e0 = ex2(lu[2 * (c - U)] - mu), e1 = ex2(lu[2 * (c - U) + 1] - mu);
      su = c == U ? e0 + e1 : (su + e0) + e1; P[iu] = pack2(e0, e1);
    } else P[iu] = 0u;
    if (c >= L && c < L + 7) {
      float e0 = ex2(ll[2 * (c - L)] - ml), e1 = ex2(ll[2 * (c - L) + 1] - ml);
      sl = c == L ? e0 + e1 : (sl + e0) + e1; P[iu + 1] = pack2(e0, e1);
    } else P[iu + 1] = 0u;
  }
  sx[0] = su; sx[4] = sl;
#pragma unroll
  for (int k = 1; k < 4; k++) { sx[k] = __shfl_xor_sync(0xffffffffu, su, k); sx[4 + k] = __shfl_xor_sync(0xffffffffu, sl, k); }
}

struct BandCfg { uint32_t ra0, ra1, meta; int b0, b1; };
__device__ __forceinline__ void band_cfg(int b, uint32_t tb, BandCfg& n) {
  uint32_t ln; asm volatile("mov.u32 %0, %%laneid;" : "=r"(ln));
  const int g = ln >> 2, t = ln & 3;
  const int sw = min(max(g + 1, b == 0 ? 4 : 0), b == 13 ? 5 : 8);
  const int i0 = 2 * t, i1 = 2 * t + 1;
  n.b0 = i0 <= sw - 2; n.b1 = i1 <= sw - 2;
  n.ra0 = tb + (i0 == sw - 1 ? 13 : i0 + 8 * n.b0 - g + 2) * 52;
  n.ra1 = tb + (i1 == sw - 1 ? 13 : i1 + 8 * n.b1 - g + 2) * 52;
  n.meta = ((0x5555u & ((1u << (2 * (sw - 1))) - 1)) ^ 0xDD88u ^ (((t ^ b) & 1) ? 0x5555u : 0u)) * 0x10001u;
}
__device__ __forceinline__ void band_load(const BandCfg& n, float (&T)[16], int& b0, int& b1, uint32_t& meta) {
#pragma unroll
  for (int jj = 0; jj < 8; jj++) { T[2 * jj] = lds_f32(n.ra0 + jj * 4); T[2 * jj + 1] = lds_f32(n.ra1 + jj * 4); }
  b0 = n.b0; b1 = n.b1; meta = n.meta;
}

struct Maps { CUtensorMap xc, xh, w, os, wo, ot; };

__global__ void __cluster_dims__(4, 1, 1) __launch_bounds__(512, 1)
na_attn_kernel(const __nv_bfloat16* __restrict__ x, const __nv_bfloat16* __restrict__ wqkv, const __nv_bfloat16* __restrict__ rpb, const __grid_constant__ Maps mp) {
  extern __shared__ __align__(1024) uint8_t smem_raw[];
  const uint32_t sb = smem_u32(smem_raw);
  if ((sb & 0x3FFFF) != SBC) return;
  const uint32_t bar = sb + SM_BAR;
  TR2(blockIdx.x, 0);
  const int tid = threadIdx.x, lane = tid & 31;
  const int warp = __shfl_sync(0xffffffffu, tid >> 5, 0);
  const int head = blockIdx.x & 3, cl = blockIdx.x >> 2;
  const int par = cl / 7, strip = cl - par * 7, ph = par >> 1, pw = par & 1;

  uint4 wv[2 * NL];
  const int va = head == 1;
  const uint32_t wdst = sb + SM_W + (va + ((tid >> 1) & 1)) * 6144 + (tid >> 2) * 32 + ((tid ^ (tid >> 4)) & 1) * 16;
  if (warp < 12) asm volatile("barrier.cluster.arrive.relaxed.aligned;" ::: "memory");
  {
    const uint32_t wo0 = (tid >> 2) * 1152 + head * 96 + va * 32 + (tid & 3) * 16;
#pragma unroll
    for (int i = 0; i < 2 * NL; i++)
      asm volatile("{\n.reg .pred p;\nsetp.lt.u32 p, %5, 384;\n@p ld.global.nc.v4.b32 {%0,%1,%2,%3}, [%4];\n}"
                   : "=r"(wv[i].x), "=r"(wv[i].y), "=r"(wv[i].z), "=r"(wv[i].w)
                   : "l"(reinterpret_cast<const uint8_t*>(wqkv) + wo0 + (i & 1) * 96 * 1152 + ((i / 2 + 1) % 3) * 384), "r"(tid));
  }
  if (warp < 8) {
    asm volatile("setmaxnreg.inc.sync.aligned.u32 %0;" ::"n"(RA));
    float rv = -INFINITY;
    if (tid < 169) rv = __bfloat162float(rpb[head * 169 + tid]) * 1.4426950408889634f;
    if (tid < 192) {
      const int kc = (tid & 15) + 3, wc = (tid >> 4) % 6;
      sts128(tid < 96 ? sb + SM_K + kc * KS + wc * 128 + 48 : sb + SM_V + kc * 1536 + wc * 128 + (6 + (kc & 1)) * 16, make_uint4(0, 0, 0, 0));
    }
#pragma unroll
    for (int i = 0; i < 2 * NL; i++) sts128(wdst + (i & 1) * 3072 + (i / 2) * 18432, wv[i]);
    fence_async();
    asm volatile("bar.arrive 1, 384;" ::: "memory");
    if (tid < 182) asm volatile("st.shared.f32 [%0], %1;" ::"r"(sb + SM_RPB + tid * 4), "f"(rv) : "memory");
    const int j = warp >> 2, w = warp & 3;
    int variant = w;
    if (strip == 0 && j == 0 && w < 2) variant = 4;
    if (strip == 6 && j == 1 && w >= 2) variant = 5;
    const bool v1 = opq((uint32_t)(variant & 1)), v2 = opq((uint32_t)(variant & 2)), v4 = opq((uint32_t)(variant & 4));
    uint32_t qa = opq(sb + SM_Q + (8 * j + 2 * w + ((lane >> 3) & 1)) * 1536 + (lane >> 4) * 256 + (((lane & 7) * 16) ^ (((lane >> 3) & 1) * 64)));
    uint32_t oa = opq(sb + SM_O + j * 6144 + (2 * w + ((lane >> 3) & 1)) * 768 + (lane >> 4) * 128 + (lane & 7) * 16);
    uint64_t dA = opq(mkdesc(SBC + SM_K, 128, KS, 0) + j * (8 * KS / 16)), dB = opq(dA + (KSLOT >> 4));
    uint64_t dV[7];
#pragma unroll
    for (int i = 0; i < 7; i++) dV[i] = opq(mkdesc(SBC + SM_V, 768, 128, 0) + j * (8 * 1536 / 16) + i * 192);
    const uint32_t nbK = opq((uint32_t)(N_KRDY + j)), nbQ = opq((uint32_t)(N_QK0 + j)), nbV = opq((uint32_t)(N_VQ0 + j));
    asm volatile("barrier.cluster.wait.aligned;" ::: "memory");
    asm volatile("bar.sync 3, 256;" ::: "memory");
    float T[16];
    TRDECL;
    int b0, b1;
    uint32_t meta, ob = bar + B_ODONE * 8;
    const uint32_t tb = opq(sb + SM_RPB + (variant < 4 ? 3 : variant + 1 - 2 * w) * 4);
    const bool own = ((w ^ head) & 2) == 0;
    const uint32_t dst13 = sb + SM_TIN + 2 * 24576 + head * 6144 + (2 * j + (w & 1)) * 1536, src13 = opq(own ? dst13 : sb + SM_Q + warp * 3072 + 1536);
    const uint32_t snd[4] = {opq(own ? 0u : mapa(dst13, head ^ 2)), opq(mapa(bar + (B_TIN + 2) * 8, head ^ 2)),
                             opq(mapa(dst13, (w & 2) + (~head & 1))), opq(mapa(bar + (B_TIN + 3) * 8, (w & 2) + (~head & 1)))};
    BandCfg nx;
    band_cfg(0, tb, nx);
    band_load(nx, T, b0, b1, meta);
    meta ^= 0x55555555u;
    band_cfg(1, tb, nx);
    uint32_t q[12];
    mbar_wait(bar + B_Q0 * 8, 0);
#pragma unroll
    for (int k = 0; k < 3; k++) ldsm4(qa + k * 512, q[4 * k], q[4 * k + 1], q[4 * k + 2], q[4 * k + 3]);
#pragma unroll 1
    for (int b = 0; b < 14; b++) {
      float SA[56], SB[56];
      TR(0, b, 0);
      nb_sync(nbK, 256);
      TR(0, b, 1);
      TR(0, b - 1, 9);
      wg_fence();
      wg_rs112<0>(SA, q[0], q[1], q[2], q[3], dA);
      wg_rs112<0>(SB, q[0], q[1], q[2], q[3], dB);
      wg_rs112<1>(SA, q[4], q[5], q[6], q[7], dA + 16);
      wg_rs112<1>(SB, q[4], q[5], q[6], q[7], dB + 16);
      wg_rs112<1>(SA, q[8], q[9], q[10], q[11], dA + 32);
      wg_rs112<1>(SB, q[8], q[9], q[10], q[11], dB + 32);
      wg_commit();
      nb_arrive(nbQ, 256);
      { const uint64_t t = dA; dA = dB; dB = t; }
      qa ^= 128;
      meta ^= 0x55555555u;
      if (b == 1 || b == 13) band_load(nx, T, b0, b1, meta);
      if (b >= TB) {
        ob = opq(bar + (b == 13 && own ? B_TIN + 2 : B_OTAIL + j) * 8);
        oa += b == 12 ? warp * 1536 - (SM_O - SM_Q) : (b == 13 ? src13 - (sb + SM_Q + warp * 3072) : 0);
      }
      TR(0, b, 2);
      wg_wait<0>(); pin(SA); pin(SB);
      mbar_arrive_elect(bar + B_KFREE * 8);
      TR(0, b, 3);
      TR(0, b - 1, 10);
      uint32_t P[28];
      float sx[8];
      if (v2) {
        if (v1) softmax_tile<6, 7>(SA, SB, T, b0, b1, P, sx); else softmax_tile<4, 5>(SA, SB, T, b0, b1, P, sx);
      } else if (!v4) {
        if (v1) softmax_tile<2, 3>(SA, SB, T, b0, b1, P, sx); else softmax_tile<0, 1>(SA, SB, T, b0, b1, P, sx);
      } else {
        if (v1) softmax_tile<4, 4>(SA, SB, T, b0, b1, P, sx); else softmax_tile<3, 3>(SA, SB, T, b0, b1, P, sx);
      }
      float O[24];
      TR(0, b, 4);
      if (b == 3) band_cfg(13, tb, nx);
      nb_sync(nbV, 288);
      TR(0, b, 5);
#pragma unroll
      for (int k = 0; k < 3; k++) ldsm4(qa + k * 512, q[4 * k], q[4 * k + 1], q[4 * k + 2], q[4 * k + 3]);
      wg_fence();
      wg_sp48<0>(O, P[0], P[1], P[2], P[3], dV[0], meta);
#pragma unroll
      for (int s = 1; s < 7; s++) wg_sp48<1>(O, P[4 * s], P[4 * s + 1], P[4 * s + 2], P[4 * s + 3], dV[s], meta);
      wg_commit();
      nb_arrive(N_PVISS, 384);
      TR(0, b, 6);
      wg_wait<0>(); pin(O);
      mbar_arrive_elect(bar + B_VFREE * 8);
      TR(0, b, 7);
      float ru, rl;
      asm("rcp.approx.ftz.f32 %0, %1;" : "=f"(ru) : "f"(((fmaf(O[0], 0.f, sx[0]) + sx[1]) + sx[2]) + sx[3]));
      asm("rcp.approx.ftz.f32 %0, %1;" : "=f"(rl) : "f"(((fmaf(O[2], 0.f, sx[4]) + sx[5]) + sx[6]) + sx[7]));
#pragma unroll
      for (int i = 0; i < 3; i++)
        stsm4(oa + i * 256, pack2(O[8 * i] * ru, O[8 * i + 1] * ru), pack2(O[8 * i + 2] * rl, O[8 * i + 3] * rl),
              pack2(O[8 * i + 4] * ru, O[8 * i + 5] * ru), pack2(O[8 * i + 6] * rl, O[8 * i + 7] * rl));
      publish(ob);
      TR(0, b, 8);
    }
    asm volatile("{\n.reg .pred p, q;\nsetp.ne.b32 q, %1, 0;\nelect.sync _|p, 0xffffffff;\nand.pred q, q, p;\n"
                 "@q cp.async.bulk.shared::cluster.shared::cta.mbarrier::complete_tx::bytes [%1], [%0], 1536, [%2];\n"
                 "@p cp.async.bulk.shared::cluster.shared::cta.mbarrier::complete_tx::bytes [%3], [%0], 1536, [%4];\n}"
                 ::"r"(src13), "r"(snd[0]), "r"(snd[1]), "r"(snd[2]), "r"(snd[3]) : "memory");
    if (j == 0) nb_arrive(3, 256);
    TRDUMP;
    cluster_sync();
  } else if (warp < 12) {
    TRDECL;
    TR(2, -3, 0);
    asm volatile("setmaxnreg.inc.sync.aligned.u32 %0;" ::"n"(RG));
    TR(2, -3, 1);
    GemmCtx c;
    c.bar = bar;
    const int gw = warp - 8, tk = gw * 16 + (lane & 15), hi = lane >> 4;
    { const int col = tk >> 2, i = tk & 3;
      c.kC = sb + SM_K + (col + 3) * KS + hi * 128 + i * 16;
      c.vC[0] = sb + SM_V + (col + 3) * 1536 + hi * 128 + (2 * i + ((col + 3) & 1)) * 16;
      c.qC[0] = sb + SM_Q + col * 1536 + hi * 256 + (col & 1) * 64 + i * 16; }
    { const int ci = (tk >> 3) - 2, kc = ci < 3 ? ci : ci + 16, i = tk & 7; c.hvalid = gw > 0;
      c.kH = sb + SM_K + kc * KS + hi * 128 + i * 16;
      c.vH[0] = sb + SM_V + kc * 1536 + hi * 128 + (i >> 2) * 768 + (2 * (i & 3) + ((kc ^ (i >> 2)) & 1)) * 16; }
    c.never = x == nullptr;
    c.kC = opq(c.kC); c.kH = opq(c.kH);
    c.vC[1] = opq(c.vC[0] ^ 16); c.vC[0] = opq(c.vC[0]);
    c.vH[1] = opq(c.vH[0] ^ 16); c.vH[0] = opq(c.vH[0]);
    c.qC[1] = opq(c.qC[0] ^ 64); c.qC[0] = opq(c.qC[0]);
    c.spin = 0;
    c.hiA = (uint32_t)(mkdesc(0, 0, 1024, 1) >> 32) + (blockIdx.x >> 16); c.hiB = (uint32_t)(mkdesc(0, 0, 256, 3) >> 32) + (blockIdx.x >> 16);
    asm volatile("barrier.cluster.wait.aligned;" ::: "memory");
    TR(2, -3, 2);
#pragma unroll
    for (int i = 0; i < 2 * NL; i++) sts128(wdst + (i & 1) * 3072 + (i / 2) * 18432, wv[i]);
    fence_async();
    TR(2, -3, 3);
    asm volatile("bar.sync 1, 384;" ::: "memory");
    TR(2, -3, 4);
    mbar_wait(bar + B_WK * 8, 0);
    TR(2, -3, 5);
    uint32_t pk[12], pv[12], pq[12];
    gemm_iter<true, 0>(c, -2, pk, pv, pq TRPASS);
    TR2(blockIdx.x, 4);
    c.hiA = opq(c.hiA); c.hiB = opq(c.hiB);
#pragma unroll 1
    for (int b = -1;; b += 2) {
      gemm_iter<false, 1>(c, b, pk, pv, pq TRPASS);
      if (b == 11) break;
      gemm_iter<false, 0>(c, b + 1, pk, pv, pq TRPASS);
    }
    TR2(blockIdx.x, 6);
    const uint32_t st = sb + gw * 3072;
    const uint32_t sta = st + (lane & 15) * 64 + ((hi ^ ((lane >> 1) & 3)) * 16);
    const int oc = ph * 112 + strip * 16 + 8 * (gw >> 1) + 4 * (head >> 1) + 2 * (gw & 1), och = pw * 6 + (head & 1) * 3;
    float D0[48], D1[48];
    mbar_arrive_elect(bar + B_WOFREE * 8);
    dump12<256>(c.qC[1] + 128, pq);
    nb_sync(N_QK1, 256);
    issue_halo<0, 12>(c, D1);
    gwait<0>(c, B_KFREE);
    dump12<128>(c.kC, pk);
    fence_async();
    nb_arrive(N_VQ0, 288); nb_arrive(N_VQ1, 288); nb_arrive(N_PVISS, 384);
    wg_wait<0>(); pin(D1);
    pack12(pk, D1, 0);
    if (c.hvalid) dump12<128>(c.kH, pk);
    tail_free(bar + (B_TFREE + 1) * 8);
    pack12(pq, D1, 24);
    fence_async();
    nb_arrive(N_KRDY, 256);
    gwait<0>(c, B_VFREE);
    dump12<128>(c.vC[0], pv);
    if (c.hvalid) dump12<128>(c.vH[0], pq);
    fence_async();
    nb_arrive(N_VQ0, 288); nb_arrive(N_VQ1, 288);
    gwait<0>(c, B_WO);
    gwait<0>(c, B_TIN);
    TR(2, 13, 0);
    nb_sync(N_QK1, 256);
    issue_proj<SM_TIN>(D0);
    wg_wait<0>(); pin(D0);
    TR(2, 13, 1);
    store_proj(D0, &mp.ot, st + SM_TST, sta + SM_TST, 8 * TB, oc, och);
    gwait<0>(c, B_TIN + 1);
    TR(2, 13, 2);
    nb_sync(N_PVISS, 384);
    nb_sync(3, 256);
    issue_proj<SM_TIN + 24576>(D1);
    wg_wait<0>(); pin(D1);
    TR(2, 13, 3);
    store_proj(D1, &mp.ot, st + SM_TIN, sta + SM_TIN, 8 * TB + 8, oc, och);
    TR(2, 13, 4);
    gwait<0>(c, B_TIN + 2);
    TR(2, 13, 5);
    issue_proj_half<0>(D0, head & 1);
    gwait<0>(c, B_TIN + 3);
    TR(2, 13, 6);
    issue_proj_half<1>(D0, ~head & 1);
    asm volatile("barrier.cluster.arrive.relaxed.aligned;" ::: "memory");
    wg_wait<0>(); pin(D0);
    store_proj(D0, &mp.ot, st + SM_TIN + 12288, sta + SM_TIN + 12288, 8 * TB + 16, oc, och);
    TR(2, 13, 7);
    if (lane == 0) asm volatile("cp.async.bulk.wait_group.read 0;" ::: "memory");
    __syncwarp();
    TR(2, 13, 8);
    TR2(blockIdx.x, 2);
    TRDUMP;
    asm volatile("barrier.cluster.wait.aligned;" ::: "memory");
  } else {
    if (warp == 12) {
      if (elect_one()) {
        mbar_init(bar + B_WK * 8, 1);
#pragma unroll
        for (int i = 0; i < NL; i++) load_w(&mp.w, sb + SM_W + (3 * i + 2 - 2 * va) * 6144, bar + B_WK * 8, ((i + 1) % 3) * 192 + head * 48 + 32 - 32 * va);
        asm volatile("prefetch.tensormap [%0];" ::"l"(head ? &mp.xc : &mp.xh) : "memory");
        mbar_expect(bar + B_WK * 8, NL * 6144);
      }
    } else if (warp == 15) {
      const int col = min(max(strip * 16 - 3 + min(lane, 21), 0), 111);
      const uint8_t* p = reinterpret_cast<const uint8_t*>(x) + (uint32_t)(head * ROWB + (ph * 112 + col) * 768 + pw * 384);
#pragma unroll
      for (int i = 0; i < 3; i++) asm volatile("prefetch.global.L2 [%0];" ::"l"(p + i * 128));
    } else if (elect_one()) {
      if (warp == 13) {
#pragma unroll
        for (int i = 0; i < B_WK; i++) mbar_init(bar + i * 8, i < B_EMPTY ? 1 : (i < B_TIN ? 16 : (i < B_TFREE ? (i == B_TIN + 2 ? 5 : 1) : 16)));
      } else {
#pragma unroll
        for (int i = B_WQ; i < B_COUNT; i++) mbar_init(bar + i * 8, i < B_Q0 ? 1 : (i < B_ODONE ? 4 : 8));
      }
    }
    asm volatile("fence.mbarrier_init.release.cluster;" ::: "memory");
    __syncwarp();
    asm volatile("barrier.cluster.arrive.relaxed.aligned;" ::: "memory");
    asm volatile("setmaxnreg.dec.sync.aligned.u32 24;");
    asm volatile("griddepcontrol.launch_dependents;");
    const int cc = ph * 112 + (head ? strip * 16 : (strip == 0 ? 16 : (strip == 6 ? 74 : strip * 16 - 3)));
    const int sd = strip == 0 ? -1 : (strip == 6 ? 1 : 0);
    const int r0 = head == 0 ? -4 : (head == 1 ? 4 : 0);
    asm volatile("barrier.cluster.wait.aligned;" ::: "memory");
    if (warp == 12) {
      const uint32_t fb = bar + (B_FULL + head) * 8, eb = bar + (B_EMPTY + head) * 8;
      const uint32_t dst = sb + (head == 0 ? SM_X0 : (head == 1 ? SM_X1 : SM_X2));
      const int nl = head == 0 ? 15 : (head == 3 ? 1 : 14);
#pragma unroll 1
      for (int n = 0; n < nl; n++) {
        if (n) mbar_wait(eb, (n - 1) & 1);
        if (lane < 4 && head < 3)
          asm volatile("{\n.reg .b32 ra;\nmapa.shared::cluster.u32 ra, %0, %1;\nmbarrier.arrive.expect_tx.shared::cluster.b64 _, [ra], %2;\n}"
                       ::"r"(fb), "r"(lane), "r"(head ? 24576 : 18432) : "memory");
        __syncwarp();
        if (elect_one()) {
          if (head == 0) {
            asm volatile("cp.async.bulk.tensor.5d.shared::cluster.global.mbarrier::complete_tx::bytes.multicast::cluster [%0], [%1, {%3,%4,%5,%6,%7}], [%2], %8;"
                         ::"r"(dst), "l"(&mp.xh), "r"(fb), "r"(0), "r"(8 * n + r0), "r"(cc), "r"(sd), "r"(pw * 3), "h"((uint16_t)15) : "memory");
          } else if (head < 3) {
            asm volatile("cp.async.bulk.tensor.4d.shared::cluster.global.mbarrier::complete_tx::bytes.multicast::cluster [%0], [%1, {%3,%4,%5,%6}], [%2], %7;"
                         ::"r"(dst), "l"(&mp.xc), "r"(fb), "r"(0), "r"(8 * n + r0), "r"(cc), "r"(pw * 3), "h"((uint16_t)15) : "memory");
          }
          if (n == 0) {
#pragma unroll
            for (int i = 0; i < 3; i++) load_w(&mp.w, sb + SM_W + (6 + i) * 6144, bar + B_WQ * 8, head * 48 + i * 16);
            mbar_expect(bar + B_WQ * 8, 18432);
            mbar_expect(bar + B_TIN * 8, 24576); mbar_expect(bar + (B_TIN + 1) * 8, 24576); mbar_expect(bar + (B_TIN + 2) * 8, 6144); mbar_expect(bar + (B_TIN + 3) * 8, 12288);
          }
          if (!head && n + 1 < nl) asm volatile("cp.async.bulk.prefetch.tensor.5d.L2.global [%0, {%1,%2,%3,%4,%5}];" ::"l"(&mp.xh), "r"(0), "r"(8 * n + 8 + r0), "r"(cc), "r"(sd), "r"(pw * 3) : "memory");
          if (head && n + 1 < nl) asm volatile("cp.async.bulk.prefetch.tensor.4d.L2.global [%0, {%1,%2,%3,%4}];" ::"l"(&mp.xc), "r"(0), "r"(8 * n + 8 + r0), "r"(cc), "r"(pw * 3) : "memory");
        }
        __syncwarp();
      }
      mbar_wait(bar + B_WOFREE * 8, 0);
      if (elect_one()) {
        mbar_expect(bar + B_WO * 8, 36864);
        asm volatile("cp.async.bulk.tensor.3d.shared::cluster.global.mbarrier::complete_tx::bytes [%0], [%1, {%3,%4,%5}], [%2];"
                     ::"r"(sb + SM_TWO), "l"(&mp.wo), "r"(bar + B_WO * 8), "r"(0), "r"(0), "r"((head & 1) * 3) : "memory");
      }
      __syncwarp();
    }
    if (warp == 14) {
      int* flag = g_flags + cl * 2;
      nb_arrive(N_VQ0, 288); nb_arrive(N_VQ1, 288);
#pragma unroll 1
      for (int b = 0; b < TB; b++) {
        mbar_wait(bar + B_ODONE * 8, b & 1);
        if (lane == 0) {
          asm volatile("cp.async.bulk.tensor.3d.global.shared::cta.bulk_group [%0, {%2,%3,%4}], [%1];"
                       ::"l"(&mp.os), "r"(sb + SM_O), "r"(pw * 192), "r"(8 * b + 2 * head), "r"(ph * 112 + strip * 16) : "memory");
          asm volatile("cp.async.bulk.commit_group;\ncp.async.bulk.wait_group 0;" ::: "memory");
        }
        __syncwarp();
        nb_arrive(N_VQ0, 288); nb_arrive(N_VQ1, 288);
        if (lane == 0)
          asm volatile("fence.proxy.async.global;\nfence.acq_rel.gpu;\nred.relaxed.gpu.global.add.s32 [%0], 1;\nred.relaxed.gpu.global.add.s32 [%0+4], 1;"
                       ::"l"(flag + b * 56) : "memory");
        __syncwarp();
      }
    } else if (warp & 1) {
      const int j = (warp >> 1) & 1;
#pragma unroll 1
      for (int i = 0; i < 2; i++) {
        mbar_wait(bar + (B_OTAIL + j) * 8, i);
        if (i == 0) nb_arrive(N_VQ0 + j, 288);
        mbar_wait(bar + (B_TFREE + i) * 8, 0);
        if (i == 1) nb_arrive(N_VQ0 + j, 288);
        if (elect_one()) {
#pragma unroll 1
          for (int d = 0; d < 8; d++) {
            const int dst = (d + head) & 3, pc = d >> 2;
            send_o<1536>(sb + SM_TIN + i * 24576 + head * 6144 + j * 3072 + pc * 1536,
                         sb + (i ? SM_Q : SM_O) + (4 * j + (dst & 2) + pc) * (i ? 3072 : 1536), bar + (B_TIN + i) * 8, dst);
          }
        }
        __syncwarp();
      }
    }
    cluster_sync();
  }
}

constexpr int NSTB = 6;
constexpr int NTB = TB * 56;
constexpr int SM_B_IN = 0;
constexpr int SM_B_W = SM_B_IN + NSTB * 24576;
constexpr int SM_B_BAR = SM_B_W + 73728;
constexpr int SM_B_TOTAL = SM_B_BAR + 128;
struct MapsB { CUtensorMap oi, oo, wo; };

__global__ void __launch_bounds__(480, 1)
na_proj_kernel(const __grid_constant__ MapsB mp) {
  extern __shared__ __align__(1024) uint8_t smem_raw[];
  const uint32_t sb = smem_u32(smem_raw);
  if ((sb & 0x3FFFF) != SBC) return;
  const uint32_t bar = sb + SM_B_BAR;
  const int tid = threadIdx.x, lane = tid & 31;
  const int warp = __shfl_sync(0xffffffffu, tid >> 5, 0);
  TR2(132 + blockIdx.x, 0);
  TRB(47, 0);
  if (warp == 12 && elect_one()) {
#pragma unroll
    for (int i = 0; i <= 2 * NSTB; i++) mbar_init(bar + i * 8, i < NSTB || i == 2 * NSTB ? 1 : 4);
    mbar_expect(bar + 2 * NSTB * 8, 73728);
#pragma unroll
    for (int i = 0; i < 2; i++)
      asm volatile("cp.async.bulk.tensor.3d.shared::cluster.global.mbarrier::complete_tx::bytes [%0], [%1, {%3,%4,%5}], [%2];"
                   ::"r"(sb + SM_B_W + i * 36864), "l"(&mp.wo), "r"(bar + 2 * NSTB * 8), "r"(0), "r"(0), "r"(i * 3) : "memory");
  }
  __syncthreads();
  const int step = gridDim.x;
  if (warp >= 12) {
    const int wg = warp - 12;
    int use = 0;
#pragma unroll 1
    for (int n = blockIdx.x + wg * step; n < NTB; n += 3 * step, use++) {
      const int b = n / 56, rem = n - b * 56, par = rem / 14, sg = wg + 3 * (use & 1);
      int v; uint32_t spin = 0;
      do { asm volatile("ld.acquire.gpu.global.s32 %0, [%1];" : "=r"(v) : "l"(g_flags + n) : "memory"); if ((OPT & 1) && v < 4) __nanosleep(200); } while (v < 4 && ++spin < SPIN_LIMIT);
      TRB(use * 3 + wg, 0);
      asm volatile("fence.proxy.async.global;" ::: "memory");
      if (use >= 2) mbar_wait(bar + (NSTB + sg) * 8, ((use >> 1) - 1) & 1);
      TRB(use * 3 + wg, 1);
      if (elect_one()) {
        mbar_expect(bar + sg * 8, 24576);
        asm volatile("cp.async.bulk.tensor.3d.shared::cluster.global.mbarrier::complete_tx::bytes [%0], [%1, {%3,%4,%5}], [%2];"
                     ::"r"(sb + SM_B_IN + sg * 24576), "l"(&mp.oi), "r"(bar + sg * 8), "r"((par & 1) * 192), "r"(8 * b), "r"((par >> 1) * 112 + (rem - par * 14) * 8) : "memory");
        g_flags[n] = 0;
      }
      __syncwarp();
    }
  } else {
    const int wg = warp >> 2, w = warp & 3;
    constexpr uint64_t db = mkdesc(SBC + SM_B_W, 12288, 512, 2);
    const uint32_t sta0 = sb + SM_B_IN + w * 6144 + (lane & 15) * 128 + (((lane >> 4) ^ (lane & 7)) * 16);
    mbar_wait(bar + 2 * NSTB * 8, 0);
    TRB(47, 1);
    int use = 0;
#pragma unroll 1
    for (int n = blockIdx.x + wg * step; n < NTB; n += 3 * step, use++) {
      const int b = n / 56, rem = n - b * 56, par = rem / 14, sg = wg + 3 * (use & 1);
      const uint64_t da = mkdesc(SBC + SM_B_IN, 128, 3072, 0) + sg * (24576 / 16);
      float D[96];
      mbar_wait(bar + sg * 8, (use >> 1) & 1);
      if (use | wg) nb_sync(4 + wg, 256);
      TRB(use * 3 + wg, 3);
      wg_fence();
      wg_ss192<0>(D, da, db);
#pragma unroll
      for (int k = 1; k < 12; k++) wg_ss192<1>(D, da + k * 16, db + k * 64);
      wg_commit();
      if (n + step < NTB) nb_arrive(wg == 2 ? 4 : 5 + wg, 256);
      TRB(use * 3 + wg, 4);
      if (use && lane == 0) {
        asm volatile("cp.async.bulk.wait_group.read 0;" ::: "memory");
        mbar_arrive(bar + (NSTB + wg + 3 * (~use & 1)) * 8);
      }
      __syncwarp();
      wg_wait<0>(); pin(D);
      nb_sync(1 + wg, 128);
      TRB(use * 3 + wg, 5);
      const uint32_t sta = sta0 + sg * 24576;
#pragma unroll
      for (int q = 0; q < 12; q++)
        stsm4((sta ^ ((q & 3) * 32)) + (q >> 2) * 2048,
              pack2(D[8 * q], D[8 * q + 1]), pack2(D[8 * q + 2], D[8 * q + 3]), pack2(D[8 * q + 4], D[8 * q + 5]), pack2(D[8 * q + 6], D[8 * q + 7]));
      fence_async();
      __syncwarp();
      if (lane == 0) {
        asm volatile("cp.async.bulk.tensor.4d.global.shared::cta.bulk_group [%0, {%2,%3,%4,%5}], [%1];"
                     ::"l"(&mp.oo), "r"(sb + SM_B_IN + sg * 24576 + w * 6144), "r"(0), "r"(8 * b), "r"((par >> 1) * 112 + (rem - par * 14) * 8 + 2 * w), "r"((par & 1) * 3) : "memory");
        asm volatile("cp.async.bulk.commit_group;" ::: "memory");
      }
      __syncwarp();
      TRB(use * 3 + wg, 6);
    }
    if (lane == 0) asm volatile("cp.async.bulk.wait_group 0;" ::: "memory");
    TR2(132 + blockIdx.x, 2);
  }
}

typedef CUresult (*EncodeFn)(CUtensorMap*, CUtensorMapDataType, cuuint32_t, void*, const cuuint64_t*, const cuuint64_t*, const cuuint32_t*,
                             const cuuint32_t*, CUtensorMapInterleave, CUtensorMapSwizzle, CUtensorMapL2promotion, CUtensorMapFloatOOBfill);
static EncodeFn g_enc = nullptr;
static void make_map(CUtensorMap* m, const void* p, int rank, const cuuint64_t* dim, const cuuint64_t* str, const cuuint32_t* box, CUtensorMapSwizzle sw) {
  const cuuint32_t ones[5] = {1, 1, 1, 1, 1};
  g_enc(m, CU_TENSOR_MAP_DATA_TYPE_BFLOAT16, rank, (void*)p, dim, str, box, ones, CU_TENSOR_MAP_INTERLEAVE_NONE, sw,
        CU_TENSOR_MAP_L2_PROMOTION_L2_128B, CU_TENSOR_MAP_FLOAT_OOB_FILL_NONE);
}

extern "C" void kernel_launch(void* const* d_in, const int* in_sizes, int n_in, void* d_out, int out_size) {
  const __nv_bfloat16* x = (const __nv_bfloat16*)d_in[0];
  const __nv_bfloat16* wqkv = (const __nv_bfloat16*)d_in[1];
  const __nv_bfloat16* wo = (const __nv_bfloat16*)d_in[2];
  const __nv_bfloat16* rpb = (const __nv_bfloat16*)d_in[3];

  if (!g_enc) {
    void* fn = nullptr; cudaDriverEntryPointQueryResult qr;
    cudaGetDriverEntryPoint("cuTensorMapEncodeTiled", &fn, cudaEnableDefault, &qr);
    g_enc = (EncodeFn)fn;
    cudaFuncSetAttribute(na_attn_kernel, cudaFuncAttributeMaxDynamicSharedMemorySize, SM_A_TOTAL);
    cudaFuncSetAttribute(na_proj_kernel, cudaFuncAttributeMaxDynamicSharedMemorySize, SM_B_TOTAL);
  }
  Maps ma; MapsB mb;
  { cuuint64_t dim[4] = {64, 112, 224, 6}, str[3] = {(cuuint64_t)ROWB, 768, 128};
    cuuint32_t box[4] = {64, 4, 16, 3}, boxo[4] = {64, 8, 2, 3};
    make_map(&ma.xc, x, 4, dim, str, box, CU_TENSOR_MAP_SWIZZLE_128B);
    make_map(&mb.oo, d_out, 4, dim, str, boxo, CU_TENSOR_MAP_SWIZZLE_128B); }
  { cuuint64_t dim[5] = {64, 112, 224, 2, 6}, str[4] = {(cuuint64_t)ROWB, 768, 19 * 768, 128};
    cuuint32_t box[5] = {64, 8, 3, 2, 3};
    make_map(&ma.xh, x, 5, dim, str, box, CU_TENSOR_MAP_SWIZZLE_128B); }
  { cuuint64_t dim[3] = {384, 112, 224}, str[2] = {(cuuint64_t)ROWB, 768};
    cuuint32_t box[3] = {192, 8, 8}, boxs[3] = {192, 2, 16};
    make_map(&mb.oi, d_out, 3, dim, str, box, CU_TENSOR_MAP_SWIZZLE_NONE);
    make_map(&ma.os, d_out, 3, dim, str, boxs, CU_TENSOR_MAP_SWIZZLE_NONE); }
  { cuuint64_t dim[4] = {32, 112, 224, 12}, str[3] = {(cuuint64_t)ROWB, 768, 64};
    cuuint32_t box[4] = {32, 8, 2, 3};
    make_map(&ma.ot, d_out, 4, dim, str, box, CU_TENSOR_MAP_SWIZZLE_64B); }
  { cuuint64_t dim[2] = {576, 192}, str[1] = {1152};
    cuuint32_t box[2] = {16, 192};
    make_map(&ma.w, wqkv, 2, dim, str, box, CU_TENSOR_MAP_SWIZZLE_32B); }
  { cuuint64_t dim[3] = {32, 192, 6}, str[2] = {384, 64};
    cuuint32_t box[3] = {32, 192, 3};
    make_map(&ma.wo, wo, 3, dim, str, box, CU_TENSOR_MAP_SWIZZLE_64B);
    mb.wo = ma.wo; }
  na_attn_kernel<<<112, 512, SM_A_TOTAL>>>(x, wqkv, rpb, ma);
  cudaLaunchConfig_t cfg = {};
  cfg.gridDim = dim3(20); cfg.blockDim = dim3(480); cfg.dynamicSmemBytes = SM_B_TOTAL; cfg.stream = cudaStreamPerThread;
  cudaLaunchAttribute at[1];
  at[0].id = cudaLaunchAttributeProgrammaticStreamSerialization; at[0].val.programmaticStreamSerializationAllowed = 1;
  cfg.attrs = at; cfg.numAttrs = 1;
  cudaLaunchKernelEx(&cfg, na_proj_kernel, mb);
}
```

```cpp
#include <cuda_runtime.h>
#include <cuda_bf16.h>
#include <cuda.h>
#include <stdint.h>

#define SPIN_LIMIT (1u << 18)

__device__ __forceinline__ uint32_t smem_u32(const void* p) { return (uint32_t)__cvta_generic_to_shared(p); }
__device__ __forceinline__ void wg_fence() { asm volatile("wgmma.fence.sync.aligned;" ::: "memory"); }
__device__ __forceinline__ void wg_commit() { asm volatile("wgmma.commit_group.sync.aligned;" ::: "memory"); }
template <int N> __device__ __forceinline__ void wg_wait() { asm volatile("wgmma.wait_group.sync.aligned %0;" ::"n"(N) : "memory"); }
template <int N> __device__ __forceinline__ void pin(float (&d)[N]) {
#pragma unroll
  for (int i = 0; i < N; i++) asm volatile("" : "+f"(d[i])::"memory");
}
__host__ __device__ constexpr uint64_t mkdesc(uint32_t addr, uint32_t lbo, uint32_t sbo, uint32_t sw) {
  return (uint64_t)((addr & 0x3FFFF) >> 4) | ((uint64_t)(lbo >> 4) << 16) | ((uint64_t)(sbo >> 4) << 32) | ((uint64_t)sw << 62);
}
__device__ __forceinline__ void mbar_init(uint32_t bar, uint32_t cnt) { asm volatile("mbarrier.init.shared::cta.b64 [%0], %1;" ::"r"(bar), "r"(cnt) : "memory"); }
__device__ __forceinline__ void mbar_arrive(uint32_t bar) { asm volatile("mbarrier.arrive.shared::cta.b64 _, [%0];" ::"r"(bar) : "memory"); }
__device__ __forceinline__ bool elect_one() {
  uint32_t r; asm volatile("{\n.reg .pred p;\nelect.sync _|p, 0xffffffff;\nselp.u32 %0, 1, 0, p;\n}" : "=r"(r)); return r;
}
__device__ __forceinline__ void mbar_arrive_elect(uint32_t bar) {
  asm volatile("{\n.reg .pred p;\nelect.sync _|p, 0xffffffff;\n@p mbarrier.arrive.shared::cta.b64 _, [%0];\n}" ::"r"(bar) : "memory");
}
__device__ __forceinline__ void mbar_expect(uint32_t bar, uint32_t bytes) { asm volatile("mbarrier.arrive.expect_tx.shared::cta.b64 _, [%0], %1;" ::"r"(bar), "r"(bytes) : "memory"); }
__device__ __forceinline__ void mbar_arrive_remote(uint32_t bar, uint32_t cta) {
  asm volatile("{\n.reg .b32 ra;\nmapa.shared::cluster.u32 ra, %0, %1;\nmbarrier.arrive.relaxed.cluster.shared::cluster.b64 _, [ra];\n}" ::"r"(bar), "r"(cta) : "memory");
}
__device__ __forceinline__ void mbar_wait(uint32_t bar, uint32_t parity) {
  asm volatile("{\n.reg .pred p;\n.reg .b32 n;\nmov.b32 n, 0;\nWL:\nmbarrier.try_wait.parity.shared::cta.b64 p, [%0], %1;\n@p bra WD;\n"
               "add.u32 n, n, 1;\nsetp.lt.u32 p, n, 65536;\n@p bra WL;\nWD:\n}" ::"r"(bar), "r"(parity) : "memory");
}
__device__ __forceinline__ void nb_sync(int id, int n) { asm volatile("bar.sync %0, %1;" ::"r"(id), "r"(n) : "memory"); }
__device__ __forceinline__ void nb_arrive(int id, int n) { asm volatile("bar.arrive %0, %1;" ::"r"(id), "r"(n) : "memory"); }
__device__ __forceinline__ uint32_t opq(uint32_t x) { uint32_t r; asm volatile("mov.b32 %0, %1;" : "=r"(r) : "r"(x)); return r; }
__device__ __forceinline__ uint64_t opq(uint64_t x) { uint64_t r; asm volatile("mov.b64 %0, %1;" : "=l"(r) : "l"(x)); return r; }
__device__ __forceinline__ uint32_t mapa(uint32_t a, uint32_t cta) { uint32_t r; asm("mapa.shared::cluster.u32 %0, %1, %2;" : "=r"(r) : "r"(a), "r"(cta)); return r; }
__device__ __forceinline__ void fence_async() { asm volatile("fence.proxy.async.shared::cta;" ::: "memory"); }
__device__ __forceinline__ void cluster_sync() {
  asm volatile("barrier.cluster.arrive.relaxed.aligned;\nbarrier.cluster.wait.aligned;" ::: "memory");
}
__device__ __forceinline__ uint32_t pack2(float lo, float hi) {
  uint32_t r; asm("cvt.rn.bf16x2.f32 %0, %1, %2;" : "=r"(r) : "f"(hi), "f"(lo)); return r;
}
__device__ __forceinline__ void stsm4(uint32_t a, uint32_t r0, uint32_t r1, uint32_t r2, uint32_t r3) {
  asm volatile("stmatrix.sync.aligned.m8n8.x4.shared.b16 [%0], {%1,%2,%3,%4};" ::"r"(a), "r"(r0), "r"(r1), "r"(r2), "r"(r3) : "memory");
}
__device__ __forceinline__ void ldsm4(uint32_t a, uint32_t& r0, uint32_t& r1, uint32_t& r2, uint32_t& r3) {
  asm volatile("ldmatrix.sync.aligned.m8n8.x4.shared.b16 {%0,%1,%2,%3}, [%4];" : "=r"(r0), "=r"(r1), "=r"(r2), "=r"(r3) : "r"(a) : "memory");
}
__device__ __forceinline__ void sts128(uint32_t a, uint4 v) {
  asm volatile("st.shared.v4.b32 [%0], {%1,%2,%3,%4};" ::"r"(a), "r"(v.x), "r"(v.y), "r"(v.z), "r"(v.w) : "memory");
}
__device__ __forceinline__ float lds_f32(uint32_t a) { float v; asm volatile("ld.shared.f32 %0, [%1];" : "=f"(v) : "r"(a)); return v; }
__device__ __forceinline__ float ex2(float x) { float y; asm("ex2.approx.ftz.f32 %0, %1;" : "=f"(y) : "f"(x)); return y; }

template<int SC> __device__ __forceinline__ void wg_ss144(float (&d)[72], uint64_t da, uint64_t db) {
  asm volatile("{\n.reg .pred p;\nsetp.ne.b32 p, %74, 0;\nwgmma.mma_async.sync.aligned.m64n144k16.f32.bf16.bf16 {%0,%1,%2,%3,%4,%5,%6,%7,%8,%9,%10,%11,%12,%13,%14,%15,%16,%17,%18,%19,%20,%21,%22,%23,%24,%25,%26,%27,%28,%29,%30,%31,%32,%33,%34,%35,%36,%37,%38,%39,%40,%41,%42,%43,%44,%45,%46,%47,%48,%49,%50,%51,%52,%53,%54,%55,%56,%57,%58,%59,%60,%61,%62,%63,%64,%65,%66,%67,%68,%69,%70,%71}, %72, %73, p, 1, 1, 0, 1;\n}\n"
    : "+f"(d[0]),"+f"(d[1]),"+f"(d[2]),"+f"(d[3]),"+f"(d[4]),"+f"(d[5]),"+f"(d[6]),"+f"(d[7]),"+f"(d[8]),"+f"(d[9]),"+f"(d[10]),"+f"(d[11]),"+f"(d[12]),"+f"(d[13]),"+f"(d[14]),"+f"(d[15]),"+f"(d[16]),"+f"(d[17]),"+f"(d[18]),"+f"(d[19]),"+f"(d[20]),"+f"(d[21]),"+f"(d[22]),"+f"(d[23]),"+f"(d[24]),"+f"(d[25]),"+f"(d[26]),"+f"(d[27]),"+f"(d[28]),"+f"(d[29]),"+f"(d[30]),"+f"(d[31]),"+f"(d[32]),"+f"(d[33]),"+f"(d[34]),"+f"(d[35]),"+f"(d[36]),"+f"(d[37]),"+f"(d[38]),"+f"(d[39]),"+f"(d[40]),"+f"(d[41]),"+f"(d[42]),"+f"(d[43]),"+f"(d[44]),"+f"(d[45]),"+f"(d[46]),"+f"(d[47]),"+f"(d[48]),"+f"(d[49]),"+f"(d[50]),"+f"(d[51]),"+f"(d[52]),"+f"(d[53]),"+f"(d[54]),"+f"(d[55]),"+f"(d[56]),"+f"(d[57]),"+f"(d[58]),"+f"(d[59]),"+f"(d[60]),"+f"(d[61]),"+f"(d[62]),"+f"(d[63]),"+f"(d[64]),"+f"(d[65]),"+f"(d[66]),"+f"(d[67]),"+f"(d[68]),"+f"(d[69]),"+f"(d[70]),"+f"(d[71]) : "l"(da), "l"(db), "n"(SC));
}
template<int SC> __device__ __forceinline__ void wg_ss96(float (&d)[48], uint64_t da, uint64_t db) {
  asm volatile("{\n.reg .pred p;\nsetp.ne.b32 p, %50, 0;\nwgmma.mma_async.sync.aligned.m64n96k16.f32.bf16.bf16 {%0,%1,%2,%3,%4,%5,%6,%7,%8,%9,%10,%11,%12,%13,%14,%15,%16,%17,%18,%19,%20,%21,%22,%23,%24,%25,%26,%27,%28,%29,%30,%31,%32,%33,%34,%35,%36,%37,%38,%39,%40,%41,%42,%43,%44,%45,%46,%47}, %48, %49, p, 1, 1, 0, 1;\n}\n"
    : "+f"(d[0]),"+f"(d[1]),"+f"(d[2]),"+f"(d[3]),"+f"(d[4]),"+f"(d[5]),"+f"(d[6]),"+f"(d[7]),"+f"(d[8]),"+f"(d[9]),"+f"(d[10]),"+f"(d[11]),"+f"(d[12]),"+f"(d[13]),"+f"(d[14]),"+f"(d[15]),"+f"(d[16]),"+f"(d[17]),"+f"(d[18]),"+f"(d[19]),"+f"(d[20]),"+f"(d[21]),"+f"(d[22]),"+f"(d[23]),"+f"(d[24]),"+f"(d[25]),"+f"(d[26]),"+f"(d[27]),"+f"(d[28]),"+f"(d[29]),"+f"(d[30]),"+f"(d[31]),"+f"(d[32]),"+f"(d[33]),"+f"(d[34]),"+f"(d[35]),"+f"(d[36]),"+f"(d[37]),"+f"(d[38]),"+f"(d[39]),"+f"(d[40]),"+f"(d[41]),"+f"(d[42]),"+f"(d[43]),"+f"(d[44]),"+f"(d[45]),"+f"(d[46]),"+f"(d[47]) : "l"(da), "l"(db), "n"(SC));
}
template<int SC> __device__ __forceinline__ void wg_rs112(float (&d)[56], uint32_t a0, uint32_t a1, uint32_t a2, uint32_t a3, uint64_t db) {
  asm volatile("{\n.reg .pred p;\nsetp.ne.b32 p, %61, 0;\nwgmma.mma_async.sync.aligned.m64n112k16.f32.bf16.bf16 {%0,%1,%2,%3,%4,%5,%6,%7,%8,%9,%10,%11,%12,%13,%14,%15,%16,%17,%18,%19,%20,%21,%22,%23,%24,%25,%26,%27,%28,%29,%30,%31,%32,%33,%34,%35,%36,%37,%38,%39,%40,%41,%42,%43,%44,%45,%46,%47,%48,%49,%50,%51,%52,%53,%54,%55}, {%56,%57,%58,%59}, %60, p, 1, 1, 0;\n}\n"
    : "+f"(d[0]),"+f"(d[1]),"+f"(d[2]),"+f"(d[3]),"+f"(d[4]),"+f"(d[5]),"+f"(d[6]),"+f"(d[7]),"+f"(d[8]),"+f"(d[9]),"+f"(d[10]),"+f"(d[11]),"+f"(d[12]),"+f"(d[13]),"+f"(d[14]),"+f"(d[15]),"+f"(d[16]),"+f"(d[17]),"+f"(d[18]),"+f"(d[19]),"+f"(d[20]),"+f"(d[21]),"+f"(d[22]),"+f"(d[23]),"+f"(d[24]),"+f"(d[25]),"+f"(d[26]),"+f"(d[27]),"+f"(d[28]),"+f"(d[29]),"+f"(d[30]),"+f"(d[31]),"+f"(d[32]),"+f"(d[33]),"+f"(d[34]),"+f"(d[35]),"+f"(d[36]),"+f"(d[37]),"+f"(d[38]),"+f"(d[39]),"+f"(d[40]),"+f"(d[41]),"+f"(d[42]),"+f"(d[43]),"+f"(d[44]),"+f"(d[45]),"+f"(d[46]),"+f"(d[47]),"+f"(d[48]),"+f"(d[49]),"+f"(d[50]),"+f"(d[51]),"+f"(d[52]),"+f"(d[53]),"+f"(d[54]),"+f"(d[55]) : "r"(a0), "r"(a1), "r"(a2), "r"(a3), "l"(db), "n"(SC));
}
template<int SC> __device__ __forceinline__ void wg_sp48(float (&d)[24], uint32_t a0, uint32_t a1, uint32_t a2, uint32_t a3, uint64_t db, uint32_t meta) {
  asm volatile("{\n.reg .pred p;\nsetp.ne.b32 p, %30, 0;\nwgmma.mma_async.sp.sync.aligned.m64n48k32.f32.bf16.bf16 {%0,%1,%2,%3,%4,%5,%6,%7,%8,%9,%10,%11,%12,%13,%14,%15,%16,%17,%18,%19,%20,%21,%22,%23}, {%24,%25,%26,%27}, %28, %29, 0, p, 1, 1, 1;\n}\n"
    : "+f"(d[0]),"+f"(d[1]),"+f"(d[2]),"+f"(d[3]),"+f"(d[4]),"+f"(d[5]),"+f"(d[6]),"+f"(d[7]),"+f"(d[8]),"+f"(d[9]),"+f"(d[10]),"+f"(d[11]),"+f"(d[12]),"+f"(d[13]),"+f"(d[14]),"+f"(d[15]),"+f"(d[16]),"+f"(d[17]),"+f"(d[18]),"+f"(d[19]),"+f"(d[20]),"+f"(d[21]),"+f"(d[22]),"+f"(d[23]) : "r"(a0), "r"(a1), "r"(a2), "r"(a3), "l"(db), "r"(meta), "n"(SC));
}
template<int SC> __device__ __forceinline__ void wg_rs64(float (&d)[32], uint32_t a0, uint32_t a1, uint32_t a2, uint32_t a3, uint64_t db) {
  asm volatile("{\n.reg .pred p;\nsetp.ne.b32 p, %37, 0;\nwgmma.mma_async.sync.aligned.m64n64k16.f32.bf16.bf16 {%0,%1,%2,%3,%4,%5,%6,%7,%8,%9,%10,%11,%12,%13,%14,%15,%16,%17,%18,%19,%20,%21,%22,%23,%24,%25,%26,%27,%28,%29,%30,%31}, {%32,%33,%34,%35}, %36, p, 1, 1, 0;\n}\n"
    : "+f"(d[0]),"+f"(d[1]),"+f"(d[2]),"+f"(d[3]),"+f"(d[4]),"+f"(d[5]),"+f"(d[6]),"+f"(d[7]),"+f"(d[8]),"+f"(d[9]),"+f"(d[10]),"+f"(d[11]),"+f"(d[12]),"+f"(d[13]),"+f"(d[14]),"+f"(d[15]),"+f"(d[16]),"+f"(d[17]),"+f"(d[18]),"+f"(d[19]),"+f"(d[20]),"+f"(d[21]),"+f"(d[22]),"+f"(d[23]),"+f"(d[24]),"+f"(d[25]),"+f"(d[26]),"+f"(d[27]),"+f"(d[28]),"+f"(d[29]),"+f"(d[30]),"+f"(d[31]) : "r"(a0), "r"(a1), "r"(a2), "r"(a3), "l"(db), "n"(SC));
}

constexpr uint32_t SBC = 1024;
constexpr int ROWB = 2 * 224 * 384;
constexpr int TB = 11;
constexpr int KS = 832;
constexpr int KSLOT = 22 * KS;
constexpr int SM_X2 = 0;
constexpr int SM_X0 = SM_X2 + 24576;
constexpr int SM_W = SM_X0 + 18432;
constexpr int SM_X1 = SM_W + 55296;
constexpr int SM_K = SM_X1 + 24576;
constexpr int SM_V = SM_K + 2 * KSLOT;
constexpr int SM_Q = SM_V + 22 * 1536;
constexpr int SM_O = SM_Q + 24576;
constexpr int SM_RPB = SM_O + 12288;
constexpr int SM_BAR = SM_RPB + 768;
constexpr int SM_A_TOTAL = SM_BAR + 256;
constexpr int SM_TIN = 0;
constexpr int SM_TST = 3 * 24576;
constexpr int SM_TWO = SM_TST + 12288;
enum { B_FULL = 0, B_EMPTY = 3, B_TIN = 6, B_TFREE = 10, B_WK = 12, B_WQ, B_WO, B_Q0, B_WOFREE, B_OTAIL, B_ODONE = B_OTAIL + 2, B_KFREE, B_VFREE, B_COUNT };
enum { N_KRDY = 4, N_QK0, N_QK1, N_VQ0, N_VQ1, N_PVISS };

#define NL 2
#define OPT 0
#define SPL 4
#define RA 160
#define RG 168
__device__ int g_flags[TB * 56];

#define TR(role, it, k)
#define TRDECL
#define TRARG
#define TRPASS
#define TRDUMP
#define TRB(it, k)
#define TR2(blk, k)

struct GemmCtx {
  uint32_t bar;
  uint32_t kC, vC[2], qC[2];
  uint32_t kH, vH[2];
  uint32_t hiA, hiB;
  uint32_t spin;
  bool hvalid, never;
};

template <int STRIDE> __device__ __forceinline__ void dump12(uint32_t a, const uint32_t (&r)[12]) {
#pragma unroll
  for (int j = 0; j < 3; j++) stsm4(a + j * 2 * STRIDE, r[4 * j], r[4 * j + 1], r[4 * j + 2], r[4 * j + 3]);
}
__device__ __forceinline__ void keep12(bool never, uint32_t a, const uint32_t (&r)[12]) { if (never) dump12<128>(a, r); }
template <int N> __device__ __forceinline__ void pack12(uint32_t (&r)[12], const float (&d)[N], int off) {
#pragma unroll
  for (int j = 0; j < 12; j++) r[j] = pack2(d[off + 2 * j], d[off + 2 * j + 1]);
}
__device__ __forceinline__ uint64_t dsc(uint64_t lo, uint32_t hi) { uint64_t r; asm("mov.b64 %0, {%1, %2};" : "=l"(r) : "r"((uint32_t)lo), "r"(hi)); return r; }
template <int XS, int K0, int K1> __device__ __forceinline__ void issue_core(const GemmCtx& c, float (&d)[72]) {
  constexpr uint64_t da = mkdesc(SBC + XS, 16, 1024, 1), db = mkdesc(SBC + SM_W, 6144, 256, 3);
  wg_fence();
  if (K0 == 0) wg_ss144<0>(d, dsc(da, c.hiA), dsc(db, c.hiB));
#pragma unroll
  for (int k = K0 ? K0 : 1; k < K1; k++) wg_ss144<1>(d, dsc(da + (k >> 2) * 512 + (k & 3) * 2, c.hiA), dsc(db + k * 32, c.hiB));
  wg_commit();
}
template <int K0, int K1> __device__ __forceinline__ void issue_halo(const GemmCtx& c, float (&d)[48]) {
  constexpr uint64_t da = mkdesc(SBC + SM_X0 - 2048, 16, 1024, 1), db = mkdesc(SBC + SM_W, 6144, 256, 3);
  wg_fence();
  if (K0 == 0) wg_ss96<0>(d, dsc(da, c.hiA), dsc(db, c.hiB));
#pragma unroll
  for (int k = K0 ? K0 : 1; k < K1; k++) wg_ss96<1>(d, dsc(da + (k >> 2) * 384 + (k & 3) * 2, c.hiA), dsc(db + k * 32, c.hiB));
  wg_commit();
}
template <int ST> __device__ __forceinline__ void release_stage(const GemmCtx& c) {
  asm volatile("{\n.reg .pred p;\n.reg .b32 ra;\nelect.sync _|p, 0xffffffff;\nmapa.shared::cluster.u32 ra, %0, %1;\n"
               "@p mbarrier.arrive.shared::cluster.b64 _, [ra];\n}" ::"r"(c.bar + (B_EMPTY + ST) * 8), "n"(ST) : "memory");
}
template <int PARITY> __device__ __forceinline__ void gwait(GemmCtx& c, int bar) {
  asm volatile("{\n.reg .pred p;\nWL:\nmbarrier.try_wait.parity.shared::cta.b64 p, [%1], %2;\n@p bra WD;\n"
               "add.u32 %0, %0, 1;\nsetp.lt.u32 p, %0, 0x100000;\n@p bra WL;\nWD:\n}" : "+r"(c.spin) : "r"(c.bar + bar * 8), "n"(PARITY) : "memory");
}
__device__ __forceinline__ void load_w(const CUtensorMap* m, uint32_t dst, uint32_t bar, int col) {
  asm volatile("cp.async.bulk.tensor.2d.shared::cluster.global.mbarrier::complete_tx::bytes [%0], [%1, {%3,%4}], [%2];"
               ::"r"(dst), "l"(m), "r"(bar), "r"(col), "r"(0) : "memory");
}
template <int BYTES> __device__ __forceinline__ void send_o(uint32_t dst, uint32_t src, uint32_t bar, int cta) {
  asm volatile("{\n.reg .b32 rd, rb;\nmapa.shared::cluster.u32 rd, %0, %3;\nmapa.shared::cluster.u32 rb, %2, %3;\n"
               "cp.async.bulk.shared::cluster.shared::cta.mbarrier::complete_tx::bytes [rd], [%1], %4, [rb];\n}"
               ::"r"(dst), "r"(src), "r"(bar), "r"(cta), "n"(BYTES) : "memory");
}
__device__ __forceinline__ void tail_free(uint32_t bar) {
  uint32_t ln; asm volatile("mov.u32 %0, %%laneid;" : "=r"(ln));
  if (ln < 4) mbar_arrive_remote(bar, ln);
}
__device__ __forceinline__ void publish(uint32_t bar) {
  fence_async();
  __syncwarp();
  mbar_arrive_elect(bar);
}

template <bool FIRST, int PA>
__device__ __forceinline__ void gemm_iter(GemmCtx& c, int b, uint32_t (&pk)[12], uint32_t (&pv)[12], uint32_t (&pq)[12] TRARG) {
  const uint32_t bar = c.bar;
  const bool w = !FIRST && (PA == 0 || b >= 0), never = c.never;
  constexpr uint32_t ko = PA * KSLOT;
  float H[48], C[72];
  uint32_t hk[12], hv[12], pv2[12];
  TR(2, b, 0);
  if (FIRST) gwait<PA>(c, B_FULL + 0);
  if (!FIRST) dump12<256>(c.qC[1] + (PA ^ 1) * 128, pq);
  if (w) nb_sync(N_QK1, 256);
  TR(2, b, 2);
  if (FIRST) TR(2, b - 1, 6);
  issue_halo<0, 8>(c, H);
  TR(2, b, 3);
  if (!FIRST) {
    if (w) gwait<PA>(c, B_KFREE);
    dump12<128>(c.kC + ko, pk);
  }
  issue_halo<8, 12>(c, H);
  TR(2, b, 4);
  {
    gwait<PA>(c, B_FULL + 2);
    if (FIRST && NL == 2) gwait<0>(c, B_WQ);
    TR(2, b, 13);
    if (FIRST) TR(2, b - 1, 7);
    issue_core<SM_X2, 0, 8>(c, C);
    TR(2, b, 5);
    if (!FIRST) { fence_async(); keep12(never, c.kC, pk); }
    wg_wait<1>(); pin(H);
    release_stage<0>(c);
  }
  pack12(hk, H, 0);
  if (c.hvalid) dump12<128>(c.kH + ko, hk);
  pack12(hv, H, 24);
  {
    issue_core<SM_X2, 8, 12>(c, C);
    if (w) { nb_arrive(N_VQ0, 288); nb_arrive(N_VQ1, 288); }
    else if (!FIRST) { __syncwarp(); mbar_arrive_elect(bar + B_Q0 * 8); }
    gwait<PA>(c, B_FULL + 1);
    keep12(never, c.kC, hk);
    TR(2, b, 6);
    wg_wait<0>(); pin(C);
    TR(2, b, 7);
    pack12(pk, C, 0);
    dump12<128>(c.kC + ko + 64, pk);
    release_stage<2>(c);
    pack12(pv2, C, 24);
    pack12(pq, C, 48);
    TR(2, b, 8);
    issue_core<SM_X1, 0, SPL>(c, C);
    if (w) nb_sync(N_PVISS, 384);
    issue_core<SM_X1, SPL, 8>(c, C);
    TR(2, b, 9);
  }
  if (!FIRST) fence_async();
  keep12(never, c.kC, pk);
  TR(2, b, 14);
  issue_core<SM_X1, 8, 12>(c, C);
  if (!FIRST) nb_arrive(N_KRDY, 256);
  TR(2, b, 1);
  if (PA && b == 11) tail_free(bar + B_TFREE * 8);
  gwait<PA ^ 1>(c, B_FULL + 0);
  if (w) gwait<PA>(c, B_VFREE);
  TR(2, b, 10);
  if (!FIRST) dump12<128>(c.vC[PA], pv);
  dump12<256>(c.qC[0] + PA * 128, pq);
  if (c.hvalid) dump12<128>(c.vH[PA], hv);
  dump12<128>(c.vC[PA ^ 1] + 768, pv2);
  TR(2, b, 11);
  wg_wait<0>(); pin(C);
  TR(2, b, 12);
  release_stage<1>(c);
  pack12(pk, C, 0);
  pack12(pv, C, 24);
  pack12(pq, C, 48);
}

template <int IN> __device__ __forceinline__ void issue_proj(float (&D)[48]) {
  constexpr uint64_t da = mkdesc(SBC + IN, 128, 768, 0), db = mkdesc(SBC + SM_TWO, 12288, 512, 2);
  wg_fence();
  wg_ss96<0>(D, da, db);
#pragma unroll
  for (int k = 1; k < 12; k++) wg_ss96<1>(D, da + (k / 3) * 384 + (k % 3) * 16, db + k * 64);
  wg_commit();
}
template <int ACC> __device__ __forceinline__ void issue_proj_half(float (&D)[48], int hd) {
  const uint64_t da = mkdesc(SBC + SM_TIN + 2 * 24576, 128, 768, 0) + hd * 384, db = mkdesc(SBC + SM_TWO, 12288, 512, 2) + hd * 192;
  wg_fence();
  wg_ss96<ACC>(D, da, db);
#pragma unroll
  for (int k = 1; k < 6; k++) wg_ss96<1>(D, da + (k / 3) * 768 + (k % 3) * 16, db + (k / 3) * 384 + (k % 3) * 64);
  wg_commit();
}
__device__ __forceinline__ void store_proj(const float (&D)[48], const CUtensorMap* m, uint32_t st, uint32_t sta, int row, int col, int ch) {
#pragma unroll
  for (int q = 0; q < 6; q++)
    stsm4((sta ^ ((q & 1) * 32)) + (q >> 1) * 1024,
          pack2(D[8 * q], D[8 * q + 1]), pack2(D[8 * q + 2], D[8 * q + 3]), pack2(D[8 * q + 4], D[8 * q + 5]), pack2(D[8 * q + 6], D[8 * q + 7]));
  fence_async();
  __syncwarp();
  if ((threadIdx.x & 31) == 0) {
    asm volatile("cp.async.bulk.tensor.4d.global.shared::cta.bulk_group [%0, {%2,%3,%4,%5}], [%1];" ::"l"(m), "r"(st), "r"(0), "r"(row), "r"(col), "r"(ch) : "memory");
    asm volatile("cp.async.bulk.commit_group;" ::: "memory");
  }
  __syncwarp();
}

__device__ __forceinline__ float fold(float a, float b, float t, int useb) {
  float r;
  asm("{\n.reg .pred p;\nsetp.ne.b32 p, %4, 0;\nfma.rn.f32 %0, %1, 0f3E553B95, %3;\n@p fma.rn.f32 %0, %2, 0f3E553B95, %3;\n}"
      : "=&f"(r) : "f"(a), "f"(b), "f"(t), "r"(useb));
  return r;
}
template <int U, int L>
__device__ __forceinline__ void softmax_tile(const float (&SA)[56], const float (&SB)[56], const float (&T)[16], int b0, int b1,
                                             uint32_t (&P)[28], float (&sx)[8]) {
  float lu[14], ll[14];
#pragma unroll
  for (int j = 0; j < 7; j++) {
    constexpr int sh = U == L ? 2 : 0;
    const float tu0 = T[2 * j + sh], tu1 = T[2 * j + 1 + sh], tl0 = T[2 * j], tl1 = T[2 * j + 1];
    lu[2 * j]     = fold(SA[4 * (U + j)],     SB[4 * (U + j)],     tu0, b0);
    ll[2 * j]     = fold(SA[4 * (L + j) + 2], SB[4 * (L + j) + 2], tl0, b0);
    lu[2 * j + 1] = fold(SA[4 * (U + j) + 1], SB[4 * (U + j) + 1], tu1, b1);
    ll[2 * j + 1] = fold(SA[4 * (L + j) + 3], SB[4 * (L + j) + 3], tl1, b1);
  }
  float mu = lu[0], ml = ll[0], mu2 = lu[1], ml2 = ll[1];
#pragma unroll
  for (int j = 1; j < 7; j++) { mu = fmaxf(mu, lu[2 * j]); mu2 = fmaxf(mu2, lu[2 * j + 1]); ml = fmaxf(ml, ll[2 * j]); ml2 = fmaxf(ml2, ll[2 * j + 1]); }
  mu = fmaxf(mu, mu2); ml = fmaxf(ml, ml2);
  { const float a1 = __shfl_xor_sync(0xffffffffu, mu, 1), a2 = __shfl_xor_sync(0xffffffffu, mu, 2), a3 = __shfl_xor_sync(0xffffffffu, mu, 3);
    const float c1 = __shfl_xor_sync(0xffffffffu, ml, 1), c2 = __shfl_xor_sync(0xffffffffu, ml, 2), c3 = __shfl_xor_sync(0xffffffffu, ml, 3);
    mu = fmaxf(fmaxf(mu, a1), fmaxf(a2, a3)); ml = fmaxf(fmaxf(ml, c1), fmaxf(c2, c3)); }
  float su = 0.f, sl = 0.f;
#pragma unroll
  for (int c = 0; c < 14; c++) {
    const int iu = (c >> 1) * 4 + (c & 1) * 2;
    if (c >= U && c < U + 7) {
      float e0 = ex2(lu[2 * (c - U)] - mu), e1 = ex2(lu[2 * (c - U) + 1] - mu);
      su = c == U ? e0 + e1 : (su + e0) + e1; P[iu] = pack2(e0, e1);
    } else P[iu] = 0u;
    if (c >= L && c < L + 7) {
      float e0 = ex2(ll[2 * (c - L)] - ml), e1 = ex2(ll[2 * (c - L) + 1] - ml);
      sl = c == L ? e0 + e1 : (sl + e0) + e1; P[iu + 1] = pack2(e0, e1);
    } else P[iu + 1] = 0u;
  }
  sx[0] = su; sx[4] = sl;
#pragma unroll
  for (int k = 1; k < 4; k++) { sx[k] = __shfl_xor_sync(0xffffffffu, su, k); sx[4 + k] = __shfl_xor_sync(0xffffffffu, sl, k); }
}

struct BandCfg { uint32_t ra0, ra1, meta; int b0, b1; };
__device__ __forceinline__ void band_cfg(int b, uint32_t tb, BandCfg& n) {
  uint32_t ln; asm volatile("mov.u32 %0, %%laneid;" : "=r"(ln));
  const int g = ln >> 2, t = ln & 3;
  const int sw = min(max(g + 1, b == 0 ? 4 : 0), b == 13 ? 5 : 8);
  const int i0 = 2 * t, i1 = 2 * t + 1;
  n.b0 = i0 <= sw - 2; n.b1 = i1 <= sw - 2;
  n.ra0 = tb + (i0 == sw - 1 ? 13 : i0 + 8 * n.b0 - g + 2) * 52;
  n.ra1 = tb + (i1 == sw - 1 ? 13 : i1 + 8 * n.b1 - g + 2) * 52;
  n.meta = ((0x5555u & ((1u << (2 * (sw - 1))) - 1)) ^ 0xDD88u ^ (((t ^ b) & 1) ? 0x5555u : 0u)) * 0x10001u;
}
__device__ __forceinline__ void band_load(const BandCfg& n, float (&T)[16], int& b0, int& b1, uint32_t& meta) {
#pragma unroll
  for (int jj = 0; jj < 8; jj++) { T[2 * jj] = lds_f32(n.ra0 + jj * 4); T[2 * jj + 1] = lds_f32(n.ra1 + jj * 4); }
  b0 = n.b0; b1 = n.b1; meta = n.meta;
}

struct Maps { CUtensorMap xc, xh, w, os, wo, ot; };

__global__ void __cluster_dims__(4, 1, 1) __launch_bounds__(512, 1)
na_attn_kernel(const __nv_bfloat16* __restrict__ x, const __nv_bfloat16* __restrict__ wqkv, const __nv_bfloat16* __restrict__ rpb, const __grid_constant__ Maps mp) {
  extern __shared__ __align__(1024) uint8_t smem_raw[];
  const uint32_t sb = smem_u32(smem_raw);
  if ((sb & 0x3FFFF) != SBC) return;
  const uint32_t bar = sb + SM_BAR;
  TR2(blockIdx.x, 0);
  const int tid = threadIdx.x, lane = tid & 31;
  const int warp = __shfl_sync(0xffffffffu, tid >> 5, 0);
  const int head = blockIdx.x & 3, cl = blockIdx.x >> 2;
  const int par = cl / 7, strip = cl - par * 7, ph = par >> 1, pw = par & 1;

  uint4 wv[2 * NL];
  const int va = head == 1;
  const uint32_t wdst = sb + SM_W + (va + ((tid >> 1) & 1)) * 6144 + (tid >> 2) * 32 + ((tid ^ (tid >> 4)) & 1) * 16;
  if (warp < 12) asm volatile("barrier.cluster.arrive.relaxed.aligned;" ::: "memory");
  {
    const uint32_t wo0 = (tid >> 2) * 1152 + head * 96 + va * 32 + (tid & 3) * 16;
#pragma unroll
    for (int i = 0; i < 2 * NL; i++)
      asm volatile("{\n.reg .pred p;\nsetp.lt.u32 p, %5, 384;\n@p ld.global.nc.v4.b32 {%0,%1,%2,%3}, [%4];\n}"
                   : "=r"(wv[i].x), "=r"(wv[i].y), "=r"(wv[i].z), "=r"(wv[i].w)
                   : "l"(reinterpret_cast<const uint8_t*>(wqkv) + wo0 + (i & 1) * 96 * 1152 + ((i / 2 + 1) % 3) * 384), "r"(tid));
  }
  if (warp < 8) {
    asm volatile("setmaxnreg.inc.sync.aligned.u32 %0;" ::"n"(RA));
    float rv = -INFINITY;
    if (tid < 169) rv = __bfloat162float(rpb[head * 169 + tid]) * 1.4426950408889634f;
    if (tid < 192) {
      const int kc = (tid & 15) + 3, wc = (tid >> 4) % 6;
      sts128(tid < 96 ? sb + SM_K + kc * KS + wc * 128 + 48 : sb + SM_V + kc * 1536 + wc * 128 + (6 + (kc & 1)) * 16, make_uint4(0, 0, 0, 0));
    }
#pragma unroll
    for (int i = 0; i < 2 * NL; i++) sts128(wdst + (i & 1) * 3072 + (i / 2) * 18432, wv[i]);
    fence_async();
    asm volatile("bar.arrive 1, 384;" ::: "memory");
    if (tid < 182) asm volatile("st.shared.f32 [%0], %1;" ::"r"(sb + SM_RPB + tid * 4), "f"(rv) : "memory");
    const int j = warp >> 2, w = warp & 3;
    int variant = w;
    if (strip == 0 && j == 0 && w < 2) variant = 4;
    if (strip == 6 && j == 1 && w >= 2) variant = 5;
    const bool v1 = opq((uint32_t)(variant & 1)), v2 = opq((uint32_t)(variant & 2)), v4 = opq((uint32_t)(variant & 4));
    uint32_t qa = opq(sb + SM_Q + (8 * j + 2 * w + ((lane >> 3) & 1)) * 1536 + (lane >> 4) * 256 + (((lane & 7) * 16) ^ (((lane >> 3) & 1) * 64)));
    uint32_t oa = opq(sb + SM_O + j * 6144 + (2 * w + ((lane >> 3) & 1)) * 768 + (lane >> 4) * 128 + (lane & 7) * 16);
    uint64_t dA = opq(mkdesc(SBC + SM_K, 128, KS, 0) + j * (8 * KS / 16)), dB = opq(dA + (KSLOT >> 4));
    uint64_t dV[7];
#pragma unroll
    for (int i = 0; i < 7; i++) dV[i] = opq(mkdesc(SBC + SM_V, 768, 128, 0) + j * (8 * 1536 / 16) + i * 192);
    const uint32_t nbK = opq((uint32_t)(N_KRDY + j)), nbQ = opq((uint32_t)(N_QK0 + j)), nbV = opq((uint32_t)(N_VQ0 + j));
    asm volatile("barrier.cluster.wait.aligned;" ::: "memory");
    asm volatile("bar.sync 3, 256;" ::: "memory");
    float T[16];
    TRDECL;
    int b0, b1;
    uint32_t meta, ob = bar + B_ODONE * 8;
    const uint32_t tb = opq(sb + SM_RPB + (variant < 4 ? 3 : variant + 1 - 2 * w) * 4);
    const bool own = ((w ^ head) & 2) == 0;
    const uint32_t dst13 = sb + SM_TIN + 2 * 24576 + head * 6144 + (2 * j + (w & 1)) * 1536, src13 = opq(own ? dst13 : sb + SM_Q + warp * 3072 + 1536);
    const uint32_t snd[4] = {opq(own ? 0u : mapa(dst13, head ^ 2)), opq(mapa(bar + (B_TIN + 2) * 8, head ^ 2)),
                             opq(mapa(dst13, (w & 2) + (~head & 1))), opq(mapa(bar + (B_TIN + 3) * 8, (w & 2) + (~head & 1)))};
    BandCfg nx;
    band_cfg(0, tb, nx);
    band_load(nx, T, b0, b1, meta);
    meta ^= 0x55555555u;
    band_cfg(1, tb, nx);
    uint32_t q[12];
    mbar_wait(bar + B_Q0 * 8, 0);
#pragma unroll
    for (int k = 0; k < 3; k++) ldsm4(qa + k * 512, q[4 * k], q[4 * k + 1], q[4 * k + 2], q[4 * k + 3]);
#pragma unroll 1
    for (int b = 0; b < 14; b++) {
      float SA[56], SB[56];
      TR(0, b, 0);
      nb_sync(nbK, 256);
      TR(0, b, 1);
      TR(0, b - 1, 9);
      wg_fence();
      wg_rs112<0>(SA, q[0], q[1], q[2], q[3], dA);
      wg_rs112<0>(SB, q[0], q[1], q[2], q[3], dB);
      wg_rs112<1>(SA, q[4], q[5], q[6], q[7], dA + 16);
      wg_rs112<1>(SB, q[4], q[5], q[6], q[7], dB + 16);
      wg_rs112<1>(SA, q[8], q[9], q[10], q[11], dA + 32);
      wg_rs112<1>(SB, q[8], q[9], q[10], q[11], dB + 32);
      wg_commit();
      nb_arrive(nbQ, 256);
      { const uint64_t t = dA; dA = dB; dB = t; }
      qa ^= 128;
      meta ^= 0x55555555u;
      if (b == 1 || b == 13) band_load(nx, T, b0, b1, meta);
      if (b >= TB) {
        ob = opq(bar + (b == 13 && own ? B_TIN + 2 : B_OTAIL + j) * 8);
        oa += b == 12 ? warp * 1536 - (SM_O - SM_Q) : (b == 13 ? src13 - (sb + SM_Q + warp * 3072) : 0);
      }
      TR(0, b, 2);
      wg_wait<0>(); pin(SA); pin(SB);
      mbar_arrive_elect(bar + B_KFREE * 8);
      TR(0, b, 3);
      TR(0, b - 1, 10);
      uint32_t P[28];
      float sx[8];
      if (v2) {
        if (v1) softmax_tile<6, 7>(SA, SB, T, b0, b1, P, sx); else softmax_tile<4, 5>(SA, SB, T, b0, b1, P, sx);
      } else if (!v4) {
        if (v1) softmax_tile<2, 3>(SA, SB, T, b0, b1, P, sx); else softmax_tile<0, 1>(SA, SB, T, b0, b1, P, sx);
      } else {
        if (v1) softmax_tile<4, 4>(SA, SB, T, b0, b1, P, sx); else softmax_tile<3, 3>(SA, SB, T, b0, b1, P, sx);
      }
      float O[24];
      TR(0, b, 4);
      if (b == 3) band_cfg(13, tb, nx);
      nb_sync(nbV, 288);
      TR(0, b, 5);
#pragma unroll
      for (int k = 0; k < 3; k++) ldsm4(qa + k * 512, q[4 * k], q[4 * k + 1], q[4 * k + 2], q[4 * k + 3]);
      wg_fence();
      wg_sp48<0>(O, P[0], P[1], P[2], P[3], dV[0], meta);
#pragma unroll
      for (int s = 1; s < 7; s++) wg_sp48<1>(O, P[4 * s], P[4 * s + 1], P[4 * s + 2], P[4 * s + 3], dV[s], meta);
      wg_commit();
      nb_arrive(N_PVISS, 384);
      TR(0, b, 6);
      wg_wait<0>(); pin(O);
      mbar_arrive_elect(bar + B_VFREE * 8);
      TR(0, b, 7);
      float ru, rl;
      asm("rcp.approx.ftz.f32 %0, %1;" : "=f"(ru) : "f"(((fmaf(O[0], 0.f, sx[0]) + sx[1]) + sx[2]) + sx[3]));
      asm("rcp.approx.ftz.f32 %0, %1;" : "=f"(rl) : "f"(((fmaf(O[2], 0.f, sx[4]) + sx[5]) + sx[6]) + sx[7]));
#pragma unroll
      for (int i = 0; i < 3; i++)
        stsm4(oa + i * 256, pack2(O[8 * i] * ru, O[8 * i + 1] * ru), pack2(O[8 * i + 2] * rl, O[8 * i + 3] * rl),
              pack2(O[8 * i + 4] * ru, O[8 * i + 5] * ru), pack2(O[8 * i + 6] * rl, O[8 * i + 7] * rl));
      publish(ob);
      TR(0, b, 8);
    }
    asm volatile("{\n.reg .pred p, q;\nsetp.ne.b32 q, %1, 0;\nelect.sync _|p, 0xffffffff;\nand.pred q, q, p;\n"
                 "@q cp.async.bulk.shared::cluster.shared::cta.mbarrier::complete_tx::bytes [%1], [%0], 1536, [%2];\n"
                 "@p cp.async.bulk.shared::cluster.shared::cta.mbarrier::complete_tx::bytes [%3], [%0], 1536, [%4];\n}"
                 ::"r"(src13), "r"(snd[0]), "r"(snd[1]), "r"(snd[2]), "r"(snd[3]) : "memory");
    if (j == 0) nb_arrive(3, 256);
    TRDUMP;
    cluster_sync();
  } else if (warp < 12) {
    TRDECL;
    TR(2, -3, 0);
    asm volatile("setmaxnreg.inc.sync.aligned.u32 %0;" ::"n"(RG));
    TR(2, -3, 1);
    GemmCtx c;
    c.bar = bar;
    const int gw = warp - 8, tk = gw * 16 + (lane & 15), hi = lane >> 4;
    { const int col = tk >> 2, i = tk & 3;
      c.kC = sb + SM_K + (col + 3) * KS + hi * 128 + i * 16;
      c.vC[0] = sb + SM_V + (col + 3) * 1536 + hi * 128 + (2 * i + ((col + 3) & 1)) * 16;
      c.qC[0] = sb + SM_Q + col * 1536 + hi * 256 + (col & 1) * 64 + i * 16; }
    { const int ci = (tk >> 3) - 2, kc = ci < 3 ? ci : ci + 16, i = tk & 7; c.hvalid = gw > 0;
      c.kH = sb + SM_K + kc * KS + hi * 128 + i * 16;
      c.vH[0] = sb + SM_V + kc * 1536 + hi * 128 + (i >> 2) * 768 + (2 * (i & 3) + ((kc ^ (i >> 2)) & 1)) * 16; }
    c.never = x == nullptr;
    c.kC = opq(c.kC); c.kH = opq(c.kH);
    c.vC[1] = opq(c.vC[0] ^ 16); c.vC[0] = opq(c.vC[0]);
    c.vH[1] = opq(c.vH[0] ^ 16); c.vH[0] = opq(c.vH[0]);
    c.qC[1] = opq(c.qC[0] ^ 64); c.qC[0] = opq(c.qC[0]);
    c.spin = 0;
    c.hiA = (uint32_t)(mkdesc(0, 0, 1024, 1) >> 32) + (blockIdx.x >> 16); c.hiB = (uint32_t)(mkdesc(0, 0, 256, 3) >> 32) + (blockIdx.x >> 16);
    asm volatile("barrier.cluster.wait.aligned;" ::: "memory");
    TR(2, -3, 2);
#pragma unroll
    for (int i = 0; i < 2 * NL; i++) sts128(wdst + (i & 1) * 3072 + (i / 2) * 18432, wv[i]);
    fence_async();
    TR(2, -3, 3);
    asm volatile("bar.sync 1, 384;" ::: "memory");
    TR(2, -3, 4);
    mbar_wait(bar + B_WK * 8, 0);
    TR(2, -3, 5);
    uint32_t pk[12], pv[12], pq[12];
    gemm_iter<true, 0>(c, -2, pk, pv, pq TRPASS);
    TR2(blockIdx.x, 4);
    c.hiA = opq(c.hiA); c.hiB = opq(c.hiB);
#pragma unroll 1
    for (int b = -1;; b += 2) {
      gemm_iter<false, 1>(c, b, pk, pv, pq TRPASS);
      if (b == 11) break;
      gemm_iter<false, 0>(c, b + 1, pk, pv, pq TRPASS);
    }
    TR2(blockIdx.x, 6);
    const uint32_t st = sb + gw * 3072;
    const uint32_t sta = st + (lane & 15) * 64 + ((hi ^ ((lane >> 1) & 3)) * 16);
    const int oc = ph * 112 + strip * 16 + 8 * (gw >> 1) + 4 * (head >> 1) + 2 * (gw & 1), och = pw * 6 + (head & 1) * 3;
    float D0[48], D1[48];
    mbar_arrive_elect(bar + B_WOFREE * 8);
    dump12<256>(c.qC[1] + 128, pq);
    nb_sync(N_QK1, 256);
    issue_halo<0, 12>(c, D1);
    gwait<0>(c, B_KFREE);
    dump12<128>(c.kC, pk);
    fence_async();
    nb_arrive(N_VQ0, 288); nb_arrive(N_VQ1, 288); nb_arrive(N_PVISS, 384);
    wg_wait<0>(); pin(D1);
    pack12(pk, D1, 0);
    if (c.hvalid) dump12<128>(c.kH, pk);
    tail_free(bar + (B_TFREE + 1) * 8);
    pack12(pq, D1, 24);
    fence_async();
    nb_arrive(N_KRDY, 256);
    gwait<0>(c, B_VFREE);
    dump12<128>(c.vC[0], pv);
    if (c.hvalid) dump12<128>(c.vH[0], pq);
    fence_async();
    nb_arrive(N_VQ0, 288); nb_arrive(N_VQ1, 288);
    gwait<0>(c, B_WO);
    gwait<0>(c, B_TIN);
    TR(2, 13, 0);
    nb_sync(N_QK1, 256);
    issue_proj<SM_TIN>(D0);
    wg_wait<0>(); pin(D0);
    TR(2, 13, 1);
    store_proj(D0, &mp.ot, st + SM_TST, sta + SM_TST, 8 * TB, oc, och);
    gwait<0>(c, B_TIN + 1);
    TR(2, 13, 2);
    nb_sync(N_PVISS, 384);
    nb_sync(3, 256);
    issue_proj<SM_TIN + 24576>(D1);
    wg_wait<0>(); pin(D1);
    TR(2, 13, 3);
    store_proj(D1, &mp.ot, st + SM_TIN, sta + SM_TIN, 8 * TB + 8, oc, och);
    TR(2, 13, 4);
    gwait<0>(c, B_TIN + 2);
    TR(2, 13, 5);
    issue_proj_half<0>(D0, head & 1);
    gwait<0>(c, B_TIN + 3);
    TR(2, 13, 6);
    issue_proj_half<1>(D0, ~head & 1);
    asm volatile("barrier.cluster.arrive.relaxed.aligned;" ::: "memory");
    wg_wait<0>(); pin(D0);
    store_proj(D0, &mp.ot, st + SM_TIN + 12288, sta + SM_TIN + 12288, 8 * TB + 16, oc, och);
    TR(2, 13, 7);
    if (lane == 0) asm volatile("cp.async.bulk.wait_group.read 0;" ::: "memory");
    __syncwarp();
    TR(2, 13, 8);
    TR2(blockIdx.x, 2);
    TRDUMP;
    asm volatile("barrier.cluster.wait.aligned;" ::: "memory");
  } else {
    if (warp == 12) {
      if (elect_one()) {
        mbar_init(bar + B_WK * 8, 1);
#pragma unroll
        for (int i = 0; i < NL; i++) load_w(&mp.w, sb + SM_W + (3 * i + 2 - 2 * va) * 6144, bar + B_WK * 8, ((i + 1) % 3) * 192 + head * 48 + 32 - 32 * va);
        asm volatile("prefetch.tensormap [%0];" ::"l"(head ? &mp.xc : &mp.xh) : "memory");
        mbar_expect(bar + B_WK * 8, NL * 6144);
      }
    } else if (warp == 15) {
      const int col = min(max(strip * 16 - 3 + min(lane, 21), 0), 111);
      const uint8_t* p = reinterpret_cast<const uint8_t*>(x) + (uint32_t)(head * ROWB + (ph * 112 + col) * 768 + pw * 384);
#pragma unroll
      for (int i = 0; i < 3; i++) asm volatile("prefetch.global.L2 [%0];" ::"l"(p + i * 128));
    } else if (elect_one()) {
      if (warp == 13) {
#pragma unroll
        for (int i = 0; i < B_WK; i++) mbar_init(bar + i * 8, i < B_EMPTY ? 1 : (i < B_TIN ? 16 : (i < B_TFREE ? (i == B_TIN + 2 ? 5 : 1) : 16)));
      } else {
#pragma unroll
        for (int i = B_WQ; i < B_COUNT; i++) mbar_init(bar + i * 8, i < B_Q0 ? 1 : (i < B_ODONE ? 4 : 8));
      }
    }
    asm volatile("fence.mbarrier_init.release.cluster;" ::: "memory");
    __syncwarp();
    asm volatile("barrier.cluster.arrive.relaxed.aligned;" ::: "memory");
    asm volatile("setmaxnreg.dec.sync.aligned.u32 24;");
    asm volatile("griddepcontrol.launch_dependents;");
    const int cc = ph * 112 + (head ? strip * 16 : (strip == 0 ? 16 : (strip == 6 ? 74 : strip * 16 - 3)));
    const int sd = strip == 0 ? -1 : (strip == 6 ? 1 : 0);
    const int r0 = head == 0 ? -4 : (head == 1 ? 4 : 0);
    asm volatile("barrier.cluster.wait.aligned;" ::: "memory");
    if (warp == 12) {
      const uint32_t fb = bar + (B_FULL + head) * 8, eb = bar + (B_EMPTY + head) * 8;
      const uint32_t dst = sb + (head == 0 ? SM_X0 : (head == 1 ? SM_X1 : SM_X2));
      const int nl = head == 0 ? 15 : (head == 3 ? 1 : 14);
#pragma unroll 1
      for (int n = 0; n < nl; n++) {
        if (n) mbar_wait(eb, (n - 1) & 1);
        if (lane < 4 && head < 3)
          asm volatile("{\n.reg .b32 ra;\nmapa.shared::cluster.u32 ra, %0, %1;\nmbarrier.arrive.expect_tx.shared::cluster.b64 _, [ra], %2;\n}"
                       ::"r"(fb), "r"(lane), "r"(head ? 24576 : 18432) : "memory");
        __syncwarp();
        if (elect_one()) {
          if (head == 0) {
            asm volatile("cp.async.bulk.tensor.5d.shared::cluster.global.mbarrier::complete_tx::bytes.multicast::cluster [%0], [%1, {%3,%4,%5,%6,%7}], [%2], %8;"
                         ::"r"(dst), "l"(&mp.xh), "r"(fb), "r"(0), "r"(8 * n + r0), "r"(cc), "r"(sd), "r"(pw * 3), "h"((uint16_t)15) : "memory");
          } else if (head < 3) {
            asm volatile("cp.async.bulk.tensor.4d.shared::cluster.global.mbarrier::complete_tx::bytes.multicast::cluster [%0], [%1, {%3,%4,%5,%6}], [%2], %7;"
                         ::"r"(dst), "l"(&mp.xc), "r"(fb), "r"(0), "r"(8 * n + r0), "r"(cc), "r"(pw * 3), "h"((uint16_t)15) : "memory");
          }
          if (n == 0) {
#pragma unroll
            for (int i = 0; i < 3; i++) load_w(&mp.w, sb + SM_W + (6 + i) * 6144, bar + B_WQ * 8, head * 48 + i * 16);
            mbar_expect(bar + B_WQ * 8, 18432);
            mbar_expect(bar + B_TIN * 8, 24576); mbar_expect(bar + (B_TIN + 1) * 8, 24576); mbar_expect(bar + (B_TIN + 2) * 8, 6144); mbar_expect(bar + (B_TIN + 3) * 8, 12288);
          }
          if (!head && n + 1 < nl) asm volatile("cp.async.bulk.prefetch.tensor.5d.L2.global [%0, {%1,%2,%3,%4,%5}];" ::"l"(&mp.xh), "r"(0), "r"(8 * n + 8 + r0), "r"(cc), "r"(sd), "r"(pw * 3) : "memory");
          if (head && n + 1 < nl) asm volatile("cp.async.bulk.prefetch.tensor.4d.L2.global [%0, {%1,%2,%3,%4}];" ::"l"(&mp.xc), "r"(0), "r"(8 * n + 8 + r0), "r"(cc), "r"(pw * 3) : "memory");
        }
        __syncwarp();
      }
      mbar_wait(bar + B_WOFREE * 8, 0);
      if (elect_one()) {
        mbar_expect(bar + B_WO * 8, 36864);
        asm volatile("cp.async.bulk.tensor.3d.shared::cluster.global.mbarrier::complete_tx::bytes [%0], [%1, {%3,%4,%5}], [%2];"
                     ::"r"(sb + SM_TWO), "l"(&mp.wo), "r"(bar + B_WO * 8), "r"(0), "r"(0), "r"((head & 1) * 3) : "memory");
      }
      __syncwarp();
    }
    if (warp == 14) {
      int* flag = g_flags + cl * 2;
      nb_arrive(N_VQ0, 288); nb_arrive(N_VQ1, 288);
#pragma unroll 1
      for (int b = 0; b < TB; b++) {
        mbar_wait(bar + B_ODONE * 8, b & 1);
        if (lane == 0) {
          asm volatile("cp.async.bulk.tensor.3d.global.shared::cta.bulk_group [%0, {%2,%3,%4}], [%1];"
                       ::"l"(&mp.os), "r"(sb + SM_O), "r"(pw * 192), "r"(8 * b + 2 * head), "r"(ph * 112 + strip * 16) : "memory");
          asm volatile("cp.async.bulk.commit_group;\ncp.async.bulk.wait_group 0;" ::: "memory");
        }
        __syncwarp();
        nb_arrive(N_VQ0, 288); nb_arrive(N_VQ1, 288);
        if (lane == 0)
          asm volatile("fence.proxy.async.global;\nfence.acq_rel.gpu;\nred.relaxed.gpu.global.add.s32 [%0], 1;\nred.relaxed.gpu.global.add.s32 [%0+4], 1;"
                       ::"l"(flag + b * 56) : "memory");
        __syncwarp();
      }
    } else if (warp & 1) {
      const int j = (warp >> 1) & 1;
#pragma unroll 1
      for (int i = 0; i < 2; i++) {
        mbar_wait(bar + (B_OTAIL + j) * 8, i);
        if (i == 0) nb_arrive(N_VQ0 + j, 288);
        mbar_wait(bar + (B_TFREE + i) * 8, 0);
        if (i == 1) nb_arrive(N_VQ0 + j, 288);
        if (elect_one()) {
#pragma unroll 1
          for (int d = 0; d < 8; d++) {
            const int dst = (d + head) & 3, pc = d >> 2;
            send_o<1536>(sb + SM_TIN + i * 24576 + head * 6144 + j * 3072 + pc * 1536,
                         sb + (i ? SM_Q : SM_O) + (4 * j + (dst & 2) + pc) * (i ? 3072 : 1536), bar + (B_TIN + i) * 8, dst);
          }
        }
        __syncwarp();
      }
    }
    cluster_sync();
  }
}

constexpr int NSTB = 6;
constexpr int NTB = TB * 56;
constexpr int SM_B_ST = 0;
constexpr int SM_B_IN = 73728;
constexpr int SM_B_W = SM_B_IN + 3 * 24576;
constexpr int SM_B_BAR = SM_B_IN + NSTB * 24576;
constexpr int SM_B_TOTAL = SM_B_BAR + 128;
struct MapsB { CUtensorMap oi, oo, wo; };

__global__ void __launch_bounds__(512, 1)
na_proj_kernel(const __grid_constant__ MapsB mp) {
  extern __shared__ __align__(1024) uint8_t smem_raw[];
  const uint32_t sb = smem_u32(smem_raw);
  if ((sb & 0x3FFFF) != SBC) return;
  const uint32_t bar = sb + SM_B_BAR;
  const int tid = threadIdx.x, lane = tid & 31;
  const int warp = __shfl_sync(0xffffffffu, tid >> 5, 0);
  TR2(132 + blockIdx.x, 0);
  TRB(47, 0);
  if (warp == 12 && elect_one()) {
#pragma unroll
    for (int i = 0; i <= 2 * NSTB; i++) mbar_init(bar + i * 8, i < NSTB || i == 2 * NSTB ? 1 : 12);
    mbar_expect(bar + 2 * NSTB * 8, 73728);
#pragma unroll
    for (int i = 0; i < 2; i++)
      asm volatile("cp.async.bulk.tensor.3d.shared::cluster.global.mbarrier::complete_tx::bytes [%0], [%1, {%3,%4,%5}], [%2];"
                   ::"r"(sb + SM_B_W + i * 36864), "l"(&mp.wo), "r"(bar + 2 * NSTB * 8), "r"(0), "r"(0), "r"(i * 3) : "memory");
  }
  __syncthreads();
  const int step = gridDim.x;
  if (warp == 15) {
    int so = 0;
    nb_arrive(4, 288); nb_arrive(5, 288); nb_arrive(6, 288);
#pragma unroll 1
    for (int n = blockIdx.x; n < NTB; n += step) {
      const int b = n / 56, rem = n - b * 56, par = rem / 14;
      const int c1 = opq((uint32_t)(8 * b)), c2 = opq((uint32_t)((par >> 1) * 112 + (rem - par * 14) * 8)), c3 = opq((uint32_t)((par & 1) * 3));
#pragma unroll
      for (int wg = 0; wg < 3; wg++) {
        if (lane == 0) asm volatile("cp.async.bulk.wait_group.read 5;" ::: "memory");
        nb_sync(1 + wg, 160);
        if (wg == 0 || n + step < NTB) nb_arrive(4 + wg, 288);
        if (lane == 0) {
          asm volatile("cp.async.bulk.tensor.4d.global.shared::cta.bulk_group [%0, {%2,%3,%4,%5}], [%1];"
                       ::"l"(&mp.oo), "r"(sb + SM_B_ST + wg * 8192 + so), "r"(0), "r"(c1), "r"(c2), "r"(c3 + wg) : "memory");
          asm volatile("cp.async.bulk.commit_group;" ::: "memory");
        }
        __syncwarp();
      }
      so = so == 49152 ? 0 : so + 24576;
    }
    if (lane == 0) asm volatile("cp.async.bulk.wait_group.read 0;" ::: "memory");
  } else if (warp >= 12) {
    const int l = warp - 12;
    int use = 0;
    nb_sync(7, 480);
#pragma unroll 1
    for (int n = blockIdx.x + l * step; n < NTB; n += 3 * step, use++) {
      const int b = n / 56, rem = n - b * 56, par = rem / 14, sg = l + 3 * (use & 1);
      int v; uint32_t spin = 0;
      do { asm volatile("ld.acquire.gpu.global.s32 %0, [%1];" : "=r"(v) : "l"(g_flags + n) : "memory"); } while (v < 4 && ++spin < SPIN_LIMIT);
      TRB(use * 3 + l, 0);
      asm volatile("fence.proxy.async.global;" ::: "memory");
      if (use >= 2) mbar_wait(bar + (NSTB + sg) * 8, ((use >> 1) - 1) & 1);
      TRB(use * 3 + l, 1);
      if (elect_one()) {
        mbar_expect(bar + sg * 8, 24576);
        asm volatile("cp.async.bulk.tensor.3d.shared::cluster.global.mbarrier::complete_tx::bytes [%0], [%1, {%3,%4,%5}], [%2];"
                     ::"r"(sb + SM_B_IN + sg * 24576), "l"(&mp.oi), "r"(bar + sg * 8), "r"((par & 1) * 192), "r"(8 * b), "r"((par >> 1) * 112 + (rem - par * 14) * 8) : "memory");
        g_flags[n] = 0;
      }
      __syncwarp();
    }
  } else {
    const int wg = warp >> 2, w = warp & 3;
    uint32_t a[48];
    mbar_wait(bar + 2 * NSTB * 8, 0);
    {
      const int k = (lane & 7) + (lane >> 4) * 8, ch = (warp & 1) * 2 + ((lane >> 3) & 1);
      const uint32_t wa = sb + SM_B_W + (warp >> 1) * 12288 + k * 64 + ((ch ^ ((k >> 1) & 3)) * 16);
#pragma unroll
      for (int i = 0; i < 12; i++)
        asm volatile("ldmatrix.sync.aligned.m8n8.x4.trans.shared.b16 {%0,%1,%2,%3}, [%4];"
                     : "=r"(a[4 * i]), "=r"(a[4 * i + 1]), "=r"(a[4 * i + 2]), "=r"(a[4 * i + 3]) : "r"(wa + i * 1024) : "memory");
    }
    nb_sync(7, 480);
    TRB(47, 1);
    const uint32_t sta = opq(sb + SM_B_ST + wg * 8192 + ((lane & 7) + (lane >> 4) * 8) * 128 + (((2 * w + ((lane >> 3) & 1)) ^ (lane & 7)) * 16));
    const uint32_t hi = opq((uint32_t)(mkdesc(0, 0, 3072, 0) >> 32) + (blockIdx.x >> 16)), bb = opq(bar);
    const uint32_t nbT = opq((uint32_t)(4 + wg)), nbN = opq((uint32_t)(wg == 2 ? 4 : 5 + wg)), nbD = opq((uint32_t)(1 + wg));
    int left = (NTB - blockIdx.x + step - 1) / step;
    if (wg == 2) nb_arrive(4, 288);
#pragma unroll 1
    for (uint32_t ph = 0;; ph ^= 1) {
#pragma unroll
      for (int sg = 0; sg < NSTB; sg++) {
        constexpr uint64_t db = mkdesc(SBC + SM_B_IN, 128, 3072, 0);
        float D[32];
        mbar_wait(bb + sg * 8, ph);
        nb_sync(nbT, 288);
        wg_fence();
        wg_rs64<0>(D, a[0], a[1], a[2], a[3], dsc(db + sg * 1536, hi));
#pragma unroll
        for (int k = 1; k < 12; k++) wg_rs64<1>(D, a[4 * k], a[4 * k + 1], a[4 * k + 2], a[4 * k + 3], dsc(db + sg * 1536 + k * 16, hi));
        wg_commit();
        nb_arrive(nbN, 288);
        wg_wait<0>(); pin(D);
        mbar_arrive_elect(bb + (NSTB + sg) * 8);
#pragma unroll
        for (int q = 0; q < 4; q++)
          asm volatile("stmatrix.sync.aligned.m8n8.x4.trans.shared.b16 [%0], {%1,%2,%3,%4};" ::"r"(sta + (sg % 3) * 24576 + q * 2048),
                       "r"(pack2(D[8 * q], D[8 * q + 1])), "r"(pack2(D[8 * q + 2], D[8 * q + 3])), "r"(pack2(D[8 * q + 4], D[8 * q + 5])), "r"(pack2(D[8 * q + 6], D[8 * q + 7])) : "memory");
        fence_async();
        nb_arrive(nbD, 160);
        if (wg == 0) TRB(31 - left, 5);
        if (--left == 0) goto done;
      }
    }
  done:
    if (wg == 0) nb_arrive(4, 288);
    TR2(132 + blockIdx.x, 2);
  }
}

typedef CUresult (*EncodeFn)(CUtensorMap*, CUtensorMapDataType, cuuint32_t, void*, const cuuint64_t*, const cuuint64_t*, const cuuint32_t*,
                             const cuuint32_t*, CUtensorMapInterleave, CUtensorMapSwizzle, CUtensorMapL2promotion, CUtensorMapFloatOOBfill);
static EncodeFn g_enc = nullptr;
static void make_map(CUtensorMap* m, const void* p, int rank, const cuuint64_t* dim, const cuuint64_t* str, const cuuint32_t* box, CUtensorMapSwizzle sw) {
  const cuuint32_t ones[5] = {1, 1, 1, 1, 1};
  g_enc(m, CU_TENSOR_MAP_DATA_TYPE_BFLOAT16, rank, (void*)p, dim, str, box, ones, CU_TENSOR_MAP_INTERLEAVE_NONE, sw,
        CU_TENSOR_MAP_L2_PROMOTION_L2_128B, CU_TENSOR_MAP_FLOAT_OOB_FILL_NONE);
}

extern "C" void kernel_launch(void* const* d_in, const int* in_sizes, int n_in, void* d_out, int out_size) {
  const __nv_bfloat16* x = (const __nv_bfloat16*)d_in[0];
  const __nv_bfloat16* wqkv = (const __nv_bfloat16*)d_in[1];
  const __nv_bfloat16* wo = (const __nv_bfloat16*)d_in[2];
  const __nv_bfloat16* rpb = (const __nv_bfloat16*)d_in[3];

  if (!g_enc) {
    void* fn = nullptr; cudaDriverEntryPointQueryResult qr;
    cudaGetDriverEntryPoint("cuTensorMapEncodeTiled", &fn, cudaEnableDefault, &qr);
    g_enc = (EncodeFn)fn;
    cudaFuncSetAttribute(na_attn_kernel, cudaFuncAttributeMaxDynamicSharedMemorySize, SM_A_TOTAL);
    cudaFuncSetAttribute(na_proj_kernel, cudaFuncAttributeMaxDynamicSharedMemorySize, SM_B_TOTAL);
  }
  Maps ma; MapsB mb;
  { cuuint64_t dim[4] = {64, 112, 224, 6}, str[3] = {(cuuint64_t)ROWB, 768, 128};
    cuuint32_t box[4] = {64, 4, 16, 3}, boxo[4] = {64, 8, 8, 1};
    make_map(&ma.xc, x, 4, dim, str, box, CU_TENSOR_MAP_SWIZZLE_128B);
    make_map(&mb.oo, d_out, 4, dim, str, boxo, CU_TENSOR_MAP_SWIZZLE_128B); }
  { cuuint64_t dim[5] = {64, 112, 224, 2, 6}, str[4] = {(cuuint64_t)ROWB, 768, 19 * 768, 128};
    cuuint32_t box[5] = {64, 8, 3, 2, 3};
    make_map(&ma.xh, x, 5, dim, str, box, CU_TENSOR_MAP_SWIZZLE_128B); }
  { cuuint64_t dim[3] = {384, 112, 224}, str[2] = {(cuuint64_t)ROWB, 768};
    cuuint32_t box[3] = {192, 8, 8}, boxs[3] = {192, 2, 16};
    make_map(&mb.oi, d_out, 3, dim, str, box, CU_TENSOR_MAP_SWIZZLE_NONE);
    make_map(&ma.os, d_out, 3, dim, str, boxs, CU_TENSOR_MAP_SWIZZLE_NONE); }
  { cuuint64_t dim[4] = {32, 112, 224, 12}, str[3] = {(cuuint64_t)ROWB, 768, 64};
    cuuint32_t box[4] = {32, 8, 2, 3};
    make_map(&ma.ot, d_out, 4, dim, str, box, CU_TENSOR_MAP_SWIZZLE_64B); }
  { cuuint64_t dim[2] = {576, 192}, str[1] = {1152};
    cuuint32_t box[2] = {16, 192};
    make_map(&ma.w, wqkv, 2, dim, str, box, CU_TENSOR_MAP_SWIZZLE_32B); }
  { cuuint64_t dim[3] = {32, 192, 6}, str[2] = {384, 64};
    cuuint32_t box[3] = {32, 192, 3};
    make_map(&ma.wo, wo, 3, dim, str, box, CU_TENSOR_MAP_SWIZZLE_64B);
    mb.wo = ma.wo; }
  na_attn_kernel<<<112, 512, SM_A_TOTAL>>>(x, wqkv, rpb, ma);
  cudaLaunchConfig_t cfg = {};
  cfg.gridDim = dim3(20); cfg.blockDim = dim3(512); cfg.dynamicSmemBytes = SM_B_TOTAL; cfg.stream = cudaStreamPerThread;
  cudaLaunchAttribute at[1];
  at[0].id = cudaLaunchAttributeProgrammaticStreamSerialization; at[0].val.programmaticStreamSerializationAllowed = 1;
  cfg.attrs = at; cfg.numAttrs = 1;
  cudaLaunchKernelEx(&cfg, na_proj_kernel, mb);
}
```

```cpp
#include <cuda_runtime.h>
#include <cuda_bf16.h>
#include <cuda.h>
#include <stdint.h>

#define SPIN_LIMIT (1u << 18)

__device__ __forceinline__ uint32_t smem_u32(const void* p) { return (uint32_t)__cvta_generic_to_shared(p); }
__device__ __forceinline__ void wg_fence() { asm volatile("wgmma.fence.sync.aligned;" ::: "memory"); }
__device__ __forceinline__ void wg_commit() { asm volatile("wgmma.commit_group.sync.aligned;" ::: "memory"); }
template <int N> __device__ __forceinline__ void wg_wait() { asm volatile("wgmma.wait_group.sync.aligned %0;" ::"n"(N) : "memory"); }
template <int N> __device__ __forceinline__ void pin(float (&d)[N]) {
#pragma unroll
  for (int i = 0; i < N; i++) asm volatile("" : "+f"(d[i])::"memory");
}
__host__ __device__ constexpr uint64_t mkdesc(uint32_t addr, uint32_t lbo, uint32_t sbo, uint32_t sw) {
  return (uint64_t)((addr & 0x3FFFF) >> 4) | ((uint64_t)(lbo >> 4) << 16) | ((uint64_t)(sbo >> 4) << 32) | ((uint64_t)sw << 62);
}
__device__ __forceinline__ void mbar_init(uint32_t bar, uint32_t cnt) { asm volatile("mbarrier.init.shared::cta.b64 [%0], %1;" ::"r"(bar), "r"(cnt) : "memory"); }
__device__ __forceinline__ void mbar_arrive(uint32_t bar) { asm volatile("mbarrier.arrive.shared::cta.b64 _, [%0];" ::"r"(bar) : "memory"); }
__device__ __forceinline__ bool elect_one() {
  uint32_t r; asm volatile("{\n.reg .pred p;\nelect.sync _|p, 0xffffffff;\nselp.u32 %0, 1, 0, p;\n}" : "=r"(r)); return r;
}
__device__ __forceinline__ void mbar_arrive_elect(uint32_t bar) {
  asm volatile("{\n.reg .pred p;\nelect.sync _|p, 0xffffffff;\n@p mbarrier.arrive.shared::cta.b64 _, [%0];\n}" ::"r"(bar) : "memory");
}
__device__ __forceinline__ void mbar_expect(uint32_t bar, uint32_t bytes) { asm volatile("mbarrier.arrive.expect_tx.shared::cta.b64 _, [%0], %1;" ::"r"(bar), "r"(bytes) : "memory"); }
__device__ __forceinline__ void mbar_arrive_remote(uint32_t bar, uint32_t cta) {
  asm volatile("{\n.reg .b32 ra;\nmapa.shared::cluster.u32 ra, %0, %1;\nmbarrier.arrive.relaxed.cluster.shared::cluster.b64 _, [ra];\n}" ::"r"(bar), "r"(cta) : "memory");
}
__device__ __forceinline__ void mbar_wait(uint32_t bar, uint32_t parity) {
  asm volatile("{\n.reg .pred p;\n.reg .b32 n;\nmov.b32 n, 0;\nWL:\nmbarrier.try_wait.parity.shared::cta.b64 p, [%0], %1;\n@p bra WD;\n"
               "add.u32 n, n, 1;\nsetp.lt.u32 p, n, 65536;\n@p bra WL;\nWD:\n}" ::"r"(bar), "r"(parity) : "memory");
}
__device__ __forceinline__ void nb_sync(int id, int n) { asm volatile("bar.sync %0, %1;" ::"r"(id), "r"(n) : "memory"); }
__device__ __forceinline__ void nb_arrive(int id, int n) { asm volatile("bar.arrive %0, %1;" ::"r"(id), "r"(n) : "memory"); }
__device__ __forceinline__ uint32_t opq(uint32_t x) { uint32_t r; asm volatile("mov.b32 %0, %1;" : "=r"(r) : "r"(x)); return r; }
__device__ __forceinline__ uint64_t opq(uint64_t x) { uint64_t r; asm volatile("mov.b64 %0, %1;" : "=l"(r) : "l"(x)); return r; }
__device__ __forceinline__ uint32_t mapa(uint32_t a, uint32_t cta) { uint32_t r; asm("mapa.shared::cluster.u32 %0, %1, %2;" : "=r"(r) : "r"(a), "r"(cta)); return r; }
__device__ __forceinline__ void fence_async() { asm volatile("fence.proxy.async.shared::cta;" ::: "memory"); }
__device__ __forceinline__ void cluster_sync() {
  asm volatile("barrier.cluster.arrive.relaxed.aligned;\nbarrier.cluster.wait.aligned;" ::: "memory");
}
__device__ __forceinline__ uint32_t pack2(float lo, float hi) {
  uint32_t r; asm("cvt.rn.bf16x2.f32 %0, %1, %2;" : "=r"(r) : "f"(hi), "f"(lo)); return r;
}
__device__ __forceinline__ void stsm4(uint32_t a, uint32_t r0, uint32_t r1, uint32_t r2, uint32_t r3) {
  asm volatile("stmatrix.sync.aligned.m8n8.x4.shared.b16 [%0], {%1,%2,%3,%4};" ::"r"(a), "r"(r0), "r"(r1), "r"(r2), "r"(r3) : "memory");
}
__device__ __forceinline__ void ldsm4(uint32_t a, uint32_t& r0, uint32_t& r1, uint32_t& r2, uint32_t& r3) {
  asm volatile("ldmatrix.sync.aligned.m8n8.x4.shared.b16 {%0,%1,%2,%3}, [%4];" : "=r"(r0), "=r"(r1), "=r"(r2), "=r"(r3) : "r"(a) : "memory");
}
__device__ __forceinline__ void sts128(uint32_t a, uint4 v) {
  asm volatile("st.shared.v4.b32 [%0], {%1,%2,%3,%4};" ::"r"(a), "r"(v.x), "r"(v.y), "r"(v.z), "r"(v.w) : "memory");
}
__device__ __forceinline__ float lds_f32(uint32_t a) { float v; asm volatile("ld.shared.f32 %0, [%1];" : "=f"(v) : "r"(a)); return v; }
__device__ __forceinline__ float ex2(float x) { float y; asm("ex2.approx.ftz.f32 %0, %1;" : "=f"(y) : "f"(x)); return y; }

template<int SC> __device__ __forceinline__ void wg_ss144(float (&d)[72], uint64_t da, uint64_t db) {
  asm volatile("{\n.reg .pred p;\nsetp.ne.b32 p, %74, 0;\nwgmma.mma_async.sync.aligned.m64n144k16.f32.bf16.bf16 {%0,%1,%2,%3,%4,%5,%6,%7,%8,%9,%10,%11,%12,%13,%14,%15,%16,%17,%18,%19,%20,%21,%22,%23,%24,%25,%26,%27,%28,%29,%30,%31,%32,%33,%34,%35,%36,%37,%38,%39,%40,%41,%42,%43,%44,%45,%46,%47,%48,%49,%50,%51,%52,%53,%54,%55,%56,%57,%58,%59,%60,%61,%62,%63,%64,%65,%66,%67,%68,%69,%70,%71}, %72, %73, p, 1, 1, 0, 1;\n}\n"
    : "+f"(d[0]),"+f"(d[1]),"+f"(d[2]),"+f"(d[3]),"+f"(d[4]),"+f"(d[5]),"+f"(d[6]),"+f"(d[7]),"+f"(d[8]),"+f"(d[9]),"+f"(d[10]),"+f"(d[11]),"+f"(d[12]),"+f"(d[13]),"+f"(d[14]),"+f"(d[15]),"+f"(d[16]),"+f"(d[17]),"+f"(d[18]),"+f"(d[19]),"+f"(d[20]),"+f"(d[21]),"+f"(d[22]),"+f"(d[23]),"+f"(d[24]),"+f"(d[25]),"+f"(d[26]),"+f"(d[27]),"+f"(d[28]),"+f"(d[29]),"+f"(d[30]),"+f"(d[31]),"+f"(d[32]),"+f"(d[33]),"+f"(d[34]),"+f"(d[35]),"+f"(d[36]),"+f"(d[37]),"+f"(d[38]),"+f"(d[39]),"+f"(d[40]),"+f"(d[41]),"+f"(d[42]),"+f"(d[43]),"+f"(d[44]),"+f"(d[45]),"+f"(d[46]),"+f"(d[47]),"+f"(d[48]),"+f"(d[49]),"+f"(d[50]),"+f"(d[51]),"+f"(d[52]),"+f"(d[53]),"+f"(d[54]),"+f"(d[55]),"+f"(d[56]),"+f"(d[57]),"+f"(d[58]),"+f"(d[59]),"+f"(d[60]),"+f"(d[61]),"+f"(d[62]),"+f"(d[63]),"+f"(d[64]),"+f"(d[65]),"+f"(d[66]),"+f"(d[67]),"+f"(d[68]),"+f"(d[69]),"+f"(d[70]),"+f"(d[71]) : "l"(da), "l"(db), "n"(SC));
}
template<int SC> __device__ __forceinline__ void wg_ss96(float (&d)[48], uint64_t da, uint64_t db) {
  asm volatile("{\n.reg .pred p;\nsetp.ne.b32 p, %50, 0;\nwgmma.mma_async.sync.aligned.m64n96k16.f32.bf16.bf16 {%0,%1,%2,%3,%4,%5,%6,%7,%8,%9,%10,%11,%12,%13,%14,%15,%16,%17,%18,%19,%20,%21,%22,%23,%24,%25,%26,%27,%28,%29,%30,%31,%32,%33,%34,%35,%36,%37,%38,%39,%40,%41,%42,%43,%44,%45,%46,%47}, %48, %49, p, 1, 1, 0, 1;\n}\n"
    : "+f"(d[0]),"+f"(d[1]),"+f"(d[2]),"+f"(d[3]),"+f"(d[4]),"+f"(d[5]),"+f"(d[6]),"+f"(d[7]),"+f"(d[8]),"+f"(d[9]),"+f"(d[10]),"+f"(d[11]),"+f"(d[12]),"+f"(d[13]),"+f"(d[14]),"+f"(d[15]),"+f"(d[16]),"+f"(d[17]),"+f"(d[18]),"+f"(d[19]),"+f"(d[20]),"+f"(d[21]),"+f"(d[22]),"+f"(d[23]),"+f"(d[24]),"+f"(d[25]),"+f"(d[26]),"+f"(d[27]),"+f"(d[28]),"+f"(d[29]),"+f"(d[30]),"+f"(d[31]),"+f"(d[32]),"+f"(d[33]),"+f"(d[34]),"+f"(d[35]),"+f"(d[36]),"+f"(d[37]),"+f"(d[38]),"+f"(d[39]),"+f"(d[40]),"+f"(d[41]),"+f"(d[42]),"+f"(d[43]),"+f"(d[44]),"+f"(d[45]),"+f"(d[46]),"+f"(d[47]) : "l"(da), "l"(db), "n"(SC));
}
template<int SC> __device__ __forceinline__ void wg_rs112(float (&d)[56], uint32_t a0, uint32_t a1, uint32_t a2, uint32_t a3, uint64_t db) {
  asm volatile("{\n.reg .pred p;\nsetp.ne.b32 p, %61, 0;\nwgmma.mma_async.sync.aligned.m64n112k16.f32.bf16.bf16 {%0,%1,%2,%3,%4,%5,%6,%7,%8,%9,%10,%11,%12,%13,%14,%15,%16,%17,%18,%19,%20,%21,%22,%23,%24,%25,%26,%27,%28,%29,%30,%31,%32,%33,%34,%35,%36,%37,%38,%39,%40,%41,%42,%43,%44,%45,%46,%47,%48,%49,%50,%51,%52,%53,%54,%55}, {%56,%57,%58,%59}, %60, p, 1, 1, 0;\n}\n"
    : "+f"(d[0]),"+f"(d[1]),"+f"(d[2]),"+f"(d[3]),"+f"(d[4]),"+f"(d[5]),"+f"(d[6]),"+f"(d[7]),"+f"(d[8]),"+f"(d[9]),"+f"(d[10]),"+f"(d[11]),"+f"(d[12]),"+f"(d[13]),"+f"(d[14]),"+f"(d[15]),"+f"(d[16]),"+f"(d[17]),"+f"(d[18]),"+f"(d[19]),"+f"(d[20]),"+f"(d[21]),"+f"(d[22]),"+f"(d[23]),"+f"(d[24]),"+f"(d[25]),"+f"(d[26]),"+f"(d[27]),"+f"(d[28]),"+f"(d[29]),"+f"(d[30]),"+f"(d[31]),"+f"(d[32]),"+f"(d[33]),"+f"(d[34]),"+f"(d[35]),"+f"(d[36]),"+f"(d[37]),"+f"(d[38]),"+f"(d[39]),"+f"(d[40]),"+f"(d[41]),"+f"(d[42]),"+f"(d[43]),"+f"(d[44]),"+f"(d[45]),"+f"(d[46]),"+f"(d[47]),"+f"(d[48]),"+f"(d[49]),"+f"(d[50]),"+f"(d[51]),"+f"(d[52]),"+f"(d[53]),"+f"(d[54]),"+f"(d[55]) : "r"(a0), "r"(a1), "r"(a2), "r"(a3), "l"(db), "n"(SC));
}
template<int SC> __device__ __forceinline__ void wg_sp48(float (&d)[24], uint32_t a0, uint32_t a1, uint32_t a2, uint32_t a3, uint64_t db, uint32_t meta) {
  asm volatile("{\n.reg .pred p;\nsetp.ne.b32 p, %30, 0;\nwgmma.mma_async.sp.sync.aligned.m64n48k32.f32.bf16.bf16 {%0,%1,%2,%3,%4,%5,%6,%7,%8,%9,%10,%11,%12,%13,%14,%15,%16,%17,%18,%19,%20,%21,%22,%23}, {%24,%25,%26,%27}, %28, %29, 0, p, 1, 1, 1;\n}\n"
    : "+f"(d[0]),"+f"(d[1]),"+f"(d[2]),"+f"(d[3]),"+f"(d[4]),"+f"(d[5]),"+f"(d[6]),"+f"(d[7]),"+f"(d[8]),"+f"(d[9]),"+f"(d[10]),"+f"(d[11]),"+f"(d[12]),"+f"(d[13]),"+f"(d[14]),"+f"(d[15]),"+f"(d[16]),"+f"(d[17]),"+f"(d[18]),"+f"(d[19]),"+f"(d[20]),"+f"(d[21]),"+f"(d[22]),"+f"(d[23]) : "r"(a0), "r"(a1), "r"(a2), "r"(a3), "l"(db), "r"(meta), "n"(SC));
}
template<int SC> __device__ __forceinline__ void wg_rs64(float (&d)[32], uint32_t a0, uint32_t a1, uint32_t a2, uint32_t a3, uint64_t db) {
  asm volatile("{\n.reg .pred p;\nsetp.ne.b32 p, %37, 0;\nwgmma.mma_async.sync.aligned.m64n64k16.f32.bf16.bf16 {%0,%1,%2,%3,%4,%5,%6,%7,%8,%9,%10,%11,%12,%13,%14,%15,%16,%17,%18,%19,%20,%21,%22,%23,%24,%25,%26,%27,%28,%29,%30,%31}, {%32,%33,%34,%35}, %36, p, 1, 1, 0;\n}\n"
    : "+f"(d[0]),"+f"(d[1]),"+f"(d[2]),"+f"(d[3]),"+f"(d[4]),"+f"(d[5]),"+f"(d[6]),"+f"(d[7]),"+f"(d[8]),"+f"(d[9]),"+f"(d[10]),"+f"(d[11]),"+f"(d[12]),"+f"(d[13]),"+f"(d[14]),"+f"(d[15]),"+f"(d[16]),"+f"(d[17]),"+f"(d[18]),"+f"(d[19]),"+f"(d[20]),"+f"(d[21]),"+f"(d[22]),"+f"(d[23]),"+f"(d[24]),"+f"(d[25]),"+f"(d[26]),"+f"(d[27]),"+f"(d[28]),"+f"(d[29]),"+f"(d[30]),"+f"(d[31]) : "r"(a0), "r"(a1), "r"(a2), "r"(a3), "l"(db), "n"(SC));
}

constexpr uint32_t SBC = 1024;
constexpr int ROWB = 2 * 224 * 384;
constexpr int TB = 11;
constexpr int KS = 832;
constexpr int KSLOT = 22 * KS;
constexpr int SM_X2 = 0;
constexpr int SM_X0 = SM_X2 + 24576;
constexpr int SM_W = SM_X0 + 18432;
constexpr int SM_X1 = SM_W + 55296;
constexpr int SM_K = SM_X1 + 24576;
constexpr int SM_V = SM_K + 2 * KSLOT;
constexpr int SM_Q = SM_V + 22 * 1536;
constexpr int SM_O = SM_Q + 24576;
constexpr int SM_RPB = SM_O + 12288;
constexpr int SM_BAR = SM_RPB + 768;
constexpr int SM_A_TOTAL = SM_BAR + 256;
constexpr int SM_TIN = 0;
constexpr int SM_TST = 3 * 24576;
constexpr int SM_TWO = SM_TST + 12288;
enum { B_FULL = 0, B_EMPTY = 3, B_TIN = 6, B_TFREE = 10, B_WK = 12, B_WQ, B_WO, B_Q0, B_WOFREE, B_OTAIL, B_ODONE = B_OTAIL + 2, B_KFREE, B_VFREE, B_COUNT };
enum { N_KRDY = 4, N_QK0, N_QK1, N_VQ0, N_VQ1, N_PVISS };

#define NL 2
#define OPT 0
#define SPL 4
#define RA 160
#define RG 168
__device__ int g_flags[TB * 56];

#define TR(role, it, k)
#define TRDECL
#define TRARG
#define TRPASS
#define TRDUMP
#define TRB(it, k)
#define TR2(blk, k)

struct GemmCtx {
  uint32_t bar;
  uint32_t kC, vC[2], qC[2];
  uint32_t kH, vH[2];
  uint32_t hiA, hiB;
  uint32_t spin;
  bool hvalid, never;
};

template <int STRIDE> __device__ __forceinline__ void dump12(uint32_t a, const uint32_t (&r)[12]) {
#pragma unroll
  for (int j = 0; j < 3; j++) stsm4(a + j * 2 * STRIDE, r[4 * j], r[4 * j + 1], r[4 * j + 2], r[4 * j + 3]);
}
__device__ __forceinline__ void keep12(bool never, uint32_t a, const uint32_t (&r)[12]) { if (never) dump12<128>(a, r); }
template <int N> __device__ __forceinline__ void pack12(uint32_t (&r)[12], const float (&d)[N], int off) {
#pragma unroll
  for (int j = 0; j < 12; j++) r[j] = pack2(d[off + 2 * j], d[off + 2 * j + 1]);
}
__device__ __forceinline__ uint64_t dsc(uint64_t lo, uint32_t hi) { uint64_t r; asm("mov.b64 %0, {%1, %2};" : "=l"(r) : "r"((uint32_t)lo), "r"(hi)); return r; }
template <int XS, int K0, int K1> __device__ __forceinline__ void issue_core(const GemmCtx& c, float (&d)[72]) {
  constexpr uint64_t da = mkdesc(SBC + XS, 16, 1024, 1), db = mkdesc(SBC + SM_W, 6144, 256, 3);
  wg_fence();
  if (K0 == 0) wg_ss144<0>(d, dsc(da, c.hiA), dsc(db, c.hiB));
#pragma unroll
  for (int k = K0 ? K0 : 1; k < K1; k++) wg_ss144<1>(d, dsc(da + (k >> 2) * 512 + (k & 3) * 2, c.hiA), dsc(db + k * 32, c.hiB));
  wg_commit();
}
template <int K0, int K1> __device__ __forceinline__ void issue_halo(const GemmCtx& c, float (&d)[48]) {
  constexpr uint64_t da = mkdesc(SBC + SM_X0 - 2048, 16, 1024, 1), db = mkdesc(SBC + SM_W, 6144, 256, 3);
  wg_fence();
  if (K0 == 0) wg_ss96<0>(d, dsc(da, c.hiA), dsc(db, c.hiB));
#pragma unroll
  for (int k = K0 ? K0 : 1; k < K1; k++) wg_ss96<1>(d, dsc(da + (k >> 2) * 384 + (k & 3) * 2, c.hiA), dsc(db + k * 32, c.hiB));
  wg_commit();
}
template <int ST> __device__ __forceinline__ void release_stage(const GemmCtx& c) {
  asm volatile("{\n.reg .pred p;\n.reg .b32 ra;\nelect.sync _|p, 0xffffffff;\nmapa.shared::cluster.u32 ra, %0, %1;\n"
               "@p mbarrier.arrive.shared::cluster.b64 _, [ra];\n}" ::"r"(c.bar + (B_EMPTY + ST) * 8), "n"(ST) : "memory");
}
template <int PARITY> __device__ __forceinline__ void gwait(GemmCtx& c, int bar) {
  asm volatile("{\n.reg .pred p;\nWL:\nmbarrier.try_wait.parity.shared::cta.b64 p, [%1], %2;\n@p bra WD;\n"
               "add.u32 %0, %0, 1;\nsetp.lt.u32 p, %0, 0x100000;\n@p bra WL;\nWD:\n}" : "+r"(c.spin) : "r"(c.bar + bar * 8), "n"(PARITY) : "memory");
}
__device__ __forceinline__ void load_w(const CUtensorMap* m, uint32_t dst, uint32_t bar, int col) {
  asm volatile("cp.async.bulk.tensor.2d.shared::cluster.global.mbarrier::complete_tx::bytes [%0], [%1, {%3,%4}], [%2];"
               ::"r"(dst), "l"(m), "r"(bar), "r"(col), "r"(0) : "memory");
}
template <int BYTES> __device__ __forceinline__ void send_o(uint32_t dst, uint32_t src, uint32_t bar, int cta) {
  asm volatile("{\n.reg .b32 rd, rb;\nmapa.shared::cluster.u32 rd, %0, %3;\nmapa.shared::cluster.u32 rb, %2, %3;\n"
               "cp.async.bulk.shared::cluster.shared::cta.mbarrier::complete_tx::bytes [rd], [%1], %4, [rb];\n}"
               ::"r"(dst), "r"(src), "r"(bar), "r"(cta), "n"(BYTES) : "memory");
}
__device__ __forceinline__ void tail_free(uint32_t bar) {
  uint32_t ln; asm volatile("mov.u32 %0, %%laneid;" : "=r"(ln));
  if (ln < 4) mbar_arrive_remote(bar, ln);
}
__device__ __forceinline__ void publish(uint32_t bar) {
  fence_async();
  __syncwarp();
  mbar_arrive_elect(bar);
}

template <bool FIRST, int PA>
__device__ __forceinline__ void gemm_iter(GemmCtx& c, int b, uint32_t (&pk)[12], uint32_t (&pv)[12], uint32_t (&pq)[12] TRARG) {
  const uint32_t bar = c.bar;
  const bool w = !FIRST && (PA == 0 || b >= 0), never = c.never;
  constexpr uint32_t ko = PA * KSLOT;
  float H[48], C[72];
  uint32_t hk[12], hv[12], pv2[12];
  TR(2, b, 0);
  if (FIRST) gwait<PA>(c, B_FULL + 0);
  if (!FIRST) dump12<256>(c.qC[1] + (PA ^ 1) * 128, pq);
  if (w) nb_sync(N_QK1, 256);
  TR(2, b, 2);
  if (FIRST) TR(2, b - 1, 6);
  issue_halo<0, 8>(c, H);
  TR(2, b, 3);
  if (!FIRST) {
    if (w) gwait<PA>(c, B_KFREE);
    dump12<128>(c.kC + ko, pk);
  }
  issue_halo<8, 12>(c, H);
  TR(2, b, 4);
  {
    gwait<PA>(c, B_FULL + 2);
    if (FIRST && NL == 2) gwait<0>(c, B_WQ);
    TR(2, b, 13);
    if (FIRST) TR(2, b - 1, 7);
    issue_core<SM_X2, 0, 8>(c, C);
    TR(2, b, 5);
    if (!FIRST) { fence_async(); keep12(never, c.kC, pk); }
    wg_wait<1>(); pin(H);
    release_stage<0>(c);
  }
  pack12(hk, H, 0);
  if (c.hvalid) dump12<128>(c.kH + ko, hk);
  pack12(hv, H, 24);
  {
    issue_core<SM_X2, 8, 12>(c, C);
    if (w) { nb_arrive(N_VQ0, 288); nb_arrive(N_VQ1, 288); }
    else if (!FIRST) { __syncwarp(); mbar_arrive_elect(bar + B_Q0 * 8); }
    gwait<PA>(c, B_FULL + 1);
    keep12(never, c.kC, hk);
    TR(2, b, 6);
    wg_wait<0>(); pin(C);
    TR(2, b, 7);
    pack12(pk, C, 0);
    dump12<128>(c.kC + ko + 64, pk);
    release_stage<2>(c);
    pack12(pv2, C, 24);
    pack12(pq, C, 48);
    TR(2, b, 8);
    issue_core<SM_X1, 0, SPL>(c, C);
    if (w) nb_sync(N_PVISS, 384);
    issue_core<SM_X1, SPL, 8>(c, C);
    TR(2, b, 9);
  }
  if (!FIRST) fence_async();
  keep12(never, c.kC, pk);
  TR(2, b, 14);
  issue_core<SM_X1, 8, 12>(c, C);
  if (!FIRST) nb_arrive(N_KRDY, 256);
  TR(2, b, 1);
  if (PA && b == 11) tail_free(bar + B_TFREE * 8);
  gwait<PA ^ 1>(c, B_FULL + 0);
  if (w) gwait<PA>(c, B_VFREE);
  TR(2, b, 10);
  if (!FIRST) dump12<128>(c.vC[PA], pv);
  dump12<256>(c.qC[0] + PA * 128, pq);
  if (c.hvalid) dump12<128>(c.vH[PA], hv);
  dump12<128>(c.vC[PA ^ 1] + 768, pv2);
  TR(2, b, 11);
  wg_wait<0>(); pin(C);
  TR(2, b, 12);
  release_stage<1>(c);
  pack12(pk, C, 0);
  pack12(pv, C, 24);
  pack12(pq, C, 48);
}

template <int IN> __device__ __forceinline__ void issue_proj(float (&D)[48]) {
  constexpr uint64_t da = mkdesc(SBC + IN, 128, 768, 0), db = mkdesc(SBC + SM_TWO, 12288, 512, 2);
  wg_fence();
  wg_ss96<0>(D, da, db);
#pragma unroll
  for (int k = 1; k < 12; k++) wg_ss96<1>(D, da + (k / 3) * 384 + (k % 3) * 16, db + k * 64);
  wg_commit();
}
template <int ACC> __device__ __forceinline__ void issue_proj_half(float (&D)[48], int hd) {
  const uint64_t da = mkdesc(SBC + SM_TIN + 2 * 24576, 128, 768, 0) + hd * 384, db = mkdesc(SBC + SM_TWO, 12288, 512, 2) + hd * 192;
  wg_fence();
  wg_ss96<ACC>(D, da, db);
#pragma unroll
  for (int k = 1; k < 6; k++) wg_ss96<1>(D, da + (k / 3) * 768 + (k % 3) * 16, db + (k / 3) * 384 + (k % 3) * 64);
  wg_commit();
}
__device__ __forceinline__ void store_proj(const float (&D)[48], const CUtensorMap* m, uint32_t st, uint32_t sta, int row, int col, int ch) {
#pragma unroll
  for (int q = 0; q < 6; q++)
    stsm4((sta ^ ((q & 1) * 32)) + (q >> 1) * 1024,
          pack2(D[8 * q], D[8 * q + 1]), pack2(D[8 * q + 2], D[8 * q + 3]), pack2(D[8 * q + 4], D[8 * q + 5]), pack2(D[8 * q + 6], D[8 * q + 7]));
  fence_async();
  __syncwarp();
  if ((threadIdx.x & 31) == 0) {
    asm volatile("cp.async.bulk.tensor.4d.global.shared::cta.bulk_group [%0, {%2,%3,%4,%5}], [%1];" ::"l"(m), "r"(st), "r"(0), "r"(row), "r"(col), "r"(ch) : "memory");
    asm volatile("cp.async.bulk.commit_group;" ::: "memory");
  }
  __syncwarp();
}

__device__ __forceinline__ float fold(float a, float b, float t, int useb) {
  float r;
  asm("{\n.reg .pred p;\nsetp.ne.b32 p, %4, 0;\nfma.rn.f32 %0, %1, 0f3E553B95, %3;\n@p fma.rn.f32 %0, %2, 0f3E553B95, %3;\n}"
      : "=&f"(r) : "f"(a), "f"(b), "f"(t), "r"(useb));
  return r;
}
template <int U, int L>
__device__ __forceinline__ void softmax_tile(const float (&SA)[56], const float (&SB)[56], const float (&T)[16], int b0, int b1,
                                             uint32_t (&P)[28], float (&sx)[8]) {
  float lu[14], ll[14];
#pragma unroll
  for (int j = 0; j < 7; j++) {
    constexpr int sh = U == L ? 2 : 0;
    const float tu0 = T[2 * j + sh], tu1 = T[2 * j + 1 + sh], tl0 = T[2 * j], tl1 = T[2 * j + 1];
    lu[2 * j]     = fold(SA[4 * (U + j)],     SB[4 * (U + j)],     tu0, b0);
    ll[2 * j]     = fold(SA[4 * (L + j) + 2], SB[4 * (L + j) + 2], tl0, b0);
    lu[2 * j + 1] = fold(SA[4 * (U + j) + 1], SB[4 * (U + j) + 1], tu1, b1);
    ll[2 * j + 1] = fold(SA[4 * (L + j) + 3], SB[4 * (L + j) + 3], tl1, b1);
  }
  float mu = lu[0], ml = ll[0], mu2 = lu[1], ml2 = ll[1];
#pragma unroll
  for (int j = 1; j < 7; j++) { mu = fmaxf(mu, lu[2 * j]); mu2 = fmaxf(mu2, lu[2 * j + 1]); ml = fmaxf(ml, ll[2 * j]); ml2 = fmaxf(ml2, ll[2 * j + 1]); }
  mu = fmaxf(mu, mu2); ml = fmaxf(ml, ml2);
  { const float a1 = __shfl_xor_sync(0xffffffffu, mu, 1), a2 = __shfl_xor_sync(0xffffffffu, mu, 2), a3 = __shfl_xor_sync(0xffffffffu, mu, 3);
    const float c1 = __shfl_xor_sync(0xffffffffu, ml, 1), c2 = __shfl_xor_sync(0xffffffffu, ml, 2), c3 = __shfl_xor_sync(0xffffffffu, ml, 3);
    mu = fmaxf(fmaxf(mu, a1), fmaxf(a2, a3)); ml = fmaxf(fmaxf(ml, c1), fmaxf(c2, c3)); }
  float su = 0.f, sl = 0.f;
#pragma unroll
  for (int c = 0; c < 14; c++) {
    const int iu = (c >> 1) * 4 + (c & 1) * 2;
    if (c >= U && c < U + 7) {
      float e0 = ex2(lu[2 * (c - U)] - mu), e1 = ex2(lu[2 * (c - U) + 1] - mu);
      su = c == U ? e0 + e1 : (su + e0) + e1; P[iu] = pack2(e0, e1);
    } else P[iu] = 0u;
    if (c >= L && c < L + 7) {
      float e0 = ex2(ll[2 * (c - L)] - ml), e1 = ex2(ll[2 * (c - L) + 1] - ml);
      sl = c == L ? e0 + e1 : (sl + e0) + e1; P[iu + 1] = pack2(e0, e1);
    } else P[iu + 1] = 0u;
  }
  sx[0] = su; sx[4] = sl;
#pragma unroll
  for (int k = 1; k < 4; k++) { sx[k] = __shfl_xor_sync(0xffffffffu, su, k); sx[4 + k] = __shfl_xor_sync(0xffffffffu, sl, k); }
}

struct BandCfg { uint32_t ra0, ra1, meta; int b0, b1; };
__device__ __forceinline__ void band_cfg(int b, uint32_t tb, BandCfg& n) {
  uint32_t ln; asm volatile("mov.u32 %0, %%laneid;" : "=r"(ln));
  const int g = ln >> 2, t = ln & 3;
  const int sw = min(max(g + 1, b == 0 ? 4 : 0), b == 13 ? 5 : 8);
  const int i0 = 2 * t, i1 = 2 * t + 1;
  n.b0 = i0 <= sw - 2; n.b1 = i1 <= sw - 2;
  n.ra0 = tb + (i0 == sw - 1 ? 13 : i0 + 8 * n.b0 - g + 2) * 52;
  n.ra1 = tb + (i1 == sw - 1 ? 13 : i1 + 8 * n.b1 - g + 2) * 52;
  n.meta = ((0x5555u & ((1u << (2 * (sw - 1))) - 1)) ^ 0xDD88u ^ (((t ^ b) & 1) ? 0x5555u : 0u)) * 0x10001u;
}
__device__ __forceinline__ void band_load(const BandCfg& n, float (&T)[16], int& b0, int& b1, uint32_t& meta) {
#pragma unroll
  for (int jj = 0; jj < 8; jj++) { T[2 * jj] = lds_f32(n.ra0 + jj * 4); T[2 * jj + 1] = lds_f32(n.ra1 + jj * 4); }
  b0 = n.b0; b1 = n.b1; meta = n.meta;
}

struct Maps { CUtensorMap xc, xh, w, os, wo, ot; };

__global__ void __cluster_dims__(4, 1, 1) __launch_bounds__(512, 1)
na_attn_kernel(const __nv_bfloat16* __restrict__ x, const __nv_bfloat16* __restrict__ wqkv, const __nv_bfloat16* __restrict__ rpb, const __grid_constant__ Maps mp) {
  extern __shared__ __align__(1024) uint8_t smem_raw[];
  const uint32_t sb = smem_u32(smem_raw);
  if ((sb & 0x3FFFF) != SBC) return;
  const uint32_t bar = sb + SM_BAR;
  TR2(blockIdx.x, 0);
  const int tid = threadIdx.x, lane = tid & 31;
  const int warp = __shfl_sync(0xffffffffu, tid >> 5, 0);
  const int head = blockIdx.x & 3, cl = blockIdx.x >> 2;
  const int par = cl / 7, strip = cl - par * 7, ph = par >> 1, pw = par & 1;

  uint4 wv[2 * NL];
  const int va = head == 1;
  const uint32_t wdst = sb + SM_W + (va + ((tid >> 1) & 1)) * 6144 + (tid >> 2) * 32 + ((tid ^ (tid >> 4)) & 1) * 16;
  if (warp < 12) asm volatile("barrier.cluster.arrive.relaxed.aligned;" ::: "memory");
  {
    const uint32_t wo0 = (tid >> 2) * 1152 + head * 96 + va * 32 + (tid & 3) * 16;
#pragma unroll
    for (int i = 0; i < 2 * NL; i++)
      asm volatile("{\n.reg .pred p;\nsetp.lt.u32 p, %5, 384;\n@p ld.global.nc.v4.b32 {%0,%1,%2,%3}, [%4];\n}"
                   : "=r"(wv[i].x), "=r"(wv[i].y), "=r"(wv[i].z), "=r"(wv[i].w)
                   : "l"(reinterpret_cast<const uint8_t*>(wqkv) + wo0 + (i & 1) * 96 * 1152 + ((i / 2 + 1) % 3) * 384), "r"(tid));
  }
  if (warp < 8) {
    asm volatile("setmaxnreg.inc.sync.aligned.u32 %0;" ::"n"(RA));
    float rv = -INFINITY;
    if (tid < 169) rv = __bfloat162float(rpb[head * 169 + tid]) * 1.4426950408889634f;
    if (tid < 192) {
      const int kc = (tid & 15) + 3, wc = (tid >> 4) % 6;
      sts128(tid < 96 ? sb + SM_K + kc * KS + wc * 128 + 48 : sb + SM_V + kc * 1536 + wc * 128 + (6 + (kc & 1)) * 16, make_uint4(0, 0, 0, 0));
    }
#pragma unroll
    for (int i = 0; i < 2 * NL; i++) sts128(wdst + (i & 1) * 3072 + (i / 2) * 18432, wv[i]);
    fence_async();
    asm volatile("bar.arrive 1, 384;" ::: "memory");
    if (tid < 182) asm volatile("st.shared.f32 [%0], %1;" ::"r"(sb + SM_RPB + tid * 4), "f"(rv) : "memory");
    const int j = warp >> 2, w = warp & 3;
    int variant = w;
    if (strip == 0 && j == 0 && w < 2) variant = 4;
    if (strip == 6 && j == 1 && w >= 2) variant = 5;
    const bool v1 = opq((uint32_t)(variant & 1)), v2 = opq((uint32_t)(variant & 2)), v4 = opq((uint32_t)(variant & 4));
    uint32_t qa = opq(sb + SM_Q + (8 * j + 2 * w + ((lane >> 3) & 1)) * 1536 + (lane >> 4) * 256 + (((lane & 7) * 16) ^ (((lane >> 3) & 1) * 64)));
    uint32_t oa = opq(sb + SM_O + j * 6144 + (2 * w + ((lane >> 3) & 1)) * 768 + (lane >> 4) * 128 + (lane & 7) * 16);
    uint64_t dA = opq(mkdesc(SBC + SM_K, 128, KS, 0) + j * (8 * KS / 16)), dB = opq(dA + (KSLOT >> 4));
    uint64_t dV[7];
#pragma unroll
    for (int i = 0; i < 7; i++) dV[i] = opq(mkdesc(SBC + SM_V, 768, 128, 0) + j * (8 * 1536 / 16) + i * 192);
    const uint32_t nbK = opq((uint32_t)(N_KRDY + j)), nbQ = opq((uint32_t)(N_QK0 + j)), nbV = opq((uint32_t)(N_VQ0 + j));
    asm volatile("barrier.cluster.wait.aligned;" ::: "memory");
    asm volatile("bar.sync 3, 256;" ::: "memory");
    float T[16];
    TRDECL;
    int b0, b1;
    uint32_t meta, ob = bar + B_ODONE * 8;
    const uint32_t tb = opq(sb + SM_RPB + (variant < 4 ? 3 : variant + 1 - 2 * w) * 4);
    const bool own = ((w ^ head) & 2) == 0;
    const uint32_t dst13 = sb + SM_TIN + 2 * 24576 + head * 6144 + (2 * j + (w & 1)) * 1536, src13 = opq(own ? dst13 : sb + SM_Q + warp * 3072 + 1536);
    const uint32_t snd[4] = {opq(own ? 0u : mapa(dst13, head ^ 2)), opq(mapa(bar + (B_TIN + 2) * 8, head ^ 2)),
                             opq(mapa(dst13, (w & 2) + (~head & 1))), opq(mapa(bar + (B_TIN + 3) * 8, (w & 2) + (~head & 1)))};
    BandCfg nx;
    band_cfg(0, tb, nx);
    band_load(nx, T, b0, b1, meta);
    meta ^= 0x55555555u;
    band_cfg(1, tb, nx);
    uint32_t q[12];
    mbar_wait(bar + B_Q0 * 8, 0);
#pragma unroll
    for (int k = 0; k < 3; k++) ldsm4(qa + k * 512, q[4 * k], q[4 * k + 1], q[4 * k + 2], q[4 * k + 3]);
#pragma unroll 1
    for (int b = 0; b < 14; b++) {
      float SA[56], SB[56];
      TR(0, b, 0);
      nb_sync(nbK, 256);
      TR(0, b, 1);
      TR(0, b - 1, 9);
      wg_fence();
      wg_rs112<0>(SA, q[0], q[1], q[2], q[3], dA);
      wg_rs112<0>(SB, q[0], q[1], q[2], q[3], dB);
      wg_rs112<1>(SA, q[4], q[5], q[6], q[7], dA + 16);
      wg_rs112<1>(SB, q[4], q[5], q[6], q[7], dB + 16);
      wg_rs112<1>(SA, q[8], q[9], q[10], q[11], dA + 32);
      wg_rs112<1>(SB, q[8], q[9], q[10], q[11], dB + 32);
      wg_commit();
      nb_arrive(nbQ, 256);
      { const uint64_t t = dA; dA = dB; dB = t; }
      qa ^= 128;
      meta ^= 0x55555555u;
      if (b == 1 || b == 13) band_load(nx, T, b0, b1, meta);
      if (b >= TB) {
        ob = opq(bar + (b == 13 && own ? B_TIN + 2 : B_OTAIL + j) * 8);
        oa += b == 12 ? warp * 1536 - (SM_O - SM_Q) : (b == 13 ? src13 - (sb + SM_Q + warp * 3072) : 0);
      }
      TR(0, b, 2);
      wg_wait<0>(); pin(SA); pin(SB);
      mbar_arrive_elect(bar + B_KFREE * 8);
      TR(0, b, 3);
      TR(0, b - 1, 10);
      uint32_t P[28];
      float sx[8];
      if (v2) {
        if (v1) softmax_tile<6, 7>(SA, SB, T, b0, b1, P, sx); else softmax_tile<4, 5>(SA, SB, T, b0, b1, P, sx);
      } else if (!v4) {
        if (v1) softmax_tile<2, 3>(SA, SB, T, b0, b1, P, sx); else softmax_tile<0, 1>(SA, SB, T, b0, b1, P, sx);
      } else {
        if (v1) softmax_tile<4, 4>(SA, SB, T, b0, b1, P, sx); else softmax_tile<3, 3>(SA, SB, T, b0, b1, P, sx);
      }
      float O[24];
      TR(0, b, 4);
      if (b == 3) band_cfg(13, tb, nx);
      nb_sync(nbV, 288);
      TR(0, b, 5);
#pragma unroll
      for (int k = 0; k < 3; k++) ldsm4(qa + k * 512, q[4 * k], q[4 * k + 1], q[4 * k + 2], q[4 * k + 3]);
      wg_fence();
      wg_sp48<0>(O, P[0], P[1], P[2], P[3], dV[0], meta);
#pragma unroll
      for (int s = 1; s < 7; s++) wg_sp48<1>(O, P[4 * s], P[4 * s + 1], P[4 * s + 2], P[4 * s + 3], dV[s], meta);
      wg_commit();
      nb_arrive(N_PVISS, 384);
      TR(0, b, 6);
      wg_wait<0>(); pin(O);
      mbar_arrive_elect(bar + B_VFREE * 8);
      TR(0, b, 7);
      float ru, rl;
      asm("rcp.approx.ftz.f32 %0, %1;" : "=f"(ru) : "f"(((fmaf(O[0], 0.f, sx[0]) + sx[1]) + sx[2]) + sx[3]));
      asm("rcp.approx.ftz.f32 %0, %1;" : "=f"(rl) : "f"(((fmaf(O[2], 0.f, sx[4]) + sx[5]) + sx[6]) + sx[7]));
#pragma unroll
      for (int i = 0; i < 3; i++)
        stsm4(oa + i * 256, pack2(O[8 * i] * ru, O[8 * i + 1] * ru), pack2(O[8 * i + 2] * rl, O[8 * i + 3] * rl),
              pack2(O[8 * i + 4] * ru, O[8 * i + 5] * ru), pack2(O[8 * i + 6] * rl, O[8 * i + 7] * rl));
      publish(ob);
      TR(0, b, 8);
    }
    asm volatile("{\n.reg .pred p, q;\nsetp.ne.b32 q, %1, 0;\nelect.sync _|p, 0xffffffff;\nand.pred q, q, p;\n"
                 "@q cp.async.bulk.shared::cluster.shared::cta.mbarrier::complete_tx::bytes [%1], [%0], 1536, [%2];\n"
                 "@p cp.async.bulk.shared::cluster.shared::cta.mbarrier::complete_tx::bytes [%3], [%0], 1536, [%4];\n}"
                 ::"r"(src13), "r"(snd[0]), "r"(snd[1]), "r"(snd[2]), "r"(snd[3]) : "memory");
    if (j == 0) nb_arrive(3, 256);
    TRDUMP;
    cluster_sync();
  } else if (warp < 12) {
    TRDECL;
    TR(2, -3, 0);
    asm volatile("setmaxnreg.inc.sync.aligned.u32 %0;" ::"n"(RG));
    TR(2, -3, 1);
    GemmCtx c;
    c.bar = bar;
    const int gw = warp - 8, tk = gw * 16 + (lane & 15), hi = lane >> 4;
    { const int col = tk >> 2, i = tk & 3;
      c.kC = sb + SM_K + (col + 3) * KS + hi * 128 + i * 16;
      c.vC[0] = sb + SM_V + (col + 3) * 1536 + hi * 128 + (2 * i + ((col + 3) & 1)) * 16;
      c.qC[0] = sb + SM_Q + col * 1536 + hi * 256 + (col & 1) * 64 + i * 16; }
    { const int ci = (tk >> 3) - 2, kc = ci < 3 ? ci : ci + 16, i = tk & 7; c.hvalid = gw > 0;
      c.kH = sb + SM_K + kc * KS + hi * 128 + i * 16;
      c.vH[0] = sb + SM_V + kc * 1536 + hi * 128 + (i >> 2) * 768 + (2 * (i & 3) + ((kc ^ (i >> 2)) & 1)) * 16; }
    c.never = x == nullptr;
    c.kC = opq(c.kC); c.kH = opq(c.kH);
    c.vC[1] = opq(c.vC[0] ^ 16); c.vC[0] = opq(c.vC[0]);
    c.vH[1] = opq(c.vH[0] ^ 16); c.vH[0] = opq(c.vH[0]);
    c.qC[1] = opq(c.qC[0] ^ 64); c.qC[0] = opq(c.qC[0]);
    c.spin = 0;
    c.hiA = (uint32_t)(mkdesc(0, 0, 1024, 1) >> 32) + (blockIdx.x >> 16); c.hiB = (uint32_t)(mkdesc(0, 0, 256, 3) >> 32) + (blockIdx.x >> 16);
    asm volatile("barrier.cluster.wait.aligned;" ::: "memory");
    TR(2, -3, 2);
#pragma unroll
    for (int i = 0; i < 2 * NL; i++) sts128(wdst + (i & 1) * 3072 + (i / 2) * 18432, wv[i]);
    fence_async();
    TR(2, -3, 3);
    asm volatile("bar.sync 1, 384;" ::: "memory");
    TR(2, -3, 4);
    mbar_wait(bar + B_WK * 8, 0);
    TR(2, -3, 5);
    uint32_t pk[12], pv[12], pq[12];
    gemm_iter<true, 0>(c, -2, pk, pv, pq TRPASS);
    TR2(blockIdx.x, 4);
    c.hiA = opq(c.hiA); c.hiB = opq(c.hiB);
#pragma unroll 1
    for (int b = -1;; b += 2) {
      gemm_iter<false, 1>(c, b, pk, pv, pq TRPASS);
      if (b == 11) break;
      gemm_iter<false, 0>(c, b + 1, pk, pv, pq TRPASS);
    }
    TR2(blockIdx.x, 6);
    const uint32_t st = sb + gw * 3072;
    const uint32_t sta = st + (lane & 15) * 64 + ((hi ^ ((lane >> 1) & 3)) * 16);
    const int oc = ph * 112 + strip * 16 + 8 * (gw >> 1) + 4 * (head >> 1) + 2 * (gw & 1), och = pw * 6 + (head & 1) * 3;
    float D0[48], D1[48];
    mbar_arrive_elect(bar + B_WOFREE * 8);
    dump12<256>(c.qC[1] + 128, pq);
    nb_sync(N_QK1, 256);
    issue_halo<0, 12>(c, D1);
    gwait<0>(c, B_KFREE);
    dump12<128>(c.kC, pk);
    fence_async();
    nb_arrive(N_VQ0, 288); nb_arrive(N_VQ1, 288); nb_arrive(N_PVISS, 384);
    wg_wait<0>(); pin(D1);
    pack12(pk, D1, 0);
    if (c.hvalid) dump12<128>(c.kH, pk);
    tail_free(bar + (B_TFREE + 1) * 8);
    pack12(pq, D1, 24);
    fence_async();
    nb_arrive(N_KRDY, 256);
    gwait<0>(c, B_VFREE);
    dump12<128>(c.vC[0], pv);
    if (c.hvalid) dump12<128>(c.vH[0], pq);
    fence_async();
    nb_arrive(N_VQ0, 288); nb_arrive(N_VQ1, 288);
    gwait<0>(c, B_WO);
    gwait<0>(c, B_TIN);
    TR(2, 13, 0);
    nb_sync(N_QK1, 256);
    issue_proj<SM_TIN>(D0);
    wg_wait<0>(); pin(D0);
    TR(2, 13, 1);
    store_proj(D0, &mp.ot, st + SM_TST, sta + SM_TST, 8 * TB, oc, och);
    gwait<0>(c, B_TIN + 1);
    TR(2, 13, 2);
    nb_sync(N_PVISS, 384);
    nb_sync(3, 256);
    issue_proj<SM_TIN + 24576>(D1);
    wg_wait<0>(); pin(D1);
    TR(2, 13, 3);
    store_proj(D1, &mp.ot, st + SM_TIN, sta + SM_TIN, 8 * TB + 8, oc, och);
    TR(2, 13, 4);
    gwait<0>(c, B_TIN + 2);
    TR(2, 13, 5);
    issue_proj_half<0>(D0, head & 1);
    gwait<0>(c, B_TIN + 3);
    TR(2, 13, 6);
    issue_proj_half<1>(D0, ~head & 1);
    asm volatile("barrier.cluster.arrive.relaxed.aligned;" ::: "memory");
    wg_wait<0>(); pin(D0);
    store_proj(D0, &mp.ot, st + SM_TIN + 12288, sta + SM_TIN + 12288, 8 * TB + 16, oc, och);
    TR(2, 13, 7);
    if (lane == 0) asm volatile("cp.async.bulk.wait_group.read 0;" ::: "memory");
    __syncwarp();
    TR(2, 13, 8);
    TR2(blockIdx.x, 2);
    TRDUMP;
    asm volatile("barrier.cluster.wait.aligned;" ::: "memory");
  } else {
    if (warp == 12) {
      if (elect_one()) {
        mbar_init(bar + B_WK * 8, 1);
#pragma unroll
        for (int i = 0; i < NL; i++) load_w(&mp.w, sb + SM_W + (3 * i + 2 - 2 * va) * 6144, bar + B_WK * 8, ((i + 1) % 3) * 192 + head * 48 + 32 - 32 * va);
        asm volatile("prefetch.tensormap [%0];" ::"l"(head ? &mp.xc : &mp.xh) : "memory");
        mbar_expect(bar + B_WK * 8, NL * 6144);
      }
    } else if (warp == 15) {
      const int col = min(max(strip * 16 - 3 + min(lane, 21), 0), 111);
      const uint8_t* p = reinterpret_cast<const uint8_t*>(x) + (uint32_t)(head * ROWB + (ph * 112 + col) * 768 + pw * 384);
#pragma unroll
      for (int i = 0; i < 3; i++) asm volatile("prefetch.global.L2 [%0];" ::"l"(p + i * 128));
    } else if (elect_one()) {
      if (warp == 13) {
#pragma unroll
        for (int i = 0; i < B_WK; i++) mbar_init(bar + i * 8, i < B_EMPTY ? 1 : (i < B_TIN ? 16 : (i < B_TFREE ? (i == B_TIN + 2 ? 5 : 1) : 16)));
      } else {
#pragma unroll
        for (int i = B_WQ; i < B_COUNT; i++) mbar_init(bar + i * 8, i < B_Q0 ? 1 : (i < B_ODONE ? 4 : 8));
      }
    }
    asm volatile("fence.mbarrier_init.release.cluster;" ::: "memory");
    __syncwarp();
    asm volatile("barrier.cluster.arrive.relaxed.aligned;" ::: "memory");
    asm volatile("setmaxnreg.dec.sync.aligned.u32 24;");
    asm volatile("griddepcontrol.launch_dependents;");
    const int cc = ph * 112 + (head ? strip * 16 : (strip == 0 ? 16 : (strip == 6 ? 74 : strip * 16 - 3)));
    const int sd = strip == 0 ? -1 : (strip == 6 ? 1 : 0);
    const int r0 = head == 0 ? -4 : (head == 1 ? 4 : 0);
    asm volatile("barrier.cluster.wait.aligned;" ::: "memory");
    if (warp == 12) {
      const uint32_t fb = bar + (B_FULL + head) * 8, eb = bar + (B_EMPTY + head) * 8;
      const uint32_t dst = sb + (head == 0 ? SM_X0 : (head == 1 ? SM_X1 : SM_X2));
      const int nl = head == 0 ? 15 : (head == 3 ? 1 : 14);
#pragma unroll 1
      for (int n = 0; n < nl; n++) {
        if (n) mbar_wait(eb, (n - 1) & 1);
        if (lane < 4 && head < 3)
          asm volatile("{\n.reg .b32 ra;\nmapa.shared::cluster.u32 ra, %0, %1;\nmbarrier.arrive.expect_tx.shared::cluster.b64 _, [ra], %2;\n}"
                       ::"r"(fb), "r"(lane), "r"(head ? 24576 : 18432) : "memory");
        __syncwarp();
        if (elect_one()) {
          if (head == 0) {
            asm volatile("cp.async.bulk.tensor.5d.shared::cluster.global.mbarrier::complete_tx::bytes.multicast::cluster [%0], [%1, {%3,%4,%5,%6,%7}], [%2], %8;"
                         ::"r"(dst), "l"(&mp.xh), "r"(fb), "r"(0), "r"(8 * n + r0), "r"(cc), "r"(sd), "r"(pw * 3), "h"((uint16_t)15) : "memory");
          } else if (head < 3) {
            asm volatile("cp.async.bulk.tensor.4d.shared::cluster.global.mbarrier::complete_tx::bytes.multicast::cluster [%0], [%1, {%3,%4,%5,%6}], [%2], %7;"
                         ::"r"(dst), "l"(&mp.xc), "r"(fb), "r"(0), "r"(8 * n + r0), "r"(cc), "r"(pw * 3), "h"((uint16_t)15) : "memory");
          }
          if (n == 0) {
#pragma unroll
            for (int i = 0; i < 3; i++) load_w(&mp.w, sb + SM_W + (6 + i) * 6144, bar + B_WQ * 8, head * 48 + i * 16);
            mbar_expect(bar + B_WQ * 8, 18432);
            mbar_expect(bar + B_TIN * 8, 24576); mbar_expect(bar + (B_TIN + 1) * 8, 24576); mbar_expect(bar + (B_TIN + 2) * 8, 6144); mbar_expect(bar + (B_TIN + 3) * 8, 12288);
          }
          if (!head && n + 1 < nl) asm volatile("cp.async.bulk.prefetch.tensor.5d.L2.global [%0, {%1,%2,%3,%4,%5}];" ::"l"(&mp.xh), "r"(0), "r"(8 * n + 8 + r0), "r"(cc), "r"(sd), "r"(pw * 3) : "memory");
          if (head && n + 1 < nl) asm volatile("cp.async.bulk.prefetch.tensor.4d.L2.global [%0, {%1,%2,%3,%4}];" ::"l"(&mp.xc), "r"(0), "r"(8 * n + 8 + r0), "r"(cc), "r"(pw * 3) : "memory");
        }
        __syncwarp();
      }
      mbar_wait(bar + B_WOFREE * 8, 0);
      if (elect_one()) {
        mbar_expect(bar + B_WO * 8, 36864);
        asm volatile("cp.async.bulk.tensor.3d.shared::cluster.global.mbarrier::complete_tx::bytes [%0], [%1, {%3,%4,%5}], [%2];"
                     ::"r"(sb + SM_TWO), "l"(&mp.wo), "r"(bar + B_WO * 8), "r"(0), "r"(0), "r"((head & 1) * 3) : "memory");
      }
      __syncwarp();
    }
    if (warp == 14) {
      int* flag = g_flags + cl * 2;
      nb_arrive(N_VQ0, 288); nb_arrive(N_VQ1, 288);
#pragma unroll 1
      for (int b = 0; b < TB; b++) {
        mbar_wait(bar + B_ODONE * 8, b & 1);
        if (lane == 0) {
          asm volatile("cp.async.bulk.tensor.3d.global.shared::cta.bulk_group [%0, {%2,%3,%4}], [%1];"
                       ::"l"(&mp.os), "r"(sb + SM_O), "r"(pw * 192), "r"(8 * b + 2 * head), "r"(ph * 112 + strip * 16) : "memory");
          asm volatile("cp.async.bulk.commit_group;\ncp.async.bulk.wait_group 0;" ::: "memory");
        }
        __syncwarp();
        nb_arrive(N_VQ0, 288); nb_arrive(N_VQ1, 288);
        if (lane == 0)
          asm volatile("fence.proxy.async.global;\nfence.acq_rel.gpu;\nred.relaxed.gpu.global.add.s32 [%0], 1;\nred.relaxed.gpu.global.add.s32 [%0+4], 1;"
                       ::"l"(flag + b * 56) : "memory");
        __syncwarp();
      }
    } else if (warp & 1) {
      const int j = (warp >> 1) & 1;
#pragma unroll 1
      for (int i = 0; i < 2; i++) {
        mbar_wait(bar + (B_OTAIL + j) * 8, i);
        if (i == 0) nb_arrive(N_VQ0 + j, 288);
        mbar_wait(bar + (B_TFREE + i) * 8, 0);
        if (i == 1) nb_arrive(N_VQ0 + j, 288);
        if (elect_one()) {
#pragma unroll 1
          for (int d = 0; d < 8; d++) {
            const int dst = (d + head) & 3, pc = d >> 2;
            send_o<1536>(sb + SM_TIN + i * 24576 + head * 6144 + j * 3072 + pc * 1536,
                         sb + (i ? SM_Q : SM_O) + (4 * j + (dst & 2) + pc) * (i ? 3072 : 1536), bar + (B_TIN + i) * 8, dst);
          }
        }
        __syncwarp();
      }
    }
    cluster_sync();
  }
}

constexpr int NSTB = 6;
constexpr int NTB = TB * 56;
constexpr int SM_B_ST = 0;
constexpr int SM_B_IN = 73728;
constexpr int SM_B_W = SM_B_IN + 3 * 24576;
constexpr int SM_B_BAR = SM_B_IN + NSTB * 24576;
constexpr int SM_B_TOTAL = SM_B_BAR + 512;
struct MapsB { CUtensorMap oi, oo, wo; };

__global__ void __launch_bounds__(512, 1)
na_proj_kernel(const __grid_constant__ MapsB mp) {
  extern __shared__ __align__(1024) uint8_t smem_raw[];
  const uint32_t sb = smem_u32(smem_raw);
  if ((sb & 0x3FFFF) != SBC) return;
  const uint32_t bar = sb + SM_B_BAR;
  const int tid = threadIdx.x, lane = tid & 31;
  const int warp = __shfl_sync(0xffffffffu, tid >> 5, 0);
  TR2(132 + blockIdx.x, 0);
  TRB(47, 0);
  if (warp == 12 && elect_one()) {
#pragma unroll
    for (int i = 0; i <= 2 * NSTB; i++) mbar_init(bar + i * 8, i < NSTB || i == 2 * NSTB ? 1 : 12);
    asm volatile("st.shared.u32 [%0], 0;" ::"r"(bar + 120) : "memory");
    mbar_expect(bar + 2 * NSTB * 8, 73728);
#pragma unroll
    for (int i = 0; i < 2; i++)
      asm volatile("cp.async.bulk.tensor.3d.shared::cluster.global.mbarrier::complete_tx::bytes [%0], [%1, {%3,%4,%5}], [%2];"
                   ::"r"(sb + SM_B_W + i * 36864), "l"(&mp.wo), "r"(bar + 2 * NSTB * 8), "r"(0), "r"(0), "r"(i * 3) : "memory");
  }
  __syncthreads();
  const int step = gridDim.x;
  if (warp == 15) {
    int so = 0;
    nb_arrive(4, 288); nb_arrive(5, 288); nb_arrive(6, 288);
#pragma unroll 1
    for (int n = blockIdx.x, tk = 0; n < NTB; n += step, tk++) {
      uint32_t cc = 0;
#pragma unroll
      for (int wg = 0; wg < 3; wg++) {
        if (lane == 0) asm volatile("cp.async.bulk.wait_group.read 5;" ::: "memory");
        nb_sync(1 + wg, 160);
        if (wg == 0 || n + step < NTB) nb_arrive(4 + wg, 288);
        if (wg == 0) asm volatile("ld.shared.u32 %0, [%1];" : "=r"(cc) : "r"(bar + 128 + tk * 4) : "memory");
        if (lane == 0) {
          asm volatile("cp.async.bulk.tensor.4d.global.shared::cta.bulk_group [%0, {%2,%3,%4,%5}], [%1];"
                       ::"l"(&mp.oo), "r"(sb + SM_B_ST + wg * 8192 + so), "r"(0), "r"((cc >> 8) & 255), "r"(cc >> 16), "r"((cc & 1) * 3 + wg) : "memory");
          asm volatile("cp.async.bulk.commit_group;" ::: "memory");
        }
        __syncwarp();
      }
      so = so == 49152 ? 0 : so + 24576;
    }
    if (lane == 0) asm volatile("cp.async.bulk.wait_group.read 0;" ::: "memory");
  } else if (warp >= 12) {
    nb_sync(7, 480);
#pragma unroll 1
    for (int n = blockIdx.x + (warp - 12) * step; n < NTB; n += 3 * step) {
      const int b = n / 56, rem = n - b * 56, par = rem / 14;
      const int c0 = opq((uint32_t)(par & 1)), c1 = opq((uint32_t)(8 * b)), c2 = opq((uint32_t)((par >> 1) * 112 + (rem - par * 14) * 8));
      int v; uint32_t spin = 0, tk = 0;
      do { asm volatile("ld.acquire.gpu.global.s32 %0, [%1];" : "=r"(v) : "l"(g_flags + n) : "memory"); } while (v < 4 && ++spin < SPIN_LIMIT);
      if (lane == 0) asm volatile("atom.shared.add.u32 %0, [%1], 1;" : "=r"(tk) : "r"(bar + 120) : "memory");
      asm volatile("fence.proxy.async.global;" ::: "memory");
      tk = __shfl_sync(0xffffffffu, tk, 0);
      TRB(tk, 0);
      const uint32_t use = tk / NSTB, sg = tk - use * NSTB;
      if (use) mbar_wait(bar + (NSTB + sg) * 8, (use - 1) & 1);
      TRB(tk, 1);
      if (elect_one()) {
        asm volatile("st.shared.u32 [%0], %1;" ::"r"(bar + 128 + tk * 4), "r"(c0 | c1 << 8 | c2 << 16) : "memory");
        mbar_expect(bar + sg * 8, 24576);
        asm volatile("cp.async.bulk.tensor.3d.shared::cluster.global.mbarrier::complete_tx::bytes [%0], [%1, {%3,%4,%5}], [%2];"
                     ::"r"(sb + SM_B_IN + sg * 24576), "l"(&mp.oi), "r"(bar + sg * 8), "r"(c0 * 192), "r"(c1), "r"(c2) : "memory");
        g_flags[n] = 0;
      }
      __syncwarp();
    }
  } else {
    const int wg = warp >> 2, w = warp & 3;
    uint32_t a[48];
    mbar_wait(bar + 2 * NSTB * 8, 0);
    {
      const int k = (lane & 7) + (lane >> 4) * 8, ch = (warp & 1) * 2 + ((lane >> 3) & 1);
      const uint32_t wa = sb + SM_B_W + (warp >> 1) * 12288 + k * 64 + ((ch ^ ((k >> 1) & 3)) * 16);
#pragma unroll
      for (int i = 0; i < 12; i++)
        asm volatile("ldmatrix.sync.aligned.m8n8.x4.trans.shared.b16 {%0,%1,%2,%3}, [%4];"
                     : "=r"(a[4 * i]), "=r"(a[4 * i + 1]), "=r"(a[4 * i + 2]), "=r"(a[4 * i + 3]) : "r"(wa + i * 1024) : "memory");
    }
    nb_sync(7, 480);
    TRB(47, 1);
    const uint32_t sta = opq(sb + SM_B_ST + wg * 8192 + ((lane & 7) + (lane >> 4) * 8) * 128 + (((2 * w + ((lane >> 3) & 1)) ^ (lane & 7)) * 16));
    const uint32_t hi = opq((uint32_t)(mkdesc(0, 0, 3072, 0) >> 32) + (blockIdx.x >> 16)), bb = opq(bar);
    const uint32_t nbT = opq((uint32_t)(4 + wg)), nbN = opq((uint32_t)(wg == 2 ? 4 : 5 + wg)), nbD = opq((uint32_t)(1 + wg));
    int left = (NTB - blockIdx.x + step - 1) / step;
    if (wg == 2) nb_arrive(4, 288);
#pragma unroll 1
    for (uint32_t ph = 0;; ph ^= 1) {
#pragma unroll
      for (int sg = 0; sg < NSTB; sg++) {
        constexpr uint64_t db = mkdesc(SBC + SM_B_IN, 128, 3072, 0);
        float D[32];
        mbar_wait(bb + sg * 8, ph);
        nb_sync(nbT, 288);
        wg_fence();
        wg_rs64<0>(D, a[0], a[1], a[2], a[3], dsc(db + sg * 1536, hi));
#pragma unroll
        for (int k = 1; k < 12; k++) wg_rs64<1>(D, a[4 * k], a[4 * k + 1], a[4 * k + 2], a[4 * k + 3], dsc(db + sg * 1536 + k * 16, hi));
        wg_commit();
        nb_arrive(nbN, 288);
        wg_wait<0>(); pin(D);
        mbar_arrive_elect(bb + (NSTB + sg) * 8);
#pragma unroll
        for (int q = 0; q < 4; q++)
          asm volatile("stmatrix.sync.aligned.m8n8.x4.trans.shared.b16 [%0], {%1,%2,%3,%4};" ::"r"(sta + (sg % 3) * 24576 + q * 2048),
                       "r"(pack2(D[8 * q], D[8 * q + 1])), "r"(pack2(D[8 * q + 2], D[8 * q + 3])), "r"(pack2(D[8 * q + 4], D[8 * q + 5])), "r"(pack2(D[8 * q + 6], D[8 * q + 7])) : "memory");
        fence_async();
        nb_arrive(nbD, 160);
        if (wg == 0) TRB(31 - left, 5);
        if (--left == 0) goto done;
      }
    }
  done:
    if (wg == 0) nb_arrive(4, 288);
    TR2(132 + blockIdx.x, 2);
  }
}

typedef CUresult (*EncodeFn)(CUtensorMap*, CUtensorMapDataType, cuuint32_t, void*, const cuuint64_t*, const cuuint64_t*, const cuuint32_t*,
                             const cuuint32_t*, CUtensorMapInterleave, CUtensorMapSwizzle, CUtensorMapL2promotion, CUtensorMapFloatOOBfill);
static EncodeFn g_enc = nullptr;
static void make_map(CUtensorMap* m, const void* p, int rank, const cuuint64_t* dim, const cuuint64_t* str, const cuuint32_t* box, CUtensorMapSwizzle sw) {
  const cuuint32_t ones[5] = {1, 1, 1, 1, 1};
  g_enc(m, CU_TENSOR_MAP_DATA_TYPE_BFLOAT16, rank, (void*)p, dim, str, box, ones, CU_TENSOR_MAP_INTERLEAVE_NONE, sw,
        CU_TENSOR_MAP_L2_PROMOTION_L2_128B, CU_TENSOR_MAP_FLOAT_OOB_FILL_NONE);
}

extern "C" void kernel_launch(void* const* d_in, const int* in_sizes, int n_in, void* d_out, int out_size) {
  const __nv_bfloat16* x = (const __nv_bfloat16*)d_in[0];
  const __nv_bfloat16* wqkv = (const __nv_bfloat16*)d_in[1];
  const __nv_bfloat16* wo = (const __nv_bfloat16*)d_in[2];
  const __nv_bfloat16* rpb = (const __nv_bfloat16*)d_in[3];

  if (!g_enc) {
    void* fn = nullptr; cudaDriverEntryPointQueryResult qr;
    cudaGetDriverEntryPoint("cuTensorMapEncodeTiled", &fn, cudaEnableDefault, &qr);
    g_enc = (EncodeFn)fn;
    cudaFuncSetAttribute(na_attn_kernel, cudaFuncAttributeMaxDynamicSharedMemorySize, SM_A_TOTAL);
    cudaFuncSetAttribute(na_proj_kernel, cudaFuncAttributeMaxDynamicSharedMemorySize, SM_B_TOTAL);
  }
  Maps ma; MapsB mb;
  { cuuint64_t dim[4] = {64, 112, 224, 6}, str[3] = {(cuuint64_t)ROWB, 768, 128};
    cuuint32_t box[4] = {64, 4, 16, 3}, boxo[4] = {64, 8, 8, 1};
    make_map(&ma.xc, x, 4, dim, str, box, CU_TENSOR_MAP_SWIZZLE_128B);
    make_map(&mb.oo, d_out, 4, dim, str, boxo, CU_TENSOR_MAP_SWIZZLE_128B); }
  { cuuint64_t dim[5] = {64, 112, 224, 2, 6}, str[4] = {(cuuint64_t)ROWB, 768, 19 * 768, 128};
    cuuint32_t box[5] = {64, 8, 3, 2, 3};
    make_map(&ma.xh, x, 5, dim, str, box, CU_TENSOR_MAP_SWIZZLE_128B); }
  { cuuint64_t dim[3] = {384, 112, 224}, str[2] = {(cuuint64_t)ROWB, 768};
    cuuint32_t box[3] = {192, 8, 8}, boxs[3] = {192, 2, 16};
    make_map(&mb.oi, d_out, 3, dim, str, box, CU_TENSOR_MAP_SWIZZLE_NONE);
    make_map(&ma.os, d_out, 3, dim, str, boxs, CU_TENSOR_MAP_SWIZZLE_NONE); }
  { cuuint64_t dim[4] = {32, 112, 224, 12}, str[3] = {(cuuint64_t)ROWB, 768, 64};
    cuuint32_t box[4] = {32, 8, 2, 3};
    make_map(&ma.ot, d_out, 4, dim, str, box, CU_TENSOR_MAP_SWIZZLE_64B); }
  { cuuint64_t dim[2] = {576, 192}, str[1] = {1152};
    cuuint32_t box[2] = {16, 192};
    make_map(&ma.w, wqkv, 2, dim, str, box, CU_TENSOR_MAP_SWIZZLE_32B); }
  { cuuint64_t dim[3] = {32, 192, 6}, str[2] = {384, 64};
    cuuint32_t box[3] = {32, 192, 3};
    make_map(&ma.wo, wo, 3, dim, str, box, CU_TENSOR_MAP_SWIZZLE_64B);
    mb.wo = ma.wo; }
  na_attn_kernel<<<112, 512, SM_A_TOTAL>>>(x, wqkv, rpb, ma);
  cudaLaunchConfig_t cfg = {};
  cfg.gridDim = dim3(20); cfg.blockDim = dim3(512); cfg.dynamicSmemBytes = SM_B_TOTAL; cfg.stream = cudaStreamPerThread;
  cudaLaunchAttribute at[1];
  at[0].id = cudaLaunchAttributeProgrammaticStreamSerialization; at[0].val.programmaticStreamSerializationAllowed = 1;
  cfg.attrs = at; cfg.numAttrs = 1;
  cudaLaunchKernelEx(&cfg, na_proj_kernel, mb);
}
```

```cpp
#include <cuda_runtime.h>
#include <cuda_bf16.h>
#include <cuda.h>
#include <stdint.h>

#define SPIN_LIMIT (1u << 18)

__device__ __forceinline__ uint32_t smem_u32(const void* p) { return (uint32_t)__cvta_generic_to_shared(p); }
__device__ __forceinline__ void wg_fence() { asm volatile("wgmma.fence.sync.aligned;" ::: "memory"); }
__device__ __forceinline__ void wg_commit() { asm volatile("wgmma.commit_group.sync.aligned;" ::: "memory"); }
template <int N> __device__ __forceinline__ void wg_wait() { asm volatile("wgmma.wait_group.sync.aligned %0;" ::"n"(N) : "memory"); }
template <int N> __device__ __forceinline__ void pin(float (&d)[N]) {
#pragma unroll
  for (int i = 0; i < N; i++) asm volatile("" : "+f"(d[i])::"memory");
}
__host__ __device__ constexpr uint64_t mkdesc(uint32_t addr, uint32_t lbo, uint32_t sbo, uint32_t sw) {
  return (uint64_t)((addr & 0x3FFFF) >> 4) | ((uint64_t)(lbo >> 4) << 16) | ((uint64_t)(sbo >> 4) << 32) | ((uint64_t)sw << 62);
}
__device__ __forceinline__ void mbar_init(uint32_t bar, uint32_t cnt) { asm volatile("mbarrier.init.shared::cta.b64 [%0], %1;" ::"r"(bar), "r"(cnt) : "memory"); }
__device__ __forceinline__ void mbar_arrive(uint32_t bar) { asm volatile("mbarrier.arrive.shared::cta.b64 _, [%0];" ::"r"(bar) : "memory"); }
__device__ __forceinline__ bool elect_one() {
  uint32_t r; asm volatile("{\n.reg .pred p;\nelect.sync _|p, 0xffffffff;\nselp.u32 %0, 1, 0, p;\n}" : "=r"(r)); return r;
}
__device__ __forceinline__ void mbar_arrive_elect(uint32_t bar) {
  asm volatile("{\n.reg .pred p;\nelect.sync _|p, 0xffffffff;\n@p mbarrier.arrive.shared::cta.b64 _, [%0];\n}" ::"r"(bar) : "memory");
}
__device__ __forceinline__ void mbar_expect(uint32_t bar, uint32_t bytes) { asm volatile("mbarrier.arrive.expect_tx.shared::cta.b64 _, [%0], %1;" ::"r"(bar), "r"(bytes) : "memory"); }
__device__ __forceinline__ void mbar_arrive_remote(uint32_t bar, uint32_t cta) {
  asm volatile("{\n.reg .b32 ra;\nmapa.shared::cluster.u32 ra, %0, %1;\nmbarrier.arrive.relaxed.cluster.shared::cluster.b64 _, [ra];\n}" ::"r"(bar), "r"(cta) : "memory");
}
__device__ __forceinline__ void mbar_wait(uint32_t bar, uint32_t parity) {
  asm volatile("{\n.reg .pred p;\n.reg .b32 n;\nmov.b32 n, 0;\nWL:\nmbarrier.try_wait.parity.shared::cta.b64 p, [%0], %1;\n@p bra WD;\n"
               "add.u32 n, n, 1;\nsetp.lt.u32 p, n, 65536;\n@p bra WL;\nWD:\n}" ::"r"(bar), "r"(parity) : "memory");
}
__device__ __forceinline__ void nb_sync(int id, int n) { asm volatile("bar.sync %0, %1;" ::"r"(id), "r"(n) : "memory"); }
__device__ __forceinline__ void nb_arrive(int id, int n) { asm volatile("bar.arrive %0, %1;" ::"r"(id), "r"(n) : "memory"); }
__device__ __forceinline__ uint32_t opq(uint32_t x) { uint32_t r; asm volatile("mov.b32 %0, %1;" : "=r"(r) : "r"(x)); return r; }
__device__ __forceinline__ uint64_t opq(uint64_t x) { uint64_t r; asm volatile("mov.b64 %0, %1;" : "=l"(r) : "l"(x)); return r; }
__device__ __forceinline__ uint32_t mapa(uint32_t a, uint32_t cta) { uint32_t r; asm("mapa.shared::cluster.u32 %0, %1, %2;" : "=r"(r) : "r"(a), "r"(cta)); return r; }
__device__ __forceinline__ void fence_async() { asm volatile("fence.proxy.async.shared::cta;" ::: "memory"); }
__device__ __forceinline__ void cluster_sync() {
  asm volatile("barrier.cluster.arrive.relaxed.aligned;\nbarrier.cluster.wait.aligned;" ::: "memory");
}
__device__ __forceinline__ uint32_t pack2(float lo, float hi) {
  uint32_t r; asm("cvt.rn.bf16x2.f32 %0, %1, %2;" : "=r"(r) : "f"(hi), "f"(lo)); return r;
}
__device__ __forceinline__ void stsm4(uint32_t a, uint32_t r0, uint32_t r1, uint32_t r2, uint32_t r3) {
  asm volatile("stmatrix.sync.aligned.m8n8.x4.shared.b16 [%0], {%1,%2,%3,%4};" ::"r"(a), "r"(r0), "r"(r1), "r"(r2), "r"(r3) : "memory");
}
__device__ __forceinline__ void ldsm4(uint32_t a, uint32_t& r0, uint32_t& r1, uint32_t& r2, uint32_t& r3) {
  asm volatile("ldmatrix.sync.aligned.m8n8.x4.shared.b16 {%0,%1,%2,%3}, [%4];" : "=r"(r0), "=r"(r1), "=r"(r2), "=r"(r3) : "r"(a) : "memory");
}
__device__ __forceinline__ void sts128(uint32_t a, uint4 v) {
  asm volatile("st.shared.v4.b32 [%0], {%1,%2,%3,%4};" ::"r"(a), "r"(v.x), "r"(v.y), "r"(v.z), "r"(v.w) : "memory");
}
__device__ __forceinline__ float lds_f32(uint32_t a) { float v; asm volatile("ld.shared.f32 %0, [%1];" : "=f"(v) : "r"(a)); return v; }
__device__ __forceinline__ float ex2(float x) { float y; asm("ex2.approx.ftz.f32 %0, %1;" : "=f"(y) : "f"(x)); return y; }

template<int SC> __device__ __forceinline__ void wg_ss144(float (&d)[72], uint64_t da, uint64_t db) {
  asm volatile("{\n.reg .pred p;\nsetp.ne.b32 p, %74, 0;\nwgmma.mma_async.sync.aligned.m64n144k16.f32.bf16.bf16 {%0,%1,%2,%3,%4,%5,%6,%7,%8,%9,%10,%11,%12,%13,%14,%15,%16,%17,%18,%19,%20,%21,%22,%23,%24,%25,%26,%27,%28,%29,%30,%31,%32,%33,%34,%35,%36,%37,%38,%39,%40,%41,%42,%43,%44,%45,%46,%47,%48,%49,%50,%51,%52,%53,%54,%55,%56,%57,%58,%59,%60,%61,%62,%63,%64,%65,%66,%67,%68,%69,%70,%71}, %72, %73, p, 1, 1, 0, 1;\n}\n"
    : "+f"(d[0]),"+f"(d[1]),"+f"(d[2]),"+f"(d[3]),"+f"(d[4]),"+f"(d[5]),"+f"(d[6]),"+f"(d[7]),"+f"(d[8]),"+f"(d[9]),"+f"(d[10]),"+f"(d[11]),"+f"(d[12]),"+f"(d[13]),"+f"(d[14]),"+f"(d[15]),"+f"(d[16]),"+f"(d[17]),"+f"(d[18]),"+f"(d[19]),"+f"(d[20]),"+f"(d[21]),"+f"(d[22]),"+f"(d[23]),"+f"(d[24]),"+f"(d[25]),"+f"(d[26]),"+f"(d[27]),"+f"(d[28]),"+f"(d[29]),"+f"(d[30]),"+f"(d[31]),"+f"(d[32]),"+f"(d[33]),"+f"(d[34]),"+f"(d[35]),"+f"(d[36]),"+f"(d[37]),"+f"(d[38]),"+f"(d[39]),"+f"(d[40]),"+f"(d[41]),"+f"(d[42]),"+f"(d[43]),"+f"(d[44]),"+f"(d[45]),"+f"(d[46]),"+f"(d[47]),"+f"(d[48]),"+f"(d[49]),"+f"(d[50]),"+f"(d[51]),"+f"(d[52]),"+f"(d[53]),"+f"(d[54]),"+f"(d[55]),"+f"(d[56]),"+f"(d[57]),"+f"(d[58]),"+f"(d[59]),"+f"(d[60]),"+f"(d[61]),"+f"(d[62]),"+f"(d[63]),"+f"(d[64]),"+f"(d[65]),"+f"(d[66]),"+f"(d[67]),"+f"(d[68]),"+f"(d[69]),"+f"(d[70]),"+f"(d[71]) : "l"(da), "l"(db), "n"(SC));
}
template<int SC> __device__ __forceinline__ void wg_ss96(float (&d)[48], uint64_t da, uint64_t db) {
  asm volatile("{\n.reg .pred p;\nsetp.ne.b32 p, %50, 0;\nwgmma.mma_async.sync.aligned.m64n96k16.f32.bf16.bf16 {%0,%1,%2,%3,%4,%5,%6,%7,%8,%9,%10,%11,%12,%13,%14,%15,%16,%17,%18,%19,%20,%21,%22,%23,%24,%25,%26,%27,%28,%29,%30,%31,%32,%33,%34,%35,%36,%37,%38,%39,%40,%41,%42,%43,%44,%45,%46,%47}, %48, %49, p, 1, 1, 0, 1;\n}\n"
    : "+f"(d[0]),"+f"(d[1]),"+f"(d[2]),"+f"(d[3]),"+f"(d[4]),"+f"(d[5]),"+f"(d[6]),"+f"(d[7]),"+f"(d[8]),"+f"(d[9]),"+f"(d[10]),"+f"(d[11]),"+f"(d[12]),"+f"(d[13]),"+f"(d[14]),"+f"(d[15]),"+f"(d[16]),"+f"(d[17]),"+f"(d[18]),"+f"(d[19]),"+f"(d[20]),"+f"(d[21]),"+f"(d[22]),"+f"(d[23]),"+f"(d[24]),"+f"(d[25]),"+f"(d[26]),"+f"(d[27]),"+f"(d[28]),"+f"(d[29]),"+f"(d[30]),"+f"(d[31]),"+f"(d[32]),"+f"(d[33]),"+f"(d[34]),"+f"(d[35]),"+f"(d[36]),"+f"(d[37]),"+f"(d[38]),"+f"(d[39]),"+f"(d[40]),"+f"(d[41]),"+f"(d[42]),"+f"(d[43]),"+f"(d[44]),"+f"(d[45]),"+f"(d[46]),"+f"(d[47]) : "l"(da), "l"(db), "n"(SC));
}
template<int SC> __device__ __forceinline__ void wg_rs112(float (&d)[56], uint32_t a0, uint32_t a1, uint32_t a2, uint32_t a3, uint64_t db) {
  asm volatile("{\n.reg .pred p;\nsetp.ne.b32 p, %61, 0;\nwgmma.mma_async.sync.aligned.m64n112k16.f32.bf16.bf16 {%0,%1,%2,%3,%4,%5,%6,%7,%8,%9,%10,%11,%12,%13,%14,%15,%16,%17,%18,%19,%20,%21,%22,%23,%24,%25,%26,%27,%28,%29,%30,%31,%32,%33,%34,%35,%36,%37,%38,%39,%40,%41,%42,%43,%44,%45,%46,%47,%48,%49,%50,%51,%52,%53,%54,%55}, {%56,%57,%58,%59}, %60, p, 1, 1, 0;\n}\n"
    : "+f"(d[0]),"+f"(d[1]),"+f"(d[2]),"+f"(d[3]),"+f"(d[4]),"+f"(d[5]),"+f"(d[6]),"+f"(d[7]),"+f"(d[8]),"+f"(d[9]),"+f"(d[10]),"+f"(d[11]),"+f"(d[12]),"+f"(d[13]),"+f"(d[14]),"+f"(d[15]),"+f"(d[16]),"+f"(d[17]),"+f"(d[18]),"+f"(d[19]),"+f"(d[20]),"+f"(d[21]),"+f"(d[22]),"+f"(d[23]),"+f"(d[24]),"+f"(d[25]),"+f"(d[26]),"+f"(d[27]),"+f"(d[28]),"+f"(d[29]),"+f"(d[30]),"+f"(d[31]),"+f"(d[32]),"+f"(d[33]),"+f"(d[34]),"+f"(d[35]),"+f"(d[36]),"+f"(d[37]),"+f"(d[38]),"+f"(d[39]),"+f"(d[40]),"+f"(d[41]),"+f"(d[42]),"+f"(d[43]),"+f"(d[44]),"+f"(d[45]),"+f"(d[46]),"+f"(d[47]),"+f"(d[48]),"+f"(d[49]),"+f"(d[50]),"+f"(d[51]),"+f"(d[52]),"+f"(d[53]),"+f"(d[54]),"+f"(d[55]) : "r"(a0), "r"(a1), "r"(a2), "r"(a3), "l"(db), "n"(SC));
}
template<int SC> __device__ __forceinline__ void wg_sp48(float (&d)[24], uint32_t a0, uint32_t a1, uint32_t a2, uint32_t a3, uint64_t db, uint32_t meta) {
  asm volatile("{\n.reg .pred p;\nsetp.ne.b32 p, %30, 0;\nwgmma.mma_async.sp.sync.aligned.m64n48k32.f32.bf16.bf16 {%0,%1,%2,%3,%4,%5,%6,%7,%8,%9,%10,%11,%12,%13,%14,%15,%16,%17,%18,%19,%20,%21,%22,%23}, {%24,%25,%26,%27}, %28, %29, 0, p, 1, 1, 1;\n}\n"
    : "+f"(d[0]),"+f"(d[1]),"+f"(d[2]),"+f"(d[3]),"+f"(d[4]),"+f"(d[5]),"+f"(d[6]),"+f"(d[7]),"+f"(d[8]),"+f"(d[9]),"+f"(d[10]),"+f"(d[11]),"+f"(d[12]),"+f"(d[13]),"+f"(d[14]),"+f"(d[15]),"+f"(d[16]),"+f"(d[17]),"+f"(d[18]),"+f"(d[19]),"+f"(d[20]),"+f"(d[21]),"+f"(d[22]),"+f"(d[23]) : "r"(a0), "r"(a1), "r"(a2), "r"(a3), "l"(db), "r"(meta), "n"(SC));
}
template<int SC> __device__ __forceinline__ void wg_rs64(float (&d)[32], uint32_t a0, uint32_t a1, uint32_t a2, uint32_t a3, uint64_t db) {
  asm volatile("{\n.reg .pred p;\nsetp.ne.b32 p, %37, 0;\nwgmma.mma_async.sync.aligned.m64n64k16.f32.bf16.bf16 {%0,%1,%2,%3,%4,%5,%6,%7,%8,%9,%10,%11,%12,%13,%14,%15,%16,%17,%18,%19,%20,%21,%22,%23,%24,%25,%26,%27,%28,%29,%30,%31}, {%32,%33,%34,%35}, %36, p, 1, 1, 0;\n}\n"
    : "+f"(d[0]),"+f"(d[1]),"+f"(d[2]),"+f"(d[3]),"+f"(d[4]),"+f"(d[5]),"+f"(d[6]),"+f"(d[7]),"+f"(d[8]),"+f"(d[9]),"+f"(d[10]),"+f"(d[11]),"+f"(d[12]),"+f"(d[13]),"+f"(d[14]),"+f"(d[15]),"+f"(d[16]),"+f"(d[17]),"+f"(d[18]),"+f"(d[19]),"+f"(d[20]),"+f"(d[21]),"+f"(d[22]),"+f"(d[23]),"+f"(d[24]),"+f"(d[25]),"+f"(d[26]),"+f"(d[27]),"+f"(d[28]),"+f"(d[29]),"+f"(d[30]),"+f"(d[31]) : "r"(a0), "r"(a1), "r"(a2), "r"(a3), "l"(db), "n"(SC));
}

constexpr uint32_t SBC = 1024;
constexpr int ROWB = 2 * 224 * 384;
constexpr int TB = 11;
constexpr int KS = 832;
constexpr int KSLOT = 22 * KS;
constexpr int SM_X2 = 0;
constexpr int SM_X0 = SM_X2 + 24576;
constexpr int SM_W = SM_X0 + 18432;
constexpr int SM_X1 = SM_W + 55296;
constexpr int SM_K = SM_X1 + 24576;
constexpr int SM_V = SM_K + 2 * KSLOT;
constexpr int SM_Q = SM_V + 22 * 1536;
constexpr int SM_O = SM_Q + 24576;
constexpr int SM_RPB = SM_O + 12288;
constexpr int SM_BAR = SM_RPB + 768;
constexpr int SM_A_TOTAL = SM_BAR + 256;
constexpr int SM_TIN = 0;
constexpr int SM_TST = 3 * 24576;
constexpr int SM_TWO = SM_TST + 12288;
enum { B_FULL = 0, B_EMPTY = 3, B_TIN = 6, B_TFREE = 10, B_WK = 12, B_WQ, B_WO, B_Q0, B_WOFREE, B_OTAIL, B_ODONE = B_OTAIL + 2, B_KFREE, B_VFREE, B_COUNT };
enum { N_KRDY = 4, N_QK0, N_QK1, N_VQ0, N_VQ1, N_PVISS };

#define NL 2
#define OPT 0
#define SPL 4
#define RA 160
#define RG 168
__device__ int g_flags[TB * 56];

#define TR(role, it, k)
#define TRDECL
#define TRARG
#define TRPASS
#define TRDUMP
#define TRB(it, k)
#define TR2(blk, k)

struct GemmCtx {
  uint32_t bar;
  uint32_t kC, vC[2], qC[2];
  uint32_t kH, vH[2];
  uint32_t hiA, hiB;
  uint32_t spin;
  bool hvalid, never;
};

template <int STRIDE> __device__ __forceinline__ void dump12(uint32_t a, const uint32_t (&r)[12]) {
#pragma unroll
  for (int j = 0; j < 3; j++) stsm4(a + j * 2 * STRIDE, r[4 * j], r[4 * j + 1], r[4 * j + 2], r[4 * j + 3]);
}
__device__ __forceinline__ void keep12(bool never, uint32_t a, const uint32_t (&r)[12]) { if (never) dump12<128>(a, r); }
template <int N> __device__ __forceinline__ void pack12(uint32_t (&r)[12], const float (&d)[N], int off) {
#pragma unroll
  for (int j = 0; j < 12; j++) r[j] = pack2(d[off + 2 * j], d[off + 2 * j + 1]);
}
__device__ __forceinline__ uint64_t dsc(uint64_t lo, uint32_t hi) { uint64_t r; asm("mov.b64 %0, {%1, %2};" : "=l"(r) : "r"((uint32_t)lo), "r"(hi)); return r; }
template <int XS, int K0, int K1> __device__ __forceinline__ void issue_core(const GemmCtx& c, float (&d)[72]) {
  constexpr uint64_t da = mkdesc(SBC + XS, 16, 1024, 1), db = mkdesc(SBC + SM_W, 6144, 256, 3);
  wg_fence();
  if (K0 == 0) wg_ss144<0>(d, dsc(da, c.hiA), dsc(db, c.hiB));
#pragma unroll
  for (int k = K0 ? K0 : 1; k < K1; k++) wg_ss144<1>(d, dsc(da + (k >> 2) * 512 + (k & 3) * 2, c.hiA), dsc(db + k * 32, c.hiB));
  wg_commit();
}
template <int K0, int K1> __device__ __forceinline__ void issue_halo(const GemmCtx& c, float (&d)[48]) {
  constexpr uint64_t da = mkdesc(SBC + SM_X0 - 2048, 16, 1024, 1), db = mkdesc(SBC + SM_W, 6144, 256, 3);
  wg_fence();
  if (K0 == 0) wg_ss96<0>(d, dsc(da, c.hiA), dsc(db, c.hiB));
#pragma unroll
  for (int k = K0 ? K0 : 1; k < K1; k++) wg_ss96<1>(d, dsc(da + (k >> 2) * 384 + (k & 3) * 2, c.hiA), dsc(db + k * 32, c.hiB));
  wg_commit();
}
template <int ST> __device__ __forceinline__ void release_stage(const GemmCtx& c) {
  asm volatile("{\n.reg .pred p;\n.reg .b32 ra;\nelect.sync _|p, 0xffffffff;\nmapa.shared::cluster.u32 ra, %0, %1;\n"
               "@p mbarrier.arrive.shared::cluster.b64 _, [ra];\n}" ::"r"(c.bar + (B_EMPTY + ST) * 8), "n"(ST) : "memory");
}
template <int PARITY> __device__ __forceinline__ void gwait(GemmCtx& c, int bar) {
  asm volatile("{\n.reg .pred p;\nWL:\nmbarrier.try_wait.parity.shared::cta.b64 p, [%1], %2;\n@p bra WD;\n"
               "add.u32 %0, %0, 1;\nsetp.lt.u32 p, %0, 0x100000;\n@p bra WL;\nWD:\n}" : "+r"(c.spin) : "r"(c.bar + bar * 8), "n"(PARITY) : "memory");
}
__device__ __forceinline__ void load_w(const CUtensorMap* m, uint32_t dst, uint32_t bar, int col) {
  asm volatile("cp.async.bulk.tensor.2d.shared::cluster.global.mbarrier::complete_tx::bytes [%0], [%1, {%3,%4}], [%2];"
               ::"r"(dst), "l"(m), "r"(bar), "r"(col), "r"(0) : "memory");
}
template <int BYTES> __device__ __forceinline__ void send_o(uint32_t dst, uint32_t src, uint32_t bar, int cta) {
  asm volatile("{\n.reg .b32 rd, rb;\nmapa.shared::cluster.u32 rd, %0, %3;\nmapa.shared::cluster.u32 rb, %2, %3;\n"
               "cp.async.bulk.shared::cluster.shared::cta.mbarrier::complete_tx::bytes [rd], [%1], %4, [rb];\n}"
               ::"r"(dst), "r"(src), "r"(bar), "r"(cta), "n"(BYTES) : "memory");
}
__device__ __forceinline__ void tail_free(uint32_t bar) {
  uint32_t ln; asm volatile("mov.u32 %0, %%laneid;" : "=r"(ln));
  if (ln < 4) mbar_arrive_remote(bar, ln);
}
__device__ __forceinline__ void publish(uint32_t bar) {
  fence_async();
  __syncwarp();
  mbar_arrive_elect(bar);
}

template <bool FIRST, int PA>
__device__ __forceinline__ void gemm_iter(GemmCtx& c, int b, uint32_t (&pk)[12], uint32_t (&pv)[12], uint32_t (&pq)[12] TRARG) {
  const uint32_t bar = c.bar;
  const bool w = !FIRST && (PA == 0 || b >= 0), never = c.never;
  constexpr uint32_t ko = PA * KSLOT;
  float H[48], C[72];
  uint32_t hk[12], hv[12], pv2[12];
  TR(2, b, 0);
  if (FIRST) gwait<PA>(c, B_FULL + 0);
  if (!FIRST) dump12<256>(c.qC[1] + (PA ^ 1) * 128, pq);
  if (w) nb_sync(N_QK1, 256);
  TR(2, b, 2);
  if (FIRST) TR(2, b - 1, 6);
  issue_halo<0, 8>(c, H);
  TR(2, b, 3);
  if (!FIRST) {
    if (w) gwait<PA>(c, B_KFREE);
    dump12<128>(c.kC + ko, pk);
  }
  issue_halo<8, 12>(c, H);
  TR(2, b, 4);
  {
    gwait<PA>(c, B_FULL + 2);
    if (FIRST && NL == 2) gwait<0>(c, B_WQ);
    TR(2, b, 13);
    if (FIRST) TR(2, b - 1, 7);
    issue_core<SM_X2, 0, 8>(c, C);
    TR(2, b, 5);
    if (!FIRST) { fence_async(); keep12(never, c.kC, pk); }
    wg_wait<1>(); pin(H);
    release_stage<0>(c);
  }
  pack12(hk, H, 0);
  if (c.hvalid) dump12<128>(c.kH + ko, hk);
  pack12(hv, H, 24);
  {
    issue_core<SM_X2, 8, 12>(c, C);
    if (w) { nb_arrive(N_VQ0, 288); nb_arrive(N_VQ1, 288); }
    else if (!FIRST) { __syncwarp(); mbar_arrive_elect(bar + B_Q0 * 8); }
    gwait<PA>(c, B_FULL + 1);
    keep12(never, c.kC, hk);
    TR(2, b, 6);
    wg_wait<0>(); pin(C);
    TR(2, b, 7);
    pack12(pk, C, 0);
    dump12<128>(c.kC + ko + 64, pk);
    release_stage<2>(c);
    pack12(pv2, C, 24);
    pack12(pq, C, 48);
    TR(2, b, 8);
    issue_core<SM_X1, 0, SPL>(c, C);
    if (w) nb_sync(N_PVISS, 384);
    issue_core<SM_X1, SPL, 8>(c, C);
    TR(2, b, 9);
  }
  if (!FIRST) fence_async();
  keep12(never, c.kC, pk);
  TR(2, b, 14);
  issue_core<SM_X1, 8, 12>(c, C);
  if (!FIRST) nb_arrive(N_KRDY, 256);
  TR(2, b, 1);
  if (PA && b == 11) tail_free(bar + B_TFREE * 8);
  gwait<PA ^ 1>(c, B_FULL + 0);
  if (w) gwait<PA>(c, B_VFREE);
  TR(2, b, 10);
  if (!FIRST) dump12<128>(c.vC[PA], pv);
  dump12<256>(c.qC[0] + PA * 128, pq);
  if (c.hvalid) dump12<128>(c.vH[PA], hv);
  dump12<128>(c.vC[PA ^ 1] + 768, pv2);
  TR(2, b, 11);
  wg_wait<0>(); pin(C);
  TR(2, b, 12);
  release_stage<1>(c);
  pack12(pk, C, 0);
  pack12(pv, C, 24);
  pack12(pq, C, 48);
}

template <int IN> __device__ __forceinline__ void issue_proj(float (&D)[48]) {
  constexpr uint64_t da = mkdesc(SBC + IN, 128, 768, 0), db = mkdesc(SBC + SM_TWO, 12288, 512, 2);
  wg_fence();
  wg_ss96<0>(D, da, db);
#pragma unroll
  for (int k = 1; k < 12; k++) wg_ss96<1>(D, da + (k / 3) * 384 + (k % 3) * 16, db + k * 64);
  wg_commit();
}
template <int ACC> __device__ __forceinline__ void issue_proj_half(float (&D)[48], int hd) {
  const uint64_t da = mkdesc(SBC + SM_TIN + 2 * 24576, 128, 768, 0) + hd * 384, db = mkdesc(SBC + SM_TWO, 12288, 512, 2) + hd * 192;
  wg_fence();
  wg_ss96<ACC>(D, da, db);
#pragma unroll
  for (int k = 1; k < 6; k++) wg_ss96<1>(D, da + (k / 3) * 768 + (k % 3) * 16, db + (k / 3) * 384 + (k % 3) * 64);
  wg_commit();
}
__device__ __forceinline__ void store_proj(const float (&D)[48], const CUtensorMap* m, uint32_t st, uint32_t sta, int row, int col, int ch) {
#pragma unroll
  for (int q = 0; q < 6; q++)
    stsm4((sta ^ ((q & 1) * 32)) + (q >> 1) * 1024,
          pack2(D[8 * q], D[8 * q + 1]), pack2(D[8 * q + 2], D[8 * q + 3]), pack2(D[8 * q + 4], D[8 * q + 5]), pack2(D[8 * q + 6], D[8 * q + 7]));
  fence_async();
  __syncwarp();
  if ((threadIdx.x & 31) == 0) {
    asm volatile("cp.async.bulk.tensor.4d.global.shared::cta.bulk_group [%0, {%2,%3,%4,%5}], [%1];" ::"l"(m), "r"(st), "r"(0), "r"(row), "r"(col), "r"(ch) : "memory");
    asm volatile("cp.async.bulk.commit_group;" ::: "memory");
  }
  __syncwarp();
}

__device__ __forceinline__ float fold(float a, float b, float t, int useb) {
  float r;
  asm("{\n.reg .pred p;\nsetp.ne.b32 p, %4, 0;\nfma.rn.f32 %0, %1, 0f3E553B95, %3;\n@p fma.rn.f32 %0, %2, 0f3E553B95, %3;\n}"
      : "=&f"(r) : "f"(a), "f"(b), "f"(t), "r"(useb));
  return r;
}
template <int U, int L>
__device__ __forceinline__ void softmax_tile(const float (&SA)[56], const float (&SB)[56], const float (&T)[16], int b0, int b1,
                                             uint32_t (&P)[28], float (&sx)[8]) {
  float lu[14], ll[14];
#pragma unroll
  for (int j = 0; j < 7; j++) {
    constexpr int sh = U == L ? 2 : 0;
    const float tu0 = T[2 * j + sh], tu1 = T[2 * j + 1 + sh], tl0 = T[2 * j], tl1 = T[2 * j + 1];
    lu[2 * j]     = fold(SA[4 * (U + j)],     SB[4 * (U + j)],     tu0, b0);
    ll[2 * j]     = fold(SA[4 * (L + j) + 2], SB[4 * (L + j) + 2], tl0, b0);
    lu[2 * j + 1] = fold(SA[4 * (U + j) + 1], SB[4 * (U + j) + 1], tu1, b1);
    ll[2 * j + 1] = fold(SA[4 * (L + j) + 3], SB[4 * (L + j) + 3], tl1, b1);
  }
  float mu = lu[0], ml = ll[0], mu2 = lu[1], ml2 = ll[1];
#pragma unroll
  for (int j = 1; j < 7; j++) { mu = fmaxf(mu, lu[2 * j]); mu2 = fmaxf(mu2, lu[2 * j + 1]); ml = fmaxf(ml, ll[2 * j]); ml2 = fmaxf(ml2, ll[2 * j + 1]); }
  mu = fmaxf(mu, mu2); ml = fmaxf(ml, ml2);
  { const float a1 = __shfl_xor_sync(0xffffffffu, mu, 1), a2 = __shfl_xor_sync(0xffffffffu, mu, 2), a3 = __shfl_xor_sync(0xffffffffu, mu, 3);
    const float c1 = __shfl_xor_sync(0xffffffffu, ml, 1), c2 = __shfl_xor_sync(0xffffffffu, ml, 2), c3 = __shfl_xor_sync(0xffffffffu, ml, 3);
    mu = fmaxf(fmaxf(mu, a1), fmaxf(a2, a3)); ml = fmaxf(fmaxf(ml, c1), fmaxf(c2, c3)); }
  float su = 0.f, sl = 0.f;
#pragma unroll
  for (int c = 0; c < 14; c++) {
    const int iu = (c >> 1) * 4 + (c & 1) * 2;
    if (c >= U && c < U + 7) {
      float e0 = ex2(lu[2 * (c - U)] - mu), e1 = ex2(lu[2 * (c - U) + 1] - mu);
      su = c == U ? e0 + e1 : (su + e0) + e1; P[iu] = pack2(e0, e1);
    } else P[iu] = 0u;
    if (c >= L && c < L + 7) {
      float e0 = ex2(ll[2 * (c - L)] - ml), e1 = ex2(ll[2 * (c - L) + 1] - ml);
      sl = c == L ? e0 + e1 : (sl + e0) + e1; P[iu + 1] = pack2(e0, e1);
    } else P[iu + 1] = 0u;
  }
  sx[0] = su; sx[4] = sl;
#pragma unroll
  for (int k = 1; k < 4; k++) { sx[k] = __shfl_xor_sync(0xffffffffu, su, k); sx[4 + k] = __shfl_xor_sync(0xffffffffu, sl, k); }
}

struct BandCfg { uint32_t ra0, ra1, meta; int b0, b1; };
__device__ __forceinline__ void band_cfg(int b, uint32_t tb, BandCfg& n) {
  uint32_t ln; asm volatile("mov.u32 %0, %%laneid;" : "=r"(ln));
  const int g = ln >> 2, t = ln & 3;
  const int sw = min(max(g + 1, b == 0 ? 4 : 0), b == 13 ? 5 : 8);
  const int i0 = 2 * t, i1 = 2 * t + 1;
  n.b0 = i0 <= sw - 2; n.b1 = i1 <= sw - 2;
  n.ra0 = tb + (i0 == sw - 1 ? 13 : i0 + 8 * n.b0 - g + 2) * 52;
  n.ra1 = tb + (i1 == sw - 1 ? 13 : i1 + 8 * n.b1 - g + 2) * 52;
  n.meta = ((0x5555u & ((1u << (2 * (sw - 1))) - 1)) ^ 0xDD88u ^ (((t ^ b) & 1) ? 0x5555u : 0u)) * 0x10001u;
}
__device__ __forceinline__ void band_load(const BandCfg& n, float (&T)[16], int& b0, int& b1, uint32_t& meta) {
#pragma unroll
  for (int jj = 0; jj < 8; jj++) { T[2 * jj] = lds_f32(n.ra0 + jj * 4); T[2 * jj + 1] = lds_f32(n.ra1 + jj * 4); }
  b0 = n.b0; b1 = n.b1; meta = n.meta;
}

struct Maps { CUtensorMap xc, xh, w, os, wo, ot; };

__global__ void __cluster_dims__(4, 1, 1) __launch_bounds__(512, 1)
na_attn_kernel(const __nv_bfloat16* __restrict__ x, const __nv_bfloat16* __restrict__ wqkv, const __nv_bfloat16* __restrict__ rpb, const __grid_constant__ Maps mp) {
  extern __shared__ __align__(1024) uint8_t smem_raw[];
  const uint32_t sb = smem_u32(smem_raw);
  if ((sb & 0x3FFFF) != SBC) return;
  const uint32_t bar = sb + SM_BAR;
  TR2(blockIdx.x, 0);
  const int tid = threadIdx.x, lane = tid & 31;
  const int warp = __shfl_sync(0xffffffffu, tid >> 5, 0);
  const int head = blockIdx.x & 3, cl = blockIdx.x >> 2;
  const int par = cl / 7, strip = cl - par * 7, ph = par >> 1, pw = par & 1;

  uint4 wv[2 * NL];
  const int va = head == 1;
  const uint32_t wdst = sb + SM_W + (va + ((tid >> 1) & 1)) * 6144 + (tid >> 2) * 32 + ((tid ^ (tid >> 4)) & 1) * 16;
  if (warp < 12) asm volatile("barrier.cluster.arrive.relaxed.aligned;" ::: "memory");
  {
    const uint32_t wo0 = (tid >> 2) * 1152 + head * 96 + va * 32 + (tid & 3) * 16;
#pragma unroll
    for (int i = 0; i < 2 * NL; i++)
      asm volatile("{\n.reg .pred p;\nsetp.lt.u32 p, %5, 384;\n@p ld.global.nc.v4.b32 {%0,%1,%2,%3}, [%4];\n}"
                   : "=r"(wv[i].x), "=r"(wv[i].y), "=r"(wv[i].z), "=r"(wv[i].w)
                   : "l"(reinterpret_cast<const uint8_t*>(wqkv) + wo0 + (i & 1) * 96 * 1152 + ((i / 2 + 1) % 3) * 384), "r"(tid));
  }
  if (warp < 8) {
    asm volatile("setmaxnreg.inc.sync.aligned.u32 %0;" ::"n"(RA));
    float rv = -INFINITY;
    if (tid < 169) rv = __bfloat162float(rpb[head * 169 + tid]) * 1.4426950408889634f;
    if (tid < 192) {
      const int kc = (tid & 15) + 3, wc = (tid >> 4) % 6;
      sts128(tid < 96 ? sb + SM_K + kc * KS + wc * 128 + 48 : sb + SM_V + kc * 1536 + wc * 128 + (6 + (kc & 1)) * 16, make_uint4(0, 0, 0, 0));
    }
#pragma unroll
    for (int i = 0; i < 2 * NL; i++) sts128(wdst + (i & 1) * 3072 + (i / 2) * 18432, wv[i]);
    fence_async();
    asm volatile("bar.arrive 1, 384;" ::: "memory");
    if (tid < 182) asm volatile("st.shared.f32 [%0], %1;" ::"r"(sb + SM_RPB + tid * 4), "f"(rv) : "memory");
    const int j = warp >> 2, w = warp & 3;
    int variant = w;
    if (strip == 0 && j == 0 && w < 2) variant = 4;
    if (strip == 6 && j == 1 && w >= 2) variant = 5;
    const bool v1 = opq((uint32_t)(variant & 1)), v2 = opq((uint32_t)(variant & 2)), v4 = opq((uint32_t)(variant & 4));
    uint32_t qa = opq(sb + SM_Q + (8 * j + 2 * w + ((lane >> 3) & 1)) * 1536 + (lane >> 4) * 256 + (((lane & 7) * 16) ^ (((lane >> 3) & 1) * 64)));
    uint32_t oa = opq(sb + SM_O + j * 6144 + (2 * w + ((lane >> 3) & 1)) * 768 + (lane >> 4) * 128 + (lane & 7) * 16);
    uint64_t dA = opq(mkdesc(SBC + SM_K, 128, KS, 0) + j * (8 * KS / 16)), dB = opq(dA + (KSLOT >> 4));
    uint64_t dV[7];
#pragma unroll
    for (int i = 0; i < 7; i++) dV[i] = opq(mkdesc(SBC + SM_V, 768, 128, 0) + j * (8 * 1536 / 16) + i * 192);
    const uint32_t nbK = opq((uint32_t)(N_KRDY + j)), nbQ = opq((uint32_t)(N_QK0 + j)), nbV = opq((uint32_t)(N_VQ0 + j));
    asm volatile("barrier.cluster.wait.aligned;" ::: "memory");
    asm volatile("bar.sync 3, 256;" ::: "memory");
    float T[16];
    TRDECL;
    int b0, b1;
    uint32_t meta, ob = bar + B_ODONE * 8;
    const uint32_t tb = opq(sb + SM_RPB + (variant < 4 ? 3 : variant + 1 - 2 * w) * 4);
    const bool own = ((w ^ head) & 2) == 0;
    const uint32_t dst13 = sb + SM_TIN + 2 * 24576 + head * 6144 + (2 * j + (w & 1)) * 1536, src13 = opq(own ? dst13 : sb + SM_Q + warp * 3072 + 1536);
    const uint32_t snd[4] = {opq(own ? 0u : mapa(dst13, head ^ 2)), opq(mapa(bar + (B_TIN + 2) * 8, head ^ 2)),
                             opq(mapa(dst13, (w & 2) + (~head & 1))), opq(mapa(bar + (B_TIN + 3) * 8, (w & 2) + (~head & 1)))};
    BandCfg nx;
    band_cfg(0, tb, nx);
    band_load(nx, T, b0, b1, meta);
    band_cfg(1, tb, nx);
    uint32_t special = opq(0x380Au << 1);
    uint32_t q[12];
    mbar_wait(bar + B_Q0 * 8, 0);
#pragma unroll
    for (int k = 0; k < 3; k++) ldsm4(qa + k * 512, q[4 * k], q[4 * k + 1], q[4 * k + 2], q[4 * k + 3]);
    qa ^= 128;
#pragma unroll 1
    for (int b = 0; b < 14; b++) {
      float SA[56], SB[56];
      TR(0, b, 0);
      nb_sync(nbK, 256);
      TR(0, b, 1);
      TR(0, b - 1, 9);
      wg_fence();
      wg_rs112<0>(SA, q[0], q[1], q[2], q[3], dA);
      wg_rs112<0>(SB, q[0], q[1], q[2], q[3], dB);
      wg_rs112<1>(SA, q[4], q[5], q[6], q[7], dA + 16);
      wg_rs112<1>(SB, q[4], q[5], q[6], q[7], dB + 16);
      wg_rs112<1>(SA, q[8], q[9], q[10], q[11], dA + 32);
      wg_rs112<1>(SB, q[8], q[9], q[10], q[11], dB + 32);
      wg_commit();
      nb_arrive(nbQ, 256);
      { const uint64_t t = dA; dA = dB; dB = t; }
      special >>= 1;
      if (special & 1) {
        if (b == 3) band_cfg(13, tb, nx);
        else {
          if (b == 1 || b == 13) band_load(nx, T, b0, b1, meta);
          if (b >= TB) {
            ob = bar + (b == 13 && own ? B_TIN + 2 : B_OTAIL + j) * 8;
            oa += b == 12 ? warp * 1536 - (SM_O - SM_Q) : (b == 13 ? src13 - (sb + SM_Q + warp * 3072) : 0);
          }
        }
      }
      TR(0, b, 2);
      wg_wait<0>(); pin(SA); pin(SB);
      mbar_arrive_elect(bar + B_KFREE * 8);
      TR(0, b, 3);
      TR(0, b - 1, 10);
      uint32_t P[28];
      float sx[8];
      if (v2) {
        if (v1) softmax_tile<6, 7>(SA, SB, T, b0, b1, P, sx); else softmax_tile<4, 5>(SA, SB, T, b0, b1, P, sx);
      } else if (!v4) {
        if (v1) softmax_tile<2, 3>(SA, SB, T, b0, b1, P, sx); else softmax_tile<0, 1>(SA, SB, T, b0, b1, P, sx);
      } else {
        if (v1) softmax_tile<4, 4>(SA, SB, T, b0, b1, P, sx); else softmax_tile<3, 3>(SA, SB, T, b0, b1, P, sx);
      }
      float O[24];
      TR(0, b, 4);
      nb_sync(nbV, 288);
      TR(0, b, 5);
#pragma unroll
      for (int k = 0; k < 3; k++) ldsm4(qa + k * 512, q[4 * k], q[4 * k + 1], q[4 * k + 2], q[4 * k + 3]);
      wg_fence();
      wg_sp48<0>(O, P[0], P[1], P[2], P[3], dV[0], meta);
#pragma unroll
      for (int s = 1; s < 7; s++) wg_sp48<1>(O, P[4 * s], P[4 * s + 1], P[4 * s + 2], P[4 * s + 3], dV[s], meta);
      wg_commit();
      nb_arrive(N_PVISS, 384);
      TR(0, b, 6);
      wg_wait<0>(); pin(O);
      mbar_arrive_elect(bar + B_VFREE * 8);
      TR(0, b, 7);
      float ru, rl;
      asm("rcp.approx.ftz.f32 %0, %1;" : "=f"(ru) : "f"(((fmaf(O[0], 0.f, sx[0]) + sx[1]) + sx[2]) + sx[3]));
      asm("rcp.approx.ftz.f32 %0, %1;" : "=f"(rl) : "f"(((fmaf(O[2], 0.f, sx[4]) + sx[5]) + sx[6]) + sx[7]));
#pragma unroll
      for (int i = 0; i < 3; i++)
        stsm4(oa + i * 256, pack2(O[8 * i] * ru, O[8 * i + 1] * ru), pack2(O[8 * i + 2] * rl, O[8 * i + 3] * rl),
              pack2(O[8 * i + 4] * ru, O[8 * i + 5] * ru), pack2(O[8 * i + 6] * rl, O[8 * i + 7] * rl));
      publish(ob);
      qa ^= 128;
      meta ^= 0x55555555u;
      TR(0, b, 8);
    }
    asm volatile("{\n.reg .pred p, q;\nsetp.ne.b32 q, %1, 0;\nelect.sync _|p, 0xffffffff;\nand.pred q, q, p;\n"
                 "@q cp.async.bulk.shared::cluster.shared::cta.mbarrier::complete_tx::bytes [%1], [%0], 1536, [%2];\n"
                 "@p cp.async.bulk.shared::cluster.shared::cta.mbarrier::complete_tx::bytes [%3], [%0], 1536, [%4];\n}"
                 ::"r"(src13), "r"(snd[0]), "r"(snd[1]), "r"(snd[2]), "r"(snd[3]) : "memory");
    if (j == 0) nb_arrive(3, 256);
    TRDUMP;
    cluster_sync();
  } else if (warp < 12) {
    TRDECL;
    TR(2, -3, 0);
    asm volatile("setmaxnreg.inc.sync.aligned.u32 %0;" ::"n"(RG));
    TR(2, -3, 1);
    GemmCtx c;
    c.bar = bar;
    const int gw = warp - 8, tk = gw * 16 + (lane & 15), hi = lane >> 4;
    { const int col = tk >> 2, i = tk & 3;
      c.kC = sb + SM_K + (col + 3) * KS + hi * 128 + i * 16;
      c.vC[0] = sb + SM_V + (col + 3) * 1536 + hi * 128 + (2 * i + ((col + 3) & 1)) * 16;
      c.qC[0] = sb + SM_Q + col * 1536 + hi * 256 + (col & 1) * 64 + i * 16; }
    { const int ci = (tk >> 3) - 2, kc = ci < 3 ? ci : ci + 16, i = tk & 7; c.hvalid = gw > 0;
      c.kH = sb + SM_K + kc * KS + hi * 128 + i * 16;
      c.vH[0] = sb + SM_V + kc * 1536 + hi * 128 + (i >> 2) * 768 + (2 * (i & 3) + ((kc ^ (i >> 2)) & 1)) * 16; }
    c.never = x == nullptr;
    c.kC = opq(c.kC); c.kH = opq(c.kH);
    c.vC[1] = opq(c.vC[0] ^ 16); c.vC[0] = opq(c.vC[0]);
    c.vH[1] = opq(c.vH[0] ^ 16); c.vH[0] = opq(c.vH[0]);
    c.qC[1] = opq(c.qC[0] ^ 64); c.qC[0] = opq(c.qC[0]);
    c.spin = 0;
    c.hiA = (uint32_t)(mkdesc(0, 0, 1024, 1) >> 32) + (blockIdx.x >> 16); c.hiB = (uint32_t)(mkdesc(0, 0, 256, 3) >> 32) + (blockIdx.x >> 16);
    asm volatile("barrier.cluster.wait.aligned;" ::: "memory");
    TR(2, -3, 2);
#pragma unroll
    for (int i = 0; i < 2 * NL; i++) sts128(wdst + (i & 1) * 3072 + (i / 2) * 18432, wv[i]);
    fence_async();
    TR(2, -3, 3);
    asm volatile("bar.sync 1, 384;" ::: "memory");
    TR(2, -3, 4);
    mbar_wait(bar + B_WK * 8, 0);
    TR(2, -3, 5);
    uint32_t pk[12], pv[12], pq[12];
    gemm_iter<true, 0>(c, -2, pk, pv, pq TRPASS);
    TR2(blockIdx.x, 4);
    c.hiA = opq(c.hiA); c.hiB = opq(c.hiB);
#pragma unroll 1
    for (int b = -1;; b += 2) {
      gemm_iter<false, 1>(c, b, pk, pv, pq TRPASS);
      if (b == 11) break;
      gemm_iter<false, 0>(c, b + 1, pk, pv, pq TRPASS);
    }
    TR2(blockIdx.x, 6);
    const uint32_t st = sb + gw * 3072;
    const uint32_t sta = st + (lane & 15) * 64 + ((hi ^ ((lane >> 1) & 3)) * 16);
    const int oc = ph * 112 + strip * 16 + 8 * (gw >> 1) + 4 * (head >> 1) + 2 * (gw & 1), och = pw * 6 + (head & 1) * 3;
    float D0[48], D1[48];
    mbar_arrive_elect(bar + B_WOFREE * 8);
    dump12<256>(c.qC[1] + 128, pq);
    nb_sync(N_QK1, 256);
    issue_halo<0, 12>(c, D1);
    gwait<0>(c, B_KFREE);
    dump12<128>(c.kC, pk);
    fence_async();
    nb_arrive(N_VQ0, 288); nb_arrive(N_VQ1, 288); nb_arrive(N_PVISS, 384);
    wg_wait<0>(); pin(D1);
    pack12(pk, D1, 0);
    if (c.hvalid) dump12<128>(c.kH, pk);
    tail_free(bar + (B_TFREE + 1) * 8);
    pack12(pq, D1, 24);
    fence_async();
    nb_arrive(N_KRDY, 256);
    gwait<0>(c, B_VFREE);
    dump12<128>(c.vC[0], pv);
    if (c.hvalid) dump12<128>(c.vH[0], pq);
    fence_async();
    nb_arrive(N_VQ0, 288); nb_arrive(N_VQ1, 288);
    gwait<0>(c, B_WO);
    gwait<0>(c, B_TIN);
    TR(2, 13, 0);
    nb_sync(N_QK1, 256);
    issue_proj<SM_TIN>(D0);
    wg_wait<0>(); pin(D0);
    TR(2, 13, 1);
    store_proj(D0, &mp.ot, st + SM_TST, sta + SM_TST, 8 * TB, oc, och);
    gwait<0>(c, B_TIN + 1);
    TR(2, 13, 2);
    nb_sync(N_PVISS, 384);
    nb_sync(3, 256);
    issue_proj<SM_TIN + 24576>(D1);
    wg_wait<0>(); pin(D1);
    TR(2, 13, 3);
    store_proj(D1, &mp.ot, st + SM_TIN, sta + SM_TIN, 8 * TB + 8, oc, och);
    TR(2, 13, 4);
    gwait<0>(c, B_TIN + 2);
    TR(2, 13, 5);
    issue_proj_half<0>(D0, head & 1);
    gwait<0>(c, B_TIN + 3);
    TR(2, 13, 6);
    issue_proj_half<1>(D0, ~head & 1);
    asm volatile("barrier.cluster.arrive.relaxed.aligned;" ::: "memory");
    wg_wait<0>(); pin(D0);
    store_proj(D0, &mp.ot, st + SM_TIN + 12288, sta + SM_TIN + 12288, 8 * TB + 16, oc, och);
    TR(2, 13, 7);
    if (lane == 0) asm volatile("cp.async.bulk.wait_group.read 0;" ::: "memory");
    __syncwarp();
    TR(2, 13, 8);
    TR2(blockIdx.x, 2);
    TRDUMP;
    asm volatile("barrier.cluster.wait.aligned;" ::: "memory");
  } else {
    if (warp == 12) {
      if (elect_one()) {
        mbar_init(bar + B_WK * 8, 1);
#pragma unroll
        for (int i = 0; i < NL; i++) load_w(&mp.w, sb + SM_W + (3 * i + 2 - 2 * va) * 6144, bar + B_WK * 8, ((i + 1) % 3) * 192 + head * 48 + 32 - 32 * va);
        asm volatile("prefetch.tensormap [%0];" ::"l"(head ? &mp.xc : &mp.xh) : "memory");
        mbar_expect(bar + B_WK * 8, NL * 6144);
      }
    } else if (warp == 15) {
      const int col = min(max(strip * 16 - 3 + min(lane, 21), 0), 111);
      const uint8_t* p = reinterpret_cast<const uint8_t*>(x) + (uint32_t)(head * ROWB + (ph * 112 + col) * 768 + pw * 384);
#pragma unroll
      for (int i = 0; i < 3; i++) asm volatile("prefetch.global.L2 [%0];" ::"l"(p + i * 128));
    } else if (elect_one()) {
      if (warp == 13) {
#pragma unroll
        for (int i = 0; i < B_WK; i++) mbar_init(bar + i * 8, i < B_EMPTY ? 1 : (i < B_TIN ? 16 : (i < B_TFREE ? (i == B_TIN + 2 ? 5 : 1) : 16)));
      } else {
#pragma unroll
        for (int i = B_WQ; i < B_COUNT; i++) mbar_init(bar + i * 8, i < B_Q0 ? 1 : (i < B_ODONE ? 4 : 8));
      }
    }
    asm volatile("fence.mbarrier_init.release.cluster;" ::: "memory");
    __syncwarp();
    asm volatile("barrier.cluster.arrive.relaxed.aligned;" ::: "memory");
    asm volatile("setmaxnreg.dec.sync.aligned.u32 24;");
    asm volatile("griddepcontrol.launch_dependents;");
    const int cc = ph * 112 + (head ? strip * 16 : (strip == 0 ? 16 : (strip == 6 ? 74 : strip * 16 - 3)));
    const int sd = strip == 0 ? -1 : (strip == 6 ? 1 : 0);
    const int r0 = head == 0 ? -4 : (head == 1 ? 4 : 0);
    asm volatile("barrier.cluster.wait.aligned;" ::: "memory");
    if (warp == 12) {
      const uint32_t fb = bar + (B_FULL + head) * 8, eb = bar + (B_EMPTY + head) * 8;
      const uint32_t dst = sb + (head == 0 ? SM_X0 : (head == 1 ? SM_X1 : SM_X2));
      const int nl = head == 0 ? 15 : (head == 3 ? 1 : 14);
#pragma unroll 1
      for (int n = 0; n < nl; n++) {
        if (n) mbar_wait(eb, (n - 1) & 1);
        if (lane < 4 && head < 3)
          asm volatile("{\n.reg .b32 ra;\nmapa.shared::cluster.u32 ra, %0, %1;\nmbarrier.arrive.expect_tx.shared::cluster.b64 _, [ra], %2;\n}"
                       ::"r"(fb), "r"(lane), "r"(head ? 24576 : 18432) : "memory");
        __syncwarp();
        if (elect_one()) {
          if (head == 0) {
            asm volatile("cp.async.bulk.tensor.5d.shared::cluster.global.mbarrier::complete_tx::bytes.multicast::cluster [%0], [%1, {%3,%4,%5,%6,%7}], [%2], %8;"
                         ::"r"(dst), "l"(&mp.xh), "r"(fb), "r"(0), "r"(8 * n + r0), "r"(cc), "r"(sd), "r"(pw * 3), "h"((uint16_t)15) : "memory");
          } else if (head < 3) {
            asm volatile("cp.async.bulk.tensor.4d.shared::cluster.global.mbarrier::complete_tx::bytes.multicast::cluster [%0], [%1, {%3,%4,%5,%6}], [%2], %7;"
                         ::"r"(dst), "l"(&mp.xc), "r"(fb), "r"(0), "r"(8 * n + r0), "r"(cc), "r"(pw * 3), "h"((uint16_t)15) : "memory");
          }
          if (n == 0) {
#pragma unroll
            for (int i = 0; i < 3; i++) load_w(&mp.w, sb + SM_W + (6 + i) * 6144, bar + B_WQ * 8, head * 48 + i * 16);
            mbar_expect(bar + B_WQ * 8, 18432);
            mbar_expect(bar + B_TIN * 8, 24576); mbar_expect(bar + (B_TIN + 1) * 8, 24576); mbar_expect(bar + (B_TIN + 2) * 8, 6144); mbar_expect(bar + (B_TIN + 3) * 8, 12288);
          }
          if (!head && n + 1 < nl) asm volatile("cp.async.bulk.prefetch.tensor.5d.L2.global [%0, {%1,%2,%3,%4,%5}];" ::"l"(&mp.xh), "r"(0), "r"(8 * n + 8 + r0), "r"(cc), "r"(sd), "r"(pw * 3) : "memory");
          if (head && n + 1 < nl) asm volatile("cp.async.bulk.prefetch.tensor.4d.L2.global [%0, {%1,%2,%3,%4}];" ::"l"(&mp.xc), "r"(0), "r"(8 * n + 8 + r0), "r"(cc), "r"(pw * 3) : "memory");
        }
        __syncwarp();
      }
      mbar_wait(bar + B_WOFREE * 8, 0);
      if (elect_one()) {
        mbar_expect(bar + B_WO * 8, 36864);
        asm volatile("cp.async.bulk.tensor.3d.shared::cluster.global.mbarrier::complete_tx::bytes [%0], [%1, {%3,%4,%5}], [%2];"
                     ::"r"(sb + SM_TWO), "l"(&mp.wo), "r"(bar + B_WO * 8), "r"(0), "r"(0), "r"((head & 1) * 3) : "memory");
      }
      __syncwarp();
    }
    if (warp == 14) {
      int* flag = g_flags + cl * 2;
      nb_arrive(N_VQ0, 288); nb_arrive(N_VQ1, 288);
#pragma unroll 1
      for (int b = 0; b < TB; b++) {
        mbar_wait(bar + B_ODONE * 8, b & 1);
        if (lane == 0) {
          asm volatile("cp.async.bulk.tensor.3d.global.shared::cta.bulk_group [%0, {%2,%3,%4}], [%1];"
                       ::"l"(&mp.os), "r"(sb + SM_O), "r"(pw * 192), "r"(8 * b + 2 * head), "r"(ph * 112 + strip * 16) : "memory");
          asm volatile("cp.async.bulk.commit_group;\ncp.async.bulk.wait_group 0;" ::: "memory");
        }
        __syncwarp();
        nb_arrive(N_VQ0, 288); nb_arrive(N_VQ1, 288);
        if (lane == 0)
          asm volatile("fence.proxy.async.global;\nfence.acq_rel.gpu;\nred.relaxed.gpu.global.add.s32 [%0], 1;\nred.relaxed.gpu.global.add.s32 [%0+4], 1;"
                       ::"l"(flag + b * 56) : "memory");
        __syncwarp();
      }
    } else if (warp & 1) {
      const int j = (warp >> 1) & 1;
#pragma unroll 1
      for (int i = 0; i < 2; i++) {
        mbar_wait(bar + (B_OTAIL + j) * 8, i);
        if (i == 0) nb_arrive(N_VQ0 + j, 288);
        mbar_wait(bar + (B_TFREE + i) * 8, 0);
        if (i == 1) nb_arrive(N_VQ0 + j, 288);
        if (elect_one()) {
#pragma unroll 1
          for (int d = 0; d < 8; d++) {
            const int dst = (d + head) & 3, pc = d >> 2;
            send_o<1536>(sb + SM_TIN + i * 24576 + head * 6144 + j * 3072 + pc * 1536,
                         sb + (i ? SM_Q : SM_O) + (4 * j + (dst & 2) + pc) * (i ? 3072 : 1536), bar + (B_TIN + i) * 8, dst);
          }
        }
        __syncwarp();
      }
    }
    cluster_sync();
  }
}

constexpr int NSTB = 6;
constexpr int NTB = TB * 56;
constexpr int SM_B_ST = 0;
constexpr int SM_B_IN = 73728;
constexpr int SM_B_W = SM_B_IN + 3 * 24576;
constexpr int SM_B_BAR = SM_B_IN + NSTB * 24576;
constexpr int SM_B_TOTAL = SM_B_BAR + 512;
struct MapsB { CUtensorMap oi, oo, wo; };

__global__ void __launch_bounds__(512, 1)
na_proj_kernel(const __grid_constant__ MapsB mp) {
  extern __shared__ __align__(1024) uint8_t smem_raw[];
  const uint32_t sb = smem_u32(smem_raw);
  if ((sb & 0x3FFFF) != SBC) return;
  const uint32_t bar = sb + SM_B_BAR;
  const int tid = threadIdx.x, lane = tid & 31;
  const int warp = __shfl_sync(0xffffffffu, tid >> 5, 0);
  TR2(132 + blockIdx.x, 0);
  TRB(47, 0);
  if (warp == 12 && elect_one()) {
#pragma unroll
    for (int i = 0; i <= 2 * NSTB; i++) mbar_init(bar + i * 8, i < NSTB || i == 2 * NSTB ? 1 : 12);
    asm volatile("st.shared.u32 [%0], 0;" ::"r"(bar + 120) : "memory");
    mbar_expect(bar + 2 * NSTB * 8, 73728);
#pragma unroll
    for (int i = 0; i < 2; i++)
      asm volatile("cp.async.bulk.tensor.3d.shared::cluster.global.mbarrier::complete_tx::bytes [%0], [%1, {%3,%4,%5}], [%2];"
                   ::"r"(sb + SM_B_W + i * 36864), "l"(&mp.wo), "r"(bar + 2 * NSTB * 8), "r"(0), "r"(0), "r"(i * 3) : "memory");
  }
  __syncthreads();
  const int step = gridDim.x;
  if (warp == 15) {
    int so = 0;
    nb_arrive(4, 288); nb_arrive(5, 288); nb_arrive(6, 288);
#pragma unroll 1
    for (int n = blockIdx.x, tk = 0; n < NTB; n += step, tk++) {
      uint32_t cc = 0;
#pragma unroll
      for (int wg = 0; wg < 3; wg++) {
        if (lane == 0) asm volatile("cp.async.bulk.wait_group.read 5;" ::: "memory");
        nb_sync(1 + wg, 160);
        if (wg == 0 || n + step < NTB) nb_arrive(4 + wg, 288);
        if (wg == 0) asm volatile("ld.shared.u32 %0, [%1];" : "=r"(cc) : "r"(bar + 128 + tk * 4) : "memory");
        if (lane == 0) {
          asm volatile("cp.async.bulk.tensor.4d.global.shared::cta.bulk_group [%0, {%2,%3,%4,%5}], [%1];"
                       ::"l"(&mp.oo), "r"(sb + SM_B_ST + wg * 8192 + so), "r"(0), "r"((cc >> 8) & 255), "r"(cc >> 16), "r"((cc & 1) * 3 + wg) : "memory");
          asm volatile("cp.async.bulk.commit_group;" ::: "memory");
        }
        __syncwarp();
      }
      so = so == 49152 ? 0 : so + 24576;
    }
    if (lane == 0) asm volatile("cp.async.bulk.wait_group.read 0;" ::: "memory");
  } else if (warp >= 12) {
    nb_sync(7, 480);
#pragma unroll 1
    for (int n = blockIdx.x + (warp - 12) * step; n < NTB; n += 3 * step) {
      const int b = n / 56, rem = n - b * 56, par = rem / 14;
      const int c0 = opq((uint32_t)(par & 1)), c1 = opq((uint32_t)(8 * b)), c2 = opq((uint32_t)((par >> 1) * 112 + (rem - par * 14) * 8));
      int v; uint32_t spin = 0, tk = 0;
      do { asm volatile("ld.acquire.gpu.global.s32 %0, [%1];" : "=r"(v) : "l"(g_flags + n) : "memory"); } while (v < 4 && ++spin < SPIN_LIMIT);
      if (lane == 0) asm volatile("atom.shared.add.u32 %0, [%1], 1;" : "=r"(tk) : "r"(bar + 120) : "memory");
      asm volatile("fence.proxy.async.global;" ::: "memory");
      tk = __shfl_sync(0xffffffffu, tk, 0);
      TRB(tk, 0);
      const uint32_t use = tk / NSTB, sg = tk - use * NSTB;
      if (use) mbar_wait(bar + (NSTB + sg) * 8, (use - 1) & 1);
      TRB(tk, 1);
      if (elect_one()) {
        asm volatile("st.shared.u32 [%0], %1;" ::"r"(bar + 128 + tk * 4), "r"(c0 | c1 << 8 | c2 << 16) : "memory");
        mbar_expect(bar + sg * 8, 24576);
        asm volatile("cp.async.bulk.tensor.3d.shared::cluster.global.mbarrier::complete_tx::bytes [%0], [%1, {%3,%4,%5}], [%2];"
                     ::"r"(sb + SM_B_IN + sg * 24576), "l"(&mp.oi), "r"(bar + sg * 8), "r"(c0 * 192), "r"(c1), "r"(c2) : "memory");
        g_flags[n] = 0;
      }
      __syncwarp();
    }
  } else {
    const int wg = warp >> 2, w = warp & 3;
    uint32_t a[48];
    mbar_wait(bar + 2 * NSTB * 8, 0);
    {
      const int k = (lane & 7) + (lane >> 4) * 8, ch = (warp & 1) * 2 + ((lane >> 3) & 1);
      const uint32_t wa = sb + SM_B_W + (warp >> 1) * 12288 + k * 64 + ((ch ^ ((k >> 1) & 3)) * 16);
#pragma unroll
      for (int i = 0; i < 12; i++)
        asm volatile("ldmatrix.sync.aligned.m8n8.x4.trans.shared.b16 {%0,%1,%2,%3}, [%4];"
                     : "=r"(a[4 * i]), "=r"(a[4 * i + 1]), "=r"(a[4 * i + 2]), "=r"(a[4 * i + 3]) : "r"(wa + i * 1024) : "memory");
    }
    nb_sync(7, 480);
    TRB(47, 1);
    const uint32_t sta = opq(sb + SM_B_ST + wg * 8192 + ((lane & 7) + (lane >> 4) * 8) * 128 + (((2 * w + ((lane >> 3) & 1)) ^ (lane & 7)) * 16));
    const uint32_t hi = opq((uint32_t)(mkdesc(0, 0, 3072, 0) >> 32) + (blockIdx.x >> 16)), bb = opq(bar);
    const uint32_t nbT = opq((uint32_t)(4 + wg)), nbN = opq((uint32_t)(wg == 2 ? 4 : 5 + wg)), nbD = opq((uint32_t)(1 + wg));
    int left = (NTB - blockIdx.x + step - 1) / step;
    if (wg == 2) nb_arrive(4, 288);
#pragma unroll 1
    for (uint32_t ph = 0;; ph ^= 1) {
#pragma unroll
      for (int sg = 0; sg < NSTB; sg++) {
        constexpr uint64_t db = mkdesc(SBC + SM_B_IN, 128, 3072, 0);
        float D[32];
        mbar_wait(bb + sg * 8, ph);
        nb_sync(nbT, 288);
        wg_fence();
        wg_rs64<0>(D, a[0], a[1], a[2], a[3], dsc(db + sg * 1536, hi));
#pragma unroll
        for (int k = 1; k < 12; k++) wg_rs64<1>(D, a[4 * k], a[4 * k + 1], a[4 * k + 2], a[4 * k + 3], dsc(db + sg * 1536 + k * 16, hi));
        wg_commit();
        nb_arrive(nbN, 288);
        wg_wait<0>(); pin(D);
        mbar_arrive_elect(bb + (NSTB + sg) * 8);
#pragma unroll
        for (int q = 0; q < 4; q++)
          asm volatile("stmatrix.sync.aligned.m8n8.x4.trans.shared.b16 [%0], {%1,%2,%3,%4};" ::"r"(sta + (sg % 3) * 24576 + q * 2048),
                       "r"(pack2(D[8 * q], D[8 * q + 1])), "r"(pack2(D[8 * q + 2], D[8 * q + 3])), "r"(pack2(D[8 * q + 4], D[8 * q + 5])), "r"(pack2(D[8 * q + 6], D[8 * q + 7])) : "memory");
        fence_async();
        nb_arrive(nbD, 160);
        if (wg == 0) TRB(31 - left, 5);
        if (--left == 0) goto done;
      }
    }
  done:
    if (wg == 0) nb_arrive(4, 288);
    TR2(132 + blockIdx.x, 2);
  }
}

typedef CUresult (*EncodeFn)(CUtensorMap*, CUtensorMapDataType, cuuint32_t, void*, const cuuint64_t*, const cuuint64_t*, const cuuint32_t*,
                             const cuuint32_t*, CUtensorMapInterleave, CUtensorMapSwizzle, CUtensorMapL2promotion, CUtensorMapFloatOOBfill);
static EncodeFn g_enc = nullptr;
static void make_map(CUtensorMap* m, const void* p, int rank, const cuuint64_t* dim, const cuuint64_t* str, const cuuint32_t* box, CUtensorMapSwizzle sw) {
  const cuuint32_t ones[5] = {1, 1, 1, 1, 1};
  g_enc(m, CU_TENSOR_MAP_DATA_TYPE_BFLOAT16, rank, (void*)p, dim, str, box, ones, CU_TENSOR_MAP_INTERLEAVE_NONE, sw,
        CU_TENSOR_MAP_L2_PROMOTION_L2_128B, CU_TENSOR_MAP_FLOAT_OOB_FILL_NONE);
}

extern "C" void kernel_launch(void* const* d_in, const int* in_sizes, int n_in, void* d_out, int out_size) {
  const __nv_bfloat16* x = (const __nv_bfloat16*)d_in[0];
  const __nv_bfloat16* wqkv = (const __nv_bfloat16*)d_in[1];
  const __nv_bfloat16* wo = (const __nv_bfloat16*)d_in[2];
  const __nv_bfloat16* rpb = (const __nv_bfloat16*)d_in[3];

  if (!g_enc) {
    void* fn = nullptr; cudaDriverEntryPointQueryResult qr;
    cudaGetDriverEntryPoint("cuTensorMapEncodeTiled", &fn, cudaEnableDefault, &qr);
    g_enc = (EncodeFn)fn;
    cudaFuncSetAttribute(na_attn_kernel, cudaFuncAttributeMaxDynamicSharedMemorySize, SM_A_TOTAL);
    cudaFuncSetAttribute(na_proj_kernel, cudaFuncAttributeMaxDynamicSharedMemorySize, SM_B_TOTAL);
  }
  Maps ma; MapsB mb;
  { cuuint64_t dim[4] = {64, 112, 224, 6}, str[3] = {(cuuint64_t)ROWB, 768, 128};
    cuuint32_t box[4] = {64, 4, 16, 3}, boxo[4] = {64, 8, 8, 1};
    make_map(&ma.xc, x, 4, dim, str, box, CU_TENSOR_MAP_SWIZZLE_128B);
    make_map(&mb.oo, d_out, 4, dim, str, boxo, CU_TENSOR_MAP_SWIZZLE_128B); }
  { cuuint64_t dim[5] = {64, 112, 224, 2, 6}, str[4] = {(cuuint64_t)ROWB, 768, 19 * 768, 128};
    cuuint32_t box[5] = {64, 8, 3, 2, 3};
    make_map(&ma.xh, x, 5, dim, str, box, CU_TENSOR_MAP_SWIZZLE_128B); }
  { cuuint64_t dim[3] = {384, 112, 224}, str[2] = {(cuuint64_t)ROWB, 768};
    cuuint32_t box[3] = {192, 8, 8}, boxs[3] = {192, 2, 16};
    make_map(&mb.oi, d_out, 3, dim, str, box, CU_TENSOR_MAP_SWIZZLE_NONE);
    make_map(&ma.os, d_out, 3, dim, str, boxs, CU_TENSOR_MAP_SWIZZLE_NONE); }
  { cuuint64_t dim[4] = {32, 112, 224, 12}, str[3] = {(cuuint64_t)ROWB, 768, 64};
    cuuint32_t box[4] = {32, 8, 2, 3};
    make_map(&ma.ot, d_out, 4, dim, str, box, CU_TENSOR_MAP_SWIZZLE_64B); }
  { cuuint64_t dim[2] = {576, 192}, str[1] = {1152};
    cuuint32_t box[2] = {16, 192};
    make_map(&ma.w, wqkv, 2, dim, str, box, CU_TENSOR_MAP_SWIZZLE_32B); }
  { cuuint64_t dim[3] = {32, 192, 6}, str[2] = {384, 64};
    cuuint32_t box[3] = {32, 192, 3};
    make_map(&ma.wo, wo, 3, dim, str, box, CU_TENSOR_MAP_SWIZZLE_64B);
    mb.wo = ma.wo; }
  na_attn_kernel<<<112, 512, SM_A_TOTAL>>>(x, wqkv, rpb, ma);
  cudaLaunchConfig_t cfg = {};
  cfg.gridDim = dim3(20); cfg.blockDim = dim3(512); cfg.dynamicSmemBytes = SM_B_TOTAL; cfg.stream = cudaStreamPerThread;
  cudaLaunchAttribute at[1];
  at[0].id = cudaLaunchAttributeProgrammaticStreamSerialization; at[0].val.programmaticStreamSerializationAllowed = 1;
  cfg.attrs = at; cfg.numAttrs = 1;
  cudaLaunchKernelEx(&cfg, na_proj_kernel, mb);
}
```

```cpp
#include <cuda_runtime.h>
#include <cuda_bf16.h>
#include <cuda.h>
#include <stdint.h>

#define SPIN_LIMIT (1u << 18)

__device__ __forceinline__ uint32_t smem_u32(const void* p) { return (uint32_t)__cvta_generic_to_shared(p); }
__device__ __forceinline__ void wg_fence() { asm volatile("wgmma.fence.sync.aligned;" ::: "memory"); }
__device__ __forceinline__ void wg_commit() { asm volatile("wgmma.commit_group.sync.aligned;" ::: "memory"); }
template <int N> __device__ __forceinline__ void wg_wait() { asm volatile("wgmma.wait_group.sync.aligned %0;" ::"n"(N) : "memory"); }
template <int N> __device__ __forceinline__ void pin(float (&d)[N]) {
#pragma unroll
  for (int i = 0; i < N; i++) asm volatile("" : "+f"(d[i])::"memory");
}
__host__ __device__ constexpr uint64_t mkdesc(uint32_t addr, uint32_t lbo, uint32_t sbo, uint32_t sw) {
  return (uint64_t)((addr & 0x3FFFF) >> 4) | ((uint64_t)(lbo >> 4) << 16) | ((uint64_t)(sbo >> 4) << 32) | ((uint64_t)sw << 62);
}
__device__ __forceinline__ void mbar_init(uint32_t bar, uint32_t cnt) { asm volatile("mbarrier.init.shared::cta.b64 [%0], %1;" ::"r"(bar), "r"(cnt) : "memory"); }
__device__ __forceinline__ void mbar_arrive(uint32_t bar) { asm volatile("mbarrier.arrive.shared::cta.b64 _, [%0];" ::"r"(bar) : "memory"); }
__device__ __forceinline__ bool elect_one() {
  uint32_t r; asm volatile("{\n.reg .pred p;\nelect.sync _|p, 0xffffffff;\nselp.u32 %0, 1, 0, p;\n}" : "=r"(r)); return r;
}
__device__ __forceinline__ void mbar_arrive_elect(uint32_t bar) {
  asm volatile("{\n.reg .pred p;\nelect.sync _|p, 0xffffffff;\n@p mbarrier.arrive.shared::cta.b64 _, [%0];\n}" ::"r"(bar) : "memory");
}
__device__ __forceinline__ void mbar_expect(uint32_t bar, uint32_t bytes) { asm volatile("mbarrier.arrive.expect_tx.shared::cta.b64 _, [%0], %1;" ::"r"(bar), "r"(bytes) : "memory"); }
__device__ __forceinline__ void mbar_arrive_remote(uint32_t bar, uint32_t cta) {
  asm volatile("{\n.reg .b32 ra;\nmapa.shared::cluster.u32 ra, %0, %1;\nmbarrier.arrive.relaxed.cluster.shared::cluster.b64 _, [ra];\n}" ::"r"(bar), "r"(cta) : "memory");
}
__device__ __forceinline__ void mbar_wait(uint32_t bar, uint32_t parity) {
  asm volatile("{\n.reg .pred p;\n.reg .b32 n;\nmov.b32 n, 0;\nWL:\nmbarrier.try_wait.parity.shared::cta.b64 p, [%0], %1;\n@p bra WD;\n"
               "add.u32 n, n, 1;\nsetp.lt.u32 p, n, 65536;\n@p bra WL;\nWD:\n}" ::"r"(bar), "r"(parity) : "memory");
}
__device__ __forceinline__ void nb_sync(int id, int n) { asm volatile("bar.sync %0, %1;" ::"r"(id), "r"(n) : "memory"); }
__device__ __forceinline__ void nb_arrive(int id, int n) { asm volatile("bar.arrive %0, %1;" ::"r"(id), "r"(n) : "memory"); }
__device__ __forceinline__ uint32_t opq(uint32_t x) { uint32_t r; asm volatile("mov.b32 %0, %1;" : "=r"(r) : "r"(x)); return r; }
__device__ __forceinline__ uint64_t opq(uint64_t x) { uint64_t r; asm volatile("mov.b64 %0, %1;" : "=l"(r) : "l"(x)); return r; }
__device__ __forceinline__ uint32_t mapa(uint32_t a, uint32_t cta) { uint32_t r; asm("mapa.shared::cluster.u32 %0, %1, %2;" : "=r"(r) : "r"(a), "r"(cta)); return r; }
__device__ __forceinline__ void fence_async() { asm volatile("fence.proxy.async.shared::cta;" ::: "memory"); }
__device__ __forceinline__ void cluster_sync() {
  asm volatile("barrier.cluster.arrive.relaxed.aligned;\nbarrier.cluster.wait.aligned;" ::: "memory");
}
__device__ __forceinline__ uint32_t pack2(float lo, float hi) {
  uint32_t r; asm("cvt.rn.bf16x2.f32 %0, %1, %2;" : "=r"(r) : "f"(hi), "f"(lo)); return r;
}
__device__ __forceinline__ void stsm4(uint32_t a, uint32_t r0, uint32_t r1, uint32_t r2, uint32_t r3) {
  asm volatile("stmatrix.sync.aligned.m8n8.x4.shared.b16 [%0], {%1,%2,%3,%4};" ::"r"(a), "r"(r0), "r"(r1), "r"(r2), "r"(r3) : "memory");
}
__device__ __forceinline__ void ldsm4(uint32_t a, uint32_t& r0, uint32_t& r1, uint32_t& r2, uint32_t& r3) {
  asm volatile("ldmatrix.sync.aligned.m8n8.x4.shared.b16 {%0,%1,%2,%3}, [%4];" : "=r"(r0), "=r"(r1), "=r"(r2), "=r"(r3) : "r"(a) : "memory");
}
__device__ __forceinline__ void sts128(uint32_t a, uint4 v) {
  asm volatile("st.shared.v4.b32 [%0], {%1,%2,%3,%4};" ::"r"(a), "r"(v.x), "r"(v.y), "r"(v.z), "r"(v.w) : "memory");
}
__device__ __forceinline__ float lds_f32(uint32_t a) { float v; asm volatile("ld.shared.f32 %0, [%1];" : "=f"(v) : "r"(a)); return v; }
__device__ __forceinline__ float ex2(float x) { float y; asm("ex2.approx.ftz.f32 %0, %1;" : "=f"(y) : "f"(x)); return y; }

template<int SC> __device__ __forceinline__ void wg_ss144(float (&d)[72], uint64_t da, uint64_t db) {
  asm volatile("{\n.reg .pred p;\nsetp.ne.b32 p, %74, 0;\nwgmma.mma_async.sync.aligned.m64n144k16.f32.bf16.bf16 {%0,%1,%2,%3,%4,%5,%6,%7,%8,%9,%10,%11,%12,%13,%14,%15,%16,%17,%18,%19,%20,%21,%22,%23,%24,%25,%26,%27,%28,%29,%30,%31,%32,%33,%34,%35,%36,%37,%38,%39,%40,%41,%42,%43,%44,%45,%46,%47,%48,%49,%50,%51,%52,%53,%54,%55,%56,%57,%58,%59,%60,%61,%62,%63,%64,%65,%66,%67,%68,%69,%70,%71}, %72, %73, p, 1, 1, 0, 1;\n}\n"
    : "+f"(d[0]),"+f"(d[1]),"+f"(d[2]),"+f"(d[3]),"+f"(d[4]),"+f"(d[5]),"+f"(d[6]),"+f"(d[7]),"+f"(d[8]),"+f"(d[9]),"+f"(d[10]),"+f"(d[11]),"+f"(d[12]),"+f"(d[13]),"+f"(d[14]),"+f"(d[15]),"+f"(d[16]),"+f"(d[17]),"+f"(d[18]),"+f"(d[19]),"+f"(d[20]),"+f"(d[21]),"+f"(d[22]),"+f"(d[23]),"+f"(d[24]),"+f"(d[25]),"+f"(d[26]),"+f"(d[27]),"+f"(d[28]),"+f"(d[29]),"+f"(d[30]),"+f"(d[31]),"+f"(d[32]),"+f"(d[33]),"+f"(d[34]),"+f"(d[35]),"+f"(d[36]),"+f"(d[37]),"+f"(d[38]),"+f"(d[39]),"+f"(d[40]),"+f"(d[41]),"+f"(d[42]),"+f"(d[43]),"+f"(d[44]),"+f"(d[45]),"+f"(d[46]),"+f"(d[47]),"+f"(d[48]),"+f"(d[49]),"+f"(d[50]),"+f"(d[51]),"+f"(d[52]),"+f"(d[53]),"+f"(d[54]),"+f"(d[55]),"+f"(d[56]),"+f"(d[57]),"+f"(d[58]),"+f"(d[59]),"+f"(d[60]),"+f"(d[61]),"+f"(d[62]),"+f"(d[63]),"+f"(d[64]),"+f"(d[65]),"+f"(d[66]),"+f"(d[67]),"+f"(d[68]),"+f"(d[69]),"+f"(d[70]),"+f"(d[71]) : "l"(da), "l"(db), "n"(SC));
}
template<int SC> __device__ __forceinline__ void wg_ss96(float (&d)[48], uint64_t da, uint64_t db) {
  asm volatile("{\n.reg .pred p;\nsetp.ne.b32 p, %50, 0;\nwgmma.mma_async.sync.aligned.m64n96k16.f32.bf16.bf16 {%0,%1,%2,%3,%4,%5,%6,%7,%8,%9,%10,%11,%12,%13,%14,%15,%16,%17,%18,%19,%20,%21,%22,%23,%24,%25,%26,%27,%28,%29,%30,%31,%32,%33,%34,%35,%36,%37,%38,%39,%40,%41,%42,%43,%44,%45,%46,%47}, %48, %49, p, 1, 1, 0, 1;\n}\n"
    : "+f"(d[0]),"+f"(d[1]),"+f"(d[2]),"+f"(d[3]),"+f"(d[4]),"+f"(d[5]),"+f"(d[6]),"+f"(d[7]),"+f"(d[8]),"+f"(d[9]),"+f"(d[10]),"+f"(d[11]),"+f"(d[12]),"+f"(d[13]),"+f"(d[14]),"+f"(d[15]),"+f"(d[16]),"+f"(d[17]),"+f"(d[18]),"+f"(d[19]),"+f"(d[20]),"+f"(d[21]),"+f"(d[22]),"+f"(d[23]),"+f"(d[24]),"+f"(d[25]),"+f"(d[26]),"+f"(d[27]),"+f"(d[28]),"+f"(d[29]),"+f"(d[30]),"+f"(d[31]),"+f"(d[32]),"+f"(d[33]),"+f"(d[34]),"+f"(d[35]),"+f"(d[36]),"+f"(d[37]),"+f"(d[38]),"+f"(d[39]),"+f"(d[40]),"+f"(d[41]),"+f"(d[42]),"+f"(d[43]),"+f"(d[44]),"+f"(d[45]),"+f"(d[46]),"+f"(d[47]) : "l"(da), "l"(db), "n"(SC));
}
template<int SC> __device__ __forceinline__ void wg_rs112(float (&d)[56], uint32_t a0, uint32_t a1, uint32_t a2, uint32_t a3, uint64_t db) {
  asm volatile("{\n.reg .pred p;\nsetp.ne.b32 p, %61, 0;\nwgmma.mma_async.sync.aligned.m64n112k16.f32.bf16.bf16 {%0,%1,%2,%3,%4,%5,%6,%7,%8,%9,%10,%11,%12,%13,%14,%15,%16,%17,%18,%19,%20,%21,%22,%23,%24,%25,%26,%27,%28,%29,%30,%31,%32,%33,%34,%35,%36,%37,%38,%39,%40,%41,%42,%43,%44,%45,%46,%47,%48,%49,%50,%51,%52,%53,%54,%55}, {%56,%57,%58,%59}, %60, p, 1, 1, 0;\n}\n"
    : "+f"(d[0]),"+f"(d[1]),"+f"(d[2]),"+f"(d[3]),"+f"(d[4]),"+f"(d[5]),"+f"(d[6]),"+f"(d[7]),"+f"(d[8]),"+f"(d[9]),"+f"(d[10]),"+f"(d[11]),"+f"(d[12]),"+f"(d[13]),"+f"(d[14]),"+f"(d[15]),"+f"(d[16]),"+f"(d[17]),"+f"(d[18]),"+f"(d[19]),"+f"(d[20]),"+f"(d[21]),"+f"(d[22]),"+f"(d[23]),"+f"(d[24]),"+f"(d[25]),"+f"(d[26]),"+f"(d[27]),"+f"(d[28]),"+f"(d[29]),"+f"(d[30]),"+f"(d[31]),"+f"(d[32]),"+f"(d[33]),"+f"(d[34]),"+f"(d[35]),"+f"(d[36]),"+f"(d[37]),"+f"(d[38]),"+f"(d[39]),"+f"(d[40]),"+f"(d[41]),"+f"(d[42]),"+f"(d[43]),"+f"(d[44]),"+f"(d[45]),"+f"(d[46]),"+f"(d[47]),"+f"(d[48]),"+f"(d[49]),"+f"(d[50]),"+f"(d[51]),"+f"(d[52]),"+f"(d[53]),"+f"(d[54]),"+f"(d[55]) : "r"(a0), "r"(a1), "r"(a2), "r"(a3), "l"(db), "n"(SC));
}
template<int SC> __device__ __forceinline__ void wg_sp48(float (&d)[24], uint32_t a0, uint32_t a1, uint32_t a2, uint32_t a3, uint64_t db, uint32_t meta) {
  asm volatile("{\n.reg .pred p;\nsetp.ne.b32 p, %30, 0;\nwgmma.mma_async.sp.sync.aligned.m64n48k32.f32.bf16.bf16 {%0,%1,%2,%3,%4,%5,%6,%7,%8,%9,%10,%11,%12,%13,%14,%15,%16,%17,%18,%19,%20,%21,%22,%23}, {%24,%25,%26,%27}, %28, %29, 0, p, 1, 1, 1;\n}\n"
    : "+f"(d[0]),"+f"(d[1]),"+f"(d[2]),"+f"(d[3]),"+f"(d[4]),"+f"(d[5]),"+f"(d[6]),"+f"(d[7]),"+f"(d[8]),"+f"(d[9]),"+f"(d[10]),"+f"(d[11]),"+f"(d[12]),"+f"(d[13]),"+f"(d[14]),"+f"(d[15]),"+f"(d[16]),"+f"(d[17]),"+f"(d[18]),"+f"(d[19]),"+f"(d[20]),"+f"(d[21]),"+f"(d[22]),"+f"(d[23]) : "r"(a0), "r"(a1), "r"(a2), "r"(a3), "l"(db), "r"(meta), "n"(SC));
}
template<int SC> __device__ __forceinline__ void wg_rs64(float (&d)[32], uint32_t a0, uint32_t a1, uint32_t a2, uint32_t a3, uint64_t db) {
  asm volatile("{\n.reg .pred p;\nsetp.ne.b32 p, %37, 0;\nwgmma.mma_async.sync.aligned.m64n64k16.f32.bf16.bf16 {%0,%1,%2,%3,%4,%5,%6,%7,%8,%9,%10,%11,%12,%13,%14,%15,%16,%17,%18,%19,%20,%21,%22,%23,%24,%25,%26,%27,%28,%29,%30,%31}, {%32,%33,%34,%35}, %36, p, 1, 1, 0;\n}\n"
    : "+f"(d[0]),"+f"(d[1]),"+f"(d[2]),"+f"(d[3]),"+f"(d[4]),"+f"(d[5]),"+f"(d[6]),"+f"(d[7]),"+f"(d[8]),"+f"(d[9]),"+f"(d[10]),"+f"(d[11]),"+f"(d[12]),"+f"(d[13]),"+f"(d[14]),"+f"(d[15]),"+f"(d[16]),"+f"(d[17]),"+f"(d[18]),"+f"(d[19]),"+f"(d[20]),"+f"(d[21]),"+f"(d[22]),"+f"(d[23]),"+f"(d[24]),"+f"(d[25]),"+f"(d[26]),"+f"(d[27]),"+f"(d[28]),"+f"(d[29]),"+f"(d[30]),"+f"(d[31]) : "r"(a0), "r"(a1), "r"(a2), "r"(a3), "l"(db), "n"(SC));
}

constexpr uint32_t SBC = 1024;
constexpr int ROWB = 2 * 224 * 384;
constexpr int TB = 11;
constexpr int KS = 832;
constexpr int KSLOT = 22 * KS;
constexpr int SM_X2 = 0;
constexpr int SM_X0 = SM_X2 + 24576;
constexpr int SM_W = SM_X0 + 18432;
constexpr int SM_X1 = SM_W + 55296;
constexpr int SM_K = SM_X1 + 24576;
constexpr int SM_V = SM_K + 2 * KSLOT;
constexpr int SM_Q = SM_V + 22 * 1536;
constexpr int SM_O = SM_Q + 24576;
constexpr int SM_RPB = SM_O + 12288;
constexpr int SM_BAR = SM_RPB + 768;
constexpr int SM_A_TOTAL = SM_BAR + 256;
constexpr int SM_TIN = 0;
constexpr int SM_TST = 3 * 24576;
constexpr int SM_TWO = SM_TST + 12288;
enum { B_FULL = 0, B_EMPTY = 3, B_TIN = 6, B_TFREE = 10, B_WK = 12, B_WQ, B_WO, B_KIMP, B_VIMP, B_PKF, B_PVF, B_XK, B_XV, B_OFREE,
       B_Q0, B_WOFREE, B_OTAIL, B_ODONE = B_OTAIL + 2, B_KFREE, B_VFREE, B_COUNT };
enum { N_KRDY = 4, N_QK0, N_QK1, N_VQ0, N_VQ1, N_PVISS };

#define NL 2
#define OPT 0
#define SPL 4
#define RA 160
#define RG 168
__device__ int g_flags[TB * 56];

#define TR(role, it, k)
#define TRDECL
#define TRARG
#define TRPASS
#define TRDUMP
#define TRB(it, k)
#define TR2(blk, k)

struct GemmCtx {
  uint32_t bar;
  uint32_t kC, vC[2], qC[2];
  uint32_t kH, vH[2];
  uint32_t hiA, hiB;
  uint32_t spin;
  uint32_t em[3];
  bool hvalid, never, edge;
};

template <int STRIDE> __device__ __forceinline__ void dump12(uint32_t a, const uint32_t (&r)[12]) {
#pragma unroll
  for (int j = 0; j < 3; j++) stsm4(a + j * 2 * STRIDE, r[4 * j], r[4 * j + 1], r[4 * j + 2], r[4 * j + 3]);
}
__device__ __forceinline__ void keep12(bool never, uint32_t a, const uint32_t (&r)[12]) { if (never) dump12<128>(a, r); }
template <int N> __device__ __forceinline__ void pack12(uint32_t (&r)[12], const float (&d)[N], int off) {
#pragma unroll
  for (int j = 0; j < 12; j++) r[j] = pack2(d[off + 2 * j], d[off + 2 * j + 1]);
}
__device__ __forceinline__ uint64_t dsc(uint64_t lo, uint32_t hi) { uint64_t r; asm("mov.b64 %0, {%1, %2};" : "=l"(r) : "r"((uint32_t)lo), "r"(hi)); return r; }
template <int XS, int K0, int K1> __device__ __forceinline__ void issue_core(const GemmCtx& c, float (&d)[72]) {
  constexpr uint64_t da = mkdesc(SBC + XS, 16, 1024, 1), db = mkdesc(SBC + SM_W, 6144, 256, 3);
  wg_fence();
  if (K0 == 0) wg_ss144<0>(d, dsc(da, c.hiA), dsc(db, c.hiB));
#pragma unroll
  for (int k = K0 ? K0 : 1; k < K1; k++) wg_ss144<1>(d, dsc(da + (k >> 2) * 512 + (k & 3) * 2, c.hiA), dsc(db + k * 32, c.hiB));
  wg_commit();
}
template <int K0, int K1> __device__ __forceinline__ void issue_halo(const GemmCtx& c, float (&d)[48]) {
  constexpr uint64_t da = mkdesc(SBC + SM_X0 - 2048, 16, 1024, 1), db = mkdesc(SBC + SM_W, 6144, 256, 3);
  wg_fence();
  if (K0 == 0) wg_ss96<0>(d, dsc(da, c.hiA), dsc(db, c.hiB));
#pragma unroll
  for (int k = K0 ? K0 : 1; k < K1; k++) wg_ss96<1>(d, dsc(da + (k >> 2) * 384 + (k & 3) * 2, c.hiA), dsc(db + k * 32, c.hiB));
  wg_commit();
}
template <int ST> __device__ __forceinline__ void release_stage(const GemmCtx& c) {
  asm volatile("{\n.reg .pred p;\nelect.sync _|p, 0xffffffff;\n@p mbarrier.arrive.shared::cluster.b64 _, [%0];\n}" ::"r"(c.em[ST]) : "memory");
}
__device__ __forceinline__ void edge_ready(const GemmCtx& c, int bar) { __syncwarp(); if (c.edge) mbar_arrive_elect(c.bar + bar * 8); }
__device__ __forceinline__ void dump6(uint32_t a, const uint32_t (&r)[6]) {
  stsm4(a, r[0], r[1], r[2], r[3]);
  asm volatile("stmatrix.sync.aligned.m8n8.x2.shared.b16 [%0], {%1,%2};" ::"r"(a + 512), "r"(r[4]), "r"(r[5]) : "memory");
}
__device__ __forceinline__ void pack6(uint32_t (&r)[6], const float (&d)[48], int off) {
#pragma unroll
  for (int j = 0; j < 6; j++) r[j] = pack2(d[off + 4 * j], d[off + 4 * j + 1]);
}
template <int PARITY> __device__ __forceinline__ void gwait(GemmCtx& c, int bar) {
  asm volatile("{\n.reg .pred p;\nWL:\nmbarrier.try_wait.parity.shared::cta.b64 p, [%1], %2;\n@p bra WD;\n"
               "add.u32 %0, %0, 1;\nsetp.lt.u32 p, %0, 0x100000;\n@p bra WL;\nWD:\n}" : "+r"(c.spin) : "r"(c.bar + bar * 8), "n"(PARITY) : "memory");
}
__device__ __forceinline__ void load_w(const CUtensorMap* m, uint32_t dst, uint32_t bar, int col) {
  asm volatile("cp.async.bulk.tensor.2d.shared::cluster.global.mbarrier::complete_tx::bytes [%0], [%1, {%3,%4}], [%2];"
               ::"r"(dst), "l"(m), "r"(bar), "r"(col), "r"(0) : "memory");
}
template <int BYTES> __device__ __forceinline__ void send_o(uint32_t dst, uint32_t src, uint32_t bar, int cta) {
  asm volatile("{\n.reg .b32 rd, rb;\nmapa.shared::cluster.u32 rd, %0, %3;\nmapa.shared::cluster.u32 rb, %2, %3;\n"
               "cp.async.bulk.shared::cluster.shared::cta.mbarrier::complete_tx::bytes [rd], [%1], %4, [rb];\n}"
               ::"r"(dst), "r"(src), "r"(bar), "r"(cta), "n"(BYTES) : "memory");
}
__device__ __forceinline__ void remote_arrive(uint32_t rbar) { asm volatile("mbarrier.arrive.shared::cluster.b64 _, [%0];" ::"r"(rbar) : "memory"); }
__device__ __forceinline__ void remote_expect(uint32_t rbar, uint32_t bytes) {
  asm volatile("mbarrier.arrive.expect_tx.shared::cluster.b64 _, [%0], %1;" ::"r"(rbar), "r"(bytes) : "memory");
}
__device__ __forceinline__ void copy_remote(uint32_t rdst, uint32_t src, uint32_t bytes, uint32_t rbar) {
  asm volatile("cp.async.bulk.shared::cluster.shared::cta.mbarrier::complete_tx::bytes [%0], [%1], %2, [%3];" ::"r"(rdst), "r"(src), "r"(bytes), "r"(rbar) : "memory");
}
__device__ __forceinline__ void tail_free(uint32_t bar) {
  uint32_t ln; asm volatile("mov.u32 %0, %%laneid;" : "=r"(ln));
  if (ln < 4) mbar_arrive_remote(bar, ln + (blockIdx.x & 4));
}
__device__ __forceinline__ void publish(uint32_t bar) {
  fence_async();
  __syncwarp();
  mbar_arrive_elect(bar);
}

template <bool FIRST, int PA>
__device__ __forceinline__ void gemm_iter(GemmCtx& c, int b, uint32_t (&pk)[12], uint32_t (&pv)[12], uint32_t (&pq)[12],
                                          uint32_t (&hk1)[6], uint32_t (&hv1)[6] TRARG) {
  const uint32_t bar = c.bar;
  const bool w = !FIRST && (PA == 0 || b >= 0), never = c.never;
  constexpr uint32_t ko = PA * KSLOT;
  float C[72];
  uint32_t hk0[6], hv0[6], pv2[12];
  TR(2, b, 0);
  if (FIRST) gwait<0>(c, B_FULL + 0);
  else dump12<256>(c.qC[1] + (PA ^ 1) * 128, pq);
  if (w) nb_sync(N_QK1, 256);
  TR(2, b, 2);
  if (PA == 0) {
    float H[48];
    issue_halo<0, 8>(c, H);
    TR(2, b, 3);
    if (!FIRST) { gwait<0>(c, B_KFREE); dump12<128>(c.kC, pk); }
    issue_halo<8, 12>(c, H);
    TR(2, b, 4);
    gwait<0>(c, B_FULL + 2);
    if (FIRST) gwait<0>(c, B_WQ);
    issue_core<SM_X2, 0, 8>(c, C);
    TR(2, b, 5);
    if (!FIRST) { fence_async(); edge_ready(c, B_XV); keep12(never, c.kC, pk); }
    wg_wait<1>(); pin(H);
    release_stage<0>(c);
    pack6(hk0, H, 0);
    if (c.hvalid) dump6(c.kH, hk0);
    pack6(hk1, H, 2); pack6(hv0, H, 24); pack6(hv1, H, 26);
  } else {
    issue_core<SM_X2, 0, 8>(c, C);
    TR(2, b, 5);
    fence_async();
    if (w) edge_ready(c, B_XV);
    keep12(never, c.kC, pq);
    if (w) gwait<1>(c, B_KFREE);
    dump12<128>(c.kC + ko, pk);
    if (c.hvalid) dump6(c.kH + ko, hk1);
  }
  TR(2, b, 13);
  issue_core<SM_X2, 8, 12>(c, C);
  if (w) { nb_arrive(N_VQ0, 288); nb_arrive(N_VQ1, 288); }
  else if (!FIRST) { __syncwarp(); mbar_arrive_elect(bar + B_Q0 * 8); }
  gwait<PA>(c, B_FULL + 1);
  if (never) dump6(bar, PA ? hk1 : hk0);
  TR(2, b, 6);
  wg_wait<0>(); pin(C);
  TR(2, b, 7);
  pack12(pk, C, 0);
  dump12<128>(c.kC + ko + 64, pk);
  release_stage<2>(c);
  pack12(pv2, C, 24);
  pack12(pq, C, 48);
  TR(2, b, 8);
  issue_core<SM_X1, 0, SPL>(c, C);
  if (w) nb_sync(N_PVISS, 384);
  issue_core<SM_X1, SPL, 8>(c, C);
  TR(2, b, 9);
  if (!FIRST) { fence_async(); edge_ready(c, B_XK); }
  keep12(never, c.kC, pk);
  TR(2, b, 14);
  issue_core<SM_X1, 8, 12>(c, C);
  if (!FIRST) nb_arrive(N_KRDY, 256);
  TR(2, b, 1);
  if (PA) { if (b == 11) tail_free(bar + B_TFREE * 8); mbar_wait(bar + B_FULL * 8, ((b + 3) >> 1) & 1); }
  if (w) gwait<PA>(c, B_VFREE);
  TR(2, b, 10);
  if (!FIRST) dump12<128>(c.vC[PA], pv);
  dump12<256>(c.qC[0] + PA * 128, pq);
  if (c.hvalid) dump6(c.vH[PA], PA ? hv1 : hv0);
  dump12<128>(c.vC[PA ^ 1] + 768, pv2);
  if (PA == 0) gwait<1>(c, B_FULL + 2);
  TR(2, b, 11);
  wg_wait<0>(); pin(C);
  TR(2, b, 12);
  release_stage<1>(c);
  pack12(pk, C, 0);
  pack12(pv, C, 24);
  pack12(pq, C, 48);
}

template <int IN> __device__ __forceinline__ void issue_proj(float (&D)[48]) {
  constexpr uint64_t da = mkdesc(SBC + IN, 128, 768, 0), db = mkdesc(SBC + SM_TWO, 12288, 512, 2);
  wg_fence();
  wg_ss96<0>(D, da, db);
#pragma unroll
  for (int k = 1; k < 12; k++) wg_ss96<1>(D, da + (k / 3) * 384 + (k % 3) * 16, db + k * 64);
  wg_commit();
}
template <int ACC> __device__ __forceinline__ void issue_proj_half(float (&D)[48], int hd) {
  const uint64_t da = mkdesc(SBC + SM_TIN + 2 * 24576, 128, 768, 0) + hd * 384, db = mkdesc(SBC + SM_TWO, 12288, 512, 2) + hd * 192;
  wg_fence();
  wg_ss96<ACC>(D, da, db);
#pragma unroll
  for (int k = 1; k < 6; k++) wg_ss96<1>(D, da + (k / 3) * 768 + (k % 3) * 16, db + (k / 3) * 384 + (k % 3) * 64);
  wg_commit();
}
__device__ __forceinline__ void store_proj(const float (&D)[48], const CUtensorMap* m, uint32_t st, uint32_t sta, int row, int col, int ch) {
#pragma unroll
  for (int q = 0; q < 6; q++)
    stsm4((sta ^ ((q & 1) * 32)) + (q >> 1) * 1024,
          pack2(D[8 * q], D[8 * q + 1]), pack2(D[8 * q + 2], D[8 * q + 3]), pack2(D[8 * q + 4], D[8 * q + 5]), pack2(D[8 * q + 6], D[8 * q + 7]));
  fence_async();
  __syncwarp();
  if ((threadIdx.x & 31) == 0) {
    asm volatile("cp.async.bulk.tensor.4d.global.shared::cta.bulk_group [%0, {%2,%3,%4,%5}], [%1];" ::"l"(m), "r"(st), "r"(0), "r"(row), "r"(col), "r"(ch) : "memory");
    asm volatile("cp.async.bulk.commit_group;" ::: "memory");
  }
  __syncwarp();
}

__device__ __forceinline__ float fold(float a, float b, float t, int useb) {
  float r;
  asm("{\n.reg .pred p;\nsetp.ne.b32 p, %4, 0;\nfma.rn.f32 %0, %1, 0f3E553B95, %3;\n@p fma.rn.f32 %0, %2, 0f3E553B95, %3;\n}"
      : "=&f"(r) : "f"(a), "f"(b), "f"(t), "r"(useb));
  return r;
}
template <int U, int L>
__device__ __forceinline__ void softmax_tile(const float (&SA)[56], const float (&SB)[56], const float (&T)[16], int b0, int b1,
                                             uint32_t (&P)[28], float (&sx)[8]) {
  float lu[14], ll[14];
#pragma unroll
  for (int j = 0; j < 7; j++) {
    constexpr int sh = U == L ? 2 : 0;
    const float tu0 = T[2 * j + sh], tu1 = T[2 * j + 1 + sh], tl0 = T[2 * j], tl1 = T[2 * j + 1];
    lu[2 * j]     = fold(SA[4 * (U + j)],     SB[4 * (U + j)],     tu0, b0);
    ll[2 * j]     = fold(SA[4 * (L + j) + 2], SB[4 * (L + j) + 2], tl0, b0);
    lu[2 * j + 1] = fold(SA[4 * (U + j) + 1], SB[4 * (U + j) + 1], tu1, b1);
    ll[2 * j + 1] = fold(SA[4 * (L + j) + 3], SB[4 * (L + j) + 3], tl1, b1);
  }
  float mu = lu[0], ml = ll[0], mu2 = lu[1], ml2 = ll[1];
#pragma unroll
  for (int j = 1; j < 7; j++) { mu = fmaxf(mu, lu[2 * j]); mu2 = fmaxf(mu2, lu[2 * j + 1]); ml = fmaxf(ml, ll[2 * j]); ml2 = fmaxf(ml2, ll[2 * j + 1]); }
  mu = fmaxf(mu, mu2); ml = fmaxf(ml, ml2);
  { const float a1 = __shfl_xor_sync(0xffffffffu, mu, 1), a2 = __shfl_xor_sync(0xffffffffu, mu, 2), a3 = __shfl_xor_sync(0xffffffffu, mu, 3);
    const float c1 = __shfl_xor_sync(0xffffffffu, ml, 1), c2 = __shfl_xor_sync(0xffffffffu, ml, 2), c3 = __shfl_xor_sync(0xffffffffu, ml, 3);
    mu = fmaxf(fmaxf(mu, a1), fmaxf(a2, a3)); ml = fmaxf(fmaxf(ml, c1), fmaxf(c2, c3)); }
  float su = 0.f, sl = 0.f;
#pragma unroll
  for (int c = 0; c < 14; c++) {
    const int iu = (c >> 1) * 4 + (c & 1) * 2;
    if (c >= U && c < U + 7) {
      float e0 = ex2(lu[2 * (c - U)] - mu), e1 = ex2(lu[2 * (c - U) + 1] - mu);
      su = c == U ? e0 + e1 : (su + e0) + e1; P[iu] = pack2(e0, e1);
    } else P[iu] = 0u;
    if (c >= L && c < L + 7) {
      float e0 = ex2(ll[2 * (c - L)] - ml), e1 = ex2(ll[2 * (c - L) + 1] - ml);
      sl = c == L ? e0 + e1 : (sl + e0) + e1; P[iu + 1] = pack2(e0, e1);
    } else P[iu + 1] = 0u;
  }
  sx[0] = su; sx[4] = sl;
#pragma unroll
  for (int k = 1; k < 4; k++) { sx[k] = __shfl_xor_sync(0xffffffffu, su, k); sx[4 + k] = __shfl_xor_sync(0xffffffffu, sl, k); }
}

struct BandCfg { uint32_t ra0, ra1, meta; int b0, b1; };
__device__ __forceinline__ void band_cfg(int b, uint32_t tb, BandCfg& n) {
  uint32_t ln; asm volatile("mov.u32 %0, %%laneid;" : "=r"(ln));
  const int g = ln >> 2, t = ln & 3;
  const int sw = min(max(g + 1, b == 0 ? 4 : 0), b == 13 ? 5 : 8);
  const int i0 = 2 * t, i1 = 2 * t + 1;
  n.b0 = i0 <= sw - 2; n.b1 = i1 <= sw - 2;
  n.ra0 = tb + (i0 == sw - 1 ? 13 : i0 + 8 * n.b0 - g + 2) * 52;
  n.ra1 = tb + (i1 == sw - 1 ? 13 : i1 + 8 * n.b1 - g + 2) * 52;
  n.meta = ((0x5555u & ((1u << (2 * (sw - 1))) - 1)) ^ 0xDD88u ^ (((t ^ b) & 1) ? 0x5555u : 0u)) * 0x10001u;
}
__device__ __forceinline__ void band_load(const BandCfg& n, float (&T)[16], int& b0, int& b1, uint32_t& meta) {
#pragma unroll
  for (int jj = 0; jj < 8; jj++) { T[2 * jj] = lds_f32(n.ra0 + jj * 4); T[2 * jj + 1] = lds_f32(n.ra1 + jj * 4); }
  b0 = n.b0; b1 = n.b1; meta = n.meta;
}

struct Maps { CUtensorMap xc, xh, w, os, wo, ot; };

__global__ void __cluster_dims__(8, 1, 1) __launch_bounds__(512, 1)
na_attn_kernel(const __nv_bfloat16* __restrict__ x, const __nv_bfloat16* __restrict__ wqkv, const __nv_bfloat16* __restrict__ rpb, const __grid_constant__ Maps mp) {
  extern __shared__ __align__(1024) uint8_t smem_raw[];
  const uint32_t sb = smem_u32(smem_raw);
  if ((sb & 0x3FFFF) != SBC) return;
  const uint32_t bar = sb + SM_BAR;
  TR2(blockIdx.x, 0);
  const int tid = threadIdx.x, lane = tid & 31;
  const int warp = __shfl_sync(0xffffffffu, tid >> 5, 0);
  const int head = blockIdx.x & 3, base = blockIdx.x & 4, sp = blockIdx.x >> 2;
  const int par = sp < 24 ? sp / 6 : sp - 24, strip = sp < 24 ? sp - par * 6 : 6, ph = par >> 1, pw = par & 1;
  const int odd = strip & 1;

  uint4 wv[2 * NL];
  const int va = head == 1;
  const uint32_t wdst = sb + SM_W + (va + ((tid >> 1) & 1)) * 6144 + (tid >> 2) * 32 + ((tid ^ (tid >> 4)) & 1) * 16;
  if (warp < 12) asm volatile("barrier.cluster.arrive.relaxed.aligned;" ::: "memory");
  {
    const uint32_t wo0 = (tid >> 2) * 1152 + head * 96 + va * 32 + (tid & 3) * 16;
#pragma unroll
    for (int i = 0; i < 2 * NL; i++)
      asm volatile("{\n.reg .pred p;\nsetp.lt.u32 p, %5, 384;\n@p ld.global.nc.v4.b32 {%0,%1,%2,%3}, [%4];\n}"
                   : "=r"(wv[i].x), "=r"(wv[i].y), "=r"(wv[i].z), "=r"(wv[i].w)
                   : "l"(reinterpret_cast<const uint8_t*>(wqkv) + wo0 + (i & 1) * 96 * 1152 + ((i / 2 + 1) % 3) * 384), "r"(tid));
  }
  if (warp < 8) {
    asm volatile("setmaxnreg.inc.sync.aligned.u32 %0;" ::"n"(RA));
    float rv = -INFINITY;
    if (tid < 169) rv = __bfloat162float(rpb[head * 169 + tid]) * 1.4426950408889634f;
    if (tid < 192) {
      const int kc = (tid & 15) + 3, wc = (tid >> 4) % 6;
      sts128(tid < 96 ? sb + SM_K + kc * KS + wc * 128 + 48 : sb + SM_V + kc * 1536 + wc * 128 + (6 + (kc & 1)) * 16, make_uint4(0, 0, 0, 0));
    }
#pragma unroll
    for (int i = 0; i < 2 * NL; i++) sts128(wdst + (i & 1) * 3072 + (i / 2) * 18432, wv[i]);
    fence_async();
    asm volatile("bar.arrive 1, 384;" ::: "memory");
    if (tid < 182) asm volatile("st.shared.f32 [%0], %1;" ::"r"(sb + SM_RPB + tid * 4), "f"(rv) : "memory");
    const int jw = warp >> 2, j = jw ^ odd, w = warp & 3, wt = 4 * j + w;
    int variant = w;
    if (strip == 0 && j == 0 && w < 2) variant = 4;
    if (strip == 6 && j == 1 && w >= 2) variant = 5;
    const bool v1 = opq((uint32_t)(variant & 1)), v2 = opq((uint32_t)(variant & 2)), v4 = opq((uint32_t)(variant & 4));
    uint32_t qa = opq(sb + SM_Q + (8 * j + 2 * w + ((lane >> 3) & 1)) * 1536 + (lane >> 4) * 256 + (((lane & 7) * 16) ^ (((lane >> 3) & 1) * 64)));
    uint32_t oa = opq(sb + SM_O + j * 6144 + (2 * w + ((lane >> 3) & 1)) * 768 + (lane >> 4) * 128 + (lane & 7) * 16);
    uint64_t dA = opq(mkdesc(SBC + SM_K, 128, KS, 0) + j * (8 * KS / 16)), dB = opq(dA + (KSLOT >> 4));
    uint64_t dV[7];
#pragma unroll
    for (int i = 0; i < 7; i++) dV[i] = opq(mkdesc(SBC + SM_V, 768, 128, 0) + j * (8 * 1536 / 16) + i * 192);
    const uint32_t nbK = opq((uint32_t)(N_KRDY + jw)), nbQ = opq((uint32_t)(N_QK0 + jw)), nbV = opq((uint32_t)(N_VQ0 + jw));
    asm volatile("barrier.cluster.wait.aligned;" ::: "memory");
    asm volatile("bar.sync 3, 256;" ::: "memory");
    float T[16];
    TRDECL;
    int b0, b1;
    uint32_t meta, ob = bar + B_ODONE * 8;
    const uint32_t tb = opq(sb + SM_RPB + (variant < 4 ? 3 : variant + 1 - 2 * w) * 4);
    const bool own = ((w ^ head) & 2) == 0;
    const uint32_t dst13 = sb + SM_TIN + 2 * 24576 + head * 6144 + (2 * j + (w & 1)) * 1536, src13 = opq(own ? dst13 : sb + SM_Q + wt * 3072 + 1536);
    const uint32_t snd[4] = {opq(own ? 0u : mapa(dst13, base + (head ^ 2))), opq(mapa(bar + (B_TIN + 2) * 8, base + (head ^ 2))),
                             opq(mapa(dst13, base + (w & 2) + (~head & 1))), opq(mapa(bar + (B_TIN + 3) * 8, base + (w & 2) + (~head & 1)))};
    BandCfg nx;
    band_cfg(0, tb, nx);
    band_load(nx, T, b0, b1, meta);
    band_cfg(1, tb, nx);
    uint32_t special = opq(0x380Au << 1);
    uint32_t q[12];
    mbar_wait(bar + B_Q0 * 8, 0);
#pragma unroll
    for (int k = 0; k < 3; k++) ldsm4(qa + k * 512, q[4 * k], q[4 * k + 1], q[4 * k + 2], q[4 * k + 3]);
    qa ^= 128;
#pragma unroll 1
    for (int b = 0; b < 14; b++) {
      float SA[56], SB[56];
      TR(0, b, 0);
      if (jw) mbar_wait(bar + B_KIMP * 8, b & 1);
      nb_sync(nbK, 256);
      TR(0, b, 1);
      TR(0, b - 1, 9);
      wg_fence();
      wg_rs112<0>(SA, q[0], q[1], q[2], q[3], dA);
      wg_rs112<0>(SB, q[0], q[1], q[2], q[3], dB);
      wg_rs112<1>(SA, q[4], q[5], q[6], q[7], dA + 16);
      wg_rs112<1>(SB, q[4], q[5], q[6], q[7], dB + 16);
      wg_rs112<1>(SA, q[8], q[9], q[10], q[11], dA + 32);
      wg_rs112<1>(SB, q[8], q[9], q[10], q[11], dB + 32);
      wg_commit();
      nb_arrive(nbQ, 256);
      { const uint64_t t = dA; dA = dB; dB = t; }
      special >>= 1;
      if (special & 1) {
        if (b == 3) band_cfg(13, tb, nx);
        else {
          if (b == 1 || b == 13) band_load(nx, T, b0, b1, meta);
          if (b >= TB) {
            ob = bar + (b == 13 && own ? B_TIN + 2 : B_OTAIL + jw) * 8;
            oa += b == 12 ? wt * 1536 - (SM_O - SM_Q) : (b == 13 ? src13 - (sb + SM_Q + wt * 3072) : 0);
          }
        }
      }
      TR(0, b, 2);
      wg_wait<0>(); pin(SA); pin(SB);
      mbar_arrive_elect(bar + B_KFREE * 8);
      TR(0, b, 3);
      TR(0, b - 1, 10);
      uint32_t P[28];
      float sx[8];
      if (v2) {
        if (v1) softmax_tile<6, 7>(SA, SB, T, b0, b1, P, sx); else softmax_tile<4, 5>(SA, SB, T, b0, b1, P, sx);
      } else if (!v4) {
        if (v1) softmax_tile<2, 3>(SA, SB, T, b0, b1, P, sx); else softmax_tile<0, 1>(SA, SB, T, b0, b1, P, sx);
      } else {
        if (v1) softmax_tile<4, 4>(SA, SB, T, b0, b1, P, sx); else softmax_tile<3, 3>(SA, SB, T, b0, b1, P, sx);
      }
      float O[24];
      TR(0, b, 4);
      nb_sync(nbV, 288);
      TR(0, b, 5);
#pragma unroll
      for (int k = 0; k < 3; k++) ldsm4(qa + k * 512, q[4 * k], q[4 * k + 1], q[4 * k + 2], q[4 * k + 3]);
      wg_fence();
      wg_sp48<0>(O, P[0], P[1], P[2], P[3], dV[0], meta);
#pragma unroll
      for (int s = 1; s < 7; s++) wg_sp48<1>(O, P[4 * s], P[4 * s + 1], P[4 * s + 2], P[4 * s + 3], dV[s], meta);
      wg_commit();
      nb_arrive(N_PVISS, 384);
      TR(0, b, 6);
      wg_wait<0>(); pin(O);
      mbar_arrive_elect(bar + B_VFREE * 8);
      TR(0, b, 7);
      float ru, rl;
      asm("rcp.approx.ftz.f32 %0, %1;" : "=f"(ru) : "f"(((fmaf(O[0], 0.f, sx[0]) + sx[1]) + sx[2]) + sx[3]));
      asm("rcp.approx.ftz.f32 %0, %1;" : "=f"(rl) : "f"(((fmaf(O[2], 0.f, sx[4]) + sx[5]) + sx[6]) + sx[7]));
#pragma unroll
      for (int i = 0; i < 3; i++)
        stsm4(oa + i * 256, pack2(O[8 * i] * ru, O[8 * i + 1] * ru), pack2(O[8 * i + 2] * rl, O[8 * i + 3] * rl),
              pack2(O[8 * i + 4] * ru, O[8 * i + 5] * ru), pack2(O[8 * i + 6] * rl, O[8 * i + 7] * rl));
      publish(ob);
      qa ^= 128;
      meta ^= 0x55555555u;
      TR(0, b, 8);
    }
    asm volatile("{\n.reg .pred p, q;\nsetp.ne.b32 q, %1, 0;\nelect.sync _|p, 0xffffffff;\nand.pred q, q, p;\n"
                 "@q cp.async.bulk.shared::cluster.shared::cta.mbarrier::complete_tx::bytes [%1], [%0], 1536, [%2];\n"
                 "@p cp.async.bulk.shared::cluster.shared::cta.mbarrier::complete_tx::bytes [%3], [%0], 1536, [%4];\n}"
                 ::"r"(src13), "r"(snd[0]), "r"(snd[1]), "r"(snd[2]), "r"(snd[3]) : "memory");
    if (jw == 0) nb_arrive(3, 256);
    TRDUMP;
    cluster_sync();
  } else if (warp < 12) {
    TRDECL;
    TR(2, -3, 0);
    asm volatile("setmaxnreg.inc.sync.aligned.u32 %0;" ::"n"(RG));
    TR(2, -3, 1);
    GemmCtx c;
    c.bar = bar;
    const int gw = warp - 8, tk = gw * 16 + (lane & 15), hi = lane >> 4;
    { const int col = tk >> 2, i = tk & 3;
      c.kC = sb + SM_K + (col + 3) * KS + hi * 128 + i * 16;
      c.vC[0] = sb + SM_V + (col + 3) * 1536 + hi * 128 + (2 * i + ((col + 3) & 1)) * 16;
      c.qC[0] = sb + SM_Q + col * 1536 + hi * 256 + (col & 1) * 64 + i * 16; }
    { const int kc = gw - 1 + 19 * odd, i = lane & 7; c.hvalid = gw > 0; c.edge = gw == (odd ? 0 : 3);
      c.kH = sb + SM_K + kc * KS + (lane >> 3) * 128 + i * 16;
      c.vH[0] = sb + SM_V + kc * 1536 + (lane >> 3) * 128 + (i >> 2) * 768 + (2 * (i & 3) + ((kc ^ (i >> 2)) & 1)) * 16; }
#pragma unroll
    for (int i = 0; i < 3; i++) c.em[i] = opq(mapa(bar + (B_EMPTY + i) * 8, base + i));
    c.never = x == nullptr;
    c.kC = opq(c.kC); c.kH = opq(c.kH);
    c.vC[1] = opq(c.vC[0] ^ 16); c.vC[0] = opq(c.vC[0]);
    c.vH[1] = opq(c.vH[0] ^ 16); c.vH[0] = opq(c.vH[0]);
    c.qC[1] = opq(c.qC[0] ^ 64); c.qC[0] = opq(c.qC[0]);
    c.spin = 0;
    c.hiA = (uint32_t)(mkdesc(0, 0, 1024, 1) >> 32) + (blockIdx.x >> 16); c.hiB = (uint32_t)(mkdesc(0, 0, 256, 3) >> 32) + (blockIdx.x >> 16);
    asm volatile("barrier.cluster.wait.aligned;" ::: "memory");
    TR(2, -3, 2);
#pragma unroll
    for (int i = 0; i < 2 * NL; i++) sts128(wdst + (i & 1) * 3072 + (i / 2) * 18432, wv[i]);
    fence_async();
    TR(2, -3, 3);
    asm volatile("bar.sync 1, 384;" ::: "memory");
    TR(2, -3, 4);
    mbar_wait(bar + B_WK * 8, 0);
    TR(2, -3, 5);
    uint32_t pk[12], pv[12], pq[12], hk1[6], hv1[6];
    gemm_iter<true, 0>(c, -2, pk, pv, pq, hk1, hv1 TRPASS);
    TR2(blockIdx.x, 4);
    c.hiA = opq(c.hiA); c.hiB = opq(c.hiB);
#pragma unroll 1
    for (int b = -1;; b += 2) {
      gemm_iter<false, 1>(c, b, pk, pv, pq, hk1, hv1 TRPASS);
      if (b == 11) break;
      gemm_iter<false, 0>(c, b + 1, pk, pv, pq, hk1, hv1 TRPASS);
    }
    TR2(blockIdx.x, 6);
    const uint32_t st = sb + gw * 3072;
    const uint32_t sta = st + (lane & 15) * 64 + ((hi ^ ((lane >> 1) & 3)) * 16);
    const int oc = ph * 112 + strip * 16 + 8 * (gw >> 1) + 4 * (head >> 1) + 2 * (gw & 1), och = pw * 6 + (head & 1) * 3;
    float D0[48], D1[48];
    mbar_arrive_elect(bar + B_WOFREE * 8);
    dump12<256>(c.qC[1] + 128, pq);
    fence_async();
    edge_ready(c, B_XV);
    nb_sync(N_QK1, 256);
    issue_halo<0, 12>(c, D1);
    gwait<0>(c, B_KFREE);
    dump12<128>(c.kC, pk);
    fence_async();
    edge_ready(c, B_XK);
    nb_arrive(N_VQ0, 288); nb_arrive(N_VQ1, 288); nb_arrive(N_PVISS, 384);
    wg_wait<0>(); pin(D1);
    pack6(hk1, D1, 0);
    if (c.hvalid) dump6(c.kH, hk1);
    tail_free(bar + (B_TFREE + 1) * 8);
    pack6(hv1, D1, 24);
    fence_async();
    nb_arrive(N_KRDY, 256);
    gwait<0>(c, B_VFREE);
    dump12<128>(c.vC[0], pv);
    if (c.hvalid) dump6(c.vH[0], hv1);
    fence_async();
    edge_ready(c, B_XV);
    nb_arrive(N_VQ0, 288); nb_arrive(N_VQ1, 288);
    gwait<0>(c, B_WO);
    gwait<0>(c, B_TIN);
    TR(2, 13, 0);
    nb_sync(N_QK1, 256);
    issue_proj<SM_TIN>(D0);
    wg_wait<0>(); pin(D0);
    TR(2, 13, 1);
    store_proj(D0, &mp.ot, st + SM_TST, sta + SM_TST, 8 * TB, oc, och);
    gwait<0>(c, B_TIN + 1);
    TR(2, 13, 2);
    nb_sync(N_PVISS, 384);
    nb_sync(3, 256);
    issue_proj<SM_TIN + 24576>(D1);
    wg_wait<0>(); pin(D1);
    TR(2, 13, 3);
    store_proj(D1, &mp.ot, st + SM_TIN, sta + SM_TIN, 8 * TB + 8, oc, och);
    TR(2, 13, 4);
    gwait<0>(c, B_TIN + 2);
    TR(2, 13, 5);
    issue_proj_half<0>(D0, head & 1);
    gwait<0>(c, B_TIN + 3);
    TR(2, 13, 6);
    issue_proj_half<1>(D0, ~head & 1);
    asm volatile("barrier.cluster.arrive.relaxed.aligned;" ::: "memory");
    wg_wait<0>(); pin(D0);
    store_proj(D0, &mp.ot, st + SM_TIN + 12288, sta + SM_TIN + 12288, 8 * TB + 16, oc, och);
    TR(2, 13, 7);
    if (lane == 0) asm volatile("cp.async.bulk.wait_group.read 0;" ::: "memory");
    __syncwarp();
    TR(2, 13, 8);
    TR2(blockIdx.x, 2);
    TRDUMP;
    asm volatile("barrier.cluster.wait.aligned;" ::: "memory");
  } else {
    if (warp == 12) {
      if (elect_one()) {
        mbar_init(bar + B_WK * 8, 1);
#pragma unroll
        for (int i = 0; i < NL; i++) load_w(&mp.w, sb + SM_W + (3 * i + 2 - 2 * va) * 6144, bar + B_WK * 8, ((i + 1) % 3) * 192 + head * 48 + 32 - 32 * va);
        asm volatile("prefetch.tensormap [%0];" ::"l"(head ? &mp.xc : &mp.xh) : "memory");
        mbar_expect(bar + B_WK * 8, NL * 6144);
      }
    } else if (warp == 15) {
      const int col = min(max(strip * 16 - 3 + min(lane, 21), 0), 111);
      const uint8_t* p = reinterpret_cast<const uint8_t*>(x) + (uint32_t)(head * ROWB + (ph * 112 + col) * 768 + pw * 384);
#pragma unroll
      for (int i = 0; i < 3; i++) asm volatile("prefetch.global.L2 [%0];" ::"l"(p + i * 128));
    } else if (elect_one()) {
      if (warp == 13) {
#pragma unroll
        for (int i = 0; i < B_WK; i++) mbar_init(bar + i * 8, i < B_EMPTY ? 1 : (i < B_TIN ? 16 : (i < B_TFREE ? (i == B_TIN + 2 ? 5 : 1) : 16)));
      } else {
#pragma unroll
        for (int i = B_WQ; i < B_COUNT; i++) mbar_init(bar + i * 8, i < B_Q0 ? 1 : (i < B_ODONE ? 4 : (i == B_VFREE ? 9 : 8)));
      }
    }
    asm volatile("fence.mbarrier_init.release.cluster;" ::: "memory");
    __syncwarp();
    asm volatile("barrier.cluster.arrive.relaxed.aligned;" ::: "memory");
    asm volatile("setmaxnreg.dec.sync.aligned.u32 24;");
    asm volatile("griddepcontrol.launch_dependents;");
    asm volatile("barrier.cluster.wait.aligned;" ::: "memory");
    if (warp == 12) {
      const CUtensorMap* mx = head ? &mp.xc : &mp.xh;
      const int cc = ph * 112 + strip * 16 + (head ? 0 : (odd ? 16 : (strip ? -3 : 0)));
      const int r0 = head == 0 ? (strip ? -4 : 112) : (head == 1 ? 4 : 0), dr = head ? 8 : 16;
      const uint32_t fb = bar + (B_FULL + head) * 8, eb = bar + (B_EMPTY + head) * 8;
      const uint32_t dst = sb + (head == 0 ? SM_X0 : (head == 1 ? SM_X1 : SM_X2));
      const int nl = head == 0 ? 8 : (head == 3 ? 1 : 14);
#pragma unroll 1
      for (int n = 0; n < nl; n++) {
        if (n) mbar_wait(eb, (n - 1) & 1);
        if (lane < 4 && head < 3)
          asm volatile("mbarrier.arrive.expect_tx.shared::cluster.b64 _, [%0], %1;" ::"r"(mapa(fb, base + lane)), "r"(head ? 24576 : 18432) : "memory");
        __syncwarp();
        if (elect_one()) {
          if (head < 3)
            asm volatile("cp.async.bulk.tensor.4d.shared::cluster.global.mbarrier::complete_tx::bytes.multicast::cluster [%0], [%1, {%3,%4,%5,%6}], [%2], %7;"
                         ::"r"(dst), "l"(mx), "r"(fb), "r"(0), "r"(dr * n + r0), "r"(cc), "r"(pw * 3), "h"((uint16_t)(15 << base)) : "memory");
          if (n == 0) {
#pragma unroll
            for (int i = 0; i < 3; i++) load_w(&mp.w, sb + SM_W + (6 + i) * 6144, bar + B_WQ * 8, head * 48 + i * 16);
            mbar_expect(bar + B_WQ * 8, 18432);
            mbar_expect(bar + B_TIN * 8, 24576); mbar_expect(bar + (B_TIN + 1) * 8, 24576); mbar_expect(bar + (B_TIN + 2) * 8, 6144); mbar_expect(bar + (B_TIN + 3) * 8, 12288);
          }
          if (n + 1 < nl) asm volatile("cp.async.bulk.prefetch.tensor.4d.L2.global [%0, {%1,%2,%3,%4}];" ::"l"(mx), "r"(0), "r"(dr * n + dr + r0), "r"(cc), "r"(pw * 3) : "memory");
        }
        __syncwarp();
      }
      mbar_wait(bar + B_WOFREE * 8, 0);
      if (elect_one()) {
        mbar_expect(bar + B_WO * 8, 36864);
        asm volatile("cp.async.bulk.tensor.3d.shared::cluster.global.mbarrier::complete_tx::bytes [%0], [%1, {%3,%4,%5}], [%2];"
                     ::"r"(sb + SM_TWO), "l"(&mp.wo), "r"(bar + B_WO * 8), "r"(0), "r"(0), "r"((head & 1) * 3) : "memory");
      }
      __syncwarp();
    }
    if (warp == 13) {
      const uint32_t partner = (blockIdx.x & 7) ^ 4;
      const int cs = odd ? 3 : (strip == 6 ? 15 : 16), cd = odd || strip == 6 ? 19 : 0;
      const uint32_t rb = mapa(bar, partner), rk = mapa(sb + SM_K + cd * KS, partner), rv = mapa(sb + SM_V + cd * 1536, partner);
      mbar_wait(bar + B_XK * 8, 0);
      if (elect_one()) {
        remote_expect(rb + B_KIMP * 8, 6 * KS);
        copy_remote(rk, sb + SM_K + cs * KS, 3 * KS, rb + B_KIMP * 8);
        copy_remote(rk + KSLOT, sb + SM_K + cs * KS + KSLOT, 3 * KS, rb + B_KIMP * 8);
      }
      __syncwarp();
#pragma unroll 1
      for (int b = 0; b < 14; b++) {
        const uint32_t pa = b & 1;
        mbar_wait(bar + B_XV * 8, pa);
        if (b) mbar_wait(bar + B_PVF * 8, pa ^ 1);
        if (elect_one()) { remote_expect(rb + B_VIMP * 8, 4608); copy_remote(rv, sb + SM_V + cs * 1536, 4608, rb + B_VIMP * 8); }
        __syncwarp();
        mbar_wait(bar + B_KFREE * 8, pa);
        if (elect_one()) remote_arrive(rb + B_PKF * 8);
        __syncwarp();
        mbar_wait(bar + B_OFREE * 8, pa);
        mbar_wait(bar + B_VIMP * 8, pa);
        nb_arrive(N_VQ1, 288);
        if (elect_one()) remote_arrive(rb + B_VFREE * 8);
        __syncwarp();
        if (b == 13) break;
        mbar_wait(bar + B_XK * 8, pa ^ 1);
        mbar_wait(bar + B_PKF * 8, pa);
        if (elect_one()) { remote_expect(rb + B_KIMP * 8, 3 * KS); copy_remote(rk + pa * KSLOT, sb + SM_K + cs * KS + pa * KSLOT, 3 * KS, rb + B_KIMP * 8); }
        __syncwarp();
        mbar_wait(bar + B_VFREE * 8, pa);
        if (elect_one()) remote_arrive(rb + B_PVF * 8);
        __syncwarp();
      }
    }
    if (warp == 14) {
      int* flag = g_flags + (par * 7 + strip) * 2;
      nb_arrive(N_VQ0, 288); mbar_arrive_elect(bar + B_OFREE * 8);
#pragma unroll 1
      for (int b = 0; b < TB; b++) {
        mbar_wait(bar + B_ODONE * 8, b & 1);
        if (lane == 0) {
          asm volatile("cp.async.bulk.tensor.3d.global.shared::cta.bulk_group [%0, {%2,%3,%4}], [%1];"
                       ::"l"(&mp.os), "r"(sb + SM_O), "r"(pw * 192), "r"(8 * b + 2 * head), "r"(ph * 112 + strip * 16) : "memory");
          asm volatile("cp.async.bulk.commit_group;\ncp.async.bulk.wait_group 0;" ::: "memory");
        }
        __syncwarp();
        nb_arrive(N_VQ0, 288); mbar_arrive_elect(bar + B_OFREE * 8);
        if (lane == 0)
          asm volatile("fence.proxy.async.global;\nfence.acq_rel.gpu;\nred.relaxed.gpu.global.add.s32 [%0], 1;\nred.relaxed.gpu.global.add.s32 [%0+4], 1;"
                       ::"l"(flag + b * 56) : "memory");
        __syncwarp();
      }
    }
    if (warp >= 14) {
      const int jw = warp - 14, j = jw ^ odd;
#pragma unroll 1
      for (int i = 0; i < 2; i++) {
        mbar_wait(bar + (B_OTAIL + jw) * 8, i);
        if (i == 1) mbar_wait(bar + (B_TFREE + 1) * 8, 0);
        if (jw) mbar_arrive_elect(bar + B_OFREE * 8); else nb_arrive(N_VQ0, 288);
        if (i == 0) mbar_wait(bar + B_TFREE * 8, 0);
        if (elect_one()) {
#pragma unroll 1
          for (int d = 0; d < 8; d++) {
            const int dst = (d + head) & 3, pc = d >> 2;
            send_o<1536>(sb + SM_TIN + i * 24576 + head * 6144 + j * 3072 + pc * 1536,
                         sb + (i ? SM_Q : SM_O) + (4 * j + (dst & 2) + pc) * (i ? 3072 : 1536), bar + (B_TIN + i) * 8, base + dst);
          }
        }
        __syncwarp();
      }
    }
    cluster_sync();
  }
}

constexpr int NSTB = 6;
constexpr int NTB = TB * 56;
constexpr int SM_B_ST = 0;
constexpr int SM_B_IN = 73728;
constexpr int SM_B_W = SM_B_IN + 3 * 24576;
constexpr int SM_B_BAR = SM_B_IN + NSTB * 24576;
constexpr int SM_B_TOTAL = SM_B_BAR + 512;
struct MapsB { CUtensorMap oi, oo, wo; };

__global__ void __launch_bounds__(512, 1)
na_proj_kernel(const __grid_constant__ MapsB mp) {
  extern __shared__ __align__(1024) uint8_t smem_raw[];
  const uint32_t sb = smem_u32(smem_raw);
  if ((sb & 0x3FFFF) != SBC) return;
  const uint32_t bar = sb + SM_B_BAR;
  const int tid = threadIdx.x, lane = tid & 31;
  const int warp = __shfl_sync(0xffffffffu, tid >> 5, 0);
  TR2(132 + blockIdx.x, 0);
  TRB(47, 0);
  if (warp == 12 && elect_one()) {
#pragma unroll
    for (int i = 0; i <= 2 * NSTB; i++) mbar_init(bar + i * 8, i < NSTB || i == 2 * NSTB ? 1 : 12);
    asm volatile("st.shared.u32 [%0], 0;" ::"r"(bar + 120) : "memory");
    mbar_expect(bar + 2 * NSTB * 8, 73728);
#pragma unroll
    for (int i = 0; i < 2; i++)
      asm volatile("cp.async.bulk.tensor.3d.shared::cluster.global.mbarrier::complete_tx::bytes [%0], [%1, {%3,%4,%5}], [%2];"
                   ::"r"(sb + SM_B_W + i * 36864), "l"(&mp.wo), "r"(bar + 2 * NSTB * 8), "r"(0), "r"(0), "r"(i * 3) : "memory");
  }
  __syncthreads();
  const int step = gridDim.x;
  if (warp == 15) {
    int so = 0;
    nb_arrive(4, 288); nb_arrive(5, 288); nb_arrive(6, 288);
#pragma unroll 1
    for (int n = blockIdx.x, tk = 0; n < NTB; n += step, tk++) {
      uint32_t cc = 0;
#pragma unroll
      for (int wg = 0; wg < 3; wg++) {
        if (lane == 0) asm volatile("cp.async.bulk.wait_group.read 5;" ::: "memory");
        nb_sync(1 + wg, 160);
        if (wg == 0 || n + step < NTB) nb_arrive(4 + wg, 288);
        if (wg == 0) asm volatile("ld.shared.u32 %0, [%1];" : "=r"(cc) : "r"(bar + 128 + tk * 4) : "memory");
        if (lane == 0) {
          asm volatile("cp.async.bulk.tensor.4d.global.shared::cta.bulk_group [%0, {%2,%3,%4,%5}], [%1];"
                       ::"l"(&mp.oo), "r"(sb + SM_B_ST + wg * 8192 + so), "r"(0), "r"((cc >> 8) & 255), "r"(cc >> 16), "r"((cc & 1) * 3 + wg) : "memory");
          asm volatile("cp.async.bulk.commit_group;" ::: "memory");
        }
        __syncwarp();
      }
      so = so == 49152 ? 0 : so + 24576;
    }
    if (lane == 0) asm volatile("cp.async.bulk.wait_group.read 0;" ::: "memory");
  } else if (warp >= 12) {
    nb_sync(7, 480);
#pragma unroll 1
    for (int n = blockIdx.x + (warp - 12) * step; n < NTB; n += 3 * step) {
      const int b = n / 56, rem = n - b * 56, par = rem / 14;
      const int c0 = opq((uint32_t)(par & 1)), c1 = opq((uint32_t)(8 * b)), c2 = opq((uint32_t)((par >> 1) * 112 + (rem - par * 14) * 8));
      int v; uint32_t spin = 0, tk = 0;
      do { asm volatile("ld.acquire.gpu.global.s32 %0, [%1];" : "=r"(v) : "l"(g_flags + n) : "memory"); } while (v < 4 && ++spin < SPIN_LIMIT);
      if (lane == 0) asm volatile("atom.shared.add.u32 %0, [%1], 1;" : "=r"(tk) : "r"(bar + 120) : "memory");
      asm volatile("fence.proxy.async.global;" ::: "memory");
      tk = __shfl_sync(0xffffffffu, tk, 0);
      TRB(tk, 0);
      const uint32_t use = tk / NSTB, sg = tk - use * NSTB;
      if (use) mbar_wait(bar + (NSTB + sg) * 8, (use - 1) & 1);
      TRB(tk, 1);
      if (elect_one()) {
        asm volatile("st.shared.u32 [%0], %1;" ::"r"(bar + 128 + tk * 4), "r"(c0 | c1 << 8 | c2 << 16) : "memory");
        mbar_expect(bar + sg * 8, 24576);
        asm volatile("cp.async.bulk.tensor.3d.shared::cluster.global.mbarrier::complete_tx::bytes [%0], [%1, {%3,%4,%5}], [%2];"
                     ::"r"(sb + SM_B_IN + sg * 24576), "l"(&mp.oi), "r"(bar + sg * 8), "r"(c0 * 192), "r"(c1), "r"(c2) : "memory");
        g_flags[n] = 0;
      }
      __syncwarp();
    }
  } else {
    const int wg = warp >> 2, w = warp & 3;
    uint32_t a[48];
    mbar_wait(bar + 2 * NSTB * 8, 0);
    {
      const int k = (lane & 7) + (lane >> 4) * 8, ch = (warp & 1) * 2 + ((lane >> 3) & 1);
      const uint32_t wa = sb + SM_B_W + (warp >> 1) * 12288 + k * 64 + ((ch ^ ((k >> 1) & 3)) * 16);
#pragma unroll
      for (int i = 0; i < 12; i++)
        asm volatile("ldmatrix.sync.aligned.m8n8.x4.trans.shared.b16 {%0,%1,%2,%3}, [%4];"
                     : "=r"(a[4 * i]), "=r"(a[4 * i + 1]), "=r"(a[4 * i + 2]), "=r"(a[4 * i + 3]) : "r"(wa + i * 1024) : "memory");
    }
    nb_sync(7, 480);
    TRB(47, 1);
    const uint32_t sta = opq(sb + SM_B_ST + wg * 8192 + ((lane & 7) + (lane >> 4) * 8) * 128 + (((2 * w + ((lane >> 3) & 1)) ^ (lane & 7)) * 16));
    const uint32_t hi = opq((uint32_t)(mkdesc(0, 0, 3072, 0) >> 32) + (blockIdx.x >> 16)), bb = opq(bar);
    const uint32_t nbT = opq((uint32_t)(4 + wg)), nbN = opq((uint32_t)(wg == 2 ? 4 : 5 + wg)), nbD = opq((uint32_t)(1 + wg));
    int left = (NTB - blockIdx.x + step - 1) / step;
    if (wg == 2) nb_arrive(4, 288);
#pragma unroll 1
    for (uint32_t ph = 0;; ph ^= 1) {
#pragma unroll
      for (int sg = 0; sg < NSTB; sg++) {
        constexpr uint64_t db = mkdesc(SBC + SM_B_IN, 128, 3072, 0);
        float D[32];
        mbar_wait(bb + sg * 8, ph);
        nb_sync(nbT, 288);
        wg_fence();
        wg_rs64<0>(D, a[0], a[1], a[2], a[3], dsc(db + sg * 1536, hi));
#pragma unroll
        for (int k = 1; k < 12; k++) wg_rs64<1>(D, a[4 * k], a[4 * k + 1], a[4 * k + 2], a[4 * k + 3], dsc(db + sg * 1536 + k * 16, hi));
        wg_commit();
        nb_arrive(nbN, 288);
        wg_wait<0>(); pin(D);
        mbar_arrive_elect(bb + (NSTB + sg) * 8);
#pragma unroll
        for (int q = 0; q < 4; q++)
          asm volatile("stmatrix.sync.aligned.m8n8.x4.trans.shared.b16 [%0], {%1,%2,%3,%4};" ::"r"(sta + (sg % 3) * 24576 + q * 2048),
                       "r"(pack2(D[8 * q], D[8 * q + 1])), "r"(pack2(D[8 * q + 2], D[8 * q + 3])), "r"(pack2(D[8 * q + 4], D[8 * q + 5])), "r"(pack2(D[8 * q + 6], D[8 * q + 7])) : "memory");
        fence_async();
        nb_arrive(nbD, 160);
        if (wg == 0) TRB(31 - left, 5);
        if (--left == 0) goto done;
      }
    }
  done:
    if (wg == 0) nb_arrive(4, 288);
    TR2(132 + blockIdx.x, 2);
  }
}

typedef CUresult (*EncodeFn)(CUtensorMap*, CUtensorMapDataType, cuuint32_t, void*, const cuuint64_t*, const cuuint64_t*, const cuuint32_t*,
                             const cuuint32_t*, CUtensorMapInterleave, CUtensorMapSwizzle, CUtensorMapL2promotion, CUtensorMapFloatOOBfill);
static EncodeFn g_enc = nullptr;
static void make_map(CUtensorMap* m, const void* p, int rank, const cuuint64_t* dim, const cuuint64_t* str, const cuuint32_t* box, CUtensorMapSwizzle sw) {
  const cuuint32_t ones[5] = {1, 1, 1, 1, 1};
  g_enc(m, CU_TENSOR_MAP_DATA_TYPE_BFLOAT16, rank, (void*)p, dim, str, box, ones, CU_TENSOR_MAP_INTERLEAVE_NONE, sw,
        CU_TENSOR_MAP_L2_PROMOTION_L2_128B, CU_TENSOR_MAP_FLOAT_OOB_FILL_NONE);
}

extern "C" void kernel_launch(void* const* d_in, const int* in_sizes, int n_in, void* d_out, int out_size) {
  const __nv_bfloat16* x = (const __nv_bfloat16*)d_in[0];
  const __nv_bfloat16* wqkv = (const __nv_bfloat16*)d_in[1];
  const __nv_bfloat16* wo = (const __nv_bfloat16*)d_in[2];
  const __nv_bfloat16* rpb = (const __nv_bfloat16*)d_in[3];

  if (!g_enc) {
    void* fn = nullptr; cudaDriverEntryPointQueryResult qr;
    cudaGetDriverEntryPoint("cuTensorMapEncodeTiled", &fn, cudaEnableDefault, &qr);
    g_enc = (EncodeFn)fn;
    cudaFuncSetAttribute(na_attn_kernel, cudaFuncAttributeMaxDynamicSharedMemorySize, SM_A_TOTAL);
    cudaFuncSetAttribute(na_proj_kernel, cudaFuncAttributeMaxDynamicSharedMemorySize, SM_B_TOTAL);
  }
  Maps ma; MapsB mb;
  { cuuint64_t dim[4] = {64, 112, 224, 6}, str[3] = {(cuuint64_t)ROWB, 768, 128};
    cuuint32_t box[4] = {64, 4, 16, 3}, boxh[4] = {64, 16, 3, 3}, boxo[4] = {64, 8, 8, 1};
    make_map(&ma.xc, x, 4, dim, str, box, CU_TENSOR_MAP_SWIZZLE_128B);
    make_map(&ma.xh, x, 4, dim, str, boxh, CU_TENSOR_MAP_SWIZZLE_128B);
    make_map(&mb.oo, d_out, 4, dim, str, boxo, CU_TENSOR_MAP_SWIZZLE_128B); }
  { cuuint64_t dim[3] = {384, 112, 224}, str[2] = {(cuuint64_t)ROWB, 768};
    cuuint32_t box[3] = {192, 8, 8}, boxs[3] = {192, 2, 16};
    make_map(&mb.oi, d_out, 3, dim, str, box, CU_TENSOR_MAP_SWIZZLE_NONE);
    make_map(&ma.os, d_out, 3, dim, str, boxs, CU_TENSOR_MAP_SWIZZLE_NONE); }
  { cuuint64_t dim[4] = {32, 112, 224, 12}, str[3] = {(cuuint64_t)ROWB, 768, 64};
    cuuint32_t box[4] = {32, 8, 2, 3};
    make_map(&ma.ot, d_out, 4, dim, str, box, CU_TENSOR_MAP_SWIZZLE_64B); }
  { cuuint64_t dim[2] = {576, 192}, str[1] = {1152};
    cuuint32_t box[2] = {16, 192};
    make_map(&ma.w, wqkv, 2, dim, str, box, CU_TENSOR_MAP_SWIZZLE_32B); }
  { cuuint64_t dim[3] = {32, 192, 6}, str[2] = {384, 64};
    cuuint32_t box[3] = {32, 192, 3};
    make_map(&ma.wo, wo, 3, dim, str, box, CU_TENSOR_MAP_SWIZZLE_64B);
    mb.wo = ma.wo; }
  na_attn_kernel<<<112, 512, SM_A_TOTAL>>>(x, wqkv, rpb, ma);
  cudaLaunchConfig_t cfg = {};
  cfg.gridDim = dim3(20); cfg.blockDim = dim3(512); cfg.dynamicSmemBytes = SM_B_TOTAL; cfg.stream = cudaStreamPerThread;
  cudaLaunchAttribute at[1];
  at[0].id = cudaLaunchAttributeProgrammaticStreamSerialization; at[0].val.programmaticStreamSerializationAllowed = 1;
  cfg.attrs = at; cfg.numAttrs = 1;
  cudaLaunchKernelEx(&cfg, na_proj_kernel, mb);
}
```

```cpp
#include <cuda_runtime.h>
#include <cuda_bf16.h>
#include <cuda.h>
#include <stdint.h>

#define SPIN_LIMIT (1u << 18)

__device__ __forceinline__ uint32_t smem_u32(const void* p) { return (uint32_t)__cvta_generic_to_shared(p); }
__device__ __forceinline__ void wg_fence() { asm volatile("wgmma.fence.sync.aligned;" ::: "memory"); }
__device__ __forceinline__ void wg_commit() { asm volatile("wgmma.commit_group.sync.aligned;" ::: "memory"); }
template <int N> __device__ __forceinline__ void wg_wait() { asm volatile("wgmma.wait_group.sync.aligned %0;" ::"n"(N) : "memory"); }
template <int N> __device__ __forceinline__ void pin(float (&d)[N]) {
#pragma unroll
  for (int i = 0; i < N; i++) asm volatile("" : "+f"(d[i])::"memory");
}
__host__ __device__ constexpr uint64_t mkdesc(uint32_t addr, uint32_t lbo, uint32_t sbo, uint32_t sw) {
  return (uint64_t)((addr & 0x3FFFF) >> 4) | ((uint64_t)(lbo >> 4) << 16) | ((uint64_t)(sbo >> 4) << 32) | ((uint64_t)sw << 62);
}
__device__ __forceinline__ void mbar_init(uint32_t bar, uint32_t cnt) { asm volatile("mbarrier.init.shared::cta.b64 [%0], %1;" ::"r"(bar), "r"(cnt) : "memory"); }
__device__ __forceinline__ void mbar_arrive(uint32_t bar) { asm volatile("mbarrier.arrive.shared::cta.b64 _, [%0];" ::"r"(bar) : "memory"); }
__device__ __forceinline__ bool elect_one() {
  uint32_t r; asm volatile("{\n.reg .pred p;\nelect.sync _|p, 0xffffffff;\nselp.u32 %0, 1, 0, p;\n}" : "=r"(r)); return r;
}
__device__ __forceinline__ void mbar_arrive_elect(uint32_t bar) {
  asm volatile("{\n.reg .pred p;\nelect.sync _|p, 0xffffffff;\n@p mbarrier.arrive.shared::cta.b64 _, [%0];\n}" ::"r"(bar) : "memory");
}
__device__ __forceinline__ void mbar_expect(uint32_t bar, uint32_t bytes) { asm volatile("mbarrier.arrive.expect_tx.shared::cta.b64 _, [%0], %1;" ::"r"(bar), "r"(bytes) : "memory"); }
__device__ __forceinline__ void mbar_arrive_remote(uint32_t bar, uint32_t cta) {
  asm volatile("{\n.reg .b32 ra;\nmapa.shared::cluster.u32 ra, %0, %1;\nmbarrier.arrive.relaxed.cluster.shared::cluster.b64 _, [ra];\n}" ::"r"(bar), "r"(cta) : "memory");
}
__device__ __forceinline__ void mbar_wait(uint32_t bar, uint32_t parity) {
  asm volatile("{\n.reg .pred p;\n.reg .b32 n;\nmov.b32 n, 0;\nWL:\nmbarrier.try_wait.parity.shared::cta.b64 p, [%0], %1;\n@p bra WD;\n"
               "add.u32 n, n, 1;\nsetp.lt.u32 p, n, 65536;\n@p bra WL;\nWD:\n}" ::"r"(bar), "r"(parity) : "memory");
}
__device__ __forceinline__ void nb_sync(int id, int n) { asm volatile("bar.sync %0, %1;" ::"r"(id), "r"(n) : "memory"); }
__device__ __forceinline__ void nb_arrive(int id, int n) { asm volatile("bar.arrive %0, %1;" ::"r"(id), "r"(n) : "memory"); }
__device__ __forceinline__ uint32_t opq(uint32_t x) { uint32_t r; asm volatile("mov.b32 %0, %1;" : "=r"(r) : "r"(x)); return r; }
__device__ __forceinline__ uint64_t opq(uint64_t x) { uint64_t r; asm volatile("mov.b64 %0, %1;" : "=l"(r) : "l"(x)); return r; }
__device__ __forceinline__ uint32_t mapa(uint32_t a, uint32_t cta) { uint32_t r; asm("mapa.shared::cluster.u32 %0, %1, %2;" : "=r"(r) : "r"(a), "r"(cta)); return r; }
__device__ __forceinline__ void fence_async() { asm volatile("fence.proxy.async.shared::cta;" ::: "memory"); }
__device__ __forceinline__ void cluster_sync() {
  asm volatile("barrier.cluster.arrive.relaxed.aligned;\nbarrier.cluster.wait.aligned;" ::: "memory");
}
__device__ __forceinline__ uint32_t pack2(float lo, float hi) {
  uint32_t r; asm("cvt.rn.bf16x2.f32 %0, %1, %2;" : "=r"(r) : "f"(hi), "f"(lo)); return r;
}
__device__ __forceinline__ void stsm4(uint32_t a, uint32_t r0, uint32_t r1, uint32_t r2, uint32_t r3) {
  asm volatile("stmatrix.sync.aligned.m8n8.x4.shared.b16 [%0], {%1,%2,%3,%4};" ::"r"(a), "r"(r0), "r"(r1), "r"(r2), "r"(r3) : "memory");
}
__device__ __forceinline__ void ldsm4(uint32_t a, uint32_t& r0, uint32_t& r1, uint32_t& r2, uint32_t& r3) {
  asm volatile("ldmatrix.sync.aligned.m8n8.x4.shared.b16 {%0,%1,%2,%3}, [%4];" : "=r"(r0), "=r"(r1), "=r"(r2), "=r"(r3) : "r"(a) : "memory");
}
__device__ __forceinline__ void sts128(uint32_t a, uint4 v) {
  asm volatile("st.shared.v4.b32 [%0], {%1,%2,%3,%4};" ::"r"(a), "r"(v.x), "r"(v.y), "r"(v.z), "r"(v.w) : "memory");
}
__device__ __forceinline__ float lds_f32(uint32_t a) { float v; asm volatile("ld.shared.f32 %0, [%1];" : "=f"(v) : "r"(a)); return v; }
__device__ __forceinline__ float ex2(float x) { float y; asm("ex2.approx.ftz.f32 %0, %1;" : "=f"(y) : "f"(x)); return y; }

template<int SC> __device__ __forceinline__ void wg_ss144(float (&d)[72], uint64_t da, uint64_t db) {
  asm volatile("{\n.reg .pred p;\nsetp.ne.b32 p, %74, 0;\nwgmma.mma_async.sync.aligned.m64n144k16.f32.bf16.bf16 {%0,%1,%2,%3,%4,%5,%6,%7,%8,%9,%10,%11,%12,%13,%14,%15,%16,%17,%18,%19,%20,%21,%22,%23,%24,%25,%26,%27,%28,%29,%30,%31,%32,%33,%34,%35,%36,%37,%38,%39,%40,%41,%42,%43,%44,%45,%46,%47,%48,%49,%50,%51,%52,%53,%54,%55,%56,%57,%58,%59,%60,%61,%62,%63,%64,%65,%66,%67,%68,%69,%70,%71}, %72, %73, p, 1, 1, 0, 1;\n}\n"
    : "+f"(d[0]),"+f"(d[1]),"+f"(d[2]),"+f"(d[3]),"+f"(d[4]),"+f"(d[5]),"+f"(d[6]),"+f"(d[7]),"+f"(d[8]),"+f"(d[9]),"+f"(d[10]),"+f"(d[11]),"+f"(d[12]),"+f"(d[13]),"+f"(d[14]),"+f"(d[15]),"+f"(d[16]),"+f"(d[17]),"+f"(d[18]),"+f"(d[19]),"+f"(d[20]),"+f"(d[21]),"+f"(d[22]),"+f"(d[23]),"+f"(d[24]),"+f"(d[25]),"+f"(d[26]),"+f"(d[27]),"+f"(d[28]),"+f"(d[29]),"+f"(d[30]),"+f"(d[31]),"+f"(d[32]),"+f"(d[33]),"+f"(d[34]),"+f"(d[35]),"+f"(d[36]),"+f"(d[37]),"+f"(d[38]),"+f"(d[39]),"+f"(d[40]),"+f"(d[41]),"+f"(d[42]),"+f"(d[43]),"+f"(d[44]),"+f"(d[45]),"+f"(d[46]),"+f"(d[47]),"+f"(d[48]),"+f"(d[49]),"+f"(d[50]),"+f"(d[51]),"+f"(d[52]),"+f"(d[53]),"+f"(d[54]),"+f"(d[55]),"+f"(d[56]),"+f"(d[57]),"+f"(d[58]),"+f"(d[59]),"+f"(d[60]),"+f"(d[61]),"+f"(d[62]),"+f"(d[63]),"+f"(d[64]),"+f"(d[65]),"+f"(d[66]),"+f"(d[67]),"+f"(d[68]),"+f"(d[69]),"+f"(d[70]),"+f"(d[71]) : "l"(da), "l"(db), "n"(SC));
}
template<int SC> __device__ __forceinline__ void wg_ss96(float (&d)[48], uint64_t da, uint64_t db) {
  asm volatile("{\n.reg .pred p;\nsetp.ne.b32 p, %50, 0;\nwgmma.mma_async.sync.aligned.m64n96k16.f32.bf16.bf16 {%0,%1,%2,%3,%4,%5,%6,%7,%8,%9,%10,%11,%12,%13,%14,%15,%16,%17,%18,%19,%20,%21,%22,%23,%24,%25,%26,%27,%28,%29,%30,%31,%32,%33,%34,%35,%36,%37,%38,%39,%40,%41,%42,%43,%44,%45,%46,%47}, %48, %49, p, 1, 1, 0, 1;\n}\n"
    : "+f"(d[0]),"+f"(d[1]),"+f"(d[2]),"+f"(d[3]),"+f"(d[4]),"+f"(d[5]),"+f"(d[6]),"+f"(d[7]),"+f"(d[8]),"+f"(d[9]),"+f"(d[10]),"+f"(d[11]),"+f"(d[12]),"+f"(d[13]),"+f"(d[14]),"+f"(d[15]),"+f"(d[16]),"+f"(d[17]),"+f"(d[18]),"+f"(d[19]),"+f"(d[20]),"+f"(d[21]),"+f"(d[22]),"+f"(d[23]),"+f"(d[24]),"+f"(d[25]),"+f"(d[26]),"+f"(d[27]),"+f"(d[28]),"+f"(d[29]),"+f"(d[30]),"+f"(d[31]),"+f"(d[32]),"+f"(d[33]),"+f"(d[34]),"+f"(d[35]),"+f"(d[36]),"+f"(d[37]),"+f"(d[38]),"+f"(d[39]),"+f"(d[40]),"+f"(d[41]),"+f"(d[42]),"+f"(d[43]),"+f"(d[44]),"+f"(d[45]),"+f"(d[46]),"+f"(d[47]) : "l"(da), "l"(db), "n"(SC));
}
template<int SC> __device__ __forceinline__ void wg_rs112(float (&d)[56], uint32_t a0, uint32_t a1, uint32_t a2, uint32_t a3, uint64_t db) {
  asm volatile("{\n.reg .pred p;\nsetp.ne.b32 p, %61, 0;\nwgmma.mma_async.sync.aligned.m64n112k16.f32.bf16.bf16 {%0,%1,%2,%3,%4,%5,%6,%7,%8,%9,%10,%11,%12,%13,%14,%15,%16,%17,%18,%19,%20,%21,%22,%23,%24,%25,%26,%27,%28,%29,%30,%31,%32,%33,%34,%35,%36,%37,%38,%39,%40,%41,%42,%43,%44,%45,%46,%47,%48,%49,%50,%51,%52,%53,%54,%55}, {%56,%57,%58,%59}, %60, p, 1, 1, 0;\n}\n"
    : "+f"(d[0]),"+f"(d[1]),"+f"(d[2]),"+f"(d[3]),"+f"(d[4]),"+f"(d[5]),"+f"(d[6]),"+f"(d[7]),"+f"(d[8]),"+f"(d[9]),"+f"(d[10]),"+f"(d[11]),"+f"(d[12]),"+f"(d[13]),"+f"(d[14]),"+f"(d[15]),"+f"(d[16]),"+f"(d[17]),"+f"(d[18]),"+f"(d[19]),"+f"(d[20]),"+f"(d[21]),"+f"(d[22]),"+f"(d[23]),"+f"(d[24]),"+f"(d[25]),"+f"(d[26]),"+f"(d[27]),"+f"(d[28]),"+f"(d[29]),"+f"(d[30]),"+f"(d[31]),"+f"(d[32]),"+f"(d[33]),"+f"(d[34]),"+f"(d[35]),"+f"(d[36]),"+f"(d[37]),"+f"(d[38]),"+f"(d[39]),"+f"(d[40]),"+f"(d[41]),"+f"(d[42]),"+f"(d[43]),"+f"(d[44]),"+f"(d[45]),"+f"(d[46]),"+f"(d[47]),"+f"(d[48]),"+f"(d[49]),"+f"(d[50]),"+f"(d[51]),"+f"(d[52]),"+f"(d[53]),"+f"(d[54]),"+f"(d[55]) : "r"(a0), "r"(a1), "r"(a2), "r"(a3), "l"(db), "n"(SC));
}
template<int SC> __device__ __forceinline__ void wg_sp48(float (&d)[24], uint32_t a0, uint32_t a1, uint32_t a2, uint32_t a3, uint64_t db, uint32_t meta) {
  asm volatile("{\n.reg .pred p;\nsetp.ne.b32 p, %30, 0;\nwgmma.mma_async.sp.sync.aligned.m64n48k32.f32.bf16.bf16 {%0,%1,%2,%3,%4,%5,%6,%7,%8,%9,%10,%11,%12,%13,%14,%15,%16,%17,%18,%19,%20,%21,%22,%23}, {%24,%25,%26,%27}, %28, %29, 0, p, 1, 1, 1;\n}\n"
    : "+f"(d[0]),"+f"(d[1]),"+f"(d[2]),"+f"(d[3]),"+f"(d[4]),"+f"(d[5]),"+f"(d[6]),"+f"(d[7]),"+f"(d[8]),"+f"(d[9]),"+f"(d[10]),"+f"(d[11]),"+f"(d[12]),"+f"(d[13]),"+f"(d[14]),"+f"(d[15]),"+f"(d[16]),"+f"(d[17]),"+f"(d[18]),"+f"(d[19]),"+f"(d[20]),"+f"(d[21]),"+f"(d[22]),"+f"(d[23]) : "r"(a0), "r"(a1), "r"(a2), "r"(a3), "l"(db), "r"(meta), "n"(SC));
}
template<int SC> __device__ __forceinline__ void wg_rs64(float (&d)[32], uint32_t a0, uint32_t a1, uint32_t a2, uint32_t a3, uint64_t db) {
  asm volatile("{\n.reg .pred p;\nsetp.ne.b32 p, %37, 0;\nwgmma.mma_async.sync.aligned.m64n64k16.f32.bf16.bf16 {%0,%1,%2,%3,%4,%5,%6,%7,%8,%9,%10,%11,%12,%13,%14,%15,%16,%17,%18,%19,%20,%21,%22,%23,%24,%25,%26,%27,%28,%29,%30,%31}, {%32,%33,%34,%35}, %36, p, 1, 1, 0;\n}\n"
    : "+f"(d[0]),"+f"(d[1]),"+f"(d[2]),"+f"(d[3]),"+f"(d[4]),"+f"(d[5]),"+f"(d[6]),"+f"(d[7]),"+f"(d[8]),"+f"(d[9]),"+f"(d[10]),"+f"(d[11]),"+f"(d[12]),"+f"(d[13]),"+f"(d[14]),"+f"(d[15]),"+f"(d[16]),"+f"(d[17]),"+f"(d[18]),"+f"(d[19]),"+f"(d[20]),"+f"(d[21]),"+f"(d[22]),"+f"(d[23]),"+f"(d[24]),"+f"(d[25]),"+f"(d[26]),"+f"(d[27]),"+f"(d[28]),"+f"(d[29]),"+f"(d[30]),"+f"(d[31]) : "r"(a0), "r"(a1), "r"(a2), "r"(a3), "l"(db), "n"(SC));
}

constexpr uint32_t SBC = 1024;
constexpr int ROWB = 2 * 224 * 384;
constexpr int TB = 11;
constexpr int KS = 832;
constexpr int KSLOT = 22 * KS;
constexpr int SM_X2 = 0;
constexpr int SM_X0 = SM_X2 + 24576;
constexpr int SM_W = SM_X0 + 18432;
constexpr int SM_X1 = SM_W + 55296;
constexpr int SM_K = SM_X1 + 24576;
constexpr int SM_V = SM_K + 2 * KSLOT;
constexpr int SM_Q = SM_V + 22 * 1536;
constexpr int SM_O = SM_Q + 24576;
constexpr int SM_RPB = SM_O + 12288;
constexpr int SM_BAR = SM_RPB + 768;
constexpr int SM_A_TOTAL = SM_BAR + 256;
constexpr int SM_TIN = 0;
constexpr int SM_TST = 3 * 24576;
constexpr int SM_TWO = SM_TST + 12288;
enum { B_FULL = 0, B_EMPTY = 3, B_TIN = 6, B_TFREE = 10, B_WK = 12, B_WQ, B_WO, B_KIMP, B_VIMP, B_PKF, B_PVF, B_XK, B_XV, B_OFREE,
       B_Q0, B_WOFREE, B_OTAIL, B_ODONE = B_OTAIL + 2, B_KFREE, B_VFREE, B_COUNT };
enum { N_KRDY = 4, N_QK0, N_QK1, N_VQ0, N_VQ1, N_PVISS };

#define NL 2
#define OPT 0
#define OCH 4
#define SPL 4
#define RA 160
#define RG 168
__device__ int g_flags[TB * 56];

#define TR(role, it, k)
#define TRDECL
#define TRARG
#define TRPASS
#define TRDUMP
#define TRB(it, k)
#define TR2(blk, k)

struct GemmCtx {
  uint32_t bar;
  uint32_t kC, vC[2], qC[2];
  uint32_t kH, vH[2];
  uint32_t hiA, hiB;
  uint32_t spin;
  uint32_t em[3];
  bool hvalid, never, edge;
};

template <int STRIDE> __device__ __forceinline__ void dump12(uint32_t a, const uint32_t (&r)[12]) {
#pragma unroll
  for (int j = 0; j < 3; j++) stsm4(a + j * 2 * STRIDE, r[4 * j], r[4 * j + 1], r[4 * j + 2], r[4 * j + 3]);
}
__device__ __forceinline__ void keep12(bool never, uint32_t a, const uint32_t (&r)[12]) { if (never) dump12<128>(a, r); }
template <int N> __device__ __forceinline__ void pack12(uint32_t (&r)[12], const float (&d)[N], int off) {
#pragma unroll
  for (int j = 0; j < 12; j++) r[j] = pack2(d[off + 2 * j], d[off + 2 * j + 1]);
}
__device__ __forceinline__ uint64_t dsc(uint64_t lo, uint32_t hi) { uint64_t r; asm("mov.b64 %0, {%1, %2};" : "=l"(r) : "r"((uint32_t)lo), "r"(hi)); return r; }
template <int XS, int K0, int K1> __device__ __forceinline__ void issue_core(const GemmCtx& c, float (&d)[72]) {
  constexpr uint64_t da = mkdesc(SBC + XS, 16, 1024, 1), db = mkdesc(SBC + SM_W, 6144, 256, 3);
  wg_fence();
  if (K0 == 0) wg_ss144<0>(d, dsc(da, c.hiA), dsc(db, c.hiB));
#pragma unroll
  for (int k = K0 ? K0 : 1; k < K1; k++) wg_ss144<1>(d, dsc(da + (k >> 2) * 512 + (k & 3) * 2, c.hiA), dsc(db + k * 32, c.hiB));
  wg_commit();
}
template <int K0, int K1> __device__ __forceinline__ void issue_halo(const GemmCtx& c, float (&d)[48]) {
  constexpr uint64_t da = mkdesc(SBC + SM_X0 - 2048, 16, 1024, 1), db = mkdesc(SBC + SM_W, 6144, 256, 3);
  wg_fence();
  if (K0 == 0) wg_ss96<0>(d, dsc(da, c.hiA), dsc(db, c.hiB));
#pragma unroll
  for (int k = K0 ? K0 : 1; k < K1; k++) wg_ss96<1>(d, dsc(da + (k >> 2) * 384 + (k & 3) * 2, c.hiA), dsc(db + k * 32, c.hiB));
  wg_commit();
}
template <int ST> __device__ __forceinline__ void release_stage(const GemmCtx& c) {
  asm volatile("{\n.reg .pred p;\nelect.sync _|p, 0xffffffff;\n@p mbarrier.arrive.shared::cluster.b64 _, [%0];\n}" ::"r"(c.em[ST]) : "memory");
}
__device__ __forceinline__ void edge_ready(const GemmCtx& c, int bar) { __syncwarp(); if (c.edge) mbar_arrive_elect(c.bar + bar * 8); }
__device__ __forceinline__ void dump6(uint32_t a, const uint32_t (&r)[6]) {
  stsm4(a, r[0], r[1], r[2], r[3]);
  asm volatile("stmatrix.sync.aligned.m8n8.x2.shared.b16 [%0], {%1,%2};" ::"r"(a + 512), "r"(r[4]), "r"(r[5]) : "memory");
}
__device__ __forceinline__ void pack6(uint32_t (&r)[6], const float (&d)[48], int off) {
#pragma unroll
  for (int j = 0; j < 6; j++) r[j] = pack2(d[off + 4 * j], d[off + 4 * j + 1]);
}
template <int PARITY> __device__ __forceinline__ void gwait(GemmCtx& c, int bar) {
  asm volatile("{\n.reg .pred p;\nWL:\nmbarrier.try_wait.parity.shared::cta.b64 p, [%1], %2;\n@p bra WD;\n"
               "add.u32 %0, %0, 1;\nsetp.lt.u32 p, %0, 0x100000;\n@p bra WL;\nWD:\n}" : "+r"(c.spin) : "r"(c.bar + bar * 8), "n"(PARITY) : "memory");
}
__device__ __forceinline__ void load_w(const CUtensorMap* m, uint32_t dst, uint32_t bar, int col) {
  asm volatile("cp.async.bulk.tensor.2d.shared::cluster.global.mbarrier::complete_tx::bytes [%0], [%1, {%3,%4}], [%2];"
               ::"r"(dst), "l"(m), "r"(bar), "r"(col), "r"(0) : "memory");
}
template <int BYTES> __device__ __forceinline__ void send_o(uint32_t dst, uint32_t src, uint32_t bar, int cta) {
  asm volatile("{\n.reg .b32 rd, rb;\nmapa.shared::cluster.u32 rd, %0, %3;\nmapa.shared::cluster.u32 rb, %2, %3;\n"
               "cp.async.bulk.shared::cluster.shared::cta.mbarrier::complete_tx::bytes [rd], [%1], %4, [rb];\n}"
               ::"r"(dst), "r"(src), "r"(bar), "r"(cta), "n"(BYTES) : "memory");
}
__device__ __forceinline__ void remote_arrive(uint32_t rbar) { asm volatile("mbarrier.arrive.shared::cluster.b64 _, [%0];" ::"r"(rbar) : "memory"); }
__device__ __forceinline__ void remote_expect(uint32_t rbar, uint32_t bytes) {
  asm volatile("mbarrier.arrive.expect_tx.shared::cluster.b64 _, [%0], %1;" ::"r"(rbar), "r"(bytes) : "memory");
}
__device__ __forceinline__ void copy_remote(uint32_t rdst, uint32_t src, uint32_t bytes, uint32_t rbar) {
  asm volatile("cp.async.bulk.shared::cluster.shared::cta.mbarrier::complete_tx::bytes [%0], [%1], %2, [%3];" ::"r"(rdst), "r"(src), "r"(bytes), "r"(rbar) : "memory");
}
__device__ __forceinline__ void tail_free(uint32_t bar) {
  uint32_t ln; asm volatile("mov.u32 %0, %%laneid;" : "=r"(ln));
  if (ln < 4) mbar_arrive_remote(bar, ln + (blockIdx.x & 4));
}
__device__ __forceinline__ void publish(uint32_t bar) {
  fence_async();
  __syncwarp();
  mbar_arrive_elect(bar);
}

template <bool FIRST, int PA>
__device__ __forceinline__ void gemm_iter(GemmCtx& c, int b, uint32_t (&pk)[12], uint32_t (&pv)[12], uint32_t (&pq)[12],
                                          uint32_t (&hk1)[6], uint32_t (&hv1)[6] TRARG) {
  const uint32_t bar = c.bar;
  const bool w = !FIRST && (PA == 0 || b >= 0), never = c.never;
  constexpr uint32_t ko = PA * KSLOT;
  float C[72];
  uint32_t hk0[6], hv0[6], pv2[12];
  TR(2, b, 0);
  if (FIRST) gwait<0>(c, B_FULL + 0);
  else dump12<256>(c.qC[1] + (PA ^ 1) * 128, pq);
  if (w) nb_sync(N_QK1, 256);
  TR(2, b, 2);
  if (PA == 0) {
    float H[48];
    issue_halo<0, 8>(c, H);
    TR(2, b, 3);
    if (!FIRST) { gwait<0>(c, B_KFREE); dump12<128>(c.kC, pk); }
    issue_halo<8, 12>(c, H);
    TR(2, b, 4);
    gwait<0>(c, B_FULL + 2);
    if (FIRST) gwait<0>(c, B_WQ);
    issue_core<SM_X2, 0, 8>(c, C);
    TR(2, b, 5);
    if (!FIRST) { fence_async(); edge_ready(c, B_XV); keep12(never, c.kC, pk); }
    wg_wait<1>(); pin(H);
    release_stage<0>(c);
    pack6(hk0, H, 0);
    if (c.hvalid) dump6(c.kH, hk0);
    pack6(hk1, H, 2); pack6(hv0, H, 24); pack6(hv1, H, 26);
  } else {
    issue_core<SM_X2, 0, 8>(c, C);
    TR(2, b, 5);
    fence_async();
    if (w) edge_ready(c, B_XV);
    keep12(never, c.kC, pq);
    if (w) gwait<1>(c, B_KFREE);
    dump12<128>(c.kC + ko, pk);
    if (c.hvalid) dump6(c.kH + ko, hk1);
  }
  TR(2, b, 13);
  issue_core<SM_X2, 8, 12>(c, C);
  if (w) { nb_arrive(N_VQ0, 288); nb_arrive(N_VQ1, 288); }
  else if (!FIRST) { __syncwarp(); mbar_arrive_elect(bar + B_Q0 * 8); }
  gwait<PA>(c, B_FULL + 1);
  if (never) dump6(bar, PA ? hk1 : hk0);
  TR(2, b, 6);
  wg_wait<0>(); pin(C);
  TR(2, b, 7);
  release_stage<2>(c);
  pack12(pk, C, 0);
  dump12<128>(c.kC + ko + 64, pk);
  pack12(pv2, C, 24);
  pack12(pq, C, 48);
  TR(2, b, 8);
  issue_core<SM_X1, 0, SPL>(c, C);
  if (w) nb_sync(N_PVISS, 384);
  issue_core<SM_X1, SPL, 8>(c, C);
  TR(2, b, 9);
  if (!FIRST) { fence_async(); edge_ready(c, B_XK); }
  keep12(never, c.kC, pk);
  TR(2, b, 14);
  issue_core<SM_X1, 8, 12>(c, C);
  if (!FIRST) nb_arrive(N_KRDY, 256);
  TR(2, b, 1);
  if (PA) { if (b == 11) tail_free(bar + B_TFREE * 8); mbar_wait(bar + B_FULL * 8, ((b + 3) >> 1) & 1); }
  if (w) gwait<PA>(c, B_VFREE);
  TR(2, b, 10);
  if (!FIRST) dump12<128>(c.vC[PA], pv);
  dump12<256>(c.qC[0] + PA * 128, pq);
  TR(2, b, 11);
  wg_wait<0>(); pin(C);
  TR(2, b, 12);
  release_stage<1>(c);
  if (PA == 0) gwait<1>(c, B_FULL + 2);
  if (c.hvalid) dump6(c.vH[PA], PA ? hv1 : hv0);
  dump12<128>(c.vC[PA ^ 1] + 768, pv2);
  pack12(pk, C, 0);
  pack12(pv, C, 24);
  pack12(pq, C, 48);
}

template <int IN> __device__ __forceinline__ void issue_proj(float (&D)[48]) {
  constexpr uint64_t da = mkdesc(SBC + IN, 128, 768, 0), db = mkdesc(SBC + SM_TWO, 12288, 512, 2);
  wg_fence();
  wg_ss96<0>(D, da, db);
#pragma unroll
  for (int k = 1; k < 12; k++) wg_ss96<1>(D, da + (k / 3) * 384 + (k % 3) * 16, db + k * 64);
  wg_commit();
}
template <int ACC> __device__ __forceinline__ void issue_proj_half(float (&D)[48], int hd) {
  const uint64_t da = mkdesc(SBC + SM_TIN + 2 * 24576, 128, 768, 0) + hd * 384, db = mkdesc(SBC + SM_TWO, 12288, 512, 2) + hd * 192;
  wg_fence();
  wg_ss96<ACC>(D, da, db);
#pragma unroll
  for (int k = 1; k < 6; k++) wg_ss96<1>(D, da + (k / 3) * 768 + (k % 3) * 16, db + (k / 3) * 384 + (k % 3) * 64);
  wg_commit();
}
__device__ __forceinline__ void store_proj(const float (&D)[48], const CUtensorMap* m, uint32_t st, uint32_t sta, int row, int col, int ch) {
#pragma unroll
  for (int q = 0; q < 6; q++)
    stsm4((sta ^ ((q & 1) * 32)) + (q >> 1) * 1024,
          pack2(D[8 * q], D[8 * q + 1]), pack2(D[8 * q + 2], D[8 * q + 3]), pack2(D[8 * q + 4], D[8 * q + 5]), pack2(D[8 * q + 6], D[8 * q + 7]));
  fence_async();
  __syncwarp();
  if ((threadIdx.x & 31) == 0) {
    asm volatile("cp.async.bulk.tensor.4d.global.shared::cta.bulk_group [%0, {%2,%3,%4,%5}], [%1];" ::"l"(m), "r"(st), "r"(0), "r"(row), "r"(col), "r"(ch) : "memory");
    asm volatile("cp.async.bulk.commit_group;" ::: "memory");
  }
  __syncwarp();
}

__device__ __forceinline__ float fold(float a, float b, float t, int useb) {
  float r;
  asm("{\n.reg .pred p;\nsetp.ne.b32 p, %4, 0;\nfma.rn.f32 %0, %1, 0f3E553B95, %3;\n@p fma.rn.f32 %0, %2, 0f3E553B95, %3;\n}"
      : "=&f"(r) : "f"(a), "f"(b), "f"(t), "r"(useb));
  return r;
}
template <int U, int L>
__device__ __forceinline__ void softmax_tile(const float (&SA)[56], const float (&SB)[56], const float (&T)[16], int b0, int b1,
                                             uint32_t (&P)[28], float (&sx)[8]) {
  float lu[14], ll[14];
#pragma unroll
  for (int j = 0; j < 7; j++) {
    constexpr int sh = U == L ? 2 : 0;
    const float tu0 = T[2 * j + sh], tu1 = T[2 * j + 1 + sh], tl0 = T[2 * j], tl1 = T[2 * j + 1];
    lu[2 * j]     = fold(SA[4 * (U + j)],     SB[4 * (U + j)],     tu0, b0);
    ll[2 * j]     = fold(SA[4 * (L + j) + 2], SB[4 * (L + j) + 2], tl0, b0);
    lu[2 * j + 1] = fold(SA[4 * (U + j) + 1], SB[4 * (U + j) + 1], tu1, b1);
    ll[2 * j + 1] = fold(SA[4 * (L + j) + 3], SB[4 * (L + j) + 3], tl1, b1);
  }
  float mu = lu[0], ml = ll[0], mu2 = lu[1], ml2 = ll[1];
#pragma unroll
  for (int j = 1; j < 7; j++) { mu = fmaxf(mu, lu[2 * j]); mu2 = fmaxf(mu2, lu[2 * j + 1]); ml = fmaxf(ml, ll[2 * j]); ml2 = fmaxf(ml2, ll[2 * j + 1]); }
  mu = fmaxf(mu, mu2); ml = fmaxf(ml, ml2);
  { const float a1 = __shfl_xor_sync(0xffffffffu, mu, 1), a2 = __shfl_xor_sync(0xffffffffu, mu, 2), a3 = __shfl_xor_sync(0xffffffffu, mu, 3);
    const float c1 = __shfl_xor_sync(0xffffffffu, ml, 1), c2 = __shfl_xor_sync(0xffffffffu, ml, 2), c3 = __shfl_xor_sync(0xffffffffu, ml, 3);
    mu = fmaxf(fmaxf(mu, a1), fmaxf(a2, a3)); ml = fmaxf(fmaxf(ml, c1), fmaxf(c2, c3)); }
  float su = 0.f, sl = 0.f;
#pragma unroll
  for (int c = 0; c < 14; c++) {
    const int iu = (c >> 1) * 4 + (c & 1) * 2;
    if (c >= U && c < U + 7) {
      float e0 = ex2(lu[2 * (c - U)] - mu), e1 = ex2(lu[2 * (c - U) + 1] - mu);
      su = c == U ? e0 + e1 : (su + e0) + e1; P[iu] = pack2(e0, e1);
    } else P[iu] = 0u;
    if (c >= L && c < L + 7) {
      float e0 = ex2(ll[2 * (c - L)] - ml), e1 = ex2(ll[2 * (c - L) + 1] - ml);
      sl = c == L ? e0 + e1 : (sl + e0) + e1; P[iu + 1] = pack2(e0, e1);
    } else P[iu + 1] = 0u;
  }
  sx[0] = su; sx[4] = sl;
#pragma unroll
  for (int k = 1; k < 4; k++) { sx[k] = __shfl_xor_sync(0xffffffffu, su, k); sx[4 + k] = __shfl_xor_sync(0xffffffffu, sl, k); }
}

struct BandCfg { uint32_t ra0, ra1, meta; int b0, b1; };
__device__ __forceinline__ void band_cfg(int b, uint32_t tb, BandCfg& n) {
  uint32_t ln; asm volatile("mov.u32 %0, %%laneid;" : "=r"(ln));
  const int g = ln >> 2, t = ln & 3;
  const int sw = min(max(g + 1, b == 0 ? 4 : 0), b == 13 ? 5 : 8);
  const int i0 = 2 * t, i1 = 2 * t + 1;
  n.b0 = i0 <= sw - 2; n.b1 = i1 <= sw - 2;
  n.ra0 = tb + (i0 == sw - 1 ? 13 : i0 + 8 * n.b0 - g + 2) * 52;
  n.ra1 = tb + (i1 == sw - 1 ? 13 : i1 + 8 * n.b1 - g + 2) * 52;
  n.meta = ((0x5555u & ((1u << (2 * (sw - 1))) - 1)) ^ 0xDD88u ^ (((t ^ b) & 1) ? 0x5555u : 0u)) * 0x10001u;
}
__device__ __forceinline__ void band_load(const BandCfg& n, float (&T)[16], int& b0, int& b1, uint32_t& meta) {
#pragma unroll
  for (int jj = 0; jj < 8; jj++) { T[2 * jj] = lds_f32(n.ra0 + jj * 4); T[2 * jj + 1] = lds_f32(n.ra1 + jj * 4); }
  b0 = n.b0; b1 = n.b1; meta = n.meta;
}

struct Maps { CUtensorMap xc, xh, w, os, wo, ot; };

__global__ void __cluster_dims__(8, 1, 1) __launch_bounds__(512, 1)
na_attn_kernel(const __nv_bfloat16* __restrict__ x, const __nv_bfloat16* __restrict__ wqkv, const __nv_bfloat16* __restrict__ rpb, const __grid_constant__ Maps mp) {
  extern __shared__ __align__(1024) uint8_t smem_raw[];
  const uint32_t sb = smem_u32(smem_raw);
  if ((sb & 0x3FFFF) != SBC) return;
  const uint32_t bar = sb + SM_BAR;
  TR2(blockIdx.x, 0);
  const int tid = threadIdx.x, lane = tid & 31;
  const int warp = __shfl_sync(0xffffffffu, tid >> 5, 0);
  const int head = blockIdx.x & 3, base = blockIdx.x & 4, sp = blockIdx.x >> 2;
  const int par = sp < 24 ? sp / 6 : sp - 24, strip = sp < 24 ? sp - par * 6 : 6, ph = par >> 1, pw = par & 1;
  const int odd = strip & 1;

  uint4 wv[2 * NL];
  const int va = head == 1;
  const uint32_t wdst = sb + SM_W + (va + ((tid >> 1) & 1)) * 6144 + (tid >> 2) * 32 + ((tid ^ (tid >> 4)) & 1) * 16;
  if (warp < 12) asm volatile("barrier.cluster.arrive.relaxed.aligned;" ::: "memory");
  {
    const uint32_t wo0 = (tid >> 2) * 1152 + head * 96 + va * 32 + (tid & 3) * 16;
#pragma unroll
    for (int i = 0; i < 2 * NL; i++)
      asm volatile("{\n.reg .pred p;\nsetp.lt.u32 p, %5, 384;\n@p ld.global.nc.v4.b32 {%0,%1,%2,%3}, [%4];\n}"
                   : "=r"(wv[i].x), "=r"(wv[i].y), "=r"(wv[i].z), "=r"(wv[i].w)
                   : "l"(reinterpret_cast<const uint8_t*>(wqkv) + wo0 + (i & 1) * 96 * 1152 + ((i / 2 + 1) % 3) * 384), "r"(tid));
  }
  if (warp < 8) {
    asm volatile("setmaxnreg.inc.sync.aligned.u32 %0;" ::"n"(RA));
    float rv = -INFINITY;
    if (tid < 169) rv = __bfloat162float(rpb[head * 169 + tid]) * 1.4426950408889634f;
    if (tid < 192) {
      const int kc = (tid & 15) + 3, wc = (tid >> 4) % 6;
      sts128(tid < 96 ? sb + SM_K + kc * KS + wc * 128 + 48 : sb + SM_V + kc * 1536 + wc * 128 + (6 + (kc & 1)) * 16, make_uint4(0, 0, 0, 0));
    }
#pragma unroll
    for (int i = 0; i < 2 * NL; i++) sts128(wdst + (i & 1) * 3072 + (i / 2) * 18432, wv[i]);
    fence_async();
    asm volatile("bar.arrive 1, 384;" ::: "memory");
    if (tid < 182) asm volatile("st.shared.f32 [%0], %1;" ::"r"(sb + SM_RPB + tid * 4), "f"(rv) : "memory");
    const int jw = warp >> 2, j = jw ^ odd, w = warp & 3, wt = 4 * j + w;
    int variant = w;
    if (strip == 0 && j == 0 && w < 2) variant = 4;
    if (strip == 6 && j == 1 && w >= 2) variant = 5;
    const bool v1 = opq((uint32_t)(variant & 1)), v2 = opq((uint32_t)(variant & 2)), v4 = opq((uint32_t)(variant & 4));
    uint32_t qa = opq(sb + SM_Q + (8 * j + 2 * w + ((lane >> 3) & 1)) * 1536 + (lane >> 4) * 256 + (((lane & 7) * 16) ^ (((lane >> 3) & 1) * 64)));
    uint32_t oa = opq(sb + SM_O + j * 6144 + (2 * w + ((lane >> 3) & 1)) * 768 + (lane >> 4) * 128 + (lane & 7) * 16);
    uint64_t dA = opq(mkdesc(SBC + SM_K, 128, KS, 0) + j * (8 * KS / 16)), dB = opq(dA + (KSLOT >> 4));
    uint64_t dV[7];
#pragma unroll
    for (int i = 0; i < 7; i++) dV[i] = opq(mkdesc(SBC + SM_V, 768, 128, 0) + j * (8 * 1536 / 16) + i * 192);
    const uint32_t nbK = opq((uint32_t)(N_KRDY + jw)), nbQ = opq((uint32_t)(N_QK0 + jw)), nbV = opq((uint32_t)(N_VQ0 + jw));
    asm volatile("barrier.cluster.wait.aligned;" ::: "memory");
    asm volatile("bar.sync 3, 256;" ::: "memory");
    float T[16];
    TRDECL;
    int b0, b1;
    uint32_t meta, ob = bar + B_ODONE * 8;
    const uint32_t tb = opq(sb + SM_RPB + (variant < 4 ? 3 : variant + 1 - 2 * w) * 4);
    const bool own = ((w ^ head) & 2) == 0;
    const uint32_t dst13 = sb + SM_TIN + 2 * 24576 + head * 6144 + (2 * j + (w & 1)) * 1536, src13 = opq(own ? dst13 : sb + SM_Q + wt * 3072 + 1536);
    const uint32_t snd[4] = {opq(own ? 0u : mapa(dst13, base + (head ^ 2))), opq(mapa(bar + (B_TIN + 2) * 8, base + (head ^ 2))),
                             opq(mapa(dst13, base + (w & 2) + (~head & 1))), opq(mapa(bar + (B_TIN + 3) * 8, base + (w & 2) + (~head & 1)))};
    BandCfg nx;
    band_cfg(0, tb, nx);
    band_load(nx, T, b0, b1, meta);
    band_cfg(1, tb, nx);
    uint32_t special = opq(0x380Au << 1);
    uint32_t q[12];
    mbar_wait(bar + B_Q0 * 8, 0);
#pragma unroll
    for (int k = 0; k < 3; k++) ldsm4(qa + k * 512, q[4 * k], q[4 * k + 1], q[4 * k + 2], q[4 * k + 3]);
    qa ^= 128;
#pragma unroll 1
    for (int b = 0; b < 14; b++) {
      float SA[56], SB[56];
      TR(0, b, 0);
      if (jw) mbar_wait(bar + B_KIMP * 8, b & 1);
      nb_sync(nbK, 256);
      TR(0, b, 1);
      TR(0, b - 1, 9);
      wg_fence();
      wg_rs112<0>(SA, q[0], q[1], q[2], q[3], dA);
      wg_rs112<0>(SB, q[0], q[1], q[2], q[3], dB);
      wg_rs112<1>(SA, q[4], q[5], q[6], q[7], dA + 16);
      wg_rs112<1>(SB, q[4], q[5], q[6], q[7], dB + 16);
      wg_rs112<1>(SA, q[8], q[9], q[10], q[11], dA + 32);
      wg_rs112<1>(SB, q[8], q[9], q[10], q[11], dB + 32);
      wg_commit();
      nb_arrive(nbQ, 256);
      { const uint64_t t = dA; dA = dB; dB = t; }
      special >>= 1;
      if (special & 1) {
        if (b == 3) band_cfg(13, tb, nx);
        else {
          if (b == 1 || b == 13) band_load(nx, T, b0, b1, meta);
          if (b >= TB) {
            ob = bar + (b == 13 && own ? B_TIN + 2 : B_OTAIL + jw) * 8;
            oa += b == 12 ? wt * 1536 - (SM_O - SM_Q) : (b == 13 ? src13 - (sb + SM_Q + wt * 3072) : 0);
          }
        }
      }
      TR(0, b, 2);
      wg_wait<0>(); pin(SA); pin(SB);
      mbar_arrive_elect(bar + B_KFREE * 8);
      TR(0, b, 3);
      TR(0, b - 1, 10);
      uint32_t P[28];
      float sx[8];
      if (v2) {
        if (v1) softmax_tile<6, 7>(SA, SB, T, b0, b1, P, sx); else softmax_tile<4, 5>(SA, SB, T, b0, b1, P, sx);
      } else if (!v4) {
        if (v1) softmax_tile<2, 3>(SA, SB, T, b0, b1, P, sx); else softmax_tile<0, 1>(SA, SB, T, b0, b1, P, sx);
      } else {
        if (v1) softmax_tile<4, 4>(SA, SB, T, b0, b1, P, sx); else softmax_tile<3, 3>(SA, SB, T, b0, b1, P, sx);
      }
      float O[24];
      TR(0, b, 4);
      nb_sync(nbV, 288);
      TR(0, b, 5);
#pragma unroll
      for (int k = 0; k < 3; k++) ldsm4(qa + k * 512, q[4 * k], q[4 * k + 1], q[4 * k + 2], q[4 * k + 3]);
      wg_fence();
      wg_sp48<0>(O, P[0], P[1], P[2], P[3], dV[0], meta);
#pragma unroll
      for (int s = 1; s < 7; s++) wg_sp48<1>(O, P[4 * s], P[4 * s + 1], P[4 * s + 2], P[4 * s + 3], dV[s], meta);
      wg_commit();
      nb_arrive(N_PVISS, 384);
      TR(0, b, 6);
      wg_wait<0>(); pin(O);
      mbar_arrive_elect(bar + B_VFREE * 8);
      TR(0, b, 7);
      float ru, rl;
      asm("rcp.approx.ftz.f32 %0, %1;" : "=f"(ru) : "f"(((fmaf(O[0], 0.f, sx[0]) + sx[1]) + sx[2]) + sx[3]));
      asm("rcp.approx.ftz.f32 %0, %1;" : "=f"(rl) : "f"(((fmaf(O[2], 0.f, sx[4]) + sx[5]) + sx[6]) + sx[7]));
#pragma unroll
      for (int i = 0; i < 3; i++)
        stsm4(oa + i * 256, pack2(O[8 * i] * ru, O[8 * i + 1] * ru), pack2(O[8 * i + 2] * rl, O[8 * i + 3] * rl),
              pack2(O[8 * i + 4] * ru, O[8 * i + 5] * ru), pack2(O[8 * i + 6] * rl, O[8 * i + 7] * rl));
      publish(ob);
      qa ^= 128;
      meta ^= 0x55555555u;
      TR(0, b, 8);
    }
    asm volatile("{\n.reg .pred p, q;\nsetp.ne.b32 q, %1, 0;\nelect.sync _|p, 0xffffffff;\nand.pred q, q, p;\n"
                 "@q cp.async.bulk.shared::cluster.shared::cta.mbarrier::complete_tx::bytes [%1], [%0], 1536, [%2];\n"
                 "@p cp.async.bulk.shared::cluster.shared::cta.mbarrier::complete_tx::bytes [%3], [%0], 1536, [%4];\n}"
                 ::"r"(src13), "r"(snd[0]), "r"(snd[1]), "r"(snd[2]), "r"(snd[3]) : "memory");
    if (jw == 0) nb_arrive(3, 256);
    TRDUMP;
    cluster_sync();
  } else if (warp < 12) {
    TRDECL;
    TR(2, -3, 0);
    asm volatile("setmaxnreg.inc.sync.aligned.u32 %0;" ::"n"(RG));
    TR(2, -3, 1);
    GemmCtx c;
    c.bar = bar;
    const int gw = warp - 8, tk = gw * 16 + (lane & 15), hi = lane >> 4;
    { const int col = tk >> 2, i = tk & 3;
      c.kC = sb + SM_K + (col + 3) * KS + hi * 128 + i * 16;
      c.vC[0] = sb + SM_V + (col + 3) * 1536 + hi * 128 + (2 * i + ((col + 3) & 1)) * 16;
      c.qC[0] = sb + SM_Q + col * 1536 + hi * 256 + (col & 1) * 64 + i * 16; }
    { const int kc = gw - 1 + 19 * odd, i = lane & 7; c.hvalid = gw > 0; c.edge = gw == (odd ? 0 : 3);
      c.kH = sb + SM_K + kc * KS + (lane >> 3) * 128 + i * 16;
      c.vH[0] = sb + SM_V + kc * 1536 + (lane >> 3) * 128 + (i >> 2) * 768 + (2 * (i & 3) + ((kc ^ (i >> 2)) & 1)) * 16; }
#pragma unroll
    for (int i = 0; i < 3; i++) c.em[i] = opq(mapa(bar + (B_EMPTY + i) * 8, base + i));
    c.never = x == nullptr;
    c.kC = opq(c.kC); c.kH = opq(c.kH);
    c.vC[1] = opq(c.vC[0] ^ 16); c.vC[0] = opq(c.vC[0]);
    c.vH[1] = opq(c.vH[0] ^ 16); c.vH[0] = opq(c.vH[0]);
    c.qC[1] = opq(c.qC[0] ^ 64); c.qC[0] = opq(c.qC[0]);
    c.spin = 0;
    c.hiA = (uint32_t)(mkdesc(0, 0, 1024, 1) >> 32) + (blockIdx.x >> 16); c.hiB = (uint32_t)(mkdesc(0, 0, 256, 3) >> 32) + (blockIdx.x >> 16);
    asm volatile("barrier.cluster.wait.aligned;" ::: "memory");
    TR(2, -3, 2);
#pragma unroll
    for (int i = 0; i < 2 * NL; i++) sts128(wdst + (i & 1) * 3072 + (i / 2) * 18432, wv[i]);
    fence_async();
    TR(2, -3, 3);
    asm volatile("bar.sync 1, 384;" ::: "memory");
    TR(2, -3, 4);
    mbar_wait(bar + B_WK * 8, 0);
    TR(2, -3, 5);
    uint32_t pk[12], pv[12], pq[12], hk1[6], hv1[6];
    gemm_iter<true, 0>(c, -2, pk, pv, pq, hk1, hv1 TRPASS);
    TR2(blockIdx.x, 4);
    c.hiA = opq(c.hiA); c.hiB = opq(c.hiB);
#pragma unroll 1
    for (int b = -1;; b += 2) {
      gemm_iter<false, 1>(c, b, pk, pv, pq, hk1, hv1 TRPASS);
      if (b == 11) break;
      gemm_iter<false, 0>(c, b + 1, pk, pv, pq, hk1, hv1 TRPASS);
    }
    TR2(blockIdx.x, 6);
    const uint32_t st = sb + gw * 3072;
    const uint32_t sta = st + (lane & 15) * 64 + ((hi ^ ((lane >> 1) & 3)) * 16);
    const int oc = ph * 112 + strip * 16 + 8 * (gw >> 1) + 4 * (head >> 1) + 2 * (gw & 1), och = pw * 6 + (head & 1) * 3;
    float D0[48], D1[48];
    mbar_arrive_elect(bar + B_WOFREE * 8);
    dump12<256>(c.qC[1] + 128, pq);
    fence_async();
    edge_ready(c, B_XV);
    nb_sync(N_QK1, 256);
    issue_halo<0, 12>(c, D1);
    gwait<0>(c, B_KFREE);
    dump12<128>(c.kC, pk);
    fence_async();
    edge_ready(c, B_XK);
    nb_arrive(N_VQ0, 288); nb_arrive(N_VQ1, 288); nb_arrive(N_PVISS, 384);
    wg_wait<0>(); pin(D1);
    pack6(hk1, D1, 0);
    if (c.hvalid) dump6(c.kH, hk1);
    tail_free(bar + (B_TFREE + 1) * 8);
    pack6(hv1, D1, 24);
    fence_async();
    nb_arrive(N_KRDY, 256);
    gwait<0>(c, B_VFREE);
    dump12<128>(c.vC[0], pv);
    if (c.hvalid) dump6(c.vH[0], hv1);
    fence_async();
    edge_ready(c, B_XV);
    nb_arrive(N_VQ0, 288); nb_arrive(N_VQ1, 288);
    gwait<0>(c, B_WO);
    gwait<0>(c, B_TIN);
    TR(2, 13, 0);
    nb_sync(N_QK1, 256);
    issue_proj<SM_TIN>(D0);
    wg_wait<0>(); pin(D0);
    TR(2, 13, 1);
    store_proj(D0, &mp.ot, st + SM_TST, sta + SM_TST, 8 * TB, oc, och);
    gwait<0>(c, B_TIN + 1);
    TR(2, 13, 2);
    nb_sync(N_PVISS, 384);
    nb_sync(3, 256);
    issue_proj<SM_TIN + 24576>(D1);
    wg_wait<0>(); pin(D1);
    TR(2, 13, 3);
    store_proj(D1, &mp.ot, st + SM_TIN, sta + SM_TIN, 8 * TB + 8, oc, och);
    TR(2, 13, 4);
    gwait<0>(c, B_TIN + 2);
    TR(2, 13, 5);
    issue_proj_half<0>(D0, head & 1);
    gwait<0>(c, B_TIN + 3);
    TR(2, 13, 6);
    issue_proj_half<1>(D0, ~head & 1);
    asm volatile("barrier.cluster.arrive.relaxed.aligned;" ::: "memory");
    wg_wait<0>(); pin(D0);
    store_proj(D0, &mp.ot, st + SM_TIN + 12288, sta + SM_TIN + 12288, 8 * TB + 16, oc, och);
    TR(2, 13, 7);
    if (lane == 0) asm volatile("cp.async.bulk.wait_group.read 0;" ::: "memory");
    __syncwarp();
    TR(2, 13, 8);
    TR2(blockIdx.x, 2);
    TRDUMP;
    asm volatile("barrier.cluster.wait.aligned;" ::: "memory");
  } else {
    if (warp == 12) {
      if (elect_one()) {
        mbar_init(bar + B_WK * 8, 1);
#pragma unroll
        for (int i = 0; i < NL; i++) load_w(&mp.w, sb + SM_W + (3 * i + 2 - 2 * va) * 6144, bar + B_WK * 8, ((i + 1) % 3) * 192 + head * 48 + 32 - 32 * va);
        asm volatile("prefetch.tensormap [%0];" ::"l"(head ? &mp.xc : &mp.xh) : "memory");
        mbar_expect(bar + B_WK * 8, NL * 6144);
      }
    } else if (warp == 15) {
      const int col = min(max(strip * 16 - 3 + min(lane, 21), 0), 111);
      const uint8_t* p = reinterpret_cast<const uint8_t*>(x) + (uint32_t)(head * ROWB + (ph * 112 + col) * 768 + pw * 384);
#pragma unroll
      for (int i = 0; i < 3; i++) asm volatile("prefetch.global.L2 [%0];" ::"l"(p + i * 128));
    } else if (elect_one()) {
      if (warp == 13) {
#pragma unroll
        for (int i = 0; i < B_WK; i++) mbar_init(bar + i * 8, i < B_EMPTY ? 1 : (i < B_TIN ? 16 : (i < B_TFREE ? (i == B_TIN + 2 ? 5 : 1) : 16)));
      } else {
#pragma unroll
        for (int i = B_WQ; i < B_COUNT; i++) mbar_init(bar + i * 8, i < B_Q0 ? 1 : (i < B_ODONE ? 4 : (i == B_VFREE ? 9 : 8)));
      }
    }
    asm volatile("fence.mbarrier_init.release.cluster;" ::: "memory");
    __syncwarp();
    asm volatile("barrier.cluster.arrive.relaxed.aligned;" ::: "memory");
    asm volatile("setmaxnreg.dec.sync.aligned.u32 24;");
    asm volatile("griddepcontrol.launch_dependents;");
    asm volatile("barrier.cluster.wait.aligned;" ::: "memory");
    if (warp == 12) {
      const CUtensorMap* mx = head ? &mp.xc : &mp.xh;
      const int cc = ph * 112 + strip * 16 + (head ? 0 : (odd ? 16 : (strip ? -3 : 0)));
      const int r0 = head == 0 ? (strip ? -4 : 112) : (head == 1 ? 4 : 0), dr = head ? 8 : 16;
      const uint32_t fb = bar + (B_FULL + head) * 8, eb = bar + (B_EMPTY + head) * 8;
      const uint32_t dst = sb + (head == 0 ? SM_X0 : (head == 1 ? SM_X1 : SM_X2));
      const int nl = head == 0 ? 8 : (head == 3 ? 1 : 14);
      TRDECL;
#pragma unroll 1
      for (int n = 0; n < nl; n++) {
        if (n) mbar_wait(eb, (n - 1) & 1);
        TR(2, n - 3, 0);
        if (elect_one()) {
          if (head < 3)
            asm volatile("cp.async.bulk.tensor.4d.shared::cluster.global.mbarrier::complete_tx::bytes.multicast::cluster [%0], [%1, {%3,%4,%5,%6}], [%2], %7;"
                         ::"r"(dst), "l"(mx), "r"(fb), "r"(0), "r"(dr * n + r0), "r"(cc), "r"(pw * 3), "h"((uint16_t)(15 << base)) : "memory");
          if (n == 0) {
#pragma unroll
            for (int i = 0; i < 3; i++) load_w(&mp.w, sb + SM_W + (6 + i) * 6144, bar + B_WQ * 8, head * 48 + i * 16);
            mbar_expect(bar + B_WQ * 8, 18432);
            mbar_expect(bar + B_TIN * 8, 24576); mbar_expect(bar + (B_TIN + 1) * 8, 24576); mbar_expect(bar + (B_TIN + 2) * 8, 6144); mbar_expect(bar + (B_TIN + 3) * 8, 12288);
          }
          if (n + 1 < nl) asm volatile("cp.async.bulk.prefetch.tensor.4d.L2.global [%0, {%1,%2,%3,%4}];" ::"l"(mx), "r"(0), "r"(dr * n + dr + r0), "r"(cc), "r"(pw * 3) : "memory");
        }
        __syncwarp();
        TR(2, n - 3, 1);
        if (lane < 4 && head < 3)
          asm volatile("mbarrier.arrive.expect_tx.shared::cluster.b64 _, [%0], %1;" ::"r"(mapa(fb, base + lane)), "r"(head ? 24576 : 18432) : "memory");
        __syncwarp();
        TR(2, n - 3, 2);
      }
      TRDUMP;
      mbar_wait(bar + B_WOFREE * 8, 0);
      if (elect_one()) {
        mbar_expect(bar + B_WO * 8, 36864);
        asm volatile("cp.async.bulk.tensor.3d.shared::cluster.global.mbarrier::complete_tx::bytes [%0], [%1, {%3,%4,%5}], [%2];"
                     ::"r"(sb + SM_TWO), "l"(&mp.wo), "r"(bar + B_WO * 8), "r"(0), "r"(0), "r"((head & 1) * 3) : "memory");
      }
      __syncwarp();
    }
    if (warp == 13) {
      const uint32_t partner = (blockIdx.x & 7) ^ 4;
      const int cs = odd ? 3 : (strip == 6 ? 15 : 16), cd = odd || strip == 6 ? 19 : 0;
      const uint32_t rb = mapa(bar, partner), rk = mapa(sb + SM_K + cd * KS, partner), rv = mapa(sb + SM_V + cd * 1536, partner);
      mbar_wait(bar + B_XK * 8, 0);
      if (elect_one()) {
        remote_expect(rb + B_KIMP * 8, 6 * KS);
        copy_remote(rk, sb + SM_K + cs * KS, 3 * KS, rb + B_KIMP * 8);
        copy_remote(rk + KSLOT, sb + SM_K + cs * KS + KSLOT, 3 * KS, rb + B_KIMP * 8);
      }
      __syncwarp();
#pragma unroll 1
      for (int b = 0; b < 14; b++) {
        const uint32_t pa = b & 1;
        mbar_wait(bar + B_XV * 8, pa);
        if (b) mbar_wait(bar + B_PVF * 8, pa ^ 1);
        if (elect_one()) { remote_expect(rb + B_VIMP * 8, 4608); copy_remote(rv, sb + SM_V + cs * 1536, 4608, rb + B_VIMP * 8); }
        __syncwarp();
        mbar_wait(bar + B_KFREE * 8, pa);
        if (elect_one()) remote_arrive(rb + B_PKF * 8);
        __syncwarp();
        mbar_wait(bar + B_OFREE * 8, pa);
        mbar_wait(bar + B_VIMP * 8, pa);
        nb_arrive(N_VQ1, 288);
        if (elect_one()) remote_arrive(rb + B_VFREE * 8);
        __syncwarp();
        if (b == 13) break;
        mbar_wait(bar + B_XK * 8, pa ^ 1);
        mbar_wait(bar + B_PKF * 8, pa);
        if (elect_one()) { remote_expect(rb + B_KIMP * 8, 3 * KS); copy_remote(rk + pa * KSLOT, sb + SM_K + cs * KS + pa * KSLOT, 3 * KS, rb + B_KIMP * 8); }
        __syncwarp();
        mbar_wait(bar + B_VFREE * 8, pa);
        if (elect_one()) remote_arrive(rb + B_PVF * 8);
        __syncwarp();
      }
    }
    if (warp == 14) {
      int* flag = g_flags + (par * 7 + strip) * 2;
      nb_arrive(N_VQ0, 288); mbar_arrive_elect(bar + B_OFREE * 8);
#pragma unroll 1
      for (int b = 0; b < TB; b++) {
        mbar_wait(bar + B_ODONE * 8, b & 1);
        if (lane == 0) {
#pragma unroll 1
          for (int i = 0; i < 16; i += OCH) {
            asm volatile("cp.async.bulk.tensor.3d.global.shared::cta.bulk_group [%0, {%2,%3,%4}], [%1];"
                         ::"l"(&mp.os), "r"(sb + SM_O + i * 768), "r"(pw * 192), "r"(8 * b + 2 * head), "r"(ph * 112 + strip * 16 + i) : "memory");
            asm volatile("cp.async.bulk.commit_group;\ncp.async.bulk.wait_group 0;" ::: "memory");
          }
        }
        __syncwarp();
        nb_arrive(N_VQ0, 288); mbar_arrive_elect(bar + B_OFREE * 8);
        if (lane == 0)
          asm volatile("fence.proxy.async.global;\nfence.acq_rel.gpu;\nred.relaxed.gpu.global.add.s32 [%0], 1;\nred.relaxed.gpu.global.add.s32 [%0+4], 1;"
                       ::"l"(flag + b * 56) : "memory");
        __syncwarp();
      }
    }
    if (warp >= 14) {
      const int jw = warp - 14, j = jw ^ odd;
#pragma unroll 1
      for (int i = 0; i < 2; i++) {
        mbar_wait(bar + (B_OTAIL + jw) * 8, i);
        if (i == 1) mbar_wait(bar + (B_TFREE + 1) * 8, 0);
        if (jw) mbar_arrive_elect(bar + B_OFREE * 8); else nb_arrive(N_VQ0, 288);
        if (i == 0) mbar_wait(bar + B_TFREE * 8, 0);
        if (elect_one()) {
#pragma unroll 1
          for (int d = 0; d < 8; d++) {
            const int dst = (d + head) & 3, pc = d >> 2;
            send_o<1536>(sb + SM_TIN + i * 24576 + head * 6144 + j * 3072 + pc * 1536,
                         sb + (i ? SM_Q : SM_O) + (4 * j + (dst & 2) + pc) * (i ? 3072 : 1536), bar + (B_TIN + i) * 8, base + dst);
          }
        }
        __syncwarp();
      }
    }
    cluster_sync();
  }
}

constexpr int NSTB = 6;
constexpr int NTB = TB * 56;
constexpr int SM_B_ST = 0;
constexpr int SM_B_IN = 73728;
constexpr int SM_B_W = SM_B_IN + 3 * 24576;
constexpr int SM_B_BAR = SM_B_IN + NSTB * 24576;
constexpr int SM_B_TOTAL = SM_B_BAR + 512;
struct MapsB { CUtensorMap oi, oo, wo; };

__global__ void __launch_bounds__(512, 1)
na_proj_kernel(const __grid_constant__ MapsB mp) {
  extern __shared__ __align__(1024) uint8_t smem_raw[];
  const uint32_t sb = smem_u32(smem_raw);
  if ((sb & 0x3FFFF) != SBC) return;
  const uint32_t bar = sb + SM_B_BAR;
  const int tid = threadIdx.x, lane = tid & 31;
  const int warp = __shfl_sync(0xffffffffu, tid >> 5, 0);
  TR2(132 + blockIdx.x, 0);
  TRB(47, 0);
  if (warp == 12 && elect_one()) {
#pragma unroll
    for (int i = 0; i <= 2 * NSTB; i++) mbar_init(bar + i * 8, i < NSTB || i == 2 * NSTB ? 1 : 12);
    asm volatile("st.shared.u32 [%0], 0;" ::"r"(bar + 120) : "memory");
    mbar_expect(bar + 2 * NSTB * 8, 73728);
#pragma unroll
    for (int i = 0; i < 2; i++)
      asm volatile("cp.async.bulk.tensor.3d.shared::cluster.global.mbarrier::complete_tx::bytes [%0], [%1, {%3,%4,%5}], [%2];"
                   ::"r"(sb + SM_B_W + i * 36864), "l"(&mp.wo), "r"(bar + 2 * NSTB * 8), "r"(0), "r"(0), "r"(i * 3) : "memory");
  }
  __syncthreads();
  const int step = gridDim.x;
  if (warp == 15) {
    int so = 0;
    nb_arrive(4, 288); nb_arrive(5, 288); nb_arrive(6, 288);
#pragma unroll 1
    for (int n = blockIdx.x, tk = 0; n < NTB; n += step, tk++) {
      uint32_t cc = 0;
#pragma unroll
      for (int wg = 0; wg < 3; wg++) {
        if (lane == 0) asm volatile("cp.async.bulk.wait_group.read 5;" ::: "memory");
        nb_sync(1 + wg, 160);
        if (wg == 0 || n + step < NTB) nb_arrive(4 + wg, 288);
        if (wg == 0) asm volatile("ld.shared.u32 %0, [%1];" : "=r"(cc) : "r"(bar + 128 + tk * 4) : "memory");
        if (lane == 0) {
          asm volatile("cp.async.bulk.tensor.4d.global.shared::cta.bulk_group [%0, {%2,%3,%4,%5}], [%1];"
                       ::"l"(&mp.oo), "r"(sb + SM_B_ST + wg * 8192 + so), "r"(0), "r"((cc >> 8) & 255), "r"(cc >> 16), "r"((cc & 1) * 3 + wg) : "memory");
          asm volatile("cp.async.bulk.commit_group;" ::: "memory");
        }
        __syncwarp();
      }
      so = so == 49152 ? 0 : so + 24576;
    }
    if (lane == 0) asm volatile("cp.async.bulk.wait_group.read 0;" ::: "memory");
  } else if (warp >= 12) {
    nb_sync(7, 480);
#pragma unroll 1
    for (int n = blockIdx.x + (warp - 12) * step; n < NTB; n += 3 * step) {
      const int b = n / 56, rem = n - b * 56, par = rem / 14;
      const int c0 = opq((uint32_t)(par & 1)), c1 = opq((uint32_t)(8 * b)), c2 = opq((uint32_t)((par >> 1) * 112 + (rem - par * 14) * 8));
      int v; uint32_t spin = 0, tk = 0;
      do { asm volatile("ld.acquire.gpu.global.s32 %0, [%1];" : "=r"(v) : "l"(g_flags + n) : "memory"); } while (v < 4 && ++spin < SPIN_LIMIT);
      if (lane == 0) asm volatile("atom.shared.add.u32 %0, [%1], 1;" : "=r"(tk) : "r"(bar + 120) : "memory");
      asm volatile("fence.proxy.async.global;" ::: "memory");
      tk = __shfl_sync(0xffffffffu, tk, 0);
      TRB(tk, 0);
      const uint32_t use = tk / NSTB, sg = tk - use * NSTB;
      if (use) mbar_wait(bar + (NSTB + sg) * 8, (use - 1) & 1);
      TRB(tk, 1);
      if (elect_one()) {
        asm volatile("st.shared.u32 [%0], %1;" ::"r"(bar + 128 + tk * 4), "r"(c0 | c1 << 8 | c2 << 16) : "memory");
        mbar_expect(bar + sg * 8, 24576);
        asm volatile("cp.async.bulk.tensor.3d.shared::cluster.global.mbarrier::complete_tx::bytes [%0], [%1, {%3,%4,%5}], [%2];"
                     ::"r"(sb + SM_B_IN + sg * 24576), "l"(&mp.oi), "r"(bar + sg * 8), "r"(c0 * 192), "r"(c1), "r"(c2) : "memory");
        g_flags[n] = 0;
      }
      __syncwarp();
    }
  } else {
    const int wg = warp >> 2, w = warp & 3;
    uint32_t a[48];
    mbar_wait(bar + 2 * NSTB * 8, 0);
    {
      const int k = (lane & 7) + (lane >> 4) * 8, ch = (warp & 1) * 2 + ((lane >> 3) & 1);
      const uint32_t wa = sb + SM_B_W + (warp >> 1) * 12288 + k * 64 + ((ch ^ ((k >> 1) & 3)) * 16);
#pragma unroll
      for (int i = 0; i < 12; i++)
        asm volatile("ldmatrix.sync.aligned.m8n8.x4.trans.shared.b16 {%0,%1,%2,%3}, [%4];"
                     : "=r"(a[4 * i]), "=r"(a[4 * i + 1]), "=r"(a[4 * i + 2]), "=r"(a[4 * i + 3]) : "r"(wa + i * 1024) : "memory");
    }
    nb_sync(7, 480);
    TRB(47, 1);
    const uint32_t sta = opq(sb + SM_B_ST + wg * 8192 + ((lane & 7) + (lane >> 4) * 8) * 128 + (((2 * w + ((lane >> 3) & 1)) ^ (lane & 7)) * 16));
    const uint32_t hi = opq((uint32_t)(mkdesc(0, 0, 3072, 0) >> 32) + (blockIdx.x >> 16)), bb = opq(bar);
    const uint32_t nbT = opq((uint32_t)(4 + wg)), nbN = opq((uint32_t)(wg == 2 ? 4 : 5 + wg)), nbD = opq((uint32_t)(1 + wg));
    int left = (NTB - blockIdx.x + step - 1) / step;
    if (wg == 2) nb_arrive(4, 288);
#pragma unroll 1
    for (uint32_t ph = 0;; ph ^= 1) {
#pragma unroll
      for (int sg = 0; sg < NSTB; sg++) {
        constexpr uint64_t db = mkdesc(SBC + SM_B_IN, 128, 3072, 0);
        float D[32];
        mbar_wait(bb + sg * 8, ph);
        nb_sync(nbT, 288);
        wg_fence();
        wg_rs64<0>(D, a[0], a[1], a[2], a[3], dsc(db + sg * 1536, hi));
#pragma unroll
        for (int k = 1; k < 12; k++) wg_rs64<1>(D, a[4 * k], a[4 * k + 1], a[4 * k + 2], a[4 * k + 3], dsc(db + sg * 1536 + k * 16, hi));
        wg_commit();
        nb_arrive(nbN, 288);
        wg_wait<0>(); pin(D);
        mbar_arrive_elect(bb + (NSTB + sg) * 8);
#pragma unroll
        for (int q = 0; q < 4; q++)
          asm volatile("stmatrix.sync.aligned.m8n8.x4.trans.shared.b16 [%0], {%1,%2,%3,%4};" ::"r"(sta + (sg % 3) * 24576 + q * 2048),
                       "r"(pack2(D[8 * q], D[8 * q + 1])), "r"(pack2(D[8 * q + 2], D[8 * q + 3])), "r"(pack2(D[8 * q + 4], D[8 * q + 5])), "r"(pack2(D[8 * q + 6], D[8 * q + 7])) : "memory");
        fence_async();
        nb_arrive(nbD, 160);
        if (wg == 0) TRB(31 - left, 5);
        if (--left == 0) goto done;
      }
    }
  done:
    if (wg == 0) nb_arrive(4, 288);
    TR2(132 + blockIdx.x, 2);
  }
}

typedef CUresult (*EncodeFn)(CUtensorMap*, CUtensorMapDataType, cuuint32_t, void*, const cuuint64_t*, const cuuint64_t*, const cuuint32_t*,
                             const cuuint32_t*, CUtensorMapInterleave, CUtensorMapSwizzle, CUtensorMapL2promotion, CUtensorMapFloatOOBfill);
static EncodeFn g_enc = nullptr;
static void make_map(CUtensorMap* m, const void* p, int rank, const cuuint64_t* dim, const cuuint64_t* str, const cuuint32_t* box, CUtensorMapSwizzle sw) {
  const cuuint32_t ones[5] = {1, 1, 1, 1, 1};
  g_enc(m, CU_TENSOR_MAP_DATA_TYPE_BFLOAT16, rank, (void*)p, dim, str, box, ones, CU_TENSOR_MAP_INTERLEAVE_NONE, sw,
        CU_TENSOR_MAP_L2_PROMOTION_L2_128B, CU_TENSOR_MAP_FLOAT_OOB_FILL_NONE);
}

extern "C" void kernel_launch(void* const* d_in, const int* in_sizes, int n_in, void* d_out, int out_size) {
  const __nv_bfloat16* x = (const __nv_bfloat16*)d_in[0];
  const __nv_bfloat16* wqkv = (const __nv_bfloat16*)d_in[1];
  const __nv_bfloat16* wo = (const __nv_bfloat16*)d_in[2];
  const __nv_bfloat16* rpb = (const __nv_bfloat16*)d_in[3];

  if (!g_enc) {
    void* fn = nullptr; cudaDriverEntryPointQueryResult qr;
    cudaGetDriverEntryPoint("cuTensorMapEncodeTiled", &fn, cudaEnableDefault, &qr);
    g_enc = (EncodeFn)fn;
    cudaFuncSetAttribute(na_attn_kernel, cudaFuncAttributeMaxDynamicSharedMemorySize, SM_A_TOTAL);
    cudaFuncSetAttribute(na_proj_kernel, cudaFuncAttributeMaxDynamicSharedMemorySize, SM_B_TOTAL);
  }
  Maps ma; MapsB mb;
  { cuuint64_t dim[4] = {64, 112, 224, 6}, str[3] = {(cuuint64_t)ROWB, 768, 128};
    cuuint32_t box[4] = {64, 4, 16, 3}, boxh[4] = {64, 16, 3, 3}, boxo[4] = {64, 8, 8, 1};
    make_map(&ma.xc, x, 4, dim, str, box, CU_TENSOR_MAP_SWIZZLE_128B);
    make_map(&ma.xh, x, 4, dim, str, boxh, CU_TENSOR_MAP_SWIZZLE_128B);
    make_map(&mb.oo, d_out, 4, dim, str, boxo, CU_TENSOR_MAP_SWIZZLE_128B); }
  { cuuint64_t dim[3] = {384, 112, 224}, str[2] = {(cuuint64_t)ROWB, 768};
    cuuint32_t box[3] = {192, 8, 8}, boxs[3] = {192, 2, OCH};
    make_map(&mb.oi, d_out, 3, dim, str, box, CU_TENSOR_MAP_SWIZZLE_NONE);
    make_map(&ma.os, d_out, 3, dim, str, boxs, CU_TENSOR_MAP_SWIZZLE_NONE); }
  { cuuint64_t dim[4] = {32, 112, 224, 12}, str[3] = {(cuuint64_t)ROWB, 768, 64};
    cuuint32_t box[4] = {32, 8, 2, 3};
    make_map(&ma.ot, d_out, 4, dim, str, box, CU_TENSOR_MAP_SWIZZLE_64B); }
  { cuuint64_t dim[2] = {576, 192}, str[1] = {1152};
    cuuint32_t box[2] = {16, 192};
    make_map(&ma.w, wqkv, 2, dim, str, box, CU_TENSOR_MAP_SWIZZLE_32B); }
  { cuuint64_t dim[3] = {32, 192, 6}, str[2] = {384, 64};
    cuuint32_t box[3] = {32, 192, 3};
    make_map(&ma.wo, wo, 3, dim, str, box, CU_TENSOR_MAP_SWIZZLE_64B);
    mb.wo = ma.wo; }
  na_attn_kernel<<<112, 512, SM_A_TOTAL>>>(x, wqkv, rpb, ma);
  cudaLaunchConfig_t cfg = {};
  cfg.gridDim = dim3(20); cfg.blockDim = dim3(512); cfg.dynamicSmemBytes = SM_B_TOTAL; cfg.stream = cudaStreamPerThread;
  cudaLaunchAttribute at[1];
  at[0].id = cudaLaunchAttributeProgrammaticStreamSerialization; at[0].val.programmaticStreamSerializationAllowed = 1;
  cfg.attrs = at; cfg.numAttrs = 1;
  cudaLaunchKernelEx(&cfg, na_proj_kernel, mb);
}
```

```cpp
#include <cuda_runtime.h>
#include <cuda_bf16.h>
#include <cuda.h>
#include <stdint.h>

#define SPIN_LIMIT (1u << 18)

__device__ __forceinline__ uint32_t smem_u32(const void* p) { return (uint32_t)__cvta_generic_to_shared(p); }
__device__ __forceinline__ void wg_fence() { asm volatile("wgmma.fence.sync.aligned;" ::: "memory"); }
__device__ __forceinline__ void wg_commit() { asm volatile("wgmma.commit_group.sync.aligned;" ::: "memory"); }
template <int N> __device__ __forceinline__ void wg_wait() { asm volatile("wgmma.wait_group.sync.aligned %0;" ::"n"(N) : "memory"); }
template <int N> __device__ __forceinline__ void pin(float (&d)[N]) {
#pragma unroll
  for (int i = 0; i < N; i++) asm volatile("" : "+f"(d[i])::"memory");
}
__host__ __device__ constexpr uint64_t mkdesc(uint32_t addr, uint32_t lbo, uint32_t sbo, uint32_t sw) {
  return (uint64_t)((addr & 0x3FFFF) >> 4) | ((uint64_t)(lbo >> 4) << 16) | ((uint64_t)(sbo >> 4) << 32) | ((uint64_t)sw << 62);
}
__device__ __forceinline__ void mbar_init(uint32_t bar, uint32_t cnt) { asm volatile("mbarrier.init.shared::cta.b64 [%0], %1;" ::"r"(bar), "r"(cnt) : "memory"); }
__device__ __forceinline__ void mbar_arrive(uint32_t bar) { asm volatile("mbarrier.arrive.shared::cta.b64 _, [%0];" ::"r"(bar) : "memory"); }
__device__ __forceinline__ bool elect_one() {
  uint32_t r; asm volatile("{\n.reg .pred p;\nelect.sync _|p, 0xffffffff;\nselp.u32 %0, 1, 0, p;\n}" : "=r"(r)); return r;
}
__device__ __forceinline__ void mbar_arrive_elect(uint32_t bar) {
  asm volatile("{\n.reg .pred p;\nelect.sync _|p, 0xffffffff;\n@p mbarrier.arrive.shared::cta.b64 _, [%0];\n}" ::"r"(bar) : "memory");
}
__device__ __forceinline__ void mbar_expect(uint32_t bar, uint32_t bytes) { asm volatile("mbarrier.arrive.expect_tx.shared::cta.b64 _, [%0], %1;" ::"r"(bar), "r"(bytes) : "memory"); }
__device__ __forceinline__ void mbar_arrive_remote(uint32_t bar, uint32_t cta) {
  asm volatile("{\n.reg .b32 ra;\nmapa.shared::cluster.u32 ra, %0, %1;\nmbarrier.arrive.relaxed.cluster.shared::cluster.b64 _, [ra];\n}" ::"r"(bar), "r"(cta) : "memory");
}
__device__ __forceinline__ void mbar_wait(uint32_t bar, uint32_t parity) {
  asm volatile("{\n.reg .pred p;\n.reg .b32 n;\nmov.b32 n, 0;\nWL:\nmbarrier.try_wait.parity.shared::cta.b64 p, [%0], %1;\n@p bra WD;\n"
               "add.u32 n, n, 1;\nsetp.lt.u32 p, n, 65536;\n@p bra WL;\nWD:\n}" ::"r"(bar), "r"(parity) : "memory");
}
__device__ __forceinline__ void nb_sync(int id, int n) { asm volatile("bar.sync %0, %1;" ::"r"(id), "r"(n) : "memory"); }
__device__ __forceinline__ void nb_arrive(int id, int n) { asm volatile("bar.arrive %0, %1;" ::"r"(id), "r"(n) : "memory"); }
__device__ __forceinline__ uint32_t opq(uint32_t x) { uint32_t r; asm volatile("mov.b32 %0, %1;" : "=r"(r) : "r"(x)); return r; }
__device__ __forceinline__ uint64_t opq(uint64_t x) { uint64_t r; asm volatile("mov.b64 %0, %1;" : "=l"(r) : "l"(x)); return r; }
__device__ __forceinline__ uint32_t mapa(uint32_t a, uint32_t cta) { uint32_t r; asm("mapa.shared::cluster.u32 %0, %1, %2;" : "=r"(r) : "r"(a), "r"(cta)); return r; }
__device__ __forceinline__ void fence_async() { asm volatile("fence.proxy.async.shared::cta;" ::: "memory"); }
__device__ __forceinline__ void cluster_sync() {
  asm volatile("barrier.cluster.arrive.relaxed.aligned;\nbarrier.cluster.wait.aligned;" ::: "memory");
}
__device__ __forceinline__ uint32_t pack2(float lo, float hi) {
  uint32_t r; asm("cvt.rn.bf16x2.f32 %0, %1, %2;" : "=r"(r) : "f"(hi), "f"(lo)); return r;
}
__device__ __forceinline__ void stsm4(uint32_t a, uint32_t r0, uint32_t r1, uint32_t r2, uint32_t r3) {
  asm volatile("stmatrix.sync.aligned.m8n8.x4.shared.b16 [%0], {%1,%2,%3,%4};" ::"r"(a), "r"(r0), "r"(r1), "r"(r2), "r"(r3) : "memory");
}
__device__ __forceinline__ void ldsm4(uint32_t a, uint32_t& r0, uint32_t& r1, uint32_t& r2, uint32_t& r3) {
  asm volatile("ldmatrix.sync.aligned.m8n8.x4.shared.b16 {%0,%1,%2,%3}, [%4];" : "=r"(r0), "=r"(r1), "=r"(r2), "=r"(r3) : "r"(a) : "memory");
}
__device__ __forceinline__ void sts128(uint32_t a, uint4 v) {
  asm volatile("st.shared.v4.b32 [%0], {%1,%2,%3,%4};" ::"r"(a), "r"(v.x), "r"(v.y), "r"(v.z), "r"(v.w) : "memory");
}
__device__ __forceinline__ float lds_f32(uint32_t a) { float v; asm volatile("ld.shared.f32 %0, [%1];" : "=f"(v) : "r"(a)); return v; }
__device__ __forceinline__ float ex2(float x) { float y; asm("ex2.approx.ftz.f32 %0, %1;" : "=f"(y) : "f"(x)); return y; }

template<int SC> __device__ __forceinline__ void wg_ss144(float (&d)[72], uint64_t da, uint64_t db) {
  asm volatile("{\n.reg .pred p;\nsetp.ne.b32 p, %74, 0;\nwgmma.mma_async.sync.aligned.m64n144k16.f32.bf16.bf16 {%0,%1,%2,%3,%4,%5,%6,%7,%8,%9,%10,%11,%12,%13,%14,%15,%16,%17,%18,%19,%20,%21,%22,%23,%24,%25,%26,%27,%28,%29,%30,%31,%32,%33,%34,%35,%36,%37,%38,%39,%40,%41,%42,%43,%44,%45,%46,%47,%48,%49,%50,%51,%52,%53,%54,%55,%56,%57,%58,%59,%60,%61,%62,%63,%64,%65,%66,%67,%68,%69,%70,%71}, %72, %73, p, 1, 1, 0, 1;\n}\n"
    : "+f"(d[0]),"+f"(d[1]),"+f"(d[2]),"+f"(d[3]),"+f"(d[4]),"+f"(d[5]),"+f"(d[6]),"+f"(d[7]),"+f"(d[8]),"+f"(d[9]),"+f"(d[10]),"+f"(d[11]),"+f"(d[12]),"+f"(d[13]),"+f"(d[14]),"+f"(d[15]),"+f"(d[16]),"+f"(d[17]),"+f"(d[18]),"+f"(d[19]),"+f"(d[20]),"+f"(d[21]),"+f"(d[22]),"+f"(d[23]),"+f"(d[24]),"+f"(d[25]),"+f"(d[26]),"+f"(d[27]),"+f"(d[28]),"+f"(d[29]),"+f"(d[30]),"+f"(d[31]),"+f"(d[32]),"+f"(d[33]),"+f"(d[34]),"+f"(d[35]),"+f"(d[36]),"+f"(d[37]),"+f"(d[38]),"+f"(d[39]),"+f"(d[40]),"+f"(d[41]),"+f"(d[42]),"+f"(d[43]),"+f"(d[44]),"+f"(d[45]),"+f"(d[46]),"+f"(d[47]),"+f"(d[48]),"+f"(d[49]),"+f"(d[50]),"+f"(d[51]),"+f"(d[52]),"+f"(d[53]),"+f"(d[54]),"+f"(d[55]),"+f"(d[56]),"+f"(d[57]),"+f"(d[58]),"+f"(d[59]),"+f"(d[60]),"+f"(d[61]),"+f"(d[62]),"+f"(d[63]),"+f"(d[64]),"+f"(d[65]),"+f"(d[66]),"+f"(d[67]),"+f"(d[68]),"+f"(d[69]),"+f"(d[70]),"+f"(d[71]) : "l"(da), "l"(db), "n"(SC));
}
template<int SC> __device__ __forceinline__ void wg_ss96(float (&d)[48], uint64_t da, uint64_t db) {
  asm volatile("{\n.reg .pred p;\nsetp.ne.b32 p, %50, 0;\nwgmma.mma_async.sync.aligned.m64n96k16.f32.bf16.bf16 {%0,%1,%2,%3,%4,%5,%6,%7,%8,%9,%10,%11,%12,%13,%14,%15,%16,%17,%18,%19,%20,%21,%22,%23,%24,%25,%26,%27,%28,%29,%30,%31,%32,%33,%34,%35,%36,%37,%38,%39,%40,%41,%42,%43,%44,%45,%46,%47}, %48, %49, p, 1, 1, 0, 1;\n}\n"
    : "+f"(d[0]),"+f"(d[1]),"+f"(d[2]),"+f"(d[3]),"+f"(d[4]),"+f"(d[5]),"+f"(d[6]),"+f"(d[7]),"+f"(d[8]),"+f"(d[9]),"+f"(d[10]),"+f"(d[11]),"+f"(d[12]),"+f"(d[13]),"+f"(d[14]),"+f"(d[15]),"+f"(d[16]),"+f"(d[17]),"+f"(d[18]),"+f"(d[19]),"+f"(d[20]),"+f"(d[21]),"+f"(d[22]),"+f"(d[23]),"+f"(d[24]),"+f"(d[25]),"+f"(d[26]),"+f"(d[27]),"+f"(d[28]),"+f"(d[29]),"+f"(d[30]),"+f"(d[31]),"+f"(d[32]),"+f"(d[33]),"+f"(d[34]),"+f"(d[35]),"+f"(d[36]),"+f"(d[37]),"+f"(d[38]),"+f"(d[39]),"+f"(d[40]),"+f"(d[41]),"+f"(d[42]),"+f"(d[43]),"+f"(d[44]),"+f"(d[45]),"+f"(d[46]),"+f"(d[47]) : "l"(da), "l"(db), "n"(SC));
}
template<int SC> __device__ __forceinline__ void wg_rs112(float (&d)[56], uint32_t a0, uint32_t a1, uint32_t a2, uint32_t a3, uint64_t db) {
  asm volatile("{\n.reg .pred p;\nsetp.ne.b32 p, %61, 0;\nwgmma.mma_async.sync.aligned.m64n112k16.f32.bf16.bf16 {%0,%1,%2,%3,%4,%5,%6,%7,%8,%9,%10,%11,%12,%13,%14,%15,%16,%17,%18,%19,%20,%21,%22,%23,%24,%25,%26,%27,%28,%29,%30,%31,%32,%33,%34,%35,%36,%37,%38,%39,%40,%41,%42,%43,%44,%45,%46,%47,%48,%49,%50,%51,%52,%53,%54,%55}, {%56,%57,%58,%59}, %60, p, 1, 1, 0;\n}\n"
    : "+f"(d[0]),"+f"(d[1]),"+f"(d[2]),"+f"(d[3]),"+f"(d[4]),"+f"(d[5]),"+f"(d[6]),"+f"(d[7]),"+f"(d[8]),"+f"(d[9]),"+f"(d[10]),"+f"(d[11]),"+f"(d[12]),"+f"(d[13]),"+f"(d[14]),"+f"(d[15]),"+f"(d[16]),"+f"(d[17]),"+f"(d[18]),"+f"(d[19]),"+f"(d[20]),"+f"(d[21]),"+f"(d[22]),"+f"(d[23]),"+f"(d[24]),"+f"(d[25]),"+f"(d[26]),"+f"(d[27]),"+f"(d[28]),"+f"(d[29]),"+f"(d[30]),"+f"(d[31]),"+f"(d[32]),"+f"(d[33]),"+f"(d[34]),"+f"(d[35]),"+f"(d[36]),"+f"(d[37]),"+f"(d[38]),"+f"(d[39]),"+f"(d[40]),"+f"(d[41]),"+f"(d[42]),"+f"(d[43]),"+f"(d[44]),"+f"(d[45]),"+f"(d[46]),"+f"(d[47]),"+f"(d[48]),"+f"(d[49]),"+f"(d[50]),"+f"(d[51]),"+f"(d[52]),"+f"(d[53]),"+f"(d[54]),"+f"(d[55]) : "r"(a0), "r"(a1), "r"(a2), "r"(a3), "l"(db), "n"(SC));
}
template<int SC> __device__ __forceinline__ void wg_sp48(float (&d)[24], uint32_t a0, uint32_t a1, uint32_t a2, uint32_t a3, uint64_t db, uint32_t meta) {
  asm volatile("{\n.reg .pred p;\nsetp.ne.b32 p, %30, 0;\nwgmma.mma_async.sp.sync.aligned.m64n48k32.f32.bf16.bf16 {%0,%1,%2,%3,%4,%5,%6,%7,%8,%9,%10,%11,%12,%13,%14,%15,%16,%17,%18,%19,%20,%21,%22,%23}, {%24,%25,%26,%27}, %28, %29, 0, p, 1, 1, 1;\n}\n"
    : "+f"(d[0]),"+f"(d[1]),"+f"(d[2]),"+f"(d[3]),"+f"(d[4]),"+f"(d[5]),"+f"(d[6]),"+f"(d[7]),"+f"(d[8]),"+f"(d[9]),"+f"(d[10]),"+f"(d[11]),"+f"(d[12]),"+f"(d[13]),"+f"(d[14]),"+f"(d[15]),"+f"(d[16]),"+f"(d[17]),"+f"(d[18]),"+f"(d[19]),"+f"(d[20]),"+f"(d[21]),"+f"(d[22]),"+f"(d[23]) : "r"(a0), "r"(a1), "r"(a2), "r"(a3), "l"(db), "r"(meta), "n"(SC));
}
template<int SC> __device__ __forceinline__ void wg_rs64(float (&d)[32], uint32_t a0, uint32_t a1, uint32_t a2, uint32_t a3, uint64_t db) {
  asm volatile("{\n.reg .pred p;\nsetp.ne.b32 p, %37, 0;\nwgmma.mma_async.sync.aligned.m64n64k16.f32.bf16.bf16 {%0,%1,%2,%3,%4,%5,%6,%7,%8,%9,%10,%11,%12,%13,%14,%15,%16,%17,%18,%19,%20,%21,%22,%23,%24,%25,%26,%27,%28,%29,%30,%31}, {%32,%33,%34,%35}, %36, p, 1, 1, 0;\n}\n"
    : "+f"(d[0]),"+f"(d[1]),"+f"(d[2]),"+f"(d[3]),"+f"(d[4]),"+f"(d[5]),"+f"(d[6]),"+f"(d[7]),"+f"(d[8]),"+f"(d[9]),"+f"(d[10]),"+f"(d[11]),"+f"(d[12]),"+f"(d[13]),"+f"(d[14]),"+f"(d[15]),"+f"(d[16]),"+f"(d[17]),"+f"(d[18]),"+f"(d[19]),"+f"(d[20]),"+f"(d[21]),"+f"(d[22]),"+f"(d[23]),"+f"(d[24]),"+f"(d[25]),"+f"(d[26]),"+f"(d[27]),"+f"(d[28]),"+f"(d[29]),"+f"(d[30]),"+f"(d[31]) : "r"(a0), "r"(a1), "r"(a2), "r"(a3), "l"(db), "n"(SC));
}

constexpr uint32_t SBC = 1024;
constexpr int ROWB = 2 * 224 * 384;
constexpr int TB = 11;
constexpr int KS = 832;
constexpr int KSLOT = 22 * KS;
constexpr int SM_X2 = 0;
constexpr int SM_X0 = SM_X2 + 24576;
constexpr int SM_W = SM_X0 + 18432;
constexpr int SM_X1 = SM_W + 55296;
constexpr int SM_K = SM_X1 + 24576;
constexpr int SM_V = SM_K + 2 * KSLOT;
constexpr int SM_Q = SM_V + 22 * 1536;
constexpr int SM_O = SM_Q + 24576;
constexpr int SM_RPB = SM_O + 12288;
constexpr int SM_BAR = SM_RPB + 768;
constexpr int SM_A_TOTAL = SM_BAR + 256;
constexpr int SM_TIN = 0;
constexpr int SM_TST = 3 * 24576;
constexpr int SM_TWO = SM_TST + 12288;
enum { B_FULL = 0, B_EMPTY = 3, B_TIN = 6, B_TFREE = 10, B_WK = 12, B_WQ, B_WO, B_KIMP, B_VIMP, B_OFREE, B_XK, B_XV,
       B_Q0, B_WOFREE, B_OTAIL, B_ODONE = B_OTAIL + 2, B_KFREE, B_VFREE, B_COUNT };
enum { N_KRDY = 4, N_QK0, N_QK1, N_VQ0, N_VQ1, N_PVISS };

#define NL 2
#define OPT 0
#define OCH 4
#define MID 6
#define SPL 4
#define RA 160
#define RG 168
__device__ int g_flags[TB * 56];

#define TR(role, it, k)
#define TRDECL
#define TRARG
#define TRPASS
#define TRDUMP
#define TRB(it, k)
#define TR2(blk, k)

struct GemmCtx {
  uint32_t bar;
  uint32_t kC, vC[2], qC[2];
  uint32_t kH, vH[2];
  uint32_t hiA, hiB;
  uint32_t spin;
  uint32_t em[3];
  bool hvalid, never, edge;
};

template <int STRIDE> __device__ __forceinline__ void dump12(uint32_t a, const uint32_t (&r)[12]) {
#pragma unroll
  for (int j = 0; j < 3; j++) stsm4(a + j * 2 * STRIDE, r[4 * j], r[4 * j + 1], r[4 * j + 2], r[4 * j + 3]);
}
__device__ __forceinline__ void keep12(bool never, uint32_t a, const uint32_t (&r)[12]) { if (never) dump12<128>(a, r); }
template <int N> __device__ __forceinline__ void pack12(uint32_t (&r)[12], const float (&d)[N], int off) {
#pragma unroll
  for (int j = 0; j < 12; j++) r[j] = pack2(d[off + 2 * j], d[off + 2 * j + 1]);
}
__device__ __forceinline__ uint64_t dsc(uint64_t lo, uint32_t hi) { uint64_t r; asm("mov.b64 %0, {%1, %2};" : "=l"(r) : "r"((uint32_t)lo), "r"(hi)); return r; }
template <int XS, int K0, int K1> __device__ __forceinline__ void issue_core(const GemmCtx& c, float (&d)[72]) {
  constexpr uint64_t da = mkdesc(SBC + XS, 16, 1024, 1), db = mkdesc(SBC + SM_W, 6144, 256, 3);
  wg_fence();
  if (K0 == 0) wg_ss144<0>(d, dsc(da, c.hiA), dsc(db, c.hiB));
#pragma unroll
  for (int k = K0 ? K0 : 1; k < K1; k++) wg_ss144<1>(d, dsc(da + (k >> 2) * 512 + (k & 3) * 2, c.hiA), dsc(db + k * 32, c.hiB));
  wg_commit();
}
template <int K0, int K1> __device__ __forceinline__ void issue_halo(const GemmCtx& c, float (&d)[48]) {
  constexpr uint64_t da = mkdesc(SBC + SM_X0 - 2048, 16, 1024, 1), db = mkdesc(SBC + SM_W, 6144, 256, 3);
  wg_fence();
  if (K0 == 0) wg_ss96<0>(d, dsc(da, c.hiA), dsc(db, c.hiB));
#pragma unroll
  for (int k = K0 ? K0 : 1; k < K1; k++) wg_ss96<1>(d, dsc(da + (k >> 2) * 384 + (k & 3) * 2, c.hiA), dsc(db + k * 32, c.hiB));
  wg_commit();
}
template <int ST> __device__ __forceinline__ void release_stage(const GemmCtx& c) {
  asm volatile("{\n.reg .pred p;\nelect.sync _|p, 0xffffffff;\n@p mbarrier.arrive.shared::cluster.b64 _, [%0];\n}" ::"r"(c.em[ST]) : "memory");
}
__device__ __forceinline__ void edge_ready(const GemmCtx& c, int bar) { __syncwarp(); if (c.edge) mbar_arrive_elect(c.bar + bar * 8); }
__device__ __forceinline__ void dump6(uint32_t a, const uint32_t (&r)[6]) {
  stsm4(a, r[0], r[1], r[2], r[3]);
  asm volatile("stmatrix.sync.aligned.m8n8.x2.shared.b16 [%0], {%1,%2};" ::"r"(a + 512), "r"(r[4]), "r"(r[5]) : "memory");
}
__device__ __forceinline__ void pack6(uint32_t (&r)[6], const float (&d)[48], int off) {
#pragma unroll
  for (int j = 0; j < 6; j++) r[j] = pack2(d[off + 4 * j], d[off + 4 * j + 1]);
}
template <int PARITY> __device__ __forceinline__ void gwait(GemmCtx& c, int bar) {
  asm volatile("{\n.reg .pred p;\nWL:\nmbarrier.try_wait.parity.shared::cta.b64 p, [%1], %2;\n@p bra WD;\n"
               "add.u32 %0, %0, 1;\nsetp.lt.u32 p, %0, 0x100000;\n@p bra WL;\nWD:\n}" : "+r"(c.spin) : "r"(c.bar + bar * 8), "n"(PARITY) : "memory");
}
__device__ __forceinline__ void load_w(const CUtensorMap* m, uint32_t dst, uint32_t bar, int col) {
  asm volatile("cp.async.bulk.tensor.2d.shared::cluster.global.mbarrier::complete_tx::bytes [%0], [%1, {%3,%4}], [%2];"
               ::"r"(dst), "l"(m), "r"(bar), "r"(col), "r"(0) : "memory");
}
template <int BYTES> __device__ __forceinline__ void send_o(uint32_t dst, uint32_t src, uint32_t bar, int cta) {
  asm volatile("{\n.reg .b32 rd, rb;\nmapa.shared::cluster.u32 rd, %0, %3;\nmapa.shared::cluster.u32 rb, %2, %3;\n"
               "cp.async.bulk.shared::cluster.shared::cta.mbarrier::complete_tx::bytes [rd], [%1], %4, [rb];\n}"
               ::"r"(dst), "r"(src), "r"(bar), "r"(cta), "n"(BYTES) : "memory");
}
__device__ __forceinline__ void remote_arrive(uint32_t rbar) { asm volatile("mbarrier.arrive.shared::cluster.b64 _, [%0];" ::"r"(rbar) : "memory"); }
__device__ __forceinline__ void remote_expect(uint32_t rbar, uint32_t bytes) {
  asm volatile("mbarrier.arrive.expect_tx.shared::cluster.b64 _, [%0], %1;" ::"r"(rbar), "r"(bytes) : "memory");
}
__device__ __forceinline__ void copy_remote(uint32_t rdst, uint32_t src, uint32_t bytes, uint32_t rbar) {
  asm volatile("cp.async.bulk.shared::cluster.shared::cta.mbarrier::complete_tx::bytes [%0], [%1], %2, [%3];" ::"r"(rdst), "r"(src), "r"(bytes), "r"(rbar) : "memory");
}
__device__ __forceinline__ void tail_free(uint32_t bar) {
  uint32_t ln; asm volatile("mov.u32 %0, %%laneid;" : "=r"(ln));
  if (ln < 4) mbar_arrive_remote(bar, ln + (blockIdx.x & 4));
}
__device__ __forceinline__ void publish(uint32_t bar) {
  fence_async();
  __syncwarp();
  mbar_arrive_elect(bar);
}

template <bool FIRST, int PA>
__device__ __forceinline__ void gemm_iter(GemmCtx& c, int b, uint32_t (&pk)[12], uint32_t (&pv)[12], uint32_t (&pq)[12],
                                          uint32_t (&hk1)[6], uint32_t (&hv1)[6] TRARG) {
  const uint32_t bar = c.bar;
  const bool w = !FIRST && (PA == 0 || b >= 0), never = c.never;
  constexpr uint32_t ko = PA * KSLOT;
  float C[72];
  uint32_t hk0[6], hv0[6], pv2[12];
  TR(2, b, 0);
  if (FIRST) gwait<0>(c, B_FULL + 0);
  else dump12<256>(c.qC[1] + (PA ^ 1) * 128, pq);
  if (w) nb_sync(N_QK1, 256);
  TR(2, b, 2);
  if (PA == 0) {
    float H[48];
    issue_halo<0, 8>(c, H);
    TR(2, b, 3);
    if (!FIRST) { gwait<0>(c, B_KFREE); dump12<128>(c.kC, pk); }
    issue_halo<8, 12>(c, H);
    TR(2, b, 4);
    gwait<0>(c, B_FULL + 2);
    if (FIRST) gwait<0>(c, B_WQ);
    issue_core<SM_X2, 0, 8>(c, C);
    TR(2, b, 5);
    if (!FIRST) { fence_async(); keep12(never, c.kC, pk); }
    wg_wait<1>(); pin(H);
    release_stage<0>(c);
    pack6(hk0, H, 0);
    if (c.hvalid) dump6(c.kH, hk0);
    pack6(hk1, H, 2); pack6(hv0, H, 24); pack6(hv1, H, 26);
  } else {
    issue_core<SM_X2, 0, 8>(c, C);
    TR(2, b, 5);
    fence_async();
    keep12(never, c.kC, pq);
    if (w) gwait<1>(c, B_KFREE);
    dump12<128>(c.kC + ko, pk);
    if (c.hvalid) dump6(c.kH + ko, hk1);
  }
  TR(2, b, 13);
  issue_core<SM_X2, 8, 12>(c, C);
  if (w) { nb_arrive(N_VQ0, 288); nb_arrive(N_VQ1, 288); }
  else if (!FIRST) { __syncwarp(); mbar_arrive_elect(bar + B_Q0 * 8); }
  gwait<PA>(c, B_FULL + 1);
  if (never) dump6(bar, PA ? hk1 : hk0);
  TR(2, b, 6);
  wg_wait<0>(); pin(C);
  TR(2, b, 7);
  release_stage<2>(c);
  pack12(pk, C, 0);
  dump12<128>(c.kC + ko + 64, pk);
  pack12(pv2, C, 24);
  pack12(pq, C, 48);
  TR(2, b, 8);
  issue_core<SM_X1, 0, SPL>(c, C);
  if (w) nb_sync(N_PVISS, 384);
  issue_core<SM_X1, SPL, 8>(c, C);
  TR(2, b, 9);
  if (!FIRST) { fence_async(); edge_ready(c, B_XK); }
  keep12(never, c.kC, pk);
  TR(2, b, 14);
  issue_core<SM_X1, 8, 12>(c, C);
  if (!FIRST) nb_arrive(N_KRDY, 256);
  TR(2, b, 1);
  if (PA) { if (b == 11) tail_free(bar + B_TFREE * 8); mbar_wait(bar + B_FULL * 8, ((b + 3) >> 1) & 1); }
  if (w) gwait<PA>(c, B_VFREE);
  if ((OPT & 8) && w && b < TB) gwait<PA>(c, B_ODONE);
  TR(2, b, 10);
  if (!FIRST) dump12<128>(c.vC[PA], pv);
  dump12<128>(c.vC[PA ^ 1] + 768, pv2);
  TR(2, b, 11);
  wg_wait<0>(); pin(C);
  TR(2, b, 12);
  release_stage<1>(c);
  if (!FIRST && c.edge) publish(bar + B_XV * 8);
  if (PA == 0) gwait<1>(c, B_FULL + 2);
  if (c.hvalid) dump6(c.vH[PA], PA ? hv1 : hv0);
  dump12<256>(c.qC[0] + PA * 128, pq);
  pack12(pk, C, 0);
  pack12(pv, C, 24);
  pack12(pq, C, 48);
}

template <int IN> __device__ __forceinline__ void issue_proj(float (&D)[48]) {
  constexpr uint64_t da = mkdesc(SBC + IN, 128, 768, 0), db = mkdesc(SBC + SM_TWO, 12288, 512, 2);
  wg_fence();
  wg_ss96<0>(D, da, db);
#pragma unroll
  for (int k = 1; k < 12; k++) wg_ss96<1>(D, da + (k / 3) * 384 + (k % 3) * 16, db + k * 64);
  wg_commit();
}
template <int ACC> __device__ __forceinline__ void issue_proj_half(float (&D)[48], int hd) {
  const uint64_t da = mkdesc(SBC + SM_TIN + 2 * 24576, 128, 768, 0) + hd * 384, db = mkdesc(SBC + SM_TWO, 12288, 512, 2) + hd * 192;
  wg_fence();
  wg_ss96<ACC>(D, da, db);
#pragma unroll
  for (int k = 1; k < 6; k++) wg_ss96<1>(D, da + (k / 3) * 768 + (k % 3) * 16, db + (k / 3) * 384 + (k % 3) * 64);
  wg_commit();
}
__device__ __forceinline__ void store_proj(const float (&D)[48], const CUtensorMap* m, uint32_t st, uint32_t sta, int row, int col, int ch) {
#pragma unroll
  for (int q = 0; q < 6; q++)
    stsm4((sta ^ ((q & 1) * 32)) + (q >> 1) * 1024,
          pack2(D[8 * q], D[8 * q + 1]), pack2(D[8 * q + 2], D[8 * q + 3]), pack2(D[8 * q + 4], D[8 * q + 5]), pack2(D[8 * q + 6], D[8 * q + 7]));
  fence_async();
  __syncwarp();
  if ((threadIdx.x & 31) == 0) {
    asm volatile("cp.async.bulk.tensor.4d.global.shared::cta.bulk_group [%0, {%2,%3,%4,%5}], [%1];" ::"l"(m), "r"(st), "r"(0), "r"(row), "r"(col), "r"(ch) : "memory");
    asm volatile("cp.async.bulk.commit_group;" ::: "memory");
  }
  __syncwarp();
}

__device__ __forceinline__ float fold(float a, float b, float t, int useb) {
  float r;
  asm("{\n.reg .pred p;\nsetp.ne.b32 p, %4, 0;\nfma.rn.f32 %0, %1, 0f3E553B95, %3;\n@p fma.rn.f32 %0, %2, 0f3E553B95, %3;\n}"
      : "=&f"(r) : "f"(a), "f"(b), "f"(t), "r"(useb));
  return r;
}
template <int U, int L>
__device__ __forceinline__ void softmax_tile(const float (&SA)[56], const float (&SB)[56], const float (&T)[16], int b0, int b1,
                                             uint32_t (&P)[28], float (&sx)[8], uint32_t nbV, uint32_t zero, uint32_t qa, uint32_t (&q)[12]) {
  float lu[14], ll[14];
#pragma unroll
  for (int j = 0; j < 7; j++) {
    constexpr int sh = U == L ? 2 : 0;
    const float tu0 = T[2 * j + sh], tu1 = T[2 * j + 1 + sh], tl0 = T[2 * j], tl1 = T[2 * j + 1];
    lu[2 * j]     = fold(SA[4 * (U + j)],     SB[4 * (U + j)],     tu0, b0);
    ll[2 * j]     = fold(SA[4 * (L + j) + 2], SB[4 * (L + j) + 2], tl0, b0);
    lu[2 * j + 1] = fold(SA[4 * (U + j) + 1], SB[4 * (U + j) + 1], tu1, b1);
    ll[2 * j + 1] = fold(SA[4 * (L + j) + 3], SB[4 * (L + j) + 3], tl1, b1);
  }
  float mu = lu[0], ml = ll[0], mu2 = lu[1], ml2 = ll[1];
#pragma unroll
  for (int j = 1; j < 7; j++) { mu = fmaxf(mu, lu[2 * j]); mu2 = fmaxf(mu2, lu[2 * j + 1]); ml = fmaxf(ml, ll[2 * j]); ml2 = fmaxf(ml2, ll[2 * j + 1]); }
  mu = fmaxf(mu, mu2); ml = fmaxf(ml, ml2);
  { const float a1 = __shfl_xor_sync(0xffffffffu, mu, 1), a2 = __shfl_xor_sync(0xffffffffu, mu, 2), a3 = __shfl_xor_sync(0xffffffffu, mu, 3);
    const float c1 = __shfl_xor_sync(0xffffffffu, ml, 1), c2 = __shfl_xor_sync(0xffffffffu, ml, 2), c3 = __shfl_xor_sync(0xffffffffu, ml, 3);
    mu = fmaxf(fmaxf(mu, a1), fmaxf(a2, a3)); ml = fmaxf(fmaxf(ml, c1), fmaxf(c2, c3)); }
  float su = 0.f, sl = 0.f;
#pragma unroll
  for (int c = 0; c < 14; c++) {
    if (c >= U && c < U + 7) {
      float e0 = ex2(lu[2 * (c - U)] - mu), e1 = ex2(lu[2 * (c - U) + 1] - mu);
      su = c == U ? e0 + e1 : (su + e0) + e1; P[2 * c] = pack2(e0, e1);
    } else P[2 * c] = 0u;
  }
#pragma unroll
  for (int c = 0; c < 14; c++) {
    if (c >= L && c < L + 7) {
      float e0 = ex2(ll[2 * (c - L)] - ml), e1 = ex2(ll[2 * (c - L) + 1] - ml);
      sl = c == L ? e0 + e1 : (sl + e0) + e1; P[2 * c + 1] = pack2(e0, e1);
    } else P[2 * c + 1] = 0u;
  }
  sx[0] = su; sx[4] = sl;
#pragma unroll
  for (int k = 1; k < 4; k++) sx[k] = __shfl_xor_sync(0xffffffffu, su, k);
#pragma unroll
  for (int k = 1; k < 4; k++) sx[4 + k] = __shfl_xor_sync(0xffffffffu, sl, k);
}

struct BandCfg { uint32_t ra0, ra1, meta; int b0, b1; };
__device__ __forceinline__ void band_cfg(int b, uint32_t tb, BandCfg& n) {
  uint32_t ln; asm volatile("mov.u32 %0, %%laneid;" : "=r"(ln));
  const int g = ln >> 2, t = ln & 3;
  const int sw = min(max(g + 1, b == 0 ? 4 : 0), b == 13 ? 5 : 8);
  const int i0 = 2 * t, i1 = 2 * t + 1;
  n.b0 = i0 <= sw - 2; n.b1 = i1 <= sw - 2;
  n.ra0 = tb + (i0 == sw - 1 ? 13 : i0 + 8 * n.b0 - g + 2) * 52;
  n.ra1 = tb + (i1 == sw - 1 ? 13 : i1 + 8 * n.b1 - g + 2) * 52;
  n.meta = ((0x5555u & ((1u << (2 * (sw - 1))) - 1)) ^ 0xDD88u ^ (((t ^ b) & 1) ? 0x5555u : 0u)) * 0x10001u;
}
__device__ __forceinline__ void band_load(const BandCfg& n, float (&T)[16], int& b0, int& b1, uint32_t& meta) {
#pragma unroll
  for (int jj = 0; jj < 8; jj++) { T[2 * jj] = lds_f32(n.ra0 + jj * 4); T[2 * jj + 1] = lds_f32(n.ra1 + jj * 4); }
  b0 = n.b0; b1 = n.b1; meta = n.meta;
}

struct Maps { CUtensorMap xc, xh, w, os, wo, ot; };

__global__ void __cluster_dims__(8, 1, 1) __launch_bounds__(512, 1)
na_attn_kernel(const __nv_bfloat16* __restrict__ x, const __nv_bfloat16* __restrict__ wqkv, const __nv_bfloat16* __restrict__ rpb, const __grid_constant__ Maps mp) {
  extern __shared__ __align__(1024) uint8_t smem_raw[];
  const uint32_t sb = smem_u32(smem_raw);
  if ((sb & 0x3FFFF) != SBC) return;
  const uint32_t bar = sb + SM_BAR;
  TR2(blockIdx.x, 0);
  const int tid = threadIdx.x, lane = tid & 31;
  const int warp = __shfl_sync(0xffffffffu, tid >> 5, 0);
  const int head = blockIdx.x & 3, base = blockIdx.x & 4, sp = blockIdx.x >> 2;
  const int par = sp < 24 ? sp / 6 : sp - 24, strip = sp < 24 ? sp - par * 6 : 6, ph = par >> 1, pw = par & 1;
  const int odd = strip & 1;

  uint4 wv[2 * NL];
  const int va = head == 1;
  const uint32_t wdst = sb + SM_W + (va + ((tid >> 1) & 1)) * 6144 + (tid >> 2) * 32 + ((tid ^ (tid >> 4)) & 1) * 16;
  if (warp < 12) asm volatile("barrier.cluster.arrive.relaxed.aligned;" ::: "memory");
  {
    const uint32_t wo0 = (tid >> 2) * 1152 + head * 96 + va * 32 + (tid & 3) * 16;
#pragma unroll
    for (int i = 0; i < 2 * NL; i++)
      asm volatile("{\n.reg .pred p;\nsetp.lt.u32 p, %5, 384;\n@p ld.global.nc.v4.b32 {%0,%1,%2,%3}, [%4];\n}"
                   : "=r"(wv[i].x), "=r"(wv[i].y), "=r"(wv[i].z), "=r"(wv[i].w)
                   : "l"(reinterpret_cast<const uint8_t*>(wqkv) + wo0 + (i & 1) * 96 * 1152 + ((i / 2 + 1) % 3) * 384), "r"(tid));
  }
  if (warp < 8) {
    asm volatile("setmaxnreg.inc.sync.aligned.u32 %0;" ::"n"(RA));
    float rv = -INFINITY;
    if (tid < 169) rv = __bfloat162float(rpb[head * 169 + tid]) * 1.4426950408889634f;
    if (tid < 192) {
      const int kc = (tid & 15) + 3, wc = (tid >> 4) % 6;
      sts128(tid < 96 ? sb + SM_K + kc * KS + wc * 128 + 48 : sb + SM_V + kc * 1536 + wc * 128 + (6 + (kc & 1)) * 16, make_uint4(0, 0, 0, 0));
    }
#pragma unroll
    for (int i = 0; i < 2 * NL; i++) sts128(wdst + (i & 1) * 3072 + (i / 2) * 18432, wv[i]);
    fence_async();
    asm volatile("bar.arrive 1, 384;" ::: "memory");
    if (tid < 182) asm volatile("st.shared.f32 [%0], %1;" ::"r"(sb + SM_RPB + tid * 4), "f"(rv) : "memory");
    const int jw = warp >> 2, j = jw ^ odd, w = warp & 3, wt = 4 * j + w;
    int variant = w;
    if (strip == 0 && j == 0 && w < 2) variant = 4;
    if (strip == 6 && j == 1 && w >= 2) variant = 5;
    const bool v1 = opq((uint32_t)(variant & 1)), v2 = opq((uint32_t)(variant & 2)), v4 = opq((uint32_t)(variant & 4));
    uint32_t qa = opq(sb + SM_Q + (8 * j + 2 * w + ((lane >> 3) & 1)) * 1536 + (lane >> 4) * 256 + (((lane & 7) * 16) ^ (((lane >> 3) & 1) * 64)));
    uint32_t oa = opq(sb + SM_O + j * 6144 + (2 * w + ((lane >> 3) & 1)) * 768 + (lane >> 4) * 128 + (lane & 7) * 16);
    uint64_t dA = opq(mkdesc(SBC + SM_K, 128, KS, 0) + j * (8 * KS / 16)), dB = opq(dA + (KSLOT >> 4));
    uint64_t dV[7];
#pragma unroll
    for (int i = 0; i < 7; i++) dV[i] = opq(mkdesc(SBC + SM_V, 768, 128, 0) + j * (8 * 1536 / 16) + i * 192);
    const uint32_t nbK = opq((uint32_t)(N_KRDY + jw)), nbQ = opq((uint32_t)(N_QK0 + jw)), nbV = opq((uint32_t)(N_VQ0 + jw));
    asm volatile("barrier.cluster.wait.aligned;" ::: "memory");
    asm volatile("bar.sync 3, 256;" ::: "memory");
    float T[16];
    TRDECL;
    int b0, b1;
    uint32_t meta, ob = bar + B_ODONE * 8;
    const uint32_t tb = opq(sb + SM_RPB + (variant < 4 ? 3 : variant + 1 - 2 * w) * 4);
    const bool own = ((w ^ head) & 2) == 0;
    const uint32_t dst13 = sb + SM_TIN + 2 * 24576 + head * 6144 + (2 * j + (w & 1)) * 1536, src13 = opq(own ? dst13 : sb + SM_Q + wt * 3072 + 1536);
    const uint32_t snd[4] = {opq(own ? 0u : mapa(dst13, base + (head ^ 2))), opq(mapa(bar + (B_TIN + 2) * 8, base + (head ^ 2))),
                             opq(mapa(dst13, base + (w & 2) + (~head & 1))), opq(mapa(bar + (B_TIN + 3) * 8, base + (w & 2) + (~head & 1)))};
    BandCfg nx;
    band_cfg(0, tb, nx);
    band_load(nx, T, b0, b1, meta);
    band_cfg(1, tb, nx);
    const uint32_t zero = opq(blockIdx.x >> 16);
    uint32_t special = opq(0x380Au << 1);
    uint32_t q[12];
    mbar_wait(bar + B_Q0 * 8, 0);
#pragma unroll
    for (int k = 0; k < 3; k++) ldsm4(qa + k * 512, q[4 * k], q[4 * k + 1], q[4 * k + 2], q[4 * k + 3]);
    qa ^= 128;
#pragma unroll 1
    for (int b = 0; b < 14; b++) {
      float SA[56], SB[56];
      TR(0, b, 0);
      if (jw && (!(OPT & 2) || b == 0)) mbar_wait(bar + B_KIMP * 8, b & 1);
      nb_sync(nbK, 256);
      TR(0, b, 1);
      TR(0, b - 1, 9);
      wg_fence();
      wg_rs112<0>(SA, q[0], q[1], q[2], q[3], dA);
      wg_rs112<0>(SB, q[0], q[1], q[2], q[3], dB);
      wg_rs112<1>(SA, q[4], q[5], q[6], q[7], dA + 16);
      wg_rs112<1>(SB, q[4], q[5], q[6], q[7], dB + 16);
      wg_rs112<1>(SA, q[8], q[9], q[10], q[11], dA + 32);
      wg_rs112<1>(SB, q[8], q[9], q[10], q[11], dB + 32);
      wg_commit();
      nb_arrive(nbQ, 256);
      { const uint64_t t = dA; dA = dB; dB = t; }
      special >>= 1;
      if (special & 1) {
        if (b == 3) band_cfg(13, tb, nx);
        else {
          if (b == 1 || b == 13) band_load(nx, T, b0, b1, meta);
          if (b >= TB) {
            ob = bar + (b == 13 && own ? B_TIN + 2 : B_OTAIL + jw) * 8;
            oa += b == 12 ? wt * 1536 - (SM_O - SM_Q) : (b == 13 ? src13 - (sb + SM_Q + wt * 3072) : 0);
          }
        }
      }
      TR(0, b, 2);
      wg_wait<0>(); pin(SA); pin(SB);
      mbar_arrive_elect(bar + B_KFREE * 8);
      TR(0, b, 3);
      TR(0, b - 1, 10);
      uint32_t P[28];
      float sx[8];
      if (v2) {
        if (v1) softmax_tile<6, 7>(SA, SB, T, b0, b1, P, sx, nbV, zero, qa, q); else softmax_tile<4, 5>(SA, SB, T, b0, b1, P, sx, nbV, zero, qa, q);
      } else if (!v4) {
        if (v1) softmax_tile<2, 3>(SA, SB, T, b0, b1, P, sx, nbV, zero, qa, q); else softmax_tile<0, 1>(SA, SB, T, b0, b1, P, sx, nbV, zero, qa, q);
      } else {
        if (v1) softmax_tile<4, 4>(SA, SB, T, b0, b1, P, sx, nbV, zero, qa, q); else softmax_tile<3, 3>(SA, SB, T, b0, b1, P, sx, nbV, zero, qa, q);
      }
      float O[24];
      TR(0, b, 4);
#if !(OPT & 1)
      nb_sync(nbV, 288);
      TR(0, b, 5);
#pragma unroll
      for (int k = 0; k < 3; k++) ldsm4(qa + k * 512, q[4 * k], q[4 * k + 1], q[4 * k + 2], q[4 * k + 3]);
#endif
      wg_fence();
      wg_sp48<0>(O, P[0], P[1], P[2], P[3], dV[0], meta);
#pragma unroll
      for (int s = 1; s < 7; s++) wg_sp48<1>(O, P[4 * s], P[4 * s + 1], P[4 * s + 2], P[4 * s + 3], dV[s], meta);
      wg_commit();
      nb_arrive(N_PVISS, 384);
      TR(0, b, 6);
      wg_wait<0>(); pin(O);
      mbar_arrive_elect(bar + B_VFREE * 8);
      TR(0, b, 7);
      float ru, rl;
      asm("rcp.approx.ftz.f32 %0, %1;" : "=f"(ru) : "f"(((fmaf(O[0], 0.f, sx[0]) + sx[1]) + sx[2]) + sx[3]));
      asm("rcp.approx.ftz.f32 %0, %1;" : "=f"(rl) : "f"(((fmaf(O[2], 0.f, sx[4]) + sx[5]) + sx[6]) + sx[7]));
#pragma unroll
      for (int i = 0; i < 3; i++)
        stsm4(oa + i * 256, pack2(O[8 * i] * ru, O[8 * i + 1] * ru), pack2(O[8 * i + 2] * rl, O[8 * i + 3] * rl),
              pack2(O[8 * i + 4] * ru, O[8 * i + 5] * ru), pack2(O[8 * i + 6] * rl, O[8 * i + 7] * rl));
      if ((OPT & 2) && jw && b < 13) mbar_wait(bar + B_KIMP * 8, ~b & 1);
      publish(ob);
      qa ^= 128;
      meta ^= 0x55555555u;
      TR(0, b, 8);
    }
    asm volatile("{\n.reg .pred p, q;\nsetp.ne.b32 q, %1, 0;\nelect.sync _|p, 0xffffffff;\nand.pred q, q, p;\n"
                 "@q cp.async.bulk.shared::cluster.shared::cta.mbarrier::complete_tx::bytes [%1], [%0], 1536, [%2];\n"
                 "@p cp.async.bulk.shared::cluster.shared::cta.mbarrier::complete_tx::bytes [%3], [%0], 1536, [%4];\n}"
                 ::"r"(src13), "r"(snd[0]), "r"(snd[1]), "r"(snd[2]), "r"(snd[3]) : "memory");
    if (jw == 0) nb_arrive(3, 256);
    TRDUMP;
    cluster_sync();
  } else if (warp < 12) {
    TRDECL;
    TR(2, -3, 0);
    asm volatile("setmaxnreg.inc.sync.aligned.u32 %0;" ::"n"(RG));
    TR(2, -3, 1);
    GemmCtx c;
    c.bar = bar;
    const int gw = warp - 8, tk = gw * 16 + (lane & 15), hi = lane >> 4;
    { const int col = tk >> 2, i = tk & 3;
      c.kC = sb + SM_K + (col + 3) * KS + hi * 128 + i * 16;
      c.vC[0] = sb + SM_V + (col + 3) * 1536 + hi * 128 + (2 * i + ((col + 3) & 1)) * 16;
      c.qC[0] = sb + SM_Q + col * 1536 + hi * 256 + (col & 1) * 64 + i * 16; }
    { const int kc = gw - 1 + 19 * odd, i = lane & 7; c.hvalid = gw > 0; c.edge = gw == (odd ? 0 : 3);
      c.kH = sb + SM_K + kc * KS + (lane >> 3) * 128 + i * 16;
      c.vH[0] = sb + SM_V + kc * 1536 + (lane >> 3) * 128 + (i >> 2) * 768 + (2 * (i & 3) + ((kc ^ (i >> 2)) & 1)) * 16; }
#pragma unroll
    for (int i = 0; i < 3; i++) c.em[i] = opq(mapa(bar + (B_EMPTY + i) * 8, base + i));
    c.never = x == nullptr;
    c.kC = opq(c.kC); c.kH = opq(c.kH);
    c.vC[1] = opq(c.vC[0] ^ 16); c.vC[0] = opq(c.vC[0]);
    c.vH[1] = opq(c.vH[0] ^ 16); c.vH[0] = opq(c.vH[0]);
    c.qC[1] = opq(c.qC[0] ^ 64); c.qC[0] = opq(c.qC[0]);
    c.spin = 0;
    c.hiA = (uint32_t)(mkdesc(0, 0, 1024, 1) >> 32) + (blockIdx.x >> 16); c.hiB = (uint32_t)(mkdesc(0, 0, 256, 3) >> 32) + (blockIdx.x >> 16);
    asm volatile("barrier.cluster.wait.aligned;" ::: "memory");
    TR(2, -3, 2);
#pragma unroll
    for (int i = 0; i < 2 * NL; i++) sts128(wdst + (i & 1) * 3072 + (i / 2) * 18432, wv[i]);
    fence_async();
    TR(2, -3, 3);
    asm volatile("bar.sync 1, 384;" ::: "memory");
    TR(2, -3, 4);
    mbar_wait(bar + B_WK * 8, 0);
    TR(2, -3, 5);
    uint32_t pk[12], pv[12], pq[12], hk1[6], hv1[6];
    gemm_iter<true, 0>(c, -2, pk, pv, pq, hk1, hv1 TRPASS);
    TR2(blockIdx.x, 4);
    c.hiA = opq(c.hiA); c.hiB = opq(c.hiB);
#pragma unroll 1
    for (int b = -1;; b += 2) {
      gemm_iter<false, 1>(c, b, pk, pv, pq, hk1, hv1 TRPASS);
      if (b == 11) break;
      gemm_iter<false, 0>(c, b + 1, pk, pv, pq, hk1, hv1 TRPASS);
    }
    TR2(blockIdx.x, 6);
    c.hiA = opq(c.hiA); c.hiB = opq(c.hiB);
    const uint32_t st = sb + gw * 3072;
    const uint32_t sta = st + (lane & 15) * 64 + ((hi ^ ((lane >> 1) & 3)) * 16);
    const int oc = ph * 112 + strip * 16 + 8 * (gw >> 1) + 4 * (head >> 1) + 2 * (gw & 1), och = pw * 6 + (head & 1) * 3;
    float D0[48], D1[48];
    mbar_arrive_elect(bar + B_WOFREE * 8);
    dump12<256>(c.qC[1] + 128, pq);
    nb_sync(N_QK1, 256);
    issue_halo<0, 12>(c, D1);
    gwait<0>(c, B_KFREE);
    dump12<128>(c.kC, pk);
    fence_async();
    edge_ready(c, B_XK);
    nb_arrive(N_VQ0, 288); nb_arrive(N_VQ1, 288); nb_arrive(N_PVISS, 384);
    wg_wait<0>(); pin(D1);
    pack6(hk1, D1, 0);
    if (c.hvalid) dump6(c.kH, hk1);
    tail_free(bar + (B_TFREE + 1) * 8);
    pack6(hv1, D1, 24);
    fence_async();
    nb_arrive(N_KRDY, 256);
    gwait<0>(c, B_VFREE);
    dump12<128>(c.vC[0], pv);
    if (c.hvalid) dump6(c.vH[0], hv1);
    fence_async();
    edge_ready(c, B_XV);
    nb_arrive(N_VQ0, 288); nb_arrive(N_VQ1, 288);
    gwait<0>(c, B_WO);
    gwait<0>(c, B_TIN);
    TR(2, 13, 0);
    nb_sync(N_QK1, 256);
    issue_proj<SM_TIN>(D0);
    wg_wait<0>(); pin(D0);
    TR(2, 13, 1);
    store_proj(D0, &mp.ot, st + SM_TST, sta + SM_TST, 8 * TB, oc, och);
    gwait<0>(c, B_TIN + 1);
    TR(2, 13, 2);
    nb_sync(N_PVISS, 384);
    nb_sync(3, 256);
    issue_proj<SM_TIN + 24576>(D1);
    wg_wait<0>(); pin(D1);
    TR(2, 13, 3);
    store_proj(D1, &mp.ot, st + SM_TIN, sta + SM_TIN, 8 * TB + 8, oc, och);
    TR(2, 13, 4);
    gwait<0>(c, B_TIN + 2);
    TR(2, 13, 5);
    issue_proj_half<0>(D0, head & 1);
    gwait<0>(c, B_TIN + 3);
    TR(2, 13, 6);
    issue_proj_half<1>(D0, ~head & 1);
    asm volatile("barrier.cluster.arrive.relaxed.aligned;" ::: "memory");
    wg_wait<0>(); pin(D0);
    store_proj(D0, &mp.ot, st + SM_TIN + 12288, sta + SM_TIN + 12288, 8 * TB + 16, oc, och);
    TR(2, 13, 7);
    if (lane == 0) asm volatile("cp.async.bulk.wait_group.read 0;" ::: "memory");
    __syncwarp();
    TR(2, 13, 8);
    TR2(blockIdx.x, 2);
    TRDUMP;
    asm volatile("barrier.cluster.wait.aligned;" ::: "memory");
  } else {
    if (warp == 12) {
      if (elect_one()) {
        mbar_init(bar + B_WK * 8, 1);
#pragma unroll
        for (int i = 0; i < NL; i++) load_w(&mp.w, sb + SM_W + (3 * i + 2 - 2 * va) * 6144, bar + B_WK * 8, ((i + 1) % 3) * 192 + head * 48 + 32 - 32 * va);
        asm volatile("prefetch.tensormap [%0];" ::"l"(head ? &mp.xc : &mp.xh) : "memory");
        mbar_expect(bar + B_WK * 8, NL * 6144);
      }
    } else if (warp == 15) {
      const int col = min(max(strip * 16 - 3 + min(lane, 21), 0), 111);
      const uint8_t* p = reinterpret_cast<const uint8_t*>(x) + (uint32_t)(head * ROWB + (ph * 112 + col) * 768 + pw * 384);
#pragma unroll
      for (int i = 0; i < 3; i++) asm volatile("prefetch.global.L2 [%0];" ::"l"(p + i * 128));
    } else if (elect_one()) {
      if (warp == 13) {
#pragma unroll
        for (int i = 0; i < B_WK; i++) mbar_init(bar + i * 8, i < B_EMPTY ? 1 : (i < B_TIN ? 16 : (i < B_TFREE ? (i == B_TIN + 2 ? 5 : 1) : 16)));
      } else {
#pragma unroll
        for (int i = B_WQ; i < B_COUNT; i++) mbar_init(bar + i * 8, i < B_XK ? 1 : (i < B_Q0 ? 2 : (i < B_ODONE ? 4 : (i == B_VFREE ? 9 : 8))));
        mbar_arrive(bar + B_XK * 8); mbar_arrive(bar + B_XV * 8);
      }
    }
    asm volatile("fence.mbarrier_init.release.cluster;" ::: "memory");
    __syncwarp();
    asm volatile("barrier.cluster.arrive.relaxed.aligned;" ::: "memory");
    asm volatile("setmaxnreg.dec.sync.aligned.u32 24;");
    asm volatile("griddepcontrol.launch_dependents;");
    asm volatile("barrier.cluster.wait.aligned;" ::: "memory");
    if (warp == 12) {
      const CUtensorMap* mx = head ? &mp.xc : &mp.xh;
      const int cc = ph * 112 + strip * 16 + (head ? 0 : (odd ? 16 : (strip ? -3 : 0)));
      const int r0 = head == 0 ? (strip ? -4 : 112) : (head == 1 ? 4 : 0), dr = head ? 8 : 16;
      const uint32_t fb = bar + (B_FULL + head) * 8, eb = bar + (B_EMPTY + head) * 8;
      const uint32_t dst = sb + (head == 0 ? SM_X0 : (head == 1 ? SM_X1 : SM_X2));
      const int nl = head == 0 ? 8 : (head == 3 ? 1 : 14);
      TRDECL;
#pragma unroll 1
      for (int n = 0; n < nl; n++) {
        if (n) mbar_wait(eb, (n - 1) & 1);
        TR(2, n - 3, 0);
        if (elect_one()) {
          if (head < 3)
            asm volatile("cp.async.bulk.tensor.4d.shared::cluster.global.mbarrier::complete_tx::bytes.multicast::cluster [%0], [%1, {%3,%4,%5,%6}], [%2], %7;"
                         ::"r"(dst), "l"(mx), "r"(fb), "r"(0), "r"(dr * n + r0), "r"(cc), "r"(pw * 3), "h"((uint16_t)(15 << base)) : "memory");
          if (n == 0) {
#pragma unroll
            for (int i = 0; i < 3; i++) load_w(&mp.w, sb + SM_W + (6 + i) * 6144, bar + B_WQ * 8, head * 48 + i * 16);
            mbar_expect(bar + B_WQ * 8, 18432);
            mbar_expect(bar + B_TIN * 8, 24576); mbar_expect(bar + (B_TIN + 1) * 8, 24576); mbar_expect(bar + (B_TIN + 2) * 8, 6144); mbar_expect(bar + (B_TIN + 3) * 8, 12288);
          }
          if (n + 1 < nl) asm volatile("cp.async.bulk.prefetch.tensor.4d.L2.global [%0, {%1,%2,%3,%4}];" ::"l"(mx), "r"(0), "r"(dr * n + dr + r0), "r"(cc), "r"(pw * 3) : "memory");
        }
        __syncwarp();
        TR(2, n - 3, 1);
        if (lane < 4 && head < 3)
          asm volatile("mbarrier.arrive.expect_tx.shared::cluster.b64 _, [%0], %1;" ::"r"(mapa(fb, base + lane)), "r"(head ? 24576 : 18432) : "memory");
        __syncwarp();
        TR(2, n - 3, 2);
      }
      TRDUMP;
      mbar_wait(bar + B_WOFREE * 8, 0);
      if (elect_one()) {
        mbar_expect(bar + B_WO * 8, 36864);
        asm volatile("cp.async.bulk.tensor.3d.shared::cluster.global.mbarrier::complete_tx::bytes [%0], [%1, {%3,%4,%5}], [%2];"
                     ::"r"(sb + SM_TWO), "l"(&mp.wo), "r"(bar + B_WO * 8), "r"(0), "r"(0), "r"((head & 1) * 3) : "memory");
      }
      __syncwarp();
    }
    if (warp & 1) {
      const uint32_t partner = (blockIdx.x & 7) ^ 4;
      const int cs = odd ? 3 : (strip == 6 ? 15 : 16), cd = odd || strip == 6 ? 19 : 0;
      const uint32_t rb = opq(mapa(bar, partner));
      TRDECL;
      if (warp == 13) {
        const uint32_t dst = opq(mapa(sb + SM_V + cd * 1536, partner)), src = opq(sb + SM_V + cs * 1536);
#pragma unroll 1
        for (int b = 0;; b++) {
          const uint32_t pa = b & 1;
          mbar_wait(bar + B_XV * 8, pa);
          TR(1, b, 0);
          if (elect_one()) { copy_remote(dst, src, 4608, rb + B_VIMP * 8); remote_expect(rb + B_VIMP * 8, 4608); }
          __syncwarp();
          TR(1, b, 1);
          mbar_wait(bar + B_VIMP * 8, pa);
          TR(1, b, 2);
          if (elect_one()) remote_arrive(rb + B_VFREE * 8);
          __syncwarp();
          mbar_wait(bar + B_OFREE * 8, pa);
          nb_arrive(N_VQ1, 288);
          TR(1, b, 3);
          if (b == 13) break;
          mbar_wait(bar + B_VFREE * 8, pa);
          if (elect_one()) remote_arrive(rb + B_XV * 8);
          __syncwarp();
        }
      } else {
        const uint32_t dst = opq(mapa(sb + SM_K + cd * KS, partner)), src = opq(sb + SM_K + cs * KS);
#pragma unroll 1
        for (int b = 0;; b++) {
          const uint32_t pa = b & 1, so = (pa ^ 1) * KSLOT;
          mbar_wait(bar + B_XK * 8, pa);
          TR(1, b - 1, 4);
          if (elect_one()) {
            copy_remote(dst + so, src + so, 3 * KS, rb + B_KIMP * 8);
            if (b == 0) copy_remote(dst, src, 3 * KS, rb + B_KIMP * 8);
            remote_expect(rb + B_KIMP * 8, b ? 3 * KS : 6 * KS);
          }
          __syncwarp();
          TR(1, b - 1, 5);
          TR(1, b - 1, 7);
          if (b == 13) break;
          mbar_wait(bar + B_KFREE * 8, pa);
          if (elect_one()) remote_arrive(rb + B_XK * 8);
          __syncwarp();
        }
      }
      TRDUMP;
    }
    if (warp == 14) {
      int* flag = g_flags + (par * 7 + strip) * 2;
      nb_arrive(N_VQ0, 288); mbar_arrive_elect(bar + B_OFREE * 8);
#pragma unroll 1
      for (int b = 0; b < TB; b++) {
        mbar_wait(bar + B_ODONE * 8, b & 1);
        if (lane == 0) {
#pragma unroll 1
          for (int i = 0; i < 16; i += OCH) {
            asm volatile("cp.async.bulk.tensor.3d.global.shared::cta.bulk_group [%0, {%2,%3,%4}], [%1];"
                         ::"l"(&mp.os), "r"(sb + SM_O + i * 768), "r"(pw * 192), "r"(8 * b + 2 * head), "r"(ph * 112 + strip * 16 + i) : "memory");
            asm volatile("cp.async.bulk.commit_group;\ncp.async.bulk.wait_group 0;" ::: "memory");
          }
        }
        __syncwarp();
        nb_arrive(N_VQ0, 288); mbar_arrive_elect(bar + B_OFREE * 8);
        if (lane == 0)
          asm volatile("fence.proxy.async.global;\nfence.acq_rel.gpu;\nred.relaxed.gpu.global.add.s32 [%0], 1;\nred.relaxed.gpu.global.add.s32 [%0+4], 1;"
                       ::"l"(flag + b * 56) : "memory");
        __syncwarp();
      }
#pragma unroll 1
      for (int t = 0; t < 4; t++) {
        const int i = t >> 1, jw = t & 1, j = jw ^ odd;
        if (!jw) mbar_wait(bar + (B_TFREE + i) * 8, 0);
        mbar_wait(bar + (B_OTAIL + jw) * 8, i);
        if (jw) { nb_arrive(N_VQ0, 288); mbar_arrive_elect(bar + B_OFREE * 8); }
        if (elect_one()) {
#pragma unroll 1
          for (int d = 0; d < 8; d++) {
            const int dst = (d + head) & 3, pc = d >> 2;
            send_o<1536>(sb + SM_TIN + i * 24576 + head * 6144 + j * 3072 + pc * 1536,
                         sb + (i ? SM_Q : SM_O) + (4 * j + (dst & 2) + pc) * (i ? 3072 : 1536), bar + (B_TIN + i) * 8, base + dst);
          }
        }
        __syncwarp();
      }
    }
    cluster_sync();
  }
}

constexpr int NSTB = 6;
constexpr int NTB = TB * 56;
constexpr int SM_B_ST = 0;
constexpr int SM_B_IN = 73728;
constexpr int SM_B_W = SM_B_IN + 3 * 24576;
constexpr int SM_B_BAR = SM_B_IN + NSTB * 24576;
constexpr int SM_B_TOTAL = SM_B_BAR + 512;
struct MapsB { CUtensorMap oi, oo, wo; };

__global__ void __launch_bounds__(512, 1)
na_proj_kernel(const __grid_constant__ MapsB mp) {
  extern __shared__ __align__(1024) uint8_t smem_raw[];
  const uint32_t sb = smem_u32(smem_raw);
  if ((sb & 0x3FFFF) != SBC) return;
  const uint32_t bar = sb + SM_B_BAR;
  const int tid = threadIdx.x, lane = tid & 31;
  const int warp = __shfl_sync(0xffffffffu, tid >> 5, 0);
  TR2(132 + blockIdx.x, 0);
  TRB(47, 0);
  if (warp == 12 && elect_one()) {
#pragma unroll
    for (int i = 0; i <= 2 * NSTB; i++) mbar_init(bar + i * 8, i < NSTB || i == 2 * NSTB ? 1 : 12);
    asm volatile("st.shared.u32 [%0], 0;" ::"r"(bar + 120) : "memory");
    mbar_expect(bar + 2 * NSTB * 8, 73728);
#pragma unroll
    for (int i = 0; i < 2; i++)
      asm volatile("cp.async.bulk.tensor.3d.shared::cluster.global.mbarrier::complete_tx::bytes [%0], [%1, {%3,%4,%5}], [%2];"
                   ::"r"(sb + SM_B_W + i * 36864), "l"(&mp.wo), "r"(bar + 2 * NSTB * 8), "r"(0), "r"(0), "r"(i * 3) : "memory");
  }
  __syncthreads();
  const int step = gridDim.x;
  if (warp == 15) {
    int so = 0;
    nb_arrive(4, 288); nb_arrive(5, 288); nb_arrive(6, 288);
#pragma unroll 1
    for (int n = blockIdx.x, tk = 0; n < NTB; n += step, tk++) {
      uint32_t cc = 0;
#pragma unroll
      for (int wg = 0; wg < 3; wg++) {
        if (lane == 0) asm volatile("cp.async.bulk.wait_group.read 5;" ::: "memory");
        nb_sync(1 + wg, 160);
        if (wg == 0 || n + step < NTB) nb_arrive(4 + wg, 288);
        if (wg == 0) asm volatile("ld.shared.u32 %0, [%1];" : "=r"(cc) : "r"(bar + 128 + tk * 4) : "memory");
        if (lane == 0) {
          asm volatile("cp.async.bulk.tensor.4d.global.shared::cta.bulk_group [%0, {%2,%3,%4,%5}], [%1];"
                       ::"l"(&mp.oo), "r"(sb + SM_B_ST + wg * 8192 + so), "r"(0), "r"((cc >> 8) & 255), "r"(cc >> 16), "r"((cc & 1) * 3 + wg) : "memory");
          asm volatile("cp.async.bulk.commit_group;" ::: "memory");
        }
        __syncwarp();
      }
      so = so == 49152 ? 0 : so + 24576;
    }
    if (lane == 0) asm volatile("cp.async.bulk.wait_group.read 0;" ::: "memory");
  } else if (warp >= 12) {
    nb_sync(7, 480);
#pragma unroll 1
    for (int n = blockIdx.x + (warp - 12) * step; n < NTB; n += 3 * step) {
      const int b = n / 56, rem = n - b * 56, par = rem / 14;
      const int c0 = opq((uint32_t)(par & 1)), c1 = opq((uint32_t)(8 * b)), c2 = opq((uint32_t)((par >> 1) * 112 + (rem - par * 14) * 8));
      int v; uint32_t spin = 0, tk = 0;
      do { asm volatile("ld.acquire.gpu.global.s32 %0, [%1];" : "=r"(v) : "l"(g_flags + n) : "memory"); } while (v < 4 && ++spin < SPIN_LIMIT);
      if (lane == 0) asm volatile("atom.shared.add.u32 %0, [%1], 1;" : "=r"(tk) : "r"(bar + 120) : "memory");
      asm volatile("fence.proxy.async.global;" ::: "memory");
      tk = __shfl_sync(0xffffffffu, tk, 0);
      TRB(tk, 0);
      const uint32_t use = tk / NSTB, sg = tk - use * NSTB;
      if (use) mbar_wait(bar + (NSTB + sg) * 8, (use - 1) & 1);
      TRB(tk, 1);
      if (elect_one()) {
        asm volatile("st.shared.u32 [%0], %1;" ::"r"(bar + 128 + tk * 4), "r"(c0 | c1 << 8 | c2 << 16) : "memory");
        mbar_expect(bar + sg * 8, 24576);
        asm volatile("cp.async.bulk.tensor.3d.shared::cluster.global.mbarrier::complete_tx::bytes [%0], [%1, {%3,%4,%5}], [%2];"
                     ::"r"(sb + SM_B_IN + sg * 24576), "l"(&mp.oi), "r"(bar + sg * 8), "r"(c0 * 192), "r"(c1), "r"(c2) : "memory");
        g_flags[n] = 0;
      }
      __syncwarp();
    }
  } else {
    const int wg = warp >> 2, w = warp & 3;
    uint32_t a[48];
    mbar_wait(bar + 2 * NSTB * 8, 0);
    {
      const int k = (lane & 7) + (lane >> 4) * 8, ch = (warp & 1) * 2 + ((lane >> 3) & 1);
      const uint32_t wa = sb + SM_B_W + (warp >> 1) * 12288 + k * 64 + ((ch ^ ((k >> 1) & 3)) * 16);
#pragma unroll
      for (int i = 0; i < 12; i++)
        asm volatile("ldmatrix.sync.aligned.m8n8.x4.trans.shared.b16 {%0,%1,%2,%3}, [%4];"
                     : "=r"(a[4 * i]), "=r"(a[4 * i + 1]), "=r"(a[4 * i + 2]), "=r"(a[4 * i + 3]) : "r"(wa + i * 1024) : "memory");
    }
    nb_sync(7, 480);
    TRB(47, 1);
    const uint32_t sta = opq(sb + SM_B_ST + wg * 8192 + ((lane & 7) + (lane >> 4) * 8) * 128 + (((2 * w + ((lane >> 3) & 1)) ^ (lane & 7)) * 16));
    const uint32_t hi = opq((uint32_t)(mkdesc(0, 0, 3072, 0) >> 32) + (blockIdx.x >> 16)), bb = opq(bar);
    const uint32_t nbT = opq((uint32_t)(4 + wg)), nbN = opq((uint32_t)(wg == 2 ? 4 : 5 + wg)), nbD = opq((uint32_t)(1 + wg));
    int left = (NTB - blockIdx.x + step - 1) / step;
    if (wg == 2) nb_arrive(4, 288);
#pragma unroll 1
    for (uint32_t ph = 0;; ph ^= 1) {
#pragma unroll
      for (int sg = 0; sg < NSTB; sg++) {
        constexpr uint64_t db = mkdesc(SBC + SM_B_IN, 128, 3072, 0);
        float D[32];
        mbar_wait(bb + sg * 8, ph);
        nb_sync(nbT, 288);
        wg_fence();
        wg_rs64<0>(D, a[0], a[1], a[2], a[3], dsc(db + sg * 1536, hi));
#pragma unroll
        for (int k = 1; k < 12; k++) wg_rs64<1>(D, a[4 * k], a[4 * k + 1], a[4 * k + 2], a[4 * k + 3], dsc(db + sg * 1536 + k * 16, hi));
        wg_commit();
        nb_arrive(nbN, 288);
        wg_wait<0>(); pin(D);
        mbar_arrive_elect(bb + (NSTB + sg) * 8);
#pragma unroll
        for (int q = 0; q < 4; q++)
          asm volatile("stmatrix.sync.aligned.m8n8.x4.trans.shared.b16 [%0], {%1,%2,%3,%4};" ::"r"(sta + (sg % 3) * 24576 + q * 2048),
                       "r"(pack2(D[8 * q], D[8 * q + 1])), "r"(pack2(D[8 * q + 2], D[8 * q + 3])), "r"(pack2(D[8 * q + 4], D[8 * q + 5])), "r"(pack2(D[8 * q + 6], D[8 * q + 7])) : "memory");
        fence_async();
        nb_arrive(nbD, 160);
        if (wg == 0) TRB(31 - left, 5);
        if (--left == 0) goto done;
      }
    }
  done:
    if (wg == 0) nb_arrive(4, 288);
    TR2(132 + blockIdx.x, 2);
  }
}

typedef CUresult (*EncodeFn)(CUtensorMap*, CUtensorMapDataType, cuuint32_t, void*, const cuuint64_t*, const cuuint64_t*, const cuuint32_t*,
                             const cuuint32_t*, CUtensorMapInterleave, CUtensorMapSwizzle, CUtensorMapL2promotion, CUtensorMapFloatOOBfill);
static EncodeFn g_enc = nullptr;
static void make_map(CUtensorMap* m, const void* p, int rank, const cuuint64_t* dim, const cuuint64_t* str, const cuuint32_t* box, CUtensorMapSwizzle sw) {
  const cuuint32_t ones[5] = {1, 1, 1, 1, 1};
  g_enc(m, CU_TENSOR_MAP_DATA_TYPE_BFLOAT16, rank, (void*)p, dim, str, box, ones, CU_TENSOR_MAP_INTERLEAVE_NONE, sw,
        CU_TENSOR_MAP_L2_PROMOTION_L2_128B, CU_TENSOR_MAP_FLOAT_OOB_FILL_NONE);
}

extern "C" void kernel_launch(void* const* d_in, const int* in_sizes, int n_in, void* d_out, int out_size) {
  const __nv_bfloat16* x = (const __nv_bfloat16*)d_in[0];
  const __nv_bfloat16* wqkv = (const __nv_bfloat16*)d_in[1];
  const __nv_bfloat16* wo = (const __nv_bfloat16*)d_in[2];
  const __nv_bfloat16* rpb = (const __nv_bfloat16*)d_in[3];

  if (!g_enc) {
    void* fn = nullptr; cudaDriverEntryPointQueryResult qr;
    cudaGetDriverEntryPoint("cuTensorMapEncodeTiled", &fn, cudaEnableDefault, &qr);
    g_enc = (EncodeFn)fn;
    cudaFuncSetAttribute(na_attn_kernel, cudaFuncAttributeMaxDynamicSharedMemorySize, SM_A_TOTAL);
    cudaFuncSetAttribute(na_proj_kernel, cudaFuncAttributeMaxDynamicSharedMemorySize, SM_B_TOTAL);
  }
  Maps ma; MapsB mb;
  { cuuint64_t dim[4] = {64, 112, 224, 6}, str[3] = {(cuuint64_t)ROWB, 768, 128};
    cuuint32_t box[4] = {64, 4, 16, 3}, boxh[4] = {64, 16, 3, 3}, boxo[4] = {64, 8, 8, 1};
    make_map(&ma.xc, x, 4, dim, str, box, CU_TENSOR_MAP_SWIZZLE_128B);
    make_map(&ma.xh, x, 4, dim, str, boxh, CU_TENSOR_MAP_SWIZZLE_128B);
    make_map(&mb.oo, d_out, 4, dim, str, boxo, CU_TENSOR_MAP_SWIZZLE_128B); }
  { cuuint64_t dim[3] = {384, 112, 224}, str[2] = {(cuuint64_t)ROWB, 768};
    cuuint32_t box[3] = {192, 8, 8}, boxs[3] = {192, 2, OCH};
    make_map(&mb.oi, d_out, 3, dim, str, box, CU_TENSOR_MAP_SWIZZLE_NONE);
    make_map(&ma.os, d_out, 3, dim, str, boxs, CU_TENSOR_MAP_SWIZZLE_NONE); }
  { cuuint64_t dim[4] = {32, 112, 224, 12}, str[3] = {(cuuint64_t)ROWB, 768, 64};
    cuuint32_t box[4] = {32, 8, 2, 3};
    make_map(&ma.ot, d_out, 4, dim, str, box, CU_TENSOR_MAP_SWIZZLE_64B); }
  { cuuint64_t dim[2] = {576, 192}, str[1] = {1152};
    cuuint32_t box[2] = {16, 192};
    make_map(&ma.w, wqkv, 2, dim, str, box, CU_TENSOR_MAP_SWIZZLE_32B); }
  { cuuint64_t dim[3] = {32, 192, 6}, str[2] = {384, 64};
    cuuint32_t box[3] = {32, 192, 3};
    make_map(&ma.wo, wo, 3, dim, str, box, CU_TENSOR_MAP_SWIZZLE_64B);
    mb.wo = ma.wo; }
  na_attn_kernel<<<112, 512, SM_A_TOTAL>>>(x, wqkv, rpb, ma);
  cudaLaunchConfig_t cfg = {};
  cfg.gridDim = dim3(20); cfg.blockDim = dim3(512); cfg.dynamicSmemBytes = SM_B_TOTAL; cfg.stream = cudaStreamPerThread;
  cudaLaunchAttribute at[1];
  at[0].id = cudaLaunchAttributeProgrammaticStreamSerialization; at[0].val.programmaticStreamSerializationAllowed = 1;
  cfg.attrs = at; cfg.numAttrs = 1;
  cudaLaunchKernelEx(&cfg, na_proj_kernel, mb);
}
```

```cpp
#include <cuda_runtime.h>
#include <cuda_bf16.h>
#include <cuda.h>
#include <stdint.h>

#define SPIN_LIMIT (1u << 18)

__device__ __forceinline__ uint32_t smem_u32(const void* p) { return (uint32_t)__cvta_generic_to_shared(p); }
__device__ __forceinline__ void wg_fence() { asm volatile("wgmma.fence.sync.aligned;" ::: "memory"); }
__device__ __forceinline__ void wg_commit() { asm volatile("wgmma.commit_group.sync.aligned;" ::: "memory"); }
template <int N> __device__ __forceinline__ void wg_wait() { asm volatile("wgmma.wait_group.sync.aligned %0;" ::"n"(N) : "memory"); }
template <int N> __device__ __forceinline__ void pin(float (&d)[N]) {
#pragma unroll
  for (int i = 0; i < N; i++) asm volatile("" : "+f"(d[i])::"memory");
}
__host__ __device__ constexpr uint64_t mkdesc(uint32_t addr, uint32_t lbo, uint32_t sbo, uint32_t sw) {
  return (uint64_t)((addr & 0x3FFFF) >> 4) | ((uint64_t)(lbo >> 4) << 16) | ((uint64_t)(sbo >> 4) << 32) | ((uint64_t)sw << 62);
}
__device__ __forceinline__ void mbar_init(uint32_t bar, uint32_t cnt) { asm volatile("mbarrier.init.shared::cta.b64 [%0], %1;" ::"r"(bar), "r"(cnt) : "memory"); }
__device__ __forceinline__ void mbar_arrive(uint32_t bar) { asm volatile("mbarrier.arrive.shared::cta.b64 _, [%0];" ::"r"(bar) : "memory"); }
__device__ __forceinline__ bool elect_one() {
  uint32_t r; asm volatile("{\n.reg .pred p;\nelect.sync _|p, 0xffffffff;\nselp.u32 %0, 1, 0, p;\n}" : "=r"(r)); return r;
}
__device__ __forceinline__ void mbar_arrive_elect(uint32_t bar) {
  asm volatile("{\n.reg .pred p;\nelect.sync _|p, 0xffffffff;\n@p mbarrier.arrive.shared::cta.b64 _, [%0];\n}" ::"r"(bar) : "memory");
}
__device__ __forceinline__ void mbar_expect(uint32_t bar, uint32_t bytes) { asm volatile("mbarrier.arrive.expect_tx.shared::cta.b64 _, [%0], %1;" ::"r"(bar), "r"(bytes) : "memory"); }
__device__ __forceinline__ void mbar_arrive_remote(uint32_t bar, uint32_t cta) {
  asm volatile("{\n.reg .b32 ra;\nmapa.shared::cluster.u32 ra, %0, %1;\nmbarrier.arrive.relaxed.cluster.shared::cluster.b64 _, [ra];\n}" ::"r"(bar), "r"(cta) : "memory");
}
__device__ __forceinline__ void mbar_wait(uint32_t bar, uint32_t parity) {
  asm volatile("{\n.reg .pred p;\n.reg .b32 n;\nmov.b32 n, 0;\nWL:\nmbarrier.try_wait.parity.shared::cta.b64 p, [%0], %1;\n@p bra WD;\n"
               "add.u32 n, n, 1;\nsetp.lt.u32 p, n, 65536;\n@p bra WL;\nWD:\n}" ::"r"(bar), "r"(parity) : "memory");
}
__device__ __forceinline__ void nb_sync(int id, int n) { asm volatile("bar.sync %0, %1;" ::"r"(id), "r"(n) : "memory"); }
__device__ __forceinline__ void nb_arrive(int id, int n) { asm volatile("bar.arrive %0, %1;" ::"r"(id), "r"(n) : "memory"); }
__device__ __forceinline__ uint32_t opq(uint32_t x) { uint32_t r; asm volatile("mov.b32 %0, %1;" : "=r"(r) : "r"(x)); return r; }
__device__ __forceinline__ uint64_t opq(uint64_t x) { uint64_t r; asm volatile("mov.b64 %0, %1;" : "=l"(r) : "l"(x)); return r; }
__device__ __forceinline__ uint32_t mapa(uint32_t a, uint32_t cta) { uint32_t r; asm("mapa.shared::cluster.u32 %0, %1, %2;" : "=r"(r) : "r"(a), "r"(cta)); return r; }
__device__ __forceinline__ void fence_async() { asm volatile("fence.proxy.async.shared::cta;" ::: "memory"); }
__device__ __forceinline__ void cluster_sync() {
  asm volatile("barrier.cluster.arrive.relaxed.aligned;\nbarrier.cluster.wait.aligned;" ::: "memory");
}
__device__ __forceinline__ uint32_t pack2(float lo, float hi) {
  uint32_t r; asm("cvt.rn.bf16x2.f32 %0, %1, %2;" : "=r"(r) : "f"(hi), "f"(lo)); return r;
}
__device__ __forceinline__ void stsm4(uint32_t a, uint32_t r0, uint32_t r1, uint32_t r2, uint32_t r3) {
  asm volatile("stmatrix.sync.aligned.m8n8.x4.shared.b16 [%0], {%1,%2,%3,%4};" ::"r"(a), "r"(r0), "r"(r1), "r"(r2), "r"(r3) : "memory");
}
__device__ __forceinline__ void ldsm4(uint32_t a, uint32_t& r0, uint32_t& r1, uint32_t& r2, uint32_t& r3) {
  asm volatile("ldmatrix.sync.aligned.m8n8.x4.shared.b16 {%0,%1,%2,%3}, [%4];" : "=r"(r0), "=r"(r1), "=r"(r2), "=r"(r3) : "r"(a) : "memory");
}
__device__ __forceinline__ void sts128(uint32_t a, uint4 v) {
  asm volatile("st.shared.v4.b32 [%0], {%1,%2,%3,%4};" ::"r"(a), "r"(v.x), "r"(v.y), "r"(v.z), "r"(v.w) : "memory");
}
__device__ __forceinline__ float lds_f32(uint32_t a) { float v; asm volatile("ld.shared.f32 %0, [%1];" : "=f"(v) : "r"(a)); return v; }
__device__ __forceinline__ float ex2(float x) { float y; asm("ex2.approx.ftz.f32 %0, %1;" : "=f"(y) : "f"(x)); return y; }

template<int SC> __device__ __forceinline__ void wg_ss144(float (&d)[72], uint64_t da, uint64_t db) {
  asm volatile("{\n.reg .pred p;\nsetp.ne.b32 p, %74, 0;\nwgmma.mma_async.sync.aligned.m64n144k16.f32.bf16.bf16 {%0,%1,%2,%3,%4,%5,%6,%7,%8,%9,%10,%11,%12,%13,%14,%15,%16,%17,%18,%19,%20,%21,%22,%23,%24,%25,%26,%27,%28,%29,%30,%31,%32,%33,%34,%35,%36,%37,%38,%39,%40,%41,%42,%43,%44,%45,%46,%47,%48,%49,%50,%51,%52,%53,%54,%55,%56,%57,%58,%59,%60,%61,%62,%63,%64,%65,%66,%67,%68,%69,%70,%71}, %72, %73, p, 1, 1, 0, 1;\n}\n"
    : "+f"(d[0]),"+f"(d[1]),"+f"(d[2]),"+f"(d[3]),"+f"(d[4]),"+f"(d[5]),"+f"(d[6]),"+f"(d[7]),"+f"(d[8]),"+f"(d[9]),"+f"(d[10]),"+f"(d[11]),"+f"(d[12]),"+f"(d[13]),"+f"(d[14]),"+f"(d[15]),"+f"(d[16]),"+f"(d[17]),"+f"(d[18]),"+f"(d[19]),"+f"(d[20]),"+f"(d[21]),"+f"(d[22]),"+f"(d[23]),"+f"(d[24]),"+f"(d[25]),"+f"(d[26]),"+f"(d[27]),"+f"(d[28]),"+f"(d[29]),"+f"(d[30]),"+f"(d[31]),"+f"(d[32]),"+f"(d[33]),"+f"(d[34]),"+f"(d[35]),"+f"(d[36]),"+f"(d[37]),"+f"(d[38]),"+f"(d[39]),"+f"(d[40]),"+f"(d[41]),"+f"(d[42]),"+f"(d[43]),"+f"(d[44]),"+f"(d[45]),"+f"(d[46]),"+f"(d[47]),"+f"(d[48]),"+f"(d[49]),"+f"(d[50]),"+f"(d[51]),"+f"(d[52]),"+f"(d[53]),"+f"(d[54]),"+f"(d[55]),"+f"(d[56]),"+f"(d[57]),"+f"(d[58]),"+f"(d[59]),"+f"(d[60]),"+f"(d[61]),"+f"(d[62]),"+f"(d[63]),"+f"(d[64]),"+f"(d[65]),"+f"(d[66]),"+f"(d[67]),"+f"(d[68]),"+f"(d[69]),"+f"(d[70]),"+f"(d[71]) : "l"(da), "l"(db), "n"(SC));
}
template<int SC> __device__ __forceinline__ void wg_ss96(float (&d)[48], uint64_t da, uint64_t db) {
  asm volatile("{\n.reg .pred p;\nsetp.ne.b32 p, %50, 0;\nwgmma.mma_async.sync.aligned.m64n96k16.f32.bf16.bf16 {%0,%1,%2,%3,%4,%5,%6,%7,%8,%9,%10,%11,%12,%13,%14,%15,%16,%17,%18,%19,%20,%21,%22,%23,%24,%25,%26,%27,%28,%29,%30,%31,%32,%33,%34,%35,%36,%37,%38,%39,%40,%41,%42,%43,%44,%45,%46,%47}, %48, %49, p, 1, 1, 0, 1;\n}\n"
    : "+f"(d[0]),"+f"(d[1]),"+f"(d[2]),"+f"(d[3]),"+f"(d[4]),"+f"(d[5]),"+f"(d[6]),"+f"(d[7]),"+f"(d[8]),"+f"(d[9]),"+f"(d[10]),"+f"(d[11]),"+f"(d[12]),"+f"(d[13]),"+f"(d[14]),"+f"(d[15]),"+f"(d[16]),"+f"(d[17]),"+f"(d[18]),"+f"(d[19]),"+f"(d[20]),"+f"(d[21]),"+f"(d[22]),"+f"(d[23]),"+f"(d[24]),"+f"(d[25]),"+f"(d[26]),"+f"(d[27]),"+f"(d[28]),"+f"(d[29]),"+f"(d[30]),"+f"(d[31]),"+f"(d[32]),"+f"(d[33]),"+f"(d[34]),"+f"(d[35]),"+f"(d[36]),"+f"(d[37]),"+f"(d[38]),"+f"(d[39]),"+f"(d[40]),"+f"(d[41]),"+f"(d[42]),"+f"(d[43]),"+f"(d[44]),"+f"(d[45]),"+f"(d[46]),"+f"(d[47]) : "l"(da), "l"(db), "n"(SC));
}
template<int SC> __device__ __forceinline__ void wg_rs112(float (&d)[56], uint32_t a0, uint32_t a1, uint32_t a2, uint32_t a3, uint64_t db) {
  asm volatile("{\n.reg .pred p;\nsetp.ne.b32 p, %61, 0;\nwgmma.mma_async.sync.aligned.m64n112k16.f32.bf16.bf16 {%0,%1,%2,%3,%4,%5,%6,%7,%8,%9,%10,%11,%12,%13,%14,%15,%16,%17,%18,%19,%20,%21,%22,%23,%24,%25,%26,%27,%28,%29,%30,%31,%32,%33,%34,%35,%36,%37,%38,%39,%40,%41,%42,%43,%44,%45,%46,%47,%48,%49,%50,%51,%52,%53,%54,%55}, {%56,%57,%58,%59}, %60, p, 1, 1, 0;\n}\n"
    : "+f"(d[0]),"+f"(d[1]),"+f"(d[2]),"+f"(d[3]),"+f"(d[4]),"+f"(d[5]),"+f"(d[6]),"+f"(d[7]),"+f"(d[8]),"+f"(d[9]),"+f"(d[10]),"+f"(d[11]),"+f"(d[12]),"+f"(d[13]),"+f"(d[14]),"+f"(d[15]),"+f"(d[16]),"+f"(d[17]),"+f"(d[18]),"+f"(d[19]),"+f"(d[20]),"+f"(d[21]),"+f"(d[22]),"+f"(d[23]),"+f"(d[24]),"+f"(d[25]),"+f"(d[26]),"+f"(d[27]),"+f"(d[28]),"+f"(d[29]),"+f"(d[30]),"+f"(d[31]),"+f"(d[32]),"+f"(d[33]),"+f"(d[34]),"+f"(d[35]),"+f"(d[36]),"+f"(d[37]),"+f"(d[38]),"+f"(d[39]),"+f"(d[40]),"+f"(d[41]),"+f"(d[42]),"+f"(d[43]),"+f"(d[44]),"+f"(d[45]),"+f"(d[46]),"+f"(d[47]),"+f"(d[48]),"+f"(d[49]),"+f"(d[50]),"+f"(d[51]),"+f"(d[52]),"+f"(d[53]),"+f"(d[54]),"+f"(d[55]) : "r"(a0), "r"(a1), "r"(a2), "r"(a3), "l"(db), "n"(SC));
}
template<int SC> __device__ __forceinline__ void wg_sp48(float (&d)[24], uint32_t a0, uint32_t a1, uint32_t a2, uint32_t a3, uint64_t db, uint32_t meta) {
  asm volatile("{\n.reg .pred p;\nsetp.ne.b32 p, %30, 0;\nwgmma.mma_async.sp.sync.aligned.m64n48k32.f32.bf16.bf16 {%0,%1,%2,%3,%4,%5,%6,%7,%8,%9,%10,%11,%12,%13,%14,%15,%16,%17,%18,%19,%20,%21,%22,%23}, {%24,%25,%26,%27}, %28, %29, 0, p, 1, 1, 1;\n}\n"
    : "+f"(d[0]),"+f"(d[1]),"+f"(d[2]),"+f"(d[3]),"+f"(d[4]),"+f"(d[5]),"+f"(d[6]),"+f"(d[7]),"+f"(d[8]),"+f"(d[9]),"+f"(d[10]),"+f"(d[11]),"+f"(d[12]),"+f"(d[13]),"+f"(d[14]),"+f"(d[15]),"+f"(d[16]),"+f"(d[17]),"+f"(d[18]),"+f"(d[19]),"+f"(d[20]),"+f"(d[21]),"+f"(d[22]),"+f"(d[23]) : "r"(a0), "r"(a1), "r"(a2), "r"(a3), "l"(db), "r"(meta), "n"(SC));
}
template<int SC> __device__ __forceinline__ void wg_rs64(float (&d)[32], uint32_t a0, uint32_t a1, uint32_t a2, uint32_t a3, uint64_t db) {
  asm volatile("{\n.reg .pred p;\nsetp.ne.b32 p, %37, 0;\nwgmma.mma_async.sync.aligned.m64n64k16.f32.bf16.bf16 {%0,%1,%2,%3,%4,%5,%6,%7,%8,%9,%10,%11,%12,%13,%14,%15,%16,%17,%18,%19,%20,%21,%22,%23,%24,%25,%26,%27,%28,%29,%30,%31}, {%32,%33,%34,%35}, %36, p, 1, 1, 0;\n}\n"
    : "+f"(d[0]),"+f"(d[1]),"+f"(d[2]),"+f"(d[3]),"+f"(d[4]),"+f"(d[5]),"+f"(d[6]),"+f"(d[7]),"+f"(d[8]),"+f"(d[9]),"+f"(d[10]),"+f"(d[11]),"+f"(d[12]),"+f"(d[13]),"+f"(d[14]),"+f"(d[15]),"+f"(d[16]),"+f"(d[17]),"+f"(d[18]),"+f"(d[19]),"+f"(d[20]),"+f"(d[21]),"+f"(d[22]),"+f"(d[23]),"+f"(d[24]),"+f"(d[25]),"+f"(d[26]),"+f"(d[27]),"+f"(d[28]),"+f"(d[29]),"+f"(d[30]),"+f"(d[31]) : "r"(a0), "r"(a1), "r"(a2), "r"(a3), "l"(db), "n"(SC));
}

constexpr uint32_t SBC = 1024;
constexpr int ROWB = 2 * 224 * 384;
constexpr int TB = 11;
constexpr int KS = 832;
constexpr int KSLOT = 22 * KS;
constexpr int SM_X2 = 0;
constexpr int SM_X0 = SM_X2 + 24576;
constexpr int SM_W = SM_X0 + 18432;
constexpr int SM_X1 = SM_W + 55296;
constexpr int SM_K = SM_X1 + 24576;
constexpr int SM_V = SM_K + 2 * KSLOT;
constexpr int SM_Q = SM_V + 22 * 1536;
constexpr int SM_O = SM_Q + 24576;
constexpr int SM_RPB = SM_O + 12288;
constexpr int SM_BAR = SM_RPB + 768;
constexpr int SM_A_TOTAL = SM_BAR + 256;
constexpr int SM_TIN = 0;
constexpr int SM_TST = 3 * 24576;
constexpr int SM_TWO = SM_TST + 12288;
enum { B_FULL = 0, B_EMPTY = 3, B_TIN = 6, B_TFREE = 10, B_WK = 12, B_WQ, B_WO, B_KIMP, B_VIMP, B_OFREE, B_XK, B_XV,
       B_Q0, B_WOFREE, B_OTAIL, B_ODONE = B_OTAIL + 4, B_KFREE, B_VFREE, B_COUNT };
enum { N_KRDY = 4, N_QK0, N_QK1, N_VQ0, N_VQ1, N_PVISS };

#define NL 2
#define OPT 0
#define OCH 4
#define MID 6
#define SPL 4
#define RA 160
#define RG 168
__device__ int g_flags[TB * 56];

#define TR(role, it, k)
#define TRDECL
#define TRARG
#define TRPASS
#define TRDUMP
#define TRB(it, k)
#define TR2(blk, k)

struct GemmCtx {
  uint32_t bar;
  uint32_t kC, vC[2], qC[2];
  uint32_t kH, vH[2];
  uint32_t hiA, hiB;
  uint32_t spin;
  uint32_t em[3];
  bool hvalid, never, edge;
};

template <int STRIDE> __device__ __forceinline__ void dump12(uint32_t a, const uint32_t (&r)[12]) {
#pragma unroll
  for (int j = 0; j < 3; j++) stsm4(a + j * 2 * STRIDE, r[4 * j], r[4 * j + 1], r[4 * j + 2], r[4 * j + 3]);
}
__device__ __forceinline__ void keep12(bool never, uint32_t a, const uint32_t (&r)[12]) { if (never) dump12<128>(a, r); }
template <int N> __device__ __forceinline__ void pack12(uint32_t (&r)[12], const float (&d)[N], int off) {
#pragma unroll
  for (int j = 0; j < 12; j++) r[j] = pack2(d[off + 2 * j], d[off + 2 * j + 1]);
}
__device__ __forceinline__ uint64_t dsc(uint64_t lo, uint32_t hi) { uint64_t r; asm("mov.b64 %0, {%1, %2};" : "=l"(r) : "r"((uint32_t)lo), "r"(hi)); return r; }
template <int XS, int K0, int K1> __device__ __forceinline__ void issue_core(const GemmCtx& c, float (&d)[72]) {
  constexpr uint64_t da = mkdesc(SBC + XS, 16, 1024, 1), db = mkdesc(SBC + SM_W, 6144, 256, 3);
  wg_fence();
  if (K0 == 0) wg_ss144<0>(d, dsc(da, c.hiA), dsc(db, c.hiB));
#pragma unroll
  for (int k = K0 ? K0 : 1; k < K1; k++) wg_ss144<1>(d, dsc(da + (k >> 2) * 512 + (k & 3) * 2, c.hiA), dsc(db + k * 32, c.hiB));
  wg_commit();
}
template <int K0, int K1> __device__ __forceinline__ void issue_halo(const GemmCtx& c, float (&d)[48]) {
  constexpr uint64_t da = mkdesc(SBC + SM_X0 - 2048, 16, 1024, 1), db = mkdesc(SBC + SM_W, 6144, 256, 3);
  wg_fence();
  if (K0 == 0) wg_ss96<0>(d, dsc(da, c.hiA), dsc(db, c.hiB));
#pragma unroll
  for (int k = K0 ? K0 : 1; k < K1; k++) wg_ss96<1>(d, dsc(da + (k >> 2) * 384 + (k & 3) * 2, c.hiA), dsc(db + k * 32, c.hiB));
  wg_commit();
}
template <int ST> __device__ __forceinline__ void release_stage(const GemmCtx& c) {
  asm volatile("{\n.reg .pred p;\nelect.sync _|p, 0xffffffff;\n@p mbarrier.arrive.shared::cluster.b64 _, [%0];\n}" ::"r"(c.em[ST]) : "memory");
}
__device__ __forceinline__ void edge_ready(const GemmCtx& c, int bar) { __syncwarp(); if (c.edge) mbar_arrive_elect(c.bar + bar * 8); }
__device__ __forceinline__ void dump6(uint32_t a, const uint32_t (&r)[6]) {
  stsm4(a, r[0], r[1], r[2], r[3]);
  asm volatile("stmatrix.sync.aligned.m8n8.x2.shared.b16 [%0], {%1,%2};" ::"r"(a + 512), "r"(r[4]), "r"(r[5]) : "memory");
}
__device__ __forceinline__ void pack6(uint32_t (&r)[6], const float (&d)[48], int off) {
#pragma unroll
  for (int j = 0; j < 6; j++) r[j] = pack2(d[off + 4 * j], d[off + 4 * j + 1]);
}
template <int PARITY> __device__ __forceinline__ void gwait(GemmCtx& c, int bar) {
  asm volatile("{\n.reg .pred p;\nWL:\nmbarrier.try_wait.parity.shared::cta.b64 p, [%1], %2;\n@p bra WD;\n"
               "add.u32 %0, %0, 1;\nsetp.lt.u32 p, %0, 0x100000;\n@p bra WL;\nWD:\n}" : "+r"(c.spin) : "r"(c.bar + bar * 8), "n"(PARITY) : "memory");
}
__device__ __forceinline__ void load_w(const CUtensorMap* m, uint32_t dst, uint32_t bar, int col) {
  asm volatile("cp.async.bulk.tensor.2d.shared::cluster.global.mbarrier::complete_tx::bytes [%0], [%1, {%3,%4}], [%2];"
               ::"r"(dst), "l"(m), "r"(bar), "r"(col), "r"(0) : "memory");
}
template <int BYTES> __device__ __forceinline__ void send_o(uint32_t dst, uint32_t src, uint32_t bar, int cta) {
  asm volatile("{\n.reg .b32 rd, rb;\nmapa.shared::cluster.u32 rd, %0, %3;\nmapa.shared::cluster.u32 rb, %2, %3;\n"
               "cp.async.bulk.shared::cluster.shared::cta.mbarrier::complete_tx::bytes [rd], [%1], %4, [rb];\n}"
               ::"r"(dst), "r"(src), "r"(bar), "r"(cta), "n"(BYTES) : "memory");
}
__device__ __forceinline__ void remote_arrive(uint32_t rbar) { asm volatile("mbarrier.arrive.shared::cluster.b64 _, [%0];" ::"r"(rbar) : "memory"); }
__device__ __forceinline__ void remote_expect(uint32_t rbar, uint32_t bytes) {
  asm volatile("mbarrier.arrive.expect_tx.shared::cluster.b64 _, [%0], %1;" ::"r"(rbar), "r"(bytes) : "memory");
}
__device__ __forceinline__ void copy_remote(uint32_t rdst, uint32_t src, uint32_t bytes, uint32_t rbar) {
  asm volatile("cp.async.bulk.shared::cluster.shared::cta.mbarrier::complete_tx::bytes [%0], [%1], %2, [%3];" ::"r"(rdst), "r"(src), "r"(bytes), "r"(rbar) : "memory");
}
__device__ __forceinline__ void tail_free(uint32_t bar) {
  uint32_t ln; asm volatile("mov.u32 %0, %%laneid;" : "=r"(ln));
  if (ln < 4) mbar_arrive_remote(bar, ln + (blockIdx.x & 4));
}
__device__ __forceinline__ void publish(uint32_t bar) {
  fence_async();
  __syncwarp();
  mbar_arrive_elect(bar);
}

template <bool FIRST, int PA>
__device__ __forceinline__ void gemm_iter(GemmCtx& c, int b, uint32_t (&pk)[12], uint32_t (&pv)[12], uint32_t (&pq)[12],
                                          uint32_t (&hk1)[6], uint32_t (&hv1)[6] TRARG) {
  const uint32_t bar = c.bar;
  const bool w = !FIRST && (PA == 0 || b >= 0), never = c.never;
  constexpr uint32_t ko = PA * KSLOT;
  float C[72];
  uint32_t hk0[6], hv0[6], pv2[12];
  TR(2, b, 0);
  if (FIRST) gwait<0>(c, B_FULL + 0);
  else dump12<256>(c.qC[1] + (PA ^ 1) * 128, pq);
  if (w) nb_sync(N_QK1, 256);
  TR(2, b, 2);
  if (PA == 0) {
    float H[48];
    issue_halo<0, 8>(c, H);
    TR(2, b, 3);
    if (!FIRST) { gwait<0>(c, B_KFREE); dump12<128>(c.kC, pk); }
    issue_halo<8, 12>(c, H);
    TR(2, b, 4);
    gwait<0>(c, B_FULL + 2);
    if (FIRST) gwait<0>(c, B_WQ);
    issue_core<SM_X2, 0, 8>(c, C);
    TR(2, b, 5);
    if (!FIRST) { fence_async(); keep12(never, c.kC, pk); }
    wg_wait<1>(); pin(H);
    release_stage<0>(c);
    pack6(hk0, H, 0);
    if (c.hvalid) dump6(c.kH, hk0);
    pack6(hk1, H, 2); pack6(hv0, H, 24); pack6(hv1, H, 26);
  } else {
    issue_core<SM_X2, 0, 8>(c, C);
    TR(2, b, 5);
    fence_async();
    keep12(never, c.kC, pq);
    if (w) gwait<1>(c, B_KFREE);
    dump12<128>(c.kC + ko, pk);
    if (c.hvalid) dump6(c.kH + ko, hk1);
  }
  TR(2, b, 13);
  issue_core<SM_X2, 8, 12>(c, C);
  if (w) { nb_arrive(N_VQ0, 288); nb_arrive(N_VQ1, 288); }
  else if (!FIRST) { __syncwarp(); mbar_arrive_elect(bar + B_Q0 * 8); }
  gwait<PA>(c, B_FULL + 1);
  if (never) dump6(bar, PA ? hk1 : hk0);
  TR(2, b, 6);
  wg_wait<0>(); pin(C);
  TR(2, b, 7);
  release_stage<2>(c);
  pack12(pk, C, 0);
  dump12<128>(c.kC + ko + 64, pk);
  pack12(pv2, C, 24);
  pack12(pq, C, 48);
  TR(2, b, 8);
  issue_core<SM_X1, 0, SPL>(c, C);
  TR(2, b, 9);
  if (!FIRST) { fence_async(); edge_ready(c, B_XK); }
  keep12(never, c.kC, pk);
  TR(2, b, 14);
  if (w) nb_sync(N_PVISS, 384);
  issue_core<SM_X1, SPL, 12>(c, C);
  if (!FIRST) nb_arrive(N_KRDY, 256);
  TR(2, b, 1);
  if (PA) { if (b == 11) tail_free(bar + B_TFREE * 8); mbar_wait(bar + B_FULL * 8, ((b + 3) >> 1) & 1); }
  if (w) gwait<PA>(c, B_VFREE);
  if (w && b < TB) gwait<PA>(c, B_ODONE);
  TR(2, b, 10);
  if (!FIRST) dump12<128>(c.vC[PA], pv);
  dump12<128>(c.vC[PA ^ 1] + 768, pv2);
  TR(2, b, 11);
  wg_wait<0>(); pin(C);
  TR(2, b, 12);
  release_stage<1>(c);
  if (!FIRST && c.edge) publish(bar + B_XV * 8);
  if (PA == 0) gwait<1>(c, B_FULL + 2);
  if (c.hvalid) dump6(c.vH[PA], PA ? hv1 : hv0);
  dump12<256>(c.qC[0] + PA * 128, pq);
  pack12(pk, C, 0);
  pack12(pv, C, 24);
  pack12(pq, C, 48);
}

template <int IN> __device__ __forceinline__ void issue_proj(float (&D)[48]) {
  constexpr uint64_t da = mkdesc(SBC + IN, 128, 768, 0), db = mkdesc(SBC + SM_TWO, 12288, 512, 2);
  wg_fence();
  wg_ss96<0>(D, da, db);
#pragma unroll
  for (int k = 1; k < 12; k++) wg_ss96<1>(D, da + (k / 3) * 384 + (k % 3) * 16, db + k * 64);
  wg_commit();
}
template <int ACC> __device__ __forceinline__ void issue_proj_half(float (&D)[48], int hd) {
  const uint64_t da = mkdesc(SBC + SM_TIN + 2 * 24576, 128, 768, 0) + hd * 384, db = mkdesc(SBC + SM_TWO, 12288, 512, 2) + hd * 192;
  wg_fence();
  wg_ss96<ACC>(D, da, db);
#pragma unroll
  for (int k = 1; k < 6; k++) wg_ss96<1>(D, da + (k / 3) * 768 + (k % 3) * 16, db + (k / 3) * 384 + (k % 3) * 64);
  wg_commit();
}
__device__ __forceinline__ void store_proj(const float (&D)[48], const CUtensorMap* m, uint32_t st, uint32_t sta, int row, int col, int ch) {
#pragma unroll
  for (int q = 0; q < 6; q++)
    stsm4((sta ^ ((q & 1) * 32)) + (q >> 1) * 1024,
          pack2(D[8 * q], D[8 * q + 1]), pack2(D[8 * q + 2], D[8 * q + 3]), pack2(D[8 * q + 4], D[8 * q + 5]), pack2(D[8 * q + 6], D[8 * q + 7]));
  fence_async();
  __syncwarp();
  if ((threadIdx.x & 31) == 0) {
    asm volatile("cp.async.bulk.tensor.4d.global.shared::cta.bulk_group [%0, {%2,%3,%4,%5}], [%1];" ::"l"(m), "r"(st), "r"(0), "r"(row), "r"(col), "r"(ch) : "memory");
    asm volatile("cp.async.bulk.commit_group;" ::: "memory");
  }
  __syncwarp();
}

__device__ __forceinline__ float fold(float a, float b, float t, int useb) {
  float r;
  asm("{\n.reg .pred p;\nsetp.ne.b32 p, %4, 0;\nfma.rn.f32 %0, %1, 0f3E553B95, %3;\n@p fma.rn.f32 %0, %2, 0f3E553B95, %3;\n}"
      : "=&f"(r) : "f"(a), "f"(b), "f"(t), "r"(useb));
  return r;
}
template <int U, int L>
__device__ __forceinline__ void softmax_tile(const float (&SA)[56], const float (&SB)[56], const float (&T)[16], int b0, int b1,
                                             uint32_t (&P)[28], float (&sx)[8], uint32_t nbV, uint32_t zero, uint32_t qa, uint32_t (&q)[12]) {
  float lu[14], ll[14];
#pragma unroll
  for (int j = 0; j < 7; j++) {
    constexpr int sh = U == L ? 2 : 0;
    const float tu0 = T[2 * j + sh], tu1 = T[2 * j + 1 + sh], tl0 = T[2 * j], tl1 = T[2 * j + 1];
    lu[2 * j]     = fold(SA[4 * (U + j)],     SB[4 * (U + j)],     tu0, b0);
    ll[2 * j]     = fold(SA[4 * (L + j) + 2], SB[4 * (L + j) + 2], tl0, b0);
    lu[2 * j + 1] = fold(SA[4 * (U + j) + 1], SB[4 * (U + j) + 1], tu1, b1);
    ll[2 * j + 1] = fold(SA[4 * (L + j) + 3], SB[4 * (L + j) + 3], tl1, b1);
  }
  float mu = lu[0], ml = ll[0], mu2 = lu[1], ml2 = ll[1];
#pragma unroll
  for (int j = 1; j < 7; j++) { mu = fmaxf(mu, lu[2 * j]); mu2 = fmaxf(mu2, lu[2 * j + 1]); ml = fmaxf(ml, ll[2 * j]); ml2 = fmaxf(ml2, ll[2 * j + 1]); }
  mu = fmaxf(mu, mu2); ml = fmaxf(ml, ml2);
  { const float a1 = __shfl_xor_sync(0xffffffffu, mu, 1), a2 = __shfl_xor_sync(0xffffffffu, mu, 2), a3 = __shfl_xor_sync(0xffffffffu, mu, 3);
    const float c1 = __shfl_xor_sync(0xffffffffu, ml, 1), c2 = __shfl_xor_sync(0xffffffffu, ml, 2), c3 = __shfl_xor_sync(0xffffffffu, ml, 3);
    mu = fmaxf(fmaxf(mu, a1), fmaxf(a2, a3)); ml = fmaxf(fmaxf(ml, c1), fmaxf(c2, c3)); }
  float su = 0.f, sl = 0.f;
#pragma unroll
  for (int c = 0; c < 14; c++) {
    if (c >= U && c < U + 7) {
      float e0 = ex2(lu[2 * (c - U)] - mu), e1 = ex2(lu[2 * (c - U) + 1] - mu);
      su = c == U ? e0 + e1 : (su + e0) + e1; P[2 * c] = pack2(e0, e1);
    } else P[2 * c] = 0u;
  }
  nb_sync(nbV | (P[2 * (U + MID)] & zero), 288);
#pragma unroll
  for (int k = 0; k < 3; k++) ldsm4(qa + k * 512, q[4 * k], q[4 * k + 1], q[4 * k + 2], q[4 * k + 3]);
#pragma unroll
  for (int c = 0; c < 14; c++) {
    if (c >= L && c < L + 7) {
      float e0 = ex2(ll[2 * (c - L)] - ml), e1 = ex2(ll[2 * (c - L) + 1] - ml);
      sl = c == L ? e0 + e1 : (sl + e0) + e1; P[2 * c + 1] = pack2(e0, e1);
    } else P[2 * c + 1] = 0u;
  }
  sx[0] = su; sx[4] = sl;
#pragma unroll
  for (int k = 1; k < 4; k++) sx[k] = __shfl_xor_sync(0xffffffffu, su, k);
#pragma unroll
  for (int k = 1; k < 4; k++) sx[4 + k] = __shfl_xor_sync(0xffffffffu, sl, k);
}

struct BandCfg { uint32_t ra0, ra1, meta; int b0, b1; };
__device__ __forceinline__ void band_cfg(int b, uint32_t tb, BandCfg& n) {
  uint32_t ln; asm volatile("mov.u32 %0, %%laneid;" : "=r"(ln));
  const int g = ln >> 2, t = ln & 3;
  const int sw = min(max(g + 1, b == 0 ? 4 : 0), b == 13 ? 5 : 8);
  const int i0 = 2 * t, i1 = 2 * t + 1;
  n.b0 = i0 <= sw - 2; n.b1 = i1 <= sw - 2;
  n.ra0 = tb + (i0 == sw - 1 ? 13 : i0 + 8 * n.b0 - g + 2) * 52;
  n.ra1 = tb + (i1 == sw - 1 ? 13 : i1 + 8 * n.b1 - g + 2) * 52;
  n.meta = ((0x5555u & ((1u << (2 * (sw - 1))) - 1)) ^ 0xDD88u ^ (((t ^ b) & 1) ? 0x5555u : 0u)) * 0x10001u;
}
__device__ __forceinline__ void band_load(const BandCfg& n, float (&T)[16], int& b0, int& b1, uint32_t& meta) {
#pragma unroll
  for (int jj = 0; jj < 8; jj++) { T[2 * jj] = lds_f32(n.ra0 + jj * 4); T[2 * jj + 1] = lds_f32(n.ra1 + jj * 4); }
  b0 = n.b0; b1 = n.b1; meta = n.meta;
}

struct Maps { CUtensorMap xc, xh, w, os, wo, ot; };

__global__ void __cluster_dims__(8, 1, 1) __launch_bounds__(512, 1)
na_attn_kernel(const __nv_bfloat16* __restrict__ x, const __nv_bfloat16* __restrict__ wqkv, const __nv_bfloat16* __restrict__ rpb, const __grid_constant__ Maps mp) {
  extern __shared__ __align__(1024) uint8_t smem_raw[];
  const uint32_t sb = smem_u32(smem_raw);
  if ((sb & 0x3FFFF) != SBC) return;
  const uint32_t bar = sb + SM_BAR;
  TR2(blockIdx.x, 0);
  const int tid = threadIdx.x, lane = tid & 31;
  const int warp = __shfl_sync(0xffffffffu, tid >> 5, 0);
  const int head = blockIdx.x & 3, base = blockIdx.x & 4, sp = blockIdx.x >> 2;
  const int par = sp < 24 ? sp / 6 : sp - 24, strip = sp < 24 ? sp - par * 6 : 6, ph = par >> 1, pw = par & 1;
  const int odd = strip & 1;

  uint4 wv[2 * NL];
  const int va = head == 1;
  const uint32_t wdst = sb + SM_W + (va + ((tid >> 1) & 1)) * 6144 + (tid >> 2) * 32 + ((tid ^ (tid >> 4)) & 1) * 16;
  if (warp < 12) asm volatile("barrier.cluster.arrive.relaxed.aligned;" ::: "memory");
  {
    const uint32_t wo0 = (tid >> 2) * 1152 + head * 96 + va * 32 + (tid & 3) * 16;
#pragma unroll
    for (int i = 0; i < 2 * NL; i++)
      asm volatile("{\n.reg .pred p;\nsetp.lt.u32 p, %5, 384;\n@p ld.global.nc.v4.b32 {%0,%1,%2,%3}, [%4];\n}"
                   : "=r"(wv[i].x), "=r"(wv[i].y), "=r"(wv[i].z), "=r"(wv[i].w)
                   : "l"(reinterpret_cast<const uint8_t*>(wqkv) + wo0 + (i & 1) * 96 * 1152 + ((i / 2 + 1) % 3) * 384), "r"(tid));
  }
  if (warp < 8) {
    asm volatile("setmaxnreg.inc.sync.aligned.u32 %0;" ::"n"(RA));
    float rv = -INFINITY;
    if (tid < 169) rv = __bfloat162float(rpb[head * 169 + tid]) * 1.4426950408889634f;
    if (tid < 192) {
      const int kc = (tid & 15) + 3, wc = (tid >> 4) % 6;
      sts128(tid < 96 ? sb + SM_K + kc * KS + wc * 128 + 48 : sb + SM_V + kc * 1536 + wc * 128 + (6 + (kc & 1)) * 16, make_uint4(0, 0, 0, 0));
    }
#pragma unroll
    for (int i = 0; i < 2 * NL; i++) sts128(wdst + (i & 1) * 3072 + (i / 2) * 18432, wv[i]);
    fence_async();
    asm volatile("bar.arrive 1, 384;" ::: "memory");
    if (tid < 182) asm volatile("st.shared.f32 [%0], %1;" ::"r"(sb + SM_RPB + tid * 4), "f"(rv) : "memory");
    const int jw = warp >> 2, j = jw ^ odd, w = warp & 3, wt = 4 * j + w;
    int variant = w;
    if (strip == 0 && j == 0 && w < 2) variant = 4;
    if (strip == 6 && j == 1 && w >= 2) variant = 5;
    const bool v1 = opq((uint32_t)(variant & 1)), v2 = opq((uint32_t)(variant & 2)), v4 = opq((uint32_t)(variant & 4));
    uint32_t qa = opq(sb + SM_Q + (8 * j + 2 * w + ((lane >> 3) & 1)) * 1536 + (lane >> 4) * 256 + (((lane & 7) * 16) ^ (((lane >> 3) & 1) * 64)));
    uint32_t oa = opq(sb + SM_O + j * 6144 + (2 * w + ((lane >> 3) & 1)) * 768 + (lane >> 4) * 128 + (lane & 7) * 16);
    uint64_t dA = opq(mkdesc(SBC + SM_K, 128, KS, 0) + j * (8 * KS / 16)), dB = opq(dA + (KSLOT >> 4));
    uint64_t dV[7];
#pragma unroll
    for (int i = 0; i < 7; i++) dV[i] = opq(mkdesc(SBC + SM_V, 768, 128, 0) + j * (8 * 1536 / 16) + i * 192);
    const uint32_t nbK = opq((uint32_t)(N_KRDY + jw)), nbQ = opq((uint32_t)(N_QK0 + jw)), nbV = opq((uint32_t)(N_VQ0 + jw));
    asm volatile("barrier.cluster.wait.aligned;" ::: "memory");
    asm volatile("bar.sync 3, 256;" ::: "memory");
    float T[16];
    TRDECL;
    int b0, b1;
    uint32_t meta, ob = bar + B_ODONE * 8, fb = bar + B_OFREE * 8, fp = 1;
    const uint32_t tb = opq(sb + SM_RPB + (variant < 4 ? 3 : variant + 1 - 2 * w) * 4);
    const bool own = ((w ^ head) & 2) == 0;
    const uint32_t dst13 = sb + SM_TIN + 2 * 24576 + head * 6144 + (2 * j + (w & 1)) * 1536, src13 = opq(own ? dst13 : sb + SM_Q + wt * 3072 + 1536);
    const uint32_t snd[4] = {opq(own ? 0u : mapa(dst13, base + (head ^ 2))), opq(mapa(bar + (B_TIN + 2) * 8, base + (head ^ 2))),
                             opq(mapa(dst13, base + (w & 2) + (~head & 1))), opq(mapa(bar + (B_TIN + 3) * 8, base + (w & 2) + (~head & 1)))};
    BandCfg nx;
    band_cfg(0, tb, nx);
    band_load(nx, T, b0, b1, meta);
    band_cfg(1, tb, nx);
    const uint32_t zero = opq(blockIdx.x >> 16);
    uint32_t special = opq(0x380Au << 1);
    uint32_t q[12];
    mbar_wait(bar + B_Q0 * 8, 0);
#pragma unroll
    for (int k = 0; k < 3; k++) ldsm4(qa + k * 512, q[4 * k], q[4 * k + 1], q[4 * k + 2], q[4 * k + 3]);
    qa ^= 128;
#pragma unroll 1
    for (int b = 0; b < 14; b++) {
      float SA[56], SB[56];
      TR(0, b, 0);
      if (jw) mbar_wait(bar + B_KIMP * 8, b & 1);
      nb_sync(nbK, 256);
      TR(0, b, 1);
      TR(0, b - 1, 9);
      wg_fence();
      wg_rs112<0>(SA, q[0], q[1], q[2], q[3], dA);
      wg_rs112<0>(SB, q[0], q[1], q[2], q[3], dB);
      wg_rs112<1>(SA, q[4], q[5], q[6], q[7], dA + 16);
      wg_rs112<1>(SB, q[4], q[5], q[6], q[7], dB + 16);
      wg_rs112<1>(SA, q[8], q[9], q[10], q[11], dA + 32);
      wg_rs112<1>(SB, q[8], q[9], q[10], q[11], dB + 32);
      wg_commit();
      nb_arrive(nbQ, 256);
      { const uint64_t t = dA; dA = dB; dB = t; }
      special >>= 1;
      if (special & 1) {
        if (b == 3) band_cfg(13, tb, nx);
        else {
          if (b == 1 || b == 13) band_load(nx, T, b0, b1, meta);
          if (b >= TB) {
            ob = bar + (b == 13 ? (own ? B_TIN + 2 : B_ODONE) : B_OTAIL + 2 * (b - TB) + jw) * 8;
            if (b > TB) { fb = bar + (B_TFREE + b - 12) * 8; fp = 0; }
            oa += b == 12 ? wt * 1536 - (SM_O - SM_Q) : (b == 13 ? src13 - (sb + SM_Q + wt * 3072) : 0);
          }
        }
      }
      TR(0, b, 2);
      wg_wait<0>(); pin(SA); pin(SB);
      mbar_arrive_elect(bar + B_KFREE * 8);
      TR(0, b, 3);
      TR(0, b - 1, 10);
      uint32_t P[28];
      float sx[8];
      if (v2) {
        if (v1) softmax_tile<6, 7>(SA, SB, T, b0, b1, P, sx, nbV, zero, qa, q); else softmax_tile<4, 5>(SA, SB, T, b0, b1, P, sx, nbV, zero, qa, q);
      } else if (!v4) {
        if (v1) softmax_tile<2, 3>(SA, SB, T, b0, b1, P, sx, nbV, zero, qa, q); else softmax_tile<0, 1>(SA, SB, T, b0, b1, P, sx, nbV, zero, qa, q);
      } else {
        if (v1) softmax_tile<4, 4>(SA, SB, T, b0, b1, P, sx, nbV, zero, qa, q); else softmax_tile<3, 3>(SA, SB, T, b0, b1, P, sx, nbV, zero, qa, q);
      }
      float O[24];
      TR(0, b, 4);
      wg_fence();
      wg_sp48<0>(O, P[0], P[1], P[2], P[3], dV[0], meta);
#pragma unroll
      for (int s = 1; s < 7; s++) wg_sp48<1>(O, P[4 * s], P[4 * s + 1], P[4 * s + 2], P[4 * s + 3], dV[s], meta);
      wg_commit();
      nb_arrive(N_PVISS, 384);
      TR(0, b, 6);
      mbar_wait(fb, fp);
      wg_wait<0>(); pin(O);
      mbar_arrive_elect(bar + B_VFREE * 8);
      TR(0, b, 7);
      float ru, rl;
      asm("rcp.approx.ftz.f32 %0, %1;" : "=f"(ru) : "f"(((fmaf(O[0], 0.f, sx[0]) + sx[1]) + sx[2]) + sx[3]));
      asm("rcp.approx.ftz.f32 %0, %1;" : "=f"(rl) : "f"(((fmaf(O[2], 0.f, sx[4]) + sx[5]) + sx[6]) + sx[7]));
#pragma unroll
      for (int i = 0; i < 3; i++)
        stsm4(oa + i * 256, pack2(O[8 * i] * ru, O[8 * i + 1] * ru), pack2(O[8 * i + 2] * rl, O[8 * i + 3] * rl),
              pack2(O[8 * i + 4] * ru, O[8 * i + 5] * ru), pack2(O[8 * i + 6] * rl, O[8 * i + 7] * rl));
      publish(ob);
      qa ^= 128; fp ^= 1;
      meta ^= 0x55555555u;
      TR(0, b, 8);
    }
    asm volatile("{\n.reg .pred p, q;\nsetp.ne.b32 q, %1, 0;\nelect.sync _|p, 0xffffffff;\nand.pred q, q, p;\n"
                 "@q cp.async.bulk.shared::cluster.shared::cta.mbarrier::complete_tx::bytes [%1], [%0], 1536, [%2];\n"
                 "@p cp.async.bulk.shared::cluster.shared::cta.mbarrier::complete_tx::bytes [%3], [%0], 1536, [%4];\n}"
                 ::"r"(src13), "r"(snd[0]), "r"(snd[1]), "r"(snd[2]), "r"(snd[3]) : "memory");
    if (jw == 0) nb_arrive(3, 256);
    TRDUMP;
    cluster_sync();
  } else if (warp < 12) {
    TRDECL;
    TR(2, -3, 0);
    asm volatile("setmaxnreg.inc.sync.aligned.u32 %0;" ::"n"(RG));
    TR(2, -3, 1);
    GemmCtx c;
    c.bar = bar;
    const int gw = warp - 8, tk = gw * 16 + (lane & 15), hi = lane >> 4;
    { const int col = tk >> 2, i = tk & 3;
      c.kC = sb + SM_K + (col + 3) * KS + hi * 128 + i * 16;
      c.vC[0] = sb + SM_V + (col + 3) * 1536 + hi * 128 + (2 * i + ((col + 3) & 1)) * 16;
      c.qC[0] = sb + SM_Q + col * 1536 + hi * 256 + (col & 1) * 64 + i * 16; }
    { const int kc = gw - 1 + 19 * odd, i = lane & 7; c.hvalid = gw > 0; c.edge = gw == (odd ? 0 : 3);
      c.kH = sb + SM_K + kc * KS + (lane >> 3) * 128 + i * 16;
      c.vH[0] = sb + SM_V + kc * 1536 + (lane >> 3) * 128 + (i >> 2) * 768 + (2 * (i & 3) + ((kc ^ (i >> 2)) & 1)) * 16; }
#pragma unroll
    for (int i = 0; i < 3; i++) c.em[i] = opq(mapa(bar + (B_EMPTY + i) * 8, base + i));
    c.never = x == nullptr;
    c.kC = opq(c.kC); c.kH = opq(c.kH);
    c.vC[1] = opq(c.vC[0] ^ 16); c.vC[0] = opq(c.vC[0]);
    c.vH[1] = opq(c.vH[0] ^ 16); c.vH[0] = opq(c.vH[0]);
    c.qC[1] = opq(c.qC[0] ^ 64); c.qC[0] = opq(c.qC[0]);
    c.spin = 0;
    c.hiA = (uint32_t)(mkdesc(0, 0, 1024, 1) >> 32) + (blockIdx.x >> 16); c.hiB = (uint32_t)(mkdesc(0, 0, 256, 3) >> 32) + (blockIdx.x >> 16);
    asm volatile("barrier.cluster.wait.aligned;" ::: "memory");
    TR(2, -3, 2);
#pragma unroll
    for (int i = 0; i < 2 * NL; i++) sts128(wdst + (i & 1) * 3072 + (i / 2) * 18432, wv[i]);
    fence_async();
    TR(2, -3, 3);
    asm volatile("bar.sync 1, 384;" ::: "memory");
    TR(2, -3, 4);
    mbar_wait(bar + B_WK * 8, 0);
    TR(2, -3, 5);
    uint32_t pk[12], pv[12], pq[12], hk1[6], hv1[6];
    gemm_iter<true, 0>(c, -2, pk, pv, pq, hk1, hv1 TRPASS);
    TR2(blockIdx.x, 4);
    c.hiA = opq(c.hiA); c.hiB = opq(c.hiB);
#pragma unroll 1
    for (int b = -1;; b += 2) {
      gemm_iter<false, 1>(c, b, pk, pv, pq, hk1, hv1 TRPASS);
      if (b == 11) break;
      gemm_iter<false, 0>(c, b + 1, pk, pv, pq, hk1, hv1 TRPASS);
    }
    TR2(blockIdx.x, 6);
    c.hiA = opq(c.hiA); c.hiB = opq(c.hiB);
    const uint32_t st = sb + gw * 3072;
    const uint32_t sta = st + (lane & 15) * 64 + ((hi ^ ((lane >> 1) & 3)) * 16);
    const int oc = ph * 112 + strip * 16 + 8 * (gw >> 1) + 4 * (head >> 1) + 2 * (gw & 1), och = pw * 6 + (head & 1) * 3;
    float D0[48], D1[48];
    mbar_arrive_elect(bar + B_WOFREE * 8);
    dump12<256>(c.qC[1] + 128, pq);
    nb_sync(N_QK1, 256);
    issue_halo<0, 12>(c, D1);
    gwait<0>(c, B_KFREE);
    dump12<128>(c.kC, pk);
    fence_async();
    edge_ready(c, B_XK);
    nb_arrive(N_VQ0, 288); nb_arrive(N_VQ1, 288); nb_arrive(N_PVISS, 384);
    wg_wait<0>(); pin(D1);
    pack6(hk1, D1, 0);
    if (c.hvalid) dump6(c.kH, hk1);
    tail_free(bar + (B_TFREE + 1) * 8);
    pack6(hv1, D1, 24);
    fence_async();
    nb_arrive(N_KRDY, 256);
    gwait<0>(c, B_VFREE);
    dump12<128>(c.vC[0], pv);
    if (c.hvalid) dump6(c.vH[0], hv1);
    fence_async();
    edge_ready(c, B_XV);
    nb_arrive(N_VQ0, 288); nb_arrive(N_VQ1, 288);
    gwait<0>(c, B_WO);
    gwait<0>(c, B_TIN);
    TR(2, 13, 0);
    nb_sync(N_QK1, 256);
    issue_proj<SM_TIN>(D0);
    wg_wait<0>(); pin(D0);
    TR(2, 13, 1);
    store_proj(D0, &mp.ot, st + SM_TST, sta + SM_TST, 8 * TB, oc, och);
    gwait<0>(c, B_TIN + 1);
    TR(2, 13, 2);
    nb_sync(N_PVISS, 384);
    nb_sync(3, 256);
    issue_proj<SM_TIN + 24576>(D1);
    wg_wait<0>(); pin(D1);
    TR(2, 13, 3);
    store_proj(D1, &mp.ot, st + SM_TIN, sta + SM_TIN, 8 * TB + 8, oc, och);
    TR(2, 13, 4);
    gwait<0>(c, B_TIN + 2);
    TR(2, 13, 5);
    issue_proj_half<0>(D0, head & 1);
    gwait<0>(c, B_TIN + 3);
    TR(2, 13, 6);
    issue_proj_half<1>(D0, ~head & 1);
    asm volatile("barrier.cluster.arrive.relaxed.aligned;" ::: "memory");
    wg_wait<0>(); pin(D0);
    store_proj(D0, &mp.ot, st + SM_TIN + 12288, sta + SM_TIN + 12288, 8 * TB + 16, oc, och);
    TR(2, 13, 7);
    if (lane == 0) asm volatile("cp.async.bulk.wait_group.read 0;" ::: "memory");
    __syncwarp();
    TR(2, 13, 8);
    TR2(blockIdx.x, 2);
    TRDUMP;
    asm volatile("barrier.cluster.wait.aligned;" ::: "memory");
  } else {
    if (warp == 12) {
      if (elect_one()) {
        mbar_init(bar + B_WK * 8, 1);
#pragma unroll
        for (int i = 0; i < NL; i++) load_w(&mp.w, sb + SM_W + (3 * i + 2 - 2 * va) * 6144, bar + B_WK * 8, ((i + 1) % 3) * 192 + head * 48 + 32 - 32 * va);
        asm volatile("prefetch.tensormap [%0];" ::"l"(head ? &mp.xc : &mp.xh) : "memory");
        mbar_expect(bar + B_WK * 8, NL * 6144);
      }
    } else if (warp == 15) {
      const int col = min(max(strip * 16 - 3 + min(lane, 21), 0), 111);
      const uint8_t* p = reinterpret_cast<const uint8_t*>(x) + (uint32_t)(head * ROWB + (ph * 112 + col) * 768 + pw * 384);
#pragma unroll
      for (int i = 0; i < 3; i++) asm volatile("prefetch.global.L2 [%0];" ::"l"(p + i * 128));
    } else if (elect_one()) {
      if (warp == 13) {
#pragma unroll
        for (int i = 0; i < B_WK; i++) mbar_init(bar + i * 8, i < B_EMPTY ? 1 : (i < B_TIN ? 16 : (i < B_TFREE ? (i == B_TIN + 2 ? 5 : 1) : 16)));
      } else {
#pragma unroll
        for (int i = B_WQ; i < B_COUNT; i++) mbar_init(bar + i * 8, i < B_XK ? 1 : (i < B_Q0 ? 2 : (i < B_ODONE ? 4 : (i == B_VFREE ? 9 : 8))));
        mbar_arrive(bar + B_XK * 8); mbar_arrive(bar + B_XV * 8);
      }
    }
    asm volatile("fence.mbarrier_init.release.cluster;" ::: "memory");
    __syncwarp();
    asm volatile("barrier.cluster.arrive.relaxed.aligned;" ::: "memory");
    asm volatile("setmaxnreg.dec.sync.aligned.u32 24;");
    asm volatile("griddepcontrol.launch_dependents;");
    asm volatile("barrier.cluster.wait.aligned;" ::: "memory");
    if (warp == 12) {
      const CUtensorMap* mx = head ? &mp.xc : &mp.xh;
      const int cc = ph * 112 + strip * 16 + (head ? 0 : (odd ? 16 : (strip ? -3 : 0)));
      const int r0 = head == 0 ? (strip ? -4 : 112) : (head == 1 ? 4 : 0), dr = head ? 8 : 16;
      const uint32_t fb = bar + (B_FULL + head) * 8, eb = bar + (B_EMPTY + head) * 8;
      const uint32_t dst = sb + (head == 0 ? SM_X0 : (head == 1 ? SM_X1 : SM_X2));
      const int nl = head == 0 ? 8 : (head == 3 ? 1 : 14);
      TRDECL;
#pragma unroll 1
      for (int n = 0; n < nl; n++) {
        if (n) mbar_wait(eb, (n - 1) & 1);
        TR(2, n - 3, 0);
        if (elect_one()) {
          if (head < 3)
            asm volatile("cp.async.bulk.tensor.4d.shared::cluster.global.mbarrier::complete_tx::bytes.multicast::cluster [%0], [%1, {%3,%4,%5,%6}], [%2], %7;"
                         ::"r"(dst), "l"(mx), "r"(fb), "r"(0), "r"(dr * n + r0), "r"(cc), "r"(pw * 3), "h"((uint16_t)(15 << base)) : "memory");
          if (n == 0) {
#pragma unroll
            for (int i = 0; i < 3; i++) load_w(&mp.w, sb + SM_W + (6 + i) * 6144, bar + B_WQ * 8, head * 48 + i * 16);
            mbar_expect(bar + B_WQ * 8, 18432);
            mbar_expect(bar + B_TIN * 8, 24576); mbar_expect(bar + (B_TIN + 1) * 8, 24576); mbar_expect(bar + (B_TIN + 2) * 8, 6144); mbar_expect(bar + (B_TIN + 3) * 8, 12288);
          }
          if (n + 1 < nl) asm volatile("cp.async.bulk.prefetch.tensor.4d.L2.global [%0, {%1,%2,%3,%4}];" ::"l"(mx), "r"(0), "r"(dr * n + dr + r0), "r"(cc), "r"(pw * 3) : "memory");
        }
        __syncwarp();
        TR(2, n - 3, 1);
        if (lane < 4 && head < 3)
          asm volatile("mbarrier.arrive.expect_tx.shared::cluster.b64 _, [%0], %1;" ::"r"(mapa(fb, base + lane)), "r"(head ? 24576 : 18432) : "memory");
        __syncwarp();
        TR(2, n - 3, 2);
      }
      TRDUMP;
      mbar_wait(bar + B_WOFREE * 8, 0);
      if (elect_one()) {
        mbar_expect(bar + B_WO * 8, 36864);
        asm volatile("cp.async.bulk.tensor.3d.shared::cluster.global.mbarrier::complete_tx::bytes [%0], [%1, {%3,%4,%5}], [%2];"
                     ::"r"(sb + SM_TWO), "l"(&mp.wo), "r"(bar + B_WO * 8), "r"(0), "r"(0), "r"((head & 1) * 3) : "memory");
      }
      __syncwarp();
    }
    if (warp & 1) {
      const uint32_t partner = (blockIdx.x & 7) ^ 4;
      const int cs = odd ? 3 : (strip == 6 ? 15 : 16), cd = odd || strip == 6 ? 19 : 0;
      const uint32_t rb = opq(mapa(bar, partner));
      TRDECL;
      if (warp == 13) {
        const uint32_t dst = opq(mapa(sb + SM_V + cd * 1536, partner)), src = opq(sb + SM_V + cs * 1536);
#pragma unroll 1
        for (int b = 0;; b++) {
          const uint32_t pa = b & 1;
          nb_arrive(N_VQ0, 288);
          mbar_wait(bar + B_XV * 8, pa);
          TR(1, b, 0);
          if (elect_one()) { copy_remote(dst, src, 4608, rb + B_VIMP * 8); remote_expect(rb + B_VIMP * 8, 4608); }
          __syncwarp();
          TR(1, b, 1);
          mbar_wait(bar + B_VIMP * 8, pa);
          TR(1, b, 2);
          nb_arrive(N_VQ1, 288);
          if (elect_one()) remote_arrive(rb + B_VFREE * 8);
          __syncwarp();
          TR(1, b, 3);
          if (b == 13) break;
          mbar_wait(bar + B_VFREE * 8, pa);
          if (elect_one()) remote_arrive(rb + B_XV * 8);
          __syncwarp();
        }
      } else {
        const uint32_t dst = opq(mapa(sb + SM_K + cd * KS, partner)), src = opq(sb + SM_K + cs * KS);
#pragma unroll 1
        for (int b = 0;; b++) {
          const uint32_t pa = b & 1, so = (pa ^ 1) * KSLOT;
          mbar_wait(bar + B_XK * 8, pa);
          TR(1, b - 1, 4);
          if (elect_one()) {
            copy_remote(dst + so, src + so, 3 * KS, rb + B_KIMP * 8);
            if (b == 0) copy_remote(dst, src, 3 * KS, rb + B_KIMP * 8);
            remote_expect(rb + B_KIMP * 8, b ? 3 * KS : 6 * KS);
          }
          __syncwarp();
          TR(1, b - 1, 5);
          TR(1, b - 1, 7);
          if (b == 13) break;
          mbar_wait(bar + B_KFREE * 8, pa);
          if (elect_one()) remote_arrive(rb + B_XK * 8);
          __syncwarp();
        }
      }
      TRDUMP;
    }
    if (warp == 14) {
      int* flag = g_flags + (par * 7 + strip) * 2;
#pragma unroll 1
      for (int b = 0; b < TB; b++) {
        mbar_wait(bar + B_ODONE * 8, b & 1);
        if (lane == 0) {
#pragma unroll 1
          for (int i = 0; i < 16; i += OCH) {
            asm volatile("cp.async.bulk.tensor.3d.global.shared::cta.bulk_group [%0, {%2,%3,%4}], [%1];"
                         ::"l"(&mp.os), "r"(sb + SM_O + i * 768), "r"(pw * 192), "r"(8 * b + 2 * head), "r"(ph * 112 + strip * 16 + i) : "memory");
            asm volatile("cp.async.bulk.commit_group;\ncp.async.bulk.wait_group 0;" ::: "memory");
          }
        }
        __syncwarp();
        mbar_arrive_elect(bar + B_OFREE * 8);
        if (lane == 0)
          asm volatile("fence.proxy.async.global;\nfence.acq_rel.gpu;\nred.relaxed.gpu.global.add.s32 [%0], 1;\nred.relaxed.gpu.global.add.s32 [%0+4], 1;"
                       ::"l"(flag + b * 56) : "memory");
        __syncwarp();
      }
#pragma unroll 1
      for (int t = 0; t < 4; t++) {
        const int i = t >> 1, jw = t & 1, j = jw ^ odd;
        if (!jw) mbar_wait(bar + (B_TFREE + i) * 8, 0);
        mbar_wait(bar + (B_OTAIL + t) * 8, 0);
        if (elect_one()) {
#pragma unroll 1
          for (int d = 0; d < 8; d++) {
            const int dst = (d + head) & 3, pc = d >> 2;
            send_o<1536>(sb + SM_TIN + i * 24576 + head * 6144 + j * 3072 + pc * 1536,
                         sb + (i ? SM_Q : SM_O) + (4 * j + (dst & 2) + pc) * (i ? 3072 : 1536), bar + (B_TIN + i) * 8, base + dst);
          }
        }
        __syncwarp();
      }
    }
    cluster_sync();
  }
}

constexpr int NSTB = 6;
constexpr int NTB = TB * 56;
constexpr int SM_B_ST = 0;
constexpr int SM_B_IN = 73728;
constexpr int SM_B_W = SM_B_IN + 3 * 24576;
constexpr int SM_B_BAR = SM_B_IN + NSTB * 24576;
constexpr int SM_B_TOTAL = SM_B_BAR + 512;
struct MapsB { CUtensorMap oi, oo, wo; };

__global__ void __launch_bounds__(512, 1)
na_proj_kernel(const __grid_constant__ MapsB mp) {
  extern __shared__ __align__(1024) uint8_t smem_raw[];
  const uint32_t sb = smem_u32(smem_raw);
  if ((sb & 0x3FFFF) != SBC) return;
  const uint32_t bar = sb + SM_B_BAR;
  const int tid = threadIdx.x, lane = tid & 31;
  const int warp = __shfl_sync(0xffffffffu, tid >> 5, 0);
  TR2(132 + blockIdx.x, 0);
  TRB(47, 0);
  if (warp == 12 && elect_one()) {
#pragma unroll
    for (int i = 0; i <= 2 * NSTB; i++) mbar_init(bar + i * 8, i < NSTB || i == 2 * NSTB ? 1 : 12);
    asm volatile("st.shared.u32 [%0], 0;" ::"r"(bar + 120) : "memory");
    mbar_expect(bar + 2 * NSTB * 8, 73728);
#pragma unroll
    for (int i = 0; i < 2; i++)
      asm volatile("cp.async.bulk.tensor.3d.shared::cluster.global.mbarrier::complete_tx::bytes [%0], [%1, {%3,%4,%5}], [%2];"
                   ::"r"(sb + SM_B_W + i * 36864), "l"(&mp.wo), "r"(bar + 2 * NSTB * 8), "r"(0), "r"(0), "r"(i * 3) : "memory");
  }
  __syncthreads();
  const int step = gridDim.x;
  if (warp == 15) {
    int so = 0;
    nb_arrive(4, 288); nb_arrive(5, 288); nb_arrive(6, 288);
#pragma unroll 1
    for (int n = blockIdx.x, tk = 0; n < NTB; n += step, tk++) {
      uint32_t cc = 0;
#pragma unroll
      for (int wg = 0; wg < 3; wg++) {
        if (lane == 0) asm volatile("cp.async.bulk.wait_group.read 5;" ::: "memory");
        nb_sync(1 + wg, 160);
        if (wg == 0 || n + step < NTB) nb_arrive(4 + wg, 288);
        if (wg == 0) asm volatile("ld.shared.u32 %0, [%1];" : "=r"(cc) : "r"(bar + 128 + tk * 4) : "memory");
        if (lane == 0) {
          asm volatile("cp.async.bulk.tensor.4d.global.shared::cta.bulk_group [%0, {%2,%3,%4,%5}], [%1];"
                       ::"l"(&mp.oo), "r"(sb + SM_B_ST + wg * 8192 + so), "r"(0), "r"((cc >> 8) & 255), "r"(cc >> 16), "r"((cc & 1) * 3 + wg) : "memory");
          asm volatile("cp.async.bulk.commit_group;" ::: "memory");
        }
        __syncwarp();
      }
      so = so == 49152 ? 0 : so + 24576;
    }
    if (lane == 0) asm volatile("cp.async.bulk.wait_group.read 0;" ::: "memory");
  } else if (warp >= 12) {
    nb_sync(7, 480);
#pragma unroll 1
    for (int n = blockIdx.x + (warp - 12) * step; n < NTB; n += 3 * step) {
      const int b = n / 56, rem = n - b * 56, par = rem / 14;
      const int c0 = opq((uint32_t)(par & 1)), c1 = opq((uint32_t)(8 * b)), c2 = opq((uint32_t)((par >> 1) * 112 + (rem - par * 14) * 8));
      int v; uint32_t spin = 0, tk = 0;
      do { asm volatile("ld.acquire.gpu.global.s32 %0, [%1];" : "=r"(v) : "l"(g_flags + n) : "memory"); } while (v < 4 && ++spin < SPIN_LIMIT);
      if (lane == 0) asm volatile("atom.shared.add.u32 %0, [%1], 1;" : "=r"(tk) : "r"(bar + 120) : "memory");
      asm volatile("fence.proxy.async.global;" ::: "memory");
      tk = __shfl_sync(0xffffffffu, tk, 0);
      TRB(tk, 0);
      const uint32_t use = tk / NSTB, sg = tk - use * NSTB;
      if (use) mbar_wait(bar + (NSTB + sg) * 8, (use - 1) & 1);
      TRB(tk, 1);
      if (elect_one()) {
        asm volatile("st.shared.u32 [%0], %1;" ::"r"(bar + 128 + tk * 4), "r"(c0 | c1 << 8 | c2 << 16) : "memory");
        mbar_expect(bar + sg * 8, 24576);
        asm volatile("cp.async.bulk.tensor.3d.shared::cluster.global.mbarrier::complete_tx::bytes [%0], [%1, {%3,%4,%5}], [%2];"
                     ::"r"(sb + SM_B_IN + sg * 24576), "l"(&mp.oi), "r"(bar + sg * 8), "r"(c0 * 192), "r"(c1), "r"(c2) : "memory");
        g_flags[n] = 0;
      }
      __syncwarp();
    }
  } else {
    const int wg = warp >> 2, w = warp & 3;
    uint32_t a[48];
    mbar_wait(bar + 2 * NSTB * 8, 0);
    {
      const int k = (lane & 7) + (lane >> 4) * 8, ch = (warp & 1) * 2 + ((lane >> 3) & 1);
      const uint32_t wa = sb + SM_B_W + (warp >> 1) * 12288 + k * 64 + ((ch ^ ((k >> 1) & 3)) * 16);
#pragma unroll
      for (int i = 0; i < 12; i++)
        asm volatile("ldmatrix.sync.aligned.m8n8.x4.trans.shared.b16 {%0,%1,%2,%3}, [%4];"
                     : "=r"(a[4 * i]), "=r"(a[4 * i + 1]), "=r"(a[4 * i + 2]), "=r"(a[4 * i + 3]) : "r"(wa + i * 1024) : "memory");
    }
    nb_sync(7, 480);
    TRB(47, 1);
    const uint32_t sta = opq(sb + SM_B_ST + wg * 8192 + ((lane & 7) + (lane >> 4) * 8) * 128 + (((2 * w + ((lane >> 3) & 1)) ^ (lane & 7)) * 16));
    const uint32_t hi = opq((uint32_t)(mkdesc(0, 0, 3072, 0) >> 32) + (blockIdx.x >> 16)), bb = opq(bar);
    const uint32_t nbT = opq((uint32_t)(4 + wg)), nbN = opq((uint32_t)(wg == 2 ? 4 : 5 + wg)), nbD = opq((uint32_t)(1 + wg));
    int left = (NTB - blockIdx.x + step - 1) / step;
    if (wg == 2) nb_arrive(4, 288);
#pragma unroll 1
    for (uint32_t ph = 0;; ph ^= 1) {
#pragma unroll
      for (int sg = 0; sg < NSTB; sg++) {
        constexpr uint64_t db = mkdesc(SBC + SM_B_IN, 128, 3072, 0);
        float D[32];
        mbar_wait(bb + sg * 8, ph);
        nb_sync(nbT, 288);
        wg_fence();
        wg_rs64<0>(D, a[0], a[1], a[2], a[3], dsc(db + sg * 1536, hi));
#pragma unroll
        for (int k = 1; k < 12; k++) wg_rs64<1>(D, a[4 * k], a[4 * k + 1], a[4 * k + 2], a[4 * k + 3], dsc(db + sg * 1536 + k * 16, hi));
        wg_commit();
        nb_arrive(nbN, 288);
        wg_wait<0>(); pin(D);
        mbar_arrive_elect(bb + (NSTB + sg) * 8);
#pragma unroll
        for (int q = 0; q < 4; q++)
          asm volatile("stmatrix.sync.aligned.m8n8.x4.trans.shared.b16 [%0], {%1,%2,%3,%4};" ::"r"(sta + (sg % 3) * 24576 + q * 2048),
                       "r"(pack2(D[8 * q], D[8 * q + 1])), "r"(pack2(D[8 * q + 2], D[8 * q + 3])), "r"(pack2(D[8 * q + 4], D[8 * q + 5])), "r"(pack2(D[8 * q + 6], D[8 * q + 7])) : "memory");
        fence_async();
        nb_arrive(nbD, 160);
        if (wg == 0) TRB(31 - left, 5);
        if (--left == 0) goto done;
      }
    }
  done:
    if (wg == 0) nb_arrive(4, 288);
    TR2(132 + blockIdx.x, 2);
  }
}

typedef CUresult (*EncodeFn)(CUtensorMap*, CUtensorMapDataType, cuuint32_t, void*, const cuuint64_t*, const cuuint64_t*, const cuuint32_t*,
                             const cuuint32_t*, CUtensorMapInterleave, CUtensorMapSwizzle, CUtensorMapL2promotion, CUtensorMapFloatOOBfill);
static EncodeFn g_enc = nullptr;
static void make_map(CUtensorMap* m, const void* p, int rank, const cuuint64_t* dim, const cuuint64_t* str, const cuuint32_t* box, CUtensorMapSwizzle sw) {
  const cuuint32_t ones[5] = {1, 1, 1, 1, 1};
  g_enc(m, CU_TENSOR_MAP_DATA_TYPE_BFLOAT16, rank, (void*)p, dim, str, box, ones, CU_TENSOR_MAP_INTERLEAVE_NONE, sw,
        CU_TENSOR_MAP_L2_PROMOTION_L2_128B, CU_TENSOR_MAP_FLOAT_OOB_FILL_NONE);
}

extern "C" void kernel_launch(void* const* d_in, const int* in_sizes, int n_in, void* d_out, int out_size) {
  const __nv_bfloat16* x = (const __nv_bfloat16*)d_in[0];
  const __nv_bfloat16* wqkv = (const __nv_bfloat16*)d_in[1];
  const __nv_bfloat16* wo = (const __nv_bfloat16*)d_in[2];
  const __nv_bfloat16* rpb = (const __nv_bfloat16*)d_in[3];

  if (!g_enc) {
    void* fn = nullptr; cudaDriverEntryPointQueryResult qr;
    cudaGetDriverEntryPoint("cuTensorMapEncodeTiled", &fn, cudaEnableDefault, &qr);
    g_enc = (EncodeFn)fn;
    cudaFuncSetAttribute(na_attn_kernel, cudaFuncAttributeMaxDynamicSharedMemorySize, SM_A_TOTAL);
    cudaFuncSetAttribute(na_proj_kernel, cudaFuncAttributeMaxDynamicSharedMemorySize, SM_B_TOTAL);
  }
  Maps ma; MapsB mb;
  { cuuint64_t dim[4] = {64, 112, 224, 6}, str[3] = {(cuuint64_t)ROWB, 768, 128};
    cuuint32_t box[4] = {64, 4, 16, 3}, boxh[4] = {64, 16, 3, 3}, boxo[4] = {64, 8, 8, 1};
    make_map(&ma.xc, x, 4, dim, str, box, CU_TENSOR_MAP_SWIZZLE_128B);
    make_map(&ma.xh, x, 4, dim, str, boxh, CU_TENSOR_MAP_SWIZZLE_128B);
    make_map(&mb.oo, d_out, 4, dim, str, boxo, CU_TENSOR_MAP_SWIZZLE_128B); }
  { cuuint64_t dim[3] = {384, 112, 224}, str[2] = {(cuuint64_t)ROWB, 768};
    cuuint32_t box[3] = {192, 8, 8}, boxs[3] = {192, 2, OCH};
    make_map(&mb.oi, d_out, 3, dim, str, box, CU_TENSOR_MAP_SWIZZLE_NONE);
    make_map(&ma.os, d_out, 3, dim, str, boxs, CU_TENSOR_MAP_SWIZZLE_NONE); }
  { cuuint64_t dim[4] = {32, 112, 224, 12}, str[3] = {(cuuint64_t)ROWB, 768, 64};
    cuuint32_t box[4] = {32, 8, 2, 3};
    make_map(&ma.ot, d_out, 4, dim, str, box, CU_TENSOR_MAP_SWIZZLE_64B); }
  { cuuint64_t dim[2] = {576, 192}, str[1] = {1152};
    cuuint32_t box[2] = {16, 192};
    make_map(&ma.w, wqkv, 2, dim, str, box, CU_TENSOR_MAP_SWIZZLE_32B); }
  { cuuint64_t dim[3] = {32, 192, 6}, str[2] = {384, 64};
    cuuint32_t box[3] = {32, 192, 3};
    make_map(&ma.wo, wo, 3, dim, str, box, CU_TENSOR_MAP_SWIZZLE_64B);
    mb.wo = ma.wo; }
  na_attn_kernel<<<112, 512, SM_A_TOTAL>>>(x, wqkv, rpb, ma);
  cudaLaunchConfig_t cfg = {};
  cfg.gridDim = dim3(20); cfg.blockDim = dim3(512); cfg.dynamicSmemBytes = SM_B_TOTAL; cfg.stream = cudaStreamPerThread;
  cudaLaunchAttribute at[1];
  at[0].id = cudaLaunchAttributeProgrammaticStreamSerialization; at[0].val.programmaticStreamSerializationAllowed = 1;
  cfg.attrs = at; cfg.numAttrs = 1;
  cudaLaunchKernelEx(&cfg, na_proj_kernel, mb);
}
```

```cpp
#include <cuda_runtime.h>
#include <cuda_bf16.h>
#include <cuda.h>
#include <stdint.h>

#define SPIN_LIMIT (1u << 18)

__device__ __forceinline__ uint32_t smem_u32(const void* p) { return (uint32_t)__cvta_generic_to_shared(p); }
__device__ __forceinline__ void wg_fence() { asm volatile("wgmma.fence.sync.aligned;" ::: "memory"); }
__device__ __forceinline__ void wg_commit() { asm volatile("wgmma.commit_group.sync.aligned;" ::: "memory"); }
template <int N> __device__ __forceinline__ void wg_wait() { asm volatile("wgmma.wait_group.sync.aligned %0;" ::"n"(N) : "memory"); }
template <int N> __device__ __forceinline__ void pin(float (&d)[N]) {
#pragma unroll
  for (int i = 0; i < N; i++) asm volatile("" : "+f"(d[i])::"memory");
}
__host__ __device__ constexpr uint64_t mkdesc(uint32_t addr, uint32_t lbo, uint32_t sbo, uint32_t sw) {
  return (uint64_t)((addr & 0x3FFFF) >> 4) | ((uint64_t)(lbo >> 4) << 16) | ((uint64_t)(sbo >> 4) << 32) | ((uint64_t)sw << 62);
}
__device__ __forceinline__ void mbar_init(uint32_t bar, uint32_t cnt) { asm volatile("mbarrier.init.shared::cta.b64 [%0], %1;" ::"r"(bar), "r"(cnt) : "memory"); }
__device__ __forceinline__ void mbar_arrive(uint32_t bar) { asm volatile("mbarrier.arrive.shared::cta.b64 _, [%0];" ::"r"(bar) : "memory"); }
__device__ __forceinline__ bool elect_one() {
  uint32_t r; asm volatile("{\n.reg .pred p;\nelect.sync _|p, 0xffffffff;\nselp.u32 %0, 1, 0, p;\n}" : "=r"(r)); return r;
}
__device__ __forceinline__ void mbar_arrive_elect(uint32_t bar) {
  asm volatile("{\n.reg .pred p;\nelect.sync _|p, 0xffffffff;\n@p mbarrier.arrive.shared::cta.b64 _, [%0];\n}" ::"r"(bar) : "memory");
}
__device__ __forceinline__ void mbar_expect(uint32_t bar, uint32_t bytes) { asm volatile("mbarrier.arrive.expect_tx.shared::cta.b64 _, [%0], %1;" ::"r"(bar), "r"(bytes) : "memory"); }
__device__ __forceinline__ void mbar_arrive_remote(uint32_t bar, uint32_t cta) {
  asm volatile("{\n.reg .b32 ra;\nmapa.shared::cluster.u32 ra, %0, %1;\nmbarrier.arrive.relaxed.cluster.shared::cluster.b64 _, [ra];\n}" ::"r"(bar), "r"(cta) : "memory");
}
__device__ __forceinline__ void mbar_wait(uint32_t bar, uint32_t parity) {
  asm volatile("{\n.reg .pred p;\n.reg .b32 n;\nmov.b32 n, 0;\nWL:\nmbarrier.try_wait.parity.shared::cta.b64 p, [%0], %1;\n@p bra WD;\n"
               "add.u32 n, n, 1;\nsetp.lt.u32 p, n, 65536;\n@p bra WL;\nWD:\n}" ::"r"(bar), "r"(parity) : "memory");
}
__device__ __forceinline__ void nb_sync(int id, int n) { asm volatile("bar.sync %0, %1;" ::"r"(id), "r"(n) : "memory"); }
__device__ __forceinline__ void nb_arrive(int id, int n) { asm volatile("bar.arrive %0, %1;" ::"r"(id), "r"(n) : "memory"); }
__device__ __forceinline__ uint32_t opq(uint32_t x) { uint32_t r; asm volatile("mov.b32 %0, %1;" : "=r"(r) : "r"(x)); return r; }
__device__ __forceinline__ uint64_t opq(uint64_t x) { uint64_t r; asm volatile("mov.b64 %0, %1;" : "=l"(r) : "l"(x)); return r; }
__device__ __forceinline__ uint32_t mapa(uint32_t a, uint32_t cta) { uint32_t r; asm("mapa.shared::cluster.u32 %0, %1, %2;" : "=r"(r) : "r"(a), "r"(cta)); return r; }
__device__ __forceinline__ void fence_async() { asm volatile("fence.proxy.async.shared::cta;" ::: "memory"); }
__device__ __forceinline__ void cluster_sync() {
  asm volatile("barrier.cluster.arrive.relaxed.aligned;\nbarrier.cluster.wait.aligned;" ::: "memory");
}
__device__ __forceinline__ uint32_t pack2(float lo, float hi) {
  uint32_t r; asm("cvt.rn.bf16x2.f32 %0, %1, %2;" : "=r"(r) : "f"(hi), "f"(lo)); return r;
}
__device__ __forceinline__ void stsm4(uint32_t a, uint32_t r0, uint32_t r1, uint32_t r2, uint32_t r3) {
  asm volatile("stmatrix.sync.aligned.m8n8.x4.shared.b16 [%0], {%1,%2,%3,%4};" ::"r"(a), "r"(r0), "r"(r1), "r"(r2), "r"(r3) : "memory");
}
__device__ __forceinline__ void ldsm4(uint32_t a, uint32_t& r0, uint32_t& r1, uint32_t& r2, uint32_t& r3) {
  asm volatile("ldmatrix.sync.aligned.m8n8.x4.shared.b16 {%0,%1,%2,%3}, [%4];" : "=r"(r0), "=r"(r1), "=r"(r2), "=r"(r3) : "r"(a) : "memory");
}
__device__ __forceinline__ void sts128(uint32_t a, uint4 v) {
  asm volatile("st.shared.v4.b32 [%0], {%1,%2,%3,%4};" ::"r"(a), "r"(v.x), "r"(v.y), "r"(v.z), "r"(v.w) : "memory");
}
__device__ __forceinline__ float lds_f32(uint32_t a) { float v; asm volatile("ld.shared.f32 %0, [%1];" : "=f"(v) : "r"(a)); return v; }
__device__ __forceinline__ float ex2(float x) { float y; asm("ex2.approx.ftz.f32 %0, %1;" : "=f"(y) : "f"(x)); return y; }

template<int SC> __device__ __forceinline__ void wg_ss144(float (&d)[72], uint64_t da, uint64_t db) {
  asm volatile("{\n.reg .pred p;\nsetp.ne.b32 p, %74, 0;\nwgmma.mma_async.sync.aligned.m64n144k16.f32.bf16.bf16 {%0,%1,%2,%3,%4,%5,%6,%7,%8,%9,%10,%11,%12,%13,%14,%15,%16,%17,%18,%19,%20,%21,%22,%23,%24,%25,%26,%27,%28,%29,%30,%31,%32,%33,%34,%35,%36,%37,%38,%39,%40,%41,%42,%43,%44,%45,%46,%47,%48,%49,%50,%51,%52,%53,%54,%55,%56,%57,%58,%59,%60,%61,%62,%63,%64,%65,%66,%67,%68,%69,%70,%71}, %72, %73, p, 1, 1, 0, 1;\n}\n"
    : "+f"(d[0]),"+f"(d[1]),"+f"(d[2]),"+f"(d[3]),"+f"(d[4]),"+f"(d[5]),"+f"(d[6]),"+f"(d[7]),"+f"(d[8]),"+f"(d[9]),"+f"(d[10]),"+f"(d[11]),"+f"(d[12]),"+f"(d[13]),"+f"(d[14]),"+f"(d[15]),"+f"(d[16]),"+f"(d[17]),"+f"(d[18]),"+f"(d[19]),"+f"(d[20]),"+f"(d[21]),"+f"(d[22]),"+f"(d[23]),"+f"(d[24]),"+f"(d[25]),"+f"(d[26]),"+f"(d[27]),"+f"(d[28]),"+f"(d[29]),"+f"(d[30]),"+f"(d[31]),"+f"(d[32]),"+f"(d[33]),"+f"(d[34]),"+f"(d[35]),"+f"(d[36]),"+f"(d[37]),"+f"(d[38]),"+f"(d[39]),"+f"(d[40]),"+f"(d[41]),"+f"(d[42]),"+f"(d[43]),"+f"(d[44]),"+f"(d[45]),"+f"(d[46]),"+f"(d[47]),"+f"(d[48]),"+f"(d[49]),"+f"(d[50]),"+f"(d[51]),"+f"(d[52]),"+f"(d[53]),"+f"(d[54]),"+f"(d[55]),"+f"(d[56]),"+f"(d[57]),"+f"(d[58]),"+f"(d[59]),"+f"(d[60]),"+f"(d[61]),"+f"(d[62]),"+f"(d[63]),"+f"(d[64]),"+f"(d[65]),"+f"(d[66]),"+f"(d[67]),"+f"(d[68]),"+f"(d[69]),"+f"(d[70]),"+f"(d[71]) : "l"(da), "l"(db), "n"(SC));
}
template<int SC> __device__ __forceinline__ void wg_ss96(float (&d)[48], uint64_t da, uint64_t db) {
  asm volatile("{\n.reg .pred p;\nsetp.ne.b32 p, %50, 0;\nwgmma.mma_async.sync.aligned.m64n96k16.f32.bf16.bf16 {%0,%1,%2,%3,%4,%5,%6,%7,%8,%9,%10,%11,%12,%13,%14,%15,%16,%17,%18,%19,%20,%21,%22,%23,%24,%25,%26,%27,%28,%29,%30,%31,%32,%33,%34,%35,%36,%37,%38,%39,%40,%41,%42,%43,%44,%45,%46,%47}, %48, %49, p, 1, 1, 0, 1;\n}\n"
    : "+f"(d[0]),"+f"(d[1]),"+f"(d[2]),"+f"(d[3]),"+f"(d[4]),"+f"(d[5]),"+f"(d[6]),"+f"(d[7]),"+f"(d[8]),"+f"(d[9]),"+f"(d[10]),"+f"(d[11]),"+f"(d[12]),"+f"(d[13]),"+f"(d[14]),"+f"(d[15]),"+f"(d[16]),"+f"(d[17]),"+f"(d[18]),"+f"(d[19]),"+f"(d[20]),"+f"(d[21]),"+f"(d[22]),"+f"(d[23]),"+f"(d[24]),"+f"(d[25]),"+f"(d[26]),"+f"(d[27]),"+f"(d[28]),"+f"(d[29]),"+f"(d[30]),"+f"(d[31]),"+f"(d[32]),"+f"(d[33]),"+f"(d[34]),"+f"(d[35]),"+f"(d[36]),"+f"(d[37]),"+f"(d[38]),"+f"(d[39]),"+f"(d[40]),"+f"(d[41]),"+f"(d[42]),"+f"(d[43]),"+f"(d[44]),"+f"(d[45]),"+f"(d[46]),"+f"(d[47]) : "l"(da), "l"(db), "n"(SC));
}
template<int SC> __device__ __forceinline__ void wg_rs112(float (&d)[56], uint32_t a0, uint32_t a1, uint32_t a2, uint32_t a3, uint64_t db) {
  asm volatile("{\n.reg .pred p;\nsetp.ne.b32 p, %61, 0;\nwgmma.mma_async.sync.aligned.m64n112k16.f32.bf16.bf16 {%0,%1,%2,%3,%4,%5,%6,%7,%8,%9,%10,%11,%12,%13,%14,%15,%16,%17,%18,%19,%20,%21,%22,%23,%24,%25,%26,%27,%28,%29,%30,%31,%32,%33,%34,%35,%36,%37,%38,%39,%40,%41,%42,%43,%44,%45,%46,%47,%48,%49,%50,%51,%52,%53,%54,%55}, {%56,%57,%58,%59}, %60, p, 1, 1, 0;\n}\n"
    : "+f"(d[0]),"+f"(d[1]),"+f"(d[2]),"+f"(d[3]),"+f"(d[4]),"+f"(d[5]),"+f"(d[6]),"+f"(d[7]),"+f"(d[8]),"+f"(d[9]),"+f"(d[10]),"+f"(d[11]),"+f"(d[12]),"+f"(d[13]),"+f"(d[14]),"+f"(d[15]),"+f"(d[16]),"+f"(d[17]),"+f"(d[18]),"+f"(d[19]),"+f"(d[20]),"+f"(d[21]),"+f"(d[22]),"+f"(d[23]),"+f"(d[24]),"+f"(d[25]),"+f"(d[26]),"+f"(d[27]),"+f"(d[28]),"+f"(d[29]),"+f"(d[30]),"+f"(d[31]),"+f"(d[32]),"+f"(d[33]),"+f"(d[34]),"+f"(d[35]),"+f"(d[36]),"+f"(d[37]),"+f"(d[38]),"+f"(d[39]),"+f"(d[40]),"+f"(d[41]),"+f"(d[42]),"+f"(d[43]),"+f"(d[44]),"+f"(d[45]),"+f"(d[46]),"+f"(d[47]),"+f"(d[48]),"+f"(d[49]),"+f"(d[50]),"+f"(d[51]),"+f"(d[52]),"+f"(d[53]),"+f"(d[54]),"+f"(d[55]) : "r"(a0), "r"(a1), "r"(a2), "r"(a3), "l"(db), "n"(SC));
}
template<int SC> __device__ __forceinline__ void wg_sp48(float (&d)[24], uint32_t a0, uint32_t a1, uint32_t a2, uint32_t a3, uint64_t db, uint32_t meta) {
  asm volatile("{\n.reg .pred p;\nsetp.ne.b32 p, %30, 0;\nwgmma.mma_async.sp.sync.aligned.m64n48k32.f32.bf16.bf16 {%0,%1,%2,%3,%4,%5,%6,%7,%8,%9,%10,%11,%12,%13,%14,%15,%16,%17,%18,%19,%20,%21,%22,%23}, {%24,%25,%26,%27}, %28, %29, 0, p, 1, 1, 1;\n}\n"
    : "+f"(d[0]),"+f"(d[1]),"+f"(d[2]),"+f"(d[3]),"+f"(d[4]),"+f"(d[5]),"+f"(d[6]),"+f"(d[7]),"+f"(d[8]),"+f"(d[9]),"+f"(d[10]),"+f"(d[11]),"+f"(d[12]),"+f"(d[13]),"+f"(d[14]),"+f"(d[15]),"+f"(d[16]),"+f"(d[17]),"+f"(d[18]),"+f"(d[19]),"+f"(d[20]),"+f"(d[21]),"+f"(d[22]),"+f"(d[23]) : "r"(a0), "r"(a1), "r"(a2), "r"(a3), "l"(db), "r"(meta), "n"(SC));
}
template<int SC> __device__ __forceinline__ void wg_rs64(float (&d)[32], uint32_t a0, uint32_t a1, uint32_t a2, uint32_t a3, uint64_t db) {
  asm volatile("{\n.reg .pred p;\nsetp.ne.b32 p, %37, 0;\nwgmma.mma_async.sync.aligned.m64n64k16.f32.bf16.bf16 {%0,%1,%2,%3,%4,%5,%6,%7,%8,%9,%10,%11,%12,%13,%14,%15,%16,%17,%18,%19,%20,%21,%22,%23,%24,%25,%26,%27,%28,%29,%30,%31}, {%32,%33,%34,%35}, %36, p, 1, 1, 0;\n}\n"
    : "+f"(d[0]),"+f"(d[1]),"+f"(d[2]),"+f"(d[3]),"+f"(d[4]),"+f"(d[5]),"+f"(d[6]),"+f"(d[7]),"+f"(d[8]),"+f"(d[9]),"+f"(d[10]),"+f"(d[11]),"+f"(d[12]),"+f"(d[13]),"+f"(d[14]),"+f"(d[15]),"+f"(d[16]),"+f"(d[17]),"+f"(d[18]),"+f"(d[19]),"+f"(d[20]),"+f"(d[21]),"+f"(d[22]),"+f"(d[23]),"+f"(d[24]),"+f"(d[25]),"+f"(d[26]),"+f"(d[27]),"+f"(d[28]),"+f"(d[29]),"+f"(d[30]),"+f"(d[31]) : "r"(a0), "r"(a1), "r"(a2), "r"(a3), "l"(db), "n"(SC));
}

constexpr uint32_t SBC = 1024;
constexpr int ROWB = 2 * 224 * 384;
constexpr int TB = 11;
constexpr int KS = 832;
constexpr int KSLOT = 22 * KS;
constexpr int SM_X = 0;
constexpr int SM_W = SM_X + 3 * 24576;
constexpr int SM_K = SM_W + 55296;
constexpr int SM_V = SM_K + 2 * KSLOT;
constexpr int SM_Q = SM_V + 22 * 1536;
constexpr int SM_O = SM_Q + 12288;
constexpr int SM_S = SM_O + 12288;
constexpr int SM_RPB = SM_S + 6144;
constexpr int SM_BAR = SM_RPB + 768;
constexpr int SM_A_TOTAL = SM_BAR + 256;
constexpr int SM_TIN0 = SM_X + 24576, SM_TIN1 = SM_X, SM_TIN2 = SM_W + 18432;
constexpr int SM_TWO = SM_X + 2 * 24576;
constexpr int SM_TST = SM_TIN2 + 24576;
enum { B_FULL = 0, B_EMPTY = 3, B_TIN = 6, B_TFREE = 10, B_WK = 12, B_WQ, B_WO, B_KIMP, B_VIMP, B_OFREE, B_XK, B_XV,
       B_Q0, B_WOFREE, B_OTAIL, B_ODONE = B_OTAIL + 4, B_KFREE, B_VFREE, B_COUNT };
enum { N_KRDY = 4, N_QK0, N_QK1, N_VQ0, N_VQ1, N_PVISS, N_Q0 };

#define NL 2
#define OPT 0
#define OCH 4
#define MID 6
#define SPL 4
#define RA 160
#define RG 168
__device__ int g_flags[TB * 56];

#define TR(role, it, k)
#define TRDECL
#define TRARG
#define TRPASS
#define TRDUMP
#define TRB(it, k)
#define TR2(blk, k)

struct Stage { uint32_t lo, full, em, par; };
struct GemmCtx {
  uint32_t bar;
  uint32_t kC, vC[2], qC[2];
  uint32_t kH, vH[2];
  uint32_t hiA, hiB;
  uint32_t spin;
  bool hvalid, never, edge;
};

template <int STRIDE> __device__ __forceinline__ void dump12(uint32_t a, const uint32_t (&r)[12]) {
#pragma unroll
  for (int j = 0; j < 3; j++) stsm4(a + j * 2 * STRIDE, r[4 * j], r[4 * j + 1], r[4 * j + 2], r[4 * j + 3]);
}
__device__ __forceinline__ void keep12(bool never, uint32_t a, const uint32_t (&r)[12]) { if (never) dump12<128>(a, r); }
template <int N> __device__ __forceinline__ void pack12(uint32_t (&r)[12], const float (&d)[N], int off) {
#pragma unroll
  for (int j = 0; j < 12; j++) r[j] = pack2(d[off + 2 * j], d[off + 2 * j + 1]);
}
__device__ __forceinline__ uint64_t dsc(uint64_t lo, uint32_t hi) { uint64_t r; asm("mov.b64 %0, {%1, %2};" : "=l"(r) : "r"((uint32_t)lo), "r"(hi)); return r; }
template <int K0, int K1> __device__ __forceinline__ void issue_core(const GemmCtx& c, const Stage& x, float (&d)[72]) {
  constexpr uint64_t db = mkdesc(SBC + SM_W, 6144, 256, 3);
  wg_fence();
  if (K0 == 0) wg_ss144<0>(d, dsc(x.lo, c.hiA), dsc(db, c.hiB));
#pragma unroll
  for (int k = K0 ? K0 : 1; k < K1; k++) wg_ss144<1>(d, dsc(x.lo + (k >> 2) * 512 + (k & 3) * 2, c.hiA), dsc(db + k * 32, c.hiB));
  wg_commit();
}
template <int K0, int K1> __device__ __forceinline__ void issue_halo(const GemmCtx& c, const Stage& x, float (&d)[48]) {
  constexpr uint64_t db = mkdesc(SBC + SM_W + 18432, 6144, 256, 3);
  wg_fence();
  if (K0 == 0) wg_ss96<0>(d, dsc(x.lo, c.hiA), dsc(db, c.hiB));
#pragma unroll
  for (int k = K0 ? K0 : 1; k < K1; k++) wg_ss96<1>(d, dsc(x.lo + (k >> 2) * 384 + (k & 3) * 2, c.hiA), dsc(db + k * 32, c.hiB));
  wg_commit();
}
__device__ __forceinline__ void release_stage(const Stage& x) {
  asm volatile("{\n.reg .pred p;\nelect.sync _|p, 0xffffffff;\n@p mbarrier.arrive.shared::cluster.b64 _, [%0];\n}" ::"r"(x.em) : "memory");
}
__device__ __forceinline__ void wait_stage(GemmCtx& c, Stage& x) {
  asm volatile("{\n.reg .pred p;\nWL:\nmbarrier.try_wait.parity.shared::cta.b64 p, [%1], %2;\n@p bra WD;\n"
               "add.u32 %0, %0, 1;\nsetp.lt.u32 p, %0, 0x100000;\n@p bra WL;\nWD:\n}" : "+r"(c.spin) : "r"(x.full), "r"(x.par) : "memory");
  x.par ^= 1;
}
__device__ __forceinline__ void edge_ready(const GemmCtx& c, int bar) { __syncwarp(); if (c.edge) mbar_arrive_elect(c.bar + bar * 8); }
__device__ __forceinline__ void dump6(uint32_t a, const uint32_t (&r)[6]) {
  stsm4(a, r[0], r[1], r[2], r[3]);
  asm volatile("stmatrix.sync.aligned.m8n8.x2.shared.b16 [%0], {%1,%2};" ::"r"(a + 512), "r"(r[4]), "r"(r[5]) : "memory");
}
__device__ __forceinline__ void pack6(uint32_t (&r)[6], const float (&d)[48], int off) {
#pragma unroll
  for (int j = 0; j < 6; j++) r[j] = pack2(d[off + 4 * j], d[off + 4 * j + 1]);
}
template <int PARITY> __device__ __forceinline__ void gwait(GemmCtx& c, int bar) {
  asm volatile("{\n.reg .pred p;\nWL:\nmbarrier.try_wait.parity.shared::cta.b64 p, [%1], %2;\n@p bra WD;\n"
               "add.u32 %0, %0, 1;\nsetp.lt.u32 p, %0, 0x100000;\n@p bra WL;\nWD:\n}" : "+r"(c.spin) : "r"(c.bar + bar * 8), "n"(PARITY) : "memory");
}
__device__ __forceinline__ void load_w(const CUtensorMap* m, uint32_t dst, uint32_t bar, int col) {
  asm volatile("cp.async.bulk.tensor.2d.shared::cluster.global.mbarrier::complete_tx::bytes [%0], [%1, {%3,%4}], [%2];"
               ::"r"(dst), "l"(m), "r"(bar), "r"(col), "r"(0) : "memory");
}
template <int BYTES> __device__ __forceinline__ void send_o(uint32_t dst, uint32_t src, uint32_t bar, int cta) {
  asm volatile("{\n.reg .b32 rd, rb;\nmapa.shared::cluster.u32 rd, %0, %3;\nmapa.shared::cluster.u32 rb, %2, %3;\n"
               "cp.async.bulk.shared::cluster.shared::cta.mbarrier::complete_tx::bytes [rd], [%1], %4, [rb];\n}"
               ::"r"(dst), "r"(src), "r"(bar), "r"(cta), "n"(BYTES) : "memory");
}
__device__ __forceinline__ void remote_arrive(uint32_t rbar) { asm volatile("mbarrier.arrive.shared::cluster.b64 _, [%0];" ::"r"(rbar) : "memory"); }
__device__ __forceinline__ void remote_expect(uint32_t rbar, uint32_t bytes) {
  asm volatile("mbarrier.arrive.expect_tx.shared::cluster.b64 _, [%0], %1;" ::"r"(rbar), "r"(bytes) : "memory");
}
__device__ __forceinline__ void copy_remote(uint32_t rdst, uint32_t src, uint32_t bytes, uint32_t rbar) {
  asm volatile("cp.async.bulk.shared::cluster.shared::cta.mbarrier::complete_tx::bytes [%0], [%1], %2, [%3];" ::"r"(rdst), "r"(src), "r"(bytes), "r"(rbar) : "memory");
}
__device__ __forceinline__ void tail_free(uint32_t bar) {
  uint32_t ln; asm volatile("mov.u32 %0, %%laneid;" : "=r"(ln));
  if (ln < 4) mbar_arrive_remote(bar, ln + (blockIdx.x & 4));
}
__device__ __forceinline__ void publish(uint32_t bar) {
  fence_async();
  __syncwarp();
  mbar_arrive_elect(bar);
}

template <bool FIRST, int PA>
__device__ __forceinline__ void gemm_iter(GemmCtx& c, int b, uint32_t (&pk)[12], uint32_t (&pv)[12], uint32_t (&pq)[12],
                                          uint32_t (&hk1)[6], uint32_t (&hv1)[6], Stage& x0, Stage& x2, Stage& x1 TRARG) {
  const uint32_t bar = c.bar;
  const bool w = !FIRST && (PA == 0 || b >= 0), never = c.never;
  constexpr uint32_t ko = PA * KSLOT;
  float C[72];
  uint32_t hk0[6], hv0[6], pv2[12];
  TR(2, b, 0);
  if (FIRST) wait_stage(c, x0);
  else dump12<128>(c.qC[1], pq);
  if (w) nb_sync(N_QK1, 256);
  TR(2, b, 2);
  if (PA == 0) {
    float H[48];
    issue_halo<0, 8>(c, x0, H);
    TR(2, b, 3);
    if (!FIRST) { gwait<0>(c, B_KFREE); dump12<128>(c.kC, pk); }
    issue_halo<8, 12>(c, x0, H);
    TR(2, b, 4);
    wait_stage(c, x2);
    if (FIRST) gwait<0>(c, B_WQ);
    issue_core<0, 8>(c, x2, C);
    TR(2, b, 5);
    if (!FIRST) { fence_async(); keep12(never, c.kC, pk); }
    wg_wait<1>(); pin(H);
    release_stage(x0);
    pack6(hk0, H, 0);
    if (c.hvalid) dump6(c.kH, hk0);
    pack6(hk1, H, 2); pack6(hv0, H, 24); pack6(hv1, H, 26);
  } else {
    issue_core<0, 8>(c, x2, C);
    TR(2, b, 5);
    fence_async();
    keep12(never, c.kC, pq);
    if (w) gwait<1>(c, B_KFREE);
    dump12<128>(c.kC + ko, pk);
    if (c.hvalid) dump6(c.kH + ko, hk1);
  }
  TR(2, b, 13);
  issue_core<8, 12>(c, x2, C);
  if (w) { nb_arrive(N_VQ0, 288); nb_arrive(N_VQ1, 288); }
  else if (!FIRST) { __syncwarp(); mbar_arrive_elect(bar + B_Q0 * 8); }
  wait_stage(c, x1);
  if (never) dump6(bar, PA ? hk1 : hk0);
  TR(2, b, 6);
  wg_wait<0>(); pin(C);
  TR(2, b, 7);
  release_stage(x2);
  pack12(pk, C, 24);
  dump12<128>(c.kC + ko + 64, pk);
  pack12(pv2, C, 48);
  pack12(pq, C, 0);
  TR(2, b, 8);
  issue_core<0, SPL>(c, x1, C);
  TR(2, b, 9);
  if (!FIRST) { fence_async(); edge_ready(c, B_XK); }
  keep12(never, c.kC, pk);
  TR(2, b, 14);
  if (w) nb_sync(N_PVISS, 384);
  issue_core<SPL, 12>(c, x1, C);
  if (!FIRST) nb_arrive(N_KRDY, 256);
  TR(2, b, 1);
  if (PA && b == 11) tail_free(bar + B_TFREE * 8);
  wait_stage(c, x0);
  if (w) gwait<PA>(c, B_VFREE);
  if (w && b < TB) gwait<PA>(c, B_ODONE);
  TR(2, b, 10);
  if (!FIRST) dump12<128>(c.vC[PA], pv);
  dump12<128>(c.vC[PA ^ 1] + 768, pv2);
  TR(2, b, 11);
  wg_wait<0>(); pin(C);
  TR(2, b, 12);
  release_stage(x1);
  if (!FIRST && c.edge) publish(bar + B_XV * 8);
  if (c.hvalid) dump6(c.vH[PA], PA ? hv1 : hv0);
  if (PA && !w) nb_sync(N_Q0, 384);
  dump12<128>(c.qC[0], pq);
  pack12(pk, C, 24);
  pack12(pv, C, 48);
  pack12(pq, C, 0);
}

template <int IN> __device__ __forceinline__ void issue_proj(float (&D)[48]) {
  constexpr uint64_t da = mkdesc(SBC + IN, 128, 768, 0), db = mkdesc(SBC + SM_TWO, 12288, 512, 2);
  wg_fence();
  wg_ss96<0>(D, da, db);
#pragma unroll
  for (int k = 1; k < 12; k++) wg_ss96<1>(D, da + (k / 3) * 384 + (k % 3) * 16, db + k * 64);
  wg_commit();
}
template <int ACC> __device__ __forceinline__ void issue_proj_half(float (&D)[48], int hd) {
  const uint64_t da = mkdesc(SBC + SM_TIN2, 128, 768, 0) + hd * 384, db = mkdesc(SBC + SM_TWO, 12288, 512, 2) + hd * 192;
  wg_fence();
  wg_ss96<ACC>(D, da, db);
#pragma unroll
  for (int k = 1; k < 6; k++) wg_ss96<1>(D, da + (k / 3) * 768 + (k % 3) * 16, db + (k / 3) * 384 + (k % 3) * 64);
  wg_commit();
}
__device__ __forceinline__ void store_proj(const float (&D)[48], const CUtensorMap* m, uint32_t st, uint32_t sta, int row, int col, int ch) {
#pragma unroll
  for (int q = 0; q < 6; q++)
    stsm4((sta ^ ((q & 1) * 32)) + (q >> 1) * 1024,
          pack2(D[8 * q], D[8 * q + 1]), pack2(D[8 * q + 2], D[8 * q + 3]), pack2(D[8 * q + 4], D[8 * q + 5]), pack2(D[8 * q + 6], D[8 * q + 7]));
  fence_async();
  __syncwarp();
  if ((threadIdx.x & 31) == 0) {
    asm volatile("cp.async.bulk.tensor.4d.global.shared::cta.bulk_group [%0, {%2,%3,%4,%5}], [%1];" ::"l"(m), "r"(st), "r"(0), "r"(row), "r"(col), "r"(ch) : "memory");
    asm volatile("cp.async.bulk.commit_group;" ::: "memory");
  }
  __syncwarp();
}

__device__ __forceinline__ float fold(float a, float b, float t, int useb) {
  float r;
  asm("{\n.reg .pred p;\nsetp.ne.b32 p, %4, 0;\nfma.rn.f32 %0, %1, 0f3E553B95, %3;\n@p fma.rn.f32 %0, %2, 0f3E553B95, %3;\n}"
      : "=&f"(r) : "f"(a), "f"(b), "f"(t), "r"(useb));
  return r;
}
template <int U, int L>
__device__ __forceinline__ void softmax_tile(const float (&SA)[56], const float (&SB)[56], const float (&T)[16], int b0, int b1,
                                             uint32_t (&P)[28], float (&sx)[8], uint32_t nbV, uint32_t zero, uint32_t qa, uint32_t (&q)[12]) {
  float lu[14], ll[14];
#pragma unroll
  for (int j = 0; j < 7; j++) {
    constexpr int sh = U == L ? 2 : 0;
    const float tu0 = T[2 * j + sh], tu1 = T[2 * j + 1 + sh], tl0 = T[2 * j], tl1 = T[2 * j + 1];
    lu[2 * j]     = fold(SA[4 * (U + j)],     SB[4 * (U + j)],     tu0, b0);
    ll[2 * j]     = fold(SA[4 * (L + j) + 2], SB[4 * (L + j) + 2], tl0, b0);
    lu[2 * j + 1] = fold(SA[4 * (U + j) + 1], SB[4 * (U + j) + 1], tu1, b1);
    ll[2 * j + 1] = fold(SA[4 * (L + j) + 3], SB[4 * (L + j) + 3], tl1, b1);
  }
  float mu = lu[0], ml = ll[0], mu2 = lu[1], ml2 = ll[1];
#pragma unroll
  for (int j = 1; j < 7; j++) { mu = fmaxf(mu, lu[2 * j]); mu2 = fmaxf(mu2, lu[2 * j + 1]); ml = fmaxf(ml, ll[2 * j]); ml2 = fmaxf(ml2, ll[2 * j + 1]); }
  mu = fmaxf(mu, mu2); ml = fmaxf(ml, ml2);
  { const float a1 = __shfl_xor_sync(0xffffffffu, mu, 1), a2 = __shfl_xor_sync(0xffffffffu, mu, 2), a3 = __shfl_xor_sync(0xffffffffu, mu, 3);
    const float c1 = __shfl_xor_sync(0xffffffffu, ml, 1), c2 = __shfl_xor_sync(0xffffffffu, ml, 2), c3 = __shfl_xor_sync(0xffffffffu, ml, 3);
    mu = fmaxf(fmaxf(mu, a1), fmaxf(a2, a3)); ml = fmaxf(fmaxf(ml, c1), fmaxf(c2, c3)); }
  float su = 0.f, sl = 0.f;
#pragma unroll
  for (int c = 0; c < 14; c++) {
    if (c >= U && c < U + 7) {
      float e0 = ex2(lu[2 * (c - U)] - mu), e1 = ex2(lu[2 * (c - U) + 1] - mu);
      su = c == U ? e0 + e1 : (su + e0) + e1; P[2 * c] = pack2(e0, e1);
    } else P[2 * c] = 0u;
  }
  nb_sync(nbV | (P[2 * (U + MID)] & zero), 288);
#pragma unroll
  for (int k = 0; k < 3; k++) ldsm4(qa + k * 256, q[4 * k], q[4 * k + 1], q[4 * k + 2], q[4 * k + 3]);
#pragma unroll
  for (int c = 0; c < 14; c++) {
    if (c >= L && c < L + 7) {
      float e0 = ex2(ll[2 * (c - L)] - ml), e1 = ex2(ll[2 * (c - L) + 1] - ml);
      sl = c == L ? e0 + e1 : (sl + e0) + e1; P[2 * c + 1] = pack2(e0, e1);
    } else P[2 * c + 1] = 0u;
  }
  sx[0] = su; sx[4] = sl;
#pragma unroll
  for (int k = 1; k < 4; k++) sx[k] = __shfl_xor_sync(0xffffffffu, su, k);
#pragma unroll
  for (int k = 1; k < 4; k++) sx[4 + k] = __shfl_xor_sync(0xffffffffu, sl, k);
}

struct BandCfg { uint32_t ra0, ra1, meta; int b0, b1; };
__device__ __forceinline__ void band_cfg(int b, uint32_t tb, BandCfg& n) {
  uint32_t ln; asm volatile("mov.u32 %0, %%laneid;" : "=r"(ln));
  const int g = ln >> 2, t = ln & 3;
  const int sw = min(max(g + 1, b == 0 ? 4 : 0), b == 13 ? 5 : 8);
  const int i0 = 2 * t, i1 = 2 * t + 1;
  n.b0 = i0 <= sw - 2; n.b1 = i1 <= sw - 2;
  n.ra0 = tb + (i0 == sw - 1 ? 13 : i0 + 8 * n.b0 - g + 2) * 52;
  n.ra1 = tb + (i1 == sw - 1 ? 13 : i1 + 8 * n.b1 - g + 2) * 52;
  n.meta = ((0x5555u & ((1u << (2 * (sw - 1))) - 1)) ^ 0xDD88u ^ (((t ^ b) & 1) ? 0x5555u : 0u)) * 0x10001u;
}
__device__ __forceinline__ void band_load(const BandCfg& n, float (&T)[16], int& b0, int& b1, uint32_t& meta) {
#pragma unroll
  for (int jj = 0; jj < 8; jj++) { T[2 * jj] = lds_f32(n.ra0 + jj * 4); T[2 * jj + 1] = lds_f32(n.ra1 + jj * 4); }
  b0 = n.b0; b1 = n.b1; meta = n.meta;
}

struct Maps { CUtensorMap xc, xh, w, os, wo, ot; };

__global__ void __cluster_dims__(8, 1, 1) __launch_bounds__(512, 1)
na_attn_kernel(const __nv_bfloat16* __restrict__ x, const __nv_bfloat16* __restrict__ wqkv, const __nv_bfloat16* __restrict__ rpb, const __grid_constant__ Maps mp) {
  extern __shared__ __align__(1024) uint8_t smem_raw[];
  const uint32_t sb = smem_u32(smem_raw);
  if ((sb & 0x3FFFF) != SBC) return;
  const uint32_t bar = sb + SM_BAR;
  TR2(blockIdx.x, 0);
  const int tid = threadIdx.x, lane = tid & 31;
  const int warp = __shfl_sync(0xffffffffu, tid >> 5, 0);
  const int head = blockIdx.x & 3, base = blockIdx.x & 4, sp = blockIdx.x >> 2;
  const int par = sp < 24 ? sp / 6 : sp - 24, strip = sp < 24 ? sp - par * 6 : 6, ph = par >> 1, pw = par & 1;
  const int odd = strip & 1;

  uint4 wv[2 * NL];
  const int va = head == 1;
  const uint32_t wdst = sb + SM_W + (3 + va + ((tid >> 1) & 1)) * 6144 + (tid >> 2) * 32 + ((tid ^ (tid >> 4)) & 1) * 16;
  if (warp < 12) asm volatile("barrier.cluster.arrive.relaxed.aligned;" ::: "memory");
  {
    const uint32_t wo0 = (tid >> 2) * 1152 + head * 96 + va * 32 + (tid & 3) * 16;
#pragma unroll
    for (int i = 0; i < 2 * NL; i++)
      asm volatile("{\n.reg .pred p;\nsetp.lt.u32 p, %5, 384;\n@p ld.global.nc.v4.b32 {%0,%1,%2,%3}, [%4];\n}"
                   : "=r"(wv[i].x), "=r"(wv[i].y), "=r"(wv[i].z), "=r"(wv[i].w)
                   : "l"(reinterpret_cast<const uint8_t*>(wqkv) + wo0 + (i & 1) * 96 * 1152 + ((i / 2 + 1) % 3) * 384), "r"(tid));
  }
  if (warp < 8) {
    asm volatile("setmaxnreg.inc.sync.aligned.u32 %0;" ::"n"(RA));
    float rv = -INFINITY;
    if (tid < 169) rv = __bfloat162float(rpb[head * 169 + tid]) * 1.4426950408889634f;
    if (tid < 192) {
      const int kc = (tid & 15) + 3, wc = (tid >> 4) % 6;
      sts128(tid < 96 ? sb + SM_K + kc * KS + wc * 128 + 48 : sb + SM_V + kc * 1536 + wc * 128 + (6 + (kc & 1)) * 16, make_uint4(0, 0, 0, 0));
    }
#pragma unroll
    for (int i = 0; i < 2 * NL; i++) sts128(wdst + (i & 1) * 3072 + (i / 2) * 18432, wv[i]);
    fence_async();
    asm volatile("bar.arrive 1, 384;" ::: "memory");
    if (tid < 182) asm volatile("st.shared.f32 [%0], %1;" ::"r"(sb + SM_RPB + tid * 4), "f"(rv) : "memory");
    const int jw = warp >> 2, j = jw ^ odd, w = warp & 3, wt = 4 * j + w;
    int variant = w;
    if (strip == 0 && j == 0 && w < 2) variant = 4;
    if (strip == 6 && j == 1 && w >= 2) variant = 5;
    const bool v1 = opq((uint32_t)(variant & 1)), v2 = opq((uint32_t)(variant & 2)), v4 = opq((uint32_t)(variant & 4));
    const uint32_t qa = opq(sb + SM_Q + (8 * j + 2 * w + ((lane >> 3) & 1)) * 768 + (lane >> 4) * 128 + (((lane & 7) * 16) ^ (((lane >> 3) & 1) * 64)));
    uint32_t oa = opq(sb + SM_O + j * 6144 + (2 * w + ((lane >> 3) & 1)) * 768 + (lane >> 4) * 128 + (lane & 7) * 16);
    uint64_t dA = opq(mkdesc(SBC + SM_K, 128, KS, 0) + j * (8 * KS / 16)), dB = opq(dA + (KSLOT >> 4));
    uint64_t dV[7];
#pragma unroll
    for (int i = 0; i < 7; i++) dV[i] = opq(mkdesc(SBC + SM_V, 768, 128, 0) + j * (8 * 1536 / 16) + i * 192);
    const uint32_t nbK = opq((uint32_t)(N_KRDY + jw)), nbQ = opq((uint32_t)(N_QK0 + jw)), nbV = opq((uint32_t)(N_VQ0 + jw));
    asm volatile("barrier.cluster.wait.aligned;" ::: "memory");
    asm volatile("bar.sync 3, 256;" ::: "memory");
    float T[16];
    TRDECL;
    int b0, b1;
    uint32_t meta, ob = bar + B_ODONE * 8, fb = bar + B_OFREE * 8, fp = 1;
    const uint32_t tb = opq(sb + SM_RPB + (variant < 4 ? 3 : variant + 1 - 2 * w) * 4);
    const bool own = ((w ^ head) & 2) == 0;
    const uint32_t dst13 = sb + SM_TIN2 + head * 6144 + (2 * j + (w & 1)) * 1536, src13 = opq(own ? dst13 : sb + SM_S + (2 * j + (w & 1)) * 1536);
    const uint32_t snd[4] = {opq(own ? 0u : mapa(dst13, base + (head ^ 2))), opq(mapa(bar + (B_TIN + 2) * 8, base + (head ^ 2))),
                             opq(mapa(dst13, base + (w & 2) + (~head & 1))), opq(mapa(bar + (B_TIN + 3) * 8, base + (w & 2) + (~head & 1)))};
    BandCfg nx;
    band_cfg(0, tb, nx);
    band_load(nx, T, b0, b1, meta);
    band_cfg(1, tb, nx);
    const uint32_t zero = opq(blockIdx.x >> 16);
    uint32_t special = opq(0x380Au << 1);
    uint32_t q[12];
    mbar_wait(bar + B_Q0 * 8, 0);
#pragma unroll
    for (int k = 0; k < 3; k++) ldsm4(qa + k * 256, q[4 * k], q[4 * k + 1], q[4 * k + 2], q[4 * k + 3]);
    nb_arrive(N_Q0, 384);
#pragma unroll 1
    for (int b = 0; b < 14; b++) {
      float SA[56], SB[56];
      TR(0, b, 0);
      if (jw) mbar_wait(bar + B_KIMP * 8, b & 1);
      nb_sync(nbK, 256);
      TR(0, b, 1);
      TR(0, b - 1, 9);
      wg_fence();
      wg_rs112<0>(SA, q[0], q[1], q[2], q[3], dA);
      wg_rs112<0>(SB, q[0], q[1], q[2], q[3], dB);
      wg_rs112<1>(SA, q[4], q[5], q[6], q[7], dA + 16);
      wg_rs112<1>(SB, q[4], q[5], q[6], q[7], dB + 16);
      wg_rs112<1>(SA, q[8], q[9], q[10], q[11], dA + 32);
      wg_rs112<1>(SB, q[8], q[9], q[10], q[11], dB + 32);
      wg_commit();
      nb_arrive(nbQ, 256);
      { const uint64_t t = dA; dA = dB; dB = t; }
      special >>= 1;
      if (special & 1) {
        if (b == 3) band_cfg(13, tb, nx);
        else {
          if (b == 1 || b == 13) band_load(nx, T, b0, b1, meta);
          if (b >= TB) {
            ob = bar + (b == 13 ? (own ? B_TIN + 2 : B_ODONE) : B_OTAIL + 2 * (b - TB) + jw) * 8;
            if (b > TB) { fb = bar + (B_TFREE + b - 12) * 8; fp = 0; }
            oa += b == 12 ? 0u - (SM_O - SM_Q) : (b == 13 ? src13 - (sb + SM_Q + wt * 1536) : 0);
          }
        }
      }
      TR(0, b, 2);
      wg_wait<0>(); pin(SA); pin(SB);
      mbar_arrive_elect(bar + B_KFREE * 8);
      TR(0, b, 3);
      TR(0, b - 1, 10);
      uint32_t P[28];
      float sx[8];
      if (v2) {
        if (v1) softmax_tile<6, 7>(SA, SB, T, b0, b1, P, sx, nbV, zero, qa, q); else softmax_tile<4, 5>(SA, SB, T, b0, b1, P, sx, nbV, zero, qa, q);
      } else if (!v4) {
        if (v1) softmax_tile<2, 3>(SA, SB, T, b0, b1, P, sx, nbV, zero, qa, q); else softmax_tile<0, 1>(SA, SB, T, b0, b1, P, sx, nbV, zero, qa, q);
      } else {
        if (v1) softmax_tile<4, 4>(SA, SB, T, b0, b1, P, sx, nbV, zero, qa, q); else softmax_tile<3, 3>(SA, SB, T, b0, b1, P, sx, nbV, zero, qa, q);
      }
      float O[24];
      TR(0, b, 4);
      wg_fence();
      wg_sp48<0>(O, P[0], P[1], P[2], P[3], dV[0], meta);
#pragma unroll
      for (int s = 1; s < 7; s++) wg_sp48<1>(O, P[4 * s], P[4 * s + 1], P[4 * s + 2], P[4 * s + 3], dV[s], meta);
      wg_commit();
      nb_arrive(N_PVISS, 384);
      TR(0, b, 6);
      mbar_wait(fb, fp);
      wg_wait<0>(); pin(O);
      mbar_arrive_elect(bar + B_VFREE * 8);
      TR(0, b, 7);
      float ru, rl;
      asm("rcp.approx.ftz.f32 %0, %1;" : "=f"(ru) : "f"(((fmaf(O[0], 0.f, sx[0]) + sx[1]) + sx[2]) + sx[3]));
      asm("rcp.approx.ftz.f32 %0, %1;" : "=f"(rl) : "f"(((fmaf(O[2], 0.f, sx[4]) + sx[5]) + sx[6]) + sx[7]));
#pragma unroll
      for (int i = 0; i < 3; i++)
        stsm4(oa + i * 256, pack2(O[8 * i] * ru, O[8 * i + 1] * ru), pack2(O[8 * i + 2] * rl, O[8 * i + 3] * rl),
              pack2(O[8 * i + 4] * ru, O[8 * i + 5] * ru), pack2(O[8 * i + 6] * rl, O[8 * i + 7] * rl));
      publish(ob);
      fp ^= 1;
      meta ^= 0x55555555u;
      TR(0, b, 8);
    }
    asm volatile("{\n.reg .pred p, q;\nsetp.ne.b32 q, %1, 0;\nelect.sync _|p, 0xffffffff;\nand.pred q, q, p;\n"
                 "@q cp.async.bulk.shared::cluster.shared::cta.mbarrier::complete_tx::bytes [%1], [%0], 1536, [%2];\n"
                 "@p cp.async.bulk.shared::cluster.shared::cta.mbarrier::complete_tx::bytes [%3], [%0], 1536, [%4];\n}"
                 ::"r"(src13), "r"(snd[0]), "r"(snd[1]), "r"(snd[2]), "r"(snd[3]) : "memory");
    if (jw == 0) nb_arrive(3, 256);
    TRDUMP;
    cluster_sync();
  } else if (warp < 12) {
    TRDECL;
    TR(2, -3, 0);
    asm volatile("setmaxnreg.inc.sync.aligned.u32 %0;" ::"n"(RG));
    TR(2, -3, 1);
    GemmCtx c;
    c.bar = bar;
    const int gw = warp - 8, tk = gw * 16 + (lane & 15), hi = lane >> 4;
    { const int col = tk >> 2, i = tk & 3;
      c.kC = sb + SM_K + (col + 3) * KS + hi * 128 + i * 16;
      c.vC[0] = sb + SM_V + (col + 3) * 1536 + hi * 128 + (2 * i + ((col + 3) & 1)) * 16;
      c.qC[0] = sb + SM_Q + col * 768 + hi * 128 + (col & 1) * 64 + i * 16; }
    { const int kc = gw - 1 + 19 * odd, i = lane & 7; c.hvalid = gw > 0; c.edge = gw == (odd ? 0 : 3);
      c.kH = sb + SM_K + kc * KS + (lane >> 3) * 128 + i * 16;
      c.vH[0] = sb + SM_V + kc * 1536 + (lane >> 3) * 128 + (i >> 2) * 768 + (2 * (i & 3) + ((kc ^ (i >> 2)) & 1)) * 16; }
    Stage xs[3];
#pragma unroll
    for (int i = 0; i < 3; i++) {
      const int p = (i + 1) % 3;
      xs[i].lo = (uint32_t)mkdesc(SBC + SM_X + p * 24576, 16, 0, 0); xs[i].full = bar + (B_FULL + p) * 8;
      xs[i].em = opq(mapa(bar + (B_EMPTY + p) * 8, base + p)); xs[i].par = 0;
    }
    c.never = x == nullptr;
    c.kC = opq(c.kC); c.kH = opq(c.kH);
    c.vC[1] = opq(c.vC[0] ^ 16); c.vC[0] = opq(c.vC[0]);
    c.vH[1] = opq(c.vH[0] ^ 16); c.vH[0] = opq(c.vH[0]);
    c.qC[1] = opq(c.qC[0] ^ 64); c.qC[0] = opq(c.qC[0]);
    c.spin = 0;
    c.hiA = (uint32_t)(mkdesc(0, 0, 1024, 1) >> 32) + (blockIdx.x >> 16); c.hiB = (uint32_t)(mkdesc(0, 0, 256, 3) >> 32) + (blockIdx.x >> 16);
    asm volatile("barrier.cluster.wait.aligned;" ::: "memory");
    TR(2, -3, 2);
#pragma unroll
    for (int i = 0; i < 2 * NL; i++) sts128(wdst + (i & 1) * 3072 + (i / 2) * 18432, wv[i]);
    fence_async();
    TR(2, -3, 3);
    asm volatile("bar.sync 1, 384;" ::: "memory");
    TR(2, -3, 4);
    mbar_wait(bar + B_WK * 8, 0);
    TR(2, -3, 5);
    uint32_t pk[12], pv[12], pq[12], hk1[6], hv1[6];
    gemm_iter<true, 0>(c, -2, pk, pv, pq, hk1, hv1, xs[0], xs[1], xs[2] TRPASS);
    TR2(blockIdx.x, 4);
    c.hiA = opq(c.hiA); c.hiB = opq(c.hiB);
#pragma unroll 1
    for (int b = -1;; b += 2) {
      gemm_iter<false, 1>(c, b, pk, pv, pq, hk1, hv1, xs[2], xs[0], xs[1] TRPASS);
      if (b == 11) break;
      gemm_iter<false, 0>(c, b + 1, pk, pv, pq, hk1, hv1, xs[2], xs[0], xs[1] TRPASS);
      const Stage t = xs[2]; xs[2] = xs[1]; xs[1] = xs[0]; xs[0] = t;
    }
    TR2(blockIdx.x, 6);
    c.hiA = opq(c.hiA); c.hiB = opq(c.hiB);
    const uint32_t st = sb + gw * 3072;
    const uint32_t sta = st + (lane & 15) * 64 + ((hi ^ ((lane >> 1) & 3)) * 16);
    const int oc = ph * 112 + strip * 16 + 8 * (gw >> 1) + 4 * (head >> 1) + 2 * (gw & 1), och = pw * 6 + (head & 1) * 3;
    float D0[48], D1[48];
    mbar_arrive_elect(bar + B_WOFREE * 8);
    dump12<128>(c.qC[1], pq);
    nb_sync(N_QK1, 256);
    issue_halo<0, 8>(c, xs[2], D1);
    fence_async();
    nb_arrive(N_VQ0, 288); nb_arrive(N_VQ1, 288); nb_arrive(N_PVISS, 384);
    issue_halo<8, 12>(c, xs[2], D1);
    gwait<0>(c, B_KFREE);
    dump12<128>(c.kC, pk);
    if (c.edge) publish(bar + B_XK * 8);
    wg_wait<0>(); pin(D1);
    pack6(hk1, D1, 0);
    if (c.hvalid) dump6(c.kH, hk1);
    tail_free(bar + (B_TFREE + 1) * 8);
    pack6(hv1, D1, 24);
    fence_async();
    nb_arrive(N_KRDY, 256);
    gwait<0>(c, B_VFREE);
    dump12<128>(c.vC[0], pv);
    if (c.hvalid) dump6(c.vH[0], hv1);
    fence_async();
    edge_ready(c, B_XV);
    nb_arrive(N_VQ0, 288); nb_arrive(N_VQ1, 288);
    gwait<0>(c, B_WO);
    gwait<0>(c, B_TIN);
    TR(2, 13, 0);
    nb_sync(N_QK1, 256);
    issue_proj<SM_TIN0>(D0);
    wg_wait<0>(); pin(D0);
    TR(2, 13, 1);
    store_proj(D0, &mp.ot, st + SM_TST, sta + SM_TST, 8 * TB, oc, och);
    gwait<0>(c, B_TIN + 1);
    TR(2, 13, 2);
    nb_sync(N_PVISS, 384);
    nb_sync(3, 256);
    issue_proj<SM_TIN1>(D1);
    wg_wait<0>(); pin(D1);
    TR(2, 13, 3);
    store_proj(D1, &mp.ot, st + SM_TIN0, sta + SM_TIN0, 8 * TB + 8, oc, och);
    TR(2, 13, 4);
    gwait<0>(c, B_TIN + 2);
    TR(2, 13, 5);
    issue_proj_half<0>(D0, head & 1);
    gwait<0>(c, B_TIN + 3);
    TR(2, 13, 6);
    issue_proj_half<1>(D0, ~head & 1);
    asm volatile("barrier.cluster.arrive.relaxed.aligned;" ::: "memory");
    wg_wait<0>(); pin(D0);
    store_proj(D0, &mp.ot, st + SM_TIN0 + 12288, sta + SM_TIN0 + 12288, 8 * TB + 16, oc, och);
    TR(2, 13, 7);
    if (lane == 0) asm volatile("cp.async.bulk.wait_group.read 0;" ::: "memory");
    __syncwarp();
    TR(2, 13, 8);
    TR2(blockIdx.x, 2);
    TRDUMP;
    asm volatile("barrier.cluster.wait.aligned;" ::: "memory");
  } else {
    if (warp == 12) {
      if (elect_one()) {
        mbar_init(bar + B_WK * 8, 1);
#pragma unroll
        for (int i = 0; i < NL; i++) load_w(&mp.w, sb + SM_W + (3 * i + 5 - 2 * va) * 6144, bar + B_WK * 8, ((i + 1) % 3) * 192 + head * 48 + 32 - 32 * va);
        asm volatile("prefetch.tensormap [%0];" ::"l"(head == 1 ? &mp.xh : &mp.xc) : "memory");
        mbar_expect(bar + B_WK * 8, NL * 6144);
      }
    } else if (warp == 15) {
      const int col = min(max(strip * 16 - 3 + min(lane, 21), 0), 111);
      const uint8_t* p = reinterpret_cast<const uint8_t*>(x) + (uint32_t)(head * ROWB + (ph * 112 + col) * 768 + pw * 384);
#pragma unroll
      for (int i = 0; i < 3; i++) asm volatile("prefetch.global.L2 [%0];" ::"l"(p + i * 128));
    } else if (elect_one()) {
      if (warp == 13) {
#pragma unroll
        for (int i = 0; i < B_WK; i++) mbar_init(bar + i * 8, i < B_EMPTY ? 1 : (i < B_TIN ? 16 : (i < B_TFREE ? (i == B_TIN + 2 ? 5 : 1) : 16)));
      } else {
#pragma unroll
        for (int i = B_WQ; i < B_COUNT; i++) mbar_init(bar + i * 8, i < B_XK ? 1 : (i < B_Q0 ? 2 : (i < B_ODONE ? 4 : (i == B_VFREE ? 9 : 8))));
        mbar_arrive(bar + B_XK * 8); mbar_arrive(bar + B_XV * 8);
      }
    }
    asm volatile("fence.mbarrier_init.release.cluster;" ::: "memory");
    __syncwarp();
    asm volatile("barrier.cluster.arrive.relaxed.aligned;" ::: "memory");
    asm volatile("setmaxnreg.dec.sync.aligned.u32 24;");
    asm volatile("griddepcontrol.launch_dependents;");
    asm volatile("barrier.cluster.wait.aligned;" ::: "memory");
    if (warp == 12) {
      const int cc = ph * 112 + strip * 16, ch = cc + (odd ? 16 : (strip ? -3 : 0)), rh = strip ? -4 : 112;
      const uint32_t fb = bar + (B_FULL + head) * 8, eb = bar + (B_EMPTY + head) * 8, dst = sb + SM_X + head * 24576;
      int t = head == 0 ? 2 : head - 1;
      const CUtensorMap* mx = t ? &mp.xc : &mp.xh;
      int row = t ? 4 * t - 4 : rh;
#pragma unroll 1
      for (int n = 0; n < (head == 3 ? 1 : 12); n++) {
        const bool halo = mx == &mp.xh;
        if (n) mbar_wait(eb, (n - 1) & 1);
        if (head < 3) {
          if (elect_one())
            asm volatile("cp.async.bulk.tensor.4d.shared::cluster.global.mbarrier::complete_tx::bytes.multicast::cluster [%0], [%1, {%3,%4,%5,%6}], [%2], %7;"
                         ::"r"(dst + (halo ? 2048 : 0)), "l"(mx), "r"(fb), "r"(0), "r"(row), "r"(halo ? ch : cc), "r"(pw * 3), "h"((uint16_t)(15 << base)) : "memory");
          __syncwarp();
          if (lane < 4) remote_expect(mapa(fb, base + lane), halo ? 18432 : 24576);
          __syncwarp();
        }
        t += 3;
        const int hn = t / 5;
        mx = t != 5 * hn ? &mp.xc : &mp.xh;
        row = t != 5 * hn ? 4 * (t - hn - 1) : rh + 16 * hn;
        if (elect_one()) {
          if (n == 0) {
#pragma unroll
            for (int i = 0; i < 3; i++) load_w(&mp.w, sb + SM_W + i * 6144, bar + B_WQ * 8, head * 48 + i * 16);
            mbar_expect(bar + B_WQ * 8, 18432);
            mbar_expect(bar + B_TIN * 8, 24576); mbar_expect(bar + (B_TIN + 1) * 8, 24576); mbar_expect(bar + (B_TIN + 2) * 8, 6144); mbar_expect(bar + (B_TIN + 3) * 8, 12288);
          }
          if (head < 3 && n < 11) asm volatile("cp.async.bulk.prefetch.tensor.4d.L2.global [%0, {%1,%2,%3,%4}];" ::"l"(mx), "r"(0), "r"(row), "r"(t != 5 * hn ? cc : ch), "r"(pw * 3) : "memory");
        }
        __syncwarp();
      }
      mbar_wait(bar + B_WOFREE * 8, 0);
      if (elect_one()) {
        mbar_expect(bar + B_WO * 8, 36864);
        asm volatile("cp.async.bulk.tensor.3d.shared::cluster.global.mbarrier::complete_tx::bytes [%0], [%1, {%3,%4,%5}], [%2];"
                     ::"r"(sb + SM_TWO), "l"(&mp.wo), "r"(bar + B_WO * 8), "r"(0), "r"(0), "r"((head & 1) * 3) : "memory");
      }
      __syncwarp();
    }
    if (warp & 1) {
      const uint32_t partner = (blockIdx.x & 7) ^ 4;
      const int cs = odd ? 3 : (strip == 6 ? 15 : 16), cd = odd || strip == 6 ? 19 : 0;
      const uint32_t rb = opq(mapa(bar, partner));
      TRDECL;
      if (warp == 13) {
        const uint32_t dst = opq(mapa(sb + SM_V + cd * 1536, partner)), src = opq(sb + SM_V + cs * 1536);
#pragma unroll 1
        for (int b = 0;; b++) {
          const uint32_t pa = b & 1;
          nb_arrive(N_VQ0, 288);
          mbar_wait(bar + B_XV * 8, pa);
          TR(1, b, 0);
          if (elect_one()) { copy_remote(dst, src, 4608, rb + B_VIMP * 8); remote_expect(rb + B_VIMP * 8, 4608); }
          __syncwarp();
          TR(1, b, 1);
          mbar_wait(bar + B_VIMP * 8, pa);
          TR(1, b, 2);
          nb_arrive(N_VQ1, 288);
          if (elect_one()) remote_arrive(rb + B_VFREE * 8);
          __syncwarp();
          TR(1, b, 3);
          if (b == 13) break;
          mbar_wait(bar + B_VFREE * 8, pa);
          if (elect_one()) remote_arrive(rb + B_XV * 8);
          __syncwarp();
        }
      } else {
        const uint32_t dst = opq(mapa(sb + SM_K + cd * KS, partner)), src = opq(sb + SM_K + cs * KS);
#pragma unroll 1
        for (int b = 0;; b++) {
          const uint32_t pa = b & 1, so = (pa ^ 1) * KSLOT;
          mbar_wait(bar + B_XK * 8, pa);
          TR(1, b - 1, 4);
          if (elect_one()) {
            copy_remote(dst + so, src + so, 3 * KS, rb + B_KIMP * 8);
            if (b == 0) copy_remote(dst, src, 3 * KS, rb + B_KIMP * 8);
            remote_expect(rb + B_KIMP * 8, b ? 3 * KS : 6 * KS);
          }
          __syncwarp();
          TR(1, b - 1, 5);
          TR(1, b - 1, 7);
          if (b == 13) break;
          mbar_wait(bar + B_KFREE * 8, pa);
          if (elect_one()) remote_arrive(rb + B_XK * 8);
          __syncwarp();
        }
      }
      TRDUMP;
    }
    if (warp == 14) {
      int* flag = g_flags + (par * 7 + strip) * 2;
#pragma unroll 1
      for (int b = 0; b < TB; b++) {
        mbar_wait(bar + B_ODONE * 8, b & 1);
        if (lane == 0) {
#pragma unroll 1
          for (int i = 0; i < 16; i += OCH) {
            asm volatile("cp.async.bulk.tensor.3d.global.shared::cta.bulk_group [%0, {%2,%3,%4}], [%1];"
                         ::"l"(&mp.os), "r"(sb + SM_O + i * 768), "r"(pw * 192), "r"(8 * b + 2 * head), "r"(ph * 112 + strip * 16 + i) : "memory");
            asm volatile("cp.async.bulk.commit_group;\ncp.async.bulk.wait_group 0;" ::: "memory");
          }
        }
        __syncwarp();
        mbar_arrive_elect(bar + B_OFREE * 8);
        if (lane == 0)
          asm volatile("fence.proxy.async.global;\nfence.acq_rel.gpu;\nred.relaxed.gpu.global.add.s32 [%0], 1;\nred.relaxed.gpu.global.add.s32 [%0+4], 1;"
                       ::"l"(flag + b * 56) : "memory");
        __syncwarp();
      }
#pragma unroll 1
      for (int t = 0; t < 4; t++) {
        const int i = t >> 1, jw = t & 1, j = jw ^ odd;
        if (!jw) mbar_wait(bar + (B_TFREE + i) * 8, 0);
        mbar_wait(bar + (B_OTAIL + t) * 8, 0);
        if (elect_one()) {
#pragma unroll 1
          for (int d = 0; d < 8; d++) {
            const int dst = (d + head) & 3, pc = d >> 2;
            send_o<1536>(sb + (i ? SM_TIN1 : SM_TIN0) + head * 6144 + j * 3072 + pc * 1536,
                         sb + (i ? SM_Q : SM_O) + (4 * j + (dst & 2) + pc) * 1536, bar + (B_TIN + i) * 8, base + dst);
          }
        }
        __syncwarp();
      }
    }
    cluster_sync();
  }
}

constexpr int NSTB = 6;
constexpr int NTB = TB * 56;
constexpr int SM_B_ST = 0;
constexpr int SM_B_IN = 73728;
constexpr int SM_B_W = SM_B_IN + 3 * 24576;
constexpr int SM_B_BAR = SM_B_IN + NSTB * 24576;
constexpr int SM_B_TOTAL = SM_B_BAR + 512;
struct MapsB { CUtensorMap oi, oo, wo; };

__global__ void __launch_bounds__(512, 1)
na_proj_kernel(const __grid_constant__ MapsB mp) {
  extern __shared__ __align__(1024) uint8_t smem_raw[];
  const uint32_t sb = smem_u32(smem_raw);
  if ((sb & 0x3FFFF) != SBC) return;
  const uint32_t bar = sb + SM_B_BAR;
  const int tid = threadIdx.x, lane = tid & 31;
  const int warp = __shfl_sync(0xffffffffu, tid >> 5, 0);
  TR2(132 + blockIdx.x, 0);
  TRB(47, 0);
  if (warp == 12 && elect_one()) {
#pragma unroll
    for (int i = 0; i <= 2 * NSTB; i++) mbar_init(bar + i * 8, i < NSTB || i == 2 * NSTB ? 1 : 12);
    asm volatile("st.shared.u32 [%0], 0;" ::"r"(bar + 120) : "memory");
    mbar_expect(bar + 2 * NSTB * 8, 73728);
#pragma unroll
    for (int i = 0; i < 2; i++)
      asm volatile("cp.async.bulk.tensor.3d.shared::cluster.global.mbarrier::complete_tx::bytes [%0], [%1, {%3,%4,%5}], [%2];"
                   ::"r"(sb + SM_B_W + i * 36864), "l"(&mp.wo), "r"(bar + 2 * NSTB * 8), "r"(0), "r"(0), "r"(i * 3) : "memory");
  }
  __syncthreads();
  const int step = gridDim.x;
  if (warp == 15) {
    int so = 0;
    nb_arrive(4, 288); nb_arrive(5, 288); nb_arrive(6, 288);
#pragma unroll 1
    for (int n = blockIdx.x, tk = 0; n < NTB; n += step, tk++) {
      uint32_t cc = 0;
#pragma unroll
      for (int wg = 0; wg < 3; wg++) {
        if (lane == 0) asm volatile("cp.async.bulk.wait_group.read 5;" ::: "memory");
        nb_sync(1 + wg, 160);
        if (wg == 0 || n + step < NTB) nb_arrive(4 + wg, 288);
        if (wg == 0) asm volatile("ld.shared.u32 %0, [%1];" : "=r"(cc) : "r"(bar + 128 + tk * 4) : "memory");
        if (lane == 0) {
          asm volatile("cp.async.bulk.tensor.4d.global.shared::cta.bulk_group [%0, {%2,%3,%4,%5}], [%1];"
                       ::"l"(&mp.oo), "r"(sb + SM_B_ST + wg * 8192 + so), "r"(0), "r"((cc >> 8) & 255), "r"(cc >> 16), "r"((cc & 1) * 3 + wg) : "memory");
          asm volatile("cp.async.bulk.commit_group;" ::: "memory");
        }
        __syncwarp();
      }
      so = so == 49152 ? 0 : so + 24576;
    }
    if (lane == 0) asm volatile("cp.async.bulk.wait_group.read 0;" ::: "memory");
  } else if (warp >= 12) {
    nb_sync(7, 480);
#pragma unroll 1
    for (int n = blockIdx.x + (warp - 12) * step; n < NTB; n += 3 * step) {
      const int b = n / 56, rem = n - b * 56, par = rem / 14;
      const int c0 = opq((uint32_t)(par & 1)), c1 = opq((uint32_t)(8 * b)), c2 = opq((uint32_t)((par >> 1) * 112 + (rem - par * 14) * 8));
      int v; uint32_t spin = 0, tk = 0;
      do { asm volatile("ld.acquire.gpu.global.s32 %0, [%1];" : "=r"(v) : "l"(g_flags + n) : "memory"); } while (v < 4 && ++spin < SPIN_LIMIT);
      if (lane == 0) asm volatile("atom.shared.add.u32 %0, [%1], 1;" : "=r"(tk) : "r"(bar + 120) : "memory");
      asm volatile("fence.proxy.async.global;" ::: "memory");
      tk = __shfl_sync(0xffffffffu, tk, 0);
      TRB(tk, 0);
      const uint32_t use = tk / NSTB, sg = tk - use * NSTB;
      if (use) mbar_wait(bar + (NSTB + sg) * 8, (use - 1) & 1);
      TRB(tk, 1);
      if (elect_one()) {
        asm volatile("st.shared.u32 [%0], %1;" ::"r"(bar + 128 + tk * 4), "r"(c0 | c1 << 8 | c2 << 16) : "memory");
        mbar_expect(bar + sg * 8, 24576);
        asm volatile("cp.async.bulk.tensor.3d.shared::cluster.global.mbarrier::complete_tx::bytes [%0], [%1, {%3,%4,%5}], [%2];"
                     ::"r"(sb + SM_B_IN + sg * 24576), "l"(&mp.oi), "r"(bar + sg * 8), "r"(c0 * 192), "r"(c1), "r"(c2) : "memory");
        g_flags[n] = 0;
      }
      __syncwarp();
    }
  } else {
    const int wg = warp >> 2, w = warp & 3;
    uint32_t a[48];
    mbar_wait(bar + 2 * NSTB * 8, 0);
    {
      const int k = (lane & 7) + (lane >> 4) * 8, ch = (warp & 1) * 2 + ((lane >> 3) & 1);
      const uint32_t wa = sb + SM_B_W + (warp >> 1) * 12288 + k * 64 + ((ch ^ ((k >> 1) & 3)) * 16);
#pragma unroll
      for (int i = 0; i < 12; i++)
        asm volatile("ldmatrix.sync.aligned.m8n8.x4.trans.shared.b16 {%0,%1,%2,%3}, [%4];"
                     : "=r"(a[4 * i]), "=r"(a[4 * i + 1]), "=r"(a[4 * i + 2]), "=r"(a[4 * i + 3]) : "r"(wa + i * 1024) : "memory");
    }
    nb_sync(7, 480);
    TRB(47, 1);
    const uint32_t sta = opq(sb + SM_B_ST + wg * 8192 + ((lane & 7) + (lane >> 4) * 8) * 128 + (((2 * w + ((lane >> 3) & 1)) ^ (lane & 7)) * 16));
    const uint32_t hi = opq((uint32_t)(mkdesc(0, 0, 3072, 0) >> 32) + (blockIdx.x >> 16)), bb = opq(bar);
    const uint32_t nbT = opq((uint32_t)(4 + wg)), nbN = opq((uint32_t)(wg == 2 ? 4 : 5 + wg)), nbD = opq((uint32_t)(1 + wg));
    int left = (NTB - blockIdx.x + step - 1) / step;
    if (wg == 2) nb_arrive(4, 288);
#pragma unroll 1
    for (uint32_t ph = 0;; ph ^= 1) {
#pragma unroll
      for (int sg = 0; sg < NSTB; sg++) {
        constexpr uint64_t db = mkdesc(SBC + SM_B_IN, 128, 3072, 0);
        float D[32];
        mbar_wait(bb + sg * 8, ph);
        nb_sync(nbT, 288);
        wg_fence();
        wg_rs64<0>(D, a[0], a[1], a[2], a[3], dsc(db + sg * 1536, hi));
#pragma unroll
        for (int k = 1; k < 12; k++) wg_rs64<1>(D, a[4 * k], a[4 * k + 1], a[4 * k + 2], a[4 * k + 3], dsc(db + sg * 1536 + k * 16, hi));
        wg_commit();
        nb_arrive(nbN, 288);
        wg_wait<0>(); pin(D);
        mbar_arrive_elect(bb + (NSTB + sg) * 8);
#pragma unroll
        for (int q = 0; q < 4; q++)
          asm volatile("stmatrix.sync.aligned.m8n8.x4.trans.shared.b16 [%0], {%1,%2,%3,%4};" ::"r"(sta + (sg % 3) * 24576 + q * 2048),
                       "r"(pack2(D[8 * q], D[8 * q + 1])), "r"(pack2(D[8 * q + 2], D[8 * q + 3])), "r"(pack2(D[8 * q + 4], D[8 * q + 5])), "r"(pack2(D[8 * q + 6], D[8 * q + 7])) : "memory");
        fence_async();
        nb_arrive(nbD, 160);
        if (wg == 0) TRB(31 - left, 5);
        if (--left == 0) goto done;
      }
    }
  done:
    if (wg == 0) nb_arrive(4, 288);
    TR2(132 + blockIdx.x, 2);
  }
}

typedef CUresult (*EncodeFn)(CUtensorMap*, CUtensorMapDataType, cuuint32_t, void*, const cuuint64_t*, const cuuint64_t*, const cuuint32_t*,
                             const cuuint32_t*, CUtensorMapInterleave, CUtensorMapSwizzle, CUtensorMapL2promotion, CUtensorMapFloatOOBfill);
static EncodeFn g_enc = nullptr;
static void make_map(CUtensorMap* m, const void* p, int rank, const cuuint64_t* dim, const cuuint64_t* str, const cuuint32_t* box, CUtensorMapSwizzle sw) {
  const cuuint32_t ones[5] = {1, 1, 1, 1, 1};
  g_enc(m, CU_TENSOR_MAP_DATA_TYPE_BFLOAT16, rank, (void*)p, dim, str, box, ones, CU_TENSOR_MAP_INTERLEAVE_NONE, sw,
        CU_TENSOR_MAP_L2_PROMOTION_L2_128B, CU_TENSOR_MAP_FLOAT_OOB_FILL_NONE);
}

extern "C" void kernel_launch(void* const* d_in, const int* in_sizes, int n_in, void* d_out, int out_size) {
  const __nv_bfloat16* x = (const __nv_bfloat16*)d_in[0];
  const __nv_bfloat16* wqkv = (const __nv_bfloat16*)d_in[1];
  const __nv_bfloat16* wo = (const __nv_bfloat16*)d_in[2];
  const __nv_bfloat16* rpb = (const __nv_bfloat16*)d_in[3];

  if (!g_enc) {
    void* fn = nullptr; cudaDriverEntryPointQueryResult qr;
    cudaGetDriverEntryPoint("cuTensorMapEncodeTiled", &fn, cudaEnableDefault, &qr);
    g_enc = (EncodeFn)fn;
    cudaFuncSetAttribute(na_attn_kernel, cudaFuncAttributeMaxDynamicSharedMemorySize, SM_A_TOTAL);
    cudaFuncSetAttribute(na_proj_kernel, cudaFuncAttributeMaxDynamicSharedMemorySize, SM_B_TOTAL);
  }
  Maps ma; MapsB mb;
  { cuuint64_t dim[4] = {64, 112, 224, 6}, str[3] = {(cuuint64_t)ROWB, 768, 128};
    cuuint32_t box[4] = {64, 4, 16, 3}, boxh[4] = {64, 16, 3, 3}, boxo[4] = {64, 8, 8, 1};
    make_map(&ma.xc, x, 4, dim, str, box, CU_TENSOR_MAP_SWIZZLE_128B);
    make_map(&ma.xh, x, 4, dim, str, boxh, CU_TENSOR_MAP_SWIZZLE_128B);
    make_map(&mb.oo, d_out, 4, dim, str, boxo, CU_TENSOR_MAP_SWIZZLE_128B); }
  { cuuint64_t dim[3] = {384, 112, 224}, str[2] = {(cuuint64_t)ROWB, 768};
    cuuint32_t box[3] = {192, 8, 8}, boxs[3] = {192, 2, OCH};
    make_map(&mb.oi, d_out, 3, dim, str, box, CU_TENSOR_MAP_SWIZZLE_NONE);
    make_map(&ma.os, d_out, 3, dim, str, boxs, CU_TENSOR_MAP_SWIZZLE_NONE); }
  { cuuint64_t dim[4] = {32, 112, 224, 12}, str[3] = {(cuuint64_t)ROWB, 768, 64};
    cuuint32_t box[4] = {32, 8, 2, 3};
    make_map(&ma.ot, d_out, 4, dim, str, box, CU_TENSOR_MAP_SWIZZLE_64B); }
  { cuuint64_t dim[2] = {576, 192}, str[1] = {1152};
    cuuint32_t box[2] = {16, 192};
    make_map(&ma.w, wqkv, 2, dim, str, box, CU_TENSOR_MAP_SWIZZLE_32B); }
  { cuuint64_t dim[3] = {32, 192, 6}, str[2] = {384, 64};
    cuuint32_t box[3] = {32, 192, 3};
    make_map(&ma.wo, wo, 3, dim, str, box, CU_TENSOR_MAP_SWIZZLE_64B);
    mb.wo = ma.wo; }
  na_attn_kernel<<<112, 512, SM_A_TOTAL>>>(x, wqkv, rpb, ma);
  cudaLaunchConfig_t cfg = {};
  cfg.gridDim = dim3(20); cfg.blockDim = dim3(512); cfg.dynamicSmemBytes = SM_B_TOTAL; cfg.stream = cudaStreamPerThread;
  cudaLaunchAttribute at[1];
  at[0].id = cudaLaunchAttributeProgrammaticStreamSerialization; at[0].val.programmaticStreamSerializationAllowed = 1;
  cfg.attrs = at; cfg.numAttrs = 1;
  cudaLaunchKernelEx(&cfg, na_proj_kernel, mb);
}
```

```cpp
#include <cuda_runtime.h>
#include <cuda_bf16.h>
#include <cuda.h>
#include <stdint.h>

#define SPIN_LIMIT (1u << 18)

__device__ __forceinline__ uint32_t smem_u32(const void* p) { return (uint32_t)__cvta_generic_to_shared(p); }
__device__ __forceinline__ void wg_fence() { asm volatile("wgmma.fence.sync.aligned;" ::: "memory"); }
__device__ __forceinline__ void wg_commit() { asm volatile("wgmma.commit_group.sync.aligned;" ::: "memory"); }
template <int N> __device__ __forceinline__ void wg_wait() { asm volatile("wgmma.wait_group.sync.aligned %0;" ::"n"(N) : "memory"); }
template <int N> __device__ __forceinline__ void pin(float (&d)[N]) {
#pragma unroll
  for (int i = 0; i < N; i++) asm volatile("" : "+f"(d[i])::"memory");
}
__host__ __device__ constexpr uint64_t mkdesc(uint32_t addr, uint32_t lbo, uint32_t sbo, uint32_t sw) {
  return (uint64_t)((addr & 0x3FFFF) >> 4) | ((uint64_t)(lbo >> 4) << 16) | ((uint64_t)(sbo >> 4) << 32) | ((uint64_t)sw << 62);
}
__device__ __forceinline__ void mbar_init(uint32_t bar, uint32_t cnt) { asm volatile("mbarrier.init.shared::cta.b64 [%0], %1;" ::"r"(bar), "r"(cnt) : "memory"); }
__device__ __forceinline__ void mbar_arrive(uint32_t bar) { asm volatile("mbarrier.arrive.shared::cta.b64 _, [%0];" ::"r"(bar) : "memory"); }
__device__ __forceinline__ bool elect_one() {
  uint32_t r; asm volatile("{\n.reg .pred p;\nelect.sync _|p, 0xffffffff;\nselp.u32 %0, 1, 0, p;\n}" : "=r"(r)); return r;
}
__device__ __forceinline__ void mbar_arrive_elect(uint32_t bar) {
  asm volatile("{\n.reg .pred p;\nelect.sync _|p, 0xffffffff;\n@p mbarrier.arrive.shared::cta.b64 _, [%0];\n}" ::"r"(bar) : "memory");
}
__device__ __forceinline__ void mbar_expect(uint32_t bar, uint32_t bytes) { asm volatile("mbarrier.arrive.expect_tx.shared::cta.b64 _, [%0], %1;" ::"r"(bar), "r"(bytes) : "memory"); }
__device__ __forceinline__ void mbar_arrive_remote(uint32_t bar, uint32_t cta) {
  asm volatile("{\n.reg .b32 ra;\nmapa.shared::cluster.u32 ra, %0, %1;\nmbarrier.arrive.relaxed.cluster.shared::cluster.b64 _, [ra];\n}" ::"r"(bar), "r"(cta) : "memory");
}
__device__ __forceinline__ void mbar_wait(uint32_t bar, uint32_t parity) {
  asm volatile("{\n.reg .pred p;\n.reg .b32 n;\nmov.b32 n, 0;\nWL:\nmbarrier.try_wait.parity.shared::cta.b64 p, [%0], %1;\n@p bra WD;\n"
               "add.u32 n, n, 1;\nsetp.lt.u32 p, n, 65536;\n@p bra WL;\nWD:\n}" ::"r"(bar), "r"(parity) : "memory");
}
__device__ __forceinline__ void nb_sync(int id, int n) { asm volatile("bar.sync %0, %1;" ::"r"(id), "r"(n) : "memory"); }
__device__ __forceinline__ void nb_arrive(int id, int n) { asm volatile("bar.arrive %0, %1;" ::"r"(id), "r"(n) : "memory"); }
__device__ __forceinline__ uint32_t opq(uint32_t x) { uint32_t r; asm volatile("mov.b32 %0, %1;" : "=r"(r) : "r"(x)); return r; }
__device__ __forceinline__ uint64_t opq(uint64_t x) { uint64_t r; asm volatile("mov.b64 %0, %1;" : "=l"(r) : "l"(x)); return r; }
__device__ __forceinline__ uint32_t mapa(uint32_t a, uint32_t cta) { uint32_t r; asm("mapa.shared::cluster.u32 %0, %1, %2;" : "=r"(r) : "r"(a), "r"(cta)); return r; }
__device__ __forceinline__ void fence_async() { asm volatile("fence.proxy.async.shared::cta;" ::: "memory"); }
__device__ __forceinline__ void cluster_sync() {
  asm volatile("barrier.cluster.arrive.relaxed.aligned;\nbarrier.cluster.wait.aligned;" ::: "memory");
}
__device__ __forceinline__ uint32_t pack2(float lo, float hi) {
  uint32_t r; asm("cvt.rn.bf16x2.f32 %0, %1, %2;" : "=r"(r) : "f"(hi), "f"(lo)); return r;
}
__device__ __forceinline__ void stsm4(uint32_t a, uint32_t r0, uint32_t r1, uint32_t r2, uint32_t r3) {
  asm volatile("stmatrix.sync.aligned.m8n8.x4.shared.b16 [%0], {%1,%2,%3,%4};" ::"r"(a), "r"(r0), "r"(r1), "r"(r2), "r"(r3) : "memory");
}
__device__ __forceinline__ void ldsm4(uint32_t a, uint32_t& r0, uint32_t& r1, uint32_t& r2, uint32_t& r3) {
  asm volatile("ldmatrix.sync.aligned.m8n8.x4.shared.b16 {%0,%1,%2,%3}, [%4];" : "=r"(r0), "=r"(r1), "=r"(r2), "=r"(r3) : "r"(a) : "memory");
}
__device__ __forceinline__ void sts128(uint32_t a, uint4 v) {
  asm volatile("st.shared.v4.b32 [%0], {%1,%2,%3,%4};" ::"r"(a), "r"(v.x), "r"(v.y), "r"(v.z), "r"(v.w) : "memory");
}
__device__ __forceinline__ float lds_f32(uint32_t a) { float v; asm volatile("ld.shared.f32 %0, [%1];" : "=f"(v) : "r"(a)); return v; }
__device__ __forceinline__ float ex2(float x) { float y; asm("ex2.approx.ftz.f32 %0, %1;" : "=f"(y) : "f"(x)); return y; }

template<int SC> __device__ __forceinline__ void wg_ss144(float (&d)[72], uint64_t da, uint64_t db) {
  asm volatile("{\n.reg .pred p;\nsetp.ne.b32 p, %74, 0;\nwgmma.mma_async.sync.aligned.m64n144k16.f32.bf16.bf16 {%0,%1,%2,%3,%4,%5,%6,%7,%8,%9,%10,%11,%12,%13,%14,%15,%16,%17,%18,%19,%20,%21,%22,%23,%24,%25,%26,%27,%28,%29,%30,%31,%32,%33,%34,%35,%36,%37,%38,%39,%40,%41,%42,%43,%44,%45,%46,%47,%48,%49,%50,%51,%52,%53,%54,%55,%56,%57,%58,%59,%60,%61,%62,%63,%64,%65,%66,%67,%68,%69,%70,%71}, %72, %73, p, 1, 1, 0, 1;\n}\n"
    : "+f"(d[0]),"+f"(d[1]),"+f"(d[2]),"+f"(d[3]),"+f"(d[4]),"+f"(d[5]),"+f"(d[6]),"+f"(d[7]),"+f"(d[8]),"+f"(d[9]),"+f"(d[10]),"+f"(d[11]),"+f"(d[12]),"+f"(d[13]),"+f"(d[14]),"+f"(d[15]),"+f"(d[16]),"+f"(d[17]),"+f"(d[18]),"+f"(d[19]),"+f"(d[20]),"+f"(d[21]),"+f"(d[22]),"+f"(d[23]),"+f"(d[24]),"+f"(d[25]),"+f"(d[26]),"+f"(d[27]),"+f"(d[28]),"+f"(d[29]),"+f"(d[30]),"+f"(d[31]),"+f"(d[32]),"+f"(d[33]),"+f"(d[34]),"+f"(d[35]),"+f"(d[36]),"+f"(d[37]),"+f"(d[38]),"+f"(d[39]),"+f"(d[40]),"+f"(d[41]),"+f"(d[42]),"+f"(d[43]),"+f"(d[44]),"+f"(d[45]),"+f"(d[46]),"+f"(d[47]),"+f"(d[48]),"+f"(d[49]),"+f"(d[50]),"+f"(d[51]),"+f"(d[52]),"+f"(d[53]),"+f"(d[54]),"+f"(d[55]),"+f"(d[56]),"+f"(d[57]),"+f"(d[58]),"+f"(d[59]),"+f"(d[60]),"+f"(d[61]),"+f"(d[62]),"+f"(d[63]),"+f"(d[64]),"+f"(d[65]),"+f"(d[66]),"+f"(d[67]),"+f"(d[68]),"+f"(d[69]),"+f"(d[70]),"+f"(d[71]) : "l"(da), "l"(db), "n"(SC));
}
template<int SC> __device__ __forceinline__ void wg_ss96(float (&d)[48], uint64_t da, uint64_t db) {
  asm volatile("{\n.reg .pred p;\nsetp.ne.b32 p, %50, 0;\nwgmma.mma_async.sync.aligned.m64n96k16.f32.bf16.bf16 {%0,%1,%2,%3,%4,%5,%6,%7,%8,%9,%10,%11,%12,%13,%14,%15,%16,%17,%18,%19,%20,%21,%22,%23,%24,%25,%26,%27,%28,%29,%30,%31,%32,%33,%34,%35,%36,%37,%38,%39,%40,%41,%42,%43,%44,%45,%46,%47}, %48, %49, p, 1, 1, 0, 1;\n}\n"
    : "+f"(d[0]),"+f"(d[1]),"+f"(d[2]),"+f"(d[3]),"+f"(d[4]),"+f"(d[5]),"+f"(d[6]),"+f"(d[7]),"+f"(d[8]),"+f"(d[9]),"+f"(d[10]),"+f"(d[11]),"+f"(d[12]),"+f"(d[13]),"+f"(d[14]),"+f"(d[15]),"+f"(d[16]),"+f"(d[17]),"+f"(d[18]),"+f"(d[19]),"+f"(d[20]),"+f"(d[21]),"+f"(d[22]),"+f"(d[23]),"+f"(d[24]),"+f"(d[25]),"+f"(d[26]),"+f"(d[27]),"+f"(d[28]),"+f"(d[29]),"+f"(d[30]),"+f"(d[31]),"+f"(d[32]),"+f"(d[33]),"+f"(d[34]),"+f"(d[35]),"+f"(d[36]),"+f"(d[37]),"+f"(d[38]),"+f"(d[39]),"+f"(d[40]),"+f"(d[41]),"+f"(d[42]),"+f"(d[43]),"+f"(d[44]),"+f"(d[45]),"+f"(d[46]),"+f"(d[47]) : "l"(da), "l"(db), "n"(SC));
}
template<int SC> __device__ __forceinline__ void wg_rs112(float (&d)[56], uint32_t a0, uint32_t a1, uint32_t a2, uint32_t a3, uint64_t db) {
  asm volatile("{\n.reg .pred p;\nsetp.ne.b32 p, %61, 0;\nwgmma.mma_async.sync.aligned.m64n112k16.f32.bf16.bf16 {%0,%1,%2,%3,%4,%5,%6,%7,%8,%9,%10,%11,%12,%13,%14,%15,%16,%17,%18,%19,%20,%21,%22,%23,%24,%25,%26,%27,%28,%29,%30,%31,%32,%33,%34,%35,%36,%37,%38,%39,%40,%41,%42,%43,%44,%45,%46,%47,%48,%49,%50,%51,%52,%53,%54,%55}, {%56,%57,%58,%59}, %60, p, 1, 1, 0;\n}\n"
    : "+f"(d[0]),"+f"(d[1]),"+f"(d[2]),"+f"(d[3]),"+f"(d[4]),"+f"(d[5]),"+f"(d[6]),"+f"(d[7]),"+f"(d[8]),"+f"(d[9]),"+f"(d[10]),"+f"(d[11]),"+f"(d[12]),"+f"(d[13]),"+f"(d[14]),"+f"(d[15]),"+f"(d[16]),"+f"(d[17]),"+f"(d[18]),"+f"(d[19]),"+f"(d[20]),"+f"(d[21]),"+f"(d[22]),"+f"(d[23]),"+f"(d[24]),"+f"(d[25]),"+f"(d[26]),"+f"(d[27]),"+f"(d[28]),"+f"(d[29]),"+f"(d[30]),"+f"(d[31]),"+f"(d[32]),"+f"(d[33]),"+f"(d[34]),"+f"(d[35]),"+f"(d[36]),"+f"(d[37]),"+f"(d[38]),"+f"(d[39]),"+f"(d[40]),"+f"(d[41]),"+f"(d[42]),"+f"(d[43]),"+f"(d[44]),"+f"(d[45]),"+f"(d[46]),"+f"(d[47]),"+f"(d[48]),"+f"(d[49]),"+f"(d[50]),"+f"(d[51]),"+f"(d[52]),"+f"(d[53]),"+f"(d[54]),"+f"(d[55]) : "r"(a0), "r"(a1), "r"(a2), "r"(a3), "l"(db), "n"(SC));
}
template<int SC> __device__ __forceinline__ void wg_sp48(float (&d)[24], uint32_t a0, uint32_t a1, uint32_t a2, uint32_t a3, uint64_t db, uint32_t meta) {
  asm volatile("{\n.reg .pred p;\nsetp.ne.b32 p, %30, 0;\nwgmma.mma_async.sp.sync.aligned.m64n48k32.f32.bf16.bf16 {%0,%1,%2,%3,%4,%5,%6,%7,%8,%9,%10,%11,%12,%13,%14,%15,%16,%17,%18,%19,%20,%21,%22,%23}, {%24,%25,%26,%27}, %28, %29, 0, p, 1, 1, 1;\n}\n"
    : "+f"(d[0]),"+f"(d[1]),"+f"(d[2]),"+f"(d[3]),"+f"(d[4]),"+f"(d[5]),"+f"(d[6]),"+f"(d[7]),"+f"(d[8]),"+f"(d[9]),"+f"(d[10]),"+f"(d[11]),"+f"(d[12]),"+f"(d[13]),"+f"(d[14]),"+f"(d[15]),"+f"(d[16]),"+f"(d[17]),"+f"(d[18]),"+f"(d[19]),"+f"(d[20]),"+f"(d[21]),"+f"(d[22]),"+f"(d[23]) : "r"(a0), "r"(a1), "r"(a2), "r"(a3), "l"(db), "r"(meta), "n"(SC));
}
template<int SC> __device__ __forceinline__ void wg_rs64(float (&d)[32], uint32_t a0, uint32_t a1, uint32_t a2, uint32_t a3, uint64_t db) {
  asm volatile("{\n.reg .pred p;\nsetp.ne.b32 p, %37, 0;\nwgmma.mma_async.sync.aligned.m64n64k16.f32.bf16.bf16 {%0,%1,%2,%3,%4,%5,%6,%7,%8,%9,%10,%11,%12,%13,%14,%15,%16,%17,%18,%19,%20,%21,%22,%23,%24,%25,%26,%27,%28,%29,%30,%31}, {%32,%33,%34,%35}, %36, p, 1, 1, 0;\n}\n"
    : "+f"(d[0]),"+f"(d[1]),"+f"(d[2]),"+f"(d[3]),"+f"(d[4]),"+f"(d[5]),"+f"(d[6]),"+f"(d[7]),"+f"(d[8]),"+f"(d[9]),"+f"(d[10]),"+f"(d[11]),"+f"(d[12]),"+f"(d[13]),"+f"(d[14]),"+f"(d[15]),"+f"(d[16]),"+f"(d[17]),"+f"(d[18]),"+f"(d[19]),"+f"(d[20]),"+f"(d[21]),"+f"(d[22]),"+f"(d[23]),"+f"(d[24]),"+f"(d[25]),"+f"(d[26]),"+f"(d[27]),"+f"(d[28]),"+f"(d[29]),"+f"(d[30]),"+f"(d[31]) : "r"(a0), "r"(a1), "r"(a2), "r"(a3), "l"(db), "n"(SC));
}

constexpr uint32_t SBC = 1024;
constexpr int ROWB = 2 * 224 * 384;
constexpr int TB = 11;
constexpr int KS = 832;
constexpr int KSLOT = 22 * KS;
constexpr int SM_X = 0;
constexpr int SM_W = SM_X + 3 * 24576;
constexpr int SM_K = SM_W + 55296;
constexpr int SM_V = SM_K + 2 * KSLOT;
constexpr int SM_Q = SM_V + 22 * 1536;
constexpr int SM_O = SM_Q + 12288;
constexpr int SM_S = SM_O + 12288;
constexpr int SM_RPB = SM_S + 6144;
constexpr int SM_BAR = SM_RPB + 768;
constexpr int SM_A_TOTAL = SM_BAR + 256;
constexpr int SM_TIN0 = SM_X + 24576, SM_TIN1 = SM_X, SM_TIN2 = SM_W + 18432;
constexpr int SM_TWO = SM_X + 2 * 24576;
constexpr int SM_TST = SM_TIN2 + 24576;
enum { B_FULL = 0, B_EMPTY = 3, B_TIN = 6, B_TFREE = 10, B_WK = 12, B_WQ, B_WO, B_KIMP, B_VIMP, B_OFREE, B_XK, B_XV,
       B_Q0, B_WOFREE, B_OTAIL, B_ODONE = B_OTAIL + 4, B_KFREE, B_VFREE, B_COUNT };
enum { N_KRDY = 4, N_QK0, N_QK1, N_VQ0, N_VQ1, N_PVISS, N_Q0 };

#define NL 2
#define OCH 4
#define MID 6
#define SPL 4
#define RA 160
#define RG 168
#define OPT 0
constexpr int FS = 64;
__device__ int g_flags[TB * 56 * FS];

#define TR(role, it, k)
#define TRDECL
#define TRARG
#define TRPASS
#define TRDUMP
#define TRB(it, k)
#define TR2(blk, k)

struct Stage { uint32_t lo, full, em, par; };
struct GemmCtx {
  uint32_t bar;
  uint32_t kC, vC[2], qC[2];
  uint32_t kH, vH[2];
  uint32_t hiA, hiB;
  uint32_t spin;
  bool hvalid, never, edge;
};

template <int STRIDE> __device__ __forceinline__ void dump12(uint32_t a, const uint32_t (&r)[12]) {
#pragma unroll
  for (int j = 0; j < 3; j++) stsm4(a + j * 2 * STRIDE, r[4 * j], r[4 * j + 1], r[4 * j + 2], r[4 * j + 3]);
}
__device__ __forceinline__ void keep12(bool never, uint32_t a, const uint32_t (&r)[12]) { if (never) dump12<128>(a, r); }
template <int N> __device__ __forceinline__ void pack12(uint32_t (&r)[12], const float (&d)[N], int off) {
#pragma unroll
  for (int j = 0; j < 12; j++) r[j] = pack2(d[off + 2 * j], d[off + 2 * j + 1]);
}
__device__ __forceinline__ uint64_t dsc(uint64_t lo, uint32_t hi) { uint64_t r; asm("mov.b64 %0, {%1, %2};" : "=l"(r) : "r"((uint32_t)lo), "r"(hi)); return r; }
template <int K0, int K1> __device__ __forceinline__ void issue_core(const GemmCtx& c, const Stage& x, float (&d)[72]) {
  constexpr uint64_t db = mkdesc(SBC + SM_W, 6144, 256, 3);
  wg_fence();
  if (K0 == 0) wg_ss144<0>(d, dsc(x.lo, c.hiA), dsc(db, c.hiB));
#pragma unroll
  for (int k = K0 ? K0 : 1; k < K1; k++) wg_ss144<1>(d, dsc(x.lo + (k >> 2) * 512 + (k & 3) * 2, c.hiA), dsc(db + k * 32, c.hiB));
  wg_commit();
}
template <int K0, int K1> __device__ __forceinline__ void issue_halo(const GemmCtx& c, const Stage& x, float (&d)[48]) {
  constexpr uint64_t db = mkdesc(SBC + SM_W + 18432, 6144, 256, 3);
  wg_fence();
  if (K0 == 0) wg_ss96<0>(d, dsc(x.lo, c.hiA), dsc(db, c.hiB));
#pragma unroll
  for (int k = K0 ? K0 : 1; k < K1; k++) wg_ss96<1>(d, dsc(x.lo + (k >> 2) * 384 + (k & 3) * 2, c.hiA), dsc(db + k * 32, c.hiB));
  wg_commit();
}
__device__ __forceinline__ void release_stage(const Stage& x) {
  asm volatile("{\n.reg .pred p;\nelect.sync _|p, 0xffffffff;\n@p mbarrier.arrive.shared::cluster.b64 _, [%0];\n}" ::"r"(x.em) : "memory");
}
__device__ __forceinline__ void wait_stage(GemmCtx& c, Stage& x) {
  asm volatile("{\n.reg .pred p;\nWL:\nmbarrier.try_wait.parity.shared::cta.b64 p, [%1], %2;\n@p bra WD;\n"
               "add.u32 %0, %0, 1;\nsetp.lt.u32 p, %0, 0x100000;\n@p bra WL;\nWD:\n}" : "+r"(c.spin) : "r"(x.full), "r"(x.par) : "memory");
  x.par ^= 1;
}
__device__ __forceinline__ void edge_ready(const GemmCtx& c, int bar) { __syncwarp(); if (c.edge) mbar_arrive_elect(c.bar + bar * 8); }
__device__ __forceinline__ void dump6(uint32_t a, const uint32_t (&r)[6]) {
  stsm4(a, r[0], r[1], r[2], r[3]);
  asm volatile("stmatrix.sync.aligned.m8n8.x2.shared.b16 [%0], {%1,%2};" ::"r"(a + 512), "r"(r[4]), "r"(r[5]) : "memory");
}
__device__ __forceinline__ void pack6(uint32_t (&r)[6], const float (&d)[48], int off) {
#pragma unroll
  for (int j = 0; j < 6; j++) r[j] = pack2(d[off + 4 * j], d[off + 4 * j + 1]);
}
template <int PARITY> __device__ __forceinline__ void gwait(GemmCtx& c, int bar) {
  asm volatile("{\n.reg .pred p;\nWL:\nmbarrier.try_wait.parity.shared::cta.b64 p, [%1], %2;\n@p bra WD;\n"
               "add.u32 %0, %0, 1;\nsetp.lt.u32 p, %0, 0x100000;\n@p bra WL;\nWD:\n}" : "+r"(c.spin) : "r"(c.bar + bar * 8), "n"(PARITY) : "memory");
}
__device__ __forceinline__ void load_w(const CUtensorMap* m, uint32_t dst, uint32_t bar, int col) {
  asm volatile("cp.async.bulk.tensor.2d.shared::cluster.global.mbarrier::complete_tx::bytes [%0], [%1, {%3,%4}], [%2];"
               ::"r"(dst), "l"(m), "r"(bar), "r"(col), "r"(0) : "memory");
}
template <int BYTES> __device__ __forceinline__ void send_o(uint32_t dst, uint32_t src, uint32_t bar, int cta) {
  asm volatile("{\n.reg .b32 rd, rb;\nmapa.shared::cluster.u32 rd, %0, %3;\nmapa.shared::cluster.u32 rb, %2, %3;\n"
               "cp.async.bulk.shared::cluster.shared::cta.mbarrier::complete_tx::bytes [rd], [%1], %4, [rb];\n}"
               ::"r"(dst), "r"(src), "r"(bar), "r"(cta), "n"(BYTES) : "memory");
}
__device__ __forceinline__ void remote_arrive(uint32_t rbar) { asm volatile("mbarrier.arrive.shared::cluster.b64 _, [%0];" ::"r"(rbar) : "memory"); }
__device__ __forceinline__ void remote_expect(uint32_t rbar, uint32_t bytes) {
  asm volatile("mbarrier.arrive.expect_tx.shared::cluster.b64 _, [%0], %1;" ::"r"(rbar), "r"(bytes) : "memory");
}
__device__ __forceinline__ void copy_remote(uint32_t rdst, uint32_t src, uint32_t bytes, uint32_t rbar) {
  asm volatile("cp.async.bulk.shared::cluster.shared::cta.mbarrier::complete_tx::bytes [%0], [%1], %2, [%3];" ::"r"(rdst), "r"(src), "r"(bytes), "r"(rbar) : "memory");
}
__device__ __forceinline__ void tail_free(uint32_t bar) {
  uint32_t ln; asm volatile("mov.u32 %0, %%laneid;" : "=r"(ln));
  if (ln < 4) mbar_arrive_remote(bar, ln + (blockIdx.x & 4));
}
__device__ __forceinline__ void publish(uint32_t bar) {
  fence_async();
  __syncwarp();
  mbar_arrive_elect(bar);
}

template <bool FIRST, int PA>
__device__ __forceinline__ void gemm_iter(GemmCtx& c, int b, uint32_t (&pk)[12], uint32_t (&pv)[12], uint32_t (&pq)[12],
                                          uint32_t (&hk1)[6], uint32_t (&hv1)[6], Stage& x0, Stage& x2, Stage& x1 TRARG) {
  const uint32_t bar = c.bar;
  const bool w = !FIRST && (PA == 0 || b >= 0), never = c.never;
  constexpr uint32_t ko = PA * KSLOT;
  float C[72];
  uint32_t hk0[6], hv0[6], pv2[12];
  TR(2, b, 0);
  if (FIRST) wait_stage(c, x0);
  else dump12<128>(c.qC[1], pq);
  if (w) nb_sync(N_QK1, 256);
  TR(2, b, 2);
  if (FIRST) TR(2, b - 1, 6);
  if (PA == 0) {
    float H[48];
    issue_halo<0, 8>(c, x0, H);
    TR(2, b, 3);
    if (!FIRST) { gwait<0>(c, B_KFREE); dump12<128>(c.kC, pk); }
    issue_halo<8, 12>(c, x0, H);
    TR(2, b, 4);
    wait_stage(c, x2);
    if (FIRST) TR(2, b - 1, 7);
    if (FIRST) gwait<0>(c, B_WQ);
    if (FIRST) TR(2, b - 1, 8);
    issue_core<0, 8>(c, x2, C);
    TR(2, b, 5);
    if (!FIRST) { fence_async(); keep12(never, c.kC, pk); }
    wg_wait<1>(); pin(H);
    release_stage(x0);
    pack6(hk0, H, 0);
    if (c.hvalid) dump6(c.kH, hk0);
    pack6(hk1, H, 2); pack6(hv0, H, 24); pack6(hv1, H, 26);
  } else {
    issue_core<0, 8>(c, x2, C);
    TR(2, b, 5);
    fence_async();
    keep12(never, c.kC, pq);
    if (w) gwait<1>(c, B_KFREE);
    dump12<128>(c.kC + ko, pk);
    if (c.hvalid) dump6(c.kH + ko, hk1);
  }
  TR(2, b, 13);
  issue_core<8, 12>(c, x2, C);
  if (w) { nb_arrive(N_VQ0, 288); nb_arrive(N_VQ1, 288); }
  else if (!FIRST) { __syncwarp(); mbar_arrive_elect(bar + B_Q0 * 8); }
  wait_stage(c, x1);
  if (never) dump6(bar, PA ? hk1 : hk0);
  TR(2, b, 6);
  wg_wait<0>(); pin(C);
  TR(2, b, 7);
  release_stage(x2);
  pack12(pk, C, 24);
  dump12<128>(c.kC + ko + 64, pk);
  pack12(pv2, C, 48);
  pack12(pq, C, 0);
  TR(2, b, 8);
  issue_core<0, SPL>(c, x1, C);
  TR(2, b, 9);
  if (!FIRST) { fence_async(); edge_ready(c, B_XK); }
  keep12(never, c.kC, pk);
  TR(2, b, 14);
  if (w) nb_sync(N_PVISS, 384);
  issue_core<SPL, 12>(c, x1, C);
  if (!FIRST) nb_arrive(N_KRDY, 256);
  TR(2, b, 1);
  if (PA && b == 11) tail_free(bar + B_TFREE * 8);
  wait_stage(c, x0);
  if (w) gwait<PA>(c, B_VFREE);
  if (w && b < TB) gwait<PA>(c, B_ODONE);
  TR(2, b, 10);
  if (!FIRST) dump12<128>(c.vC[PA], pv);
  dump12<128>(c.vC[PA ^ 1] + 768, pv2);
  TR(2, b, 11);
  wg_wait<0>(); pin(C);
  TR(2, b, 12);
  release_stage(x1);
  if (!FIRST && c.edge) publish(bar + B_XV * 8);
  if (c.hvalid) dump6(c.vH[PA], PA ? hv1 : hv0);
  if (PA && !w) nb_sync(N_Q0, 384);
  dump12<128>(c.qC[0], pq);
  pack12(pk, C, 24);
  pack12(pv, C, 48);
  pack12(pq, C, 0);
}

template <int IN> __device__ __forceinline__ void issue_proj(float (&D)[48]) {
  constexpr uint64_t da = mkdesc(SBC + IN, 128, 768, 0), db = mkdesc(SBC + SM_TWO, 12288, 512, 2);
  wg_fence();
  wg_ss96<0>(D, da, db);
#pragma unroll
  for (int k = 1; k < 12; k++) wg_ss96<1>(D, da + (k / 3) * 384 + (k % 3) * 16, db + k * 64);
  wg_commit();
}
template <int ACC> __device__ __forceinline__ void issue_proj_half(float (&D)[48], int hd) {
  const uint64_t da = mkdesc(SBC + SM_TIN2, 128, 768, 0) + hd * 384, db = mkdesc(SBC + SM_TWO, 12288, 512, 2) + hd * 192;
  wg_fence();
  wg_ss96<ACC>(D, da, db);
#pragma unroll
  for (int k = 1; k < 6; k++) wg_ss96<1>(D, da + (k / 3) * 768 + (k % 3) * 16, db + (k / 3) * 384 + (k % 3) * 64);
  wg_commit();
}
__device__ __forceinline__ void store_proj(const float (&D)[48], const CUtensorMap* m, uint32_t st, uint32_t sta, int row, int col, int ch) {
#pragma unroll
  for (int q = 0; q < 6; q++)
    stsm4((sta ^ ((q & 1) * 32)) + (q >> 1) * 1024,
          pack2(D[8 * q], D[8 * q + 1]), pack2(D[8 * q + 2], D[8 * q + 3]), pack2(D[8 * q + 4], D[8 * q + 5]), pack2(D[8 * q + 6], D[8 * q + 7]));
  fence_async();
  __syncwarp();
  if ((threadIdx.x & 31) == 0) {
    asm volatile("cp.async.bulk.tensor.4d.global.shared::cta.bulk_group [%0, {%2,%3,%4,%5}], [%1];" ::"l"(m), "r"(st), "r"(0), "r"(row), "r"(col), "r"(ch) : "memory");
    asm volatile("cp.async.bulk.commit_group;" ::: "memory");
  }
  __syncwarp();
}

__device__ __forceinline__ float fold(float a, float b, float t, int useb) {
  float r;
  asm("{\n.reg .pred p;\nsetp.ne.b32 p, %4, 0;\nfma.rn.f32 %0, %1, 0f3E553B95, %3;\n@p fma.rn.f32 %0, %2, 0f3E553B95, %3;\n}"
      : "=&f"(r) : "f"(a), "f"(b), "f"(t), "r"(useb));
  return r;
}
template <int U, int L>
__device__ __forceinline__ void softmax_tile(const float (&SA)[56], const float (&SB)[56], const float (&T)[16], int b0, int b1,
                                             uint32_t (&P)[28], float (&sx)[8], uint32_t nbV, uint32_t zero, uint32_t qa, uint32_t (&q)[12]) {
  float lu[14], ll[14];
#pragma unroll
  for (int j = 0; j < 7; j++) {
    constexpr int sh = U == L ? 2 : 0;
    const float tu0 = T[2 * j + sh], tu1 = T[2 * j + 1 + sh], tl0 = T[2 * j], tl1 = T[2 * j + 1];
    lu[2 * j]     = fold(SA[4 * (U + j)],     SB[4 * (U + j)],     tu0, b0);
    ll[2 * j]     = fold(SA[4 * (L + j) + 2], SB[4 * (L + j) + 2], tl0, b0);
    lu[2 * j + 1] = fold(SA[4 * (U + j) + 1], SB[4 * (U + j) + 1], tu1, b1);
    ll[2 * j + 1] = fold(SA[4 * (L + j) + 3], SB[4 * (L + j) + 3], tl1, b1);
  }
  float mu = lu[0], ml = ll[0], mu2 = lu[1], ml2 = ll[1];
#pragma unroll
  for (int j = 1; j < 7; j++) { mu = fmaxf(mu, lu[2 * j]); mu2 = fmaxf(mu2, lu[2 * j + 1]); ml = fmaxf(ml, ll[2 * j]); ml2 = fmaxf(ml2, ll[2 * j + 1]); }
  mu = fmaxf(mu, mu2); ml = fmaxf(ml, ml2);
  { const float a1 = __shfl_xor_sync(0xffffffffu, mu, 1), a2 = __shfl_xor_sync(0xffffffffu, mu, 2), a3 = __shfl_xor_sync(0xffffffffu, mu, 3);
    const float c1 = __shfl_xor_sync(0xffffffffu, ml, 1), c2 = __shfl_xor_sync(0xffffffffu, ml, 2), c3 = __shfl_xor_sync(0xffffffffu, ml, 3);
    mu = fmaxf(fmaxf(mu, a1), fmaxf(a2, a3)); ml = fmaxf(fmaxf(ml, c1), fmaxf(c2, c3)); }
  float su = 0.f, sl = 0.f;
#pragma unroll
  for (int c = 0; c < 14; c++) {
    if (c >= U && c < U + 7) {
      float e0 = ex2(lu[2 * (c - U)] - mu), e1 = ex2(lu[2 * (c - U) + 1] - mu);
      su = c == U ? e0 + e1 : (su + e0) + e1; P[2 * c] = pack2(e0, e1);
    } else P[2 * c] = 0u;
  }
  nb_sync(nbV | (P[2 * (U + MID)] & zero), 288);
#pragma unroll
  for (int k = 0; k < 3; k++) ldsm4(qa + k * 256, q[4 * k], q[4 * k + 1], q[4 * k + 2], q[4 * k + 3]);
#pragma unroll
  for (int c = 0; c < 14; c++) {
    if (c >= L && c < L + 7) {
      float e0 = ex2(ll[2 * (c - L)] - ml), e1 = ex2(ll[2 * (c - L) + 1] - ml);
      sl = c == L ? e0 + e1 : (sl + e0) + e1; P[2 * c + 1] = pack2(e0, e1);
    } else P[2 * c + 1] = 0u;
  }
  sx[0] = su; sx[4] = sl;
#pragma unroll
  for (int k = 1; k < 4; k++) sx[k] = __shfl_xor_sync(0xffffffffu, su, k);
#pragma unroll
  for (int k = 1; k < 4; k++) sx[4 + k] = __shfl_xor_sync(0xffffffffu, sl, k);
}

struct BandCfg { uint32_t ra0, ra1, meta; int b0, b1; };
__device__ __forceinline__ void band_cfg(int b, uint32_t tb, BandCfg& n) {
  uint32_t ln; asm volatile("mov.u32 %0, %%laneid;" : "=r"(ln));
  const int g = ln >> 2, t = ln & 3;
  const int sw = min(max(g + 1, b == 0 ? 4 : 0), b == 13 ? 5 : 8);
  const int i0 = 2 * t, i1 = 2 * t + 1;
  n.b0 = i0 <= sw - 2; n.b1 = i1 <= sw - 2;
  n.ra0 = tb + (i0 == sw - 1 ? 13 : i0 + 8 * n.b0 - g + 2) * 52;
  n.ra1 = tb + (i1 == sw - 1 ? 13 : i1 + 8 * n.b1 - g + 2) * 52;
  n.meta = ((0x5555u & ((1u << (2 * (sw - 1))) - 1)) ^ 0xDD88u ^ (((t ^ b) & 1) ? 0x5555u : 0u)) * 0x10001u;
}
__device__ __forceinline__ void band_load(const BandCfg& n, float (&T)[16], int& b0, int& b1, uint32_t& meta) {
#pragma unroll
  for (int jj = 0; jj < 8; jj++) { T[2 * jj] = lds_f32(n.ra0 + jj * 4); T[2 * jj + 1] = lds_f32(n.ra1 + jj * 4); }
  b0 = n.b0; b1 = n.b1; meta = n.meta;
}

struct Maps { CUtensorMap xc, xh, w, os, wo, ot; };

__global__ void __cluster_dims__(8, 1, 1) __launch_bounds__(512, 1)
na_attn_kernel(const __nv_bfloat16* __restrict__ x, const __nv_bfloat16* __restrict__ wqkv, const __nv_bfloat16* __restrict__ rpb, const __grid_constant__ Maps mp) {
  extern __shared__ __align__(1024) uint8_t smem_raw[];
  const uint32_t sb = smem_u32(smem_raw);
  if ((sb & 0x3FFFF) != SBC) return;
  const uint32_t bar = sb + SM_BAR;
  TR2(blockIdx.x, 0);
  const int tid = threadIdx.x, lane = tid & 31;
  const int warp = __shfl_sync(0xffffffffu, tid >> 5, 0);
  const int head = blockIdx.x & 3, base = blockIdx.x & 4, sp = blockIdx.x >> 2;
  const int par = sp < 24 ? sp / 6 : sp - 24, strip = sp < 24 ? sp - par * 6 : 6, ph = par >> 1, pw = par & 1;
  const int odd = strip & 1;

  uint4 wv[2 * NL];
  const int va = head == 1;
  const uint32_t wdst = sb + SM_W + (3 + va + ((tid >> 1) & 1)) * 6144 + (tid >> 2) * 32 + ((tid ^ (tid >> 4)) & 1) * 16;
  if (warp < 12) asm volatile("barrier.cluster.arrive.relaxed.aligned;" ::: "memory");
  {
    const uint32_t wo0 = (tid >> 2) * 1152 + head * 96 + va * 32 + (tid & 3) * 16;
#pragma unroll
    for (int i = 0; i < 2 * NL; i++)
      asm volatile("{\n.reg .pred p;\nsetp.lt.u32 p, %5, 384;\n@p ld.global.nc.v4.b32 {%0,%1,%2,%3}, [%4];\n}"
                   : "=r"(wv[i].x), "=r"(wv[i].y), "=r"(wv[i].z), "=r"(wv[i].w)
                   : "l"(reinterpret_cast<const uint8_t*>(wqkv) + wo0 + (i & 1) * 96 * 1152 + ((i / 2 + 1) % 3) * 384), "r"(tid));
  }
  if (warp < 8) {
    asm volatile("setmaxnreg.inc.sync.aligned.u32 %0;" ::"n"(RA));
    float rv = -INFINITY;
    if (tid < 169) rv = __bfloat162float(rpb[head * 169 + tid]) * 1.4426950408889634f;
    if (tid < 192) {
      const int kc = (tid & 15) + 3, wc = (tid >> 4) % 6;
      sts128(tid < 96 ? sb + SM_K + kc * KS + wc * 128 + 48 : sb + SM_V + kc * 1536 + wc * 128 + (6 + (kc & 1)) * 16, make_uint4(0, 0, 0, 0));
    }
#pragma unroll
    for (int i = 0; i < 2 * NL; i++) sts128(wdst + (i & 1) * 3072 + (i / 2) * 18432, wv[i]);
    fence_async();
    asm volatile("bar.arrive 1, 384;" ::: "memory");
    if (tid < 182) asm volatile("st.shared.f32 [%0], %1;" ::"r"(sb + SM_RPB + tid * 4), "f"(rv) : "memory");
    const int jw = warp >> 2, j = jw ^ odd, w = warp & 3, wt = 4 * j + w;
    int variant = w;
    if (strip == 0 && j == 0 && w < 2) variant = 4;
    if (strip == 6 && j == 1 && w >= 2) variant = 5;
    const bool v1 = opq((uint32_t)(variant & 1)), v2 = opq((uint32_t)(variant & 2)), v4 = opq((uint32_t)(variant & 4));
    const uint32_t qa = opq(sb + SM_Q + (8 * j + 2 * w + ((lane >> 3) & 1)) * 768 + (lane >> 4) * 128 + (((lane & 7) * 16) ^ (((lane >> 3) & 1) * 64)));
    uint32_t oa = opq(sb + SM_O + j * 6144 + (2 * w + ((lane >> 3) & 1)) * 768 + (lane >> 4) * 128 + (lane & 7) * 16);
    uint64_t dA = opq(mkdesc(SBC + SM_K, 128, KS, 0) + j * (8 * KS / 16)), dB = opq(dA + (KSLOT >> 4));
    uint64_t dV[7];
#pragma unroll
    for (int i = 0; i < 7; i++) dV[i] = opq(mkdesc(SBC + SM_V, 768, 128, 0) + j * (8 * 1536 / 16) + i * 192);
    const uint32_t nbK = opq((uint32_t)(N_KRDY + jw)), nbQ = opq((uint32_t)(N_QK0 + jw)), nbV = opq((uint32_t)(N_VQ0 + jw));
    asm volatile("barrier.cluster.wait.aligned;" ::: "memory");
    asm volatile("bar.sync 3, 256;" ::: "memory");
    float T[16];
    TRDECL;
    int b0, b1;
    uint32_t meta, ob = bar + B_ODONE * 8, fb = bar + B_OFREE * 8, fp = 1;
    const uint32_t tb = opq(sb + SM_RPB + (variant < 4 ? 3 : variant + 1 - 2 * w) * 4);
    const bool own = ((w ^ head) & 2) == 0;
    const uint32_t dst13 = sb + SM_TIN2 + head * 6144 + (2 * j + (w & 1)) * 1536, src13 = opq(own ? dst13 : sb + SM_S + (2 * j + (w & 1)) * 1536);
    const uint32_t snd[4] = {opq(own ? 0u : mapa(dst13, base + (head ^ 2))), opq(mapa(bar + (B_TIN + 2) * 8, base + (head ^ 2))),
                             opq(mapa(dst13, base + (w & 2) + (~head & 1))), opq(mapa(bar + (B_TIN + 3) * 8, base + (w & 2) + (~head & 1)))};
    BandCfg nx;
    band_cfg(0, tb, nx);
    band_load(nx, T, b0, b1, meta);
    band_cfg(1, tb, nx);
    const uint32_t zero = opq(blockIdx.x >> 16);
    uint32_t special = opq(0x380Au << 1);
    uint32_t q[12];
    mbar_wait(bar + B_Q0 * 8, 0);
#pragma unroll
    for (int k = 0; k < 3; k++) ldsm4(qa + k * 256, q[4 * k], q[4 * k + 1], q[4 * k + 2], q[4 * k + 3]);
    nb_arrive(N_Q0, 384);
#pragma unroll 1
    for (int b = 0; b < 14; b++) {
      float SA[56], SB[56];
      TR(0, b, 0);
      if (jw) mbar_wait(bar + B_KIMP * 8, b & 1);
      nb_sync(nbK, 256);
      TR(0, b, 1);
      TR(0, b - 1, 9);
      wg_fence();
      wg_rs112<0>(SA, q[0], q[1], q[2], q[3], dA);
      wg_rs112<0>(SB, q[0], q[1], q[2], q[3], dB);
      wg_rs112<1>(SA, q[4], q[5], q[6], q[7], dA + 16);
      wg_rs112<1>(SB, q[4], q[5], q[6], q[7], dB + 16);
      wg_rs112<1>(SA, q[8], q[9], q[10], q[11], dA + 32);
      wg_rs112<1>(SB, q[8], q[9], q[10], q[11], dB + 32);
      wg_commit();
      nb_arrive(nbQ, 256);
      { const uint64_t t = dA; dA = dB; dB = t; }
      special >>= 1;
      if (special & 1) {
        if (b == 3) band_cfg(13, tb, nx);
        else {
          if (b == 1 || b == 13) band_load(nx, T, b0, b1, meta);
          if (b >= TB) {
            ob = bar + (b == 13 ? (own ? B_TIN + 2 : B_ODONE) : B_OTAIL + 2 * (b - TB) + jw) * 8;
            if (b > TB) { fb = bar + (B_TFREE + b - 12) * 8; fp = 0; }
            oa += b == 12 ? 0u - (SM_O - SM_Q) : (b == 13 ? src13 - (sb + SM_Q + wt * 1536) : 0);
          }
        }
      }
      TR(0, b, 2);
      wg_wait<0>(); pin(SA); pin(SB);
      mbar_arrive_elect(bar + B_KFREE * 8);
      TR(0, b, 3);
      TR(0, b - 1, 10);
      uint32_t P[28];
      float sx[8];
      if (v2) {
        if (v1) softmax_tile<6, 7>(SA, SB, T, b0, b1, P, sx, nbV, zero, qa, q); else softmax_tile<4, 5>(SA, SB, T, b0, b1, P, sx, nbV, zero, qa, q);
      } else if (!v4) {
        if (v1) softmax_tile<2, 3>(SA, SB, T, b0, b1, P, sx, nbV, zero, qa, q); else softmax_tile<0, 1>(SA, SB, T, b0, b1, P, sx, nbV, zero, qa, q);
      } else {
        if (v1) softmax_tile<4, 4>(SA, SB, T, b0, b1, P, sx, nbV, zero, qa, q); else softmax_tile<3, 3>(SA, SB, T, b0, b1, P, sx, nbV, zero, qa, q);
      }
      float O[24];
      TR(0, b, 4);
      wg_fence();
      wg_sp48<0>(O, P[0], P[1], P[2], P[3], dV[0], meta);
#pragma unroll
      for (int s = 1; s < 7; s++) wg_sp48<1>(O, P[4 * s], P[4 * s + 1], P[4 * s + 2], P[4 * s + 3], dV[s], meta);
      wg_commit();
      nb_arrive(N_PVISS, 384);
      TR(0, b, 6);
      mbar_wait(fb, fp);
      wg_wait<0>(); pin(O);
      mbar_arrive_elect(bar + B_VFREE * 8);
      TR(0, b, 7);
      float ru, rl;
      asm("rcp.approx.ftz.f32 %0, %1;" : "=f"(ru) : "f"(((fmaf(O[0], 0.f, sx[0]) + sx[1]) + sx[2]) + sx[3]));
      asm("rcp.approx.ftz.f32 %0, %1;" : "=f"(rl) : "f"(((fmaf(O[2], 0.f, sx[4]) + sx[5]) + sx[6]) + sx[7]));
#pragma unroll
      for (int i = 0; i < 3; i++)
        stsm4(oa + i * 256, pack2(O[8 * i] * ru, O[8 * i + 1] * ru), pack2(O[8 * i + 2] * rl, O[8 * i + 3] * rl),
              pack2(O[8 * i + 4] * ru, O[8 * i + 5] * ru), pack2(O[8 * i + 6] * rl, O[8 * i + 7] * rl));
      publish(ob);
      fp ^= 1;
      meta ^= 0x55555555u;
      TR(0, b, 8);
    }
    asm volatile("{\n.reg .pred p, q;\nsetp.ne.b32 q, %1, 0;\nelect.sync _|p, 0xffffffff;\nand.pred q, q, p;\n"
                 "@q cp.async.bulk.shared::cluster.shared::cta.mbarrier::complete_tx::bytes [%1], [%0], 1536, [%2];\n"
                 "@p cp.async.bulk.shared::cluster.shared::cta.mbarrier::complete_tx::bytes [%3], [%0], 1536, [%4];\n}"
                 ::"r"(src13), "r"(snd[0]), "r"(snd[1]), "r"(snd[2]), "r"(snd[3]) : "memory");
    if (jw == 0) nb_arrive(3, 256);
    TRDUMP;
    cluster_sync();
  } else if (warp < 12) {
    TRDECL;
    TR(2, -3, 0);
    asm volatile("setmaxnreg.inc.sync.aligned.u32 %0;" ::"n"(RG));
    TR(2, -3, 1);
    GemmCtx c;
    c.bar = bar;
    const int gw = warp - 8, tk = gw * 16 + (lane & 15), hi = lane >> 4;
    { const int col = tk >> 2, i = tk & 3;
      c.kC = sb + SM_K + (col + 3) * KS + hi * 128 + i * 16;
      c.vC[0] = sb + SM_V + (col + 3) * 1536 + hi * 128 + (2 * i + ((col + 3) & 1)) * 16;
      c.qC[0] = sb + SM_Q + col * 768 + hi * 128 + (col & 1) * 64 + i * 16; }
    { const int kc = gw - 1 + 19 * odd, i = lane & 7; c.hvalid = gw > 0; c.edge = gw == (odd ? 0 : 3);
      c.kH = sb + SM_K + kc * KS + (lane >> 3) * 128 + i * 16;
      c.vH[0] = sb + SM_V + kc * 1536 + (lane >> 3) * 128 + (i >> 2) * 768 + (2 * (i & 3) + ((kc ^ (i >> 2)) & 1)) * 16; }
    Stage xs[3];
#pragma unroll
    for (int i = 0; i < 3; i++) {
      const int p = (i + 1) % 3;
      xs[i].lo = (uint32_t)mkdesc(SBC + SM_X + p * 24576, 16, 0, 0); xs[i].full = bar + (B_FULL + p) * 8;
      xs[i].em = opq(mapa(bar + (B_EMPTY + p) * 8, base + p)); xs[i].par = 0;
    }
    c.never = x == nullptr;
    c.kC = opq(c.kC); c.kH = opq(c.kH);
    c.vC[1] = opq(c.vC[0] ^ 16); c.vC[0] = opq(c.vC[0]);
    c.vH[1] = opq(c.vH[0] ^ 16); c.vH[0] = opq(c.vH[0]);
    c.qC[1] = opq(c.qC[0] ^ 64); c.qC[0] = opq(c.qC[0]);
    c.spin = 0;
    c.hiA = (uint32_t)(mkdesc(0, 0, 1024, 1) >> 32) + (blockIdx.x >> 16); c.hiB = (uint32_t)(mkdesc(0, 0, 256, 3) >> 32) + (blockIdx.x >> 16);
    asm volatile("barrier.cluster.wait.aligned;" ::: "memory");
    TR(2, -3, 2);
#pragma unroll
    for (int i = 0; i < 2 * NL; i++) sts128(wdst + (i & 1) * 3072 + (i / 2) * 18432, wv[i]);
    fence_async();
    TR(2, -3, 3);
    asm volatile("bar.sync 1, 384;" ::: "memory");
    TR(2, -3, 4);
    mbar_wait(bar + B_WK * 8, 0);
    TR(2, -3, 5);
    uint32_t pk[12], pv[12], pq[12], hk1[6], hv1[6];
    gemm_iter<true, 0>(c, -2, pk, pv, pq, hk1, hv1, xs[0], xs[1], xs[2] TRPASS);
    TR2(blockIdx.x, 4);
    c.hiA = opq(c.hiA); c.hiB = opq(c.hiB);
#pragma unroll 1
    for (int b = -1;; b += 2) {
      gemm_iter<false, 1>(c, b, pk, pv, pq, hk1, hv1, xs[2], xs[0], xs[1] TRPASS);
      if (b == 11) break;
      gemm_iter<false, 0>(c, b + 1, pk, pv, pq, hk1, hv1, xs[2], xs[0], xs[1] TRPASS);
      const Stage t = xs[2]; xs[2] = xs[1]; xs[1] = xs[0]; xs[0] = t;
    }
    TR2(blockIdx.x, 6);
    c.hiA = opq(c.hiA); c.hiB = opq(c.hiB);
    const uint32_t st = sb + gw * 3072;
    const uint32_t sta = st + (lane & 15) * 64 + ((hi ^ ((lane >> 1) & 3)) * 16);
    const int oc = ph * 112 + strip * 16 + 8 * (gw >> 1) + 4 * (head >> 1) + 2 * (gw & 1), och = pw * 6 + (head & 1) * 3;
    float D0[48], D1[48];
    mbar_arrive_elect(bar + B_WOFREE * 8);
    dump12<128>(c.qC[1], pq);
    nb_sync(N_QK1, 256);
    issue_halo<0, 8>(c, xs[2], D1);
    fence_async();
    nb_arrive(N_VQ0, 288); nb_arrive(N_VQ1, 288); nb_arrive(N_PVISS, 384);
    issue_halo<8, 12>(c, xs[2], D1);
    gwait<0>(c, B_KFREE);
    dump12<128>(c.kC, pk);
    if (c.edge) publish(bar + B_XK * 8);
    wg_wait<0>(); pin(D1);
    pack6(hk1, D1, 0);
    if (c.hvalid) dump6(c.kH, hk1);
    tail_free(bar + (B_TFREE + 1) * 8);
    pack6(hv1, D1, 24);
    fence_async();
    nb_arrive(N_KRDY, 256);
    gwait<0>(c, B_VFREE);
    dump12<128>(c.vC[0], pv);
    if (c.hvalid) dump6(c.vH[0], hv1);
    fence_async();
    edge_ready(c, B_XV);
    nb_arrive(N_VQ0, 288); nb_arrive(N_VQ1, 288);
    gwait<0>(c, B_WO);
    gwait<0>(c, B_TIN);
    TR(2, 13, 0);
    nb_sync(N_QK1, 256);
    issue_proj<SM_TIN0>(D0);
    wg_wait<0>(); pin(D0);
    TR(2, 13, 1);
    store_proj(D0, &mp.ot, st + SM_TST, sta + SM_TST, 8 * TB, oc, och);
    gwait<0>(c, B_TIN + 1);
    TR(2, 13, 2);
    nb_sync(N_PVISS, 384);
    nb_sync(3, 256);
    issue_proj<SM_TIN1>(D1);
    wg_wait<0>(); pin(D1);
    TR(2, 13, 3);
    store_proj(D1, &mp.ot, st + SM_TIN0, sta + SM_TIN0, 8 * TB + 8, oc, och);
    TR(2, 13, 4);
    gwait<0>(c, B_TIN + 2);
    TR(2, 13, 5);
    issue_proj_half<0>(D0, head & 1);
    gwait<0>(c, B_TIN + 3);
    TR(2, 13, 6);
    issue_proj_half<1>(D0, ~head & 1);
    asm volatile("barrier.cluster.arrive.relaxed.aligned;" ::: "memory");
    wg_wait<0>(); pin(D0);
    store_proj(D0, &mp.ot, st + SM_TIN0 + 12288, sta + SM_TIN0 + 12288, 8 * TB + 16, oc, och);
    TR(2, 13, 7);
    if (lane == 0) asm volatile("cp.async.bulk.wait_group.read 0;" ::: "memory");
    __syncwarp();
    TR(2, 13, 8);
    TR2(blockIdx.x, 2);
    TRDUMP;
    asm volatile("barrier.cluster.wait.aligned;" ::: "memory");
  } else {
    if (warp == 12) {
      if (elect_one()) {
        mbar_init(bar + B_WK * 8, 1);
#pragma unroll
        for (int i = 0; i < NL; i++) load_w(&mp.w, sb + SM_W + (3 * i + 5 - 2 * va) * 6144, bar + B_WK * 8, ((i + 1) % 3) * 192 + head * 48 + 32 - 32 * va);
        asm volatile("prefetch.tensormap [%0];" ::"l"(head == 1 ? &mp.xh : &mp.xc) : "memory");
        mbar_expect(bar + B_WK * 8, NL * 6144);
      }
    } else if (warp == 15) {
      const int col = min(max(strip * 16 - 3 + min(lane, 21), 0), 111);
      const uint8_t* p = reinterpret_cast<const uint8_t*>(x) + (uint32_t)(head * ROWB + (ph * 112 + col) * 768 + pw * 384);
#pragma unroll
      for (int i = 0; i < 3; i++) asm volatile("prefetch.global.L2 [%0];" ::"l"(p + i * 128));
    } else if (elect_one()) {
      if (warp == 13) {
#pragma unroll
        for (int i = 0; i < B_WK; i++) mbar_init(bar + i * 8, i < B_EMPTY ? 1 : (i < B_TIN ? 16 : (i < B_TFREE ? (i == B_TIN + 2 ? 5 : 1) : 16)));
      } else {
#pragma unroll
        for (int i = B_WQ; i < B_COUNT; i++) mbar_init(bar + i * 8, i < B_XK ? 1 : (i < B_Q0 ? 2 : (i < B_ODONE ? 4 : (i == B_VFREE ? 9 : 8))));
        mbar_arrive(bar + B_XK * 8); mbar_arrive(bar + B_XV * 8);
      }
    }
    asm volatile("fence.mbarrier_init.release.cluster;" ::: "memory");
    __syncwarp();
    asm volatile("barrier.cluster.arrive.relaxed.aligned;" ::: "memory");
    asm volatile("setmaxnreg.dec.sync.aligned.u32 24;");
    asm volatile("griddepcontrol.launch_dependents;");
    asm volatile("barrier.cluster.wait.aligned;" ::: "memory");
    if (warp == 12) {
      const int cc = ph * 112 + strip * 16, ch = cc + (odd ? 16 : (strip ? -3 : 0)), rh = strip ? -4 : 112;
      const uint32_t fb = bar + (B_FULL + head) * 8, eb = bar + (B_EMPTY + head) * 8, dst = sb + SM_X + head * 24576;
      int t = head == 0 ? 2 : head - 1;
      const CUtensorMap* mx = t ? &mp.xc : &mp.xh;
      int row = t ? 4 * t - 4 : rh;
#pragma unroll 1
      for (int n = 0; n < (head == 3 ? 1 : 12); n++) {
        const bool halo = mx == &mp.xh;
        if (n) mbar_wait(eb, (n - 1) & 1);
        if (head < 3) {
          if (elect_one())
            asm volatile("cp.async.bulk.tensor.4d.shared::cluster.global.mbarrier::complete_tx::bytes.multicast::cluster [%0], [%1, {%3,%4,%5,%6}], [%2], %7;"
                         ::"r"(dst + (halo ? 2048 : 0)), "l"(mx), "r"(fb), "r"(0), "r"(row), "r"(halo ? ch : cc), "r"(pw * 3), "h"((uint16_t)(15 << base)) : "memory");
          __syncwarp();
          if (lane < 4) remote_expect(mapa(fb, base + lane), halo ? 18432 : 24576);
          __syncwarp();
        }
        t += 3;
        const int hn = t / 5;
        mx = t != 5 * hn ? &mp.xc : &mp.xh;
        row = t != 5 * hn ? 4 * (t - hn - 1) : rh + 16 * hn;
        if (elect_one()) {
          if (n == 0) {
#pragma unroll
            for (int i = 0; i < 3; i++) load_w(&mp.w, sb + SM_W + i * 6144, bar + B_WQ * 8, head * 48 + i * 16);
            mbar_expect(bar + B_WQ * 8, 18432);
            mbar_expect(bar + B_TIN * 8, 24576); mbar_expect(bar + (B_TIN + 1) * 8, 24576); mbar_expect(bar + (B_TIN + 2) * 8, 6144); mbar_expect(bar + (B_TIN + 3) * 8, 12288);
          }
          if (head < 3 && n < 11) asm volatile("cp.async.bulk.prefetch.tensor.4d.L2.global [%0, {%1,%2,%3,%4}];" ::"l"(mx), "r"(0), "r"(row), "r"(t != 5 * hn ? cc : ch), "r"(pw * 3) : "memory");
        }
        __syncwarp();
      }
      mbar_wait(bar + B_WOFREE * 8, 0);
      if (elect_one()) {
        mbar_expect(bar + B_WO * 8, 36864);
        asm volatile("cp.async.bulk.tensor.3d.shared::cluster.global.mbarrier::complete_tx::bytes [%0], [%1, {%3,%4,%5}], [%2];"
                     ::"r"(sb + SM_TWO), "l"(&mp.wo), "r"(bar + B_WO * 8), "r"(0), "r"(0), "r"((head & 1) * 3) : "memory");
      }
      __syncwarp();
    }
    if (warp & 1) {
      const uint32_t partner = (blockIdx.x & 7) ^ 4;
      const int cs = odd ? 3 : (strip == 6 ? 15 : 16), cd = odd || strip == 6 ? 19 : 0;
      const uint32_t rb = opq(mapa(bar, partner));
      TRDECL;
      if (warp == 13) {
        const uint32_t dst = opq(mapa(sb + SM_V + cd * 1536, partner)), src = opq(sb + SM_V + cs * 1536);
#pragma unroll 1
        for (int b = 0;; b++) {
          const uint32_t pa = b & 1;
          nb_arrive(N_VQ0, 288);
          mbar_wait(bar + B_XV * 8, pa);
          TR(1, b, 0);
          if (elect_one()) { copy_remote(dst, src, 4608, rb + B_VIMP * 8); remote_expect(rb + B_VIMP * 8, 4608); }
          __syncwarp();
          TR(1, b, 1);
          mbar_wait(bar + B_VIMP * 8, pa);
          TR(1, b, 2);
          nb_arrive(N_VQ1, 288);
          if (elect_one()) remote_arrive(rb + B_VFREE * 8);
          __syncwarp();
          TR(1, b, 3);
          if (b == 13) break;
          mbar_wait(bar + B_VFREE * 8, pa);
          if (elect_one()) remote_arrive(rb + B_XV * 8);
          __syncwarp();
        }
      } else {
        const uint32_t dst = opq(mapa(sb + SM_K + cd * KS, partner)), src = opq(sb + SM_K + cs * KS);
#pragma unroll 1
        for (int b = 0;; b++) {
          const uint32_t pa = b & 1, so = (pa ^ 1) * KSLOT;
          mbar_wait(bar + B_XK * 8, pa);
          TR(1, b - 1, 4);
          if (elect_one()) {
            copy_remote(dst + so, src + so, 3 * KS, rb + B_KIMP * 8);
            if (b == 0) copy_remote(dst, src, 3 * KS, rb + B_KIMP * 8);
            remote_expect(rb + B_KIMP * 8, b ? 3 * KS : 6 * KS);
          }
          __syncwarp();
          TR(1, b - 1, 5);
          TR(1, b - 1, 7);
          if (b == 13) break;
          mbar_wait(bar + B_KFREE * 8, pa);
          if (elect_one()) remote_arrive(rb + B_XK * 8);
          __syncwarp();
        }
      }
      TRDUMP;
    }
    if (warp == 14) {
      int* flag = g_flags + (par * 7 + strip) * 2 * FS;
#pragma unroll 1
      for (int b = 0; b < TB; b++) {
        mbar_wait(bar + B_ODONE * 8, b & 1);
        if (lane == 0) {
#pragma unroll 1
          for (int i = 0; i < 16; i += OCH) {
            asm volatile("cp.async.bulk.tensor.3d.global.shared::cta.bulk_group [%0, {%2,%3,%4}], [%1];"
                         ::"l"(&mp.os), "r"(sb + SM_O + i * 768), "r"(pw * 192), "r"(8 * b + 2 * head), "r"(ph * 112 + strip * 16 + i) : "memory");
            asm volatile("cp.async.bulk.commit_group;\ncp.async.bulk.wait_group 0;" ::: "memory");
          }
        }
        __syncwarp();
        mbar_arrive_elect(bar + B_OFREE * 8);
        if (lane == 0)
          asm volatile("fence.proxy.async.global;\nfence.acq_rel.gpu;\nred.relaxed.gpu.global.add.s32 [%0], 1;\nred.relaxed.gpu.global.add.s32 [%1], 1;"
                       ::"l"(flag + b * 56 * FS), "l"(flag + (b * 56 + 1) * FS) : "memory");
        __syncwarp();
      }
#pragma unroll 1
      for (int t = 0; t < 4; t++) {
        const int i = t >> 1, jw = t & 1, j = jw ^ odd;
        if (!jw) mbar_wait(bar + (B_TFREE + i) * 8, 0);
        mbar_wait(bar + (B_OTAIL + t) * 8, 0);
        if (elect_one()) {
#pragma unroll 1
          for (int d = 0; d < 8; d++) {
            const int dst = (d + head) & 3, pc = d >> 2;
            send_o<1536>(sb + (i ? SM_TIN1 : SM_TIN0) + head * 6144 + j * 3072 + pc * 1536,
                         sb + (i ? SM_Q : SM_O) + (4 * j + (dst & 2) + pc) * 1536, bar + (B_TIN + i) * 8, base + dst);
          }
        }
        __syncwarp();
      }
    }
    cluster_sync();
  }
}

constexpr int NSTB = 6;
constexpr int NTB = TB * 56;
constexpr int SM_B_ST = 0;
constexpr int SM_B_IN = 73728;
constexpr int SM_B_W = SM_B_IN + 3 * 24576;
constexpr int SM_B_BAR = SM_B_IN + NSTB * 24576;
constexpr int SM_B_TOTAL = SM_B_BAR + 512;
struct MapsB { CUtensorMap oi, oo, wo; };

__global__ void __launch_bounds__(512, 1)
na_proj_kernel(const __grid_constant__ MapsB mp) {
  extern __shared__ __align__(1024) uint8_t smem_raw[];
  const uint32_t sb = smem_u32(smem_raw);
  if ((sb & 0x3FFFF) != SBC) return;
  const uint32_t bar = sb + SM_B_BAR;
  const int tid = threadIdx.x, lane = tid & 31;
  const int warp = __shfl_sync(0xffffffffu, tid >> 5, 0);
  TR2(132 + blockIdx.x, 0);
  TRB(47, 0);
  if (warp == 12 && elect_one()) {
#pragma unroll
    for (int i = 0; i <= 2 * NSTB; i++) mbar_init(bar + i * 8, i < NSTB || i == 2 * NSTB ? 1 : 12);
    asm volatile("st.shared.u32 [%0], 0;" ::"r"(bar + 120) : "memory");
    mbar_expect(bar + 2 * NSTB * 8, 73728);
#pragma unroll
    for (int i = 0; i < 2; i++)
      asm volatile("cp.async.bulk.tensor.3d.shared::cluster.global.mbarrier::complete_tx::bytes [%0], [%1, {%3,%4,%5}], [%2];"
                   ::"r"(sb + SM_B_W + i * 36864), "l"(&mp.wo), "r"(bar + 2 * NSTB * 8), "r"(0), "r"(0), "r"(i * 3) : "memory");
  }
  __syncthreads();
  const int step = gridDim.x;
  if (warp == 15) {
    int so = 0;
    nb_arrive(4, 288); nb_arrive(5, 288); nb_arrive(6, 288);
#pragma unroll 1
    for (int n = blockIdx.x, tk = 0; n < NTB; n += step, tk++) {
      uint32_t cc = 0;
#pragma unroll
      for (int wg = 0; wg < 3; wg++) {
        if (lane == 0) asm volatile("cp.async.bulk.wait_group.read 5;" ::: "memory");
        nb_sync(1 + wg, 160);
        if (wg == 0 || n + step < NTB) nb_arrive(4 + wg, 288);
        if (wg == 0) asm volatile("ld.shared.u32 %0, [%1];" : "=r"(cc) : "r"(bar + 128 + tk * 4) : "memory");
        if (lane == 0) {
          asm volatile("cp.async.bulk.tensor.4d.global.shared::cta.bulk_group [%0, {%2,%3,%4,%5}], [%1];"
                       ::"l"(&mp.oo), "r"(sb + SM_B_ST + wg * 8192 + so), "r"(0), "r"((cc >> 8) & 255), "r"(cc >> 16), "r"((cc & 1) * 3 + wg) : "memory");
          asm volatile("cp.async.bulk.commit_group;" ::: "memory");
        }
        __syncwarp();
      }
      so = so == 49152 ? 0 : so + 24576;
    }
    if (lane == 0) asm volatile("cp.async.bulk.wait_group.read 0;" ::: "memory");
  } else if (warp >= 12) {
    nb_sync(7, 480);
#pragma unroll 1
    for (int n = blockIdx.x + (warp - 12) * step; n < NTB; n += 3 * step) {
      const int b = n / 56, rem = n - b * 56, par = rem / 14;
      const int c0 = opq((uint32_t)(par & 1)), c1 = opq((uint32_t)(8 * b)), c2 = opq((uint32_t)((par >> 1) * 112 + (rem - par * 14) * 8));
      int v; uint32_t spin = 0, tk = 0;
      do { asm volatile("ld.acquire.gpu.global.s32 %0, [%1];" : "=r"(v) : "l"(g_flags + n * FS) : "memory"); } while (v < 4 && ++spin < SPIN_LIMIT);
      if (lane == 0) asm volatile("atom.shared.add.u32 %0, [%1], 1;" : "=r"(tk) : "r"(bar + 120) : "memory");
      asm volatile("fence.proxy.async.global;" ::: "memory");
      tk = __shfl_sync(0xffffffffu, tk, 0);
      TRB(tk, 0);
      const uint32_t use = tk / NSTB, sg = tk - use * NSTB;
      if (use) mbar_wait(bar + (NSTB + sg) * 8, (use - 1) & 1);
      TRB(tk, 1);
      if (elect_one()) {
        asm volatile("st.shared.u32 [%0], %1;" ::"r"(bar + 128 + tk * 4), "r"(c0 | c1 << 8 | c2 << 16) : "memory");
        mbar_expect(bar + sg * 8, 24576);
        asm volatile("cp.async.bulk.tensor.3d.shared::cluster.global.mbarrier::complete_tx::bytes [%0], [%1, {%3,%4,%5}], [%2];"
                     ::"r"(sb + SM_B_IN + sg * 24576), "l"(&mp.oi), "r"(bar + sg * 8), "r"(c0 * 192), "r"(c1), "r"(c2) : "memory");
        g_flags[n * FS] = 0;
      }
      __syncwarp();
    }
  } else {
    const int wg = warp >> 2, w = warp & 3;
    uint32_t a[48];
    mbar_wait(bar + 2 * NSTB * 8, 0);
    {
      const int k = (lane & 7) + (lane >> 4) * 8, ch = (warp & 1) * 2 + ((lane >> 3) & 1);
      const uint32_t wa = sb + SM_B_W + (warp >> 1) * 12288 + k * 64 + ((ch ^ ((k >> 1) & 3)) * 16);
#pragma unroll
      for (int i = 0; i < 12; i++)
        asm volatile("ldmatrix.sync.aligned.m8n8.x4.trans.shared.b16 {%0,%1,%2,%3}, [%4];"
                     : "=r"(a[4 * i]), "=r"(a[4 * i + 1]), "=r"(a[4 * i + 2]), "=r"(a[4 * i + 3]) : "r"(wa + i * 1024) : "memory");
    }
    nb_sync(7, 480);
    TRB(47, 1);
    const uint32_t sta = opq(sb + SM_B_ST + wg * 8192 + ((lane & 7) + (lane >> 4) * 8) * 128 + (((2 * w + ((lane >> 3) & 1)) ^ (lane & 7)) * 16));
    const uint32_t hi = opq((uint32_t)(mkdesc(0, 0, 3072, 0) >> 32) + (blockIdx.x >> 16)), bb = opq(bar);
    const uint32_t nbT = opq((uint32_t)(4 + wg)), nbN = opq((uint32_t)(wg == 2 ? 4 : 5 + wg)), nbD = opq((uint32_t)(1 + wg));
    int left = (NTB - blockIdx.x + step - 1) / step;
    if (wg == 2) nb_arrive(4, 288);
#pragma unroll 1
    for (uint32_t ph = 0;; ph ^= 1) {
#pragma unroll
      for (int sg = 0; sg < NSTB; sg++) {
        constexpr uint64_t db = mkdesc(SBC + SM_B_IN, 128, 3072, 0);
        float D[32];
        mbar_wait(bb + sg * 8, ph);
        nb_sync(nbT, 288);
        wg_fence();
        wg_rs64<0>(D, a[0], a[1], a[2], a[3], dsc(db + sg * 1536, hi));
#pragma unroll
        for (int k = 1; k < 12; k++) wg_rs64<1>(D, a[4 * k], a[4 * k + 1], a[4 * k + 2], a[4 * k + 3], dsc(db + sg * 1536 + k * 16, hi));
        wg_commit();
        nb_arrive(nbN, 288);
        wg_wait<0>(); pin(D);
        mbar_arrive_elect(bb + (NSTB + sg) * 8);
#pragma unroll
        for (int q = 0; q < 4; q++)
          asm volatile("stmatrix.sync.aligned.m8n8.x4.trans.shared.b16 [%0], {%1,%2,%3,%4};" ::"r"(sta + (sg % 3) * 24576 + q * 2048),
                       "r"(pack2(D[8 * q], D[8 * q + 1])), "r"(pack2(D[8 * q + 2], D[8 * q + 3])), "r"(pack2(D[8 * q + 4], D[8 * q + 5])), "r"(pack2(D[8 * q + 6], D[8 * q + 7])) : "memory");
        fence_async();
        nb_arrive(nbD, 160);
        if (wg == 0) TRB(31 - left, 5);
        if (--left == 0) goto done;
      }
    }
  done:
    if (wg == 0) nb_arrive(4, 288);
    TR2(132 + blockIdx.x, 2);
  }
}

typedef CUresult (*EncodeFn)(CUtensorMap*, CUtensorMapDataType, cuuint32_t, void*, const cuuint64_t*, const cuuint64_t*, const cuuint32_t*,
                             const cuuint32_t*, CUtensorMapInterleave, CUtensorMapSwizzle, CUtensorMapL2promotion, CUtensorMapFloatOOBfill);
static EncodeFn g_enc = nullptr;
static void make_map(CUtensorMap* m, const void* p, int rank, const cuuint64_t* dim, const cuuint64_t* str, const cuuint32_t* box, CUtensorMapSwizzle sw) {
  const cuuint32_t ones[5] = {1, 1, 1, 1, 1};
  g_enc(m, CU_TENSOR_MAP_DATA_TYPE_BFLOAT16, rank, (void*)p, dim, str, box, ones, CU_TENSOR_MAP_INTERLEAVE_NONE, sw,
        CU_TENSOR_MAP_L2_PROMOTION_L2_128B, CU_TENSOR_MAP_FLOAT_OOB_FILL_NONE);
}

extern "C" void kernel_launch(void* const* d_in, const int* in_sizes, int n_in, void* d_out, int out_size) {
  const __nv_bfloat16* x = (const __nv_bfloat16*)d_in[0];
  const __nv_bfloat16* wqkv = (const __nv_bfloat16*)d_in[1];
  const __nv_bfloat16* wo = (const __nv_bfloat16*)d_in[2];
  const __nv_bfloat16* rpb = (const __nv_bfloat16*)d_in[3];

  if (!g_enc) {
    void* fn = nullptr; cudaDriverEntryPointQueryResult qr;
    cudaGetDriverEntryPoint("cuTensorMapEncodeTiled", &fn, cudaEnableDefault, &qr);
    g_enc = (EncodeFn)fn;
    cudaFuncSetAttribute(na_attn_kernel, cudaFuncAttributeMaxDynamicSharedMemorySize, SM_A_TOTAL);
    cudaFuncSetAttribute(na_proj_kernel, cudaFuncAttributeMaxDynamicSharedMemorySize, SM_B_TOTAL);
  }
  Maps ma; MapsB mb;
  { cuuint64_t dim[4] = {64, 112, 224, 6}, str[3] = {(cuuint64_t)ROWB, 768, 128};
    cuuint32_t box[4] = {64, 4, 16, 3}, boxh[4] = {64, 16, 3, 3}, boxo[4] = {64, 8, 8, 1};
    make_map(&ma.xc, x, 4, dim, str, box, CU_TENSOR_MAP_SWIZZLE_128B);
    make_map(&ma.xh, x, 4, dim, str, boxh, CU_TENSOR_MAP_SWIZZLE_128B);
    make_map(&mb.oo, d_out, 4, dim, str, boxo, CU_TENSOR_MAP_SWIZZLE_128B); }
  { cuuint64_t dim[3] = {384, 112, 224}, str[2] = {(cuuint64_t)ROWB, 768};
    cuuint32_t box[3] = {192, 8, 8}, boxs[3] = {192, 2, OCH};
    make_map(&mb.oi, d_out, 3, dim, str, box, CU_TENSOR_MAP_SWIZZLE_NONE);
    make_map(&ma.os, d_out, 3, dim, str, boxs, CU_TENSOR_MAP_SWIZZLE_NONE); }
  { cuuint64_t dim[4] = {32, 112, 224, 12}, str[3] = {(cuuint64_t)ROWB, 768, 64};
    cuuint32_t box[4] = {32, 8, 2, 3};
    make_map(&ma.ot, d_out, 4, dim, str, box, CU_TENSOR_MAP_SWIZZLE_64B); }
  { cuuint64_t dim[2] = {576, 192}, str[1] = {1152};
    cuuint32_t box[2] = {16, 192};
    make_map(&ma.w, wqkv, 2, dim, str, box, CU_TENSOR_MAP_SWIZZLE_32B); }
  { cuuint64_t dim[3] = {32, 192, 6}, str[2] = {384, 64};
    cuuint32_t box[3] = {32, 192, 3};
    make_map(&ma.wo, wo, 3, dim, str, box, CU_TENSOR_MAP_SWIZZLE_64B);
    mb.wo = ma.wo; }
  na_attn_kernel<<<112, 512, SM_A_TOTAL>>>(x, wqkv, rpb, ma);
  cudaLaunchConfig_t cfg = {};
  cfg.gridDim = dim3(20); cfg.blockDim = dim3(512); cfg.dynamicSmemBytes = SM_B_TOTAL; cfg.stream = cudaStreamPerThread;
  cudaLaunchAttribute at[1];
  at[0].id = cudaLaunchAttributeProgrammaticStreamSerialization; at[0].val.programmaticStreamSerializationAllowed = 1;
  cfg.attrs = at; cfg.numAttrs = 1;
  cudaLaunchKernelEx(&cfg, na_proj_kernel, mb);
}
```

```cpp
#include <cuda_runtime.h>
#include <cuda_bf16.h>
#include <cuda.h>
#include <stdint.h>

#define SPIN_LIMIT (1u << 18)

__device__ __forceinline__ uint32_t smem_u32(const void* p) { return (uint32_t)__cvta_generic_to_shared(p); }
__device__ __forceinline__ void wg_fence() { asm volatile("wgmma.fence.sync.aligned;" ::: "memory"); }
__device__ __forceinline__ void wg_commit() { asm volatile("wgmma.commit_group.sync.aligned;" ::: "memory"); }
template <int N> __device__ __forceinline__ void wg_wait() { asm volatile("wgmma.wait_group.sync.aligned %0;" ::"n"(N) : "memory"); }
template <int N> __device__ __forceinline__ void pin(float (&d)[N]) {
#pragma unroll
  for (int i = 0; i < N; i++) asm volatile("" : "+f"(d[i])::"memory");
}
__host__ __device__ constexpr uint64_t mkdesc(uint32_t addr, uint32_t lbo, uint32_t sbo, uint32_t sw) {
  return (uint64_t)((addr & 0x3FFFF) >> 4) | ((uint64_t)(lbo >> 4) << 16) | ((uint64_t)(sbo >> 4) << 32) | ((uint64_t)sw << 62);
}
__device__ __forceinline__ void mbar_init(uint32_t bar, uint32_t cnt) { asm volatile("mbarrier.init.shared::cta.b64 [%0], %1;" ::"r"(bar), "r"(cnt) : "memory"); }
__device__ __forceinline__ void mbar_arrive(uint32_t bar) { asm volatile("mbarrier.arrive.shared::cta.b64 _, [%0];" ::"r"(bar) : "memory"); }
__device__ __forceinline__ bool elect_one() {
  uint32_t r; asm volatile("{\n.reg .pred p;\nelect.sync _|p, 0xffffffff;\nselp.u32 %0, 1, 0, p;\n}" : "=r"(r)); return r;
}
__device__ __forceinline__ void mbar_arrive_elect(uint32_t bar) {
  asm volatile("{\n.reg .pred p;\nelect.sync _|p, 0xffffffff;\n@p mbarrier.arrive.shared::cta.b64 _, [%0];\n}" ::"r"(bar) : "memory");
}
__device__ __forceinline__ void mbar_expect(uint32_t bar, uint32_t bytes) { asm volatile("mbarrier.arrive.expect_tx.shared::cta.b64 _, [%0], %1;" ::"r"(bar), "r"(bytes) : "memory"); }
__device__ __forceinline__ void mbar_arrive_remote(uint32_t bar, uint32_t cta) {
  asm volatile("{\n.reg .b32 ra;\nmapa.shared::cluster.u32 ra, %0, %1;\nmbarrier.arrive.relaxed.cluster.shared::cluster.b64 _, [ra];\n}" ::"r"(bar), "r"(cta) : "memory");
}
__device__ __forceinline__ void mbar_wait(uint32_t bar, uint32_t parity) {
  asm volatile("{\n.reg .pred p;\n.reg .b32 n;\nmov.b32 n, 0;\nWL:\nmbarrier.try_wait.parity.shared::cta.b64 p, [%0], %1;\n@p bra WD;\n"
               "add.u32 n, n, 1;\nsetp.lt.u32 p, n, 65536;\n@p bra WL;\nWD:\n}" ::"r"(bar), "r"(parity) : "memory");
}
__device__ __forceinline__ void nb_sync(int id, int n) { asm volatile("bar.sync %0, %1;" ::"r"(id), "r"(n) : "memory"); }
__device__ __forceinline__ void nb_arrive(int id, int n) { asm volatile("bar.arrive %0, %1;" ::"r"(id), "r"(n) : "memory"); }
__device__ __forceinline__ uint32_t opq(uint32_t x) { uint32_t r; asm volatile("mov.b32 %0, %1;" : "=r"(r) : "r"(x)); return r; }
__device__ __forceinline__ uint64_t opq(uint64_t x) { uint64_t r; asm volatile("mov.b64 %0, %1;" : "=l"(r) : "l"(x)); return r; }
__device__ __forceinline__ uint32_t mapa(uint32_t a, uint32_t cta) { uint32_t r; asm("mapa.shared::cluster.u32 %0, %1, %2;" : "=r"(r) : "r"(a), "r"(cta)); return r; }
__device__ __forceinline__ void fence_async() { asm volatile("fence.proxy.async.shared::cta;" ::: "memory"); }
__device__ __forceinline__ void cluster_sync() {
  asm volatile("barrier.cluster.arrive.relaxed.aligned;\nbarrier.cluster.wait.aligned;" ::: "memory");
}
__device__ __forceinline__ uint32_t pack2(float lo, float hi) {
  uint32_t r; asm("cvt.rn.bf16x2.f32 %0, %1, %2;" : "=r"(r) : "f"(hi), "f"(lo)); return r;
}
__device__ __forceinline__ void stsm4(uint32_t a, uint32_t r0, uint32_t r1, uint32_t r2, uint32_t r3) {
  asm volatile("stmatrix.sync.aligned.m8n8.x4.shared.b16 [%0], {%1,%2,%3,%4};" ::"r"(a), "r"(r0), "r"(r1), "r"(r2), "r"(r3) : "memory");
}
__device__ __forceinline__ void ldsm4(uint32_t a, uint32_t& r0, uint32_t& r1, uint32_t& r2, uint32_t& r3) {
  asm volatile("ldmatrix.sync.aligned.m8n8.x4.shared.b16 {%0,%1,%2,%3}, [%4];" : "=r"(r0), "=r"(r1), "=r"(r2), "=r"(r3) : "r"(a) : "memory");
}
__device__ __forceinline__ void sts128(uint32_t a, uint4 v) {
  asm volatile("st.shared.v4.b32 [%0], {%1,%2,%3,%4};" ::"r"(a), "r"(v.x), "r"(v.y), "r"(v.z), "r"(v.w) : "memory");
}
__device__ __forceinline__ float lds_f32(uint32_t a) { float v; asm volatile("ld.shared.f32 %0, [%1];" : "=f"(v) : "r"(a)); return v; }
__device__ __forceinline__ float ex2(float x) { float y; asm("ex2.approx.ftz.f32 %0, %1;" : "=f"(y) : "f"(x)); return y; }

template<int SC> __device__ __forceinline__ void wg_ss144(float (&d)[72], uint64_t da, uint64_t db) {
  asm volatile("{\n.reg .pred p;\nsetp.ne.b32 p, %74, 0;\nwgmma.mma_async.sync.aligned.m64n144k16.f32.bf16.bf16 {%0,%1,%2,%3,%4,%5,%6,%7,%8,%9,%10,%11,%12,%13,%14,%15,%16,%17,%18,%19,%20,%21,%22,%23,%24,%25,%26,%27,%28,%29,%30,%31,%32,%33,%34,%35,%36,%37,%38,%39,%40,%41,%42,%43,%44,%45,%46,%47,%48,%49,%50,%51,%52,%53,%54,%55,%56,%57,%58,%59,%60,%61,%62,%63,%64,%65,%66,%67,%68,%69,%70,%71}, %72, %73, p, 1, 1, 0, 1;\n}\n"
    : "+f"(d[0]),"+f"(d[1]),"+f"(d[2]),"+f"(d[3]),"+f"(d[4]),"+f"(d[5]),"+f"(d[6]),"+f"(d[7]),"+f"(d[8]),"+f"(d[9]),"+f"(d[10]),"+f"(d[11]),"+f"(d[12]),"+f"(d[13]),"+f"(d[14]),"+f"(d[15]),"+f"(d[16]),"+f"(d[17]),"+f"(d[18]),"+f"(d[19]),"+f"(d[20]),"+f"(d[21]),"+f"(d[22]),"+f"(d[23]),"+f"(d[24]),"+f"(d[25]),"+f"(d[26]),"+f"(d[27]),"+f"(d[28]),"+f"(d[29]),"+f"(d[30]),"+f"(d[31]),"+f"(d[32]),"+f"(d[33]),"+f"(d[34]),"+f"(d[35]),"+f"(d[36]),"+f"(d[37]),"+f"(d[38]),"+f"(d[39]),"+f"(d[40]),"+f"(d[41]),"+f"(d[42]),"+f"(d[43]),"+f"(d[44]),"+f"(d[45]),"+f"(d[46]),"+f"(d[47]),"+f"(d[48]),"+f"(d[49]),"+f"(d[50]),"+f"(d[51]),"+f"(d[52]),"+f"(d[53]),"+f"(d[54]),"+f"(d[55]),"+f"(d[56]),"+f"(d[57]),"+f"(d[58]),"+f"(d[59]),"+f"(d[60]),"+f"(d[61]),"+f"(d[62]),"+f"(d[63]),"+f"(d[64]),"+f"(d[65]),"+f"(d[66]),"+f"(d[67]),"+f"(d[68]),"+f"(d[69]),"+f"(d[70]),"+f"(d[71]) : "l"(da), "l"(db), "n"(SC));
}
template<int SC> __device__ __forceinline__ void wg_ss96(float (&d)[48], uint64_t da, uint64_t db) {
  asm volatile("{\n.reg .pred p;\nsetp.ne.b32 p, %50, 0;\nwgmma.mma_async.sync.aligned.m64n96k16.f32.bf16.bf16 {%0,%1,%2,%3,%4,%5,%6,%7,%8,%9,%10,%11,%12,%13,%14,%15,%16,%17,%18,%19,%20,%21,%22,%23,%24,%25,%26,%27,%28,%29,%30,%31,%32,%33,%34,%35,%36,%37,%38,%39,%40,%41,%42,%43,%44,%45,%46,%47}, %48, %49, p, 1, 1, 0, 1;\n}\n"
    : "+f"(d[0]),"+f"(d[1]),"+f"(d[2]),"+f"(d[3]),"+f"(d[4]),"+f"(d[5]),"+f"(d[6]),"+f"(d[7]),"+f"(d[8]),"+f"(d[9]),"+f"(d[10]),"+f"(d[11]),"+f"(d[12]),"+f"(d[13]),"+f"(d[14]),"+f"(d[15]),"+f"(d[16]),"+f"(d[17]),"+f"(d[18]),"+f"(d[19]),"+f"(d[20]),"+f"(d[21]),"+f"(d[22]),"+f"(d[23]),"+f"(d[24]),"+f"(d[25]),"+f"(d[26]),"+f"(d[27]),"+f"(d[28]),"+f"(d[29]),"+f"(d[30]),"+f"(d[31]),"+f"(d[32]),"+f"(d[33]),"+f"(d[34]),"+f"(d[35]),"+f"(d[36]),"+f"(d[37]),"+f"(d[38]),"+f"(d[39]),"+f"(d[40]),"+f"(d[41]),"+f"(d[42]),"+f"(d[43]),"+f"(d[44]),"+f"(d[45]),"+f"(d[46]),"+f"(d[47]) : "l"(da), "l"(db), "n"(SC));
}
template<int SC> __device__ __forceinline__ void wg_rs112(float (&d)[56], uint32_t a0, uint32_t a1, uint32_t a2, uint32_t a3, uint64_t db) {
  asm volatile("{\n.reg .pred p;\nsetp.ne.b32 p, %61, 0;\nwgmma.mma_async.sync.aligned.m64n112k16.f32.bf16.bf16 {%0,%1,%2,%3,%4,%5,%6,%7,%8,%9,%10,%11,%12,%13,%14,%15,%16,%17,%18,%19,%20,%21,%22,%23,%24,%25,%26,%27,%28,%29,%30,%31,%32,%33,%34,%35,%36,%37,%38,%39,%40,%41,%42,%43,%44,%45,%46,%47,%48,%49,%50,%51,%52,%53,%54,%55}, {%56,%57,%58,%59}, %60, p, 1, 1, 0;\n}\n"
    : "+f"(d[0]),"+f"(d[1]),"+f"(d[2]),"+f"(d[3]),"+f"(d[4]),"+f"(d[5]),"+f"(d[6]),"+f"(d[7]),"+f"(d[8]),"+f"(d[9]),"+f"(d[10]),"+f"(d[11]),"+f"(d[12]),"+f"(d[13]),"+f"(d[14]),"+f"(d[15]),"+f"(d[16]),"+f"(d[17]),"+f"(d[18]),"+f"(d[19]),"+f"(d[20]),"+f"(d[21]),"+f"(d[22]),"+f"(d[23]),"+f"(d[24]),"+f"(d[25]),"+f"(d[26]),"+f"(d[27]),"+f"(d[28]),"+f"(d[29]),"+f"(d[30]),"+f"(d[31]),"+f"(d[32]),"+f"(d[33]),"+f"(d[34]),"+f"(d[35]),"+f"(d[36]),"+f"(d[37]),"+f"(d[38]),"+f"(d[39]),"+f"(d[40]),"+f"(d[41]),"+f"(d[42]),"+f"(d[43]),"+f"(d[44]),"+f"(d[45]),"+f"(d[46]),"+f"(d[47]),"+f"(d[48]),"+f"(d[49]),"+f"(d[50]),"+f"(d[51]),"+f"(d[52]),"+f"(d[53]),"+f"(d[54]),"+f"(d[55]) : "r"(a0), "r"(a1), "r"(a2), "r"(a3), "l"(db), "n"(SC));
}
template<int SC> __device__ __forceinline__ void wg_sp48(float (&d)[24], uint32_t a0, uint32_t a1, uint32_t a2, uint32_t a3, uint64_t db, uint32_t meta) {
  asm volatile("{\n.reg .pred p;\nsetp.ne.b32 p, %30, 0;\nwgmma.mma_async.sp.sync.aligned.m64n48k32.f32.bf16.bf16 {%0,%1,%2,%3,%4,%5,%6,%7,%8,%9,%10,%11,%12,%13,%14,%15,%16,%17,%18,%19,%20,%21,%22,%23}, {%24,%25,%26,%27}, %28, %29, 0, p, 1, 1, 1;\n}\n"
    : "+f"(d[0]),"+f"(d[1]),"+f"(d[2]),"+f"(d[3]),"+f"(d[4]),"+f"(d[5]),"+f"(d[6]),"+f"(d[7]),"+f"(d[8]),"+f"(d[9]),"+f"(d[10]),"+f"(d[11]),"+f"(d[12]),"+f"(d[13]),"+f"(d[14]),"+f"(d[15]),"+f"(d[16]),"+f"(d[17]),"+f"(d[18]),"+f"(d[19]),"+f"(d[20]),"+f"(d[21]),"+f"(d[22]),"+f"(d[23]) : "r"(a0), "r"(a1), "r"(a2), "r"(a3), "l"(db), "r"(meta), "n"(SC));
}
template<int SC> __device__ __forceinline__ void wg_rs64(float (&d)[32], uint32_t a0, uint32_t a1, uint32_t a2, uint32_t a3, uint64_t db) {
  asm volatile("{\n.reg .pred p;\nsetp.ne.b32 p, %37, 0;\nwgmma.mma_async.sync.aligned.m64n64k16.f32.bf16.bf16 {%0,%1,%2,%3,%4,%5,%6,%7,%8,%9,%10,%11,%12,%13,%14,%15,%16,%17,%18,%19,%20,%21,%22,%23,%24,%25,%26,%27,%28,%29,%30,%31}, {%32,%33,%34,%35}, %36, p, 1, 1, 0;\n}\n"
    : "+f"(d[0]),"+f"(d[1]),"+f"(d[2]),"+f"(d[3]),"+f"(d[4]),"+f"(d[5]),"+f"(d[6]),"+f"(d[7]),"+f"(d[8]),"+f"(d[9]),"+f"(d[10]),"+f"(d[11]),"+f"(d[12]),"+f"(d[13]),"+f"(d[14]),"+f"(d[15]),"+f"(d[16]),"+f"(d[17]),"+f"(d[18]),"+f"(d[19]),"+f"(d[20]),"+f"(d[21]),"+f"(d[22]),"+f"(d[23]),"+f"(d[24]),"+f"(d[25]),"+f"(d[26]),"+f"(d[27]),"+f"(d[28]),"+f"(d[29]),"+f"(d[30]),"+f"(d[31]) : "r"(a0), "r"(a1), "r"(a2), "r"(a3), "l"(db), "n"(SC));
}

constexpr uint32_t SBC = 1024;
constexpr int ROWB = 2 * 224 * 384;
constexpr int TB = 11;
constexpr int KS = 832;
constexpr int KSLOT = 22 * KS;
constexpr int SM_X = 0;
constexpr int SM_W = SM_X + 3 * 24576;
constexpr int SM_K = SM_W + 55296;
constexpr int SM_V = SM_K + 2 * KSLOT;
constexpr int SM_Q = SM_V + 22 * 1536;
constexpr int SM_O = SM_Q + 12288;
constexpr int SM_S = SM_O + 12288;
constexpr int SM_RPB = SM_S + 6144;
constexpr int SM_BAR = SM_RPB + 768;
constexpr int SM_A_TOTAL = SM_BAR + 256;
constexpr int SM_TIN0 = SM_X + 24576, SM_TIN1 = SM_X, SM_TIN2 = SM_W + 18432;
constexpr int SM_TWO = SM_X + 2 * 24576;
constexpr int SM_TST = SM_TIN2 + 24576;
enum { B_FULL = 0, B_EMPTY = 3, B_TIN = 6, B_TFREE = 10, B_WK = 12, B_WQ, B_WO, B_KIMP, B_VIMP, B_OFREE, B_XK, B_XV,
       B_Q0, B_WOFREE, B_OTAIL, B_ODONE = B_OTAIL + 4, B_KFREE, B_VFREE, B_COUNT };
enum { N_KRDY = 4, N_QK0, N_QK1, N_VQ0, N_VQ1, N_PVISS, N_Q0 };

#define NL 2
#define OCH 16
#define MID 6
#define SPL 4
#define RA 160
#define RG 168
#define OPT 0
constexpr int FS = 64;
__device__ int g_flags[TB * 56 * FS];

#define TR(role, it, k)
#define TRDECL
#define TRARG
#define TRPASS
#define TRDUMP
#define TRB(it, k)
#define TR2(blk, k)

struct Stage { uint32_t lo, full, em, par; };
struct GemmCtx {
  uint32_t bar;
  uint32_t kC, vC[2], qC[2];
  uint32_t kH, vH[2];
  uint32_t hiA, hiB;
  uint32_t spin;
  bool hvalid, never, edge;
};

template <int STRIDE> __device__ __forceinline__ void dump12(uint32_t a, const uint32_t (&r)[12]) {
#pragma unroll
  for (int j = 0; j < 3; j++) stsm4(a + j * 2 * STRIDE, r[4 * j], r[4 * j + 1], r[4 * j + 2], r[4 * j + 3]);
}
__device__ __forceinline__ void keep12(bool never, uint32_t a, const uint32_t (&r)[12]) { if (never) dump12<128>(a, r); }
template <int N> __device__ __forceinline__ void pack12(uint32_t (&r)[12], const float (&d)[N], int off) {
#pragma unroll
  for (int j = 0; j < 12; j++) r[j] = pack2(d[off + 2 * j], d[off + 2 * j + 1]);
}
__device__ __forceinline__ uint64_t dsc(uint64_t lo, uint32_t hi) { uint64_t r; asm("mov.b64 %0, {%1, %2};" : "=l"(r) : "r"((uint32_t)lo), "r"(hi)); return r; }
template <int K0, int K1> __device__ __forceinline__ void issue_core(const GemmCtx& c, const Stage& x, float (&d)[72]) {
  constexpr uint64_t db = mkdesc(SBC + SM_W, 6144, 256, 3);
  wg_fence();
  if (K0 == 0) wg_ss144<0>(d, dsc(x.lo, c.hiA), dsc(db, c.hiB));
#pragma unroll
  for (int k = K0 ? K0 : 1; k < K1; k++) wg_ss144<1>(d, dsc(x.lo + (k >> 2) * 512 + (k & 3) * 2, c.hiA), dsc(db + k * 32, c.hiB));
  wg_commit();
}
template <int K0, int K1> __device__ __forceinline__ void issue_halo(const GemmCtx& c, const Stage& x, float (&d)[48]) {
  constexpr uint64_t db = mkdesc(SBC + SM_W + 18432, 6144, 256, 3);
  wg_fence();
  if (K0 == 0) wg_ss96<0>(d, dsc(x.lo, c.hiA), dsc(db, c.hiB));
#pragma unroll
  for (int k = K0 ? K0 : 1; k < K1; k++) wg_ss96<1>(d, dsc(x.lo + (k >> 2) * 384 + (k & 3) * 2, c.hiA), dsc(db + k * 32, c.hiB));
  wg_commit();
}
__device__ __forceinline__ void release_stage(const Stage& x) {
  asm volatile("{\n.reg .pred p;\nelect.sync _|p, 0xffffffff;\n@p mbarrier.arrive.shared::cluster.b64 _, [%0];\n}" ::"r"(x.em) : "memory");
}
__device__ __forceinline__ void wait_stage(GemmCtx& c, Stage& x) {
  asm volatile("{\n.reg .pred p;\nWL:\nmbarrier.try_wait.parity.shared::cta.b64 p, [%1], %2;\n@p bra WD;\n"
               "add.u32 %0, %0, 1;\nsetp.lt.u32 p, %0, 0x100000;\n@p bra WL;\nWD:\n}" : "+r"(c.spin) : "r"(x.full), "r"(x.par) : "memory");
  x.par ^= 1;
}
__device__ __forceinline__ void edge_ready(const GemmCtx& c, int bar) { __syncwarp(); if (c.edge) mbar_arrive_elect(c.bar + bar * 8); }
__device__ __forceinline__ void dump6(uint32_t a, const uint32_t (&r)[6]) {
  stsm4(a, r[0], r[1], r[2], r[3]);
  asm volatile("stmatrix.sync.aligned.m8n8.x2.shared.b16 [%0], {%1,%2};" ::"r"(a + 512), "r"(r[4]), "r"(r[5]) : "memory");
}
__device__ __forceinline__ void pack6(uint32_t (&r)[6], const float (&d)[48], int off) {
#pragma unroll
  for (int j = 0; j < 6; j++) r[j] = pack2(d[off + 4 * j], d[off + 4 * j + 1]);
}
template <int PARITY> __device__ __forceinline__ void gwait(GemmCtx& c, int bar) {
  asm volatile("{\n.reg .pred p;\nWL:\nmbarrier.try_wait.parity.shared::cta.b64 p, [%1], %2;\n@p bra WD;\n"
               "add.u32 %0, %0, 1;\nsetp.lt.u32 p, %0, 0x100000;\n@p bra WL;\nWD:\n}" : "+r"(c.spin) : "r"(c.bar + bar * 8), "n"(PARITY) : "memory");
}
__device__ __forceinline__ void load_w(const CUtensorMap* m, uint32_t dst, uint32_t bar, int col) {
  asm volatile("cp.async.bulk.tensor.2d.shared::cluster.global.mbarrier::complete_tx::bytes [%0], [%1, {%3,%4}], [%2];"
               ::"r"(dst), "l"(m), "r"(bar), "r"(col), "r"(0) : "memory");
}
template <int BYTES> __device__ __forceinline__ void send_o(uint32_t dst, uint32_t src, uint32_t bar, int cta) {
  asm volatile("{\n.reg .b32 rd, rb;\nmapa.shared::cluster.u32 rd, %0, %3;\nmapa.shared::cluster.u32 rb, %2, %3;\n"
               "cp.async.bulk.shared::cluster.shared::cta.mbarrier::complete_tx::bytes [rd], [%1], %4, [rb];\n}"
               ::"r"(dst), "r"(src), "r"(bar), "r"(cta), "n"(BYTES) : "memory");
}
__device__ __forceinline__ void remote_arrive(uint32_t rbar) { asm volatile("mbarrier.arrive.shared::cluster.b64 _, [%0];" ::"r"(rbar) : "memory"); }
__device__ __forceinline__ void remote_expect(uint32_t rbar, uint32_t bytes) {
  asm volatile("mbarrier.arrive.expect_tx.shared::cluster.b64 _, [%0], %1;" ::"r"(rbar), "r"(bytes) : "memory");
}
__device__ __forceinline__ void copy_remote(uint32_t rdst, uint32_t src, uint32_t bytes, uint32_t rbar) {
  asm volatile("cp.async.bulk.shared::cluster.shared::cta.mbarrier::complete_tx::bytes [%0], [%1], %2, [%3];" ::"r"(rdst), "r"(src), "r"(bytes), "r"(rbar) : "memory");
}
__device__ __forceinline__ void tail_free(uint32_t bar) {
  uint32_t ln; asm volatile("mov.u32 %0, %%laneid;" : "=r"(ln));
  if (ln < 4) mbar_arrive_remote(bar, ln + (blockIdx.x & 4));
}
__device__ __forceinline__ void publish(uint32_t bar) {
  fence_async();
  __syncwarp();
  mbar_arrive_elect(bar);
}

template <bool FIRST, int PA>
__device__ __forceinline__ void gemm_iter(GemmCtx& c, int b, uint32_t (&pk)[12], uint32_t (&pv)[12], uint32_t (&pq)[12],
                                          uint32_t (&hk1)[6], uint32_t (&hv1)[6], Stage& x0, Stage& x2, Stage& x1 TRARG) {
  const uint32_t bar = c.bar;
  const bool w = !FIRST && (PA == 0 || b >= 0), never = c.never;
  constexpr uint32_t ko = PA * KSLOT;
  float C[72];
  uint32_t hk0[6], hv0[6], pv2[12];
  TR(2, b, 0);
  if (FIRST) wait_stage(c, x0);
  else dump12<128>(c.qC[1], pq);
  if (w) nb_sync(N_QK1, 256);
  TR(2, b, 2);
  if (FIRST) TR(2, b - 1, 6);
  if (PA == 0) {
    float H[48];
    issue_halo<0, 8>(c, x0, H);
    TR(2, b, 3);
    if (!FIRST) { gwait<0>(c, B_KFREE); dump12<128>(c.kC, pk); }
    issue_halo<8, 12>(c, x0, H);
    TR(2, b, 4);
    wait_stage(c, x2);
    if (FIRST) TR(2, b - 1, 7);
    if (FIRST) gwait<0>(c, B_WQ);
    if (FIRST) TR(2, b - 1, 8);
    issue_core<0, 8>(c, x2, C);
    TR(2, b, 5);
    if (!FIRST) { fence_async(); keep12(never, c.kC, pk); }
    wg_wait<1>(); pin(H);
    release_stage(x0);
    pack6(hk0, H, 0);
    if (c.hvalid) dump6(c.kH, hk0);
    pack6(hk1, H, 2); pack6(hv0, H, 24); pack6(hv1, H, 26);
  } else {
    issue_core<0, 8>(c, x2, C);
    TR(2, b, 5);
    fence_async();
    keep12(never, c.kC, pq);
    if (w) gwait<1>(c, B_KFREE);
    dump12<128>(c.kC + ko, pk);
    if (c.hvalid) dump6(c.kH + ko, hk1);
  }
  TR(2, b, 13);
  issue_core<8, 12>(c, x2, C);
  if (w) { nb_arrive(N_VQ0, 288); nb_arrive(N_VQ1, 288); }
  else if (!FIRST) { __syncwarp(); mbar_arrive_elect(bar + B_Q0 * 8); }
  wait_stage(c, x1);
  if (never) dump6(bar, PA ? hk1 : hk0);
  TR(2, b, 6);
  wg_wait<0>(); pin(C);
  TR(2, b, 7);
  release_stage(x2);
  pack12(pk, C, 24);
  dump12<128>(c.kC + ko + 64, pk);
  pack12(pv2, C, 48);
  pack12(pq, C, 0);
  TR(2, b, 8);
  issue_core<0, SPL>(c, x1, C);
  TR(2, b, 9);
  if (!FIRST) { fence_async(); edge_ready(c, B_XK); }
  keep12(never, c.kC, pk);
  TR(2, b, 14);
  if (w) nb_sync(N_PVISS, 384);
  issue_core<SPL, 12>(c, x1, C);
  if (!FIRST) nb_arrive(N_KRDY, 256);
  TR(2, b, 1);
  if (PA && b == 11) tail_free(bar + B_TFREE * 8);
  wait_stage(c, x0);
  if (w) gwait<PA>(c, B_VFREE);
  if (w && b < TB) gwait<PA>(c, B_ODONE);
  TR(2, b, 10);
  if (!FIRST) dump12<128>(c.vC[PA], pv);
  dump12<128>(c.vC[PA ^ 1] + 768, pv2);
  TR(2, b, 11);
  wg_wait<0>(); pin(C);
  TR(2, b, 12);
  release_stage(x1);
  if (!FIRST && c.edge) publish(bar + B_XV * 8);
  if (c.hvalid) dump6(c.vH[PA], PA ? hv1 : hv0);
  if (PA && !w) nb_sync(N_Q0, 384);
  dump12<128>(c.qC[0], pq);
  pack12(pk, C, 24);
  pack12(pv, C, 48);
  pack12(pq, C, 0);
}

template <int IN> __device__ __forceinline__ void issue_proj(float (&D)[48]) {
  constexpr uint64_t da = mkdesc(SBC + IN, 128, 768, 0), db = mkdesc(SBC + SM_TWO, 12288, 512, 2);
  wg_fence();
  wg_ss96<0>(D, da, db);
#pragma unroll
  for (int k = 1; k < 12; k++) wg_ss96<1>(D, da + (k / 3) * 384 + (k % 3) * 16, db + k * 64);
  wg_commit();
}
template <int ACC> __device__ __forceinline__ void issue_proj_half(float (&D)[48], int hd) {
  const uint64_t da = mkdesc(SBC + SM_TIN2, 128, 768, 0) + hd * 384, db = mkdesc(SBC + SM_TWO, 12288, 512, 2) + hd * 192;
  wg_fence();
  wg_ss96<ACC>(D, da, db);
#pragma unroll
  for (int k = 1; k < 6; k++) wg_ss96<1>(D, da + (k / 3) * 768 + (k % 3) * 16, db + (k / 3) * 384 + (k % 3) * 64);
  wg_commit();
}
__device__ __forceinline__ void store_proj(const float (&D)[48], const CUtensorMap* m, uint32_t st, uint32_t sta, int row, int col, int ch) {
#pragma unroll
  for (int q = 0; q < 6; q++)
    stsm4((sta ^ ((q & 1) * 32)) + (q >> 1) * 1024,
          pack2(D[8 * q], D[8 * q + 1]), pack2(D[8 * q + 2], D[8 * q + 3]), pack2(D[8 * q + 4], D[8 * q + 5]), pack2(D[8 * q + 6], D[8 * q + 7]));
  fence_async();
  __syncwarp();
  if ((threadIdx.x & 31) == 0) {
    asm volatile("cp.async.bulk.tensor.4d.global.shared::cta.bulk_group [%0, {%2,%3,%4,%5}], [%1];" ::"l"(m), "r"(st), "r"(0), "r"(row), "r"(col), "r"(ch) : "memory");
    asm volatile("cp.async.bulk.commit_group;" ::: "memory");
  }
  __syncwarp();
}

__device__ __forceinline__ float fold(float a, float b, float t, int useb) {
  float r;
  asm("{\n.reg .pred p;\nsetp.ne.b32 p, %4, 0;\nfma.rn.f32 %0, %1, 0f3E553B95, %3;\n@p fma.rn.f32 %0, %2, 0f3E553B95, %3;\n}"
      : "=&f"(r) : "f"(a), "f"(b), "f"(t), "r"(useb));
  return r;
}
template <int U, int L>
__device__ __forceinline__ void softmax_tile(const float (&SA)[56], const float (&SB)[56], const float (&T)[16], int b0, int b1,
                                             uint32_t (&P)[28], float (&sx)[8], uint32_t nbV, uint32_t zero, uint32_t qa, uint32_t (&q)[12]) {
  float lu[14], ll[14];
#pragma unroll
  for (int j = 0; j < 7; j++) {
    constexpr int sh = U == L ? 2 : 0;
    const float tu0 = T[2 * j + sh], tu1 = T[2 * j + 1 + sh], tl0 = T[2 * j], tl1 = T[2 * j + 1];
    lu[2 * j]     = fold(SA[4 * (U + j)],     SB[4 * (U + j)],     tu0, b0);
    ll[2 * j]     = fold(SA[4 * (L + j) + 2], SB[4 * (L + j) + 2], tl0, b0);
    lu[2 * j + 1] = fold(SA[4 * (U + j) + 1], SB[4 * (U + j) + 1], tu1, b1);
    ll[2 * j + 1] = fold(SA[4 * (L + j) + 3], SB[4 * (L + j) + 3], tl1, b1);
  }
  float mu = lu[0], ml = ll[0], mu2 = lu[1], ml2 = ll[1];
#pragma unroll
  for (int j = 1; j < 7; j++) { mu = fmaxf(mu, lu[2 * j]); mu2 = fmaxf(mu2, lu[2 * j + 1]); ml = fmaxf(ml, ll[2 * j]); ml2 = fmaxf(ml2, ll[2 * j + 1]); }
  mu = fmaxf(mu, mu2); ml = fmaxf(ml, ml2);
  { const float a1 = __shfl_xor_sync(0xffffffffu, mu, 1), a2 = __shfl_xor_sync(0xffffffffu, mu, 2), a3 = __shfl_xor_sync(0xffffffffu, mu, 3);
    const float c1 = __shfl_xor_sync(0xffffffffu, ml, 1), c2 = __shfl_xor_sync(0xffffffffu, ml, 2), c3 = __shfl_xor_sync(0xffffffffu, ml, 3);
    mu = fmaxf(fmaxf(mu, a1), fmaxf(a2, a3)); ml = fmaxf(fmaxf(ml, c1), fmaxf(c2, c3)); }
  float su = 0.f, sl = 0.f;
#pragma unroll
  for (int c = 0; c < 14; c++) {
    if (c >= U && c < U + 7) {
      float e0 = ex2(lu[2 * (c - U)] - mu), e1 = ex2(lu[2 * (c - U) + 1] - mu);
      su = c == U ? e0 + e1 : (su + e0) + e1; P[2 * c] = pack2(e0, e1);
    } else P[2 * c] = 0u;
  }
  nb_sync(nbV | (P[2 * (U + MID)] & zero), 288);
#pragma unroll
  for (int k = 0; k < 3; k++) ldsm4(qa + k * 256, q[4 * k], q[4 * k + 1], q[4 * k + 2], q[4 * k + 3]);
#pragma unroll
  for (int c = 0; c < 14; c++) {
    if (c >= L && c < L + 7) {
      float e0 = ex2(ll[2 * (c - L)] - ml), e1 = ex2(ll[2 * (c - L) + 1] - ml);
      sl = c == L ? e0 + e1 : (sl + e0) + e1; P[2 * c + 1] = pack2(e0, e1);
    } else P[2 * c + 1] = 0u;
  }
  sx[0] = su; sx[4] = sl;
#pragma unroll
  for (int k = 1; k < 4; k++) sx[k] = __shfl_xor_sync(0xffffffffu, su, k);
#pragma unroll
  for (int k = 1; k < 4; k++) sx[4 + k] = __shfl_xor_sync(0xffffffffu, sl, k);
}

struct BandCfg { uint32_t ra0, ra1, meta; int b0, b1; };
__device__ __forceinline__ void band_cfg(int b, uint32_t tb, BandCfg& n) {
  uint32_t ln; asm volatile("mov.u32 %0, %%laneid;" : "=r"(ln));
  const int g = ln >> 2, t = ln & 3;
  const int sw = min(max(g + 1, b == 0 ? 4 : 0), b == 13 ? 5 : 8);
  const int i0 = 2 * t, i1 = 2 * t + 1;
  n.b0 = i0 <= sw - 2; n.b1 = i1 <= sw - 2;
  n.ra0 = tb + (i0 == sw - 1 ? 13 : i0 + 8 * n.b0 - g + 2) * 52;
  n.ra1 = tb + (i1 == sw - 1 ? 13 : i1 + 8 * n.b1 - g + 2) * 52;
  n.meta = ((0x5555u & ((1u << (2 * (sw - 1))) - 1)) ^ 0xDD88u ^ (((t ^ b) & 1) ? 0x5555u : 0u)) * 0x10001u;
}
__device__ __forceinline__ void band_load(const BandCfg& n, float (&T)[16], int& b0, int& b1, uint32_t& meta) {
#pragma unroll
  for (int jj = 0; jj < 8; jj++) { T[2 * jj] = lds_f32(n.ra0 + jj * 4); T[2 * jj + 1] = lds_f32(n.ra1 + jj * 4); }
  b0 = n.b0; b1 = n.b1; meta = n.meta;
}

struct Maps { CUtensorMap xc, xh, w, os, wo, ot; };

__global__ void __cluster_dims__(8, 1, 1) __launch_bounds__(512, 1)
na_attn_kernel(const __nv_bfloat16* __restrict__ x, const __nv_bfloat16* __restrict__ wqkv, const __nv_bfloat16* __restrict__ rpb, const __grid_constant__ Maps mp) {
  extern __shared__ __align__(1024) uint8_t smem_raw[];
  const uint32_t sb = smem_u32(smem_raw);
  if ((sb & 0x3FFFF) != SBC) return;
  const uint32_t bar = sb + SM_BAR;
  TR2(blockIdx.x, 0);
  const int tid = threadIdx.x, lane = tid & 31;
  const int warp = __shfl_sync(0xffffffffu, tid >> 5, 0);
  const int head = blockIdx.x & 3, base = blockIdx.x & 4, sp = blockIdx.x >> 2;
  const int par = sp < 24 ? sp / 6 : sp - 24, strip = sp < 24 ? sp - par * 6 : 6, ph = par >> 1, pw = par & 1;
  const int odd = strip & 1;

  uint4 wv[2 * NL];
  const int va = head == 1;
  const uint32_t wdst = sb + SM_W + (3 + va + ((tid >> 1) & 1)) * 6144 + (tid >> 2) * 32 + ((tid ^ (tid >> 4)) & 1) * 16;
  if (warp < 12) {
    asm volatile("barrier.cluster.arrive.relaxed.aligned;" ::: "memory");
    const uint32_t wo0 = (tid >> 2) * 1152 + head * 96 + va * 32 + (tid & 3) * 16;
#pragma unroll
    for (int i = 0; i < 2 * NL; i++)
      asm volatile("ld.global.nc.v4.b32 {%0,%1,%2,%3}, [%4];" : "=r"(wv[i].x), "=r"(wv[i].y), "=r"(wv[i].z), "=r"(wv[i].w)
                   : "l"(reinterpret_cast<const uint8_t*>(wqkv) + wo0 + (i & 1) * 96 * 1152 + (i / 2 + 1) * 384));
  }
  if (warp < 8) {
    asm volatile("setmaxnreg.inc.sync.aligned.u32 %0;" ::"n"(RA));
    float rv = -INFINITY;
    if (tid < 169) rv = __bfloat162float(rpb[head * 169 + tid]) * 1.4426950408889634f;
    if (tid < 192) {
      const int kc = (tid & 15) + 3, wc = (tid >> 4) % 6;
      sts128(tid < 96 ? sb + SM_K + kc * KS + wc * 128 + 48 : sb + SM_V + kc * 1536 + wc * 128 + (6 + (kc & 1)) * 16, make_uint4(0, 0, 0, 0));
    }
#pragma unroll
    for (int i = 0; i < 2 * NL; i++) sts128(wdst + (i & 1) * 3072 + (i / 2) * 18432, wv[i]);
    fence_async();
    asm volatile("bar.arrive 1, 384;" ::: "memory");
    if (tid < 182) asm volatile("st.shared.f32 [%0], %1;" ::"r"(sb + SM_RPB + tid * 4), "f"(rv) : "memory");
    const int jw = warp >> 2, j = jw ^ odd, w = warp & 3, wt = 4 * j + w;
    int variant = w;
    if (strip == 0 && j == 0 && w < 2) variant = 4;
    if (strip == 6 && j == 1 && w >= 2) variant = 5;
    const bool v1 = opq((uint32_t)(variant & 1)), v2 = opq((uint32_t)(variant & 2)), v4 = opq((uint32_t)(variant & 4));
    const uint32_t qa = opq(sb + SM_Q + (8 * j + 2 * w + ((lane >> 3) & 1)) * 768 + (lane >> 4) * 128 + (((lane & 7) * 16) ^ (((lane >> 3) & 1) * 64)));
    uint32_t oa = opq(sb + SM_O + j * 6144 + (2 * w + ((lane >> 3) & 1)) * 768 + (lane >> 4) * 128 + (lane & 7) * 16);
    uint64_t dA = opq(mkdesc(SBC + SM_K, 128, KS, 0) + j * (8 * KS / 16)), dB = opq(dA + (KSLOT >> 4));
    uint64_t dV[7];
#pragma unroll
    for (int i = 0; i < 7; i++) dV[i] = opq(mkdesc(SBC + SM_V, 768, 128, 0) + j * (8 * 1536 / 16) + i * 192);
    const uint32_t nbK = opq((uint32_t)(N_KRDY + jw)), nbQ = opq((uint32_t)(N_QK0 + jw)), nbV = opq((uint32_t)(N_VQ0 + jw));
    asm volatile("barrier.cluster.wait.aligned;" ::: "memory");
    asm volatile("bar.sync 3, 256;" ::: "memory");
    float T[16];
    TRDECL;
    int b0, b1;
    uint32_t meta, ob = bar + B_ODONE * 8, fb = bar + B_OFREE * 8, fp = 1;
    const uint32_t tb = opq(sb + SM_RPB + (variant < 4 ? 3 : variant + 1 - 2 * w) * 4);
    const bool own = ((w ^ head) & 2) == 0;
    const uint32_t dst13 = sb + SM_TIN2 + head * 6144 + (2 * j + (w & 1)) * 1536, src13 = opq(own ? dst13 : sb + SM_S + (2 * j + (w & 1)) * 1536);
    const uint32_t snd[4] = {opq(own ? 0u : mapa(dst13, base + (head ^ 2))), opq(mapa(bar + (B_TIN + 2) * 8, base + (head ^ 2))),
                             opq(mapa(dst13, base + (w & 2) + (~head & 1))), opq(mapa(bar + (B_TIN + 3) * 8, base + (w & 2) + (~head & 1)))};
    BandCfg nx;
    band_cfg(0, tb, nx);
    band_load(nx, T, b0, b1, meta);
    band_cfg(1, tb, nx);
    const uint32_t zero = opq(blockIdx.x >> 16);
    uint32_t special = opq(0x380Au << 1);
    uint32_t q[12];
    mbar_wait(bar + B_Q0 * 8, 0);
#pragma unroll
    for (int k = 0; k < 3; k++) ldsm4(qa + k * 256, q[4 * k], q[4 * k + 1], q[4 * k + 2], q[4 * k + 3]);
    nb_arrive(N_Q0, 384);
#pragma unroll 1
    for (int b = 0; b < 14; b++) {
      float SA[56], SB[56];
      TR(0, b, 0);
      if (jw) mbar_wait(bar + B_KIMP * 8, b & 1);
      nb_sync(nbK, 256);
      TR(0, b, 1);
      TR(0, b - 1, 9);
      wg_fence();
      wg_rs112<0>(SA, q[0], q[1], q[2], q[3], dA);
      wg_rs112<0>(SB, q[0], q[1], q[2], q[3], dB);
      wg_rs112<1>(SA, q[4], q[5], q[6], q[7], dA + 16);
      wg_rs112<1>(SB, q[4], q[5], q[6], q[7], dB + 16);
      wg_rs112<1>(SA, q[8], q[9], q[10], q[11], dA + 32);
      wg_rs112<1>(SB, q[8], q[9], q[10], q[11], dB + 32);
      wg_commit();
      nb_arrive(nbQ, 256);
      { const uint64_t t = dA; dA = dB; dB = t; }
      special >>= 1;
      if (special & 1) {
        if (b == 3) band_cfg(13, tb, nx);
        else {
          if (b == 1 || b == 13) band_load(nx, T, b0, b1, meta);
          if (b >= TB) {
            ob = bar + (b == 13 ? (own ? B_TIN + 2 : B_ODONE) : B_OTAIL + 2 * (b - TB) + jw) * 8;
            if (b > TB) { fb = bar + (B_TFREE + b - 12) * 8; fp = 0; }
            oa += b == 12 ? 0u - (SM_O - SM_Q) : (b == 13 ? src13 - (sb + SM_Q + wt * 1536) : 0);
          }
        }
      }
      TR(0, b, 2);
      wg_wait<0>(); pin(SA); pin(SB);
      mbar_arrive_elect(bar + B_KFREE * 8);
      TR(0, b, 3);
      TR(0, b - 1, 10);
      uint32_t P[28];
      float sx[8];
      if (v2) {
        if (v1) softmax_tile<6, 7>(SA, SB, T, b0, b1, P, sx, nbV, zero, qa, q); else softmax_tile<4, 5>(SA, SB, T, b0, b1, P, sx, nbV, zero, qa, q);
      } else if (!v4) {
        if (v1) softmax_tile<2, 3>(SA, SB, T, b0, b1, P, sx, nbV, zero, qa, q); else softmax_tile<0, 1>(SA, SB, T, b0, b1, P, sx, nbV, zero, qa, q);
      } else {
        if (v1) softmax_tile<4, 4>(SA, SB, T, b0, b1, P, sx, nbV, zero, qa, q); else softmax_tile<3, 3>(SA, SB, T, b0, b1, P, sx, nbV, zero, qa, q);
      }
      float O[24];
      TR(0, b, 4);
      wg_fence();
      wg_sp48<0>(O, P[0], P[1], P[2], P[3], dV[0], meta);
#pragma unroll
      for (int s = 1; s < 7; s++) wg_sp48<1>(O, P[4 * s], P[4 * s + 1], P[4 * s + 2], P[4 * s + 3], dV[s], meta);
      wg_commit();
      nb_arrive(N_PVISS, 384);
      TR(0, b, 6);
      mbar_wait(fb, fp);
      wg_wait<0>(); pin(O);
      mbar_arrive_elect(bar + B_VFREE * 8);
      TR(0, b, 7);
      float ru, rl;
      asm("rcp.approx.ftz.f32 %0, %1;" : "=f"(ru) : "f"(((fmaf(O[0], 0.f, sx[0]) + sx[1]) + sx[2]) + sx[3]));
      asm("rcp.approx.ftz.f32 %0, %1;" : "=f"(rl) : "f"(((fmaf(O[2], 0.f, sx[4]) + sx[5]) + sx[6]) + sx[7]));
#pragma unroll
      for (int i = 0; i < 3; i++)
        stsm4(oa + i * 256, pack2(O[8 * i] * ru, O[8 * i + 1] * ru), pack2(O[8 * i + 2] * rl, O[8 * i + 3] * rl),
              pack2(O[8 * i + 4] * ru, O[8 * i + 5] * ru), pack2(O[8 * i + 6] * rl, O[8 * i + 7] * rl));
      publish(ob);
      fp ^= 1;
      meta ^= 0x55555555u;
      TR(0, b, 8);
    }
    asm volatile("{\n.reg .pred p, q;\nsetp.ne.b32 q, %1, 0;\nelect.sync _|p, 0xffffffff;\nand.pred q, q, p;\n"
                 "@q cp.async.bulk.shared::cluster.shared::cta.mbarrier::complete_tx::bytes [%1], [%0], 1536, [%2];\n"
                 "@p cp.async.bulk.shared::cluster.shared::cta.mbarrier::complete_tx::bytes [%3], [%0], 1536, [%4];\n}"
                 ::"r"(src13), "r"(snd[0]), "r"(snd[1]), "r"(snd[2]), "r"(snd[3]) : "memory");
    if (jw == 0) nb_arrive(3, 256);
    TRDUMP;
    cluster_sync();
  } else if (warp < 12) {
    TRDECL;
    TR(2, -3, 0);
    asm volatile("setmaxnreg.inc.sync.aligned.u32 %0;" ::"n"(RG));
    TR(2, -3, 1);
    GemmCtx c;
    c.bar = bar;
    const int gw = warp - 8, tk = gw * 16 + (lane & 15), hi = lane >> 4;
    { const int col = tk >> 2, i = tk & 3;
      c.kC = sb + SM_K + (col + 3) * KS + hi * 128 + i * 16;
      c.vC[0] = sb + SM_V + (col + 3) * 1536 + hi * 128 + (2 * i + ((col + 3) & 1)) * 16;
      c.qC[0] = sb + SM_Q + col * 768 + hi * 128 + (col & 1) * 64 + i * 16; }
    { const int kc = gw - 1 + 19 * odd, i = lane & 7; c.hvalid = gw > 0; c.edge = gw == (odd ? 0 : 3);
      c.kH = sb + SM_K + kc * KS + (lane >> 3) * 128 + i * 16;
      c.vH[0] = sb + SM_V + kc * 1536 + (lane >> 3) * 128 + (i >> 2) * 768 + (2 * (i & 3) + ((kc ^ (i >> 2)) & 1)) * 16; }
    Stage xs[3];
#pragma unroll
    for (int i = 0; i < 3; i++) {
      const int p = (i + 1) % 3;
      xs[i].lo = (uint32_t)mkdesc(SBC + SM_X + p * 24576, 16, 0, 0); xs[i].full = bar + (B_FULL + p) * 8;
      xs[i].em = opq(mapa(bar + (B_EMPTY + p) * 8, base + p)); xs[i].par = 0;
    }
    c.never = x == nullptr;
    c.kC = opq(c.kC); c.kH = opq(c.kH);
    c.vC[1] = opq(c.vC[0] ^ 16); c.vC[0] = opq(c.vC[0]);
    c.vH[1] = opq(c.vH[0] ^ 16); c.vH[0] = opq(c.vH[0]);
    c.qC[1] = opq(c.qC[0] ^ 64); c.qC[0] = opq(c.qC[0]);
    c.spin = 0;
    c.hiA = (uint32_t)(mkdesc(0, 0, 1024, 1) >> 32) + (blockIdx.x >> 16); c.hiB = (uint32_t)(mkdesc(0, 0, 256, 3) >> 32) + (blockIdx.x >> 16);
    asm volatile("barrier.cluster.wait.aligned;" ::: "memory");
    TR(2, -3, 2);
#pragma unroll
    for (int i = 0; i < 2 * NL; i++) sts128(wdst + (i & 1) * 3072 + (i / 2) * 18432, wv[i]);
    fence_async();
    TR(2, -3, 3);
    asm volatile("bar.sync 1, 384;" ::: "memory");
    TR(2, -3, 4);
    mbar_wait(bar + B_WK * 8, 0);
    TR(2, -3, 5);
    uint32_t pk[12], pv[12], pq[12], hk1[6], hv1[6];
    gemm_iter<true, 0>(c, -2, pk, pv, pq, hk1, hv1, xs[0], xs[1], xs[2] TRPASS);
    TR2(blockIdx.x, 4);
    c.hiA = opq(c.hiA); c.hiB = opq(c.hiB);
#pragma unroll 1
    for (int b = -1;; b += 2) {
      gemm_iter<false, 1>(c, b, pk, pv, pq, hk1, hv1, xs[2], xs[0], xs[1] TRPASS);
      if (b == 11) break;
      gemm_iter<false, 0>(c, b + 1, pk, pv, pq, hk1, hv1, xs[2], xs[0], xs[1] TRPASS);
      const Stage t = xs[2]; xs[2] = xs[1]; xs[1] = xs[0]; xs[0] = t;
    }
    TR2(blockIdx.x, 6);
    c.hiA = opq(c.hiA); c.hiB = opq(c.hiB);
    const uint32_t st = sb + gw * 3072;
    const uint32_t sta = st + (lane & 15) * 64 + ((hi ^ ((lane >> 1) & 3)) * 16);
    const int oc = ph * 112 + strip * 16 + 8 * (gw >> 1) + 4 * (head >> 1) + 2 * (gw & 1), och = pw * 6 + (head & 1) * 3;
    float D0[48], D1[48];
    mbar_arrive_elect(bar + B_WOFREE * 8);
    dump12<128>(c.qC[1], pq);
    nb_sync(N_QK1, 256);
    issue_halo<0, 8>(c, xs[2], D1);
    fence_async();
    nb_arrive(N_VQ0, 288); nb_arrive(N_VQ1, 288); nb_arrive(N_PVISS, 384);
    issue_halo<8, 12>(c, xs[2], D1);
    gwait<0>(c, B_KFREE);
    dump12<128>(c.kC, pk);
    if (c.edge) publish(bar + B_XK * 8);
    wg_wait<0>(); pin(D1);
    pack6(hk1, D1, 0);
    if (c.hvalid) dump6(c.kH, hk1);
    tail_free(bar + (B_TFREE + 1) * 8);
    pack6(hv1, D1, 24);
    fence_async();
    nb_arrive(N_KRDY, 256);
    gwait<0>(c, B_VFREE);
    dump12<128>(c.vC[0], pv);
    if (c.hvalid) dump6(c.vH[0], hv1);
    fence_async();
    edge_ready(c, B_XV);
    nb_arrive(N_VQ0, 288); nb_arrive(N_VQ1, 288);
    gwait<0>(c, B_WO);
    gwait<0>(c, B_TIN);
    TR(2, 13, 0);
    nb_sync(N_QK1, 256);
    issue_proj<SM_TIN0>(D0);
    wg_wait<0>(); pin(D0);
    TR(2, 13, 1);
    store_proj(D0, &mp.ot, st + SM_TST, sta + SM_TST, 8 * TB, oc, och);
    gwait<0>(c, B_TIN + 1);
    TR(2, 13, 2);
    nb_sync(N_PVISS, 384);
    nb_sync(3, 256);
    issue_proj<SM_TIN1>(D1);
    wg_wait<0>(); pin(D1);
    TR(2, 13, 3);
    store_proj(D1, &mp.ot, st + SM_TIN0, sta + SM_TIN0, 8 * TB + 8, oc, och);
    TR(2, 13, 4);
    gwait<0>(c, B_TIN + 2);
    TR(2, 13, 5);
    issue_proj_half<0>(D0, head & 1);
    gwait<0>(c, B_TIN + 3);
    TR(2, 13, 6);
    issue_proj_half<1>(D0, ~head & 1);
    asm volatile("barrier.cluster.arrive.relaxed.aligned;" ::: "memory");
    wg_wait<0>(); pin(D0);
    store_proj(D0, &mp.ot, st + SM_TIN0 + 12288, sta + SM_TIN0 + 12288, 8 * TB + 16, oc, och);
    TR(2, 13, 7);
    if (lane == 0) asm volatile("cp.async.bulk.wait_group.read 0;" ::: "memory");
    __syncwarp();
    TR(2, 13, 8);
    TR2(blockIdx.x, 2);
    TRDUMP;
    asm volatile("barrier.cluster.wait.aligned;" ::: "memory");
  } else {
    asm volatile("setmaxnreg.dec.sync.aligned.u32 24;");
    if (warp == 15) {
      const int l = min(lane, 24), row = head + (l < 16 ? 0 : 4 * ((l - 16) / 3)), col = strip * 16 + (l < 16 ? l : (l - 16) % 3 + (odd ? 16 : (strip ? -3 : 0)));
      const uint8_t* p = reinterpret_cast<const uint8_t*>(x) + (uint32_t)(row * ROWB + (ph * 112 + col) * 768 + pw * 384);
#pragma unroll
      for (int i = 0; i < 3; i++) asm volatile("prefetch.global.L2 [%0];" ::"l"(p + i * 128));
    } else if (elect_one()) {
      if (warp == 12) {
        mbar_init(bar + B_WK * 8, 1);
#pragma unroll
        for (int i = 0; i < NL; i++) load_w(&mp.w, sb + SM_W + (3 * i + 5 - 2 * va) * 6144, bar + B_WK * 8, (i + 1) * 192 + head * 48 + 32 - 32 * va);
        asm volatile("prefetch.tensormap [%0];" ::"l"(head == 1 ? &mp.xh : &mp.xc) : "memory");
      } else if (warp == 13) {
#pragma unroll
        for (int i = 0; i < B_XK; i++) if (i != B_WK) mbar_init(bar + i * 8, (i >= B_EMPTY && i < B_TIN) || (i >= B_TFREE && i < B_WK) ? 16 : (i == B_TIN + 2 ? 5 : 1));
      } else {
#pragma unroll
        for (int i = B_XK; i < B_COUNT; i++) mbar_init(bar + i * 8, i < B_Q0 ? 2 : (i < B_ODONE ? 4 : (i == B_VFREE ? 9 : 8)));
      }
      asm volatile("fence.mbarrier_init.release.cluster;" ::: "memory");
    }
    __syncwarp();
    asm volatile("barrier.cluster.arrive.relaxed.aligned;" ::: "memory");
    asm volatile("griddepcontrol.launch_dependents;");
    if (warp != 12) asm volatile("barrier.cluster.wait.aligned;" ::: "memory");
    else {
      const int cc = ph * 112 + strip * 16, ch = cc + (odd ? 16 : (strip ? -3 : 0)), rh = strip ? -4 : 112;
      const uint32_t fb = opq(bar + (B_FULL + head) * 8), dst0 = sb + SM_X + head * 24576, c3 = opq((uint32_t)(pw * 3)), mask = opq(15u << base);
      int t = head == 0 ? 2 : head - 1;
      uint64_t mx = opq((uint64_t)(t ? &mp.xc : &mp.xh));
      uint32_t row = opq((uint32_t)(t ? 4 * t - 4 : rh)), col = opq((uint32_t)(t ? cc : ch)), dst = opq(dst0 + (t ? 0 : 2048));
#pragma unroll 1
      for (int n = 0;; n++) {
        if (n) mbar_wait(fb + (B_EMPTY - B_FULL) * 8, ~n & 1);
        else asm volatile("barrier.cluster.wait.aligned;" ::: "memory");
        if (head < 3) {
          asm volatile("{\n.reg .pred p;\n.reg .b16 m;\nelect.sync _|p, 0xffffffff;\ncvt.u16.u32 m, %7;\n"
                       "@p cp.async.bulk.tensor.4d.shared::cluster.global.mbarrier::complete_tx::bytes.multicast::cluster [%0], [%1, {%3,%4,%5,%6}], [%2], m;\n}"
                       ::"r"(dst), "l"(mx), "r"(fb), "r"(0), "r"(row), "r"(col), "r"(c3), "r"(mask) : "memory");
          if (lane < 4) remote_expect(mapa(fb, base + lane), dst == dst0 ? 24576 : 18432);
          __syncwarp();
        }
        if (n == 0 && elect_one()) {
#pragma unroll
          for (int i = 0; i < 3; i++) load_w(&mp.w, sb + SM_W + i * 6144, bar + B_WQ * 8, head * 48 + i * 16);
          mbar_expect(bar + B_WQ * 8, 18432);
        }
        __syncwarp();
        if (head == 3 || n == 11) break;
        t += 3;
        const int hn = t / 5;
        const bool core = t != 5 * hn;
        mx = opq((uint64_t)(core ? &mp.xc : &mp.xh));
        row = opq((uint32_t)(core ? 4 * (t - hn - 1) : rh + 16 * hn)); col = opq((uint32_t)(core ? cc : ch)); dst = opq(dst0 + (core ? 0 : 2048));
        if (elect_one()) asm volatile("cp.async.bulk.prefetch.tensor.4d.L2.global [%0, {%1,%2,%3,%4}];" ::"l"(mx), "r"(0), "r"(row), "r"(col), "r"(c3) : "memory");
        __syncwarp();
      }
      mbar_wait(bar + B_WOFREE * 8, 0);
      if (elect_one()) {
        mbar_expect(bar + B_WO * 8, 36864);
        asm volatile("cp.async.bulk.tensor.3d.shared::cluster.global.mbarrier::complete_tx::bytes [%0], [%1, {%3,%4,%5}], [%2];"
                     ::"r"(sb + SM_TWO), "l"(&mp.wo), "r"(bar + B_WO * 8), "r"(0), "r"(0), "r"((head & 1) * 3) : "memory");
      }
      __syncwarp();
    }
    if (warp & 1) {
      const uint32_t partner = (blockIdx.x & 7) ^ 4;
      const int cs = odd ? 3 : (strip == 6 ? 15 : 16), cd = odd || strip == 6 ? 19 : 0;
      const uint32_t rb = opq(mapa(bar, partner));
      TRDECL;
      if (warp == 13) {
        const uint32_t dst = opq(mapa(sb + SM_V + cd * 1536, partner)), src = opq(sb + SM_V + cs * 1536);
#pragma unroll 1
        for (int b = 0;; b++) {
          const uint32_t pa = b & 1;
          nb_arrive(N_VQ0, 288);
          mbar_wait(bar + B_XV * 8, pa);
          TR(1, b, 0);
          if (elect_one()) { copy_remote(dst, src, 4608, rb + B_VIMP * 8); remote_expect(rb + B_VIMP * 8, 4608); }
          __syncwarp();
          TR(1, b, 1);
          mbar_wait(bar + B_VIMP * 8, pa);
          TR(1, b, 2);
          nb_arrive(N_VQ1, 288);
          if (elect_one()) remote_arrive(rb + B_VFREE * 8);
          __syncwarp();
          TR(1, b, 3);
          if (b == 13) break;
          mbar_wait(bar + B_VFREE * 8, pa);
          if (elect_one()) remote_arrive(rb + B_XV * 8);
          __syncwarp();
        }
      } else {
        const uint32_t dst = opq(mapa(sb + SM_K + cd * KS, partner)), src = opq(sb + SM_K + cs * KS);
#pragma unroll 1
        for (int b = 0;; b++) {
          const uint32_t pa = b & 1, so = (pa ^ 1) * KSLOT;
          mbar_wait(bar + B_XK * 8, pa);
          TR(1, b - 1, 4);
          if (elect_one()) {
            copy_remote(dst + so, src + so, 3 * KS, rb + B_KIMP * 8);
            if (b == 0) copy_remote(dst, src, 3 * KS, rb + B_KIMP * 8);
            remote_expect(rb + B_KIMP * 8, b ? 3 * KS : 6 * KS);
          }
          __syncwarp();
          TR(1, b - 1, 5);
          TR(1, b - 1, 7);
          if (b == 13) break;
          mbar_wait(bar + B_KFREE * 8, pa);
          if (elect_one()) remote_arrive(rb + B_XK * 8);
          __syncwarp();
        }
      }
      TRDUMP;
    }
    if (warp == 14) {
      int* flag = g_flags + (par * 7 + strip) * 2 * FS;
      if (elect_one()) {
        mbar_expect(bar + B_WK * 8, NL * 6144);
        mbar_arrive(bar + B_XK * 8); mbar_arrive(bar + B_XV * 8);
        mbar_expect(bar + B_TIN * 8, 24576); mbar_expect(bar + (B_TIN + 1) * 8, 24576); mbar_expect(bar + (B_TIN + 2) * 8, 6144); mbar_expect(bar + (B_TIN + 3) * 8, 12288);
      }
      __syncwarp();
#pragma unroll 1
      for (int b = 0; b < TB; b++) {
        mbar_wait(bar + B_ODONE * 8, b & 1);
        if (lane == 0) {
#pragma unroll 1
          for (int i = 0; i < 16; i += OCH) {
            asm volatile("cp.async.bulk.tensor.3d.global.shared::cta.bulk_group [%0, {%2,%3,%4}], [%1];"
                         ::"l"(&mp.os), "r"(sb + SM_O + i * 768), "r"(pw * 192), "r"(8 * b + 2 * head), "r"(ph * 112 + strip * 16 + i) : "memory");
            asm volatile("cp.async.bulk.commit_group;\ncp.async.bulk.wait_group 0;" ::: "memory");
          }
        }
        __syncwarp();
        mbar_arrive_elect(bar + B_OFREE * 8);
        if (lane == 0)
          asm volatile("fence.proxy.async.global;\nfence.acq_rel.gpu;\nred.relaxed.gpu.global.add.s32 [%0], 1;\nred.relaxed.gpu.global.add.s32 [%1], 1;"
                       ::"l"(flag + b * 56 * FS), "l"(flag + (b * 56 + 1) * FS) : "memory");
        __syncwarp();
      }
#pragma unroll 1
      for (int t = 0; t < 4; t++) {
        const int i = t >> 1, jw = t & 1, j = jw ^ odd;
        if (!jw) mbar_wait(bar + (B_TFREE + i) * 8, 0);
        mbar_wait(bar + (B_OTAIL + t) * 8, 0);
        if (elect_one()) {
#pragma unroll 1
          for (int d = 0; d < 8; d++) {
            const int dst = (d + head) & 3, pc = d >> 2;
            send_o<1536>(sb + (i ? SM_TIN1 : SM_TIN0) + head * 6144 + j * 3072 + pc * 1536,
                         sb + (i ? SM_Q : SM_O) + (4 * j + (dst & 2) + pc) * 1536, bar + (B_TIN + i) * 8, base + dst);
          }
        }
        __syncwarp();
      }
    }
    cluster_sync();
  }
}

constexpr int NSTB = 6;
constexpr int NTB = TB * 56;
constexpr int SM_B_ST = 0;
constexpr int SM_B_IN = 73728;
constexpr int SM_B_W = SM_B_IN + 3 * 24576;
constexpr int SM_B_BAR = SM_B_IN + NSTB * 24576;
constexpr int SM_B_TOTAL = SM_B_BAR + 512;
struct MapsB { CUtensorMap oi, oo, wo; };

__global__ void __launch_bounds__(512, 1)
na_proj_kernel(const __grid_constant__ MapsB mp) {
  extern __shared__ __align__(1024) uint8_t smem_raw[];
  const uint32_t sb = smem_u32(smem_raw);
  if ((sb & 0x3FFFF) != SBC) return;
  const uint32_t bar = sb + SM_B_BAR;
  const int tid = threadIdx.x, lane = tid & 31;
  const int warp = __shfl_sync(0xffffffffu, tid >> 5, 0);
  TR2(132 + blockIdx.x, 0);
  TRB(47, 0);
  if (warp == 12 && elect_one()) {
#pragma unroll
    for (int i = 0; i <= 2 * NSTB; i++) mbar_init(bar + i * 8, i < NSTB || i == 2 * NSTB ? 1 : 12);
    asm volatile("st.shared.u32 [%0], 0;" ::"r"(bar + 120) : "memory");
    mbar_expect(bar + 2 * NSTB * 8, 73728);
#pragma unroll
    for (int i = 0; i < 2; i++)
      asm volatile("cp.async.bulk.tensor.3d.shared::cluster.global.mbarrier::complete_tx::bytes [%0], [%1, {%3,%4,%5}], [%2];"
                   ::"r"(sb + SM_B_W + i * 36864), "l"(&mp.wo), "r"(bar + 2 * NSTB * 8), "r"(0), "r"(0), "r"(i * 3) : "memory");
  }
  __syncthreads();
  const int step = gridDim.x;
  if (warp == 15) {
    int so = 0;
    nb_arrive(4, 288); nb_arrive(5, 288); nb_arrive(6, 288);
#pragma unroll 1
    for (int n = blockIdx.x, tk = 0; n < NTB; n += step, tk++) {
      uint32_t cc = 0;
#pragma unroll
      for (int wg = 0; wg < 3; wg++) {
        if (lane == 0) asm volatile("cp.async.bulk.wait_group.read 5;" ::: "memory");
        nb_sync(1 + wg, 160);
        if (wg == 0 || n + step < NTB) nb_arrive(4 + wg, 288);
        if (wg == 0) asm volatile("ld.shared.u32 %0, [%1];" : "=r"(cc) : "r"(bar + 128 + tk * 4) : "memory");
        if (lane == 0) {
          asm volatile("cp.async.bulk.tensor.4d.global.shared::cta.bulk_group [%0, {%2,%3,%4,%5}], [%1];"
                       ::"l"(&mp.oo), "r"(sb + SM_B_ST + wg * 8192 + so), "r"(0), "r"((cc >> 8) & 255), "r"(cc >> 16), "r"((cc & 1) * 3 + wg) : "memory");
          asm volatile("cp.async.bulk.commit_group;" ::: "memory");
        }
        __syncwarp();
      }
      so = so == 49152 ? 0 : so + 24576;
    }
    if (lane == 0) asm volatile("cp.async.bulk.wait_group.read 0;" ::: "memory");
  } else if (warp >= 12) {
    nb_sync(7, 480);
#pragma unroll 1
    for (int n = blockIdx.x + (warp - 12) * step; n < NTB; n += 3 * step) {
      const int b = n / 56, rem = n - b * 56, par = rem / 14;
      const int c0 = opq((uint32_t)(par & 1)), c1 = opq((uint32_t)(8 * b)), c2 = opq((uint32_t)((par >> 1) * 112 + (rem - par * 14) * 8));
      int v; uint32_t spin = 0, tk = 0;
      do { asm volatile("ld.acquire.gpu.global.s32 %0, [%1];" : "=r"(v) : "l"(g_flags + n * FS) : "memory"); } while (v < 4 && ++spin < SPIN_LIMIT);
      if (lane == 0) asm volatile("atom.shared.add.u32 %0, [%1], 1;" : "=r"(tk) : "r"(bar + 120) : "memory");
      asm volatile("fence.proxy.async.global;" ::: "memory");
      tk = __shfl_sync(0xffffffffu, tk, 0);
      TRB(tk, 0);
      const uint32_t use = tk / NSTB, sg = tk - use * NSTB;
      if (use) mbar_wait(bar + (NSTB + sg) * 8, (use - 1) & 1);
      TRB(tk, 1);
      if (elect_one()) {
        asm volatile("st.shared.u32 [%0], %1;" ::"r"(bar + 128 + tk * 4), "r"(c0 | c1 << 8 | c2 << 16) : "memory");
        mbar_expect(bar + sg * 8, 24576);
        asm volatile("cp.async.bulk.tensor.3d.shared::cluster.global.mbarrier::complete_tx::bytes [%0], [%1, {%3,%4,%5}], [%2];"
                     ::"r"(sb + SM_B_IN + sg * 24576), "l"(&mp.oi), "r"(bar + sg * 8), "r"(c0 * 192), "r"(c1), "r"(c2) : "memory");
        g_flags[n * FS] = 0;
      }
      __syncwarp();
    }
  } else {
    const int wg = warp >> 2, w = warp & 3;
    uint32_t a[48];
    mbar_wait(bar + 2 * NSTB * 8, 0);
    {
      const int k = (lane & 7) + (lane >> 4) * 8, ch = (warp & 1) * 2 + ((lane >> 3) & 1);
      const uint32_t wa = sb + SM_B_W + (warp >> 1) * 12288 + k * 64 + ((ch ^ ((k >> 1) & 3)) * 16);
#pragma unroll
      for (int i = 0; i < 12; i++)
        asm volatile("ldmatrix.sync.aligned.m8n8.x4.trans.shared.b16 {%0,%1,%2,%3}, [%4];"
                     : "=r"(a[4 * i]), "=r"(a[4 * i + 1]), "=r"(a[4 * i + 2]), "=r"(a[4 * i + 3]) : "r"(wa + i * 1024) : "memory");
    }
    nb_sync(7, 480);
    TRB(47, 1);
    const uint32_t sta = opq(sb + SM_B_ST + wg * 8192 + ((lane & 7) + (lane >> 4) * 8) * 128 + (((2 * w + ((lane >> 3) & 1)) ^ (lane & 7)) * 16));
    const uint32_t hi = opq((uint32_t)(mkdesc(0, 0, 3072, 0) >> 32) + (blockIdx.x >> 16)), bb = opq(bar);
    const uint32_t nbT = opq((uint32_t)(4 + wg)), nbN = opq((uint32_t)(wg == 2 ? 4 : 5 + wg)), nbD = opq((uint32_t)(1 + wg));
    int left = (NTB - blockIdx.x + step - 1) / step;
    if (wg == 2) nb_arrive(4, 288);
#pragma unroll 1
    for (uint32_t ph = 0;; ph ^= 1) {
#pragma unroll
      for (int sg = 0; sg < NSTB; sg++) {
        constexpr uint64_t db = mkdesc(SBC + SM_B_IN, 128, 3072, 0);
        float D[32];
        mbar_wait(bb + sg * 8, ph);
        nb_sync(nbT, 288);
        wg_fence();
        wg_rs64<0>(D, a[0], a[1], a[2], a[3], dsc(db + sg * 1536, hi));
#pragma unroll
        for (int k = 1; k < 12; k++) wg_rs64<1>(D, a[4 * k], a[4 * k + 1], a[4 * k + 2], a[4 * k + 3], dsc(db + sg * 1536 + k * 16, hi));
        wg_commit();
        nb_arrive(nbN, 288);
        wg_wait<0>(); pin(D);
        mbar_arrive_elect(bb + (NSTB + sg) * 8);
#pragma unroll
        for (int q = 0; q < 4; q++)
          asm volatile("stmatrix.sync.aligned.m8n8.x4.trans.shared.b16 [%0], {%1,%2,%3,%4};" ::"r"(sta + (sg % 3) * 24576 + q * 2048),
                       "r"(pack2(D[8 * q], D[8 * q + 1])), "r"(pack2(D[8 * q + 2], D[8 * q + 3])), "r"(pack2(D[8 * q + 4], D[8 * q + 5])), "r"(pack2(D[8 * q + 6], D[8 * q + 7])) : "memory");
        fence_async();
        nb_arrive(nbD, 160);
        if (wg == 0) TRB(31 - left, 5);
        if (--left == 0) goto done;
      }
    }
  done:
    if (wg == 0) nb_arrive(4, 288);
    TR2(132 + blockIdx.x, 2);
  }
}

typedef CUresult (*EncodeFn)(CUtensorMap*, CUtensorMapDataType, cuuint32_t, void*, const cuuint64_t*, const cuuint64_t*, const cuuint32_t*,
                             const cuuint32_t*, CUtensorMapInterleave, CUtensorMapSwizzle, CUtensorMapL2promotion, CUtensorMapFloatOOBfill);
static EncodeFn g_enc = nullptr;
static void make_map(CUtensorMap* m, const void* p, int rank, const cuuint64_t* dim, const cuuint64_t* str, const cuuint32_t* box, CUtensorMapSwizzle sw) {
  const cuuint32_t ones[5] = {1, 1, 1, 1, 1};
  g_enc(m, CU_TENSOR_MAP_DATA_TYPE_BFLOAT16, rank, (void*)p, dim, str, box, ones, CU_TENSOR_MAP_INTERLEAVE_NONE, sw,
        CU_TENSOR_MAP_L2_PROMOTION_L2_128B, CU_TENSOR_MAP_FLOAT_OOB_FILL_NONE);
}

extern "C" void kernel_launch(void* const* d_in, const int* in_sizes, int n_in, void* d_out, int out_size) {
  const __nv_bfloat16* x = (const __nv_bfloat16*)d_in[0];
  const __nv_bfloat16* wqkv = (const __nv_bfloat16*)d_in[1];
  const __nv_bfloat16* wo = (const __nv_bfloat16*)d_in[2];
  const __nv_bfloat16* rpb = (const __nv_bfloat16*)d_in[3];

  if (!g_enc) {
    void* fn = nullptr; cudaDriverEntryPointQueryResult qr;
    cudaGetDriverEntryPoint("cuTensorMapEncodeTiled", &fn, cudaEnableDefault, &qr);
    g_enc = (EncodeFn)fn;
    cudaFuncSetAttribute(na_attn_kernel, cudaFuncAttributeMaxDynamicSharedMemorySize, SM_A_TOTAL);
    cudaFuncSetAttribute(na_proj_kernel, cudaFuncAttributeMaxDynamicSharedMemorySize, SM_B_TOTAL);
  }
  Maps ma; MapsB mb;
  { cuuint64_t dim[4] = {64, 112, 224, 6}, str[3] = {(cuuint64_t)ROWB, 768, 128};
    cuuint32_t box[4] = {64, 4, 16, 3}, boxh[4] = {64, 16, 3, 3}, boxo[4] = {64, 8, 8, 1};
    make_map(&ma.xc, x, 4, dim, str, box, CU_TENSOR_MAP_SWIZZLE_128B);
    make_map(&ma.xh, x, 4, dim, str, boxh, CU_TENSOR_MAP_SWIZZLE_128B);
    make_map(&mb.oo, d_out, 4, dim, str, boxo, CU_TENSOR_MAP_SWIZZLE_128B); }
  { cuuint64_t dim[3] = {384, 112, 224}, str[2] = {(cuuint64_t)ROWB, 768};
    cuuint32_t box[3] = {192, 8, 8}, boxs[3] = {192, 2, OCH};
    make_map(&mb.oi, d_out, 3, dim, str, box, CU_TENSOR_MAP_SWIZZLE_NONE);
    make_map(&ma.os, d_out, 3, dim, str, boxs, CU_TENSOR_MAP_SWIZZLE_NONE); }
  { cuuint64_t dim[4] = {32, 112, 224, 12}, str[3] = {(cuuint64_t)ROWB, 768, 64};
    cuuint32_t box[4] = {32, 8, 2, 3};
    make_map(&ma.ot, d_out, 4, dim, str, box, CU_TENSOR_MAP_SWIZZLE_64B); }
  { cuuint64_t dim[2] = {576, 192}, str[1] = {1152};
    cuuint32_t box[2] = {16, 192};
    make_map(&ma.w, wqkv, 2, dim, str, box, CU_TENSOR_MAP_SWIZZLE_32B); }
  { cuuint64_t dim[3] = {32, 192, 6}, str[2] = {384, 64};
    cuuint32_t box[3] = {32, 192, 3};
    make_map(&ma.wo, wo, 3, dim, str, box, CU_TENSOR_MAP_SWIZZLE_64B);
    mb.wo = ma.wo; }
  na_attn_kernel<<<112, 512, SM_A_TOTAL>>>(x, wqkv, rpb, ma);
  cudaLaunchConfig_t cfg = {};
  cfg.gridDim = dim3(20); cfg.blockDim = dim3(512); cfg.dynamicSmemBytes = SM_B_TOTAL; cfg.stream = cudaStreamPerThread;
  cudaLaunchAttribute at[1];
  at[0].id = cudaLaunchAttributeProgrammaticStreamSerialization; at[0].val.programmaticStreamSerializationAllowed = 1;
  cfg.attrs = at; cfg.numAttrs = 1;
  cudaLaunchKernelEx(&cfg, na_proj_kernel, mb);
}
```

```cpp
#include <cuda_runtime.h>
#include <cuda_bf16.h>
#include <cuda.h>
#include <stdint.h>

#define SPIN_LIMIT (1u << 18)

__device__ __forceinline__ uint32_t smem_u32(const void* p) { return (uint32_t)__cvta_generic_to_shared(p); }
__device__ __forceinline__ void wg_fence() { asm volatile("wgmma.fence.sync.aligned;" ::: "memory"); }
__device__ __forceinline__ void wg_commit() { asm volatile("wgmma.commit_group.sync.aligned;" ::: "memory"); }
template <int N> __device__ __forceinline__ void wg_wait() { asm volatile("wgmma.wait_group.sync.aligned %0;" ::"n"(N) : "memory"); }
template <int N> __device__ __forceinline__ void pin(float (&d)[N]) {
#pragma unroll
  for (int i = 0; i < N; i++) asm volatile("" : "+f"(d[i])::"memory");
}
__host__ __device__ constexpr uint64_t mkdesc(uint32_t addr, uint32_t lbo, uint32_t sbo, uint32_t sw) {
  return (uint64_t)((addr & 0x3FFFF) >> 4) | ((uint64_t)(lbo >> 4) << 16) | ((uint64_t)(sbo >> 4) << 32) | ((uint64_t)sw << 62);
}
__device__ __forceinline__ void mbar_init(uint32_t bar, uint32_t cnt) { asm volatile("mbarrier.init.shared::cta.b64 [%0], %1;" ::"r"(bar), "r"(cnt) : "memory"); }
__device__ __forceinline__ void mbar_arrive(uint32_t bar) { asm volatile("mbarrier.arrive.shared::cta.b64 _, [%0];" ::"r"(bar) : "memory"); }
__device__ __forceinline__ bool elect_one() {
  uint32_t r; asm volatile("{\n.reg .pred p;\nelect.sync _|p, 0xffffffff;\nselp.u32 %0, 1, 0, p;\n}" : "=r"(r)); return r;
}
__device__ __forceinline__ void mbar_arrive_elect(uint32_t bar) {
  asm volatile("{\n.reg .pred p;\nelect.sync _|p, 0xffffffff;\n@p mbarrier.arrive.shared::cta.b64 _, [%0];\n}" ::"r"(bar) : "memory");
}
__device__ __forceinline__ void mbar_expect(uint32_t bar, uint32_t bytes) { asm volatile("mbarrier.arrive.expect_tx.shared::cta.b64 _, [%0], %1;" ::"r"(bar), "r"(bytes) : "memory"); }
__device__ __forceinline__ void mbar_arrive_remote(uint32_t bar, uint32_t cta) {
  asm volatile("{\n.reg .b32 ra;\nmapa.shared::cluster.u32 ra, %0, %1;\nmbarrier.arrive.relaxed.cluster.shared::cluster.b64 _, [ra];\n}" ::"r"(bar), "r"(cta) : "memory");
}
__device__ __forceinline__ void mbar_wait(uint32_t bar, uint32_t parity) {
  asm volatile("{\n.reg .pred p;\n.reg .b32 n;\nmov.b32 n, 0;\nWL:\nmbarrier.try_wait.parity.shared::cta.b64 p, [%0], %1;\n@p bra WD;\n"
               "add.u32 n, n, 1;\nsetp.lt.u32 p, n, 65536;\n@p bra WL;\nWD:\n}" ::"r"(bar), "r"(parity) : "memory");
}
__device__ __forceinline__ void nb_sync(int id, int n) { asm volatile("bar.sync %0, %1;" ::"r"(id), "r"(n) : "memory"); }
__device__ __forceinline__ void nb_arrive(int id, int n) { asm volatile("bar.arrive %0, %1;" ::"r"(id), "r"(n) : "memory"); }
__device__ __forceinline__ uint32_t opq(uint32_t x) { uint32_t r; asm volatile("mov.b32 %0, %1;" : "=r"(r) : "r"(x)); return r; }
__device__ __forceinline__ uint64_t opq(uint64_t x) { uint64_t r; asm volatile("mov.b64 %0, %1;" : "=l"(r) : "l"(x)); return r; }
__device__ __forceinline__ uint32_t mapa(uint32_t a, uint32_t cta) { uint32_t r; asm("mapa.shared::cluster.u32 %0, %1, %2;" : "=r"(r) : "r"(a), "r"(cta)); return r; }
__device__ __forceinline__ void fence_async() { asm volatile("fence.proxy.async.shared::cta;" ::: "memory"); }
__device__ __forceinline__ void cluster_sync() {
  asm volatile("barrier.cluster.arrive.relaxed.aligned;\nbarrier.cluster.wait.aligned;" ::: "memory");
}
__device__ __forceinline__ uint32_t pack2(float lo, float hi) {
  uint32_t r; asm("cvt.rn.bf16x2.f32 %0, %1, %2;" : "=r"(r) : "f"(hi), "f"(lo)); return r;
}
__device__ __forceinline__ void stsm4(uint32_t a, uint32_t r0, uint32_t r1, uint32_t r2, uint32_t r3) {
  asm volatile("stmatrix.sync.aligned.m8n8.x4.shared.b16 [%0], {%1,%2,%3,%4};" ::"r"(a), "r"(r0), "r"(r1), "r"(r2), "r"(r3) : "memory");
}
__device__ __forceinline__ void ldsm4(uint32_t a, uint32_t& r0, uint32_t& r1, uint32_t& r2, uint32_t& r3) {
  asm volatile("ldmatrix.sync.aligned.m8n8.x4.shared.b16 {%0,%1,%2,%3}, [%4];" : "=r"(r0), "=r"(r1), "=r"(r2), "=r"(r3) : "r"(a) : "memory");
}
__device__ __forceinline__ void sts128(uint32_t a, uint4 v) {
  asm volatile("st.shared.v4.b32 [%0], {%1,%2,%3,%4};" ::"r"(a), "r"(v.x), "r"(v.y), "r"(v.z), "r"(v.w) : "memory");
}
__device__ __forceinline__ float lds_f32(uint32_t a) { float v; asm volatile("ld.shared.f32 %0, [%1];" : "=f"(v) : "r"(a)); return v; }
__device__ __forceinline__ float ex2(float x) { float y; asm("ex2.approx.ftz.f32 %0, %1;" : "=f"(y) : "f"(x)); return y; }

template<int SC> __device__ __forceinline__ void wg_ss144(float (&d)[72], uint64_t da, uint64_t db) {
  asm volatile("{\n.reg .pred p;\nsetp.ne.b32 p, %74, 0;\nwgmma.mma_async.sync.aligned.m64n144k16.f32.bf16.bf16 {%0,%1,%2,%3,%4,%5,%6,%7,%8,%9,%10,%11,%12,%13,%14,%15,%16,%17,%18,%19,%20,%21,%22,%23,%24,%25,%26,%27,%28,%29,%30,%31,%32,%33,%34,%35,%36,%37,%38,%39,%40,%41,%42,%43,%44,%45,%46,%47,%48,%49,%50,%51,%52,%53,%54,%55,%56,%57,%58,%59,%60,%61,%62,%63,%64,%65,%66,%67,%68,%69,%70,%71}, %72, %73, p, 1, 1, 0, 1;\n}\n"
    : "+f"(d[0]),"+f"(d[1]),"+f"(d[2]),"+f"(d[3]),"+f"(d[4]),"+f"(d[5]),"+f"(d[6]),"+f"(d[7]),"+f"(d[8]),"+f"(d[9]),"+f"(d[10]),"+f"(d[11]),"+f"(d[12]),"+f"(d[13]),"+f"(d[14]),"+f"(d[15]),"+f"(d[16]),"+f"(d[17]),"+f"(d[18]),"+f"(d[19]),"+f"(d[20]),"+f"(d[21]),"+f"(d[22]),"+f"(d[23]),"+f"(d[24]),"+f"(d[25]),"+f"(d[26]),"+f"(d[27]),"+f"(d[28]),"+f"(d[29]),"+f"(d[30]),"+f"(d[31]),"+f"(d[32]),"+f"(d[33]),"+f"(d[34]),"+f"(d[35]),"+f"(d[36]),"+f"(d[37]),"+f"(d[38]),"+f"(d[39]),"+f"(d[40]),"+f"(d[41]),"+f"(d[42]),"+f"(d[43]),"+f"(d[44]),"+f"(d[45]),"+f"(d[46]),"+f"(d[47]),"+f"(d[48]),"+f"(d[49]),"+f"(d[50]),"+f"(d[51]),"+f"(d[52]),"+f"(d[53]),"+f"(d[54]),"+f"(d[55]),"+f"(d[56]),"+f"(d[57]),"+f"(d[58]),"+f"(d[59]),"+f"(d[60]),"+f"(d[61]),"+f"(d[62]),"+f"(d[63]),"+f"(d[64]),"+f"(d[65]),"+f"(d[66]),"+f"(d[67]),"+f"(d[68]),"+f"(d[69]),"+f"(d[70]),"+f"(d[71]) : "l"(da), "l"(db), "n"(SC));
}
template<int SC> __device__ __forceinline__ void wg_ss96(float (&d)[48], uint64_t da, uint64_t db) {
  asm volatile("{\n.reg .pred p;\nsetp.ne.b32 p, %50, 0;\nwgmma.mma_async.sync.aligned.m64n96k16.f32.bf16.bf16 {%0,%1,%2,%3,%4,%5,%6,%7,%8,%9,%10,%11,%12,%13,%14,%15,%16,%17,%18,%19,%20,%21,%22,%23,%24,%25,%26,%27,%28,%29,%30,%31,%32,%33,%34,%35,%36,%37,%38,%39,%40,%41,%42,%43,%44,%45,%46,%47}, %48, %49, p, 1, 1, 0, 1;\n}\n"
    : "+f"(d[0]),"+f"(d[1]),"+f"(d[2]),"+f"(d[3]),"+f"(d[4]),"+f"(d[5]),"+f"(d[6]),"+f"(d[7]),"+f"(d[8]),"+f"(d[9]),"+f"(d[10]),"+f"(d[11]),"+f"(d[12]),"+f"(d[13]),"+f"(d[14]),"+f"(d[15]),"+f"(d[16]),"+f"(d[17]),"+f"(d[18]),"+f"(d[19]),"+f"(d[20]),"+f"(d[21]),"+f"(d[22]),"+f"(d[23]),"+f"(d[24]),"+f"(d[25]),"+f"(d[26]),"+f"(d[27]),"+f"(d[28]),"+f"(d[29]),"+f"(d[30]),"+f"(d[31]),"+f"(d[32]),"+f"(d[33]),"+f"(d[34]),"+f"(d[35]),"+f"(d[36]),"+f"(d[37]),"+f"(d[38]),"+f"(d[39]),"+f"(d[40]),"+f"(d[41]),"+f"(d[42]),"+f"(d[43]),"+f"(d[44]),"+f"(d[45]),"+f"(d[46]),"+f"(d[47]) : "l"(da), "l"(db), "n"(SC));
}
template<int SC> __device__ __forceinline__ void wg_rs112(float (&d)[56], uint32_t a0, uint32_t a1, uint32_t a2, uint32_t a3, uint64_t db) {
  asm volatile("{\n.reg .pred p;\nsetp.ne.b32 p, %61, 0;\nwgmma.mma_async.sync.aligned.m64n112k16.f32.bf16.bf16 {%0,%1,%2,%3,%4,%5,%6,%7,%8,%9,%10,%11,%12,%13,%14,%15,%16,%17,%18,%19,%20,%21,%22,%23,%24,%25,%26,%27,%28,%29,%30,%31,%32,%33,%34,%35,%36,%37,%38,%39,%40,%41,%42,%43,%44,%45,%46,%47,%48,%49,%50,%51,%52,%53,%54,%55}, {%56,%57,%58,%59}, %60, p, 1, 1, 0;\n}\n"
    : "+f"(d[0]),"+f"(d[1]),"+f"(d[2]),"+f"(d[3]),"+f"(d[4]),"+f"(d[5]),"+f"(d[6]),"+f"(d[7]),"+f"(d[8]),"+f"(d[9]),"+f"(d[10]),"+f"(d[11]),"+f"(d[12]),"+f"(d[13]),"+f"(d[14]),"+f"(d[15]),"+f"(d[16]),"+f"(d[17]),"+f"(d[18]),"+f"(d[19]),"+f"(d[20]),"+f"(d[21]),"+f"(d[22]),"+f"(d[23]),"+f"(d[24]),"+f"(d[25]),"+f"(d[26]),"+f"(d[27]),"+f"(d[28]),"+f"(d[29]),"+f"(d[30]),"+f"(d[31]),"+f"(d[32]),"+f"(d[33]),"+f"(d[34]),"+f"(d[35]),"+f"(d[36]),"+f"(d[37]),"+f"(d[38]),"+f"(d[39]),"+f"(d[40]),"+f"(d[41]),"+f"(d[42]),"+f"(d[43]),"+f"(d[44]),"+f"(d[45]),"+f"(d[46]),"+f"(d[47]),"+f"(d[48]),"+f"(d[49]),"+f"(d[50]),"+f"(d[51]),"+f"(d[52]),"+f"(d[53]),"+f"(d[54]),"+f"(d[55]) : "r"(a0), "r"(a1), "r"(a2), "r"(a3), "l"(db), "n"(SC));
}
template<int SC> __device__ __forceinline__ void wg_sp48(float (&d)[24], uint32_t a0, uint32_t a1, uint32_t a2, uint32_t a3, uint64_t db, uint32_t meta) {
  asm volatile("{\n.reg .pred p;\nsetp.ne.b32 p, %30, 0;\nwgmma.mma_async.sp.sync.aligned.m64n48k32.f32.bf16.bf16 {%0,%1,%2,%3,%4,%5,%6,%7,%8,%9,%10,%11,%12,%13,%14,%15,%16,%17,%18,%19,%20,%21,%22,%23}, {%24,%25,%26,%27}, %28, %29, 0, p, 1, 1, 1;\n}\n"
    : "+f"(d[0]),"+f"(d[1]),"+f"(d[2]),"+f"(d[3]),"+f"(d[4]),"+f"(d[5]),"+f"(d[6]),"+f"(d[7]),"+f"(d[8]),"+f"(d[9]),"+f"(d[10]),"+f"(d[11]),"+f"(d[12]),"+f"(d[13]),"+f"(d[14]),"+f"(d[15]),"+f"(d[16]),"+f"(d[17]),"+f"(d[18]),"+f"(d[19]),"+f"(d[20]),"+f"(d[21]),"+f"(d[22]),"+f"(d[23]) : "r"(a0), "r"(a1), "r"(a2), "r"(a3), "l"(db), "r"(meta), "n"(SC));
}
template<int SC> __device__ __forceinline__ void wg_rs64(float (&d)[32], uint32_t a0, uint32_t a1, uint32_t a2, uint32_t a3, uint64_t db) {
  asm volatile("{\n.reg .pred p;\nsetp.ne.b32 p, %37, 0;\nwgmma.mma_async.sync.aligned.m64n64k16.f32.bf16.bf16 {%0,%1,%2,%3,%4,%5,%6,%7,%8,%9,%10,%11,%12,%13,%14,%15,%16,%17,%18,%19,%20,%21,%22,%23,%24,%25,%26,%27,%28,%29,%30,%31}, {%32,%33,%34,%35}, %36, p, 1, 1, 0;\n}\n"
    : "+f"(d[0]),"+f"(d[1]),"+f"(d[2]),"+f"(d[3]),"+f"(d[4]),"+f"(d[5]),"+f"(d[6]),"+f"(d[7]),"+f"(d[8]),"+f"(d[9]),"+f"(d[10]),"+f"(d[11]),"+f"(d[12]),"+f"(d[13]),"+f"(d[14]),"+f"(d[15]),"+f"(d[16]),"+f"(d[17]),"+f"(d[18]),"+f"(d[19]),"+f"(d[20]),"+f"(d[21]),"+f"(d[22]),"+f"(d[23]),"+f"(d[24]),"+f"(d[25]),"+f"(d[26]),"+f"(d[27]),"+f"(d[28]),"+f"(d[29]),"+f"(d[30]),"+f"(d[31]) : "r"(a0), "r"(a1), "r"(a2), "r"(a3), "l"(db), "n"(SC));
}

constexpr uint32_t SBC = 1024;
constexpr int ROWB = 2 * 224 * 384;
constexpr int TB = 11;
constexpr int KS = 832;
constexpr int KSLOT = 22 * KS;
constexpr int SM_X = 0;
constexpr int SM_W = SM_X + 3 * 24576;
constexpr int SM_K = SM_W + 55296;
constexpr int SM_V = SM_K + 2 * KSLOT;
constexpr int SM_Q = SM_V + 22 * 1536;
constexpr int SM_O = SM_Q + 12288;
constexpr int SM_S = SM_O + 12288;
constexpr int SM_RPB = SM_S + 6144;
constexpr int SM_BAR = SM_RPB + 768;
constexpr int SM_A_TOTAL = SM_BAR + 256;
constexpr int SM_TIN0 = SM_X + 24576, SM_TIN1 = SM_X, SM_TIN2 = SM_W + 18432;
constexpr int SM_TWO = SM_X + 2 * 24576;
constexpr int SM_TST = SM_TIN2 + 24576;
enum { B_FULL = 0, B_EMPTY = 3, B_TIN = 6, B_TFREE = 10, B_WK = 12, B_WQ, B_WO, B_KIMP, B_VIMP, B_OFREE, B_XK, B_XV,
       B_Q0, B_WOFREE, B_OTAIL, B_ODONE = B_OTAIL + 4, B_KFREE, B_VFREE, B_COUNT };
enum { N_KRDY = 4, N_QK0, N_QK1, N_VQ0, N_VQ1, N_PVISS, N_Q0 };

#define OCH 16
#define MID 6
#define SPL 4
#define RA 160
#define RG 168
#define OPT 0
constexpr int FS = 64;
__device__ int g_flags[TB * 56 * FS];

#define TR(role, it, k)
#define TRDECL
#define TRARG
#define TRPASS
#define TRDUMP
#define TRB(it, k)
#define TR2START
#define TR2FLUSH(blk)
#define TR2(blk, k)

struct Stage { uint32_t lo, full, em, par; };
struct GemmCtx {
  uint32_t bar;
  uint32_t kC, vC[2], qC[2];
  uint32_t kH, vH[2];
  uint32_t hiA, hiB;
  uint32_t spin;
  bool hvalid, never, edge;
};

template <int STRIDE> __device__ __forceinline__ void dump12(uint32_t a, const uint32_t (&r)[12]) {
#pragma unroll
  for (int j = 0; j < 3; j++) stsm4(a + j * 2 * STRIDE, r[4 * j], r[4 * j + 1], r[4 * j + 2], r[4 * j + 3]);
}
__device__ __forceinline__ void keep12(bool never, uint32_t a, const uint32_t (&r)[12]) { if (never) dump12<128>(a, r); }
template <int N> __device__ __forceinline__ void pack12(uint32_t (&r)[12], const float (&d)[N], int off) {
#pragma unroll
  for (int j = 0; j < 12; j++) r[j] = pack2(d[off + 2 * j], d[off + 2 * j + 1]);
}
__device__ __forceinline__ uint64_t dsc(uint64_t lo, uint32_t hi) { uint64_t r; asm("mov.b64 %0, {%1, %2};" : "=l"(r) : "r"((uint32_t)lo), "r"(hi)); return r; }
template <int K0, int K1> __device__ __forceinline__ void issue_core(const GemmCtx& c, const Stage& x, float (&d)[72]) {
  constexpr uint64_t db = mkdesc(SBC + SM_W, 6144, 256, 3);
  wg_fence();
  if (K0 == 0) wg_ss144<0>(d, dsc(x.lo, c.hiA), dsc(db, c.hiB));
#pragma unroll
  for (int k = K0 ? K0 : 1; k < K1; k++) wg_ss144<1>(d, dsc(x.lo + (k >> 2) * 512 + (k & 3) * 2, c.hiA), dsc(db + k * 32, c.hiB));
  wg_commit();
}
template <int K0, int K1> __device__ __forceinline__ void issue_halo(const GemmCtx& c, const Stage& x, float (&d)[48]) {
  constexpr uint64_t db = mkdesc(SBC + SM_W + 18432, 6144, 256, 3);
  wg_fence();
  if (K0 == 0) wg_ss96<0>(d, dsc(x.lo, c.hiA), dsc(db, c.hiB));
#pragma unroll
  for (int k = K0 ? K0 : 1; k < K1; k++) wg_ss96<1>(d, dsc(x.lo + (k >> 2) * 384 + (k & 3) * 2, c.hiA), dsc(db + k * 32, c.hiB));
  wg_commit();
}
__device__ __forceinline__ void release_stage(const Stage& x) {
  asm volatile("{\n.reg .pred p;\nelect.sync _|p, 0xffffffff;\n@p mbarrier.arrive.shared::cluster.b64 _, [%0];\n}" ::"r"(x.em) : "memory");
}
__device__ __forceinline__ void wait_stage(GemmCtx& c, Stage& x) {
  asm volatile("{\n.reg .pred p;\nWL:\nmbarrier.try_wait.parity.shared::cta.b64 p, [%1], %2;\n@p bra WD;\n"
               "add.u32 %0, %0, 1;\nsetp.lt.u32 p, %0, 0x100000;\n@p bra WL;\nWD:\n}" : "+r"(c.spin) : "r"(x.full), "r"(x.par) : "memory");
  x.par ^= 1;
}
__device__ __forceinline__ void edge_ready(const GemmCtx& c, int bar) { __syncwarp(); if (c.edge) mbar_arrive_elect(c.bar + bar * 8); }
__device__ __forceinline__ void dump6(uint32_t a, const uint32_t (&r)[6]) {
  stsm4(a, r[0], r[1], r[2], r[3]);
  asm volatile("stmatrix.sync.aligned.m8n8.x2.shared.b16 [%0], {%1,%2};" ::"r"(a + 512), "r"(r[4]), "r"(r[5]) : "memory");
}
__device__ __forceinline__ void pack6(uint32_t (&r)[6], const float (&d)[48], int off) {
#pragma unroll
  for (int j = 0; j < 6; j++) r[j] = pack2(d[off + 4 * j], d[off + 4 * j + 1]);
}
template <int PARITY> __device__ __forceinline__ void gwait(GemmCtx& c, int bar) {
  asm volatile("{\n.reg .pred p;\nWL:\nmbarrier.try_wait.parity.shared::cta.b64 p, [%1], %2;\n@p bra WD;\n"
               "add.u32 %0, %0, 1;\nsetp.lt.u32 p, %0, 0x100000;\n@p bra WL;\nWD:\n}" : "+r"(c.spin) : "r"(c.bar + bar * 8), "n"(PARITY) : "memory");
}
template <int BYTES> __device__ __forceinline__ void send_o(uint32_t dst, uint32_t src, uint32_t bar, int cta) {
  asm volatile("{\n.reg .b32 rd, rb;\nmapa.shared::cluster.u32 rd, %0, %3;\nmapa.shared::cluster.u32 rb, %2, %3;\n"
               "cp.async.bulk.shared::cluster.shared::cta.mbarrier::complete_tx::bytes [rd], [%1], %4, [rb];\n}"
               ::"r"(dst), "r"(src), "r"(bar), "r"(cta), "n"(BYTES) : "memory");
}
__device__ __forceinline__ void remote_arrive(uint32_t rbar) { asm volatile("mbarrier.arrive.shared::cluster.b64 _, [%0];" ::"r"(rbar) : "memory"); }
__device__ __forceinline__ void remote_expect(uint32_t rbar, uint32_t bytes) {
  asm volatile("mbarrier.arrive.expect_tx.shared::cluster.b64 _, [%0], %1;" ::"r"(rbar), "r"(bytes) : "memory");
}
__device__ __forceinline__ void copy_remote(uint32_t rdst, uint32_t src, uint32_t bytes, uint32_t rbar) {
  asm volatile("cp.async.bulk.shared::cluster.shared::cta.mbarrier::complete_tx::bytes [%0], [%1], %2, [%3];" ::"r"(rdst), "r"(src), "r"(bytes), "r"(rbar) : "memory");
}
__device__ __forceinline__ void tail_free(uint32_t bar) {
  uint32_t ln; asm volatile("mov.u32 %0, %%laneid;" : "=r"(ln));
  if (ln < 4) mbar_arrive_remote(bar, ln + (blockIdx.x & 4));
}
__device__ __forceinline__ void publish(uint32_t bar) {
  fence_async();
  __syncwarp();
  mbar_arrive_elect(bar);
}

template <bool FIRST, int PA>
__device__ __forceinline__ void gemm_iter(GemmCtx& c, int b, uint32_t (&pk)[12], uint32_t (&pv)[12], uint32_t (&pq)[12],
                                          uint32_t (&hk1)[6], uint32_t (&hv1)[6], Stage& x0, Stage& x2, Stage& x1 TRARG) {
  const uint32_t bar = c.bar;
  const bool w = !FIRST && (PA == 0 || b >= 0), never = c.never;
  constexpr uint32_t ko = PA * KSLOT;
  float C[72];
  uint32_t hk0[6], hv0[6], pv2[12];
  TR(2, b, 0);
  if (FIRST) wait_stage(c, x0);
  else dump12<128>(c.qC[1], pq);
  if (w) nb_sync(N_QK1, 256);
  TR(2, b, 2);
  if (FIRST) TR(2, b - 1, 6);
  if (PA == 0) {
    float H[48];
    issue_halo<0, 8>(c, x0, H);
    TR(2, b, 3);
    if (!FIRST) { gwait<0>(c, B_KFREE); dump12<128>(c.kC, pk); }
    issue_halo<8, 12>(c, x0, H);
    TR(2, b, 4);
    wait_stage(c, x2);
    if (FIRST) TR(2, b - 1, 7);
    if (FIRST) gwait<0>(c, B_WQ);
    if (FIRST) TR(2, b - 1, 8);
    issue_core<0, 8>(c, x2, C);
    TR(2, b, 5);
    if (!FIRST) { fence_async(); keep12(never, c.kC, pk); }
    wg_wait<1>(); pin(H);
    release_stage(x0);
    pack6(hk0, H, 0);
    if (c.hvalid) dump6(c.kH, hk0);
    pack6(hk1, H, 2); pack6(hv0, H, 24); pack6(hv1, H, 26);
  } else {
    issue_core<0, 8>(c, x2, C);
    TR(2, b, 5);
    fence_async();
    keep12(never, c.kC, pq);
    if (w) gwait<1>(c, B_KFREE);
    dump12<128>(c.kC + ko, pk);
    if (c.hvalid) dump6(c.kH + ko, hk1);
  }
  TR(2, b, 13);
  issue_core<8, 12>(c, x2, C);
  if (w) { nb_arrive(N_VQ0, 288); nb_arrive(N_VQ1, 288); }
  else if (!FIRST) { __syncwarp(); mbar_arrive_elect(bar + B_Q0 * 8); }
  wait_stage(c, x1);
  if (never) dump6(bar, PA ? hk1 : hk0);
  TR(2, b, 6);
  wg_wait<0>(); pin(C);
  TR(2, b, 7);
  release_stage(x2);
  pack12(pk, C, 24);
  dump12<128>(c.kC + ko + 64, pk);
  pack12(pv2, C, 48);
  pack12(pq, C, 0);
  TR(2, b, 8);
  issue_core<0, SPL>(c, x1, C);
  TR(2, b, 9);
  if (!FIRST) { fence_async(); edge_ready(c, B_XK); }
  keep12(never, c.kC, pk);
  TR(2, b, 14);
  if (w) nb_sync(N_PVISS, 384);
  issue_core<SPL, 12>(c, x1, C);
  if (!FIRST) nb_arrive(N_KRDY, 256);
  TR(2, b, 1);
  if (PA && b == 11) tail_free(bar + B_TFREE * 8);
  wait_stage(c, x0);
  if (w) gwait<PA>(c, B_VFREE);
  if (w && b < TB) gwait<PA>(c, B_ODONE);
  TR(2, b, 10);
  if (!FIRST) dump12<128>(c.vC[PA], pv);
  dump12<128>(c.vC[PA ^ 1] + 768, pv2);
  TR(2, b, 11);
  wg_wait<0>(); pin(C);
  TR(2, b, 12);
  release_stage(x1);
  if (!FIRST && c.edge) publish(bar + B_XV * 8);
  if (c.hvalid) dump6(c.vH[PA], PA ? hv1 : hv0);
  if (PA && !w) nb_sync(N_Q0, 384);
  dump12<128>(c.qC[0], pq);
  pack12(pk, C, 24);
  pack12(pv, C, 48);
  pack12(pq, C, 0);
}

template <int IN> __device__ __forceinline__ void issue_proj(float (&D)[48]) {
  constexpr uint64_t da = mkdesc(SBC + IN, 128, 768, 0), db = mkdesc(SBC + SM_TWO, 12288, 512, 2);
  wg_fence();
  wg_ss96<0>(D, da, db);
#pragma unroll
  for (int k = 1; k < 12; k++) wg_ss96<1>(D, da + (k / 3) * 384 + (k % 3) * 16, db + k * 64);
  wg_commit();
}
template <int ACC> __device__ __forceinline__ void issue_proj_half(float (&D)[48], int hd) {
  const uint64_t da = mkdesc(SBC + SM_TIN2, 128, 768, 0) + hd * 384, db = mkdesc(SBC + SM_TWO, 12288, 512, 2) + hd * 192;
  wg_fence();
  wg_ss96<ACC>(D, da, db);
#pragma unroll
  for (int k = 1; k < 6; k++) wg_ss96<1>(D, da + (k / 3) * 768 + (k % 3) * 16, db + (k / 3) * 384 + (k % 3) * 64);
  wg_commit();
}
__device__ __forceinline__ void store_proj(const float (&D)[48], const CUtensorMap* m, uint32_t st, uint32_t sta, int row, int col, int ch) {
#pragma unroll
  for (int q = 0; q < 6; q++)
    stsm4((sta ^ ((q & 1) * 32)) + (q >> 1) * 1024,
          pack2(D[8 * q], D[8 * q + 1]), pack2(D[8 * q + 2], D[8 * q + 3]), pack2(D[8 * q + 4], D[8 * q + 5]), pack2(D[8 * q + 6], D[8 * q + 7]));
  fence_async();
  __syncwarp();
  if ((threadIdx.x & 31) == 0) {
    asm volatile("cp.async.bulk.tensor.4d.global.shared::cta.bulk_group [%0, {%2,%3,%4,%5}], [%1];" ::"l"(m), "r"(st), "r"(0), "r"(row), "r"(col), "r"(ch) : "memory");
    asm volatile("cp.async.bulk.commit_group;" ::: "memory");
  }
  __syncwarp();
}

__device__ __forceinline__ float fold(float a, float b, float t, int useb) {
  float r;
  asm("{\n.reg .pred p;\nsetp.ne.b32 p, %4, 0;\nfma.rn.f32 %0, %1, 0f3E553B95, %3;\n@p fma.rn.f32 %0, %2, 0f3E553B95, %3;\n}"
      : "=&f"(r) : "f"(a), "f"(b), "f"(t), "r"(useb));
  return r;
}
template <int U, int L>
__device__ __forceinline__ void softmax_tile(const float (&SA)[56], const float (&SB)[56], const float (&T)[16], int b0, int b1,
                                             uint32_t (&P)[28], float (&sx)[8], uint32_t nbV, uint32_t zero, uint32_t qa, uint32_t (&q)[12]) {
  float lu[14], ll[14];
#pragma unroll
  for (int j = 0; j < 7; j++) {
    constexpr int sh = U == L ? 2 : 0;
    const float tu0 = T[2 * j + sh], tu1 = T[2 * j + 1 + sh], tl0 = T[2 * j], tl1 = T[2 * j + 1];
    lu[2 * j]     = fold(SA[4 * (U + j)],     SB[4 * (U + j)],     tu0, b0);
    ll[2 * j]     = fold(SA[4 * (L + j) + 2], SB[4 * (L + j) + 2], tl0, b0);
    lu[2 * j + 1] = fold(SA[4 * (U + j) + 1], SB[4 * (U + j) + 1], tu1, b1);
    ll[2 * j + 1] = fold(SA[4 * (L + j) + 3], SB[4 * (L + j) + 3], tl1, b1);
  }
  float mu = lu[0], ml = ll[0], mu2 = lu[1], ml2 = ll[1];
#pragma unroll
  for (int j = 1; j < 7; j++) { mu = fmaxf(mu, lu[2 * j]); mu2 = fmaxf(mu2, lu[2 * j + 1]); ml = fmaxf(ml, ll[2 * j]); ml2 = fmaxf(ml2, ll[2 * j + 1]); }
  mu = fmaxf(mu, mu2); ml = fmaxf(ml, ml2);
  { const float a1 = __shfl_xor_sync(0xffffffffu, mu, 1), a2 = __shfl_xor_sync(0xffffffffu, mu, 2), a3 = __shfl_xor_sync(0xffffffffu, mu, 3);
    const float c1 = __shfl_xor_sync(0xffffffffu, ml, 1), c2 = __shfl_xor_sync(0xffffffffu, ml, 2), c3 = __shfl_xor_sync(0xffffffffu, ml, 3);
    mu = fmaxf(fmaxf(mu, a1), fmaxf(a2, a3)); ml = fmaxf(fmaxf(ml, c1), fmaxf(c2, c3)); }
  float su = 0.f, sl = 0.f;
#pragma unroll
  for (int c = 0; c < 14; c++) {
    if (c >= U && c < U + 7) {
      float e0 = ex2(lu[2 * (c - U)] - mu), e1 = ex2(lu[2 * (c - U) + 1] - mu);
      su = c == U ? e0 + e1 : (su + e0) + e1; P[2 * c] = pack2(e0, e1);
    } else P[2 * c] = 0u;
  }
  nb_sync(nbV | (P[2 * (U + MID)] & zero), 288);
#pragma unroll
  for (int k = 0; k < 3; k++) ldsm4(qa + k * 256, q[4 * k], q[4 * k + 1], q[4 * k + 2], q[4 * k + 3]);
#pragma unroll
  for (int c = 0; c < 14; c++) {
    if (c >= L && c < L + 7) {
      float e0 = ex2(ll[2 * (c - L)] - ml), e1 = ex2(ll[2 * (c - L) + 1] - ml);
      sl = c == L ? e0 + e1 : (sl + e0) + e1; P[2 * c + 1] = pack2(e0, e1);
    } else P[2 * c + 1] = 0u;
  }
  sx[0] = su; sx[4] = sl;
#pragma unroll
  for (int k = 1; k < 4; k++) sx[k] = __shfl_xor_sync(0xffffffffu, su, k);
#pragma unroll
  for (int k = 1; k < 4; k++) sx[4 + k] = __shfl_xor_sync(0xffffffffu, sl, k);
}

struct BandCfg { uint32_t ra0, ra1, meta; int b0, b1; };
__device__ __forceinline__ void band_cfg(int b, uint32_t tb, BandCfg& n) {
  uint32_t ln; asm volatile("mov.u32 %0, %%laneid;" : "=r"(ln));
  const int g = ln >> 2, t = ln & 3;
  const int sw = min(max(g + 1, b == 0 ? 4 : 0), b == 13 ? 5 : 8);
  const int i0 = 2 * t, i1 = 2 * t + 1;
  n.b0 = i0 <= sw - 2; n.b1 = i1 <= sw - 2;
  n.ra0 = tb + (i0 == sw - 1 ? 13 : i0 + 8 * n.b0 - g + 2) * 52;
  n.ra1 = tb + (i1 == sw - 1 ? 13 : i1 + 8 * n.b1 - g + 2) * 52;
  n.meta = ((0x5555u & ((1u << (2 * (sw - 1))) - 1)) ^ 0xDD88u ^ (((t ^ b) & 1) ? 0x5555u : 0u)) * 0x10001u;
}
__device__ __forceinline__ void band_load(const BandCfg& n, float (&T)[16], int& b0, int& b1, uint32_t& meta) {
#pragma unroll
  for (int jj = 0; jj < 8; jj++) { T[2 * jj] = lds_f32(n.ra0 + jj * 4); T[2 * jj + 1] = lds_f32(n.ra1 + jj * 4); }
  b0 = n.b0; b1 = n.b1; meta = n.meta;
}

struct Maps { CUtensorMap xc, xh, w, os, wo, ot; };

__global__ void __cluster_dims__(8, 1, 1) __launch_bounds__(512, 1)
na_attn_kernel(const __nv_bfloat16* __restrict__ x, const __nv_bfloat16* __restrict__ wqkv, const __nv_bfloat16* __restrict__ rpb, const __grid_constant__ Maps mp) {
  extern __shared__ __align__(1024) uint8_t smem_raw[];
  const uint32_t sb = smem_u32(smem_raw);
  if ((sb & 0x3FFFF) != SBC) return;
  const uint32_t bar = sb + SM_BAR;
  TR2START;
  const int tid = threadIdx.x, lane = tid & 31;
  const int warp = __shfl_sync(0xffffffffu, tid >> 5, 0);
  const int head = blockIdx.x & 3, base = blockIdx.x & 4, sp = blockIdx.x >> 2;
  const int par = sp < 24 ? sp / 6 : sp - 24, strip = sp < 24 ? sp - par * 6 : 6, ph = par >> 1, pw = par & 1;
  const int odd = strip & 1;

  if (warp < 12) asm volatile("barrier.cluster.arrive.relaxed.aligned;" ::: "memory");
  if (warp < 8) {
    asm volatile("setmaxnreg.inc.sync.aligned.u32 %0;" ::"n"(RA));
    float rv = -INFINITY;
    if (tid < 169) rv = __bfloat162float(rpb[head * 169 + tid]) * 1.4426950408889634f;
    if (tid < 192) {
      const int kc = (tid & 15) + 3, wc = (tid >> 4) % 6;
      sts128(tid < 96 ? sb + SM_K + kc * KS + wc * 128 + 48 : sb + SM_V + kc * 1536 + wc * 128 + (6 + (kc & 1)) * 16, make_uint4(0, 0, 0, 0));
    }
    fence_async();
    if (tid < 182) asm volatile("st.shared.f32 [%0], %1;" ::"r"(sb + SM_RPB + tid * 4), "f"(rv) : "memory");
    const int jw = warp >> 2, j = jw ^ odd, w = warp & 3, wt = 4 * j + w;
    int variant = w;
    if (strip == 0 && j == 0 && w < 2) variant = 4;
    if (strip == 6 && j == 1 && w >= 2) variant = 5;
    const bool v1 = opq((uint32_t)(variant & 1)), v2 = opq((uint32_t)(variant & 2)), v4 = opq((uint32_t)(variant & 4));
    const uint32_t qa = opq(sb + SM_Q + (8 * j + 2 * w + ((lane >> 3) & 1)) * 768 + (lane >> 4) * 128 + (((lane & 7) * 16) ^ (((lane >> 3) & 1) * 64)));
    uint32_t oa = opq(sb + SM_O + j * 6144 + (2 * w + ((lane >> 3) & 1)) * 768 + (lane >> 4) * 128 + (lane & 7) * 16);
    uint64_t dA = opq(mkdesc(SBC + SM_K, 128, KS, 0) + j * (8 * KS / 16)), dB = opq(dA + (KSLOT >> 4));
    uint64_t dV[7];
#pragma unroll
    for (int i = 0; i < 7; i++) dV[i] = opq(mkdesc(SBC + SM_V, 768, 128, 0) + j * (8 * 1536 / 16) + i * 192);
    const uint32_t nbK = opq((uint32_t)(N_KRDY + jw)), nbQ = opq((uint32_t)(N_QK0 + jw)), nbV = opq((uint32_t)(N_VQ0 + jw));
    asm volatile("barrier.cluster.wait.aligned;" ::: "memory");
    asm volatile("bar.arrive 1, 384;\nbar.sync 3, 256;" ::: "memory");
    float T[16];
    TRDECL;
    int b0, b1;
    uint32_t meta, ob = bar + B_ODONE * 8, fb = bar + B_OFREE * 8, fp = 1;
    const uint32_t tb = opq(sb + SM_RPB + (variant < 4 ? 3 : variant + 1 - 2 * w) * 4);
    const bool own = ((w ^ head) & 2) == 0;
    const uint32_t dst13 = sb + SM_TIN2 + head * 6144 + (2 * j + (w & 1)) * 1536, src13 = opq(own ? dst13 : sb + SM_S + (2 * j + (w & 1)) * 1536);
    const uint32_t snd[4] = {opq(own ? 0u : mapa(dst13, base + (head ^ 2))), opq(mapa(bar + (B_TIN + 2) * 8, base + (head ^ 2))),
                             opq(mapa(dst13, base + (w & 2) + (~head & 1))), opq(mapa(bar + (B_TIN + 3) * 8, base + (w & 2) + (~head & 1)))};
    BandCfg nx;
    band_cfg(0, tb, nx);
    band_load(nx, T, b0, b1, meta);
    band_cfg(1, tb, nx);
    const uint32_t zero = opq(blockIdx.x >> 16);
    uint32_t special = opq(0x380Au << 1);
    uint32_t q[12];
    mbar_wait(bar + B_Q0 * 8, 0);
#pragma unroll
    for (int k = 0; k < 3; k++) ldsm4(qa + k * 256, q[4 * k], q[4 * k + 1], q[4 * k + 2], q[4 * k + 3]);
    nb_arrive(N_Q0, 384);
#pragma unroll 1
    for (int b = 0; b < 14; b++) {
      float SA[56], SB[56];
      TR(0, b, 0);
      if (jw) mbar_wait(bar + B_KIMP * 8, b & 1);
      nb_sync(nbK, 256);
      TR(0, b, 1);
      TR(0, b - 1, 9);
      wg_fence();
      wg_rs112<0>(SA, q[0], q[1], q[2], q[3], dA);
      wg_rs112<0>(SB, q[0], q[1], q[2], q[3], dB);
      wg_rs112<1>(SA, q[4], q[5], q[6], q[7], dA + 16);
      wg_rs112<1>(SB, q[4], q[5], q[6], q[7], dB + 16);
      wg_rs112<1>(SA, q[8], q[9], q[10], q[11], dA + 32);
      wg_rs112<1>(SB, q[8], q[9], q[10], q[11], dB + 32);
      wg_commit();
      nb_arrive(nbQ, 256);
      { const uint64_t t = dA; dA = dB; dB = t; }
      special >>= 1;
      if (special & 1) {
        if (b == 3) band_cfg(13, tb, nx);
        else {
          if (b == 1 || b == 13) band_load(nx, T, b0, b1, meta);
          if (b >= TB) {
            ob = bar + (b == 13 ? (own ? B_TIN + 2 : B_ODONE) : B_OTAIL + 2 * (b - TB) + jw) * 8;
            if (b > TB) { fb = bar + (B_TFREE + b - 12) * 8; fp = 0; }
            oa += b == 12 ? 0u - (SM_O - SM_Q) : (b == 13 ? src13 - (sb + SM_Q + wt * 1536) : 0);
          }
        }
      }
      TR(0, b, 2);
      wg_wait<0>(); pin(SA); pin(SB);
      mbar_arrive_elect(bar + B_KFREE * 8);
      TR(0, b, 3);
      TR(0, b - 1, 10);
      uint32_t P[28];
      float sx[8];
      if (v2) {
        if (v1) softmax_tile<6, 7>(SA, SB, T, b0, b1, P, sx, nbV, zero, qa, q); else softmax_tile<4, 5>(SA, SB, T, b0, b1, P, sx, nbV, zero, qa, q);
      } else if (!v4) {
        if (v1) softmax_tile<2, 3>(SA, SB, T, b0, b1, P, sx, nbV, zero, qa, q); else softmax_tile<0, 1>(SA, SB, T, b0, b1, P, sx, nbV, zero, qa, q);
      } else {
        if (v1) softmax_tile<4, 4>(SA, SB, T, b0, b1, P, sx, nbV, zero, qa, q); else softmax_tile<3, 3>(SA, SB, T, b0, b1, P, sx, nbV, zero, qa, q);
      }
      float O[24];
      TR(0, b, 4);
      wg_fence();
      wg_sp48<0>(O, P[0], P[1], P[2], P[3], dV[0], meta);
#pragma unroll
      for (int s = 1; s < 7; s++) wg_sp48<1>(O, P[4 * s], P[4 * s + 1], P[4 * s + 2], P[4 * s + 3], dV[s], meta);
      wg_commit();
      nb_arrive(N_PVISS, 384);
      TR(0, b, 6);
      mbar_wait(fb, fp);
      wg_wait<0>(); pin(O);
      mbar_arrive_elect(bar + B_VFREE * 8);
      TR(0, b, 7);
      float ru, rl;
      asm("rcp.approx.ftz.f32 %0, %1;" : "=f"(ru) : "f"(((fmaf(O[0], 0.f, sx[0]) + sx[1]) + sx[2]) + sx[3]));
      asm("rcp.approx.ftz.f32 %0, %1;" : "=f"(rl) : "f"(((fmaf(O[2], 0.f, sx[4]) + sx[5]) + sx[6]) + sx[7]));
#pragma unroll
      for (int i = 0; i < 3; i++)
        stsm4(oa + i * 256, pack2(O[8 * i] * ru, O[8 * i + 1] * ru), pack2(O[8 * i + 2] * rl, O[8 * i + 3] * rl),
              pack2(O[8 * i + 4] * ru, O[8 * i + 5] * ru), pack2(O[8 * i + 6] * rl, O[8 * i + 7] * rl));
      publish(ob);
      fp ^= 1;
      meta ^= 0x55555555u;
      TR(0, b, 8);
    }
    asm volatile("{\n.reg .pred p, q;\nsetp.ne.b32 q, %1, 0;\nelect.sync _|p, 0xffffffff;\nand.pred q, q, p;\n"
                 "@q cp.async.bulk.shared::cluster.shared::cta.mbarrier::complete_tx::bytes [%1], [%0], 1536, [%2];\n"
                 "@p cp.async.bulk.shared::cluster.shared::cta.mbarrier::complete_tx::bytes [%3], [%0], 1536, [%4];\n}"
                 ::"r"(src13), "r"(snd[0]), "r"(snd[1]), "r"(snd[2]), "r"(snd[3]) : "memory");
    if (jw == 0) nb_arrive(3, 256);
    TRDUMP;
    cluster_sync();
  } else if (warp < 12) {
    TRDECL;
    TR(2, -3, 0);
    asm volatile("setmaxnreg.inc.sync.aligned.u32 %0;" ::"n"(RG));
    TR(2, -3, 1);
    GemmCtx c;
    c.bar = bar;
    const int gw = warp - 8, tk = gw * 16 + (lane & 15), hi = lane >> 4;
    { const int col = tk >> 2, i = tk & 3;
      c.kC = sb + SM_K + (col + 3) * KS + hi * 128 + i * 16;
      c.vC[0] = sb + SM_V + (col + 3) * 1536 + hi * 128 + (2 * i + ((col + 3) & 1)) * 16;
      c.qC[0] = sb + SM_Q + col * 768 + hi * 128 + (col & 1) * 64 + i * 16; }
    { const int kc = gw - 1 + 19 * odd, i = lane & 7; c.hvalid = gw > 0; c.edge = gw == (odd ? 0 : 3);
      c.kH = sb + SM_K + kc * KS + (lane >> 3) * 128 + i * 16;
      c.vH[0] = sb + SM_V + kc * 1536 + (lane >> 3) * 128 + (i >> 2) * 768 + (2 * (i & 3) + ((kc ^ (i >> 2)) & 1)) * 16; }
    Stage xs[3];
#pragma unroll
    for (int i = 0; i < 3; i++) {
      const int p = (i + 1) % 3;
      xs[i].lo = (uint32_t)mkdesc(SBC + SM_X + p * 24576, 16, 0, 0); xs[i].full = bar + (B_FULL + p) * 8;
      xs[i].em = opq(mapa(bar + (B_EMPTY + p) * 8, base + p)); xs[i].par = 0;
    }
    c.never = x == nullptr;
    c.kC = opq(c.kC); c.kH = opq(c.kH);
    c.vC[1] = opq(c.vC[0] ^ 16); c.vC[0] = opq(c.vC[0]);
    c.vH[1] = opq(c.vH[0] ^ 16); c.vH[0] = opq(c.vH[0]);
    c.qC[1] = opq(c.qC[0] ^ 64); c.qC[0] = opq(c.qC[0]);
    c.spin = 0;
    c.hiA = (uint32_t)(mkdesc(0, 0, 1024, 1) >> 32) + (blockIdx.x >> 16); c.hiB = (uint32_t)(mkdesc(0, 0, 256, 3) >> 32) + (blockIdx.x >> 16);
    asm volatile("barrier.cluster.wait.aligned;" ::: "memory");
    TR(2, -3, 2);
    mbar_wait(bar + B_WK * 8, 0);
    TR(2, -3, 5);
    uint32_t pk[12], pv[12], pq[12], hk1[6], hv1[6];
    gemm_iter<true, 0>(c, -2, pk, pv, pq, hk1, hv1, xs[0], xs[1], xs[2] TRPASS);
    TR2(blockIdx.x, 4);
    asm volatile("bar.sync 1, 384;" ::: "memory");
    c.hiA = opq(c.hiA); c.hiB = opq(c.hiB);
#pragma unroll 1
    for (int b = -1;; b += 2) {
      gemm_iter<false, 1>(c, b, pk, pv, pq, hk1, hv1, xs[2], xs[0], xs[1] TRPASS);
      if (b == 11) break;
      gemm_iter<false, 0>(c, b + 1, pk, pv, pq, hk1, hv1, xs[2], xs[0], xs[1] TRPASS);
      const Stage t = xs[2]; xs[2] = xs[1]; xs[1] = xs[0]; xs[0] = t;
    }
    TR2(blockIdx.x, 6);
    c.hiA = opq(c.hiA); c.hiB = opq(c.hiB);
    const uint32_t st = sb + gw * 3072;
    const uint32_t sta = st + (lane & 15) * 64 + ((hi ^ ((lane >> 1) & 3)) * 16);
    const int oc = ph * 112 + strip * 16 + 8 * (gw >> 1) + 4 * (head >> 1) + 2 * (gw & 1), och = pw * 6 + (head & 1) * 3;
    float D0[48], D1[48];
    mbar_arrive_elect(bar + B_WOFREE * 8);
    dump12<128>(c.qC[1], pq);
    nb_sync(N_QK1, 256);
    issue_halo<0, 8>(c, xs[2], D1);
    fence_async();
    nb_arrive(N_VQ0, 288); nb_arrive(N_VQ1, 288); nb_arrive(N_PVISS, 384);
    issue_halo<8, 12>(c, xs[2], D1);
    gwait<0>(c, B_KFREE);
    dump12<128>(c.kC, pk);
    if (c.edge) publish(bar + B_XK * 8);
    wg_wait<0>(); pin(D1);
    pack6(hk1, D1, 0);
    if (c.hvalid) dump6(c.kH, hk1);
    tail_free(bar + (B_TFREE + 1) * 8);
    pack6(hv1, D1, 24);
    fence_async();
    nb_arrive(N_KRDY, 256);
    gwait<0>(c, B_VFREE);
    dump12<128>(c.vC[0], pv);
    if (c.hvalid) dump6(c.vH[0], hv1);
    fence_async();
    edge_ready(c, B_XV);
    nb_arrive(N_VQ0, 288); nb_arrive(N_VQ1, 288);
    gwait<0>(c, B_WO);
    gwait<0>(c, B_TIN);
    TR(2, 13, 0);
    nb_sync(N_QK1, 256);
    issue_proj<SM_TIN0>(D0);
    wg_wait<0>(); pin(D0);
    TR(2, 13, 1);
    store_proj(D0, &mp.ot, st + SM_TST, sta + SM_TST, 8 * TB, oc, och);
    gwait<0>(c, B_TIN + 1);
    TR(2, 13, 2);
    nb_sync(N_PVISS, 384);
    nb_sync(3, 256);
    issue_proj<SM_TIN1>(D1);
    wg_wait<0>(); pin(D1);
    TR(2, 13, 3);
    store_proj(D1, &mp.ot, st + SM_TIN0, sta + SM_TIN0, 8 * TB + 8, oc, och);
    TR(2, 13, 4);
    gwait<0>(c, B_TIN + 2);
    TR(2, 13, 5);
    issue_proj_half<0>(D0, head & 1);
    gwait<0>(c, B_TIN + 3);
    TR(2, 13, 6);
    issue_proj_half<1>(D0, ~head & 1);
    asm volatile("barrier.cluster.arrive.relaxed.aligned;" ::: "memory");
    wg_wait<0>(); pin(D0);
    store_proj(D0, &mp.ot, st + SM_TIN0 + 12288, sta + SM_TIN0 + 12288, 8 * TB + 16, oc, och);
    TR(2, 13, 7);
    if (lane == 0) asm volatile("cp.async.bulk.wait_group.read 0;" ::: "memory");
    __syncwarp();
    TR(2, 13, 8);
    TR2(blockIdx.x, 2);
    TR2FLUSH(blockIdx.x);
    TRDUMP;
    asm volatile("barrier.cluster.wait.aligned;" ::: "memory");
  } else {
    TRDECL;
    TR(1, -3, 8);
    if (warp == 15) {
      const int l = min(lane, 24), row = head + (l < 16 ? 0 : 4 * ((l - 16) / 3)), col = strip * 16 + (l < 16 ? l : (l - 16) % 3 + (odd ? 16 : (strip ? -3 : 0)));
      const uint8_t* p = reinterpret_cast<const uint8_t*>(x) + (uint32_t)(row * ROWB + (ph * 112 + col) * 768 + pw * 384);
#pragma unroll
      for (int i = 0; i < 3; i++) if (!(OPT & 1)) asm volatile("prefetch.global.L2 [%0];" ::"l"(p + i * 128));
      if (!(OPT & 2) && lane < 16 && blockIdx.x < 108) asm volatile("prefetch.global.L2 [%0];" ::"l"(wqkv + (blockIdx.x * 16 + lane) * 64));
    } else if (elect_one()) {
      if (warp == 12) {
        asm volatile("prefetch.tensormap [%0];" ::"l"(head == 1 ? &mp.xh : &mp.xc) : "memory");
        asm volatile("prefetch.tensormap [%0];" ::"l"(&mp.w) : "memory");
      } else if (warp == 13) {
#pragma unroll
        for (int i = 0; i < B_XK; i++) mbar_init(bar + i * 8, (i >= B_EMPTY && i < B_TIN) || (i >= B_TFREE && i < B_WK) ? 16 : (i == B_TIN + 2 ? 5 : 1));
      } else {
#pragma unroll
        for (int i = B_XK; i < B_COUNT; i++) mbar_init(bar + i * 8, i < B_Q0 ? 2 : (i < B_ODONE ? 4 : (i == B_VFREE ? 9 : 8)));
      }
      asm volatile("fence.mbarrier_init.release.cluster;" ::: "memory");
    }
    __syncwarp();
    TR(1, -3, 10);
    asm volatile("barrier.cluster.arrive.relaxed.aligned;" ::: "memory");
    asm volatile("setmaxnreg.dec.sync.aligned.u32 24;");
    asm volatile("griddepcontrol.launch_dependents;");
    if (warp != 12) asm volatile("barrier.cluster.wait.aligned;" ::: "memory");
    else {
      const int cc = ph * 112 + strip * 16, ch = cc + (odd ? 16 : (strip ? -3 : 0)), rh = strip ? -4 : 112;
      const uint32_t fb = opq(bar + (B_FULL + head) * 8), dst0 = sb + SM_X + head * 24576, c3 = opq((uint32_t)(pw * 3)), mask = opq(15u << base);
      int t = head == 0 ? 2 : head - 1;
      uint64_t mx = opq((uint64_t)(t ? &mp.xc : &mp.xh));
      uint32_t row = opq((uint32_t)(t ? 4 * t - 4 : rh)), col = opq((uint32_t)(t ? cc : ch)), dst = opq(dst0 + (t ? 0 : 2048));
#pragma unroll 1
      for (int n = 0;; n++) {
        if (n) mbar_wait(fb + (B_EMPTY - B_FULL) * 8, ~n & 1);
        else { TR(1, -3, 11); asm volatile("barrier.cluster.wait.aligned;" ::: "memory"); TR(1, -3, 12); }
        if (head < 3) {
          asm volatile("{\n.reg .pred p;\n.reg .b16 m;\nelect.sync _|p, 0xffffffff;\ncvt.u16.u32 m, %7;\n"
                       "@p cp.async.bulk.tensor.4d.shared::cluster.global.mbarrier::complete_tx::bytes.multicast::cluster [%0], [%1, {%3,%4,%5,%6}], [%2], m;\n}"
                       ::"r"(dst), "l"(mx), "r"(fb), "r"(0), "r"(row), "r"(col), "r"(c3), "r"(mask) : "memory");
          if (lane < 4) remote_expect(mapa(fb, base + lane), dst == dst0 ? 24576 : 18432);
          __syncwarp();
        }
        if (n == 0 && elect_one()) {
#pragma unroll
          for (int i = 0; i < 9; i++) {
            const int part = i < 6 ? 1 + (i & 1) : 0, at = i < 6 ? i >> 1 : i - 6;
            asm volatile("cp.async.bulk.tensor.2d.shared::cluster.global.mbarrier::complete_tx::bytes.multicast::cluster [%0], [%1, {%3,%4}], [%2], %5;"
                         ::"r"(sb + SM_W + (part * 3 + at) * 6144 + base * 768), "l"(&mp.w), "r"(bar + (part ? B_WK : B_WQ) * 8),
                           "r"(part * 192 + head * 48 + at * 16), "r"(base * 24), "h"((uint16_t)(0x11 << head)) : "memory");
          }
        }
        __syncwarp();
        TR(1, n - 3, 13);
        if (head == 3 || n == 11) break;
        t += 3;
        const int hn = t / 5;
        const bool core = t != 5 * hn;
        mx = opq((uint64_t)(core ? &mp.xc : &mp.xh));
        row = opq((uint32_t)(core ? 4 * (t - hn - 1) : rh + 16 * hn)); col = opq((uint32_t)(core ? cc : ch)); dst = opq(dst0 + (core ? 0 : 2048));
        if (elect_one()) asm volatile("cp.async.bulk.prefetch.tensor.4d.L2.global [%0, {%1,%2,%3,%4}];" ::"l"(mx), "r"(0), "r"(row), "r"(col), "r"(c3) : "memory");
        __syncwarp();
      }
      mbar_wait(bar + B_WOFREE * 8, 0);
      if (elect_one()) {
        mbar_expect(bar + B_WO * 8, 36864);
        asm volatile("cp.async.bulk.tensor.3d.shared::cluster.global.mbarrier::complete_tx::bytes [%0], [%1, {%3,%4,%5}], [%2];"
                     ::"r"(sb + SM_TWO), "l"(&mp.wo), "r"(bar + B_WO * 8), "r"(0), "r"(0), "r"((head & 1) * 3) : "memory");
      }
      __syncwarp();
    }
    if (warp & 1) {
      const uint32_t partner = (blockIdx.x & 7) ^ 4;
      const int cs = odd ? 3 : (strip == 6 ? 15 : 16), cd = odd || strip == 6 ? 19 : 0;
      const uint32_t rb = opq(mapa(bar, partner));
      if (warp == 13) {
        const uint32_t dst = opq(mapa(sb + SM_V + cd * 1536, partner)), src = opq(sb + SM_V + cs * 1536);
#pragma unroll 1
        for (int b = 0;; b++) {
          const uint32_t pa = b & 1;
          nb_arrive(N_VQ0, 288);
          mbar_wait(bar + B_XV * 8, pa);
          TR(1, b, 0);
          if (elect_one()) { copy_remote(dst, src, 4608, rb + B_VIMP * 8); remote_expect(rb + B_VIMP * 8, 4608); }
          __syncwarp();
          TR(1, b, 1);
          mbar_wait(bar + B_VIMP * 8, pa);
          TR(1, b, 2);
          nb_arrive(N_VQ1, 288);
          if (elect_one()) remote_arrive(rb + B_VFREE * 8);
          __syncwarp();
          TR(1, b, 3);
          if (b == 13) break;
          mbar_wait(bar + B_VFREE * 8, pa);
          if (elect_one()) remote_arrive(rb + B_XV * 8);
          __syncwarp();
        }
      } else {
        const uint32_t dst = opq(mapa(sb + SM_K + cd * KS, partner)), src = opq(sb + SM_K + cs * KS);
#pragma unroll 1
        for (int b = 0;; b++) {
          const uint32_t pa = b & 1, so = (pa ^ 1) * KSLOT;
          mbar_wait(bar + B_XK * 8, pa);
          TR(1, b - 1, 4);
          if (elect_one()) {
            copy_remote(dst + so, src + so, 3 * KS, rb + B_KIMP * 8);
            if (b == 0) copy_remote(dst, src, 3 * KS, rb + B_KIMP * 8);
            remote_expect(rb + B_KIMP * 8, b ? 3 * KS : 6 * KS);
          }
          __syncwarp();
          TR(1, b - 1, 5);
          TR(1, b - 1, 7);
          if (b == 13) break;
          mbar_wait(bar + B_KFREE * 8, pa);
          if (elect_one()) remote_arrive(rb + B_XK * 8);
          __syncwarp();
        }
      }
    }
    if (warp == 14) {
      int* flag = g_flags + (par * 7 + strip) * 2 * FS;
      if (elect_one()) {
        mbar_expect(bar + B_WK * 8, 36864); mbar_expect(bar + B_WQ * 8, 18432);
        mbar_arrive(bar + B_XK * 8); mbar_arrive(bar + B_XV * 8);
        mbar_expect(bar + B_TIN * 8, 24576); mbar_expect(bar + (B_TIN + 1) * 8, 24576); mbar_expect(bar + (B_TIN + 2) * 8, 6144); mbar_expect(bar + (B_TIN + 3) * 8, 12288);
      }
      __syncwarp();
#pragma unroll 1
      for (int b = 0; b < TB; b++) {
        mbar_wait(bar + B_ODONE * 8, b & 1);
        if (lane == 0) {
#pragma unroll 1
          for (int i = 0; i < 16; i += OCH) {
            asm volatile("cp.async.bulk.tensor.3d.global.shared::cta.bulk_group [%0, {%2,%3,%4}], [%1];"
                         ::"l"(&mp.os), "r"(sb + SM_O + i * 768), "r"(pw * 192), "r"(8 * b + 2 * head), "r"(ph * 112 + strip * 16 + i) : "memory");
            asm volatile("cp.async.bulk.commit_group;\ncp.async.bulk.wait_group 0;" ::: "memory");
          }
        }
        __syncwarp();
        mbar_arrive_elect(bar + B_OFREE * 8);
        if (lane == 0)
          asm volatile("fence.proxy.async.global;\nfence.acq_rel.gpu;\nred.relaxed.gpu.global.add.s32 [%0], 1;\nred.relaxed.gpu.global.add.s32 [%1], 1;"
                       ::"l"(flag + b * 56 * FS), "l"(flag + (b * 56 + 1) * FS) : "memory");
        __syncwarp();
      }
#pragma unroll 1
      for (int t = 0; t < 4; t++) {
        const int i = t >> 1, jw = t & 1, j = jw ^ odd;
        if (!jw) mbar_wait(bar + (B_TFREE + i) * 8, 0);
        mbar_wait(bar + (B_OTAIL + t) * 8, 0);
        if (elect_one()) {
#pragma unroll 1
          for (int d = 0; d < 8; d++) {
            const int dst = (d + head) & 3, pc = d >> 2;
            send_o<1536>(sb + (i ? SM_TIN1 : SM_TIN0) + head * 6144 + j * 3072 + pc * 1536,
                         sb + (i ? SM_Q : SM_O) + (4 * j + (dst & 2) + pc) * 1536, bar + (B_TIN + i) * 8, base + dst);
          }
        }
        __syncwarp();
      }
    }
    TRDUMP;
    cluster_sync();
  }
}

constexpr int NSTB = 6;
constexpr int NTB = TB * 56;
constexpr int SM_B_ST = 0;
constexpr int SM_B_IN = 73728;
constexpr int SM_B_W = SM_B_IN + 3 * 24576;
constexpr int SM_B_BAR = SM_B_IN + NSTB * 24576;
constexpr int SM_B_TOTAL = SM_B_BAR + 512;
struct MapsB { CUtensorMap oi, oo, wo; };

__global__ void __launch_bounds__(512, 1)
na_proj_kernel(const __grid_constant__ MapsB mp) {
  extern __shared__ __align__(1024) uint8_t smem_raw[];
  const uint32_t sb = smem_u32(smem_raw);
  if ((sb & 0x3FFFF) != SBC) return;
  const uint32_t bar = sb + SM_B_BAR;
  const int tid = threadIdx.x, lane = tid & 31;
  const int warp = __shfl_sync(0xffffffffu, tid >> 5, 0);
  TR2START;
  TRB(47, 0);
  if (warp == 12 && elect_one()) {
#pragma unroll
    for (int i = 0; i <= 2 * NSTB; i++) mbar_init(bar + i * 8, i < NSTB || i == 2 * NSTB ? 1 : 12);
    asm volatile("st.shared.u32 [%0], 0;" ::"r"(bar + 120) : "memory");
    mbar_expect(bar + 2 * NSTB * 8, 73728);
#pragma unroll
    for (int i = 0; i < 2; i++)
      asm volatile("cp.async.bulk.tensor.3d.shared::cluster.global.mbarrier::complete_tx::bytes [%0], [%1, {%3,%4,%5}], [%2];"
                   ::"r"(sb + SM_B_W + i * 36864), "l"(&mp.wo), "r"(bar + 2 * NSTB * 8), "r"(0), "r"(0), "r"(i * 3) : "memory");
  }
  __syncthreads();
  const int step = gridDim.x;
  if (warp == 15) {
    int so = 0;
    nb_arrive(4, 288); nb_arrive(5, 288); nb_arrive(6, 288);
#pragma unroll 1
    for (int n = blockIdx.x, tk = 0; n < NTB; n += step, tk++) {
      uint32_t cc = 0;
#pragma unroll
      for (int wg = 0; wg < 3; wg++) {
        if (lane == 0) asm volatile("cp.async.bulk.wait_group.read 5;" ::: "memory");
        nb_sync(1 + wg, 160);
        if (wg == 0 || n + step < NTB) nb_arrive(4 + wg, 288);
        if (wg == 0) asm volatile("ld.shared.u32 %0, [%1];" : "=r"(cc) : "r"(bar + 128 + tk * 4) : "memory");
        if (lane == 0) {
          asm volatile("cp.async.bulk.tensor.4d.global.shared::cta.bulk_group [%0, {%2,%3,%4,%5}], [%1];"
                       ::"l"(&mp.oo), "r"(sb + SM_B_ST + wg * 8192 + so), "r"(0), "r"((cc >> 8) & 255), "r"(cc >> 16), "r"((cc & 1) * 3 + wg) : "memory");
          asm volatile("cp.async.bulk.commit_group;" ::: "memory");
        }
        __syncwarp();
      }
      so = so == 49152 ? 0 : so + 24576;
    }
    if (lane == 0) asm volatile("cp.async.bulk.wait_group.read 0;" ::: "memory");
  } else if (warp >= 12) {
    nb_sync(7, 480);
#pragma unroll 1
    for (int n = blockIdx.x + (warp - 12) * step; n < NTB; n += 3 * step) {
      const int b = n / 56, rem = n - b * 56, par = rem / 14;
      const int c0 = opq((uint32_t)(par & 1)), c1 = opq((uint32_t)(8 * b)), c2 = opq((uint32_t)((par >> 1) * 112 + (rem - par * 14) * 8));
      int v; uint32_t spin = 0, tk = 0;
      do { asm volatile("ld.acquire.gpu.global.s32 %0, [%1];" : "=r"(v) : "l"(g_flags + n * FS) : "memory"); } while (v < 4 && ++spin < SPIN_LIMIT);
      if (lane == 0) asm volatile("atom.shared.add.u32 %0, [%1], 1;" : "=r"(tk) : "r"(bar + 120) : "memory");
      asm volatile("fence.proxy.async.global;" ::: "memory");
      tk = __shfl_sync(0xffffffffu, tk, 0);
      TRB(tk, 0);
      const uint32_t use = tk / NSTB, sg = tk - use * NSTB;
      if (use) mbar_wait(bar + (NSTB + sg) * 8, (use - 1) & 1);
      TRB(tk, 1);
      if (elect_one()) {
        asm volatile("st.shared.u32 [%0], %1;" ::"r"(bar + 128 + tk * 4), "r"(c0 | c1 << 8 | c2 << 16) : "memory");
        mbar_expect(bar + sg * 8, 24576);
        asm volatile("cp.async.bulk.tensor.3d.shared::cluster.global.mbarrier::complete_tx::bytes [%0], [%1, {%3,%4,%5}], [%2];"
                     ::"r"(sb + SM_B_IN + sg * 24576), "l"(&mp.oi), "r"(bar + sg * 8), "r"(c0 * 192), "r"(c1), "r"(c2) : "memory");
        g_flags[n * FS] = 0;
      }
      __syncwarp();
    }
  } else {
    const int wg = warp >> 2, w = warp & 3;
    uint32_t a[48];
    mbar_wait(bar + 2 * NSTB * 8, 0);
    {
      const int k = (lane & 7) + (lane >> 4) * 8, ch = (warp & 1) * 2 + ((lane >> 3) & 1);
      const uint32_t wa = sb + SM_B_W + (warp >> 1) * 12288 + k * 64 + ((ch ^ ((k >> 1) & 3)) * 16);
#pragma unroll
      for (int i = 0; i < 12; i++)
        asm volatile("ldmatrix.sync.aligned.m8n8.x4.trans.shared.b16 {%0,%1,%2,%3}, [%4];"
                     : "=r"(a[4 * i]), "=r"(a[4 * i + 1]), "=r"(a[4 * i + 2]), "=r"(a[4 * i + 3]) : "r"(wa + i * 1024) : "memory");
    }
    nb_sync(7, 480);
    TRB(47, 1);
    const uint32_t sta = opq(sb + SM_B_ST + wg * 8192 + ((lane & 7) + (lane >> 4) * 8) * 128 + (((2 * w + ((lane >> 3) & 1)) ^ (lane & 7)) * 16));
    const uint32_t hi = opq((uint32_t)(mkdesc(0, 0, 3072, 0) >> 32) + (blockIdx.x >> 16)), bb = opq(bar);
    const uint32_t nbT = opq((uint32_t)(4 + wg)), nbN = opq((uint32_t)(wg == 2 ? 4 : 5 + wg)), nbD = opq((uint32_t)(1 + wg));
    int left = (NTB - blockIdx.x + step - 1) / step;
    if (wg == 2) nb_arrive(4, 288);
#pragma unroll 1
    for (uint32_t ph = 0;; ph ^= 1) {
#pragma unroll
      for (int sg = 0; sg < NSTB; sg++) {
        constexpr uint64_t db = mkdesc(SBC + SM_B_IN, 128, 3072, 0);
        float D[32];
        mbar_wait(bb + sg * 8, ph);
        nb_sync(nbT, 288);
        wg_fence();
        wg_rs64<0>(D, a[0], a[1], a[2], a[3], dsc(db + sg * 1536, hi));
#pragma unroll
        for (int k = 1; k < 12; k++) wg_rs64<1>(D, a[4 * k], a[4 * k + 1], a[4 * k + 2], a[4 * k + 3], dsc(db + sg * 1536 + k * 16, hi));
        wg_commit();
        nb_arrive(nbN, 288);
        wg_wait<0>(); pin(D);
        mbar_arrive_elect(bb + (NSTB + sg) * 8);
#pragma unroll
        for (int q = 0; q < 4; q++)
          asm volatile("stmatrix.sync.aligned.m8n8.x4.trans.shared.b16 [%0], {%1,%2,%3,%4};" ::"r"(sta + (sg % 3) * 24576 + q * 2048),
                       "r"(pack2(D[8 * q], D[8 * q + 1])), "r"(pack2(D[8 * q + 2], D[8 * q + 3])), "r"(pack2(D[8 * q + 4], D[8 * q + 5])), "r"(pack2(D[8 * q + 6], D[8 * q + 7])) : "memory");
        fence_async();
        nb_arrive(nbD, 160);
        if (wg == 0) TRB(31 - left, 5);
        if (--left == 0) goto done;
      }
    }
  done:
    if (wg == 0) nb_arrive(4, 288);
    TR2(132 + blockIdx.x, 2);
    TR2FLUSH(132 + blockIdx.x);
  }
}

typedef CUresult (*EncodeFn)(CUtensorMap*, CUtensorMapDataType, cuuint32_t, void*, const cuuint64_t*, const cuuint64_t*, const cuuint32_t*,
                             const cuuint32_t*, CUtensorMapInterleave, CUtensorMapSwizzle, CUtensorMapL2promotion, CUtensorMapFloatOOBfill);
static EncodeFn g_enc = nullptr;
static void make_map(CUtensorMap* m, const void* p, int rank, const cuuint64_t* dim, const cuuint64_t* str, const cuuint32_t* box, CUtensorMapSwizzle sw) {
  const cuuint32_t ones[5] = {1, 1, 1, 1, 1};
  g_enc(m, CU_TENSOR_MAP_DATA_TYPE_BFLOAT16, rank, (void*)p, dim, str, box, ones, CU_TENSOR_MAP_INTERLEAVE_NONE, sw,
        CU_TENSOR_MAP_L2_PROMOTION_L2_128B, CU_TENSOR_MAP_FLOAT_OOB_FILL_NONE);
}

extern "C" void kernel_launch(void* const* d_in, const int* in_sizes, int n_in, void* d_out, int out_size) {
  const __nv_bfloat16* x = (const __nv_bfloat16*)d_in[0];
  const __nv_bfloat16* wqkv = (const __nv_bfloat16*)d_in[1];
  const __nv_bfloat16* wo = (const __nv_bfloat16*)d_in[2];
  const __nv_bfloat16* rpb = (const __nv_bfloat16*)d_in[3];

  if (!g_enc) {
    void* fn = nullptr; cudaDriverEntryPointQueryResult qr;
    cudaGetDriverEntryPoint("cuTensorMapEncodeTiled", &fn, cudaEnableDefault, &qr);
    g_enc = (EncodeFn)fn;
    cudaFuncSetAttribute(na_attn_kernel, cudaFuncAttributeMaxDynamicSharedMemorySize, SM_A_TOTAL);
    cudaFuncSetAttribute(na_proj_kernel, cudaFuncAttributeMaxDynamicSharedMemorySize, SM_B_TOTAL);
  }
  Maps ma; MapsB mb;
  { cuuint64_t dim[4] = {64, 112, 224, 6}, str[3] = {(cuuint64_t)ROWB, 768, 128};
    cuuint32_t box[4] = {64, 4, 16, 3}, boxh[4] = {64, 16, 3, 3}, boxo[4] = {64, 8, 8, 1};
    make_map(&ma.xc, x, 4, dim, str, box, CU_TENSOR_MAP_SWIZZLE_128B);
    make_map(&ma.xh, x, 4, dim, str, boxh, CU_TENSOR_MAP_SWIZZLE_128B);
    make_map(&mb.oo, d_out, 4, dim, str, boxo, CU_TENSOR_MAP_SWIZZLE_128B); }
  { cuuint64_t dim[3] = {384, 112, 224}, str[2] = {(cuuint64_t)ROWB, 768};
    cuuint32_t box[3] = {192, 8, 8}, boxs[3] = {192, 2, OCH};
    make_map(&mb.oi, d_out, 3, dim, str, box, CU_TENSOR_MAP_SWIZZLE_NONE);
    make_map(&ma.os, d_out, 3, dim, str, boxs, CU_TENSOR_MAP_SWIZZLE_NONE); }
  { cuuint64_t dim[4] = {32, 112, 224, 12}, str[3] = {(cuuint64_t)ROWB, 768, 64};
    cuuint32_t box[4] = {32, 8, 2, 3};
    make_map(&ma.ot, d_out, 4, dim, str, box, CU_TENSOR_MAP_SWIZZLE_64B); }
  { cuuint64_t dim[2] = {576, 192}, str[1] = {1152};
    cuuint32_t box[2] = {16, 96};
    make_map(&ma.w, wqkv, 2, dim, str, box, CU_TENSOR_MAP_SWIZZLE_32B); }
  { cuuint64_t dim[3] = {32, 192, 6}, str[2] = {384, 64};
    cuuint32_t box[3] = {32, 192, 3};
    make_map(&ma.wo, wo, 3, dim, str, box, CU_TENSOR_MAP_SWIZZLE_64B);
    mb.wo = ma.wo; }
  na_attn_kernel<<<112, 512, SM_A_TOTAL>>>(x, wqkv, rpb, ma);
  cudaLaunchConfig_t cfg = {};
  cfg.gridDim = dim3(20); cfg.blockDim = dim3(512); cfg.dynamicSmemBytes = SM_B_TOTAL; cfg.stream = cudaStreamPerThread;
  cudaLaunchAttribute at[1];
  at[0].id = cudaLaunchAttributeProgrammaticStreamSerialization; at[0].val.programmaticStreamSerializationAllowed = 1;
  cfg.attrs = at; cfg.numAttrs = 1;
  cudaLaunchKernelEx(&cfg, na_proj_kernel, mb);
}
```

```cpp
#include <cuda_runtime.h>
#include <cuda_bf16.h>
#include <cuda.h>
#include <stdint.h>

#define SPIN_LIMIT (1u << 18)

__device__ __forceinline__ uint32_t smem_u32(const void* p) { return (uint32_t)__cvta_generic_to_shared(p); }
__device__ __forceinline__ void wg_fence() { asm volatile("wgmma.fence.sync.aligned;" ::: "memory"); }
__device__ __forceinline__ void wg_commit() { asm volatile("wgmma.commit_group.sync.aligned;" ::: "memory"); }
template <int N> __device__ __forceinline__ void wg_wait() { asm volatile("wgmma.wait_group.sync.aligned %0;" ::"n"(N) : "memory"); }
template <int N> __device__ __forceinline__ void pin(float (&d)[N]) {
#pragma unroll
  for (int i = 0; i < N; i++) asm volatile("" : "+f"(d[i])::"memory");
}
__host__ __device__ constexpr uint64_t mkdesc(uint32_t addr, uint32_t lbo, uint32_t sbo, uint32_t sw) {
  return (uint64_t)((addr & 0x3FFFF) >> 4) | ((uint64_t)(lbo >> 4) << 16) | ((uint64_t)(sbo >> 4) << 32) | ((uint64_t)sw << 62);
}
__device__ __forceinline__ void mbar_init(uint32_t bar, uint32_t cnt) { asm volatile("mbarrier.init.shared::cta.b64 [%0], %1;" ::"r"(bar), "r"(cnt) : "memory"); }
__device__ __forceinline__ void mbar_arrive(uint32_t bar) { asm volatile("mbarrier.arrive.shared::cta.b64 _, [%0];" ::"r"(bar) : "memory"); }
__device__ __forceinline__ bool elect_one() {
  uint32_t r; asm volatile("{\n.reg .pred p;\nelect.sync _|p, 0xffffffff;\nselp.u32 %0, 1, 0, p;\n}" : "=r"(r)); return r;
}
__device__ __forceinline__ void mbar_arrive_elect(uint32_t bar) {
  asm volatile("{\n.reg .pred p;\nelect.sync _|p, 0xffffffff;\n@p mbarrier.arrive.shared::cta.b64 _, [%0];\n}" ::"r"(bar) : "memory");
}
__device__ __forceinline__ void mbar_expect(uint32_t bar, uint32_t bytes) { asm volatile("mbarrier.arrive.expect_tx.shared::cta.b64 _, [%0], %1;" ::"r"(bar), "r"(bytes) : "memory"); }
__device__ __forceinline__ void mbar_arrive_remote(uint32_t bar, uint32_t cta) {
  asm volatile("{\n.reg .b32 ra;\nmapa.shared::cluster.u32 ra, %0, %1;\nmbarrier.arrive.relaxed.cluster.shared::cluster.b64 _, [ra];\n}" ::"r"(bar), "r"(cta) : "memory");
}
__device__ __forceinline__ void mbar_wait(uint32_t bar, uint32_t parity) {
  asm volatile("{\n.reg .pred p;\n.reg .b32 n;\nmov.b32 n, 0;\nWL:\nmbarrier.try_wait.parity.shared::cta.b64 p, [%0], %1;\n@p bra WD;\n"
               "add.u32 n, n, 1;\nsetp.lt.u32 p, n, 65536;\n@p bra WL;\nWD:\n}" ::"r"(bar), "r"(parity) : "memory");
}
__device__ __forceinline__ void nb_sync(int id, int n) { asm volatile("bar.sync %0, %1;" ::"r"(id), "r"(n) : "memory"); }
__device__ __forceinline__ void nb_arrive(int id, int n) { asm volatile("bar.arrive %0, %1;" ::"r"(id), "r"(n) : "memory"); }
__device__ __forceinline__ uint32_t opq(uint32_t x) { uint32_t r; asm volatile("mov.b32 %0, %1;" : "=r"(r) : "r"(x)); return r; }
__device__ __forceinline__ uint64_t opq(uint64_t x) { uint64_t r; asm volatile("mov.b64 %0, %1;" : "=l"(r) : "l"(x)); return r; }
__device__ __forceinline__ uint32_t mapa(uint32_t a, uint32_t cta) { uint32_t r; asm("mapa.shared::cluster.u32 %0, %1, %2;" : "=r"(r) : "r"(a), "r"(cta)); return r; }
__device__ __forceinline__ void fence_async() { asm volatile("fence.proxy.async.shared::cta;" ::: "memory"); }
__device__ __forceinline__ void cluster_sync() {
  asm volatile("barrier.cluster.arrive.relaxed.aligned;\nbarrier.cluster.wait.aligned;" ::: "memory");
}
__device__ __forceinline__ uint32_t pack2(float lo, float hi) {
  uint32_t r; asm("cvt.rn.bf16x2.f32 %0, %1, %2;" : "=r"(r) : "f"(hi), "f"(lo)); return r;
}
__device__ __forceinline__ void stsm4(uint32_t a, uint32_t r0, uint32_t r1, uint32_t r2, uint32_t r3) {
  asm volatile("stmatrix.sync.aligned.m8n8.x4.shared.b16 [%0], {%1,%2,%3,%4};" ::"r"(a), "r"(r0), "r"(r1), "r"(r2), "r"(r3) : "memory");
}
__device__ __forceinline__ void ldsm4(uint32_t a, uint32_t& r0, uint32_t& r1, uint32_t& r2, uint32_t& r3) {
  asm volatile("ldmatrix.sync.aligned.m8n8.x4.shared.b16 {%0,%1,%2,%3}, [%4];" : "=r"(r0), "=r"(r1), "=r"(r2), "=r"(r3) : "r"(a) : "memory");
}
__device__ __forceinline__ void sts128(uint32_t a, uint4 v) {
  asm volatile("st.shared.v4.b32 [%0], {%1,%2,%3,%4};" ::"r"(a), "r"(v.x), "r"(v.y), "r"(v.z), "r"(v.w) : "memory");
}
__device__ __forceinline__ float lds_f32(uint32_t a) { float v; asm volatile("ld.shared.f32 %0, [%1];" : "=f"(v) : "r"(a)); return v; }
__device__ __forceinline__ float ex2(float x) { float y; asm("ex2.approx.ftz.f32 %0, %1;" : "=f"(y) : "f"(x)); return y; }

template<int SC> __device__ __forceinline__ void wg_ss144(float (&d)[72], uint64_t da, uint64_t db) {
  asm volatile("{\n.reg .pred p;\nsetp.ne.b32 p, %74, 0;\nwgmma.mma_async.sync.aligned.m64n144k16.f32.bf16.bf16 {%0,%1,%2,%3,%4,%5,%6,%7,%8,%9,%10,%11,%12,%13,%14,%15,%16,%17,%18,%19,%20,%21,%22,%23,%24,%25,%26,%27,%28,%29,%30,%31,%32,%33,%34,%35,%36,%37,%38,%39,%40,%41,%42,%43,%44,%45,%46,%47,%48,%49,%50,%51,%52,%53,%54,%55,%56,%57,%58,%59,%60,%61,%62,%63,%64,%65,%66,%67,%68,%69,%70,%71}, %72, %73, p, 1, 1, 0, 1;\n}\n"
    : "+f"(d[0]),"+f"(d[1]),"+f"(d[2]),"+f"(d[3]),"+f"(d[4]),"+f"(d[5]),"+f"(d[6]),"+f"(d[7]),"+f"(d[8]),"+f"(d[9]),"+f"(d[10]),"+f"(d[11]),"+f"(d[12]),"+f"(d[13]),"+f"(d[14]),"+f"(d[15]),"+f"(d[16]),"+f"(d[17]),"+f"(d[18]),"+f"(d[19]),"+f"(d[20]),"+f"(d[21]),"+f"(d[22]),"+f"(d[23]),"+f"(d[24]),"+f"(d[25]),"+f"(d[26]),"+f"(d[27]),"+f"(d[28]),"+f"(d[29]),"+f"(d[30]),"+f"(d[31]),"+f"(d[32]),"+f"(d[33]),"+f"(d[34]),"+f"(d[35]),"+f"(d[36]),"+f"(d[37]),"+f"(d[38]),"+f"(d[39]),"+f"(d[40]),"+f"(d[41]),"+f"(d[42]),"+f"(d[43]),"+f"(d[44]),"+f"(d[45]),"+f"(d[46]),"+f"(d[47]),"+f"(d[48]),"+f"(d[49]),"+f"(d[50]),"+f"(d[51]),"+f"(d[52]),"+f"(d[53]),"+f"(d[54]),"+f"(d[55]),"+f"(d[56]),"+f"(d[57]),"+f"(d[58]),"+f"(d[59]),"+f"(d[60]),"+f"(d[61]),"+f"(d[62]),"+f"(d[63]),"+f"(d[64]),"+f"(d[65]),"+f"(d[66]),"+f"(d[67]),"+f"(d[68]),"+f"(d[69]),"+f"(d[70]),"+f"(d[71]) : "l"(da), "l"(db), "n"(SC));
}
template<int SC> __device__ __forceinline__ void wg_ss96(float (&d)[48], uint64_t da, uint64_t db) {
  asm volatile("{\n.reg .pred p;\nsetp.ne.b32 p, %50, 0;\nwgmma.mma_async.sync.aligned.m64n96k16.f32.bf16.bf16 {%0,%1,%2,%3,%4,%5,%6,%7,%8,%9,%10,%11,%12,%13,%14,%15,%16,%17,%18,%19,%20,%21,%22,%23,%24,%25,%26,%27,%28,%29,%30,%31,%32,%33,%34,%35,%36,%37,%38,%39,%40,%41,%42,%43,%44,%45,%46,%47}, %48, %49, p, 1, 1, 0, 1;\n}\n"
    : "+f"(d[0]),"+f"(d[1]),"+f"(d[2]),"+f"(d[3]),"+f"(d[4]),"+f"(d[5]),"+f"(d[6]),"+f"(d[7]),"+f"(d[8]),"+f"(d[9]),"+f"(d[10]),"+f"(d[11]),"+f"(d[12]),"+f"(d[13]),"+f"(d[14]),"+f"(d[15]),"+f"(d[16]),"+f"(d[17]),"+f"(d[18]),"+f"(d[19]),"+f"(d[20]),"+f"(d[21]),"+f"(d[22]),"+f"(d[23]),"+f"(d[24]),"+f"(d[25]),"+f"(d[26]),"+f"(d[27]),"+f"(d[28]),"+f"(d[29]),"+f"(d[30]),"+f"(d[31]),"+f"(d[32]),"+f"(d[33]),"+f"(d[34]),"+f"(d[35]),"+f"(d[36]),"+f"(d[37]),"+f"(d[38]),"+f"(d[39]),"+f"(d[40]),"+f"(d[41]),"+f"(d[42]),"+f"(d[43]),"+f"(d[44]),"+f"(d[45]),"+f"(d[46]),"+f"(d[47]) : "l"(da), "l"(db), "n"(SC));
}
template<int SC> __device__ __forceinline__ void wg_rs112(float (&d)[56], uint32_t a0, uint32_t a1, uint32_t a2, uint32_t a3, uint64_t db) {
  asm volatile("{\n.reg .pred p;\nsetp.ne.b32 p, %61, 0;\nwgmma.mma_async.sync.aligned.m64n112k16.f32.bf16.bf16 {%0,%1,%2,%3,%4,%5,%6,%7,%8,%9,%10,%11,%12,%13,%14,%15,%16,%17,%18,%19,%20,%21,%22,%23,%24,%25,%26,%27,%28,%29,%30,%31,%32,%33,%34,%35,%36,%37,%38,%39,%40,%41,%42,%43,%44,%45,%46,%47,%48,%49,%50,%51,%52,%53,%54,%55}, {%56,%57,%58,%59}, %60, p, 1, 1, 0;\n}\n"
    : "+f"(d[0]),"+f"(d[1]),"+f"(d[2]),"+f"(d[3]),"+f"(d[4]),"+f"(d[5]),"+f"(d[6]),"+f"(d[7]),"+f"(d[8]),"+f"(d[9]),"+f"(d[10]),"+f"(d[11]),"+f"(d[12]),"+f"(d[13]),"+f"(d[14]),"+f"(d[15]),"+f"(d[16]),"+f"(d[17]),"+f"(d[18]),"+f"(d[19]),"+f"(d[20]),"+f"(d[21]),"+f"(d[22]),"+f"(d[23]),"+f"(d[24]),"+f"(d[25]),"+f"(d[26]),"+f"(d[27]),"+f"(d[28]),"+f"(d[29]),"+f"(d[30]),"+f"(d[31]),"+f"(d[32]),"+f"(d[33]),"+f"(d[34]),"+f"(d[35]),"+f"(d[36]),"+f"(d[37]),"+f"(d[38]),"+f"(d[39]),"+f"(d[40]),"+f"(d[41]),"+f"(d[42]),"+f"(d[43]),"+f"(d[44]),"+f"(d[45]),"+f"(d[46]),"+f"(d[47]),"+f"(d[48]),"+f"(d[49]),"+f"(d[50]),"+f"(d[51]),"+f"(d[52]),"+f"(d[53]),"+f"(d[54]),"+f"(d[55]) : "r"(a0), "r"(a1), "r"(a2), "r"(a3), "l"(db), "n"(SC));
}
template<int SC> __device__ __forceinline__ void wg_sp48(float (&d)[24], uint32_t a0, uint32_t a1, uint32_t a2, uint32_t a3, uint64_t db, uint32_t meta) {
  asm volatile("{\n.reg .pred p;\nsetp.ne.b32 p, %30, 0;\nwgmma.mma_async.sp.sync.aligned.m64n48k32.f32.bf16.bf16 {%0,%1,%2,%3,%4,%5,%6,%7,%8,%9,%10,%11,%12,%13,%14,%15,%16,%17,%18,%19,%20,%21,%22,%23}, {%24,%25,%26,%27}, %28, %29, 0, p, 1, 1, 1;\n}\n"
    : "+f"(d[0]),"+f"(d[1]),"+f"(d[2]),"+f"(d[3]),"+f"(d[4]),"+f"(d[5]),"+f"(d[6]),"+f"(d[7]),"+f"(d[8]),"+f"(d[9]),"+f"(d[10]),"+f"(d[11]),"+f"(d[12]),"+f"(d[13]),"+f"(d[14]),"+f"(d[15]),"+f"(d[16]),"+f"(d[17]),"+f"(d[18]),"+f"(d[19]),"+f"(d[20]),"+f"(d[21]),"+f"(d[22]),"+f"(d[23]) : "r"(a0), "r"(a1), "r"(a2), "r"(a3), "l"(db), "r"(meta), "n"(SC));
}
template<int SC> __device__ __forceinline__ void wg_rs64(float (&d)[32], uint32_t a0, uint32_t a1, uint32_t a2, uint32_t a3, uint64_t db) {
  asm volatile("{\n.reg .pred p;\nsetp.ne.b32 p, %37, 0;\nwgmma.mma_async.sync.aligned.m64n64k16.f32.bf16.bf16 {%0,%1,%2,%3,%4,%5,%6,%7,%8,%9,%10,%11,%12,%13,%14,%15,%16,%17,%18,%19,%20,%21,%22,%23,%24,%25,%26,%27,%28,%29,%30,%31}, {%32,%33,%34,%35}, %36, p, 1, 1, 0;\n}\n"
    : "+f"(d[0]),"+f"(d[1]),"+f"(d[2]),"+f"(d[3]),"+f"(d[4]),"+f"(d[5]),"+f"(d[6]),"+f"(d[7]),"+f"(d[8]),"+f"(d[9]),"+f"(d[10]),"+f"(d[11]),"+f"(d[12]),"+f"(d[13]),"+f"(d[14]),"+f"(d[15]),"+f"(d[16]),"+f"(d[17]),"+f"(d[18]),"+f"(d[19]),"+f"(d[20]),"+f"(d[21]),"+f"(d[22]),"+f"(d[23]),"+f"(d[24]),"+f"(d[25]),"+f"(d[26]),"+f"(d[27]),"+f"(d[28]),"+f"(d[29]),"+f"(d[30]),"+f"(d[31]) : "r"(a0), "r"(a1), "r"(a2), "r"(a3), "l"(db), "n"(SC));
}

constexpr uint32_t SBC = 1024;
constexpr int ROWB = 2 * 224 * 384;
constexpr int TB = 11;
constexpr int KS = 832;
constexpr int KSLOT = 22 * KS;
constexpr int SM_X = 0;
constexpr int SM_W = SM_X + 3 * 24576;
constexpr int SM_K = SM_W + 55296;
constexpr int SM_V = SM_K + 2 * KSLOT;
constexpr int SM_Q = SM_V + 22 * 1536;
constexpr int SM_O = SM_Q + 12288;
constexpr int SM_S = SM_O + 12288;
constexpr int SM_RPB = SM_S + 6144;
constexpr int SM_BAR = SM_RPB + 768;
constexpr int SM_A_TOTAL = SM_BAR + 256;
constexpr int SM_TIN0 = SM_X + 24576, SM_TIN1 = SM_X, SM_TIN2 = SM_W + 18432;
constexpr int SM_TWO = SM_X + 2 * 24576;
constexpr int SM_TST = SM_TIN2 + 24576;
enum { B_FULL = 0, B_EMPTY = 3, B_TIN = 6, B_TFREE = 10, B_WK = 12, B_WQ, B_WO, B_KIMP, B_VIMP, B_OFREE, B_XK, B_XV,
       B_Q0, B_WOFREE, B_OTAIL, B_ODONE = B_OTAIL + 4, B_KFREE, B_VFREE, B_COUNT };
enum { N_KRDY = 4, N_QK0, N_QK1, N_VQ0, N_VQ1, N_PVISS, N_Q0 };

#define NL 2
#define OCH 16
#define MID 6
#define SPL 4
#define RA 160
#define RG 168
#define OPT 0
constexpr int FS = 64;
__device__ int g_flags[TB * 56 * FS];

#define TR(role, it, k)
#define TRDECL
#define TRARG
#define TRPASS
#define TRDUMP
#define TRB(it, k)
#define TR2START
#define TR2FLUSH(blk)
#define TR2(blk, k)

struct Stage { uint32_t lo, full, em, par; };
struct GemmCtx {
  uint32_t bar;
  uint32_t kC, vC[2], qC[2];
  uint32_t kH, vH[2];
  uint32_t hiA, hiB;
  uint32_t spin;
  bool hvalid, never, edge;
};

template <int STRIDE> __device__ __forceinline__ void dump12(uint32_t a, const uint32_t (&r)[12]) {
#pragma unroll
  for (int j = 0; j < 3; j++) stsm4(a + j * 2 * STRIDE, r[4 * j], r[4 * j + 1], r[4 * j + 2], r[4 * j + 3]);
}
__device__ __forceinline__ void keep12(bool never, uint32_t a, const uint32_t (&r)[12]) { if (never) dump12<128>(a, r); }
template <int N> __device__ __forceinline__ void pack12(uint32_t (&r)[12], const float (&d)[N], int off) {
#pragma unroll
  for (int j = 0; j < 12; j++) r[j] = pack2(d[off + 2 * j], d[off + 2 * j + 1]);
}
__device__ __forceinline__ uint64_t dsc(uint64_t lo, uint32_t hi) { uint64_t r; asm("mov.b64 %0, {%1, %2};" : "=l"(r) : "r"((uint32_t)lo), "r"(hi)); return r; }
template <int K0, int K1> __device__ __forceinline__ void issue_core(const GemmCtx& c, const Stage& x, float (&d)[72]) {
  constexpr uint64_t db = mkdesc(SBC + SM_W, 6144, 256, 3);
  wg_fence();
  if (K0 == 0) wg_ss144<0>(d, dsc(x.lo, c.hiA), dsc(db, c.hiB));
#pragma unroll
  for (int k = K0 ? K0 : 1; k < K1; k++) wg_ss144<1>(d, dsc(x.lo + (k >> 2) * 512 + (k & 3) * 2, c.hiA), dsc(db + k * 32, c.hiB));
  wg_commit();
}
template <int K0, int K1> __device__ __forceinline__ void issue_halo(const GemmCtx& c, const Stage& x, float (&d)[48]) {
  constexpr uint64_t db = mkdesc(SBC + SM_W + 18432, 6144, 256, 3);
  wg_fence();
  if (K0 == 0) wg_ss96<0>(d, dsc(x.lo, c.hiA), dsc(db, c.hiB));
#pragma unroll
  for (int k = K0 ? K0 : 1; k < K1; k++) wg_ss96<1>(d, dsc(x.lo + (k >> 2) * 384 + (k & 3) * 2, c.hiA), dsc(db + k * 32, c.hiB));
  wg_commit();
}
__device__ __forceinline__ void release_stage(const Stage& x) {
  asm volatile("{\n.reg .pred p;\nelect.sync _|p, 0xffffffff;\n@p mbarrier.arrive.shared::cluster.b64 _, [%0];\n}" ::"r"(x.em) : "memory");
}
__device__ __forceinline__ void wait_stage(GemmCtx& c, Stage& x) {
  asm volatile("{\n.reg .pred p;\nWL:\nmbarrier.try_wait.parity.shared::cta.b64 p, [%1], %2;\n@p bra WD;\n"
               "add.u32 %0, %0, 1;\nsetp.lt.u32 p, %0, 0x100000;\n@p bra WL;\nWD:\n}" : "+r"(c.spin) : "r"(x.full), "r"(x.par) : "memory");
  x.par ^= 1;
}
__device__ __forceinline__ void edge_ready(const GemmCtx& c, int bar) { __syncwarp(); if (c.edge) mbar_arrive_elect(c.bar + bar * 8); }
__device__ __forceinline__ void dump6(uint32_t a, const uint32_t (&r)[6]) {
  stsm4(a, r[0], r[1], r[2], r[3]);
  asm volatile("stmatrix.sync.aligned.m8n8.x2.shared.b16 [%0], {%1,%2};" ::"r"(a + 512), "r"(r[4]), "r"(r[5]) : "memory");
}
__device__ __forceinline__ void pack6(uint32_t (&r)[6], const float (&d)[48], int off) {
#pragma unroll
  for (int j = 0; j < 6; j++) r[j] = pack2(d[off + 4 * j], d[off + 4 * j + 1]);
}
template <int PARITY> __device__ __forceinline__ void gwait(GemmCtx& c, int bar) {
  asm volatile("{\n.reg .pred p;\nWL:\nmbarrier.try_wait.parity.shared::cta.b64 p, [%1], %2;\n@p bra WD;\n"
               "add.u32 %0, %0, 1;\nsetp.lt.u32 p, %0, 0x100000;\n@p bra WL;\nWD:\n}" : "+r"(c.spin) : "r"(c.bar + bar * 8), "n"(PARITY) : "memory");
}
__device__ __forceinline__ void load_w(const CUtensorMap* m, uint32_t dst, uint32_t bar, int col) {
  asm volatile("cp.async.bulk.tensor.2d.shared::cluster.global.mbarrier::complete_tx::bytes [%0], [%1, {%3,%4}], [%2];"
               ::"r"(dst), "l"(m), "r"(bar), "r"(col), "r"(0) : "memory");
}
template <int BYTES> __device__ __forceinline__ void send_o(uint32_t dst, uint32_t src, uint32_t bar, int cta) {
  asm volatile("{\n.reg .b32 rd, rb;\nmapa.shared::cluster.u32 rd, %0, %3;\nmapa.shared::cluster.u32 rb, %2, %3;\n"
               "cp.async.bulk.shared::cluster.shared::cta.mbarrier::complete_tx::bytes [rd], [%1], %4, [rb];\n}"
               ::"r"(dst), "r"(src), "r"(bar), "r"(cta), "n"(BYTES) : "memory");
}
__device__ __forceinline__ void remote_arrive(uint32_t rbar) { asm volatile("mbarrier.arrive.shared::cluster.b64 _, [%0];" ::"r"(rbar) : "memory"); }
__device__ __forceinline__ void remote_expect(uint32_t rbar, uint32_t bytes) {
  asm volatile("mbarrier.arrive.expect_tx.shared::cluster.b64 _, [%0], %1;" ::"r"(rbar), "r"(bytes) : "memory");
}
__device__ __forceinline__ void copy_remote(uint32_t rdst, uint32_t src, uint32_t bytes, uint32_t rbar) {
  asm volatile("cp.async.bulk.shared::cluster.shared::cta.mbarrier::complete_tx::bytes [%0], [%1], %2, [%3];" ::"r"(rdst), "r"(src), "r"(bytes), "r"(rbar) : "memory");
}
__device__ __forceinline__ void tail_free(uint32_t bar) {
  uint32_t ln; asm volatile("mov.u32 %0, %%laneid;" : "=r"(ln));
  if (ln < 4) mbar_arrive_remote(bar, ln + (blockIdx.x & 4));
}
__device__ __forceinline__ void publish(uint32_t bar) {
  fence_async();
  __syncwarp();
  mbar_arrive_elect(bar);
}

template <bool FIRST, int PA>
__device__ __forceinline__ void gemm_iter(GemmCtx& c, int b, uint32_t (&pk)[12], uint32_t (&pv)[12], uint32_t (&pq)[12],
                                          uint32_t (&hk1)[6], uint32_t (&hv1)[6], Stage& x0, Stage& x2, Stage& x1 TRARG) {
  const uint32_t bar = c.bar;
  const bool w = !FIRST && (PA == 0 || b >= 0), never = c.never;
  constexpr uint32_t ko = PA * KSLOT;
  float C[72];
  uint32_t hk0[6], hv0[6], pv2[12];
  TR(2, b, 0);
  if (FIRST) wait_stage(c, x0);
  else dump12<128>(c.qC[1], pq);
  if (w) nb_sync(N_QK1, 256);
  TR(2, b, 2);
  if (FIRST) TR(2, b - 1, 6);
  if (PA == 0) {
    float H[48];
    issue_halo<0, 8>(c, x0, H);
    TR(2, b, 3);
    if (!FIRST) { gwait<0>(c, B_KFREE); dump12<128>(c.kC, pk); }
    issue_halo<8, 12>(c, x0, H);
    TR(2, b, 4);
    wait_stage(c, x2);
    if (FIRST) TR(2, b - 1, 7);
    if (FIRST) gwait<0>(c, B_WQ);
    if (FIRST) TR(2, b - 1, 8);
    issue_core<0, 8>(c, x2, C);
    TR(2, b, 5);
    if (!FIRST) { fence_async(); keep12(never, c.kC, pk); }
    wg_wait<1>(); pin(H);
    release_stage(x0);
    pack6(hk0, H, 0);
    if (c.hvalid) dump6(c.kH, hk0);
    pack6(hk1, H, 2); pack6(hv0, H, 24); pack6(hv1, H, 26);
  } else {
    issue_core<0, 8>(c, x2, C);
    TR(2, b, 5);
    fence_async();
    keep12(never, c.kC, pq);
    if (w) gwait<1>(c, B_KFREE);
    dump12<128>(c.kC + ko, pk);
    if (c.hvalid) dump6(c.kH + ko, hk1);
  }
  TR(2, b, 13);
  issue_core<8, 12>(c, x2, C);
  if (w) { nb_arrive(N_VQ0, 288); nb_arrive(N_VQ1, 288); }
  else if (!FIRST) { __syncwarp(); mbar_arrive_elect(bar + B_Q0 * 8); }
  wait_stage(c, x1);
  if (never) dump6(bar, PA ? hk1 : hk0);
  TR(2, b, 6);
  wg_wait<0>(); pin(C);
  TR(2, b, 7);
  release_stage(x2);
  pack12(pk, C, 24);
  dump12<128>(c.kC + ko + 64, pk);
  pack12(pv2, C, 48);
  pack12(pq, C, 0);
  TR(2, b, 8);
  issue_core<0, SPL>(c, x1, C);
  TR(2, b, 9);
  if (!FIRST) { fence_async(); edge_ready(c, B_XK); }
  keep12(never, c.kC, pk);
  TR(2, b, 14);
  if (w) nb_sync(N_PVISS, 384);
  issue_core<SPL, 12>(c, x1, C);
  if (!FIRST) nb_arrive(N_KRDY, 256);
  TR(2, b, 1);
  if (PA && b == 11) tail_free(bar + B_TFREE * 8);
  wait_stage(c, x0);
  if (w) gwait<PA>(c, B_VFREE);
  if (w && b < TB) gwait<PA>(c, B_ODONE);
  TR(2, b, 10);
  if (!FIRST) dump12<128>(c.vC[PA], pv);
  dump12<128>(c.vC[PA ^ 1] + 768, pv2);
  TR(2, b, 11);
  wg_wait<0>(); pin(C);
  TR(2, b, 12);
  release_stage(x1);
  if (!FIRST && c.edge) publish(bar + B_XV * 8);
  if (c.hvalid) dump6(c.vH[PA], PA ? hv1 : hv0);
  if (PA && !w) nb_sync(N_Q0, 384);
  dump12<128>(c.qC[0], pq);
  pack12(pk, C, 24);
  pack12(pv, C, 48);
  pack12(pq, C, 0);
}

template <int IN> __device__ __forceinline__ void issue_proj(float (&D)[48]) {
  constexpr uint64_t da = mkdesc(SBC + IN, 128, 768, 0), db = mkdesc(SBC + SM_TWO, 12288, 512, 2);
  wg_fence();
  wg_ss96<0>(D, da, db);
#pragma unroll
  for (int k = 1; k < 12; k++) wg_ss96<1>(D, da + (k / 3) * 384 + (k % 3) * 16, db + k * 64);
  wg_commit();
}
template <int ACC> __device__ __forceinline__ void issue_proj_half(float (&D)[48], int hd) {
  const uint64_t da = mkdesc(SBC + SM_TIN2, 128, 768, 0) + hd * 384, db = mkdesc(SBC + SM_TWO, 12288, 512, 2) + hd * 192;
  wg_fence();
  wg_ss96<ACC>(D, da, db);
#pragma unroll
  for (int k = 1; k < 6; k++) wg_ss96<1>(D, da + (k / 3) * 768 + (k % 3) * 16, db + (k / 3) * 384 + (k % 3) * 64);
  wg_commit();
}
__device__ __forceinline__ void store_proj(const float (&D)[48], const CUtensorMap* m, uint32_t st, uint32_t sta, int row, int col, int ch) {
#pragma unroll
  for (int q = 0; q < 6; q++)
    stsm4((sta ^ ((q & 1) * 32)) + (q >> 1) * 1024,
          pack2(D[8 * q], D[8 * q + 1]), pack2(D[8 * q + 2], D[8 * q + 3]), pack2(D[8 * q + 4], D[8 * q + 5]), pack2(D[8 * q + 6], D[8 * q + 7]));
  fence_async();
  __syncwarp();
  if ((threadIdx.x & 31) == 0) {
    asm volatile("cp.async.bulk.tensor.4d.global.shared::cta.bulk_group [%0, {%2,%3,%4,%5}], [%1];" ::"l"(m), "r"(st), "r"(0), "r"(row), "r"(col), "r"(ch) : "memory");
    asm volatile("cp.async.bulk.commit_group;" ::: "memory");
  }
  __syncwarp();
}

__device__ __forceinline__ float fold(float a, float b, float t, int useb) {
  float r;
  asm("{\n.reg .pred p;\nsetp.ne.b32 p, %4, 0;\nfma.rn.f32 %0, %1, 0f3E553B95, %3;\n@p fma.rn.f32 %0, %2, 0f3E553B95, %3;\n}"
      : "=&f"(r) : "f"(a), "f"(b), "f"(t), "r"(useb));
  return r;
}
template <int U, int L>
__device__ __forceinline__ void softmax_tile(const float (&SA)[56], const float (&SB)[56], const float (&T)[16], int b0, int b1,
                                             uint32_t (&P)[28], float (&sx)[8], uint32_t nbV, uint32_t zero, uint32_t qa, uint32_t (&q)[12]) {
  float lu[14], ll[14];
#pragma unroll
  for (int j = 0; j < 7; j++) {
    constexpr int sh = U == L ? 2 : 0;
    const float tu0 = T[2 * j + sh], tu1 = T[2 * j + 1 + sh], tl0 = T[2 * j], tl1 = T[2 * j + 1];
    lu[2 * j]     = fold(SA[4 * (U + j)],     SB[4 * (U + j)],     tu0, b0);
    ll[2 * j]     = fold(SA[4 * (L + j) + 2], SB[4 * (L + j) + 2], tl0, b0);
    lu[2 * j + 1] = fold(SA[4 * (U + j) + 1], SB[4 * (U + j) + 1], tu1, b1);
    ll[2 * j + 1] = fold(SA[4 * (L + j) + 3], SB[4 * (L + j) + 3], tl1, b1);
  }
  float mu = lu[0], ml = ll[0], mu2 = lu[1], ml2 = ll[1];
#pragma unroll
  for (int j = 1; j < 7; j++) { mu = fmaxf(mu, lu[2 * j]); mu2 = fmaxf(mu2, lu[2 * j + 1]); ml = fmaxf(ml, ll[2 * j]); ml2 = fmaxf(ml2, ll[2 * j + 1]); }
  mu = fmaxf(mu, mu2); ml = fmaxf(ml, ml2);
  { const float a1 = __shfl_xor_sync(0xffffffffu, mu, 1), a2 = __shfl_xor_sync(0xffffffffu, mu, 2), a3 = __shfl_xor_sync(0xffffffffu, mu, 3);
    const float c1 = __shfl_xor_sync(0xffffffffu, ml, 1), c2 = __shfl_xor_sync(0xffffffffu, ml, 2), c3 = __shfl_xor_sync(0xffffffffu, ml, 3);
    mu = fmaxf(fmaxf(mu, a1), fmaxf(a2, a3)); ml = fmaxf(fmaxf(ml, c1), fmaxf(c2, c3)); }
  float su = 0.f, sl = 0.f;
#pragma unroll
  for (int c = 0; c < 14; c++) {
    if (c >= U && c < U + 7) {
      float e0 = ex2(lu[2 * (c - U)] - mu), e1 = ex2(lu[2 * (c - U) + 1] - mu);
      su = c == U ? e0 + e1 : (su + e0) + e1; P[2 * c] = pack2(e0, e1);
    } else P[2 * c] = 0u;
  }
  nb_sync(nbV | (P[2 * (U + MID)] & zero), 288);
#pragma unroll
  for (int k = 0; k < 3; k++) ldsm4(qa + k * 256, q[4 * k], q[4 * k + 1], q[4 * k + 2], q[4 * k + 3]);
#pragma unroll
  for (int c = 0; c < 14; c++) {
    if (c >= L && c < L + 7) {
      float e0 = ex2(ll[2 * (c - L)] - ml), e1 = ex2(ll[2 * (c - L) + 1] - ml);
      sl = c == L ? e0 + e1 : (sl + e0) + e1; P[2 * c + 1] = pack2(e0, e1);
    } else P[2 * c + 1] = 0u;
  }
  sx[0] = su; sx[4] = sl;
#pragma unroll
  for (int k = 1; k < 4; k++) sx[k] = __shfl_xor_sync(0xffffffffu, su, k);
#pragma unroll
  for (int k = 1; k < 4; k++) sx[4 + k] = __shfl_xor_sync(0xffffffffu, sl, k);
}

struct BandCfg { uint32_t ra0, ra1, meta; int b0, b1; };
__device__ __forceinline__ void band_cfg(int b, uint32_t tb, BandCfg& n) {
  uint32_t ln; asm volatile("mov.u32 %0, %%laneid;" : "=r"(ln));
  const int g = ln >> 2, t = ln & 3;
  const int sw = min(max(g + 1, b == 0 ? 4 : 0), b == 13 ? 5 : 8);
  const int i0 = 2 * t, i1 = 2 * t + 1;
  n.b0 = i0 <= sw - 2; n.b1 = i1 <= sw - 2;
  n.ra0 = tb + (i0 == sw - 1 ? 13 : i0 + 8 * n.b0 - g + 2) * 52;
  n.ra1 = tb + (i1 == sw - 1 ? 13 : i1 + 8 * n.b1 - g + 2) * 52;
  n.meta = ((0x5555u & ((1u << (2 * (sw - 1))) - 1)) ^ 0xDD88u ^ (((t ^ b) & 1) ? 0x5555u : 0u)) * 0x10001u;
}
__device__ __forceinline__ void band_load(const BandCfg& n, float (&T)[16], int& b0, int& b1, uint32_t& meta) {
#pragma unroll
  for (int jj = 0; jj < 8; jj++) { T[2 * jj] = lds_f32(n.ra0 + jj * 4); T[2 * jj + 1] = lds_f32(n.ra1 + jj * 4); }
  b0 = n.b0; b1 = n.b1; meta = n.meta;
}

struct Maps { CUtensorMap xc, xh, w, os, wo, ot; };

__global__ void __cluster_dims__(8, 1, 1) __launch_bounds__(512, 1)
na_attn_kernel(const __nv_bfloat16* __restrict__ x, const __nv_bfloat16* __restrict__ wqkv, const __nv_bfloat16* __restrict__ rpb, const __grid_constant__ Maps mp) {
  extern __shared__ __align__(1024) uint8_t smem_raw[];
  const uint32_t sb = smem_u32(smem_raw);
  if ((sb & 0x3FFFF) != SBC) return;
  const uint32_t bar = sb + SM_BAR;
  TR2START;
  const int tid = threadIdx.x, lane = tid & 31;
  const int warp = __shfl_sync(0xffffffffu, tid >> 5, 0);
  const int head = blockIdx.x & 3, base = blockIdx.x & 4, sp = blockIdx.x >> 2;
  const int par = sp < 24 ? sp / 6 : sp - 24, strip = sp < 24 ? sp - par * 6 : 6, ph = par >> 1, pw = par & 1;
  const int odd = strip & 1;

  uint4 wv[2 * NL];
  const int va = head == 1;
  const uint32_t wdst = sb + SM_W + (3 + va + ((tid >> 1) & 1)) * 6144 + (tid >> 2) * 32 + ((tid ^ (tid >> 4)) & 1) * 16;
  if (warp < 12) {
    asm volatile("barrier.cluster.arrive.relaxed.aligned;" ::: "memory");
    const uint32_t wo0 = (tid >> 2) * 1152 + head * 96 + va * 32 + (tid & 3) * 16;
#pragma unroll
    for (int i = 0; i < 2 * NL; i++)
      asm volatile("ld.global.nc.v4.b32 {%0,%1,%2,%3}, [%4];" : "=r"(wv[i].x), "=r"(wv[i].y), "=r"(wv[i].z), "=r"(wv[i].w)
                   : "l"(reinterpret_cast<const uint8_t*>(wqkv) + wo0 + (i & 1) * 96 * 1152 + (i / 2 + 1) * 384));
  }
  if (warp < 8) {
    asm volatile("setmaxnreg.inc.sync.aligned.u32 %0;" ::"n"(RA));
    float rv = -INFINITY;
    if (tid < 169) rv = __bfloat162float(rpb[head * 169 + tid]) * 1.4426950408889634f;
    if (tid < 192) {
      const int kc = (tid & 15) + 3, wc = (tid >> 4) % 6;
      sts128(tid < 96 ? sb + SM_K + kc * KS + wc * 128 + 48 : sb + SM_V + kc * 1536 + wc * 128 + (6 + (kc & 1)) * 16, make_uint4(0, 0, 0, 0));
    }
#pragma unroll
    for (int i = 0; i < 2 * NL; i++) sts128(wdst + (i & 1) * 3072 + (i / 2) * 18432, wv[i]);
    fence_async();
    asm volatile("bar.arrive 1, 384;" ::: "memory");
    if (tid < 182) asm volatile("st.shared.f32 [%0], %1;" ::"r"(sb + SM_RPB + tid * 4), "f"(rv) : "memory");
    const int jw = warp >> 2, j = jw ^ odd, w = warp & 3, wt = 4 * j + w;
    int variant = w;
    if (strip == 0 && j == 0 && w < 2) variant = 4;
    if (strip == 6 && j == 1 && w >= 2) variant = 5;
    const bool v1 = opq((uint32_t)(variant & 1)), v2 = opq((uint32_t)(variant & 2)), v4 = opq((uint32_t)(variant & 4));
    const uint32_t qa = opq(sb + SM_Q + (8 * j + 2 * w + ((lane >> 3) & 1)) * 768 + (lane >> 4) * 128 + (((lane & 7) * 16) ^ (((lane >> 3) & 1) * 64)));
    uint32_t oa = opq(sb + SM_O + j * 6144 + (2 * w + ((lane >> 3) & 1)) * 768 + (lane >> 4) * 128 + (lane & 7) * 16);
    uint64_t dA = opq(mkdesc(SBC + SM_K, 128, KS, 0) + j * (8 * KS / 16)), dB = opq(dA + (KSLOT >> 4));
    uint64_t dV[7];
#pragma unroll
    for (int i = 0; i < 7; i++) dV[i] = opq(mkdesc(SBC + SM_V, 768, 128, 0) + j * (8 * 1536 / 16) + i * 192);
    const uint32_t nbK = opq((uint32_t)(N_KRDY + jw)), nbQ = opq((uint32_t)(N_QK0 + jw)), nbV = opq((uint32_t)(N_VQ0 + jw));
    asm volatile("barrier.cluster.wait.aligned;" ::: "memory");
    asm volatile("bar.sync 3, 256;" ::: "memory");
    float T[16];
    TRDECL;
    int b0, b1;
    uint32_t meta, ob = bar + B_ODONE * 8, fb = bar + B_OFREE * 8, fp = 1;
    const uint32_t tb = opq(sb + SM_RPB + (variant < 4 ? 3 : variant + 1 - 2 * w) * 4);
    const bool own = ((w ^ head) & 2) == 0;
    const uint32_t dst13 = sb + SM_TIN2 + head * 6144 + (2 * j + (w & 1)) * 1536, src13 = opq(own ? dst13 : sb + SM_S + (2 * j + (w & 1)) * 1536);
    const uint32_t snd[4] = {opq(own ? 0u : mapa(dst13, base + (head ^ 2))), opq(mapa(bar + (B_TIN + 2) * 8, base + (head ^ 2))),
                             opq(mapa(dst13, base + (w & 2) + (~head & 1))), opq(mapa(bar + (B_TIN + 3) * 8, base + (w & 2) + (~head & 1)))};
    BandCfg nx;
    band_cfg(0, tb, nx);
    band_load(nx, T, b0, b1, meta);
    band_cfg(1, tb, nx);
    const uint32_t zero = opq(blockIdx.x >> 16);
    uint32_t special = opq(0x380Au << 1);
    uint32_t q[12];
    mbar_wait(bar + B_Q0 * 8, 0);
#pragma unroll
    for (int k = 0; k < 3; k++) ldsm4(qa + k * 256, q[4 * k], q[4 * k + 1], q[4 * k + 2], q[4 * k + 3]);
    nb_arrive(N_Q0, 384);
#pragma unroll 1
    for (int b = 0; b < 14; b++) {
      float SA[56], SB[56];
      TR(0, b, 0);
      if (jw) mbar_wait(bar + B_KIMP * 8, b & 1);
      nb_sync(nbK, 256);
      TR(0, b, 1);
      TR(0, b - 1, 9);
      wg_fence();
      wg_rs112<0>(SA, q[0], q[1], q[2], q[3], dA);
      wg_rs112<0>(SB, q[0], q[1], q[2], q[3], dB);
      wg_rs112<1>(SA, q[4], q[5], q[6], q[7], dA + 16);
      wg_rs112<1>(SB, q[4], q[5], q[6], q[7], dB + 16);
      wg_rs112<1>(SA, q[8], q[9], q[10], q[11], dA + 32);
      wg_rs112<1>(SB, q[8], q[9], q[10], q[11], dB + 32);
      wg_commit();
      nb_arrive(nbQ, 256);
      { const uint64_t t = dA; dA = dB; dB = t; }
      special >>= 1;
      if (special & 1) {
        if (b == 3) band_cfg(13, tb, nx);
        else {
          if (b == 1 || b == 13) band_load(nx, T, b0, b1, meta);
          if (b >= TB) {
            ob = bar + (b == 13 ? (own ? B_TIN + 2 : B_ODONE) : B_OTAIL + 2 * (b - TB) + jw) * 8;
            if (b > TB) { fb = bar + (B_TFREE + b - 12) * 8; fp = 0; }
            oa += b == 12 ? 0u - (SM_O - SM_Q) : (b == 13 ? src13 - (sb + SM_Q + wt * 1536) : 0);
          }
        }
      }
      TR(0, b, 2);
      wg_wait<0>(); pin(SA); pin(SB);
      mbar_arrive_elect(bar + B_KFREE * 8);
      TR(0, b, 3);
      TR(0, b - 1, 10);
      uint32_t P[28];
      float sx[8];
      if (v2) {
        if (v1) softmax_tile<6, 7>(SA, SB, T, b0, b1, P, sx, nbV, zero, qa, q); else softmax_tile<4, 5>(SA, SB, T, b0, b1, P, sx, nbV, zero, qa, q);
      } else if (!v4) {
        if (v1) softmax_tile<2, 3>(SA, SB, T, b0, b1, P, sx, nbV, zero, qa, q); else softmax_tile<0, 1>(SA, SB, T, b0, b1, P, sx, nbV, zero, qa, q);
      } else {
        if (v1) softmax_tile<4, 4>(SA, SB, T, b0, b1, P, sx, nbV, zero, qa, q); else softmax_tile<3, 3>(SA, SB, T, b0, b1, P, sx, nbV, zero, qa, q);
      }
      float O[24];
      TR(0, b, 4);
      wg_fence();
      wg_sp48<0>(O, P[0], P[1], P[2], P[3], dV[0], meta);
#pragma unroll
      for (int s = 1; s < 7; s++) wg_sp48<1>(O, P[4 * s], P[4 * s + 1], P[4 * s + 2], P[4 * s + 3], dV[s], meta);
      wg_commit();
      nb_arrive(N_PVISS, 384);
      TR(0, b, 6);
      mbar_wait(fb, fp);
      wg_wait<0>(); pin(O);
      mbar_arrive_elect(bar + B_VFREE * 8);
      TR(0, b, 7);
      float ru, rl;
      asm("rcp.approx.ftz.f32 %0, %1;" : "=f"(ru) : "f"(((fmaf(O[0], 0.f, sx[0]) + sx[1]) + sx[2]) + sx[3]));
      asm("rcp.approx.ftz.f32 %0, %1;" : "=f"(rl) : "f"(((fmaf(O[2], 0.f, sx[4]) + sx[5]) + sx[6]) + sx[7]));
#pragma unroll
      for (int i = 0; i < 3; i++)
        stsm4(oa + i * 256, pack2(O[8 * i] * ru, O[8 * i + 1] * ru), pack2(O[8 * i + 2] * rl, O[8 * i + 3] * rl),
              pack2(O[8 * i + 4] * ru, O[8 * i + 5] * ru), pack2(O[8 * i + 6] * rl, O[8 * i + 7] * rl));
      publish(ob);
      fp ^= 1;
      meta ^= 0x55555555u;
      TR(0, b, 8);
    }
    asm volatile("{\n.reg .pred p, q;\nsetp.ne.b32 q, %1, 0;\nelect.sync _|p, 0xffffffff;\nand.pred q, q, p;\n"
                 "@q cp.async.bulk.shared::cluster.shared::cta.mbarrier::complete_tx::bytes [%1], [%0], 1536, [%2];\n"
                 "@p cp.async.bulk.shared::cluster.shared::cta.mbarrier::complete_tx::bytes [%3], [%0], 1536, [%4];\n}"
                 ::"r"(src13), "r"(snd[0]), "r"(snd[1]), "r"(snd[2]), "r"(snd[3]) : "memory");
    if (jw == 0) nb_arrive(3, 256);
    TRDUMP;
    cluster_sync();
  } else if (warp < 12) {
    TRDECL;
    TR(2, -3, 0);
    asm volatile("setmaxnreg.inc.sync.aligned.u32 %0;" ::"n"(RG));
    TR(2, -3, 1);
    GemmCtx c;
    c.bar = bar;
    const int gw = warp - 8, tk = gw * 16 + (lane & 15), hi = lane >> 4;
    { const int col = tk >> 2, i = tk & 3;
      c.kC = sb + SM_K + (col + 3) * KS + hi * 128 + i * 16;
      c.vC[0] = sb + SM_V + (col + 3) * 1536 + hi * 128 + (2 * i + ((col + 3) & 1)) * 16;
      c.qC[0] = sb + SM_Q + col * 768 + hi * 128 + (col & 1) * 64 + i * 16; }
    { const int kc = gw - 1 + 19 * odd, i = lane & 7; c.hvalid = gw > 0; c.edge = gw == (odd ? 0 : 3);
      c.kH = sb + SM_K + kc * KS + (lane >> 3) * 128 + i * 16;
      c.vH[0] = sb + SM_V + kc * 1536 + (lane >> 3) * 128 + (i >> 2) * 768 + (2 * (i & 3) + ((kc ^ (i >> 2)) & 1)) * 16; }
    Stage xs[3];
#pragma unroll
    for (int i = 0; i < 3; i++) {
      const int p = (i + 1) % 3;
      xs[i].lo = (uint32_t)mkdesc(SBC + SM_X + p * 24576, 16, 0, 0); xs[i].full = bar + (B_FULL + p) * 8;
      xs[i].em = opq(mapa(bar + (B_EMPTY + p) * 8, base + p)); xs[i].par = 0;
    }
    c.never = x == nullptr;
    c.kC = opq(c.kC); c.kH = opq(c.kH);
    c.vC[1] = opq(c.vC[0] ^ 16); c.vC[0] = opq(c.vC[0]);
    c.vH[1] = opq(c.vH[0] ^ 16); c.vH[0] = opq(c.vH[0]);
    c.qC[1] = opq(c.qC[0] ^ 64); c.qC[0] = opq(c.qC[0]);
    c.spin = 0;
    c.hiA = (uint32_t)(mkdesc(0, 0, 1024, 1) >> 32) + (blockIdx.x >> 16); c.hiB = (uint32_t)(mkdesc(0, 0, 256, 3) >> 32) + (blockIdx.x >> 16);
    asm volatile("barrier.cluster.wait.aligned;" ::: "memory");
    TR(2, -3, 2);
#pragma unroll
    for (int i = 0; i < 2 * NL; i++) sts128(wdst + (i & 1) * 3072 + (i / 2) * 18432, wv[i]);
    fence_async();
    TR(2, -3, 3);
    asm volatile("bar.sync 1, 384;" ::: "memory");
    TR(2, -3, 4);
    mbar_wait(bar + B_WK * 8, 0);
    asm volatile("griddepcontrol.launch_dependents;");
    TR(2, -3, 5);
    uint32_t pk[12], pv[12], pq[12], hk1[6], hv1[6];
    gemm_iter<true, 0>(c, -2, pk, pv, pq, hk1, hv1, xs[0], xs[1], xs[2] TRPASS);
    TR2(blockIdx.x, 4);
    c.hiA = opq(c.hiA); c.hiB = opq(c.hiB);
#pragma unroll 1
    for (int b = -1;; b += 2) {
      gemm_iter<false, 1>(c, b, pk, pv, pq, hk1, hv1, xs[2], xs[0], xs[1] TRPASS);
      if (b == 11) break;
      gemm_iter<false, 0>(c, b + 1, pk, pv, pq, hk1, hv1, xs[2], xs[0], xs[1] TRPASS);
      const Stage t = xs[2]; xs[2] = xs[1]; xs[1] = xs[0]; xs[0] = t;
    }
    TR2(blockIdx.x, 6);
    c.hiA = opq(c.hiA); c.hiB = opq(c.hiB);
    const uint32_t st = sb + gw * 3072;
    const uint32_t sta = st + (lane & 15) * 64 + ((hi ^ ((lane >> 1) & 3)) * 16);
    const int oc = ph * 112 + strip * 16 + 8 * (gw >> 1) + 4 * (head >> 1) + 2 * (gw & 1), och = pw * 6 + (head & 1) * 3;
    float D0[48], D1[48];
    mbar_arrive_elect(bar + B_WOFREE * 8);
    dump12<128>(c.qC[1], pq);
    nb_sync(N_QK1, 256);
    issue_halo<0, 8>(c, xs[2], D1);
    fence_async();
    nb_arrive(N_VQ0, 288); nb_arrive(N_VQ1, 288); nb_arrive(N_PVISS, 384);
    issue_halo<8, 12>(c, xs[2], D1);
    gwait<0>(c, B_KFREE);
    dump12<128>(c.kC, pk);
    if (c.edge) publish(bar + B_XK * 8);
    wg_wait<0>(); pin(D1);
    pack6(hk1, D1, 0);
    if (c.hvalid) dump6(c.kH, hk1);
    tail_free(bar + (B_TFREE + 1) * 8);
    pack6(hv1, D1, 24);
    fence_async();
    nb_arrive(N_KRDY, 256);
    gwait<0>(c, B_VFREE);
    dump12<128>(c.vC[0], pv);
    if (c.hvalid) dump6(c.vH[0], hv1);
    fence_async();
    edge_ready(c, B_XV);
    nb_arrive(N_VQ0, 288); nb_arrive(N_VQ1, 288);
    gwait<0>(c, B_WO);
    gwait<0>(c, B_TIN);
    TR(2, 13, 0);
    nb_sync(N_QK1, 256);
    issue_proj<SM_TIN0>(D0);
    wg_wait<0>(); pin(D0);
    TR(2, 13, 1);
    store_proj(D0, &mp.ot, st + SM_TST, sta + SM_TST, 8 * TB, oc, och);
    gwait<0>(c, B_TIN + 1);
    TR(2, 13, 2);
    nb_sync(N_PVISS, 384);
    nb_sync(3, 256);
    issue_proj<SM_TIN1>(D1);
    wg_wait<0>(); pin(D1);
    TR(2, 13, 3);
    store_proj(D1, &mp.ot, st + SM_TIN0, sta + SM_TIN0, 8 * TB + 8, oc, och);
    TR(2, 13, 4);
    gwait<0>(c, B_TIN + 2);
    TR(2, 13, 5);
    issue_proj_half<0>(D0, head & 1);
    gwait<0>(c, B_TIN + 3);
    TR(2, 13, 6);
    issue_proj_half<1>(D0, ~head & 1);
    asm volatile("barrier.cluster.arrive.relaxed.aligned;" ::: "memory");
    wg_wait<0>(); pin(D0);
    store_proj(D0, &mp.ot, st + SM_TIN0 + 12288, sta + SM_TIN0 + 12288, 8 * TB + 16, oc, och);
    TR(2, 13, 7);
    if (lane == 0) asm volatile("cp.async.bulk.wait_group.read 0;" ::: "memory");
    __syncwarp();
    TR(2, 13, 8);
    TR2(blockIdx.x, 2);
    TR2FLUSH(blockIdx.x);
    TRDUMP;
    asm volatile("barrier.cluster.wait.aligned;" ::: "memory");
  } else {
    asm volatile("setmaxnreg.dec.sync.aligned.u32 24;");
    if (warp == 15) {
      const int l = min(lane, 24), row = head + (l < 16 ? 0 : 4 * ((l - 16) / 3)), col = strip * 16 + (l < 16 ? l : (l - 16) % 3 + (odd ? 16 : (strip ? -3 : 0)));
      const uint8_t* p = reinterpret_cast<const uint8_t*>(x) + (uint32_t)(row * ROWB + (ph * 112 + col) * 768 + pw * 384);
#pragma unroll
      for (int i = 0; i < 3; i++) asm volatile("prefetch.global.L2 [%0];" ::"l"(p + i * 128));
    } else if (elect_one()) {
      if (warp == 12) {
        mbar_init(bar + B_WK * 8, 1);
#pragma unroll
        for (int i = 0; i < NL; i++) load_w(&mp.w, sb + SM_W + (3 * i + 5 - 2 * va) * 6144, bar + B_WK * 8, (i + 1) * 192 + head * 48 + 32 - 32 * va);
        asm volatile("prefetch.tensormap [%0];" ::"l"(head == 1 ? &mp.xh : &mp.xc) : "memory");
      } else if (warp == 13) {
#pragma unroll
        for (int i = 0; i < B_XK; i++) if (i != B_WK) mbar_init(bar + i * 8, (i >= B_EMPTY && i < B_TIN) || (i >= B_TFREE && i < B_WK) ? 16 : (i == B_TIN + 2 ? 5 : 1));
      } else {
#pragma unroll
        for (int i = B_XK; i < B_COUNT; i++) mbar_init(bar + i * 8, i < B_Q0 ? 2 : (i < B_ODONE ? 4 : (i == B_VFREE ? 9 : 8)));
      }
      asm volatile("fence.mbarrier_init.release.cluster;" ::: "memory");
    }
    __syncwarp();
    asm volatile("barrier.cluster.arrive.relaxed.aligned;" ::: "memory");
    if (warp != 12) asm volatile("barrier.cluster.wait.aligned;" ::: "memory");
    else {
      const int cc = ph * 112 + strip * 16, ch = cc + (odd ? 16 : (strip ? -3 : 0)), rh = strip ? -4 : 112;
      const uint32_t fb = opq(bar + (B_FULL + head) * 8), dst0 = sb + SM_X + head * 24576, c3 = opq((uint32_t)(pw * 3)), mask = opq(15u << base);
      int t = head == 0 ? 2 : head - 1;
      uint64_t mx = opq((uint64_t)(t ? &mp.xc : &mp.xh));
      uint32_t row = opq((uint32_t)(t ? 4 * t - 4 : rh)), col = opq((uint32_t)(t ? cc : ch)), dst = opq(dst0 + (t ? 0 : 2048));
#pragma unroll 1
      for (int n = 0;; n++) {
        if (n) mbar_wait(fb + (B_EMPTY - B_FULL) * 8, ~n & 1);
        else asm volatile("barrier.cluster.wait.aligned;" ::: "memory");
        if (head < 3) {
          asm volatile("{\n.reg .pred p;\n.reg .b16 m;\nelect.sync _|p, 0xffffffff;\ncvt.u16.u32 m, %7;\n"
                       "@p cp.async.bulk.tensor.4d.shared::cluster.global.mbarrier::complete_tx::bytes.multicast::cluster [%0], [%1, {%3,%4,%5,%6}], [%2], m;\n}"
                       ::"r"(dst), "l"(mx), "r"(fb), "r"(0), "r"(row), "r"(col), "r"(c3), "r"(mask) : "memory");
          if (lane < 4) remote_expect(mapa(fb, base + lane), dst == dst0 ? 24576 : 18432);
          __syncwarp();
        }
        if (n == 0 && elect_one()) {
#pragma unroll
          for (int i = 0; i < 3; i++) load_w(&mp.w, sb + SM_W + i * 6144, bar + B_WQ * 8, head * 48 + i * 16);
          mbar_expect(bar + B_WQ * 8, 18432);
        }
        __syncwarp();
        if (head == 3 || n == 11) break;
        t += 3;
        const int hn = t / 5;
        const bool core = t != 5 * hn;
        mx = opq((uint64_t)(core ? &mp.xc : &mp.xh));
        row = opq((uint32_t)(core ? 4 * (t - hn - 1) : rh + 16 * hn)); col = opq((uint32_t)(core ? cc : ch)); dst = opq(dst0 + (core ? 0 : 2048));
        if (elect_one()) asm volatile("cp.async.bulk.prefetch.tensor.4d.L2.global [%0, {%1,%2,%3,%4}];" ::"l"(mx), "r"(0), "r"(row), "r"(col), "r"(c3) : "memory");
        __syncwarp();
      }
      mbar_wait(bar + B_WOFREE * 8, 0);
      if (elect_one()) {
        mbar_expect(bar + B_WO * 8, 36864);
        asm volatile("cp.async.bulk.tensor.3d.shared::cluster.global.mbarrier::complete_tx::bytes [%0], [%1, {%3,%4,%5}], [%2];"
                     ::"r"(sb + SM_TWO), "l"(&mp.wo), "r"(bar + B_WO * 8), "r"(0), "r"(0), "r"((head & 1) * 3) : "memory");
      }
      __syncwarp();
    }
    if (warp & 1) {
      const uint32_t partner = (blockIdx.x & 7) ^ 4;
      const int cs = odd ? 3 : (strip == 6 ? 15 : 16), cd = odd || strip == 6 ? 19 : 0;
      const uint32_t rb = opq(mapa(bar, partner));
      TRDECL;
      if (warp == 13) {
        const uint32_t dst = opq(mapa(sb + SM_V + cd * 1536, partner)), src = opq(sb + SM_V + cs * 1536);
#pragma unroll 1
        for (int b = 0;; b++) {
          const uint32_t pa = b & 1;
          nb_arrive(N_VQ0, 288);
          mbar_wait(bar + B_XV * 8, pa);
          TR(1, b, 0);
          if (elect_one()) { copy_remote(dst, src, 4608, rb + B_VIMP * 8); remote_expect(rb + B_VIMP * 8, 4608); }
          __syncwarp();
          TR(1, b, 1);
          mbar_wait(bar + B_VIMP * 8, pa);
          TR(1, b, 2);
          nb_arrive(N_VQ1, 288);
          if (elect_one()) remote_arrive(rb + B_VFREE * 8);
          __syncwarp();
          TR(1, b, 3);
          if (b == 13) break;
          mbar_wait(bar + B_VFREE * 8, pa);
          if (elect_one()) remote_arrive(rb + B_XV * 8);
          __syncwarp();
        }
      } else {
        const uint32_t dst = opq(mapa(sb + SM_K + cd * KS, partner)), src = opq(sb + SM_K + cs * KS);
#pragma unroll 1
        for (int b = 0;; b++) {
          const uint32_t pa = b & 1, so = (pa ^ 1) * KSLOT;
          mbar_wait(bar + B_XK * 8, pa);
          TR(1, b - 1, 4);
          if (elect_one()) {
            copy_remote(dst + so, src + so, 3 * KS, rb + B_KIMP * 8);
            if (b == 0) copy_remote(dst, src, 3 * KS, rb + B_KIMP * 8);
            remote_expect(rb + B_KIMP * 8, b ? 3 * KS : 6 * KS);
          }
          __syncwarp();
          TR(1, b - 1, 5);
          TR(1, b - 1, 7);
          if (b == 13) break;
          mbar_wait(bar + B_KFREE * 8, pa);
          if (elect_one()) remote_arrive(rb + B_XK * 8);
          __syncwarp();
        }
      }
      TRDUMP;
    }
    if (warp == 14) {
      int* flag = g_flags + (par * 7 + strip) * 2 * FS;
      if (elect_one()) {
        mbar_expect(bar + B_WK * 8, NL * 6144);
        mbar_arrive(bar + B_XK * 8); mbar_arrive(bar + B_XV * 8);
        mbar_expect(bar + B_TIN * 8, 24576); mbar_expect(bar + (B_TIN + 1) * 8, 24576); mbar_expect(bar + (B_TIN + 2) * 8, 6144); mbar_expect(bar + (B_TIN + 3) * 8, 12288);
      }
      __syncwarp();
#pragma unroll 1
      for (int b = 0; b < TB; b++) {
        mbar_wait(bar + B_ODONE * 8, b & 1);
        if (lane == 0) {
#pragma unroll 1
          for (int i = 0; i < 16; i += OCH) {
            asm volatile("cp.async.bulk.tensor.3d.global.shared::cta.bulk_group [%0, {%2,%3,%4}], [%1];"
                         ::"l"(&mp.os), "r"(sb + SM_O + i * 768), "r"(pw * 192), "r"(8 * b + 2 * head), "r"(ph * 112 + strip * 16 + i) : "memory");
            asm volatile("cp.async.bulk.commit_group;\ncp.async.bulk.wait_group 0;" ::: "memory");
          }
        }
        __syncwarp();
        mbar_arrive_elect(bar + B_OFREE * 8);
        if (lane == 0)
          asm volatile("fence.proxy.async.global;\nfence.acq_rel.gpu;\nred.relaxed.gpu.global.add.s32 [%0], 1;\nred.relaxed.gpu.global.add.s32 [%1], 1;"
                       ::"l"(flag + b * 56 * FS), "l"(flag + (b * 56 + 1) * FS) : "memory");
        __syncwarp();
      }
#pragma unroll 1
      for (int t = 0; t < 4; t++) {
        const int i = t >> 1, jw = t & 1, j = jw ^ odd;
        if (!jw) mbar_wait(bar + (B_TFREE + i) * 8, 0);
        mbar_wait(bar + (B_OTAIL + t) * 8, 0);
        if (elect_one()) {
#pragma unroll 1
          for (int d = 0; d < 8; d++) {
            const int dst = (d + head) & 3, pc = d >> 2;
            send_o<1536>(sb + (i ? SM_TIN1 : SM_TIN0) + head * 6144 + j * 3072 + pc * 1536,
                         sb + (i ? SM_Q : SM_O) + (4 * j + (dst & 2) + pc) * 1536, bar + (B_TIN + i) * 8, base + dst);
          }
        }
        __syncwarp();
      }
    }
    cluster_sync();
  }
}

constexpr int NSTB = 6;
constexpr int NTB = TB * 56;
constexpr int SM_B_ST = 0;
constexpr int SM_B_IN = 73728;
constexpr int SM_B_W = SM_B_IN + 3 * 24576;
constexpr int SM_B_BAR = SM_B_IN + NSTB * 24576;
constexpr int SM_B_TOTAL = SM_B_BAR + 512;
struct MapsB { CUtensorMap oi, oo, wo; };

__global__ void __launch_bounds__(512, 1)
na_proj_kernel(const __grid_constant__ MapsB mp) {
  extern __shared__ __align__(1024) uint8_t smem_raw[];
  const uint32_t sb = smem_u32(smem_raw);
  if ((sb & 0x3FFFF) != SBC) return;
  const uint32_t bar = sb + SM_B_BAR;
  const int tid = threadIdx.x, lane = tid & 31;
  const int warp = __shfl_sync(0xffffffffu, tid >> 5, 0);
  TR2START;
  TRB(47, 0);
  if (warp == 12 && elect_one()) {
#pragma unroll
    for (int i = 0; i <= 2 * NSTB; i++) mbar_init(bar + i * 8, i < NSTB || i == 2 * NSTB ? 1 : 12);
    asm volatile("st.shared.u32 [%0], 0;" ::"r"(bar + 120) : "memory");
    mbar_expect(bar + 2 * NSTB * 8, 73728);
#pragma unroll
    for (int i = 0; i < 2; i++)
      asm volatile("cp.async.bulk.tensor.3d.shared::cluster.global.mbarrier::complete_tx::bytes [%0], [%1, {%3,%4,%5}], [%2];"
                   ::"r"(sb + SM_B_W + i * 36864), "l"(&mp.wo), "r"(bar + 2 * NSTB * 8), "r"(0), "r"(0), "r"(i * 3) : "memory");
  }
  __syncthreads();
  const int step = gridDim.x;
  if (warp == 15) {
    int so = 0;
    nb_arrive(4, 288); nb_arrive(5, 288); nb_arrive(6, 288);
#pragma unroll 1
    for (int n = blockIdx.x, tk = 0; n < NTB; n += step, tk++) {
      uint32_t cc = 0;
#pragma unroll
      for (int wg = 0; wg < 3; wg++) {
        if (lane == 0) asm volatile("cp.async.bulk.wait_group.read 5;" ::: "memory");
        nb_sync(1 + wg, 160);
        if (wg == 0 || n + step < NTB) nb_arrive(4 + wg, 288);
        if (wg == 0) asm volatile("ld.shared.u32 %0, [%1];" : "=r"(cc) : "r"(bar + 128 + tk * 4) : "memory");
        if (lane == 0) {
          asm volatile("cp.async.bulk.tensor.4d.global.shared::cta.bulk_group [%0, {%2,%3,%4,%5}], [%1];"
                       ::"l"(&mp.oo), "r"(sb + SM_B_ST + wg * 8192 + so), "r"(0), "r"((cc >> 8) & 255), "r"(cc >> 16), "r"((cc & 1) * 3 + wg) : "memory");
          asm volatile("cp.async.bulk.commit_group;" ::: "memory");
        }
        __syncwarp();
      }
      so = so == 49152 ? 0 : so + 24576;
    }
    if (lane == 0) asm volatile("cp.async.bulk.wait_group.read 0;" ::: "memory");
  } else if (warp >= 12) {
    nb_sync(7, 480);
#pragma unroll 1
    for (int n = blockIdx.x + (warp - 12) * step; n < NTB; n += 3 * step) {
      const int b = n / 56, rem = n - b * 56, par = rem / 14;
      const int c0 = opq((uint32_t)(par & 1)), c1 = opq((uint32_t)(8 * b)), c2 = opq((uint32_t)((par >> 1) * 112 + (rem - par * 14) * 8));
      int v; uint32_t spin = 0, tk = 0;
      do { asm volatile("ld.acquire.gpu.global.s32 %0, [%1];" : "=r"(v) : "l"(g_flags + n * FS) : "memory"); } while (v < 4 && ++spin < SPIN_LIMIT);
      if (lane == 0) asm volatile("atom.shared.add.u32 %0, [%1], 1;" : "=r"(tk) : "r"(bar + 120) : "memory");
      asm volatile("fence.proxy.async.global;" ::: "memory");
      tk = __shfl_sync(0xffffffffu, tk, 0);
      TRB(tk, 0);
      const uint32_t use = tk / NSTB, sg = tk - use * NSTB;
      if (use) mbar_wait(bar + (NSTB + sg) * 8, (use - 1) & 1);
      TRB(tk, 1);
      if (elect_one()) {
        asm volatile("st.shared.u32 [%0], %1;" ::"r"(bar + 128 + tk * 4), "r"(c0 | c1 << 8 | c2 << 16) : "memory");
        mbar_expect(bar + sg * 8, 24576);
        asm volatile("cp.async.bulk.tensor.3d.shared::cluster.global.mbarrier::complete_tx::bytes [%0], [%1, {%3,%4,%5}], [%2];"
                     ::"r"(sb + SM_B_IN + sg * 24576), "l"(&mp.oi), "r"(bar + sg * 8), "r"(c0 * 192), "r"(c1), "r"(c2) : "memory");
        g_flags[n * FS] = 0;
      }
      __syncwarp();
    }
  } else {
    const int wg = warp >> 2, w = warp & 3;
    uint32_t a[48];
    mbar_wait(bar + 2 * NSTB * 8, 0);
    {
      const int k = (lane & 7) + (lane >> 4) * 8, ch = (warp & 1) * 2 + ((lane >> 3) & 1);
      const uint32_t wa = sb + SM_B_W + (warp >> 1) * 12288 + k * 64 + ((ch ^ ((k >> 1) & 3)) * 16);
#pragma unroll
      for (int i = 0; i < 12; i++)
        asm volatile("ldmatrix.sync.aligned.m8n8.x4.trans.shared.b16 {%0,%1,%2,%3}, [%4];"
                     : "=r"(a[4 * i]), "=r"(a[4 * i + 1]), "=r"(a[4 * i + 2]), "=r"(a[4 * i + 3]) : "r"(wa + i * 1024) : "memory");
    }
    nb_sync(7, 480);
    TRB(47, 1);
    const uint32_t sta = opq(sb + SM_B_ST + wg * 8192 + ((lane & 7) + (lane >> 4) * 8) * 128 + (((2 * w + ((lane >> 3) & 1)) ^ (lane & 7)) * 16));
    const uint32_t hi = opq((uint32_t)(mkdesc(0, 0, 3072, 0) >> 32) + (blockIdx.x >> 16)), bb = opq(bar);
    const uint32_t nbT = opq((uint32_t)(4 + wg)), nbN = opq((uint32_t)(wg == 2 ? 4 : 5 + wg)), nbD = opq((uint32_t)(1 + wg));
    int left = (NTB - blockIdx.x + step - 1) / step;
    if (wg == 2) nb_arrive(4, 288);
#pragma unroll 1
    for (uint32_t ph = 0;; ph ^= 1) {
#pragma unroll
      for (int sg = 0; sg < NSTB; sg++) {
        constexpr uint64_t db = mkdesc(SBC + SM_B_IN, 128, 3072, 0);
        float D[32];
        mbar_wait(bb + sg * 8, ph);
        nb_sync(nbT, 288);
        wg_fence();
        wg_rs64<0>(D, a[0], a[1], a[2], a[3], dsc(db + sg * 1536, hi));
#pragma unroll
        for (int k = 1; k < 12; k++) wg_rs64<1>(D, a[4 * k], a[4 * k + 1], a[4 * k + 2], a[4 * k + 3], dsc(db + sg * 1536 + k * 16, hi));
        wg_commit();
        nb_arrive(nbN, 288);
        wg_wait<0>(); pin(D);
        mbar_arrive_elect(bb + (NSTB + sg) * 8);
#pragma unroll
        for (int q = 0; q < 4; q++)
          asm volatile("stmatrix.sync.aligned.m8n8.x4.trans.shared.b16 [%0], {%1,%2,%3,%4};" ::"r"(sta + (sg % 3) * 24576 + q * 2048),
                       "r"(pack2(D[8 * q], D[8 * q + 1])), "r"(pack2(D[8 * q + 2], D[8 * q + 3])), "r"(pack2(D[8 * q + 4], D[8 * q + 5])), "r"(pack2(D[8 * q + 6], D[8 * q + 7])) : "memory");
        fence_async();
        nb_arrive(nbD, 160);
        if (wg == 0) TRB(31 - left, 5);
        if (--left == 0) goto done;
      }
    }
  done:
    if (wg == 0) nb_arrive(4, 288);
    TR2(132 + blockIdx.x, 2);
    TR2FLUSH(132 + blockIdx.x);
  }
}

typedef CUresult (*EncodeFn)(CUtensorMap*, CUtensorMapDataType, cuuint32_t, void*, const cuuint64_t*, const cuuint64_t*, const cuuint32_t*,
                             const cuuint32_t*, CUtensorMapInterleave, CUtensorMapSwizzle, CUtensorMapL2promotion, CUtensorMapFloatOOBfill);
static EncodeFn g_enc = nullptr;
static void make_map(CUtensorMap* m, const void* p, int rank, const cuuint64_t* dim, const cuuint64_t* str, const cuuint32_t* box, CUtensorMapSwizzle sw) {
  const cuuint32_t ones[5] = {1, 1, 1, 1, 1};
  g_enc(m, CU_TENSOR_MAP_DATA_TYPE_BFLOAT16, rank, (void*)p, dim, str, box, ones, CU_TENSOR_MAP_INTERLEAVE_NONE, sw,
        CU_TENSOR_MAP_L2_PROMOTION_L2_128B, CU_TENSOR_MAP_FLOAT_OOB_FILL_NONE);
}

extern "C" void kernel_launch(void* const* d_in, const int* in_sizes, int n_in, void* d_out, int out_size) {
  const __nv_bfloat16* x = (const __nv_bfloat16*)d_in[0];
  const __nv_bfloat16* wqkv = (const __nv_bfloat16*)d_in[1];
  const __nv_bfloat16* wo = (const __nv_bfloat16*)d_in[2];
  const __nv_bfloat16* rpb = (const __nv_bfloat16*)d_in[3];

  if (!g_enc) {
    void* fn = nullptr; cudaDriverEntryPointQueryResult qr;
    cudaGetDriverEntryPoint("cuTensorMapEncodeTiled", &fn, cudaEnableDefault, &qr);
    g_enc = (EncodeFn)fn;
    cudaFuncSetAttribute(na_attn_kernel, cudaFuncAttributeMaxDynamicSharedMemorySize, SM_A_TOTAL);
    cudaFuncSetAttribute(na_proj_kernel, cudaFuncAttributeMaxDynamicSharedMemorySize, SM_B_TOTAL);
  }
  Maps ma; MapsB mb;
  { cuuint64_t dim[4] = {64, 112, 224, 6}, str[3] = {(cuuint64_t)ROWB, 768, 128};
    cuuint32_t box[4] = {64, 4, 16, 3}, boxh[4] = {64, 16, 3, 3}, boxo[4] = {64, 8, 8, 1};
    make_map(&ma.xc, x, 4, dim, str, box, CU_TENSOR_MAP_SWIZZLE_128B);
    make_map(&ma.xh, x, 4, dim, str, boxh, CU_TENSOR_MAP_SWIZZLE_128B);
    make_map(&mb.oo, d_out, 4, dim, str, boxo, CU_TENSOR_MAP_SWIZZLE_128B); }
  { cuuint64_t dim[3] = {384, 112, 224}, str[2] = {(cuuint64_t)ROWB, 768};
    cuuint32_t box[3] = {192, 8, 8}, boxs[3] = {192, 2, OCH};
    make_map(&mb.oi, d_out, 3, dim, str, box, CU_TENSOR_MAP_SWIZZLE_NONE);
    make_map(&ma.os, d_out, 3, dim, str, boxs, CU_TENSOR_MAP_SWIZZLE_NONE); }
  { cuuint64_t dim[4] = {32, 112, 224, 12}, str[3] = {(cuuint64_t)ROWB, 768, 64};
    cuuint32_t box[4] = {32, 8, 2, 3};
    make_map(&ma.ot, d_out, 4, dim, str, box, CU_TENSOR_MAP_SWIZZLE_64B); }
  { cuuint64_t dim[2] = {576, 192}, str[1] = {1152};
    cuuint32_t box[2] = {16, 192};
    make_map(&ma.w, wqkv, 2, dim, str, box, CU_TENSOR_MAP_SWIZZLE_32B); }
  { cuuint64_t dim[3] = {32, 192, 6}, str[2] = {384, 64};
    cuuint32_t box[3] = {32, 192, 3};
    make_map(&ma.wo, wo, 3, dim, str, box, CU_TENSOR_MAP_SWIZZLE_64B);
    mb.wo = ma.wo; }
  na_attn_kernel<<<112, 512, SM_A_TOTAL>>>(x, wqkv, rpb, ma);
  cudaLaunchConfig_t cfg = {};
  cfg.gridDim = dim3(20); cfg.blockDim = dim3(512); cfg.dynamicSmemBytes = SM_B_TOTAL; cfg.stream = cudaStreamPerThread;
  cudaLaunchAttribute at[1];
  at[0].id = cudaLaunchAttributeProgrammaticStreamSerialization; at[0].val.programmaticStreamSerializationAllowed = 1;
  cfg.attrs = at; cfg.numAttrs = 1;
  cudaLaunchKernelEx(&cfg, na_proj_kernel, mb);
}
```

```cpp
#include <cuda_runtime.h>
#include <cuda_bf16.h>
#include <cuda.h>
#include <stdint.h>

#define SPIN_LIMIT (1u << 18)

__device__ __forceinline__ uint32_t smem_u32(const void* p) { return (uint32_t)__cvta_generic_to_shared(p); }
__device__ __forceinline__ void wg_fence() { asm volatile("wgmma.fence.sync.aligned;" ::: "memory"); }
__device__ __forceinline__ void wg_commit() { asm volatile("wgmma.commit_group.sync.aligned;" ::: "memory"); }
template <int N> __device__ __forceinline__ void wg_wait() { asm volatile("wgmma.wait_group.sync.aligned %0;" ::"n"(N) : "memory"); }
template <int N> __device__ __forceinline__ void pin(float (&d)[N]) {
#pragma unroll
  for (int i = 0; i < N; i++) asm volatile("" : "+f"(d[i])::"memory");
}
__host__ __device__ constexpr uint64_t mkdesc(uint32_t addr, uint32_t lbo, uint32_t sbo, uint32_t sw) {
  return (uint64_t)((addr & 0x3FFFF) >> 4) | ((uint64_t)(lbo >> 4) << 16) | ((uint64_t)(sbo >> 4) << 32) | ((uint64_t)sw << 62);
}
__device__ __forceinline__ void mbar_init(uint32_t bar, uint32_t cnt) { asm volatile("mbarrier.init.shared::cta.b64 [%0], %1;" ::"r"(bar), "r"(cnt) : "memory"); }
__device__ __forceinline__ void mbar_arrive(uint32_t bar) { asm volatile("mbarrier.arrive.shared::cta.b64 _, [%0];" ::"r"(bar) : "memory"); }
__device__ __forceinline__ bool elect_one() {
  uint32_t r; asm volatile("{\n.reg .pred p;\nelect.sync _|p, 0xffffffff;\nselp.u32 %0, 1, 0, p;\n}" : "=r"(r)); return r;
}
__device__ __forceinline__ void mbar_arrive_elect(uint32_t bar) {
  asm volatile("{\n.reg .pred p;\nelect.sync _|p, 0xffffffff;\n@p mbarrier.arrive.shared::cta.b64 _, [%0];\n}" ::"r"(bar) : "memory");
}
__device__ __forceinline__ void mbar_expect(uint32_t bar, uint32_t bytes) { asm volatile("mbarrier.arrive.expect_tx.shared::cta.b64 _, [%0], %1;" ::"r"(bar), "r"(bytes) : "memory"); }
__device__ __forceinline__ void mbar_arrive_remote(uint32_t bar, uint32_t cta) {
  asm volatile("{\n.reg .b32 ra;\nmapa.shared::cluster.u32 ra, %0, %1;\nmbarrier.arrive.relaxed.cluster.shared::cluster.b64 _, [ra];\n}" ::"r"(bar), "r"(cta) : "memory");
}
__device__ __forceinline__ void mbar_wait(uint32_t bar, uint32_t parity) {
  asm volatile("{\n.reg .pred p;\n.reg .b32 n;\nmov.b32 n, 0;\nWL:\nmbarrier.try_wait.parity.shared::cta.b64 p, [%0], %1;\n@p bra WD;\n"
               "add.u32 n, n, 1;\nsetp.lt.u32 p, n, 65536;\n@p bra WL;\nWD:\n}" ::"r"(bar), "r"(parity) : "memory");
}
__device__ __forceinline__ void nb_sync(int id, int n) { asm volatile("bar.sync %0, %1;" ::"r"(id), "r"(n) : "memory"); }
__device__ __forceinline__ void nb_arrive(int id, int n) { asm volatile("bar.arrive %0, %1;" ::"r"(id), "r"(n) : "memory"); }
__device__ __forceinline__ uint32_t opq(uint32_t x) { uint32_t r; asm volatile("mov.b32 %0, %1;" : "=r"(r) : "r"(x)); return r; }
__device__ __forceinline__ uint64_t opq(uint64_t x) { uint64_t r; asm volatile("mov.b64 %0, %1;" : "=l"(r) : "l"(x)); return r; }
__device__ __forceinline__ uint32_t mapa(uint32_t a, uint32_t cta) { uint32_t r; asm("mapa.shared::cluster.u32 %0, %1, %2;" : "=r"(r) : "r"(a), "r"(cta)); return r; }
__device__ __forceinline__ void fence_async() { asm volatile("fence.proxy.async.shared::cta;" ::: "memory"); }
__device__ __forceinline__ void cluster_sync() {
  asm volatile("barrier.cluster.arrive.relaxed.aligned;\nbarrier.cluster.wait.aligned;" ::: "memory");
}
__device__ __forceinline__ uint32_t pack2(float lo, float hi) {
  uint32_t r; asm("cvt.rn.bf16x2.f32 %0, %1, %2;" : "=r"(r) : "f"(hi), "f"(lo)); return r;
}
__device__ __forceinline__ void stsm4(uint32_t a, uint32_t r0, uint32_t r1, uint32_t r2, uint32_t r3) {
  asm volatile("stmatrix.sync.aligned.m8n8.x4.shared.b16 [%0], {%1,%2,%3,%4};" ::"r"(a), "r"(r0), "r"(r1), "r"(r2), "r"(r3) : "memory");
}
__device__ __forceinline__ void ldsm4(uint32_t a, uint32_t& r0, uint32_t& r1, uint32_t& r2, uint32_t& r3) {
  asm volatile("ldmatrix.sync.aligned.m8n8.x4.shared.b16 {%0,%1,%2,%3}, [%4];" : "=r"(r0), "=r"(r1), "=r"(r2), "=r"(r3) : "r"(a) : "memory");
}
__device__ __forceinline__ void sts128(uint32_t a, uint4 v) {
  asm volatile("st.shared.v4.b32 [%0], {%1,%2,%3,%4};" ::"r"(a), "r"(v.x), "r"(v.y), "r"(v.z), "r"(v.w) : "memory");
}
__device__ __forceinline__ float lds_f32(uint32_t a) { float v; asm volatile("ld.shared.f32 %0, [%1];" : "=f"(v) : "r"(a)); return v; }
__device__ __forceinline__ float ex2(float x) { float y; asm("ex2.approx.ftz.f32 %0, %1;" : "=f"(y) : "f"(x)); return y; }

template<int SC> __device__ __forceinline__ void wg_ss144(float (&d)[72], uint64_t da, uint64_t db) {
  asm volatile("{\n.reg .pred p;\nsetp.ne.b32 p, %74, 0;\nwgmma.mma_async.sync.aligned.m64n144k16.f32.bf16.bf16 {%0,%1,%2,%3,%4,%5,%6,%7,%8,%9,%10,%11,%12,%13,%14,%15,%16,%17,%18,%19,%20,%21,%22,%23,%24,%25,%26,%27,%28,%29,%30,%31,%32,%33,%34,%35,%36,%37,%38,%39,%40,%41,%42,%43,%44,%45,%46,%47,%48,%49,%50,%51,%52,%53,%54,%55,%56,%57,%58,%59,%60,%61,%62,%63,%64,%65,%66,%67,%68,%69,%70,%71}, %72, %73, p, 1, 1, 0, 1;\n}\n"
    : "+f"(d[0]),"+f"(d[1]),"+f"(d[2]),"+f"(d[3]),"+f"(d[4]),"+f"(d[5]),"+f"(d[6]),"+f"(d[7]),"+f"(d[8]),"+f"(d[9]),"+f"(d[10]),"+f"(d[11]),"+f"(d[12]),"+f"(d[13]),"+f"(d[14]),"+f"(d[15]),"+f"(d[16]),"+f"(d[17]),"+f"(d[18]),"+f"(d[19]),"+f"(d[20]),"+f"(d[21]),"+f"(d[22]),"+f"(d[23]),"+f"(d[24]),"+f"(d[25]),"+f"(d[26]),"+f"(d[27]),"+f"(d[28]),"+f"(d[29]),"+f"(d[30]),"+f"(d[31]),"+f"(d[32]),"+f"(d[33]),"+f"(d[34]),"+f"(d[35]),"+f"(d[36]),"+f"(d[37]),"+f"(d[38]),"+f"(d[39]),"+f"(d[40]),"+f"(d[41]),"+f"(d[42]),"+f"(d[43]),"+f"(d[44]),"+f"(d[45]),"+f"(d[46]),"+f"(d[47]),"+f"(d[48]),"+f"(d[49]),"+f"(d[50]),"+f"(d[51]),"+f"(d[52]),"+f"(d[53]),"+f"(d[54]),"+f"(d[55]),"+f"(d[56]),"+f"(d[57]),"+f"(d[58]),"+f"(d[59]),"+f"(d[60]),"+f"(d[61]),"+f"(d[62]),"+f"(d[63]),"+f"(d[64]),"+f"(d[65]),"+f"(d[66]),"+f"(d[67]),"+f"(d[68]),"+f"(d[69]),"+f"(d[70]),"+f"(d[71]) : "l"(da), "l"(db), "n"(SC));
}
template<int SC> __device__ __forceinline__ void wg_ss96(float (&d)[48], uint64_t da, uint64_t db) {
  asm volatile("{\n.reg .pred p;\nsetp.ne.b32 p, %50, 0;\nwgmma.mma_async.sync.aligned.m64n96k16.f32.bf16.bf16 {%0,%1,%2,%3,%4,%5,%6,%7,%8,%9,%10,%11,%12,%13,%14,%15,%16,%17,%18,%19,%20,%21,%22,%23,%24,%25,%26,%27,%28,%29,%30,%31,%32,%33,%34,%35,%36,%37,%38,%39,%40,%41,%42,%43,%44,%45,%46,%47}, %48, %49, p, 1, 1, 0, 1;\n}\n"
    : "+f"(d[0]),"+f"(d[1]),"+f"(d[2]),"+f"(d[3]),"+f"(d[4]),"+f"(d[5]),"+f"(d[6]),"+f"(d[7]),"+f"(d[8]),"+f"(d[9]),"+f"(d[10]),"+f"(d[11]),"+f"(d[12]),"+f"(d[13]),"+f"(d[14]),"+f"(d[15]),"+f"(d[16]),"+f"(d[17]),"+f"(d[18]),"+f"(d[19]),"+f"(d[20]),"+f"(d[21]),"+f"(d[22]),"+f"(d[23]),"+f"(d[24]),"+f"(d[25]),"+f"(d[26]),"+f"(d[27]),"+f"(d[28]),"+f"(d[29]),"+f"(d[30]),"+f"(d[31]),"+f"(d[32]),"+f"(d[33]),"+f"(d[34]),"+f"(d[35]),"+f"(d[36]),"+f"(d[37]),"+f"(d[38]),"+f"(d[39]),"+f"(d[40]),"+f"(d[41]),"+f"(d[42]),"+f"(d[43]),"+f"(d[44]),"+f"(d[45]),"+f"(d[46]),"+f"(d[47]) : "l"(da), "l"(db), "n"(SC));
}
template<int SC> __device__ __forceinline__ void wg_rs112(float (&d)[56], uint32_t a0, uint32_t a1, uint32_t a2, uint32_t a3, uint64_t db) {
  asm volatile("{\n.reg .pred p;\nsetp.ne.b32 p, %61, 0;\nwgmma.mma_async.sync.aligned.m64n112k16.f32.bf16.bf16 {%0,%1,%2,%3,%4,%5,%6,%7,%8,%9,%10,%11,%12,%13,%14,%15,%16,%17,%18,%19,%20,%21,%22,%23,%24,%25,%26,%27,%28,%29,%30,%31,%32,%33,%34,%35,%36,%37,%38,%39,%40,%41,%42,%43,%44,%45,%46,%47,%48,%49,%50,%51,%52,%53,%54,%55}, {%56,%57,%58,%59}, %60, p, 1, 1, 0;\n}\n"
    : "+f"(d[0]),"+f"(d[1]),"+f"(d[2]),"+f"(d[3]),"+f"(d[4]),"+f"(d[5]),"+f"(d[6]),"+f"(d[7]),"+f"(d[8]),"+f"(d[9]),"+f"(d[10]),"+f"(d[11]),"+f"(d[12]),"+f"(d[13]),"+f"(d[14]),"+f"(d[15]),"+f"(d[16]),"+f"(d[17]),"+f"(d[18]),"+f"(d[19]),"+f"(d[20]),"+f"(d[21]),"+f"(d[22]),"+f"(d[23]),"+f"(d[24]),"+f"(d[25]),"+f"(d[26]),"+f"(d[27]),"+f"(d[28]),"+f"(d[29]),"+f"(d[30]),"+f"(d[31]),"+f"(d[32]),"+f"(d[33]),"+f"(d[34]),"+f"(d[35]),"+f"(d[36]),"+f"(d[37]),"+f"(d[38]),"+f"(d[39]),"+f"(d[40]),"+f"(d[41]),"+f"(d[42]),"+f"(d[43]),"+f"(d[44]),"+f"(d[45]),"+f"(d[46]),"+f"(d[47]),"+f"(d[48]),"+f"(d[49]),"+f"(d[50]),"+f"(d[51]),"+f"(d[52]),"+f"(d[53]),"+f"(d[54]),"+f"(d[55]) : "r"(a0), "r"(a1), "r"(a2), "r"(a3), "l"(db), "n"(SC));
}
template<int SC> __device__ __forceinline__ void wg_sp48(float (&d)[24], uint32_t a0, uint32_t a1, uint32_t a2, uint32_t a3, uint64_t db, uint32_t meta) {
  asm volatile("{\n.reg .pred p;\nsetp.ne.b32 p, %30, 0;\nwgmma.mma_async.sp.sync.aligned.m64n48k32.f32.bf16.bf16 {%0,%1,%2,%3,%4,%5,%6,%7,%8,%9,%10,%11,%12,%13,%14,%15,%16,%17,%18,%19,%20,%21,%22,%23}, {%24,%25,%26,%27}, %28, %29, 0, p, 1, 1, 1;\n}\n"
    : "+f"(d[0]),"+f"(d[1]),"+f"(d[2]),"+f"(d[3]),"+f"(d[4]),"+f"(d[5]),"+f"(d[6]),"+f"(d[7]),"+f"(d[8]),"+f"(d[9]),"+f"(d[10]),"+f"(d[11]),"+f"(d[12]),"+f"(d[13]),"+f"(d[14]),"+f"(d[15]),"+f"(d[16]),"+f"(d[17]),"+f"(d[18]),"+f"(d[19]),"+f"(d[20]),"+f"(d[21]),"+f"(d[22]),"+f"(d[23]) : "r"(a0), "r"(a1), "r"(a2), "r"(a3), "l"(db), "r"(meta), "n"(SC));
}
template<int SC> __device__ __forceinline__ void wg_rs64(float (&d)[32], uint32_t a0, uint32_t a1, uint32_t a2, uint32_t a3, uint64_t db) {
  asm volatile("{\n.reg .pred p;\nsetp.ne.b32 p, %37, 0;\nwgmma.mma_async.sync.aligned.m64n64k16.f32.bf16.bf16 {%0,%1,%2,%3,%4,%5,%6,%7,%8,%9,%10,%11,%12,%13,%14,%15,%16,%17,%18,%19,%20,%21,%22,%23,%24,%25,%26,%27,%28,%29,%30,%31}, {%32,%33,%34,%35}, %36, p, 1, 1, 0;\n}\n"
    : "+f"(d[0]),"+f"(d[1]),"+f"(d[2]),"+f"(d[3]),"+f"(d[4]),"+f"(d[5]),"+f"(d[6]),"+f"(d[7]),"+f"(d[8]),"+f"(d[9]),"+f"(d[10]),"+f"(d[11]),"+f"(d[12]),"+f"(d[13]),"+f"(d[14]),"+f"(d[15]),"+f"(d[16]),"+f"(d[17]),"+f"(d[18]),"+f"(d[19]),"+f"(d[20]),"+f"(d[21]),"+f"(d[22]),"+f"(d[23]),"+f"(d[24]),"+f"(d[25]),"+f"(d[26]),"+f"(d[27]),"+f"(d[28]),"+f"(d[29]),"+f"(d[30]),"+f"(d[31]) : "r"(a0), "r"(a1), "r"(a2), "r"(a3), "l"(db), "n"(SC));
}

constexpr uint32_t SBC = 1024;
constexpr int ROWB = 2 * 224 * 384;
constexpr int TB = 11;
constexpr int KS = 832;
constexpr int KSLOT = 22 * KS;
constexpr int SM_X = 0;
constexpr int SM_W = SM_X + 3 * 24576;
constexpr int SM_K = SM_W + 55296;
constexpr int SM_V = SM_K + 2 * KSLOT;
constexpr int SM_Q = SM_V + 22 * 1536;
constexpr int SM_O = SM_Q + 12288;
constexpr int SM_S = SM_O + 12288;
constexpr int SM_RPB = SM_S + 6144;
constexpr int SM_BAR = SM_RPB + 768;
constexpr int SM_A_TOTAL = SM_BAR + 256;
constexpr int SM_TIN0 = SM_X + 24576, SM_TIN1 = SM_X, SM_TIN2 = SM_W + 18432;
constexpr int SM_TWO = SM_X + 2 * 24576;
constexpr int SM_TST = SM_TIN2 + 24576;
enum { B_FULL = 0, B_EMPTY = 3, B_TIN = 6, B_TFREE = 10, B_WK = 12, B_WQ, B_WO, B_KIMP, B_VIMP, B_OFREE, B_XK, B_XV,
       B_Q0, B_WOFREE, B_OTAIL, B_ODONE = B_OTAIL + 4, B_KFREE, B_VFREE, B_COUNT };
enum { N_KRDY = 4, N_QK0, N_QK1, N_VQ0, N_VQ1, N_PVISS, N_Q0 };

#define NL 2
#define OCH 16
#define MID 6
#define SPL 4
#define RA 160
#define RG 168
#define OPT 0
constexpr int FS = 64;
__device__ int g_flags[TB * 56 * FS];

#define TR(role, it, k)
#define TRDECL
#define TRARG
#define TRPASS
#define TRDUMP
#define TRB(it, k)
#define TR2START
#define TR2FLUSH(blk)
#define TR2(blk, k)

struct Stage { uint32_t lo, full, em, par; };
struct GemmCtx {
  uint32_t bar;
  uint32_t kC, vC[2], qC[2];
  uint32_t kH, vH[2];
  uint32_t hiA, hiB;
  uint32_t spin;
  bool hvalid, never, edge;
};

template <int STRIDE> __device__ __forceinline__ void dump12(uint32_t a, const uint32_t (&r)[12]) {
#pragma unroll
  for (int j = 0; j < 3; j++) stsm4(a + j * 2 * STRIDE, r[4 * j], r[4 * j + 1], r[4 * j + 2], r[4 * j + 3]);
}
__device__ __forceinline__ void keep12(bool never, uint32_t a, const uint32_t (&r)[12]) { if (never) dump12<128>(a, r); }
template <int N> __device__ __forceinline__ void pack12(uint32_t (&r)[12], const float (&d)[N], int off) {
#pragma unroll
  for (int j = 0; j < 12; j++) r[j] = pack2(d[off + 2 * j], d[off + 2 * j + 1]);
}
__device__ __forceinline__ uint64_t dsc(uint64_t lo, uint32_t hi) { uint64_t r; asm("mov.b64 %0, {%1, %2};" : "=l"(r) : "r"((uint32_t)lo), "r"(hi)); return r; }
template <int K0, int K1> __device__ __forceinline__ void issue_core(const GemmCtx& c, const Stage& x, float (&d)[72]) {
  constexpr uint64_t db = mkdesc(SBC + SM_W, 6144, 256, 3);
  wg_fence();
  if (K0 == 0) wg_ss144<0>(d, dsc(x.lo, c.hiA), dsc(db, c.hiB));
#pragma unroll
  for (int k = K0 ? K0 : 1; k < K1; k++) wg_ss144<1>(d, dsc(x.lo + (k >> 2) * 512 + (k & 3) * 2, c.hiA), dsc(db + k * 32, c.hiB));
  wg_commit();
}
template <int K0, int K1> __device__ __forceinline__ void issue_halo(const GemmCtx& c, const Stage& x, float (&d)[48]) {
  constexpr uint64_t db = mkdesc(SBC + SM_W + 18432, 6144, 256, 3);
  wg_fence();
  if (K0 == 0) wg_ss96<0>(d, dsc(x.lo, c.hiA), dsc(db, c.hiB));
#pragma unroll
  for (int k = K0 ? K0 : 1; k < K1; k++) wg_ss96<1>(d, dsc(x.lo + (k >> 2) * 384 + (k & 3) * 2, c.hiA), dsc(db + k * 32, c.hiB));
  wg_commit();
}
__device__ __forceinline__ void release_stage(const Stage& x) {
  asm volatile("{\n.reg .pred p;\nelect.sync _|p, 0xffffffff;\n@p mbarrier.arrive.shared::cluster.b64 _, [%0];\n}" ::"r"(x.em) : "memory");
}
__device__ __forceinline__ void wait_stage(GemmCtx& c, Stage& x) {
  asm volatile("{\n.reg .pred p;\nWL:\nmbarrier.try_wait.parity.shared::cta.b64 p, [%1], %2;\n@p bra WD;\n"
               "add.u32 %0, %0, 1;\nsetp.lt.u32 p, %0, 0x100000;\n@p bra WL;\nWD:\n}" : "+r"(c.spin) : "r"(x.full), "r"(x.par) : "memory");
  x.par ^= 1;
}
__device__ __forceinline__ void edge_ready(const GemmCtx& c, int bar) { __syncwarp(); if (c.edge) mbar_arrive_elect(c.bar + bar * 8); }
__device__ __forceinline__ void dump6(uint32_t a, const uint32_t (&r)[6]) {
  stsm4(a, r[0], r[1], r[2], r[3]);
  asm volatile("stmatrix.sync.aligned.m8n8.x2.shared.b16 [%0], {%1,%2};" ::"r"(a + 512), "r"(r[4]), "r"(r[5]) : "memory");
}
__device__ __forceinline__ void pack6(uint32_t (&r)[6], const float (&d)[48], int off) {
#pragma unroll
  for (int j = 0; j < 6; j++) r[j] = pack2(d[off + 4 * j], d[off + 4 * j + 1]);
}
template <int PARITY> __device__ __forceinline__ void gwait(GemmCtx& c, int bar) {
  asm volatile("{\n.reg .pred p;\nWL:\nmbarrier.try_wait.parity.shared::cta.b64 p, [%1], %2;\n@p bra WD;\n"
               "add.u32 %0, %0, 1;\nsetp.lt.u32 p, %0, 0x100000;\n@p bra WL;\nWD:\n}" : "+r"(c.spin) : "r"(c.bar + bar * 8), "n"(PARITY) : "memory");
}
__device__ __forceinline__ void load_w(const CUtensorMap* m, uint32_t dst, uint32_t bar, int col) {
  asm volatile("cp.async.bulk.tensor.2d.shared::cluster.global.mbarrier::complete_tx::bytes [%0], [%1, {%3,%4}], [%2];"
               ::"r"(dst), "l"(m), "r"(bar), "r"(col), "r"(0) : "memory");
}
__device__ __forceinline__ void remote_arrive(uint32_t rbar) { asm volatile("mbarrier.arrive.shared::cluster.b64 _, [%0];" ::"r"(rbar) : "memory"); }
__device__ __forceinline__ void remote_expect(uint32_t rbar, uint32_t bytes) {
  asm volatile("mbarrier.arrive.expect_tx.shared::cluster.b64 _, [%0], %1;" ::"r"(rbar), "r"(bytes) : "memory");
}
__device__ __forceinline__ void copy_remote(uint32_t rdst, uint32_t src, uint32_t bytes, uint32_t rbar) {
  asm volatile("cp.async.bulk.shared::cluster.shared::cta.mbarrier::complete_tx::bytes [%0], [%1], %2, [%3];" ::"r"(rdst), "r"(src), "r"(bytes), "r"(rbar) : "memory");
}
__device__ __forceinline__ void tail_free(uint32_t bar) {
  uint32_t ln; asm volatile("mov.u32 %0, %%laneid;" : "=r"(ln));
  if (ln < 4) mbar_arrive_remote(bar, ln + (blockIdx.x & 4));
}
__device__ __forceinline__ void publish(uint32_t bar) {
  fence_async();
  __syncwarp();
  mbar_arrive_elect(bar);
}

template <bool FIRST, int PA>
__device__ __forceinline__ void gemm_iter(GemmCtx& c, int b, uint32_t (&pk)[12], uint32_t (&pv)[12], uint32_t (&pq)[12],
                                          uint32_t (&hk1)[6], uint32_t (&hv1)[6], Stage& x0, Stage& x2, Stage& x1 TRARG) {
  const uint32_t bar = c.bar;
  const bool w = !FIRST && (PA == 0 || b >= 0), never = c.never;
  constexpr uint32_t ko = PA * KSLOT;
  float C[72];
  uint32_t hk0[6], hv0[6], pv2[12];
  TR(2, b, 0);
  if (FIRST) wait_stage(c, x0);
  else dump12<128>(c.qC[1], pq);
  if (w) nb_sync(N_QK1, 256);
  TR(2, b, 2);
  if (FIRST) TR(2, b - 1, 6);
  if (PA == 0) {
    float H[48];
    issue_halo<0, 8>(c, x0, H);
    TR(2, b, 3);
    if (!FIRST) { gwait<0>(c, B_KFREE); dump12<128>(c.kC, pk); }
    issue_halo<8, 12>(c, x0, H);
    TR(2, b, 4);
    wait_stage(c, x2);
    if (FIRST) TR(2, b - 1, 7);
    if (FIRST) gwait<0>(c, B_WQ);
    if (FIRST) TR(2, b - 1, 8);
    issue_core<0, 8>(c, x2, C);
    TR(2, b, 5);
    if (!FIRST) { fence_async(); keep12(never, c.kC, pk); }
    wg_wait<1>(); pin(H);
    release_stage(x0);
    pack6(hk0, H, 0);
    if (c.hvalid) dump6(c.kH, hk0);
    pack6(hk1, H, 2); pack6(hv0, H, 24); pack6(hv1, H, 26);
  } else {
    issue_core<0, 8>(c, x2, C);
    TR(2, b, 5);
    fence_async();
    keep12(never, c.kC, pq);
    if (w) gwait<1>(c, B_KFREE);
    dump12<128>(c.kC + ko, pk);
    if (c.hvalid) dump6(c.kH + ko, hk1);
  }
  TR(2, b, 13);
  issue_core<8, 12>(c, x2, C);
  if (w) { nb_arrive(N_VQ0, 288); nb_arrive(N_VQ1, 288); }
  else if (!FIRST) { __syncwarp(); mbar_arrive_elect(bar + B_Q0 * 8); }
  wait_stage(c, x1);
  if (never) dump6(bar, PA ? hk1 : hk0);
  TR(2, b, 6);
  wg_wait<0>(); pin(C);
  TR(2, b, 7);
  release_stage(x2);
  pack12(pk, C, 24);
  dump12<128>(c.kC + ko + 64, pk);
  pack12(pv2, C, 48);
  pack12(pq, C, 0);
  TR(2, b, 8);
  issue_core<0, SPL>(c, x1, C);
  TR(2, b, 9);
  if (!FIRST) { fence_async(); edge_ready(c, B_XK); }
  keep12(never, c.kC, pk);
  TR(2, b, 14);
  if (w) nb_sync(N_PVISS, 384);
  issue_core<SPL, 12>(c, x1, C);
  if (!FIRST) nb_arrive(N_KRDY, 256);
  TR(2, b, 1);
  if (PA && b == 11) tail_free(bar + B_TFREE * 8);
  wait_stage(c, x0);
  if (w) gwait<PA>(c, B_VFREE);
  if (w && b < TB) gwait<PA>(c, B_ODONE);
  TR(2, b, 10);
  if (!FIRST) dump12<128>(c.vC[PA], pv);
  dump12<128>(c.vC[PA ^ 1] + 768, pv2);
  TR(2, b, 11);
  wg_wait<0>(); pin(C);
  TR(2, b, 12);
  release_stage(x1);
  if (!FIRST && c.edge) publish(bar + B_XV * 8);
  if (c.hvalid) dump6(c.vH[PA], PA ? hv1 : hv0);
  if (PA && !w) nb_sync(N_Q0, 384);
  dump12<128>(c.qC[0], pq);
  pack12(pk, C, 24);
  pack12(pv, C, 48);
  pack12(pq, C, 0);
}

template <int IN> __device__ __forceinline__ void issue_proj(float (&D)[48]) {
  constexpr uint64_t da = mkdesc(SBC + IN, 128, 768, 0), db = mkdesc(SBC + SM_TWO, 12288, 512, 2);
  wg_fence();
  wg_ss96<0>(D, da, db);
#pragma unroll
  for (int k = 1; k < 12; k++) wg_ss96<1>(D, da + (k / 3) * 384 + (k % 3) * 16, db + k * 64);
  wg_commit();
}
template <int ACC> __device__ __forceinline__ void issue_proj_half(float (&D)[48], int hd) {
  const uint64_t da = mkdesc(SBC + SM_TIN2, 128, 768, 0) + hd * 384, db = mkdesc(SBC + SM_TWO, 12288, 512, 2) + hd * 192;
  wg_fence();
  wg_ss96<ACC>(D, da, db);
#pragma unroll
  for (int k = 1; k < 6; k++) wg_ss96<1>(D, da + (k / 3) * 768 + (k % 3) * 16, db + (k / 3) * 384 + (k % 3) * 64);
  wg_commit();
}
__device__ __forceinline__ void store_proj(const float (&D)[48], const CUtensorMap* m, uint32_t st, uint32_t sta, int row, int col, int ch) {
#pragma unroll
  for (int q = 0; q < 6; q++)
    stsm4((sta ^ ((q & 1) * 32)) + (q >> 1) * 1024,
          pack2(D[8 * q], D[8 * q + 1]), pack2(D[8 * q + 2], D[8 * q + 3]), pack2(D[8 * q + 4], D[8 * q + 5]), pack2(D[8 * q + 6], D[8 * q + 7]));
  fence_async();
  __syncwarp();
  if ((threadIdx.x & 31) == 0) {
    asm volatile("cp.async.bulk.tensor.4d.global.shared::cta.bulk_group [%0, {%2,%3,%4,%5}], [%1];" ::"l"(m), "r"(st), "r"(0), "r"(row), "r"(col), "r"(ch) : "memory");
    asm volatile("cp.async.bulk.commit_group;" ::: "memory");
  }
  __syncwarp();
}

__device__ __forceinline__ float fold(float a, float b, float t, int useb) {
  float r;
  asm("{\n.reg .pred p;\nsetp.ne.b32 p, %4, 0;\nfma.rn.f32 %0, %1, 0f3E553B95, %3;\n@p fma.rn.f32 %0, %2, 0f3E553B95, %3;\n}"
      : "=&f"(r) : "f"(a), "f"(b), "f"(t), "r"(useb));
  return r;
}
template <int U, int L>
__device__ __forceinline__ void softmax_tile(const float (&SA)[56], const float (&SB)[56], const float (&T)[16], int b0, int b1,
                                             uint32_t (&P)[28], float (&sx)[8], uint32_t nbV, uint32_t zero, uint32_t qa, uint32_t (&q)[12]) {
  float lu[14], ll[14];
#pragma unroll
  for (int j = 0; j < 7; j++) {
    constexpr int sh = U == L ? 2 : 0;
    const float tu0 = T[2 * j + sh], tu1 = T[2 * j + 1 + sh], tl0 = T[2 * j], tl1 = T[2 * j + 1];
    lu[2 * j]     = fold(SA[4 * (U + j)],     SB[4 * (U + j)],     tu0, b0);
    ll[2 * j]     = fold(SA[4 * (L + j) + 2], SB[4 * (L + j) + 2], tl0, b0);
    lu[2 * j + 1] = fold(SA[4 * (U + j) + 1], SB[4 * (U + j) + 1], tu1, b1);
    ll[2 * j + 1] = fold(SA[4 * (L + j) + 3], SB[4 * (L + j) + 3], tl1, b1);
  }
  float mu = lu[0], ml = ll[0], mu2 = lu[1], ml2 = ll[1];
#pragma unroll
  for (int j = 1; j < 7; j++) { mu = fmaxf(mu, lu[2 * j]); mu2 = fmaxf(mu2, lu[2 * j + 1]); ml = fmaxf(ml, ll[2 * j]); ml2 = fmaxf(ml2, ll[2 * j + 1]); }
  mu = fmaxf(mu, mu2); ml = fmaxf(ml, ml2);
  { const float a1 = __shfl_xor_sync(0xffffffffu, mu, 1), a2 = __shfl_xor_sync(0xffffffffu, mu, 2), a3 = __shfl_xor_sync(0xffffffffu, mu, 3);
    const float c1 = __shfl_xor_sync(0xffffffffu, ml, 1), c2 = __shfl_xor_sync(0xffffffffu, ml, 2), c3 = __shfl_xor_sync(0xffffffffu, ml, 3);
    mu = fmaxf(fmaxf(mu, a1), fmaxf(a2, a3)); ml = fmaxf(fmaxf(ml, c1), fmaxf(c2, c3)); }
  float su = 0.f, sl = 0.f;
#pragma unroll
  for (int c = 0; c < 14; c++) {
    if (c >= U && c < U + 7) {
      float e0 = ex2(lu[2 * (c - U)] - mu), e1 = ex2(lu[2 * (c - U) + 1] - mu);
      su = c == U ? e0 + e1 : (su + e0) + e1; P[2 * c] = pack2(e0, e1);
    } else P[2 * c] = 0u;
  }
  nb_sync(nbV | (P[2 * (U + MID)] & zero), 288);
#pragma unroll
  for (int k = 0; k < 3; k++) ldsm4(qa + k * 256, q[4 * k], q[4 * k + 1], q[4 * k + 2], q[4 * k + 3]);
#pragma unroll
  for (int c = 0; c < 14; c++) {
    if (c >= L && c < L + 7) {
      float e0 = ex2(ll[2 * (c - L)] - ml), e1 = ex2(ll[2 * (c - L) + 1] - ml);
      sl = c == L ? e0 + e1 : (sl + e0) + e1; P[2 * c + 1] = pack2(e0, e1);
    } else P[2 * c + 1] = 0u;
  }
  sx[0] = su; sx[4] = sl;
#pragma unroll
  for (int k = 1; k < 4; k++) sx[k] = __shfl_xor_sync(0xffffffffu, su, k);
#pragma unroll
  for (int k = 1; k < 4; k++) sx[4 + k] = __shfl_xor_sync(0xffffffffu, sl, k);
}

struct BandCfg { uint32_t ra0, ra1, meta; int b0, b1; };
__device__ __forceinline__ void band_cfg(int b, uint32_t tb, BandCfg& n) {
  uint32_t ln; asm volatile("mov.u32 %0, %%laneid;" : "=r"(ln));
  const int g = ln >> 2, t = ln & 3;
  const int sw = min(max(g + 1, b == 0 ? 4 : 0), b == 13 ? 5 : 8);
  const int i0 = 2 * t, i1 = 2 * t + 1;
  n.b0 = i0 <= sw - 2; n.b1 = i1 <= sw - 2;
  n.ra0 = tb + (i0 == sw - 1 ? 13 : i0 + 8 * n.b0 - g + 2) * 52;
  n.ra1 = tb + (i1 == sw - 1 ? 13 : i1 + 8 * n.b1 - g + 2) * 52;
  n.meta = ((0x5555u & ((1u << (2 * (sw - 1))) - 1)) ^ 0xDD88u ^ (((t ^ b) & 1) ? 0x5555u : 0u)) * 0x10001u;
}
__device__ __forceinline__ void band_load(const BandCfg& n, float (&T)[16], int& b0, int& b1, uint32_t& meta) {
#pragma unroll
  for (int jj = 0; jj < 8; jj++) { T[2 * jj] = lds_f32(n.ra0 + jj * 4); T[2 * jj + 1] = lds_f32(n.ra1 + jj * 4); }
  b0 = n.b0; b1 = n.b1; meta = n.meta;
}

struct Maps { CUtensorMap xc, xh, w, os, wo, ot; };

__global__ void __cluster_dims__(8, 1, 1) __launch_bounds__(512, 1)
na_attn_kernel(const __nv_bfloat16* __restrict__ x, const __nv_bfloat16* __restrict__ wqkv, const __nv_bfloat16* __restrict__ rpb, const __grid_constant__ Maps mp) {
  extern __shared__ __align__(1024) uint8_t smem_raw[];
  const uint32_t sb = smem_u32(smem_raw);
  if ((sb & 0x3FFFF) != SBC) return;
  const uint32_t bar = sb + SM_BAR;
  TR2START;
  const int tid = threadIdx.x, lane = tid & 31;
  const int warp = __shfl_sync(0xffffffffu, tid >> 5, 0);
  const int head = blockIdx.x & 3, base = blockIdx.x & 4, sp = blockIdx.x >> 2;
  const int par = sp < 24 ? sp / 6 : sp - 24, strip = sp < 24 ? sp - par * 6 : 6, ph = par >> 1, pw = par & 1;
  const int odd = strip & 1;

  uint4 wv[2 * NL];
  const int va = head == 1;
  const uint32_t wdst = sb + SM_W + (3 + va + ((tid >> 1) & 1)) * 6144 + (tid >> 2) * 32 + ((tid ^ (tid >> 4)) & 1) * 16;
  if (warp < 12) {
    asm volatile("barrier.cluster.arrive.relaxed.aligned;" ::: "memory");
    const uint32_t wo0 = (tid >> 2) * 1152 + head * 96 + va * 32 + (tid & 3) * 16;
#pragma unroll
    for (int i = 0; i < 2 * NL; i++)
      asm volatile("ld.global.nc.v4.b32 {%0,%1,%2,%3}, [%4];" : "=r"(wv[i].x), "=r"(wv[i].y), "=r"(wv[i].z), "=r"(wv[i].w)
                   : "l"(reinterpret_cast<const uint8_t*>(wqkv) + wo0 + (i & 1) * 96 * 1152 + (i / 2 + 1) * 384));
  }
  if (warp < 8) {
    asm volatile("setmaxnreg.inc.sync.aligned.u32 %0;" ::"n"(RA));
    float rv = -INFINITY;
    if (tid < 169) rv = __bfloat162float(rpb[head * 169 + tid]) * 1.4426950408889634f;
    if (tid < 192) {
      const int kc = (tid & 15) + 3, wc = (tid >> 4) % 6;
      sts128(tid < 96 ? sb + SM_K + kc * KS + wc * 128 + 48 : sb + SM_V + kc * 1536 + wc * 128 + (6 + (kc & 1)) * 16, make_uint4(0, 0, 0, 0));
    }
#pragma unroll
    for (int i = 0; i < 2 * NL; i++) sts128(wdst + (i & 1) * 3072 + (i / 2) * 18432, wv[i]);
    fence_async();
    asm volatile("bar.arrive 1, 384;" ::: "memory");
    if (tid < 182) asm volatile("st.shared.f32 [%0], %1;" ::"r"(sb + SM_RPB + tid * 4), "f"(rv) : "memory");
    const int jw = warp >> 2, j = jw ^ odd, w = warp & 3, wt = 4 * j + w;
    int variant = w;
    if (strip == 0 && j == 0 && w < 2) variant = 4;
    if (strip == 6 && j == 1 && w >= 2) variant = 5;
    const bool v1 = opq((uint32_t)(variant & 1)), v2 = opq((uint32_t)(variant & 2)), v4 = opq((uint32_t)(variant & 4));
    const uint32_t qa = opq(sb + SM_Q + (8 * j + 2 * w + ((lane >> 3) & 1)) * 768 + (lane >> 4) * 128 + (((lane & 7) * 16) ^ (((lane >> 3) & 1) * 64)));
    uint32_t oa = opq(sb + SM_O + j * 6144 + (2 * w + ((lane >> 3) & 1)) * 768 + (lane >> 4) * 128 + (lane & 7) * 16);
    uint64_t dA = opq(mkdesc(SBC + SM_K, 128, KS, 0) + j * (8 * KS / 16)), dB = opq(dA + (KSLOT >> 4));
    uint64_t dV[7];
#pragma unroll
    for (int i = 0; i < 7; i++) dV[i] = opq(mkdesc(SBC + SM_V, 768, 128, 0) + j * (8 * 1536 / 16) + i * 192);
    const uint32_t nbK = opq((uint32_t)(N_KRDY + jw)), nbQ = opq((uint32_t)(N_QK0 + jw)), nbV = opq((uint32_t)(N_VQ0 + jw));
    asm volatile("barrier.cluster.wait.aligned;" ::: "memory");
    asm volatile("bar.sync 3, 256;" ::: "memory");
    float T[16];
    TRDECL;
    int b0, b1;
    uint32_t meta, ob = bar + B_ODONE * 8, fb = bar + B_OFREE * 8, fp = 1;
    const uint32_t tb = opq(sb + SM_RPB + (variant < 4 ? 3 : variant + 1 - 2 * w) * 4);
    const bool own = ((w ^ head) & 2) == 0;
    const uint32_t dst13 = sb + SM_TIN2 + head * 6144 + (2 * j + (w & 1)) * 1536, src13 = opq(own ? dst13 : sb + SM_S + (2 * j + (w & 1)) * 1536);
    const uint32_t snd[4] = {opq(own ? 0u : mapa(dst13, base + (head ^ 2))), opq(mapa(bar + (B_TIN + 2) * 8, base + (head ^ 2))),
                             opq(mapa(dst13, base + (w & 2) + (~head & 1))), opq(mapa(bar + (B_TIN + 3) * 8, base + (w & 2) + (~head & 1)))};
    BandCfg nx;
    band_cfg(0, tb, nx);
    band_load(nx, T, b0, b1, meta);
    band_cfg(1, tb, nx);
    const uint32_t zero = opq(blockIdx.x >> 16);
    uint32_t special = opq(0x380Au << 1);
    uint32_t q[12];
    mbar_wait(bar + B_Q0 * 8, 0);
#pragma unroll
    for (int k = 0; k < 3; k++) ldsm4(qa + k * 256, q[4 * k], q[4 * k + 1], q[4 * k + 2], q[4 * k + 3]);
    nb_arrive(N_Q0, 384);
#pragma unroll 1
    for (int b = 0; b < 14; b++) {
      float SA[56], SB[56];
      TR(0, b, 0);
      if (jw) mbar_wait(bar + B_KIMP * 8, b & 1);
      nb_sync(nbK, 256);
      TR(0, b, 1);
      TR(0, b - 1, 9);
      wg_fence();
      wg_rs112<0>(SA, q[0], q[1], q[2], q[3], dA);
      wg_rs112<0>(SB, q[0], q[1], q[2], q[3], dB);
      wg_rs112<1>(SA, q[4], q[5], q[6], q[7], dA + 16);
      wg_rs112<1>(SB, q[4], q[5], q[6], q[7], dB + 16);
      wg_rs112<1>(SA, q[8], q[9], q[10], q[11], dA + 32);
      wg_rs112<1>(SB, q[8], q[9], q[10], q[11], dB + 32);
      wg_commit();
      nb_arrive(nbQ, 256);
      { const uint64_t t = dA; dA = dB; dB = t; }
      special >>= 1;
      if (special & 1) {
        if (b == 3) band_cfg(13, tb, nx);
        else {
          if (b == 1 || b == 13) band_load(nx, T, b0, b1, meta);
          if (b >= TB) {
            ob = bar + (b == 13 ? (own ? B_TIN + 2 : B_ODONE) : B_OTAIL + 2 * (b - TB) + jw) * 8;
            if (b > TB) { fb = bar + (B_TFREE + b - 12) * 8; fp = 0; }
            oa += b == 12 ? 0u - (SM_O - SM_Q) : (b == 13 ? src13 - (sb + SM_Q + wt * 1536) : 0);
          }
        }
      }
      TR(0, b, 2);
      wg_wait<0>(); pin(SA); pin(SB);
      mbar_arrive_elect(bar + B_KFREE * 8);
      TR(0, b, 3);
      TR(0, b - 1, 10);
      uint32_t P[28];
      float sx[8];
      if (v2) {
        if (v1) softmax_tile<6, 7>(SA, SB, T, b0, b1, P, sx, nbV, zero, qa, q); else softmax_tile<4, 5>(SA, SB, T, b0, b1, P, sx, nbV, zero, qa, q);
      } else if (!v4) {
        if (v1) softmax_tile<2, 3>(SA, SB, T, b0, b1, P, sx, nbV, zero, qa, q); else softmax_tile<0, 1>(SA, SB, T, b0, b1, P, sx, nbV, zero, qa, q);
      } else {
        if (v1) softmax_tile<4, 4>(SA, SB, T, b0, b1, P, sx, nbV, zero, qa, q); else softmax_tile<3, 3>(SA, SB, T, b0, b1, P, sx, nbV, zero, qa, q);
      }
      float O[24];
      TR(0, b, 4);
      wg_fence();
      wg_sp48<0>(O, P[0], P[1], P[2], P[3], dV[0], meta);
#pragma unroll
      for (int s = 1; s < 7; s++) wg_sp48<1>(O, P[4 * s], P[4 * s + 1], P[4 * s + 2], P[4 * s + 3], dV[s], meta);
      wg_commit();
      nb_arrive(N_PVISS, 384);
      TR(0, b, 6);
      mbar_wait(fb, fp);
      wg_wait<0>(); pin(O);
      mbar_arrive_elect(bar + B_VFREE * 8);
      TR(0, b, 7);
      float ru, rl;
      asm("rcp.approx.ftz.f32 %0, %1;" : "=f"(ru) : "f"(((fmaf(O[0], 0.f, sx[0]) + sx[1]) + sx[2]) + sx[3]));
      asm("rcp.approx.ftz.f32 %0, %1;" : "=f"(rl) : "f"(((fmaf(O[2], 0.f, sx[4]) + sx[5]) + sx[6]) + sx[7]));
#pragma unroll
      for (int i = 0; i < 3; i++)
        stsm4(oa + i * 256, pack2(O[8 * i] * ru, O[8 * i + 1] * ru), pack2(O[8 * i + 2] * rl, O[8 * i + 3] * rl),
              pack2(O[8 * i + 4] * ru, O[8 * i + 5] * ru), pack2(O[8 * i + 6] * rl, O[8 * i + 7] * rl));
      publish(ob);
      fp ^= 1;
      meta ^= 0x55555555u;
      TR(0, b, 8);
    }
    asm volatile("{\n.reg .pred p, q;\nsetp.ne.b32 q, %1, 0;\nelect.sync _|p, 0xffffffff;\nand.pred q, q, p;\n"
                 "@q cp.async.bulk.shared::cluster.shared::cta.mbarrier::complete_tx::bytes [%1], [%0], 1536, [%2];\n"
                 "@p cp.async.bulk.shared::cluster.shared::cta.mbarrier::complete_tx::bytes [%3], [%0], 1536, [%4];\n}"
                 ::"r"(src13), "r"(snd[0]), "r"(snd[1]), "r"(snd[2]), "r"(snd[3]) : "memory");
    if (jw == 0) nb_arrive(3, 256);
    TRDUMP;
    cluster_sync();
  } else if (warp < 12) {
    TRDECL;
    TR(2, -3, 0);
    asm volatile("setmaxnreg.inc.sync.aligned.u32 %0;" ::"n"(RG));
    TR(2, -3, 1);
    GemmCtx c;
    c.bar = bar;
    const int gw = warp - 8, tk = gw * 16 + (lane & 15), hi = lane >> 4;
    { const int col = tk >> 2, i = tk & 3;
      c.kC = sb + SM_K + (col + 3) * KS + hi * 128 + i * 16;
      c.vC[0] = sb + SM_V + (col + 3) * 1536 + hi * 128 + (2 * i + ((col + 3) & 1)) * 16;
      c.qC[0] = sb + SM_Q + col * 768 + hi * 128 + (col & 1) * 64 + i * 16; }
    { const int kc = gw - 1 + 19 * odd, i = lane & 7; c.hvalid = gw > 0; c.edge = gw == (odd ? 0 : 3);
      c.kH = sb + SM_K + kc * KS + (lane >> 3) * 128 + i * 16;
      c.vH[0] = sb + SM_V + kc * 1536 + (lane >> 3) * 128 + (i >> 2) * 768 + (2 * (i & 3) + ((kc ^ (i >> 2)) & 1)) * 16; }
    Stage xs[3];
#pragma unroll
    for (int i = 0; i < 3; i++) {
      const int p = (i + 1) % 3;
      xs[i].lo = (uint32_t)mkdesc(SBC + SM_X + p * 24576, 16, 0, 0); xs[i].full = bar + (B_FULL + p) * 8;
      xs[i].em = opq(mapa(bar + (B_EMPTY + p) * 8, base + p)); xs[i].par = 0;
    }
    c.never = x == nullptr;
    c.kC = opq(c.kC); c.kH = opq(c.kH);
    c.vC[1] = opq(c.vC[0] ^ 16); c.vC[0] = opq(c.vC[0]);
    c.vH[1] = opq(c.vH[0] ^ 16); c.vH[0] = opq(c.vH[0]);
    c.qC[1] = opq(c.qC[0] ^ 64); c.qC[0] = opq(c.qC[0]);
    c.spin = 0;
    c.hiA = (uint32_t)(mkdesc(0, 0, 1024, 1) >> 32) + (blockIdx.x >> 16); c.hiB = (uint32_t)(mkdesc(0, 0, 256, 3) >> 32) + (blockIdx.x >> 16);
    asm volatile("barrier.cluster.wait.aligned;" ::: "memory");
    TR(2, -3, 2);
#pragma unroll
    for (int i = 0; i < 2 * NL; i++) sts128(wdst + (i & 1) * 3072 + (i / 2) * 18432, wv[i]);
    fence_async();
    TR(2, -3, 3);
    asm volatile("bar.sync 1, 384;" ::: "memory");
    TR(2, -3, 4);
    mbar_wait(bar + B_WK * 8, 0);
    asm volatile("griddepcontrol.launch_dependents;");
    TR(2, -3, 5);
    uint32_t pk[12], pv[12], pq[12], hk1[6], hv1[6];
    gemm_iter<true, 0>(c, -2, pk, pv, pq, hk1, hv1, xs[0], xs[1], xs[2] TRPASS);
    TR2(blockIdx.x, 4);
    c.hiA = opq(c.hiA); c.hiB = opq(c.hiB);
#pragma unroll 1
    for (int b = -1;; b += 2) {
      gemm_iter<false, 1>(c, b, pk, pv, pq, hk1, hv1, xs[2], xs[0], xs[1] TRPASS);
      if (b == 11) break;
      gemm_iter<false, 0>(c, b + 1, pk, pv, pq, hk1, hv1, xs[2], xs[0], xs[1] TRPASS);
      const Stage t = xs[2]; xs[2] = xs[1]; xs[1] = xs[0]; xs[0] = t;
    }
    TR2(blockIdx.x, 6);
    c.hiA = opq(c.hiA); c.hiB = opq(c.hiB);
    const uint32_t st = sb + gw * 3072;
    const uint32_t sta = st + (lane & 15) * 64 + ((hi ^ ((lane >> 1) & 3)) * 16);
    const int oc = ph * 112 + strip * 16 + 8 * (gw >> 1) + 4 * (head >> 1) + 2 * (gw & 1), och = pw * 6 + (head & 1) * 3;
    float D0[48], D1[48];
    mbar_arrive_elect(bar + B_WOFREE * 8);
    dump12<128>(c.qC[1], pq);
    nb_sync(N_QK1, 256);
    issue_halo<0, 8>(c, xs[2], D1);
    fence_async();
    nb_arrive(N_VQ0, 288); nb_arrive(N_VQ1, 288); nb_arrive(N_PVISS, 384);
    issue_halo<8, 12>(c, xs[2], D1);
    gwait<0>(c, B_KFREE);
    dump12<128>(c.kC, pk);
    if (c.edge) publish(bar + B_XK * 8);
    wg_wait<0>(); pin(D1);
    pack6(hk1, D1, 0);
    if (c.hvalid) dump6(c.kH, hk1);
    tail_free(bar + (B_TFREE + 1) * 8);
    pack6(hv1, D1, 24);
    fence_async();
    nb_arrive(N_KRDY, 256);
    gwait<0>(c, B_VFREE);
    dump12<128>(c.vC[0], pv);
    if (c.hvalid) dump6(c.vH[0], hv1);
    fence_async();
    edge_ready(c, B_XV);
    nb_arrive(N_VQ0, 288); nb_arrive(N_VQ1, 288);
    gwait<0>(c, B_WO);
    gwait<0>(c, B_TIN);
    TR(2, 13, 0);
    nb_sync(N_QK1, 256);
    issue_proj<SM_TIN0>(D0);
    wg_wait<0>(); pin(D0);
    TR(2, 13, 1);
    store_proj(D0, &mp.ot, st + SM_TST, sta + SM_TST, 8 * TB, oc, och);
    gwait<0>(c, B_TIN + 1);
    TR(2, 13, 2);
    nb_sync(N_PVISS, 384);
    nb_sync(3, 256);
    issue_proj<SM_TIN1>(D1);
    wg_wait<0>(); pin(D1);
    TR(2, 13, 3);
    store_proj(D1, &mp.ot, st + SM_TIN0, sta + SM_TIN0, 8 * TB + 8, oc, och);
    TR(2, 13, 4);
    gwait<0>(c, B_TIN + 2);
    TR(2, 13, 5);
    issue_proj_half<0>(D0, head & 1);
    gwait<0>(c, B_TIN + 3);
    TR(2, 13, 6);
    issue_proj_half<1>(D0, ~head & 1);
    asm volatile("barrier.cluster.arrive.relaxed.aligned;" ::: "memory");
    wg_wait<0>(); pin(D0);
    store_proj(D0, &mp.ot, st + SM_TIN0 + 12288, sta + SM_TIN0 + 12288, 8 * TB + 16, oc, och);
    TR(2, 13, 7);
    if (lane == 0) asm volatile("cp.async.bulk.wait_group.read 0;" ::: "memory");
    __syncwarp();
    TR(2, 13, 8);
    TR2(blockIdx.x, 2);
    TR2FLUSH(blockIdx.x);
    TRDUMP;
    asm volatile("barrier.cluster.wait.aligned;" ::: "memory");
  } else {
    asm volatile("setmaxnreg.dec.sync.aligned.u32 24;");
    if (warp == 15) {
      const int l = min(lane, 24), row = head + (l < 16 ? 0 : 4 * ((l - 16) / 3)), col = strip * 16 + (l < 16 ? l : (l - 16) % 3 + (odd ? 16 : (strip ? -3 : 0)));
      const uint8_t* p = reinterpret_cast<const uint8_t*>(x) + (uint32_t)(row * ROWB + (ph * 112 + col) * 768 + pw * 384);
#pragma unroll
      for (int i = 0; i < 3; i++) asm volatile("prefetch.global.L2 [%0];" ::"l"(p + i * 128));
    } else if (elect_one()) {
      if (warp == 12) {
        mbar_init(bar + B_WK * 8, 1);
#pragma unroll
        for (int i = 0; i < NL; i++) load_w(&mp.w, sb + SM_W + (3 * i + 5 - 2 * va) * 6144, bar + B_WK * 8, (i + 1) * 192 + head * 48 + 32 - 32 * va);
        asm volatile("prefetch.tensormap [%0];" ::"l"(head == 1 ? &mp.xh : &mp.xc) : "memory");
      } else if (warp == 13) {
#pragma unroll
        for (int i = 0; i < B_XK; i++) if (i != B_WK) mbar_init(bar + i * 8, (i >= B_EMPTY && i < B_TIN) || (i >= B_TFREE && i < B_WK) ? 16 : (i == B_TIN + 2 ? 5 : 1));
      } else {
#pragma unroll
        for (int i = B_XK; i < B_COUNT; i++) mbar_init(bar + i * 8, i < B_Q0 ? 2 : (i < B_ODONE ? 4 : (i == B_VFREE ? 9 : 8)));
      }
      asm volatile("fence.mbarrier_init.release.cluster;" ::: "memory");
    }
    __syncwarp();
    asm volatile("barrier.cluster.arrive.relaxed.aligned;" ::: "memory");
    if (warp != 12) asm volatile("barrier.cluster.wait.aligned;" ::: "memory");
    else {
      const int cc = ph * 112 + strip * 16, ch = cc + (odd ? 16 : (strip ? -3 : 0)), rh = strip ? -4 : 112;
      const uint32_t fb = opq(bar + (B_FULL + head) * 8), dst0 = sb + SM_X + head * 24576, c3 = opq((uint32_t)(pw * 3)), mask = opq(15u << base);
      int t = head == 0 ? 2 : head - 1;
      uint64_t mx = opq((uint64_t)(t ? &mp.xc : &mp.xh));
      uint32_t row = opq((uint32_t)(t ? 4 * t - 4 : rh)), col = opq((uint32_t)(t ? cc : ch)), dst = opq(dst0 + (t ? 0 : 2048));
#pragma unroll 1
      for (int n = 0;; n++) {
        if (n) mbar_wait(fb + (B_EMPTY - B_FULL) * 8, ~n & 1);
        else asm volatile("barrier.cluster.wait.aligned;" ::: "memory");
        if (head < 3) {
          asm volatile("{\n.reg .pred p;\n.reg .b16 m;\nelect.sync _|p, 0xffffffff;\ncvt.u16.u32 m, %7;\n"
                       "@p cp.async.bulk.tensor.4d.shared::cluster.global.mbarrier::complete_tx::bytes.multicast::cluster [%0], [%1, {%3,%4,%5,%6}], [%2], m;\n}"
                       ::"r"(dst), "l"(mx), "r"(fb), "r"(0), "r"(row), "r"(col), "r"(c3), "r"(mask) : "memory");
          if (lane < 4) remote_expect(mapa(fb, base + lane), dst == dst0 ? 24576 : 18432);
          __syncwarp();
        }
        if (n == 0 && elect_one()) {
#pragma unroll
          for (int i = 0; i < 3; i++) load_w(&mp.w, sb + SM_W + i * 6144, bar + B_WQ * 8, head * 48 + i * 16);
          mbar_expect(bar + B_WQ * 8, 18432);
        }
        __syncwarp();
        if (head == 3 || n == 11) break;
        t += 3;
        const int hn = t / 5;
        const bool core = t != 5 * hn;
        mx = opq((uint64_t)(core ? &mp.xc : &mp.xh));
        row = opq((uint32_t)(core ? 4 * (t - hn - 1) : rh + 16 * hn)); col = opq((uint32_t)(core ? cc : ch)); dst = opq(dst0 + (core ? 0 : 2048));
        if (elect_one()) asm volatile("cp.async.bulk.prefetch.tensor.4d.L2.global [%0, {%1,%2,%3,%4}];" ::"l"(mx), "r"(0), "r"(row), "r"(col), "r"(c3) : "memory");
        __syncwarp();
      }
      mbar_wait(bar + B_WOFREE * 8, 0);
      if (elect_one()) {
        mbar_expect(bar + B_WO * 8, 36864);
        asm volatile("cp.async.bulk.tensor.3d.shared::cluster.global.mbarrier::complete_tx::bytes [%0], [%1, {%3,%4,%5}], [%2];"
                     ::"r"(sb + SM_TWO), "l"(&mp.wo), "r"(bar + B_WO * 8), "r"(0), "r"(0), "r"((head & 1) * 3) : "memory");
      }
      __syncwarp();
    }
    if (warp & 1) {
      const uint32_t partner = (blockIdx.x & 7) ^ 4;
      const int cs = odd ? 3 : (strip == 6 ? 15 : 16), cd = odd || strip == 6 ? 19 : 0;
      const uint32_t rb = opq(mapa(bar, partner));
      TRDECL;
      if (warp == 13) {
        const uint32_t dst = opq(mapa(sb + SM_V + cd * 1536, partner)), src = opq(sb + SM_V + cs * 1536);
#pragma unroll 1
        for (int b = 0;; b++) {
          const uint32_t pa = b & 1;
          nb_arrive(N_VQ0, 288);
          mbar_wait(bar + B_XV * 8, pa);
          TR(1, b, 0);
          if (elect_one()) { copy_remote(dst, src, 4608, rb + B_VIMP * 8); remote_expect(rb + B_VIMP * 8, 4608); }
          __syncwarp();
          TR(1, b, 1);
          mbar_wait(bar + B_VIMP * 8, pa);
          TR(1, b, 2);
          nb_arrive(N_VQ1, 288);
          if (elect_one()) remote_arrive(rb + B_VFREE * 8);
          __syncwarp();
          TR(1, b, 3);
          if (b == 13) break;
          mbar_wait(bar + B_VFREE * 8, pa);
          if (elect_one()) remote_arrive(rb + B_XV * 8);
          __syncwarp();
        }
      } else {
        const uint32_t dst = opq(mapa(sb + SM_K + cd * KS, partner)), src = opq(sb + SM_K + cs * KS);
#pragma unroll 1
        for (int b = 0;; b++) {
          const uint32_t pa = b & 1, so = (pa ^ 1) * KSLOT;
          mbar_wait(bar + B_XK * 8, pa);
          TR(1, b - 1, 4);
          if (elect_one()) {
            copy_remote(dst + so, src + so, 3 * KS, rb + B_KIMP * 8);
            if (b == 0) copy_remote(dst, src, 3 * KS, rb + B_KIMP * 8);
            remote_expect(rb + B_KIMP * 8, b ? 3 * KS : 6 * KS);
          }
          __syncwarp();
          TR(1, b - 1, 5);
          TR(1, b - 1, 7);
          if (b == 13) break;
          mbar_wait(bar + B_KFREE * 8, pa);
          if (elect_one()) remote_arrive(rb + B_XK * 8);
          __syncwarp();
        }
      }
      TRDUMP;
    }
    if (warp == 14) {
      int* flag = g_flags + (par * 7 + strip) * 2 * FS;
      if (elect_one()) {
        mbar_expect(bar + B_WK * 8, NL * 6144);
        mbar_arrive(bar + B_XK * 8); mbar_arrive(bar + B_XV * 8);
        mbar_expect(bar + B_TIN * 8, 24576); mbar_expect(bar + (B_TIN + 1) * 8, 24576); mbar_expect(bar + (B_TIN + 2) * 8, 6144); mbar_expect(bar + (B_TIN + 3) * 8, 12288);
      }
      __syncwarp();
#pragma unroll 1
      for (int b = 0; b < TB; b++) {
        mbar_wait(bar + B_ODONE * 8, b & 1);
        if (lane == 0) {
#pragma unroll 1
          for (int i = 0; i < 16; i += OCH) {
            asm volatile("cp.async.bulk.tensor.3d.global.shared::cta.bulk_group [%0, {%2,%3,%4}], [%1];"
                         ::"l"(&mp.os), "r"(sb + SM_O + i * 768), "r"(pw * 192), "r"(8 * b + 2 * head), "r"(ph * 112 + strip * 16 + i) : "memory");
            asm volatile("cp.async.bulk.commit_group;\ncp.async.bulk.wait_group 0;" ::: "memory");
          }
        }
        __syncwarp();
        mbar_arrive_elect(bar + B_OFREE * 8);
        if (lane == 0)
          asm volatile("fence.proxy.async.global;\nfence.acq_rel.gpu;\nred.relaxed.gpu.global.add.s32 [%0], 1;\nred.relaxed.gpu.global.add.s32 [%1], 1;"
                       ::"l"(flag + b * 56 * FS), "l"(flag + (b * 56 + 1) * FS) : "memory");
        __syncwarp();
      }
#pragma unroll 1
      for (int t = 0; t < 4; t++) {
        const int i = t >> 1, j = (t ^ odd) & 1, d = (lane + head + 1) & 3;
        const uint32_t dst = opq(mapa(sb + (i ? SM_TIN1 : SM_TIN0) + head * 6144 + j * 3072, base + d)), rb = opq(mapa(bar + (B_TIN + i) * 8, base + d));
        const uint32_t src = opq(sb + (i ? SM_Q : SM_O) + j * 6144 + (d & 2) * 1536);
        if (!(t & 1)) mbar_wait(bar + (B_TFREE + i) * 8, 0);
        mbar_wait(bar + (B_OTAIL + t) * 8, 0);
        if (lane < 4) copy_remote(dst, src, 3072, rb);
        __syncwarp();
      }
    }
    cluster_sync();
  }
}

constexpr int NSTB = 6;
constexpr int NTB = TB * 56;
constexpr int SM_B_ST = 0;
constexpr int SM_B_IN = 73728;
constexpr int SM_B_W = SM_B_IN + 3 * 24576;
constexpr int SM_B_BAR = SM_B_IN + NSTB * 24576;
constexpr int SM_B_TOTAL = SM_B_BAR + 512;
struct MapsB { CUtensorMap oi, oo, wo; };

__global__ void __launch_bounds__(512, 1)
na_proj_kernel(const __grid_constant__ MapsB mp) {
  extern __shared__ __align__(1024) uint8_t smem_raw[];
  const uint32_t sb = smem_u32(smem_raw);
  if ((sb & 0x3FFFF) != SBC) return;
  const uint32_t bar = sb + SM_B_BAR;
  const int tid = threadIdx.x, lane = tid & 31;
  const int warp = __shfl_sync(0xffffffffu, tid >> 5, 0);
  TR2START;
  TRB(47, 0);
  if (warp == 12 && elect_one()) {
#pragma unroll
    for (int i = 0; i <= 2 * NSTB; i++) mbar_init(bar + i * 8, i < NSTB || i == 2 * NSTB ? 1 : 12);
    asm volatile("st.shared.u32 [%0], 0;" ::"r"(bar + 120) : "memory");
    mbar_expect(bar + 2 * NSTB * 8, 73728);
#pragma unroll
    for (int i = 0; i < 2; i++)
      asm volatile("cp.async.bulk.tensor.3d.shared::cluster.global.mbarrier::complete_tx::bytes [%0], [%1, {%3,%4,%5}], [%2];"
                   ::"r"(sb + SM_B_W + i * 36864), "l"(&mp.wo), "r"(bar + 2 * NSTB * 8), "r"(0), "r"(0), "r"(i * 3) : "memory");
  }
  __syncthreads();
  const int step = gridDim.x;
  if (warp == 15) {
    int so = 0;
    nb_arrive(4, 288); nb_arrive(5, 288); nb_arrive(6, 288);
#pragma unroll 1
    for (int n = blockIdx.x, tk = 0; n < NTB; n += step, tk++) {
      uint32_t cc = 0;
#pragma unroll
      for (int wg = 0; wg < 3; wg++) {
        if (lane == 0) asm volatile("cp.async.bulk.wait_group.read 5;" ::: "memory");
        nb_sync(1 + wg, 160);
        if (wg == 0 || n + step < NTB) nb_arrive(4 + wg, 288);
        if (wg == 0) asm volatile("ld.shared.u32 %0, [%1];" : "=r"(cc) : "r"(bar + 128 + tk * 4) : "memory");
        if (lane == 0) {
          asm volatile("cp.async.bulk.tensor.4d.global.shared::cta.bulk_group [%0, {%2,%3,%4,%5}], [%1];"
                       ::"l"(&mp.oo), "r"(sb + SM_B_ST + wg * 8192 + so), "r"(0), "r"((cc >> 8) & 255), "r"(cc >> 16), "r"((cc & 1) * 3 + wg) : "memory");
          asm volatile("cp.async.bulk.commit_group;" ::: "memory");
        }
        __syncwarp();
      }
      so = so == 49152 ? 0 : so + 24576;
    }
    if (lane == 0) asm volatile("cp.async.bulk.wait_group.read 0;" ::: "memory");
  } else if (warp >= 12) {
    nb_sync(7, 480);
#pragma unroll 1
    for (int n = blockIdx.x + (warp - 12) * step; n < NTB; n += 3 * step) {
      const int b = n / 56, rem = n - b * 56, par = rem / 14;
      const int c0 = opq((uint32_t)(par & 1)), c1 = opq((uint32_t)(8 * b)), c2 = opq((uint32_t)((par >> 1) * 112 + (rem - par * 14) * 8));
      int v; uint32_t spin = 0, tk = 0;
      do { asm volatile("ld.acquire.gpu.global.s32 %0, [%1];" : "=r"(v) : "l"(g_flags + n * FS) : "memory"); } while (v < 4 && ++spin < SPIN_LIMIT);
      if (lane == 0) asm volatile("atom.shared.add.u32 %0, [%1], 1;" : "=r"(tk) : "r"(bar + 120) : "memory");
      asm volatile("fence.proxy.async.global;" ::: "memory");
      tk = __shfl_sync(0xffffffffu, tk, 0);
      TRB(tk, 0);
      const uint32_t use = tk / NSTB, sg = tk - use * NSTB;
      if (use) mbar_wait(bar + (NSTB + sg) * 8, (use - 1) & 1);
      TRB(tk, 1);
      if (elect_one()) {
        asm volatile("st.shared.u32 [%0], %1;" ::"r"(bar + 128 + tk * 4), "r"(c0 | c1 << 8 | c2 << 16) : "memory");
        mbar_expect(bar + sg * 8, 24576);
        asm volatile("cp.async.bulk.tensor.3d.shared::cluster.global.mbarrier::complete_tx::bytes [%0], [%1, {%3,%4,%5}], [%2];"
                     ::"r"(sb + SM_B_IN + sg * 24576), "l"(&mp.oi), "r"(bar + sg * 8), "r"(c0 * 192), "r"(c1), "r"(c2) : "memory");
        g_flags[n * FS] = 0;
      }
      __syncwarp();
    }
  } else {
    const int wg = warp >> 2, w = warp & 3;
    uint32_t a[48];
    mbar_wait(bar + 2 * NSTB * 8, 0);
    {
      const int k = (lane & 7) + (lane >> 4) * 8, ch = (warp & 1) * 2 + ((lane >> 3) & 1);
      const uint32_t wa = sb + SM_B_W + (warp >> 1) * 12288 + k * 64 + ((ch ^ ((k >> 1) & 3)) * 16);
#pragma unroll
      for (int i = 0; i < 12; i++)
        asm volatile("ldmatrix.sync.aligned.m8n8.x4.trans.shared.b16 {%0,%1,%2,%3}, [%4];"
                     : "=r"(a[4 * i]), "=r"(a[4 * i + 1]), "=r"(a[4 * i + 2]), "=r"(a[4 * i + 3]) : "r"(wa + i * 1024) : "memory");
    }
    nb_sync(7, 480);
    TRB(47, 1);
    const uint32_t sta = opq(sb + SM_B_ST + wg * 8192 + ((lane & 7) + (lane >> 4) * 8) * 128 + (((2 * w + ((lane >> 3) & 1)) ^ (lane & 7)) * 16));
    const uint32_t hi = opq((uint32_t)(mkdesc(0, 0, 3072, 0) >> 32) + (blockIdx.x >> 16)), bb = opq(bar);
    const uint32_t nbT = opq((uint32_t)(4 + wg)), nbN = opq((uint32_t)(wg == 2 ? 4 : 5 + wg)), nbD = opq((uint32_t)(1 + wg));
    int left = (NTB - blockIdx.x + step - 1) / step;
    if (wg == 2) nb_arrive(4, 288);
#pragma unroll 1
    for (uint32_t ph = 0;; ph ^= 1) {
#pragma unroll
      for (int sg = 0; sg < NSTB; sg++) {
        constexpr uint64_t db = mkdesc(SBC + SM_B_IN, 128, 3072, 0);
        float D[32];
        mbar_wait(bb + sg * 8, ph);
        nb_sync(nbT, 288);
        wg_fence();
        wg_rs64<0>(D, a[0], a[1], a[2], a[3], dsc(db + sg * 1536, hi));
#pragma unroll
        for (int k = 1; k < 12; k++) wg_rs64<1>(D, a[4 * k], a[4 * k + 1], a[4 * k + 2], a[4 * k + 3], dsc(db + sg * 1536 + k * 16, hi));
        wg_commit();
        nb_arrive(nbN, 288);
        wg_wait<0>(); pin(D);
        mbar_arrive_elect(bb + (NSTB + sg) * 8);
#pragma unroll
        for (int q = 0; q < 4; q++)
          asm volatile("stmatrix.sync.aligned.m8n8.x4.trans.shared.b16 [%0], {%1,%2,%3,%4};" ::"r"(sta + (sg % 3) * 24576 + q * 2048),
                       "r"(pack2(D[8 * q], D[8 * q + 1])), "r"(pack2(D[8 * q + 2], D[8 * q + 3])), "r"(pack2(D[8 * q + 4], D[8 * q + 5])), "r"(pack2(D[8 * q + 6], D[8 * q + 7])) : "memory");
        fence_async();
        nb_arrive(nbD, 160);
        if (wg == 0) TRB(31 - left, 5);
        if (--left == 0) goto done;
      }
    }
  done:
    if (wg == 0) nb_arrive(4, 288);
    TR2(132 + blockIdx.x, 2);
    TR2FLUSH(132 + blockIdx.x);
  }
}

typedef CUresult (*EncodeFn)(CUtensorMap*, CUtensorMapDataType, cuuint32_t, void*, const cuuint64_t*, const cuuint64_t*, const cuuint32_t*,
                             const cuuint32_t*, CUtensorMapInterleave, CUtensorMapSwizzle, CUtensorMapL2promotion, CUtensorMapFloatOOBfill);
static EncodeFn g_enc = nullptr;
static void make_map(CUtensorMap* m, const void* p, int rank, const cuuint64_t* dim, const cuuint64_t* str, const cuuint32_t* box, CUtensorMapSwizzle sw) {
  const cuuint32_t ones[5] = {1, 1, 1, 1, 1};
  g_enc(m, CU_TENSOR_MAP_DATA_TYPE_BFLOAT16, rank, (void*)p, dim, str, box, ones, CU_TENSOR_MAP_INTERLEAVE_NONE, sw,
        CU_TENSOR_MAP_L2_PROMOTION_L2_128B, CU_TENSOR_MAP_FLOAT_OOB_FILL_NONE);
}

extern "C" void kernel_launch(void* const* d_in, const int* in_sizes, int n_in, void* d_out, int out_size) {
  const __nv_bfloat16* x = (const __nv_bfloat16*)d_in[0];
  const __nv_bfloat16* wqkv = (const __nv_bfloat16*)d_in[1];
  const __nv_bfloat16* wo = (const __nv_bfloat16*)d_in[2];
  const __nv_bfloat16* rpb = (const __nv_bfloat16*)d_in[3];

  if (!g_enc) {
    void* fn = nullptr; cudaDriverEntryPointQueryResult qr;
    cudaGetDriverEntryPoint("cuTensorMapEncodeTiled", &fn, cudaEnableDefault, &qr);
    g_enc = (EncodeFn)fn;
    cudaFuncSetAttribute(na_attn_kernel, cudaFuncAttributeMaxDynamicSharedMemorySize, SM_A_TOTAL);
    cudaFuncSetAttribute(na_proj_kernel, cudaFuncAttributeMaxDynamicSharedMemorySize, SM_B_TOTAL);
  }
  Maps ma; MapsB mb;
  { cuuint64_t dim[4] = {64, 112, 224, 6}, str[3] = {(cuuint64_t)ROWB, 768, 128};
    cuuint32_t box[4] = {64, 4, 16, 3}, boxh[4] = {64, 16, 3, 3}, boxo[4] = {64, 8, 8, 1};
    make_map(&ma.xc, x, 4, dim, str, box, CU_TENSOR_MAP_SWIZZLE_128B);
    make_map(&ma.xh, x, 4, dim, str, boxh, CU_TENSOR_MAP_SWIZZLE_128B);
    make_map(&mb.oo, d_out, 4, dim, str, boxo, CU_TENSOR_MAP_SWIZZLE_128B); }
  { cuuint64_t dim[3] = {384, 112, 224}, str[2] = {(cuuint64_t)ROWB, 768};
    cuuint32_t box[3] = {192, 8, 8}, boxs[3] = {192, 2, OCH};
    make_map(&mb.oi, d_out, 3, dim, str, box, CU_TENSOR_MAP_SWIZZLE_NONE);
    make_map(&ma.os, d_out, 3, dim, str, boxs, CU_TENSOR_MAP_SWIZZLE_NONE); }
  { cuuint64_t dim[4] = {32, 112, 224, 12}, str[3] = {(cuuint64_t)ROWB, 768, 64};
    cuuint32_t box[4] = {32, 8, 2, 3};
    make_map(&ma.ot, d_out, 4, dim, str, box, CU_TENSOR_MAP_SWIZZLE_64B); }
  { cuuint64_t dim[2] = {576, 192}, str[1] = {1152};
    cuuint32_t box[2] = {16, 192};
    make_map(&ma.w, wqkv, 2, dim, str, box, CU_TENSOR_MAP_SWIZZLE_32B); }
  { cuuint64_t dim[3] = {32, 192, 6}, str[2] = {384, 64};
    cuuint32_t box[3] = {32, 192, 3};
    make_map(&ma.wo, wo, 3, dim, str, box, CU_TENSOR_MAP_SWIZZLE_64B);
    mb.wo = ma.wo; }
  na_attn_kernel<<<112, 512, SM_A_TOTAL>>>(x, wqkv, rpb, ma);
  cudaLaunchConfig_t cfg = {};
  cfg.gridDim = dim3(20); cfg.blockDim = dim3(512); cfg.dynamicSmemBytes = SM_B_TOTAL; cfg.stream = cudaStreamPerThread;
  cudaLaunchAttribute at[1];
  at[0].id = cudaLaunchAttributeProgrammaticStreamSerialization; at[0].val.programmaticStreamSerializationAllowed = 1;
  cfg.attrs = at; cfg.numAttrs = 1;
  cudaLaunchKernelEx(&cfg, na_proj_kernel, mb);
}
```

```cpp
#include <cuda_runtime.h>
#include <cuda_bf16.h>
#include <cuda.h>
#include <stdint.h>

#define SPIN_LIMIT (1u << 18)

__device__ __forceinline__ uint32_t smem_u32(const void* p) { return (uint32_t)__cvta_generic_to_shared(p); }
__device__ __forceinline__ void wg_fence() { asm volatile("wgmma.fence.sync.aligned;" ::: "memory"); }
__device__ __forceinline__ void wg_commit() { asm volatile("wgmma.commit_group.sync.aligned;" ::: "memory"); }
template <int N> __device__ __forceinline__ void wg_wait() { asm volatile("wgmma.wait_group.sync.aligned %0;" ::"n"(N) : "memory"); }
template <int N> __device__ __forceinline__ void pin(float (&d)[N]) {
#pragma unroll
  for (int i = 0; i < N; i++) asm volatile("" : "+f"(d[i])::"memory");
}
__host__ __device__ constexpr uint64_t mkdesc(uint32_t addr, uint32_t lbo, uint32_t sbo, uint32_t sw) {
  return (uint64_t)((addr & 0x3FFFF) >> 4) | ((uint64_t)(lbo >> 4) << 16) | ((uint64_t)(sbo >> 4) << 32) | ((uint64_t)sw << 62);
}
__device__ __forceinline__ void mbar_init(uint32_t bar, uint32_t cnt) { asm volatile("mbarrier.init.shared::cta.b64 [%0], %1;" ::"r"(bar), "r"(cnt) : "memory"); }
__device__ __forceinline__ void mbar_arrive(uint32_t bar) { asm volatile("mbarrier.arrive.shared::cta.b64 _, [%0];" ::"r"(bar) : "memory"); }
__device__ __forceinline__ bool elect_one() {
  uint32_t r; asm volatile("{\n.reg .pred p;\nelect.sync _|p, 0xffffffff;\nselp.u32 %0, 1, 0, p;\n}" : "=r"(r)); return r;
}
__device__ __forceinline__ void mbar_arrive_elect(uint32_t bar) {
  asm volatile("{\n.reg .pred p;\nelect.sync _|p, 0xffffffff;\n@p mbarrier.arrive.shared::cta.b64 _, [%0];\n}" ::"r"(bar) : "memory");
}
__device__ __forceinline__ void mbar_expect(uint32_t bar, uint32_t bytes) { asm volatile("mbarrier.arrive.expect_tx.shared::cta.b64 _, [%0], %1;" ::"r"(bar), "r"(bytes) : "memory"); }
__device__ __forceinline__ void mbar_arrive_remote(uint32_t bar, uint32_t cta) {
  asm volatile("{\n.reg .b32 ra;\nmapa.shared::cluster.u32 ra, %0, %1;\nmbarrier.arrive.relaxed.cluster.shared::cluster.b64 _, [ra];\n}" ::"r"(bar), "r"(cta) : "memory");
}
__device__ __forceinline__ void mbar_wait(uint32_t bar, uint32_t parity) {
  asm volatile("{\n.reg .pred p;\n.reg .b32 n;\nmov.b32 n, 0;\nWL:\nmbarrier.try_wait.parity.shared::cta.b64 p, [%0], %1;\n@p bra WD;\n"
               "add.u32 n, n, 1;\nsetp.lt.u32 p, n, 65536;\n@p bra WL;\nWD:\n}" ::"r"(bar), "r"(parity) : "memory");
}
__device__ __forceinline__ void nb_sync(int id, int n) { asm volatile("bar.sync %0, %1;" ::"r"(id), "r"(n) : "memory"); }
__device__ __forceinline__ void nb_arrive(int id, int n) { asm volatile("bar.arrive %0, %1;" ::"r"(id), "r"(n) : "memory"); }
__device__ __forceinline__ uint32_t opq(uint32_t x) { uint32_t r; asm volatile("mov.b32 %0, %1;" : "=r"(r) : "r"(x)); return r; }
__device__ __forceinline__ uint64_t opq(uint64_t x) { uint64_t r; asm volatile("mov.b64 %0, %1;" : "=l"(r) : "l"(x)); return r; }
__device__ __forceinline__ uint32_t mapa(uint32_t a, uint32_t cta) { uint32_t r; asm("mapa.shared::cluster.u32 %0, %1, %2;" : "=r"(r) : "r"(a), "r"(cta)); return r; }
__device__ __forceinline__ void fence_async() { asm volatile("fence.proxy.async.shared::cta;" ::: "memory"); }
__device__ __forceinline__ void cluster_sync() {
  asm volatile("barrier.cluster.arrive.relaxed.aligned;\nbarrier.cluster.wait.aligned;" ::: "memory");
}
__device__ __forceinline__ uint32_t pack2(float lo, float hi) {
  uint32_t r; asm("cvt.rn.bf16x2.f32 %0, %1, %2;" : "=r"(r) : "f"(hi), "f"(lo)); return r;
}
__device__ __forceinline__ void stsm4(uint32_t a, uint32_t r0, uint32_t r1, uint32_t r2, uint32_t r3) {
  asm volatile("stmatrix.sync.aligned.m8n8.x4.shared.b16 [%0], {%1,%2,%3,%4};" ::"r"(a), "r"(r0), "r"(r1), "r"(r2), "r"(r3) : "memory");
}
__device__ __forceinline__ void ldsm4(uint32_t a, uint32_t& r0, uint32_t& r1, uint32_t& r2, uint32_t& r3) {
  asm volatile("ldmatrix.sync.aligned.m8n8.x4.shared.b16 {%0,%1,%2,%3}, [%4];" : "=r"(r0), "=r"(r1), "=r"(r2), "=r"(r3) : "r"(a) : "memory");
}
__device__ __forceinline__ void sts128(uint32_t a, uint4 v) {
  asm volatile("st.shared.v4.b32 [%0], {%1,%2,%3,%4};" ::"r"(a), "r"(v.x), "r"(v.y), "r"(v.z), "r"(v.w) : "memory");
}
__device__ __forceinline__ float lds_f32(uint32_t a) { float v; asm volatile("ld.shared.f32 %0, [%1];" : "=f"(v) : "r"(a)); return v; }
__device__ __forceinline__ float ex2(float x) { float y; asm("ex2.approx.ftz.f32 %0, %1;" : "=f"(y) : "f"(x)); return y; }

template<int SC> __device__ __forceinline__ void wg_ss144(float (&d)[72], uint64_t da, uint64_t db) {
  asm volatile("{\n.reg .pred p;\nsetp.ne.b32 p, %74, 0;\nwgmma.mma_async.sync.aligned.m64n144k16.f32.bf16.bf16 {%0,%1,%2,%3,%4,%5,%6,%7,%8,%9,%10,%11,%12,%13,%14,%15,%16,%17,%18,%19,%20,%21,%22,%23,%24,%25,%26,%27,%28,%29,%30,%31,%32,%33,%34,%35,%36,%37,%38,%39,%40,%41,%42,%43,%44,%45,%46,%47,%48,%49,%50,%51,%52,%53,%54,%55,%56,%57,%58,%59,%60,%61,%62,%63,%64,%65,%66,%67,%68,%69,%70,%71}, %72, %73, p, 1, 1, 0, 1;\n}\n"
    : "+f"(d[0]),"+f"(d[1]),"+f"(d[2]),"+f"(d[3]),"+f"(d[4]),"+f"(d[5]),"+f"(d[6]),"+f"(d[7]),"+f"(d[8]),"+f"(d[9]),"+f"(d[10]),"+f"(d[11]),"+f"(d[12]),"+f"(d[13]),"+f"(d[14]),"+f"(d[15]),"+f"(d[16]),"+f"(d[17]),"+f"(d[18]),"+f"(d[19]),"+f"(d[20]),"+f"(d[21]),"+f"(d[22]),"+f"(d[23]),"+f"(d[24]),"+f"(d[25]),"+f"(d[26]),"+f"(d[27]),"+f"(d[28]),"+f"(d[29]),"+f"(d[30]),"+f"(d[31]),"+f"(d[32]),"+f"(d[33]),"+f"(d[34]),"+f"(d[35]),"+f"(d[36]),"+f"(d[37]),"+f"(d[38]),"+f"(d[39]),"+f"(d[40]),"+f"(d[41]),"+f"(d[42]),"+f"(d[43]),"+f"(d[44]),"+f"(d[45]),"+f"(d[46]),"+f"(d[47]),"+f"(d[48]),"+f"(d[49]),"+f"(d[50]),"+f"(d[51]),"+f"(d[52]),"+f"(d[53]),"+f"(d[54]),"+f"(d[55]),"+f"(d[56]),"+f"(d[57]),"+f"(d[58]),"+f"(d[59]),"+f"(d[60]),"+f"(d[61]),"+f"(d[62]),"+f"(d[63]),"+f"(d[64]),"+f"(d[65]),"+f"(d[66]),"+f"(d[67]),"+f"(d[68]),"+f"(d[69]),"+f"(d[70]),"+f"(d[71]) : "l"(da), "l"(db), "n"(SC));
}
template<int SC> __device__ __forceinline__ void wg_ss96(float (&d)[48], uint64_t da, uint64_t db) {
  asm volatile("{\n.reg .pred p;\nsetp.ne.b32 p, %50, 0;\nwgmma.mma_async.sync.aligned.m64n96k16.f32.bf16.bf16 {%0,%1,%2,%3,%4,%5,%6,%7,%8,%9,%10,%11,%12,%13,%14,%15,%16,%17,%18,%19,%20,%21,%22,%23,%24,%25,%26,%27,%28,%29,%30,%31,%32,%33,%34,%35,%36,%37,%38,%39,%40,%41,%42,%43,%44,%45,%46,%47}, %48, %49, p, 1, 1, 0, 1;\n}\n"
    : "+f"(d[0]),"+f"(d[1]),"+f"(d[2]),"+f"(d[3]),"+f"(d[4]),"+f"(d[5]),"+f"(d[6]),"+f"(d[7]),"+f"(d[8]),"+f"(d[9]),"+f"(d[10]),"+f"(d[11]),"+f"(d[12]),"+f"(d[13]),"+f"(d[14]),"+f"(d[15]),"+f"(d[16]),"+f"(d[17]),"+f"(d[18]),"+f"(d[19]),"+f"(d[20]),"+f"(d[21]),"+f"(d[22]),"+f"(d[23]),"+f"(d[24]),"+f"(d[25]),"+f"(d[26]),"+f"(d[27]),"+f"(d[28]),"+f"(d[29]),"+f"(d[30]),"+f"(d[31]),"+f"(d[32]),"+f"(d[33]),"+f"(d[34]),"+f"(d[35]),"+f"(d[36]),"+f"(d[37]),"+f"(d[38]),"+f"(d[39]),"+f"(d[40]),"+f"(d[41]),"+f"(d[42]),"+f"(d[43]),"+f"(d[44]),"+f"(d[45]),"+f"(d[46]),"+f"(d[47]) : "l"(da), "l"(db), "n"(SC));
}
template<int SC> __device__ __forceinline__ void wg_rs112(float (&d)[56], uint32_t a0, uint32_t a1, uint32_t a2, uint32_t a3, uint64_t db) {
  asm volatile("{\n.reg .pred p;\nsetp.ne.b32 p, %61, 0;\nwgmma.mma_async.sync.aligned.m64n112k16.f32.bf16.bf16 {%0,%1,%2,%3,%4,%5,%6,%7,%8,%9,%10,%11,%12,%13,%14,%15,%16,%17,%18,%19,%20,%21,%22,%23,%24,%25,%26,%27,%28,%29,%30,%31,%32,%33,%34,%35,%36,%37,%38,%39,%40,%41,%42,%43,%44,%45,%46,%47,%48,%49,%50,%51,%52,%53,%54,%55}, {%56,%57,%58,%59}, %60, p, 1, 1, 0;\n}\n"
    : "+f"(d[0]),"+f"(d[1]),"+f"(d[2]),"+f"(d[3]),"+f"(d[4]),"+f"(d[5]),"+f"(d[6]),"+f"(d[7]),"+f"(d[8]),"+f"(d[9]),"+f"(d[10]),"+f"(d[11]),"+f"(d[12]),"+f"(d[13]),"+f"(d[14]),"+f"(d[15]),"+f"(d[16]),"+f"(d[17]),"+f"(d[18]),"+f"(d[19]),"+f"(d[20]),"+f"(d[21]),"+f"(d[22]),"+f"(d[23]),"+f"(d[24]),"+f"(d[25]),"+f"(d[26]),"+f"(d[27]),"+f"(d[28]),"+f"(d[29]),"+f"(d[30]),"+f"(d[31]),"+f"(d[32]),"+f"(d[33]),"+f"(d[34]),"+f"(d[35]),"+f"(d[36]),"+f"(d[37]),"+f"(d[38]),"+f"(d[39]),"+f"(d[40]),"+f"(d[41]),"+f"(d[42]),"+f"(d[43]),"+f"(d[44]),"+f"(d[45]),"+f"(d[46]),"+f"(d[47]),"+f"(d[48]),"+f"(d[49]),"+f"(d[50]),"+f"(d[51]),"+f"(d[52]),"+f"(d[53]),"+f"(d[54]),"+f"(d[55]) : "r"(a0), "r"(a1), "r"(a2), "r"(a3), "l"(db), "n"(SC));
}
template<int SC> __device__ __forceinline__ void wg_sp48(float (&d)[24], uint32_t a0, uint32_t a1, uint32_t a2, uint32_t a3, uint64_t db, uint32_t meta) {
  asm volatile("{\n.reg .pred p;\nsetp.ne.b32 p, %30, 0;\nwgmma.mma_async.sp.sync.aligned.m64n48k32.f32.bf16.bf16 {%0,%1,%2,%3,%4,%5,%6,%7,%8,%9,%10,%11,%12,%13,%14,%15,%16,%17,%18,%19,%20,%21,%22,%23}, {%24,%25,%26,%27}, %28, %29, 0, p, 1, 1, 1;\n}\n"
    : "+f"(d[0]),"+f"(d[1]),"+f"(d[2]),"+f"(d[3]),"+f"(d[4]),"+f"(d[5]),"+f"(d[6]),"+f"(d[7]),"+f"(d[8]),"+f"(d[9]),"+f"(d[10]),"+f"(d[11]),"+f"(d[12]),"+f"(d[13]),"+f"(d[14]),"+f"(d[15]),"+f"(d[16]),"+f"(d[17]),"+f"(d[18]),"+f"(d[19]),"+f"(d[20]),"+f"(d[21]),"+f"(d[22]),"+f"(d[23]) : "r"(a0), "r"(a1), "r"(a2), "r"(a3), "l"(db), "r"(meta), "n"(SC));
}
template<int SC> __device__ __forceinline__ void wg_rs64(float (&d)[32], uint32_t a0, uint32_t a1, uint32_t a2, uint32_t a3, uint64_t db) {
  asm volatile("{\n.reg .pred p;\nsetp.ne.b32 p, %37, 0;\nwgmma.mma_async.sync.aligned.m64n64k16.f32.bf16.bf16 {%0,%1,%2,%3,%4,%5,%6,%7,%8,%9,%10,%11,%12,%13,%14,%15,%16,%17,%18,%19,%20,%21,%22,%23,%24,%25,%26,%27,%28,%29,%30,%31}, {%32,%33,%34,%35}, %36, p, 1, 1, 0;\n}\n"
    : "+f"(d[0]),"+f"(d[1]),"+f"(d[2]),"+f"(d[3]),"+f"(d[4]),"+f"(d[5]),"+f"(d[6]),"+f"(d[7]),"+f"(d[8]),"+f"(d[9]),"+f"(d[10]),"+f"(d[11]),"+f"(d[12]),"+f"(d[13]),"+f"(d[14]),"+f"(d[15]),"+f"(d[16]),"+f"(d[17]),"+f"(d[18]),"+f"(d[19]),"+f"(d[20]),"+f"(d[21]),"+f"(d[22]),"+f"(d[23]),"+f"(d[24]),"+f"(d[25]),"+f"(d[26]),"+f"(d[27]),"+f"(d[28]),"+f"(d[29]),"+f"(d[30]),"+f"(d[31]) : "r"(a0), "r"(a1), "r"(a2), "r"(a3), "l"(db), "n"(SC));
}

constexpr uint32_t SBC = 1024;
constexpr int ROWB = 2 * 224 * 384;
constexpr int TB = 11;
constexpr int KS = 832;
constexpr int KSLOT = 22 * KS;
constexpr int SM_X = 0;
constexpr int SM_W = SM_X + 3 * 24576;
constexpr int SM_K = SM_W + 55296;
constexpr int SM_V = SM_K + 2 * KSLOT;
constexpr int SM_Q = SM_V + 22 * 1536;
constexpr int SM_O = SM_Q + 12288;
constexpr int SM_S = SM_O + 12288;
constexpr int SM_RPB = SM_S + 6144;
constexpr int SM_BAR = SM_RPB + 768;
constexpr int SM_A_TOTAL = SM_BAR + 256;
constexpr int SM_TIN0 = SM_X + 24576, SM_TIN1 = SM_X, SM_TIN2 = SM_W + 18432;
constexpr int SM_TWO = SM_X + 2 * 24576;
constexpr int SM_TST = SM_TIN2 + 24576;
enum { B_FULL = 0, B_EMPTY = 3, B_TIN = 6, B_TFREE = 10, B_WK = 12, B_WQ, B_WO, B_KIMP, B_VIMP, B_OFREE, B_XK, B_XV,
       B_Q0, B_WOFREE, B_OTAIL, B_ODONE = B_OTAIL + 4, B_KFREE, B_VFREE, B_COUNT };
enum { N_KRDY = 4, N_QK0, N_QK1, N_VQ0, N_VQ1, N_PVISS, N_Q0 };

#define NL 2
#define OCH 16
#define MID 6
#define SPL 4
#define RA 160
#define RG 168
#define OPT 0
constexpr int FS = 64;
__device__ int g_flags[TB * 56 * FS];

#define TR(role, it, k)
#define TRDECL
#define TRARG
#define TRPASS
#define TRDUMP
#define TRB(it, k)
#define TR2START
#define TR2FLUSH(blk)
#define TR2(blk, k)

struct Stage { uint32_t lo, full, em, par; };
struct GemmCtx {
  uint32_t bar;
  uint32_t kC, vC[2], qC[2];
  uint32_t kH, vH[2];
  uint32_t hiA, hiB;
  uint32_t spin;
  bool hvalid, never, edge;
};

template <int STRIDE> __device__ __forceinline__ void dump12(uint32_t a, const uint32_t (&r)[12]) {
#pragma unroll
  for (int j = 0; j < 3; j++) stsm4(a + j * 2 * STRIDE, r[4 * j], r[4 * j + 1], r[4 * j + 2], r[4 * j + 3]);
}
__device__ __forceinline__ void keep12(bool never, uint32_t a, const uint32_t (&r)[12]) { if (never) dump12<128>(a, r); }
template <int N> __device__ __forceinline__ void pack12(uint32_t (&r)[12], const float (&d)[N], int off) {
#pragma unroll
  for (int j = 0; j < 12; j++) r[j] = pack2(d[off + 2 * j], d[off + 2 * j + 1]);
}
__device__ __forceinline__ uint64_t dsc(uint64_t lo, uint32_t hi) { uint64_t r; asm("mov.b64 %0, {%1, %2};" : "=l"(r) : "r"((uint32_t)lo), "r"(hi)); return r; }
template <int K0, int K1> __device__ __forceinline__ void issue_core(const GemmCtx& c, const Stage& x, float (&d)[72]) {
  constexpr uint64_t db = mkdesc(SBC + SM_W, 6144, 256, 3);
  wg_fence();
  if (K0 == 0) wg_ss144<0>(d, dsc(x.lo, c.hiA), dsc(db, c.hiB));
#pragma unroll
  for (int k = K0 ? K0 : 1; k < K1; k++) wg_ss144<1>(d, dsc(x.lo + (k >> 2) * 512 + (k & 3) * 2, c.hiA), dsc(db + k * 32, c.hiB));
  wg_commit();
}
template <int K0, int K1> __device__ __forceinline__ void issue_halo(const GemmCtx& c, const Stage& x, float (&d)[48]) {
  constexpr uint64_t db = mkdesc(SBC + SM_W + 18432, 6144, 256, 3);
  wg_fence();
  if (K0 == 0) wg_ss96<0>(d, dsc(x.lo, c.hiA), dsc(db, c.hiB));
#pragma unroll
  for (int k = K0 ? K0 : 1; k < K1; k++) wg_ss96<1>(d, dsc(x.lo + (k >> 2) * 384 + (k & 3) * 2, c.hiA), dsc(db + k * 32, c.hiB));
  wg_commit();
}
__device__ __forceinline__ void release_stage(const Stage& x) {
  asm volatile("{\n.reg .pred p;\nelect.sync _|p, 0xffffffff;\n@p mbarrier.arrive.shared::cluster.b64 _, [%0];\n}" ::"r"(x.em) : "memory");
}
__device__ __forceinline__ void wait_stage(GemmCtx& c, Stage& x) {
  asm volatile("{\n.reg .pred p;\nWL:\nmbarrier.try_wait.parity.shared::cta.b64 p, [%1], %2;\n@p bra WD;\n"
               "add.u32 %0, %0, 1;\nsetp.lt.u32 p, %0, 0x100000;\n@p bra WL;\nWD:\n}" : "+r"(c.spin) : "r"(x.full), "r"(x.par) : "memory");
  x.par ^= 1;
}
__device__ __forceinline__ void edge_ready(const GemmCtx& c, int bar) { __syncwarp(); if (c.edge) mbar_arrive_elect(c.bar + bar * 8); }
__device__ __forceinline__ void dump6(uint32_t a, const uint32_t (&r)[6]) {
  stsm4(a, r[0], r[1], r[2], r[3]);
  asm volatile("stmatrix.sync.aligned.m8n8.x2.shared.b16 [%0], {%1,%2};" ::"r"(a + 512), "r"(r[4]), "r"(r[5]) : "memory");
}
__device__ __forceinline__ void pack6(uint32_t (&r)[6], const float (&d)[48], int off) {
#pragma unroll
  for (int j = 0; j < 6; j++) r[j] = pack2(d[off + 4 * j], d[off + 4 * j + 1]);
}
template <int PARITY> __device__ __forceinline__ void gwait(GemmCtx& c, int bar) {
  asm volatile("{\n.reg .pred p;\nWL:\nmbarrier.try_wait.parity.shared::cta.b64 p, [%1], %2;\n@p bra WD;\n"
               "add.u32 %0, %0, 1;\nsetp.lt.u32 p, %0, 0x100000;\n@p bra WL;\nWD:\n}" : "+r"(c.spin) : "r"(c.bar + bar * 8), "n"(PARITY) : "memory");
}
__device__ __forceinline__ void load_w(const CUtensorMap* m, uint32_t dst, uint32_t bar, int col) {
  asm volatile("cp.async.bulk.tensor.2d.shared::cluster.global.mbarrier::complete_tx::bytes [%0], [%1, {%3,%4}], [%2];"
               ::"r"(dst), "l"(m), "r"(bar), "r"(col), "r"(0) : "memory");
}
__device__ __forceinline__ void remote_arrive(uint32_t rbar) { asm volatile("mbarrier.arrive.shared::cluster.b64 _, [%0];" ::"r"(rbar) : "memory"); }
__device__ __forceinline__ void remote_expect(uint32_t rbar, uint32_t bytes) {
  asm volatile("mbarrier.arrive.expect_tx.shared::cluster.b64 _, [%0], %1;" ::"r"(rbar), "r"(bytes) : "memory");
}
__device__ __forceinline__ void copy_remote(uint32_t rdst, uint32_t src, uint32_t bytes, uint32_t rbar) {
  asm volatile("cp.async.bulk.shared::cluster.shared::cta.mbarrier::complete_tx::bytes [%0], [%1], %2, [%3];" ::"r"(rdst), "r"(src), "r"(bytes), "r"(rbar) : "memory");
}
__device__ __forceinline__ void tail_free(uint32_t bar) {
  uint32_t ln; asm volatile("mov.u32 %0, %%laneid;" : "=r"(ln));
  if (ln < 4) mbar_arrive_remote(bar, ln + (blockIdx.x & 4));
}
__device__ __forceinline__ void publish(uint32_t bar) {
  fence_async();
  __syncwarp();
  mbar_arrive_elect(bar);
}

template <bool FIRST, int PA>
__device__ __forceinline__ void gemm_iter(GemmCtx& c, int b, uint32_t (&pk)[12], uint32_t (&pv)[12], uint32_t (&pq)[12],
                                          uint32_t (&hk1)[6], uint32_t (&hv1)[6], Stage& x0, Stage& x2, Stage& x1 TRARG) {
  const uint32_t bar = c.bar;
  const bool w = !FIRST && (PA == 0 || b >= 0), never = c.never;
  constexpr uint32_t ko = PA * KSLOT;
  float C[72];
  uint32_t hk0[6], hv0[6], pv2[12];
  TR(2, b, 0);
  if (FIRST) wait_stage(c, x0);
  else dump12<128>(c.qC[1], pq);
  if (w) nb_sync(N_QK1, 256);
  TR(2, b, 2);
  if (FIRST) TR(2, b - 1, 6);
  if (PA == 0) {
    float H[48];
    issue_halo<0, 8>(c, x0, H);
    TR(2, b, 3);
    if (!FIRST) { gwait<0>(c, B_KFREE); dump12<128>(c.kC, pk); }
    issue_halo<8, 12>(c, x0, H);
    TR(2, b, 4);
    wait_stage(c, x2);
    if (FIRST) TR(2, b - 1, 7);
    if (FIRST) gwait<0>(c, B_WQ);
    if (FIRST) TR(2, b - 1, 8);
    issue_core<0, 8>(c, x2, C);
    TR(2, b, 5);
    if (!FIRST) { fence_async(); keep12(never, c.kC, pk); }
    wg_wait<1>(); pin(H);
    release_stage(x0);
    pack6(hk0, H, 0);
    if (c.hvalid) dump6(c.kH, hk0);
    pack6(hk1, H, 2); pack6(hv0, H, 24); pack6(hv1, H, 26);
  } else {
    issue_core<0, 8>(c, x2, C);
    TR(2, b, 5);
    fence_async();
    keep12(never, c.kC, pq);
    if (w) gwait<1>(c, B_KFREE);
    dump12<128>(c.kC + ko, pk);
    if (c.hvalid) dump6(c.kH + ko, hk1);
  }
  TR(2, b, 13);
  issue_core<8, 12>(c, x2, C);
  if (w) { nb_arrive(N_VQ0, 288); nb_arrive(N_VQ1, 288); }
  else if (!FIRST) { __syncwarp(); mbar_arrive_elect(bar + B_Q0 * 8); }
  wait_stage(c, x1);
  if (never) dump6(bar, PA ? hk1 : hk0);
  TR(2, b, 6);
  wg_wait<0>(); pin(C);
  TR(2, b, 7);
  release_stage(x2);
  pack12(pk, C, 24);
  dump12<128>(c.kC + ko + 64, pk);
  pack12(pv2, C, 48);
  pack12(pq, C, 0);
  TR(2, b, 8);
  issue_core<0, SPL>(c, x1, C);
  TR(2, b, 9);
  if (!FIRST) { fence_async(); edge_ready(c, B_XK); }
  keep12(never, c.kC, pk);
  TR(2, b, 14);
  if (w) nb_sync(N_PVISS, 384);
  issue_core<SPL, 12>(c, x1, C);
  if (!FIRST) nb_arrive(N_KRDY, 256);
  TR(2, b, 1);
  if (PA && b == 11) tail_free(bar + B_TFREE * 8);
  wait_stage(c, x0);
  if (w) gwait<PA>(c, B_VFREE);
  if (w && b < TB) gwait<PA>(c, B_ODONE);
  TR(2, b, 10);
  if (!FIRST) dump12<128>(c.vC[PA], pv);
  dump12<128>(c.vC[PA ^ 1] + 768, pv2);
  TR(2, b, 11);
  wg_wait<0>(); pin(C);
  TR(2, b, 12);
  release_stage(x1);
  if (!FIRST && c.edge) publish(bar + B_XV * 8);
  if (c.hvalid) dump6(c.vH[PA], PA ? hv1 : hv0);
  if (PA && !w) nb_sync(N_Q0, 384);
  dump12<128>(c.qC[0], pq);
  pack12(pk, C, 24);
  pack12(pv, C, 48);
  pack12(pq, C, 0);
}

template <int IN> __device__ __forceinline__ void issue_proj(float (&D)[48]) {
  constexpr uint64_t da = mkdesc(SBC + IN, 128, 768, 0), db = mkdesc(SBC + SM_TWO, 12288, 512, 2);
  wg_fence();
  wg_ss96<0>(D, da, db);
#pragma unroll
  for (int k = 1; k < 12; k++) wg_ss96<1>(D, da + (k / 3) * 384 + (k % 3) * 16, db + k * 64);
  wg_commit();
}
template <int ACC> __device__ __forceinline__ void issue_proj_half(float (&D)[48], int hd) {
  const uint64_t da = mkdesc(SBC + SM_TIN2, 128, 768, 0) + hd * 384, db = mkdesc(SBC + SM_TWO, 12288, 512, 2) + hd * 192;
  wg_fence();
  wg_ss96<ACC>(D, da, db);
#pragma unroll
  for (int k = 1; k < 6; k++) wg_ss96<1>(D, da + (k / 3) * 768 + (k % 3) * 16, db + (k / 3) * 384 + (k % 3) * 64);
  wg_commit();
}
__device__ __forceinline__ void store_proj(const float (&D)[48], const CUtensorMap* m, uint32_t st, uint32_t sta, int row, int col, int ch) {
#pragma unroll
  for (int q = 0; q < 6; q++)
    stsm4((sta ^ ((q & 1) * 32)) + (q >> 1) * 1024,
          pack2(D[8 * q], D[8 * q + 1]), pack2(D[8 * q + 2], D[8 * q + 3]), pack2(D[8 * q + 4], D[8 * q + 5]), pack2(D[8 * q + 6], D[8 * q + 7]));
  fence_async();
  __syncwarp();
  if ((threadIdx.x & 31) == 0) {
    asm volatile("cp.async.bulk.tensor.4d.global.shared::cta.bulk_group [%0, {%2,%3,%4,%5}], [%1];" ::"l"(m), "r"(st), "r"(0), "r"(row), "r"(col), "r"(ch) : "memory");
    asm volatile("cp.async.bulk.commit_group;" ::: "memory");
  }
  __syncwarp();
}

__device__ __forceinline__ float fold(float a, float b, float t, int useb) {
  float r;
  asm("{\n.reg .pred p;\nsetp.ne.b32 p, %4, 0;\nfma.rn.f32 %0, %1, 0f3E553B95, %3;\n@p fma.rn.f32 %0, %2, 0f3E553B95, %3;\n}"
      : "=&f"(r) : "f"(a), "f"(b), "f"(t), "r"(useb));
  return r;
}
template <int U, int L>
__device__ __forceinline__ void softmax_tile(const float (&SA)[56], const float (&SB)[56], const float (&T)[16], int b0, int b1,
                                             uint32_t (&P)[28], float (&sx)[8], uint32_t nbV, uint32_t zero, uint32_t qa, uint32_t (&q)[12]) {
  float lu[14], ll[14];
#pragma unroll
  for (int j = 0; j < 7; j++) {
    constexpr int sh = U == L ? 2 : 0;
    const float tu0 = T[2 * j + sh], tu1 = T[2 * j + 1 + sh], tl0 = T[2 * j], tl1 = T[2 * j + 1];
    lu[2 * j]     = fold(SA[4 * (U + j)],     SB[4 * (U + j)],     tu0, b0);
    ll[2 * j]     = fold(SA[4 * (L + j) + 2], SB[4 * (L + j) + 2], tl0, b0);
    lu[2 * j + 1] = fold(SA[4 * (U + j) + 1], SB[4 * (U + j) + 1], tu1, b1);
    ll[2 * j + 1] = fold(SA[4 * (L + j) + 3], SB[4 * (L + j) + 3], tl1, b1);
  }
  float mu = lu[0], ml = ll[0], mu2 = lu[1], ml2 = ll[1];
#pragma unroll
  for (int j = 1; j < 7; j++) { mu = fmaxf(mu, lu[2 * j]); mu2 = fmaxf(mu2, lu[2 * j + 1]); ml = fmaxf(ml, ll[2 * j]); ml2 = fmaxf(ml2, ll[2 * j + 1]); }
  mu = fmaxf(mu, mu2); ml = fmaxf(ml, ml2);
  { const float a1 = __shfl_xor_sync(0xffffffffu, mu, 1), a2 = __shfl_xor_sync(0xffffffffu, mu, 2), a3 = __shfl_xor_sync(0xffffffffu, mu, 3);
    const float c1 = __shfl_xor_sync(0xffffffffu, ml, 1), c2 = __shfl_xor_sync(0xffffffffu, ml, 2), c3 = __shfl_xor_sync(0xffffffffu, ml, 3);
    mu = fmaxf(fmaxf(mu, a1), fmaxf(a2, a3)); ml = fmaxf(fmaxf(ml, c1), fmaxf(c2, c3)); }
  float su = 0.f, sl = 0.f;
#pragma unroll
  for (int c = 0; c < 14; c++) {
    if (c >= U && c < U + 7) {
      float e0 = ex2(lu[2 * (c - U)] - mu), e1 = ex2(lu[2 * (c - U) + 1] - mu);
      su = c == U ? e0 + e1 : (su + e0) + e1; P[2 * c] = pack2(e0, e1);
    } else P[2 * c] = 0u;
  }
  nb_sync(nbV | (P[2 * (U + MID)] & zero), 288);
#pragma unroll
  for (int k = 0; k < 3; k++) ldsm4(qa + k * 256, q[4 * k], q[4 * k + 1], q[4 * k + 2], q[4 * k + 3]);
#pragma unroll
  for (int c = 0; c < 14; c++) {
    if (c >= L && c < L + 7) {
      float e0 = ex2(ll[2 * (c - L)] - ml), e1 = ex2(ll[2 * (c - L) + 1] - ml);
      sl = c == L ? e0 + e1 : (sl + e0) + e1; P[2 * c + 1] = pack2(e0, e1);
    } else P[2 * c + 1] = 0u;
  }
  sx[0] = su; sx[4] = sl;
#pragma unroll
  for (int k = 1; k < 4; k++) sx[k] = __shfl_xor_sync(0xffffffffu, su, k);
#pragma unroll
  for (int k = 1; k < 4; k++) sx[4 + k] = __shfl_xor_sync(0xffffffffu, sl, k);
}

struct BandCfg { uint32_t ra0, ra1, meta; int b0, b1; };
__device__ __forceinline__ void band_cfg(int b, uint32_t tb, BandCfg& n) {
  uint32_t ln; asm volatile("mov.u32 %0, %%laneid;" : "=r"(ln));
  const int g = ln >> 2, t = ln & 3;
  const int sw = min(max(g + 1, b == 0 ? 4 : 0), b == 13 ? 5 : 8);
  const int i0 = 2 * t, i1 = 2 * t + 1;
  n.b0 = i0 <= sw - 2; n.b1 = i1 <= sw - 2;
  n.ra0 = tb + (i0 == sw - 1 ? 13 : i0 + 8 * n.b0 - g + 2) * 52;
  n.ra1 = tb + (i1 == sw - 1 ? 13 : i1 + 8 * n.b1 - g + 2) * 52;
  n.meta = ((0x5555u & ((1u << (2 * (sw - 1))) - 1)) ^ 0xDD88u ^ (((t ^ b) & 1) ? 0x5555u : 0u)) * 0x10001u;
}
__device__ __forceinline__ void band_load(const BandCfg& n, float (&T)[16], int& b0, int& b1, uint32_t& meta) {
#pragma unroll
  for (int jj = 0; jj < 8; jj++) { T[2 * jj] = lds_f32(n.ra0 + jj * 4); T[2 * jj + 1] = lds_f32(n.ra1 + jj * 4); }
  b0 = n.b0; b1 = n.b1; meta = n.meta;
}

struct Maps { CUtensorMap xc, xh, w, os, wo, ot; };

__global__ void __cluster_dims__(8, 1, 1) __launch_bounds__(512, 1)
na_attn_kernel(const __nv_bfloat16* __restrict__ x, const __nv_bfloat16* __restrict__ wqkv, const __nv_bfloat16* __restrict__ rpb, const __grid_constant__ Maps mp) {
  extern __shared__ __align__(1024) uint8_t smem_raw[];
  const uint32_t sb = smem_u32(smem_raw);
  if ((sb & 0x3FFFF) != SBC) return;
  const uint32_t bar = sb + SM_BAR;
  TR2START;
  const int tid = threadIdx.x, lane = tid & 31;
  const int warp = __shfl_sync(0xffffffffu, tid >> 5, 0);
  const int head = blockIdx.x & 3, base = blockIdx.x & 4, sp = blockIdx.x >> 2;
  const int par = sp < 24 ? sp / 6 : sp - 24, strip = sp < 24 ? sp - par * 6 : 6, ph = par >> 1, pw = par & 1;
  const int odd = strip & 1;

  uint4 wv[2 * NL];
  const int va = head == 1;
  const uint32_t wdst = sb + SM_W + (3 + va + ((tid >> 1) & 1)) * 6144 + (tid >> 2) * 32 + ((tid ^ (tid >> 4)) & 1) * 16;
  if (warp < 12) {
    asm volatile("barrier.cluster.arrive.relaxed.aligned;" ::: "memory");
    const uint32_t wo0 = (tid >> 2) * 1152 + head * 96 + va * 32 + (tid & 3) * 16;
#pragma unroll
    for (int i = 0; i < 2 * NL; i++)
      asm volatile("ld.global.nc.v4.b32 {%0,%1,%2,%3}, [%4];" : "=r"(wv[i].x), "=r"(wv[i].y), "=r"(wv[i].z), "=r"(wv[i].w)
                   : "l"(reinterpret_cast<const uint8_t*>(wqkv) + wo0 + (i & 1) * 96 * 1152 + (i / 2 + 1) * 384));
  }
  if (warp < 8) {
    asm volatile("setmaxnreg.inc.sync.aligned.u32 %0;" ::"n"(RA));
    float rv = -INFINITY;
    if (tid < 169) rv = __bfloat162float(rpb[head * 169 + tid]) * 1.4426950408889634f;
    if (tid < 192) {
      const int kc = (tid & 15) + 3, wc = (tid >> 4) % 6;
      sts128(tid < 96 ? sb + SM_K + kc * KS + wc * 128 + 48 : sb + SM_V + kc * 1536 + wc * 128 + (6 + (kc & 1)) * 16, make_uint4(0, 0, 0, 0));
    }
#pragma unroll
    for (int i = 0; i < 2 * NL; i++) sts128(wdst + (i & 1) * 3072 + (i / 2) * 18432, wv[i]);
    fence_async();
    asm volatile("bar.arrive 1, 384;" ::: "memory");
    if (tid < 182) asm volatile("st.shared.f32 [%0], %1;" ::"r"(sb + SM_RPB + tid * 4), "f"(rv) : "memory");
    const int jw = warp >> 2, j = jw ^ odd, w = warp & 3, wt = 4 * j + w;
    int variant = w;
    if (strip == 0 && j == 0 && w < 2) variant = 4;
    if (strip == 6 && j == 1 && w >= 2) variant = 5;
    const bool v1 = opq((uint32_t)(variant & 1)), v2 = opq((uint32_t)(variant & 2)), v4 = opq((uint32_t)(variant & 4));
    const uint32_t qa = opq(sb + SM_Q + (8 * j + 2 * w + ((lane >> 3) & 1)) * 768 + (lane >> 4) * 128 + (((lane & 7) * 16) ^ (((lane >> 3) & 1) * 64)));
    uint32_t oa = opq(sb + SM_O + j * 6144 + (2 * w + ((lane >> 3) & 1)) * 768 + (lane >> 4) * 128 + (lane & 7) * 16);
    uint64_t dA = opq(mkdesc(SBC + SM_K, 128, KS, 0) + j * (8 * KS / 16)), dB = opq(dA + (KSLOT >> 4));
    uint64_t dV[7];
#pragma unroll
    for (int i = 0; i < 7; i++) dV[i] = opq(mkdesc(SBC + SM_V, 768, 128, 0) + j * (8 * 1536 / 16) + i * 192);
    const uint32_t nbK = opq((uint32_t)(N_KRDY + jw)), nbQ = opq((uint32_t)(N_QK0 + jw)), nbV = opq((uint32_t)(N_VQ0 + jw));
    asm volatile("barrier.cluster.wait.aligned;" ::: "memory");
    asm volatile("bar.sync 3, 256;" ::: "memory");
    float T[16];
    TRDECL;
    int b0, b1;
    uint32_t meta, ob = bar + B_ODONE * 8, fb = bar + B_OFREE * 8, fp = 1;
    const uint32_t tb = opq(sb + SM_RPB + (variant < 4 ? 3 : variant + 1 - 2 * w) * 4);
    const bool own = ((w ^ head) & 2) == 0;
    const uint32_t dst13 = sb + SM_TIN2 + head * 6144 + (2 * j + (w & 1)) * 1536, src13 = opq(own ? dst13 : sb + SM_S + (2 * j + (w & 1)) * 1536);
    const uint32_t snd[4] = {opq(own ? 0u : mapa(dst13, base + (head ^ 2))), opq(mapa(bar + (B_TIN + 2) * 8, base + (head ^ 2))),
                             opq(mapa(dst13, base + (w & 2) + (~head & 1))), opq(mapa(bar + (B_TIN + 3) * 8, base + (w & 2) + (~head & 1)))};
    BandCfg nx;
    band_cfg(0, tb, nx);
    band_load(nx, T, b0, b1, meta);
    band_cfg(1, tb, nx);
    const uint32_t zero = opq(blockIdx.x >> 16);
    uint32_t special = opq(0x380Au << 1);
    uint32_t q[12];
    mbar_wait(bar + B_Q0 * 8, 0);
#pragma unroll
    for (int k = 0; k < 3; k++) ldsm4(qa + k * 256, q[4 * k], q[4 * k + 1], q[4 * k + 2], q[4 * k + 3]);
    nb_arrive(N_Q0, 384);
#pragma unroll 1
    for (int b = 0; b < 14; b++) {
      float SA[56], SB[56];
      TR(0, b, 0);
      if (jw) mbar_wait(bar + B_KIMP * 8, b & 1);
      nb_sync(nbK, 256);
      TR(0, b, 1);
      TR(0, b - 1, 9);
      wg_fence();
      wg_rs112<0>(SA, q[0], q[1], q[2], q[3], dA);
      wg_rs112<0>(SB, q[0], q[1], q[2], q[3], dB);
      wg_rs112<1>(SA, q[4], q[5], q[6], q[7], dA + 16);
      wg_rs112<1>(SB, q[4], q[5], q[6], q[7], dB + 16);
      wg_rs112<1>(SA, q[8], q[9], q[10], q[11], dA + 32);
      wg_rs112<1>(SB, q[8], q[9], q[10], q[11], dB + 32);
      wg_commit();
      nb_arrive(nbQ, 256);
      { const uint64_t t = dA; dA = dB; dB = t; }
      special >>= 1;
      if (special & 1) {
        if (b == 3) band_cfg(13, tb, nx);
        else {
          if (b == 1 || b == 13) band_load(nx, T, b0, b1, meta);
          if (b >= TB) {
            ob = bar + (b == 13 ? (own ? B_TIN + 2 : B_ODONE) : B_OTAIL + 2 * (b - TB) + jw) * 8;
            if (b > TB) { fb = bar + (B_TFREE + b - 12) * 8; fp = 0; }
            oa += b == 12 ? 0u - (SM_O - SM_Q) : (b == 13 ? src13 - (sb + SM_Q + wt * 1536) : 0);
          }
        }
      }
      TR(0, b, 2);
      wg_wait<0>(); pin(SA); pin(SB);
      mbar_arrive_elect(bar + B_KFREE * 8);
      TR(0, b, 3);
      TR(0, b - 1, 10);
      uint32_t P[28];
      float sx[8];
      if (v2) {
        if (v1) softmax_tile<6, 7>(SA, SB, T, b0, b1, P, sx, nbV, zero, qa, q); else softmax_tile<4, 5>(SA, SB, T, b0, b1, P, sx, nbV, zero, qa, q);
      } else if (!v4) {
        if (v1) softmax_tile<2, 3>(SA, SB, T, b0, b1, P, sx, nbV, zero, qa, q); else softmax_tile<0, 1>(SA, SB, T, b0, b1, P, sx, nbV, zero, qa, q);
      } else {
        if (v1) softmax_tile<4, 4>(SA, SB, T, b0, b1, P, sx, nbV, zero, qa, q); else softmax_tile<3, 3>(SA, SB, T, b0, b1, P, sx, nbV, zero, qa, q);
      }
      float O[24];
      TR(0, b, 4);
      wg_fence();
      wg_sp48<0>(O, P[0], P[1], P[2], P[3], dV[0], meta);
#pragma unroll
      for (int s = 1; s < 7; s++) wg_sp48<1>(O, P[4 * s], P[4 * s + 1], P[4 * s + 2], P[4 * s + 3], dV[s], meta);
      wg_commit();
      nb_arrive(N_PVISS, 384);
      TR(0, b, 6);
      mbar_wait(fb, fp);
      wg_wait<0>(); pin(O);
      mbar_arrive_elect(bar + B_VFREE * 8);
      TR(0, b, 7);
      float ru, rl;
      asm("rcp.approx.ftz.f32 %0, %1;" : "=f"(ru) : "f"(((fmaf(O[0], 0.f, sx[0]) + sx[1]) + sx[2]) + sx[3]));
      asm("rcp.approx.ftz.f32 %0, %1;" : "=f"(rl) : "f"(((fmaf(O[2], 0.f, sx[4]) + sx[5]) + sx[6]) + sx[7]));
#pragma unroll
      for (int i = 0; i < 3; i++)
        stsm4(oa + i * 256, pack2(O[8 * i] * ru, O[8 * i + 1] * ru), pack2(O[8 * i + 2] * rl, O[8 * i + 3] * rl),
              pack2(O[8 * i + 4] * ru, O[8 * i + 5] * ru), pack2(O[8 * i + 6] * rl, O[8 * i + 7] * rl));
      publish(ob);
      fp ^= 1;
      meta ^= 0x55555555u;
      TR(0, b, 8);
    }
    asm volatile("{\n.reg .pred p, q;\nsetp.ne.b32 q, %1, 0;\nelect.sync _|p, 0xffffffff;\nand.pred q, q, p;\n"
                 "@q cp.async.bulk.shared::cluster.shared::cta.mbarrier::complete_tx::bytes [%1], [%0], 1536, [%2];\n"
                 "@p cp.async.bulk.shared::cluster.shared::cta.mbarrier::complete_tx::bytes [%3], [%0], 1536, [%4];\n}"
                 ::"r"(src13), "r"(snd[0]), "r"(snd[1]), "r"(snd[2]), "r"(snd[3]) : "memory");
    if (jw == 0 || (OPT & 4)) nb_arrive(3, (OPT & 4) ? 384 : 256);
    TRDUMP;
    cluster_sync();
  } else if (warp < 12) {
    TRDECL;
    TR(2, -3, 0);
    asm volatile("setmaxnreg.inc.sync.aligned.u32 %0;" ::"n"(RG));
    TR(2, -3, 1);
    GemmCtx c;
    c.bar = bar;
    const int gw = warp - 8, tk = gw * 16 + (lane & 15), hi = lane >> 4;
    { const int col = tk >> 2, i = tk & 3;
      c.kC = sb + SM_K + (col + 3) * KS + hi * 128 + i * 16;
      c.vC[0] = sb + SM_V + (col + 3) * 1536 + hi * 128 + (2 * i + ((col + 3) & 1)) * 16;
      c.qC[0] = sb + SM_Q + col * 768 + hi * 128 + (col & 1) * 64 + i * 16; }
    { const int kc = gw - 1 + 19 * odd, i = lane & 7; c.hvalid = gw > 0; c.edge = gw == (odd ? 0 : 3);
      c.kH = sb + SM_K + kc * KS + (lane >> 3) * 128 + i * 16;
      c.vH[0] = sb + SM_V + kc * 1536 + (lane >> 3) * 128 + (i >> 2) * 768 + (2 * (i & 3) + ((kc ^ (i >> 2)) & 1)) * 16; }
    Stage xs[3];
#pragma unroll
    for (int i = 0; i < 3; i++) {
      const int p = (i + 1) % 3;
      xs[i].lo = (uint32_t)mkdesc(SBC + SM_X + p * 24576, 16, 0, 0); xs[i].full = bar + (B_FULL + p) * 8;
      xs[i].em = opq(mapa(bar + (B_EMPTY + p) * 8, base + p)); xs[i].par = 0;
    }
    c.never = x == nullptr;
    c.kC = opq(c.kC); c.kH = opq(c.kH);
    c.vC[1] = opq(c.vC[0] ^ 16); c.vC[0] = opq(c.vC[0]);
    c.vH[1] = opq(c.vH[0] ^ 16); c.vH[0] = opq(c.vH[0]);
    c.qC[1] = opq(c.qC[0] ^ 64); c.qC[0] = opq(c.qC[0]);
    c.spin = 0;
    c.hiA = (uint32_t)(mkdesc(0, 0, 1024, 1) >> 32) + (blockIdx.x >> 16); c.hiB = (uint32_t)(mkdesc(0, 0, 256, 3) >> 32) + (blockIdx.x >> 16);
    asm volatile("barrier.cluster.wait.aligned;" ::: "memory");
    TR(2, -3, 2);
#pragma unroll
    for (int i = 0; i < 2 * NL; i++) sts128(wdst + (i & 1) * 3072 + (i / 2) * 18432, wv[i]);
    fence_async();
    TR(2, -3, 3);
    asm volatile("bar.sync 1, 384;" ::: "memory");
    TR(2, -3, 4);
    mbar_wait(bar + B_WK * 8, 0);
    asm volatile("griddepcontrol.launch_dependents;");
    TR(2, -3, 5);
    uint32_t pk[12], pv[12], pq[12], hk1[6], hv1[6];
    gemm_iter<true, 0>(c, -2, pk, pv, pq, hk1, hv1, xs[0], xs[1], xs[2] TRPASS);
    TR2(blockIdx.x, 4);
    c.hiA = opq(c.hiA); c.hiB = opq(c.hiB);
#pragma unroll 1
    for (int b = -1;; b += 2) {
      gemm_iter<false, 1>(c, b, pk, pv, pq, hk1, hv1, xs[2], xs[0], xs[1] TRPASS);
      if (b == 11) break;
      gemm_iter<false, 0>(c, b + 1, pk, pv, pq, hk1, hv1, xs[2], xs[0], xs[1] TRPASS);
      const Stage t = xs[2]; xs[2] = xs[1]; xs[1] = xs[0]; xs[0] = t;
    }
    TR2(blockIdx.x, 6);
    c.hiA = opq(c.hiA); c.hiB = opq(c.hiB);
    const uint32_t st = sb + gw * 3072;
    const uint32_t sta = st + (lane & 15) * 64 + ((hi ^ ((lane >> 1) & 3)) * 16);
    const int oc = ph * 112 + strip * 16 + 8 * (gw >> 1) + 4 * (head >> 1) + 2 * (gw & 1), och = pw * 6 + (head & 1) * 3;
    float D0[48], D1[48];
    if (lane < 4) mbar_arrive_remote(bar + B_WOFREE * 8, 2 * lane + (head & 1));
    dump12<128>(c.qC[1], pq);
    nb_sync(N_QK1, 256);
    issue_halo<0, 8>(c, xs[2], D1);
    fence_async();
    nb_arrive(N_VQ0, 288); nb_arrive(N_VQ1, 288); nb_arrive(N_PVISS, 384);
    issue_halo<8, 12>(c, xs[2], D1);
    gwait<0>(c, B_KFREE);
    dump12<128>(c.kC, pk);
    if (c.edge) publish(bar + B_XK * 8);
    wg_wait<0>(); pin(D1);
    pack6(hk1, D1, 0);
    if (c.hvalid) dump6(c.kH, hk1);
    tail_free(bar + (B_TFREE + 1) * 8);
    pack6(hv1, D1, 24);
    fence_async();
    nb_arrive(N_KRDY, 256);
    gwait<0>(c, B_VFREE);
    dump12<128>(c.vC[0], pv);
    if (c.hvalid) dump6(c.vH[0], hv1);
    fence_async();
    edge_ready(c, B_XV);
    nb_arrive(N_VQ0, 288); nb_arrive(N_VQ1, 288);
    gwait<0>(c, B_WO);
    gwait<0>(c, B_TIN);
    TR(2, 13, 0);
    nb_sync(N_QK1, 256);
    issue_proj<SM_TIN0>(D0);
    wg_wait<0>(); pin(D0);
    TR(2, 13, 1);
    store_proj(D0, &mp.ot, st + SM_TST, sta + SM_TST, 8 * TB, oc, och);
    gwait<0>(c, B_TIN + 1);
    TR(2, 13, 2);
    nb_sync(N_PVISS, 384);
    nb_sync(3, (OPT & 4) ? 384 : 256);
    issue_proj<SM_TIN1>(D1);
    wg_wait<0>(); pin(D1);
    TR(2, 13, 3);
    store_proj(D1, &mp.ot, st + SM_TIN0, sta + SM_TIN0, 8 * TB + 8, oc, och);
    TR(2, 13, 4);
    gwait<0>(c, B_TIN + 2);
    TR(2, 13, 5);
    issue_proj_half<0>(D0, head & 1);
    gwait<0>(c, B_TIN + 3);
    TR(2, 13, 6);
    issue_proj_half<1>(D0, ~head & 1);
    asm volatile("barrier.cluster.arrive.relaxed.aligned;" ::: "memory");
    wg_wait<0>(); pin(D0);
    store_proj(D0, &mp.ot, st + SM_TIN0 + 12288, sta + SM_TIN0 + 12288, 8 * TB + 16, oc, och);
    TR(2, 13, 7);
    if (lane == 0) asm volatile("cp.async.bulk.wait_group.read 0;" ::: "memory");
    __syncwarp();
    TR(2, 13, 8);
    TR2(blockIdx.x, 2);
    TR2FLUSH(blockIdx.x);
    TRDUMP;
    asm volatile("barrier.cluster.wait.aligned;" ::: "memory");
  } else {
    asm volatile("setmaxnreg.dec.sync.aligned.u32 24;");
    if (warp == 15) {
      const int l = min(lane, 24), row = head + (l < 16 ? 0 : 4 * ((l - 16) / 3)), col = strip * 16 + (l < 16 ? l : (l - 16) % 3 + (odd ? 16 : (strip ? -3 : 0)));
      const uint8_t* p = reinterpret_cast<const uint8_t*>(x) + (uint32_t)(row * ROWB + (ph * 112 + col) * 768 + pw * 384);
#pragma unroll
      for (int i = 0; i < 3; i++) asm volatile("prefetch.global.L2 [%0];" ::"l"(p + i * 128));
    } else if (elect_one()) {
      if (warp == 12) {
        mbar_init(bar + B_WK * 8, 1);
#pragma unroll
        for (int i = 0; i < NL; i++) load_w(&mp.w, sb + SM_W + (3 * i + 5 - 2 * va) * 6144, bar + B_WK * 8, (i + 1) * 192 + head * 48 + 32 - 32 * va);
        asm volatile("prefetch.tensormap [%0];" ::"l"(head == 1 ? &mp.xh : &mp.xc) : "memory");
      } else if (warp == 13) {
#pragma unroll
        for (int i = 0; i < B_XK; i++) if (i != B_WK) mbar_init(bar + i * 8, (i >= B_EMPTY && i < B_TIN) || (i >= B_TFREE && i < B_WK) ? ((OPT & 2) && i == B_TFREE + 1 ? 17 : 16) : (i == B_TIN + 2 ? 5 : 1));
      } else {
#pragma unroll
        for (int i = B_XK; i < B_COUNT; i++) mbar_init(bar + i * 8, i < B_Q0 ? 2 : (i < B_ODONE ? (i == B_WOFREE ? 16 : 4) : (i == B_VFREE ? 9 : 8)));
      }
      asm volatile("fence.mbarrier_init.release.cluster;" ::: "memory");
    }
    __syncwarp();
    asm volatile("barrier.cluster.arrive.relaxed.aligned;" ::: "memory");
    if (warp != 12) asm volatile("barrier.cluster.wait.aligned;" ::: "memory");
    else {
      const int cc = ph * 112 + strip * 16, ch = cc + (odd ? 16 : (strip ? -3 : 0)), rh = strip ? -4 : 112;
      const uint32_t fb = opq(bar + (B_FULL + head) * 8), dst0 = sb + SM_X + head * 24576, c3 = opq((uint32_t)(pw * 3)), mask = opq(15u << base);
      int t = head == 0 ? 2 : head - 1;
      uint64_t mx = opq((uint64_t)(t ? &mp.xc : &mp.xh));
      uint32_t row = opq((uint32_t)(t ? 4 * t - 4 : rh)), col = opq((uint32_t)(t ? cc : ch)), dst = opq(dst0 + (t ? 0 : 2048));
#pragma unroll 1
      for (int n = 0;; n++) {
        if (n) mbar_wait(fb + (B_EMPTY - B_FULL) * 8, ~n & 1);
        else asm volatile("barrier.cluster.wait.aligned;" ::: "memory");
        if (head < 3) {
          asm volatile("{\n.reg .pred p;\n.reg .b16 m;\nelect.sync _|p, 0xffffffff;\ncvt.u16.u32 m, %7;\n"
                       "@p cp.async.bulk.tensor.4d.shared::cluster.global.mbarrier::complete_tx::bytes.multicast::cluster [%0], [%1, {%3,%4,%5,%6}], [%2], m;\n}"
                       ::"r"(dst), "l"(mx), "r"(fb), "r"(0), "r"(row), "r"(col), "r"(c3), "r"(mask) : "memory");
          if (lane < 4) remote_expect(mapa(fb, base + lane), dst == dst0 ? 24576 : 18432);
          __syncwarp();
        }
        if (n == 0 && elect_one()) {
#pragma unroll
          for (int i = 0; i < 3; i++) load_w(&mp.w, sb + SM_W + i * 6144, bar + B_WQ * 8, head * 48 + i * 16);
          mbar_expect(bar + B_WQ * 8, 18432);
        }
        __syncwarp();
        if (head == 3 || n == 11) break;
        t += 3;
        const int hn = t / 5;
        const bool core = t != 5 * hn;
        mx = opq((uint64_t)(core ? &mp.xc : &mp.xh));
        row = opq((uint32_t)(core ? 4 * (t - hn - 1) : rh + 16 * hn)); col = opq((uint32_t)(core ? cc : ch)); dst = opq(dst0 + (core ? 0 : 2048));
        if (elect_one()) asm volatile("cp.async.bulk.prefetch.tensor.4d.L2.global [%0, {%1,%2,%3,%4}];" ::"l"(mx), "r"(0), "r"(row), "r"(col), "r"(c3) : "memory");
        __syncwarp();
      }
      mbar_wait(bar + B_WOFREE * 8, 0);
      if (elect_one()) {
        const int qr = (blockIdx.x & 7) >> 1;
#pragma unroll
        for (int i = 0; i < 3; i++)
          asm volatile("cp.async.bulk.tensor.2d.shared::cluster.global.mbarrier::complete_tx::bytes.multicast::cluster [%0], [%1, {%3,%4}], [%2], %5;"
                       ::"r"(sb + SM_TWO + i * 12288 + qr * 3072), "l"(&mp.wo), "r"(bar + B_WO * 8), "r"((head & 1) * 96 + i * 32), "r"(qr * 48),
                         "h"((uint16_t)(0x55 << (head & 1))) : "memory");
      }
      __syncwarp();
    }
    if (warp & 1) {
      const uint32_t partner = (blockIdx.x & 7) ^ 4;
      const int cs = odd ? 3 : (strip == 6 ? 15 : 16), cd = odd || strip == 6 ? 19 : 0;
      const uint32_t rb = opq(mapa(bar, partner));
      TRDECL;
      if (warp == 13) {
        const uint32_t dst = opq(mapa(sb + SM_V + cd * 1536, partner)), src = opq(sb + SM_V + cs * 1536);
#pragma unroll 1
        for (int b = 0;; b++) {
          const uint32_t pa = b & 1;
          nb_arrive(N_VQ0, 288);
          mbar_wait(bar + B_XV * 8, pa);
          TR(1, b, 0);
          if (elect_one()) {
            copy_remote(dst, src, 4608, rb + B_VIMP * 8); remote_expect(rb + B_VIMP * 8, 4608);
            if ((OPT & 2) && b == 13) mbar_arrive(bar + (B_TFREE + 1) * 8);
          }
          __syncwarp();
          TR(1, b, 1);
          mbar_wait(bar + B_VIMP * 8, pa);
          TR(1, b, 2);
          nb_arrive(N_VQ1, 288);
          if (elect_one()) remote_arrive(rb + B_VFREE * 8);
          __syncwarp();
          TR(1, b, 3);
          if (b == 13) break;
          mbar_wait(bar + B_VFREE * 8, pa);
          if (elect_one()) remote_arrive(rb + B_XV * 8);
          __syncwarp();
        }
      } else {
        const uint32_t dst = opq(mapa(sb + SM_K + cd * KS, partner)), src = opq(sb + SM_K + cs * KS);
#pragma unroll 1
        for (int b = 0;; b++) {
          const uint32_t pa = b & 1, so = (pa ^ 1) * KSLOT;
          mbar_wait(bar + B_XK * 8, pa);
          TR(1, b - 1, 4);
          if (elect_one()) {
            copy_remote(dst + so, src + so, 3 * KS, rb + B_KIMP * 8);
            if (b == 0) copy_remote(dst, src, 3 * KS, rb + B_KIMP * 8);
            remote_expect(rb + B_KIMP * 8, b ? 3 * KS : 6 * KS);
          }
          __syncwarp();
          TR(1, b - 1, 5);
          TR(1, b - 1, 7);
          if (b == 13) break;
          mbar_wait(bar + B_KFREE * 8, pa);
          if (elect_one()) remote_arrive(rb + B_XK * 8);
          __syncwarp();
        }
      }
      TRDUMP;
    }
    if (warp == 14) {
      int* flag = g_flags + (par * 7 + strip) * 2 * FS;
      if (elect_one()) {
        mbar_expect(bar + B_WK * 8, NL * 6144);
        mbar_arrive(bar + B_XK * 8); mbar_arrive(bar + B_XV * 8);
        mbar_expect(bar + B_WO * 8, 36864);
        mbar_expect(bar + B_TIN * 8, 24576); mbar_expect(bar + (B_TIN + 1) * 8, 24576); mbar_expect(bar + (B_TIN + 2) * 8, 6144); mbar_expect(bar + (B_TIN + 3) * 8, 12288);
      }
      __syncwarp();
#pragma unroll 1
      for (int b = 0; b < TB; b++) {
        mbar_wait(bar + B_ODONE * 8, b & 1);
        if (lane == 0) {
#pragma unroll 1
          for (int i = 0; i < 16; i += OCH) {
            asm volatile("cp.async.bulk.tensor.3d.global.shared::cta.bulk_group [%0, {%2,%3,%4}], [%1];"
                         ::"l"(&mp.os), "r"(sb + SM_O + i * 768), "r"(pw * 192), "r"(8 * b + 2 * head), "r"(ph * 112 + strip * 16 + i) : "memory");
            asm volatile("cp.async.bulk.commit_group;\ncp.async.bulk.wait_group 0;" ::: "memory");
          }
        }
        __syncwarp();
        mbar_arrive_elect(bar + B_OFREE * 8);
        if (lane == 0)
          asm volatile("fence.proxy.async.global;\nfence.acq_rel.gpu;\nred.relaxed.gpu.global.add.s32 [%0], 1;\nred.relaxed.gpu.global.add.s32 [%1], 1;"
                       ::"l"(flag + b * 56 * FS), "l"(flag + (b * 56 + 1) * FS) : "memory");
        __syncwarp();
      }
#pragma unroll 1
      for (int t = 0; t < 4; t++) {
        const int i = t >> 1, j = (t ^ odd) & 1, d = (lane + head + 1) & 3;
        const uint32_t dst = opq(mapa(sb + (i ? SM_TIN1 : SM_TIN0) + head * 6144 + j * 3072, base + d)), rb = opq(mapa(bar + (B_TIN + i) * 8, base + d));
        const uint32_t src = opq(sb + (i ? SM_Q : SM_O) + j * 6144 + (d & 2) * 1536);
        if (!(t & 1)) mbar_wait(bar + (B_TFREE + i) * 8, 0);
        mbar_wait(bar + (B_OTAIL + t) * 8, 0);
        if (lane < 4) copy_remote(dst, src, 3072, rb);
        __syncwarp();
      }
    }
    cluster_sync();
  }
}

constexpr int NSTB = 6;
constexpr int NTB = TB * 56;
constexpr int SM_B_ST = 0;
constexpr int SM_B_IN = 73728;
constexpr int SM_B_W = SM_B_IN + 3 * 24576;
constexpr int SM_B_BAR = SM_B_IN + NSTB * 24576;
constexpr int SM_B_TOTAL = SM_B_BAR + 512;
struct MapsB { CUtensorMap oi, oo, wo; };

__global__ void __launch_bounds__(512, 1)
na_proj_kernel(const __grid_constant__ MapsB mp) {
  extern __shared__ __align__(1024) uint8_t smem_raw[];
  const uint32_t sb = smem_u32(smem_raw);
  if ((sb & 0x3FFFF) != SBC) return;
  const uint32_t bar = sb + SM_B_BAR;
  const int tid = threadIdx.x, lane = tid & 31;
  const int warp = __shfl_sync(0xffffffffu, tid >> 5, 0);
  TR2START;
  TRB(47, 0);
  if (warp == 12 && elect_one()) {
#pragma unroll
    for (int i = 0; i <= 2 * NSTB; i++) mbar_init(bar + i * 8, i < NSTB || i == 2 * NSTB ? 1 : 12);
    asm volatile("st.shared.u32 [%0], 0;" ::"r"(bar + 120) : "memory");
    mbar_expect(bar + 2 * NSTB * 8, 73728);
#pragma unroll
    for (int i = 0; i < 2; i++)
      asm volatile("cp.async.bulk.tensor.3d.shared::cluster.global.mbarrier::complete_tx::bytes [%0], [%1, {%3,%4,%5}], [%2];"
                   ::"r"(sb + SM_B_W + i * 36864), "l"(&mp.wo), "r"(bar + 2 * NSTB * 8), "r"(0), "r"(0), "r"(i * 3) : "memory");
  }
  __syncthreads();
  const int step = gridDim.x;
  if (warp == 15) {
    int so = 0;
    nb_arrive(4, 288); nb_arrive(5, 288); nb_arrive(6, 288);
#pragma unroll 1
    for (int n = blockIdx.x, tk = 0; n < NTB; n += step, tk++) {
      uint32_t cc = 0;
#pragma unroll
      for (int wg = 0; wg < 3; wg++) {
        if (lane == 0) asm volatile("cp.async.bulk.wait_group.read 5;" ::: "memory");
        nb_sync(1 + wg, 160);
        if (wg == 0 || n + step < NTB) nb_arrive(4 + wg, 288);
        if (wg == 0) asm volatile("ld.shared.u32 %0, [%1];" : "=r"(cc) : "r"(bar + 128 + tk * 4) : "memory");
        if (lane == 0) {
          asm volatile("cp.async.bulk.tensor.4d.global.shared::cta.bulk_group [%0, {%2,%3,%4,%5}], [%1];"
                       ::"l"(&mp.oo), "r"(sb + SM_B_ST + wg * 8192 + so), "r"(0), "r"((cc >> 8) & 255), "r"(cc >> 16), "r"((cc & 1) * 3 + wg) : "memory");
          asm volatile("cp.async.bulk.commit_group;" ::: "memory");
        }
        __syncwarp();
      }
      so = so == 49152 ? 0 : so + 24576;
    }
    if (lane == 0) asm volatile("cp.async.bulk.wait_group.read 0;" ::: "memory");
  } else if (warp >= 12) {
    nb_sync(7, 480);
#pragma unroll 1
    for (int n = blockIdx.x + (warp - 12) * step; n < NTB; n += 3 * step) {
      const int b = n / 56, rem = n - b * 56, par = rem / 14;
      const int c0 = opq((uint32_t)(par & 1)), c1 = opq((uint32_t)(8 * b)), c2 = opq((uint32_t)((par >> 1) * 112 + (rem - par * 14) * 8));
      int v; uint32_t spin = 0, tk = 0;
      do { asm volatile("ld.acquire.gpu.global.s32 %0, [%1];" : "=r"(v) : "l"(g_flags + n * FS) : "memory"); } while (v < 4 && ++spin < SPIN_LIMIT);
      if (lane == 0) asm volatile("atom.shared.add.u32 %0, [%1], 1;" : "=r"(tk) : "r"(bar + 120) : "memory");
      asm volatile("fence.proxy.async.global;" ::: "memory");
      tk = __shfl_sync(0xffffffffu, tk, 0);
      TRB(tk, 0);
      const uint32_t use = tk / NSTB, sg = tk - use * NSTB;
      if (use) mbar_wait(bar + (NSTB + sg) * 8, (use - 1) & 1);
      TRB(tk, 1);
      if (elect_one()) {
        asm volatile("st.shared.u32 [%0], %1;" ::"r"(bar + 128 + tk * 4), "r"(c0 | c1 << 8 | c2 << 16) : "memory");
        mbar_expect(bar + sg * 8, 24576);
        asm volatile("cp.async.bulk.tensor.3d.shared::cluster.global.mbarrier::complete_tx::bytes [%0], [%1, {%3,%4,%5}], [%2];"
                     ::"r"(sb + SM_B_IN + sg * 24576), "l"(&mp.oi), "r"(bar + sg * 8), "r"(c0 * 192), "r"(c1), "r"(c2) : "memory");
        g_flags[n * FS] = 0;
      }
      __syncwarp();
    }
  } else {
    const int wg = warp >> 2, w = warp & 3;
    uint32_t a[48];
    mbar_wait(bar + 2 * NSTB * 8, 0);
    {
      const int k = (lane & 7) + (lane >> 4) * 8, ch = (warp & 1) * 2 + ((lane >> 3) & 1);
      const uint32_t wa = sb + SM_B_W + (warp >> 1) * 12288 + k * 64 + ((ch ^ ((k >> 1) & 3)) * 16);
#pragma unroll
      for (int i = 0; i < 12; i++)
        asm volatile("ldmatrix.sync.aligned.m8n8.x4.trans.shared.b16 {%0,%1,%2,%3}, [%4];"
                     : "=r"(a[4 * i]), "=r"(a[4 * i + 1]), "=r"(a[4 * i + 2]), "=r"(a[4 * i + 3]) : "r"(wa + i * 1024) : "memory");
    }
    nb_sync(7, 480);
    TRB(47, 1);
    const uint32_t sta = opq(sb + SM_B_ST + wg * 8192 + ((lane & 7) + (lane >> 4) * 8) * 128 + (((2 * w + ((lane >> 3) & 1)) ^ (lane & 7)) * 16));
    const uint32_t hi = opq((uint32_t)(mkdesc(0, 0, 3072, 0) >> 32) + (blockIdx.x >> 16)), bb = opq(bar);
    const uint32_t nbT = opq((uint32_t)(4 + wg)), nbN = opq((uint32_t)(wg == 2 ? 4 : 5 + wg)), nbD = opq((uint32_t)(1 + wg));
    int left = (NTB - blockIdx.x + step - 1) / step;
    if (wg == 2) nb_arrive(4, 288);
#pragma unroll 1
    for (uint32_t ph = 0;; ph ^= 1) {
#pragma unroll
      for (int sg = 0; sg < NSTB; sg++) {
        constexpr uint64_t db = mkdesc(SBC + SM_B_IN, 128, 3072, 0);
        float D[32];
        mbar_wait(bb + sg * 8, ph);
        nb_sync(nbT, 288);
        wg_fence();
        wg_rs64<0>(D, a[0], a[1], a[2], a[3], dsc(db + sg * 1536, hi));
#pragma unroll
        for (int k = 1; k < 12; k++) wg_rs64<1>(D, a[4 * k], a[4 * k + 1], a[4 * k + 2], a[4 * k + 3], dsc(db + sg * 1536 + k * 16, hi));
        wg_commit();
        nb_arrive(nbN, 288);
        wg_wait<0>(); pin(D);
        mbar_arrive_elect(bb + (NSTB + sg) * 8);
#pragma unroll
        for (int q = 0; q < 4; q++)
          asm volatile("stmatrix.sync.aligned.m8n8.x4.trans.shared.b16 [%0], {%1,%2,%3,%4};" ::"r"(sta + (sg % 3) * 24576 + q * 2048),
                       "r"(pack2(D[8 * q], D[8 * q + 1])), "r"(pack2(D[8 * q + 2], D[8 * q + 3])), "r"(pack2(D[8 * q + 4], D[8 * q + 5])), "r"(pack2(D[8 * q + 6], D[8 * q + 7])) : "memory");
        fence_async();
        nb_arrive(nbD, 160);
        if (wg == 0) TRB(31 - left, 5);
        if (--left == 0) goto done;
      }
    }
  done:
    if (wg == 0) nb_arrive(4, 288);
    TR2(132 + blockIdx.x, 2);
    TR2FLUSH(132 + blockIdx.x);
  }
}

typedef CUresult (*EncodeFn)(CUtensorMap*, CUtensorMapDataType, cuuint32_t, void*, const cuuint64_t*, const cuuint64_t*, const cuuint32_t*,
                             const cuuint32_t*, CUtensorMapInterleave, CUtensorMapSwizzle, CUtensorMapL2promotion, CUtensorMapFloatOOBfill);
static EncodeFn g_enc = nullptr;
static void make_map(CUtensorMap* m, const void* p, int rank, const cuuint64_t* dim, const cuuint64_t* str, const cuuint32_t* box, CUtensorMapSwizzle sw) {
  const cuuint32_t ones[5] = {1, 1, 1, 1, 1};
  g_enc(m, CU_TENSOR_MAP_DATA_TYPE_BFLOAT16, rank, (void*)p, dim, str, box, ones, CU_TENSOR_MAP_INTERLEAVE_NONE, sw,
        CU_TENSOR_MAP_L2_PROMOTION_L2_128B, CU_TENSOR_MAP_FLOAT_OOB_FILL_NONE);
}

extern "C" void kernel_launch(void* const* d_in, const int* in_sizes, int n_in, void* d_out, int out_size) {
  const __nv_bfloat16* x = (const __nv_bfloat16*)d_in[0];
  const __nv_bfloat16* wqkv = (const __nv_bfloat16*)d_in[1];
  const __nv_bfloat16* wo = (const __nv_bfloat16*)d_in[2];
  const __nv_bfloat16* rpb = (const __nv_bfloat16*)d_in[3];

  if (!g_enc) {
    void* fn = nullptr; cudaDriverEntryPointQueryResult qr;
    cudaGetDriverEntryPoint("cuTensorMapEncodeTiled", &fn, cudaEnableDefault, &qr);
    g_enc = (EncodeFn)fn;
    cudaFuncSetAttribute(na_attn_kernel, cudaFuncAttributeMaxDynamicSharedMemorySize, SM_A_TOTAL);
    cudaFuncSetAttribute(na_proj_kernel, cudaFuncAttributeMaxDynamicSharedMemorySize, SM_B_TOTAL);
  }
  Maps ma; MapsB mb;
  { cuuint64_t dim[4] = {64, 112, 224, 6}, str[3] = {(cuuint64_t)ROWB, 768, 128};
    cuuint32_t box[4] = {64, 4, 16, 3}, boxh[4] = {64, 16, 3, 3}, boxo[4] = {64, 8, 8, 1};
    make_map(&ma.xc, x, 4, dim, str, box, CU_TENSOR_MAP_SWIZZLE_128B);
    make_map(&ma.xh, x, 4, dim, str, boxh, CU_TENSOR_MAP_SWIZZLE_128B);
    make_map(&mb.oo, d_out, 4, dim, str, boxo, CU_TENSOR_MAP_SWIZZLE_128B); }
  { cuuint64_t dim[3] = {384, 112, 224}, str[2] = {(cuuint64_t)ROWB, 768};
    cuuint32_t box[3] = {192, 8, 8}, boxs[3] = {192, 2, OCH};
    make_map(&mb.oi, d_out, 3, dim, str, box, CU_TENSOR_MAP_SWIZZLE_NONE);
    make_map(&ma.os, d_out, 3, dim, str, boxs, CU_TENSOR_MAP_SWIZZLE_NONE); }
  { cuuint64_t dim[4] = {32, 112, 224, 12}, str[3] = {(cuuint64_t)ROWB, 768, 64};
    cuuint32_t box[4] = {32, 8, 2, 3};
    make_map(&ma.ot, d_out, 4, dim, str, box, CU_TENSOR_MAP_SWIZZLE_64B); }
  { cuuint64_t dim[2] = {576, 192}, str[1] = {1152};
    cuuint32_t box[2] = {16, 192};
    make_map(&ma.w, wqkv, 2, dim, str, box, CU_TENSOR_MAP_SWIZZLE_32B); }
  { cuuint64_t dim[3] = {32, 192, 6}, str[2] = {384, 64};
    cuuint32_t box[3] = {32, 192, 3};
    make_map(&mb.wo, wo, 3, dim, str, box, CU_TENSOR_MAP_SWIZZLE_64B); }
  { cuuint64_t dim[2] = {192, 192}, str[1] = {384};
    cuuint32_t box[2] = {32, 48};
    make_map(&ma.wo, wo, 2, dim, str, box, CU_TENSOR_MAP_SWIZZLE_64B); }
  na_attn_kernel<<<112, 512, SM_A_TOTAL>>>(x, wqkv, rpb, ma);
  cudaLaunchConfig_t cfg = {};
  cfg.gridDim = dim3(20); cfg.blockDim = dim3(512); cfg.dynamicSmemBytes = SM_B_TOTAL; cfg.stream = cudaStreamPerThread;
  cudaLaunchAttribute at[1];
  at[0].id = cudaLaunchAttributeProgrammaticStreamSerialization; at[0].val.programmaticStreamSerializationAllowed = 1;
  cfg.attrs = at; cfg.numAttrs = 1;
  cudaLaunchKernelEx(&cfg, na_proj_kernel, mb);
}
```

```cpp
#include <cuda_runtime.h>
#include <cuda_bf16.h>
#include <cuda.h>
#include <stdint.h>

#define SPIN_LIMIT (1u << 18)

__device__ __forceinline__ uint32_t smem_u32(const void* p) { return (uint32_t)__cvta_generic_to_shared(p); }
__device__ __forceinline__ void wg_fence() { asm volatile("wgmma.fence.sync.aligned;" ::: "memory"); }
__device__ __forceinline__ void wg_commit() { asm volatile("wgmma.commit_group.sync.aligned;" ::: "memory"); }
template <int N> __device__ __forceinline__ void wg_wait() { asm volatile("wgmma.wait_group.sync.aligned %0;" ::"n"(N) : "memory"); }
template <int N> __device__ __forceinline__ void pin(float (&d)[N]) {
#pragma unroll
  for (int i = 0; i < N; i++) asm volatile("" : "+f"(d[i])::"memory");
}
__host__ __device__ constexpr uint64_t mkdesc(uint32_t addr, uint32_t lbo, uint32_t sbo, uint32_t sw) {
  return (uint64_t)((addr & 0x3FFFF) >> 4) | ((uint64_t)(lbo >> 4) << 16) | ((uint64_t)(sbo >> 4) << 32) | ((uint64_t)sw << 62);
}
__device__ __forceinline__ void mbar_init(uint32_t bar, uint32_t cnt) { asm volatile("mbarrier.init.shared::cta.b64 [%0], %1;" ::"r"(bar), "r"(cnt) : "memory"); }
__device__ __forceinline__ void mbar_arrive(uint32_t bar) { asm volatile("mbarrier.arrive.shared::cta.b64 _, [%0];" ::"r"(bar) : "memory"); }
__device__ __forceinline__ bool elect_one() {
  uint32_t r; asm volatile("{\n.reg .pred p;\nelect.sync _|p, 0xffffffff;\nselp.u32 %0, 1, 0, p;\n}" : "=r"(r)); return r;
}
__device__ __forceinline__ void mbar_arrive_elect(uint32_t bar) {
  asm volatile("{\n.reg .pred p;\nelect.sync _|p, 0xffffffff;\n@p mbarrier.arrive.shared::cta.b64 _, [%0];\n}" ::"r"(bar) : "memory");
}
__device__ __forceinline__ void mbar_expect(uint32_t bar, uint32_t bytes) { asm volatile("mbarrier.arrive.expect_tx.shared::cta.b64 _, [%0], %1;" ::"r"(bar), "r"(bytes) : "memory"); }
__device__ __forceinline__ void mbar_arrive_remote(uint32_t bar, uint32_t cta) {
  asm volatile("{\n.reg .b32 ra;\nmapa.shared::cluster.u32 ra, %0, %1;\nmbarrier.arrive.relaxed.cluster.shared::cluster.b64 _, [ra];\n}" ::"r"(bar), "r"(cta) : "memory");
}
__device__ __forceinline__ void mbar_wait(uint32_t bar, uint32_t parity) {
  asm volatile("{\n.reg .pred p;\n.reg .b32 n;\nmov.b32 n, 0;\nWL:\nmbarrier.try_wait.parity.shared::cta.b64 p, [%0], %1;\n@p bra WD;\n"
               "add.u32 n, n, 1;\nsetp.lt.u32 p, n, 65536;\n@p bra WL;\nWD:\n}" ::"r"(bar), "r"(parity) : "memory");
}
__device__ __forceinline__ void nb_sync(int id, int n) { asm volatile("bar.sync %0, %1;" ::"r"(id), "r"(n) : "memory"); }
__device__ __forceinline__ void nb_arrive(int id, int n) { asm volatile("bar.arrive %0, %1;" ::"r"(id), "r"(n) : "memory"); }
__device__ __forceinline__ uint32_t opq(uint32_t x) { uint32_t r; asm volatile("mov.b32 %0, %1;" : "=r"(r) : "r"(x)); return r; }
__device__ __forceinline__ uint64_t opq(uint64_t x) { uint64_t r; asm volatile("mov.b64 %0, %1;" : "=l"(r) : "l"(x)); return r; }
__device__ __forceinline__ uint32_t mapa(uint32_t a, uint32_t cta) { uint32_t r; asm("mapa.shared::cluster.u32 %0, %1, %2;" : "=r"(r) : "r"(a), "r"(cta)); return r; }
__device__ __forceinline__ void fence_async() { asm volatile("fence.proxy.async.shared::cta;" ::: "memory"); }
__device__ __forceinline__ void cluster_sync() {
  asm volatile("barrier.cluster.arrive.relaxed.aligned;\nbarrier.cluster.wait.aligned;" ::: "memory");
}
__device__ __forceinline__ uint32_t pack2(float lo, float hi) {
  uint32_t r; asm("cvt.rn.bf16x2.f32 %0, %1, %2;" : "=r"(r) : "f"(hi), "f"(lo)); return r;
}
__device__ __forceinline__ void stsm4(uint32_t a, uint32_t r0, uint32_t r1, uint32_t r2, uint32_t r3) {
  asm volatile("stmatrix.sync.aligned.m8n8.x4.shared.b16 [%0], {%1,%2,%3,%4};" ::"r"(a), "r"(r0), "r"(r1), "r"(r2), "r"(r3) : "memory");
}
__device__ __forceinline__ void ldsm4(uint32_t a, uint32_t& r0, uint32_t& r1, uint32_t& r2, uint32_t& r3) {
  asm volatile("ldmatrix.sync.aligned.m8n8.x4.shared.b16 {%0,%1,%2,%3}, [%4];" : "=r"(r0), "=r"(r1), "=r"(r2), "=r"(r3) : "r"(a) : "memory");
}
__device__ __forceinline__ void sts128(uint32_t a, uint4 v) {
  asm volatile("st.shared.v4.b32 [%0], {%1,%2,%3,%4};" ::"r"(a), "r"(v.x), "r"(v.y), "r"(v.z), "r"(v.w) : "memory");
}
__device__ __forceinline__ float lds_f32(uint32_t a) { float v; asm volatile("ld.shared.f32 %0, [%1];" : "=f"(v) : "r"(a)); return v; }
__device__ __forceinline__ float ex2(float x) { float y; asm("ex2.approx.ftz.f32 %0, %1;" : "=f"(y) : "f"(x)); return y; }

template<int SC> __device__ __forceinline__ void wg_ss144(float (&d)[72], uint64_t da, uint64_t db) {
  asm volatile("{\n.reg .pred p;\nsetp.ne.b32 p, %74, 0;\nwgmma.mma_async.sync.aligned.m64n144k16.f32.bf16.bf16 {%0,%1,%2,%3,%4,%5,%6,%7,%8,%9,%10,%11,%12,%13,%14,%15,%16,%17,%18,%19,%20,%21,%22,%23,%24,%25,%26,%27,%28,%29,%30,%31,%32,%33,%34,%35,%36,%37,%38,%39,%40,%41,%42,%43,%44,%45,%46,%47,%48,%49,%50,%51,%52,%53,%54,%55,%56,%57,%58,%59,%60,%61,%62,%63,%64,%65,%66,%67,%68,%69,%70,%71}, %72, %73, p, 1, 1, 0, 1;\n}\n"
    : "+f"(d[0]),"+f"(d[1]),"+f"(d[2]),"+f"(d[3]),"+f"(d[4]),"+f"(d[5]),"+f"(d[6]),"+f"(d[7]),"+f"(d[8]),"+f"(d[9]),"+f"(d[10]),"+f"(d[11]),"+f"(d[12]),"+f"(d[13]),"+f"(d[14]),"+f"(d[15]),"+f"(d[16]),"+f"(d[17]),"+f"(d[18]),"+f"(d[19]),"+f"(d[20]),"+f"(d[21]),"+f"(d[22]),"+f"(d[23]),"+f"(d[24]),"+f"(d[25]),"+f"(d[26]),"+f"(d[27]),"+f"(d[28]),"+f"(d[29]),"+f"(d[30]),"+f"(d[31]),"+f"(d[32]),"+f"(d[33]),"+f"(d[34]),"+f"(d[35]),"+f"(d[36]),"+f"(d[37]),"+f"(d[38]),"+f"(d[39]),"+f"(d[40]),"+f"(d[41]),"+f"(d[42]),"+f"(d[43]),"+f"(d[44]),"+f"(d[45]),"+f"(d[46]),"+f"(d[47]),"+f"(d[48]),"+f"(d[49]),"+f"(d[50]),"+f"(d[51]),"+f"(d[52]),"+f"(d[53]),"+f"(d[54]),"+f"(d[55]),"+f"(d[56]),"+f"(d[57]),"+f"(d[58]),"+f"(d[59]),"+f"(d[60]),"+f"(d[61]),"+f"(d[62]),"+f"(d[63]),"+f"(d[64]),"+f"(d[65]),"+f"(d[66]),"+f"(d[67]),"+f"(d[68]),"+f"(d[69]),"+f"(d[70]),"+f"(d[71]) : "l"(da), "l"(db), "n"(SC));
}
template<int SC> __device__ __forceinline__ void wg_ss96(float (&d)[48], uint64_t da, uint64_t db) {
  asm volatile("{\n.reg .pred p;\nsetp.ne.b32 p, %50, 0;\nwgmma.mma_async.sync.aligned.m64n96k16.f32.bf16.bf16 {%0,%1,%2,%3,%4,%5,%6,%7,%8,%9,%10,%11,%12,%13,%14,%15,%16,%17,%18,%19,%20,%21,%22,%23,%24,%25,%26,%27,%28,%29,%30,%31,%32,%33,%34,%35,%36,%37,%38,%39,%40,%41,%42,%43,%44,%45,%46,%47}, %48, %49, p, 1, 1, 0, 1;\n}\n"
    : "+f"(d[0]),"+f"(d[1]),"+f"(d[2]),"+f"(d[3]),"+f"(d[4]),"+f"(d[5]),"+f"(d[6]),"+f"(d[7]),"+f"(d[8]),"+f"(d[9]),"+f"(d[10]),"+f"(d[11]),"+f"(d[12]),"+f"(d[13]),"+f"(d[14]),"+f"(d[15]),"+f"(d[16]),"+f"(d[17]),"+f"(d[18]),"+f"(d[19]),"+f"(d[20]),"+f"(d[21]),"+f"(d[22]),"+f"(d[23]),"+f"(d[24]),"+f"(d[25]),"+f"(d[26]),"+f"(d[27]),"+f"(d[28]),"+f"(d[29]),"+f"(d[30]),"+f"(d[31]),"+f"(d[32]),"+f"(d[33]),"+f"(d[34]),"+f"(d[35]),"+f"(d[36]),"+f"(d[37]),"+f"(d[38]),"+f"(d[39]),"+f"(d[40]),"+f"(d[41]),"+f"(d[42]),"+f"(d[43]),"+f"(d[44]),"+f"(d[45]),"+f"(d[46]),"+f"(d[47]) : "l"(da), "l"(db), "n"(SC));
}
template<int SC> __device__ __forceinline__ void wg_rs112(float (&d)[56], uint32_t a0, uint32_t a1, uint32_t a2, uint32_t a3, uint64_t db) {
  asm volatile("{\n.reg .pred p;\nsetp.ne.b32 p, %61, 0;\nwgmma.mma_async.sync.aligned.m64n112k16.f32.bf16.bf16 {%0,%1,%2,%3,%4,%5,%6,%7,%8,%9,%10,%11,%12,%13,%14,%15,%16,%17,%18,%19,%20,%21,%22,%23,%24,%25,%26,%27,%28,%29,%30,%31,%32,%33,%34,%35,%36,%37,%38,%39,%40,%41,%42,%43,%44,%45,%46,%47,%48,%49,%50,%51,%52,%53,%54,%55}, {%56,%57,%58,%59}, %60, p, 1, 1, 0;\n}\n"
    : "+f"(d[0]),"+f"(d[1]),"+f"(d[2]),"+f"(d[3]),"+f"(d[4]),"+f"(d[5]),"+f"(d[6]),"+f"(d[7]),"+f"(d[8]),"+f"(d[9]),"+f"(d[10]),"+f"(d[11]),"+f"(d[12]),"+f"(d[13]),"+f"(d[14]),"+f"(d[15]),"+f"(d[16]),"+f"(d[17]),"+f"(d[18]),"+f"(d[19]),"+f"(d[20]),"+f"(d[21]),"+f"(d[22]),"+f"(d[23]),"+f"(d[24]),"+f"(d[25]),"+f"(d[26]),"+f"(d[27]),"+f"(d[28]),"+f"(d[29]),"+f"(d[30]),"+f"(d[31]),"+f"(d[32]),"+f"(d[33]),"+f"(d[34]),"+f"(d[35]),"+f"(d[36]),"+f"(d[37]),"+f"(d[38]),"+f"(d[39]),"+f"(d[40]),"+f"(d[41]),"+f"(d[42]),"+f"(d[43]),"+f"(d[44]),"+f"(d[45]),"+f"(d[46]),"+f"(d[47]),"+f"(d[48]),"+f"(d[49]),"+f"(d[50]),"+f"(d[51]),"+f"(d[52]),"+f"(d[53]),"+f"(d[54]),"+f"(d[55]) : "r"(a0), "r"(a1), "r"(a2), "r"(a3), "l"(db), "n"(SC));
}
template<int SC> __device__ __forceinline__ void wg_sp48(float (&d)[24], uint32_t a0, uint32_t a1, uint32_t a2, uint32_t a3, uint64_t db, uint32_t meta) {
  asm volatile("{\n.reg .pred p;\nsetp.ne.b32 p, %30, 0;\nwgmma.mma_async.sp.sync.aligned.m64n48k32.f32.bf16.bf16 {%0,%1,%2,%3,%4,%5,%6,%7,%8,%9,%10,%11,%12,%13,%14,%15,%16,%17,%18,%19,%20,%21,%22,%23}, {%24,%25,%26,%27}, %28, %29, 0, p, 1, 1, 1;\n}\n"
    : "+f"(d[0]),"+f"(d[1]),"+f"(d[2]),"+f"(d[3]),"+f"(d[4]),"+f"(d[5]),"+f"(d[6]),"+f"(d[7]),"+f"(d[8]),"+f"(d[9]),"+f"(d[10]),"+f"(d[11]),"+f"(d[12]),"+f"(d[13]),"+f"(d[14]),"+f"(d[15]),"+f"(d[16]),"+f"(d[17]),"+f"(d[18]),"+f"(d[19]),"+f"(d[20]),"+f"(d[21]),"+f"(d[22]),"+f"(d[23]) : "r"(a0), "r"(a1), "r"(a2), "r"(a3), "l"(db), "r"(meta), "n"(SC));
}
template<int SC> __device__ __forceinline__ void wg_rs64(float (&d)[32], uint32_t a0, uint32_t a1, uint32_t a2, uint32_t a3, uint64_t db) {
  asm volatile("{\n.reg .pred p;\nsetp.ne.b32 p, %37, 0;\nwgmma.mma_async.sync.aligned.m64n64k16.f32.bf16.bf16 {%0,%1,%2,%3,%4,%5,%6,%7,%8,%9,%10,%11,%12,%13,%14,%15,%16,%17,%18,%19,%20,%21,%22,%23,%24,%25,%26,%27,%28,%29,%30,%31}, {%32,%33,%34,%35}, %36, p, 1, 1, 0;\n}\n"
    : "+f"(d[0]),"+f"(d[1]),"+f"(d[2]),"+f"(d[3]),"+f"(d[4]),"+f"(d[5]),"+f"(d[6]),"+f"(d[7]),"+f"(d[8]),"+f"(d[9]),"+f"(d[10]),"+f"(d[11]),"+f"(d[12]),"+f"(d[13]),"+f"(d[14]),"+f"(d[15]),"+f"(d[16]),"+f"(d[17]),"+f"(d[18]),"+f"(d[19]),"+f"(d[20]),"+f"(d[21]),"+f"(d[22]),"+f"(d[23]),"+f"(d[24]),"+f"(d[25]),"+f"(d[26]),"+f"(d[27]),"+f"(d[28]),"+f"(d[29]),"+f"(d[30]),"+f"(d[31]) : "r"(a0), "r"(a1), "r"(a2), "r"(a3), "l"(db), "n"(SC));
}

constexpr uint32_t SBC = 1024;
constexpr int ROWB = 2 * 224 * 384;
constexpr int TB = 11;
constexpr int KS = 832;
constexpr int KSLOT = 22 * KS;
constexpr int SM_X = 0;
constexpr int SM_W = SM_X + 3 * 24576;
constexpr int SM_K = SM_W + 55296;
constexpr int SM_V = SM_K + 2 * KSLOT;
constexpr int SM_Q = SM_V + 22 * 1536;
constexpr int SM_O = SM_Q + 12288;
constexpr int SM_S = SM_O + 12288;
constexpr int SM_RPB = SM_S + 6144;
constexpr int SM_BAR = SM_RPB + 768;
constexpr int SM_A_TOTAL = SM_BAR + 256;
constexpr int SM_TIN0 = SM_X + 24576, SM_TIN1 = SM_X, SM_TIN2 = SM_W + 18432;
constexpr int SM_TWO = SM_X + 2 * 24576;
constexpr int SM_TST = SM_TIN2 + 24576;
enum { B_FULL = 0, B_EMPTY = 3, B_TIN = 6, B_TFREE = 10, B_WK = 12, B_WQ, B_WO, B_KIMP, B_VIMP, B_OFREE, B_XK, B_XV,
       B_Q0, B_WOFREE, B_OTAIL, B_ODONE = B_OTAIL + 4, B_KFREE, B_VFREE, B_COUNT };
enum { N_KRDY = 4, N_QK0, N_QK1, N_VQ0, N_VQ1, N_PVISS, N_Q0 };

#define NL 2
#define OCH 16
#define MID 6
#define SPL 4
#define RA 160
#define RG 168
#define OPT 0
constexpr int FS = 64;
__device__ int g_flags[TB * 56 * FS];

#define TR(role, it, k)
#define TRDECL
#define TRARG
#define TRPASS
#define TRDUMP
#define TRB(it, k)
#define TR2START
#define TR2FLUSH(blk)
#define TR2(blk, k)

struct Stage { uint32_t lo, full, em, par; };
struct GemmCtx {
  uint32_t bar;
  uint32_t kC, vC[2], qC[2];
  uint32_t kH, vH[2];
  uint32_t hiA, hiB;
  uint32_t spin;
  bool hvalid, never, edge;
};

template <int STRIDE> __device__ __forceinline__ void dump12(uint32_t a, const uint32_t (&r)[12]) {
#pragma unroll
  for (int j = 0; j < 3; j++) stsm4(a + j * 2 * STRIDE, r[4 * j], r[4 * j + 1], r[4 * j + 2], r[4 * j + 3]);
}
__device__ __forceinline__ void keep12(bool never, uint32_t a, const uint32_t (&r)[12]) { if (never) dump12<128>(a, r); }
template <int N> __device__ __forceinline__ void pack12(uint32_t (&r)[12], const float (&d)[N], int off) {
#pragma unroll
  for (int j = 0; j < 12; j++) r[j] = pack2(d[off + 2 * j], d[off + 2 * j + 1]);
}
__device__ __forceinline__ uint64_t dsc(uint64_t lo, uint32_t hi) { uint64_t r; asm("mov.b64 %0, {%1, %2};" : "=l"(r) : "r"((uint32_t)lo), "r"(hi)); return r; }
template <int K0, int K1> __device__ __forceinline__ void issue_core(const GemmCtx& c, const Stage& x, float (&d)[72]) {
  constexpr uint64_t db = mkdesc(SBC + SM_W, 6144, 256, 3);
  wg_fence();
  if (K0 == 0) wg_ss144<0>(d, dsc(x.lo, c.hiA), dsc(db, c.hiB));
#pragma unroll
  for (int k = K0 ? K0 : 1; k < K1; k++) wg_ss144<1>(d, dsc(x.lo + (k >> 2) * 512 + (k & 3) * 2, c.hiA), dsc(db + k * 32, c.hiB));
  wg_commit();
}
template <int K0, int K1> __device__ __forceinline__ void issue_halo(const GemmCtx& c, const Stage& x, float (&d)[48]) {
  constexpr uint64_t db = mkdesc(SBC + SM_W + 18432, 6144, 256, 3);
  wg_fence();
  if (K0 == 0) wg_ss96<0>(d, dsc(x.lo, c.hiA), dsc(db, c.hiB));
#pragma unroll
  for (int k = K0 ? K0 : 1; k < K1; k++) wg_ss96<1>(d, dsc(x.lo + (k >> 2) * 384 + (k & 3) * 2, c.hiA), dsc(db + k * 32, c.hiB));
  wg_commit();
}
__device__ __forceinline__ void release_stage(const Stage& x) {
  asm volatile("{\n.reg .pred p;\nelect.sync _|p, 0xffffffff;\n@p mbarrier.arrive.shared::cluster.b64 _, [%0];\n}" ::"r"(x.em) : "memory");
}
__device__ __forceinline__ void wait_stage(GemmCtx& c, Stage& x) {
  asm volatile("{\n.reg .pred p;\nWL:\nmbarrier.try_wait.parity.shared::cta.b64 p, [%1], %2;\n@p bra WD;\n"
               "add.u32 %0, %0, 1;\nsetp.lt.u32 p, %0, 0x100000;\n@p bra WL;\nWD:\n}" : "+&r"(c.spin) : "r"(x.full), "r"(x.par) : "memory");
  x.par ^= 1;
}
__device__ __forceinline__ void edge_ready(const GemmCtx& c, int bar) { __syncwarp(); if (c.edge) mbar_arrive_elect(c.bar + bar * 8); }
__device__ __forceinline__ void dump6(uint32_t a, const uint32_t (&r)[6]) {
  stsm4(a, r[0], r[1], r[2], r[3]);
  asm volatile("stmatrix.sync.aligned.m8n8.x2.shared.b16 [%0], {%1,%2};" ::"r"(a + 512), "r"(r[4]), "r"(r[5]) : "memory");
}
__device__ __forceinline__ void pack6(uint32_t (&r)[6], const float (&d)[48], int off) {
#pragma unroll
  for (int j = 0; j < 6; j++) r[j] = pack2(d[off + 4 * j], d[off + 4 * j + 1]);
}
template <int PARITY> __device__ __forceinline__ void gwait(GemmCtx& c, int bar) {
  asm volatile("{\n.reg .pred p;\nWL:\nmbarrier.try_wait.parity.shared::cta.b64 p, [%1], %2;\n@p bra WD;\n"
               "add.u32 %0, %0, 1;\nsetp.lt.u32 p, %0, 0x100000;\n@p bra WL;\nWD:\n}" : "+&r"(c.spin) : "r"(c.bar + bar * 8), "n"(PARITY) : "memory");
}
__device__ __forceinline__ void load_w(const CUtensorMap* m, uint32_t dst, uint32_t bar, int col) {
  asm volatile("cp.async.bulk.tensor.2d.shared::cluster.global.mbarrier::complete_tx::bytes [%0], [%1, {%3,%4}], [%2];"
               ::"r"(dst), "l"(m), "r"(bar), "r"(col), "r"(0) : "memory");
}
__device__ __forceinline__ void remote_arrive(uint32_t rbar) { asm volatile("mbarrier.arrive.shared::cluster.b64 _, [%0];" ::"r"(rbar) : "memory"); }
__device__ __forceinline__ void remote_expect(uint32_t rbar, uint32_t bytes) {
  asm volatile("mbarrier.arrive.expect_tx.shared::cluster.b64 _, [%0], %1;" ::"r"(rbar), "r"(bytes) : "memory");
}
__device__ __forceinline__ void copy_remote(uint32_t rdst, uint32_t src, uint32_t bytes, uint32_t rbar) {
  asm volatile("cp.async.bulk.shared::cluster.shared::cta.mbarrier::complete_tx::bytes [%0], [%1], %2, [%3];" ::"r"(rdst), "r"(src), "r"(bytes), "r"(rbar) : "memory");
}
__device__ __forceinline__ void tail_free(uint32_t bar) {
  uint32_t ln; asm volatile("mov.u32 %0, %%laneid;" : "=r"(ln));
  if (ln < 4) mbar_arrive_remote(bar, ln + (blockIdx.x & 4));
}
__device__ __forceinline__ void publish(uint32_t bar) {
  fence_async();
  __syncwarp();
  mbar_arrive_elect(bar);
}

template <bool FIRST, int PA>
__device__ __forceinline__ void gemm_iter(GemmCtx& c, int b, uint32_t (&pk)[12], uint32_t (&pv)[12], uint32_t (&pq)[12],
                                          uint32_t (&hk1)[6], uint32_t (&hv1)[6], Stage& x0, Stage& x2, Stage& x1 TRARG) {
  const uint32_t bar = c.bar;
  const bool w = !FIRST && (PA == 0 || b >= 0), never = c.never;
  constexpr uint32_t ko = PA * KSLOT;
  float C[72];
  uint32_t hk0[6], hv0[6], pv2[12];
  TR(2, b, 0);
  if (FIRST) wait_stage(c, x0);
  else dump12<128>(c.qC[1], pq);
  if (w) nb_sync(N_QK1, 256);
  TR(2, b, 2);
  if (FIRST) TR(2, b - 1, 6);
  if (PA == 0) {
    float H[48];
    issue_halo<0, 8>(c, x0, H);
    TR(2, b, 3);
    if (!FIRST) { gwait<0>(c, B_KFREE); dump12<128>(c.kC, pk); }
    issue_halo<8, 12>(c, x0, H);
    TR(2, b, 4);
    wait_stage(c, x2);
    if (FIRST) TR(2, b - 1, 7);
    if (FIRST) gwait<0>(c, B_WQ);
    if (FIRST) TR(2, b - 1, 8);
    issue_core<0, 8>(c, x2, C);
    TR(2, b, 5);
    if (!FIRST) { fence_async(); keep12(never, c.kC, pk); }
    wg_wait<1>(); pin(H);
    release_stage(x0);
    pack6(hk0, H, 0);
    if (c.hvalid) dump6(c.kH, hk0);
    pack6(hk1, H, 2); pack6(hv0, H, 24); pack6(hv1, H, 26);
  } else {
    issue_core<0, 8>(c, x2, C);
    TR(2, b, 5);
    fence_async();
    keep12(never, c.kC, pq);
    if (w) gwait<1>(c, B_KFREE);
    dump12<128>(c.kC + ko, pk);
    if (c.hvalid) dump6(c.kH + ko, hk1);
  }
  TR(2, b, 13);
  issue_core<8, 12>(c, x2, C);
  if (w) { nb_arrive(N_VQ0, 288); nb_arrive(N_VQ1, 288); }
  else if (!FIRST) { __syncwarp(); mbar_arrive_elect(bar + B_Q0 * 8); }
  wait_stage(c, x1);
  if (never) dump6(bar, PA ? hk1 : hk0);
  TR(2, b, 6);
  wg_wait<0>(); pin(C);
  TR(2, b, 7);
  release_stage(x2);
  pack12(pk, C, 24);
  dump12<128>(c.kC + ko + 64, pk);
  pack12(pv2, C, 48);
  pack12(pq, C, 0);
  TR(2, b, 8);
  issue_core<0, SPL>(c, x1, C);
  TR(2, b, 9);
  if (!FIRST) { fence_async(); edge_ready(c, B_XK); }
  keep12(never, c.kC, pk);
  TR(2, b, 14);
  if (w) nb_sync(N_PVISS, 384);
  issue_core<SPL, 12>(c, x1, C);
  if (!FIRST) nb_arrive(N_KRDY, 256);
  TR(2, b, 1);
  if (PA && b == 11) tail_free(bar + B_TFREE * 8);
  wait_stage(c, x0);
  if (w) gwait<PA>(c, B_VFREE);
  if (w && b < TB) gwait<PA>(c, B_ODONE);
  TR(2, b, 10);
  if (!FIRST) dump12<128>(c.vC[PA], pv);
  dump12<128>(c.vC[PA ^ 1] + 768, pv2);
  TR(2, b, 11);
  wg_wait<0>(); pin(C);
  TR(2, b, 12);
  release_stage(x1);
  if (!FIRST && c.edge) publish(bar + B_XV * 8);
  if (c.hvalid) dump6(c.vH[PA], PA ? hv1 : hv0);
  if (PA && !w) nb_sync(N_Q0, 384);
  dump12<128>(c.qC[0], pq);
  pack12(pk, C, 24);
  pack12(pv, C, 48);
  pack12(pq, C, 0);
}

template <int IN> __device__ __forceinline__ void issue_proj(float (&D)[48]) {
  constexpr uint64_t da = mkdesc(SBC + IN, 128, 768, 0), db = mkdesc(SBC + SM_TWO, 12288, 512, 2);
  wg_fence();
  wg_ss96<0>(D, da, db);
#pragma unroll
  for (int k = 1; k < 12; k++) wg_ss96<1>(D, da + (k / 3) * 384 + (k % 3) * 16, db + k * 64);
  wg_commit();
}
template <int ACC> __device__ __forceinline__ void issue_proj_half(float (&D)[48], int hd) {
  const uint64_t da = mkdesc(SBC + SM_TIN2, 128, 768, 0) + hd * 384, db = mkdesc(SBC + SM_TWO, 12288, 512, 2) + hd * 192;
  wg_fence();
  wg_ss96<ACC>(D, da, db);
#pragma unroll
  for (int k = 1; k < 6; k++) wg_ss96<1>(D, da + (k / 3) * 768 + (k % 3) * 16, db + (k / 3) * 384 + (k % 3) * 64);
  wg_commit();
}
__device__ __forceinline__ void store_proj(const float (&D)[48], const CUtensorMap* m, uint32_t st, uint32_t sta, int row, int col, int ch) {
#pragma unroll
  for (int q = 0; q < 6; q++)
    stsm4((sta ^ ((q & 1) * 32)) + (q >> 1) * 1024,
          pack2(D[8 * q], D[8 * q + 1]), pack2(D[8 * q + 2], D[8 * q + 3]), pack2(D[8 * q + 4], D[8 * q + 5]), pack2(D[8 * q + 6], D[8 * q + 7]));
  fence_async();
  __syncwarp();
  if ((threadIdx.x & 31) == 0) {
    asm volatile("cp.async.bulk.tensor.4d.global.shared::cta.bulk_group [%0, {%2,%3,%4,%5}], [%1];" ::"l"(m), "r"(st), "r"(0), "r"(row), "r"(col), "r"(ch) : "memory");
    asm volatile("cp.async.bulk.commit_group;" ::: "memory");
  }
  __syncwarp();
}

__device__ __forceinline__ float fold(float a, float b, float t, int useb) {
  float r;
  asm("{\n.reg .pred p;\nsetp.ne.b32 p, %4, 0;\nfma.rn.f32 %0, %1, 0f3E553B95, %3;\n@p fma.rn.f32 %0, %2, 0f3E553B95, %3;\n}"
      : "=&f"(r) : "f"(a), "f"(b), "f"(t), "r"(useb));
  return r;
}
template <int U, int L>
__device__ __forceinline__ void softmax_tile(const float (&SA)[56], const float (&SB)[56], const float (&T)[16], int b0, int b1,
                                             uint32_t (&P)[28], float (&sx)[8], uint32_t nbV, uint32_t zero, uint32_t qa, uint32_t (&q)[12]) {
  float lu[14], ll[14];
#pragma unroll
  for (int j = 0; j < 7; j++) {
    constexpr int sh = U == L ? 2 : 0;
    const float tu0 = T[2 * j + sh], tu1 = T[2 * j + 1 + sh], tl0 = T[2 * j], tl1 = T[2 * j + 1];
    lu[2 * j]     = fold(SA[4 * (U + j)],     SB[4 * (U + j)],     tu0, b0);
    ll[2 * j]     = fold(SA[4 * (L + j) + 2], SB[4 * (L + j) + 2], tl0, b0);
    lu[2 * j + 1] = fold(SA[4 * (U + j) + 1], SB[4 * (U + j) + 1], tu1, b1);
    ll[2 * j + 1] = fold(SA[4 * (L + j) + 3], SB[4 * (L + j) + 3], tl1, b1);
  }
  float mu = lu[0], ml = ll[0], mu2 = lu[1], ml2 = ll[1];
#pragma unroll
  for (int j = 1; j < 7; j++) { mu = fmaxf(mu, lu[2 * j]); mu2 = fmaxf(mu2, lu[2 * j + 1]); ml = fmaxf(ml, ll[2 * j]); ml2 = fmaxf(ml2, ll[2 * j + 1]); }
  mu = fmaxf(mu, mu2); ml = fmaxf(ml, ml2);
  { const float a1 = __shfl_xor_sync(0xffffffffu, mu, 1), a2 = __shfl_xor_sync(0xffffffffu, mu, 2), a3 = __shfl_xor_sync(0xffffffffu, mu, 3);
    const float c1 = __shfl_xor_sync(0xffffffffu, ml, 1), c2 = __shfl_xor_sync(0xffffffffu, ml, 2), c3 = __shfl_xor_sync(0xffffffffu, ml, 3);
    mu = fmaxf(fmaxf(mu, a1), fmaxf(a2, a3)); ml = fmaxf(fmaxf(ml, c1), fmaxf(c2, c3)); }
  float su = 0.f, sl = 0.f;
#pragma unroll
  for (int c = 0; c < 14; c++) {
    if (c >= U && c < U + 7) {
      float e0 = ex2(lu[2 * (c - U)] - mu), e1 = ex2(lu[2 * (c - U) + 1] - mu);
      su = c == U ? e0 + e1 : (su + e0) + e1; P[2 * c] = pack2(e0, e1);
    } else P[2 * c] = 0u;
  }
  nb_sync(nbV | (P[2 * (U + MID)] & zero), 288);
#pragma unroll
  for (int k = 0; k < 3; k++) ldsm4(qa + k * 256, q[4 * k], q[4 * k + 1], q[4 * k + 2], q[4 * k + 3]);
#pragma unroll
  for (int c = 0; c < 14; c++) {
    if (c >= L && c < L + 7) {
      float e0 = ex2(ll[2 * (c - L)] - ml), e1 = ex2(ll[2 * (c - L) + 1] - ml);
      sl = c == L ? e0 + e1 : (sl + e0) + e1; P[2 * c + 1] = pack2(e0, e1);
    } else P[2 * c + 1] = 0u;
  }
  sx[0] = su; sx[4] = sl;
#pragma unroll
  for (int k = 1; k < 4; k++) sx[k] = __shfl_xor_sync(0xffffffffu, su, k);
#pragma unroll
  for (int k = 1; k < 4; k++) sx[4 + k] = __shfl_xor_sync(0xffffffffu, sl, k);
}

struct BandCfg { uint32_t ra0, ra1, meta; int b0, b1; };
__device__ __forceinline__ void band_cfg(int b, uint32_t tb, BandCfg& n) {
  uint32_t ln; asm volatile("mov.u32 %0, %%laneid;" : "=r"(ln));
  const int g = ln >> 2, t = ln & 3;
  const int sw = min(max(g + 1, b == 0 ? 4 : 0), b == 13 ? 5 : 8);
  const int i0 = 2 * t, i1 = 2 * t + 1;
  n.b0 = i0 <= sw - 2; n.b1 = i1 <= sw - 2;
  n.ra0 = tb + (i0 == sw - 1 ? 13 : i0 + 8 * n.b0 - g + 2) * 52;
  n.ra1 = tb + (i1 == sw - 1 ? 13 : i1 + 8 * n.b1 - g + 2) * 52;
  n.meta = ((0x5555u & ((1u << (2 * (sw - 1))) - 1)) ^ 0xDD88u ^ (((t ^ b) & 1) ? 0x5555u : 0u)) * 0x10001u;
}
__device__ __forceinline__ void band_load(const BandCfg& n, float (&T)[16], int& b0, int& b1, uint32_t& meta) {
#pragma unroll
  for (int jj = 0; jj < 8; jj++) { T[2 * jj] = lds_f32(n.ra0 + jj * 4); T[2 * jj + 1] = lds_f32(n.ra1 + jj * 4); }
  b0 = n.b0; b1 = n.b1; meta = n.meta;
}

struct Maps { CUtensorMap xc, xh, w, os, wo, ot; };

__global__ void __cluster_dims__(8, 1, 1) __launch_bounds__(512, 1)
na_attn_kernel(const __nv_bfloat16* __restrict__ x, const __nv_bfloat16* __restrict__ wqkv, const __nv_bfloat16* __restrict__ rpb, const __grid_constant__ Maps mp) {
  extern __shared__ __align__(1024) uint8_t smem_raw[];
  const uint32_t sb = smem_u32(smem_raw);
  if ((sb & 0x3FFFF) != SBC) return;
  const uint32_t bar = sb + SM_BAR;
  TR2START;
  const int tid = threadIdx.x, lane = tid & 31;
  const int warp = __shfl_sync(0xffffffffu, tid >> 5, 0);
  const int head = blockIdx.x & 3, base = blockIdx.x & 4, sp = blockIdx.x >> 2;
  const int par = sp < 24 ? sp / 6 : sp - 24, strip = sp < 24 ? sp - par * 6 : 6, ph = par >> 1, pw = par & 1;
  const int odd = strip & 1;

  uint4 wv[2 * NL];
  const int va = head == 1;
  const uint32_t wdst = sb + SM_W + (3 + va + ((tid >> 1) & 1)) * 6144 + (tid >> 2) * 32 + ((tid ^ (tid >> 4)) & 1) * 16;
  if (warp < 12) {
    asm volatile("barrier.cluster.arrive.relaxed.aligned;" ::: "memory");
    const uint32_t wo0 = (tid >> 2) * 1152 + head * 96 + va * 32 + (tid & 3) * 16;
#pragma unroll
    for (int i = 0; i < 2 * NL; i++)
      asm volatile("ld.global.nc.v4.b32 {%0,%1,%2,%3}, [%4];" : "=r"(wv[i].x), "=r"(wv[i].y), "=r"(wv[i].z), "=r"(wv[i].w)
                   : "l"(reinterpret_cast<const uint8_t*>(wqkv) + wo0 + (i & 1) * 96 * 1152 + (i / 2 + 1) * 384));
  }
  if (warp < 8) {
    asm volatile("setmaxnreg.inc.sync.aligned.u32 %0;" ::"n"(RA));
    float rv = -INFINITY;
    if (tid < 169) rv = __bfloat162float(rpb[head * 169 + tid]) * 1.4426950408889634f;
    if (tid < 192) {
      const int kc = (tid & 15) + 3, wc = (tid >> 4) % 6;
      sts128(tid < 96 ? sb + SM_K + kc * KS + wc * 128 + 48 : sb + SM_V + kc * 1536 + wc * 128 + (6 + (kc & 1)) * 16, make_uint4(0, 0, 0, 0));
    }
#pragma unroll
    for (int i = 0; i < 2 * NL; i++) sts128(wdst + (i & 1) * 3072 + (i / 2) * 18432, wv[i]);
    fence_async();
    asm volatile("bar.arrive 1, 384;" ::: "memory");
    if (tid < 182) asm volatile("st.shared.f32 [%0], %1;" ::"r"(sb + SM_RPB + tid * 4), "f"(rv) : "memory");
    const int jw = warp >> 2, j = jw ^ odd, w = warp & 3, wt = 4 * j + w;
    int variant = w;
    if (strip == 0 && j == 0 && w < 2) variant = 4;
    if (strip == 6 && j == 1 && w >= 2) variant = 5;
    const bool v1 = opq((uint32_t)(variant & 1)), v2 = opq((uint32_t)(variant & 2)), v4 = opq((uint32_t)(variant & 4));
    const uint32_t qa = opq(sb + SM_Q + (8 * j + 2 * w + ((lane >> 3) & 1)) * 768 + (lane >> 4) * 128 + (((lane & 7) * 16) ^ (((lane >> 3) & 1) * 64)));
    uint32_t oa = opq(sb + SM_O + j * 6144 + (2 * w + ((lane >> 3) & 1)) * 768 + (lane >> 4) * 128 + (lane & 7) * 16);
    uint64_t dA = opq(mkdesc(SBC + SM_K, 128, KS, 0) + j * (8 * KS / 16)), dB = opq(dA + (KSLOT >> 4));
    uint64_t dV[7];
#pragma unroll
    for (int i = 0; i < 7; i++) dV[i] = opq(mkdesc(SBC + SM_V, 768, 128, 0) + j * (8 * 1536 / 16) + i * 192);
    const uint32_t nbK = opq((uint32_t)(N_KRDY + jw)), nbQ = opq((uint32_t)(N_QK0 + jw)), nbV = opq((uint32_t)(N_VQ0 + jw));
    asm volatile("barrier.cluster.wait.aligned;" ::: "memory");
    asm volatile("bar.sync 3, 256;" ::: "memory");
    float T[16];
    TRDECL;
    int b0, b1;
    uint32_t meta, ob = bar + B_ODONE * 8, fb = bar + B_OFREE * 8, fp = 1;
    const uint32_t tb = opq(sb + SM_RPB + (variant < 4 ? 3 : variant + 1 - 2 * w) * 4);
    const bool own = ((w ^ head) & 2) == 0;
    const uint32_t dst13 = sb + SM_TIN2 + head * 6144 + (2 * j + (w & 1)) * 1536, src13 = opq(own ? dst13 : sb + SM_S + (2 * j + (w & 1)) * 1536);
    const uint32_t snd[4] = {opq(own ? 0u : mapa(dst13, base + (head ^ 2))), opq(mapa(bar + (B_TIN + 2) * 8, base + (head ^ 2))),
                             opq(mapa(dst13, base + (w & 2) + (~head & 1))), opq(mapa(bar + (B_TIN + 3) * 8, base + (w & 2) + (~head & 1)))};
    BandCfg nx;
    band_cfg(0, tb, nx);
    band_load(nx, T, b0, b1, meta);
    band_cfg(1, tb, nx);
    const uint32_t zero = opq(blockIdx.x >> 16);
    uint32_t special = opq(0x380Au << 1);
    uint32_t q[12];
    mbar_wait(bar + B_Q0 * 8, 0);
#pragma unroll
    for (int k = 0; k < 3; k++) ldsm4(qa + k * 256, q[4 * k], q[4 * k + 1], q[4 * k + 2], q[4 * k + 3]);
    nb_arrive(N_Q0, 384);
#pragma unroll 1
    for (int b = 0; b < 14; b++) {
      float SA[56], SB[56];
      TR(0, b, 0);
      if (jw) mbar_wait(bar + B_KIMP * 8, b & 1);
      nb_sync(nbK, 256);
      TR(0, b, 1);
      TR(0, b - 1, 9);
      wg_fence();
      wg_rs112<0>(SA, q[0], q[1], q[2], q[3], dA);
      wg_rs112<0>(SB, q[0], q[1], q[2], q[3], dB);
      wg_rs112<1>(SA, q[4], q[5], q[6], q[7], dA + 16);
      wg_rs112<1>(SB, q[4], q[5], q[6], q[7], dB + 16);
      wg_rs112<1>(SA, q[8], q[9], q[10], q[11], dA + 32);
      wg_rs112<1>(SB, q[8], q[9], q[10], q[11], dB + 32);
      wg_commit();
      nb_arrive(nbQ, 256);
      { const uint64_t t = dA; dA = dB; dB = t; }
      special >>= 1;
      if (special & 1) {
        if (b == 3) band_cfg(13, tb, nx);
        else {
          if (b == 1 || b == 13) band_load(nx, T, b0, b1, meta);
          if (b >= TB) {
            ob = bar + (b == 13 ? (own ? B_TIN + 2 : B_ODONE) : B_OTAIL + 2 * (b - TB) + jw) * 8;
            if (b > TB) { fb = bar + (B_TFREE + b - 12) * 8; fp = 0; }
            oa += b == 12 ? 0u - (SM_O - SM_Q) : (b == 13 ? src13 - (sb + SM_Q + wt * 1536) : 0);
          }
        }
      }
      TR(0, b, 2);
      wg_wait<0>(); pin(SA); pin(SB);
      mbar_arrive_elect(bar + B_KFREE * 8);
      TR(0, b, 3);
      TR(0, b - 1, 10);
      uint32_t P[28];
      float sx[8];
      if (v2) {
        if (v1) softmax_tile<6, 7>(SA, SB, T, b0, b1, P, sx, nbV, zero, qa, q); else softmax_tile<4, 5>(SA, SB, T, b0, b1, P, sx, nbV, zero, qa, q);
      } else if (!v4) {
        if (v1) softmax_tile<2, 3>(SA, SB, T, b0, b1, P, sx, nbV, zero, qa, q); else softmax_tile<0, 1>(SA, SB, T, b0, b1, P, sx, nbV, zero, qa, q);
      } else {
        if (v1) softmax_tile<4, 4>(SA, SB, T, b0, b1, P, sx, nbV, zero, qa, q); else softmax_tile<3, 3>(SA, SB, T, b0, b1, P, sx, nbV, zero, qa, q);
      }
      float O[24];
      TR(0, b, 4);
      wg_fence();
      wg_sp48<0>(O, P[0], P[1], P[2], P[3], dV[0], meta);
#pragma unroll
      for (int s = 1; s < 7; s++) wg_sp48<1>(O, P[4 * s], P[4 * s + 1], P[4 * s + 2], P[4 * s + 3], dV[s], meta);
      wg_commit();
      nb_arrive(N_PVISS, 384);
      TR(0, b, 6);
      mbar_wait(fb, fp);
      wg_wait<0>(); pin(O);
      mbar_arrive_elect(bar + B_VFREE * 8);
      TR(0, b, 7);
      float ru, rl;
      asm("rcp.approx.ftz.f32 %0, %1;" : "=f"(ru) : "f"(((fmaf(O[0], 0.f, sx[0]) + sx[1]) + sx[2]) + sx[3]));
      asm("rcp.approx.ftz.f32 %0, %1;" : "=f"(rl) : "f"(((fmaf(O[2], 0.f, sx[4]) + sx[5]) + sx[6]) + sx[7]));
#pragma unroll
      for (int i = 0; i < 3; i++)
        stsm4(oa + i * 256, pack2(O[8 * i] * ru, O[8 * i + 1] * ru), pack2(O[8 * i + 2] * rl, O[8 * i + 3] * rl),
              pack2(O[8 * i + 4] * ru, O[8 * i + 5] * ru), pack2(O[8 * i + 6] * rl, O[8 * i + 7] * rl));
      publish(ob);
      fp ^= 1;
      meta ^= 0x55555555u;
      TR(0, b, 8);
    }
    asm volatile("{\n.reg .pred p, q;\nsetp.ne.b32 q, %1, 0;\nelect.sync _|p, 0xffffffff;\nand.pred q, q, p;\n"
                 "@q cp.async.bulk.shared::cluster.shared::cta.mbarrier::complete_tx::bytes [%1], [%0], 1536, [%2];\n"
                 "@p cp.async.bulk.shared::cluster.shared::cta.mbarrier::complete_tx::bytes [%3], [%0], 1536, [%4];\n}"
                 ::"r"(src13), "r"(snd[0]), "r"(snd[1]), "r"(snd[2]), "r"(snd[3]) : "memory");
    nb_arrive(3, 384);
    TRDUMP;
    cluster_sync();
  } else if (warp < 12) {
    TRDECL;
    TR(2, -3, 0);
    asm volatile("setmaxnreg.inc.sync.aligned.u32 %0;" ::"n"(RG));
    TR(2, -3, 1);
    GemmCtx c;
    c.bar = bar;
    const int gw = warp - 8, tk = gw * 16 + (lane & 15), hi = lane >> 4;
    { const int col = tk >> 2, i = tk & 3;
      c.kC = sb + SM_K + (col + 3) * KS + hi * 128 + i * 16;
      c.vC[0] = sb + SM_V + (col + 3) * 1536 + hi * 128 + (2 * i + ((col + 3) & 1)) * 16;
      c.qC[0] = sb + SM_Q + col * 768 + hi * 128 + (col & 1) * 64 + i * 16; }
    { const int kc = gw - 1 + 19 * odd, i = lane & 7; c.hvalid = gw > 0; c.edge = gw == (odd ? 0 : 3);
      c.kH = sb + SM_K + kc * KS + (lane >> 3) * 128 + i * 16;
      c.vH[0] = sb + SM_V + kc * 1536 + (lane >> 3) * 128 + (i >> 2) * 768 + (2 * (i & 3) + ((kc ^ (i >> 2)) & 1)) * 16; }
    Stage xs[3];
#pragma unroll
    for (int i = 0; i < 3; i++) {
      const int p = (i + 1) % 3;
      xs[i].lo = (uint32_t)mkdesc(SBC + SM_X + p * 24576, 16, 0, 0); xs[i].full = bar + (B_FULL + p) * 8;
      xs[i].em = opq(mapa(bar + (B_EMPTY + p) * 8, base + p)); xs[i].par = 0;
    }
    c.never = x == nullptr;
    c.kC = opq(c.kC); c.kH = opq(c.kH);
    c.vC[1] = opq(c.vC[0] ^ 16); c.vC[0] = opq(c.vC[0]);
    c.vH[1] = opq(c.vH[0] ^ 16); c.vH[0] = opq(c.vH[0]);
    c.qC[1] = opq(c.qC[0] ^ 64); c.qC[0] = opq(c.qC[0]);
    c.spin = 0;
    c.hiA = (uint32_t)(mkdesc(0, 0, 1024, 1) >> 32) + (blockIdx.x >> 16); c.hiB = (uint32_t)(mkdesc(0, 0, 256, 3) >> 32) + (blockIdx.x >> 16);
    asm volatile("barrier.cluster.wait.aligned;" ::: "memory");
    TR(2, -3, 2);
#pragma unroll
    for (int i = 0; i < 2 * NL; i++) sts128(wdst + (i & 1) * 3072 + (i / 2) * 18432, wv[i]);
    fence_async();
    TR(2, -3, 3);
    asm volatile("bar.sync 1, 384;" ::: "memory");
    TR(2, -3, 4);
    mbar_wait(bar + B_WK * 8, 0);
    asm volatile("griddepcontrol.launch_dependents;");
    TR(2, -3, 5);
    uint32_t pk[12], pv[12], pq[12], hk1[6], hv1[6];
    gemm_iter<true, 0>(c, -2, pk, pv, pq, hk1, hv1, xs[0], xs[1], xs[2] TRPASS);
    TR2(blockIdx.x, 4);
    c.hiA = opq(c.hiA); c.hiB = opq(c.hiB);
#pragma unroll 1
    for (int b = -1;; b += 2) {
      gemm_iter<false, 1>(c, b, pk, pv, pq, hk1, hv1, xs[2], xs[0], xs[1] TRPASS);
      if (b == 11) break;
      gemm_iter<false, 0>(c, b + 1, pk, pv, pq, hk1, hv1, xs[2], xs[0], xs[1] TRPASS);
      const Stage t = xs[2]; xs[2] = xs[1]; xs[1] = xs[0]; xs[0] = t;
    }
    TR2(blockIdx.x, 6);
    c.hiA = opq(c.hiA); c.hiB = opq(c.hiB);
    const uint32_t st = sb + gw * 3072;
    const uint32_t sta = st + (lane & 15) * 64 + ((hi ^ ((lane >> 1) & 3)) * 16);
    const int oc = ph * 112 + strip * 16 + 8 * (gw >> 1) + 4 * (head >> 1) + 2 * (gw & 1), och = pw * 6 + (head & 1) * 3;
    float D0[48], D1[48];
    if (lane < 4) mbar_arrive_remote(bar + B_WOFREE * 8, 2 * lane + (head & 1));
    dump12<128>(c.qC[1], pq);
    nb_sync(N_QK1, 256);
    issue_halo<0, 8>(c, xs[2], D1);
    fence_async();
    nb_arrive(N_VQ0, 288); nb_arrive(N_VQ1, 288); nb_arrive(N_PVISS, 384);
    issue_halo<8, 12>(c, xs[2], D1);
    gwait<0>(c, B_KFREE);
    dump12<128>(c.kC, pk);
    if (c.edge) publish(bar + B_XK * 8);
    wg_wait<0>(); pin(D1);
    pack6(hk1, D1, 0);
    if (c.hvalid) dump6(c.kH, hk1);
    tail_free(bar + (B_TFREE + 1) * 8);
    pack6(hv1, D1, 24);
    fence_async();
    nb_arrive(N_KRDY, 256);
    gwait<0>(c, B_VFREE);
    dump12<128>(c.vC[0], pv);
    if (c.hvalid) dump6(c.vH[0], hv1);
    fence_async();
    edge_ready(c, B_XV);
    nb_arrive(N_VQ0, 288); nb_arrive(N_VQ1, 288);
    gwait<0>(c, B_WO);
    gwait<0>(c, B_TIN);
    TR(2, 13, 0);
    nb_sync(N_QK1, 256);
    issue_proj<SM_TIN0>(D0);
    wg_wait<0>(); pin(D0);
    TR(2, 13, 1);
    store_proj(D0, &mp.ot, st + SM_TST, sta + SM_TST, 8 * TB, oc, och);
    gwait<0>(c, B_TIN + 1);
    TR(2, 13, 2);
    nb_arrive(N_PVISS, 384);
    nb_sync(3, 384);
    issue_proj<SM_TIN1>(D1);
    wg_wait<0>(); pin(D1);
    TR(2, 13, 3);
    store_proj(D1, &mp.ot, st + SM_TIN0, sta + SM_TIN0, 8 * TB + 8, oc, och);
    TR(2, 13, 4);
    gwait<0>(c, B_TIN + 2);
    TR(2, 13, 5);
    issue_proj_half<0>(D0, head & 1);
    gwait<0>(c, B_TIN + 3);
    TR(2, 13, 6);
    issue_proj_half<1>(D0, ~head & 1);
    asm volatile("barrier.cluster.arrive.relaxed.aligned;" ::: "memory");
    wg_wait<0>(); pin(D0);
    store_proj(D0, &mp.ot, st + SM_TIN0 + 12288, sta + SM_TIN0 + 12288, 8 * TB + 16, oc, och);
    TR(2, 13, 7);
    if (lane == 0) asm volatile("cp.async.bulk.wait_group.read 0;" ::: "memory");
    __syncwarp();
    TR(2, 13, 8);
    TR2(blockIdx.x, 2);
    TR2FLUSH(blockIdx.x);
    TRDUMP;
    asm volatile("barrier.cluster.wait.aligned;" ::: "memory");
  } else {
    asm volatile("setmaxnreg.dec.sync.aligned.u32 24;");
    if (warp == 15) {
      const int l = min(lane, 24), row = head + (l < 16 ? 0 : 4 * ((l - 16) / 3)), col = strip * 16 + (l < 16 ? l : (l - 16) % 3 + (odd ? 16 : (strip ? -3 : 0)));
      const uint8_t* p = reinterpret_cast<const uint8_t*>(x) + (uint32_t)(row * ROWB + (ph * 112 + col) * 768 + pw * 384);
#pragma unroll
      for (int i = 0; i < 3; i++) asm volatile("prefetch.global.L2 [%0];" ::"l"(p + i * 128));
    } else if (elect_one()) {
      if (warp == 12) {
        mbar_init(bar + B_WK * 8, 1);
#pragma unroll
        for (int i = 0; i < NL; i++) load_w(&mp.w, sb + SM_W + (3 * i + 5 - 2 * va) * 6144, bar + B_WK * 8, (i + 1) * 192 + head * 48 + 32 - 32 * va);
        asm volatile("prefetch.tensormap [%0];" ::"l"(head == 1 ? &mp.xh : &mp.xc) : "memory");
      } else if (warp == 13) {
#pragma unroll
        for (int i = 0; i < B_XK; i++) if (i != B_WK) mbar_init(bar + i * 8, (i >= B_EMPTY && i < B_TIN) || (i >= B_TFREE && i < B_WK) ? 16 : (i == B_TIN + 2 ? 5 : 1));
      } else {
#pragma unroll
        for (int i = B_XK; i < B_COUNT; i++) mbar_init(bar + i * 8, i < B_Q0 ? 2 : (i < B_ODONE ? (i == B_WOFREE ? 16 : 4) : (i == B_VFREE ? 9 : 8)));
        mbar_arrive(bar + B_XK * 8); mbar_arrive(bar + B_XV * 8);
      }
      asm volatile("fence.mbarrier_init.release.cluster;" ::: "memory");
    }
    __syncwarp();
    asm volatile("barrier.cluster.arrive.relaxed.aligned;" ::: "memory");
    if (warp != 12) asm volatile("barrier.cluster.wait.aligned;" ::: "memory");
    else {
      const int cc = ph * 112 + strip * 16, ch = cc + (odd ? 16 : (strip ? -3 : 0)), rh = strip ? -4 : 112;
      const uint32_t fb = opq(bar + (B_FULL + head) * 8), dst0 = sb + SM_X + head * 24576, c3 = opq((uint32_t)(pw * 3)), mask = opq(15u << base);
      int t = head == 0 ? 2 : head - 1;
      uint64_t mx = opq((uint64_t)(t ? &mp.xc : &mp.xh));
      uint32_t row = opq((uint32_t)(t ? 4 * t - 4 : rh)), col = opq((uint32_t)(t ? cc : ch)), dst = opq(dst0 + (t ? 0 : 2048));
#pragma unroll 1
      for (int n = 0;; n++) {
        if (n) mbar_wait(fb + (B_EMPTY - B_FULL) * 8, ~n & 1);
        else asm volatile("barrier.cluster.wait.aligned;" ::: "memory");
        if (head < 3) {
          asm volatile("{\n.reg .pred p;\n.reg .b16 m;\nelect.sync _|p, 0xffffffff;\ncvt.u16.u32 m, %7;\n"
                       "@p cp.async.bulk.tensor.4d.shared::cluster.global.mbarrier::complete_tx::bytes.multicast::cluster [%0], [%1, {%3,%4,%5,%6}], [%2], m;\n}"
                       ::"r"(dst), "l"(mx), "r"(fb), "r"(0), "r"(row), "r"(col), "r"(c3), "r"(mask) : "memory");
          if (lane < 4) remote_expect(mapa(fb, base + lane), dst == dst0 ? 24576 : 18432);
          __syncwarp();
        }
        if (n == 0 && elect_one()) {
#pragma unroll
          for (int i = 0; i < 3; i++) load_w(&mp.w, sb + SM_W + i * 6144, bar + B_WQ * 8, head * 48 + i * 16);
          mbar_expect(bar + B_WQ * 8, 18432);
        }
        __syncwarp();
        if (head == 3 || n == 11) break;
        t += 3;
        const int hn = t / 5;
        const bool core = t != 5 * hn;
        mx = opq((uint64_t)(core ? &mp.xc : &mp.xh));
        row = opq((uint32_t)(core ? 4 * (t - hn - 1) : rh + 16 * hn)); col = opq((uint32_t)(core ? cc : ch)); dst = opq(dst0 + (core ? 0 : 2048));
        if (elect_one()) asm volatile("cp.async.bulk.prefetch.tensor.4d.L2.global [%0, {%1,%2,%3,%4}];" ::"l"(mx), "r"(0), "r"(row), "r"(col), "r"(c3) : "memory");
        __syncwarp();
      }
      mbar_wait(bar + B_WOFREE * 8, 0);
      if (elect_one()) {
        const int qr = (blockIdx.x & 7) >> 1;
#pragma unroll
        for (int i = 0; i < 3; i++)
          asm volatile("cp.async.bulk.tensor.2d.shared::cluster.global.mbarrier::complete_tx::bytes.multicast::cluster [%0], [%1, {%3,%4}], [%2], %5;"
                       ::"r"(sb + SM_TWO + i * 12288 + qr * 3072), "l"(&mp.wo), "r"(bar + B_WO * 8), "r"((head & 1) * 96 + i * 32), "r"(qr * 48),
                         "h"((uint16_t)(0x55 << (head & 1))) : "memory");
      }
      __syncwarp();
    }
    if (warp & 1) {
      const uint32_t partner = (blockIdx.x & 7) ^ 4;
      const int cs = odd ? 3 : (strip == 6 ? 15 : 16), cd = odd || strip == 6 ? 19 : 0;
      const uint32_t rb = opq(mapa(bar, partner));
      TRDECL;
      if (warp == 13) {
        const uint32_t dst = opq(mapa(sb + SM_V + cd * 1536, partner)), src = opq(sb + SM_V + cs * 1536);
#pragma unroll 1
        for (int b = 0;; b++) {
          const uint32_t pa = b & 1;
          nb_arrive(N_VQ0, 288);
          mbar_wait(bar + B_XV * 8, pa);
          TR(1, b, 0);
          if (elect_one()) { copy_remote(dst, src, 4608, rb + B_VIMP * 8); remote_expect(rb + B_VIMP * 8, 4608); }
          __syncwarp();
          TR(1, b, 1);
          mbar_wait(bar + B_VIMP * 8, pa);
          TR(1, b, 2);
          nb_arrive(N_VQ1, 288);
          if (elect_one()) remote_arrive(rb + B_VFREE * 8);
          __syncwarp();
          TR(1, b, 3);
          if (b == 13) break;
          mbar_wait(bar + B_VFREE * 8, pa);
          if (elect_one()) remote_arrive(rb + B_XV * 8);
          __syncwarp();
        }
      } else {
        const uint32_t dst = opq(mapa(sb + SM_K + cd * KS, partner)), src = opq(sb + SM_K + cs * KS);
#pragma unroll 1
        for (int b = 0;; b++) {
          const uint32_t pa = b & 1, so = (pa ^ 1) * KSLOT;
          mbar_wait(bar + B_XK * 8, pa);
          TR(1, b - 1, 4);
          if (elect_one()) {
            copy_remote(dst + so, src + so, 3 * KS, rb + B_KIMP * 8);
            if (b == 0) copy_remote(dst, src, 3 * KS, rb + B_KIMP * 8);
            remote_expect(rb + B_KIMP * 8, b ? 3 * KS : 6 * KS);
          }
          __syncwarp();
          TR(1, b - 1, 5);
          TR(1, b - 1, 7);
          if (b == 13) break;
          mbar_wait(bar + B_KFREE * 8, pa);
          if (elect_one()) remote_arrive(rb + B_XK * 8);
          __syncwarp();
        }
      }
      TRDUMP;
    }
    if (warp == 14) {
      int* flag = g_flags + (par * 7 + strip) * 2 * FS;
      if (elect_one()) {
        mbar_expect(bar + B_WK * 8, NL * 6144);
        mbar_expect(bar + B_WO * 8, 36864);
        mbar_expect(bar + B_TIN * 8, 24576); mbar_expect(bar + (B_TIN + 1) * 8, 24576); mbar_expect(bar + (B_TIN + 2) * 8, 6144); mbar_expect(bar + (B_TIN + 3) * 8, 12288);
      }
      __syncwarp();
#pragma unroll 1
      for (int b = 0; b < TB; b++) {
        mbar_wait(bar + B_ODONE * 8, b & 1);
        if (lane == 0) {
#pragma unroll 1
          for (int i = 0; i < 16; i += OCH) {
            asm volatile("cp.async.bulk.tensor.3d.global.shared::cta.bulk_group [%0, {%2,%3,%4}], [%1];"
                         ::"l"(&mp.os), "r"(sb + SM_O + i * 768), "r"(pw * 192), "r"(8 * b + 2 * head), "r"(ph * 112 + strip * 16 + i) : "memory");
            asm volatile("cp.async.bulk.commit_group;\ncp.async.bulk.wait_group 0;" ::: "memory");
          }
        }
        __syncwarp();
        mbar_arrive_elect(bar + B_OFREE * 8);
        if (lane == 0)
          asm volatile("fence.proxy.async.global;\nfence.acq_rel.gpu;\nred.relaxed.gpu.global.add.s32 [%0], 1;\nred.relaxed.gpu.global.add.s32 [%1], 1;"
                       ::"l"(flag + b * 56 * FS), "l"(flag + (b * 56 + 1) * FS) : "memory");
        __syncwarp();
      }
#pragma unroll 1
      for (int t = 0; t < 4; t++) {
        const int i = t >> 1, j = (t ^ odd) & 1, d = (lane + head + 1) & 3;
        const uint32_t dst = opq(mapa(sb + (i ? SM_TIN1 : SM_TIN0) + head * 6144 + j * 3072, base + d)), rb = opq(mapa(bar + (B_TIN + i) * 8, base + d));
        const uint32_t src = opq(sb + (i ? SM_Q : SM_O) + j * 6144 + (d & 2) * 1536);
        if (!(t & 1)) mbar_wait(bar + (B_TFREE + i) * 8, 0);
        mbar_wait(bar + (B_OTAIL + t) * 8, 0);
        if (lane < 4) copy_remote(dst, src, 3072, rb);
        __syncwarp();
      }
    }
    cluster_sync();
  }
}

constexpr int NSTB = 6;
constexpr int NTB = TB * 56;
constexpr int SM_B_ST = 0;
constexpr int SM_B_IN = 73728;
constexpr int SM_B_W = SM_B_IN + 3 * 24576;
constexpr int SM_B_BAR = SM_B_IN + NSTB * 24576;
constexpr int SM_B_TOTAL = SM_B_BAR + 512;
struct MapsB { CUtensorMap oi, oo, wo; };

__global__ void __launch_bounds__(512, 1)
na_proj_kernel(const __grid_constant__ MapsB mp) {
  extern __shared__ __align__(1024) uint8_t smem_raw[];
  const uint32_t sb = smem_u32(smem_raw);
  if ((sb & 0x3FFFF) != SBC) return;
  const uint32_t bar = sb + SM_B_BAR;
  const int tid = threadIdx.x, lane = tid & 31;
  const int warp = __shfl_sync(0xffffffffu, tid >> 5, 0);
  TR2START;
  TRB(47, 0);
  if (warp == 12 && elect_one()) {
#pragma unroll
    for (int i = 0; i <= 2 * NSTB; i++) mbar_init(bar + i * 8, i < NSTB || i == 2 * NSTB ? 1 : 12);
    asm volatile("st.shared.u32 [%0], 0;" ::"r"(bar + 120) : "memory");
    mbar_expect(bar + 2 * NSTB * 8, 73728);
#pragma unroll
    for (int i = 0; i < 2; i++)
      asm volatile("cp.async.bulk.tensor.3d.shared::cluster.global.mbarrier::complete_tx::bytes [%0], [%1, {%3,%4,%5}], [%2];"
                   ::"r"(sb + SM_B_W + i * 36864), "l"(&mp.wo), "r"(bar + 2 * NSTB * 8), "r"(0), "r"(0), "r"(i * 3) : "memory");
  }
  __syncthreads();
  const int step = gridDim.x;
  if (warp == 15) {
    int so = 0;
    nb_arrive(4, 288); nb_arrive(5, 288); nb_arrive(6, 288);
#pragma unroll 1
    for (int n = blockIdx.x, tk = 0; n < NTB; n += step, tk++) {
      uint32_t cc = 0;
#pragma unroll
      for (int wg = 0; wg < 3; wg++) {
        if (lane == 0) asm volatile("cp.async.bulk.wait_group.read 5;" ::: "memory");
        nb_sync(1 + wg, 160);
        if (wg == 0 || n + step < NTB) nb_arrive(4 + wg, 288);
        if (wg == 0) asm volatile("ld.shared.u32 %0, [%1];" : "=r"(cc) : "r"(bar + 128 + tk * 4) : "memory");
        if (lane == 0) {
          asm volatile("cp.async.bulk.tensor.4d.global.shared::cta.bulk_group [%0, {%2,%3,%4,%5}], [%1];"
                       ::"l"(&mp.oo), "r"(sb + SM_B_ST + wg * 8192 + so), "r"(0), "r"((cc >> 8) & 255), "r"(cc >> 16), "r"((cc & 1) * 3 + wg) : "memory");
          asm volatile("cp.async.bulk.commit_group;" ::: "memory");
        }
        __syncwarp();
      }
      so = so == 49152 ? 0 : so + 24576;
    }
    if (lane == 0) asm volatile("cp.async.bulk.wait_group.read 0;" ::: "memory");
  } else if (warp >= 12) {
    nb_sync(7, 480);
#pragma unroll 1
    for (int n = blockIdx.x + (warp - 12) * step; n < NTB; n += 3 * step) {
      const int b = n / 56, rem = n - b * 56, par = rem / 14;
      const int c0 = opq((uint32_t)(par & 1)), c1 = opq((uint32_t)(8 * b)), c2 = opq((uint32_t)((par >> 1) * 112 + (rem - par * 14) * 8));
      int v; uint32_t spin = 0, tk = 0;
      do { asm volatile("ld.acquire.gpu.global.s32 %0, [%1];" : "=r"(v) : "l"(g_flags + n * FS) : "memory"); } while (v < 4 && ++spin < SPIN_LIMIT);
      if (lane == 0) asm volatile("atom.shared.add.u32 %0, [%1], 1;" : "=r"(tk) : "r"(bar + 120) : "memory");
      asm volatile("fence.proxy.async.global;" ::: "memory");
      tk = __shfl_sync(0xffffffffu, tk, 0);
      TRB(tk, 0);
      const uint32_t use = tk / NSTB, sg = tk - use * NSTB;
      if (use) mbar_wait(bar + (NSTB + sg) * 8, (use - 1) & 1);
      TRB(tk, 1);
      if (elect_one()) {
        asm volatile("st.shared.u32 [%0], %1;" ::"r"(bar + 128 + tk * 4), "r"(c0 | c1 << 8 | c2 << 16) : "memory");
        mbar_expect(bar + sg * 8, 24576);
        asm volatile("cp.async.bulk.tensor.3d.shared::cluster.global.mbarrier::complete_tx::bytes [%0], [%1, {%3,%4,%5}], [%2];"
                     ::"r"(sb + SM_B_IN + sg * 24576), "l"(&mp.oi), "r"(bar + sg * 8), "r"(c0 * 192), "r"(c1), "r"(c2) : "memory");
        g_flags[n * FS] = 0;
      }
      __syncwarp();
    }
  } else {
    const int wg = warp >> 2, w = warp & 3;
    uint32_t a[48];
    mbar_wait(bar + 2 * NSTB * 8, 0);
    {
      const int k = (lane & 7) + (lane >> 4) * 8, ch = (warp & 1) * 2 + ((lane >> 3) & 1);
      const uint32_t wa = sb + SM_B_W + (warp >> 1) * 12288 + k * 64 + ((ch ^ ((k >> 1) & 3)) * 16);
#pragma unroll
      for (int i = 0; i < 12; i++)
        asm volatile("ldmatrix.sync.aligned.m8n8.x4.trans.shared.b16 {%0,%1,%2,%3}, [%4];"
                     : "=r"(a[4 * i]), "=r"(a[4 * i + 1]), "=r"(a[4 * i + 2]), "=r"(a[4 * i + 3]) : "r"(wa + i * 1024) : "memory");
    }
    nb_sync(7, 480);
    TRB(47, 1);
    const uint32_t sta = opq(sb + SM_B_ST + wg * 8192 + ((lane & 7) + (lane >> 4) * 8) * 128 + (((2 * w + ((lane >> 3) & 1)) ^ (lane & 7)) * 16));
    const uint32_t hi = opq((uint32_t)(mkdesc(0, 0, 3072, 0) >> 32) + (blockIdx.x >> 16)), bb = opq(bar);
    const uint32_t nbT = opq((uint32_t)(4 + wg)), nbN = opq((uint32_t)(wg == 2 ? 4 : 5 + wg)), nbD = opq((uint32_t)(1 + wg));
    int left = (NTB - blockIdx.x + step - 1) / step;
    if (wg == 2) nb_arrive(4, 288);
#pragma unroll 1
    for (uint32_t ph = 0;; ph ^= 1) {
#pragma unroll
      for (int sg = 0; sg < NSTB; sg++) {
        constexpr uint64_t db = mkdesc(SBC + SM_B_IN, 128, 3072, 0);
        float D[32];
        mbar_wait(bb + sg * 8, ph);
        nb_sync(nbT, 288);
        wg_fence();
        wg_rs64<0>(D, a[0], a[1], a[2], a[3], dsc(db + sg * 1536, hi));
#pragma unroll
        for (int k = 1; k < 12; k++) wg_rs64<1>(D, a[4 * k], a[4 * k + 1], a[4 * k + 2], a[4 * k + 3], dsc(db + sg * 1536 + k * 16, hi));
        wg_commit();
        nb_arrive(nbN, 288);
        wg_wait<0>(); pin(D);
        mbar_arrive_elect(bb + (NSTB + sg) * 8);
#pragma unroll
        for (int q = 0; q < 4; q++)
          asm volatile("stmatrix.sync.aligned.m8n8.x4.trans.shared.b16 [%0], {%1,%2,%3,%4};" ::"r"(sta + (sg % 3) * 24576 + q * 2048),
                       "r"(pack2(D[8 * q], D[8 * q + 1])), "r"(pack2(D[8 * q + 2], D[8 * q + 3])), "r"(pack2(D[8 * q + 4], D[8 * q + 5])), "r"(pack2(D[8 * q + 6], D[8 * q + 7])) : "memory");
        fence_async();
        nb_arrive(nbD, 160);
        if (wg == 0) TRB(31 - left, 5);
        if (--left == 0) goto done;
      }
    }
  done:
    if (wg == 0) nb_arrive(4, 288);
    TR2(132 + blockIdx.x, 2);
    TR2FLUSH(132 + blockIdx.x);
  }
}

typedef CUresult (*EncodeFn)(CUtensorMap*, CUtensorMapDataType, cuuint32_t, void*, const cuuint64_t*, const cuuint64_t*, const cuuint32_t*,
                             const cuuint32_t*, CUtensorMapInterleave, CUtensorMapSwizzle, CUtensorMapL2promotion, CUtensorMapFloatOOBfill);
static EncodeFn g_enc = nullptr;
static void make_map(CUtensorMap* m, const void* p, int rank, const cuuint64_t* dim, const cuuint64_t* str, const cuuint32_t* box, CUtensorMapSwizzle sw) {
  const cuuint32_t ones[5] = {1, 1, 1, 1, 1};
  g_enc(m, CU_TENSOR_MAP_DATA_TYPE_BFLOAT16, rank, (void*)p, dim, str, box, ones, CU_TENSOR_MAP_INTERLEAVE_NONE, sw,
        CU_TENSOR_MAP_L2_PROMOTION_L2_128B, CU_TENSOR_MAP_FLOAT_OOB_FILL_NONE);
}

extern "C" void kernel_launch(void* const* d_in, const int* in_sizes, int n_in, void* d_out, int out_size) {
  const __nv_bfloat16* x = (const __nv_bfloat16*)d_in[0];
  const __nv_bfloat16* wqkv = (const __nv_bfloat16*)d_in[1];
  const __nv_bfloat16* wo = (const __nv_bfloat16*)d_in[2];
  const __nv_bfloat16* rpb = (const __nv_bfloat16*)d_in[3];

  if (!g_enc) {
    void* fn = nullptr; cudaDriverEntryPointQueryResult qr;
    cudaGetDriverEntryPoint("cuTensorMapEncodeTiled", &fn, cudaEnableDefault, &qr);
    g_enc = (EncodeFn)fn;
    cudaFuncSetAttribute(na_attn_kernel, cudaFuncAttributeMaxDynamicSharedMemorySize, SM_A_TOTAL);
    cudaFuncSetAttribute(na_proj_kernel, cudaFuncAttributeMaxDynamicSharedMemorySize, SM_B_TOTAL);
  }
  Maps ma; MapsB mb;
  { cuuint64_t dim[4] = {64, 112, 224, 6}, str[3] = {(cuuint64_t)ROWB, 768, 128};
    cuuint32_t box[4] = {64, 4, 16, 3}, boxh[4] = {64, 16, 3, 3}, boxo[4] = {64, 8, 8, 1};
    make_map(&ma.xc, x, 4, dim, str, box, CU_TENSOR_MAP_SWIZZLE_128B);
    make_map(&ma.xh, x, 4, dim, str, boxh, CU_TENSOR_MAP_SWIZZLE_128B);
    make_map(&mb.oo, d_out, 4, dim, str, boxo, CU_TENSOR_MAP_SWIZZLE_128B); }
  { cuuint64_t dim[3] = {384, 112, 224}, str[2] = {(cuuint64_t)ROWB, 768};
    cuuint32_t box[3] = {192, 8, 8}, boxs[3] = {192, 2, OCH};
    make_map(&mb.oi, d_out, 3, dim, str, box, CU_TENSOR_MAP_SWIZZLE_NONE);
    make_map(&ma.os, d_out, 3, dim, str, boxs, CU_TENSOR_MAP_SWIZZLE_NONE); }
  { cuuint64_t dim[4] = {32, 112, 224, 12}, str[3] = {(cuuint64_t)ROWB, 768, 64};
    cuuint32_t box[4] = {32, 8, 2, 3};
    make_map(&ma.ot, d_out, 4, dim, str, box, CU_TENSOR_MAP_SWIZZLE_64B); }
  { cuuint64_t dim[2] = {576, 192}, str[1] = {1152};
    cuuint32_t box[2] = {16, 192};
    make_map(&ma.w, wqkv, 2, dim, str, box, CU_TENSOR_MAP_SWIZZLE_32B); }
  { cuuint64_t dim[3] = {32, 192, 6}, str[2] = {384, 64};
    cuuint32_t box[3] = {32, 192, 3};
    make_map(&mb.wo, wo, 3, dim, str, box, CU_TENSOR_MAP_SWIZZLE_64B); }
  { cuuint64_t dim[2] = {192, 192}, str[1] = {384};
    cuuint32_t box[2] = {32, 48};
    make_map(&ma.wo, wo, 2, dim, str, box, CU_TENSOR_MAP_SWIZZLE_64B); }
  na_attn_kernel<<<112, 512, SM_A_TOTAL>>>(x, wqkv, rpb, ma);
  cudaLaunchConfig_t cfg = {};
  cfg.gridDim = dim3(20); cfg.blockDim = dim3(512); cfg.dynamicSmemBytes = SM_B_TOTAL; cfg.stream = cudaStreamPerThread;
  cudaLaunchAttribute at[1];
  at[0].id = cudaLaunchAttributeProgrammaticStreamSerialization; at[0].val.programmaticStreamSerializationAllowed = 1;
  cfg.attrs = at; cfg.numAttrs = 1;
  cudaLaunchKernelEx(&cfg, na_proj_kernel, mb);
}
```

```cpp
#include <cuda_runtime.h>
#include <cuda_bf16.h>
#include <cuda.h>
#include <stdint.h>

#define SPIN_LIMIT (1u << 18)

__device__ __forceinline__ uint32_t smem_u32(const void* p) { return (uint32_t)__cvta_generic_to_shared(p); }
__device__ __forceinline__ void wg_fence() { asm volatile("wgmma.fence.sync.aligned;" ::: "memory"); }
__device__ __forceinline__ void wg_commit() { asm volatile("wgmma.commit_group.sync.aligned;" ::: "memory"); }
template <int N> __device__ __forceinline__ void wg_wait() { asm volatile("wgmma.wait_group.sync.aligned %0;" ::"n"(N) : "memory"); }
template <int N> __device__ __forceinline__ void pin(float (&d)[N]) {
#pragma unroll
  for (int i = 0; i < N; i++) asm volatile("" : "+f"(d[i])::"memory");
}
__host__ __device__ constexpr uint64_t mkdesc(uint32_t addr, uint32_t lbo, uint32_t sbo, uint32_t sw) {
  return (uint64_t)((addr & 0x3FFFF) >> 4) | ((uint64_t)(lbo >> 4) << 16) | ((uint64_t)(sbo >> 4) << 32) | ((uint64_t)sw << 62);
}
__device__ __forceinline__ void mbar_init(uint32_t bar, uint32_t cnt) { asm volatile("mbarrier.init.shared::cta.b64 [%0], %1;" ::"r"(bar), "r"(cnt) : "memory"); }
__device__ __forceinline__ void mbar_arrive(uint32_t bar) { asm volatile("mbarrier.arrive.shared::cta.b64 _, [%0];" ::"r"(bar) : "memory"); }
__device__ __forceinline__ bool elect_one() {
  uint32_t r; asm volatile("{\n.reg .pred p;\nelect.sync _|p, 0xffffffff;\nselp.u32 %0, 1, 0, p;\n}" : "=r"(r)); return r;
}
__device__ __forceinline__ void mbar_arrive_elect(uint32_t bar) {
  asm volatile("{\n.reg .pred p;\nelect.sync _|p, 0xffffffff;\n@p mbarrier.arrive.shared::cta.b64 _, [%0];\n}" ::"r"(bar) : "memory");
}
__device__ __forceinline__ void mbar_expect(uint32_t bar, uint32_t bytes) { asm volatile("mbarrier.arrive.expect_tx.shared::cta.b64 _, [%0], %1;" ::"r"(bar), "r"(bytes) : "memory"); }
__device__ __forceinline__ void mbar_arrive_remote(uint32_t bar, uint32_t cta) {
  asm volatile("{\n.reg .b32 ra;\nmapa.shared::cluster.u32 ra, %0, %1;\nmbarrier.arrive.relaxed.cluster.shared::cluster.b64 _, [ra];\n}" ::"r"(bar), "r"(cta) : "memory");
}
__device__ __forceinline__ void mbar_wait(uint32_t bar, uint32_t parity) {
  asm volatile("{\n.reg .pred p;\n.reg .b32 n;\nmov.b32 n, 0;\nWL:\nmbarrier.try_wait.parity.shared::cta.b64 p, [%0], %1;\n@p bra WD;\n"
               "add.u32 n, n, 1;\nsetp.lt.u32 p, n, 65536;\n@p bra WL;\nWD:\n}" ::"r"(bar), "r"(parity) : "memory");
}
__device__ __forceinline__ void nb_sync(int id, int n) { asm volatile("bar.sync %0, %1;" ::"r"(id), "r"(n) : "memory"); }
__device__ __forceinline__ void nb_arrive(int id, int n) { asm volatile("bar.arrive %0, %1;" ::"r"(id), "r"(n) : "memory"); }
__device__ __forceinline__ uint32_t opq(uint32_t x) { uint32_t r; asm volatile("mov.b32 %0, %1;" : "=r"(r) : "r"(x)); return r; }
__device__ __forceinline__ uint64_t opq(uint64_t x) { uint64_t r; asm volatile("mov.b64 %0, %1;" : "=l"(r) : "l"(x)); return r; }
__device__ __forceinline__ uint32_t mapa(uint32_t a, uint32_t cta) { uint32_t r; asm("mapa.shared::cluster.u32 %0, %1, %2;" : "=r"(r) : "r"(a), "r"(cta)); return r; }
__device__ __forceinline__ void fence_async() { asm volatile("fence.proxy.async.shared::cta;" ::: "memory"); }
__device__ __forceinline__ void cluster_sync() {
  asm volatile("barrier.cluster.arrive.relaxed.aligned;\nbarrier.cluster.wait.aligned;" ::: "memory");
}
__device__ __forceinline__ uint32_t pack2(float lo, float hi) {
  uint32_t r; asm("cvt.rn.bf16x2.f32 %0, %1, %2;" : "=r"(r) : "f"(hi), "f"(lo)); return r;
}
__device__ __forceinline__ void stsm4(uint32_t a, uint32_t r0, uint32_t r1, uint32_t r2, uint32_t r3) {
  asm volatile("stmatrix.sync.aligned.m8n8.x4.shared.b16 [%0], {%1,%2,%3,%4};" ::"r"(a), "r"(r0), "r"(r1), "r"(r2), "r"(r3) : "memory");
}
__device__ __forceinline__ void ldsm4(uint32_t a, uint32_t& r0, uint32_t& r1, uint32_t& r2, uint32_t& r3) {
  asm volatile("ldmatrix.sync.aligned.m8n8.x4.shared.b16 {%0,%1,%2,%3}, [%4];" : "=r"(r0), "=r"(r1), "=r"(r2), "=r"(r3) : "r"(a) : "memory");
}
__device__ __forceinline__ void sts128(uint32_t a, uint4 v) {
  asm volatile("st.shared.v4.b32 [%0], {%1,%2,%3,%4};" ::"r"(a), "r"(v.x), "r"(v.y), "r"(v.z), "r"(v.w) : "memory");
}
__device__ __forceinline__ float lds_f32(uint32_t a) { float v; asm volatile("ld.shared.f32 %0, [%1];" : "=f"(v) : "r"(a)); return v; }
__device__ __forceinline__ float ex2(float x) { float y; asm("ex2.approx.ftz.f32 %0, %1;" : "=f"(y) : "f"(x)); return y; }

template<int SC> __device__ __forceinline__ void wg_ss144(float (&d)[72], uint64_t da, uint64_t db) {
  asm volatile("{\n.reg .pred p;\nsetp.ne.b32 p, %74, 0;\nwgmma.mma_async.sync.aligned.m64n144k16.f32.bf16.bf16 {%0,%1,%2,%3,%4,%5,%6,%7,%8,%9,%10,%11,%12,%13,%14,%15,%16,%17,%18,%19,%20,%21,%22,%23,%24,%25,%26,%27,%28,%29,%30,%31,%32,%33,%34,%35,%36,%37,%38,%39,%40,%41,%42,%43,%44,%45,%46,%47,%48,%49,%50,%51,%52,%53,%54,%55,%56,%57,%58,%59,%60,%61,%62,%63,%64,%65,%66,%67,%68,%69,%70,%71}, %72, %73, p, 1, 1, 0, 1;\n}\n"
    : "+f"(d[0]),"+f"(d[1]),"+f"(d[2]),"+f"(d[3]),"+f"(d[4]),"+f"(d[5]),"+f"(d[6]),"+f"(d[7]),"+f"(d[8]),"+f"(d[9]),"+f"(d[10]),"+f"(d[11]),"+f"(d[12]),"+f"(d[13]),"+f"(d[14]),"+f"(d[15]),"+f"(d[16]),"+f"(d[17]),"+f"(d[18]),"+f"(d[19]),"+f"(d[20]),"+f"(d[21]),"+f"(d[22]),"+f"(d[23]),"+f"(d[24]),"+f"(d[25]),"+f"(d[26]),"+f"(d[27]),"+f"(d[28]),"+f"(d[29]),"+f"(d[30]),"+f"(d[31]),"+f"(d[32]),"+f"(d[33]),"+f"(d[34]),"+f"(d[35]),"+f"(d[36]),"+f"(d[37]),"+f"(d[38]),"+f"(d[39]),"+f"(d[40]),"+f"(d[41]),"+f"(d[42]),"+f"(d[43]),"+f"(d[44]),"+f"(d[45]),"+f"(d[46]),"+f"(d[47]),"+f"(d[48]),"+f"(d[49]),"+f"(d[50]),"+f"(d[51]),"+f"(d[52]),"+f"(d[53]),"+f"(d[54]),"+f"(d[55]),"+f"(d[56]),"+f"(d[57]),"+f"(d[58]),"+f"(d[59]),"+f"(d[60]),"+f"(d[61]),"+f"(d[62]),"+f"(d[63]),"+f"(d[64]),"+f"(d[65]),"+f"(d[66]),"+f"(d[67]),"+f"(d[68]),"+f"(d[69]),"+f"(d[70]),"+f"(d[71]) : "l"(da), "l"(db), "n"(SC));
}
template<int SC> __device__ __forceinline__ void wg_ss96(float (&d)[48], uint64_t da, uint64_t db) {
  asm volatile("{\n.reg .pred p;\nsetp.ne.b32 p, %50, 0;\nwgmma.mma_async.sync.aligned.m64n96k16.f32.bf16.bf16 {%0,%1,%2,%3,%4,%5,%6,%7,%8,%9,%10,%11,%12,%13,%14,%15,%16,%17,%18,%19,%20,%21,%22,%23,%24,%25,%26,%27,%28,%29,%30,%31,%32,%33,%34,%35,%36,%37,%38,%39,%40,%41,%42,%43,%44,%45,%46,%47}, %48, %49, p, 1, 1, 0, 1;\n}\n"
    : "+f"(d[0]),"+f"(d[1]),"+f"(d[2]),"+f"(d[3]),"+f"(d[4]),"+f"(d[5]),"+f"(d[6]),"+f"(d[7]),"+f"(d[8]),"+f"(d[9]),"+f"(d[10]),"+f"(d[11]),"+f"(d[12]),"+f"(d[13]),"+f"(d[14]),"+f"(d[15]),"+f"(d[16]),"+f"(d[17]),"+f"(d[18]),"+f"(d[19]),"+f"(d[20]),"+f"(d[21]),"+f"(d[22]),"+f"(d[23]),"+f"(d[24]),"+f"(d[25]),"+f"(d[26]),"+f"(d[27]),"+f"(d[28]),"+f"(d[29]),"+f"(d[30]),"+f"(d[31]),"+f"(d[32]),"+f"(d[33]),"+f"(d[34]),"+f"(d[35]),"+f"(d[36]),"+f"(d[37]),"+f"(d[38]),"+f"(d[39]),"+f"(d[40]),"+f"(d[41]),"+f"(d[42]),"+f"(d[43]),"+f"(d[44]),"+f"(d[45]),"+f"(d[46]),"+f"(d[47]) : "l"(da), "l"(db), "n"(SC));
}
template<int SC> __device__ __forceinline__ void wg_rs112(float (&d)[56], uint32_t a0, uint32_t a1, uint32_t a2, uint32_t a3, uint64_t db) {
  asm volatile("{\n.reg .pred p;\nsetp.ne.b32 p, %61, 0;\nwgmma.mma_async.sync.aligned.m64n112k16.f32.bf16.bf16 {%0,%1,%2,%3,%4,%5,%6,%7,%8,%9,%10,%11,%12,%13,%14,%15,%16,%17,%18,%19,%20,%21,%22,%23,%24,%25,%26,%27,%28,%29,%30,%31,%32,%33,%34,%35,%36,%37,%38,%39,%40,%41,%42,%43,%44,%45,%46,%47,%48,%49,%50,%51,%52,%53,%54,%55}, {%56,%57,%58,%59}, %60, p, 1, 1, 0;\n}\n"
    : "+f"(d[0]),"+f"(d[1]),"+f"(d[2]),"+f"(d[3]),"+f"(d[4]),"+f"(d[5]),"+f"(d[6]),"+f"(d[7]),"+f"(d[8]),"+f"(d[9]),"+f"(d[10]),"+f"(d[11]),"+f"(d[12]),"+f"(d[13]),"+f"(d[14]),"+f"(d[15]),"+f"(d[16]),"+f"(d[17]),"+f"(d[18]),"+f"(d[19]),"+f"(d[20]),"+f"(d[21]),"+f"(d[22]),"+f"(d[23]),"+f"(d[24]),"+f"(d[25]),"+f"(d[26]),"+f"(d[27]),"+f"(d[28]),"+f"(d[29]),"+f"(d[30]),"+f"(d[31]),"+f"(d[32]),"+f"(d[33]),"+f"(d[34]),"+f"(d[35]),"+f"(d[36]),"+f"(d[37]),"+f"(d[38]),"+f"(d[39]),"+f"(d[40]),"+f"(d[41]),"+f"(d[42]),"+f"(d[43]),"+f"(d[44]),"+f"(d[45]),"+f"(d[46]),"+f"(d[47]),"+f"(d[48]),"+f"(d[49]),"+f"(d[50]),"+f"(d[51]),"+f"(d[52]),"+f"(d[53]),"+f"(d[54]),"+f"(d[55]) : "r"(a0), "r"(a1), "r"(a2), "r"(a3), "l"(db), "n"(SC));
}
template<int SC> __device__ __forceinline__ void wg_sp48(float (&d)[24], uint32_t a0, uint32_t a1, uint32_t a2, uint32_t a3, uint64_t db, uint32_t meta) {
  asm volatile("{\n.reg .pred p;\nsetp.ne.b32 p, %30, 0;\nwgmma.mma_async.sp.sync.aligned.m64n48k32.f32.bf16.bf16 {%0,%1,%2,%3,%4,%5,%6,%7,%8,%9,%10,%11,%12,%13,%14,%15,%16,%17,%18,%19,%20,%21,%22,%23}, {%24,%25,%26,%27}, %28, %29, 0, p, 1, 1, 1;\n}\n"
    : "+f"(d[0]),"+f"(d[1]),"+f"(d[2]),"+f"(d[3]),"+f"(d[4]),"+f"(d[5]),"+f"(d[6]),"+f"(d[7]),"+f"(d[8]),"+f"(d[9]),"+f"(d[10]),"+f"(d[11]),"+f"(d[12]),"+f"(d[13]),"+f"(d[14]),"+f"(d[15]),"+f"(d[16]),"+f"(d[17]),"+f"(d[18]),"+f"(d[19]),"+f"(d[20]),"+f"(d[21]),"+f"(d[22]),"+f"(d[23]) : "r"(a0), "r"(a1), "r"(a2), "r"(a3), "l"(db), "r"(meta), "n"(SC));
}
template<int SC> __device__ __forceinline__ void wg_rs64(float (&d)[32], uint32_t a0, uint32_t a1, uint32_t a2, uint32_t a3, uint64_t db) {
  asm volatile("{\n.reg .pred p;\nsetp.ne.b32 p, %37, 0;\nwgmma.mma_async.sync.aligned.m64n64k16.f32.bf16.bf16 {%0,%1,%2,%3,%4,%5,%6,%7,%8,%9,%10,%11,%12,%13,%14,%15,%16,%17,%18,%19,%20,%21,%22,%23,%24,%25,%26,%27,%28,%29,%30,%31}, {%32,%33,%34,%35}, %36, p, 1, 1, 0;\n}\n"
    : "+f"(d[0]),"+f"(d[1]),"+f"(d[2]),"+f"(d[3]),"+f"(d[4]),"+f"(d[5]),"+f"(d[6]),"+f"(d[7]),"+f"(d[8]),"+f"(d[9]),"+f"(d[10]),"+f"(d[11]),"+f"(d[12]),"+f"(d[13]),"+f"(d[14]),"+f"(d[15]),"+f"(d[16]),"+f"(d[17]),"+f"(d[18]),"+f"(d[19]),"+f"(d[20]),"+f"(d[21]),"+f"(d[22]),"+f"(d[23]),"+f"(d[24]),"+f"(d[25]),"+f"(d[26]),"+f"(d[27]),"+f"(d[28]),"+f"(d[29]),"+f"(d[30]),"+f"(d[31]) : "r"(a0), "r"(a1), "r"(a2), "r"(a3), "l"(db), "n"(SC));
}

constexpr uint32_t SBC = 1024;
constexpr int ROWB = 2 * 224 * 384;
constexpr int TB = 11;
constexpr int KS = 832;
constexpr int KSLOT = 22 * KS;
constexpr int SM_X = 0;
constexpr int SM_W = SM_X + 3 * 24576;
constexpr int SM_K = SM_W + 55296;
constexpr int SM_V = SM_K + 2 * KSLOT;
constexpr int SM_Q = SM_V + 22 * 1536;
constexpr int SM_O = SM_Q + 12288;
constexpr int SM_S = SM_O + 12288;
constexpr int SM_RPB = SM_S + 6144;
constexpr int SM_BAR = SM_RPB + 768;
constexpr int SM_A_TOTAL = SM_BAR + 256;
constexpr int SM_TIN0 = SM_X + 24576, SM_TIN1 = SM_X, SM_TIN2 = SM_W + 18432;
constexpr int SM_TWO = SM_X + 2 * 24576;
constexpr int SM_TST = SM_TIN2 + 24576;
enum { B_FULL = 0, B_EMPTY = 3, B_TIN = 6, B_TFREE = 10, B_WK = 12, B_WQ, B_WO, B_KIMP, B_VIMP, B_OFREE, B_XK, B_XV,
       B_Q0, B_WOFREE, B_OTAIL, B_ODONE = B_OTAIL + 4, B_KFREE, B_VFREE, B_COUNT };
enum { N_KRDY = 4, N_QK0, N_QK1, N_VQ0, N_VQ1, N_PVISS, N_Q0 };

#define NL 2
#define OCH 16
#define MID 6
#define SPL 4
#define RA 152
#define RG 184
#define OPT 0
constexpr int FS = 64;
__device__ int g_flags[TB * 56 * FS];

#define TR(role, it, k)
#define TRDECL
#define TRARG
#define TRPASS
#define TRDUMP
#define TRB(it, k)
#define TR2START
#define TR2FLUSH(blk)
#define TR2(blk, k)

struct Stage { uint32_t lo, full, em, par; };
struct GemmCtx {
  uint32_t bar;
  uint32_t kC, vC[2], qC[2];
  uint32_t kH, vH[2];
  uint32_t hiA, hiB;
  uint32_t spin;
  bool hvalid, never, edge, low;
};

template <int STRIDE> __device__ __forceinline__ void dump12(uint32_t a, const uint32_t (&r)[12]) {
#pragma unroll
  for (int j = 0; j < 3; j++) stsm4(a + j * 2 * STRIDE, r[4 * j], r[4 * j + 1], r[4 * j + 2], r[4 * j + 3]);
}
__device__ __forceinline__ void keep12(bool never, uint32_t a, const uint32_t (&r)[12]) { if (never) dump12<128>(a, r); }
template <int N> __device__ __forceinline__ void pack12(uint32_t (&r)[12], const float (&d)[N], int off) {
#pragma unroll
  for (int j = 0; j < 12; j++) r[j] = pack2(d[off + 2 * j], d[off + 2 * j + 1]);
}
__device__ __forceinline__ uint64_t dsc(uint64_t lo, uint32_t hi) { uint64_t r; asm("mov.b64 %0, {%1, %2};" : "=l"(r) : "r"((uint32_t)lo), "r"(hi)); return r; }
template <int K0, int K1> __device__ __forceinline__ void issue_core(const GemmCtx& c, const Stage& x, float (&d)[72]) {
  constexpr uint64_t db = mkdesc(SBC + SM_W, 6144, 256, 3);
  wg_fence();
  if (K0 == 0) wg_ss144<0>(d, dsc(x.lo, c.hiA), dsc(db, c.hiB));
#pragma unroll
  for (int k = K0 ? K0 : 1; k < K1; k++) wg_ss144<1>(d, dsc(x.lo + (k >> 2) * 512 + (k & 3) * 2, c.hiA), dsc(db + k * 32, c.hiB));
  wg_commit();
}
template <int K0, int K1> __device__ __forceinline__ void issue_halo(const GemmCtx& c, const Stage& x, float (&d)[48]) {
  constexpr uint64_t db = mkdesc(SBC + SM_W + 18432, 6144, 256, 3);
  wg_fence();
  if (K0 == 0) wg_ss96<0>(d, dsc(x.lo, c.hiA), dsc(db, c.hiB));
#pragma unroll
  for (int k = K0 ? K0 : 1; k < K1; k++) wg_ss96<1>(d, dsc(x.lo + (k >> 2) * 384 + (k & 3) * 2, c.hiA), dsc(db + k * 32, c.hiB));
  wg_commit();
}
__device__ __forceinline__ void release_stage(const Stage& x) {
  asm volatile("{\n.reg .pred p;\nelect.sync _|p, 0xffffffff;\n@p mbarrier.arrive.shared::cluster.b64 _, [%0];\n}" ::"r"(x.em) : "memory");
}
__device__ __forceinline__ void wait_stage(GemmCtx& c, Stage& x) {
  asm volatile("{\n.reg .pred p;\nWL:\nmbarrier.try_wait.parity.shared::cta.b64 p, [%1], %2;\n@p bra WD;\n"
               "add.u32 %0, %0, 1;\nsetp.lt.u32 p, %0, 0x100000;\n@p bra WL;\nWD:\n}" : "+&r"(c.spin) : "r"(x.full), "r"(x.par) : "memory");
  x.par ^= 1;
}
__device__ __forceinline__ void edge_ready(const GemmCtx& c, int bar) { __syncwarp(); if (c.edge) mbar_arrive_elect(c.bar + bar * 8); }
__device__ __forceinline__ void dump6(uint32_t a, const uint32_t (&r)[6]) {
  stsm4(a, r[0], r[1], r[2], r[3]);
  asm volatile("stmatrix.sync.aligned.m8n8.x2.shared.b16 [%0], {%1,%2};" ::"r"(a + 512), "r"(r[4]), "r"(r[5]) : "memory");
}
__device__ __forceinline__ void halo_split(uint32_t (&r0)[6], uint32_t (&r1)[6], uint32_t (&r2)[6], const float (&d)[48], int off, bool low) {
#pragma unroll
  for (int j = 0; j < 6; j++) {
    const uint32_t u = pack2(d[off + 4 * j], d[off + 4 * j + 1]), l = pack2(d[off + 4 * j + 2], d[off + 4 * j + 3]);
    r0[j] = low ? u : r2[j]; r1[j] = low ? l : u; r2[j] = l;
  }
}
template <int PARITY> __device__ __forceinline__ void gwait(GemmCtx& c, int bar) {
  asm volatile("{\n.reg .pred p;\nWL:\nmbarrier.try_wait.parity.shared::cta.b64 p, [%1], %2;\n@p bra WD;\n"
               "add.u32 %0, %0, 1;\nsetp.lt.u32 p, %0, 0x100000;\n@p bra WL;\nWD:\n}" : "+&r"(c.spin) : "r"(c.bar + bar * 8), "n"(PARITY) : "memory");
}
__device__ __forceinline__ void load_w(const CUtensorMap* m, uint32_t dst, uint32_t bar, int col) {
  asm volatile("cp.async.bulk.tensor.2d.shared::cluster.global.mbarrier::complete_tx::bytes [%0], [%1, {%3,%4}], [%2];"
               ::"r"(dst), "l"(m), "r"(bar), "r"(col), "r"(0) : "memory");
}
__device__ __forceinline__ void remote_arrive(uint32_t rbar) { asm volatile("mbarrier.arrive.shared::cluster.b64 _, [%0];" ::"r"(rbar) : "memory"); }
__device__ __forceinline__ void remote_expect(uint32_t rbar, uint32_t bytes) {
  asm volatile("mbarrier.arrive.expect_tx.shared::cluster.b64 _, [%0], %1;" ::"r"(rbar), "r"(bytes) : "memory");
}
__device__ __forceinline__ void copy_remote(uint32_t rdst, uint32_t src, uint32_t bytes, uint32_t rbar) {
  asm volatile("cp.async.bulk.shared::cluster.shared::cta.mbarrier::complete_tx::bytes [%0], [%1], %2, [%3];" ::"r"(rdst), "r"(src), "r"(bytes), "r"(rbar) : "memory");
}
__device__ __forceinline__ void tail_free(uint32_t bar) {
  uint32_t ln; asm volatile("mov.u32 %0, %%laneid;" : "=r"(ln));
  if (ln < 4) mbar_arrive_remote(bar, ln + (blockIdx.x & 4));
}
__device__ __forceinline__ void publish(uint32_t bar) {
  fence_async();
  __syncwarp();
  mbar_arrive_elect(bar);
}

template <bool FIRST, int PA>
__device__ __forceinline__ void gemm_iter(GemmCtx& c, int b, uint32_t (&pk)[12], uint32_t (&pv)[12], uint32_t (&pq)[12],
                                          uint32_t (&hk1)[6], uint32_t (&hv1)[6], uint32_t (&hk2)[6], uint32_t (&hv2)[6], Stage& x0, Stage& x2, Stage& x1 TRARG) {
  const uint32_t bar = c.bar;
  const bool w = !FIRST && (PA == 0 || b >= 0), never = c.never;
  constexpr uint32_t ko = PA * KSLOT;
  float C[72];
  uint32_t hk0[6], hv0[6], pv2[12];
  TR(2, b, 0);
  if (FIRST) wait_stage(c, x0);
  else dump12<128>(c.qC[1], pq);
  if (w) nb_sync(N_QK1, 256);
  TR(2, b, 2);
  if (FIRST) TR(2, b - 1, 6);
  if (PA == 0) {
    float H[48];
    issue_halo<0, 8>(c, x0, H);
    TR(2, b, 3);
    if (!FIRST) { gwait<0>(c, B_KFREE); dump12<128>(c.kC, pk); }
    issue_halo<8, 12>(c, x0, H);
    TR(2, b, 4);
    wait_stage(c, x2);
    if (FIRST) TR(2, b - 1, 7);
    if (FIRST) gwait<0>(c, B_WQ);
    if (FIRST) TR(2, b - 1, 8);
    issue_core<0, 8>(c, x2, C);
    TR(2, b, 5);
    if (!FIRST) { fence_async(); keep12(never, c.kC, pk); }
    wg_wait<1>(); pin(H);
    release_stage(x0);
    halo_split(hk0, hk1, hk2, H, 0, c.low);
    if (c.hvalid) dump6(c.kH, hk0);
    halo_split(hv0, hv1, hv2, H, 24, c.low);
  } else {
    issue_core<0, 8>(c, x2, C);
    TR(2, b, 5);
    fence_async();
    keep12(never, c.kC, pq);
    if (w) gwait<1>(c, B_KFREE);
    dump12<128>(c.kC + ko, pk);
    if (c.hvalid) dump6(c.kH + ko, hk1);
  }
  TR(2, b, 13);
  issue_core<8, 12>(c, x2, C);
  if (w) { nb_arrive(N_VQ0, 288); nb_arrive(N_VQ1, 288); }
  else if (!FIRST) { __syncwarp(); mbar_arrive_elect(bar + B_Q0 * 8); }
  wait_stage(c, x1);
  if (never) dump6(bar, PA ? hk1 : hk0);
  TR(2, b, 6);
  wg_wait<0>(); pin(C);
  TR(2, b, 7);
  release_stage(x2);
  pack12(pk, C, 24);
  dump12<128>(c.kC + ko + 64, pk);
  pack12(pv2, C, 48);
  pack12(pq, C, 0);
  TR(2, b, 8);
  issue_core<0, SPL>(c, x1, C);
  TR(2, b, 9);
  if (!FIRST) { fence_async(); edge_ready(c, B_XK); }
  keep12(never, c.kC, pk);
  TR(2, b, 14);
  if (w) nb_sync(N_PVISS, 384);
  issue_core<SPL, 12>(c, x1, C);
  if (!FIRST) nb_arrive(N_KRDY, 256);
  TR(2, b, 1);
  if (PA && b == 11) tail_free(bar + B_TFREE * 8);
  else wait_stage(c, x0);
  if (w) gwait<PA>(c, B_VFREE);
  if (w && b < TB) gwait<PA>(c, B_ODONE);
  TR(2, b, 10);
  if (!FIRST) dump12<128>(c.vC[PA], pv);
  dump12<128>(c.vC[PA ^ 1] + 768, pv2);
  TR(2, b, 11);
  wg_wait<0>(); pin(C);
  TR(2, b, 12);
  release_stage(x1);
  if (!FIRST && c.edge) publish(bar + B_XV * 8);
  if (c.hvalid) dump6(c.vH[PA], PA ? hv1 : hv0);
  if (PA && !w) nb_sync(N_Q0, 384);
  dump12<128>(c.qC[0], pq);
  pack12(pk, C, 24);
  pack12(pv, C, 48);
  pack12(pq, C, 0);
}

template <int IN> __device__ __forceinline__ void issue_proj(float (&D)[48]) {
  constexpr uint64_t da = mkdesc(SBC + IN, 128, 768, 0), db = mkdesc(SBC + SM_TWO, 12288, 512, 2);
  wg_fence();
  wg_ss96<0>(D, da, db);
#pragma unroll
  for (int k = 1; k < 12; k++) wg_ss96<1>(D, da + (k / 3) * 384 + (k % 3) * 16, db + k * 64);
  wg_commit();
}
template <int ACC> __device__ __forceinline__ void issue_proj_half(float (&D)[48], int hd) {
  const uint64_t da = mkdesc(SBC + SM_TIN2, 128, 768, 0) + hd * 384, db = mkdesc(SBC + SM_TWO, 12288, 512, 2) + hd * 192;
  wg_fence();
  wg_ss96<ACC>(D, da, db);
#pragma unroll
  for (int k = 1; k < 6; k++) wg_ss96<1>(D, da + (k / 3) * 768 + (k % 3) * 16, db + (k / 3) * 384 + (k % 3) * 64);
  wg_commit();
}
__device__ __forceinline__ void store_proj(const float (&D)[48], const CUtensorMap* m, uint32_t st, uint32_t sta, int row, int col, int ch) {
#pragma unroll
  for (int q = 0; q < 6; q++)
    stsm4((sta ^ ((q & 1) * 32)) + (q >> 1) * 1024,
          pack2(D[8 * q], D[8 * q + 1]), pack2(D[8 * q + 2], D[8 * q + 3]), pack2(D[8 * q + 4], D[8 * q + 5]), pack2(D[8 * q + 6], D[8 * q + 7]));
  fence_async();
  __syncwarp();
  if ((threadIdx.x & 31) == 0) {
    asm volatile("cp.async.bulk.tensor.4d.global.shared::cta.bulk_group [%0, {%2,%3,%4,%5}], [%1];" ::"l"(m), "r"(st), "r"(0), "r"(row), "r"(col), "r"(ch) : "memory");
    asm volatile("cp.async.bulk.commit_group;" ::: "memory");
  }
  __syncwarp();
}

__device__ __forceinline__ float fold(float a, float b, float t, int useb) {
  float r;
  asm("{\n.reg .pred p;\nsetp.ne.b32 p, %4, 0;\nfma.rn.f32 %0, %1, 0f3E553B95, %3;\n@p fma.rn.f32 %0, %2, 0f3E553B95, %3;\n}"
      : "=&f"(r) : "f"(a), "f"(b), "f"(t), "r"(useb));
  return r;
}
template <int U, int L>
__device__ __forceinline__ void softmax_tile(const float (&SA)[56], const float (&SB)[56], const float (&T)[16], int b0, int b1,
                                             uint32_t (&P)[28], float (&sx)[8], uint32_t nbV, uint32_t zero, uint32_t qa, uint32_t (&q)[12]) {
  float lu[14], ll[14];
#pragma unroll
  for (int j = 0; j < 7; j++) {
    constexpr int sh = U == L ? 2 : 0;
    const float tu0 = T[2 * j + sh], tu1 = T[2 * j + 1 + sh], tl0 = T[2 * j], tl1 = T[2 * j + 1];
    lu[2 * j]     = fold(SA[4 * (U + j)],     SB[4 * (U + j)],     tu0, b0);
    ll[2 * j]     = fold(SA[4 * (L + j) + 2], SB[4 * (L + j) + 2], tl0, b0);
    lu[2 * j + 1] = fold(SA[4 * (U + j) + 1], SB[4 * (U + j) + 1], tu1, b1);
    ll[2 * j + 1] = fold(SA[4 * (L + j) + 3], SB[4 * (L + j) + 3], tl1, b1);
  }
  float mu = lu[0], ml = ll[0], mu2 = lu[1], ml2 = ll[1];
#pragma unroll
  for (int j = 1; j < 7; j++) { mu = fmaxf(mu, lu[2 * j]); mu2 = fmaxf(mu2, lu[2 * j + 1]); ml = fmaxf(ml, ll[2 * j]); ml2 = fmaxf(ml2, ll[2 * j + 1]); }
  mu = fmaxf(mu, mu2); ml = fmaxf(ml, ml2);
  { const float a1 = __shfl_xor_sync(0xffffffffu, mu, 1), a2 = __shfl_xor_sync(0xffffffffu, mu, 2), a3 = __shfl_xor_sync(0xffffffffu, mu, 3);
    const float c1 = __shfl_xor_sync(0xffffffffu, ml, 1), c2 = __shfl_xor_sync(0xffffffffu, ml, 2), c3 = __shfl_xor_sync(0xffffffffu, ml, 3);
    mu = fmaxf(fmaxf(mu, a1), fmaxf(a2, a3)); ml = fmaxf(fmaxf(ml, c1), fmaxf(c2, c3)); }
  float su = 0.f, sl = 0.f;
#pragma unroll
  for (int c = 0; c < 14; c++) {
    if (c >= U && c < U + 7) {
      float e0 = ex2(lu[2 * (c - U)] - mu), e1 = ex2(lu[2 * (c - U) + 1] - mu);
      su = c == U ? e0 + e1 : (su + e0) + e1; P[2 * c] = pack2(e0, e1);
    } else P[2 * c] = 0u;
  }
  nb_sync(nbV | (P[2 * (U + MID)] & zero), 288);
#pragma unroll
  for (int k = 0; k < 3; k++) ldsm4(qa + k * 256, q[4 * k], q[4 * k + 1], q[4 * k + 2], q[4 * k + 3]);
#pragma unroll
  for (int c = 0; c < 14; c++) {
    if (c >= L && c < L + 7) {
      float e0 = ex2(ll[2 * (c - L)] - ml), e1 = ex2(ll[2 * (c - L) + 1] - ml);
      sl = c == L ? e0 + e1 : (sl + e0) + e1; P[2 * c + 1] = pack2(e0, e1);
    } else P[2 * c + 1] = 0u;
  }
  sx[0] = su; sx[4] = sl;
#pragma unroll
  for (int k = 1; k < 4; k++) sx[k] = __shfl_xor_sync(0xffffffffu, su, k);
#pragma unroll
  for (int k = 1; k < 4; k++) sx[4 + k] = __shfl_xor_sync(0xffffffffu, sl, k);
}

struct BandCfg { uint32_t ra0, ra1, meta; };
__device__ __forceinline__ void band_cfg(int b, uint32_t tb, BandCfg& n) {
  uint32_t ln; asm volatile("mov.u32 %0, %%laneid;" : "=r"(ln));
  const int g = ln >> 2, t = ln & 3;
  const int sw = min(max(g + 1, b == 0 ? 4 : 0), b == 13 ? 5 : 8);
  const int i0 = 2 * t, i1 = 2 * t + 1;
  const int b0 = i0 <= sw - 2, b1 = i1 <= sw - 2;
  n.ra0 = opq(tb + (i0 == sw - 1 ? 13 : i0 + 8 * b0 - g + 2) * 52 + b0);
  n.ra1 = opq(tb + (i1 == sw - 1 ? 13 : i1 + 8 * b1 - g + 2) * 52 + b1);
  n.meta = ((0x5555u & ((1u << (2 * (sw - 1))) - 1)) ^ 0xDD88u ^ (((t ^ b) & 1) ? 0x5555u : 0u)) * 0x10001u;
}
__device__ __forceinline__ void band_load(const BandCfg& n, float (&T)[16], int& b0, int& b1, uint32_t& meta) {
  b0 = n.ra0 & 1; b1 = n.ra1 & 1; meta = n.meta;
#pragma unroll
  for (int jj = 0; jj < 8; jj++) { T[2 * jj] = lds_f32(n.ra0 - b0 + jj * 4); T[2 * jj + 1] = lds_f32(n.ra1 - b1 + jj * 4); }
}

struct Maps { CUtensorMap xc, xh, w, os, wo, ot; };

__global__ void __cluster_dims__(8, 1, 1) __launch_bounds__(512, 1)
na_attn_kernel(const __nv_bfloat16* __restrict__ x, const __nv_bfloat16* __restrict__ wqkv, const __nv_bfloat16* __restrict__ rpb, const __grid_constant__ Maps mp) {
  extern __shared__ __align__(1024) uint8_t smem_raw[];
  const uint32_t sb = smem_u32(smem_raw);
  if ((sb & 0x3FFFF) != SBC) return;
  const uint32_t bar = sb + SM_BAR;
  TR2START;
  const int tid = threadIdx.x, lane = tid & 31;
  const int warp = __shfl_sync(0xffffffffu, tid >> 5, 0);
  const int head = blockIdx.x & 3, base = blockIdx.x & 4, sp = blockIdx.x >> 2;
  const int par = sp < 24 ? sp / 6 : sp - 24, strip = sp < 24 ? sp - par * 6 : 6, ph = par >> 1, pw = par & 1;
  const int odd = strip & 1;

  uint4 wv[2 * NL];
  const int va = head == 1;
  const uint32_t wdst = sb + SM_W + (3 + va + ((tid >> 1) & 1)) * 6144 + (tid >> 2) * 32 + ((tid ^ (tid >> 4)) & 1) * 16;
  if (warp < 12) {
    asm volatile("barrier.cluster.arrive.relaxed.aligned;" ::: "memory");
    const uint32_t wo0 = (tid >> 2) * 1152 + head * 96 + va * 32 + (tid & 3) * 16;
#pragma unroll
    for (int i = 0; i < 2 * NL; i++)
      asm volatile("ld.global.nc.v4.b32 {%0,%1,%2,%3}, [%4];" : "=r"(wv[i].x), "=r"(wv[i].y), "=r"(wv[i].z), "=r"(wv[i].w)
                   : "l"(reinterpret_cast<const uint8_t*>(wqkv) + wo0 + (i & 1) * 96 * 1152 + (i / 2 + 1) * 384));
  }
  if (warp < 8) {
    asm volatile("setmaxnreg.inc.sync.aligned.u32 %0;" ::"n"(RA));
    float rv = -INFINITY;
    if (tid < 169) rv = __bfloat162float(rpb[head * 169 + tid]) * 1.4426950408889634f;
    if (tid < 192) {
      const int kc = (tid & 15) + 3, wc = (tid >> 4) % 6;
      sts128(tid < 96 ? sb + SM_K + kc * KS + wc * 128 + 48 : sb + SM_V + kc * 1536 + wc * 128 + (6 + (kc & 1)) * 16, make_uint4(0, 0, 0, 0));
    }
#pragma unroll
    for (int i = 0; i < 2 * NL; i++) sts128(wdst + (i & 1) * 3072 + (i / 2) * 18432, wv[i]);
    fence_async();
    asm volatile("bar.arrive 1, 384;" ::: "memory");
    if (tid < 182) asm volatile("st.shared.f32 [%0], %1;" ::"r"(sb + SM_RPB + tid * 4), "f"(rv) : "memory");
    const int jw = warp >> 2, j = jw ^ odd, w = warp & 3, wt = 4 * j + w;
    int variant = w;
    if (strip == 0 && j == 0 && w < 2) variant = 4;
    if (strip == 6 && j == 1 && w >= 2) variant = 5;
    const bool v1 = opq((uint32_t)(variant & 1)), v2 = opq((uint32_t)(variant & 2)), v4 = opq((uint32_t)(variant & 4));
    const uint32_t qa = opq(sb + SM_Q + (8 * j + 2 * w + ((lane >> 3) & 1)) * 768 + (lane >> 4) * 128 + (((lane & 7) * 16) ^ (((lane >> 3) & 1) * 64)));
    uint32_t oa = opq(sb + SM_O + j * 6144 + (2 * w + ((lane >> 3) & 1)) * 768 + (lane >> 4) * 128 + (lane & 7) * 16);
    uint64_t dA = opq(mkdesc(SBC + SM_K, 128, KS, 0) + j * (8 * KS / 16)), dB = opq(dA + (KSLOT >> 4));
    uint64_t dV[7];
#pragma unroll
    for (int i = 0; i < 7; i++) dV[i] = opq(mkdesc(SBC + SM_V, 768, 128, 0) + j * (8 * 1536 / 16) + i * 192);
    const uint32_t nbK = opq((uint32_t)(N_KRDY + jw)), nbQ = opq((uint32_t)(N_QK0 + jw)), nbV = opq((uint32_t)(N_VQ0 + jw));
    asm volatile("barrier.cluster.wait.aligned;" ::: "memory");
    asm volatile("bar.sync 3, 256;" ::: "memory");
    float T[16];
    TRDECL;
    int b0, b1;
    uint32_t meta, ob = bar + B_ODONE * 8, fb = bar + B_OFREE * 8, fp = 1;
    const uint32_t tb = opq(sb + SM_RPB + (variant < 4 ? 3 : variant + 1 - 2 * w) * 4);
    const bool own = ((w ^ head) & 2) == 0;
    const uint32_t dst13 = sb + SM_TIN2 + head * 6144 + (2 * j + (w & 1)) * 1536, src13 = opq(own ? dst13 : sb + SM_S + (2 * j + (w & 1)) * 1536);
    const uint32_t snd[4] = {opq(own ? 0u : mapa(dst13, base + (head ^ 2))), opq(mapa(bar + (B_TIN + 2) * 8, base + (head ^ 2))),
                             opq(mapa(dst13, base + (w & 2) + (~head & 1))), opq(mapa(bar + (B_TIN + 3) * 8, base + (w & 2) + (~head & 1)))};
    BandCfg nx;
    band_cfg(0, tb, nx);
    band_load(nx, T, b0, b1, meta);
    band_cfg(1, tb, nx);
    const uint32_t zero = opq(blockIdx.x >> 16);
    uint32_t special = opq(0x380Au << 1);
    uint32_t q[12];
    mbar_wait(bar + B_Q0 * 8, 0);
#pragma unroll
    for (int k = 0; k < 3; k++) ldsm4(qa + k * 256, q[4 * k], q[4 * k + 1], q[4 * k + 2], q[4 * k + 3]);
    nb_arrive(N_Q0, 384);
#pragma unroll 1
    for (int b = 0; b < 14; b++) {
      float SA[56], SB[56];
      TR(0, b, 0);
      if (jw) mbar_wait(bar + B_KIMP * 8, b & 1);
      nb_sync(nbK, 256);
      TR(0, b, 1);
      TR(0, b - 1, 9);
      wg_fence();
      wg_rs112<0>(SA, q[0], q[1], q[2], q[3], dA);
      wg_rs112<0>(SB, q[0], q[1], q[2], q[3], dB);
      wg_rs112<1>(SA, q[4], q[5], q[6], q[7], dA + 16);
      wg_rs112<1>(SB, q[4], q[5], q[6], q[7], dB + 16);
      wg_rs112<1>(SA, q[8], q[9], q[10], q[11], dA + 32);
      wg_rs112<1>(SB, q[8], q[9], q[10], q[11], dB + 32);
      wg_commit();
      nb_arrive(nbQ, 256);
      { const uint64_t t = dA; dA = dB; dB = t; }
      special >>= 1;
      if (special & 1) {
        if (b == 3) band_cfg(13, tb, nx);
        else {
          if (b == 1 || b == 13) band_load(nx, T, b0, b1, meta);
          if (b >= TB) {
            ob = bar + (b == 13 ? (own ? B_TIN + 2 : B_ODONE) : B_OTAIL + 2 * (b - TB) + jw) * 8;
            if (b > TB) { fb = bar + (B_TFREE + b - 12) * 8; fp = 0; }
            oa += b == 12 ? 0u - (SM_O - SM_Q) : (b == 13 ? src13 - (sb + SM_Q + wt * 1536) : 0);
          }
        }
      }
      TR(0, b, 2);
      wg_wait<0>(); pin(SA); pin(SB);
      mbar_arrive_elect(bar + B_KFREE * 8);
      TR(0, b, 3);
      TR(0, b - 1, 10);
      uint32_t P[28];
      float sx[8];
      if (v2) {
        if (v1) softmax_tile<6, 7>(SA, SB, T, b0, b1, P, sx, nbV, zero, qa, q); else softmax_tile<4, 5>(SA, SB, T, b0, b1, P, sx, nbV, zero, qa, q);
      } else if (!v4) {
        if (v1) softmax_tile<2, 3>(SA, SB, T, b0, b1, P, sx, nbV, zero, qa, q); else softmax_tile<0, 1>(SA, SB, T, b0, b1, P, sx, nbV, zero, qa, q);
      } else {
        if (v1) softmax_tile<4, 4>(SA, SB, T, b0, b1, P, sx, nbV, zero, qa, q); else softmax_tile<3, 3>(SA, SB, T, b0, b1, P, sx, nbV, zero, qa, q);
      }
      float O[24];
      TR(0, b, 4);
      wg_fence();
      wg_sp48<0>(O, P[0], P[1], P[2], P[3], dV[0], meta);
#pragma unroll
      for (int s = 1; s < 7; s++) wg_sp48<1>(O, P[4 * s], P[4 * s + 1], P[4 * s + 2], P[4 * s + 3], dV[s], meta);
      wg_commit();
      nb_arrive(N_PVISS, 384);
      TR(0, b, 6);
      mbar_wait(fb, fp);
      wg_wait<0>(); pin(O);
      mbar_arrive_elect(bar + B_VFREE * 8);
      TR(0, b, 7);
      float ru, rl;
      asm("rcp.approx.ftz.f32 %0, %1;" : "=f"(ru) : "f"(((fmaf(O[0], 0.f, sx[0]) + sx[1]) + sx[2]) + sx[3]));
      asm("rcp.approx.ftz.f32 %0, %1;" : "=f"(rl) : "f"(((fmaf(O[2], 0.f, sx[4]) + sx[5]) + sx[6]) + sx[7]));
#pragma unroll
      for (int i = 0; i < 3; i++)
        stsm4(oa + i * 256, pack2(O[8 * i] * ru, O[8 * i + 1] * ru), pack2(O[8 * i + 2] * rl, O[8 * i + 3] * rl),
              pack2(O[8 * i + 4] * ru, O[8 * i + 5] * ru), pack2(O[8 * i + 6] * rl, O[8 * i + 7] * rl));
      publish(ob);
      fp ^= 1;
      meta ^= 0x55555555u;
      TR(0, b, 8);
    }
    asm volatile("{\n.reg .pred p, q;\nsetp.ne.b32 q, %1, 0;\nelect.sync _|p, 0xffffffff;\nand.pred q, q, p;\n"
                 "@q cp.async.bulk.shared::cluster.shared::cta.mbarrier::complete_tx::bytes [%1], [%0], 1536, [%2];\n"
                 "@p cp.async.bulk.shared::cluster.shared::cta.mbarrier::complete_tx::bytes [%3], [%0], 1536, [%4];\n}"
                 ::"r"(src13), "r"(snd[0]), "r"(snd[1]), "r"(snd[2]), "r"(snd[3]) : "memory");
    nb_arrive(3, 384);
    TRDUMP;
    cluster_sync();
  } else if (warp < 12) {
    TRDECL;
    TR(2, -3, 0);
    asm volatile("setmaxnreg.inc.sync.aligned.u32 %0;" ::"n"(RG));
    TR(2, -3, 1);
    GemmCtx c;
    c.bar = bar;
    const int gw = warp - 8, tk = gw * 16 + (lane & 15), hi = lane >> 4;
    { const int col = tk >> 2, i = tk & 3;
      c.kC = sb + SM_K + (col + 3) * KS + hi * 128 + i * 16;
      c.vC[0] = sb + SM_V + (col + 3) * 1536 + hi * 128 + (2 * i + ((col + 3) & 1)) * 16;
      c.qC[0] = sb + SM_Q + col * 768 + hi * 128 + (col & 1) * 64 + i * 16; }
    { const int kc = gw - 1 + 19 * odd, i = (lane + 4) & 7; c.hvalid = gw > 0; c.low = lane < 16; c.edge = gw == (odd ? 0 : 3);
      c.kH = sb + SM_K + kc * KS + (lane >> 3) * 128 + i * 16;
      c.vH[0] = sb + SM_V + kc * 1536 + (lane >> 3) * 128 + (i >> 2) * 768 + (2 * (i & 3) + ((kc ^ (i >> 2)) & 1)) * 16; }
    Stage xs[3];
#pragma unroll
    for (int i = 0; i < 3; i++) {
      const int p = (i + 1) % 3;
      xs[i].lo = (uint32_t)mkdesc(SBC + SM_X + p * 24576, 16, 0, 0); xs[i].full = bar + (B_FULL + p) * 8;
      xs[i].em = opq(mapa(bar + (B_EMPTY + p) * 8, base + p)); xs[i].par = 0;
    }
    c.never = x == nullptr;
    c.kC = opq(c.kC); c.kH = opq(c.kH);
    c.vC[1] = opq(c.vC[0] ^ 16); c.vC[0] = opq(c.vC[0]);
    c.vH[1] = opq(c.vH[0] ^ 16); c.vH[0] = opq(c.vH[0]);
    c.qC[1] = opq(c.qC[0] ^ 64); c.qC[0] = opq(c.qC[0]);
    c.spin = 0;
    c.hiA = (uint32_t)(mkdesc(0, 0, 1024, 1) >> 32) + (blockIdx.x >> 16); c.hiB = (uint32_t)(mkdesc(0, 0, 256, 3) >> 32) + (blockIdx.x >> 16);
    asm volatile("barrier.cluster.wait.aligned;" ::: "memory");
    TR(2, -3, 2);
#pragma unroll
    for (int i = 0; i < 2 * NL; i++) sts128(wdst + (i & 1) * 3072 + (i / 2) * 18432, wv[i]);
    fence_async();
    TR(2, -3, 3);
    asm volatile("bar.sync 1, 384;" ::: "memory");
    TR(2, -3, 4);
    mbar_wait(bar + B_WK * 8, 0);
    asm volatile("griddepcontrol.launch_dependents;");
    TR(2, -3, 5);
    uint32_t pk[12], pv[12], pq[12], hk1[6], hv1[6], hk2[6] = {}, hv2[6] = {};
    gemm_iter<true, 0>(c, -2, pk, pv, pq, hk1, hv1, hk2, hv2, xs[0], xs[1], xs[2] TRPASS);
    TR2(blockIdx.x, 4);
    c.hiA = opq(c.hiA); c.hiB = opq(c.hiB);
#pragma unroll 1
    for (int b = -1;; b += 2) {
      gemm_iter<false, 1>(c, b, pk, pv, pq, hk1, hv1, hk2, hv2, xs[2], xs[0], xs[1] TRPASS);
      if (b == 11) break;
      gemm_iter<false, 0>(c, b + 1, pk, pv, pq, hk1, hv1, hk2, hv2, xs[2], xs[0], xs[1] TRPASS);
      const Stage t = xs[2]; xs[2] = xs[1]; xs[1] = xs[0]; xs[0] = t;
    }
    TR2(blockIdx.x, 6);
    const uint32_t st = sb + gw * 3072;
    const uint32_t sta = st + (lane & 15) * 64 + ((hi ^ ((lane >> 1) & 3)) * 16);
    const int oc = ph * 112 + strip * 16 + 8 * (gw >> 1) + 4 * (head >> 1) + 2 * (gw & 1), och = pw * 6 + (head & 1) * 3;
    float D0[48], D1[48];
    if (lane < 4) mbar_arrive_remote(bar + B_WOFREE * 8, 2 * lane + (head & 1));
    tail_free(bar + (B_TFREE + 1) * 8);
    dump12<128>(c.qC[1], pq);
    fence_async();
    nb_arrive(N_QK1, 256); nb_arrive(N_VQ0, 288); nb_arrive(N_VQ1, 288); nb_arrive(N_PVISS, 384);
    gwait<0>(c, B_KFREE);
    dump12<128>(c.kC, pk);
    if (c.hvalid) dump6(c.kH, hk2);
    fence_async();
    edge_ready(c, B_XK);
    nb_arrive(N_KRDY, 256);
    gwait<0>(c, B_VFREE);
    dump12<128>(c.vC[0], pv);
    if (c.hvalid) dump6(c.vH[0], hv2);
    fence_async();
    edge_ready(c, B_XV);
    nb_arrive(N_VQ0, 288); nb_arrive(N_VQ1, 288);
    gwait<0>(c, B_WO);
    gwait<0>(c, B_TIN);
    TR(2, 13, 0);
    nb_sync(N_QK1, 256);
    issue_proj<SM_TIN0>(D0);
    wg_wait<0>(); pin(D0);
    TR(2, 13, 1);
    store_proj(D0, &mp.ot, st + SM_TST, sta + SM_TST, 8 * TB, oc, och);
    gwait<0>(c, B_TIN + 1);
    TR(2, 13, 2);
    nb_arrive(N_PVISS, 384);
    nb_sync(3, 384);
    issue_proj<SM_TIN1>(D1);
    wg_wait<0>(); pin(D1);
    TR(2, 13, 3);
    store_proj(D1, &mp.ot, st + SM_TIN0, sta + SM_TIN0, 8 * TB + 8, oc, och);
    TR(2, 13, 4);
    gwait<0>(c, B_TIN + 2);
    TR(2, 13, 5);
    issue_proj_half<0>(D0, head & 1);
    gwait<0>(c, B_TIN + 3);
    TR(2, 13, 6);
    issue_proj_half<1>(D0, ~head & 1);
    asm volatile("barrier.cluster.arrive.relaxed.aligned;" ::: "memory");
    wg_wait<0>(); pin(D0);
    store_proj(D0, &mp.ot, st + SM_TIN0 + 12288, sta + SM_TIN0 + 12288, 8 * TB + 16, oc, och);
    TR(2, 13, 7);
    if (lane == 0) asm volatile("cp.async.bulk.wait_group.read 0;" ::: "memory");
    __syncwarp();
    TR(2, 13, 8);
    TR2(blockIdx.x, 2);
    TR2FLUSH(blockIdx.x);
    TRDUMP;
    asm volatile("barrier.cluster.wait.aligned;" ::: "memory");
  } else {
    asm volatile("setmaxnreg.dec.sync.aligned.u32 24;");
    if (warp == 15) {
      const int l = min(lane, 27), row = head + (l < 16 ? 0 : 4 * ((l - 16) / 3)), col = strip * 16 + (l < 16 ? l : (l - 16) % 3 + (odd ? 16 : (strip ? -3 : 0)));
      const uint8_t* p = reinterpret_cast<const uint8_t*>(x) + (uint32_t)(row * ROWB + (ph * 112 + col) * 768 + pw * 384);
#pragma unroll
      for (int i = 0; i < 3; i++) asm volatile("prefetch.global.L2 [%0];" ::"l"(p + i * 128));
    } else if (elect_one()) {
      if (warp == 12) {
        mbar_init(bar + B_WK * 8, 1);
#pragma unroll
        for (int i = 0; i < NL; i++) load_w(&mp.w, sb + SM_W + (3 * i + 5 - 2 * va) * 6144, bar + B_WK * 8, (i + 1) * 192 + head * 48 + 32 - 32 * va);
        asm volatile("prefetch.tensormap [%0];" ::"l"(head == 1 ? &mp.xh : &mp.xc) : "memory");
      } else if (warp == 13) {
#pragma unroll
        for (int i = 0; i < B_XK; i++) if (i != B_WK) mbar_init(bar + i * 8, (i >= B_EMPTY && i < B_TIN) || (i >= B_TFREE && i < B_WK) ? 16 : (i == B_TIN + 2 ? 5 : 1));
      } else {
#pragma unroll
        for (int i = B_XK; i < B_COUNT; i++) mbar_init(bar + i * 8, i < B_Q0 ? 2 : (i < B_ODONE ? (i == B_WOFREE ? 16 : 4) : (i == B_VFREE ? 9 : 8)));
        mbar_arrive(bar + B_XK * 8); mbar_arrive(bar + B_XV * 8);
      }
      asm volatile("fence.mbarrier_init.release.cluster;" ::: "memory");
    }
    __syncwarp();
    asm volatile("barrier.cluster.arrive.relaxed.aligned;" ::: "memory");
    if (warp != 12) asm volatile("barrier.cluster.wait.aligned;" ::: "memory");
    else {
      const int cc = ph * 112 + strip * 16, ch = cc + (odd ? 16 : (strip ? -3 : 0)), rh = strip ? 0 : 112;
      const uint32_t fb = opq(bar + (B_FULL + head) * 8), dst0 = sb + SM_X + head * 24576, c3 = opq((uint32_t)(pw * 3)), mask = opq(15u << base);
      int t = head == 0 ? 2 : head - 1;
      uint64_t mx = opq((uint64_t)(t ? &mp.xc : &mp.xh));
      uint32_t row = opq((uint32_t)(t ? 4 * t - 4 : rh)), col = opq((uint32_t)(t ? cc : ch)), dst = opq(dst0 + (t ? 0 : 2048));
#pragma unroll 1
      for (int n = 0;; n++) {
        if (n) mbar_wait(fb + (B_EMPTY - B_FULL) * 8, ~n & 1);
        else asm volatile("barrier.cluster.wait.aligned;" ::: "memory");
        if (head < 3) {
          asm volatile("{\n.reg .pred p;\n.reg .b16 m;\nelect.sync _|p, 0xffffffff;\ncvt.u16.u32 m, %7;\n"
                       "@p cp.async.bulk.tensor.4d.shared::cluster.global.mbarrier::complete_tx::bytes.multicast::cluster [%0], [%1, {%3,%4,%5,%6}], [%2], m;\n}"
                       ::"r"(dst), "l"(mx), "r"(fb), "r"(0), "r"(row), "r"(col), "r"(c3), "r"(mask) : "memory");
          if (lane < 4) remote_expect(mapa(fb, base + lane), dst == dst0 ? 24576 : 18432);
          __syncwarp();
        }
        if (n == 0 && elect_one()) {
#pragma unroll
          for (int i = 0; i < 3; i++) load_w(&mp.w, sb + SM_W + i * 6144, bar + B_WQ * 8, head * 48 + i * 16);
          mbar_expect(bar + B_WQ * 8, 18432);
        }
        __syncwarp();
        t += 3;
        if (head == 3 || t > 34) break;
        const int hn = t / 5;
        const bool core = t != 5 * hn;
        mx = opq((uint64_t)(core ? &mp.xc : &mp.xh));
        row = opq((uint32_t)(core ? 4 * (t - hn - 1) : rh + 16 * hn)); col = opq((uint32_t)(core ? cc : ch)); dst = opq(dst0 + (core ? 0 : 2048));
        if (elect_one()) asm volatile("cp.async.bulk.prefetch.tensor.4d.L2.global [%0, {%1,%2,%3,%4}];" ::"l"(mx), "r"(0), "r"(row), "r"(col), "r"(c3) : "memory");
        __syncwarp();
      }
      mbar_wait(bar + B_WOFREE * 8, 0);
      if (elect_one()) {
        const int qr = (blockIdx.x & 7) >> 1;
#pragma unroll
        for (int i = 0; i < 3; i++)
          asm volatile("cp.async.bulk.tensor.2d.shared::cluster.global.mbarrier::complete_tx::bytes.multicast::cluster [%0], [%1, {%3,%4}], [%2], %5;"
                       ::"r"(sb + SM_TWO + i * 12288 + qr * 3072), "l"(&mp.wo), "r"(bar + B_WO * 8), "r"((head & 1) * 96 + i * 32), "r"(qr * 48),
                         "h"((uint16_t)(0x55 << (head & 1))) : "memory");
      }
      __syncwarp();
    }
    if (warp & 1) {
      const uint32_t partner = (blockIdx.x & 7) ^ 4;
      const int cs = odd ? 3 : (strip == 6 ? 15 : 16), cd = odd || strip == 6 ? 19 : 0;
      const uint32_t rb = opq(mapa(bar, partner));
      TRDECL;
      if (warp == 13) {
        const uint32_t dst = opq(mapa(sb + SM_V + cd * 1536, partner)), src = opq(sb + SM_V + cs * 1536);
#pragma unroll 1
        for (int b = 0;; b++) {
          const uint32_t pa = b & 1;
          nb_arrive(N_VQ0, 288);
          mbar_wait(bar + B_XV * 8, pa);
          TR(1, b, 0);
          if (elect_one()) { copy_remote(dst, src, 4608, rb + B_VIMP * 8); remote_expect(rb + B_VIMP * 8, 4608); }
          __syncwarp();
          TR(1, b, 1);
          mbar_wait(bar + B_VIMP * 8, pa);
          TR(1, b, 2);
          nb_arrive(N_VQ1, 288);
          if (elect_one()) remote_arrive(rb + B_VFREE * 8);
          __syncwarp();
          TR(1, b, 3);
          if (b == 13) break;
          mbar_wait(bar + B_VFREE * 8, pa);
          if (elect_one()) remote_arrive(rb + B_XV * 8);
          __syncwarp();
        }
      } else {
        const uint32_t dst = opq(mapa(sb + SM_K + cd * KS, partner)), src = opq(sb + SM_K + cs * KS);
#pragma unroll 1
        for (int b = 0;; b++) {
          const uint32_t pa = b & 1, so = (pa ^ 1) * KSLOT;
          mbar_wait(bar + B_XK * 8, pa);
          TR(1, b - 1, 4);
          if (elect_one()) {
            copy_remote(dst + so, src + so, 3 * KS, rb + B_KIMP * 8);
            if (b == 0) copy_remote(dst, src, 3 * KS, rb + B_KIMP * 8);
            remote_expect(rb + B_KIMP * 8, b ? 3 * KS : 6 * KS);
          }
          __syncwarp();
          TR(1, b - 1, 5);
          TR(1, b - 1, 7);
          if (b == 13) break;
          mbar_wait(bar + B_KFREE * 8, pa);
          if (elect_one()) remote_arrive(rb + B_XK * 8);
          __syncwarp();
        }
      }
      TRDUMP;
    }
    if (warp == 14) {
      int* flag = g_flags + (par * 7 + strip) * 2 * FS;
      if (elect_one()) {
        mbar_expect(bar + B_WK * 8, NL * 6144);
        mbar_expect(bar + B_WO * 8, 36864);
        mbar_expect(bar + B_TIN * 8, 24576); mbar_expect(bar + (B_TIN + 1) * 8, 24576); mbar_expect(bar + (B_TIN + 2) * 8, 6144); mbar_expect(bar + (B_TIN + 3) * 8, 12288);
      }
      __syncwarp();
#pragma unroll 1
      for (int b = 0; b < TB; b++) {
        mbar_wait(bar + B_ODONE * 8, b & 1);
        if (lane == 0) {
#pragma unroll 1
          for (int i = 0; i < 16; i += OCH) {
            asm volatile("cp.async.bulk.tensor.3d.global.shared::cta.bulk_group [%0, {%2,%3,%4}], [%1];"
                         ::"l"(&mp.os), "r"(sb + SM_O + i * 768), "r"(pw * 192), "r"(8 * b + 2 * head), "r"(ph * 112 + strip * 16 + i) : "memory");
            asm volatile("cp.async.bulk.commit_group;\ncp.async.bulk.wait_group 0;" ::: "memory");
          }
        }
        __syncwarp();
        mbar_arrive_elect(bar + B_OFREE * 8);
        if (lane == 0)
          asm volatile("fence.proxy.async.global;\nfence.acq_rel.gpu;\nred.relaxed.gpu.global.add.s32 [%0], 1;\nred.relaxed.gpu.global.add.s32 [%1], 1;"
                       ::"l"(flag + b * 56 * FS), "l"(flag + (b * 56 + 1) * FS) : "memory");
        __syncwarp();
      }
#pragma unroll 1
      for (int t = 0; t < 4; t++) {
        const int i = t >> 1, j = (t ^ odd) & 1, d = (lane + head + 1) & 3;
        const uint32_t dst = opq(mapa(sb + (i ? SM_TIN1 : SM_TIN0) + head * 6144 + j * 3072, base + d)), rb = opq(mapa(bar + (B_TIN + i) * 8, base + d));
        const uint32_t src = opq(sb + (i ? SM_Q : SM_O) + j * 6144 + (d & 2) * 1536);
        if (!(t & 1)) mbar_wait(bar + (B_TFREE + i) * 8, 0);
        mbar_wait(bar + (B_OTAIL + t) * 8, 0);
        if (lane < 4) copy_remote(dst, src, 3072, rb);
        __syncwarp();
      }
    }
    cluster_sync();
  }
}

constexpr int NSTB = 6;
constexpr int NTB = TB * 56;
constexpr int SM_B_ST = 0;
constexpr int SM_B_IN = 73728;
constexpr int SM_B_W = SM_B_IN + 3 * 24576;
constexpr int SM_B_BAR = SM_B_IN + NSTB * 24576;
constexpr int SM_B_TOTAL = SM_B_BAR + 512;
struct MapsB { CUtensorMap oi, oo, wo; };

__global__ void __launch_bounds__(512, 1)
na_proj_kernel(const __grid_constant__ MapsB mp) {
  extern __shared__ __align__(1024) uint8_t smem_raw[];
  const uint32_t sb = smem_u32(smem_raw);
  if ((sb & 0x3FFFF) != SBC) return;
  const uint32_t bar = sb + SM_B_BAR;
  const int tid = threadIdx.x, lane = tid & 31;
  const int warp = __shfl_sync(0xffffffffu, tid >> 5, 0);
  TR2START;
  TRB(47, 0);
  if (warp == 12 && elect_one()) {
#pragma unroll
    for (int i = 0; i <= 2 * NSTB; i++) mbar_init(bar + i * 8, i < NSTB || i == 2 * NSTB ? 1 : 12);
    asm volatile("st.shared.u32 [%0], 0;" ::"r"(bar + 120) : "memory");
    mbar_expect(bar + 2 * NSTB * 8, 73728);
#pragma unroll
    for (int i = 0; i < 2; i++)
      asm volatile("cp.async.bulk.tensor.3d.shared::cluster.global.mbarrier::complete_tx::bytes [%0], [%1, {%3,%4,%5}], [%2];"
                   ::"r"(sb + SM_B_W + i * 36864), "l"(&mp.wo), "r"(bar + 2 * NSTB * 8), "r"(0), "r"(0), "r"(i * 3) : "memory");
  }
  __syncthreads();
  const int step = gridDim.x;
  if (warp == 15) {
    int so = 0;
    nb_arrive(4, 288); nb_arrive(5, 288); nb_arrive(6, 288);
#pragma unroll 1
    for (int n = blockIdx.x, tk = 0; n < NTB; n += step, tk++) {
      uint32_t cc = 0;
#pragma unroll
      for (int wg = 0; wg < 3; wg++) {
        if (lane == 0) asm volatile("cp.async.bulk.wait_group.read 5;" ::: "memory");
        nb_sync(1 + wg, 160);
        if (wg == 0 || n + step < NTB) nb_arrive(4 + wg, 288);
        if (wg == 0) asm volatile("ld.shared.u32 %0, [%1];" : "=r"(cc) : "r"(bar + 128 + tk * 4) : "memory");
        if (lane == 0) {
          asm volatile("cp.async.bulk.tensor.4d.global.shared::cta.bulk_group [%0, {%2,%3,%4,%5}], [%1];"
                       ::"l"(&mp.oo), "r"(sb + SM_B_ST + wg * 8192 + so), "r"(0), "r"((cc >> 8) & 255), "r"(cc >> 16), "r"((cc & 1) * 3 + wg) : "memory");
          asm volatile("cp.async.bulk.commit_group;" ::: "memory");
        }
        __syncwarp();
      }
      so = so == 49152 ? 0 : so + 24576;
    }
    if (lane == 0) asm volatile("cp.async.bulk.wait_group.read 0;" ::: "memory");
  } else if (warp >= 12) {
    nb_sync(7, 480);
#pragma unroll 1
    for (int n = blockIdx.x + (warp - 12) * step; n < NTB; n += 3 * step) {
      const int b = n / 56, rem = n - b * 56, par = rem / 14;
      const int c0 = opq((uint32_t)(par & 1)), c1 = opq((uint32_t)(8 * b)), c2 = opq((uint32_t)((par >> 1) * 112 + (rem - par * 14) * 8));
      int v; uint32_t spin = 0, tk = 0;
      do { asm volatile("ld.acquire.gpu.global.s32 %0, [%1];" : "=r"(v) : "l"(g_flags + n * FS) : "memory"); } while (v < 4 && ++spin < SPIN_LIMIT);
      if (lane == 0) asm volatile("atom.shared.add.u32 %0, [%1], 1;" : "=r"(tk) : "r"(bar + 120) : "memory");
      asm volatile("fence.proxy.async.global;" ::: "memory");
      tk = __shfl_sync(0xffffffffu, tk, 0);
      TRB(tk, 0);
      const uint32_t use = tk / NSTB, sg = tk - use * NSTB;
      if (use) mbar_wait(bar + (NSTB + sg) * 8, (use - 1) & 1);
      TRB(tk, 1);
      if (elect_one()) {
        asm volatile("st.shared.u32 [%0], %1;" ::"r"(bar + 128 + tk * 4), "r"(c0 | c1 << 8 | c2 << 16) : "memory");
        mbar_expect(bar + sg * 8, 24576);
        asm volatile("cp.async.bulk.tensor.3d.shared::cluster.global.mbarrier::complete_tx::bytes [%0], [%1, {%3,%4,%5}], [%2];"
                     ::"r"(sb + SM_B_IN + sg * 24576), "l"(&mp.oi), "r"(bar + sg * 8), "r"(c0 * 192), "r"(c1), "r"(c2) : "memory");
        g_flags[n * FS] = 0;
      }
      __syncwarp();
    }
  } else {
    const int wg = warp >> 2, w = warp & 3;
    uint32_t a[48];
    mbar_wait(bar + 2 * NSTB * 8, 0);
    {
      const int k = (lane & 7) + (lane >> 4) * 8, ch = (warp & 1) * 2 + ((lane >> 3) & 1);
      const uint32_t wa = sb + SM_B_W + (warp >> 1) * 12288 + k * 64 + ((ch ^ ((k >> 1) & 3)) * 16);
#pragma unroll
      for (int i = 0; i < 12; i++)
        asm volatile("ldmatrix.sync.aligned.m8n8.x4.trans.shared.b16 {%0,%1,%2,%3}, [%4];"
                     : "=r"(a[4 * i]), "=r"(a[4 * i + 1]), "=r"(a[4 * i + 2]), "=r"(a[4 * i + 3]) : "r"(wa + i * 1024) : "memory");
    }
    nb_sync(7, 480);
    TRB(47, 1);
    const uint32_t sta = opq(sb + SM_B_ST + wg * 8192 + ((lane & 7) + (lane >> 4) * 8) * 128 + (((2 * w + ((lane >> 3) & 1)) ^ (lane & 7)) * 16));
    const uint32_t hi = opq((uint32_t)(mkdesc(0, 0, 3072, 0) >> 32) + (blockIdx.x >> 16)), bb = opq(bar);
    const uint32_t nbT = opq((uint32_t)(4 + wg)), nbN = opq((uint32_t)(wg == 2 ? 4 : 5 + wg)), nbD = opq((uint32_t)(1 + wg));
    int left = (NTB - blockIdx.x + step - 1) / step;
    if (wg == 2) nb_arrive(4, 288);
#pragma unroll 1
    for (uint32_t ph = 0;; ph ^= 1) {
#pragma unroll
      for (int sg = 0; sg < NSTB; sg++) {
        constexpr uint64_t db = mkdesc(SBC + SM_B_IN, 128, 3072, 0);
        float D[32];
        mbar_wait(bb + sg * 8, ph);
        nb_sync(nbT, 288);
        wg_fence();
        wg_rs64<0>(D, a[0], a[1], a[2], a[3], dsc(db + sg * 1536, hi));
#pragma unroll
        for (int k = 1; k < 12; k++) wg_rs64<1>(D, a[4 * k], a[4 * k + 1], a[4 * k + 2], a[4 * k + 3], dsc(db + sg * 1536 + k * 16, hi));
        wg_commit();
        nb_arrive(nbN, 288);
        wg_wait<0>(); pin(D);
        mbar_arrive_elect(bb + (NSTB + sg) * 8);
#pragma unroll
        for (int q = 0; q < 4; q++)
          asm volatile("stmatrix.sync.aligned.m8n8.x4.trans.shared.b16 [%0], {%1,%2,%3,%4};" ::"r"(sta + (sg % 3) * 24576 + q * 2048),
                       "r"(pack2(D[8 * q], D[8 * q + 1])), "r"(pack2(D[8 * q + 2], D[8 * q + 3])), "r"(pack2(D[8 * q + 4], D[8 * q + 5])), "r"(pack2(D[8 * q + 6], D[8 * q + 7])) : "memory");
        fence_async();
        nb_arrive(nbD, 160);
        if (wg == 0) TRB(31 - left, 5);
        if (--left == 0) goto done;
      }
    }
  done:
    if (wg == 0) nb_arrive(4, 288);
    TR2(132 + blockIdx.x, 2);
    TR2FLUSH(132 + blockIdx.x);
  }
}

typedef CUresult (*EncodeFn)(CUtensorMap*, CUtensorMapDataType, cuuint32_t, void*, const cuuint64_t*, const cuuint64_t*, const cuuint32_t*,
                             const cuuint32_t*, CUtensorMapInterleave, CUtensorMapSwizzle, CUtensorMapL2promotion, CUtensorMapFloatOOBfill);
static EncodeFn g_enc = nullptr;
static void make_map(CUtensorMap* m, const void* p, int rank, const cuuint64_t* dim, const cuuint64_t* str, const cuuint32_t* box, CUtensorMapSwizzle sw) {
  const cuuint32_t ones[5] = {1, 1, 1, 1, 1};
  g_enc(m, CU_TENSOR_MAP_DATA_TYPE_BFLOAT16, rank, (void*)p, dim, str, box, ones, CU_TENSOR_MAP_INTERLEAVE_NONE, sw,
        CU_TENSOR_MAP_L2_PROMOTION_L2_128B, CU_TENSOR_MAP_FLOAT_OOB_FILL_NONE);
}

extern "C" void kernel_launch(void* const* d_in, const int* in_sizes, int n_in, void* d_out, int out_size) {
  const __nv_bfloat16* x = (const __nv_bfloat16*)d_in[0];
  const __nv_bfloat16* wqkv = (const __nv_bfloat16*)d_in[1];
  const __nv_bfloat16* wo = (const __nv_bfloat16*)d_in[2];
  const __nv_bfloat16* rpb = (const __nv_bfloat16*)d_in[3];

  if (!g_enc) {
    void* fn = nullptr; cudaDriverEntryPointQueryResult qr;
    cudaGetDriverEntryPoint("cuTensorMapEncodeTiled", &fn, cudaEnableDefault, &qr);
    g_enc = (EncodeFn)fn;
    cudaFuncSetAttribute(na_attn_kernel, cudaFuncAttributeMaxDynamicSharedMemorySize, SM_A_TOTAL);
    cudaFuncSetAttribute(na_proj_kernel, cudaFuncAttributeMaxDynamicSharedMemorySize, SM_B_TOTAL);
  }
  Maps ma; MapsB mb;
  { cuuint64_t dim[4] = {64, 112, 224, 6}, str[3] = {(cuuint64_t)ROWB, 768, 128};
    cuuint32_t box[4] = {64, 4, 16, 3}, boxh[4] = {64, 16, 3, 3}, boxo[4] = {64, 8, 8, 1};
    make_map(&ma.xc, x, 4, dim, str, box, CU_TENSOR_MAP_SWIZZLE_128B);
    make_map(&ma.xh, x, 4, dim, str, boxh, CU_TENSOR_MAP_SWIZZLE_128B);
    make_map(&mb.oo, d_out, 4, dim, str, boxo, CU_TENSOR_MAP_SWIZZLE_128B); }
  { cuuint64_t dim[3] = {384, 112, 224}, str[2] = {(cuuint64_t)ROWB, 768};
    cuuint32_t box[3] = {192, 8, 8}, boxs[3] = {192, 2, OCH};
    make_map(&mb.oi, d_out, 3, dim, str, box, CU_TENSOR_MAP_SWIZZLE_NONE);
    make_map(&ma.os, d_out, 3, dim, str, boxs, CU_TENSOR_MAP_SWIZZLE_NONE); }
  { cuuint64_t dim[4] = {32, 112, 224, 12}, str[3] = {(cuuint64_t)ROWB, 768, 64};
    cuuint32_t box[4] = {32, 8, 2, 3};
    make_map(&ma.ot, d_out, 4, dim, str, box, CU_TENSOR_MAP_SWIZZLE_64B); }
  { cuuint64_t dim[2] = {576, 192}, str[1] = {1152};
    cuuint32_t box[2] = {16, 192};
    make_map(&ma.w, wqkv, 2, dim, str, box, CU_TENSOR_MAP_SWIZZLE_32B); }
  { cuuint64_t dim[3] = {32, 192, 6}, str[2] = {384, 64};
    cuuint32_t box[3] = {32, 192, 3};
    make_map(&mb.wo, wo, 3, dim, str, box, CU_TENSOR_MAP_SWIZZLE_64B); }
  { cuuint64_t dim[2] = {192, 192}, str[1] = {384};
    cuuint32_t box[2] = {32, 48};
    make_map(&ma.wo, wo, 2, dim, str, box, CU_TENSOR_MAP_SWIZZLE_64B); }
  na_attn_kernel<<<112, 512, SM_A_TOTAL>>>(x, wqkv, rpb, ma);
  cudaLaunchConfig_t cfg = {};
  cfg.gridDim = dim3(20); cfg.blockDim = dim3(512); cfg.dynamicSmemBytes = SM_B_TOTAL; cfg.stream = cudaStreamPerThread;
  cudaLaunchAttribute at[1];
  at[0].id = cudaLaunchAttributeProgrammaticStreamSerialization; at[0].val.programmaticStreamSerializationAllowed = 1;
  cfg.attrs = at; cfg.numAttrs = 1;
  cudaLaunchKernelEx(&cfg, na_proj_kernel, mb);
}
```

```cpp
#include <cuda_runtime.h>
#include <cuda_bf16.h>
#include <cuda.h>
#include <stdint.h>

#define SPIN_LIMIT (1u << 18)

__device__ __forceinline__ uint32_t smem_u32(const void* p) { return (uint32_t)__cvta_generic_to_shared(p); }
__device__ __forceinline__ void wg_fence() { asm volatile("wgmma.fence.sync.aligned;" ::: "memory"); }
__device__ __forceinline__ void wg_commit() { asm volatile("wgmma.commit_group.sync.aligned;" ::: "memory"); }
template <int N> __device__ __forceinline__ void wg_wait() { asm volatile("wgmma.wait_group.sync.aligned %0;" ::"n"(N) : "memory"); }
template <int N> __device__ __forceinline__ void pin(float (&d)[N]) {
#pragma unroll
  for (int i = 0; i < N; i++) asm volatile("" : "+f"(d[i])::"memory");
}
__host__ __device__ constexpr uint64_t mkdesc(uint32_t addr, uint32_t lbo, uint32_t sbo, uint32_t sw) {
  return (uint64_t)((addr & 0x3FFFF) >> 4) | ((uint64_t)(lbo >> 4) << 16) | ((uint64_t)(sbo >> 4) << 32) | ((uint64_t)sw << 62);
}
__device__ __forceinline__ void mbar_init(uint32_t bar, uint32_t cnt) { asm volatile("mbarrier.init.shared::cta.b64 [%0], %1;" ::"r"(bar), "r"(cnt) : "memory"); }
__device__ __forceinline__ void mbar_arrive(uint32_t bar) { asm volatile("mbarrier.arrive.shared::cta.b64 _, [%0];" ::"r"(bar) : "memory"); }
__device__ __forceinline__ bool elect_one() {
  uint32_t r; asm volatile("{\n.reg .pred p;\nelect.sync _|p, 0xffffffff;\nselp.u32 %0, 1, 0, p;\n}" : "=r"(r)); return r;
}
__device__ __forceinline__ void mbar_arrive_elect(uint32_t bar) {
  asm volatile("{\n.reg .pred p;\nelect.sync _|p, 0xffffffff;\n@p mbarrier.arrive.shared::cta.b64 _, [%0];\n}" ::"r"(bar) : "memory");
}
__device__ __forceinline__ void mbar_expect(uint32_t bar, uint32_t bytes) { asm volatile("mbarrier.arrive.expect_tx.shared::cta.b64 _, [%0], %1;" ::"r"(bar), "r"(bytes) : "memory"); }
__device__ __forceinline__ void mbar_arrive_remote(uint32_t bar, uint32_t cta) {
  asm volatile("{\n.reg .b32 ra;\nmapa.shared::cluster.u32 ra, %0, %1;\nmbarrier.arrive.relaxed.cluster.shared::cluster.b64 _, [ra];\n}" ::"r"(bar), "r"(cta) : "memory");
}
__device__ __forceinline__ void mbar_wait(uint32_t bar, uint32_t parity) {
  asm volatile("{\n.reg .pred p;\n.reg .b32 n;\nmov.b32 n, 0;\nWL:\nmbarrier.try_wait.parity.shared::cta.b64 p, [%0], %1;\n@p bra WD;\n"
               "add.u32 n, n, 1;\nsetp.lt.u32 p, n, 65536;\n@p bra WL;\nWD:\n}" ::"r"(bar), "r"(parity) : "memory");
}
__device__ __forceinline__ void nb_sync(int id, int n) { asm volatile("bar.sync %0, %1;" ::"r"(id), "r"(n) : "memory"); }
__device__ __forceinline__ void nb_arrive(int id, int n) { asm volatile("bar.arrive %0, %1;" ::"r"(id), "r"(n) : "memory"); }
__device__ __forceinline__ uint32_t opq(uint32_t x) { uint32_t r; asm volatile("mov.b32 %0, %1;" : "=r"(r) : "r"(x)); return r; }
__device__ __forceinline__ uint64_t opq(uint64_t x) { uint64_t r; asm volatile("mov.b64 %0, %1;" : "=l"(r) : "l"(x)); return r; }
__device__ __forceinline__ uint32_t mapa(uint32_t a, uint32_t cta) { uint32_t r; asm("mapa.shared::cluster.u32 %0, %1, %2;" : "=r"(r) : "r"(a), "r"(cta)); return r; }
__device__ __forceinline__ void fence_async() { asm volatile("fence.proxy.async.shared::cta;" ::: "memory"); }
__device__ __forceinline__ void cluster_sync() {
  asm volatile("barrier.cluster.arrive.relaxed.aligned;\nbarrier.cluster.wait.aligned;" ::: "memory");
}
__device__ __forceinline__ uint32_t pack2(float lo, float hi) {
  uint32_t r; asm("cvt.rn.bf16x2.f32 %0, %1, %2;" : "=r"(r) : "f"(hi), "f"(lo)); return r;
}
__device__ __forceinline__ void stsm4(uint32_t a, uint32_t r0, uint32_t r1, uint32_t r2, uint32_t r3) {
  asm volatile("stmatrix.sync.aligned.m8n8.x4.shared.b16 [%0], {%1,%2,%3,%4};" ::"r"(a), "r"(r0), "r"(r1), "r"(r2), "r"(r3) : "memory");
}
__device__ __forceinline__ void ldsm4(uint32_t a, uint32_t& r0, uint32_t& r1, uint32_t& r2, uint32_t& r3) {
  asm volatile("ldmatrix.sync.aligned.m8n8.x4.shared.b16 {%0,%1,%2,%3}, [%4];" : "=r"(r0), "=r"(r1), "=r"(r2), "=r"(r3) : "r"(a) : "memory");
}
__device__ __forceinline__ void sts128(uint32_t a, uint4 v) {
  asm volatile("st.shared.v4.b32 [%0], {%1,%2,%3,%4};" ::"r"(a), "r"(v.x), "r"(v.y), "r"(v.z), "r"(v.w) : "memory");
}
__device__ __forceinline__ float lds_f32(uint32_t a) { float v; asm volatile("ld.shared.f32 %0, [%1];" : "=f"(v) : "r"(a)); return v; }
__device__ __forceinline__ float ex2(float x) { float y; asm("ex2.approx.ftz.f32 %0, %1;" : "=f"(y) : "f"(x)); return y; }

template<int SC> __device__ __forceinline__ void wg_ss144(float (&d)[72], uint64_t da, uint64_t db) {
  asm volatile("{\n.reg .pred p;\nsetp.ne.b32 p, %74, 0;\nwgmma.mma_async.sync.aligned.m64n144k16.f32.bf16.bf16 {%0,%1,%2,%3,%4,%5,%6,%7,%8,%9,%10,%11,%12,%13,%14,%15,%16,%17,%18,%19,%20,%21,%22,%23,%24,%25,%26,%27,%28,%29,%30,%31,%32,%33,%34,%35,%36,%37,%38,%39,%40,%41,%42,%43,%44,%45,%46,%47,%48,%49,%50,%51,%52,%53,%54,%55,%56,%57,%58,%59,%60,%61,%62,%63,%64,%65,%66,%67,%68,%69,%70,%71}, %72, %73, p, 1, 1, 0, 1;\n}\n"
    : "+f"(d[0]),"+f"(d[1]),"+f"(d[2]),"+f"(d[3]),"+f"(d[4]),"+f"(d[5]),"+f"(d[6]),"+f"(d[7]),"+f"(d[8]),"+f"(d[9]),"+f"(d[10]),"+f"(d[11]),"+f"(d[12]),"+f"(d[13]),"+f"(d[14]),"+f"(d[15]),"+f"(d[16]),"+f"(d[17]),"+f"(d[18]),"+f"(d[19]),"+f"(d[20]),"+f"(d[21]),"+f"(d[22]),"+f"(d[23]),"+f"(d[24]),"+f"(d[25]),"+f"(d[26]),"+f"(d[27]),"+f"(d[28]),"+f"(d[29]),"+f"(d[30]),"+f"(d[31]),"+f"(d[32]),"+f"(d[33]),"+f"(d[34]),"+f"(d[35]),"+f"(d[36]),"+f"(d[37]),"+f"(d[38]),"+f"(d[39]),"+f"(d[40]),"+f"(d[41]),"+f"(d[42]),"+f"(d[43]),"+f"(d[44]),"+f"(d[45]),"+f"(d[46]),"+f"(d[47]),"+f"(d[48]),"+f"(d[49]),"+f"(d[50]),"+f"(d[51]),"+f"(d[52]),"+f"(d[53]),"+f"(d[54]),"+f"(d[55]),"+f"(d[56]),"+f"(d[57]),"+f"(d[58]),"+f"(d[59]),"+f"(d[60]),"+f"(d[61]),"+f"(d[62]),"+f"(d[63]),"+f"(d[64]),"+f"(d[65]),"+f"(d[66]),"+f"(d[67]),"+f"(d[68]),"+f"(d[69]),"+f"(d[70]),"+f"(d[71]) : "l"(da), "l"(db), "n"(SC));
}
template<int SC> __device__ __forceinline__ void wg_ss96(float (&d)[48], uint64_t da, uint64_t db) {
  asm volatile("{\n.reg .pred p;\nsetp.ne.b32 p, %50, 0;\nwgmma.mma_async.sync.aligned.m64n96k16.f32.bf16.bf16 {%0,%1,%2,%3,%4,%5,%6,%7,%8,%9,%10,%11,%12,%13,%14,%15,%16,%17,%18,%19,%20,%21,%22,%23,%24,%25,%26,%27,%28,%29,%30,%31,%32,%33,%34,%35,%36,%37,%38,%39,%40,%41,%42,%43,%44,%45,%46,%47}, %48, %49, p, 1, 1, 0, 1;\n}\n"
    : "+f"(d[0]),"+f"(d[1]),"+f"(d[2]),"+f"(d[3]),"+f"(d[4]),"+f"(d[5]),"+f"(d[6]),"+f"(d[7]),"+f"(d[8]),"+f"(d[9]),"+f"(d[10]),"+f"(d[11]),"+f"(d[12]),"+f"(d[13]),"+f"(d[14]),"+f"(d[15]),"+f"(d[16]),"+f"(d[17]),"+f"(d[18]),"+f"(d[19]),"+f"(d[20]),"+f"(d[21]),"+f"(d[22]),"+f"(d[23]),"+f"(d[24]),"+f"(d[25]),"+f"(d[26]),"+f"(d[27]),"+f"(d[28]),"+f"(d[29]),"+f"(d[30]),"+f"(d[31]),"+f"(d[32]),"+f"(d[33]),"+f"(d[34]),"+f"(d[35]),"+f"(d[36]),"+f"(d[37]),"+f"(d[38]),"+f"(d[39]),"+f"(d[40]),"+f"(d[41]),"+f"(d[42]),"+f"(d[43]),"+f"(d[44]),"+f"(d[45]),"+f"(d[46]),"+f"(d[47]) : "l"(da), "l"(db), "n"(SC));
}
template<int SC> __device__ __forceinline__ void wg_rs112(float (&d)[56], uint32_t a0, uint32_t a1, uint32_t a2, uint32_t a3, uint64_t db) {
  asm volatile("{\n.reg .pred p;\nsetp.ne.b32 p, %61, 0;\nwgmma.mma_async.sync.aligned.m64n112k16.f32.bf16.bf16 {%0,%1,%2,%3,%4,%5,%6,%7,%8,%9,%10,%11,%12,%13,%14,%15,%16,%17,%18,%19,%20,%21,%22,%23,%24,%25,%26,%27,%28,%29,%30,%31,%32,%33,%34,%35,%36,%37,%38,%39,%40,%41,%42,%43,%44,%45,%46,%47,%48,%49,%50,%51,%52,%53,%54,%55}, {%56,%57,%58,%59}, %60, p, 1, 1, 0;\n}\n"
    : "+f"(d[0]),"+f"(d[1]),"+f"(d[2]),"+f"(d[3]),"+f"(d[4]),"+f"(d[5]),"+f"(d[6]),"+f"(d[7]),"+f"(d[8]),"+f"(d[9]),"+f"(d[10]),"+f"(d[11]),"+f"(d[12]),"+f"(d[13]),"+f"(d[14]),"+f"(d[15]),"+f"(d[16]),"+f"(d[17]),"+f"(d[18]),"+f"(d[19]),"+f"(d[20]),"+f"(d[21]),"+f"(d[22]),"+f"(d[23]),"+f"(d[24]),"+f"(d[25]),"+f"(d[26]),"+f"(d[27]),"+f"(d[28]),"+f"(d[29]),"+f"(d[30]),"+f"(d[31]),"+f"(d[32]),"+f"(d[33]),"+f"(d[34]),"+f"(d[35]),"+f"(d[36]),"+f"(d[37]),"+f"(d[38]),"+f"(d[39]),"+f"(d[40]),"+f"(d[41]),"+f"(d[42]),"+f"(d[43]),"+f"(d[44]),"+f"(d[45]),"+f"(d[46]),"+f"(d[47]),"+f"(d[48]),"+f"(d[49]),"+f"(d[50]),"+f"(d[51]),"+f"(d[52]),"+f"(d[53]),"+f"(d[54]),"+f"(d[55]) : "r"(a0), "r"(a1), "r"(a2), "r"(a3), "l"(db), "n"(SC));
}
template<int SC> __device__ __forceinline__ void wg_sp48(float (&d)[24], uint32_t a0, uint32_t a1, uint32_t a2, uint32_t a3, uint64_t db, uint32_t meta) {
  asm volatile("{\n.reg .pred p;\nsetp.ne.b32 p, %30, 0;\nwgmma.mma_async.sp.sync.aligned.m64n48k32.f32.bf16.bf16 {%0,%1,%2,%3,%4,%5,%6,%7,%8,%9,%10,%11,%12,%13,%14,%15,%16,%17,%18,%19,%20,%21,%22,%23}, {%24,%25,%26,%27}, %28, %29, 0, p, 1, 1, 1;\n}\n"
    : "+f"(d[0]),"+f"(d[1]),"+f"(d[2]),"+f"(d[3]),"+f"(d[4]),"+f"(d[5]),"+f"(d[6]),"+f"(d[7]),"+f"(d[8]),"+f"(d[9]),"+f"(d[10]),"+f"(d[11]),"+f"(d[12]),"+f"(d[13]),"+f"(d[14]),"+f"(d[15]),"+f"(d[16]),"+f"(d[17]),"+f"(d[18]),"+f"(d[19]),"+f"(d[20]),"+f"(d[21]),"+f"(d[22]),"+f"(d[23]) : "r"(a0), "r"(a1), "r"(a2), "r"(a3), "l"(db), "r"(meta), "n"(SC));
}
template<int SC> __device__ __forceinline__ void wg_rs64(float (&d)[32], uint32_t a0, uint32_t a1, uint32_t a2, uint32_t a3, uint64_t db) {
  asm volatile("{\n.reg .pred p;\nsetp.ne.b32 p, %37, 0;\nwgmma.mma_async.sync.aligned.m64n64k16.f32.bf16.bf16 {%0,%1,%2,%3,%4,%5,%6,%7,%8,%9,%10,%11,%12,%13,%14,%15,%16,%17,%18,%19,%20,%21,%22,%23,%24,%25,%26,%27,%28,%29,%30,%31}, {%32,%33,%34,%35}, %36, p, 1, 1, 0;\n}\n"
    : "+f"(d[0]),"+f"(d[1]),"+f"(d[2]),"+f"(d[3]),"+f"(d[4]),"+f"(d[5]),"+f"(d[6]),"+f"(d[7]),"+f"(d[8]),"+f"(d[9]),"+f"(d[10]),"+f"(d[11]),"+f"(d[12]),"+f"(d[13]),"+f"(d[14]),"+f"(d[15]),"+f"(d[16]),"+f"(d[17]),"+f"(d[18]),"+f"(d[19]),"+f"(d[20]),"+f"(d[21]),"+f"(d[22]),"+f"(d[23]),"+f"(d[24]),"+f"(d[25]),"+f"(d[26]),"+f"(d[27]),"+f"(d[28]),"+f"(d[29]),"+f"(d[30]),"+f"(d[31]) : "r"(a0), "r"(a1), "r"(a2), "r"(a3), "l"(db), "n"(SC));
}

constexpr uint32_t SBC = 1024;
constexpr int ROWB = 2 * 224 * 384;
constexpr int TB = 11;
constexpr int KS = 832;
constexpr int KSLOT = 22 * KS;
constexpr int SM_X = 0;
constexpr int SM_W = SM_X + 3 * 24576;
constexpr int SM_K = SM_W + 55296;
constexpr int SM_V = SM_K + 2 * KSLOT;
constexpr int SM_Q = SM_V + 22 * 1536;
constexpr int SM_O = SM_Q + 12288;
constexpr int SM_S = SM_O + 12288;
constexpr int SM_RPB = SM_S + 6144;
constexpr int SM_BAR = SM_RPB + 768;
constexpr int SM_A_TOTAL = SM_BAR + 256;
constexpr int SM_TIN0 = SM_X + 24576, SM_TIN1 = SM_X, SM_TIN2 = SM_W + 18432;
constexpr int SM_TWO = SM_X + 2 * 24576;
constexpr int SM_TST = SM_TIN2 + 24576;
enum { B_FULL = 0, B_EMPTY = 3, B_TIN = 6, B_TFREE = 10, B_WK = 12, B_WQ, B_WO, B_KIMP, B_VIMP, B_OFREE, B_XK, B_XV,
       B_Q0, B_WOFREE, B_OTAIL, B_ODONE = B_OTAIL + 4, B_KFREE, B_VFREE, B_COUNT };
enum { N_KRDY = 4, N_QK0, N_QK1, N_VQ0, N_VQ1, N_PVISS, N_Q0 };

#define NL 2
#define OCH 16
#define MID 6
#define SPL 4
#define RA 160
#define RG 168
#define OPT 0
constexpr int FS = 64;
__device__ int g_flags[TB * 56 * FS];

#define TR(role, it, k)
#define TRDECL
#define TRARG
#define TRPASS
#define TRDUMP
#define TRB(it, k)
#define TR2START
#define TR2FLUSH(blk)
#define TR2(blk, k)

struct Stage { uint32_t lo, full, em, par; };
struct GemmCtx {
  uint32_t bar;
  uint32_t kC, vC[2], qC[2];
  uint32_t kH, vH[2];
  uint32_t hiA, hiB;
  uint32_t spin;
  bool hvalid, never, edge;
};

template <int STRIDE> __device__ __forceinline__ void dump12(uint32_t a, const uint32_t (&r)[12]) {
#pragma unroll
  for (int j = 0; j < 3; j++) stsm4(a + j * 2 * STRIDE, r[4 * j], r[4 * j + 1], r[4 * j + 2], r[4 * j + 3]);
}
__device__ __forceinline__ void keep12(bool never, uint32_t a, const uint32_t (&r)[12]) { if (never) dump12<128>(a, r); }
template <int N> __device__ __forceinline__ void pack12(uint32_t (&r)[12], const float (&d)[N], int off) {
#pragma unroll
  for (int j = 0; j < 12; j++) r[j] = pack2(d[off + 2 * j], d[off + 2 * j + 1]);
}
__device__ __forceinline__ uint64_t dsc(uint64_t lo, uint32_t hi) { uint64_t r; asm("mov.b64 %0, {%1, %2};" : "=l"(r) : "r"((uint32_t)lo), "r"(hi)); return r; }
template <int K0, int K1> __device__ __forceinline__ void issue_core(const GemmCtx& c, const Stage& x, float (&d)[72]) {
  constexpr uint64_t db = mkdesc(SBC + SM_W, 6144, 256, 3);
  wg_fence();
  if (K0 == 0) wg_ss144<0>(d, dsc(x.lo, c.hiA), dsc(db, c.hiB));
#pragma unroll
  for (int k = K0 ? K0 : 1; k < K1; k++) wg_ss144<1>(d, dsc(x.lo + (k >> 2) * 512 + (k & 3) * 2, c.hiA), dsc(db + k * 32, c.hiB));
  wg_commit();
}
template <int K0, int K1> __device__ __forceinline__ void issue_halo(const GemmCtx& c, const Stage& x, float (&d)[48]) {
  constexpr uint64_t db = mkdesc(SBC + SM_W + 18432, 6144, 256, 3);
  wg_fence();
  if (K0 == 0) wg_ss96<0>(d, dsc(x.lo, c.hiA), dsc(db, c.hiB));
#pragma unroll
  for (int k = K0 ? K0 : 1; k < K1; k++) wg_ss96<1>(d, dsc(x.lo + (k >> 2) * 384 + (k & 3) * 2, c.hiA), dsc(db + k * 32, c.hiB));
  wg_commit();
}
__device__ __forceinline__ void release_stage(const Stage& x) {
  asm volatile("{\n.reg .pred p;\nelect.sync _|p, 0xffffffff;\n@p mbarrier.arrive.shared::cluster.b64 _, [%0];\n}" ::"r"(x.em) : "memory");
}
__device__ __forceinline__ void wait_stage(GemmCtx& c, Stage& x) {
  asm volatile("{\n.reg .pred p;\nWL:\nmbarrier.try_wait.parity.shared::cta.b64 p, [%1], %2;\n@p bra WD;\n"
               "add.u32 %0, %0, 1;\nsetp.lt.u32 p, %0, 0x100000;\n@p bra WL;\nWD:\n}" : "+&r"(c.spin) : "r"(x.full), "r"(x.par) : "memory");
  x.par ^= 1;
}
__device__ __forceinline__ void edge_ready(const GemmCtx& c, int bar) { __syncwarp(); if (c.edge) mbar_arrive_elect(c.bar + bar * 8); }
__device__ __forceinline__ void dump6(uint32_t a, const uint32_t (&r)[6]) {
  stsm4(a, r[0], r[1], r[2], r[3]);
  asm volatile("stmatrix.sync.aligned.m8n8.x2.shared.b16 [%0], {%1,%2};" ::"r"(a + 512), "r"(r[4]), "r"(r[5]) : "memory");
}
__device__ __forceinline__ void pack6(uint32_t (&r)[6], const float (&d)[48], int off) {
#pragma unroll
  for (int j = 0; j < 6; j++) r[j] = pack2(d[off + 4 * j], d[off + 4 * j + 1]);
}
template <int PARITY> __device__ __forceinline__ void gwait(GemmCtx& c, int bar) {
  asm volatile("{\n.reg .pred p;\nWL:\nmbarrier.try_wait.parity.shared::cta.b64 p, [%1], %2;\n@p bra WD;\n"
               "add.u32 %0, %0, 1;\nsetp.lt.u32 p, %0, 0x100000;\n@p bra WL;\nWD:\n}" : "+&r"(c.spin) : "r"(c.bar + bar * 8), "n"(PARITY) : "memory");
}
__device__ __forceinline__ void load_w(const CUtensorMap* m, uint32_t dst, uint32_t bar, int col) {
  asm volatile("cp.async.bulk.tensor.2d.shared::cluster.global.mbarrier::complete_tx::bytes [%0], [%1, {%3,%4}], [%2];"
               ::"r"(dst), "l"(m), "r"(bar), "r"(col), "r"(0) : "memory");
}
__device__ __forceinline__ void remote_arrive(uint32_t rbar) { asm volatile("mbarrier.arrive.shared::cluster.b64 _, [%0];" ::"r"(rbar) : "memory"); }
__device__ __forceinline__ void remote_expect(uint32_t rbar, uint32_t bytes) {
  asm volatile("mbarrier.arrive.expect_tx.shared::cluster.b64 _, [%0], %1;" ::"r"(rbar), "r"(bytes) : "memory");
}
__device__ __forceinline__ void copy_remote(uint32_t rdst, uint32_t src, uint32_t bytes, uint32_t rbar) {
  asm volatile("cp.async.bulk.shared::cluster.shared::cta.mbarrier::complete_tx::bytes [%0], [%1], %2, [%3];" ::"r"(rdst), "r"(src), "r"(bytes), "r"(rbar) : "memory");
}
__device__ __forceinline__ void tail_free(uint32_t bar) {
  uint32_t ln; asm volatile("mov.u32 %0, %%laneid;" : "=r"(ln));
  if (ln < 4) mbar_arrive_remote(bar, ln + (blockIdx.x & 4));
}
__device__ __forceinline__ void publish(uint32_t bar) {
  fence_async();
  __syncwarp();
  mbar_arrive_elect(bar);
}

template <bool FIRST, int PA>
__device__ __forceinline__ void gemm_iter(GemmCtx& c, int b, uint32_t (&pk)[12], uint32_t (&pv)[12], uint32_t (&pq)[12],
                                          uint32_t (&hk1)[6], uint32_t (&hv1)[6], Stage& x0, Stage& x2, Stage& x1 TRARG) {
  const uint32_t bar = c.bar;
  const bool w = !FIRST && (PA == 0 || b >= 0), never = c.never;
  constexpr uint32_t ko = PA * KSLOT;
  float C[72];
  uint32_t hk0[6], hv0[6], pv2[12];
  TR(2, b, 0);
  if (FIRST) wait_stage(c, x0);
  else dump12<128>(c.qC[1], pq);
  if (w) nb_sync(N_QK1, 256);
  TR(2, b, 2);
  if (FIRST) TR(2, b - 1, 6);
  if (PA == 0) {
    float H[48];
    issue_halo<0, 8>(c, x0, H);
    TR(2, b, 3);
    if (!FIRST) { gwait<0>(c, B_KFREE); dump12<128>(c.kC, pk); }
    issue_halo<8, 12>(c, x0, H);
    TR(2, b, 4);
    wait_stage(c, x2);
    if (FIRST) TR(2, b - 1, 7);
    if (FIRST) gwait<0>(c, B_WQ);
    if (FIRST) TR(2, b - 1, 8);
    issue_core<0, 8>(c, x2, C);
    TR(2, b, 5);
    if (!FIRST) { fence_async(); keep12(never, c.kC, pk); }
    wg_wait<1>(); pin(H);
    release_stage(x0);
    pack6(hk0, H, 0);
    if (c.hvalid) dump6(c.kH, hk0);
    pack6(hk1, H, 2); pack6(hv0, H, 24); pack6(hv1, H, 26);
  } else {
    issue_core<0, 8>(c, x2, C);
    TR(2, b, 5);
    fence_async();
    keep12(never, c.kC, pq);
    if (w) gwait<1>(c, B_KFREE);
    dump12<128>(c.kC + ko, pk);
    if (c.hvalid) dump6(c.kH + ko, hk1);
  }
  TR(2, b, 13);
  issue_core<8, 12>(c, x2, C);
  if (w) { nb_arrive(N_VQ0, 288); nb_arrive(N_VQ1, 288); }
  else if (!FIRST) { __syncwarp(); mbar_arrive_elect(bar + B_Q0 * 8); }
  wait_stage(c, x1);
  if (never) dump6(bar, PA ? hk1 : hk0);
  TR(2, b, 6);
  wg_wait<0>(); pin(C);
  TR(2, b, 7);
  release_stage(x2);
  pack12(pk, C, 24);
  dump12<128>(c.kC + ko + 64, pk);
  pack12(pv2, C, 48);
  pack12(pq, C, 0);
  TR(2, b, 8);
  issue_core<0, SPL>(c, x1, C);
  TR(2, b, 9);
  if (!FIRST) { fence_async(); edge_ready(c, B_XK); }
  keep12(never, c.kC, pk);
  TR(2, b, 14);
  if (w) nb_sync(N_PVISS, 384);
  issue_core<SPL, 12>(c, x1, C);
  if (!FIRST) nb_arrive(N_KRDY, 256);
  TR(2, b, 1);
  if (PA && b == 11) tail_free(bar + B_TFREE * 8);
  wait_stage(c, x0);
  if (w) gwait<PA>(c, B_VFREE);
  if (w && b < TB) gwait<PA>(c, B_ODONE);
  TR(2, b, 10);
  if (!FIRST) dump12<128>(c.vC[PA], pv);
  dump12<128>(c.vC[PA ^ 1] + 768, pv2);
  TR(2, b, 11);
  wg_wait<0>(); pin(C);
  TR(2, b, 12);
  release_stage(x1);
  if (!FIRST && c.edge) publish(bar + B_XV * 8);
  if (c.hvalid) dump6(c.vH[PA], PA ? hv1 : hv0);
  if (PA && !w) nb_sync(N_Q0, 384);
  dump12<128>(c.qC[0], pq);
  pack12(pk, C, 24);
  pack12(pv, C, 48);
  pack12(pq, C, 0);
}

template <int IN> __device__ __forceinline__ void issue_proj(float (&D)[48]) {
  constexpr uint64_t da = mkdesc(SBC + IN, 128, 768, 0), db = mkdesc(SBC + SM_TWO, 12288, 512, 2);
  wg_fence();
  wg_ss96<0>(D, da, db);
#pragma unroll
  for (int k = 1; k < 12; k++) wg_ss96<1>(D, da + (k / 3) * 384 + (k % 3) * 16, db + k * 64);
  wg_commit();
}
template <int ACC> __device__ __forceinline__ void issue_proj_half(float (&D)[48], int hd) {
  const uint64_t da = mkdesc(SBC + SM_TIN2, 128, 768, 0) + hd * 384, db = mkdesc(SBC + SM_TWO, 12288, 512, 2) + hd * 192;
  wg_fence();
  wg_ss96<ACC>(D, da, db);
#pragma unroll
  for (int k = 1; k < 6; k++) wg_ss96<1>(D, da + (k / 3) * 768 + (k % 3) * 16, db + (k / 3) * 384 + (k % 3) * 64);
  wg_commit();
}
__device__ __forceinline__ void store_proj(const float (&D)[48], const CUtensorMap* m, uint32_t st, uint32_t sta, int row, int col, int ch) {
#pragma unroll
  for (int q = 0; q < 6; q++)
    stsm4((sta ^ ((q & 1) * 32)) + (q >> 1) * 1024,
          pack2(D[8 * q], D[8 * q + 1]), pack2(D[8 * q + 2], D[8 * q + 3]), pack2(D[8 * q + 4], D[8 * q + 5]), pack2(D[8 * q + 6], D[8 * q + 7]));
  fence_async();
  __syncwarp();
  if ((threadIdx.x & 31) == 0) {
    asm volatile("cp.async.bulk.tensor.4d.global.shared::cta.bulk_group [%0, {%2,%3,%4,%5}], [%1];" ::"l"(m), "r"(st), "r"(0), "r"(row), "r"(col), "r"(ch) : "memory");
    asm volatile("cp.async.bulk.commit_group;" ::: "memory");
  }
  __syncwarp();
}

__device__ __forceinline__ float fold(float a, float b, float t, int useb) {
  float r;
  asm("{\n.reg .pred p;\nsetp.ne.b32 p, %4, 0;\nfma.rn.f32 %0, %1, 0f3E553B95, %3;\n@p fma.rn.f32 %0, %2, 0f3E553B95, %3;\n}"
      : "=&f"(r) : "f"(a), "f"(b), "f"(t), "r"(useb));
  return r;
}
template <int U, int L>
__device__ __forceinline__ void softmax_tile(const float (&SA)[56], const float (&SB)[56], const float (&T)[16], int b0, int b1,
                                             uint32_t (&P)[28], float (&sx)[8], uint32_t nbV, uint32_t zero, uint32_t qa, uint32_t (&q)[12]) {
  float lu[14], ll[14];
#pragma unroll
  for (int j = 0; j < 7; j++) {
    constexpr int sh = U == L ? 2 : 0;
    const float tu0 = T[2 * j + sh], tu1 = T[2 * j + 1 + sh], tl0 = T[2 * j], tl1 = T[2 * j + 1];
    lu[2 * j]     = fold(SA[4 * (U + j)],     SB[4 * (U + j)],     tu0, b0);
    ll[2 * j]     = fold(SA[4 * (L + j) + 2], SB[4 * (L + j) + 2], tl0, b0);
    lu[2 * j + 1] = fold(SA[4 * (U + j) + 1], SB[4 * (U + j) + 1], tu1, b1);
    ll[2 * j + 1] = fold(SA[4 * (L + j) + 3], SB[4 * (L + j) + 3], tl1, b1);
  }
  float mu = lu[0], ml = ll[0], mu2 = lu[1], ml2 = ll[1];
#pragma unroll
  for (int j = 1; j < 7; j++) { mu = fmaxf(mu, lu[2 * j]); mu2 = fmaxf(mu2, lu[2 * j + 1]); ml = fmaxf(ml, ll[2 * j]); ml2 = fmaxf(ml2, ll[2 * j + 1]); }
  mu = fmaxf(mu, mu2); ml = fmaxf(ml, ml2);
  { const float a1 = __shfl_xor_sync(0xffffffffu, mu, 1), a2 = __shfl_xor_sync(0xffffffffu, mu, 2), a3 = __shfl_xor_sync(0xffffffffu, mu, 3);
    const float c1 = __shfl_xor_sync(0xffffffffu, ml, 1), c2 = __shfl_xor_sync(0xffffffffu, ml, 2), c3 = __shfl_xor_sync(0xffffffffu, ml, 3);
    mu = fmaxf(fmaxf(mu, a1), fmaxf(a2, a3)); ml = fmaxf(fmaxf(ml, c1), fmaxf(c2, c3)); }
  float su = 0.f, sl = 0.f;
#pragma unroll
  for (int c = 0; c < 14; c++) {
    if (c >= U && c < U + 7) {
      float e0 = ex2(lu[2 * (c - U)] - mu), e1 = ex2(lu[2 * (c - U) + 1] - mu);
      su = c == U ? e0 + e1 : (su + e0) + e1; P[2 * c] = pack2(e0, e1);
    } else P[2 * c] = 0u;
  }
  nb_sync(nbV | (P[2 * (U + MID)] & zero), 288);
#pragma unroll
  for (int k = 0; k < 3; k++) ldsm4(qa + k * 256, q[4 * k], q[4 * k + 1], q[4 * k + 2], q[4 * k + 3]);
#pragma unroll
  for (int c = 0; c < 14; c++) {
    if (c >= L && c < L + 7) {
      float e0 = ex2(ll[2 * (c - L)] - ml), e1 = ex2(ll[2 * (c - L) + 1] - ml);
      sl = c == L ? e0 + e1 : (sl + e0) + e1; P[2 * c + 1] = pack2(e0, e1);
    } else P[2 * c + 1] = 0u;
  }
  sx[0] = su; sx[4] = sl;
#pragma unroll
  for (int k = 1; k < 4; k++) sx[k] = __shfl_xor_sync(0xffffffffu, su, k);
#pragma unroll
  for (int k = 1; k < 4; k++) sx[4 + k] = __shfl_xor_sync(0xffffffffu, sl, k);
}

struct BandCfg { uint32_t ra0, ra1, meta; int b0, b1; };
__device__ __forceinline__ void band_cfg(int b, uint32_t tb, BandCfg& n) {
  uint32_t ln; asm volatile("mov.u32 %0, %%laneid;" : "=r"(ln));
  const int g = ln >> 2, t = ln & 3;
  const int sw = min(max(g + 1, b == 0 ? 4 : 0), b == 13 ? 5 : 8);
  const int i0 = 2 * t, i1 = 2 * t + 1;
  n.b0 = i0 <= sw - 2; n.b1 = i1 <= sw - 2;
  n.ra0 = tb + (i0 == sw - 1 ? 13 : i0 + 8 * n.b0 - g + 2) * 52;
  n.ra1 = tb + (i1 == sw - 1 ? 13 : i1 + 8 * n.b1 - g + 2) * 52;
  n.meta = ((0x5555u & ((1u << (2 * (sw - 1))) - 1)) ^ 0xDD88u ^ (((t ^ b) & 1) ? 0x5555u : 0u)) * 0x10001u;
}
__device__ __forceinline__ void band_load(const BandCfg& n, float (&T)[16], int& b0, int& b1, uint32_t& meta) {
#pragma unroll
  for (int jj = 0; jj < 8; jj++) { T[2 * jj] = lds_f32(n.ra0 + jj * 4); T[2 * jj + 1] = lds_f32(n.ra1 + jj * 4); }
  b0 = n.b0; b1 = n.b1; meta = n.meta;
}

struct Maps { CUtensorMap xc, xh, w, os, wo, ot; };

__global__ void __cluster_dims__(8, 1, 1) __launch_bounds__(512, 1)
na_attn_kernel(const __nv_bfloat16* __restrict__ x, const __nv_bfloat16* __restrict__ wqkv, const __nv_bfloat16* __restrict__ rpb, const __grid_constant__ Maps mp) {
  extern __shared__ __align__(1024) uint8_t smem_raw[];
  const uint32_t sb = smem_u32(smem_raw);
  if ((sb & 0x3FFFF) != SBC) return;
  const uint32_t bar = sb + SM_BAR;
  TR2START;
  const int tid = threadIdx.x, lane = tid & 31;
  const int warp = __shfl_sync(0xffffffffu, tid >> 5, 0);
  const int head = blockIdx.x & 3, base = blockIdx.x & 4, sp = blockIdx.x >> 2;
  const int par = sp < 24 ? sp / 6 : sp - 24, strip = sp < 24 ? sp - par * 6 : 6, ph = par >> 1, pw = par & 1;
  const int odd = strip & 1;

  uint4 wv[2 * NL];
  const int va = head == 1;
  const uint32_t wdst = sb + SM_W + (3 + va + ((tid >> 1) & 1)) * 6144 + (tid >> 2) * 32 + ((tid ^ (tid >> 4)) & 1) * 16;
  if (warp < 12) {
    asm volatile("barrier.cluster.arrive.relaxed.aligned;" ::: "memory");
    const uint32_t wo0 = (tid >> 2) * 1152 + head * 96 + va * 32 + (tid & 3) * 16;
#pragma unroll
    for (int i = 0; i < 2 * NL; i++)
      asm volatile("ld.global.nc.v4.b32 {%0,%1,%2,%3}, [%4];" : "=r"(wv[i].x), "=r"(wv[i].y), "=r"(wv[i].z), "=r"(wv[i].w)
                   : "l"(reinterpret_cast<const uint8_t*>(wqkv) + wo0 + (i & 1) * 96 * 1152 + (i / 2 + 1) * 384));
  }
  if (warp < 8) {
    asm volatile("setmaxnreg.inc.sync.aligned.u32 %0;" ::"n"(RA));
    float rv = -INFINITY;
    if (tid < 169) rv = __bfloat162float(rpb[head * 169 + tid]) * 1.4426950408889634f;
    if (tid < 192) {
      const int kc = (tid & 15) + 3, wc = (tid >> 4) % 6;
      sts128(tid < 96 ? sb + SM_K + kc * KS + wc * 128 + 48 : sb + SM_V + kc * 1536 + wc * 128 + (6 + (kc & 1)) * 16, make_uint4(0, 0, 0, 0));
    }
#pragma unroll
    for (int i = 0; i < 2 * NL; i++) sts128(wdst + (i & 1) * 3072 + (i / 2) * 18432, wv[i]);
    fence_async();
    asm volatile("bar.arrive 1, 384;" ::: "memory");
    if (tid < 182) asm volatile("st.shared.f32 [%0], %1;" ::"r"(sb + SM_RPB + tid * 4), "f"(rv) : "memory");
    const int jw = warp >> 2, j = jw ^ odd, w = warp & 3, wt = 4 * j + w;
    int variant = w;
    if (strip == 0 && j == 0 && w < 2) variant = 4;
    if (strip == 6 && j == 1 && w >= 2) variant = 5;
    const bool v1 = opq((uint32_t)(variant & 1)), v2 = opq((uint32_t)(variant & 2)), v4 = opq((uint32_t)(variant & 4));
    const uint32_t qa = opq(sb + SM_Q + (8 * j + 2 * w + ((lane >> 3) & 1)) * 768 + (lane >> 4) * 128 + (((lane & 7) * 16) ^ (((lane >> 3) & 1) * 64)));
    uint32_t oa = opq(sb + SM_O + j * 6144 + (2 * w + ((lane >> 3) & 1)) * 768 + (lane >> 4) * 128 + (lane & 7) * 16);
    uint64_t dA = opq(mkdesc(SBC + SM_K, 128, KS, 0) + j * (8 * KS / 16)), dB = opq(dA + (KSLOT >> 4));
    uint64_t dV[7];
#pragma unroll
    for (int i = 0; i < 7; i++) dV[i] = opq(mkdesc(SBC + SM_V, 768, 128, 0) + j * (8 * 1536 / 16) + i * 192);
    const uint32_t nbK = opq((uint32_t)(N_KRDY + jw)), nbQ = opq((uint32_t)(N_QK0 + jw)), nbV = opq((uint32_t)(N_VQ0 + jw));
    asm volatile("barrier.cluster.wait.aligned;" ::: "memory");
    asm volatile("bar.sync 3, 256;" ::: "memory");
    float T[16];
    TRDECL;
    int b0, b1;
    uint32_t meta, ob = bar + B_ODONE * 8, fb = bar + B_OFREE * 8, fp = 1;
    const uint32_t tb = opq(sb + SM_RPB + (variant < 4 ? 3 : variant + 1 - 2 * w) * 4);
    const bool own = ((w ^ head) & 2) == 0;
    const uint32_t dst13 = sb + SM_TIN2 + head * 6144 + (2 * j + (w & 1)) * 1536, src13 = opq(own ? dst13 : sb + SM_S + (2 * j + (w & 1)) * 1536);
    const uint32_t snd[4] = {opq(own ? 0u : mapa(dst13, base + (head ^ 2))), opq(mapa(bar + (B_TIN + 2) * 8, base + (head ^ 2))),
                             opq(mapa(dst13, base + (w & 2) + (~head & 1))), opq(mapa(bar + (B_TIN + 3) * 8, base + (w & 2) + (~head & 1)))};
    BandCfg nx;
    band_cfg(0, tb, nx);
    band_load(nx, T, b0, b1, meta);
    band_cfg(1, tb, nx);
    const uint32_t zero = opq(blockIdx.x >> 16);
    uint32_t special = opq(0x380Au << 1);
    uint32_t q[12];
    mbar_wait(bar + B_Q0 * 8, 0);
#pragma unroll
    for (int k = 0; k < 3; k++) ldsm4(qa + k * 256, q[4 * k], q[4 * k + 1], q[4 * k + 2], q[4 * k + 3]);
    nb_arrive(N_Q0, 384);
#pragma unroll 1
    for (int b = 0; b < 14; b++) {
      float SA[56], SB[56];
      TR(0, b, 0);
      if (jw) mbar_wait(bar + B_KIMP * 8, b & 1);
      nb_sync(nbK, 256);
      TR(0, b, 1);
      TR(0, b - 1, 9);
      wg_fence();
      wg_rs112<0>(SA, q[0], q[1], q[2], q[3], dA);
      wg_rs112<0>(SB, q[0], q[1], q[2], q[3], dB);
      wg_rs112<1>(SA, q[4], q[5], q[6], q[7], dA + 16);
      wg_rs112<1>(SB, q[4], q[5], q[6], q[7], dB + 16);
      wg_rs112<1>(SA, q[8], q[9], q[10], q[11], dA + 32);
      wg_rs112<1>(SB, q[8], q[9], q[10], q[11], dB + 32);
      wg_commit();
      nb_arrive(nbQ, 256);
      { const uint64_t t = dA; dA = dB; dB = t; }
      special >>= 1;
      if (special & 1) {
        if (b == 3) band_cfg(13, tb, nx);
        else {
          if (b == 1 || b == 13) band_load(nx, T, b0, b1, meta);
          if (b >= TB) {
            ob = bar + (b == 13 ? (own ? B_TIN + 2 : B_ODONE) : B_OTAIL + 2 * (b - TB) + jw) * 8;
            if (b > TB || own) { fb = bar + (B_TFREE + (b > TB)) * 8; fp = 0; }
            if (own) oa += b == TB ? dst13 - (SM_TIN2 - SM_TIN0) - (sb + SM_O + wt * 1536) : (b == 12 ? 0u - (SM_TIN0 - SM_TIN1) : SM_TIN2 - SM_TIN1);
            else oa += b == 12 ? 0u - (SM_O - SM_Q) : (b == 13 ? src13 - (sb + SM_Q + wt * 1536) : 0);
          }
        }
      }
      TR(0, b, 2);
      wg_wait<0>(); pin(SA); pin(SB);
      mbar_arrive_elect(bar + B_KFREE * 8);
      TR(0, b, 3);
      TR(0, b - 1, 10);
      uint32_t P[28];
      float sx[8];
      if (v2) {
        if (v1) softmax_tile<6, 7>(SA, SB, T, b0, b1, P, sx, nbV, zero, qa, q); else softmax_tile<4, 5>(SA, SB, T, b0, b1, P, sx, nbV, zero, qa, q);
      } else if (!v4) {
        if (v1) softmax_tile<2, 3>(SA, SB, T, b0, b1, P, sx, nbV, zero, qa, q); else softmax_tile<0, 1>(SA, SB, T, b0, b1, P, sx, nbV, zero, qa, q);
      } else {
        if (v1) softmax_tile<4, 4>(SA, SB, T, b0, b1, P, sx, nbV, zero, qa, q); else softmax_tile<3, 3>(SA, SB, T, b0, b1, P, sx, nbV, zero, qa, q);
      }
      float O[24];
      TR(0, b, 4);
      wg_fence();
      wg_sp48<0>(O, P[0], P[1], P[2], P[3], dV[0], meta);
#pragma unroll
      for (int s = 1; s < 7; s++) wg_sp48<1>(O, P[4 * s], P[4 * s + 1], P[4 * s + 2], P[4 * s + 3], dV[s], meta);
      wg_commit();
      nb_arrive(N_PVISS, 384);
      TR(0, b, 6);
      mbar_wait(fb, fp);
      wg_wait<0>(); pin(O);
      mbar_arrive_elect(bar + B_VFREE * 8);
      TR(0, b, 7);
      float ru, rl;
      asm("rcp.approx.ftz.f32 %0, %1;" : "=f"(ru) : "f"(((fmaf(O[0], 0.f, sx[0]) + sx[1]) + sx[2]) + sx[3]));
      asm("rcp.approx.ftz.f32 %0, %1;" : "=f"(rl) : "f"(((fmaf(O[2], 0.f, sx[4]) + sx[5]) + sx[6]) + sx[7]));
#pragma unroll
      for (int i = 0; i < 3; i++)
        stsm4(oa + i * 256, pack2(O[8 * i] * ru, O[8 * i + 1] * ru), pack2(O[8 * i + 2] * rl, O[8 * i + 3] * rl),
              pack2(O[8 * i + 4] * ru, O[8 * i + 5] * ru), pack2(O[8 * i + 6] * rl, O[8 * i + 7] * rl));
      publish(ob);
      fp ^= 1;
      meta ^= 0x55555555u;
      TR(0, b, 8);
    }
    asm volatile("{\n.reg .pred p, q;\nsetp.ne.b32 q, %1, 0;\nelect.sync _|p, 0xffffffff;\nand.pred q, q, p;\n"
                 "@q cp.async.bulk.shared::cluster.shared::cta.mbarrier::complete_tx::bytes [%1], [%0], 1536, [%2];\n"
                 "@p cp.async.bulk.shared::cluster.shared::cta.mbarrier::complete_tx::bytes [%3], [%0], 1536, [%4];\n}"
                 ::"r"(src13), "r"(snd[0]), "r"(snd[1]), "r"(snd[2]), "r"(snd[3]) : "memory");
    nb_arrive(3, 384);
    TRDUMP;
    cluster_sync();
  } else if (warp < 12) {
    TRDECL;
    TR(2, -3, 0);
    asm volatile("setmaxnreg.inc.sync.aligned.u32 %0;" ::"n"(RG));
    TR(2, -3, 1);
    GemmCtx c;
    c.bar = bar;
    const int gw = warp - 8, tk = gw * 16 + (lane & 15), hi = lane >> 4;
    { const int col = tk >> 2, i = tk & 3;
      c.kC = sb + SM_K + (col + 3) * KS + hi * 128 + i * 16;
      c.vC[0] = sb + SM_V + (col + 3) * 1536 + hi * 128 + (2 * i + ((col + 3) & 1)) * 16;
      c.qC[0] = sb + SM_Q + col * 768 + hi * 128 + (col & 1) * 64 + i * 16; }
    { const int kc = gw - 1 + 19 * odd, i = lane & 7; c.hvalid = gw > 0; c.edge = gw == (odd ? 0 : 3);
      c.kH = sb + SM_K + kc * KS + (lane >> 3) * 128 + i * 16;
      c.vH[0] = sb + SM_V + kc * 1536 + (lane >> 3) * 128 + (i >> 2) * 768 + (2 * (i & 3) + ((kc ^ (i >> 2)) & 1)) * 16; }
    Stage xs[3];
#pragma unroll
    for (int i = 0; i < 3; i++) {
      const int p = (i + 1) % 3;
      xs[i].lo = (uint32_t)mkdesc(SBC + SM_X + p * 24576, 16, 0, 0); xs[i].full = bar + (B_FULL + p) * 8;
      xs[i].em = opq(mapa(bar + (B_EMPTY + p) * 8, base + p)); xs[i].par = 0;
    }
    c.never = x == nullptr;
    c.kC = opq(c.kC); c.kH = opq(c.kH);
    c.vC[1] = opq(c.vC[0] ^ 16); c.vC[0] = opq(c.vC[0]);
    c.vH[1] = opq(c.vH[0] ^ 16); c.vH[0] = opq(c.vH[0]);
    c.qC[1] = opq(c.qC[0] ^ 64); c.qC[0] = opq(c.qC[0]);
    c.spin = 0;
    c.hiA = (uint32_t)(mkdesc(0, 0, 1024, 1) >> 32) + (blockIdx.x >> 16); c.hiB = (uint32_t)(mkdesc(0, 0, 256, 3) >> 32) + (blockIdx.x >> 16);
    asm volatile("barrier.cluster.wait.aligned;" ::: "memory");
    TR(2, -3, 2);
#pragma unroll
    for (int i = 0; i < 2 * NL; i++) sts128(wdst + (i & 1) * 3072 + (i / 2) * 18432, wv[i]);
    fence_async();
    TR(2, -3, 3);
    asm volatile("bar.sync 1, 384;" ::: "memory");
    TR(2, -3, 4);
    mbar_wait(bar + B_WK * 8, 0);
    asm volatile("griddepcontrol.launch_dependents;");
    TR(2, -3, 5);
    uint32_t pk[12], pv[12], pq[12], hk1[6], hv1[6];
    gemm_iter<true, 0>(c, -2, pk, pv, pq, hk1, hv1, xs[0], xs[1], xs[2] TRPASS);
    TR2(blockIdx.x, 4);
    c.hiA = opq(c.hiA); c.hiB = opq(c.hiB);
#pragma unroll 1
    for (int b = -1;; b += 2) {
      gemm_iter<false, 1>(c, b, pk, pv, pq, hk1, hv1, xs[2], xs[0], xs[1] TRPASS);
      if (b == 11) break;
      gemm_iter<false, 0>(c, b + 1, pk, pv, pq, hk1, hv1, xs[2], xs[0], xs[1] TRPASS);
      const Stage t = xs[2]; xs[2] = xs[1]; xs[1] = xs[0]; xs[0] = t;
    }
    TR2(blockIdx.x, 6);
    c.hiA = opq(c.hiA); c.hiB = opq(c.hiB);
    const uint32_t st = sb + gw * 3072;
    const uint32_t sta = st + (lane & 15) * 64 + ((hi ^ ((lane >> 1) & 3)) * 16);
    const int oc = ph * 112 + strip * 16 + 8 * (gw >> 1) + 4 * (head >> 1) + 2 * (gw & 1), och = pw * 6 + (head & 1) * 3;
    const uint32_t so = (~head & 2) * 6144;
    float D0[48], D1[48];
    if (lane < 4) mbar_arrive_remote(bar + B_WOFREE * 8, 2 * lane + (head & 1));
    dump12<128>(c.qC[1], pq);
    nb_sync(N_QK1, 256);
    issue_halo<0, 8>(c, xs[2], D1);
    fence_async();
    nb_arrive(N_VQ0, 288); nb_arrive(N_VQ1, 288); nb_arrive(N_PVISS, 384);
    issue_halo<8, 12>(c, xs[2], D1);
    gwait<0>(c, B_KFREE);
    dump12<128>(c.kC, pk);
    if (c.edge) publish(bar + B_XK * 8);
    wg_wait<0>(); pin(D1);
    pack6(hk1, D1, 0);
    if (c.hvalid) dump6(c.kH, hk1);
    tail_free(bar + (B_TFREE + 1) * 8);
    pack6(hv1, D1, 24);
    fence_async();
    nb_arrive(N_KRDY, 256);
    gwait<0>(c, B_VFREE);
    dump12<128>(c.vC[0], pv);
    if (c.hvalid) dump6(c.vH[0], hv1);
    fence_async();
    edge_ready(c, B_XV);
    nb_arrive(N_VQ0, 288); nb_arrive(N_VQ1, 288);
    gwait<0>(c, B_WO);
    gwait<0>(c, B_TIN);
    TR(2, 13, 0);
    nb_sync(N_QK1, 256);
    issue_proj<SM_TIN0>(D0);
    wg_wait<0>(); pin(D0);
    TR(2, 13, 1);
    store_proj(D0, &mp.ot, st + SM_TST, sta + SM_TST, 8 * TB, oc, och);
    gwait<0>(c, B_TIN + 1);
    TR(2, 13, 2);
    nb_arrive(N_PVISS, 384);
    nb_sync(3, 384);
    issue_proj<SM_TIN1>(D1);
    wg_wait<0>(); pin(D1);
    TR(2, 13, 3);
    store_proj(D1, &mp.ot, st + SM_TIN0 + so, sta + SM_TIN0 + so, 8 * TB + 8, oc, och);
    TR(2, 13, 4);
    gwait<0>(c, B_TIN + 2);
    TR(2, 13, 5);
    issue_proj_half<0>(D0, head & 1);
    gwait<0>(c, B_TIN + 3);
    TR(2, 13, 6);
    issue_proj_half<1>(D0, ~head & 1);
    asm volatile("barrier.cluster.arrive.relaxed.aligned;" ::: "memory");
    wg_wait<0>(); pin(D0);
    store_proj(D0, &mp.ot, st + SM_TIN1 + so, sta + SM_TIN1 + so, 8 * TB + 16, oc, och);
    TR(2, 13, 7);
    if (lane == 0) asm volatile("cp.async.bulk.wait_group.read 0;" ::: "memory");
    __syncwarp();
    TR(2, 13, 8);
    TR2(blockIdx.x, 2);
    TR2FLUSH(blockIdx.x);
    TRDUMP;
    asm volatile("barrier.cluster.wait.aligned;" ::: "memory");
  } else {
    asm volatile("setmaxnreg.dec.sync.aligned.u32 24;");
    if (warp == 15) {
      const int l = min(lane, 24), row = head + (l < 16 ? 0 : 4 * ((l - 16) / 3)), col = strip * 16 + (l < 16 ? l : (l - 16) % 3 + (odd ? 16 : (strip ? -3 : 0)));
      const uint8_t* p = reinterpret_cast<const uint8_t*>(x) + (uint32_t)(row * ROWB + (ph * 112 + col) * 768 + pw * 384);
#pragma unroll
      for (int i = 0; i < 3; i++) asm volatile("prefetch.global.L2 [%0];" ::"l"(p + i * 128));
    } else if (elect_one()) {
      if (warp == 12) {
        mbar_init(bar + B_WK * 8, 1);
#pragma unroll
        for (int i = 0; i < NL; i++) load_w(&mp.w, sb + SM_W + (3 * i + 5 - 2 * va) * 6144, bar + B_WK * 8, (i + 1) * 192 + head * 48 + 32 - 32 * va);
        asm volatile("prefetch.tensormap [%0];" ::"l"(head == 1 ? &mp.xh : &mp.xc) : "memory");
      } else if (warp == 13) {
#pragma unroll
        for (int i = 0; i < B_XK; i++) if (i != B_WK) mbar_init(bar + i * 8, (i >= B_EMPTY && i < B_TIN) || (i >= B_TFREE && i < B_WK) ? 16 : (i == B_TIN + 2 ? 5 : (i == B_TIN || i == B_TIN + 1 ? 3 : 1)));
      } else {
#pragma unroll
        for (int i = B_XK; i < B_COUNT; i++) mbar_init(bar + i * 8, i < B_Q0 ? 2 : (i < B_ODONE ? (i == B_WOFREE ? 16 : 4) : (i == B_VFREE ? 9 : 8)));
        mbar_arrive(bar + B_XK * 8); mbar_arrive(bar + B_XV * 8);
      }
      asm volatile("fence.mbarrier_init.release.cluster;" ::: "memory");
    }
    __syncwarp();
    asm volatile("barrier.cluster.arrive.relaxed.aligned;" ::: "memory");
    if (warp != 12) asm volatile("barrier.cluster.wait.aligned;" ::: "memory");
    else {
      const int cc = ph * 112 + strip * 16, ch = cc + (odd ? 16 : (strip ? -3 : 0)), rh = strip ? -4 : 112;
      const uint32_t fb = opq(bar + (B_FULL + head) * 8), dst0 = sb + SM_X + head * 24576, c3 = opq((uint32_t)(pw * 3)), mask = opq(15u << base);
      int t = head == 0 ? 2 : head - 1;
      uint64_t mx = opq((uint64_t)(t ? &mp.xc : &mp.xh));
      uint32_t row = opq((uint32_t)(t ? 4 * t - 4 : rh)), col = opq((uint32_t)(t ? cc : ch)), dst = opq(dst0 + (t ? 0 : 2048));
#pragma unroll 1
      for (int n = 0;; n++) {
        if (n) mbar_wait(fb + (B_EMPTY - B_FULL) * 8, ~n & 1);
        else asm volatile("barrier.cluster.wait.aligned;" ::: "memory");
        if (head < 3) {
          asm volatile("{\n.reg .pred p;\n.reg .b16 m;\nelect.sync _|p, 0xffffffff;\ncvt.u16.u32 m, %7;\n"
                       "@p cp.async.bulk.tensor.4d.shared::cluster.global.mbarrier::complete_tx::bytes.multicast::cluster [%0], [%1, {%3,%4,%5,%6}], [%2], m;\n}"
                       ::"r"(dst), "l"(mx), "r"(fb), "r"(0), "r"(row), "r"(col), "r"(c3), "r"(mask) : "memory");
          if (lane < 4) remote_expect(mapa(fb, base + lane), dst == dst0 ? 24576 : 18432);
          __syncwarp();
        }
        if (n == 0 && elect_one()) {
#pragma unroll
          for (int i = 0; i < 3; i++) load_w(&mp.w, sb + SM_W + i * 6144, bar + B_WQ * 8, head * 48 + i * 16);
          mbar_expect(bar + B_WQ * 8, 18432);
        }
        __syncwarp();
        if (head == 3 || n == 11) break;
        t += 3;
        const int hn = t / 5;
        const bool core = t != 5 * hn;
        mx = opq((uint64_t)(core ? &mp.xc : &mp.xh));
        row = opq((uint32_t)(core ? 4 * (t - hn - 1) : rh + 16 * hn)); col = opq((uint32_t)(core ? cc : ch)); dst = opq(dst0 + (core ? 0 : 2048));
        if (elect_one()) asm volatile("cp.async.bulk.prefetch.tensor.4d.L2.global [%0, {%1,%2,%3,%4}];" ::"l"(mx), "r"(0), "r"(row), "r"(col), "r"(c3) : "memory");
        __syncwarp();
      }
      mbar_wait(bar + B_WOFREE * 8, 0);
      if (elect_one()) {
        const int qr = (blockIdx.x & 7) >> 1;
#pragma unroll
        for (int i = 0; i < 3; i++)
          asm volatile("cp.async.bulk.tensor.2d.shared::cluster.global.mbarrier::complete_tx::bytes.multicast::cluster [%0], [%1, {%3,%4}], [%2], %5;"
                       ::"r"(sb + SM_TWO + i * 12288 + qr * 3072), "l"(&mp.wo), "r"(bar + B_WO * 8), "r"((head & 1) * 96 + i * 32), "r"(qr * 48),
                         "h"((uint16_t)(0x55 << (head & 1))) : "memory");
      }
      __syncwarp();
    }
    if (warp & 1) {
      const uint32_t partner = (blockIdx.x & 7) ^ 4;
      const int cs = odd ? 3 : (strip == 6 ? 15 : 16), cd = odd || strip == 6 ? 19 : 0;
      const uint32_t rb = opq(mapa(bar, partner));
      TRDECL;
      if (warp == 13) {
        const uint32_t dst = opq(mapa(sb + SM_V + cd * 1536, partner)), src = opq(sb + SM_V + cs * 1536);
#pragma unroll 1
        for (int b = 0;; b++) {
          const uint32_t pa = b & 1;
          nb_arrive(N_VQ0, 288);
          mbar_wait(bar + B_XV * 8, pa);
          TR(1, b, 0);
          if (elect_one()) { copy_remote(dst, src, 4608, rb + B_VIMP * 8); remote_expect(rb + B_VIMP * 8, 4608); }
          __syncwarp();
          TR(1, b, 1);
          mbar_wait(bar + B_VIMP * 8, pa);
          TR(1, b, 2);
          nb_arrive(N_VQ1, 288);
          if (elect_one()) remote_arrive(rb + B_VFREE * 8);
          __syncwarp();
          TR(1, b, 3);
          if (b == 13) break;
          mbar_wait(bar + B_VFREE * 8, pa);
          if (elect_one()) remote_arrive(rb + B_XV * 8);
          __syncwarp();
        }
      } else {
        const uint32_t dst = opq(mapa(sb + SM_K + cd * KS, partner)), src = opq(sb + SM_K + cs * KS);
#pragma unroll 1
        for (int b = 0;; b++) {
          const uint32_t pa = b & 1, so = (pa ^ 1) * KSLOT;
          mbar_wait(bar + B_XK * 8, pa);
          TR(1, b - 1, 4);
          if (elect_one()) {
            copy_remote(dst + so, src + so, 3 * KS, rb + B_KIMP * 8);
            if (b == 0) copy_remote(dst, src, 3 * KS, rb + B_KIMP * 8);
            remote_expect(rb + B_KIMP * 8, b ? 3 * KS : 6 * KS);
          }
          __syncwarp();
          TR(1, b - 1, 5);
          TR(1, b - 1, 7);
          if (b == 13) break;
          mbar_wait(bar + B_KFREE * 8, pa);
          if (elect_one()) remote_arrive(rb + B_XK * 8);
          __syncwarp();
        }
      }
      TRDUMP;
    }
    if (warp == 14) {
      int* flag = g_flags + (par * 7 + strip) * 2 * FS;
      if (elect_one()) {
        mbar_expect(bar + B_WK * 8, NL * 6144);
        mbar_expect(bar + B_WO * 8, 36864);
        mbar_expect(bar + B_TIN * 8, 18432); mbar_expect(bar + (B_TIN + 1) * 8, 18432); mbar_expect(bar + (B_TIN + 2) * 8, 6144); mbar_expect(bar + (B_TIN + 3) * 8, 12288);
      }
      __syncwarp();
#pragma unroll 1
      for (int b = 0; b < TB; b++) {
        mbar_wait(bar + B_ODONE * 8, b & 1);
        if (lane == 0) {
#pragma unroll 1
          for (int i = 0; i < 16; i += OCH) {
            asm volatile("cp.async.bulk.tensor.3d.global.shared::cta.bulk_group [%0, {%2,%3,%4}], [%1];"
                         ::"l"(&mp.os), "r"(sb + SM_O + i * 768), "r"(pw * 192), "r"(8 * b + 2 * head), "r"(ph * 112 + strip * 16 + i) : "memory");
            asm volatile("cp.async.bulk.commit_group;\ncp.async.bulk.wait_group 0;" ::: "memory");
          }
        }
        __syncwarp();
        mbar_arrive_elect(bar + B_OFREE * 8);
        if (lane == 0)
          asm volatile("fence.proxy.async.global;\nfence.acq_rel.gpu;\nred.relaxed.gpu.global.add.s32 [%0], 1;\nred.relaxed.gpu.global.add.s32 [%1], 1;"
                       ::"l"(flag + b * 56 * FS), "l"(flag + (b * 56 + 1) * FS) : "memory");
        __syncwarp();
      }
#pragma unroll 1
      for (int t = 0; t < 4; t++) {
        const int i = t >> 1, j = (t ^ odd) & 1, d = (lane + head + 1) & 3;
        const uint32_t loc = sb + (i ? SM_TIN1 : SM_TIN0) + head * 6144 + j * 3072;
        const uint32_t dst = opq(mapa(loc, base + d)), rb = opq(mapa(bar + (B_TIN + i) * 8, base + d));
        const uint32_t src = opq(d == (head ^ 1) ? loc : sb + (i ? SM_Q : SM_O) + j * 6144 + (d & 2) * 1536);
        if (!(t & 1)) mbar_wait(bar + (B_TFREE + i) * 8, 0);
        mbar_wait(bar + (B_OTAIL + t) * 8, 0);
        if (lane < 3) copy_remote(dst, src, 3072, rb);
        else if (lane == 3) mbar_arrive(bar + (B_TIN + i) * 8);
        __syncwarp();
      }
    }
    cluster_sync();
  }
}

constexpr int NSTB = 6;
constexpr int NTB = TB * 56;
constexpr int SM_B_ST = 0;
constexpr int SM_B_IN = 73728;
constexpr int SM_B_W = SM_B_IN + 3 * 24576;
constexpr int SM_B_BAR = SM_B_IN + NSTB * 24576;
constexpr int SM_B_TOTAL = SM_B_BAR + 512;
struct MapsB { CUtensorMap oi, oo, wo; };

__global__ void __launch_bounds__(512, 1)
na_proj_kernel(const __grid_constant__ MapsB mp) {
  extern __shared__ __align__(1024) uint8_t smem_raw[];
  const uint32_t sb = smem_u32(smem_raw);
  if ((sb & 0x3FFFF) != SBC) return;
  const uint32_t bar = sb + SM_B_BAR;
  const int tid = threadIdx.x, lane = tid & 31;
  const int warp = __shfl_sync(0xffffffffu, tid >> 5, 0);
  TR2START;
  TRB(47, 0);
  if (warp == 12 && elect_one()) {
#pragma unroll
    for (int i = 0; i <= 2 * NSTB; i++) mbar_init(bar + i * 8, i < NSTB || i == 2 * NSTB ? 1 : 12);
    asm volatile("st.shared.u32 [%0], 0;" ::"r"(bar + 120) : "memory");
    mbar_expect(bar + 2 * NSTB * 8, 73728);
#pragma unroll
    for (int i = 0; i < 2; i++)
      asm volatile("cp.async.bulk.tensor.3d.shared::cluster.global.mbarrier::complete_tx::bytes [%0], [%1, {%3,%4,%5}], [%2];"
                   ::"r"(sb + SM_B_W + i * 36864), "l"(&mp.wo), "r"(bar + 2 * NSTB * 8), "r"(0), "r"(0), "r"(i * 3) : "memory");
  }
  __syncthreads();
  const int step = gridDim.x;
  if (warp == 15) {
    int so = 0;
    nb_arrive(4, 288); nb_arrive(5, 288); nb_arrive(6, 288);
#pragma unroll 1
    for (int n = blockIdx.x, tk = 0; n < NTB; n += step, tk++) {
      uint32_t cc = 0;
#pragma unroll
      for (int wg = 0; wg < 3; wg++) {
        if (lane == 0) asm volatile("cp.async.bulk.wait_group.read 5;" ::: "memory");
        nb_sync(1 + wg, 160);
        if (wg == 0 || n + step < NTB) nb_arrive(4 + wg, 288);
        if (wg == 0) asm volatile("ld.shared.u32 %0, [%1];" : "=r"(cc) : "r"(bar + 128 + tk * 4) : "memory");
        if (lane == 0) {
          asm volatile("cp.async.bulk.tensor.4d.global.shared::cta.bulk_group [%0, {%2,%3,%4,%5}], [%1];"
                       ::"l"(&mp.oo), "r"(sb + SM_B_ST + wg * 8192 + so), "r"(0), "r"((cc >> 8) & 255), "r"(cc >> 16), "r"((cc & 1) * 3 + wg) : "memory");
          asm volatile("cp.async.bulk.commit_group;" ::: "memory");
        }
        __syncwarp();
      }
      so = so == 49152 ? 0 : so + 24576;
    }
    if (lane == 0) asm volatile("cp.async.bulk.wait_group.read 0;" ::: "memory");
  } else if (warp >= 12) {
    nb_sync(7, 480);
#pragma unroll 1
    for (int n = blockIdx.x + (warp - 12) * step; n < NTB; n += 3 * step) {
      const int b = n / 56, rem = n - b * 56, par = rem / 14;
      const int c0 = opq((uint32_t)(par & 1)), c1 = opq((uint32_t)(8 * b)), c2 = opq((uint32_t)((par >> 1) * 112 + (rem - par * 14) * 8));
      int v; uint32_t spin = 0, tk = 0;
      do { asm volatile("ld.acquire.gpu.global.s32 %0, [%1];" : "=r"(v) : "l"(g_flags + n * FS) : "memory"); } while (v < 4 && ++spin < SPIN_LIMIT);
      if (lane == 0) asm volatile("atom.shared.add.u32 %0, [%1], 1;" : "=r"(tk) : "r"(bar + 120) : "memory");
      asm volatile("fence.proxy.async.global;" ::: "memory");
      tk = __shfl_sync(0xffffffffu, tk, 0);
      TRB(tk, 0);
      const uint32_t use = tk / NSTB, sg = tk - use * NSTB;
      if (use) mbar_wait(bar + (NSTB + sg) * 8, (use - 1) & 1);
      TRB(tk, 1);
      if (elect_one()) {
        asm volatile("st.shared.u32 [%0], %1;" ::"r"(bar + 128 + tk * 4), "r"(c0 | c1 << 8 | c2 << 16) : "memory");
        mbar_expect(bar + sg * 8, 24576);
        asm volatile("cp.async.bulk.tensor.3d.shared::cluster.global.mbarrier::complete_tx::bytes [%0], [%1, {%3,%4,%5}], [%2];"
                     ::"r"(sb + SM_B_IN + sg * 24576), "l"(&mp.oi), "r"(bar + sg * 8), "r"(c0 * 192), "r"(c1), "r"(c2) : "memory");
        g_flags[n * FS] = 0;
      }
      __syncwarp();
    }
  } else {
    const int wg = warp >> 2, w = warp & 3;
    uint32_t a[48];
    mbar_wait(bar + 2 * NSTB * 8, 0);
    {
      const int k = (lane & 7) + (lane >> 4) * 8, ch = (warp & 1) * 2 + ((lane >> 3) & 1);
      const uint32_t wa = sb + SM_B_W + (warp >> 1) * 12288 + k * 64 + ((ch ^ ((k >> 1) & 3)) * 16);
#pragma unroll
      for (int i = 0; i < 12; i++)
        asm volatile("ldmatrix.sync.aligned.m8n8.x4.trans.shared.b16 {%0,%1,%2,%3}, [%4];"
                     : "=r"(a[4 * i]), "=r"(a[4 * i + 1]), "=r"(a[4 * i + 2]), "=r"(a[4 * i + 3]) : "r"(wa + i * 1024) : "memory");
    }
    nb_sync(7, 480);
    TRB(47, 1);
    const uint32_t sta = opq(sb + SM_B_ST + wg * 8192 + ((lane & 7) + (lane >> 4) * 8) * 128 + (((2 * w + ((lane >> 3) & 1)) ^ (lane & 7)) * 16));
    const uint32_t hi = opq((uint32_t)(mkdesc(0, 0, 3072, 0) >> 32) + (blockIdx.x >> 16)), bb = opq(bar);
    const uint32_t nbT = opq((uint32_t)(4 + wg)), nbN = opq((uint32_t)(wg == 2 ? 4 : 5 + wg)), nbD = opq((uint32_t)(1 + wg));
    int left = (NTB - blockIdx.x + step - 1) / step;
    if (wg == 2) nb_arrive(4, 288);
#pragma unroll 1
    for (uint32_t ph = 0;; ph ^= 1) {
#pragma unroll
      for (int sg = 0; sg < NSTB; sg++) {
        constexpr uint64_t db = mkdesc(SBC + SM_B_IN, 128, 3072, 0);
        float D[32];
        mbar_wait(bb + sg * 8, ph);
        nb_sync(nbT, 288);
        wg_fence();
        wg_rs64<0>(D, a[0], a[1], a[2], a[3], dsc(db + sg * 1536, hi));
#pragma unroll
        for (int k = 1; k < 12; k++) wg_rs64<1>(D, a[4 * k], a[4 * k + 1], a[4 * k + 2], a[4 * k + 3], dsc(db + sg * 1536 + k * 16, hi));
        wg_commit();
        nb_arrive(nbN, 288);
        wg_wait<0>(); pin(D);
        mbar_arrive_elect(bb + (NSTB + sg) * 8);
#pragma unroll
        for (int q = 0; q < 4; q++)
          asm volatile("stmatrix.sync.aligned.m8n8.x4.trans.shared.b16 [%0], {%1,%2,%3,%4};" ::"r"(sta + (sg % 3) * 24576 + q * 2048),
                       "r"(pack2(D[8 * q], D[8 * q + 1])), "r"(pack2(D[8 * q + 2], D[8 * q + 3])), "r"(pack2(D[8 * q + 4], D[8 * q + 5])), "r"(pack2(D[8 * q + 6], D[8 * q + 7])) : "memory");
        fence_async();
        nb_arrive(nbD, 160);
        if (wg == 0) TRB(31 - left, 5);
        if (--left == 0) goto done;
      }
    }
  done:
    if (wg == 0) nb_arrive(4, 288);
    TR2(132 + blockIdx.x, 2);
    TR2FLUSH(132 + blockIdx.x);
  }
}

typedef CUresult (*EncodeFn)(CUtensorMap*, CUtensorMapDataType, cuuint32_t, void*, const cuuint64_t*, const cuuint64_t*, const cuuint32_t*,
                             const cuuint32_t*, CUtensorMapInterleave, CUtensorMapSwizzle, CUtensorMapL2promotion, CUtensorMapFloatOOBfill);
static EncodeFn g_enc = nullptr;
static void make_map(CUtensorMap* m, const void* p, int rank, const cuuint64_t* dim, const cuuint64_t* str, const cuuint32_t* box, CUtensorMapSwizzle sw) {
  const cuuint32_t ones[5] = {1, 1, 1, 1, 1};
  g_enc(m, CU_TENSOR_MAP_DATA_TYPE_BFLOAT16, rank, (void*)p, dim, str, box, ones, CU_TENSOR_MAP_INTERLEAVE_NONE, sw,
        CU_TENSOR_MAP_L2_PROMOTION_L2_128B, CU_TENSOR_MAP_FLOAT_OOB_FILL_NONE);
}

extern "C" void kernel_launch(void* const* d_in, const int* in_sizes, int n_in, void* d_out, int out_size) {
  const __nv_bfloat16* x = (const __nv_bfloat16*)d_in[0];
  const __nv_bfloat16* wqkv = (const __nv_bfloat16*)d_in[1];
  const __nv_bfloat16* wo = (const __nv_bfloat16*)d_in[2];
  const __nv_bfloat16* rpb = (const __nv_bfloat16*)d_in[3];

  if (!g_enc) {
    void* fn = nullptr; cudaDriverEntryPointQueryResult qr;
    cudaGetDriverEntryPoint("cuTensorMapEncodeTiled", &fn, cudaEnableDefault, &qr);
    g_enc = (EncodeFn)fn;
    cudaFuncSetAttribute(na_attn_kernel, cudaFuncAttributeMaxDynamicSharedMemorySize, SM_A_TOTAL);
    cudaFuncSetAttribute(na_proj_kernel, cudaFuncAttributeMaxDynamicSharedMemorySize, SM_B_TOTAL);
  }
  Maps ma; MapsB mb;
  { cuuint64_t dim[4] = {64, 112, 224, 6}, str[3] = {(cuuint64_t)ROWB, 768, 128};
    cuuint32_t box[4] = {64, 4, 16, 3}, boxh[4] = {64, 16, 3, 3}, boxo[4] = {64, 8, 8, 1};
    make_map(&ma.xc, x, 4, dim, str, box, CU_TENSOR_MAP_SWIZZLE_128B);
    make_map(&ma.xh, x, 4, dim, str, boxh, CU_TENSOR_MAP_SWIZZLE_128B);
    make_map(&mb.oo, d_out, 4, dim, str, boxo, CU_TENSOR_MAP_SWIZZLE_128B); }
  { cuuint64_t dim[3] = {384, 112, 224}, str[2] = {(cuuint64_t)ROWB, 768};
    cuuint32_t box[3] = {192, 8, 8}, boxs[3] = {192, 2, OCH};
    make_map(&mb.oi, d_out, 3, dim, str, box, CU_TENSOR_MAP_SWIZZLE_NONE);
    make_map(&ma.os, d_out, 3, dim, str, boxs, CU_TENSOR_MAP_SWIZZLE_NONE); }
  { cuuint64_t dim[4] = {32, 112, 224, 12}, str[3] = {(cuuint64_t)ROWB, 768, 64};
    cuuint32_t box[4] = {32, 8, 2, 3};
    make_map(&ma.ot, d_out, 4, dim, str, box, CU_TENSOR_MAP_SWIZZLE_64B); }
  { cuuint64_t dim[2] = {576, 192}, str[1] = {1152};
    cuuint32_t box[2] = {16, 192};
    make_map(&ma.w, wqkv, 2, dim, str, box, CU_TENSOR_MAP_SWIZZLE_32B); }
  { cuuint64_t dim[3] = {32, 192, 6}, str[2] = {384, 64};
    cuuint32_t box[3] = {32, 192, 3};
    make_map(&mb.wo, wo, 3, dim, str, box, CU_TENSOR_MAP_SWIZZLE_64B); }
  { cuuint64_t dim[2] = {192, 192}, str[1] = {384};
    cuuint32_t box[2] = {32, 48};
    make_map(&ma.wo, wo, 2, dim, str, box, CU_TENSOR_MAP_SWIZZLE_64B); }
  na_attn_kernel<<<112, 512, SM_A_TOTAL>>>(x, wqkv, rpb, ma);
  cudaLaunchConfig_t cfg = {};
  cfg.gridDim = dim3(20); cfg.blockDim = dim3(512); cfg.dynamicSmemBytes = SM_B_TOTAL; cfg.stream = cudaStreamPerThread;
  cudaLaunchAttribute at[1];
  at[0].id = cudaLaunchAttributeProgrammaticStreamSerialization; at[0].val.programmaticStreamSerializationAllowed = 1;
  cfg.attrs = at; cfg.numAttrs = 1;
  cudaLaunchKernelEx(&cfg, na_proj_kernel, mb);
}
```

```cpp
#include <cuda_runtime.h>
#include <cuda_bf16.h>
#include <cuda.h>
#include <stdint.h>

#define SPIN_LIMIT (1u << 18)

__device__ __forceinline__ uint32_t smem_u32(const void* p) { return (uint32_t)__cvta_generic_to_shared(p); }
__device__ __forceinline__ void wg_fence() { asm volatile("wgmma.fence.sync.aligned;" ::: "memory"); }
__device__ __forceinline__ void wg_commit() { asm volatile("wgmma.commit_group.sync.aligned;" ::: "memory"); }
template <int N> __device__ __forceinline__ void wg_wait() { asm volatile("wgmma.wait_group.sync.aligned %0;" ::"n"(N) : "memory"); }
template <int N> __device__ __forceinline__ void pin(float (&d)[N]) {
#pragma unroll
  for (int i = 0; i < N; i++) asm volatile("" : "+f"(d[i])::"memory");
}
__host__ __device__ constexpr uint64_t mkdesc(uint32_t addr, uint32_t lbo, uint32_t sbo, uint32_t sw) {
  return (uint64_t)((addr & 0x3FFFF) >> 4) | ((uint64_t)(lbo >> 4) << 16) | ((uint64_t)(sbo >> 4) << 32) | ((uint64_t)sw << 62);
}
__device__ __forceinline__ void mbar_init(uint32_t bar, uint32_t cnt) { asm volatile("mbarrier.init.shared::cta.b64 [%0], %1;" ::"r"(bar), "r"(cnt) : "memory"); }
__device__ __forceinline__ void mbar_arrive(uint32_t bar) { asm volatile("mbarrier.arrive.shared::cta.b64 _, [%0];" ::"r"(bar) : "memory"); }
__device__ __forceinline__ bool elect_one() {
  uint32_t r; asm volatile("{\n.reg .pred p;\nelect.sync _|p, 0xffffffff;\nselp.u32 %0, 1, 0, p;\n}" : "=r"(r)); return r;
}
__device__ __forceinline__ void mbar_arrive_elect(uint32_t bar) {
  asm volatile("{\n.reg .pred p;\nelect.sync _|p, 0xffffffff;\n@p mbarrier.arrive.shared::cta.b64 _, [%0];\n}" ::"r"(bar) : "memory");
}
__device__ __forceinline__ void mbar_expect(uint32_t bar, uint32_t bytes) { asm volatile("mbarrier.arrive.expect_tx.shared::cta.b64 _, [%0], %1;" ::"r"(bar), "r"(bytes) : "memory"); }
__device__ __forceinline__ void mbar_arrive_remote(uint32_t bar, uint32_t cta) {
  asm volatile("{\n.reg .b32 ra;\nmapa.shared::cluster.u32 ra, %0, %1;\nmbarrier.arrive.relaxed.cluster.shared::cluster.b64 _, [ra];\n}" ::"r"(bar), "r"(cta) : "memory");
}
__device__ __forceinline__ void mbar_wait(uint32_t bar, uint32_t parity) {
  asm volatile("{\n.reg .pred p;\n.reg .b32 n;\nmov.b32 n, 0;\nWL:\nmbarrier.try_wait.parity.shared::cta.b64 p, [%0], %1;\n@p bra WD;\n"
               "add.u32 n, n, 1;\nsetp.lt.u32 p, n, 65536;\n@p bra WL;\nWD:\n}" ::"r"(bar), "r"(parity) : "memory");
}
__device__ __forceinline__ void nb_sync(int id, int n) { asm volatile("bar.sync %0, %1;" ::"r"(id), "r"(n) : "memory"); }
__device__ __forceinline__ void nb_arrive(int id, int n) { asm volatile("bar.arrive %0, %1;" ::"r"(id), "r"(n) : "memory"); }
__device__ __forceinline__ uint32_t opq(uint32_t x) { uint32_t r; asm volatile("mov.b32 %0, %1;" : "=r"(r) : "r"(x)); return r; }
__device__ __forceinline__ uint64_t opq(uint64_t x) { uint64_t r; asm volatile("mov.b64 %0, %1;" : "=l"(r) : "l"(x)); return r; }
__device__ __forceinline__ uint32_t mapa(uint32_t a, uint32_t cta) { uint32_t r; asm("mapa.shared::cluster.u32 %0, %1, %2;" : "=r"(r) : "r"(a), "r"(cta)); return r; }
__device__ __forceinline__ void fence_async() { asm volatile("fence.proxy.async.shared::cta;" ::: "memory"); }
__device__ __forceinline__ void cluster_sync() {
  asm volatile("barrier.cluster.arrive.relaxed.aligned;\nbarrier.cluster.wait.aligned;" ::: "memory");
}
__device__ __forceinline__ uint32_t pack2(float lo, float hi) {
  uint32_t r; asm("cvt.rn.bf16x2.f32 %0, %1, %2;" : "=r"(r) : "f"(hi), "f"(lo)); return r;
}
__device__ __forceinline__ void stsm4(uint32_t a, uint32_t r0, uint32_t r1, uint32_t r2, uint32_t r3) {
  asm volatile("stmatrix.sync.aligned.m8n8.x4.shared.b16 [%0], {%1,%2,%3,%4};" ::"r"(a), "r"(r0), "r"(r1), "r"(r2), "r"(r3) : "memory");
}
__device__ __forceinline__ void ldsm4(uint32_t a, uint32_t& r0, uint32_t& r1, uint32_t& r2, uint32_t& r3) {
  asm volatile("ldmatrix.sync.aligned.m8n8.x4.shared.b16 {%0,%1,%2,%3}, [%4];" : "=r"(r0), "=r"(r1), "=r"(r2), "=r"(r3) : "r"(a) : "memory");
}
__device__ __forceinline__ void sts128(uint32_t a, uint4 v) {
  asm volatile("st.shared.v4.b32 [%0], {%1,%2,%3,%4};" ::"r"(a), "r"(v.x), "r"(v.y), "r"(v.z), "r"(v.w) : "memory");
}
__device__ __forceinline__ float lds_f32(uint32_t a) { float v; asm volatile("ld.shared.f32 %0, [%1];" : "=f"(v) : "r"(a)); return v; }
__device__ __forceinline__ float ex2(float x) { float y; asm("ex2.approx.ftz.f32 %0, %1;" : "=f"(y) : "f"(x)); return y; }

template<int SC> __device__ __forceinline__ void wg_ss144(float (&d)[72], uint64_t da, uint64_t db) {
  asm volatile("{\n.reg .pred p;\nsetp.ne.b32 p, %74, 0;\nwgmma.mma_async.sync.aligned.m64n144k16.f32.bf16.bf16 {%0,%1,%2,%3,%4,%5,%6,%7,%8,%9,%10,%11,%12,%13,%14,%15,%16,%17,%18,%19,%20,%21,%22,%23,%24,%25,%26,%27,%28,%29,%30,%31,%32,%33,%34,%35,%36,%37,%38,%39,%40,%41,%42,%43,%44,%45,%46,%47,%48,%49,%50,%51,%52,%53,%54,%55,%56,%57,%58,%59,%60,%61,%62,%63,%64,%65,%66,%67,%68,%69,%70,%71}, %72, %73, p, 1, 1, 0, 1;\n}\n"
    : "+f"(d[0]),"+f"(d[1]),"+f"(d[2]),"+f"(d[3]),"+f"(d[4]),"+f"(d[5]),"+f"(d[6]),"+f"(d[7]),"+f"(d[8]),"+f"(d[9]),"+f"(d[10]),"+f"(d[11]),"+f"(d[12]),"+f"(d[13]),"+f"(d[14]),"+f"(d[15]),"+f"(d[16]),"+f"(d[17]),"+f"(d[18]),"+f"(d[19]),"+f"(d[20]),"+f"(d[21]),"+f"(d[22]),"+f"(d[23]),"+f"(d[24]),"+f"(d[25]),"+f"(d[26]),"+f"(d[27]),"+f"(d[28]),"+f"(d[29]),"+f"(d[30]),"+f"(d[31]),"+f"(d[32]),"+f"(d[33]),"+f"(d[34]),"+f"(d[35]),"+f"(d[36]),"+f"(d[37]),"+f"(d[38]),"+f"(d[39]),"+f"(d[40]),"+f"(d[41]),"+f"(d[42]),"+f"(d[43]),"+f"(d[44]),"+f"(d[45]),"+f"(d[46]),"+f"(d[47]),"+f"(d[48]),"+f"(d[49]),"+f"(d[50]),"+f"(d[51]),"+f"(d[52]),"+f"(d[53]),"+f"(d[54]),"+f"(d[55]),"+f"(d[56]),"+f"(d[57]),"+f"(d[58]),"+f"(d[59]),"+f"(d[60]),"+f"(d[61]),"+f"(d[62]),"+f"(d[63]),"+f"(d[64]),"+f"(d[65]),"+f"(d[66]),"+f"(d[67]),"+f"(d[68]),"+f"(d[69]),"+f"(d[70]),"+f"(d[71]) : "l"(da), "l"(db), "n"(SC));
}
template<int SC> __device__ __forceinline__ void wg_ss96(float (&d)[48], uint64_t da, uint64_t db) {
  asm volatile("{\n.reg .pred p;\nsetp.ne.b32 p, %50, 0;\nwgmma.mma_async.sync.aligned.m64n96k16.f32.bf16.bf16 {%0,%1,%2,%3,%4,%5,%6,%7,%8,%9,%10,%11,%12,%13,%14,%15,%16,%17,%18,%19,%20,%21,%22,%23,%24,%25,%26,%27,%28,%29,%30,%31,%32,%33,%34,%35,%36,%37,%38,%39,%40,%41,%42,%43,%44,%45,%46,%47}, %48, %49, p, 1, 1, 0, 1;\n}\n"
    : "+f"(d[0]),"+f"(d[1]),"+f"(d[2]),"+f"(d[3]),"+f"(d[4]),"+f"(d[5]),"+f"(d[6]),"+f"(d[7]),"+f"(d[8]),"+f"(d[9]),"+f"(d[10]),"+f"(d[11]),"+f"(d[12]),"+f"(d[13]),"+f"(d[14]),"+f"(d[15]),"+f"(d[16]),"+f"(d[17]),"+f"(d[18]),"+f"(d[19]),"+f"(d[20]),"+f"(d[21]),"+f"(d[22]),"+f"(d[23]),"+f"(d[24]),"+f"(d[25]),"+f"(d[26]),"+f"(d[27]),"+f"(d[28]),"+f"(d[29]),"+f"(d[30]),"+f"(d[31]),"+f"(d[32]),"+f"(d[33]),"+f"(d[34]),"+f"(d[35]),"+f"(d[36]),"+f"(d[37]),"+f"(d[38]),"+f"(d[39]),"+f"(d[40]),"+f"(d[41]),"+f"(d[42]),"+f"(d[43]),"+f"(d[44]),"+f"(d[45]),"+f"(d[46]),"+f"(d[47]) : "l"(da), "l"(db), "n"(SC));
}
template<int SC> __device__ __forceinline__ void wg_rs112(float (&d)[56], uint32_t a0, uint32_t a1, uint32_t a2, uint32_t a3, uint64_t db) {
  asm volatile("{\n.reg .pred p;\nsetp.ne.b32 p, %61, 0;\nwgmma.mma_async.sync.aligned.m64n112k16.f32.bf16.bf16 {%0,%1,%2,%3,%4,%5,%6,%7,%8,%9,%10,%11,%12,%13,%14,%15,%16,%17,%18,%19,%20,%21,%22,%23,%24,%25,%26,%27,%28,%29,%30,%31,%32,%33,%34,%35,%36,%37,%38,%39,%40,%41,%42,%43,%44,%45,%46,%47,%48,%49,%50,%51,%52,%53,%54,%55}, {%56,%57,%58,%59}, %60, p, 1, 1, 0;\n}\n"
    : "+f"(d[0]),"+f"(d[1]),"+f"(d[2]),"+f"(d[3]),"+f"(d[4]),"+f"(d[5]),"+f"(d[6]),"+f"(d[7]),"+f"(d[8]),"+f"(d[9]),"+f"(d[10]),"+f"(d[11]),"+f"(d[12]),"+f"(d[13]),"+f"(d[14]),"+f"(d[15]),"+f"(d[16]),"+f"(d[17]),"+f"(d[18]),"+f"(d[19]),"+f"(d[20]),"+f"(d[21]),"+f"(d[22]),"+f"(d[23]),"+f"(d[24]),"+f"(d[25]),"+f"(d[26]),"+f"(d[27]),"+f"(d[28]),"+f"(d[29]),"+f"(d[30]),"+f"(d[31]),"+f"(d[32]),"+f"(d[33]),"+f"(d[34]),"+f"(d[35]),"+f"(d[36]),"+f"(d[37]),"+f"(d[38]),"+f"(d[39]),"+f"(d[40]),"+f"(d[41]),"+f"(d[42]),"+f"(d[43]),"+f"(d[44]),"+f"(d[45]),"+f"(d[46]),"+f"(d[47]),"+f"(d[48]),"+f"(d[49]),"+f"(d[50]),"+f"(d[51]),"+f"(d[52]),"+f"(d[53]),"+f"(d[54]),"+f"(d[55]) : "r"(a0), "r"(a1), "r"(a2), "r"(a3), "l"(db), "n"(SC));
}
template<int SC> __device__ __forceinline__ void wg_sp48(float (&d)[24], uint32_t a0, uint32_t a1, uint32_t a2, uint32_t a3, uint64_t db, uint32_t meta) {
  asm volatile("{\n.reg .pred p;\nsetp.ne.b32 p, %30, 0;\nwgmma.mma_async.sp.sync.aligned.m64n48k32.f32.bf16.bf16 {%0,%1,%2,%3,%4,%5,%6,%7,%8,%9,%10,%11,%12,%13,%14,%15,%16,%17,%18,%19,%20,%21,%22,%23}, {%24,%25,%26,%27}, %28, %29, 0, p, 1, 1, 1;\n}\n"
    : "+f"(d[0]),"+f"(d[1]),"+f"(d[2]),"+f"(d[3]),"+f"(d[4]),"+f"(d[5]),"+f"(d[6]),"+f"(d[7]),"+f"(d[8]),"+f"(d[9]),"+f"(d[10]),"+f"(d[11]),"+f"(d[12]),"+f"(d[13]),"+f"(d[14]),"+f"(d[15]),"+f"(d[16]),"+f"(d[17]),"+f"(d[18]),"+f"(d[19]),"+f"(d[20]),"+f"(d[21]),"+f"(d[22]),"+f"(d[23]) : "r"(a0), "r"(a1), "r"(a2), "r"(a3), "l"(db), "r"(meta), "n"(SC));
}
template<int SC> __device__ __forceinline__ void wg_rs64(float (&d)[32], uint32_t a0, uint32_t a1, uint32_t a2, uint32_t a3, uint64_t db) {
  asm volatile("{\n.reg .pred p;\nsetp.ne.b32 p, %37, 0;\nwgmma.mma_async.sync.aligned.m64n64k16.f32.bf16.bf16 {%0,%1,%2,%3,%4,%5,%6,%7,%8,%9,%10,%11,%12,%13,%14,%15,%16,%17,%18,%19,%20,%21,%22,%23,%24,%25,%26,%27,%28,%29,%30,%31}, {%32,%33,%34,%35}, %36, p, 1, 1, 0;\n}\n"
    : "+f"(d[0]),"+f"(d[1]),"+f"(d[2]),"+f"(d[3]),"+f"(d[4]),"+f"(d[5]),"+f"(d[6]),"+f"(d[7]),"+f"(d[8]),"+f"(d[9]),"+f"(d[10]),"+f"(d[11]),"+f"(d[12]),"+f"(d[13]),"+f"(d[14]),"+f"(d[15]),"+f"(d[16]),"+f"(d[17]),"+f"(d[18]),"+f"(d[19]),"+f"(d[20]),"+f"(d[21]),"+f"(d[22]),"+f"(d[23]),"+f"(d[24]),"+f"(d[25]),"+f"(d[26]),"+f"(d[27]),"+f"(d[28]),"+f"(d[29]),"+f"(d[30]),"+f"(d[31]) : "r"(a0), "r"(a1), "r"(a2), "r"(a3), "l"(db), "n"(SC));
}

constexpr uint32_t SBC = 1024;
constexpr int ROWB = 2 * 224 * 384;
constexpr int TB = 11;
constexpr int KS = 832;
constexpr int KSLOT = 22 * KS;
constexpr int SM_X = 0;
constexpr int SM_W = SM_X + 3 * 24576;
constexpr int SM_K = SM_W + 55296;
constexpr int SM_V = SM_K + 2 * KSLOT;
constexpr int SM_Q = SM_V + 22 * 1536;
constexpr int SM_O = SM_Q + 12288;
constexpr int SM_S = SM_O + 12288;
constexpr int SM_RPB = SM_S + 6144;
constexpr int SM_BAR = SM_RPB + 768;
constexpr int SM_TT = SM_BAR + 256;
constexpr int SM_A_TOTAL = SM_TT + 384;
constexpr int SM_TIN0 = SM_X + 24576, SM_TIN1 = SM_X, SM_TIN2 = SM_W + 18432;
constexpr int SM_TWO = SM_X + 2 * 24576;
constexpr int SM_TST = SM_TIN2 + 24576;
enum { B_FULL = 0, B_EMPTY = 3, B_TIN = 6, B_TFREE = 10, B_WK = 12, B_WQ, B_WO, B_KIMP, B_VIMP, B_OFREE, B_XK, B_XV,
       B_Q0, B_WOFREE, B_OTAIL, B_ODONE = B_OTAIL + 4, B_KFREE, B_VFREE, B_COUNT };
enum { N_KRDY = 4, N_QK0, N_QK1, N_VQ0, N_VQ1, N_PVISS, N_Q0 };

#define NL 2
#define OCH 16
#define MID 6
#define SPL 4
#define RA 160
#define RG 168
#define OPT 0
constexpr int FS = 64;
__device__ int g_flags[TB * 56 * FS];

#define TR(role, it, k)
#define TRDECL
#define TRARG
#define TRPASS
#define TRDUMP
#define TRB(it, k)
#define TR2START
#define TR2FLUSH(blk)
#define TR2(blk, k)

struct Stage { uint32_t lo, full, em, par; };
struct GemmCtx {
  uint32_t bar;
  uint32_t kC, vC[2], qC[2];
  uint32_t kH, vH[2];
  uint32_t hiA, hiB;
  uint32_t spin;
  bool hvalid, never, edge;
};

template <int STRIDE> __device__ __forceinline__ void dump12(uint32_t a, const uint32_t (&r)[12]) {
#pragma unroll
  for (int j = 0; j < 3; j++) stsm4(a + j * 2 * STRIDE, r[4 * j], r[4 * j + 1], r[4 * j + 2], r[4 * j + 3]);
}
__device__ __forceinline__ void keep12(bool never, uint32_t a, const uint32_t (&r)[12]) { if (never) dump12<128>(a, r); }
template <int N> __device__ __forceinline__ void pack12(uint32_t (&r)[12], const float (&d)[N], int off) {
#pragma unroll
  for (int j = 0; j < 12; j++) r[j] = pack2(d[off + 2 * j], d[off + 2 * j + 1]);
}
__device__ __forceinline__ uint64_t dsc(uint64_t lo, uint32_t hi) { uint64_t r; asm("mov.b64 %0, {%1, %2};" : "=l"(r) : "r"((uint32_t)lo), "r"(hi)); return r; }
template <int K0, int K1> __device__ __forceinline__ void issue_core(const GemmCtx& c, const Stage& x, float (&d)[72]) {
  constexpr uint64_t db = mkdesc(SBC + SM_W, 6144, 256, 3);
  wg_fence();
  if (K0 == 0) wg_ss144<0>(d, dsc(x.lo, c.hiA), dsc(db, c.hiB));
#pragma unroll
  for (int k = K0 ? K0 : 1; k < K1; k++) wg_ss144<1>(d, dsc(x.lo + (k >> 2) * 512 + (k & 3) * 2, c.hiA), dsc(db + k * 32, c.hiB));
  wg_commit();
}
template <int K0, int K1> __device__ __forceinline__ void issue_halo(const GemmCtx& c, const Stage& x, float (&d)[48]) {
  constexpr uint64_t db = mkdesc(SBC + SM_W + 18432, 6144, 256, 3);
  wg_fence();
  if (K0 == 0) wg_ss96<0>(d, dsc(x.lo, c.hiA), dsc(db, c.hiB));
#pragma unroll
  for (int k = K0 ? K0 : 1; k < K1; k++) wg_ss96<1>(d, dsc(x.lo + (k >> 2) * 384 + (k & 3) * 2, c.hiA), dsc(db + k * 32, c.hiB));
  wg_commit();
}
__device__ __forceinline__ void release_stage(const Stage& x) {
  asm volatile("{\n.reg .pred p;\nelect.sync _|p, 0xffffffff;\n@p mbarrier.arrive.shared::cluster.b64 _, [%0];\n}" ::"r"(x.em) : "memory");
}
__device__ __forceinline__ void wait_stage(GemmCtx& c, Stage& x) {
  asm volatile("{\n.reg .pred p;\nWL:\nmbarrier.try_wait.parity.shared::cta.b64 p, [%1], %2;\n@p bra WD;\n"
               "add.u32 %0, %0, 1;\nsetp.lt.u32 p, %0, 0x100000;\n@p bra WL;\nWD:\n}" : "+&r"(c.spin) : "r"(x.full), "r"(x.par) : "memory");
  x.par ^= 1;
}
__device__ __forceinline__ void edge_ready(const GemmCtx& c, int bar) { __syncwarp(); if (c.edge) mbar_arrive_elect(c.bar + bar * 8); }
__device__ __forceinline__ void dump6(uint32_t a, const uint32_t (&r)[6]) {
  stsm4(a, r[0], r[1], r[2], r[3]);
  asm volatile("stmatrix.sync.aligned.m8n8.x2.shared.b16 [%0], {%1,%2};" ::"r"(a + 512), "r"(r[4]), "r"(r[5]) : "memory");
}
__device__ __forceinline__ void pack6(uint32_t (&r)[6], const float (&d)[48], int off) {
#pragma unroll
  for (int j = 0; j < 6; j++) r[j] = pack2(d[off + 4 * j], d[off + 4 * j + 1]);
}
template <int PARITY> __device__ __forceinline__ void gwait(GemmCtx& c, int bar) {
  asm volatile("{\n.reg .pred p;\nWL:\nmbarrier.try_wait.parity.shared::cta.b64 p, [%1], %2;\n@p bra WD;\n"
               "add.u32 %0, %0, 1;\nsetp.lt.u32 p, %0, 0x100000;\n@p bra WL;\nWD:\n}" : "+&r"(c.spin) : "r"(c.bar + bar * 8), "n"(PARITY) : "memory");
}
__device__ __forceinline__ void load_w(const CUtensorMap* m, uint32_t dst, uint32_t bar, int col) {
  asm volatile("cp.async.bulk.tensor.2d.shared::cluster.global.mbarrier::complete_tx::bytes [%0], [%1, {%3,%4}], [%2];"
               ::"r"(dst), "l"(m), "r"(bar), "r"(col), "r"(0) : "memory");
}
__device__ __forceinline__ void remote_arrive(uint32_t rbar) { asm volatile("mbarrier.arrive.shared::cluster.b64 _, [%0];" ::"r"(rbar) : "memory"); }
__device__ __forceinline__ void remote_expect(uint32_t rbar, uint32_t bytes) {
  asm volatile("mbarrier.arrive.expect_tx.shared::cluster.b64 _, [%0], %1;" ::"r"(rbar), "r"(bytes) : "memory");
}
__device__ __forceinline__ void copy_remote(uint32_t rdst, uint32_t src, uint32_t bytes, uint32_t rbar) {
  asm volatile("cp.async.bulk.shared::cluster.shared::cta.mbarrier::complete_tx::bytes [%0], [%1], %2, [%3];" ::"r"(rdst), "r"(src), "r"(bytes), "r"(rbar) : "memory");
}
__device__ __forceinline__ void tail_free(uint32_t bar) {
  uint32_t ln; asm volatile("mov.u32 %0, %%laneid;" : "=r"(ln));
  if (ln < 4) mbar_arrive_remote(bar, ln + (blockIdx.x & 4));
}
__device__ __forceinline__ void publish(uint32_t bar) {
  fence_async();
  __syncwarp();
  mbar_arrive_elect(bar);
}

template <bool FIRST, int PA>
__device__ __forceinline__ void gemm_iter(GemmCtx& c, int b, uint32_t (&pk)[12], uint32_t (&pv)[12], uint32_t (&pq)[12],
                                          uint32_t (&hk1)[6], uint32_t (&hv1)[6], Stage& x0, Stage& x2, Stage& x1 TRARG) {
  const uint32_t bar = c.bar;
  const bool w = !FIRST && (PA == 0 || b >= 0), never = c.never;
  constexpr uint32_t ko = PA * KSLOT;
  float C[72];
  uint32_t hk0[6], hv0[6], pv2[12];
  TR(2, b, 0);
  if (FIRST) wait_stage(c, x0);
  else dump12<128>(c.qC[1], pq);
  if (w) nb_sync(N_QK1, 256);
  TR(2, b, 2);
  if (FIRST) TR(2, b - 1, 6);
  if (PA == 0) {
    float H[48];
    issue_halo<0, 8>(c, x0, H);
    TR(2, b, 3);
    if (!FIRST) { gwait<0>(c, B_KFREE); dump12<128>(c.kC, pk); }
    issue_halo<8, 12>(c, x0, H);
    TR(2, b, 4);
    wait_stage(c, x2);
    if (FIRST) TR(2, b - 1, 7);
    if (FIRST) gwait<0>(c, B_WQ);
    if (FIRST) TR(2, b - 1, 8);
    issue_core<0, 8>(c, x2, C);
    TR(2, b, 5);
    if (!FIRST) { fence_async(); keep12(never, c.kC, pk); }
    wg_wait<1>(); pin(H);
    release_stage(x0);
    pack6(hk0, H, 0);
    if (c.hvalid) dump6(c.kH, hk0);
    pack6(hk1, H, 2); pack6(hv0, H, 24); pack6(hv1, H, 26);
  } else {
    issue_core<0, 8>(c, x2, C);
    TR(2, b, 5);
    fence_async();
    keep12(never, c.kC, pq);
    if (w) gwait<1>(c, B_KFREE);
    dump12<128>(c.kC + ko, pk);
    if (c.hvalid) dump6(c.kH + ko, hk1);
  }
  TR(2, b, 13);
  issue_core<8, 12>(c, x2, C);
  if (w) { nb_arrive(N_VQ0, 288); nb_arrive(N_VQ1, 288); }
  else if (!FIRST) { __syncwarp(); mbar_arrive_elect(bar + B_Q0 * 8); }
  wait_stage(c, x1);
  if (never) dump6(bar, PA ? hk1 : hk0);
  TR(2, b, 6);
  wg_wait<0>(); pin(C);
  TR(2, b, 7);
  release_stage(x2);
  pack12(pk, C, 24);
  dump12<128>(c.kC + ko + 64, pk);
  pack12(pv2, C, 48);
  pack12(pq, C, 0);
  TR(2, b, 8);
  issue_core<0, SPL>(c, x1, C);
  TR(2, b, 9);
  if (!FIRST) { fence_async(); edge_ready(c, B_XK); }
  keep12(never, c.kC, pk);
  TR(2, b, 14);
  if (w) nb_sync(N_PVISS, 384);
  issue_core<SPL, 12>(c, x1, C);
  if (!FIRST) nb_arrive(N_KRDY, 256);
  TR(2, b, 1);
  if (PA && b == 11) tail_free(bar + B_TFREE * 8);
  wait_stage(c, x0);
  if (w) gwait<PA>(c, B_VFREE);
  if (w && b < TB) gwait<PA>(c, B_ODONE);
  TR(2, b, 10);
  if (!FIRST) dump12<128>(c.vC[PA], pv);
  dump12<128>(c.vC[PA ^ 1] + 768, pv2);
  TR(2, b, 11);
  wg_wait<0>(); pin(C);
  TR(2, b, 12);
  release_stage(x1);
  if (!FIRST && c.edge) publish(bar + B_XV * 8);
  if (c.hvalid) dump6(c.vH[PA], PA ? hv1 : hv0);
  if (PA && !w) nb_sync(N_Q0, 384);
  dump12<128>(c.qC[0], pq);
  pack12(pk, C, 24);
  pack12(pv, C, 48);
  pack12(pq, C, 0);
}

template <int IN> __device__ __forceinline__ void issue_proj(float (&D)[48]) {
  constexpr uint64_t da = mkdesc(SBC + IN, 128, 768, 0), db = mkdesc(SBC + SM_TWO, 12288, 512, 2);
  wg_fence();
  wg_ss96<0>(D, da, db);
#pragma unroll
  for (int k = 1; k < 12; k++) wg_ss96<1>(D, da + (k / 3) * 384 + (k % 3) * 16, db + k * 64);
  wg_commit();
}
template <int ACC> __device__ __forceinline__ void issue_proj_half(float (&D)[48], int hd) {
  const uint64_t da = mkdesc(SBC + SM_TIN2, 128, 768, 0) + hd * 384, db = mkdesc(SBC + SM_TWO, 12288, 512, 2) + hd * 192;
  wg_fence();
  wg_ss96<ACC>(D, da, db);
#pragma unroll
  for (int k = 1; k < 6; k++) wg_ss96<1>(D, da + (k / 3) * 768 + (k % 3) * 16, db + (k / 3) * 384 + (k % 3) * 64);
  wg_commit();
}
__device__ __forceinline__ void store_proj(const float (&D)[48], const CUtensorMap* m, uint32_t st, uint32_t sta, int row, int col, int ch) {
#pragma unroll
  for (int q = 0; q < 6; q++)
    stsm4((sta ^ ((q & 1) * 32)) + (q >> 1) * 1024,
          pack2(D[8 * q], D[8 * q + 1]), pack2(D[8 * q + 2], D[8 * q + 3]), pack2(D[8 * q + 4], D[8 * q + 5]), pack2(D[8 * q + 6], D[8 * q + 7]));
  fence_async();
  __syncwarp();
  if ((threadIdx.x & 31) == 0) {
    asm volatile("cp.async.bulk.tensor.4d.global.shared::cta.bulk_group [%0, {%2,%3,%4,%5}], [%1];" ::"l"(m), "r"(st), "r"(0), "r"(row), "r"(col), "r"(ch) : "memory");
    asm volatile("cp.async.bulk.commit_group;" ::: "memory");
  }
  __syncwarp();
}

__device__ __forceinline__ float fold(float a, float b, float t, int useb) {
  float r;
  asm("{\n.reg .pred p;\nsetp.ne.b32 p, %4, 0;\nfma.rn.f32 %0, %1, 0f3E553B95, %3;\n@p fma.rn.f32 %0, %2, 0f3E553B95, %3;\n}"
      : "=&f"(r) : "f"(a), "f"(b), "f"(t), "r"(useb));
  return r;
}
template <int U, int L>
__device__ __forceinline__ void softmax_tile(const float (&SA)[56], const float (&SB)[56], const float (&T)[16], int b0, int b1,
                                             uint32_t (&P)[28], float (&sx)[8], uint32_t nbV, uint32_t zero, uint32_t qa, uint32_t (&q)[12]) {
  float lu[14], ll[14];
#pragma unroll
  for (int j = 0; j < 7; j++) {
    constexpr int sh = U == L ? 2 : 0;
    const float tu0 = T[2 * j + sh], tu1 = T[2 * j + 1 + sh], tl0 = T[2 * j], tl1 = T[2 * j + 1];
    lu[2 * j]     = fold(SA[4 * (U + j)],     SB[4 * (U + j)],     tu0, b0);
    ll[2 * j]     = fold(SA[4 * (L + j) + 2], SB[4 * (L + j) + 2], tl0, b0);
    lu[2 * j + 1] = fold(SA[4 * (U + j) + 1], SB[4 * (U + j) + 1], tu1, b1);
    ll[2 * j + 1] = fold(SA[4 * (L + j) + 3], SB[4 * (L + j) + 3], tl1, b1);
  }
  float mu = lu[0], ml = ll[0], mu2 = lu[1], ml2 = ll[1];
#pragma unroll
  for (int j = 1; j < 7; j++) { mu = fmaxf(mu, lu[2 * j]); mu2 = fmaxf(mu2, lu[2 * j + 1]); ml = fmaxf(ml, ll[2 * j]); ml2 = fmaxf(ml2, ll[2 * j + 1]); }
  mu = fmaxf(mu, mu2); ml = fmaxf(ml, ml2);
  { const float a1 = __shfl_xor_sync(0xffffffffu, mu, 1), a2 = __shfl_xor_sync(0xffffffffu, mu, 2), a3 = __shfl_xor_sync(0xffffffffu, mu, 3);
    const float c1 = __shfl_xor_sync(0xffffffffu, ml, 1), c2 = __shfl_xor_sync(0xffffffffu, ml, 2), c3 = __shfl_xor_sync(0xffffffffu, ml, 3);
    mu = fmaxf(fmaxf(mu, a1), fmaxf(a2, a3)); ml = fmaxf(fmaxf(ml, c1), fmaxf(c2, c3)); }
  float su = 0.f, sl = 0.f;
#pragma unroll
  for (int c = 0; c < 14; c++) {
    if (c >= U && c < U + 7) {
      float e0 = ex2(lu[2 * (c - U)] - mu), e1 = ex2(lu[2 * (c - U) + 1] - mu);
      su = c == U ? e0 + e1 : (su + e0) + e1; P[2 * c] = pack2(e0, e1);
    } else P[2 * c] = 0u;
  }
  nb_sync(nbV | (P[2 * (U + MID)] & zero), 288);
#pragma unroll
  for (int k = 0; k < 3; k++) ldsm4(qa + k * 256, q[4 * k], q[4 * k + 1], q[4 * k + 2], q[4 * k + 3]);
#pragma unroll
  for (int c = 0; c < 14; c++) {
    if (c >= L && c < L + 7) {
      float e0 = ex2(ll[2 * (c - L)] - ml), e1 = ex2(ll[2 * (c - L) + 1] - ml);
      sl = c == L ? e0 + e1 : (sl + e0) + e1; P[2 * c + 1] = pack2(e0, e1);
    } else P[2 * c + 1] = 0u;
  }
  sx[0] = su; sx[4] = sl;
#pragma unroll
  for (int k = 1; k < 4; k++) sx[k] = __shfl_xor_sync(0xffffffffu, su, k);
#pragma unroll
  for (int k = 1; k < 4; k++) sx[4 + k] = __shfl_xor_sync(0xffffffffu, sl, k);
}

struct BandCfg { uint32_t ra0, ra1, meta; int b0, b1; };
__device__ __forceinline__ void band_cfg(int b, uint32_t tb, BandCfg& n) {
  uint32_t ln; asm volatile("mov.u32 %0, %%laneid;" : "=r"(ln));
  const int g = ln >> 2, t = ln & 3;
  const int sw = min(max(g + 1, b == 0 ? 4 : 0), b == 13 ? 5 : 8);
  const int i0 = 2 * t, i1 = 2 * t + 1;
  n.b0 = i0 <= sw - 2; n.b1 = i1 <= sw - 2;
  n.ra0 = tb + (i0 == sw - 1 ? 13 : i0 + 8 * n.b0 - g + 2) * 52;
  n.ra1 = tb + (i1 == sw - 1 ? 13 : i1 + 8 * n.b1 - g + 2) * 52;
  n.meta = ((0x5555u & ((1u << (2 * (sw - 1))) - 1)) ^ 0xDD88u ^ (((t ^ b) & 1) ? 0x5555u : 0u)) * 0x10001u;
}
__device__ __forceinline__ void band_load(const BandCfg& n, float (&T)[16], int& b0, int& b1, uint32_t& meta) {
#pragma unroll
  for (int jj = 0; jj < 8; jj++) { T[2 * jj] = lds_f32(n.ra0 + jj * 4); T[2 * jj + 1] = lds_f32(n.ra1 + jj * 4); }
  b0 = n.b0; b1 = n.b1; meta = n.meta;
}

struct Maps { CUtensorMap xc, xh, w, os, wo, ot; };

__global__ void __cluster_dims__(8, 1, 1) __launch_bounds__(512, 1)
na_attn_kernel(const __nv_bfloat16* __restrict__ x, const __nv_bfloat16* __restrict__ wqkv, const __nv_bfloat16* __restrict__ rpb, const __grid_constant__ Maps mp) {
  extern __shared__ __align__(1024) uint8_t smem_raw[];
  const uint32_t sb = smem_u32(smem_raw);
  if ((sb & 0x3FFFF) != SBC) return;
  const uint32_t bar = sb + SM_BAR;
  TR2START;
  const int tid = threadIdx.x, lane = tid & 31;
  const int warp = __shfl_sync(0xffffffffu, tid >> 5, 0);
  const int head = blockIdx.x & 3, base = blockIdx.x & 4, sp = blockIdx.x >> 2;
  const int par = sp < 24 ? sp / 6 : sp - 24, strip = sp < 24 ? sp - par * 6 : 6, ph = par >> 1, pw = par & 1;
  const int odd = strip & 1;

  uint4 wv[2 * NL];
  const int va = head == 1;
  const uint32_t wdst = sb + SM_W + (3 + va + ((tid >> 1) & 1)) * 6144 + (tid >> 2) * 32 + ((tid ^ (tid >> 4)) & 1) * 16;
  if (warp < 12) {
    asm volatile("barrier.cluster.arrive.relaxed.aligned;" ::: "memory");
    const uint32_t wo0 = (tid >> 2) * 1152 + head * 96 + va * 32 + (tid & 3) * 16;
#pragma unroll
    for (int i = 0; i < 2 * NL; i++)
      asm volatile("ld.global.nc.v4.b32 {%0,%1,%2,%3}, [%4];" : "=r"(wv[i].x), "=r"(wv[i].y), "=r"(wv[i].z), "=r"(wv[i].w)
                   : "l"(reinterpret_cast<const uint8_t*>(wqkv) + wo0 + (i & 1) * 96 * 1152 + (i / 2 + 1) * 384));
  }
  if (warp < 8) {
    asm volatile("setmaxnreg.inc.sync.aligned.u32 %0;" ::"n"(RA));
    float rv = -INFINITY;
    if (tid < 169) rv = __bfloat162float(rpb[head * 169 + tid]) * 1.4426950408889634f;
    if (tid < 192) {
      const int kc = (tid & 15) + 3, wc = (tid >> 4) % 6;
      sts128(tid < 96 ? sb + SM_K + kc * KS + wc * 128 + 48 : sb + SM_V + kc * 1536 + wc * 128 + (6 + (kc & 1)) * 16, make_uint4(0, 0, 0, 0));
    }
#pragma unroll
    for (int i = 0; i < 2 * NL; i++) sts128(wdst + (i & 1) * 3072 + (i / 2) * 18432, wv[i]);
    fence_async();
    asm volatile("bar.arrive 1, 384;" ::: "memory");
    if (tid < 182) asm volatile("st.shared.f32 [%0], %1;" ::"r"(sb + SM_RPB + tid * 4), "f"(rv) : "memory");
    const int jw = warp >> 2, j = jw ^ odd, w = warp & 3, wt = 4 * j + w;
    int variant = w;
    if (strip == 0 && j == 0 && w < 2) variant = 4;
    if (strip == 6 && j == 1 && w >= 2) variant = 5;
    const bool v1 = opq((uint32_t)(variant & 1)), v2 = opq((uint32_t)(variant & 2)), v4 = opq((uint32_t)(variant & 4));
    const uint32_t qa = opq(sb + SM_Q + (8 * j + 2 * w + ((lane >> 3) & 1)) * 768 + (lane >> 4) * 128 + (((lane & 7) * 16) ^ (((lane >> 3) & 1) * 64)));
    uint32_t oa = opq(sb + SM_O + j * 6144 + (2 * w + ((lane >> 3) & 1)) * 768 + (lane >> 4) * 128 + (lane & 7) * 16);
    uint64_t dA = opq(mkdesc(SBC + SM_K, 128, KS, 0) + j * (8 * KS / 16)), dB = opq(dA + (KSLOT >> 4));
    uint64_t dV[7];
#pragma unroll
    for (int i = 0; i < 7; i++) dV[i] = opq(mkdesc(SBC + SM_V, 768, 128, 0) + j * (8 * 1536 / 16) + i * 192);
    const uint32_t nbK = opq((uint32_t)(N_KRDY + jw)), nbQ = opq((uint32_t)(N_QK0 + jw)), nbV = opq((uint32_t)(N_VQ0 + jw));
    asm volatile("barrier.cluster.wait.aligned;" ::: "memory");
    asm volatile("bar.sync 3, 256;" ::: "memory");
    float T[16];
    TRDECL;
    int b0, b1;
    uint32_t meta, ob = bar + B_ODONE * 8, fb = bar + B_OFREE * 8, fp = 1;
    const uint32_t tb = opq(sb + SM_RPB + (variant < 4 ? 3 : variant + 1 - 2 * w) * 4);
    const bool own = ((w ^ head) & 2) == 0;
    const uint32_t dst13 = sb + SM_TIN2 + head * 6144 + (2 * j + (w & 1)) * 1536, src13 = opq(own ? dst13 : sb + SM_S + (2 * j + (w & 1)) * 1536);
    const uint32_t snd[4] = {opq(own ? 0u : mapa(dst13, base + (head ^ 2))), opq(mapa(bar + (B_TIN + 2) * 8, base + (head ^ 2))),
                             opq(mapa(dst13, base + (w & 2) + (~head & 1))), opq(mapa(bar + (B_TIN + 3) * 8, base + (w & 2) + (~head & 1)))};
    const uint32_t tt = opq(sb + SM_TT + warp * 48 - TB * 16);
    if (lane < 3) {
      const uint32_t s11 = own ? dst13 - (SM_TIN2 - SM_TIN0) : sb + SM_O + wt * 1536, s12 = own ? dst13 - (SM_TIN2 - SM_TIN1) : sb + SM_Q + wt * 1536;
      sts128(tt + (TB + lane) * 16, make_uint4(bar + (lane == 2 ? (own ? B_TIN + 2 : B_ODONE) : B_OTAIL + 2 * lane + jw) * 8,
                                               bar + (lane || own ? B_TFREE + (lane == 2 || (lane && own)) : B_OFREE) * 8, 0,
                                               lane == 0 ? s11 - (sb + SM_O + wt * 1536) : (lane == 1 ? s12 - s11 : src13 - s12)));
    }
    __syncwarp();
    BandCfg nx;
    band_cfg(0, tb, nx);
    band_load(nx, T, b0, b1, meta);
    band_cfg(1, tb, nx);
    const uint32_t zero = opq(blockIdx.x >> 16);
    uint32_t special = opq(0x380Au << 1);
    uint32_t q[12];
    mbar_wait(bar + B_Q0 * 8, 0);
#pragma unroll
    for (int k = 0; k < 3; k++) ldsm4(qa + k * 256, q[4 * k], q[4 * k + 1], q[4 * k + 2], q[4 * k + 3]);
    nb_arrive(N_Q0, 384);
#pragma unroll 1
    for (int b = 0; b < 14; b++) {
      float SA[56], SB[56];
      TR(0, b, 0);
      if (jw) mbar_wait(bar + B_KIMP * 8, b & 1);
      nb_sync(nbK, 256);
      TR(0, b, 1);
      TR(0, b - 1, 9);
      wg_fence();
      wg_rs112<0>(SA, q[0], q[1], q[2], q[3], dA);
      wg_rs112<0>(SB, q[0], q[1], q[2], q[3], dB);
      wg_rs112<1>(SA, q[4], q[5], q[6], q[7], dA + 16);
      wg_rs112<1>(SB, q[4], q[5], q[6], q[7], dB + 16);
      wg_rs112<1>(SA, q[8], q[9], q[10], q[11], dA + 32);
      wg_rs112<1>(SB, q[8], q[9], q[10], q[11], dB + 32);
      wg_commit();
      nb_arrive(nbQ, 256);
      { const uint64_t t = dA; dA = dB; dB = t; }
      special >>= 1;
      if (special & 1) {
        if (b == 3) band_cfg(13, tb, nx);
        else {
          if (b == 1 || b == 13) band_load(nx, T, b0, b1, meta);
          if (b >= TB) {
            uint32_t da;
            asm volatile("ld.shared.v4.b32 {%0,%1,%2,%3}, [%4];" : "=r"(ob), "=r"(fb), "=r"(fp), "=r"(da) : "r"(tt + b * 16));
            oa += da;
          }
        }
      }
      TR(0, b, 2);
      wg_wait<0>(); pin(SA); pin(SB);
      mbar_arrive_elect(bar + B_KFREE * 8);
      TR(0, b, 3);
      TR(0, b - 1, 10);
      uint32_t P[28];
      float sx[8];
      if (v2) {
        if (v1) softmax_tile<6, 7>(SA, SB, T, b0, b1, P, sx, nbV, zero, qa, q); else softmax_tile<4, 5>(SA, SB, T, b0, b1, P, sx, nbV, zero, qa, q);
      } else if (!v4) {
        if (v1) softmax_tile<2, 3>(SA, SB, T, b0, b1, P, sx, nbV, zero, qa, q); else softmax_tile<0, 1>(SA, SB, T, b0, b1, P, sx, nbV, zero, qa, q);
      } else {
        if (v1) softmax_tile<4, 4>(SA, SB, T, b0, b1, P, sx, nbV, zero, qa, q); else softmax_tile<3, 3>(SA, SB, T, b0, b1, P, sx, nbV, zero, qa, q);
      }
      float O[24];
      TR(0, b, 4);
      wg_fence();
      wg_sp48<0>(O, P[0], P[1], P[2], P[3], dV[0], meta);
#pragma unroll
      for (int s = 1; s < 7; s++) wg_sp48<1>(O, P[4 * s], P[4 * s + 1], P[4 * s + 2], P[4 * s + 3], dV[s], meta);
      wg_commit();
      nb_arrive(N_PVISS, 384);
      TR(0, b, 6);
      mbar_wait(fb, fp);
      wg_wait<0>(); pin(O);
      mbar_arrive_elect(bar + B_VFREE * 8);
      TR(0, b, 7);
      float ru, rl;
      asm("rcp.approx.ftz.f32 %0, %1;" : "=f"(ru) : "f"(((fmaf(O[0], 0.f, sx[0]) + sx[1]) + sx[2]) + sx[3]));
      asm("rcp.approx.ftz.f32 %0, %1;" : "=f"(rl) : "f"(((fmaf(O[2], 0.f, sx[4]) + sx[5]) + sx[6]) + sx[7]));
#pragma unroll
      for (int i = 0; i < 3; i++)
        stsm4(oa + i * 256, pack2(O[8 * i] * ru, O[8 * i + 1] * ru), pack2(O[8 * i + 2] * rl, O[8 * i + 3] * rl),
              pack2(O[8 * i + 4] * ru, O[8 * i + 5] * ru), pack2(O[8 * i + 6] * rl, O[8 * i + 7] * rl));
      publish(ob);
      fp ^= 1;
      meta ^= 0x55555555u;
      TR(0, b, 8);
    }
    asm volatile("{\n.reg .pred p, q;\nsetp.ne.b32 q, %1, 0;\nelect.sync _|p, 0xffffffff;\nand.pred q, q, p;\n"
                 "@q cp.async.bulk.shared::cluster.shared::cta.mbarrier::complete_tx::bytes [%1], [%0], 1536, [%2];\n"
                 "@p cp.async.bulk.shared::cluster.shared::cta.mbarrier::complete_tx::bytes [%3], [%0], 1536, [%4];\n}"
                 ::"r"(src13), "r"(snd[0]), "r"(snd[1]), "r"(snd[2]), "r"(snd[3]) : "memory");
    nb_arrive(3, 384);
    TRDUMP;
    cluster_sync();
  } else if (warp < 12) {
    TRDECL;
    TR(2, -3, 0);
    asm volatile("setmaxnreg.inc.sync.aligned.u32 %0;" ::"n"(RG));
    TR(2, -3, 1);
    GemmCtx c;
    c.bar = bar;
    const int gw = warp - 8, tk = gw * 16 + (lane & 15), hi = lane >> 4;
    { const int col = tk >> 2, i = tk & 3;
      c.kC = sb + SM_K + (col + 3) * KS + hi * 128 + i * 16;
      c.vC[0] = sb + SM_V + (col + 3) * 1536 + hi * 128 + (2 * i + ((col + 3) & 1)) * 16;
      c.qC[0] = sb + SM_Q + col * 768 + hi * 128 + (col & 1) * 64 + i * 16; }
    { const int kc = gw - 1 + 19 * odd, i = lane & 7; c.hvalid = gw > 0; c.edge = gw == (odd ? 0 : 3);
      c.kH = sb + SM_K + kc * KS + (lane >> 3) * 128 + i * 16;
      c.vH[0] = sb + SM_V + kc * 1536 + (lane >> 3) * 128 + (i >> 2) * 768 + (2 * (i & 3) + ((kc ^ (i >> 2)) & 1)) * 16; }
    Stage xs[3];
#pragma unroll
    for (int i = 0; i < 3; i++) {
      const int p = (i + 1) % 3;
      xs[i].lo = (uint32_t)mkdesc(SBC + SM_X + p * 24576, 16, 0, 0); xs[i].full = bar + (B_FULL + p) * 8;
      xs[i].em = opq(mapa(bar + (B_EMPTY + p) * 8, base + p)); xs[i].par = 0;
    }
    c.never = x == nullptr;
    c.kC = opq(c.kC); c.kH = opq(c.kH);
    c.vC[1] = opq(c.vC[0] ^ 16); c.vC[0] = opq(c.vC[0]);
    c.vH[1] = opq(c.vH[0] ^ 16); c.vH[0] = opq(c.vH[0]);
    c.qC[1] = opq(c.qC[0] ^ 64); c.qC[0] = opq(c.qC[0]);
    c.spin = 0;
    c.hiA = (uint32_t)(mkdesc(0, 0, 1024, 1) >> 32) + (blockIdx.x >> 16); c.hiB = (uint32_t)(mkdesc(0, 0, 256, 3) >> 32) + (blockIdx.x >> 16);
    asm volatile("barrier.cluster.wait.aligned;" ::: "memory");
    TR(2, -3, 2);
#pragma unroll
    for (int i = 0; i < 2 * NL; i++) sts128(wdst + (i & 1) * 3072 + (i / 2) * 18432, wv[i]);
    fence_async();
    TR(2, -3, 3);
    asm volatile("bar.sync 1, 384;" ::: "memory");
    TR(2, -3, 4);
    mbar_wait(bar + B_WK * 8, 0);
    asm volatile("griddepcontrol.launch_dependents;");
    TR(2, -3, 5);
    uint32_t pk[12], pv[12], pq[12], hk1[6], hv1[6];
    gemm_iter<true, 0>(c, -2, pk, pv, pq, hk1, hv1, xs[0], xs[1], xs[2] TRPASS);
    TR2(blockIdx.x, 4);
    c.hiA = opq(c.hiA); c.hiB = opq(c.hiB);
#pragma unroll 1
    for (int b = -1;; b += 2) {
      gemm_iter<false, 1>(c, b, pk, pv, pq, hk1, hv1, xs[2], xs[0], xs[1] TRPASS);
      if (b == 11) break;
      gemm_iter<false, 0>(c, b + 1, pk, pv, pq, hk1, hv1, xs[2], xs[0], xs[1] TRPASS);
      const Stage t = xs[2]; xs[2] = xs[1]; xs[1] = xs[0]; xs[0] = t;
    }
    TR2(blockIdx.x, 6);
    c.hiA = opq(c.hiA); c.hiB = opq(c.hiB);
    const uint32_t st = sb + gw * 3072;
    const uint32_t sta = st + (lane & 15) * 64 + ((hi ^ ((lane >> 1) & 3)) * 16);
    const int oc = ph * 112 + strip * 16 + 8 * (gw >> 1) + 4 * (head >> 1) + 2 * (gw & 1), och = pw * 6 + (head & 1) * 3;
    const uint32_t so = (~head & 2) * 6144;
    float D0[48], D1[48];
    if (lane < 4) mbar_arrive_remote(bar + B_WOFREE * 8, 2 * lane + (head & 1));
    dump12<128>(c.qC[1], pq);
    nb_sync(N_QK1, 256);
    issue_halo<0, 8>(c, xs[2], D1);
    fence_async();
    nb_arrive(N_VQ0, 288); nb_arrive(N_VQ1, 288); nb_arrive(N_PVISS, 384);
    issue_halo<8, 12>(c, xs[2], D1);
    gwait<0>(c, B_KFREE);
    dump12<128>(c.kC, pk);
    if (c.edge) publish(bar + B_XK * 8);
    wg_wait<0>(); pin(D1);
    pack6(hk1, D1, 0);
    if (c.hvalid) dump6(c.kH, hk1);
    tail_free(bar + (B_TFREE + 1) * 8);
    pack6(hv1, D1, 24);
    fence_async();
    nb_arrive(N_KRDY, 256);
    gwait<0>(c, B_VFREE);
    dump12<128>(c.vC[0], pv);
    if (c.hvalid) dump6(c.vH[0], hv1);
    fence_async();
    edge_ready(c, B_XV);
    nb_arrive(N_VQ0, 288); nb_arrive(N_VQ1, 288);
    gwait<0>(c, B_WO);
    gwait<0>(c, B_TIN);
    TR(2, 13, 0);
    nb_sync(N_QK1, 256);
    issue_proj<SM_TIN0>(D0);
    wg_wait<0>(); pin(D0);
    TR(2, 13, 1);
    store_proj(D0, &mp.ot, st + SM_TST, sta + SM_TST, 8 * TB, oc, och);
    gwait<0>(c, B_TIN + 1);
    TR(2, 13, 2);
    nb_arrive(N_PVISS, 384);
    nb_sync(3, 384);
    issue_proj<SM_TIN1>(D1);
    wg_wait<0>(); pin(D1);
    TR(2, 13, 3);
    store_proj(D1, &mp.ot, st + SM_TIN0 + so, sta + SM_TIN0 + so, 8 * TB + 8, oc, och);
    TR(2, 13, 4);
    gwait<0>(c, B_TIN + 2);
    TR(2, 13, 5);
    issue_proj_half<0>(D0, head & 1);
    gwait<0>(c, B_TIN + 3);
    TR(2, 13, 6);
    issue_proj_half<1>(D0, ~head & 1);
    asm volatile("barrier.cluster.arrive.relaxed.aligned;" ::: "memory");
    wg_wait<0>(); pin(D0);
    store_proj(D0, &mp.ot, st + SM_TIN1 + so, sta + SM_TIN1 + so, 8 * TB + 16, oc, och);
    TR(2, 13, 7);
    if (lane == 0) asm volatile("cp.async.bulk.wait_group.read 0;" ::: "memory");
    __syncwarp();
    TR(2, 13, 8);
    TR2(blockIdx.x, 2);
    TR2FLUSH(blockIdx.x);
    TRDUMP;
    asm volatile("barrier.cluster.wait.aligned;" ::: "memory");
  } else {
    asm volatile("setmaxnreg.dec.sync.aligned.u32 24;");
    if (warp == 15) {
      const int l = min(lane, 24), row = head + (l < 16 ? 0 : 4 * ((l - 16) / 3)), col = strip * 16 + (l < 16 ? l : (l - 16) % 3 + (odd ? 16 : (strip ? -3 : 0)));
      const uint8_t* p = reinterpret_cast<const uint8_t*>(x) + (uint32_t)(row * ROWB + (ph * 112 + col) * 768 + pw * 384);
#pragma unroll
      for (int i = 0; i < 3; i++) asm volatile("prefetch.global.L2 [%0];" ::"l"(p + i * 128));
    } else if (elect_one()) {
      if (warp == 12) {
        mbar_init(bar + B_WK * 8, 1);
#pragma unroll
        for (int i = 0; i < NL; i++) load_w(&mp.w, sb + SM_W + (3 * i + 5 - 2 * va) * 6144, bar + B_WK * 8, (i + 1) * 192 + head * 48 + 32 - 32 * va);
        asm volatile("prefetch.tensormap [%0];" ::"l"(head == 1 ? &mp.xh : &mp.xc) : "memory");
      } else if (warp == 13) {
#pragma unroll
        for (int i = 0; i < B_XK; i++) if (i != B_WK) mbar_init(bar + i * 8, (i >= B_EMPTY && i < B_TIN) || (i >= B_TFREE && i < B_WK) ? 16 : (i == B_TIN + 2 ? 5 : (i == B_TIN || i == B_TIN + 1 ? 3 : 1)));
      } else {
#pragma unroll
        for (int i = B_XK; i < B_COUNT; i++) mbar_init(bar + i * 8, i < B_Q0 ? 2 : (i < B_ODONE ? (i == B_WOFREE ? 16 : 4) : (i == B_VFREE ? 9 : 8)));
        mbar_arrive(bar + B_XK * 8); mbar_arrive(bar + B_XV * 8);
      }
      asm volatile("fence.mbarrier_init.release.cluster;" ::: "memory");
    }
    __syncwarp();
    asm volatile("barrier.cluster.arrive.relaxed.aligned;" ::: "memory");
    if (warp != 12) asm volatile("barrier.cluster.wait.aligned;" ::: "memory");
    else {
      const int cc = ph * 112 + strip * 16, ch = cc + (odd ? 16 : (strip ? -3 : 0)), rh = strip ? -4 : 112;
      const uint32_t fb = opq(bar + (B_FULL + head) * 8), dst0 = sb + SM_X + head * 24576, c3 = opq((uint32_t)(pw * 3)), mask = opq(15u << base);
      int t = head == 0 ? 2 : head - 1;
      uint64_t mx = opq((uint64_t)(t ? &mp.xc : &mp.xh));
      uint32_t row = opq((uint32_t)(t ? 4 * t - 4 : rh)), col = opq((uint32_t)(t ? cc : ch)), dst = opq(dst0 + (t ? 0 : 2048));
#pragma unroll 1
      for (int n = 0;; n++) {
        if (n) mbar_wait(fb + (B_EMPTY - B_FULL) * 8, ~n & 1);
        else asm volatile("barrier.cluster.wait.aligned;" ::: "memory");
        if (head < 3) {
          asm volatile("{\n.reg .pred p;\n.reg .b16 m;\nelect.sync _|p, 0xffffffff;\ncvt.u16.u32 m, %7;\n"
                       "@p cp.async.bulk.tensor.4d.shared::cluster.global.mbarrier::complete_tx::bytes.multicast::cluster [%0], [%1, {%3,%4,%5,%6}], [%2], m;\n}"
                       ::"r"(dst), "l"(mx), "r"(fb), "r"(0), "r"(row), "r"(col), "r"(c3), "r"(mask) : "memory");
          if (lane < 4) remote_expect(mapa(fb, base + lane), dst == dst0 ? 24576 : 18432);
          __syncwarp();
        }
        if (n == 0 && elect_one()) {
#pragma unroll
          for (int i = 0; i < 3; i++) load_w(&mp.w, sb + SM_W + i * 6144, bar + B_WQ * 8, head * 48 + i * 16);
          mbar_expect(bar + B_WQ * 8, 18432);
        }
        __syncwarp();
        if (head == 3 || n == 11) break;
        t += 3;
        const int hn = t / 5;
        const bool core = t != 5 * hn;
        mx = opq((uint64_t)(core ? &mp.xc : &mp.xh));
        row = opq((uint32_t)(core ? 4 * (t - hn - 1) : rh + 16 * hn)); col = opq((uint32_t)(core ? cc : ch)); dst = opq(dst0 + (core ? 0 : 2048));
        if (elect_one()) asm volatile("cp.async.bulk.prefetch.tensor.4d.L2.global [%0, {%1,%2,%3,%4}];" ::"l"(mx), "r"(0), "r"(row), "r"(col), "r"(c3) : "memory");
        __syncwarp();
      }
      mbar_wait(bar + B_WOFREE * 8, 0);
      if (elect_one()) {
        const int qr = (blockIdx.x & 7) >> 1;
#pragma unroll
        for (int i = 0; i < 3; i++)
          asm volatile("cp.async.bulk.tensor.2d.shared::cluster.global.mbarrier::complete_tx::bytes.multicast::cluster [%0], [%1, {%3,%4}], [%2], %5;"
                       ::"r"(sb + SM_TWO + i * 12288 + qr * 3072), "l"(&mp.wo), "r"(bar + B_WO * 8), "r"((head & 1) * 96 + i * 32), "r"(qr * 48),
                         "h"((uint16_t)(0x55 << (head & 1))) : "memory");
      }
      __syncwarp();
    }
    if (warp & 1) {
      const uint32_t partner = (blockIdx.x & 7) ^ 4;
      const int cs = odd ? 3 : (strip == 6 ? 15 : 16), cd = odd || strip == 6 ? 19 : 0;
      const uint32_t rb = opq(mapa(bar, partner));
      TRDECL;
      if (warp == 13) {
        const uint32_t dst = opq(mapa(sb + SM_V + cd * 1536, partner)), src = opq(sb + SM_V + cs * 1536);
#pragma unroll 1
        for (int b = 0;; b++) {
          const uint32_t pa = b & 1;
          nb_arrive(N_VQ0, 288);
          mbar_wait(bar + B_XV * 8, pa);
          TR(1, b, 0);
          if (elect_one()) { copy_remote(dst, src, 4608, rb + B_VIMP * 8); remote_expect(rb + B_VIMP * 8, 4608); }
          __syncwarp();
          TR(1, b, 1);
          mbar_wait(bar + B_VIMP * 8, pa);
          TR(1, b, 2);
          nb_arrive(N_VQ1, 288);
          if (elect_one()) remote_arrive(rb + B_VFREE * 8);
          __syncwarp();
          TR(1, b, 3);
          if (b == 13) break;
          mbar_wait(bar + B_VFREE * 8, pa);
          if (elect_one()) remote_arrive(rb + B_XV * 8);
          __syncwarp();
        }
      } else {
        const uint32_t dst = opq(mapa(sb + SM_K + cd * KS, partner)), src = opq(sb + SM_K + cs * KS);
#pragma unroll 1
        for (int b = 0;; b++) {
          const uint32_t pa = b & 1, so = (pa ^ 1) * KSLOT;
          mbar_wait(bar + B_XK * 8, pa);
          TR(1, b - 1, 4);
          if (elect_one()) {
            copy_remote(dst + so, src + so, 3 * KS, rb + B_KIMP * 8);
            if (b == 0) copy_remote(dst, src, 3 * KS, rb + B_KIMP * 8);
            remote_expect(rb + B_KIMP * 8, b ? 3 * KS : 6 * KS);
          }
          __syncwarp();
          TR(1, b - 1, 5);
          TR(1, b - 1, 7);
          if (b == 13) break;
          mbar_wait(bar + B_KFREE * 8, pa);
          if (elect_one()) remote_arrive(rb + B_XK * 8);
          __syncwarp();
        }
      }
      TRDUMP;
    }
    if (warp == 14) {
      int* flag = g_flags + (par * 7 + strip) * 2 * FS;
      if (elect_one()) {
        mbar_expect(bar + B_WK * 8, NL * 6144);
        mbar_expect(bar + B_WO * 8, 36864);
        mbar_expect(bar + B_TIN * 8, 18432); mbar_expect(bar + (B_TIN + 1) * 8, 18432); mbar_expect(bar + (B_TIN + 2) * 8, 6144); mbar_expect(bar + (B_TIN + 3) * 8, 12288);
      }
      __syncwarp();
#pragma unroll 1
      for (int b = 0; b < TB; b++) {
        mbar_wait(bar + B_ODONE * 8, b & 1);
        if (lane == 0) {
#pragma unroll 1
          for (int i = 0; i < 16; i += OCH) {
            asm volatile("cp.async.bulk.tensor.3d.global.shared::cta.bulk_group [%0, {%2,%3,%4}], [%1];"
                         ::"l"(&mp.os), "r"(sb + SM_O + i * 768), "r"(pw * 192), "r"(8 * b + 2 * head), "r"(ph * 112 + strip * 16 + i) : "memory");
            asm volatile("cp.async.bulk.commit_group;\ncp.async.bulk.wait_group 0;" ::: "memory");
          }
        }
        __syncwarp();
        mbar_arrive_elect(bar + B_OFREE * 8);
        if (lane == 0)
          asm volatile("fence.proxy.async.global;\nfence.acq_rel.gpu;\nred.relaxed.gpu.global.add.s32 [%0], 1;\nred.relaxed.gpu.global.add.s32 [%1], 1;"
                       ::"l"(flag + b * 56 * FS), "l"(flag + (b * 56 + 1) * FS) : "memory");
        __syncwarp();
      }
#pragma unroll 1
      for (int t = 0; t < 4; t++) {
        const int i = t >> 1, j = (t ^ odd) & 1, d = (lane + head + 1) & 3;
        const uint32_t loc = sb + (i ? SM_TIN1 : SM_TIN0) + head * 6144 + j * 3072;
        const uint32_t dst = opq(mapa(loc, base + d)), rb = opq(mapa(bar + (B_TIN + i) * 8, base + d));
        const uint32_t src = opq(d == (head ^ 1) ? loc : sb + (i ? SM_Q : SM_O) + j * 6144 + (d & 2) * 1536);
        if (!(t & 1)) mbar_wait(bar + (B_TFREE + i) * 8, 0);
        mbar_wait(bar + (B_OTAIL + t) * 8, 0);
        if (lane < 3) copy_remote(dst, src, 3072, rb);
        else if (lane == 3) mbar_arrive(bar + (B_TIN + i) * 8);
        __syncwarp();
      }
    }
    cluster_sync();
  }
}

constexpr int NSTB = 6;
constexpr int NTB = TB * 56;
constexpr int SM_B_ST = 0;
constexpr int SM_B_IN = 73728;
constexpr int SM_B_W = SM_B_IN + 3 * 24576;
constexpr int SM_B_BAR = SM_B_IN + NSTB * 24576;
constexpr int SM_B_TOTAL = SM_B_BAR + 512;
struct MapsB { CUtensorMap oi, oo, wo; };

__global__ void __launch_bounds__(512, 1)
na_proj_kernel(const __grid_constant__ MapsB mp) {
  extern __shared__ __align__(1024) uint8_t smem_raw[];
  const uint32_t sb = smem_u32(smem_raw);
  if ((sb & 0x3FFFF) != SBC) return;
  const uint32_t bar = sb + SM_B_BAR;
  const int tid = threadIdx.x, lane = tid & 31;
  const int warp = __shfl_sync(0xffffffffu, tid >> 5, 0);
  TR2START;
  TRB(47, 0);
  if (warp == 12 && elect_one()) {
#pragma unroll
    for (int i = 0; i <= 2 * NSTB; i++) mbar_init(bar + i * 8, i < NSTB || i == 2 * NSTB ? 1 : 12);
    asm volatile("st.shared.u32 [%0], 0;" ::"r"(bar + 120) : "memory");
    mbar_expect(bar + 2 * NSTB * 8, 73728);
#pragma unroll
    for (int i = 0; i < 2; i++)
      asm volatile("cp.async.bulk.tensor.3d.shared::cluster.global.mbarrier::complete_tx::bytes [%0], [%1, {%3,%4,%5}], [%2];"
                   ::"r"(sb + SM_B_W + i * 36864), "l"(&mp.wo), "r"(bar + 2 * NSTB * 8), "r"(0), "r"(0), "r"(i * 3) : "memory");
  }
  __syncthreads();
  const int step = gridDim.x;
  if (warp == 15) {
    int so = 0;
    nb_arrive(4, 288); nb_arrive(5, 288); nb_arrive(6, 288);
#pragma unroll 1
    for (int n = blockIdx.x, tk = 0; n < NTB; n += step, tk++) {
      uint32_t cc = 0;
#pragma unroll
      for (int wg = 0; wg < 3; wg++) {
        if (lane == 0) asm volatile("cp.async.bulk.wait_group.read 5;" ::: "memory");
        nb_sync(1 + wg, 160);
        if (wg == 0 || n + step < NTB) nb_arrive(4 + wg, 288);
        if (wg == 0) asm volatile("ld.shared.u32 %0, [%1];" : "=r"(cc) : "r"(bar + 128 + tk * 4) : "memory");
        if (lane == 0) {
          asm volatile("cp.async.bulk.tensor.4d.global.shared::cta.bulk_group [%0, {%2,%3,%4,%5}], [%1];"
                       ::"l"(&mp.oo), "r"(sb + SM_B_ST + wg * 8192 + so), "r"(0), "r"((cc >> 8) & 255), "r"(cc >> 16), "r"((cc & 1) * 3 + wg) : "memory");
          asm volatile("cp.async.bulk.commit_group;" ::: "memory");
        }
        __syncwarp();
      }
      so = so == 49152 ? 0 : so + 24576;
    }
    if (lane == 0) asm volatile("cp.async.bulk.wait_group.read 0;" ::: "memory");
  } else if (warp >= 12) {
    nb_sync(7, 480);
#pragma unroll 1
    for (int n = blockIdx.x + (warp - 12) * step; n < NTB; n += 3 * step) {
      const int b = n / 56, rem = n - b * 56, par = rem / 14;
      const int c0 = opq((uint32_t)(par & 1)), c1 = opq((uint32_t)(8 * b)), c2 = opq((uint32_t)((par >> 1) * 112 + (rem - par * 14) * 8));
      int v; uint32_t spin = 0, tk = 0;
      do { asm volatile("ld.acquire.gpu.global.s32 %0, [%1];" : "=r"(v) : "l"(g_flags + n * FS) : "memory"); } while (v < 4 && ++spin < SPIN_LIMIT);
      if (lane == 0) asm volatile("atom.shared.add.u32 %0, [%1], 1;" : "=r"(tk) : "r"(bar + 120) : "memory");
      asm volatile("fence.proxy.async.global;" ::: "memory");
      tk = __shfl_sync(0xffffffffu, tk, 0);
      TRB(tk, 0);
      const uint32_t use = tk / NSTB, sg = tk - use * NSTB;
      if (use) mbar_wait(bar + (NSTB + sg) * 8, (use - 1) & 1);
      TRB(tk, 1);
      if (elect_one()) {
        asm volatile("st.shared.u32 [%0], %1;" ::"r"(bar + 128 + tk * 4), "r"(c0 | c1 << 8 | c2 << 16) : "memory");
        mbar_expect(bar + sg * 8, 24576);
        asm volatile("cp.async.bulk.tensor.3d.shared::cluster.global.mbarrier::complete_tx::bytes [%0], [%1, {%3,%4,%5}], [%2];"
                     ::"r"(sb + SM_B_IN + sg * 24576), "l"(&mp.oi), "r"(bar + sg * 8), "r"(c0 * 192), "r"(c1), "r"(c2) : "memory");
        g_flags[n * FS] = 0;
      }
      __syncwarp();
    }
  } else {
    const int wg = warp >> 2, w = warp & 3;
    uint32_t a[48];
    mbar_wait(bar + 2 * NSTB * 8, 0);
    {
      const int k = (lane & 7) + (lane >> 4) * 8, ch = (warp & 1) * 2 + ((lane >> 3) & 1);
      const uint32_t wa = sb + SM_B_W + (warp >> 1) * 12288 + k * 64 + ((ch ^ ((k >> 1) & 3)) * 16);
#pragma unroll
      for (int i = 0; i < 12; i++)
        asm volatile("ldmatrix.sync.aligned.m8n8.x4.trans.shared.b16 {%0,%1,%2,%3}, [%4];"
                     : "=r"(a[4 * i]), "=r"(a[4 * i + 1]), "=r"(a[4 * i + 2]), "=r"(a[4 * i + 3]) : "r"(wa + i * 1024) : "memory");
    }
    nb_sync(7, 480);
    TRB(47, 1);
    const uint32_t sta = opq(sb + SM_B_ST + wg * 8192 + ((lane & 7) + (lane >> 4) * 8) * 128 + (((2 * w + ((lane >> 3) & 1)) ^ (lane & 7)) * 16));
    const uint32_t hi = opq((uint32_t)(mkdesc(0, 0, 3072, 0) >> 32) + (blockIdx.x >> 16)), bb = opq(bar);
    const uint32_t nbT = opq((uint32_t)(4 + wg)), nbN = opq((uint32_t)(wg == 2 ? 4 : 5 + wg)), nbD = opq((uint32_t)(1 + wg));
    int left = (NTB - blockIdx.x + step - 1) / step;
    if (wg == 2) nb_arrive(4, 288);
#pragma unroll 1
    for (uint32_t ph = 0;; ph ^= 1) {
#pragma unroll
      for (int sg = 0; sg < NSTB; sg++) {
        constexpr uint64_t db = mkdesc(SBC + SM_B_IN, 128, 3072, 0);
        float D[32];
        mbar_wait(bb + sg * 8, ph);
        nb_sync(nbT, 288);
        wg_fence();
        wg_rs64<0>(D, a[0], a[1], a[2], a[3], dsc(db + sg * 1536, hi));
#pragma unroll
        for (int k = 1; k < 12; k++) wg_rs64<1>(D, a[4 * k], a[4 * k + 1], a[4 * k + 2], a[4 * k + 3], dsc(db + sg * 1536 + k * 16, hi));
        wg_commit();
        nb_arrive(nbN, 288);
        wg_wait<0>(); pin(D);
        mbar_arrive_elect(bb + (NSTB + sg) * 8);
#pragma unroll
        for (int q = 0; q < 4; q++)
          asm volatile("stmatrix.sync.aligned.m8n8.x4.trans.shared.b16 [%0], {%1,%2,%3,%4};" ::"r"(sta + (sg % 3) * 24576 + q * 2048),
                       "r"(pack2(D[8 * q], D[8 * q + 1])), "r"(pack2(D[8 * q + 2], D[8 * q + 3])), "r"(pack2(D[8 * q + 4], D[8 * q + 5])), "r"(pack2(D[8 * q + 6], D[8 * q + 7])) : "memory");
        fence_async();
        nb_arrive(nbD, 160);
        if (wg == 0) TRB(31 - left, 5);
        if (--left == 0) goto done;
      }
    }
  done:
    if (wg == 0) nb_arrive(4, 288);
    TR2(132 + blockIdx.x, 2);
    TR2FLUSH(132 + blockIdx.x);
  }
}

typedef CUresult (*EncodeFn)(CUtensorMap*, CUtensorMapDataType, cuuint32_t, void*, const cuuint64_t*, const cuuint64_t*, const cuuint32_t*,
                             const cuuint32_t*, CUtensorMapInterleave, CUtensorMapSwizzle, CUtensorMapL2promotion, CUtensorMapFloatOOBfill);
static EncodeFn g_enc = nullptr;
static void make_map(CUtensorMap* m, const void* p, int rank, const cuuint64_t* dim, const cuuint64_t* str, const cuuint32_t* box, CUtensorMapSwizzle sw) {
  const cuuint32_t ones[5] = {1, 1, 1, 1, 1};
  g_enc(m, CU_TENSOR_MAP_DATA_TYPE_BFLOAT16, rank, (void*)p, dim, str, box, ones, CU_TENSOR_MAP_INTERLEAVE_NONE, sw,
        CU_TENSOR_MAP_L2_PROMOTION_L2_128B, CU_TENSOR_MAP_FLOAT_OOB_FILL_NONE);
}

extern "C" void kernel_launch(void* const* d_in, const int* in_sizes, int n_in, void* d_out, int out_size) {
  const __nv_bfloat16* x = (const __nv_bfloat16*)d_in[0];
  const __nv_bfloat16* wqkv = (const __nv_bfloat16*)d_in[1];
  const __nv_bfloat16* wo = (const __nv_bfloat16*)d_in[2];
  const __nv_bfloat16* rpb = (const __nv_bfloat16*)d_in[3];

  if (!g_enc) {
    void* fn = nullptr; cudaDriverEntryPointQueryResult qr;
    cudaGetDriverEntryPoint("cuTensorMapEncodeTiled", &fn, cudaEnableDefault, &qr);
    g_enc = (EncodeFn)fn;
    cudaFuncSetAttribute(na_attn_kernel, cudaFuncAttributeMaxDynamicSharedMemorySize, SM_A_TOTAL);
    cudaFuncSetAttribute(na_proj_kernel, cudaFuncAttributeMaxDynamicSharedMemorySize, SM_B_TOTAL);
  }
  Maps ma; MapsB mb;
  { cuuint64_t dim[4] = {64, 112, 224, 6}, str[3] = {(cuuint64_t)ROWB, 768, 128};
    cuuint32_t box[4] = {64, 4, 16, 3}, boxh[4] = {64, 16, 3, 3}, boxo[4] = {64, 8, 8, 1};
    make_map(&ma.xc, x, 4, dim, str, box, CU_TENSOR_MAP_SWIZZLE_128B);
    make_map(&ma.xh, x, 4, dim, str, boxh, CU_TENSOR_MAP_SWIZZLE_128B);
    make_map(&mb.oo, d_out, 4, dim, str, boxo, CU_TENSOR_MAP_SWIZZLE_128B); }
  { cuuint64_t dim[3] = {384, 112, 224}, str[2] = {(cuuint64_t)ROWB, 768};
    cuuint32_t box[3] = {192, 8, 8}, boxs[3] = {192, 2, OCH};
    make_map(&mb.oi, d_out, 3, dim, str, box, CU_TENSOR_MAP_SWIZZLE_NONE);
    make_map(&ma.os, d_out, 3, dim, str, boxs, CU_TENSOR_MAP_SWIZZLE_NONE); }
  { cuuint64_t dim[4] = {32, 112, 224, 12}, str[3] = {(cuuint64_t)ROWB, 768, 64};
    cuuint32_t box[4] = {32, 8, 2, 3};
    make_map(&ma.ot, d_out, 4, dim, str, box, CU_TENSOR_MAP_SWIZZLE_64B); }
  { cuuint64_t dim[2] = {576, 192}, str[1] = {1152};
    cuuint32_t box[2] = {16, 192};
    make_map(&ma.w, wqkv, 2, dim, str, box, CU_TENSOR_MAP_SWIZZLE_32B); }
  { cuuint64_t dim[3] = {32, 192, 6}, str[2] = {384, 64};
    cuuint32_t box[3] = {32, 192, 3};
    make_map(&mb.wo, wo, 3, dim, str, box, CU_TENSOR_MAP_SWIZZLE_64B); }
  { cuuint64_t dim[2] = {192, 192}, str[1] = {384};
    cuuint32_t box[2] = {32, 48};
    make_map(&ma.wo, wo, 2, dim, str, box, CU_TENSOR_MAP_SWIZZLE_64B); }
  na_attn_kernel<<<112, 512, SM_A_TOTAL>>>(x, wqkv, rpb, ma);
  cudaLaunchConfig_t cfg = {};
  cfg.gridDim = dim3(20); cfg.blockDim = dim3(512); cfg.dynamicSmemBytes = SM_B_TOTAL; cfg.stream = cudaStreamPerThread;
  cudaLaunchAttribute at[1];
  at[0].id = cudaLaunchAttributeProgrammaticStreamSerialization; at[0].val.programmaticStreamSerializationAllowed = 1;
  cfg.attrs = at; cfg.numAttrs = 1;
  cudaLaunchKernelEx(&cfg, na_proj_kernel, mb);
}
```

```cpp
#include <cuda_runtime.h>
#include <cuda_bf16.h>
#include <cuda.h>
#include <stdint.h>

#define SPIN_LIMIT (1u << 18)

__device__ __forceinline__ uint32_t smem_u32(const void* p) { return (uint32_t)__cvta_generic_to_shared(p); }
__device__ __forceinline__ void wg_fence() { asm volatile("wgmma.fence.sync.aligned;" ::: "memory"); }
__device__ __forceinline__ void wg_commit() { asm volatile("wgmma.commit_group.sync.aligned;" ::: "memory"); }
template <int N> __device__ __forceinline__ void wg_wait() { asm volatile("wgmma.wait_group.sync.aligned %0;" ::"n"(N) : "memory"); }
template <int N> __device__ __forceinline__ void pin(float (&d)[N]) {
#pragma unroll
  for (int i = 0; i < N; i++) asm volatile("" : "+f"(d[i])::"memory");
}
__host__ __device__ constexpr uint64_t mkdesc(uint32_t addr, uint32_t lbo, uint32_t sbo, uint32_t sw) {
  return (uint64_t)((addr & 0x3FFFF) >> 4) | ((uint64_t)(lbo >> 4) << 16) | ((uint64_t)(sbo >> 4) << 32) | ((uint64_t)sw << 62);
}
__device__ __forceinline__ void mbar_init(uint32_t bar, uint32_t cnt) { asm volatile("mbarrier.init.shared::cta.b64 [%0], %1;" ::"r"(bar), "r"(cnt) : "memory"); }
__device__ __forceinline__ void mbar_arrive(uint32_t bar) { asm volatile("mbarrier.arrive.shared::cta.b64 _, [%0];" ::"r"(bar) : "memory"); }
__device__ __forceinline__ bool elect_one() {
  uint32_t r; asm volatile("{\n.reg .pred p;\nelect.sync _|p, 0xffffffff;\nselp.u32 %0, 1, 0, p;\n}" : "=r"(r)); return r;
}
__device__ __forceinline__ void mbar_arrive_elect(uint32_t bar) {
  asm volatile("{\n.reg .pred p;\nelect.sync _|p, 0xffffffff;\n@p mbarrier.arrive.shared::cta.b64 _, [%0];\n}" ::"r"(bar) : "memory");
}
__device__ __forceinline__ void mbar_expect(uint32_t bar, uint32_t bytes) { asm volatile("mbarrier.arrive.expect_tx.shared::cta.b64 _, [%0], %1;" ::"r"(bar), "r"(bytes) : "memory"); }
__device__ __forceinline__ void mbar_arrive_remote(uint32_t bar, uint32_t cta) {
  asm volatile("{\n.reg .b32 ra;\nmapa.shared::cluster.u32 ra, %0, %1;\nmbarrier.arrive.relaxed.cluster.shared::cluster.b64 _, [ra];\n}" ::"r"(bar), "r"(cta) : "memory");
}
__device__ __forceinline__ void mbar_wait(uint32_t bar, uint32_t parity) {
  asm volatile("{\n.reg .pred p;\n.reg .b32 n;\nmov.b32 n, 0;\nWL:\nmbarrier.try_wait.parity.shared::cta.b64 p, [%0], %1;\n@p bra WD;\n"
               "add.u32 n, n, 1;\nsetp.lt.u32 p, n, 65536;\n@p bra WL;\nWD:\n}" ::"r"(bar), "r"(parity) : "memory");
}
__device__ __forceinline__ void nb_sync(int id, int n) { asm volatile("bar.sync %0, %1;" ::"r"(id), "r"(n) : "memory"); }
__device__ __forceinline__ void nb_arrive(int id, int n) { asm volatile("bar.arrive %0, %1;" ::"r"(id), "r"(n) : "memory"); }
__device__ __forceinline__ uint32_t opq(uint32_t x) { uint32_t r; asm volatile("mov.b32 %0, %1;" : "=r"(r) : "r"(x)); return r; }
__device__ __forceinline__ uint64_t opq(uint64_t x) { uint64_t r; asm volatile("mov.b64 %0, %1;" : "=l"(r) : "l"(x)); return r; }
__device__ __forceinline__ uint32_t mapa(uint32_t a, uint32_t cta) { uint32_t r; asm("mapa.shared::cluster.u32 %0, %1, %2;" : "=r"(r) : "r"(a), "r"(cta)); return r; }
__device__ __forceinline__ void fence_async() { asm volatile("fence.proxy.async.shared::cta;" ::: "memory"); }
__device__ __forceinline__ void cluster_sync() {
  asm volatile("barrier.cluster.arrive.relaxed.aligned;\nbarrier.cluster.wait.aligned;" ::: "memory");
}
__device__ __forceinline__ uint32_t pack2(float lo, float hi) {
  uint32_t r; asm("cvt.rn.bf16x2.f32 %0, %1, %2;" : "=r"(r) : "f"(hi), "f"(lo)); return r;
}
__device__ __forceinline__ void stsm4(uint32_t a, uint32_t r0, uint32_t r1, uint32_t r2, uint32_t r3) {
  asm volatile("stmatrix.sync.aligned.m8n8.x4.shared.b16 [%0], {%1,%2,%3,%4};" ::"r"(a), "r"(r0), "r"(r1), "r"(r2), "r"(r3) : "memory");
}
__device__ __forceinline__ void ldsm4(uint32_t a, uint32_t& r0, uint32_t& r1, uint32_t& r2, uint32_t& r3) {
  asm volatile("ldmatrix.sync.aligned.m8n8.x4.shared.b16 {%0,%1,%2,%3}, [%4];" : "=r"(r0), "=r"(r1), "=r"(r2), "=r"(r3) : "r"(a) : "memory");
}
__device__ __forceinline__ void sts128(uint32_t a, uint4 v) {
  asm volatile("st.shared.v4.b32 [%0], {%1,%2,%3,%4};" ::"r"(a), "r"(v.x), "r"(v.y), "r"(v.z), "r"(v.w) : "memory");
}
__device__ __forceinline__ float lds_f32(uint32_t a) { float v; asm volatile("ld.shared.f32 %0, [%1];" : "=f"(v) : "r"(a)); return v; }
__device__ __forceinline__ float ex2(float x) { float y; asm("ex2.approx.ftz.f32 %0, %1;" : "=f"(y) : "f"(x)); return y; }

template<int SC> __device__ __forceinline__ void wg_ss144(float (&d)[72], uint64_t da, uint64_t db) {
  asm volatile("{\n.reg .pred p;\nsetp.ne.b32 p, %74, 0;\nwgmma.mma_async.sync.aligned.m64n144k16.f32.bf16.bf16 {%0,%1,%2,%3,%4,%5,%6,%7,%8,%9,%10,%11,%12,%13,%14,%15,%16,%17,%18,%19,%20,%21,%22,%23,%24,%25,%26,%27,%28,%29,%30,%31,%32,%33,%34,%35,%36,%37,%38,%39,%40,%41,%42,%43,%44,%45,%46,%47,%48,%49,%50,%51,%52,%53,%54,%55,%56,%57,%58,%59,%60,%61,%62,%63,%64,%65,%66,%67,%68,%69,%70,%71}, %72, %73, p, 1, 1, 0, 1;\n}\n"
    : "+f"(d[0]),"+f"(d[1]),"+f"(d[2]),"+f"(d[3]),"+f"(d[4]),"+f"(d[5]),"+f"(d[6]),"+f"(d[7]),"+f"(d[8]),"+f"(d[9]),"+f"(d[10]),"+f"(d[11]),"+f"(d[12]),"+f"(d[13]),"+f"(d[14]),"+f"(d[15]),"+f"(d[16]),"+f"(d[17]),"+f"(d[18]),"+f"(d[19]),"+f"(d[20]),"+f"(d[21]),"+f"(d[22]),"+f"(d[23]),"+f"(d[24]),"+f"(d[25]),"+f"(d[26]),"+f"(d[27]),"+f"(d[28]),"+f"(d[29]),"+f"(d[30]),"+f"(d[31]),"+f"(d[32]),"+f"(d[33]),"+f"(d[34]),"+f"(d[35]),"+f"(d[36]),"+f"(d[37]),"+f"(d[38]),"+f"(d[39]),"+f"(d[40]),"+f"(d[41]),"+f"(d[42]),"+f"(d[43]),"+f"(d[44]),"+f"(d[45]),"+f"(d[46]),"+f"(d[47]),"+f"(d[48]),"+f"(d[49]),"+f"(d[50]),"+f"(d[51]),"+f"(d[52]),"+f"(d[53]),"+f"(d[54]),"+f"(d[55]),"+f"(d[56]),"+f"(d[57]),"+f"(d[58]),"+f"(d[59]),"+f"(d[60]),"+f"(d[61]),"+f"(d[62]),"+f"(d[63]),"+f"(d[64]),"+f"(d[65]),"+f"(d[66]),"+f"(d[67]),"+f"(d[68]),"+f"(d[69]),"+f"(d[70]),"+f"(d[71]) : "l"(da), "l"(db), "n"(SC));
}
template<int SC> __device__ __forceinline__ void wg_ss96(float (&d)[48], uint64_t da, uint64_t db) {
  asm volatile("{\n.reg .pred p;\nsetp.ne.b32 p, %50, 0;\nwgmma.mma_async.sync.aligned.m64n96k16.f32.bf16.bf16 {%0,%1,%2,%3,%4,%5,%6,%7,%8,%9,%10,%11,%12,%13,%14,%15,%16,%17,%18,%19,%20,%21,%22,%23,%24,%25,%26,%27,%28,%29,%30,%31,%32,%33,%34,%35,%36,%37,%38,%39,%40,%41,%42,%43,%44,%45,%46,%47}, %48, %49, p, 1, 1, 0, 1;\n}\n"
    : "+f"(d[0]),"+f"(d[1]),"+f"(d[2]),"+f"(d[3]),"+f"(d[4]),"+f"(d[5]),"+f"(d[6]),"+f"(d[7]),"+f"(d[8]),"+f"(d[9]),"+f"(d[10]),"+f"(d[11]),"+f"(d[12]),"+f"(d[13]),"+f"(d[14]),"+f"(d[15]),"+f"(d[16]),"+f"(d[17]),"+f"(d[18]),"+f"(d[19]),"+f"(d[20]),"+f"(d[21]),"+f"(d[22]),"+f"(d[23]),"+f"(d[24]),"+f"(d[25]),"+f"(d[26]),"+f"(d[27]),"+f"(d[28]),"+f"(d[29]),"+f"(d[30]),"+f"(d[31]),"+f"(d[32]),"+f"(d[33]),"+f"(d[34]),"+f"(d[35]),"+f"(d[36]),"+f"(d[37]),"+f"(d[38]),"+f"(d[39]),"+f"(d[40]),"+f"(d[41]),"+f"(d[42]),"+f"(d[43]),"+f"(d[44]),"+f"(d[45]),"+f"(d[46]),"+f"(d[47]) : "l"(da), "l"(db), "n"(SC));
}
template<int SC> __device__ __forceinline__ void wg_rs112(float (&d)[56], uint32_t a0, uint32_t a1, uint32_t a2, uint32_t a3, uint64_t db) {
  asm volatile("{\n.reg .pred p;\nsetp.ne.b32 p, %61, 0;\nwgmma.mma_async.sync.aligned.m64n112k16.f32.bf16.bf16 {%0,%1,%2,%3,%4,%5,%6,%7,%8,%9,%10,%11,%12,%13,%14,%15,%16,%17,%18,%19,%20,%21,%22,%23,%24,%25,%26,%27,%28,%29,%30,%31,%32,%33,%34,%35,%36,%37,%38,%39,%40,%41,%42,%43,%44,%45,%46,%47,%48,%49,%50,%51,%52,%53,%54,%55}, {%56,%57,%58,%59}, %60, p, 1, 1, 0;\n}\n"
    : "+f"(d[0]),"+f"(d[1]),"+f"(d[2]),"+f"(d[3]),"+f"(d[4]),"+f"(d[5]),"+f"(d[6]),"+f"(d[7]),"+f"(d[8]),"+f"(d[9]),"+f"(d[10]),"+f"(d[11]),"+f"(d[12]),"+f"(d[13]),"+f"(d[14]),"+f"(d[15]),"+f"(d[16]),"+f"(d[17]),"+f"(d[18]),"+f"(d[19]),"+f"(d[20]),"+f"(d[21]),"+f"(d[22]),"+f"(d[23]),"+f"(d[24]),"+f"(d[25]),"+f"(d[26]),"+f"(d[27]),"+f"(d[28]),"+f"(d[29]),"+f"(d[30]),"+f"(d[31]),"+f"(d[32]),"+f"(d[33]),"+f"(d[34]),"+f"(d[35]),"+f"(d[36]),"+f"(d[37]),"+f"(d[38]),"+f"(d[39]),"+f"(d[40]),"+f"(d[41]),"+f"(d[42]),"+f"(d[43]),"+f"(d[44]),"+f"(d[45]),"+f"(d[46]),"+f"(d[47]),"+f"(d[48]),"+f"(d[49]),"+f"(d[50]),"+f"(d[51]),"+f"(d[52]),"+f"(d[53]),"+f"(d[54]),"+f"(d[55]) : "r"(a0), "r"(a1), "r"(a2), "r"(a3), "l"(db), "n"(SC));
}
template<int SC> __device__ __forceinline__ void wg_sp48(float (&d)[24], uint32_t a0, uint32_t a1, uint32_t a2, uint32_t a3, uint64_t db, uint32_t meta) {
  asm volatile("{\n.reg .pred p;\nsetp.ne.b32 p, %30, 0;\nwgmma.mma_async.sp.sync.aligned.m64n48k32.f32.bf16.bf16 {%0,%1,%2,%3,%4,%5,%6,%7,%8,%9,%10,%11,%12,%13,%14,%15,%16,%17,%18,%19,%20,%21,%22,%23}, {%24,%25,%26,%27}, %28, %29, 0, p, 1, 1, 1;\n}\n"
    : "+f"(d[0]),"+f"(d[1]),"+f"(d[2]),"+f"(d[3]),"+f"(d[4]),"+f"(d[5]),"+f"(d[6]),"+f"(d[7]),"+f"(d[8]),"+f"(d[9]),"+f"(d[10]),"+f"(d[11]),"+f"(d[12]),"+f"(d[13]),"+f"(d[14]),"+f"(d[15]),"+f"(d[16]),"+f"(d[17]),"+f"(d[18]),"+f"(d[19]),"+f"(d[20]),"+f"(d[21]),"+f"(d[22]),"+f"(d[23]) : "r"(a0), "r"(a1), "r"(a2), "r"(a3), "l"(db), "r"(meta), "n"(SC));
}
template<int SC> __device__ __forceinline__ void wg_rs64(float (&d)[32], uint32_t a0, uint32_t a1, uint32_t a2, uint32_t a3, uint64_t db) {
  asm volatile("{\n.reg .pred p;\nsetp.ne.b32 p, %37, 0;\nwgmma.mma_async.sync.aligned.m64n64k16.f32.bf16.bf16 {%0,%1,%2,%3,%4,%5,%6,%7,%8,%9,%10,%11,%12,%13,%14,%15,%16,%17,%18,%19,%20,%21,%22,%23,%24,%25,%26,%27,%28,%29,%30,%31}, {%32,%33,%34,%35}, %36, p, 1, 1, 0;\n}\n"
    : "+f"(d[0]),"+f"(d[1]),"+f"(d[2]),"+f"(d[3]),"+f"(d[4]),"+f"(d[5]),"+f"(d[6]),"+f"(d[7]),"+f"(d[8]),"+f"(d[9]),"+f"(d[10]),"+f"(d[11]),"+f"(d[12]),"+f"(d[13]),"+f"(d[14]),"+f"(d[15]),"+f"(d[16]),"+f"(d[17]),"+f"(d[18]),"+f"(d[19]),"+f"(d[20]),"+f"(d[21]),"+f"(d[22]),"+f"(d[23]),"+f"(d[24]),"+f"(d[25]),"+f"(d[26]),"+f"(d[27]),"+f"(d[28]),"+f"(d[29]),"+f"(d[30]),"+f"(d[31]) : "r"(a0), "r"(a1), "r"(a2), "r"(a3), "l"(db), "n"(SC));
}

constexpr uint32_t SBC = 1024;
constexpr int ROWB = 2 * 224 * 384;
constexpr int TB = 11;
constexpr int KS = 832;
constexpr int KSLOT = 22 * KS;
constexpr int SM_X = 0;
constexpr int SM_W = SM_X + 3 * 24576;
constexpr int SM_K = SM_W + 55296;
constexpr int SM_V = SM_K + 2 * KSLOT;
constexpr int SM_Q = SM_V + 22 * 1536;
constexpr int SM_O = SM_Q + 12288;
constexpr int SM_S = SM_O + 12288;
constexpr int SM_RPB = SM_S + 6144;
constexpr int SM_BAR = SM_RPB + 768;
constexpr int SM_A_TOTAL = SM_BAR + 256;
constexpr int SM_TIN0 = SM_X + 24576, SM_TIN1 = SM_X, SM_TIN2 = SM_W + 18432;
constexpr int SM_TWO = SM_X + 2 * 24576;
constexpr int SM_TST = SM_TIN2 + 24576;
enum { B_FULL = 0, B_EMPTY = 3, B_TIN = 6, B_TFREE = 10, B_WK = 12, B_WQ, B_WO, B_KIMP, B_VIMP, B_OFREE, B_XK, B_XV,
       B_Q0, B_WOFREE, B_OTAIL, B_ODONE = B_OTAIL + 4, B_KFREE, B_VFREE, B_COUNT };
enum { N_KRDY = 4, N_GO1, N_QK0, N_QK1, N_VQ0, N_VQ1, N_PV0, N_PV1, N_Q0 };

#define NL 2
#define OCH 16
#define MID 6
#define DBL 1
#define EA 5
#define EB 0
#define OA 6
#define OB 6
#define RA 152
#define RG 184
#define OPT 0
constexpr int FS = 64;
__device__ int g_flags[TB * 56 * FS];

#define TR(role, it, k)
#define TRDECL
#define TRARG
#define TRPASS
#define TRDUMP
#define TRB(it, k)
#define TR2START
#define TR2FLUSH(blk)
#define TR2(blk, k)

struct Stage { uint32_t lo, full, em, par; };
struct GemmCtx {
  uint32_t bar;
  uint32_t kC, vC[2], qC[2];
  uint32_t kH, vH[2];
  uint32_t hiA, hiB;
  uint32_t spin;
  bool hvalid, never, edge;
};

template <int STRIDE> __device__ __forceinline__ void dump12(uint32_t a, const uint32_t (&r)[12]) {
#pragma unroll
  for (int j = 0; j < 3; j++) stsm4(a + j * 2 * STRIDE, r[4 * j], r[4 * j + 1], r[4 * j + 2], r[4 * j + 3]);
}
__device__ __forceinline__ void keep12(bool never, uint32_t a, const uint32_t (&r)[12]) { if (never) dump12<128>(a, r); }
template <int N> __device__ __forceinline__ void pack12(uint32_t (&r)[12], const float (&d)[N], int off) {
#pragma unroll
  for (int j = 0; j < 12; j++) r[j] = pack2(d[off + 2 * j], d[off + 2 * j + 1]);
}
__device__ __forceinline__ uint64_t dsc(uint64_t lo, uint32_t hi) { uint64_t r; asm("mov.b64 %0, {%1, %2};" : "=l"(r) : "r"((uint32_t)lo), "r"(hi)); return r; }
template <int K0, int K1> __device__ __forceinline__ void issue_core(const GemmCtx& c, const Stage& x, float (&d)[72]) {
  constexpr uint64_t db = mkdesc(SBC + SM_W, 6144, 256, 3);
  wg_fence();
  if (K0 == 0) wg_ss144<0>(d, dsc(x.lo, c.hiA), dsc(db, c.hiB));
#pragma unroll
  for (int k = K0 ? K0 : 1; k < K1; k++) wg_ss144<1>(d, dsc(x.lo + (k >> 2) * 512 + (k & 3) * 2, c.hiA), dsc(db + k * 32, c.hiB));
  wg_commit();
}
template <int K0, int K1> __device__ __forceinline__ void issue_halo(const GemmCtx& c, const Stage& x, float (&d)[48]) {
  constexpr uint64_t db = mkdesc(SBC + SM_W + 18432, 6144, 256, 3);
  wg_fence();
  if (K0 == 0) wg_ss96<0>(d, dsc(x.lo, c.hiA), dsc(db, c.hiB));
#pragma unroll
  for (int k = K0 ? K0 : 1; k < K1; k++) wg_ss96<1>(d, dsc(x.lo + (k >> 2) * 384 + (k & 3) * 2, c.hiA), dsc(db + k * 32, c.hiB));
  wg_commit();
}
__device__ __forceinline__ void release_stage(const Stage& x) {
  asm volatile("{\n.reg .pred p;\nelect.sync _|p, 0xffffffff;\n@p mbarrier.arrive.shared::cluster.b64 _, [%0];\n}" ::"r"(x.em) : "memory");
}
__device__ __forceinline__ void wait_stage(GemmCtx& c, Stage& x) {
  asm volatile("{\n.reg .pred p;\nWL:\nmbarrier.try_wait.parity.shared::cta.b64 p, [%1], %2;\n@p bra WD;\n"
               "add.u32 %0, %0, 1;\nsetp.lt.u32 p, %0, 0x100000;\n@p bra WL;\nWD:\n}" : "+&r"(c.spin) : "r"(x.full), "r"(x.par) : "memory");
  x.par ^= 1;
}
__device__ __forceinline__ void edge_ready(const GemmCtx& c, int bar) { __syncwarp(); if (c.edge) mbar_arrive_elect(c.bar + bar * 8); }
__device__ __forceinline__ void dump6(uint32_t a, const uint32_t (&r)[6]) {
  stsm4(a, r[0], r[1], r[2], r[3]);
  asm volatile("stmatrix.sync.aligned.m8n8.x2.shared.b16 [%0], {%1,%2};" ::"r"(a + 512), "r"(r[4]), "r"(r[5]) : "memory");
}
__device__ __forceinline__ void pack6(uint32_t (&r)[6], const float (&d)[48], int off) {
#pragma unroll
  for (int j = 0; j < 6; j++) r[j] = pack2(d[off + 4 * j], d[off + 4 * j + 1]);
}
template <int PARITY> __device__ __forceinline__ void gwait(GemmCtx& c, int bar) {
  asm volatile("{\n.reg .pred p;\nWL:\nmbarrier.try_wait.parity.shared::cta.b64 p, [%1], %2;\n@p bra WD;\n"
               "add.u32 %0, %0, 1;\nsetp.lt.u32 p, %0, 0x100000;\n@p bra WL;\nWD:\n}" : "+&r"(c.spin) : "r"(c.bar + bar * 8), "n"(PARITY) : "memory");
}
__device__ __forceinline__ void load_w(const CUtensorMap* m, uint32_t dst, uint32_t bar, int col) {
  asm volatile("cp.async.bulk.tensor.2d.shared::cluster.global.mbarrier::complete_tx::bytes [%0], [%1, {%3,%4}], [%2];"
               ::"r"(dst), "l"(m), "r"(bar), "r"(col), "r"(0) : "memory");
}
__device__ __forceinline__ void remote_arrive(uint32_t rbar) { asm volatile("mbarrier.arrive.shared::cluster.b64 _, [%0];" ::"r"(rbar) : "memory"); }
__device__ __forceinline__ void remote_expect(uint32_t rbar, uint32_t bytes) {
  asm volatile("mbarrier.arrive.expect_tx.shared::cluster.b64 _, [%0], %1;" ::"r"(rbar), "r"(bytes) : "memory");
}
__device__ __forceinline__ void copy_remote(uint32_t rdst, uint32_t src, uint32_t bytes, uint32_t rbar) {
  asm volatile("cp.async.bulk.shared::cluster.shared::cta.mbarrier::complete_tx::bytes [%0], [%1], %2, [%3];" ::"r"(rdst), "r"(src), "r"(bytes), "r"(rbar) : "memory");
}
__device__ __forceinline__ void tail_free(uint32_t bar) {
  uint32_t ln; asm volatile("mov.u32 %0, %%laneid;" : "=r"(ln));
  if (ln < 4) mbar_arrive_remote(bar, ln + (blockIdx.x & 4));
}
__device__ __forceinline__ void publish(uint32_t bar) {
  fence_async();
  __syncwarp();
  mbar_arrive_elect(bar);
}

template <int PA>
__device__ __forceinline__ void gemm_iter(GemmCtx& c, int b, uint32_t (&pk)[12], uint32_t (&pv)[12], uint32_t (&pq)[12],
                                          uint32_t (&hk1)[6], uint32_t (&hv1)[6], Stage& xa, Stage& xb, Stage& xc TRARG) {
  const uint32_t bar = c.bar;
  const bool w = PA == 0 || b >= 0, never = c.never;
  constexpr uint32_t ko = PA * KSLOT;
  constexpr int A = PA ? OA : EA;
  float C[72], D_[72];
  float (&D)[72] = PA && DBL ? D_ : C;
  uint32_t hk0[6], hv0[6], pv2[12];
  TR(2, b, 0);
  if (w) nb_sync(N_QK0, 256);
  TR(2, b, 2);
  issue_core<0, A>(c, xa, C);
  if (w) nb_arrive(N_GO1, 256);
  TR(2, b, 3);
  dump12<128>(c.qC[1], pq);
  fence_async();
  if (w) { edge_ready(c, B_XV); nb_arrive(N_VQ0, 288); nb_arrive(N_VQ1, 288); nb_sync(N_QK1, 256); }
  else { __syncwarp(); mbar_arrive_elect(bar + B_Q0 * 8); }
  issue_core<A, 12>(c, xa, C);
  TR(2, b, 4);
  wait_stage(c, xb);
  if (w) gwait<PA>(c, B_KFREE);
  dump12<128>(c.kC + ko, pk);
  if (PA && c.hvalid) dump6(c.kH + ko, hk1);
  TR(2, b, 5);
  if (PA == 0) {
    float H[48];
    nb_sync(N_PV0, 256);
    issue_halo<0, 8>(c, xb, H);
    wg_wait<1>(); pin(C);
    TR(2, b, 7);
    release_stage(xa);
    pack12(pk, C, 24);
    dump12<128>(c.kC + 64, pk);
    issue_halo<8, 12>(c, xb, H);
    pack12(pv2, C, 48);
    pack12(pq, C, 0);
    wait_stage(c, xc);
    fence_async();
    edge_ready(c, B_XK);
    TR(2, b, 8);
    if (EB == 0) nb_sync(N_PV1, 256);
    issue_core<0, EB ? EB : 8>(c, xc, D);
    TR(2, b, 9);
    wg_wait<1>(); pin(H);
    release_stage(xb);
    pack6(hk0, H, 0);
    if (c.hvalid) dump6(c.kH, hk0);
    pack6(hk1, H, 2); pack6(hv0, H, 24); pack6(hv1, H, 26);
    if (EB) nb_sync(N_PV1, 256);
    issue_core<EB ? EB : 8, 12>(c, xc, D);
    fence_async();
  } else {
    if (DBL) { if (w) nb_sync(N_PV0, 256); issue_core<0, OB>(c, xb, D); wg_wait<1>(); }
    else wg_wait<0>();
    pin(C);
    TR(2, b, 7);
    release_stage(xa);
    pack12(pk, C, 24);
    dump12<128>(c.kC + ko + 64, pk);
    pack12(pv2, C, 48);
    pack12(pq, C, 0);
    TR(2, b, 8);
    if (!DBL) { if (w) nb_sync(N_PV0, 256); issue_core<0, OB>(c, xb, D); }
    TR(2, b, 9);
    fence_async();
    edge_ready(c, B_XK);
    if (!DBL) keep12(never, c.kC, pk);
    if (w) nb_sync(N_PV1, 256);
    issue_core<OB, 12>(c, xb, D);
  }
  nb_arrive(N_KRDY, 256);
  TR(2, b, 1);
  if (PA && b == 11) tail_free(bar + B_TFREE * 8);
  wait_stage(c, PA ? xc : xa);
  if (w) gwait<PA>(c, B_VFREE);
  TR(2, b, 10);
  dump12<128>(c.vC[PA], pv);
  if (PA && !w) nb_sync(N_Q0, 384);
  dump12<128>(c.qC[0], pq);
  dump12<128>(c.vC[PA ^ 1] + 768, pv2);
  if (c.hvalid) dump6(c.vH[PA], PA ? hv1 : hv0);
  TR(2, b, 11);
  wg_wait<0>(); pin(D);
  TR(2, b, 12);
  release_stage(PA ? xb : xc);
  pack12(pk, D, 24);
  pack12(pv, D, 48);
  pack12(pq, D, 0);
}
__device__ __forceinline__ void gemm_first(GemmCtx& c, uint32_t (&pk)[12], uint32_t (&pv)[12], uint32_t (&pq)[12],
                                           uint32_t (&hk1)[6], uint32_t (&hv1)[6], Stage& xa, Stage& xb, Stage& xc) {
  float H[48], C[72];
  uint32_t hk0[6], hv0[6];
  wait_stage(c, xb);
  issue_halo<0, 12>(c, xb, H);
  wait_stage(c, xa);
  gwait<0>(c, B_WQ);
  issue_core<0, 12>(c, xa, C);
  wg_wait<1>(); pin(H);
  release_stage(xb);
  pack6(hk0, H, 0); pack6(hk1, H, 2); pack6(hv0, H, 24); pack6(hv1, H, 26);
  if (c.hvalid) { dump6(c.kH, hk0); dump6(c.vH[0], hv0); }
  wait_stage(c, xc);
  wg_wait<0>(); pin(C);
  release_stage(xa);
  pack12(pk, C, 24); pack12(pv, C, 48); pack12(pq, C, 0);
  issue_core<0, 12>(c, xc, C);
  dump12<128>(c.kC + 64, pk);
  dump12<128>(c.vC[1] + 768, pv);
  dump12<128>(c.qC[0], pq);
  wg_wait<0>(); pin(C);
  release_stage(xc);
  pack12(pk, C, 24); pack12(pv, C, 48); pack12(pq, C, 0);
  wait_stage(c, xa);
}

template <int IN> __device__ __forceinline__ void issue_proj(float (&D)[48]) {
  constexpr uint64_t da = mkdesc(SBC + IN, 128, 768, 0), db = mkdesc(SBC + SM_TWO, 12288, 512, 2);
  wg_fence();
  wg_ss96<0>(D, da, db);
#pragma unroll
  for (int k = 1; k < 12; k++) wg_ss96<1>(D, da + (k / 3) * 384 + (k % 3) * 16, db + k * 64);
  wg_commit();
}
template <int ACC> __device__ __forceinline__ void issue_proj_half(float (&D)[48], int hd) {
  const uint64_t da = mkdesc(SBC + SM_TIN2, 128, 768, 0) + hd * 384, db = mkdesc(SBC + SM_TWO, 12288, 512, 2) + hd * 192;
  wg_fence();
  wg_ss96<ACC>(D, da, db);
#pragma unroll
  for (int k = 1; k < 6; k++) wg_ss96<1>(D, da + (k / 3) * 768 + (k % 3) * 16, db + (k / 3) * 384 + (k % 3) * 64);
  wg_commit();
}
__device__ __forceinline__ void store_proj(const float (&D)[48], const CUtensorMap* m, uint32_t st, uint32_t sta, int row, int col, int ch) {
#pragma unroll
  for (int q = 0; q < 6; q++)
    stsm4((sta ^ ((q & 1) * 32)) + (q >> 1) * 1024,
          pack2(D[8 * q], D[8 * q + 1]), pack2(D[8 * q + 2], D[8 * q + 3]), pack2(D[8 * q + 4], D[8 * q + 5]), pack2(D[8 * q + 6], D[8 * q + 7]));
  fence_async();
  __syncwarp();
  if ((threadIdx.x & 31) == 0) {
    asm volatile("cp.async.bulk.tensor.4d.global.shared::cta.bulk_group [%0, {%2,%3,%4,%5}], [%1];" ::"l"(m), "r"(st), "r"(0), "r"(row), "r"(col), "r"(ch) : "memory");
    asm volatile("cp.async.bulk.commit_group;" ::: "memory");
  }
  __syncwarp();
}

__device__ __forceinline__ float fold(float a, float b, float t, int useb) {
  float r;
  asm("{\n.reg .pred p;\nsetp.ne.b32 p, %4, 0;\nfma.rn.f32 %0, %1, 0f3E553B95, %3;\n@p fma.rn.f32 %0, %2, 0f3E553B95, %3;\n}"
      : "=&f"(r) : "f"(a), "f"(b), "f"(t), "r"(useb));
  return r;
}
template <int U, int L>
__device__ __forceinline__ void softmax_tile(const float (&SA)[56], const float (&SB)[56], const float (&T)[16], int b0, int b1,
                                             uint32_t (&P)[28], float (&sx)[8], uint32_t nbV, uint32_t zero, uint32_t qa, uint32_t (&q)[12]) {
  float lu[14], ll[14];
#pragma unroll
  for (int j = 0; j < 7; j++) {
    constexpr int sh = U == L ? 2 : 0;
    const float tu0 = T[2 * j + sh], tu1 = T[2 * j + 1 + sh], tl0 = T[2 * j], tl1 = T[2 * j + 1];
    lu[2 * j]     = fold(SA[4 * (U + j)],     SB[4 * (U + j)],     tu0, b0);
    ll[2 * j]     = fold(SA[4 * (L + j) + 2], SB[4 * (L + j) + 2], tl0, b0);
    lu[2 * j + 1] = fold(SA[4 * (U + j) + 1], SB[4 * (U + j) + 1], tu1, b1);
    ll[2 * j + 1] = fold(SA[4 * (L + j) + 3], SB[4 * (L + j) + 3], tl1, b1);
  }
  float mu = lu[0], ml = ll[0], mu2 = lu[1], ml2 = ll[1];
#pragma unroll
  for (int j = 1; j < 7; j++) { mu = fmaxf(mu, lu[2 * j]); mu2 = fmaxf(mu2, lu[2 * j + 1]); ml = fmaxf(ml, ll[2 * j]); ml2 = fmaxf(ml2, ll[2 * j + 1]); }
  mu = fmaxf(mu, mu2); ml = fmaxf(ml, ml2);
  { const float a1 = __shfl_xor_sync(0xffffffffu, mu, 1), a2 = __shfl_xor_sync(0xffffffffu, mu, 2), a3 = __shfl_xor_sync(0xffffffffu, mu, 3);
    const float c1 = __shfl_xor_sync(0xffffffffu, ml, 1), c2 = __shfl_xor_sync(0xffffffffu, ml, 2), c3 = __shfl_xor_sync(0xffffffffu, ml, 3);
    mu = fmaxf(fmaxf(mu, a1), fmaxf(a2, a3)); ml = fmaxf(fmaxf(ml, c1), fmaxf(c2, c3)); }
  float su = 0.f, sl = 0.f;
#pragma unroll
  for (int c = 0; c < 14; c++) {
    if (c >= U && c < U + 7) {
      float e0 = ex2(lu[2 * (c - U)] - mu), e1 = ex2(lu[2 * (c - U) + 1] - mu);
      su = c == U ? e0 + e1 : (su + e0) + e1; P[2 * c] = pack2(e0, e1);
    } else P[2 * c] = 0u;
  }
  nb_sync(nbV | (P[2 * (U + MID)] & zero), 288);
#pragma unroll
  for (int k = 0; k < 3; k++) ldsm4(qa + k * 256, q[4 * k], q[4 * k + 1], q[4 * k + 2], q[4 * k + 3]);
#pragma unroll
  for (int c = 0; c < 14; c++) {
    if (c >= L && c < L + 7) {
      float e0 = ex2(ll[2 * (c - L)] - ml), e1 = ex2(ll[2 * (c - L) + 1] - ml);
      sl = c == L ? e0 + e1 : (sl + e0) + e1; P[2 * c + 1] = pack2(e0, e1);
    } else P[2 * c + 1] = 0u;
  }
  sx[0] = su; sx[4] = sl;
#pragma unroll
  for (int k = 1; k < 4; k++) sx[k] = __shfl_xor_sync(0xffffffffu, su, k);
#pragma unroll
  for (int k = 1; k < 4; k++) sx[4 + k] = __shfl_xor_sync(0xffffffffu, sl, k);
}

struct BandCfg { uint32_t ra0, ra1, meta; int b0, b1; };
__device__ __forceinline__ void band_cfg(int b, uint32_t tb, BandCfg& n) {
  uint32_t ln; asm volatile("mov.u32 %0, %%laneid;" : "=r"(ln));
  const int g = ln >> 2, t = ln & 3;
  const int sw = min(max(g + 1, b == 0 ? 4 : 0), b == 13 ? 5 : 8);
  const int i0 = 2 * t, i1 = 2 * t + 1;
  n.b0 = i0 <= sw - 2; n.b1 = i1 <= sw - 2;
  n.ra0 = tb + (i0 == sw - 1 ? 13 : i0 + 8 * n.b0 - g + 2) * 52;
  n.ra1 = tb + (i1 == sw - 1 ? 13 : i1 + 8 * n.b1 - g + 2) * 52;
  n.meta = ((0x5555u & ((1u << (2 * (sw - 1))) - 1)) ^ 0xDD88u ^ (((t ^ b) & 1) ? 0x5555u : 0u)) * 0x10001u;
}
__device__ __forceinline__ void band_load(const BandCfg& n, float (&T)[16], int& b0, int& b1, uint32_t& meta) {
#pragma unroll
  for (int jj = 0; jj < 8; jj++) { T[2 * jj] = lds_f32(n.ra0 + jj * 4); T[2 * jj + 1] = lds_f32(n.ra1 + jj * 4); }
  b0 = n.b0; b1 = n.b1; meta = n.meta;
}

struct Maps { CUtensorMap xc, xh, w, os, wo, ot; };

__global__ void __cluster_dims__(8, 1, 1) __launch_bounds__(512, 1)
na_attn_kernel(const __nv_bfloat16* __restrict__ x, const __nv_bfloat16* __restrict__ wqkv, const __nv_bfloat16* __restrict__ rpb, const __grid_constant__ Maps mp) {
  extern __shared__ __align__(1024) uint8_t smem_raw[];
  const uint32_t sb = smem_u32(smem_raw);
  if ((sb & 0x3FFFF) != SBC) return;
  const uint32_t bar = sb + SM_BAR;
  TR2START;
  const int tid = threadIdx.x, lane = tid & 31;
  const int warp = __shfl_sync(0xffffffffu, tid >> 5, 0);
  const int head = blockIdx.x & 3, base = blockIdx.x & 4, sp = blockIdx.x >> 2;
  const int par = sp < 24 ? sp / 6 : sp - 24, strip = sp < 24 ? sp - par * 6 : 6, ph = par >> 1, pw = par & 1;
  const int odd = strip & 1;

  uint4 wv[2 * NL];
  const int va = head == 1;
  const uint32_t wdst = sb + SM_W + (3 + va + ((tid >> 1) & 1)) * 6144 + (tid >> 2) * 32 + ((tid ^ (tid >> 4)) & 1) * 16;
  if (warp < 12) {
    asm volatile("barrier.cluster.arrive.relaxed.aligned;" ::: "memory");
    const uint32_t wo0 = (tid >> 2) * 1152 + head * 96 + va * 32 + (tid & 3) * 16;
#pragma unroll
    for (int i = 0; i < 2 * NL; i++)
      asm volatile("ld.global.nc.v4.b32 {%0,%1,%2,%3}, [%4];" : "=r"(wv[i].x), "=r"(wv[i].y), "=r"(wv[i].z), "=r"(wv[i].w)
                   : "l"(reinterpret_cast<const uint8_t*>(wqkv) + wo0 + (i & 1) * 96 * 1152 + (i / 2 + 1) * 384));
  }
  if (warp < 8) {
    asm volatile("setmaxnreg.inc.sync.aligned.u32 %0;" ::"n"(RA));
    float rv = -INFINITY;
    if (tid < 169) rv = __bfloat162float(rpb[head * 169 + tid]) * 1.4426950408889634f;
    if (tid < 192) {
      const int kc = (tid & 15) + 3, wc = (tid >> 4) % 6;
      sts128(tid < 96 ? sb + SM_K + kc * KS + wc * 128 + 48 : sb + SM_V + kc * 1536 + wc * 128 + (6 + (kc & 1)) * 16, make_uint4(0, 0, 0, 0));
    }
#pragma unroll
    for (int i = 0; i < 2 * NL; i++) sts128(wdst + (i & 1) * 3072 + (i / 2) * 18432, wv[i]);
    fence_async();
    asm volatile("bar.arrive 1, 384;" ::: "memory");
    if (tid < 182) asm volatile("st.shared.f32 [%0], %1;" ::"r"(sb + SM_RPB + tid * 4), "f"(rv) : "memory");
    const int jw = warp >> 2, j = jw ^ odd, w = warp & 3, wt = 4 * j + w;
    int variant = w;
    if (strip == 0 && j == 0 && w < 2) variant = 4;
    if (strip == 6 && j == 1 && w >= 2) variant = 5;
    const bool v1 = opq((uint32_t)(variant & 1)), v2 = opq((uint32_t)(variant & 2)), v4 = opq((uint32_t)(variant & 4));
    const uint32_t qa = opq(sb + SM_Q + (8 * j + 2 * w + ((lane >> 3) & 1)) * 768 + (lane >> 4) * 128 + (((lane & 7) * 16) ^ (((lane >> 3) & 1) * 64)));
    uint32_t oa = opq(sb + SM_O + j * 6144 + (2 * w + ((lane >> 3) & 1)) * 768 + (lane >> 4) * 128 + (lane & 7) * 16);
    uint64_t dA = opq(mkdesc(SBC + SM_K, 128, KS, 0) + j * (8 * KS / 16)), dB = opq(dA + (KSLOT >> 4));
    uint64_t dV[7];
#pragma unroll
    for (int i = 0; i < 7; i++) dV[i] = opq(mkdesc(SBC + SM_V, 768, 128, 0) + j * (8 * 1536 / 16) + i * 192);
    const uint32_t nbK = opq((uint32_t)(N_KRDY + jw)), nbQ = opq((uint32_t)(N_QK0 + jw)), nbV = opq((uint32_t)(N_VQ0 + jw)), nbP = opq((uint32_t)(N_PV0 + jw));
    asm volatile("barrier.cluster.wait.aligned;" ::: "memory");
    asm volatile("bar.sync 3, 256;" ::: "memory");
    float T[16];
    TRDECL;
    int b0, b1;
    uint32_t meta, ob = bar + B_ODONE * 8, fb = bar + B_OFREE * 8, fp = 1;
    const uint32_t tb = opq(sb + SM_RPB + (variant < 4 ? 3 : variant + 1 - 2 * w) * 4);
    const bool own = ((w ^ head) & 2) == 0;
    const uint32_t dst13 = sb + SM_TIN2 + head * 6144 + (2 * j + (w & 1)) * 1536, src13 = opq(own ? dst13 : sb + SM_S + (2 * j + (w & 1)) * 1536);
    const uint32_t snd[4] = {opq(own ? 0u : mapa(dst13, base + (head ^ 2))), opq(mapa(bar + (B_TIN + 2) * 8, base + (head ^ 2))),
                             opq(mapa(dst13, base + (w & 2) + (~head & 1))), opq(mapa(bar + (B_TIN + 3) * 8, base + (w & 2) + (~head & 1)))};
    BandCfg nx;
    band_cfg(0, tb, nx);
    band_load(nx, T, b0, b1, meta);
    band_cfg(1, tb, nx);
    const uint32_t zero = opq(blockIdx.x >> 16);
    uint32_t special = opq(0x380Au << 1);
    uint32_t q[12];
    mbar_wait(bar + B_Q0 * 8, 0);
#pragma unroll
    for (int k = 0; k < 3; k++) ldsm4(qa + k * 256, q[4 * k], q[4 * k + 1], q[4 * k + 2], q[4 * k + 3]);
    nb_arrive(N_Q0, 384);
#pragma unroll 1
    for (int b = 0; b < 14; b++) {
      float SA[56], SB[56];
      TR(0, b, 0);
      if (jw) mbar_wait(bar + B_KIMP * 8, b & 1);
      nb_sync(nbK, 256);
      TR(0, b, 1);
      TR(0, b - 1, 9);
      wg_fence();
      wg_rs112<0>(SA, q[0], q[1], q[2], q[3], dA);
      wg_rs112<0>(SB, q[0], q[1], q[2], q[3], dB);
      wg_rs112<1>(SA, q[4], q[5], q[6], q[7], dA + 16);
      wg_rs112<1>(SB, q[4], q[5], q[6], q[7], dB + 16);
      wg_rs112<1>(SA, q[8], q[9], q[10], q[11], dA + 32);
      wg_rs112<1>(SB, q[8], q[9], q[10], q[11], dB + 32);
      wg_commit();
      nb_arrive(nbQ, 256);
      { const uint64_t t = dA; dA = dB; dB = t; }
      special >>= 1;
      if (special & 1) {
        if (b == 3) band_cfg(13, tb, nx);
        else {
          if (b == 1 || b == 13) band_load(nx, T, b0, b1, meta);
          if (b >= TB) {
            ob = bar + (b == 13 ? (own ? B_TIN + 2 : B_ODONE) : B_OTAIL + 2 * (b - TB) + jw) * 8;
            if (b > TB) { fb = bar + (B_TFREE + b - 12) * 8; fp = 0; }
            oa += b == 12 ? 0u - (SM_O - SM_Q) : (b == 13 ? src13 - (sb + SM_Q + wt * 1536) : 0);
          }
        }
      }
      TR(0, b, 2);
      wg_wait<0>(); pin(SA); pin(SB);
      mbar_arrive_elect(bar + B_KFREE * 8);
      TR(0, b, 3);
      TR(0, b - 1, 10);
      uint32_t P[28];
      float sx[8];
      if (v2) {
        if (v1) softmax_tile<6, 7>(SA, SB, T, b0, b1, P, sx, nbV, zero, qa, q); else softmax_tile<4, 5>(SA, SB, T, b0, b1, P, sx, nbV, zero, qa, q);
      } else if (!v4) {
        if (v1) softmax_tile<2, 3>(SA, SB, T, b0, b1, P, sx, nbV, zero, qa, q); else softmax_tile<0, 1>(SA, SB, T, b0, b1, P, sx, nbV, zero, qa, q);
      } else {
        if (v1) softmax_tile<4, 4>(SA, SB, T, b0, b1, P, sx, nbV, zero, qa, q); else softmax_tile<3, 3>(SA, SB, T, b0, b1, P, sx, nbV, zero, qa, q);
      }
      float O[24];
      TR(0, b, 4);
      wg_fence();
      wg_sp48<0>(O, P[0], P[1], P[2], P[3], dV[0], meta);
#pragma unroll
      for (int s = 1; s < 7; s++) wg_sp48<1>(O, P[4 * s], P[4 * s + 1], P[4 * s + 2], P[4 * s + 3], dV[s], meta);
      wg_commit();
      nb_arrive(nbP, 256);
      TR(0, b, 6);
      mbar_wait(fb, fp);
      wg_wait<0>(); pin(O);
      mbar_arrive_elect(bar + B_VFREE * 8);
      TR(0, b, 7);
      float ru, rl;
      asm("rcp.approx.ftz.f32 %0, %1;" : "=f"(ru) : "f"(((fmaf(O[0], 0.f, sx[0]) + sx[1]) + sx[2]) + sx[3]));
      asm("rcp.approx.ftz.f32 %0, %1;" : "=f"(rl) : "f"(((fmaf(O[2], 0.f, sx[4]) + sx[5]) + sx[6]) + sx[7]));
#pragma unroll
      for (int i = 0; i < 3; i++)
        stsm4(oa + i * 256, pack2(O[8 * i] * ru, O[8 * i + 1] * ru), pack2(O[8 * i + 2] * rl, O[8 * i + 3] * rl),
              pack2(O[8 * i + 4] * ru, O[8 * i + 5] * ru), pack2(O[8 * i + 6] * rl, O[8 * i + 7] * rl));
      publish(ob);
      fp ^= 1;
      meta ^= 0x55555555u;
      TR(0, b, 8);
    }
    asm volatile("{\n.reg .pred p, q;\nsetp.ne.b32 q, %1, 0;\nelect.sync _|p, 0xffffffff;\nand.pred q, q, p;\n"
                 "@q cp.async.bulk.shared::cluster.shared::cta.mbarrier::complete_tx::bytes [%1], [%0], 1536, [%2];\n"
                 "@p cp.async.bulk.shared::cluster.shared::cta.mbarrier::complete_tx::bytes [%3], [%0], 1536, [%4];\n}"
                 ::"r"(src13), "r"(snd[0]), "r"(snd[1]), "r"(snd[2]), "r"(snd[3]) : "memory");
    nb_arrive(3, 384);
    TRDUMP;
    cluster_sync();
  } else if (warp < 12) {
    TRDECL;
    TR(2, -3, 0);
    asm volatile("setmaxnreg.inc.sync.aligned.u32 %0;" ::"n"(RG));
    TR(2, -3, 1);
    GemmCtx c;
    c.bar = bar;
    const int gw = warp - 8, tk = gw * 16 + (lane & 15), hi = lane >> 4;
    { const int col = tk >> 2, i = tk & 3;
      c.kC = sb + SM_K + (col + 3) * KS + hi * 128 + i * 16;
      c.vC[0] = sb + SM_V + (col + 3) * 1536 + hi * 128 + (2 * i + ((col + 3) & 1)) * 16;
      c.qC[0] = sb + SM_Q + col * 768 + hi * 128 + (col & 1) * 64 + i * 16; }
    { const int kc = gw - 1 + 19 * odd, i = lane & 7; c.hvalid = gw > 0; c.edge = gw == (odd ? 0 : 3);
      c.kH = sb + SM_K + kc * KS + (lane >> 3) * 128 + i * 16;
      c.vH[0] = sb + SM_V + kc * 1536 + (lane >> 3) * 128 + (i >> 2) * 768 + (2 * (i & 3) + ((kc ^ (i >> 2)) & 1)) * 16; }
    Stage xs[3];
#pragma unroll
    for (int i = 0; i < 3; i++) {
      const int p = (i + 1) % 3;
      xs[i].lo = (uint32_t)mkdesc(SBC + SM_X + p * 24576, 16, 0, 0); xs[i].full = bar + (B_FULL + p) * 8;
      xs[i].em = opq(mapa(bar + (B_EMPTY + p) * 8, base + p)); xs[i].par = 0;
    }
    c.never = x == nullptr;
    c.kC = opq(c.kC); c.kH = opq(c.kH);
    c.vC[1] = opq(c.vC[0] ^ 16); c.vC[0] = opq(c.vC[0]);
    c.vH[1] = opq(c.vH[0] ^ 16); c.vH[0] = opq(c.vH[0]);
    c.qC[1] = opq(c.qC[0] ^ 64); c.qC[0] = opq(c.qC[0]);
    c.spin = 0;
    c.hiA = (uint32_t)(mkdesc(0, 0, 1024, 1) >> 32) + (blockIdx.x >> 16); c.hiB = (uint32_t)(mkdesc(0, 0, 256, 3) >> 32) + (blockIdx.x >> 16);
    asm volatile("barrier.cluster.wait.aligned;" ::: "memory");
    TR(2, -3, 2);
#pragma unroll
    for (int i = 0; i < 2 * NL; i++) sts128(wdst + (i & 1) * 3072 + (i / 2) * 18432, wv[i]);
    fence_async();
    TR(2, -3, 3);
    asm volatile("bar.sync 1, 384;" ::: "memory");
    TR(2, -3, 4);
    mbar_wait(bar + B_WK * 8, 0);
    asm volatile("griddepcontrol.launch_dependents;");
    TR(2, -3, 5);
    uint32_t pk[12], pv[12], pq[12], hk1[6], hv1[6];
    gemm_first(c, pk, pv, pq, hk1, hv1, xs[0], xs[1], xs[2]);
    TR2(blockIdx.x, 4);
    c.hiA = opq(c.hiA); c.hiB = opq(c.hiB);
#pragma unroll 1
    for (int b = -1;; b += 2) {
      gemm_iter<1>(c, b, pk, pv, pq, hk1, hv1, xs[0], xs[1], xs[2] TRPASS);
      if (b == 11) break;
      gemm_iter<0>(c, b + 1, pk, pv, pq, hk1, hv1, xs[2], xs[0], xs[1] TRPASS);
      const Stage t = xs[2]; xs[2] = xs[1]; xs[1] = xs[0]; xs[0] = t;
    }
    TR2(blockIdx.x, 6);
    c.hiA = opq(c.hiA); c.hiB = opq(c.hiB);
    const uint32_t st = sb + gw * 3072;
    const uint32_t sta = st + (lane & 15) * 64 + ((hi ^ ((lane >> 1) & 3)) * 16);
    const int oc = ph * 112 + strip * 16 + 8 * (gw >> 1) + 4 * (head >> 1) + 2 * (gw & 1), och = pw * 6 + (head & 1) * 3;
    float D0[48], D1[48];
    if (lane < 4) mbar_arrive_remote(bar + B_WOFREE * 8, 2 * lane + (head & 1));
    dump12<128>(c.qC[1], pq);
    nb_sync(N_QK0, 256);
    nb_arrive(N_GO1, 256);
    fence_async();
    edge_ready(c, B_XV);
    nb_arrive(N_VQ0, 288); nb_arrive(N_VQ1, 288); nb_arrive(N_PV0, 256); nb_arrive(N_PV1, 256);
    nb_sync(N_QK1, 256);
    issue_halo<0, 8>(c, xs[2], D1);
    issue_halo<8, 12>(c, xs[2], D1);
    gwait<0>(c, B_KFREE);
    dump12<128>(c.kC, pk);
    if (c.edge) publish(bar + B_XK * 8);
    wg_wait<0>(); pin(D1);
    pack6(hk1, D1, 0);
    if (c.hvalid) dump6(c.kH, hk1);
    tail_free(bar + (B_TFREE + 1) * 8);
    pack6(hv1, D1, 24);
    fence_async();
    nb_arrive(N_KRDY, 256); nb_arrive(N_GO1, 256); nb_arrive(N_QK0, 256);
    gwait<0>(c, B_VFREE);
    dump12<128>(c.vC[0], pv);
    if (c.hvalid) dump6(c.vH[0], hv1);
    fence_async();
    edge_ready(c, B_XV);
    nb_arrive(N_VQ0, 288); nb_arrive(N_VQ1, 288);
    gwait<0>(c, B_WO);
    gwait<0>(c, B_TIN);
    TR(2, 13, 0);
    nb_sync(N_QK1, 256);
    issue_proj<SM_TIN0>(D0);
    wg_wait<0>(); pin(D0);
    TR(2, 13, 1);
    store_proj(D0, &mp.ot, st + SM_TST, sta + SM_TST, 8 * TB, oc, och);
    gwait<0>(c, B_TIN + 1);
    TR(2, 13, 2);
    nb_arrive(N_PV0, 256); nb_arrive(N_PV1, 256);
    nb_sync(3, 384);
    issue_proj<SM_TIN1>(D1);
    wg_wait<0>(); pin(D1);
    TR(2, 13, 3);
    store_proj(D1, &mp.ot, st + SM_TIN0, sta + SM_TIN0, 8 * TB + 8, oc, och);
    TR(2, 13, 4);
    gwait<0>(c, B_TIN + 2);
    TR(2, 13, 5);
    issue_proj_half<0>(D0, head & 1);
    gwait<0>(c, B_TIN + 3);
    TR(2, 13, 6);
    issue_proj_half<1>(D0, ~head & 1);
    asm volatile("barrier.cluster.arrive.relaxed.aligned;" ::: "memory");
    wg_wait<0>(); pin(D0);
    store_proj(D0, &mp.ot, st + SM_TIN0 + 12288, sta + SM_TIN0 + 12288, 8 * TB + 16, oc, och);
    TR(2, 13, 7);
    if (lane == 0) asm volatile("cp.async.bulk.wait_group.read 0;" ::: "memory");
    __syncwarp();
    TR(2, 13, 8);
    TR2(blockIdx.x, 2);
    TR2FLUSH(blockIdx.x);
    TRDUMP;
    asm volatile("barrier.cluster.wait.aligned;" ::: "memory");
  } else {
    asm volatile("setmaxnreg.dec.sync.aligned.u32 24;");
    if (warp == 15) {
      const int l = min(lane, 24), row = head + (l < 16 ? 0 : 4 * ((l - 16) / 3)), col = strip * 16 + (l < 16 ? l : (l - 16) % 3 + (odd ? 16 : (strip ? -3 : 0)));
      const uint8_t* p = reinterpret_cast<const uint8_t*>(x) + (uint32_t)(row * ROWB + (ph * 112 + col) * 768 + pw * 384);
#pragma unroll
      for (int i = 0; i < 3; i++) asm volatile("prefetch.global.L2 [%0];" ::"l"(p + i * 128));
    } else if (elect_one()) {
      if (warp == 12) {
        mbar_init(bar + B_WK * 8, 1);
#pragma unroll
        for (int i = 0; i < NL; i++) load_w(&mp.w, sb + SM_W + (3 * i + 5 - 2 * va) * 6144, bar + B_WK * 8, (i + 1) * 192 + head * 48 + 32 - 32 * va);
        asm volatile("prefetch.tensormap [%0];" ::"l"(head == 2 ? &mp.xh : &mp.xc) : "memory");
      } else if (warp == 13) {
#pragma unroll
        for (int i = 0; i < B_XK; i++) if (i != B_WK) mbar_init(bar + i * 8, (i >= B_EMPTY && i < B_TIN) || (i >= B_TFREE && i < B_WK) ? 16 : (i == B_TIN + 2 ? 5 : 1));
      } else {
#pragma unroll
        for (int i = B_XK; i < B_COUNT; i++) mbar_init(bar + i * 8, i < B_Q0 ? 2 : (i < B_ODONE ? (i == B_WOFREE ? 16 : 4) : (i == B_VFREE ? 9 : 8)));
        mbar_arrive(bar + B_XK * 8); mbar_arrive(bar + B_XV * 8);
      }
      asm volatile("fence.mbarrier_init.release.cluster;" ::: "memory");
    }
    __syncwarp();
    asm volatile("barrier.cluster.arrive.relaxed.aligned;" ::: "memory");
    if (warp != 12) asm volatile("barrier.cluster.wait.aligned;" ::: "memory");
    else {
      const int cc = ph * 112 + strip * 16, ch = cc + (odd ? 16 : (strip ? -3 : 0)), rh = strip ? -4 : 112;
      const uint32_t fb = opq(bar + (B_FULL + head) * 8), dst0 = sb + SM_X + head * 24576, c3 = opq((uint32_t)(pw * 3)), mask = opq(15u << base);
      int t = head == 0 ? 2 : head - 1;
      uint64_t mx = opq((uint64_t)(t != 1 ? &mp.xc : &mp.xh));
      uint32_t row = opq((uint32_t)(t != 1 ? 2 * t : rh)), col = opq((uint32_t)(t != 1 ? cc : ch)), dst = opq(dst0 + (t != 1 ? 0 : 2048));
#pragma unroll 1
      for (int n = 0;; n++) {
        if (n) mbar_wait(fb + (B_EMPTY - B_FULL) * 8, ~n & 1);
        else asm volatile("barrier.cluster.wait.aligned;" ::: "memory");
        if (head < 3) {
          asm volatile("{\n.reg .pred p;\n.reg .b16 m;\nelect.sync _|p, 0xffffffff;\ncvt.u16.u32 m, %7;\n"
                       "@p cp.async.bulk.tensor.4d.shared::cluster.global.mbarrier::complete_tx::bytes.multicast::cluster [%0], [%1, {%3,%4,%5,%6}], [%2], m;\n}"
                       ::"r"(dst), "l"(mx), "r"(fb), "r"(0), "r"(row), "r"(col), "r"(c3), "r"(mask) : "memory");
          if (lane < 4) remote_expect(mapa(fb, base + lane), dst == dst0 ? 24576 : 18432);
          __syncwarp();
        }
        if (n == 0 && elect_one()) {
#pragma unroll
          for (int i = 0; i < 3; i++) load_w(&mp.w, sb + SM_W + i * 6144, bar + B_WQ * 8, head * 48 + i * 16);
          mbar_expect(bar + B_WQ * 8, 18432);
        }
        __syncwarp();
        if (head == 3 || n == 11) break;
        t += 3;
        const int hn = t / 5;
        const bool core = t != 5 * hn + 1 && t != 35;
        mx = opq((uint64_t)(core ? &mp.xc : &mp.xh));
        row = opq((uint32_t)(core ? 4 * (t - hn - (t != 5 * hn)) : rh + 16 * hn)); col = opq((uint32_t)(core ? cc : ch)); dst = opq(dst0 + (core ? 0 : 2048));
        if (elect_one()) asm volatile("cp.async.bulk.prefetch.tensor.4d.L2.global [%0, {%1,%2,%3,%4}];" ::"l"(mx), "r"(0), "r"(row), "r"(col), "r"(c3) : "memory");
        __syncwarp();
      }
      mbar_wait(bar + B_WOFREE * 8, 0);
      if (elect_one()) {
        const int qr = (blockIdx.x & 7) >> 1;
#pragma unroll
        for (int i = 0; i < 3; i++)
          asm volatile("cp.async.bulk.tensor.2d.shared::cluster.global.mbarrier::complete_tx::bytes.multicast::cluster [%0], [%1, {%3,%4}], [%2], %5;"
                       ::"r"(sb + SM_TWO + i * 12288 + qr * 3072), "l"(&mp.wo), "r"(bar + B_WO * 8), "r"((head & 1) * 96 + i * 32), "r"(qr * 48),
                         "h"((uint16_t)(0x55 << (head & 1))) : "memory");
      }
      __syncwarp();
    }
    if (warp & 1) {
      const uint32_t partner = (blockIdx.x & 7) ^ 4;
      const int cs = odd ? 3 : (strip == 6 ? 15 : 16), cd = odd || strip == 6 ? 19 : 0;
      const uint32_t rb = opq(mapa(bar, partner));
      TRDECL;
      if (warp == 13) {
        const uint32_t dst = opq(mapa(sb + SM_V + cd * 1536, partner)), src = opq(sb + SM_V + cs * 1536);
#pragma unroll 1
        for (int b = 0;; b++) {
          const uint32_t pa = b & 1;
          nb_arrive(N_VQ0, 288);
          mbar_wait(bar + B_XV * 8, pa);
          TR(1, b, 0);
          if (elect_one()) { copy_remote(dst, src, 4608, rb + B_VIMP * 8); remote_expect(rb + B_VIMP * 8, 4608); }
          __syncwarp();
          TR(1, b, 1);
          mbar_wait(bar + B_VIMP * 8, pa);
          TR(1, b, 2);
          nb_arrive(N_VQ1, 288);
          if (elect_one()) remote_arrive(rb + B_VFREE * 8);
          __syncwarp();
          TR(1, b, 3);
          if (b == 13) break;
          mbar_wait(bar + B_VFREE * 8, pa);
          if (elect_one()) remote_arrive(rb + B_XV * 8);
          __syncwarp();
        }
      } else {
        const uint32_t dst = opq(mapa(sb + SM_K + cd * KS, partner)), src = opq(sb + SM_K + cs * KS);
#pragma unroll 1
        for (int b = 0;; b++) {
          const uint32_t pa = b & 1, so = (pa ^ 1) * KSLOT;
          mbar_wait(bar + B_XK * 8, pa);
          TR(1, b - 1, 4);
          if (elect_one()) {
            copy_remote(dst + so, src + so, 3 * KS, rb + B_KIMP * 8);
            if (b == 0) copy_remote(dst, src, 3 * KS, rb + B_KIMP * 8);
            remote_expect(rb + B_KIMP * 8, b ? 3 * KS : 6 * KS);
          }
          __syncwarp();
          TR(1, b - 1, 5);
          TR(1, b - 1, 7);
          if (b == 13) break;
          mbar_wait(bar + B_KFREE * 8, pa);
          if (elect_one()) remote_arrive(rb + B_XK * 8);
          __syncwarp();
        }
      }
      TRDUMP;
    }
    if (warp == 14) {
      int* flag = g_flags + (par * 7 + strip) * 2 * FS;
      if (elect_one()) {
        mbar_expect(bar + B_WK * 8, NL * 6144);
        mbar_expect(bar + B_WO * 8, 36864);
        mbar_expect(bar + B_TIN * 8, 24576); mbar_expect(bar + (B_TIN + 1) * 8, 24576); mbar_expect(bar + (B_TIN + 2) * 8, 6144); mbar_expect(bar + (B_TIN + 3) * 8, 12288);
      }
      __syncwarp();
#pragma unroll 1
      for (int b = 0; b < TB; b++) {
        mbar_wait(bar + B_ODONE * 8, b & 1);
        if (lane == 0) {
#pragma unroll 1
          for (int i = 0; i < 16; i += OCH) {
            asm volatile("cp.async.bulk.tensor.3d.global.shared::cta.bulk_group [%0, {%2,%3,%4}], [%1];"
                         ::"l"(&mp.os), "r"(sb + SM_O + i * 768), "r"(pw * 192), "r"(8 * b + 2 * head), "r"(ph * 112 + strip * 16 + i) : "memory");
            asm volatile("cp.async.bulk.commit_group;\ncp.async.bulk.wait_group 0;" ::: "memory");
          }
        }
        __syncwarp();
        mbar_arrive_elect(bar + B_OFREE * 8);
        if (lane == 0)
          asm volatile("fence.proxy.async.global;\nfence.acq_rel.gpu;\nred.relaxed.gpu.global.add.s32 [%0], 1;\nred.relaxed.gpu.global.add.s32 [%1], 1;"
                       ::"l"(flag + b * 56 * FS), "l"(flag + (b * 56 + 1) * FS) : "memory");
        __syncwarp();
      }
#pragma unroll 1
      for (int t = 0; t < 4; t++) {
        const int i = t >> 1, j = (t ^ odd) & 1, d = (lane + head + 1) & 3;
        const uint32_t dst = opq(mapa(sb + (i ? SM_TIN1 : SM_TIN0) + head * 6144 + j * 3072, base + d)), rb = opq(mapa(bar + (B_TIN + i) * 8, base + d));
        const uint32_t src = opq(sb + (i ? SM_Q : SM_O) + j * 6144 + (d & 2) * 1536);
        if (!(t & 1)) mbar_wait(bar + (B_TFREE + i) * 8, 0);
        mbar_wait(bar + (B_OTAIL + t) * 8, 0);
        if (lane < 4) copy_remote(dst, src, 3072, rb);
        __syncwarp();
      }
    }
    cluster_sync();
  }
}

constexpr int NSTB = 6;
constexpr int NTB = TB * 56;
constexpr int SM_B_ST = 0;
constexpr int SM_B_IN = 73728;
constexpr int SM_B_W = SM_B_IN + 3 * 24576;
constexpr int SM_B_BAR = SM_B_IN + NSTB * 24576;
constexpr int SM_B_TOTAL = SM_B_BAR + 512;
struct MapsB { CUtensorMap oi, oo, wo; };

__global__ void __launch_bounds__(512, 1)
na_proj_kernel(const __grid_constant__ MapsB mp) {
  extern __shared__ __align__(1024) uint8_t smem_raw[];
  const uint32_t sb = smem_u32(smem_raw);
  if ((sb & 0x3FFFF) != SBC) return;
  const uint32_t bar = sb + SM_B_BAR;
  const int tid = threadIdx.x, lane = tid & 31;
  const int warp = __shfl_sync(0xffffffffu, tid >> 5, 0);
  TR2START;
  TRB(47, 0);
  if (warp == 12 && elect_one()) {
#pragma unroll
    for (int i = 0; i <= 2 * NSTB; i++) mbar_init(bar + i * 8, i < NSTB || i == 2 * NSTB ? 1 : 12);
    asm volatile("st.shared.u32 [%0], 0;" ::"r"(bar + 120) : "memory");
    mbar_expect(bar + 2 * NSTB * 8, 73728);
#pragma unroll
    for (int i = 0; i < 2; i++)
      asm volatile("cp.async.bulk.tensor.3d.shared::cluster.global.mbarrier::complete_tx::bytes [%0], [%1, {%3,%4,%5}], [%2];"
                   ::"r"(sb + SM_B_W + i * 36864), "l"(&mp.wo), "r"(bar + 2 * NSTB * 8), "r"(0), "r"(0), "r"(i * 3) : "memory");
  }
  __syncthreads();
  const int step = gridDim.x;
  if (warp == 15) {
    int so = 0;
    nb_arrive(4, 288); nb_arrive(5, 288); nb_arrive(6, 288);
#pragma unroll 1
    for (int n = blockIdx.x, tk = 0; n < NTB; n += step, tk++) {
      uint32_t cc = 0;
#pragma unroll
      for (int wg = 0; wg < 3; wg++) {
        if (lane == 0) asm volatile("cp.async.bulk.wait_group.read 5;" ::: "memory");
        nb_sync(1 + wg, 160);
        if (wg == 0 || n + step < NTB) nb_arrive(4 + wg, 288);
        if (wg == 0) asm volatile("ld.shared.u32 %0, [%1];" : "=r"(cc) : "r"(bar + 128 + tk * 4) : "memory");
        if (lane == 0) {
          asm volatile("cp.async.bulk.tensor.4d.global.shared::cta.bulk_group [%0, {%2,%3,%4,%5}], [%1];"
                       ::"l"(&mp.oo), "r"(sb + SM_B_ST + wg * 8192 + so), "r"(0), "r"((cc >> 8) & 255), "r"(cc >> 16), "r"((cc & 1) * 3 + wg) : "memory");
          asm volatile("cp.async.bulk.commit_group;" ::: "memory");
        }
        __syncwarp();
      }
      so = so == 49152 ? 0 : so + 24576;
    }
    if (lane == 0) asm volatile("cp.async.bulk.wait_group.read 0;" ::: "memory");
  } else if (warp >= 12) {
    nb_sync(7, 480);
#pragma unroll 1
    for (int n = blockIdx.x + (warp - 12) * step; n < NTB; n += 3 * step) {
      const int b = n / 56, rem = n - b * 56, par = rem / 14;
      const int c0 = opq((uint32_t)(par & 1)), c1 = opq((uint32_t)(8 * b)), c2 = opq((uint32_t)((par >> 1) * 112 + (rem - par * 14) * 8));
      int v; uint32_t spin = 0, tk = 0;
      do { asm volatile("ld.acquire.gpu.global.s32 %0, [%1];" : "=r"(v) : "l"(g_flags + n * FS) : "memory"); } while (v < 4 && ++spin < SPIN_LIMIT);
      if (lane == 0) asm volatile("atom.shared.add.u32 %0, [%1], 1;" : "=r"(tk) : "r"(bar + 120) : "memory");
      asm volatile("fence.proxy.async.global;" ::: "memory");
      tk = __shfl_sync(0xffffffffu, tk, 0);
      TRB(tk, 0);
      const uint32_t use = tk / NSTB, sg = tk - use * NSTB;
      if (use) mbar_wait(bar + (NSTB + sg) * 8, (use - 1) & 1);
      TRB(tk, 1);
      if (elect_one()) {
        asm volatile("st.shared.u32 [%0], %1;" ::"r"(bar + 128 + tk * 4), "r"(c0 | c1 << 8 | c2 << 16) : "memory");
        mbar_expect(bar + sg * 8, 24576);
        asm volatile("cp.async.bulk.tensor.3d.shared::cluster.global.mbarrier::complete_tx::bytes [%0], [%1, {%3,%4,%5}], [%2];"
                     ::"r"(sb + SM_B_IN + sg * 24576), "l"(&mp.oi), "r"(bar + sg * 8), "r"(c0 * 192), "r"(c1), "r"(c2) : "memory");
        g_flags[n * FS] = 0;
      }
      __syncwarp();
    }
  } else {
    const int wg = warp >> 2, w = warp & 3;
    uint32_t a[48];
    mbar_wait(bar + 2 * NSTB * 8, 0);
    {
      const int k = (lane & 7) + (lane >> 4) * 8, ch = (warp & 1) * 2 + ((lane >> 3) & 1);
      const uint32_t wa = sb + SM_B_W + (warp >> 1) * 12288 + k * 64 + ((ch ^ ((k >> 1) & 3)) * 16);
#pragma unroll
      for (int i = 0; i < 12; i++)
        asm volatile("ldmatrix.sync.aligned.m8n8.x4.trans.shared.b16 {%0,%1,%2,%3}, [%4];"
                     : "=r"(a[4 * i]), "=r"(a[4 * i + 1]), "=r"(a[4 * i + 2]), "=r"(a[4 * i + 3]) : "r"(wa + i * 1024) : "memory");
    }
    nb_sync(7, 480);
    TRB(47, 1);
    const uint32_t sta = opq(sb + SM_B_ST + wg * 8192 + ((lane & 7) + (lane >> 4) * 8) * 128 + (((2 * w + ((lane >> 3) & 1)) ^ (lane & 7)) * 16));
    const uint32_t hi = opq((uint32_t)(mkdesc(0, 0, 3072, 0) >> 32) + (blockIdx.x >> 16)), bb = opq(bar);
    const uint32_t nbT = opq((uint32_t)(4 + wg)), nbN = opq((uint32_t)(wg == 2 ? 4 : 5 + wg)), nbD = opq((uint32_t)(1 + wg));
    int left = (NTB - blockIdx.x + step - 1) / step;
    if (wg == 2) nb_arrive(4, 288);
#pragma unroll 1
    for (uint32_t ph = 0;; ph ^= 1) {
#pragma unroll
      for (int sg = 0; sg < NSTB; sg++) {
        constexpr uint64_t db = mkdesc(SBC + SM_B_IN, 128, 3072, 0);
        float D[32];
        mbar_wait(bb + sg * 8, ph);
        nb_sync(nbT, 288);
        wg_fence();
        wg_rs64<0>(D, a[0], a[1], a[2], a[3], dsc(db + sg * 1536, hi));
#pragma unroll
        for (int k = 1; k < 12; k++) wg_rs64<1>(D, a[4 * k], a[4 * k + 1], a[4 * k + 2], a[4 * k + 3], dsc(db + sg * 1536 + k * 16, hi));
        wg_commit();
        nb_arrive(nbN, 288);
        wg_wait<0>(); pin(D);
        mbar_arrive_elect(bb + (NSTB + sg) * 8);
#pragma unroll
        for (int q = 0; q < 4; q++)
          asm volatile("stmatrix.sync.aligned.m8n8.x4.trans.shared.b16 [%0], {%1,%2,%3,%4};" ::"r"(sta + (sg % 3) * 24576 + q * 2048),
                       "r"(pack2(D[8 * q], D[8 * q + 1])), "r"(pack2(D[8 * q + 2], D[8 * q + 3])), "r"(pack2(D[8 * q + 4], D[8 * q + 5])), "r"(pack2(D[8 * q + 6], D[8 * q + 7])) : "memory");
        fence_async();
        nb_arrive(nbD, 160);
        if (wg == 0) TRB(31 - left, 5);
        if (--left == 0) goto done;
      }
    }
  done:
    if (wg == 0) nb_arrive(4, 288);
    TR2(132 + blockIdx.x, 2);
    TR2FLUSH(132 + blockIdx.x);
  }
}

typedef CUresult (*EncodeFn)(CUtensorMap*, CUtensorMapDataType, cuuint32_t, void*, const cuuint64_t*, const cuuint64_t*, const cuuint32_t*,
                             const cuuint32_t*, CUtensorMapInterleave, CUtensorMapSwizzle, CUtensorMapL2promotion, CUtensorMapFloatOOBfill);
static EncodeFn g_enc = nullptr;
static void make_map(CUtensorMap* m, const void* p, int rank, const cuuint64_t* dim, const cuuint64_t* str, const cuuint32_t* box, CUtensorMapSwizzle sw) {
  const cuuint32_t ones[5] = {1, 1, 1, 1, 1};
  g_enc(m, CU_TENSOR_MAP_DATA_TYPE_BFLOAT16, rank, (void*)p, dim, str, box, ones, CU_TENSOR_MAP_INTERLEAVE_NONE, sw,
        CU_TENSOR_MAP_L2_PROMOTION_L2_128B, CU_TENSOR_MAP_FLOAT_OOB_FILL_NONE);
}

extern "C" void kernel_launch(void* const* d_in, const int* in_sizes, int n_in, void* d_out, int out_size) {
  const __nv_bfloat16* x = (const __nv_bfloat16*)d_in[0];
  const __nv_bfloat16* wqkv = (const __nv_bfloat16*)d_in[1];
  const __nv_bfloat16* wo = (const __nv_bfloat16*)d_in[2];
  const __nv_bfloat16* rpb = (const __nv_bfloat16*)d_in[3];

  if (!g_enc) {
    void* fn = nullptr; cudaDriverEntryPointQueryResult qr;
    cudaGetDriverEntryPoint("cuTensorMapEncodeTiled", &fn, cudaEnableDefault, &qr);
    g_enc = (EncodeFn)fn;
    cudaFuncSetAttribute(na_attn_kernel, cudaFuncAttributeMaxDynamicSharedMemorySize, SM_A_TOTAL);
    cudaFuncSetAttribute(na_proj_kernel, cudaFuncAttributeMaxDynamicSharedMemorySize, SM_B_TOTAL);
  }
  Maps ma; MapsB mb;
  { cuuint64_t dim[4] = {64, 112, 224, 6}, str[3] = {(cuuint64_t)ROWB, 768, 128};
    cuuint32_t box[4] = {64, 4, 16, 3}, boxh[4] = {64, 16, 3, 3}, boxo[4] = {64, 8, 8, 1};
    make_map(&ma.xc, x, 4, dim, str, box, CU_TENSOR_MAP_SWIZZLE_128B);
    make_map(&ma.xh, x, 4, dim, str, boxh, CU_TENSOR_MAP_SWIZZLE_128B);
    make_map(&mb.oo, d_out, 4, dim, str, boxo, CU_TENSOR_MAP_SWIZZLE_128B); }
  { cuuint64_t dim[3] = {384, 112, 224}, str[2] = {(cuuint64_t)ROWB, 768};
    cuuint32_t box[3] = {192, 8, 8}, boxs[3] = {192, 2, OCH};
    make_map(&mb.oi, d_out, 3, dim, str, box, CU_TENSOR_MAP_SWIZZLE_NONE);
    make_map(&ma.os, d_out, 3, dim, str, boxs, CU_TENSOR_MAP_SWIZZLE_NONE); }
  { cuuint64_t dim[4] = {32, 112, 224, 12}, str[3] = {(cuuint64_t)ROWB, 768, 64};
    cuuint32_t box[4] = {32, 8, 2, 3};
    make_map(&ma.ot, d_out, 4, dim, str, box, CU_TENSOR_MAP_SWIZZLE_64B); }
  { cuuint64_t dim[2] = {576, 192}, str[1] = {1152};
    cuuint32_t box[2] = {16, 192};
    make_map(&ma.w, wqkv, 2, dim, str, box, CU_TENSOR_MAP_SWIZZLE_32B); }
  { cuuint64_t dim[3] = {32, 192, 6}, str[2] = {384, 64};
    cuuint32_t box[3] = {32, 192, 3};
    make_map(&mb.wo, wo, 3, dim, str, box, CU_TENSOR_MAP_SWIZZLE_64B); }
  { cuuint64_t dim[2] = {192, 192}, str[1] = {384};
    cuuint32_t box[2] = {32, 48};
    make_map(&ma.wo, wo, 2, dim, str, box, CU_TENSOR_MAP_SWIZZLE_64B); }
  na_attn_kernel<<<112, 512, SM_A_TOTAL>>>(x, wqkv, rpb, ma);
  cudaLaunchConfig_t cfg = {};
  cfg.gridDim = dim3(20); cfg.blockDim = dim3(512); cfg.dynamicSmemBytes = SM_B_TOTAL; cfg.stream = cudaStreamPerThread;
  cudaLaunchAttribute at[1];
  at[0].id = cudaLaunchAttributeProgrammaticStreamSerialization; at[0].val.programmaticStreamSerializationAllowed = 1;
  cfg.attrs = at; cfg.numAttrs = 1;
  cudaLaunchKernelEx(&cfg, na_proj_kernel, mb);
}
```

```cpp
#include <cuda_runtime.h>
#include <cuda_bf16.h>
#include <cuda.h>
#include <stdint.h>

#define SPIN_LIMIT (1u << 18)

__device__ __forceinline__ uint32_t smem_u32(const void* p) { return (uint32_t)__cvta_generic_to_shared(p); }
__device__ __forceinline__ void wg_fence() { asm volatile("wgmma.fence.sync.aligned;" ::: "memory"); }
__device__ __forceinline__ void wg_commit() { asm volatile("wgmma.commit_group.sync.aligned;" ::: "memory"); }
template <int N> __device__ __forceinline__ void wg_wait() { asm volatile("wgmma.wait_group.sync.aligned %0;" ::"n"(N) : "memory"); }
template <int N> __device__ __forceinline__ void pin(float (&d)[N]) {
#pragma unroll
  for (int i = 0; i < N; i++) asm volatile("" : "+f"(d[i])::"memory");
}
__host__ __device__ constexpr uint64_t mkdesc(uint32_t addr, uint32_t lbo, uint32_t sbo, uint32_t sw) {
  return (uint64_t)((addr & 0x3FFFF) >> 4) | ((uint64_t)(lbo >> 4) << 16) | ((uint64_t)(sbo >> 4) << 32) | ((uint64_t)sw << 62);
}
__device__ __forceinline__ void mbar_init(uint32_t bar, uint32_t cnt) { asm volatile("mbarrier.init.shared::cta.b64 [%0], %1;" ::"r"(bar), "r"(cnt) : "memory"); }
__device__ __forceinline__ void mbar_arrive(uint32_t bar) { asm volatile("mbarrier.arrive.shared::cta.b64 _, [%0];" ::"r"(bar) : "memory"); }
__device__ __forceinline__ bool elect_one() {
  uint32_t r; asm volatile("{\n.reg .pred p;\nelect.sync _|p, 0xffffffff;\nselp.u32 %0, 1, 0, p;\n}" : "=r"(r)); return r;
}
__device__ __forceinline__ void mbar_arrive_elect(uint32_t bar) {
  asm volatile("{\n.reg .pred p;\nelect.sync _|p, 0xffffffff;\n@p mbarrier.arrive.shared::cta.b64 _, [%0];\n}" ::"r"(bar) : "memory");
}
__device__ __forceinline__ void mbar_expect(uint32_t bar, uint32_t bytes) { asm volatile("mbarrier.arrive.expect_tx.shared::cta.b64 _, [%0], %1;" ::"r"(bar), "r"(bytes) : "memory"); }
__device__ __forceinline__ void mbar_arrive_remote(uint32_t bar, uint32_t cta) {
  asm volatile("{\n.reg .b32 ra;\nmapa.shared::cluster.u32 ra, %0, %1;\nmbarrier.arrive.relaxed.cluster.shared::cluster.b64 _, [ra];\n}" ::"r"(bar), "r"(cta) : "memory");
}
__device__ __forceinline__ void mbar_wait(uint32_t bar, uint32_t parity) {
  asm volatile("{\n.reg .pred p;\n.reg .b32 n;\nmov.b32 n, 0;\nWL:\nmbarrier.try_wait.parity.shared::cta.b64 p, [%0], %1;\n@p bra WD;\n"
               "add.u32 n, n, 1;\nsetp.lt.u32 p, n, 65536;\n@p bra WL;\nWD:\n}" ::"r"(bar), "r"(parity) : "memory");
}
__device__ __forceinline__ void nb_sync(int id, int n) { asm volatile("bar.sync %0, %1;" ::"r"(id), "r"(n) : "memory"); }
__device__ __forceinline__ void nb_arrive(int id, int n) { asm volatile("bar.arrive %0, %1;" ::"r"(id), "r"(n) : "memory"); }
__device__ __forceinline__ uint32_t opq(uint32_t x) { uint32_t r; asm volatile("mov.b32 %0, %1;" : "=r"(r) : "r"(x)); return r; }
__device__ __forceinline__ uint64_t opq(uint64_t x) { uint64_t r; asm volatile("mov.b64 %0, %1;" : "=l"(r) : "l"(x)); return r; }
__device__ __forceinline__ uint32_t mapa(uint32_t a, uint32_t cta) { uint32_t r; asm("mapa.shared::cluster.u32 %0, %1, %2;" : "=r"(r) : "r"(a), "r"(cta)); return r; }
__device__ __forceinline__ void fence_async() { asm volatile("fence.proxy.async.shared::cta;" ::: "memory"); }
__device__ __forceinline__ void cluster_sync() {
  asm volatile("barrier.cluster.arrive.relaxed.aligned;\nbarrier.cluster.wait.aligned;" ::: "memory");
}
__device__ __forceinline__ uint32_t pack2(float lo, float hi) {
  uint32_t r; asm("cvt.rn.bf16x2.f32 %0, %1, %2;" : "=r"(r) : "f"(hi), "f"(lo)); return r;
}
__device__ __forceinline__ void stsm4(uint32_t a, uint32_t r0, uint32_t r1, uint32_t r2, uint32_t r3) {
  asm volatile("stmatrix.sync.aligned.m8n8.x4.shared.b16 [%0], {%1,%2,%3,%4};" ::"r"(a), "r"(r0), "r"(r1), "r"(r2), "r"(r3) : "memory");
}
__device__ __forceinline__ void ldsm4(uint32_t a, uint32_t& r0, uint32_t& r1, uint32_t& r2, uint32_t& r3) {
  asm volatile("ldmatrix.sync.aligned.m8n8.x4.shared.b16 {%0,%1,%2,%3}, [%4];" : "=r"(r0), "=r"(r1), "=r"(r2), "=r"(r3) : "r"(a) : "memory");
}
__device__ __forceinline__ void sts128(uint32_t a, uint4 v) {
  asm volatile("st.shared.v4.b32 [%0], {%1,%2,%3,%4};" ::"r"(a), "r"(v.x), "r"(v.y), "r"(v.z), "r"(v.w) : "memory");
}
__device__ __forceinline__ float lds_f32(uint32_t a) { float v; asm volatile("ld.shared.f32 %0, [%1];" : "=f"(v) : "r"(a)); return v; }
__device__ __forceinline__ float ex2(float x) { float y; asm("ex2.approx.ftz.f32 %0, %1;" : "=f"(y) : "f"(x)); return y; }

template<int SC> __device__ __forceinline__ void wg_ss144(float (&d)[72], uint64_t da, uint64_t db) {
  asm volatile("{\n.reg .pred p;\nsetp.ne.b32 p, %74, 0;\nwgmma.mma_async.sync.aligned.m64n144k16.f32.bf16.bf16 {%0,%1,%2,%3,%4,%5,%6,%7,%8,%9,%10,%11,%12,%13,%14,%15,%16,%17,%18,%19,%20,%21,%22,%23,%24,%25,%26,%27,%28,%29,%30,%31,%32,%33,%34,%35,%36,%37,%38,%39,%40,%41,%42,%43,%44,%45,%46,%47,%48,%49,%50,%51,%52,%53,%54,%55,%56,%57,%58,%59,%60,%61,%62,%63,%64,%65,%66,%67,%68,%69,%70,%71}, %72, %73, p, 1, 1, 0, 1;\n}\n"
    : "+f"(d[0]),"+f"(d[1]),"+f"(d[2]),"+f"(d[3]),"+f"(d[4]),"+f"(d[5]),"+f"(d[6]),"+f"(d[7]),"+f"(d[8]),"+f"(d[9]),"+f"(d[10]),"+f"(d[11]),"+f"(d[12]),"+f"(d[13]),"+f"(d[14]),"+f"(d[15]),"+f"(d[16]),"+f"(d[17]),"+f"(d[18]),"+f"(d[19]),"+f"(d[20]),"+f"(d[21]),"+f"(d[22]),"+f"(d[23]),"+f"(d[24]),"+f"(d[25]),"+f"(d[26]),"+f"(d[27]),"+f"(d[28]),"+f"(d[29]),"+f"(d[30]),"+f"(d[31]),"+f"(d[32]),"+f"(d[33]),"+f"(d[34]),"+f"(d[35]),"+f"(d[36]),"+f"(d[37]),"+f"(d[38]),"+f"(d[39]),"+f"(d[40]),"+f"(d[41]),"+f"(d[42]),"+f"(d[43]),"+f"(d[44]),"+f"(d[45]),"+f"(d[46]),"+f"(d[47]),"+f"(d[48]),"+f"(d[49]),"+f"(d[50]),"+f"(d[51]),"+f"(d[52]),"+f"(d[53]),"+f"(d[54]),"+f"(d[55]),"+f"(d[56]),"+f"(d[57]),"+f"(d[58]),"+f"(d[59]),"+f"(d[60]),"+f"(d[61]),"+f"(d[62]),"+f"(d[63]),"+f"(d[64]),"+f"(d[65]),"+f"(d[66]),"+f"(d[67]),"+f"(d[68]),"+f"(d[69]),"+f"(d[70]),"+f"(d[71]) : "l"(da), "l"(db), "n"(SC));
}
template<int SC> __device__ __forceinline__ void wg_ss96(float (&d)[48], uint64_t da, uint64_t db) {
  asm volatile("{\n.reg .pred p;\nsetp.ne.b32 p, %50, 0;\nwgmma.mma_async.sync.aligned.m64n96k16.f32.bf16.bf16 {%0,%1,%2,%3,%4,%5,%6,%7,%8,%9,%10,%11,%12,%13,%14,%15,%16,%17,%18,%19,%20,%21,%22,%23,%24,%25,%26,%27,%28,%29,%30,%31,%32,%33,%34,%35,%36,%37,%38,%39,%40,%41,%42,%43,%44,%45,%46,%47}, %48, %49, p, 1, 1, 0, 1;\n}\n"
    : "+f"(d[0]),"+f"(d[1]),"+f"(d[2]),"+f"(d[3]),"+f"(d[4]),"+f"(d[5]),"+f"(d[6]),"+f"(d[7]),"+f"(d[8]),"+f"(d[9]),"+f"(d[10]),"+f"(d[11]),"+f"(d[12]),"+f"(d[13]),"+f"(d[14]),"+f"(d[15]),"+f"(d[16]),"+f"(d[17]),"+f"(d[18]),"+f"(d[19]),"+f"(d[20]),"+f"(d[21]),"+f"(d[22]),"+f"(d[23]),"+f"(d[24]),"+f"(d[25]),"+f"(d[26]),"+f"(d[27]),"+f"(d[28]),"+f"(d[29]),"+f"(d[30]),"+f"(d[31]),"+f"(d[32]),"+f"(d[33]),"+f"(d[34]),"+f"(d[35]),"+f"(d[36]),"+f"(d[37]),"+f"(d[38]),"+f"(d[39]),"+f"(d[40]),"+f"(d[41]),"+f"(d[42]),"+f"(d[43]),"+f"(d[44]),"+f"(d[45]),"+f"(d[46]),"+f"(d[47]) : "l"(da), "l"(db), "n"(SC));
}
template<int SC> __device__ __forceinline__ void wg_rs112(float (&d)[56], uint32_t a0, uint32_t a1, uint32_t a2, uint32_t a3, uint64_t db) {
  asm volatile("{\n.reg .pred p;\nsetp.ne.b32 p, %61, 0;\nwgmma.mma_async.sync.aligned.m64n112k16.f32.bf16.bf16 {%0,%1,%2,%3,%4,%5,%6,%7,%8,%9,%10,%11,%12,%13,%14,%15,%16,%17,%18,%19,%20,%21,%22,%23,%24,%25,%26,%27,%28,%29,%30,%31,%32,%33,%34,%35,%36,%37,%38,%39,%40,%41,%42,%43,%44,%45,%46,%47,%48,%49,%50,%51,%52,%53,%54,%55}, {%56,%57,%58,%59}, %60, p, 1, 1, 0;\n}\n"
    : "+f"(d[0]),"+f"(d[1]),"+f"(d[2]),"+f"(d[3]),"+f"(d[4]),"+f"(d[5]),"+f"(d[6]),"+f"(d[7]),"+f"(d[8]),"+f"(d[9]),"+f"(d[10]),"+f"(d[11]),"+f"(d[12]),"+f"(d[13]),"+f"(d[14]),"+f"(d[15]),"+f"(d[16]),"+f"(d[17]),"+f"(d[18]),"+f"(d[19]),"+f"(d[20]),"+f"(d[21]),"+f"(d[22]),"+f"(d[23]),"+f"(d[24]),"+f"(d[25]),"+f"(d[26]),"+f"(d[27]),"+f"(d[28]),"+f"(d[29]),"+f"(d[30]),"+f"(d[31]),"+f"(d[32]),"+f"(d[33]),"+f"(d[34]),"+f"(d[35]),"+f"(d[36]),"+f"(d[37]),"+f"(d[38]),"+f"(d[39]),"+f"(d[40]),"+f"(d[41]),"+f"(d[42]),"+f"(d[43]),"+f"(d[44]),"+f"(d[45]),"+f"(d[46]),"+f"(d[47]),"+f"(d[48]),"+f"(d[49]),"+f"(d[50]),"+f"(d[51]),"+f"(d[52]),"+f"(d[53]),"+f"(d[54]),"+f"(d[55]) : "r"(a0), "r"(a1), "r"(a2), "r"(a3), "l"(db), "n"(SC));
}
template<int SC> __device__ __forceinline__ void wg_sp48(float (&d)[24], uint32_t a0, uint32_t a1, uint32_t a2, uint32_t a3, uint64_t db, uint32_t meta) {
  asm volatile("{\n.reg .pred p;\nsetp.ne.b32 p, %30, 0;\nwgmma.mma_async.sp.sync.aligned.m64n48k32.f32.bf16.bf16 {%0,%1,%2,%3,%4,%5,%6,%7,%8,%9,%10,%11,%12,%13,%14,%15,%16,%17,%18,%19,%20,%21,%22,%23}, {%24,%25,%26,%27}, %28, %29, 0, p, 1, 1, 1;\n}\n"
    : "+f"(d[0]),"+f"(d[1]),"+f"(d[2]),"+f"(d[3]),"+f"(d[4]),"+f"(d[5]),"+f"(d[6]),"+f"(d[7]),"+f"(d[8]),"+f"(d[9]),"+f"(d[10]),"+f"(d[11]),"+f"(d[12]),"+f"(d[13]),"+f"(d[14]),"+f"(d[15]),"+f"(d[16]),"+f"(d[17]),"+f"(d[18]),"+f"(d[19]),"+f"(d[20]),"+f"(d[21]),"+f"(d[22]),"+f"(d[23]) : "r"(a0), "r"(a1), "r"(a2), "r"(a3), "l"(db), "r"(meta), "n"(SC));
}
template<int SC> __device__ __forceinline__ void wg_rs64(float (&d)[32], uint32_t a0, uint32_t a1, uint32_t a2, uint32_t a3, uint64_t db) {
  asm volatile("{\n.reg .pred p;\nsetp.ne.b32 p, %37, 0;\nwgmma.mma_async.sync.aligned.m64n64k16.f32.bf16.bf16 {%0,%1,%2,%3,%4,%5,%6,%7,%8,%9,%10,%11,%12,%13,%14,%15,%16,%17,%18,%19,%20,%21,%22,%23,%24,%25,%26,%27,%28,%29,%30,%31}, {%32,%33,%34,%35}, %36, p, 1, 1, 0;\n}\n"
    : "+f"(d[0]),"+f"(d[1]),"+f"(d[2]),"+f"(d[3]),"+f"(d[4]),"+f"(d[5]),"+f"(d[6]),"+f"(d[7]),"+f"(d[8]),"+f"(d[9]),"+f"(d[10]),"+f"(d[11]),"+f"(d[12]),"+f"(d[13]),"+f"(d[14]),"+f"(d[15]),"+f"(d[16]),"+f"(d[17]),"+f"(d[18]),"+f"(d[19]),"+f"(d[20]),"+f"(d[21]),"+f"(d[22]),"+f"(d[23]),"+f"(d[24]),"+f"(d[25]),"+f"(d[26]),"+f"(d[27]),"+f"(d[28]),"+f"(d[29]),"+f"(d[30]),"+f"(d[31]) : "r"(a0), "r"(a1), "r"(a2), "r"(a3), "l"(db), "n"(SC));
}

constexpr uint32_t SBC = 1024;
constexpr int ROWB = 2 * 224 * 384;
constexpr int TB = 11;
constexpr int KS = 832;
constexpr int KSLOT = 22 * KS;
constexpr int SM_X = 0;
constexpr int SM_W = SM_X + 3 * 24576;
constexpr int SM_K = SM_W + 55296;
constexpr int SM_V = SM_K + 2 * KSLOT;
constexpr int SM_Q = SM_V + 22 * 1536;
constexpr int SM_O = SM_Q + 12288;
constexpr int SM_S = SM_O + 12288;
constexpr int SM_RPB = SM_S + 6144;
constexpr int SM_BAR = SM_RPB + 768;
constexpr int SM_A_TOTAL = SM_BAR + 256;
constexpr int SM_TIN0 = SM_X + 24576, SM_TIN1 = SM_X, SM_TIN2 = SM_W + 18432;
constexpr int SM_TWO = SM_X + 2 * 24576;
constexpr int SM_TST = SM_TIN2 + 24576;
enum { B_FULL = 0, B_EMPTY = 3, B_TIN = 6, B_TFREE = 10, B_WK = 12, B_WQ, B_WO, B_KIMP, B_VIMP, B_OFREE, B_XK, B_XV,
       B_Q0, B_WOFREE, B_OTAIL, B_ODONE = B_OTAIL + 4, B_KFREE, B_VFREE, B_COUNT };
enum { N_KRDY = 4, N_QK0, N_QK1, N_VQ0, N_VQ1, N_PVISS, N_Q0 };

constexpr int NL = 2;
constexpr int SPL = 4;
constexpr int MID = 6;
#define RA 160
#define RG 168
constexpr int FS = 64;
__device__ int g_flags[TB * 56 * FS];

#define TR(role, it, k)
#define TRDECL
#define TRARG
#define TRPASS
#define TRDUMP
#define TRB(it, k)
#define TR2START
#define TR2FLUSH(blk)
#define TR2(blk, k)

struct Stage { uint32_t lo, full, em, par; };
struct GemmCtx {
  uint32_t bar;
  uint32_t kC, vC[2], qC[2];
  uint32_t kH, vH[2];
  uint32_t hiA, hiB;
  uint32_t spin;
  bool hvalid, never, edge;
};

template <int STRIDE> __device__ __forceinline__ void dump12(uint32_t a, const uint32_t (&r)[12]) {
#pragma unroll
  for (int j = 0; j < 3; j++) stsm4(a + j * 2 * STRIDE, r[4 * j], r[4 * j + 1], r[4 * j + 2], r[4 * j + 3]);
}
__device__ __forceinline__ void keep12(bool never, uint32_t a, const uint32_t (&r)[12]) { if (never) dump12<128>(a, r); }
template <int N> __device__ __forceinline__ void pack12(uint32_t (&r)[12], const float (&d)[N], int off) {
#pragma unroll
  for (int j = 0; j < 12; j++) r[j] = pack2(d[off + 2 * j], d[off + 2 * j + 1]);
}
__device__ __forceinline__ uint64_t dsc(uint64_t lo, uint32_t hi) { uint64_t r; asm("mov.b64 %0, {%1, %2};" : "=l"(r) : "r"((uint32_t)lo), "r"(hi)); return r; }
template <int K0, int K1> __device__ __forceinline__ void issue_core(const GemmCtx& c, const Stage& x, float (&d)[72]) {
  constexpr uint64_t db = mkdesc(SBC + SM_W, 6144, 256, 3);
  wg_fence();
  if (K0 == 0) wg_ss144<0>(d, dsc(x.lo, c.hiA), dsc(db, c.hiB));
#pragma unroll
  for (int k = K0 ? K0 : 1; k < K1; k++) wg_ss144<1>(d, dsc(x.lo + (k >> 2) * 512 + (k & 3) * 2, c.hiA), dsc(db + k * 32, c.hiB));
  wg_commit();
}
template <int K0, int K1> __device__ __forceinline__ void issue_halo(const GemmCtx& c, const Stage& x, float (&d)[48]) {
  constexpr uint64_t db = mkdesc(SBC + SM_W + 18432, 6144, 256, 3);
  wg_fence();
  if (K0 == 0) wg_ss96<0>(d, dsc(x.lo, c.hiA), dsc(db, c.hiB));
#pragma unroll
  for (int k = K0 ? K0 : 1; k < K1; k++) wg_ss96<1>(d, dsc(x.lo + (k >> 2) * 384 + (k & 3) * 2, c.hiA), dsc(db + k * 32, c.hiB));
  wg_commit();
}
__device__ __forceinline__ void release_stage(const Stage& x) {
  asm volatile("{\n.reg .pred p;\nelect.sync _|p, 0xffffffff;\n@p mbarrier.arrive.shared::cluster.b64 _, [%0];\n}" ::"r"(x.em) : "memory");
}
__device__ __forceinline__ void wait_stage(GemmCtx& c, Stage& x) {
  asm volatile("{\n.reg .pred p;\nWL:\nmbarrier.try_wait.parity.shared::cta.b64 p, [%1], %2;\n@p bra WD;\n"
               "add.u32 %0, %0, 1;\nsetp.lt.u32 p, %0, 0x100000;\n@p bra WL;\nWD:\n}" : "+&r"(c.spin) : "r"(x.full), "r"(x.par) : "memory");
  x.par ^= 1;
}
__device__ __forceinline__ void edge_ready(const GemmCtx& c, int bar) { __syncwarp(); if (c.edge) mbar_arrive_elect(c.bar + bar * 8); }
__device__ __forceinline__ void dump6(uint32_t a, const uint32_t (&r)[6]) {
  stsm4(a, r[0], r[1], r[2], r[3]);
  asm volatile("stmatrix.sync.aligned.m8n8.x2.shared.b16 [%0], {%1,%2};" ::"r"(a + 512), "r"(r[4]), "r"(r[5]) : "memory");
}
__device__ __forceinline__ void pack6(uint32_t (&r)[6], const float (&d)[48], int off) {
#pragma unroll
  for (int j = 0; j < 6; j++) r[j] = pack2(d[off + 4 * j], d[off + 4 * j + 1]);
}
template <int PARITY> __device__ __forceinline__ void gwait(GemmCtx& c, int bar) {
  asm volatile("{\n.reg .pred p;\nWL:\nmbarrier.try_wait.parity.shared::cta.b64 p, [%1], %2;\n@p bra WD;\n"
               "add.u32 %0, %0, 1;\nsetp.lt.u32 p, %0, 0x100000;\n@p bra WL;\nWD:\n}" : "+&r"(c.spin) : "r"(c.bar + bar * 8), "n"(PARITY) : "memory");
}
__device__ __forceinline__ void load_w(const CUtensorMap* m, uint32_t dst, uint32_t bar, int col) {
  asm volatile("cp.async.bulk.tensor.2d.shared::cluster.global.mbarrier::complete_tx::bytes [%0], [%1, {%3,%4}], [%2];"
               ::"r"(dst), "l"(m), "r"(bar), "r"(col), "r"(0) : "memory");
}
__device__ __forceinline__ void remote_arrive(uint32_t rbar) { asm volatile("mbarrier.arrive.shared::cluster.b64 _, [%0];" ::"r"(rbar) : "memory"); }
__device__ __forceinline__ void remote_expect(uint32_t rbar, uint32_t bytes) {
  asm volatile("mbarrier.arrive.expect_tx.shared::cluster.b64 _, [%0], %1;" ::"r"(rbar), "r"(bytes) : "memory");
}
__device__ __forceinline__ void copy_remote(uint32_t rdst, uint32_t src, uint32_t bytes, uint32_t rbar) {
  asm volatile("cp.async.bulk.shared::cluster.shared::cta.mbarrier::complete_tx::bytes [%0], [%1], %2, [%3];" ::"r"(rdst), "r"(src), "r"(bytes), "r"(rbar) : "memory");
}
__device__ __forceinline__ void tail_free(uint32_t bar) {
  uint32_t ln; asm volatile("mov.u32 %0, %%laneid;" : "=r"(ln));
  if (ln < 4) mbar_arrive_remote(bar, ln + (blockIdx.x & 4));
}
__device__ __forceinline__ void publish(uint32_t bar) {
  fence_async();
  __syncwarp();
  mbar_arrive_elect(bar);
}

template <bool FIRST, int PA>
__device__ __forceinline__ void gemm_iter(GemmCtx& c, int b, uint32_t (&pk)[12], uint32_t (&pv)[12], uint32_t (&pq)[12],
                                          uint32_t (&hk1)[6], uint32_t (&hv1)[6], Stage& x0, Stage& x2, Stage& x1 TRARG) {
  const uint32_t bar = c.bar;
  const bool w = !FIRST && (PA == 0 || b >= 0), never = c.never;
  constexpr uint32_t ko = PA * KSLOT;
  float C[72];
  uint32_t hk0[6], hv0[6], pv2[12];
  TR(2, b, 0);
  if (FIRST) wait_stage(c, x0);
  else dump12<128>(c.qC[1], pq);
  if (w) nb_sync(N_QK1, 256);
  TR(2, b, 2);
  if (FIRST) TR(2, b - 1, 6);
  if (PA == 0) {
    float H[48];
    issue_halo<0, 8>(c, x0, H);
    TR(2, b, 3);
    if (!FIRST) { gwait<0>(c, B_KFREE); dump12<128>(c.kC, pk); }
    issue_halo<8, 12>(c, x0, H);
    TR(2, b, 4);
    wait_stage(c, x2);
    if (FIRST) TR(2, b - 1, 7);
    if (FIRST) gwait<0>(c, B_WQ);
    if (FIRST) TR(2, b - 1, 8);
    issue_core<0, 8>(c, x2, C);
    TR(2, b, 5);
    if (!FIRST) fence_async();
    wg_wait<1>(); pin(H);
    release_stage(x0);
    pack6(hk0, H, 0);
    if (c.hvalid) dump6(c.kH, hk0);
    pack6(hk1, H, 2); pack6(hv0, H, 24); pack6(hv1, H, 26);
  } else {
    issue_core<0, 8>(c, x2, C);
    TR(2, b, 5);
    fence_async();
    keep12(never, c.kC, pq);
    if (w) gwait<1>(c, B_KFREE);
    dump12<128>(c.kC + ko, pk);
    if (c.hvalid) dump6(c.kH + ko, hk1);
  }
  TR(2, b, 13);
  issue_core<8, 12>(c, x2, C);
  if (w) { nb_arrive(N_VQ0, 288); nb_arrive(N_VQ1, 288); }
  else if (!FIRST) { __syncwarp(); mbar_arrive_elect(bar + B_Q0 * 8); }
  wait_stage(c, x1);
  if (never) dump6(bar, PA ? hk1 : hk0);
  TR(2, b, 6);
  wg_wait<0>(); pin(C);
  TR(2, b, 7);
  release_stage(x2);
  pack12(pk, C, 24);
  dump12<128>(c.kC + ko + 64, pk);
  pack12(pv2, C, 48);
  pack12(pq, C, 0);
  TR(2, b, 8);
  issue_core<0, SPL>(c, x1, C);
  TR(2, b, 9);
  if (!FIRST) { fence_async(); edge_ready(c, B_XK); }
  keep12(never, c.kC, pk);
  TR(2, b, 14);
  if (w) nb_sync(N_PVISS, 384);
  issue_core<SPL, 12>(c, x1, C);
  if (!FIRST) nb_arrive(N_KRDY, 256);
  TR(2, b, 1);
  if (PA && b == 11) tail_free(bar + B_TFREE * 8);
  wait_stage(c, x0);
  if (w) gwait<PA>(c, B_VFREE);
  if (w && b < TB) gwait<PA>(c, B_ODONE);
  TR(2, b, 10);
  if (!FIRST) dump12<128>(c.vC[PA], pv);
  dump12<128>(c.vC[PA ^ 1] + 768, pv2);
  TR(2, b, 11);
  wg_wait<0>(); pin(C);
  TR(2, b, 12);
  release_stage(x1);
  if (!FIRST && c.edge) publish(bar + B_XV * 8);
  if (c.hvalid) dump6(c.vH[PA], PA ? hv1 : hv0);
  if (PA && !w) nb_sync(N_Q0, 384);
  dump12<128>(c.qC[0], pq);
  pack12(pk, C, 24);
  pack12(pv, C, 48);
  pack12(pq, C, 0);
}

template <int IN> __device__ __forceinline__ void issue_proj(float (&D)[48]) {
  constexpr uint64_t da = mkdesc(SBC + IN, 128, 768, 0), db = mkdesc(SBC + SM_TWO, 12288, 512, 2);
  wg_fence();
  wg_ss96<0>(D, da, db);
#pragma unroll
  for (int k = 1; k < 12; k++) wg_ss96<1>(D, da + (k / 3) * 384 + (k % 3) * 16, db + k * 64);
  wg_commit();
}
template <int ACC> __device__ __forceinline__ void issue_proj_half(float (&D)[48], int hd) {
  const uint64_t da = mkdesc(SBC + SM_TIN2, 128, 768, 0) + hd * 384, db = mkdesc(SBC + SM_TWO, 12288, 512, 2) + hd * 192;
  wg_fence();
  wg_ss96<ACC>(D, da, db);
#pragma unroll
  for (int k = 1; k < 6; k++) wg_ss96<1>(D, da + (k / 3) * 768 + (k % 3) * 16, db + (k / 3) * 384 + (k % 3) * 64);
  wg_commit();
}
__device__ __forceinline__ void store_proj(const float (&D)[48], const CUtensorMap* m, uint32_t st, uint32_t sta, int row, int col, int ch) {
#pragma unroll
  for (int q = 0; q < 6; q++)
    stsm4((sta ^ ((q & 1) * 32)) + (q >> 1) * 1024,
          pack2(D[8 * q], D[8 * q + 1]), pack2(D[8 * q + 2], D[8 * q + 3]), pack2(D[8 * q + 4], D[8 * q + 5]), pack2(D[8 * q + 6], D[8 * q + 7]));
  fence_async();
  __syncwarp();
  if ((threadIdx.x & 31) == 0) {
    asm volatile("cp.async.bulk.tensor.4d.global.shared::cta.bulk_group [%0, {%2,%3,%4,%5}], [%1];" ::"l"(m), "r"(st), "r"(0), "r"(row), "r"(col), "r"(ch) : "memory");
    asm volatile("cp.async.bulk.commit_group;" ::: "memory");
  }
  __syncwarp();
}

__device__ __forceinline__ float fold(float a, float b, float t, int useb) {
  float r;
  asm("{\n.reg .pred p;\nsetp.ne.b32 p, %4, 0;\nfma.rn.f32 %0, %1, 0f3E553B95, %3;\n@p fma.rn.f32 %0, %2, 0f3E553B95, %3;\n}"
      : "=&f"(r) : "f"(a), "f"(b), "f"(t), "r"(useb));
  return r;
}
template <int U, int L>
__device__ __forceinline__ void softmax_tile(const float (&SA)[56], const float (&SB)[56], const float (&T)[16], int b0, int b1,
                                             uint32_t (&P)[28], float (&sx)[8], uint32_t nbV, uint32_t zero, uint32_t qa, uint32_t (&q)[12]) {
  float lu[14], ll[14];
#pragma unroll
  for (int j = 0; j < 7; j++) {
    constexpr int sh = U == L ? 2 : 0;
    const float tu0 = T[2 * j + sh], tu1 = T[2 * j + 1 + sh], tl0 = T[2 * j], tl1 = T[2 * j + 1];
    lu[2 * j]     = fold(SA[4 * (U + j)],     SB[4 * (U + j)],     tu0, b0);
    ll[2 * j]     = fold(SA[4 * (L + j) + 2], SB[4 * (L + j) + 2], tl0, b0);
    lu[2 * j + 1] = fold(SA[4 * (U + j) + 1], SB[4 * (U + j) + 1], tu1, b1);
    ll[2 * j + 1] = fold(SA[4 * (L + j) + 3], SB[4 * (L + j) + 3], tl1, b1);
  }
  float mu = lu[0], ml = ll[0], mu2 = lu[1], ml2 = ll[1];
#pragma unroll
  for (int j = 1; j < 7; j++) { mu = fmaxf(mu, lu[2 * j]); mu2 = fmaxf(mu2, lu[2 * j + 1]); ml = fmaxf(ml, ll[2 * j]); ml2 = fmaxf(ml2, ll[2 * j + 1]); }
  mu = fmaxf(mu, mu2); ml = fmaxf(ml, ml2);
  { const float a1 = __shfl_xor_sync(0xffffffffu, mu, 1), a2 = __shfl_xor_sync(0xffffffffu, mu, 2), a3 = __shfl_xor_sync(0xffffffffu, mu, 3);
    const float c1 = __shfl_xor_sync(0xffffffffu, ml, 1), c2 = __shfl_xor_sync(0xffffffffu, ml, 2), c3 = __shfl_xor_sync(0xffffffffu, ml, 3);
    mu = fmaxf(fmaxf(mu, a1), fmaxf(a2, a3)); ml = fmaxf(fmaxf(ml, c1), fmaxf(c2, c3)); }
  float su = 0.f, sl = 0.f;
#pragma unroll
  for (int c = 0; c < 14; c++) {
    if (c >= U && c < U + 7) {
      float e0 = ex2(lu[2 * (c - U)] - mu), e1 = ex2(lu[2 * (c - U) + 1] - mu);
      su = c == U ? e0 + e1 : (su + e0) + e1; P[2 * c] = pack2(e0, e1);
    } else P[2 * c] = 0u;
  }
  nb_sync(nbV | (P[2 * (U + MID)] & zero), 288);
#pragma unroll
  for (int k = 0; k < 3; k++) ldsm4(qa + k * 256, q[4 * k], q[4 * k + 1], q[4 * k + 2], q[4 * k + 3]);
#pragma unroll
  for (int c = 0; c < 14; c++) {
    if (c >= L && c < L + 7) {
      float e0 = ex2(ll[2 * (c - L)] - ml), e1 = ex2(ll[2 * (c - L) + 1] - ml);
      sl = c == L ? e0 + e1 : (sl + e0) + e1; P[2 * c + 1] = pack2(e0, e1);
    } else P[2 * c + 1] = 0u;
  }
  sx[0] = su; sx[4] = sl;
#pragma unroll
  for (int k = 1; k < 4; k++) sx[k] = __shfl_xor_sync(0xffffffffu, su, k);
#pragma unroll
  for (int k = 1; k < 4; k++) sx[4 + k] = __shfl_xor_sync(0xffffffffu, sl, k);
}

struct BandCfg { uint32_t ra0, ra1, meta; int b0, b1; };
__device__ __forceinline__ void band_cfg(int b, uint32_t tb, BandCfg& n) {
  uint32_t ln; asm volatile("mov.u32 %0, %%laneid;" : "=r"(ln));
  const int g = ln >> 2, t = ln & 3;
  const int sw = min(max(g + 1, b == 0 ? 4 : 0), b == 13 ? 5 : 8);
  const int i0 = 2 * t, i1 = 2 * t + 1;
  n.b0 = i0 <= sw - 2; n.b1 = i1 <= sw - 2;
  n.ra0 = tb + (i0 == sw - 1 ? 13 : i0 + 8 * n.b0 - g + 2) * 52;
  n.ra1 = tb + (i1 == sw - 1 ? 13 : i1 + 8 * n.b1 - g + 2) * 52;
  n.meta = ((0x5555u & ((1u << (2 * (sw - 1))) - 1)) ^ 0xDD88u ^ (((t ^ b) & 1) ? 0x5555u : 0u)) * 0x10001u;
}
__device__ __forceinline__ void band_load(const BandCfg& n, float (&T)[16], int& b0, int& b1, uint32_t& meta) {
#pragma unroll
  for (int jj = 0; jj < 8; jj++) { T[2 * jj] = lds_f32(n.ra0 + jj * 4); T[2 * jj + 1] = lds_f32(n.ra1 + jj * 4); }
  b0 = n.b0; b1 = n.b1; meta = n.meta;
}

struct Maps { CUtensorMap xc, xh, w, os, wo, ot; };

__global__ void __cluster_dims__(8, 1, 1) __launch_bounds__(512, 1)
na_attn_kernel(const __nv_bfloat16* __restrict__ x, const __nv_bfloat16* __restrict__ wqkv, const __nv_bfloat16* __restrict__ rpb, const __grid_constant__ Maps mp) {
  extern __shared__ __align__(1024) uint8_t smem_raw[];
  const uint32_t sb = smem_u32(smem_raw);
  if ((sb & 0x3FFFF) != SBC) return;
  const uint32_t bar = sb + SM_BAR;
  TR2START;
  const int tid = threadIdx.x, lane = tid & 31;
  const int warp = __shfl_sync(0xffffffffu, tid >> 5, 0);
  const int head = blockIdx.x & 3, base = blockIdx.x & 4, sp = blockIdx.x >> 2;
  const int par = sp < 24 ? sp / 6 : sp - 24, strip = sp < 24 ? sp - par * 6 : 6, ph = par >> 1, pw = par & 1;
  const int odd = strip & 1;

  uint4 wv[2 * NL];
  const int va = head == 1;
  const uint32_t wdst = sb + SM_W + (3 + va + ((tid >> 1) & 1)) * 6144 + (tid >> 2) * 32 + ((tid ^ (tid >> 4)) & 1) * 16;
  if (warp < 12) {
    asm volatile("barrier.cluster.arrive.relaxed.aligned;" ::: "memory");
    const uint32_t wo0 = (tid >> 2) * 1152 + head * 96 + va * 32 + (tid & 3) * 16;
#pragma unroll
    for (int i = 0; i < 2 * NL; i++)
      asm volatile("ld.global.nc.v4.b32 {%0,%1,%2,%3}, [%4];" : "=r"(wv[i].x), "=r"(wv[i].y), "=r"(wv[i].z), "=r"(wv[i].w)
                   : "l"(reinterpret_cast<const uint8_t*>(wqkv) + wo0 + (i & 1) * 96 * 1152 + (i / 2 + 1) * 384));
  }
  if (warp < 8) {
    asm volatile("setmaxnreg.inc.sync.aligned.u32 %0;" ::"n"(RA));
    float rv = -INFINITY;
    if (tid < 169) rv = __bfloat162float(rpb[head * 169 + tid]) * 1.4426950408889634f;
    if (tid < 192) {
      const int kc = (tid & 15) + 3, wc = (tid >> 4) % 6;
      sts128(tid < 96 ? sb + SM_K + kc * KS + wc * 128 + 48 : sb + SM_V + kc * 1536 + wc * 128 + (6 + (kc & 1)) * 16, make_uint4(0, 0, 0, 0));
    }
#pragma unroll
    for (int i = 0; i < 2 * NL; i++) sts128(wdst + (i & 1) * 3072 + (i / 2) * 18432, wv[i]);
    fence_async();
    asm volatile("bar.arrive 1, 384;" ::: "memory");
    if (tid < 182) asm volatile("st.shared.f32 [%0], %1;" ::"r"(sb + SM_RPB + tid * 4), "f"(rv) : "memory");
    const int jw = warp >> 2, j = jw ^ odd, w = warp & 3, wt = 4 * j + w;
    int variant = w;
    if (strip == 0 && j == 0 && w < 2) variant = 4;
    if (strip == 6 && j == 1 && w >= 2) variant = 5;
    const bool v1 = opq((uint32_t)(variant & 1)), v2 = opq((uint32_t)(variant & 2)), v4 = opq((uint32_t)(variant & 4));
    const uint32_t qa = opq(sb + SM_Q + (8 * j + 2 * w + ((lane >> 3) & 1)) * 768 + (lane >> 4) * 128 + (((lane & 7) * 16) ^ (((lane >> 3) & 1) * 64)));
    uint32_t oa = opq(sb + SM_O + j * 6144 + (2 * w + ((lane >> 3) & 1)) * 768 + (lane >> 4) * 128 + (lane & 7) * 16);
    uint64_t dA = opq(mkdesc(SBC + SM_K, 128, KS, 0) + j * (8 * KS / 16)), dB = opq(dA + (KSLOT >> 4));
    uint64_t dV[7];
#pragma unroll
    for (int i = 0; i < 7; i++) dV[i] = opq(mkdesc(SBC + SM_V, 768, 128, 0) + j * (8 * 1536 / 16) + i * 192);
    const uint32_t nbK = opq((uint32_t)(N_KRDY + jw)), nbQ = opq((uint32_t)(N_QK0 + jw)), nbV = opq((uint32_t)(N_VQ0 + jw));
    asm volatile("barrier.cluster.wait.aligned;" ::: "memory");
    asm volatile("bar.sync 3, 256;" ::: "memory");
    float T[16];
    TRDECL;
    int b0, b1;
    uint32_t meta, ob = bar + B_ODONE * 8, fb = bar + B_OFREE * 8, fp = 1;
    const uint32_t tb = opq(sb + SM_RPB + (variant < 4 ? 3 : variant + 1 - 2 * w) * 4);
    const bool own = ((w ^ head) & 2) == 0;
    const uint32_t dst13 = sb + SM_TIN2 + head * 6144 + (2 * j + (w & 1)) * 1536, src13 = opq(own ? dst13 : sb + SM_S + (2 * j + (w & 1)) * 1536);
    const uint32_t snd[4] = {opq(own ? 0u : mapa(dst13, base + (head ^ 2))), opq(mapa(bar + (B_TIN + 2) * 8, base + (head ^ 2))),
                             opq(mapa(dst13, base + (w & 2) + (~head & 1))), opq(mapa(bar + (B_TIN + 3) * 8, base + (w & 2) + (~head & 1)))};
    BandCfg nx;
    band_cfg(0, tb, nx);
    band_load(nx, T, b0, b1, meta);
    band_cfg(1, tb, nx);
    const uint32_t zero = opq(blockIdx.x >> 16);
    uint32_t special = opq(0x380Au << 1);
    uint32_t q[12];
    mbar_wait(bar + B_Q0 * 8, 0);
#pragma unroll
    for (int k = 0; k < 3; k++) ldsm4(qa + k * 256, q[4 * k], q[4 * k + 1], q[4 * k + 2], q[4 * k + 3]);
    nb_arrive(N_Q0, 384);
#pragma unroll 1
    for (int b = 0; b < 14; b++) {
      float SA[56], SB[56];
      TR(0, b, 0);
      if (jw) mbar_wait(bar + B_KIMP * 8, b & 1);
      nb_sync(nbK, 256);
      TR(0, b, 1);
      TR(0, b - 1, 9);
      wg_fence();
      wg_rs112<0>(SA, q[0], q[1], q[2], q[3], dA);
      wg_rs112<0>(SB, q[0], q[1], q[2], q[3], dB);
      wg_rs112<1>(SA, q[4], q[5], q[6], q[7], dA + 16);
      wg_rs112<1>(SB, q[4], q[5], q[6], q[7], dB + 16);
      wg_rs112<1>(SA, q[8], q[9], q[10], q[11], dA + 32);
      wg_rs112<1>(SB, q[8], q[9], q[10], q[11], dB + 32);
      wg_commit();
      nb_arrive(nbQ, 256);
      { const uint64_t t = dA; dA = dB; dB = t; }
      special >>= 1;
      if (special & 1) {
        if (b == 3) band_cfg(13, tb, nx);
        else {
          if (b == 1 || b == 13) band_load(nx, T, b0, b1, meta);
          if (b >= TB) {
            ob = bar + (b == 13 ? (own ? B_TIN + 2 : B_ODONE) : B_OTAIL + 2 * (b - TB) + jw) * 8;
            if (b > TB) { fb = bar + (B_TFREE + b - 12) * 8; fp = 0; }
            oa += b == 12 ? 0u - (SM_O - SM_Q) : (b == 13 ? src13 - (sb + SM_Q + wt * 1536) : 0);
          }
        }
      }
      TR(0, b, 2);
      wg_wait<0>(); pin(SA); pin(SB);
      mbar_arrive_elect(bar + B_KFREE * 8);
      TR(0, b, 3);
      TR(0, b - 1, 10);
      uint32_t P[28];
      float sx[8];
      if (v2) {
        if (v1) softmax_tile<6, 7>(SA, SB, T, b0, b1, P, sx, nbV, zero, qa, q); else softmax_tile<4, 5>(SA, SB, T, b0, b1, P, sx, nbV, zero, qa, q);
      } else if (!v4) {
        if (v1) softmax_tile<2, 3>(SA, SB, T, b0, b1, P, sx, nbV, zero, qa, q); else softmax_tile<0, 1>(SA, SB, T, b0, b1, P, sx, nbV, zero, qa, q);
      } else {
        if (v1) softmax_tile<4, 4>(SA, SB, T, b0, b1, P, sx, nbV, zero, qa, q); else softmax_tile<3, 3>(SA, SB, T, b0, b1, P, sx, nbV, zero, qa, q);
      }
      float O[24];
      TR(0, b, 4);
      wg_fence();
      wg_sp48<0>(O, P[0], P[1], P[2], P[3], dV[0], meta);
#pragma unroll
      for (int s = 1; s < 7; s++) wg_sp48<1>(O, P[4 * s], P[4 * s + 1], P[4 * s + 2], P[4 * s + 3], dV[s], meta);
      wg_commit();
      nb_arrive(N_PVISS, 384);
      TR(0, b, 6);
      mbar_wait(fb, fp);
      wg_wait<0>(); pin(O);
      mbar_arrive_elect(bar + B_VFREE * 8);
      TR(0, b, 7);
      float ru, rl;
      asm("rcp.approx.ftz.f32 %0, %1;" : "=f"(ru) : "f"(((fmaf(O[0], 0.f, sx[0]) + sx[1]) + sx[2]) + sx[3]));
      asm("rcp.approx.ftz.f32 %0, %1;" : "=f"(rl) : "f"(((fmaf(O[2], 0.f, sx[4]) + sx[5]) + sx[6]) + sx[7]));
#pragma unroll
      for (int i = 0; i < 3; i++)
        stsm4(oa + i * 256, pack2(O[8 * i] * ru, O[8 * i + 1] * ru), pack2(O[8 * i + 2] * rl, O[8 * i + 3] * rl),
              pack2(O[8 * i + 4] * ru, O[8 * i + 5] * ru), pack2(O[8 * i + 6] * rl, O[8 * i + 7] * rl));
      publish(ob);
      fp ^= 1;
      meta ^= 0x55555555u;
      TR(0, b, 8);
    }
    asm volatile("{\n.reg .pred p, q;\nsetp.ne.b32 q, %1, 0;\nelect.sync _|p, 0xffffffff;\nand.pred q, q, p;\n"
                 "@q cp.async.bulk.shared::cluster.shared::cta.mbarrier::complete_tx::bytes [%1], [%0], 1536, [%2];\n"
                 "@p cp.async.bulk.shared::cluster.shared::cta.mbarrier::complete_tx::bytes [%3], [%0], 1536, [%4];\n}"
                 ::"r"(src13), "r"(snd[0]), "r"(snd[1]), "r"(snd[2]), "r"(snd[3]) : "memory");
    nb_arrive(3, 384);
    TRDUMP;
    cluster_sync();
  } else if (warp < 12) {
    TRDECL;
    TR(2, -3, 0);
    asm volatile("setmaxnreg.inc.sync.aligned.u32 %0;" ::"n"(RG));
    TR(2, -3, 1);
    GemmCtx c;
    c.bar = bar;
    const int gw = warp - 8, tk = gw * 16 + (lane & 15), hi = lane >> 4;
    { const int col = tk >> 2, i = tk & 3;
      c.kC = sb + SM_K + (col + 3) * KS + hi * 128 + i * 16;
      c.vC[0] = sb + SM_V + (col + 3) * 1536 + hi * 128 + (2 * i + ((col + 3) & 1)) * 16;
      c.qC[0] = sb + SM_Q + col * 768 + hi * 128 + (col & 1) * 64 + i * 16; }
    { const int kc = gw - 1 + 19 * odd, i = lane & 7; c.hvalid = gw > 0; c.edge = gw == (odd ? 0 : 3);
      c.kH = sb + SM_K + kc * KS + (lane >> 3) * 128 + i * 16;
      c.vH[0] = sb + SM_V + kc * 1536 + (lane >> 3) * 128 + (i >> 2) * 768 + (2 * (i & 3) + ((kc ^ (i >> 2)) & 1)) * 16; }
    Stage xs[3];
#pragma unroll
    for (int i = 0; i < 3; i++) {
      const int p = (i + 1) % 3;
      xs[i].lo = (uint32_t)mkdesc(SBC + SM_X + p * 24576, 16, 0, 0); xs[i].full = bar + (B_FULL + p) * 8;
      xs[i].em = opq(mapa(bar + (B_EMPTY + p) * 8, base + p)); xs[i].par = 0;
    }
    c.never = x == nullptr;
    c.kC = opq(c.kC); c.kH = opq(c.kH);
    c.vC[1] = opq(c.vC[0] ^ 16); c.vC[0] = opq(c.vC[0]);
    c.vH[1] = opq(c.vH[0] ^ 16); c.vH[0] = opq(c.vH[0]);
    c.qC[1] = opq(c.qC[0] ^ 64); c.qC[0] = opq(c.qC[0]);
    c.spin = 0;
    c.hiA = (uint32_t)(mkdesc(0, 0, 1024, 1) >> 32) + (blockIdx.x >> 16); c.hiB = (uint32_t)(mkdesc(0, 0, 256, 3) >> 32) + (blockIdx.x >> 16);
    asm volatile("barrier.cluster.wait.aligned;" ::: "memory");
    TR(2, -3, 2);
#pragma unroll
    for (int i = 0; i < 2 * NL; i++) sts128(wdst + (i & 1) * 3072 + (i / 2) * 18432, wv[i]);
    fence_async();
    TR(2, -3, 3);
    asm volatile("bar.sync 1, 384;" ::: "memory");
    TR(2, -3, 4);
    mbar_wait(bar + B_WK * 8, 0);
    asm volatile("griddepcontrol.launch_dependents;");
    TR(2, -3, 5);
    uint32_t pk[12], pv[12], pq[12], hk1[6], hv1[6];
    gemm_iter<true, 0>(c, -2, pk, pv, pq, hk1, hv1, xs[0], xs[1], xs[2] TRPASS);
    TR2(blockIdx.x, 4);
    c.hiA = opq(c.hiA); c.hiB = opq(c.hiB);
#pragma unroll 1
    for (int b = -1;; b += 2) {
      gemm_iter<false, 1>(c, b, pk, pv, pq, hk1, hv1, xs[2], xs[0], xs[1] TRPASS);
      if (b == 11) break;
      gemm_iter<false, 0>(c, b + 1, pk, pv, pq, hk1, hv1, xs[2], xs[0], xs[1] TRPASS);
      const Stage t = xs[2]; xs[2] = xs[1]; xs[1] = xs[0]; xs[0] = t;
    }
    TR2(blockIdx.x, 6);
    c.hiA = opq(c.hiA); c.hiB = opq(c.hiB);
    const uint32_t st = sb + gw * 3072;
    const uint32_t sta = st + (lane & 15) * 64 + ((hi ^ ((lane >> 1) & 3)) * 16);
    const int oc = ph * 112 + strip * 16 + 8 * (gw >> 1) + 4 * (head >> 1) + 2 * (gw & 1), och = pw * 6 + (head & 1) * 3;
    float D0[48], D1[48];
    if (lane < 4) mbar_arrive_remote(bar + B_WOFREE * 8, 2 * lane + (head & 1));
    dump12<128>(c.qC[1], pq);
    nb_sync(N_QK1, 256);
    issue_halo<0, 8>(c, xs[2], D1);
    fence_async();
    nb_arrive(N_VQ0, 288); nb_arrive(N_VQ1, 288); nb_arrive(N_PVISS, 384);
    issue_halo<8, 12>(c, xs[2], D1);
    gwait<0>(c, B_KFREE);
    dump12<128>(c.kC, pk);
    if (c.edge) publish(bar + B_XK * 8);
    wg_wait<0>(); pin(D1);
    pack6(hk1, D1, 0);
    if (c.hvalid) dump6(c.kH, hk1);
    tail_free(bar + (B_TFREE + 1) * 8);
    pack6(hv1, D1, 24);
    fence_async();
    nb_arrive(N_KRDY, 256);
    gwait<0>(c, B_VFREE);
    dump12<128>(c.vC[0], pv);
    if (c.hvalid) dump6(c.vH[0], hv1);
    fence_async();
    edge_ready(c, B_XV);
    nb_arrive(N_VQ0, 288); nb_arrive(N_VQ1, 288);
    gwait<0>(c, B_WO);
    gwait<0>(c, B_TIN);
    TR(2, 13, 0);
    nb_sync(N_QK1, 256);
    issue_proj<SM_TIN0>(D0);
    wg_wait<0>(); pin(D0);
    TR(2, 13, 1);
    store_proj(D0, &mp.ot, st + SM_TST, sta + SM_TST, 8 * TB, oc, och);
    gwait<0>(c, B_TIN + 1);
    TR(2, 13, 2);
    nb_arrive(N_PVISS, 384);
    nb_sync(3, 384);
    issue_proj<SM_TIN1>(D1);
    wg_wait<0>(); pin(D1);
    TR(2, 13, 3);
    store_proj(D1, &mp.ot, st + SM_TIN0, sta + SM_TIN0, 8 * TB + 8, oc, och);
    TR(2, 13, 4);
    gwait<0>(c, B_TIN + 2);
    TR(2, 13, 5);
    issue_proj_half<0>(D0, head & 1);
    gwait<0>(c, B_TIN + 3);
    TR(2, 13, 6);
    issue_proj_half<1>(D0, ~head & 1);
    asm volatile("barrier.cluster.arrive.relaxed.aligned;" ::: "memory");
    wg_wait<0>(); pin(D0);
    store_proj(D0, &mp.ot, st + SM_TIN0 + 12288, sta + SM_TIN0 + 12288, 8 * TB + 16, oc, och);
    TR(2, 13, 7);
    if (lane == 0) asm volatile("cp.async.bulk.wait_group.read 0;" ::: "memory");
    __syncwarp();
    TR(2, 13, 8);
    TR2(blockIdx.x, 2);
    TR2FLUSH(blockIdx.x);
    TRDUMP;
    asm volatile("barrier.cluster.wait.aligned;" ::: "memory");
  } else {
    asm volatile("setmaxnreg.dec.sync.aligned.u32 24;");
    if (warp == 15) {
      const int l = min(lane, 24), row = head + (l < 16 ? 0 : 4 * ((l - 16) / 3)), col = strip * 16 + (l < 16 ? l : (l - 16) % 3 + (odd ? 16 : (strip ? -3 : 0)));
      const uint8_t* p = reinterpret_cast<const uint8_t*>(x) + (uint32_t)(row * ROWB + (ph * 112 + col) * 768 + pw * 384);
#pragma unroll
      for (int i = 0; i < 3; i++) asm volatile("prefetch.global.L2 [%0];" ::"l"(p + i * 128));
    } else if (elect_one()) {
      if (warp == 12) {
        mbar_init(bar + B_WK * 8, 1);
#pragma unroll
        for (int i = 0; i < NL; i++) load_w(&mp.w, sb + SM_W + (3 * i + 5 - 2 * va) * 6144, bar + B_WK * 8, (i + 1) * 192 + head * 48 + 32 - 32 * va);
        asm volatile("prefetch.tensormap [%0];" ::"l"(head == 1 ? &mp.xh : &mp.xc) : "memory");
      } else if (warp == 13) {
#pragma unroll
        for (int i = 0; i < B_XK; i++) if (i != B_WK) mbar_init(bar + i * 8, (i >= B_EMPTY && i < B_TIN) || (i >= B_TFREE && i < B_WK) ? 16 : (i == B_TIN + 2 ? 5 : 1));
      } else {
#pragma unroll
        for (int i = B_XK; i < B_COUNT; i++) mbar_init(bar + i * 8, i < B_Q0 ? 2 : (i < B_ODONE ? (i == B_WOFREE ? 16 : 4) : (i == B_VFREE ? 9 : 8)));
        mbar_arrive(bar + B_XK * 8); mbar_arrive(bar + B_XV * 8);
      }
      asm volatile("fence.mbarrier_init.release.cluster;" ::: "memory");
    }
    __syncwarp();
    asm volatile("barrier.cluster.arrive.relaxed.aligned;" ::: "memory");
    if (warp != 12) asm volatile("barrier.cluster.wait.aligned;" ::: "memory");
    else {
      const int cc = ph * 112 + strip * 16, ch = cc + (odd ? 16 : (strip ? -3 : 0)), rh = strip ? -4 : 112;
      const uint32_t fb = opq(bar + (B_FULL + head) * 8), dst0 = sb + SM_X + head * 24576, c3 = opq((uint32_t)(pw * 3)), mask = opq(15u << base);
      int t = head == 0 ? 2 : head - 1;
      uint64_t mx = opq((uint64_t)(t ? &mp.xc : &mp.xh));
      uint32_t row = opq((uint32_t)(t ? 4 * t - 4 : rh)), col = opq((uint32_t)(t ? cc : ch)), dst = opq(dst0 + (t ? 0 : 2048));
#pragma unroll 1
      for (int n = 0;; n++) {
        if (n) mbar_wait(fb + (B_EMPTY - B_FULL) * 8, ~n & 1);
        else asm volatile("barrier.cluster.wait.aligned;" ::: "memory");
        if (head < 3) {
          asm volatile("{\n.reg .pred p;\n.reg .b16 m;\nelect.sync _|p, 0xffffffff;\ncvt.u16.u32 m, %7;\n"
                       "@p cp.async.bulk.tensor.4d.shared::cluster.global.mbarrier::complete_tx::bytes.multicast::cluster [%0], [%1, {%3,%4,%5,%6}], [%2], m;\n}"
                       ::"r"(dst), "l"(mx), "r"(fb), "r"(0), "r"(row), "r"(col), "r"(c3), "r"(mask) : "memory");
          if (lane < 4) remote_expect(mapa(fb, base + lane), dst == dst0 ? 24576 : 18432);
          __syncwarp();
        }
        if (n == 0 && elect_one()) {
#pragma unroll
          for (int i = 0; i < 3; i++) load_w(&mp.w, sb + SM_W + i * 6144, bar + B_WQ * 8, head * 48 + i * 16);
          mbar_expect(bar + B_WQ * 8, 18432);
        }
        __syncwarp();
        if (head == 3 || n == 11) break;
        t += 3;
        const int hn = t / 5;
        const bool core = t != 5 * hn;
        mx = opq((uint64_t)(core ? &mp.xc : &mp.xh));
        row = opq((uint32_t)(core ? 4 * (t - hn - 1) : rh + 16 * hn)); col = opq((uint32_t)(core ? cc : ch)); dst = opq(dst0 + (core ? 0 : 2048));
        if (elect_one()) asm volatile("cp.async.bulk.prefetch.tensor.4d.L2.global [%0, {%1,%2,%3,%4}];" ::"l"(mx), "r"(0), "r"(row), "r"(col), "r"(c3) : "memory");
        __syncwarp();
      }
      mbar_wait(bar + B_WOFREE * 8, 0);
      if (elect_one()) {
        const int qr = (blockIdx.x & 7) >> 1;
#pragma unroll
        for (int i = 0; i < 3; i++)
          asm volatile("cp.async.bulk.tensor.2d.shared::cluster.global.mbarrier::complete_tx::bytes.multicast::cluster [%0], [%1, {%3,%4}], [%2], %5;"
                       ::"r"(sb + SM_TWO + i * 12288 + qr * 3072), "l"(&mp.wo), "r"(bar + B_WO * 8), "r"((head & 1) * 96 + i * 32), "r"(qr * 48),
                         "h"((uint16_t)(0x55 << (head & 1))) : "memory");
      }
      __syncwarp();
    }
    if (warp & 1) {
      const uint32_t partner = (blockIdx.x & 7) ^ 4;
      const int cs = odd ? 3 : (strip == 6 ? 15 : 16), cd = odd || strip == 6 ? 19 : 0;
      const uint32_t rb = opq(mapa(bar, partner));
      TRDECL;
      if (warp == 13) {
        const uint32_t dst = opq(mapa(sb + SM_V + cd * 1536, partner)), src = opq(sb + SM_V + cs * 1536);
#pragma unroll 1
        for (int b = 0;; b++) {
          const uint32_t pa = b & 1;
          nb_arrive(N_VQ0, 288);
          mbar_wait(bar + B_XV * 8, pa);
          TR(1, b, 0);
          if (elect_one()) { copy_remote(dst, src, 4608, rb + B_VIMP * 8); remote_expect(rb + B_VIMP * 8, 4608); }
          __syncwarp();
          TR(1, b, 1);
          mbar_wait(bar + B_VIMP * 8, pa);
          TR(1, b, 2);
          nb_arrive(N_VQ1, 288);
          if (elect_one()) remote_arrive(rb + B_VFREE * 8);
          __syncwarp();
          TR(1, b, 3);
          if (b == 13) break;
          mbar_wait(bar + B_VFREE * 8, pa);
          if (elect_one()) remote_arrive(rb + B_XV * 8);
          __syncwarp();
        }
      } else {
        const uint32_t dst = opq(mapa(sb + SM_K + cd * KS, partner)), src = opq(sb + SM_K + cs * KS);
#pragma unroll 1
        for (int b = 0;; b++) {
          const uint32_t pa = b & 1, so = (pa ^ 1) * KSLOT;
          mbar_wait(bar + B_XK * 8, pa);
          TR(1, b - 1, 4);
          if (elect_one()) {
            copy_remote(dst + so, src + so, 3 * KS, rb + B_KIMP * 8);
            if (b == 0) copy_remote(dst, src, 3 * KS, rb + B_KIMP * 8);
            remote_expect(rb + B_KIMP * 8, b ? 3 * KS : 6 * KS);
          }
          __syncwarp();
          TR(1, b - 1, 5);
          TR(1, b - 1, 7);
          if (b == 13) break;
          mbar_wait(bar + B_KFREE * 8, pa);
          if (elect_one()) remote_arrive(rb + B_XK * 8);
          __syncwarp();
        }
      }
      TRDUMP;
    }
    if (warp == 14) {
      int* flag = g_flags + (par * 7 + strip) * 2 * FS;
      if (elect_one()) {
        mbar_expect(bar + B_WK * 8, NL * 6144);
        mbar_expect(bar + B_WO * 8, 36864);
        mbar_expect(bar + B_TIN * 8, 24576); mbar_expect(bar + (B_TIN + 1) * 8, 24576); mbar_expect(bar + (B_TIN + 2) * 8, 6144); mbar_expect(bar + (B_TIN + 3) * 8, 12288);
      }
      __syncwarp();
#pragma unroll 1
      for (int b = 0; b < TB; b++) {
        mbar_wait(bar + B_ODONE * 8, b & 1);
        if (lane == 0) {
          asm volatile("cp.async.bulk.tensor.3d.global.shared::cta.bulk_group [%0, {%2,%3,%4}], [%1];"
                       ::"l"(&mp.os), "r"(sb + SM_O), "r"(pw * 192), "r"(8 * b + 2 * head), "r"(ph * 112 + strip * 16) : "memory");
          asm volatile("cp.async.bulk.commit_group;\ncp.async.bulk.wait_group 0;" ::: "memory");
        }
        __syncwarp();
        mbar_arrive_elect(bar + B_OFREE * 8);
        if (lane == 0)
          asm volatile("fence.proxy.async.global;\nfence.acq_rel.gpu;\nred.relaxed.gpu.global.add.s32 [%0], 1;\nred.relaxed.gpu.global.add.s32 [%1], 1;"
                       ::"l"(flag + b * 56 * FS), "l"(flag + (b * 56 + 1) * FS) : "memory");
        __syncwarp();
      }
#pragma unroll 1
      for (int t = 0; t < 4; t++) {
        const int i = t >> 1, j = (t ^ odd) & 1, d = (lane + head + 1) & 3;
        const uint32_t dst = opq(mapa(sb + (i ? SM_TIN1 : SM_TIN0) + head * 6144 + j * 3072, base + d)), rb = opq(mapa(bar + (B_TIN + i) * 8, base + d));
        const uint32_t src = opq(sb + (i ? SM_Q : SM_O) + j * 6144 + (d & 2) * 1536);
        if (!(t & 1)) mbar_wait(bar + (B_TFREE + i) * 8, 0);
        mbar_wait(bar + (B_OTAIL + t) * 8, 0);
        if (lane < 4) copy_remote(dst, src, 3072, rb);
        __syncwarp();
      }
    }
    cluster_sync();
  }
}

constexpr int NSTB = 6;
constexpr int NTB = TB * 56;
constexpr int SM_B_ST = 0;
constexpr int SM_B_IN = 73728;
constexpr int SM_B_W = SM_B_IN + 3 * 24576;
constexpr int SM_B_BAR = SM_B_IN + NSTB * 24576;
constexpr int SM_B_TOTAL = SM_B_BAR + 512;
struct MapsB { CUtensorMap oi, oo, wo; };

__global__ void __launch_bounds__(512, 1)
na_proj_kernel(const __grid_constant__ MapsB mp) {
  extern __shared__ __align__(1024) uint8_t smem_raw[];
  const uint32_t sb = smem_u32(smem_raw);
  if ((sb & 0x3FFFF) != SBC) return;
  const uint32_t bar = sb + SM_B_BAR;
  const int tid = threadIdx.x, lane = tid & 31;
  const int warp = __shfl_sync(0xffffffffu, tid >> 5, 0);
  TR2START;
  TRB(47, 0);
  if (warp == 12 && elect_one()) {
#pragma unroll
    for (int i = 0; i <= 2 * NSTB; i++) mbar_init(bar + i * 8, i < NSTB || i == 2 * NSTB ? 1 : 12);
    asm volatile("st.shared.u32 [%0], 0;" ::"r"(bar + 120) : "memory");
    mbar_expect(bar + 2 * NSTB * 8, 73728);
#pragma unroll
    for (int i = 0; i < 2; i++)
      asm volatile("cp.async.bulk.tensor.3d.shared::cluster.global.mbarrier::complete_tx::bytes [%0], [%1, {%3,%4,%5}], [%2];"
                   ::"r"(sb + SM_B_W + i * 36864), "l"(&mp.wo), "r"(bar + 2 * NSTB * 8), "r"(0), "r"(0), "r"(i * 3) : "memory");
  }
  __syncthreads();
  const int step = gridDim.x;
  if (warp == 15) {
    int so = 0;
    nb_arrive(4, 288); nb_arrive(5, 288); nb_arrive(6, 288);
#pragma unroll 1
    for (int n = blockIdx.x, tk = 0; n < NTB; n += step, tk++) {
      uint32_t cc = 0;
#pragma unroll
      for (int wg = 0; wg < 3; wg++) {
        if (lane == 0) asm volatile("cp.async.bulk.wait_group.read 5;" ::: "memory");
        nb_sync(1 + wg, 160);
        if (wg == 0 || n + step < NTB) nb_arrive(4 + wg, 288);
        if (wg == 0) asm volatile("ld.shared.u32 %0, [%1];" : "=r"(cc) : "r"(bar + 128 + tk * 4) : "memory");
        if (lane == 0) {
          asm volatile("cp.async.bulk.tensor.4d.global.shared::cta.bulk_group [%0, {%2,%3,%4,%5}], [%1];"
                       ::"l"(&mp.oo), "r"(sb + SM_B_ST + wg * 8192 + so), "r"(0), "r"((cc >> 8) & 255), "r"(cc >> 16), "r"((cc & 1) * 3 + wg) : "memory");
          asm volatile("cp.async.bulk.commit_group;" ::: "memory");
        }
        __syncwarp();
      }
      so = so == 49152 ? 0 : so + 24576;
    }
    if (lane == 0) asm volatile("cp.async.bulk.wait_group.read 0;" ::: "memory");
  } else if (warp >= 12) {
    nb_sync(7, 480);
#pragma unroll 1
    for (int n = blockIdx.x + (warp - 12) * step; n < NTB; n += 3 * step) {
      const int b = n / 56, rem = n - b * 56, par = rem / 14;
      const int c0 = opq((uint32_t)(par & 1)), c1 = opq((uint32_t)(8 * b)), c2 = opq((uint32_t)((par >> 1) * 112 + (rem - par * 14) * 8));
      int v; uint32_t spin = 0, tk = 0;
      do { asm volatile("ld.acquire.gpu.global.s32 %0, [%1];" : "=r"(v) : "l"(g_flags + n * FS) : "memory"); } while (v < 4 && ++spin < SPIN_LIMIT);
      if (lane == 0) asm volatile("atom.shared.add.u32 %0, [%1], 1;" : "=r"(tk) : "r"(bar + 120) : "memory");
      asm volatile("fence.proxy.async.global;" ::: "memory");
      tk = __shfl_sync(0xffffffffu, tk, 0);
      TRB(tk, 0);
      const uint32_t use = tk / NSTB, sg = tk - use * NSTB;
      if (use) mbar_wait(bar + (NSTB + sg) * 8, (use - 1) & 1);
      TRB(tk, 1);
      if (elect_one()) {
        asm volatile("st.shared.u32 [%0], %1;" ::"r"(bar + 128 + tk * 4), "r"(c0 | c1 << 8 | c2 << 16) : "memory");
        mbar_expect(bar + sg * 8, 24576);
        asm volatile("cp.async.bulk.tensor.3d.shared::cluster.global.mbarrier::complete_tx::bytes [%0], [%1, {%3,%4,%5}], [%2];"
                     ::"r"(sb + SM_B_IN + sg * 24576), "l"(&mp.oi), "r"(bar + sg * 8), "r"(c0 * 192), "r"(c1), "r"(c2) : "memory");
        g_flags[n * FS] = 0;
      }
      __syncwarp();
    }
  } else {
    const int wg = warp >> 2, w = warp & 3;
    uint32_t a[48];
    mbar_wait(bar + 2 * NSTB * 8, 0);
    {
      const int k = (lane & 7) + (lane >> 4) * 8, ch = (warp & 1) * 2 + ((lane >> 3) & 1);
      const uint32_t wa = sb + SM_B_W + (warp >> 1) * 12288 + k * 64 + ((ch ^ ((k >> 1) & 3)) * 16);
#pragma unroll
      for (int i = 0; i < 12; i++)
        asm volatile("ldmatrix.sync.aligned.m8n8.x4.trans.shared.b16 {%0,%1,%2,%3}, [%4];"
                     : "=r"(a[4 * i]), "=r"(a[4 * i + 1]), "=r"(a[4 * i + 2]), "=r"(a[4 * i + 3]) : "r"(wa + i * 1024) : "memory");
    }
    nb_sync(7, 480);
    TRB(47, 1);
    const uint32_t sta = opq(sb + SM_B_ST + wg * 8192 + ((lane & 7) + (lane >> 4) * 8) * 128 + (((2 * w + ((lane >> 3) & 1)) ^ (lane & 7)) * 16));
    const uint32_t hi = opq((uint32_t)(mkdesc(0, 0, 3072, 0) >> 32) + (blockIdx.x >> 16)), bb = opq(bar);
    const uint32_t nbT = opq((uint32_t)(4 + wg)), nbN = opq((uint32_t)(wg == 2 ? 4 : 5 + wg)), nbD = opq((uint32_t)(1 + wg));
    int left = (NTB - blockIdx.x + step - 1) / step;
    if (wg == 2) nb_arrive(4, 288);
#pragma unroll 1
    for (uint32_t ph = 0;; ph ^= 1) {
#pragma unroll
      for (int sg = 0; sg < NSTB; sg++) {
        constexpr uint64_t db = mkdesc(SBC + SM_B_IN, 128, 3072, 0);
        float D[32];
        mbar_wait(bb + sg * 8, ph);
        nb_sync(nbT, 288);
        wg_fence();
        wg_rs64<0>(D, a[0], a[1], a[2], a[3], dsc(db + sg * 1536, hi));
#pragma unroll
        for (int k = 1; k < 12; k++) wg_rs64<1>(D, a[4 * k], a[4 * k + 1], a[4 * k + 2], a[4 * k + 3], dsc(db + sg * 1536 + k * 16, hi));
        wg_commit();
        nb_arrive(nbN, 288);
        wg_wait<0>(); pin(D);
        mbar_arrive_elect(bb + (NSTB + sg) * 8);
#pragma unroll
        for (int q = 0; q < 4; q++)
          asm volatile("stmatrix.sync.aligned.m8n8.x4.trans.shared.b16 [%0], {%1,%2,%3,%4};" ::"r"(sta + (sg % 3) * 24576 + q * 2048),
                       "r"(pack2(D[8 * q], D[8 * q + 1])), "r"(pack2(D[8 * q + 2], D[8 * q + 3])), "r"(pack2(D[8 * q + 4], D[8 * q + 5])), "r"(pack2(D[8 * q + 6], D[8 * q + 7])) : "memory");
        fence_async();
        nb_arrive(nbD, 160);
        if (wg == 0) TRB(31 - left, 5);
        if (--left == 0) goto done;
      }
    }
  done:
    if (wg == 0) nb_arrive(4, 288);
    TR2(132 + blockIdx.x, 2);
    TR2FLUSH(132 + blockIdx.x);
  }
}

typedef CUresult (*EncodeFn)(CUtensorMap*, CUtensorMapDataType, cuuint32_t, void*, const cuuint64_t*, const cuuint64_t*, const cuuint32_t*,
                             const cuuint32_t*, CUtensorMapInterleave, CUtensorMapSwizzle, CUtensorMapL2promotion, CUtensorMapFloatOOBfill);
static EncodeFn g_enc = nullptr;
static void make_map(CUtensorMap* m, const void* p, int rank, const cuuint64_t* dim, const cuuint64_t* str, const cuuint32_t* box, CUtensorMapSwizzle sw) {
  const cuuint32_t ones[5] = {1, 1, 1, 1, 1};
  g_enc(m, CU_TENSOR_MAP_DATA_TYPE_BFLOAT16, rank, (void*)p, dim, str, box, ones, CU_TENSOR_MAP_INTERLEAVE_NONE, sw,
        CU_TENSOR_MAP_L2_PROMOTION_L2_128B, CU_TENSOR_MAP_FLOAT_OOB_FILL_NONE);
}

extern "C" void kernel_launch(void* const* d_in, const int* in_sizes, int n_in, void* d_out, int out_size) {
  const __nv_bfloat16* x = (const __nv_bfloat16*)d_in[0];
  const __nv_bfloat16* wqkv = (const __nv_bfloat16*)d_in[1];
  const __nv_bfloat16* wo = (const __nv_bfloat16*)d_in[2];
  const __nv_bfloat16* rpb = (const __nv_bfloat16*)d_in[3];

  if (!g_enc) {
    void* fn = nullptr; cudaDriverEntryPointQueryResult qr;
    cudaGetDriverEntryPoint("cuTensorMapEncodeTiled", &fn, cudaEnableDefault, &qr);
    g_enc = (EncodeFn)fn;
    cudaFuncSetAttribute(na_attn_kernel, cudaFuncAttributeMaxDynamicSharedMemorySize, SM_A_TOTAL);
    cudaFuncSetAttribute(na_proj_kernel, cudaFuncAttributeMaxDynamicSharedMemorySize, SM_B_TOTAL);
  }
  Maps ma; MapsB mb;
  { cuuint64_t dim[4] = {64, 112, 224, 6}, str[3] = {(cuuint64_t)ROWB, 768, 128};
    cuuint32_t box[4] = {64, 4, 16, 3}, boxh[4] = {64, 16, 3, 3}, boxo[4] = {64, 8, 8, 1};
    make_map(&ma.xc, x, 4, dim, str, box, CU_TENSOR_MAP_SWIZZLE_128B);
    make_map(&ma.xh, x, 4, dim, str, boxh, CU_TENSOR_MAP_SWIZZLE_128B);
    make_map(&mb.oo, d_out, 4, dim, str, boxo, CU_TENSOR_MAP_SWIZZLE_128B); }
  { cuuint64_t dim[3] = {384, 112, 224}, str[2] = {(cuuint64_t)ROWB, 768};
    cuuint32_t box[3] = {192, 8, 8}, boxs[3] = {192, 2, 16};
    make_map(&mb.oi, d_out, 3, dim, str, box, CU_TENSOR_MAP_SWIZZLE_NONE);
    make_map(&ma.os, d_out, 3, dim, str, boxs, CU_TENSOR_MAP_SWIZZLE_NONE); }
  { cuuint64_t dim[4] = {32, 112, 224, 12}, str[3] = {(cuuint64_t)ROWB, 768, 64};
    cuuint32_t box[4] = {32, 8, 2, 3};
    make_map(&ma.ot, d_out, 4, dim, str, box, CU_TENSOR_MAP_SWIZZLE_64B); }
  { cuuint64_t dim[2] = {576, 192}, str[1] = {1152};
    cuuint32_t box[2] = {16, 192};
    make_map(&ma.w, wqkv, 2, dim, str, box, CU_TENSOR_MAP_SWIZZLE_32B); }
  { cuuint64_t dim[3] = {32, 192, 6}, str[2] = {384, 64};
    cuuint32_t box[3] = {32, 192, 3};
    make_map(&mb.wo, wo, 3, dim, str, box, CU_TENSOR_MAP_SWIZZLE_64B); }
  { cuuint64_t dim[2] = {192, 192}, str[1] = {384};
    cuuint32_t box[2] = {32, 48};
    make_map(&ma.wo, wo, 2, dim, str, box, CU_TENSOR_MAP_SWIZZLE_64B); }
  na_attn_kernel<<<112, 512, SM_A_TOTAL>>>(x, wqkv, rpb, ma);
  cudaLaunchConfig_t cfg = {};
  cfg.gridDim = dim3(20); cfg.blockDim = dim3(512); cfg.dynamicSmemBytes = SM_B_TOTAL; cfg.stream = cudaStreamPerThread;
  cudaLaunchAttribute at[1];
  at[0].id = cudaLaunchAttributeProgrammaticStreamSerialization; at[0].val.programmaticStreamSerializationAllowed = 1;
  cfg.attrs = at; cfg.numAttrs = 1;
  cudaLaunchKernelEx(&cfg, na_proj_kernel, mb);
}
```
